```python
import torch

def _softmax(x, axis=-1):
    return torch.softmax(x, dim=axis)
def _gelu(x):
    return torch.nn.functional.gelu(x, approximate="tanh")
def _silu(x):
    return torch.nn.functional.silu(x)
def _sigmoid(x):
    return torch.sigmoid(x)
def _layernorm(x, axis=-1, eps=1e-5):
    m = x.mean(dim=axis, keepdim=True)
    v = x.var(dim=axis, keepdim=True, unbiased=False)
    return (x - m) / torch.sqrt(v + eps)
def _scatter_add(tgt, idx, src, axis=0):
    return tgt.clone().index_add_(axis, idx, src)
def _segment_sum(src, seg, n):
    out = torch.zeros((n,) + src.shape[1:], dtype=src.dtype)
    return out.index_add_(0, seg, src)
def _pad(x, pw):
    flat = tuple(v for pair in reversed(pw) for v in pair)
    return torch.nn.functional.pad(x, flat)

kernel_name = 'gated_mix__linear_kernel_hedgehog__mixer_s_mlp__prompt'

def setup_inputs():

    _w = (lambda a: (lambda t: t.to(torch.bfloat16) if t.is_floating_point() else t)(torch.as_tensor(a)))
    def _A_setup():
        B, S, D, H = 1, 2048, 640, 32
        Dh = D // H
        return {
            "x": _w((lambda *s: torch.randn(*s, dtype=torch.bfloat16) * 0.05)(B, S, D)),
            "wqkv": _w((lambda *s: torch.randn(*s, dtype=torch.bfloat16) * 3.2)(D, 3 * D)),
            "w_phi": _w((lambda *s: torch.randn(*s, dtype=torch.bfloat16) * 3.2)(H, Dh, Dh) * (Dh ** -0.5)),
            "wo": _w((lambda *s: torch.randn(*s, dtype=torch.bfloat16) * 1.6)(D, D)),
        }
    _A_in = _A_setup()

    def _B_setup():
        B, S, D, F = 1, 2048, 640, 1536
        return {
            "x":  _w((lambda *s: torch.randn(*s, dtype=torch.bfloat16) * 0.05)(B, S, D)),
            "w1": _w((lambda *s: torch.randn(*s, dtype=torch.bfloat16) * 3.2)(D, D) * (D ** -0.5)),
            "w2": _w((lambda *s: torch.randn(*s, dtype=torch.bfloat16) * 3.2)(D, D) * (D ** -0.5)),
            "w3": _w((lambda *s: torch.randn(*s, dtype=torch.bfloat16) * 3.2)(D, F) * (D ** -0.5)),
            "w4": _w((lambda *s: torch.randn(*s, dtype=torch.bfloat16) * 3.2)(F, D) * (F ** -0.5)),
        }
    _B_in = _B_setup()

    return {
        "A_x": _A_in["x"],
        "A_wqkv": _A_in["wqkv"],
        "A_w_phi": _A_in["w_phi"],
        "A_wo": _A_in["wo"],
        "B_x": _B_in["x"],
        "B_w1": _B_in["w1"],
        "B_w2": _B_in["w2"],
        "B_w3": _B_in["w3"],
        "B_w4": _B_in["w4"],
        "gate_w": _w((lambda *s: torch.randn(*s, dtype=torch.bfloat16) * 0.05)(640) * 16.0),
    }

def reference(A_x, A_wqkv, A_w_phi, A_wo, B_x, B_w1, B_w2, B_w3, B_w4, gate_w):
    def _A_ref(x, wqkv, w_phi, wo):
        B, S, D = x.shape
        H = 32; Dh = D // H
        qkv = (lambda x, *d: x.permute(*d))((x @ wqkv).reshape(B, S, 3, H, Dh), 2, 0, 3, 1, 4)
        q, k, v = qkv[0], qkv[1], qkv[2]
        pq = torch.einsum("bhsd,hdf->bhsf", q, w_phi)
        pk = torch.einsum("bhsd,hdf->bhsf", k, w_phi)
        phi_q = torch.concatenate([_softmax(pq, axis=-1), _softmax(-pq, axis=-1)], axis=-1)
        phi_k = torch.concatenate([_softmax(pk, axis=-1), _softmax(-pk, axis=-1)], axis=-1)
        kv = torch.einsum("bhsf,bhsd->bhfd", phi_k, v)
        z  = torch.einsum("bhsf->bhf", phi_k)
        num = torch.einsum("bhqf,bhfd->bhqd", phi_q, kv)
        den = torch.einsum("bhqf,bhf->bhq", phi_q, z)[..., None] + 1e-6
        o = num / den
        return (lambda x, *d: x.permute(*d))(o, 0, 2, 1, 3).reshape(B, S, D) @ wo

    def _B_ref(x, w1, w2, w3, w4):
        B, S, D = x.shape
        h = _gelu(_layernorm(x, axis=-1) @ w1)
        c = D // 4
        g0 = _pad(h[:, :, 0*c:1*c], ((0, 0), (1, 0), (0, 0)))[:, :S, :]
        g1 = _pad(h[:, :, 1*c:2*c], ((0, 0), (0, 1), (0, 0)))[:, 1:, :]
        g2 = _pad(h[:, :, 2*c:3*c], ((0, 0), (2, 0), (0, 0)))[:, :S, :]
        g3 = _pad(h[:, :, 3*c:   ], ((0, 0), (0, 2), (0, 0)))[:, 2:, :]
        hs = torch.concatenate([g0, g1, g2, g3], axis=-1) @ w2
        x1 = x + hs
        h2 = _gelu(_layernorm(x1, axis=-1) @ w3) @ w4
        return x1 + h2

    x = A_x
    g = _sigmoid((x * gate_w).sum(-1, keepdims=True))
    a = _A_ref(x, A_wqkv, A_w_phi, A_wo)
    b = _B_ref(x, B_w1, B_w2, B_w3, B_w4)
    return g * a + (1 - g) * b
```

```cpp
#include <cuda_runtime.h>
#include <cuda_bf16.h>
#include <cuda.h>
#include <stdint.h>

namespace {

constexpr int S_ = 2048, D_ = 640, F_ = 1536;
constexpr int NCTA = 128;
constexpr int KV_PAIR = 40 * 48 + 96;
constexpr int KV_J = 2 * KV_PAIR;

constexpr int SLOT_B = 49152, NB = 3;
constexpr int SLOT_A = 16384, NA = 4;
constexpr int OFF_B = 0;
constexpr int OFF_A = OFF_B + NB * SLOT_B;
constexpr int OFF_MISC = OFF_A + NA * SLOT_A;
constexpr int OFF_CS = OFF_MISC + 16384;
constexpr int OFF_BAR = OFF_CS + 1152;
constexpr int SMEM_USED = OFF_BAR + 256;
constexpr int SMEM_BYTES = SMEM_USED + 1024;

constexpr int FL_DONE = 0, FL_PREP = 1, FL_H = 2, FL_X1 = FL_H + 16, FL_KV = FL_X1 + 16, FL_PART = FL_KV + 8;
constexpr int FL_COUNT = FL_PART + 16 * 8 * 8;

struct Maps {
  CUtensorMap x, w1m, w1r, qm, qr, hs, w2, x1, w3, w4, wo;
};

}

__device__ __align__(1024) __nv_bfloat16 g_Hs[S_ * D_];
__device__ __align__(1024) __nv_bfloat16 g_X1[S_ * D_];
__device__ __align__(128) float2 g_st1[S_ * 8];
__device__ __align__(128) float4 g_xstat[S_];
__device__ __align__(128) float g_cs[D_ + F_];
__device__ __align__(128) float g_kv[2][8 * KV_J];
__device__ __align__(128) uint4 g_part[16 * 8 * 8 * 5 * 256];
__device__ __align__(128) unsigned g_flags[FL_COUNT * 32];
#define TSTAMP(n) do {} while (0)

namespace {

__device__ __forceinline__ long long gtime() { long long t; asm volatile("mov.u64 %0, %%globaltimer;" : "=l"(t)); return t; }
__device__ __forceinline__ uint32_t smem_u32(const void* p) { return (uint32_t)__cvta_generic_to_shared(p); }
__device__ __forceinline__ void mbar_init(uint32_t bar, int cnt) {
  asm volatile("mbarrier.init.shared::cta.b64 [%0], %1;" ::"r"(bar), "r"(cnt) : "memory");
}
__device__ __forceinline__ void mbar_expect_tx(uint32_t bar, int bytes) {
  asm volatile("mbarrier.arrive.expect_tx.shared::cta.b64 _, [%0], %1;" ::"r"(bar), "r"(bytes) : "memory");
}
__device__ __forceinline__ void mbar_arrive_cta(uint32_t bar, uint32_t cta) {
  asm volatile("{\n.reg .b32 ra;\nmapa.shared::cluster.u32 ra, %0, %1;\nmbarrier.arrive.shared::cluster.b64 _, [ra];\n}"
               ::"r"(bar), "r"(cta) : "memory");
}
__device__ __forceinline__ uint32_t mbar_try(uint32_t bar, uint32_t parity) {
  uint32_t ok;
  asm volatile("{\n.reg .pred p;\nmbarrier.try_wait.parity.shared::cta.b64 p, [%1], %2;\nselp.u32 %0, 1, 0, p;\n}"
               : "=r"(ok) : "r"(bar), "r"(parity) : "memory");
  return ok;
}
constexpr long long WAIT_LIMIT = 60000000LL;
__device__ __forceinline__ void mbar_wait(uint32_t bar, uint32_t parity) {
  if (mbar_try(bar, parity)) return;
  long long t0 = clock64();
  while (!mbar_try(bar, parity)) {
    if (clock64() - t0 > WAIT_LIMIT) break;
  }
}
__device__ __forceinline__ unsigned ld_acquire(const unsigned* p) {
  unsigned v;
  asm volatile("ld.acquire.gpu.global.u32 %0, [%1];" : "=r"(v) : "l"(p) : "memory");
  return v;
}
__device__ __forceinline__ void flag_wait(int idx, unsigned target) {
  const unsigned* p = g_flags + idx * 32;
  if ((int)(ld_acquire(p) - target) >= 0) return;
  long long t0 = clock64();
  while ((int)(ld_acquire(p) - target) < 0) {
    if (clock64() - t0 > WAIT_LIMIT) break;
  }
}
__device__ __forceinline__ void flag_add(int idx) {
  asm volatile("red.release.gpu.global.add.u32 [%0], 1;" ::"l"(g_flags + idx * 32) : "memory");
}
__device__ __forceinline__ void fence_async_all() { asm volatile("fence.proxy.async;" ::: "memory"); }
__device__ __forceinline__ void fence_async_smem() { asm volatile("fence.proxy.async.shared::cta;" ::: "memory"); }
__device__ __forceinline__ void bar_sync(int id, int n) { asm volatile("bar.sync %0, %1;" ::"r"(id), "r"(n) : "memory"); }

__device__ __forceinline__ void tma2d(uint32_t dst, const CUtensorMap* m, uint32_t bar, int c0, int c1) {
  asm volatile("cp.async.bulk.tensor.2d.shared::cluster.global.mbarrier::complete_tx::bytes [%0], [%1, {%3, %4}], [%2];"
               ::"r"(dst), "l"(m), "r"(bar), "r"(c0), "r"(c1) : "memory");
}
__device__ __forceinline__ void tma2d_mc(uint32_t dst, const CUtensorMap* m, uint32_t bar, int c0, int c1) {
  asm volatile("cp.async.bulk.tensor.2d.shared::cluster.global.mbarrier::complete_tx::bytes.multicast::cluster"
               " [%0], [%1, {%3, %4}], [%2], %5;"
               ::"r"(dst), "l"(m), "r"(bar), "r"(c0), "r"(c1), "h"((uint16_t)3) : "memory");
}
__device__ __forceinline__ void tma3d(uint32_t dst, const CUtensorMap* m, uint32_t bar, int c0, int c1, int c2) {
  asm volatile("cp.async.bulk.tensor.3d.shared::cluster.global.mbarrier::complete_tx::bytes [%0], [%1, {%3, %4, %5}], [%2];"
               ::"r"(dst), "l"(m), "r"(bar), "r"(c0), "r"(c1), "r"(c2) : "memory");
}
__device__ __forceinline__ void tma3d_mc(uint32_t dst, const CUtensorMap* m, uint32_t bar, int c0, int c1, int c2) {
  asm volatile("cp.async.bulk.tensor.3d.shared::cluster.global.mbarrier::complete_tx::bytes.multicast::cluster"
               " [%0], [%1, {%3, %4, %5}], [%2], %6;"
               ::"r"(dst), "l"(m), "r"(bar), "r"(c0), "r"(c1), "r"(c2), "h"((uint16_t)3) : "memory");
}
__device__ __forceinline__ void tma4d_mc(uint32_t dst, const CUtensorMap* m, uint32_t bar, int c0, int c1, int c2, int c3) {
  asm volatile("cp.async.bulk.tensor.4d.shared::cluster.global.mbarrier::complete_tx::bytes.multicast::cluster"
               " [%0], [%1, {%3, %4, %5, %6}], [%2], %7;"
               ::"r"(dst), "l"(m), "r"(bar), "r"(c0), "r"(c1), "r"(c2), "r"(c3), "h"((uint16_t)3) : "memory");
}
__device__ __forceinline__ void l2_prefetch(const void* p, uint32_t bytes) {
  asm volatile("cp.async.bulk.prefetch.L2.global [%0], %1;" ::"l"(p), "r"(bytes) : "memory");
}
__device__ __forceinline__ void prefetch_tmap(const CUtensorMap* m) {
  asm volatile("prefetch.tensormap [%0];" ::"l"(m) : "memory");
}
__device__ __forceinline__ uint64_t make_desc(uint32_t addr, uint32_t lbo, uint32_t sbo, uint32_t swz) {
  return (uint64_t)((addr & 0x3FFFF) >> 4) | ((uint64_t)(lbo >> 4) << 16) | ((uint64_t)(sbo >> 4) << 32) | ((uint64_t)swz << 62);
}
__device__ __forceinline__ void wg_fence() { asm volatile("wgmma.fence.sync.aligned;" ::: "memory"); }
__device__ __forceinline__ void wg_commit() { asm volatile("wgmma.commit_group.sync.aligned;" ::: "memory"); }
template <int N> __device__ __forceinline__ void wg_wait() { asm volatile("wgmma.wait_group.sync.aligned %0;" ::"n"(N) : "memory"); }
template <int N> __device__ __forceinline__ void fence_regs(float (&d)[N]) {
#pragma unroll
  for (int i = 0; i < N; i++) asm volatile("" : "+f"(d[i])::"memory");
}
__device__ __forceinline__ uint32_t pack_bf16(float lo, float hi) {
  uint32_t r;
  asm("cvt.rn.bf16x2.f32 %0, %1, %2;" : "=r"(r) : "f"(hi), "f"(lo));
  return r;
}
__device__ __forceinline__ float bf_lo(uint32_t v) { return __uint_as_float(v << 16); }
__device__ __forceinline__ float bf_hi(uint32_t v) { return __uint_as_float(v & 0xffff0000u); }
__device__ __forceinline__ uint32_t max_bf2(uint32_t a, uint32_t b) {
  uint32_t r; asm("max.bf16x2 %0, %1, %2;" : "=r"(r) : "r"(a), "r"(b)); return r;
}
__device__ __forceinline__ uint32_t min_bf2(uint32_t a, uint32_t b) {
  uint32_t r; asm("min.bf16x2 %0, %1, %2;" : "=r"(r) : "r"(a), "r"(b)); return r;
}
__device__ __forceinline__ float ex2(float x) { float r; asm("ex2.approx.ftz.f32 %0, %1;" : "=f"(r) : "f"(x)); return r; }
__device__ __forceinline__ float rcp(float x) { float r; asm("rcp.approx.ftz.f32 %0, %1;" : "=f"(r) : "f"(x)); return r; }
__device__ __forceinline__ float tanh_ap(float x) { float r; asm("tanh.approx.f32 %0, %1;" : "=f"(r) : "f"(x)); return r; }
__device__ __forceinline__ float gelu_s(float x, float hs) {
  float u = x * fmaf(x * x, 0.0356774081f, 0.7978845608f);
  float hx = x * hs;
  return fmaf(hx, tanh_ap(u), hx);
}
__device__ __forceinline__ void stsm4(uint32_t addr, uint32_t r0, uint32_t r1, uint32_t r2, uint32_t r3) {
  asm volatile("stmatrix.sync.aligned.m8n8.x4.shared.b16 [%0], {%1, %2, %3, %4};"
               ::"r"(addr), "r"(r0), "r"(r1), "r"(r2), "r"(r3) : "memory");
}
__device__ __forceinline__ void red_add4(float* p, float a, float b, float c, float d) {
  asm volatile("red.global.add.v4.f32 [%0], {%1, %2, %3, %4};" ::"l"(p), "f"(a), "f"(b), "f"(c), "f"(d) : "memory");
}
__device__ __forceinline__ void red_add2(float* p, float a, float b) {
  asm volatile("red.global.add.v2.f32 [%0], {%1, %2};" ::"l"(p), "f"(a), "f"(b) : "memory");
}

__device__ __forceinline__ void mma_ss256(float (&d)[128], uint64_t descA, uint64_t descB, int scaleD) {
  asm volatile("{\n.reg .pred p;\nsetp.ne.b32 p, %130, 0;\n"
      "wgmma.mma_async.sync.aligned.m64n256k16.f32.bf16.bf16 {"
      "%0, %1, %2, %3, %4, %5, %6, %7, %8, %9, %10, %11, %12, %13, %14, %15, "
      "%16, %17, %18, %19, %20, %21, %22, %23, %24, %25, %26, %27, %28, %29, %30, %31, "
      "%32, %33, %34, %35, %36, %37, %38, %39, %40, %41, %42, %43, %44, %45, %46, %47, "
      "%48, %49, %50, %51, %52, %53, %54, %55, %56, %57, %58, %59, %60, %61, %62, %63, "
      "%64, %65, %66, %67, %68, %69, %70, %71, %72, %73, %74, %75, %76, %77, %78, %79, "
      "%80, %81, %82, %83, %84, %85, %86, %87, %88, %89, %90, %91, %92, %93, %94, %95, "
      "%96, %97, %98, %99, %100, %101, %102, %103, %104, %105, %106, %107, %108, %109, %110, %111, "
      "%112, %113, %114, %115, %116, %117, %118, %119, %120, %121, %122, %123, %124, %125, %126, %127"
      "}, %128, %129, p, 1, 1, 0, 1;\n}\n"
      : "+f"(d[0]), "+f"(d[1]), "+f"(d[2]), "+f"(d[3]), "+f"(d[4]), "+f"(d[5]), "+f"(d[6]), "+f"(d[7]),
        "+f"(d[8]), "+f"(d[9]), "+f"(d[10]), "+f"(d[11]), "+f"(d[12]), "+f"(d[13]), "+f"(d[14]), "+f"(d[15]),
        "+f"(d[16]), "+f"(d[17]), "+f"(d[18]), "+f"(d[19]), "+f"(d[20]), "+f"(d[21]), "+f"(d[22]), "+f"(d[23]),
        "+f"(d[24]), "+f"(d[25]), "+f"(d[26]), "+f"(d[27]), "+f"(d[28]), "+f"(d[29]), "+f"(d[30]), "+f"(d[31]),
        "+f"(d[32]), "+f"(d[33]), "+f"(d[34]), "+f"(d[35]), "+f"(d[36]), "+f"(d[37]), "+f"(d[38]), "+f"(d[39]),
        "+f"(d[40]), "+f"(d[41]), "+f"(d[42]), "+f"(d[43]), "+f"(d[44]), "+f"(d[45]), "+f"(d[46]), "+f"(d[47]),
        "+f"(d[48]), "+f"(d[49]), "+f"(d[50]), "+f"(d[51]), "+f"(d[52]), "+f"(d[53]), "+f"(d[54]), "+f"(d[55]),
        "+f"(d[56]), "+f"(d[57]), "+f"(d[58]), "+f"(d[59]), "+f"(d[60]), "+f"(d[61]), "+f"(d[62]), "+f"(d[63]),
        "+f"(d[64]), "+f"(d[65]), "+f"(d[66]), "+f"(d[67]), "+f"(d[68]), "+f"(d[69]), "+f"(d[70]), "+f"(d[71]),
        "+f"(d[72]), "+f"(d[73]), "+f"(d[74]), "+f"(d[75]), "+f"(d[76]), "+f"(d[77]), "+f"(d[78]), "+f"(d[79]),
        "+f"(d[80]), "+f"(d[81]), "+f"(d[82]), "+f"(d[83]), "+f"(d[84]), "+f"(d[85]), "+f"(d[86]), "+f"(d[87]),
        "+f"(d[88]), "+f"(d[89]), "+f"(d[90]), "+f"(d[91]), "+f"(d[92]), "+f"(d[93]), "+f"(d[94]), "+f"(d[95]),
        "+f"(d[96]), "+f"(d[97]), "+f"(d[98]), "+f"(d[99]), "+f"(d[100]), "+f"(d[101]), "+f"(d[102]), "+f"(d[103]),
        "+f"(d[104]), "+f"(d[105]), "+f"(d[106]), "+f"(d[107]), "+f"(d[108]), "+f"(d[109]), "+f"(d[110]), "+f"(d[111]),
        "+f"(d[112]), "+f"(d[113]), "+f"(d[114]), "+f"(d[115]), "+f"(d[116]), "+f"(d[117]), "+f"(d[118]), "+f"(d[119]),
        "+f"(d[120]), "+f"(d[121]), "+f"(d[122]), "+f"(d[123]), "+f"(d[124]), "+f"(d[125]), "+f"(d[126]), "+f"(d[127])
      : "l"(descA), "l"(descB), "r"(scaleD));
}

__device__ __forceinline__ void mma_ss64(float (&d)[32], uint64_t descA, uint64_t descB, int scaleD) {
  asm volatile("{\n.reg .pred p;\nsetp.ne.b32 p, %34, 0;\n"
      "wgmma.mma_async.sync.aligned.m64n64k16.f32.bf16.bf16 {"
      "%0, %1, %2, %3, %4, %5, %6, %7, %8, %9, %10, %11, %12, %13, %14, %15, "
      "%16, %17, %18, %19, %20, %21, %22, %23, %24, %25, %26, %27, %28, %29, %30, %31"
      "}, %32, %33, p, 1, 1, 0, 1;\n}\n"
      : "+f"(d[0]), "+f"(d[1]), "+f"(d[2]), "+f"(d[3]), "+f"(d[4]), "+f"(d[5]), "+f"(d[6]), "+f"(d[7]),
        "+f"(d[8]), "+f"(d[9]), "+f"(d[10]), "+f"(d[11]), "+f"(d[12]), "+f"(d[13]), "+f"(d[14]), "+f"(d[15]),
        "+f"(d[16]), "+f"(d[17]), "+f"(d[18]), "+f"(d[19]), "+f"(d[20]), "+f"(d[21]), "+f"(d[22]), "+f"(d[23]),
        "+f"(d[24]), "+f"(d[25]), "+f"(d[26]), "+f"(d[27]), "+f"(d[28]), "+f"(d[29]), "+f"(d[30]), "+f"(d[31])
      : "l"(descA), "l"(descB), "r"(scaleD));
}

__device__ __forceinline__ void mma_ss80(float (&d)[40], uint64_t descA, uint64_t descB, int scaleD) {
  asm volatile("{\n.reg .pred p;\nsetp.ne.b32 p, %42, 0;\n"
      "wgmma.mma_async.sync.aligned.m64n80k16.f32.bf16.bf16 {"
      "%0, %1, %2, %3, %4, %5, %6, %7, %8, %9, %10, %11, %12, %13, %14, %15, "
      "%16, %17, %18, %19, %20, %21, %22, %23, %24, %25, %26, %27, %28, %29, %30, %31, "
      "%32, %33, %34, %35, %36, %37, %38, %39"
      "}, %40, %41, p, 1, 1, 0, 1;\n}\n"
      : "+f"(d[0]), "+f"(d[1]), "+f"(d[2]), "+f"(d[3]), "+f"(d[4]), "+f"(d[5]), "+f"(d[6]), "+f"(d[7]),
        "+f"(d[8]), "+f"(d[9]), "+f"(d[10]), "+f"(d[11]), "+f"(d[12]), "+f"(d[13]), "+f"(d[14]), "+f"(d[15]),
        "+f"(d[16]), "+f"(d[17]), "+f"(d[18]), "+f"(d[19]), "+f"(d[20]), "+f"(d[21]), "+f"(d[22]), "+f"(d[23]),
        "+f"(d[24]), "+f"(d[25]), "+f"(d[26]), "+f"(d[27]), "+f"(d[28]), "+f"(d[29]), "+f"(d[30]), "+f"(d[31]),
        "+f"(d[32]), "+f"(d[33]), "+f"(d[34]), "+f"(d[35]), "+f"(d[36]), "+f"(d[37]), "+f"(d[38]), "+f"(d[39])
      : "l"(descA), "l"(descB), "r"(scaleD));
}

__device__ __forceinline__ void mma_ss192(float (&d)[96], uint64_t descA, uint64_t descB, int scaleD) {
  asm volatile("{\n.reg .pred p;\nsetp.ne.b32 p, %98, 0;\n"
      "wgmma.mma_async.sync.aligned.m64n192k16.f32.bf16.bf16 {"
      "%0, %1, %2, %3, %4, %5, %6, %7, %8, %9, %10, %11, %12, %13, %14, %15, "
      "%16, %17, %18, %19, %20, %21, %22, %23, %24, %25, %26, %27, %28, %29, %30, %31, "
      "%32, %33, %34, %35, %36, %37, %38, %39, %40, %41, %42, %43, %44, %45, %46, %47, "
      "%48, %49, %50, %51, %52, %53, %54, %55, %56, %57, %58, %59, %60, %61, %62, %63, "
      "%64, %65, %66, %67, %68, %69, %70, %71, %72, %73, %74, %75, %76, %77, %78, %79, "
      "%80, %81, %82, %83, %84, %85, %86, %87, %88, %89, %90, %91, %92, %93, %94, %95"
      "}, %96, %97, p, 1, 1, 0, 1;\n}\n"
      : "+f"(d[0]), "+f"(d[1]), "+f"(d[2]), "+f"(d[3]), "+f"(d[4]), "+f"(d[5]), "+f"(d[6]), "+f"(d[7]),
        "+f"(d[8]), "+f"(d[9]), "+f"(d[10]), "+f"(d[11]), "+f"(d[12]), "+f"(d[13]), "+f"(d[14]), "+f"(d[15]),
        "+f"(d[16]), "+f"(d[17]), "+f"(d[18]), "+f"(d[19]), "+f"(d[20]), "+f"(d[21]), "+f"(d[22]), "+f"(d[23]),
        "+f"(d[24]), "+f"(d[25]), "+f"(d[26]), "+f"(d[27]), "+f"(d[28]), "+f"(d[29]), "+f"(d[30]), "+f"(d[31]),
        "+f"(d[32]), "+f"(d[33]), "+f"(d[34]), "+f"(d[35]), "+f"(d[36]), "+f"(d[37]), "+f"(d[38]), "+f"(d[39]),
        "+f"(d[40]), "+f"(d[41]), "+f"(d[42]), "+f"(d[43]), "+f"(d[44]), "+f"(d[45]), "+f"(d[46]), "+f"(d[47]),
        "+f"(d[48]), "+f"(d[49]), "+f"(d[50]), "+f"(d[51]), "+f"(d[52]), "+f"(d[53]), "+f"(d[54]), "+f"(d[55]),
        "+f"(d[56]), "+f"(d[57]), "+f"(d[58]), "+f"(d[59]), "+f"(d[60]), "+f"(d[61]), "+f"(d[62]), "+f"(d[63]),
        "+f"(d[64]), "+f"(d[65]), "+f"(d[66]), "+f"(d[67]), "+f"(d[68]), "+f"(d[69]), "+f"(d[70]), "+f"(d[71]),
        "+f"(d[72]), "+f"(d[73]), "+f"(d[74]), "+f"(d[75]), "+f"(d[76]), "+f"(d[77]), "+f"(d[78]), "+f"(d[79]),
        "+f"(d[80]), "+f"(d[81]), "+f"(d[82]), "+f"(d[83]), "+f"(d[84]), "+f"(d[85]), "+f"(d[86]), "+f"(d[87]),
        "+f"(d[88]), "+f"(d[89]), "+f"(d[90]), "+f"(d[91]), "+f"(d[92]), "+f"(d[93]), "+f"(d[94]), "+f"(d[95])
      : "l"(descA), "l"(descB), "r"(scaleD));
}

__device__ __forceinline__ void mma_ss80_tt(float (&d)[40], uint64_t descA, uint64_t descB, int scaleD) {
  asm volatile("{\n.reg .pred p;\nsetp.ne.b32 p, %42, 0;\n"
      "wgmma.mma_async.sync.aligned.m64n80k16.f32.bf16.bf16 {"
      "%0, %1, %2, %3, %4, %5, %6, %7, %8, %9, %10, %11, %12, %13, %14, %15, "
      "%16, %17, %18, %19, %20, %21, %22, %23, %24, %25, %26, %27, %28, %29, %30, %31, "
      "%32, %33, %34, %35, %36, %37, %38, %39"
      "}, %40, %41, p, 1, 1, 1, 1;\n}\n"
      : "+f"(d[0]), "+f"(d[1]), "+f"(d[2]), "+f"(d[3]), "+f"(d[4]), "+f"(d[5]), "+f"(d[6]), "+f"(d[7]),
        "+f"(d[8]), "+f"(d[9]), "+f"(d[10]), "+f"(d[11]), "+f"(d[12]), "+f"(d[13]), "+f"(d[14]), "+f"(d[15]),
        "+f"(d[16]), "+f"(d[17]), "+f"(d[18]), "+f"(d[19]), "+f"(d[20]), "+f"(d[21]), "+f"(d[22]), "+f"(d[23]),
        "+f"(d[24]), "+f"(d[25]), "+f"(d[26]), "+f"(d[27]), "+f"(d[28]), "+f"(d[29]), "+f"(d[30]), "+f"(d[31]),
        "+f"(d[32]), "+f"(d[33]), "+f"(d[34]), "+f"(d[35]), "+f"(d[36]), "+f"(d[37]), "+f"(d[38]), "+f"(d[39])
      : "l"(descA), "l"(descB), "r"(scaleD));
}

__device__ __forceinline__ void mma_rs80_k(float (&d)[40], const uint32_t (&a)[4], uint64_t descB, int scaleD) {
  asm volatile("{\n.reg .pred p;\nsetp.ne.b32 p, %45, 0;\n"
      "wgmma.mma_async.sync.aligned.m64n80k16.f32.bf16.bf16 {"
      "%0, %1, %2, %3, %4, %5, %6, %7, %8, %9, %10, %11, %12, %13, %14, %15, "
      "%16, %17, %18, %19, %20, %21, %22, %23, %24, %25, %26, %27, %28, %29, %30, %31, "
      "%32, %33, %34, %35, %36, %37, %38, %39"
      "}, {%40, %41, %42, %43}, %44, p, 1, 1, 0;\n}\n"
      : "+f"(d[0]), "+f"(d[1]), "+f"(d[2]), "+f"(d[3]), "+f"(d[4]), "+f"(d[5]), "+f"(d[6]), "+f"(d[7]),
        "+f"(d[8]), "+f"(d[9]), "+f"(d[10]), "+f"(d[11]), "+f"(d[12]), "+f"(d[13]), "+f"(d[14]), "+f"(d[15]),
        "+f"(d[16]), "+f"(d[17]), "+f"(d[18]), "+f"(d[19]), "+f"(d[20]), "+f"(d[21]), "+f"(d[22]), "+f"(d[23]),
        "+f"(d[24]), "+f"(d[25]), "+f"(d[26]), "+f"(d[27]), "+f"(d[28]), "+f"(d[29]), "+f"(d[30]), "+f"(d[31]),
        "+f"(d[32]), "+f"(d[33]), "+f"(d[34]), "+f"(d[35]), "+f"(d[36]), "+f"(d[37]), "+f"(d[38]), "+f"(d[39])
      : "r"(a[0]), "r"(a[1]), "r"(a[2]), "r"(a[3]), "l"(descB), "r"(scaleD));
}

__device__ __forceinline__ void mma_rs48_k(float (&d)[24], const uint32_t (&a)[4], uint64_t descB, int scaleD) {
  asm volatile("{\n.reg .pred p;\nsetp.ne.b32 p, %29, 0;\n"
      "wgmma.mma_async.sync.aligned.m64n48k16.f32.bf16.bf16 {"
      "%0, %1, %2, %3, %4, %5, %6, %7, %8, %9, %10, %11, %12, %13, %14, %15, "
      "%16, %17, %18, %19, %20, %21, %22, %23"
      "}, {%24, %25, %26, %27}, %28, p, 1, 1, 0;\n}\n"
      : "+f"(d[0]), "+f"(d[1]), "+f"(d[2]), "+f"(d[3]), "+f"(d[4]), "+f"(d[5]), "+f"(d[6]), "+f"(d[7]),
        "+f"(d[8]), "+f"(d[9]), "+f"(d[10]), "+f"(d[11]), "+f"(d[12]), "+f"(d[13]), "+f"(d[14]), "+f"(d[15]),
        "+f"(d[16]), "+f"(d[17]), "+f"(d[18]), "+f"(d[19]), "+f"(d[20]), "+f"(d[21]), "+f"(d[22]), "+f"(d[23])
      : "r"(a[0]), "r"(a[1]), "r"(a[2]), "r"(a[3]), "l"(descB), "r"(scaleD));
}

__device__ __forceinline__ void mma_rs80_n(float (&d)[40], const uint32_t (&a)[4], uint64_t descB, int scaleD) {
  asm volatile("{\n.reg .pred p;\nsetp.ne.b32 p, %45, 0;\n"
      "wgmma.mma_async.sync.aligned.m64n80k16.f32.bf16.bf16 {"
      "%0, %1, %2, %3, %4, %5, %6, %7, %8, %9, %10, %11, %12, %13, %14, %15, "
      "%16, %17, %18, %19, %20, %21, %22, %23, %24, %25, %26, %27, %28, %29, %30, %31, "
      "%32, %33, %34, %35, %36, %37, %38, %39"
      "}, {%40, %41, %42, %43}, %44, p, 1, 1, 1;\n}\n"
      : "+f"(d[0]), "+f"(d[1]), "+f"(d[2]), "+f"(d[3]), "+f"(d[4]), "+f"(d[5]), "+f"(d[6]), "+f"(d[7]),
        "+f"(d[8]), "+f"(d[9]), "+f"(d[10]), "+f"(d[11]), "+f"(d[12]), "+f"(d[13]), "+f"(d[14]), "+f"(d[15]),
        "+f"(d[16]), "+f"(d[17]), "+f"(d[18]), "+f"(d[19]), "+f"(d[20]), "+f"(d[21]), "+f"(d[22]), "+f"(d[23]),
        "+f"(d[24]), "+f"(d[25]), "+f"(d[26]), "+f"(d[27]), "+f"(d[28]), "+f"(d[29]), "+f"(d[30]), "+f"(d[31]),
        "+f"(d[32]), "+f"(d[33]), "+f"(d[34]), "+f"(d[35]), "+f"(d[36]), "+f"(d[37]), "+f"(d[38]), "+f"(d[39])
      : "r"(a[0]), "r"(a[1]), "r"(a[2]), "r"(a[3]), "l"(descB), "r"(scaleD));
}

__device__ __forceinline__ void feature_map(const uint32_t (&P)[2][10], uint32_t (&fr)[10][4]) {
  constexpr float L2E = 1.4426950408889634f;
#pragma unroll
  for (int p = 0; p < 2; p++) {
#pragma unroll
    for (int r = 0; r < 2; r++) {
      uint32_t mx = P[r][5 * p], mn = mx;
#pragma unroll
      for (int g = 1; g < 5; g++) { mx = max_bf2(mx, P[r][5 * p + g]); mn = min_bf2(mn, P[r][5 * p + g]); }
      mx = max_bf2(mx, __shfl_xor_sync(0xffffffffu, mx, 1));
      mn = min_bf2(mn, __shfl_xor_sync(0xffffffffu, mn, 1));
      mx = max_bf2(mx, __shfl_xor_sync(0xffffffffu, mx, 2));
      mn = min_bf2(mn, __shfl_xor_sync(0xffffffffu, mn, 2));
      float mx0 = -bf_lo(mx) * L2E, mx1 = -bf_hi(mx) * L2E, mn0 = bf_lo(mn) * L2E, mn1 = bf_hi(mn) * L2E;
      float ep0[5], ep1[5], en0[5], en1[5];
      float sp0 = 0.f, sp1 = 0.f, sn0 = 0.f, sn1 = 0.f;
#pragma unroll
      for (int g = 0; g < 5; g++) {
        float x0 = bf_lo(P[r][5 * p + g]), x1 = bf_hi(P[r][5 * p + g]);
        ep0[g] = ex2(fmaf(x0, L2E, mx0)); ep1[g] = ex2(fmaf(x1, L2E, mx1));
        en0[g] = ex2(fmaf(x0, -L2E, mn0)); en1[g] = ex2(fmaf(x1, -L2E, mn1));
        sp0 += ep0[g]; sp1 += ep1[g]; sn0 += en0[g]; sn1 += en1[g];
      }
      sp0 += __shfl_xor_sync(0xffffffffu, sp0, 1); sp1 += __shfl_xor_sync(0xffffffffu, sp1, 1);
      sn0 += __shfl_xor_sync(0xffffffffu, sn0, 1); sn1 += __shfl_xor_sync(0xffffffffu, sn1, 1);
      sp0 += __shfl_xor_sync(0xffffffffu, sp0, 2); sp1 += __shfl_xor_sync(0xffffffffu, sp1, 2);
      sn0 += __shfl_xor_sync(0xffffffffu, sn0, 2); sn1 += __shfl_xor_sync(0xffffffffu, sn1, 2);
      sp0 = rcp(sp0); sp1 = rcp(sp1); sn0 = rcp(sn0); sn1 = rcp(sn1);
#pragma unroll
      for (int g = 0; g < 5; g++) {
        fr[5 * p + g][r] = pack_bf16(ep0[g] * sp0, ep1[g] * sp1);
        fr[5 * p + g][2 + r] = pack_bf16(en0[g] * sn0, en1[g] * sn1);
      }
    }
  }
}

struct Ring {
  uint32_t idx, phase;
  template <int N> __device__ __forceinline__ void next() { if (++idx == N) { idx = 0; phase ^= 1; } }
};

}

__global__ void __cluster_dims__(2, 1, 1) __launch_bounds__(384, 1)
fused_kernel(const __grid_constant__ Maps maps, const __nv_bfloat16* __restrict__ x, const __nv_bfloat16* __restrict__ wphi,
             const __nv_bfloat16* __restrict__ w1, const __nv_bfloat16* __restrict__ w2, const __nv_bfloat16* __restrict__ w3,
             const __nv_bfloat16* __restrict__ w4, const __nv_bfloat16* __restrict__ wo, const __nv_bfloat16* __restrict__ gate_w,
             __nv_bfloat16* __restrict__ out) {
  extern __shared__ uint8_t smem_raw[];
  const uint32_t sb = (smem_u32(smem_raw) + 1023u) & ~1023u;
  uint8_t* sgen = smem_raw + (sb - smem_u32(smem_raw));
  const uint32_t fullA = sb + OFF_BAR, emptyA = fullA + 8 * NA, fullB = emptyA + 8 * NA, emptyB = fullB + 8 * NB;
  volatile unsigned* s_epoch = reinterpret_cast<volatile unsigned*>(sgen + OFF_BAR + 128);

  const int tid = threadIdx.x;
  const int rank = blockIdx.x & 1;
  const int pairIdx = blockIdx.x >> 1;
  const int I = pairIdx >> 3, j = pairIdx & 7;
  const int i = 2 * I + rank;
  const int i2 = 2 * I + (j >> 2);
  const int j2 = 2 * (j & 3) + rank;

  TSTAMP(0);
  if (tid == 0) {
    for (int s = 0; s < NA; s++) { mbar_init(fullA + 8 * s, 1); mbar_init(emptyA + 8 * s, 4); }
    for (int s = 0; s < NB; s++) { mbar_init(fullB + 8 * s, 1); mbar_init(emptyB + 8 * s, 4); }
    asm volatile("fence.mbarrier_init.release.cluster;" ::: "memory");
    *s_epoch = ld_acquire(g_flags + FL_DONE * 32) / NCTA;
  }
  if (tid == 256) { prefetch_tmap(&maps.x); }
  if (tid == 288) { prefetch_tmap(&maps.w1m); prefetch_tmap(&maps.qm); prefetch_tmap(&maps.w1r); prefetch_tmap(&maps.qr); }
  __syncthreads();
  asm volatile("barrier.cluster.arrive.aligned;\nbarrier.cluster.wait.aligned;" ::: "memory");
  const unsigned epoch = *s_epoch;

  if (tid >= 256) {
    asm volatile("setmaxnreg.dec.sync.aligned.u32 40;");
    if (tid == 256) {
      Ring r{0, 1};
      for (int k = 0; k < 10; k++) {
        mbar_wait(emptyA + 8 * r.idx, r.phase);
        mbar_expect_tx(fullA + 8 * r.idx, SLOT_A);
        tma2d(sb + OFF_A + r.idx * SLOT_A, &maps.x, fullA + 8 * r.idx, 64 * k, 128 * i);
        r.next<NA>();
      }
      prefetch_tmap(&maps.hs); prefetch_tmap(&maps.x1);
      const unsigned tgt = (epoch + 1) * 64u;
      if (i2 > 0) flag_wait(FL_H + i2 - 1, tgt);
      if (i2 < 15) flag_wait(FL_H + i2 + 1, tgt);
      flag_wait(FL_H + i2, tgt);
      fence_async_all();
      for (int k = 0; k < 10; k++) {
        mbar_wait(emptyA + 8 * r.idx, r.phase);
        mbar_expect_tx(fullA + 8 * r.idx, SLOT_A);
        tma2d_mc(sb + OFF_A + r.idx * SLOT_A + rank * 8192, &maps.hs, fullA + 8 * r.idx, 64 * k, 128 * i2 + 64 * rank);
        r.next<NA>();
      }
      flag_wait(FL_X1 + i, tgt);
      fence_async_all();
      for (int k = 0; k < 10; k++) {
        mbar_wait(emptyA + 8 * r.idx, r.phase);
        mbar_expect_tx(fullA + 8 * r.idx, SLOT_A);
        tma2d(sb + OFF_A + r.idx * SLOT_A, &maps.x1, fullA + 8 * r.idx, 64 * k, 128 * i);
        r.next<NA>();
      }
    } else if (tid == 288) {
      Ring r{0, 1};
      for (int k = 0; k < 10; k++) {
        mbar_wait(emptyB + 8 * r.idx, r.phase);
        const uint32_t bar = fullB + 8 * r.idx, slot = sb + OFF_B + r.idx * SLOT_B;
        mbar_expect_tx(bar, 40960);
        const int k0 = 64 * k + 32 * rank;
        tma4d_mc(slot + rank * 16384 + 4096, &maps.qm, bar, 0, k0, 0, j);
        tma3d_mc(slot + rank * 16384, &maps.w1m, bar, 0, k0, j);
        tma4d_mc(slot + 32768 + rank * 4096 + 1024, &maps.qr, bar, 64, k0, 0, j);
        tma3d_mc(slot + 32768 + rank * 4096, &maps.w1r, bar, 64, k0, j);
        r.next<NB>();
        if (k == 2) { prefetch_tmap(&maps.w2); prefetch_tmap(&maps.w3); prefetch_tmap(&maps.w4); prefetch_tmap(&maps.wo); }
      }
      for (int s = 0; s < 3; s++) {
        mbar_wait(emptyB + 8 * r.idx, r.phase);
        const uint32_t bar = fullB + 8 * r.idx, slot = sb + OFF_B + r.idx * SLOT_B;
        mbar_expect_tx(bar, s < 2 ? 40960 : 20480);
        tma3d(slot, &maps.w2, bar, 0, 256 * s, 5 * j2);
        if (s < 2) tma3d(slot + 20480, &maps.w2, bar, 0, 256 * s + 128, 5 * j2);
        r.next<NB>();
      }
      for (int s = 0; s < 5; s++) {
        mbar_wait(emptyB + 8 * r.idx, r.phase);
        const uint32_t bar = fullB + 8 * r.idx, slot = sb + OFF_B + r.idx * SLOT_B;
        mbar_expect_tx(bar, 49152);
        tma3d_mc(slot + rank * 24576, &maps.w3, bar, 0, 128 * s + 64 * rank, 3 * j);
        r.next<NB>();
      }
      for (int c = 0; c < 8; c++) {
        const int d = (j + 1 + c) & 7;
        mbar_wait(emptyB + 8 * r.idx, r.phase);
        const uint32_t bar = fullB + 8 * r.idx, slot = sb + OFF_B + r.idx * SLOT_B;
        mbar_expect_tx(bar, 43520);
        if (rank == 0) {
          tma3d_mc(slot, &maps.w4, bar, 0, 192 * j, 5 * d);
          tma3d_mc(slot + 30720, &maps.wo, bar, 0, 80 * j, 5 * d);
        } else {
          tma3d_mc(slot + 10240, &maps.w4, bar, 0, 192 * j + 64, 5 * d);
          tma3d_mc(slot + 20480, &maps.w4, bar, 0, 192 * j + 128, 5 * d);
        }
        r.next<NB>();
      }
    } else if (tid >= 320 && tid < 352) {
      const int lane = tid & 31;
      float* nxt = g_kv[(epoch + 1) & 1];
      constexpr int PER = 8 * KV_J / NCTA;
      for (int e = lane; e < PER; e += 32) nxt[blockIdx.x * PER + e] = 0.f;
      if (lane == 0) {
        l2_prefetch(w2 + (size_t)blockIdx.x * (D_ * D_ / NCTA), D_ * D_ * 2 / NCTA);
        l2_prefetch(w4 + (size_t)blockIdx.x * (F_ * D_ / NCTA), F_ * D_ * 2 / NCTA);
        l2_prefetch(wo + (size_t)blockIdx.x * (D_ * D_ / NCTA), D_ * D_ * 2 / NCTA);
      }
    }
    __syncwarp();
    asm volatile("barrier.cluster.arrive;\nbarrier.cluster.wait;" ::: "memory");
  } else {
    asm volatile("setmaxnreg.inc.sync.aligned.u32 232;");
    const int wg = tid >> 7, warp = tid >> 5, lane = tid & 31, t = lane & 3;
    const int rloc = warp * 16 + (lane >> 2);
    float* s_cs = reinterpret_cast<float*>(sgen + OFF_CS);

    {
      const int unit = warp == 0 ? (int)blockIdx.x : (warp == 1 && blockIdx.x < 8 ? 128 + (int)blockIdx.x : -1);
      if (unit >= 0) {
        const __nv_bfloat16* src = unit < 40 ? w1 + unit * 16 : w3 + (unit - 40) * 16;
        const int ld = unit < 40 ? D_ : F_;
        float a[8];
#pragma unroll
        for (int e = 0; e < 8; e++) a[e] = 0.f;
        const __nv_bfloat16* p = src + (size_t)(lane >> 1) * ld + (lane & 1) * 8;
#pragma unroll 20
        for (int it = 0; it < 40; it++) {
          uint4 v = __ldg(reinterpret_cast<const uint4*>(p + (size_t)it * 16 * ld));
          a[0] += bf_lo(v.x); a[1] += bf_hi(v.x); a[2] += bf_lo(v.y); a[3] += bf_hi(v.y);
          a[4] += bf_lo(v.z); a[5] += bf_hi(v.z); a[6] += bf_lo(v.w); a[7] += bf_hi(v.w);
        }
#pragma unroll
        for (int e = 0; e < 8; e++) {
#pragma unroll
          for (int o = 2; o < 32; o <<= 1) a[e] += __shfl_xor_sync(0xffffffffu, a[e], o);
        }
        if (lane < 2) {
          float4* dst = reinterpret_cast<float4*>(g_cs + unit * 16 + lane * 8);
          dst[0] = make_float4(a[0], a[1], a[2], a[3]);
          dst[1] = make_float4(a[4], a[5], a[6], a[7]);
        }
      }
      if (warp >= 2 && warp < 6) {
        const int row = blockIdx.x * 16 + (warp - 2) * 4 + (lane >> 3);
        const int l8 = lane & 7;
        uint4 v[10];
#pragma unroll
        for (int c = 0; c < 10; c++) v[c] = __ldg(reinterpret_cast<const uint4*>(x + (size_t)row * D_ + c * 64 + l8 * 8));
        float s = 0.f, gs = 0.f;
#pragma unroll
        for (int c = 0; c < 10; c++) {
          uint4 w = __ldg(reinterpret_cast<const uint4*>(gate_w + c * 64 + l8 * 8));
          s += (bf_lo(v[c].x) + bf_hi(v[c].x)) + (bf_lo(v[c].y) + bf_hi(v[c].y)) + (bf_lo(v[c].z) + bf_hi(v[c].z)) + (bf_lo(v[c].w) + bf_hi(v[c].w));
          gs = fmaf(bf_lo(v[c].x), bf_lo(w.x), gs); gs = fmaf(bf_hi(v[c].x), bf_hi(w.x), gs);
          gs = fmaf(bf_lo(v[c].y), bf_lo(w.y), gs); gs = fmaf(bf_hi(v[c].y), bf_hi(w.y), gs);
          gs = fmaf(bf_lo(v[c].z), bf_lo(w.z), gs); gs = fmaf(bf_hi(v[c].z), bf_hi(w.z), gs);
          gs = fmaf(bf_lo(v[c].w), bf_lo(w.w), gs); gs = fmaf(bf_hi(v[c].w), bf_hi(w.w), gs);
        }
#pragma unroll
        for (int o = 1; o < 8; o <<= 1) { s += __shfl_xor_sync(0xffffffffu, s, o); gs += __shfl_xor_sync(0xffffffffu, gs, o); }
        const float mean = s * (1.f / D_);
        float q = 0.f;
#pragma unroll
        for (int c = 0; c < 10; c++) {
          float d;
          d = bf_lo(v[c].x) - mean; q = fmaf(d, d, q); d = bf_hi(v[c].x) - mean; q = fmaf(d, d, q);
          d = bf_lo(v[c].y) - mean; q = fmaf(d, d, q); d = bf_hi(v[c].y) - mean; q = fmaf(d, d, q);
          d = bf_lo(v[c].z) - mean; q = fmaf(d, d, q); d = bf_hi(v[c].z) - mean; q = fmaf(d, d, q);
          d = bf_lo(v[c].w) - mean; q = fmaf(d, d, q); d = bf_hi(v[c].w) - mean; q = fmaf(d, d, q);
        }
#pragma unroll
        for (int o = 1; o < 8; o <<= 1) q += __shfl_xor_sync(0xffffffffu, q, o);
        if (l8 == 0) g_xstat[row] = make_float4(mean, rsqrtf(q * (1.f / D_) + 1e-5f), 1.f / (1.f + __expf(-gs)), 0.f);
      }
      if (warp >= 6 || warp == 1) {
        const int tt = (warp == 1 ? 0 : warp - 5) * 32 + lane;
        for (int it = tt; it < 800; it += 96) {
          const int s = it / 160, rem = it - s * 160, n = rem >> 1, half = rem & 1;
          const int p = n / 40, nn = n - 40 * p, g = nn >> 3, tq = (nn >> 1) & 3, e = nn & 1;
          const int h = 2 * p + e, f = 4 * g + tq;
          uint32_t w[4];
#pragma unroll
          for (int q2 = 0; q2 < 4; q2++) {
            uint32_t lo = 0, hi = 0;
            const int k = 16 * s + 8 * half + 2 * q2;
            const int d = k - 20 * h;
            if (d >= 0 && d < 20) {
              const unsigned short* wp = reinterpret_cast<const unsigned short*>(wphi) + (size_t)(4 * j + h) * 400 + d * 20 + f;
              lo = __ldg(wp); hi = __ldg(wp + 20);
            }
            w[q2] = lo | (hi << 16);
          }
          *reinterpret_cast<uint4*>(sgen + OFF_MISC + s * 2560 + n * 32 + ((half ^ ((n >> 2) & 1)) << 4)) = make_uint4(w[0], w[1], w[2], w[3]);
        }
        fence_async_smem();
      }
      __syncwarp();
      if (lane == 0) flag_add(FL_PREP);
    }
    TSTAMP(1);

    auto release = [&](uint32_t bar) {
      if ((tid & 127) < 2) mbar_arrive_cta(bar, tid & 1);
    };

    Ring ra{0, 0}, rb{0, 0};
    uint32_t qp[2][10];
    float st_mean[2], st_rstd[2], st_g[2];
    {
      float accM[128], accR[32];
      uint32_t pa = 0, pb = 0;
      for (int k = 0; k < 10; k++) {
        mbar_wait(fullA + 8 * ra.idx, ra.phase);
        mbar_wait(fullB + 8 * rb.idx, rb.phase);
        if (k == 0) TSTAMP(2);
        const uint32_t a0 = sb + OFF_A + ra.idx * SLOT_A + wg * 8192, b0 = sb + OFF_B + rb.idx * SLOT_B;
        wg_fence();
#pragma unroll
        for (int kk = 0; kk < 4; kk++) {
          const uint64_t da = make_desc(a0 + kk * 32, 16, 1024, 1);
          const uint64_t dm = make_desc(b0 + (kk >> 1) * 16384 + (kk & 1) * 2048, 4096, 1024, 1);
          const uint64_t dr = make_desc(b0 + 32768 + (kk >> 1) * 4096 + (kk & 1) * 512, 1024, 256, 3);
          mma_ss256(accM, da, dm, (k | kk) != 0);
          mma_ss64(accR, da, dr, (k | kk) != 0);
        }
        wg_commit();
        if (k > 0) {
          wg_wait<1>();
          if (k - 1 < 8) release(emptyA + 8 * pa);
          release(emptyB + 8 * pb);
        }
        pa = ra.idx; pb = rb.idx;
        ra.next<NA>(); rb.next<NB>();
      }
      wg_wait<0>();
      fence_regs(accM); fence_regs(accR);
      TSTAMP(3);
#define ACC(P, G, I) ((G) < 8 ? accM[(P) * 32 + ((G) & 7) * 4 + (I)] : accR[(P) * 8 + ((G) & 1) * 4 + (I)])
      {
        const int mat = lane >> 3;
        const int tok = warp * 16 + (mat & 1) * 8 + (lane & 7);
        const uint32_t ones = (t == 0) ? 0x00003f80u : 0u;
#pragma unroll
        for (int p = 0; p < 2; p++) {
          const uint32_t rowa = sb + OFF_A + p * SLOT_A + tok * 128;
#pragma unroll
          for (int gg = 0; gg < 3; gg++) {
            const int g0 = 5 * p + 2 * gg;
            uint32_t r0 = pack_bf16(ACC(3, g0, 0), ACC(3, g0, 1)), r1 = pack_bf16(ACC(3, g0, 2), ACC(3, g0, 3));
            uint32_t r2 = ones, r3 = ones;
            if (gg < 2) { r2 = pack_bf16(ACC(3, g0 + 1, 0), ACC(3, g0 + 1, 1)); r3 = pack_bf16(ACC(3, g0 + 1, 2), ACC(3, g0 + 1, 3)); }
            stsm4(rowa + (((2 * gg + (mat >> 1)) ^ (tok & 7)) << 4), r0, r1, r2, r3);
          }
        }
      }
      uint32_t kf[5][4], qf[5][4];
#pragma unroll
      for (int s = 0; s < 5; s++) {
        kf[s][0] = pack_bf16(ACC(2, 2 * s, 0), ACC(2, 2 * s, 1)); kf[s][1] = pack_bf16(ACC(2, 2 * s, 2), ACC(2, 2 * s, 3));
        kf[s][2] = pack_bf16(ACC(2, 2 * s + 1, 0), ACC(2, 2 * s + 1, 1)); kf[s][3] = pack_bf16(ACC(2, 2 * s + 1, 2), ACC(2, 2 * s + 1, 3));
        qf[s][0] = pack_bf16(ACC(1, 2 * s, 0), ACC(1, 2 * s, 1)); qf[s][1] = pack_bf16(ACC(1, 2 * s, 2), ACC(1, 2 * s, 3));
        qf[s][2] = pack_bf16(ACC(1, 2 * s + 1, 0), ACC(1, 2 * s + 1, 1)); qf[s][3] = pack_bf16(ACC(1, 2 * s + 1, 2), ACC(1, 2 * s + 1, 3));
      }
      bar_sync(1, 256);
      float pk[40], pq[40];
      wg_fence();
#pragma unroll
      for (int s = 0; s < 5; s++) mma_rs80_k(pk, kf[s], make_desc(sb + OFF_MISC + s * 2560, 16, 256, 3), s != 0);
#pragma unroll
      for (int s = 0; s < 5; s++) mma_rs80_k(pq, qf[s], make_desc(sb + OFF_MISC + s * 2560, 16, 256, 3), s != 0);
      wg_commit();

      if (lane == 0) flag_wait(FL_PREP, (epoch + 1) * (NCTA * 8u));
      __syncwarp();
      {
#pragma unroll
        for (int r = 0; r < 2; r++) {
          float4 st = __ldcg(&g_xstat[128 * i + rloc + 8 * r]);
          st_mean[r] = st.x; st_rstd[r] = st.y; st_g[r] = st.z;
        }
        const int shift = (j < 2) ? 1 : (j < 4) ? -1 : (j < 6) ? 2 : -2;
        const int row0 = 128 * i + rloc + shift, row1 = row0 + 8;
        const bool ok0 = (unsigned)row0 < (unsigned)S_, ok1 = (unsigned)row1 < (unsigned)S_;
        uint32_t* h0 = reinterpret_cast<uint32_t*>(g_Hs + (size_t)row0 * D_ + 80 * j + 2 * t);
        uint32_t* h1 = h0 + 8 * (D_ / 2);
        const float m0 = -st_mean[0] * st_rstd[0], m1 = -st_mean[1] * st_rstd[1];
#pragma unroll
        for (int g = 0; g < 10; g++) {
          const float2 cs = __ldcg(reinterpret_cast<const float2*>(g_cs + 80 * j + 8 * g + 2 * t));
          float v0 = gelu_s(fmaf(ACC(0, g, 0), st_rstd[0], m0 * cs.x), 0.5f), v1 = gelu_s(fmaf(ACC(0, g, 1), st_rstd[0], m0 * cs.y), 0.5f);
          float v2 = gelu_s(fmaf(ACC(0, g, 2), st_rstd[1], m1 * cs.x), 0.5f), v3 = gelu_s(fmaf(ACC(0, g, 3), st_rstd[1], m1 * cs.y), 0.5f);
          if (ok0) h0[4 * g] = pack_bf16(v0, v1);
          if (ok1) h1[4 * g] = pack_bf16(v2, v3);
        }
        if ((shift > 0 && i == 0 && warp == 0) || (shift < 0 && i == 15 && warp == 7)) {
          const int nz = shift > 0 ? shift : -shift;
          const int zr = shift > 0 ? 0 : S_ - nz;
          for (int e = lane; e < nz * 40; e += 32)
            reinterpret_cast<uint32_t*>(g_Hs + (size_t)(zr + e / 40) * D_ + 80 * j)[e % 40] = 0u;
        }
        fence_async_all();
        __syncwarp();
        if (lane == 0) flag_add(FL_H + i);
        if (tid < 48) reinterpret_cast<float4*>(s_cs)[tid] = __ldcg(reinterpret_cast<const float4*>(g_cs + D_ + 192 * j) + tid);
      }
#undef ACC
      TSTAMP(4);
      wg_wait<0>();
      fence_regs(pk); fence_regs(pq);
      uint32_t kp[2][10];
#pragma unroll
      for (int G = 0; G < 10; G++) {
        kp[0][G] = pack_bf16(pk[4 * G], pk[4 * G + 1]); kp[1][G] = pack_bf16(pk[4 * G + 2], pk[4 * G + 3]);
        qp[0][G] = pack_bf16(pq[4 * G], pq[4 * G + 1]); qp[1][G] = pack_bf16(pq[4 * G + 2], pq[4 * G + 3]);
      }
      uint32_t fr[10][4];
      feature_map(kp, fr);
      {
        const int mat = lane >> 3;
        const int tok = warp * 16 + (mat & 1) * 8 + (lane & 7);
        const uint32_t base = sb + OFF_B + tok * 32 + (((mat >> 1) ^ ((tok >> 2) & 1)) << 4);
#pragma unroll
        for (int G = 0; G < 10; G++) stsm4(base + G * 4096, fr[G][0], fr[G][1], fr[G][2], fr[G][3]);
      }
      fence_async_smem();
      bar_sync(1, 256);
      float kv[40];
      wg_fence();
#pragma unroll
      for (int ks = 0; ks < 8; ks++)
        mma_ss80_tt(kv, make_desc(sb + OFF_A + wg * SLOT_A + ks * 2048, 16, 1024, 1),
                    make_desc(sb + OFF_B + wg * 20480 + ks * 512, 4096, 256, 3), ks != 0);
      wg_commit();
      wg_wait<0>();
      fence_regs(kv);
      release(emptyA); release(emptyA + 8); release(emptyB);
      {
        float* dst = g_kv[epoch & 1] + j * KV_J + wg * KV_PAIR;
        const int m0 = (warp & 3) * 16 + (lane >> 2);
#pragma unroll
        for (int r = 0; r < 2; r++) {
          const int m = m0 + 8 * r;
          if (m < 40) {
            const bool hi = m >= 20;
            float v[10];
#pragma unroll
            for (int G = 0; G < 10; G++) v[G] = hi ? kv[4 * G + 2 * r + 1] : kv[4 * G + 2 * r];
            float* p = dst + m * 48 + t * 12;
            red_add4(p, v[0], v[1], v[2], v[3]); red_add4(p + 4, v[4], v[5], v[6], v[7]); red_add2(p + 8, v[8], v[9]);
          } else if (m == 40) {
#pragma unroll
            for (int e = 0; e < 2; e++) {
              float* p = dst + 1920 + t * 24 + e * 12;
              red_add4(p, kv[2 * r + e], kv[4 + 2 * r + e], kv[8 + 2 * r + e], kv[12 + 2 * r + e]);
              red_add4(p + 4, kv[16 + 2 * r + e], kv[20 + 2 * r + e], kv[24 + 2 * r + e], kv[28 + 2 * r + e]);
              red_add2(p + 8, kv[32 + 2 * r + e], kv[36 + 2 * r + e]);
            }
          }
        }
        __syncwarp();
        if (lane == 0) flag_add(FL_KV + j);
      }
    }
    TSTAMP(5);

    {
      uint32_t xv[2][10];
      {
        const uint32_t* xp = reinterpret_cast<const uint32_t*>(x + (size_t)(128 * i2 + rloc) * D_ + 80 * j2 + 2 * t);
#pragma unroll
        for (int g = 0; g < 10; g++) { xv[0][g] = __ldg(xp + 4 * g); xv[1][g] = __ldg(xp + 8 * (D_ / 2) + 4 * g); }
      }
      float acc[40];
      uint32_t pa = 0, pb = 0;
      for (int k = 0; k < 10; k++) {
        mbar_wait(fullA + 8 * ra.idx, ra.phase);
        if ((k & 3) == 0) mbar_wait(fullB + 8 * rb.idx, rb.phase);
        if (k == 0) TSTAMP(6);
        const uint32_t a0 = sb + OFF_A + ra.idx * SLOT_A + wg * 8192;
        const uint32_t b0 = sb + OFF_B + rb.idx * SLOT_B + ((k >> 1) & 1) * 20480 + (k & 1) * 2048;
        wg_fence();
#pragma unroll
        for (int kk = 0; kk < 4; kk++)
          mma_ss80(acc, make_desc(a0 + kk * 32, 16, 1024, 1), make_desc(b0 + kk * 512, 4096, 256, 3), (k | kk) != 0);
        wg_commit();
        if (k > 0) {
          wg_wait<1>();
          release(emptyA + 8 * pa);
          if ((k & 3) == 0) release(emptyB + 8 * pb);
        }
        pa = ra.idx; pb = rb.idx;
        ra.next<NA>();
        if ((k & 3) == 3 || k == 9) rb.next<NB>();
      }
      wg_wait<0>();
      fence_regs(acc);
      release(emptyA + 8 * pa); release(emptyB + 8 * pb);
      TSTAMP(7);
      uint32_t* xo = reinterpret_cast<uint32_t*>(g_X1 + (size_t)(128 * i2 + rloc) * D_ + 80 * j2 + 2 * t);
#pragma unroll
      for (int r = 0; r < 2; r++) {
        float s = 0.f;
#pragma unroll
        for (int g = 0; g < 10; g++) {
          const uint32_t v = pack_bf16(bf_lo(xv[r][g]) + acc[4 * g + 2 * r], bf_hi(xv[r][g]) + acc[4 * g + 2 * r + 1]);
          xv[r][g] = v;
          xo[r * 8 * (D_ / 2) + 4 * g] = v;
          s += bf_lo(v) + bf_hi(v);
        }
        s += __shfl_xor_sync(0xffffffffu, s, 1); s += __shfl_xor_sync(0xffffffffu, s, 2);
        const float mu = s * (1.f / 80.f);
        float q = 0.f;
#pragma unroll
        for (int g = 0; g < 10; g++) {
          const float d0 = bf_lo(xv[r][g]) - mu, d1 = bf_hi(xv[r][g]) - mu;
          q = fmaf(d0, d0, q); q = fmaf(d1, d1, q);
        }
        q += __shfl_xor_sync(0xffffffffu, q, 1); q += __shfl_xor_sync(0xffffffffu, q, 2);
        if (t == 0) g_st1[(128 * i2 + rloc + 8 * r) * 8 + j2] = make_float2(mu, q);
      }
      fence_async_all();
      __syncwarp();
      if (lane == 0) flag_add(FL_X1 + i2);
    }
    TSTAMP(8);

    uint32_t of[5][4];
    {
      uint32_t fr[10][4];
      feature_map(qp, fr);
      if (lane == 0) flag_wait(FL_KV + j, (epoch + 1) * 128u);
      __syncwarp();
      const float* src = g_kv[epoch & 1] + j * KV_J;
      for (int it = tid; it < 384; it += 256) {
        const int p = it / 192, rem = it - 192 * p, n = rem >> 2, tq = rem & 3;
        const int e = n < 40 ? (n >= 20) : (n & 1);
        const float4* sp = reinterpret_cast<const float4*>(src + p * KV_PAIR + (n < 40 ? n * 48 + tq * 12 : 1920 + tq * 24 + e * 12));
        const float4 a = __ldcg(sp), b = __ldcg(sp + 1), c = __ldcg(sp + 2);
        const float v[10] = {a.x, a.y, a.z, a.w, b.x, b.y, b.z, b.w, c.x, c.y};
        uint8_t* dst = sgen + OFF_MISC + p * 7680 + n * 32 + tq * 4;
        const int sw = (n >> 2) & 1;
#pragma unroll
        for (int G = 0; G < 10; G++) {
          const uint32_t w = e ? pack_bf16(0.f, v[G]) : pack_bf16(v[G], 0.f);
          *reinterpret_cast<uint32_t*>(dst + (G >> 1) * 1536 + (((G & 1) ^ sw) << 4)) = w;
        }
      }
      fence_async_smem();
      bar_sync(1, 256);
      float o0[24], o1[24];
      wg_fence();
#pragma unroll
      for (int g = 0; g < 5; g++) mma_rs48_k(o0, fr[g], make_desc(sb + OFF_MISC + g * 1536, 16, 256, 3), g != 0);
#pragma unroll
      for (int g = 0; g < 5; g++) mma_rs48_k(o1, fr[5 + g], make_desc(sb + OFF_MISC + 7680 + g * 1536, 16, 256, 3), g != 0);
      wg_commit();
      wg_wait<0>();
      fence_regs(o0); fence_regs(o1);
      uint32_t ob[10][2];
#pragma unroll
      for (int r = 0; r < 2; r++) {
        const float a0 = st_g[r] / (o0[20 + 2 * r] + 1e-6f), a1 = st_g[r] / (o0[21 + 2 * r] + 1e-6f);
        const float b0 = st_g[r] / (o1[20 + 2 * r] + 1e-6f), b1 = st_g[r] / (o1[21 + 2 * r] + 1e-6f);
        const float am = t < 2 ? a0 : a1, bm = t < 2 ? b0 : b1;
#pragma unroll
        for (int g = 0; g < 5; g++) {
          const float sa = g < 2 ? a0 : (g == 2 ? am : a1), sb2 = g < 2 ? b0 : (g == 2 ? bm : b1);
          ob[g][r] = pack_bf16(o0[4 * g + 2 * r] * sa, o0[4 * g + 2 * r + 1] * sa);
          ob[5 + g][r] = pack_bf16(o1[4 * g + 2 * r] * sb2, o1[4 * g + 2 * r + 1] * sb2);
        }
      }
#pragma unroll
      for (int s = 0; s < 5; s++) { of[s][0] = ob[2 * s][0]; of[s][1] = ob[2 * s][1]; of[s][2] = ob[2 * s + 1][0]; of[s][3] = ob[2 * s + 1][1]; }
    }
    TSTAMP(9);

    uint32_t hf[12][4];
    {
      float acc[96];
      uint32_t pa = 0, pb = 0;
      for (int k = 0; k < 10; k++) {
        mbar_wait(fullA + 8 * ra.idx, ra.phase);
        if ((k & 1) == 0) mbar_wait(fullB + 8 * rb.idx, rb.phase);
        if (k == 0) TSTAMP(10);
        const uint32_t a0 = sb + OFF_A + ra.idx * SLOT_A + wg * 8192;
        const uint32_t b0 = sb + OFF_B + rb.idx * SLOT_B + (k & 1) * 24576;
        wg_fence();
#pragma unroll
        for (int kk = 0; kk < 4; kk++)
          mma_ss192(acc, make_desc(a0 + kk * 32, 16, 1024, 1), make_desc(b0 + kk * 2048, 8192, 1024, 1), (k | kk) != 0);
        wg_commit();
        if (k > 0) {
          wg_wait<1>();
          release(emptyA + 8 * pa);
          if ((k & 1) == 0) release(emptyB + 8 * pb);
        }
        pa = ra.idx; pb = rb.idx;
        ra.next<NA>();
        if (k & 1) rb.next<NB>();
      }
      if (lane == 0) flag_wait(FL_X1 + i, (epoch + 1) * 64u);
      __syncwarp();
      float rs[2], mm[2];
#pragma unroll
      for (int r = 0; r < 2; r++) {
        const float4 sv = __ldcg(reinterpret_cast<const float4*>(g_st1 + (128 * i + rloc + 8 * r) * 8) + t);
        float mu = sv.x + sv.z;
        mu += __shfl_xor_sync(0xffffffffu, mu, 1); mu += __shfl_xor_sync(0xffffffffu, mu, 2);
        mu *= 0.125f;
        const float d0 = sv.x - mu, d1 = sv.z - mu;
        float q = sv.y + sv.w + 80.f * (d0 * d0 + d1 * d1);
        q += __shfl_xor_sync(0xffffffffu, q, 1); q += __shfl_xor_sync(0xffffffffu, q, 2);
        rs[r] = rsqrtf(q * (1.f / D_) + 1e-5f);
        mm[r] = -mu * rs[r];
      }
      wg_wait<0>();
      fence_regs(acc);
      release(emptyB + 8 * pb);
      TSTAMP(11);
      const float hs0 = 0.5f * (1.f - st_g[0]), hs1 = 0.5f * (1.f - st_g[1]);
#pragma unroll
      for (int g = 0; g < 24; g++) {
        const float2 cs = *reinterpret_cast<const float2*>(s_cs + 8 * g + 2 * t);
        const float v0 = gelu_s(fmaf(acc[4 * g], rs[0], mm[0] * cs.x), hs0), v1 = gelu_s(fmaf(acc[4 * g + 1], rs[0], mm[0] * cs.y), hs0);
        const float v2 = gelu_s(fmaf(acc[4 * g + 2], rs[1], mm[1] * cs.x), hs1), v3 = gelu_s(fmaf(acc[4 * g + 3], rs[1], mm[1] * cs.y), hs1);
        hf[g >> 1][(g & 1) * 2] = pack_bf16(v0, v1);
        hf[g >> 1][(g & 1) * 2 + 1] = pack_bf16(v2, v3);
      }
    }
    TSTAMP(12);

    {
      float accA[40], accB[40];
      auto issue = [&](float (&acc)[40]) {
        mbar_wait(fullB + 8 * rb.idx, rb.phase);
        const uint32_t b0 = sb + OFF_B + rb.idx * SLOT_B;
        wg_fence();
#pragma unroll
        for (int s = 0; s < 12; s++)
          mma_rs80_n(acc, hf[s], make_desc(b0 + (s >> 2) * 10240 + (s & 3) * 512, 2048, 256, 3), s != 0);
#pragma unroll
        for (int s = 0; s < 5; s++)
          mma_rs80_n(acc, of[s], make_desc(b0 + 30720 + s * 512, 2560, 256, 3), 1);
        wg_commit();
        rb.next<NB>();
      };
      auto send = [&](float (&acc)[40], int c) {
        const int d = (j + 1 + c) & 7;
        uint4* dst = g_part + (size_t)(((i * 8 + d) * 8 + j) * 5) * 256 + tid;
#pragma unroll
        for (int q = 0; q < 5; q++)
          dst[q * 256] = make_uint4(pack_bf16(acc[8 * q], acc[8 * q + 1]), pack_bf16(acc[8 * q + 2], acc[8 * q + 3]),
                                    pack_bf16(acc[8 * q + 4], acc[8 * q + 5]), pack_bf16(acc[8 * q + 6], acc[8 * q + 7]));
        __syncwarp();
        if (lane == 0) flag_add(FL_PART + (i * 8 + d) * 8 + warp);
      };
      uint32_t slot = rb.idx;
      issue(accA);
#pragma unroll 1
      for (int c = 0; c < 6; c += 2) {
        uint32_t nslot = rb.idx;
        issue(accB);
        wg_wait<1>(); fence_regs(accA);
        release(emptyB + 8 * slot); slot = nslot;
        send(accA, c);
        nslot = rb.idx;
        issue(accA);
        wg_wait<1>(); fence_regs(accB);
        release(emptyB + 8 * slot); slot = nslot;
        send(accB, c + 1);
      }
      issue(accB);
      wg_wait<1>(); fence_regs(accA);
      send(accA, 6);
      TSTAMP(13);
      uint32_t xv[2][10];
      {
        const uint32_t* xp = reinterpret_cast<const uint32_t*>(g_X1 + (size_t)(128 * i + rloc) * D_ + 80 * j + 2 * t);
#pragma unroll
        for (int g = 0; g < 10; g++) { xv[0][g] = __ldcg(xp + 4 * g); xv[1][g] = __ldcg(xp + 8 * (D_ / 2) + 4 * g); }
      }
      if (lane == 0) flag_wait(FL_PART + (i * 8 + j) * 8 + warp, (epoch + 1) * 7u);
      __syncwarp();
      TSTAMP(14);
      const float w0 = 1.f - st_g[0], w1s = 1.f - st_g[1];
#pragma unroll
      for (int g = 0; g < 10; g++) {
        accA[4 * g] = w0 * bf_lo(xv[0][g]); accA[4 * g + 1] = w0 * bf_hi(xv[0][g]);
        accA[4 * g + 2] = w1s * bf_lo(xv[1][g]); accA[4 * g + 3] = w1s * bf_hi(xv[1][g]);
      }
#pragma unroll
      for (int c = 1; c < 8; c++) {
        const int src = (j + c) & 7;
        const uint4* sp = g_part + (size_t)(((i * 8 + j) * 8 + src) * 5) * 256 + tid;
#pragma unroll
        for (int q = 0; q < 5; q++) {
          const uint4 v = __ldcg(sp + q * 256);
          accA[8 * q] += bf_lo(v.x); accA[8 * q + 1] += bf_hi(v.x); accA[8 * q + 2] += bf_lo(v.y); accA[8 * q + 3] += bf_hi(v.y);
          accA[8 * q + 4] += bf_lo(v.z); accA[8 * q + 5] += bf_hi(v.z); accA[8 * q + 6] += bf_lo(v.w); accA[8 * q + 7] += bf_hi(v.w);
        }
      }
      wg_wait<0>(); fence_regs(accB);
      uint32_t* op = reinterpret_cast<uint32_t*>(out + (size_t)(128 * i + rloc) * D_ + 80 * j + 2 * t);
#pragma unroll
      for (int g = 0; g < 10; g++) {
        op[4 * g] = pack_bf16(accA[4 * g] + accB[4 * g], accA[4 * g + 1] + accB[4 * g + 1]);
        op[8 * (D_ / 2) + 4 * g] = pack_bf16(accA[4 * g + 2] + accB[4 * g + 2], accA[4 * g + 3] + accB[4 * g + 3]);
      }
    }
    TSTAMP(15);
    if (tid == 0) flag_add(FL_DONE);
    asm volatile("barrier.cluster.arrive;\nbarrier.cluster.wait;" ::: "memory");
  }
}

namespace {
typedef CUresult (*EncodeFn)(CUtensorMap*, CUtensorMapDataType, cuuint32_t, void*, const cuuint64_t*, const cuuint64_t*,
                             const cuuint32_t*, const cuuint32_t*, CUtensorMapInterleave, CUtensorMapSwizzle,
                             CUtensorMapL2promotion, CUtensorMapFloatOOBfill);

void encode(EncodeFn fn, CUtensorMap* m, const void* ptr, int rank, const cuuint64_t* dims, const cuuint64_t* strides,
            const cuuint32_t* box, CUtensorMapSwizzle swz) {
  cuuint32_t es[5] = {1, 1, 1, 1, 1};
  fn(m, CU_TENSOR_MAP_DATA_TYPE_BFLOAT16, rank, const_cast<void*>(ptr), dims, strides, box, es, CU_TENSOR_MAP_INTERLEAVE_NONE,
     swz, CU_TENSOR_MAP_L2_PROMOTION_L2_128B, CU_TENSOR_MAP_FLOAT_OOB_FILL_NONE);
}
}

extern "C" void kernel_launch(void* const* d_in, const int* in_sizes, int n_in, void* d_out, int out_size) {
  (void)in_sizes; (void)n_in; (void)out_size;
  const __nv_bfloat16* x = (const __nv_bfloat16*)d_in[0];
  const __nv_bfloat16* wqkv = (const __nv_bfloat16*)d_in[1];
  const __nv_bfloat16* wphi = (const __nv_bfloat16*)d_in[2];
  const __nv_bfloat16* wo = (const __nv_bfloat16*)d_in[3];
  const __nv_bfloat16* w1 = (const __nv_bfloat16*)d_in[5];
  const __nv_bfloat16* w2 = (const __nv_bfloat16*)d_in[6];
  const __nv_bfloat16* w3 = (const __nv_bfloat16*)d_in[7];
  const __nv_bfloat16* w4 = (const __nv_bfloat16*)d_in[8];
  const __nv_bfloat16* gate_w = (const __nv_bfloat16*)d_in[9];

  static EncodeFn enc = nullptr;
  static void *pHs = nullptr, *pX1 = nullptr;
  if (!enc) {
    cudaDriverEntryPointQueryResult qr;
    cudaGetDriverEntryPoint("cuTensorMapEncodeTiled", (void**)&enc, cudaEnableDefault, &qr);
    cudaGetSymbolAddress(&pHs, g_Hs);
    cudaGetSymbolAddress(&pX1, g_X1);
    cudaFuncSetAttribute(fused_kernel, cudaFuncAttributeMaxDynamicSharedMemorySize, SMEM_BYTES);
  }
  Maps m;
  {
    cuuint64_t dims[2] = {D_, S_}, str[1] = {D_ * 2};
    cuuint32_t box[2] = {64, 128}, boxh[2] = {64, 64};
    encode(enc, &m.x, x, 2, dims, str, box, CU_TENSOR_MAP_SWIZZLE_128B);
    encode(enc, &m.hs, pHs, 2, dims, str, boxh, CU_TENSOR_MAP_SWIZZLE_128B);
    encode(enc, &m.x1, pX1, 2, dims, str, box, CU_TENSOR_MAP_SWIZZLE_128B);
  }
  {
    cuuint64_t dims[3] = {80, D_, 8}, str[2] = {D_ * 2, 160};
    cuuint32_t boxm[3] = {64, 32, 1}, boxr[3] = {16, 32, 1};
    encode(enc, &m.w1m, w1, 3, dims, str, boxm, CU_TENSOR_MAP_SWIZZLE_128B);
    encode(enc, &m.w1r, w1, 3, dims, str, boxr, CU_TENSOR_MAP_SWIZZLE_32B);
  }
  {
    cuuint64_t dims[4] = {80, D_, 3, 8}, str[3] = {3 * D_ * 2, D_ * 2, 160};
    cuuint32_t boxm[4] = {64, 32, 3, 1}, boxr[4] = {16, 32, 3, 1};
    encode(enc, &m.qm, wqkv, 4, dims, str, boxm, CU_TENSOR_MAP_SWIZZLE_128B);
    encode(enc, &m.qr, wqkv, 4, dims, str, boxr, CU_TENSOR_MAP_SWIZZLE_32B);
  }
  {
    cuuint64_t dims[3] = {16, D_, 40}, dims4[3] = {16, F_, 40}, str[2] = {D_ * 2, 32};
    cuuint32_t box2[3] = {16, 128, 5}, box4[3] = {16, 64, 5}, boxo[3] = {16, 80, 5};
    encode(enc, &m.w2, w2, 3, dims, str, box2, CU_TENSOR_MAP_SWIZZLE_32B);
    encode(enc, &m.w4, w4, 3, dims4, str, box4, CU_TENSOR_MAP_SWIZZLE_32B);
    encode(enc, &m.wo, wo, 3, dims, str, boxo, CU_TENSOR_MAP_SWIZZLE_32B);
  }
  {
    cuuint64_t dims[3] = {64, D_, 24}, str[2] = {F_ * 2, 128};
    cuuint32_t box[3] = {64, 64, 3};
    encode(enc, &m.w3, w3, 3, dims, str, box, CU_TENSOR_MAP_SWIZZLE_128B);
  }
  fused_kernel<<<NCTA, 384, SMEM_BYTES, cudaStreamPerThread>>>(m, x, wphi, w1, w2, w3, w4, wo, gate_w, (__nv_bfloat16*)d_out);
}
```

```cpp
#include <cuda_runtime.h>
#include <cuda_bf16.h>
#include <cuda.h>
#include <stdint.h>

namespace {

constexpr int S_ = 2048, D_ = 640, F_ = 1536;
constexpr int NCTA = 128;
constexpr int KV_PAIR = 40 * 48 + 96;
constexpr int KV_J = 2 * KV_PAIR;

constexpr int SLOT_B = 49152, NB = 3;
constexpr int SLOT_A = 16384, NA = 4;
constexpr int OFF_B = 0;
constexpr int OFF_A = OFF_B + NB * SLOT_B;
constexpr int OFF_MISC = OFF_A + NA * SLOT_A;
constexpr int OFF_CS = OFF_MISC + 16384;
constexpr int OFF_BAR = OFF_CS + 1152;
constexpr int SMEM_USED = OFF_BAR + 256;
constexpr int SMEM_BYTES = SMEM_USED + 1024;

constexpr int FL_DONE = 0, FL_PREP = 1, FL_H = 2, FL_X1 = FL_H + 16, FL_KV = FL_X1 + 16, FL_PART = FL_KV + 8;
constexpr int FL_COUNT = FL_PART + 16 * 8;
constexpr int NSIG = 11;

struct Maps {
  CUtensorMap x, w1m, w1r, qm, qr, hs, w2, x1, w3, w4, wo;
};

}

__device__ __align__(1024) __nv_bfloat16 g_Hs[S_ * D_];
__device__ __align__(1024) __nv_bfloat16 g_X1[S_ * D_];
__device__ __align__(128) float2 g_st1[S_ * 8];
__device__ __align__(128) float4 g_xstat[S_];
__device__ __align__(128) float g_cs[D_ + F_];
__device__ __align__(128) float g_kv[2][8 * KV_J];
__device__ __align__(128) uint4 g_part[16 * 8 * 8 * 5 * 256];
__device__ __align__(128) unsigned g_flags[FL_COUNT * 32];
#define TSTAMP(n) do {} while (0)

namespace {

__device__ __forceinline__ long long gtime() { long long t; asm volatile("mov.u64 %0, %%globaltimer;" : "=l"(t)); return t; }
__device__ __forceinline__ uint32_t smem_u32(const void* p) { return (uint32_t)__cvta_generic_to_shared(p); }
__device__ __forceinline__ void mbar_init(uint32_t bar, int cnt) {
  asm volatile("mbarrier.init.shared::cta.b64 [%0], %1;" ::"r"(bar), "r"(cnt) : "memory");
}
__device__ __forceinline__ void mbar_expect_tx(uint32_t bar, int bytes) {
  asm volatile("mbarrier.arrive.expect_tx.shared::cta.b64 _, [%0], %1;" ::"r"(bar), "r"(bytes) : "memory");
}
__device__ __forceinline__ void mbar_arrive_cta(uint32_t bar, uint32_t cta) {
  asm volatile("{\n.reg .b32 ra;\nmapa.shared::cluster.u32 ra, %0, %1;\nmbarrier.arrive.shared::cluster.b64 _, [ra];\n}"
               ::"r"(bar), "r"(cta) : "memory");
}
__device__ __forceinline__ uint32_t mbar_try(uint32_t bar, uint32_t parity) {
  uint32_t ok;
  asm volatile("{\n.reg .pred p;\nmbarrier.try_wait.parity.shared::cta.b64 p, [%1], %2;\nselp.u32 %0, 1, 0, p;\n}"
               : "=r"(ok) : "r"(bar), "r"(parity) : "memory");
  return ok;
}
constexpr uint32_t WAIT_LIMIT = 1u << 22;
__device__ __forceinline__ void mbar_wait(uint32_t bar, uint32_t parity) {
  uint32_t n = 0;
  while (!mbar_try(bar, parity) && ++n < WAIT_LIMIT) {}
}
__device__ __forceinline__ unsigned ld_acquire(const unsigned* p) {
  unsigned v;
  asm volatile("ld.acquire.gpu.global.u32 %0, [%1];" : "=r"(v) : "l"(p) : "memory");
  return v;
}
__device__ __forceinline__ void flag_wait(int idx, unsigned target) {
  const unsigned* p = g_flags + idx * 32;
  uint32_t n = 0;
  while ((int)(ld_acquire(p) - target) < 0 && ++n < (WAIT_LIMIT >> 4)) {}
}
__device__ __forceinline__ void flag_add(int idx) {
  asm volatile("red.release.gpu.global.add.u32 [%0], 1;" ::"l"(g_flags + idx * 32) : "memory");
}
__device__ __forceinline__ void mbar_arrive(uint32_t bar) {
  asm volatile("mbarrier.arrive.shared::cta.b64 _, [%0];" ::"r"(bar) : "memory");
}
__device__ __forceinline__ void fence_async_all() { asm volatile("fence.proxy.async;" ::: "memory"); }
__device__ __forceinline__ void fence_async_smem() { asm volatile("fence.proxy.async.shared::cta;" ::: "memory"); }
__device__ __forceinline__ void bar_sync(int id, int n) { asm volatile("bar.sync %0, %1;" ::"r"(id), "r"(n) : "memory"); }

__device__ __forceinline__ void tma2d(uint32_t dst, const CUtensorMap* m, uint32_t bar, int c0, int c1) {
  asm volatile("cp.async.bulk.tensor.2d.shared::cluster.global.mbarrier::complete_tx::bytes [%0], [%1, {%3, %4}], [%2];"
               ::"r"(dst), "l"(m), "r"(bar), "r"(c0), "r"(c1) : "memory");
}
__device__ __forceinline__ void tma2d_mc(uint32_t dst, const CUtensorMap* m, uint32_t bar, int c0, int c1) {
  asm volatile("cp.async.bulk.tensor.2d.shared::cluster.global.mbarrier::complete_tx::bytes.multicast::cluster"
               " [%0], [%1, {%3, %4}], [%2], %5;"
               ::"r"(dst), "l"(m), "r"(bar), "r"(c0), "r"(c1), "h"((uint16_t)3) : "memory");
}
__device__ __forceinline__ void tma3d(uint32_t dst, const CUtensorMap* m, uint32_t bar, int c0, int c1, int c2) {
  asm volatile("cp.async.bulk.tensor.3d.shared::cluster.global.mbarrier::complete_tx::bytes [%0], [%1, {%3, %4, %5}], [%2];"
               ::"r"(dst), "l"(m), "r"(bar), "r"(c0), "r"(c1), "r"(c2) : "memory");
}
__device__ __forceinline__ void tma3d_mc(uint32_t dst, const CUtensorMap* m, uint32_t bar, int c0, int c1, int c2) {
  asm volatile("cp.async.bulk.tensor.3d.shared::cluster.global.mbarrier::complete_tx::bytes.multicast::cluster"
               " [%0], [%1, {%3, %4, %5}], [%2], %6;"
               ::"r"(dst), "l"(m), "r"(bar), "r"(c0), "r"(c1), "r"(c2), "h"((uint16_t)3) : "memory");
}
__device__ __forceinline__ void tma4d_mc(uint32_t dst, const CUtensorMap* m, uint32_t bar, int c0, int c1, int c2, int c3) {
  asm volatile("cp.async.bulk.tensor.4d.shared::cluster.global.mbarrier::complete_tx::bytes.multicast::cluster"
               " [%0], [%1, {%3, %4, %5, %6}], [%2], %7;"
               ::"r"(dst), "l"(m), "r"(bar), "r"(c0), "r"(c1), "r"(c2), "r"(c3), "h"((uint16_t)3) : "memory");
}
__device__ __forceinline__ void l2_prefetch(const void* p, uint32_t bytes) {
  asm volatile("cp.async.bulk.prefetch.L2.global [%0], %1;" ::"l"(p), "r"(bytes) : "memory");
}
__device__ __forceinline__ void prefetch_tmap(const CUtensorMap* m) {
  asm volatile("prefetch.tensormap [%0];" ::"l"(m) : "memory");
}
__device__ __forceinline__ uint64_t make_desc(uint32_t a16, uint32_t off, uint32_t lbo, uint32_t sbo, uint32_t swz) {
  const uint32_t lo = a16 + ((off >> 4) + ((lbo >> 4) << 16)), hi = (sbo >> 4) | (swz << 30);
  uint64_t d;
  asm("mov.b64 %0, {%1, %2};" : "=l"(d) : "r"(lo), "r"(hi));
  return d;
}
__device__ __forceinline__ void wg_fence() { asm volatile("wgmma.fence.sync.aligned;" ::: "memory"); }
__device__ __forceinline__ void wg_commit() { asm volatile("wgmma.commit_group.sync.aligned;" ::: "memory"); }
template <int N> __device__ __forceinline__ void wg_wait() { asm volatile("wgmma.wait_group.sync.aligned %0;" ::"n"(N) : "memory"); }
template <int N> __device__ __forceinline__ void fence_regs(float (&d)[N]) {
#pragma unroll
  for (int i = 0; i < N; i++) asm volatile("" : "+f"(d[i])::"memory");
}
template <int N> __device__ __forceinline__ void zero_regs(float (&d)[N]) {
#pragma unroll
  for (int i = 0; i < N; i++) d[i] = 0.f;
}
__device__ __forceinline__ uint32_t pack_bf16(float lo, float hi) {
  uint32_t r;
  asm("cvt.rn.bf16x2.f32 %0, %1, %2;" : "=r"(r) : "f"(hi), "f"(lo));
  return r;
}
__device__ __forceinline__ float bf_lo(uint32_t v) { return __uint_as_float(v << 16); }
__device__ __forceinline__ float bf_hi(uint32_t v) { return __uint_as_float(v & 0xffff0000u); }
__device__ __forceinline__ uint32_t max_bf2(uint32_t a, uint32_t b) {
  uint32_t r; asm("max.bf16x2 %0, %1, %2;" : "=r"(r) : "r"(a), "r"(b)); return r;
}
__device__ __forceinline__ uint32_t min_bf2(uint32_t a, uint32_t b) {
  uint32_t r; asm("min.bf16x2 %0, %1, %2;" : "=r"(r) : "r"(a), "r"(b)); return r;
}
__device__ __forceinline__ float ex2(float x) { float r; asm("ex2.approx.ftz.f32 %0, %1;" : "=f"(r) : "f"(x)); return r; }
__device__ __forceinline__ float rcp(float x) { float r; asm("rcp.approx.ftz.f32 %0, %1;" : "=f"(r) : "f"(x)); return r; }
__device__ __forceinline__ float tanh_ap(float x) { float r; asm("tanh.approx.f32 %0, %1;" : "=f"(r) : "f"(x)); return r; }
__device__ __forceinline__ float gelu_s(float x, float hs) {
  float u = x * fmaf(x * x, 0.0356774081f, 0.7978845608f);
  float hx = x * hs;
  return fmaf(hx, tanh_ap(u), hx);
}
__device__ __forceinline__ void stsm4(uint32_t addr, uint32_t r0, uint32_t r1, uint32_t r2, uint32_t r3) {
  asm volatile("stmatrix.sync.aligned.m8n8.x4.shared.b16 [%0], {%1, %2, %3, %4};"
               ::"r"(addr), "r"(r0), "r"(r1), "r"(r2), "r"(r3) : "memory");
}
__device__ __forceinline__ void red_add4(float* p, float a, float b, float c, float d) {
  asm volatile("red.global.add.v4.f32 [%0], {%1, %2, %3, %4};" ::"l"(p), "f"(a), "f"(b), "f"(c), "f"(d) : "memory");
}
__device__ __forceinline__ void red_add2(float* p, float a, float b) {
  asm volatile("red.global.add.v2.f32 [%0], {%1, %2};" ::"l"(p), "f"(a), "f"(b) : "memory");
}

__device__ __forceinline__ void mma_ss256(float (&d)[128], uint64_t descA, uint64_t descB) {
  asm volatile("wgmma.mma_async.sync.aligned.m64n256k16.f32.bf16.bf16 {"
      "%0, %1, %2, %3, %4, %5, %6, %7, %8, %9, %10, %11, %12, %13, %14, %15, "
      "%16, %17, %18, %19, %20, %21, %22, %23, %24, %25, %26, %27, %28, %29, %30, %31, "
      "%32, %33, %34, %35, %36, %37, %38, %39, %40, %41, %42, %43, %44, %45, %46, %47, "
      "%48, %49, %50, %51, %52, %53, %54, %55, %56, %57, %58, %59, %60, %61, %62, %63, "
      "%64, %65, %66, %67, %68, %69, %70, %71, %72, %73, %74, %75, %76, %77, %78, %79, "
      "%80, %81, %82, %83, %84, %85, %86, %87, %88, %89, %90, %91, %92, %93, %94, %95, "
      "%96, %97, %98, %99, %100, %101, %102, %103, %104, %105, %106, %107, %108, %109, %110, %111, "
      "%112, %113, %114, %115, %116, %117, %118, %119, %120, %121, %122, %123, %124, %125, %126, %127"
      "}, %128, %129, 1, 1, 1, 0, 1;\n"
      : "+f"(d[0]), "+f"(d[1]), "+f"(d[2]), "+f"(d[3]), "+f"(d[4]), "+f"(d[5]), "+f"(d[6]), "+f"(d[7]),
        "+f"(d[8]), "+f"(d[9]), "+f"(d[10]), "+f"(d[11]), "+f"(d[12]), "+f"(d[13]), "+f"(d[14]), "+f"(d[15]),
        "+f"(d[16]), "+f"(d[17]), "+f"(d[18]), "+f"(d[19]), "+f"(d[20]), "+f"(d[21]), "+f"(d[22]), "+f"(d[23]),
        "+f"(d[24]), "+f"(d[25]), "+f"(d[26]), "+f"(d[27]), "+f"(d[28]), "+f"(d[29]), "+f"(d[30]), "+f"(d[31]),
        "+f"(d[32]), "+f"(d[33]), "+f"(d[34]), "+f"(d[35]), "+f"(d[36]), "+f"(d[37]), "+f"(d[38]), "+f"(d[39]),
        "+f"(d[40]), "+f"(d[41]), "+f"(d[42]), "+f"(d[43]), "+f"(d[44]), "+f"(d[45]), "+f"(d[46]), "+f"(d[47]),
        "+f"(d[48]), "+f"(d[49]), "+f"(d[50]), "+f"(d[51]), "+f"(d[52]), "+f"(d[53]), "+f"(d[54]), "+f"(d[55]),
        "+f"(d[56]), "+f"(d[57]), "+f"(d[58]), "+f"(d[59]), "+f"(d[60]), "+f"(d[61]), "+f"(d[62]), "+f"(d[63]),
        "+f"(d[64]), "+f"(d[65]), "+f"(d[66]), "+f"(d[67]), "+f"(d[68]), "+f"(d[69]), "+f"(d[70]), "+f"(d[71]),
        "+f"(d[72]), "+f"(d[73]), "+f"(d[74]), "+f"(d[75]), "+f"(d[76]), "+f"(d[77]), "+f"(d[78]), "+f"(d[79]),
        "+f"(d[80]), "+f"(d[81]), "+f"(d[82]), "+f"(d[83]), "+f"(d[84]), "+f"(d[85]), "+f"(d[86]), "+f"(d[87]),
        "+f"(d[88]), "+f"(d[89]), "+f"(d[90]), "+f"(d[91]), "+f"(d[92]), "+f"(d[93]), "+f"(d[94]), "+f"(d[95]),
        "+f"(d[96]), "+f"(d[97]), "+f"(d[98]), "+f"(d[99]), "+f"(d[100]), "+f"(d[101]), "+f"(d[102]), "+f"(d[103]),
        "+f"(d[104]), "+f"(d[105]), "+f"(d[106]), "+f"(d[107]), "+f"(d[108]), "+f"(d[109]), "+f"(d[110]), "+f"(d[111]),
        "+f"(d[112]), "+f"(d[113]), "+f"(d[114]), "+f"(d[115]), "+f"(d[116]), "+f"(d[117]), "+f"(d[118]), "+f"(d[119]),
        "+f"(d[120]), "+f"(d[121]), "+f"(d[122]), "+f"(d[123]), "+f"(d[124]), "+f"(d[125]), "+f"(d[126]), "+f"(d[127])
      : "l"(descA), "l"(descB));
}

__device__ __forceinline__ void mma_ss64(float (&d)[32], uint64_t descA, uint64_t descB) {
  asm volatile("wgmma.mma_async.sync.aligned.m64n64k16.f32.bf16.bf16 {"
      "%0, %1, %2, %3, %4, %5, %6, %7, %8, %9, %10, %11, %12, %13, %14, %15, "
      "%16, %17, %18, %19, %20, %21, %22, %23, %24, %25, %26, %27, %28, %29, %30, %31"
      "}, %32, %33, 1, 1, 1, 0, 1;\n"
      : "+f"(d[0]), "+f"(d[1]), "+f"(d[2]), "+f"(d[3]), "+f"(d[4]), "+f"(d[5]), "+f"(d[6]), "+f"(d[7]),
        "+f"(d[8]), "+f"(d[9]), "+f"(d[10]), "+f"(d[11]), "+f"(d[12]), "+f"(d[13]), "+f"(d[14]), "+f"(d[15]),
        "+f"(d[16]), "+f"(d[17]), "+f"(d[18]), "+f"(d[19]), "+f"(d[20]), "+f"(d[21]), "+f"(d[22]), "+f"(d[23]),
        "+f"(d[24]), "+f"(d[25]), "+f"(d[26]), "+f"(d[27]), "+f"(d[28]), "+f"(d[29]), "+f"(d[30]), "+f"(d[31])
      : "l"(descA), "l"(descB));
}

__device__ __forceinline__ void mma_ss80(float (&d)[40], uint64_t descA, uint64_t descB) {
  asm volatile("wgmma.mma_async.sync.aligned.m64n80k16.f32.bf16.bf16 {"
      "%0, %1, %2, %3, %4, %5, %6, %7, %8, %9, %10, %11, %12, %13, %14, %15, "
      "%16, %17, %18, %19, %20, %21, %22, %23, %24, %25, %26, %27, %28, %29, %30, %31, "
      "%32, %33, %34, %35, %36, %37, %38, %39"
      "}, %40, %41, 1, 1, 1, 0, 1;\n"
      : "+f"(d[0]), "+f"(d[1]), "+f"(d[2]), "+f"(d[3]), "+f"(d[4]), "+f"(d[5]), "+f"(d[6]), "+f"(d[7]),
        "+f"(d[8]), "+f"(d[9]), "+f"(d[10]), "+f"(d[11]), "+f"(d[12]), "+f"(d[13]), "+f"(d[14]), "+f"(d[15]),
        "+f"(d[16]), "+f"(d[17]), "+f"(d[18]), "+f"(d[19]), "+f"(d[20]), "+f"(d[21]), "+f"(d[22]), "+f"(d[23]),
        "+f"(d[24]), "+f"(d[25]), "+f"(d[26]), "+f"(d[27]), "+f"(d[28]), "+f"(d[29]), "+f"(d[30]), "+f"(d[31]),
        "+f"(d[32]), "+f"(d[33]), "+f"(d[34]), "+f"(d[35]), "+f"(d[36]), "+f"(d[37]), "+f"(d[38]), "+f"(d[39])
      : "l"(descA), "l"(descB));
}

__device__ __forceinline__ void mma_ss192(float (&d)[96], uint64_t descA, uint64_t descB) {
  asm volatile("wgmma.mma_async.sync.aligned.m64n192k16.f32.bf16.bf16 {"
      "%0, %1, %2, %3, %4, %5, %6, %7, %8, %9, %10, %11, %12, %13, %14, %15, "
      "%16, %17, %18, %19, %20, %21, %22, %23, %24, %25, %26, %27, %28, %29, %30, %31, "
      "%32, %33, %34, %35, %36, %37, %38, %39, %40, %41, %42, %43, %44, %45, %46, %47, "
      "%48, %49, %50, %51, %52, %53, %54, %55, %56, %57, %58, %59, %60, %61, %62, %63, "
      "%64, %65, %66, %67, %68, %69, %70, %71, %72, %73, %74, %75, %76, %77, %78, %79, "
      "%80, %81, %82, %83, %84, %85, %86, %87, %88, %89, %90, %91, %92, %93, %94, %95"
      "}, %96, %97, 1, 1, 1, 0, 1;\n"
      : "+f"(d[0]), "+f"(d[1]), "+f"(d[2]), "+f"(d[3]), "+f"(d[4]), "+f"(d[5]), "+f"(d[6]), "+f"(d[7]),
        "+f"(d[8]), "+f"(d[9]), "+f"(d[10]), "+f"(d[11]), "+f"(d[12]), "+f"(d[13]), "+f"(d[14]), "+f"(d[15]),
        "+f"(d[16]), "+f"(d[17]), "+f"(d[18]), "+f"(d[19]), "+f"(d[20]), "+f"(d[21]), "+f"(d[22]), "+f"(d[23]),
        "+f"(d[24]), "+f"(d[25]), "+f"(d[26]), "+f"(d[27]), "+f"(d[28]), "+f"(d[29]), "+f"(d[30]), "+f"(d[31]),
        "+f"(d[32]), "+f"(d[33]), "+f"(d[34]), "+f"(d[35]), "+f"(d[36]), "+f"(d[37]), "+f"(d[38]), "+f"(d[39]),
        "+f"(d[40]), "+f"(d[41]), "+f"(d[42]), "+f"(d[43]), "+f"(d[44]), "+f"(d[45]), "+f"(d[46]), "+f"(d[47]),
        "+f"(d[48]), "+f"(d[49]), "+f"(d[50]), "+f"(d[51]), "+f"(d[52]), "+f"(d[53]), "+f"(d[54]), "+f"(d[55]),
        "+f"(d[56]), "+f"(d[57]), "+f"(d[58]), "+f"(d[59]), "+f"(d[60]), "+f"(d[61]), "+f"(d[62]), "+f"(d[63]),
        "+f"(d[64]), "+f"(d[65]), "+f"(d[66]), "+f"(d[67]), "+f"(d[68]), "+f"(d[69]), "+f"(d[70]), "+f"(d[71]),
        "+f"(d[72]), "+f"(d[73]), "+f"(d[74]), "+f"(d[75]), "+f"(d[76]), "+f"(d[77]), "+f"(d[78]), "+f"(d[79]),
        "+f"(d[80]), "+f"(d[81]), "+f"(d[82]), "+f"(d[83]), "+f"(d[84]), "+f"(d[85]), "+f"(d[86]), "+f"(d[87]),
        "+f"(d[88]), "+f"(d[89]), "+f"(d[90]), "+f"(d[91]), "+f"(d[92]), "+f"(d[93]), "+f"(d[94]), "+f"(d[95])
      : "l"(descA), "l"(descB));
}

__device__ __forceinline__ void mma_ss80_tt(float (&d)[40], uint64_t descA, uint64_t descB) {
  asm volatile("wgmma.mma_async.sync.aligned.m64n80k16.f32.bf16.bf16 {"
      "%0, %1, %2, %3, %4, %5, %6, %7, %8, %9, %10, %11, %12, %13, %14, %15, "
      "%16, %17, %18, %19, %20, %21, %22, %23, %24, %25, %26, %27, %28, %29, %30, %31, "
      "%32, %33, %34, %35, %36, %37, %38, %39"
      "}, %40, %41, 1, 1, 1, 1, 1;\n"
      : "+f"(d[0]), "+f"(d[1]), "+f"(d[2]), "+f"(d[3]), "+f"(d[4]), "+f"(d[5]), "+f"(d[6]), "+f"(d[7]),
        "+f"(d[8]), "+f"(d[9]), "+f"(d[10]), "+f"(d[11]), "+f"(d[12]), "+f"(d[13]), "+f"(d[14]), "+f"(d[15]),
        "+f"(d[16]), "+f"(d[17]), "+f"(d[18]), "+f"(d[19]), "+f"(d[20]), "+f"(d[21]), "+f"(d[22]), "+f"(d[23]),
        "+f"(d[24]), "+f"(d[25]), "+f"(d[26]), "+f"(d[27]), "+f"(d[28]), "+f"(d[29]), "+f"(d[30]), "+f"(d[31]),
        "+f"(d[32]), "+f"(d[33]), "+f"(d[34]), "+f"(d[35]), "+f"(d[36]), "+f"(d[37]), "+f"(d[38]), "+f"(d[39])
      : "l"(descA), "l"(descB));
}
__device__ __forceinline__ void mma_ss80_tt_z(float (&d)[40], uint64_t descA, uint64_t descB) {
  asm volatile("wgmma.mma_async.sync.aligned.m64n80k16.f32.bf16.bf16 {"
      "%0, %1, %2, %3, %4, %5, %6, %7, %8, %9, %10, %11, %12, %13, %14, %15, "
      "%16, %17, %18, %19, %20, %21, %22, %23, %24, %25, %26, %27, %28, %29, %30, %31, "
      "%32, %33, %34, %35, %36, %37, %38, %39"
      "}, %40, %41, 0, 1, 1, 1, 1;\n"
      : "=f"(d[0]), "=f"(d[1]), "=f"(d[2]), "=f"(d[3]), "=f"(d[4]), "=f"(d[5]), "=f"(d[6]), "=f"(d[7]),
        "=f"(d[8]), "=f"(d[9]), "=f"(d[10]), "=f"(d[11]), "=f"(d[12]), "=f"(d[13]), "=f"(d[14]), "=f"(d[15]),
        "=f"(d[16]), "=f"(d[17]), "=f"(d[18]), "=f"(d[19]), "=f"(d[20]), "=f"(d[21]), "=f"(d[22]), "=f"(d[23]),
        "=f"(d[24]), "=f"(d[25]), "=f"(d[26]), "=f"(d[27]), "=f"(d[28]), "=f"(d[29]), "=f"(d[30]), "=f"(d[31]),
        "=f"(d[32]), "=f"(d[33]), "=f"(d[34]), "=f"(d[35]), "=f"(d[36]), "=f"(d[37]), "=f"(d[38]), "=f"(d[39])
      : "l"(descA), "l"(descB));
}

__device__ __forceinline__ void mma_rs80_k(float (&d)[40], const uint32_t (&a)[4], uint64_t descB) {
  asm volatile("wgmma.mma_async.sync.aligned.m64n80k16.f32.bf16.bf16 {"
      "%0, %1, %2, %3, %4, %5, %6, %7, %8, %9, %10, %11, %12, %13, %14, %15, "
      "%16, %17, %18, %19, %20, %21, %22, %23, %24, %25, %26, %27, %28, %29, %30, %31, "
      "%32, %33, %34, %35, %36, %37, %38, %39"
      "}, {%40, %41, %42, %43}, %44, 1, 1, 1, 0;\n"
      : "+f"(d[0]), "+f"(d[1]), "+f"(d[2]), "+f"(d[3]), "+f"(d[4]), "+f"(d[5]), "+f"(d[6]), "+f"(d[7]),
        "+f"(d[8]), "+f"(d[9]), "+f"(d[10]), "+f"(d[11]), "+f"(d[12]), "+f"(d[13]), "+f"(d[14]), "+f"(d[15]),
        "+f"(d[16]), "+f"(d[17]), "+f"(d[18]), "+f"(d[19]), "+f"(d[20]), "+f"(d[21]), "+f"(d[22]), "+f"(d[23]),
        "+f"(d[24]), "+f"(d[25]), "+f"(d[26]), "+f"(d[27]), "+f"(d[28]), "+f"(d[29]), "+f"(d[30]), "+f"(d[31]),
        "+f"(d[32]), "+f"(d[33]), "+f"(d[34]), "+f"(d[35]), "+f"(d[36]), "+f"(d[37]), "+f"(d[38]), "+f"(d[39])
      : "r"(a[0]), "r"(a[1]), "r"(a[2]), "r"(a[3]), "l"(descB));
}
__device__ __forceinline__ void mma_rs80_k_z(float (&d)[40], const uint32_t (&a)[4], uint64_t descB) {
  asm volatile("wgmma.mma_async.sync.aligned.m64n80k16.f32.bf16.bf16 {"
      "%0, %1, %2, %3, %4, %5, %6, %7, %8, %9, %10, %11, %12, %13, %14, %15, "
      "%16, %17, %18, %19, %20, %21, %22, %23, %24, %25, %26, %27, %28, %29, %30, %31, "
      "%32, %33, %34, %35, %36, %37, %38, %39"
      "}, {%40, %41, %42, %43}, %44, 0, 1, 1, 0;\n"
      : "=f"(d[0]), "=f"(d[1]), "=f"(d[2]), "=f"(d[3]), "=f"(d[4]), "=f"(d[5]), "=f"(d[6]), "=f"(d[7]),
        "=f"(d[8]), "=f"(d[9]), "=f"(d[10]), "=f"(d[11]), "=f"(d[12]), "=f"(d[13]), "=f"(d[14]), "=f"(d[15]),
        "=f"(d[16]), "=f"(d[17]), "=f"(d[18]), "=f"(d[19]), "=f"(d[20]), "=f"(d[21]), "=f"(d[22]), "=f"(d[23]),
        "=f"(d[24]), "=f"(d[25]), "=f"(d[26]), "=f"(d[27]), "=f"(d[28]), "=f"(d[29]), "=f"(d[30]), "=f"(d[31]),
        "=f"(d[32]), "=f"(d[33]), "=f"(d[34]), "=f"(d[35]), "=f"(d[36]), "=f"(d[37]), "=f"(d[38]), "=f"(d[39])
      : "r"(a[0]), "r"(a[1]), "r"(a[2]), "r"(a[3]), "l"(descB));
}

__device__ __forceinline__ void mma_rs48_k(float (&d)[24], const uint32_t (&a)[4], uint64_t descB) {
  asm volatile("wgmma.mma_async.sync.aligned.m64n48k16.f32.bf16.bf16 {"
      "%0, %1, %2, %3, %4, %5, %6, %7, %8, %9, %10, %11, %12, %13, %14, %15, "
      "%16, %17, %18, %19, %20, %21, %22, %23"
      "}, {%24, %25, %26, %27}, %28, 1, 1, 1, 0;\n"
      : "+f"(d[0]), "+f"(d[1]), "+f"(d[2]), "+f"(d[3]), "+f"(d[4]), "+f"(d[5]), "+f"(d[6]), "+f"(d[7]),
        "+f"(d[8]), "+f"(d[9]), "+f"(d[10]), "+f"(d[11]), "+f"(d[12]), "+f"(d[13]), "+f"(d[14]), "+f"(d[15]),
        "+f"(d[16]), "+f"(d[17]), "+f"(d[18]), "+f"(d[19]), "+f"(d[20]), "+f"(d[21]), "+f"(d[22]), "+f"(d[23])
      : "r"(a[0]), "r"(a[1]), "r"(a[2]), "r"(a[3]), "l"(descB));
}
__device__ __forceinline__ void mma_rs48_k_z(float (&d)[24], const uint32_t (&a)[4], uint64_t descB) {
  asm volatile("wgmma.mma_async.sync.aligned.m64n48k16.f32.bf16.bf16 {"
      "%0, %1, %2, %3, %4, %5, %6, %7, %8, %9, %10, %11, %12, %13, %14, %15, "
      "%16, %17, %18, %19, %20, %21, %22, %23"
      "}, {%24, %25, %26, %27}, %28, 0, 1, 1, 0;\n"
      : "=f"(d[0]), "=f"(d[1]), "=f"(d[2]), "=f"(d[3]), "=f"(d[4]), "=f"(d[5]), "=f"(d[6]), "=f"(d[7]),
        "=f"(d[8]), "=f"(d[9]), "=f"(d[10]), "=f"(d[11]), "=f"(d[12]), "=f"(d[13]), "=f"(d[14]), "=f"(d[15]),
        "=f"(d[16]), "=f"(d[17]), "=f"(d[18]), "=f"(d[19]), "=f"(d[20]), "=f"(d[21]), "=f"(d[22]), "=f"(d[23])
      : "r"(a[0]), "r"(a[1]), "r"(a[2]), "r"(a[3]), "l"(descB));
}

__device__ __forceinline__ void mma_rs80_n(float (&d)[40], const uint32_t (&a)[4], uint64_t descB) {
  asm volatile("wgmma.mma_async.sync.aligned.m64n80k16.f32.bf16.bf16 {"
      "%0, %1, %2, %3, %4, %5, %6, %7, %8, %9, %10, %11, %12, %13, %14, %15, "
      "%16, %17, %18, %19, %20, %21, %22, %23, %24, %25, %26, %27, %28, %29, %30, %31, "
      "%32, %33, %34, %35, %36, %37, %38, %39"
      "}, {%40, %41, %42, %43}, %44, 1, 1, 1, 1;\n"
      : "+f"(d[0]), "+f"(d[1]), "+f"(d[2]), "+f"(d[3]), "+f"(d[4]), "+f"(d[5]), "+f"(d[6]), "+f"(d[7]),
        "+f"(d[8]), "+f"(d[9]), "+f"(d[10]), "+f"(d[11]), "+f"(d[12]), "+f"(d[13]), "+f"(d[14]), "+f"(d[15]),
        "+f"(d[16]), "+f"(d[17]), "+f"(d[18]), "+f"(d[19]), "+f"(d[20]), "+f"(d[21]), "+f"(d[22]), "+f"(d[23]),
        "+f"(d[24]), "+f"(d[25]), "+f"(d[26]), "+f"(d[27]), "+f"(d[28]), "+f"(d[29]), "+f"(d[30]), "+f"(d[31]),
        "+f"(d[32]), "+f"(d[33]), "+f"(d[34]), "+f"(d[35]), "+f"(d[36]), "+f"(d[37]), "+f"(d[38]), "+f"(d[39])
      : "r"(a[0]), "r"(a[1]), "r"(a[2]), "r"(a[3]), "l"(descB));
}
__device__ __forceinline__ void mma_rs80_n_z(float (&d)[40], const uint32_t (&a)[4], uint64_t descB) {
  asm volatile("wgmma.mma_async.sync.aligned.m64n80k16.f32.bf16.bf16 {"
      "%0, %1, %2, %3, %4, %5, %6, %7, %8, %9, %10, %11, %12, %13, %14, %15, "
      "%16, %17, %18, %19, %20, %21, %22, %23, %24, %25, %26, %27, %28, %29, %30, %31, "
      "%32, %33, %34, %35, %36, %37, %38, %39"
      "}, {%40, %41, %42, %43}, %44, 0, 1, 1, 1;\n"
      : "=f"(d[0]), "=f"(d[1]), "=f"(d[2]), "=f"(d[3]), "=f"(d[4]), "=f"(d[5]), "=f"(d[6]), "=f"(d[7]),
        "=f"(d[8]), "=f"(d[9]), "=f"(d[10]), "=f"(d[11]), "=f"(d[12]), "=f"(d[13]), "=f"(d[14]), "=f"(d[15]),
        "=f"(d[16]), "=f"(d[17]), "=f"(d[18]), "=f"(d[19]), "=f"(d[20]), "=f"(d[21]), "=f"(d[22]), "=f"(d[23]),
        "=f"(d[24]), "=f"(d[25]), "=f"(d[26]), "=f"(d[27]), "=f"(d[28]), "=f"(d[29]), "=f"(d[30]), "=f"(d[31]),
        "=f"(d[32]), "=f"(d[33]), "=f"(d[34]), "=f"(d[35]), "=f"(d[36]), "=f"(d[37]), "=f"(d[38]), "=f"(d[39])
      : "r"(a[0]), "r"(a[1]), "r"(a[2]), "r"(a[3]), "l"(descB));
}

__device__ __forceinline__ void feature_map(const uint32_t (&P)[2][10], uint32_t (&fr)[10][4]) {
  constexpr float L2E = 1.4426950408889634f;
#pragma unroll
  for (int p = 0; p < 2; p++) {
#pragma unroll
    for (int r = 0; r < 2; r++) {
      uint32_t mx = P[r][5 * p], mn = mx;
#pragma unroll
      for (int g = 1; g < 5; g++) { mx = max_bf2(mx, P[r][5 * p + g]); mn = min_bf2(mn, P[r][5 * p + g]); }
      mx = max_bf2(mx, __shfl_xor_sync(0xffffffffu, mx, 1));
      mn = min_bf2(mn, __shfl_xor_sync(0xffffffffu, mn, 1));
      mx = max_bf2(mx, __shfl_xor_sync(0xffffffffu, mx, 2));
      mn = min_bf2(mn, __shfl_xor_sync(0xffffffffu, mn, 2));
      float mx0 = -bf_lo(mx) * L2E, mx1 = -bf_hi(mx) * L2E, mn0 = bf_lo(mn) * L2E, mn1 = bf_hi(mn) * L2E;
      float ep0[5], ep1[5], en0[5], en1[5];
      float sp0 = 0.f, sp1 = 0.f, sn0 = 0.f, sn1 = 0.f;
#pragma unroll
      for (int g = 0; g < 5; g++) {
        float x0 = bf_lo(P[r][5 * p + g]), x1 = bf_hi(P[r][5 * p + g]);
        ep0[g] = ex2(fmaf(x0, L2E, mx0)); ep1[g] = ex2(fmaf(x1, L2E, mx1));
        en0[g] = ex2(fmaf(x0, -L2E, mn0)); en1[g] = ex2(fmaf(x1, -L2E, mn1));
        sp0 += ep0[g]; sp1 += ep1[g]; sn0 += en0[g]; sn1 += en1[g];
      }
      sp0 += __shfl_xor_sync(0xffffffffu, sp0, 1); sp1 += __shfl_xor_sync(0xffffffffu, sp1, 1);
      sn0 += __shfl_xor_sync(0xffffffffu, sn0, 1); sn1 += __shfl_xor_sync(0xffffffffu, sn1, 1);
      sp0 += __shfl_xor_sync(0xffffffffu, sp0, 2); sp1 += __shfl_xor_sync(0xffffffffu, sp1, 2);
      sn0 += __shfl_xor_sync(0xffffffffu, sn0, 2); sn1 += __shfl_xor_sync(0xffffffffu, sn1, 2);
      sp0 = rcp(sp0); sp1 = rcp(sp1); sn0 = rcp(sn0); sn1 = rcp(sn1);
#pragma unroll
      for (int g = 0; g < 5; g++) {
        fr[5 * p + g][r] = pack_bf16(ep0[g] * sp0, ep1[g] * sp1);
        fr[5 * p + g][2 + r] = pack_bf16(en0[g] * sn0, en1[g] * sn1);
      }
    }
  }
}

struct Ring {
  uint32_t idx, phase;
  template <int N> __device__ __forceinline__ void next() { if (++idx == N) { idx = 0; phase ^= 1; } }
};

}

__global__ void __cluster_dims__(2, 1, 1) __launch_bounds__(384, 1)
fused_kernel(const __grid_constant__ Maps maps, const __nv_bfloat16* __restrict__ x, const __nv_bfloat16* __restrict__ wphi,
             const __nv_bfloat16* __restrict__ w1, const __nv_bfloat16* __restrict__ w2, const __nv_bfloat16* __restrict__ w3,
             const __nv_bfloat16* __restrict__ w4, const __nv_bfloat16* __restrict__ wo, const __nv_bfloat16* __restrict__ gate_w,
             __nv_bfloat16* __restrict__ out) {
  extern __shared__ uint8_t smem_raw[];
  const uint32_t sb = (smem_u32(smem_raw) + 1023u) & ~1023u;
  const uint32_t sb16 = (sb & 0x3FFFFu) >> 4;
  uint8_t* sgen = smem_raw + (sb - smem_u32(smem_raw));
  const uint32_t fullA = sb + OFF_BAR, emptyA = fullA + 8 * NA, fullB = emptyA + 8 * NA, emptyB = fullB + 8 * NB;
  const uint32_t sig = emptyB + 8 * NB;
  volatile unsigned* s_epoch = reinterpret_cast<volatile unsigned*>(sgen + OFF_BAR + 248);

  const int tid = threadIdx.x;
  const int rank = blockIdx.x & 1;
  const int pairIdx = blockIdx.x >> 1;
  const int I = pairIdx >> 3, j = pairIdx & 7;
  const int i = 2 * I + rank;
  const int i2 = 2 * I + (j >> 2);
  const int j2 = 2 * (j & 3) + rank;

  TSTAMP(0);
  if (tid < 2 * NA + 2 * NB + NSIG) {
    const int cnt = tid < NA ? 1 : tid < 2 * NA ? 4 : tid < 2 * NA + NB ? 1 : tid < 2 * NA + 2 * NB ? 4 : (tid == 2 * NA + 2 * NB ? 10 : 8);
    mbar_init(fullA + 8 * tid, cnt);
    asm volatile("fence.mbarrier_init.release.cluster;" ::: "memory");
  }
  if (tid == 32) *s_epoch = ld_acquire(g_flags + FL_DONE * 32) / NCTA;
  if (tid == 256) { prefetch_tmap(&maps.x); }
  if (tid == 288) { prefetch_tmap(&maps.w1m); prefetch_tmap(&maps.qm); prefetch_tmap(&maps.w1r); prefetch_tmap(&maps.qr); }
  asm volatile("barrier.cluster.arrive.aligned;\nbarrier.cluster.wait.aligned;" ::: "memory");
  const unsigned epoch = *s_epoch;

  if (tid >= 256) {
    asm volatile("setmaxnreg.dec.sync.aligned.u32 56;");
    if (tid == 256) {
      Ring r{0, 1};
      const unsigned tgt = (epoch + 1) * 8u;
#pragma unroll 1
      for (int k = 0; k < 30; k++) {
        if (k == 10) {
          prefetch_tmap(&maps.hs); prefetch_tmap(&maps.x1);
          flag_wait(FL_H + ((i2 - 1) & 15), tgt);
          flag_wait(FL_H + ((i2 + 1) & 15), tgt);
        }
        if (k == 10 || k == 20) {
          flag_wait(k == 10 ? FL_H + i2 : FL_X1 + i, tgt);
          fence_async_all();
        }
        mbar_wait(emptyA + 8 * r.idx, r.phase);
        const uint32_t bar = fullA + 8 * r.idx, slot = sb + OFF_A + r.idx * SLOT_A;
        mbar_expect_tx(bar, SLOT_A);
        if (k >= 10 && k < 20) tma2d_mc(slot + rank * 8192, &maps.hs, bar, 64 * (k - 10), 128 * i2 + 64 * rank);
        else tma2d(slot, k < 10 ? &maps.x : &maps.x1, bar, 64 * (k < 10 ? k : k - 20), 128 * i);
        r.next<NA>();
      }
    } else if (tid == 288) {
      Ring r{0, 1};
#pragma unroll 1
      for (int k = 0; k < 26; k++) {
        mbar_wait(emptyB + 8 * r.idx, r.phase);
        const uint32_t bar = fullB + 8 * r.idx, slot = sb + OFF_B + r.idx * SLOT_B;
        if (k < 10) {
          mbar_expect_tx(bar, 40960);
          const int k0 = 64 * k + 32 * rank;
          tma4d_mc(slot + rank * 16384 + 4096, &maps.qm, bar, 0, k0, 0, j);
          tma3d_mc(slot + rank * 16384, &maps.w1m, bar, 0, k0, j);
          tma4d_mc(slot + 32768 + rank * 4096 + 1024, &maps.qr, bar, 64, k0, 0, j);
          tma3d_mc(slot + 32768 + rank * 4096, &maps.w1r, bar, 64, k0, j);
          if (k == 2) { prefetch_tmap(&maps.w2); prefetch_tmap(&maps.w3); prefetch_tmap(&maps.w4); prefetch_tmap(&maps.wo); }
        } else if (k < 13) {
          const int s = k - 10;
          mbar_expect_tx(bar, s < 2 ? 40960 : 20480);
          tma3d(slot, &maps.w2, bar, 0, 256 * s, 5 * j2);
          if (s < 2) tma3d(slot + 20480, &maps.w2, bar, 0, 256 * s + 128, 5 * j2);
        } else if (k < 18) {
          mbar_expect_tx(bar, 49152);
          tma3d_mc(slot + rank * 24576, &maps.w3, bar, 0, 128 * (k - 13) + 64 * rank, 3 * j);
        } else {
          const int d = (j + k - 17) & 7;
          mbar_expect_tx(bar, 43520);
          tma3d_mc(slot + rank * 10240, &maps.w4, bar, 0, 192 * j + 64 * rank, 5 * d);
          tma3d_mc(slot + (rank ? 20480 : 30720), rank ? &maps.w4 : &maps.wo, bar, 0, rank ? 192 * j + 128 : 80 * j, 5 * d);
        }
        r.next<NB>();
      }
    } else if (tid >= 320) {
      const int lane = tid & 31, hw = (tid >> 5) & 1;
#pragma unroll 1
      for (int unit = blockIdx.x + 128 * hw; unit < 272; unit += 256) {
        const __nv_bfloat16* src = unit < 80 ? w1 + unit * 8 : w3 + (unit - 80) * 8;
        const int ld = unit < 80 ? D_ : F_;
        float a[8];
#pragma unroll
        for (int e = 0; e < 8; e++) a[e] = 0.f;
        const __nv_bfloat16* p = src + (size_t)lane * ld;
#pragma unroll 5
        for (int it = 0; it < 20; it++) {
          uint4 v = __ldg(reinterpret_cast<const uint4*>(p + (size_t)it * 32 * ld));
          a[0] += bf_lo(v.x); a[1] += bf_hi(v.x); a[2] += bf_lo(v.y); a[3] += bf_hi(v.y);
          a[4] += bf_lo(v.z); a[5] += bf_hi(v.z); a[6] += bf_lo(v.w); a[7] += bf_hi(v.w);
        }
#pragma unroll
        for (int e = 0; e < 4; e++) {
          const float snd = (lane & 1) ? a[e] : a[e + 4], keep = (lane & 1) ? a[e + 4] : a[e];
          a[e] = keep + __shfl_xor_sync(0xffffffffu, snd, 1);
        }
#pragma unroll
        for (int e = 0; e < 2; e++) {
          const float snd = (lane & 2) ? a[e] : a[e + 2], keep = (lane & 2) ? a[e + 2] : a[e];
          a[e] = keep + __shfl_xor_sync(0xffffffffu, snd, 2);
        }
        {
          const float snd = (lane & 4) ? a[0] : a[1], keep = (lane & 4) ? a[1] : a[0];
          a[0] = keep + __shfl_xor_sync(0xffffffffu, snd, 4);
        }
        a[0] += __shfl_xor_sync(0xffffffffu, a[0], 8);
        a[0] += __shfl_xor_sync(0xffffffffu, a[0], 16);
        if (lane < 8) g_cs[unit * 8 + (lane & 1) * 4 + (lane & 2) + (lane >> 2)] = a[0];
      }
      __syncwarp();
      if (lane == 0) mbar_arrive(sig);
      if (hw == 0) {
        float* nxt = g_kv[(epoch + 1) & 1];
        constexpr int PER = 8 * KV_J / NCTA;
#pragma unroll 1
        for (int e = lane; e < PER; e += 32) nxt[blockIdx.x * PER + e] = 0.f;
        if (lane == 0) {
          l2_prefetch(w2 + (size_t)blockIdx.x * (D_ * D_ / NCTA), D_ * D_ * 2 / NCTA);
          l2_prefetch(w4 + (size_t)blockIdx.x * (F_ * D_ / NCTA), F_ * D_ * 2 / NCTA);
          l2_prefetch(wo + (size_t)blockIdx.x * (D_ * D_ / NCTA), D_ * D_ * 2 / NCTA);
        }
      } else if (lane == 0) {
#pragma unroll 1
        for (int s = 0; s < NSIG; s++) {
          mbar_wait(sig + 8 * s, 0);
          const int fl = s == 0 ? FL_PREP : s == 1 ? FL_H + i : s == 2 ? FL_KV + j : s == 3 ? FL_X1 + i2
                                                                                       : FL_PART + i * 8 + ((j + s - 3) & 7);
          flag_add(fl);
        }
      }
    }
    __syncwarp();
    asm volatile("barrier.cluster.arrive;\nbarrier.cluster.wait;" ::: "memory");
  } else {
    asm volatile("setmaxnreg.inc.sync.aligned.u32 224;");
    const int wg = tid >> 7, warp = tid >> 5, lane = tid & 31, t = lane & 3;
    const int rloc = warp * 16 + (lane >> 2);
    float* s_cs = reinterpret_cast<float*>(sgen + OFF_CS);
    auto signal = [&](int s) {
      __syncwarp();
      if (lane == 0) mbar_arrive(sig + 8 * s);
    };
    auto release = [&](uint32_t bar) {
      if ((tid & 127) < 2) mbar_arrive_cta(bar, tid & 1);
    };

    {
      const int row = blockIdx.x * 16 + warp * 2 + (lane >> 4);
      const int l16 = lane & 15;
      uint4 v[5], w[5];
#pragma unroll
      for (int c = 0; c < 5; c++) {
        v[c] = __ldg(reinterpret_cast<const uint4*>(x + (size_t)row * D_ + c * 128 + l16 * 8));
        w[c] = __ldg(reinterpret_cast<const uint4*>(gate_w + c * 128 + l16 * 8));
      }
      uint4 wp = make_uint4(0, 0, 0, 0);
      if (tid < 200) wp = __ldg(reinterpret_cast<const uint4*>(wphi + (size_t)j * 1600) + tid);
#pragma unroll 1
      for (int e = tid; e < 800; e += 256) *reinterpret_cast<uint4*>(sgen + OFF_MISC + e * 16) = make_uint4(0, 0, 0, 0);
      float f[40];
      float s = 0.f, gs = 0.f;
#pragma unroll
      for (int c = 0; c < 5; c++) {
        const uint32_t vv[4] = {v[c].x, v[c].y, v[c].z, v[c].w}, ww[4] = {w[c].x, w[c].y, w[c].z, w[c].w};
#pragma unroll
        for (int e = 0; e < 4; e++) {
          f[8 * c + 2 * e] = bf_lo(vv[e]); f[8 * c + 2 * e + 1] = bf_hi(vv[e]);
          s += f[8 * c + 2 * e] + f[8 * c + 2 * e + 1];
          gs = fmaf(f[8 * c + 2 * e], bf_lo(ww[e]), gs); gs = fmaf(f[8 * c + 2 * e + 1], bf_hi(ww[e]), gs);
        }
      }
#pragma unroll
      for (int o = 1; o < 16; o <<= 1) { s += __shfl_xor_sync(0xffffffffu, s, o); gs += __shfl_xor_sync(0xffffffffu, gs, o); }
      const float mean = s * (1.f / D_);
      float q = 0.f;
#pragma unroll
      for (int e = 0; e < 40; e++) { const float d = f[e] - mean; q = fmaf(d, d, q); }
#pragma unroll
      for (int o = 1; o < 16; o <<= 1) q += __shfl_xor_sync(0xffffffffu, q, o);
      if (l16 == 0) g_xstat[row] = make_float4(mean, rsqrtf(q * (1.f / D_) + 1e-5f), rcp(1.f + __expf(-gs)), 0.f);
      signal(0);
      bar_sync(1, 256);
      if (tid < 200) {
        const uint32_t ww[4] = {wp.x, wp.y, wp.z, wp.w};
        const int h = tid / 50;
#pragma unroll
        for (int e = 0; e < 8; e++) {
          const int idx = tid * 8 + e, k = idx / 20, ff = idx - 20 * k;
          const int n = 40 * (h >> 1) + 8 * (ff >> 2) + 2 * (ff & 3) + (h & 1);
          const int off = (k >> 4) * 2560 + n * 32 + ((((k >> 3) ^ (n >> 2)) & 1) << 4) + (k & 7) * 2;
          *reinterpret_cast<unsigned short*>(sgen + OFF_MISC + off) = (unsigned short)(ww[e >> 1] >> ((e & 1) * 16));
        }
        fence_async_smem();
      }
    }
    TSTAMP(1);

    Ring ra{0, 0}, rb{0, 0};
    uint32_t qp[2][10], P[2][10];
    float st_g[2];
    {
      float accM[128], accR[32];
      zero_regs(accM); zero_regs(accR);
      float st_mean[2], st_rstd[2];
      float2 cs1[10];
      uint32_t pa = 0, pb = 0;
#pragma unroll 1
      for (int k = 0; k < 10; k++) {
        mbar_wait(fullA + 8 * ra.idx, ra.phase);
        mbar_wait(fullB + 8 * rb.idx, rb.phase);
        if (k == 0) TSTAMP(2);
        const uint32_t a0 = sb16 + ((OFF_A + ra.idx * SLOT_A + wg * 8192) >> 4), b0 = sb16 + ((OFF_B + rb.idx * SLOT_B) >> 4);
        wg_fence();
#pragma unroll
        for (int kk = 0; kk < 4; kk++) {
          const uint64_t da = make_desc(a0, kk * 32, 16, 1024, 1);
          mma_ss256(accM, da, make_desc(b0, (kk >> 1) * 16384 + (kk & 1) * 2048, 4096, 1024, 1));
          mma_ss64(accR, da, make_desc(b0, 32768 + (kk >> 1) * 4096 + (kk & 1) * 512, 1024, 256, 3));
        }
        wg_commit();
        if (k > 0) {
          wg_wait<1>();
          if (k - 1 < 8) release(emptyA + 8 * pa);
          release(emptyB + 8 * pb);
        }
        pa = ra.idx; pb = rb.idx;
        ra.next<NA>(); rb.next<NB>();
      }
      if (lane == 0) flag_wait(FL_PREP, (epoch + 1) * NCTA);
      __syncwarp();
#pragma unroll
      for (int r = 0; r < 2; r++) {
        const float4 st = __ldcg(&g_xstat[128 * i + rloc + 8 * r]);
        st_mean[r] = st.x; st_rstd[r] = st.y; st_g[r] = st.z;
      }
#pragma unroll
      for (int g = 0; g < 10; g++) cs1[g] = __ldcg(reinterpret_cast<const float2*>(g_cs + 80 * j + 8 * g + 2 * t));
      if (tid < 48) reinterpret_cast<float4*>(s_cs)[tid] = __ldcg(reinterpret_cast<const float4*>(g_cs + D_ + 192 * j) + tid);
      wg_wait<0>();
      fence_regs(accM); fence_regs(accR);
      TSTAMP(3);
#define ACC(P_, G, I_) ((G) < 8 ? accM[(P_) * 32 + ((G) & 7) * 4 + (I_)] : accR[(P_) * 8 + ((G) & 1) * 4 + (I_)])
      {
        const int mat = lane >> 3;
        const int tok = warp * 16 + (mat & 1) * 8 + (lane & 7);
        const uint32_t ones = (t == 0) ? 0x00003f80u : 0u;
#pragma unroll
        for (int p = 0; p < 2; p++) {
          const uint32_t rowa = sb + OFF_A + p * SLOT_A + tok * 128;
#pragma unroll
          for (int gg = 0; gg < 3; gg++) {
            const int g0 = 5 * p + 2 * gg;
            uint32_t r0 = pack_bf16(ACC(3, g0, 0), ACC(3, g0, 1)), r1 = pack_bf16(ACC(3, g0, 2), ACC(3, g0, 3));
            uint32_t r2 = ones, r3 = ones;
            if (gg < 2) { r2 = pack_bf16(ACC(3, g0 + 1, 0), ACC(3, g0 + 1, 1)); r3 = pack_bf16(ACC(3, g0 + 1, 2), ACC(3, g0 + 1, 3)); }
            stsm4(rowa + (((2 * gg + (mat >> 1)) ^ (tok & 7)) << 4), r0, r1, r2, r3);
          }
        }
      }
      uint32_t kf[5][4], qf[5][4];
#pragma unroll
      for (int s = 0; s < 5; s++) {
        kf[s][0] = pack_bf16(ACC(2, 2 * s, 0), ACC(2, 2 * s, 1)); kf[s][1] = pack_bf16(ACC(2, 2 * s, 2), ACC(2, 2 * s, 3));
        kf[s][2] = pack_bf16(ACC(2, 2 * s + 1, 0), ACC(2, 2 * s + 1, 1)); kf[s][3] = pack_bf16(ACC(2, 2 * s + 1, 2), ACC(2, 2 * s + 1, 3));
        qf[s][0] = pack_bf16(ACC(1, 2 * s, 0), ACC(1, 2 * s, 1)); qf[s][1] = pack_bf16(ACC(1, 2 * s, 2), ACC(1, 2 * s, 3));
        qf[s][2] = pack_bf16(ACC(1, 2 * s + 1, 0), ACC(1, 2 * s + 1, 1)); qf[s][3] = pack_bf16(ACC(1, 2 * s + 1, 2), ACC(1, 2 * s + 1, 3));
      }
      bar_sync(1, 256);
      float pk[40], pq[40];
      wg_fence();
#pragma unroll
      for (int s = 0; s < 5; s++) {
        if (s == 0) mma_rs80_k_z(pk, kf[s], make_desc(sb16, OFF_MISC, 16, 256, 3));
        else mma_rs80_k(pk, kf[s], make_desc(sb16, OFF_MISC + s * 2560, 16, 256, 3));
      }
#pragma unroll
      for (int s = 0; s < 5; s++) {
        if (s == 0) mma_rs80_k_z(pq, qf[s], make_desc(sb16, OFF_MISC, 16, 256, 3));
        else mma_rs80_k(pq, qf[s], make_desc(sb16, OFF_MISC + s * 2560, 16, 256, 3));
      }
      wg_commit();

      {
        const int shift = (j < 2) ? 1 : (j < 4) ? -1 : (j < 6) ? 2 : -2;
        const int row0 = 128 * i + rloc + shift, row1 = row0 + 8;
        const bool ok0 = (unsigned)row0 < (unsigned)S_, ok1 = (unsigned)row1 < (unsigned)S_;
        uint32_t* h0 = reinterpret_cast<uint32_t*>(g_Hs + (size_t)(row0 & (S_ - 1)) * D_ + 80 * j + 2 * t);
        uint32_t* h1 = reinterpret_cast<uint32_t*>(g_Hs + (size_t)(row1 & (S_ - 1)) * D_ + 80 * j + 2 * t);
        const float m0 = -st_mean[0] * st_rstd[0], m1 = -st_mean[1] * st_rstd[1];
#pragma unroll
        for (int g = 0; g < 10; g++) {
          const float2 cs = cs1[g];
          float v0 = gelu_s(fmaf(ACC(0, g, 0), st_rstd[0], m0 * cs.x), 0.5f), v1 = gelu_s(fmaf(ACC(0, g, 1), st_rstd[0], m0 * cs.y), 0.5f);
          float v2 = gelu_s(fmaf(ACC(0, g, 2), st_rstd[1], m1 * cs.x), 0.5f), v3 = gelu_s(fmaf(ACC(0, g, 3), st_rstd[1], m1 * cs.y), 0.5f);
          h0[4 * g] = ok0 ? pack_bf16(v0, v1) : 0u;
          h1[4 * g] = ok1 ? pack_bf16(v2, v3) : 0u;
        }
        signal(1);
      }
#undef ACC
      TSTAMP(4);
      wg_wait<0>();
      fence_regs(pk); fence_regs(pq);
#pragma unroll
      for (int G = 0; G < 10; G++) {
        P[0][G] = pack_bf16(pk[4 * G], pk[4 * G + 1]); P[1][G] = pack_bf16(pk[4 * G + 2], pk[4 * G + 3]);
        qp[0][G] = pack_bf16(pq[4 * G], pq[4 * G + 1]); qp[1][G] = pack_bf16(pq[4 * G + 2], pq[4 * G + 3]);
      }
    }

    uint32_t fr[10][4];
    float4 kvr[2][3];
#pragma unroll 1
    for (int pass = 0; pass < 2; pass++) {
      feature_map(P, fr);
      if (pass == 1) break;
      {
        const int mat = lane >> 3;
        const int tok = warp * 16 + (mat & 1) * 8 + (lane & 7);
        const uint32_t base = sb + OFF_B + tok * 32 + (((mat >> 1) ^ ((tok >> 2) & 1)) << 4);
#pragma unroll
        for (int G = 0; G < 10; G++) stsm4(base + G * 4096, fr[G][0], fr[G][1], fr[G][2], fr[G][3]);
        fence_async_smem();
        bar_sync(1, 256);
        float kv[40];
        const uint32_t a0 = sb16 + ((OFF_A + wg * SLOT_A) >> 4), b0 = sb16 + ((OFF_B + wg * 20480) >> 4);
        wg_fence();
#pragma unroll
        for (int ks = 0; ks < 8; ks++) {
          if (ks == 0) mma_ss80_tt_z(kv, make_desc(a0, 0, 16, 1024, 1), make_desc(b0, 0, 4096, 256, 3));
          else mma_ss80_tt(kv, make_desc(a0, ks * 2048, 16, 1024, 1), make_desc(b0, ks * 512, 4096, 256, 3));
        }
        wg_commit();
        wg_wait<0>();
        fence_regs(kv);
        release(emptyA); release(emptyA + 8); release(emptyB);
        float* dst = g_kv[epoch & 1] + j * KV_J + wg * KV_PAIR;
        const int m0 = (warp & 3) * 16 + (lane >> 2);
#pragma unroll
        for (int r = 0; r < 2; r++) {
          const int m = m0 + 8 * r;
          const bool hi = m >= 20;
          float v[10];
#pragma unroll
          for (int G = 0; G < 10; G++) v[G] = hi ? kv[4 * G + 2 * r + 1] : kv[4 * G + 2 * r];
          float* p = dst + (m < 40 ? m * 48 + t * 12 : 1920 + t * 24 + 12);
          if (m <= 40) { red_add4(p, v[0], v[1], v[2], v[3]); red_add4(p + 4, v[4], v[5], v[6], v[7]); red_add2(p + 8, v[8], v[9]); }
        }
        if (m0 == 32) {
          float* p = dst + 1920 + t * 24;
          red_add4(p, kv[2], kv[6], kv[10], kv[14]); red_add4(p + 4, kv[18], kv[22], kv[26], kv[30]); red_add2(p + 8, kv[34], kv[38]);
        }
        signal(2);
      }
      TSTAMP(5);

      {
        uint32_t xv[2][10];
        {
          const uint32_t* xp = reinterpret_cast<const uint32_t*>(x + (size_t)(128 * i2 + rloc) * D_ + 80 * j2 + 2 * t);
#pragma unroll
          for (int g = 0; g < 10; g++) { xv[0][g] = __ldg(xp + 4 * g); xv[1][g] = __ldg(xp + 8 * (D_ / 2) + 4 * g); }
        }
        float acc[40];
        zero_regs(acc);
        uint32_t pa = 0, pb = 0;
#pragma unroll 1
        for (int k = 0; k < 10; k++) {
          mbar_wait(fullA + 8 * ra.idx, ra.phase);
          if ((k & 3) == 0) mbar_wait(fullB + 8 * rb.idx, rb.phase);
          if (k == 0) TSTAMP(6);
          const uint32_t a0 = sb16 + ((OFF_A + ra.idx * SLOT_A + wg * 8192) >> 4);
          const uint32_t b0 = sb16 + ((OFF_B + rb.idx * SLOT_B + ((k >> 1) & 1) * 20480 + (k & 1) * 2048) >> 4);
          wg_fence();
#pragma unroll
          for (int kk = 0; kk < 4; kk++)
            mma_ss80(acc, make_desc(a0, kk * 32, 16, 1024, 1), make_desc(b0, kk * 512, 4096, 256, 3));
          wg_commit();
          if (k > 0) {
            wg_wait<1>();
            release(emptyA + 8 * pa);
            if ((k & 3) == 0) release(emptyB + 8 * pb);
          }
          pa = ra.idx; pb = rb.idx;
          ra.next<NA>();
          if ((k & 3) == 3 || k == 9) rb.next<NB>();
        }
        wg_wait<0>();
        fence_regs(acc);
        release(emptyA + 8 * pa); release(emptyB + 8 * pb);
        TSTAMP(7);
        uint32_t* xo = reinterpret_cast<uint32_t*>(g_X1 + (size_t)(128 * i2 + rloc) * D_ + 80 * j2 + 2 * t);
#pragma unroll
        for (int r = 0; r < 2; r++) {
          float s = 0.f;
#pragma unroll
          for (int g = 0; g < 10; g++) {
            const uint32_t v = pack_bf16(bf_lo(xv[r][g]) + acc[4 * g + 2 * r], bf_hi(xv[r][g]) + acc[4 * g + 2 * r + 1]);
            xo[r * 8 * (D_ / 2) + 4 * g] = v;
            acc[4 * g + 2 * r] = bf_lo(v); acc[4 * g + 2 * r + 1] = bf_hi(v);
            s += acc[4 * g + 2 * r] + acc[4 * g + 2 * r + 1];
          }
          s += __shfl_xor_sync(0xffffffffu, s, 1); s += __shfl_xor_sync(0xffffffffu, s, 2);
          const float mu = s * (1.f / 80.f);
          float q = 0.f;
#pragma unroll
          for (int g = 0; g < 10; g++) {
            const float d0 = acc[4 * g + 2 * r] - mu, d1 = acc[4 * g + 2 * r + 1] - mu;
            q = fmaf(d0, d0, q); q = fmaf(d1, d1, q);
          }
          q += __shfl_xor_sync(0xffffffffu, q, 1); q += __shfl_xor_sync(0xffffffffu, q, 2);
          if (t == 0) g_st1[(128 * i2 + rloc + 8 * r) * 8 + j2] = make_float2(mu, q);
        }
        signal(3);
      }
      TSTAMP(8);
      if (lane == 0) flag_wait(FL_KV + j, (epoch + 1) * 16u);
      __syncwarp();
#pragma unroll
      for (int u = 0; u < 2; u++) {
        const int it = tid + 256 * u, p = it / 192, rem = it - 192 * p, n = rem >> 2, tq = rem & 3;
        const float4* sp = reinterpret_cast<const float4*>(g_kv[epoch & 1] + j * KV_J + p * KV_PAIR +
                                                           (n < 40 ? n * 48 + tq * 12 : 1920 + tq * 24 + (n & 1) * 12));
        if (it < 384) { kvr[u][0] = __ldcg(sp); kvr[u][1] = __ldcg(sp + 1); kvr[u][2] = __ldcg(sp + 2); }
      }
#pragma unroll
      for (int G = 0; G < 10; G++) { P[0][G] = qp[0][G]; P[1][G] = qp[1][G]; }
    }

    uint32_t of[5][4];
    {
#pragma unroll
      for (int u = 0; u < 2; u++) {
        const int it = tid + 256 * u, p = it / 192, rem = it - 192 * p, n = rem >> 2, tq = rem & 3;
        const int sh = (n < 40 ? (n >= 20) : (n & 1)) * 16;
        const float v[10] = {kvr[u][0].x, kvr[u][0].y, kvr[u][0].z, kvr[u][0].w, kvr[u][1].x, kvr[u][1].y, kvr[u][1].z, kvr[u][1].w, kvr[u][2].x, kvr[u][2].y};
        uint8_t* dst = sgen + OFF_MISC + p * 7680 + n * 32 + tq * 4;
        const int sw = ((n >> 2) & 1) << 4;
        if (it < 384) {
#pragma unroll
          for (int G = 0; G < 10; G++)
            *reinterpret_cast<uint32_t*>(dst + (G >> 1) * 1536 + (((G & 1) << 4) ^ sw)) = pack_bf16(v[G], 0.f) << sh;
        }
      }
      fence_async_smem();
      bar_sync(1, 256);
      float o0[24], o1[24];
      wg_fence();
#pragma unroll
      for (int g = 0; g < 5; g++) {
        if (g == 0) mma_rs48_k_z(o0, fr[g], make_desc(sb16, OFF_MISC, 16, 256, 3));
        else mma_rs48_k(o0, fr[g], make_desc(sb16, OFF_MISC + g * 1536, 16, 256, 3));
      }
#pragma unroll
      for (int g = 0; g < 5; g++) {
        if (g == 0) mma_rs48_k_z(o1, fr[5], make_desc(sb16, OFF_MISC + 7680, 16, 256, 3));
        else mma_rs48_k(o1, fr[5 + g], make_desc(sb16, OFF_MISC + 7680 + g * 1536, 16, 256, 3));
      }
      wg_commit();
      wg_wait<0>();
      fence_regs(o0); fence_regs(o1);
#pragma unroll
      for (int r = 0; r < 2; r++) {
        const float a0 = __fdividef(st_g[r], o0[20 + 2 * r] + 1e-6f), a1 = __fdividef(st_g[r], o0[21 + 2 * r] + 1e-6f);
        const float b0 = __fdividef(st_g[r], o1[20 + 2 * r] + 1e-6f), b1 = __fdividef(st_g[r], o1[21 + 2 * r] + 1e-6f);
        const float am = t < 2 ? a0 : a1, bm = t < 2 ? b0 : b1;
#pragma unroll
        for (int g = 0; g < 5; g++) {
          const float sa = g < 2 ? a0 : (g == 2 ? am : a1), sb2 = g < 2 ? b0 : (g == 2 ? bm : b1);
          of[g >> 1][(g & 1) * 2 + r] = pack_bf16(o0[4 * g + 2 * r] * sa, o0[4 * g + 2 * r + 1] * sa);
          of[(5 + g) >> 1][((5 + g) & 1) * 2 + r] = pack_bf16(o1[4 * g + 2 * r] * sb2, o1[4 * g + 2 * r + 1] * sb2);
        }
      }
    }
    TSTAMP(9);

    uint32_t hf[12][4];
    {
      float acc[96];
      zero_regs(acc);
      uint32_t pa = 0, pb = 0;
#pragma unroll 1
      for (int k = 0; k < 10; k++) {
        mbar_wait(fullA + 8 * ra.idx, ra.phase);
        if ((k & 1) == 0) mbar_wait(fullB + 8 * rb.idx, rb.phase);
        if (k == 0) TSTAMP(10);
        const uint32_t a0 = sb16 + ((OFF_A + ra.idx * SLOT_A + wg * 8192) >> 4);
        const uint32_t b0 = sb16 + ((OFF_B + rb.idx * SLOT_B + (k & 1) * 24576) >> 4);
        wg_fence();
#pragma unroll
        for (int kk = 0; kk < 4; kk++)
          mma_ss192(acc, make_desc(a0, kk * 32, 16, 1024, 1), make_desc(b0, kk * 2048, 8192, 1024, 1));
        wg_commit();
        if (k > 0) {
          wg_wait<1>();
          release(emptyA + 8 * pa);
          if ((k & 1) == 0) release(emptyB + 8 * pb);
        }
        pa = ra.idx; pb = rb.idx;
        ra.next<NA>();
        if (k & 1) rb.next<NB>();
      }
      float rs[2], mm[2];
#pragma unroll
      for (int r = 0; r < 2; r++) {
        const float4 sv = __ldcg(reinterpret_cast<const float4*>(g_st1 + (128 * i + rloc + 8 * r) * 8) + t);
        float mu = sv.x + sv.z;
        mu += __shfl_xor_sync(0xffffffffu, mu, 1); mu += __shfl_xor_sync(0xffffffffu, mu, 2);
        mu *= 0.125f;
        const float d0 = sv.x - mu, d1 = sv.z - mu;
        float q = sv.y + sv.w + 80.f * (d0 * d0 + d1 * d1);
        q += __shfl_xor_sync(0xffffffffu, q, 1); q += __shfl_xor_sync(0xffffffffu, q, 2);
        rs[r] = rsqrtf(q * (1.f / D_) + 1e-5f);
        mm[r] = -mu * rs[r];
      }
      wg_wait<0>();
      fence_regs(acc);
      release(emptyB + 8 * pb);
      TSTAMP(11);
      const float hs0 = 0.5f * (1.f - st_g[0]), hs1 = 0.5f * (1.f - st_g[1]);
#pragma unroll
      for (int g = 0; g < 24; g++) {
        const float2 cs = *reinterpret_cast<const float2*>(s_cs + 8 * g + 2 * t);
        const float v0 = gelu_s(fmaf(acc[4 * g], rs[0], mm[0] * cs.x), hs0), v1 = gelu_s(fmaf(acc[4 * g + 1], rs[0], mm[0] * cs.y), hs0);
        const float v2 = gelu_s(fmaf(acc[4 * g + 2], rs[1], mm[1] * cs.x), hs1), v3 = gelu_s(fmaf(acc[4 * g + 3], rs[1], mm[1] * cs.y), hs1);
        hf[g >> 1][(g & 1) * 2] = pack_bf16(v0, v1);
        hf[g >> 1][(g & 1) * 2 + 1] = pack_bf16(v2, v3);
      }
    }
    TSTAMP(12);

    {
      float acc[40];
      uint4 pk4[5];
      auto issue = [&]() {
        mbar_wait(fullB + 8 * rb.idx, rb.phase);
        const uint32_t b0 = sb16 + ((OFF_B + rb.idx * SLOT_B) >> 4);
        wg_fence();
#pragma unroll
        for (int s = 0; s < 12; s++) {
          if (s == 0) mma_rs80_n_z(acc, hf[s], make_desc(b0, 0, 2048, 256, 3));
          else mma_rs80_n(acc, hf[s], make_desc(b0, (s >> 2) * 10240 + (s & 3) * 512, 2048, 256, 3));
        }
#pragma unroll
        for (int s = 0; s < 5; s++)
          mma_rs80_n(acc, of[s], make_desc(b0, 30720 + s * 512, 2560, 256, 3));
        wg_commit();
      };
      auto ship = [&](int c) {
        uint4* dst = g_part + (size_t)(((i * 8 + ((j + c) & 7)) * 8 + j) * 5) * 256 + tid;
#pragma unroll
        for (int q = 0; q < 5; q++) dst[q * 256] = pk4[q];
        signal(3 + c);
      };
#pragma unroll 1
      for (int c = 0; c < 7; c++) {
        issue();
        if (c > 0) ship(c);
        wg_wait<0>();
        fence_regs(acc);
        release(emptyB + 8 * rb.idx);
        rb.next<NB>();
#pragma unroll
        for (int q = 0; q < 5; q++)
          pk4[q] = make_uint4(pack_bf16(acc[8 * q], acc[8 * q + 1]), pack_bf16(acc[8 * q + 2], acc[8 * q + 3]),
                              pack_bf16(acc[8 * q + 4], acc[8 * q + 5]), pack_bf16(acc[8 * q + 6], acc[8 * q + 7]));
#pragma unroll
        for (int q = 0; q < 5; q++) asm volatile("" : "+r"(pk4[q].x), "+r"(pk4[q].y), "+r"(pk4[q].z), "+r"(pk4[q].w)::"memory");
      }
      issue();
      ship(7);
      TSTAMP(13);
      float sum[40];
      {
        const uint32_t* xp = reinterpret_cast<const uint32_t*>(g_X1 + (size_t)(128 * i + rloc) * D_ + 80 * j + 2 * t);
        const float w0 = 1.f - st_g[0], w1s = 1.f - st_g[1];
#pragma unroll
        for (int g = 0; g < 10; g++) {
          const uint32_t v0 = __ldcg(xp + 4 * g), v1 = __ldcg(xp + 8 * (D_ / 2) + 4 * g);
          sum[4 * g] = w0 * bf_lo(v0); sum[4 * g + 1] = w0 * bf_hi(v0);
          sum[4 * g + 2] = w1s * bf_lo(v1); sum[4 * g + 3] = w1s * bf_hi(v1);
        }
      }
      if (lane == 0) flag_wait(FL_PART + i * 8 + j, (epoch + 1) * 7u);
      __syncwarp();
      TSTAMP(14);
      const uint4* sp = g_part + (size_t)((i * 8 + j) * 8 * 5) * 256 + tid;
      uint4 nx[5];
#pragma unroll
      for (int q = 0; q < 5; q++) nx[q] = __ldcg(sp + (((j + 1) & 7) * 5 + q) * 256);
#pragma unroll 1
      for (int c = 1; c < 8; c++) {
        uint4 cur[5];
#pragma unroll
        for (int q = 0; q < 5; q++) cur[q] = nx[q];
        if (c < 7) {
#pragma unroll
          for (int q = 0; q < 5; q++) nx[q] = __ldcg(sp + (((j + c + 1) & 7) * 5 + q) * 256);
        }
#pragma unroll
        for (int q = 0; q < 5; q++) {
          const uint4 v = cur[q];
          sum[8 * q] += bf_lo(v.x); sum[8 * q + 1] += bf_hi(v.x); sum[8 * q + 2] += bf_lo(v.y); sum[8 * q + 3] += bf_hi(v.y);
          sum[8 * q + 4] += bf_lo(v.z); sum[8 * q + 5] += bf_hi(v.z); sum[8 * q + 6] += bf_lo(v.w); sum[8 * q + 7] += bf_hi(v.w);
        }
      }
      wg_wait<0>(); fence_regs(acc);
      uint32_t* op = reinterpret_cast<uint32_t*>(out + (size_t)(128 * i + rloc) * D_ + 80 * j + 2 * t);
#pragma unroll
      for (int g = 0; g < 10; g++) {
        op[4 * g] = pack_bf16(sum[4 * g] + acc[4 * g], sum[4 * g + 1] + acc[4 * g + 1]);
        op[8 * (D_ / 2) + 4 * g] = pack_bf16(sum[4 * g + 2] + acc[4 * g + 2], sum[4 * g + 3] + acc[4 * g + 3]);
      }
    }
    TSTAMP(15);
    if (tid == 0) asm volatile("red.relaxed.gpu.global.add.u32 [%0], 1;" ::"l"(g_flags + FL_DONE * 32) : "memory");
    asm volatile("barrier.cluster.arrive;\nbarrier.cluster.wait;" ::: "memory");
  }
}

namespace {
typedef CUresult (*EncodeFn)(CUtensorMap*, CUtensorMapDataType, cuuint32_t, void*, const cuuint64_t*, const cuuint64_t*,
                             const cuuint32_t*, const cuuint32_t*, CUtensorMapInterleave, CUtensorMapSwizzle,
                             CUtensorMapL2promotion, CUtensorMapFloatOOBfill);

void encode(EncodeFn fn, CUtensorMap* m, const void* ptr, int rank, const cuuint64_t* dims, const cuuint64_t* strides,
            const cuuint32_t* box, CUtensorMapSwizzle swz) {
  cuuint32_t es[5] = {1, 1, 1, 1, 1};
  fn(m, CU_TENSOR_MAP_DATA_TYPE_BFLOAT16, rank, const_cast<void*>(ptr), dims, strides, box, es, CU_TENSOR_MAP_INTERLEAVE_NONE,
     swz, CU_TENSOR_MAP_L2_PROMOTION_L2_128B, CU_TENSOR_MAP_FLOAT_OOB_FILL_NONE);
}
}

extern "C" void kernel_launch(void* const* d_in, const int* in_sizes, int n_in, void* d_out, int out_size) {
  (void)in_sizes; (void)n_in; (void)out_size;
  const __nv_bfloat16* x = (const __nv_bfloat16*)d_in[0];
  const __nv_bfloat16* wqkv = (const __nv_bfloat16*)d_in[1];
  const __nv_bfloat16* wphi = (const __nv_bfloat16*)d_in[2];
  const __nv_bfloat16* wo = (const __nv_bfloat16*)d_in[3];
  const __nv_bfloat16* w1 = (const __nv_bfloat16*)d_in[5];
  const __nv_bfloat16* w2 = (const __nv_bfloat16*)d_in[6];
  const __nv_bfloat16* w3 = (const __nv_bfloat16*)d_in[7];
  const __nv_bfloat16* w4 = (const __nv_bfloat16*)d_in[8];
  const __nv_bfloat16* gate_w = (const __nv_bfloat16*)d_in[9];

  static EncodeFn enc = nullptr;
  static void *pHs = nullptr, *pX1 = nullptr;
  if (!enc) {
    cudaDriverEntryPointQueryResult qr;
    cudaGetDriverEntryPoint("cuTensorMapEncodeTiled", (void**)&enc, cudaEnableDefault, &qr);
    cudaGetSymbolAddress(&pHs, g_Hs);
    cudaGetSymbolAddress(&pX1, g_X1);
    cudaFuncSetAttribute(fused_kernel, cudaFuncAttributeMaxDynamicSharedMemorySize, SMEM_BYTES);
  }
  Maps m;
  {
    cuuint64_t dims[2] = {D_, S_}, str[1] = {D_ * 2};
    cuuint32_t box[2] = {64, 128}, boxh[2] = {64, 64};
    encode(enc, &m.x, x, 2, dims, str, box, CU_TENSOR_MAP_SWIZZLE_128B);
    encode(enc, &m.hs, pHs, 2, dims, str, boxh, CU_TENSOR_MAP_SWIZZLE_128B);
    encode(enc, &m.x1, pX1, 2, dims, str, box, CU_TENSOR_MAP_SWIZZLE_128B);
  }
  {
    cuuint64_t dims[3] = {80, D_, 8}, str[2] = {D_ * 2, 160};
    cuuint32_t boxm[3] = {64, 32, 1}, boxr[3] = {16, 32, 1};
    encode(enc, &m.w1m, w1, 3, dims, str, boxm, CU_TENSOR_MAP_SWIZZLE_128B);
    encode(enc, &m.w1r, w1, 3, dims, str, boxr, CU_TENSOR_MAP_SWIZZLE_32B);
  }
  {
    cuuint64_t dims[4] = {80, D_, 3, 8}, str[3] = {3 * D_ * 2, D_ * 2, 160};
    cuuint32_t boxm[4] = {64, 32, 3, 1}, boxr[4] = {16, 32, 3, 1};
    encode(enc, &m.qm, wqkv, 4, dims, str, boxm, CU_TENSOR_MAP_SWIZZLE_128B);
    encode(enc, &m.qr, wqkv, 4, dims, str, boxr, CU_TENSOR_MAP_SWIZZLE_32B);
  }
  {
    cuuint64_t dims[3] = {16, D_, 40}, dims4[3] = {16, F_, 40}, str[2] = {D_ * 2, 32};
    cuuint32_t box2[3] = {16, 128, 5}, box4[3] = {16, 64, 5}, boxo[3] = {16, 80, 5};
    encode(enc, &m.w2, w2, 3, dims, str, box2, CU_TENSOR_MAP_SWIZZLE_32B);
    encode(enc, &m.w4, w4, 3, dims4, str, box4, CU_TENSOR_MAP_SWIZZLE_32B);
    encode(enc, &m.wo, wo, 3, dims, str, boxo, CU_TENSOR_MAP_SWIZZLE_32B);
  }
  {
    cuuint64_t dims[3] = {64, D_, 24}, str[2] = {F_ * 2, 128};
    cuuint32_t box[3] = {64, 64, 3};
    encode(enc, &m.w3, w3, 3, dims, str, box, CU_TENSOR_MAP_SWIZZLE_128B);
  }
  fused_kernel<<<NCTA, 384, SMEM_BYTES, cudaStreamPerThread>>>(m, x, wphi, w1, w2, w3, w4, wo, gate_w, (__nv_bfloat16*)d_out);
}
```

```cpp
#include <cuda_runtime.h>
#include <cuda_bf16.h>
#include <cuda.h>
#include <stdint.h>

namespace {

constexpr int S_ = 2048, D_ = 640, F_ = 1536;
constexpr int NCTA = 128;
constexpr int KV_PAIR = 40 * 48 + 96;
constexpr int KV_J = 2 * KV_PAIR;

constexpr int SLOT_B = 49152, NB = 3;
constexpr int SLOT_A = 16384, NA = 4;
constexpr int OFF_B = 0;
constexpr int OFF_A = OFF_B + NB * SLOT_B;
constexpr int OFF_STG = OFF_A + 2 * SLOT_A;
constexpr int OFF_MISC = OFF_A + NA * SLOT_A;
constexpr int OFF_GATE = OFF_MISC + 16384;
constexpr int OFF_CS = OFF_GATE + 1280;
constexpr int OFF_BAR = OFF_CS + 1088;
constexpr int SMEM_BYTES = OFF_BAR + 512;
constexpr int B_FULLA = 0, B_EMPTYA = 4, B_FULLB = 8, B_EMPTYB = 11, B_SIGH = 14, B_SIGKV = 15, B_SIGX1 = 16,
              B_SEND = 17  , B_CS = 31, B_KV = 32, B_STG = 33, B_SDONE = 34  , B_RDY = 42  , NBAR = 56;

constexpr int FL_DONE = 0, FL_H = 1, FL_X1 = FL_H + 16, FL_KV = FL_X1 + 16, FL_CS = FL_KV + 8, FL_PART = FL_CS + 8;
constexpr int FL_COUNT = FL_PART + 16 * 8;
constexpr int ACC_FLOATS = 8 * KV_J + D_ + F_;

struct Maps {
  CUtensorMap x, w1m, w1r, qm, qr, hs, w2, x1, w3, w4, wo, st_h, st_x1, st_out;
};

}

__device__ __align__(1024) __nv_bfloat16 g_Hs[(S_ + 4) * D_];
__device__ __align__(1024) __nv_bfloat16 g_X1[S_ * D_];
__device__ __align__(128) float2 g_st1[S_ * 8];
__device__ __align__(128) float g_acc[2][ACC_FLOATS];
__device__ __align__(128) uint4 g_part[16 * 8 * 8 * 5 * 256];
__device__ __align__(128) unsigned g_flags[FL_COUNT * 32];
#define TSTAMP(n) do {} while (0)
#define TSTAMPX(n) do {} while (0)

namespace {

__device__ __forceinline__ long long gtime() { long long t; asm volatile("mov.u64 %0, %%globaltimer;" : "=l"(t)); return t; }
__device__ __forceinline__ uint32_t smem_u32(const void* p) { return (uint32_t)__cvta_generic_to_shared(p); }
__device__ __forceinline__ void mbar_init(uint32_t bar, int cnt) {
  asm volatile("mbarrier.init.shared::cta.b64 [%0], %1;" ::"r"(bar), "r"(cnt) : "memory");
}
__device__ __forceinline__ void mbar_expect_tx(uint32_t bar, int bytes) {
  asm volatile("mbarrier.arrive.expect_tx.shared::cta.b64 _, [%0], %1;" ::"r"(bar), "r"(bytes) : "memory");
}
__device__ __forceinline__ void mbar_arrive_cta(uint32_t bar, uint32_t cta) {
  asm volatile("{\n.reg .b32 ra;\nmapa.shared::cluster.u32 ra, %0, %1;\nmbarrier.arrive.shared::cluster.b64 _, [ra];\n}"
               ::"r"(bar), "r"(cta) : "memory");
}
__device__ __forceinline__ uint32_t mbar_try(uint32_t bar, uint32_t parity) {
  uint32_t ok;
  asm volatile("{\n.reg .pred p;\nmbarrier.try_wait.parity.shared::cta.b64 p, [%1], %2;\nselp.u32 %0, 1, 0, p;\n}"
               : "=r"(ok) : "r"(bar), "r"(parity) : "memory");
  return ok;
}
constexpr uint32_t WAIT_LIMIT = 1u << 22;
__device__ __forceinline__ void mbar_wait(uint32_t bar, uint32_t parity) {
  uint32_t n = 0;
  while (!mbar_try(bar, parity) && ++n < WAIT_LIMIT) {}
}
__device__ __forceinline__ unsigned ld_acquire(const unsigned* p) {
  unsigned v;
  asm volatile("ld.acquire.gpu.global.u32 %0, [%1];" : "=r"(v) : "l"(p) : "memory");
  return v;
}
__device__ __forceinline__ void flag_wait(int idx, unsigned target) {
  const unsigned* p = g_flags + idx * 32;
  uint32_t n = 0;
  while ((int)(ld_acquire(p) - target) < 0 && ++n < (WAIT_LIMIT >> 4)) {}
}
__device__ __forceinline__ void flag_add(int idx) {
  asm volatile("red.release.gpu.global.add.u32 [%0], 1;" ::"l"(g_flags + idx * 32) : "memory");
}
__device__ __forceinline__ void mbar_arrive(uint32_t bar) {
  asm volatile("mbarrier.arrive.shared::cta.b64 _, [%0];" ::"r"(bar) : "memory");
}
__device__ __forceinline__ void fence_async_all() { asm volatile("fence.proxy.async;" ::: "memory"); }
__device__ __forceinline__ void fence_async_smem() { asm volatile("fence.proxy.async.shared::cta;" ::: "memory"); }
__device__ __forceinline__ void bar_sync(int id, int n) { asm volatile("bar.sync %0, %1;" ::"r"(id), "r"(n) : "memory"); }

__device__ __forceinline__ void tma2d(uint32_t dst, const CUtensorMap* m, uint32_t bar, int c0, int c1) {
  asm volatile("cp.async.bulk.tensor.2d.shared::cluster.global.mbarrier::complete_tx::bytes [%0], [%1, {%3, %4}], [%2];"
               ::"r"(dst), "l"(m), "r"(bar), "r"(c0), "r"(c1) : "memory");
}
__device__ __forceinline__ void tma2d_mc(uint32_t dst, const CUtensorMap* m, uint32_t bar, int c0, int c1) {
  asm volatile("cp.async.bulk.tensor.2d.shared::cluster.global.mbarrier::complete_tx::bytes.multicast::cluster"
               " [%0], [%1, {%3, %4}], [%2], %5;"
               ::"r"(dst), "l"(m), "r"(bar), "r"(c0), "r"(c1), "h"((uint16_t)3) : "memory");
}
__device__ __forceinline__ void tma3d(uint32_t dst, const CUtensorMap* m, uint32_t bar, int c0, int c1, int c2) {
  asm volatile("cp.async.bulk.tensor.3d.shared::cluster.global.mbarrier::complete_tx::bytes [%0], [%1, {%3, %4, %5}], [%2];"
               ::"r"(dst), "l"(m), "r"(bar), "r"(c0), "r"(c1), "r"(c2) : "memory");
}
__device__ __forceinline__ void tma3d_mc(uint32_t dst, const CUtensorMap* m, uint32_t bar, int c0, int c1, int c2) {
  asm volatile("cp.async.bulk.tensor.3d.shared::cluster.global.mbarrier::complete_tx::bytes.multicast::cluster"
               " [%0], [%1, {%3, %4, %5}], [%2], %6;"
               ::"r"(dst), "l"(m), "r"(bar), "r"(c0), "r"(c1), "r"(c2), "h"((uint16_t)3) : "memory");
}
__device__ __forceinline__ void tma4d_mc(uint32_t dst, const CUtensorMap* m, uint32_t bar, int c0, int c1, int c2, int c3) {
  asm volatile("cp.async.bulk.tensor.4d.shared::cluster.global.mbarrier::complete_tx::bytes.multicast::cluster"
               " [%0], [%1, {%3, %4, %5, %6}], [%2], %7;"
               ::"r"(dst), "l"(m), "r"(bar), "r"(c0), "r"(c1), "r"(c2), "r"(c3), "h"((uint16_t)3) : "memory");
}
__device__ __forceinline__ void tma2d_store(const CUtensorMap* m, uint32_t src, int c0, int c1) {
  asm volatile("cp.async.bulk.tensor.2d.global.shared::cta.bulk_group [%0, {%2, %3}], [%1];"
               ::"l"(m), "r"(src), "r"(c0), "r"(c1) : "memory");
}
__device__ __forceinline__ void bulk_store(void* dst, uint32_t src, uint32_t bytes) {
  asm volatile("cp.async.bulk.global.shared::cta.bulk_group [%0], [%1], %2;" ::"l"(dst), "r"(src), "r"(bytes) : "memory");
}
__device__ __forceinline__ void bulk_load(uint32_t dst, const void* src, uint32_t bytes, uint32_t bar) {
  asm volatile("cp.async.bulk.shared::cluster.global.mbarrier::complete_tx::bytes [%0], [%1], %2, [%3];"
               ::"r"(dst), "l"(src), "r"(bytes), "r"(bar) : "memory");
}
__device__ __forceinline__ void bulk_commit() { asm volatile("cp.async.bulk.commit_group;" ::: "memory"); }
template <int N> __device__ __forceinline__ void bulk_wait() { asm volatile("cp.async.bulk.wait_group %0;" ::"n"(N) : "memory"); }
__device__ __forceinline__ void bulk_wait_read() { asm volatile("cp.async.bulk.wait_group.read 0;" ::: "memory"); }
__device__ __forceinline__ void bar_arrive(int id, int n) { asm volatile("bar.arrive %0, %1;" ::"r"(id), "r"(n) : "memory"); }
__device__ __forceinline__ uint4 lds128(uint32_t a) {
  uint4 v;
  asm volatile("ld.shared.v4.u32 {%0, %1, %2, %3}, [%4];" : "=r"(v.x), "=r"(v.y), "=r"(v.z), "=r"(v.w) : "r"(a) : "memory");
  return v;
}
__device__ __forceinline__ void sts128(uint32_t a, uint4 v) {
  asm volatile("st.shared.v4.u32 [%0], {%1, %2, %3, %4};" ::"r"(a), "r"(v.x), "r"(v.y), "r"(v.z), "r"(v.w) : "memory");
}
__device__ __forceinline__ void l2_prefetch(const void* p, uint32_t bytes) {
  asm volatile("cp.async.bulk.prefetch.L2.global [%0], %1;" ::"l"(p), "r"(bytes) : "memory");
}
__device__ __forceinline__ void prefetch_tmap(const CUtensorMap* m) {
  asm volatile("prefetch.tensormap [%0];" ::"l"(m) : "memory");
}
__device__ __forceinline__ uint64_t make_desc(uint32_t a16, uint32_t off, uint32_t lbo, uint32_t sbo, uint32_t swz) {
  const uint32_t lo = a16 + ((off >> 4) + ((lbo >> 4) << 16)), hi = (sbo >> 4) | (swz << 30);
  uint64_t d;
  asm("mov.b64 %0, {%1, %2};" : "=l"(d) : "r"(lo), "r"(hi));
  return d;
}
__device__ __forceinline__ void wg_fence() { asm volatile("wgmma.fence.sync.aligned;" ::: "memory"); }
__device__ __forceinline__ void wg_commit() { asm volatile("wgmma.commit_group.sync.aligned;" ::: "memory"); }
template <int N> __device__ __forceinline__ void wg_wait() { asm volatile("wgmma.wait_group.sync.aligned %0;" ::"n"(N) : "memory"); }
template <int N> __device__ __forceinline__ void fence_regs(float (&d)[N]) {
#pragma unroll
  for (int i = 0; i < N; i++) asm volatile("" : "+f"(d[i])::"memory");
}
template <int N> __device__ __forceinline__ void zero_regs(float (&d)[N]) {
#pragma unroll
  for (int i = 0; i < N; i++) d[i] = 0.f;
}
__device__ __forceinline__ uint32_t pack_bf16(float lo, float hi) {
  uint32_t r;
  asm("cvt.rn.bf16x2.f32 %0, %1, %2;" : "=r"(r) : "f"(hi), "f"(lo));
  return r;
}
__device__ __forceinline__ float bf_lo(uint32_t v) { return __uint_as_float(v << 16); }
__device__ __forceinline__ float bf_hi(uint32_t v) { return __uint_as_float(v & 0xffff0000u); }
__device__ __forceinline__ uint32_t max_bf2(uint32_t a, uint32_t b) {
  uint32_t r; asm("max.bf16x2 %0, %1, %2;" : "=r"(r) : "r"(a), "r"(b)); return r;
}
__device__ __forceinline__ uint32_t min_bf2(uint32_t a, uint32_t b) {
  uint32_t r; asm("min.bf16x2 %0, %1, %2;" : "=r"(r) : "r"(a), "r"(b)); return r;
}
__device__ __forceinline__ float ex2(float x) { float r; asm("ex2.approx.ftz.f32 %0, %1;" : "=f"(r) : "f"(x)); return r; }
__device__ __forceinline__ float rcp(float x) { float r; asm("rcp.approx.ftz.f32 %0, %1;" : "=f"(r) : "f"(x)); return r; }
__device__ __forceinline__ float tanh_ap(float x) { float r; asm("tanh.approx.f32 %0, %1;" : "=f"(r) : "f"(x)); return r; }
__device__ __forceinline__ float gelu_s(float x, float hs) {
  float u = x * fmaf(x * x, 0.0356774081f, 0.7978845608f);
  float hx = x * hs;
  return fmaf(hx, tanh_ap(u), hx);
}
__device__ __forceinline__ void stsm4(uint32_t addr, uint32_t r0, uint32_t r1, uint32_t r2, uint32_t r3) {
  asm volatile("stmatrix.sync.aligned.m8n8.x4.shared.b16 [%0], {%1, %2, %3, %4};"
               ::"r"(addr), "r"(r0), "r"(r1), "r"(r2), "r"(r3) : "memory");
}
__device__ __forceinline__ void red_add4(float* p, float a, float b, float c, float d) {
  asm volatile("red.global.add.v4.f32 [%0], {%1, %2, %3, %4};" ::"l"(p), "f"(a), "f"(b), "f"(c), "f"(d) : "memory");
}
__device__ __forceinline__ void red_add2(float* p, float a, float b) {
  asm volatile("red.global.add.v2.f32 [%0], {%1, %2};" ::"l"(p), "f"(a), "f"(b) : "memory");
}

__device__ __forceinline__ void mma_ss256(float (&d)[128], uint64_t descA, uint64_t descB) {
  asm volatile("wgmma.mma_async.sync.aligned.m64n256k16.f32.bf16.bf16 {"
      "%0, %1, %2, %3, %4, %5, %6, %7, %8, %9, %10, %11, %12, %13, %14, %15, "
      "%16, %17, %18, %19, %20, %21, %22, %23, %24, %25, %26, %27, %28, %29, %30, %31, "
      "%32, %33, %34, %35, %36, %37, %38, %39, %40, %41, %42, %43, %44, %45, %46, %47, "
      "%48, %49, %50, %51, %52, %53, %54, %55, %56, %57, %58, %59, %60, %61, %62, %63, "
      "%64, %65, %66, %67, %68, %69, %70, %71, %72, %73, %74, %75, %76, %77, %78, %79, "
      "%80, %81, %82, %83, %84, %85, %86, %87, %88, %89, %90, %91, %92, %93, %94, %95, "
      "%96, %97, %98, %99, %100, %101, %102, %103, %104, %105, %106, %107, %108, %109, %110, %111, "
      "%112, %113, %114, %115, %116, %117, %118, %119, %120, %121, %122, %123, %124, %125, %126, %127"
      "}, %128, %129, 1, 1, 1, 0, 1;\n"
      : "+f"(d[0]), "+f"(d[1]), "+f"(d[2]), "+f"(d[3]), "+f"(d[4]), "+f"(d[5]), "+f"(d[6]), "+f"(d[7]),
        "+f"(d[8]), "+f"(d[9]), "+f"(d[10]), "+f"(d[11]), "+f"(d[12]), "+f"(d[13]), "+f"(d[14]), "+f"(d[15]),
        "+f"(d[16]), "+f"(d[17]), "+f"(d[18]), "+f"(d[19]), "+f"(d[20]), "+f"(d[21]), "+f"(d[22]), "+f"(d[23]),
        "+f"(d[24]), "+f"(d[25]), "+f"(d[26]), "+f"(d[27]), "+f"(d[28]), "+f"(d[29]), "+f"(d[30]), "+f"(d[31]),
        "+f"(d[32]), "+f"(d[33]), "+f"(d[34]), "+f"(d[35]), "+f"(d[36]), "+f"(d[37]), "+f"(d[38]), "+f"(d[39]),
        "+f"(d[40]), "+f"(d[41]), "+f"(d[42]), "+f"(d[43]), "+f"(d[44]), "+f"(d[45]), "+f"(d[46]), "+f"(d[47]),
        "+f"(d[48]), "+f"(d[49]), "+f"(d[50]), "+f"(d[51]), "+f"(d[52]), "+f"(d[53]), "+f"(d[54]), "+f"(d[55]),
        "+f"(d[56]), "+f"(d[57]), "+f"(d[58]), "+f"(d[59]), "+f"(d[60]), "+f"(d[61]), "+f"(d[62]), "+f"(d[63]),
        "+f"(d[64]), "+f"(d[65]), "+f"(d[66]), "+f"(d[67]), "+f"(d[68]), "+f"(d[69]), "+f"(d[70]), "+f"(d[71]),
        "+f"(d[72]), "+f"(d[73]), "+f"(d[74]), "+f"(d[75]), "+f"(d[76]), "+f"(d[77]), "+f"(d[78]), "+f"(d[79]),
        "+f"(d[80]), "+f"(d[81]), "+f"(d[82]), "+f"(d[83]), "+f"(d[84]), "+f"(d[85]), "+f"(d[86]), "+f"(d[87]),
        "+f"(d[88]), "+f"(d[89]), "+f"(d[90]), "+f"(d[91]), "+f"(d[92]), "+f"(d[93]), "+f"(d[94]), "+f"(d[95]),
        "+f"(d[96]), "+f"(d[97]), "+f"(d[98]), "+f"(d[99]), "+f"(d[100]), "+f"(d[101]), "+f"(d[102]), "+f"(d[103]),
        "+f"(d[104]), "+f"(d[105]), "+f"(d[106]), "+f"(d[107]), "+f"(d[108]), "+f"(d[109]), "+f"(d[110]), "+f"(d[111]),
        "+f"(d[112]), "+f"(d[113]), "+f"(d[114]), "+f"(d[115]), "+f"(d[116]), "+f"(d[117]), "+f"(d[118]), "+f"(d[119]),
        "+f"(d[120]), "+f"(d[121]), "+f"(d[122]), "+f"(d[123]), "+f"(d[124]), "+f"(d[125]), "+f"(d[126]), "+f"(d[127])
      : "l"(descA), "l"(descB));
}

__device__ __forceinline__ void mma_ss64(float (&d)[32], uint64_t descA, uint64_t descB) {
  asm volatile("wgmma.mma_async.sync.aligned.m64n64k16.f32.bf16.bf16 {"
      "%0, %1, %2, %3, %4, %5, %6, %7, %8, %9, %10, %11, %12, %13, %14, %15, "
      "%16, %17, %18, %19, %20, %21, %22, %23, %24, %25, %26, %27, %28, %29, %30, %31"
      "}, %32, %33, 1, 1, 1, 0, 1;\n"
      : "+f"(d[0]), "+f"(d[1]), "+f"(d[2]), "+f"(d[3]), "+f"(d[4]), "+f"(d[5]), "+f"(d[6]), "+f"(d[7]),
        "+f"(d[8]), "+f"(d[9]), "+f"(d[10]), "+f"(d[11]), "+f"(d[12]), "+f"(d[13]), "+f"(d[14]), "+f"(d[15]),
        "+f"(d[16]), "+f"(d[17]), "+f"(d[18]), "+f"(d[19]), "+f"(d[20]), "+f"(d[21]), "+f"(d[22]), "+f"(d[23]),
        "+f"(d[24]), "+f"(d[25]), "+f"(d[26]), "+f"(d[27]), "+f"(d[28]), "+f"(d[29]), "+f"(d[30]), "+f"(d[31])
      : "l"(descA), "l"(descB));
}

__device__ __forceinline__ void mma_ss80(float (&d)[40], uint64_t descA, uint64_t descB) {
  asm volatile("wgmma.mma_async.sync.aligned.m64n80k16.f32.bf16.bf16 {"
      "%0, %1, %2, %3, %4, %5, %6, %7, %8, %9, %10, %11, %12, %13, %14, %15, "
      "%16, %17, %18, %19, %20, %21, %22, %23, %24, %25, %26, %27, %28, %29, %30, %31, "
      "%32, %33, %34, %35, %36, %37, %38, %39"
      "}, %40, %41, 1, 1, 1, 0, 1;\n"
      : "+f"(d[0]), "+f"(d[1]), "+f"(d[2]), "+f"(d[3]), "+f"(d[4]), "+f"(d[5]), "+f"(d[6]), "+f"(d[7]),
        "+f"(d[8]), "+f"(d[9]), "+f"(d[10]), "+f"(d[11]), "+f"(d[12]), "+f"(d[13]), "+f"(d[14]), "+f"(d[15]),
        "+f"(d[16]), "+f"(d[17]), "+f"(d[18]), "+f"(d[19]), "+f"(d[20]), "+f"(d[21]), "+f"(d[22]), "+f"(d[23]),
        "+f"(d[24]), "+f"(d[25]), "+f"(d[26]), "+f"(d[27]), "+f"(d[28]), "+f"(d[29]), "+f"(d[30]), "+f"(d[31]),
        "+f"(d[32]), "+f"(d[33]), "+f"(d[34]), "+f"(d[35]), "+f"(d[36]), "+f"(d[37]), "+f"(d[38]), "+f"(d[39])
      : "l"(descA), "l"(descB));
}

__device__ __forceinline__ void mma_ss192(float (&d)[96], uint64_t descA, uint64_t descB) {
  asm volatile("wgmma.mma_async.sync.aligned.m64n192k16.f32.bf16.bf16 {"
      "%0, %1, %2, %3, %4, %5, %6, %7, %8, %9, %10, %11, %12, %13, %14, %15, "
      "%16, %17, %18, %19, %20, %21, %22, %23, %24, %25, %26, %27, %28, %29, %30, %31, "
      "%32, %33, %34, %35, %36, %37, %38, %39, %40, %41, %42, %43, %44, %45, %46, %47, "
      "%48, %49, %50, %51, %52, %53, %54, %55, %56, %57, %58, %59, %60, %61, %62, %63, "
      "%64, %65, %66, %67, %68, %69, %70, %71, %72, %73, %74, %75, %76, %77, %78, %79, "
      "%80, %81, %82, %83, %84, %85, %86, %87, %88, %89, %90, %91, %92, %93, %94, %95"
      "}, %96, %97, 1, 1, 1, 0, 1;\n"
      : "+f"(d[0]), "+f"(d[1]), "+f"(d[2]), "+f"(d[3]), "+f"(d[4]), "+f"(d[5]), "+f"(d[6]), "+f"(d[7]),
        "+f"(d[8]), "+f"(d[9]), "+f"(d[10]), "+f"(d[11]), "+f"(d[12]), "+f"(d[13]), "+f"(d[14]), "+f"(d[15]),
        "+f"(d[16]), "+f"(d[17]), "+f"(d[18]), "+f"(d[19]), "+f"(d[20]), "+f"(d[21]), "+f"(d[22]), "+f"(d[23]),
        "+f"(d[24]), "+f"(d[25]), "+f"(d[26]), "+f"(d[27]), "+f"(d[28]), "+f"(d[29]), "+f"(d[30]), "+f"(d[31]),
        "+f"(d[32]), "+f"(d[33]), "+f"(d[34]), "+f"(d[35]), "+f"(d[36]), "+f"(d[37]), "+f"(d[38]), "+f"(d[39]),
        "+f"(d[40]), "+f"(d[41]), "+f"(d[42]), "+f"(d[43]), "+f"(d[44]), "+f"(d[45]), "+f"(d[46]), "+f"(d[47]),
        "+f"(d[48]), "+f"(d[49]), "+f"(d[50]), "+f"(d[51]), "+f"(d[52]), "+f"(d[53]), "+f"(d[54]), "+f"(d[55]),
        "+f"(d[56]), "+f"(d[57]), "+f"(d[58]), "+f"(d[59]), "+f"(d[60]), "+f"(d[61]), "+f"(d[62]), "+f"(d[63]),
        "+f"(d[64]), "+f"(d[65]), "+f"(d[66]), "+f"(d[67]), "+f"(d[68]), "+f"(d[69]), "+f"(d[70]), "+f"(d[71]),
        "+f"(d[72]), "+f"(d[73]), "+f"(d[74]), "+f"(d[75]), "+f"(d[76]), "+f"(d[77]), "+f"(d[78]), "+f"(d[79]),
        "+f"(d[80]), "+f"(d[81]), "+f"(d[82]), "+f"(d[83]), "+f"(d[84]), "+f"(d[85]), "+f"(d[86]), "+f"(d[87]),
        "+f"(d[88]), "+f"(d[89]), "+f"(d[90]), "+f"(d[91]), "+f"(d[92]), "+f"(d[93]), "+f"(d[94]), "+f"(d[95])
      : "l"(descA), "l"(descB));
}

__device__ __forceinline__ void mma_ss80_tt(float (&d)[40], uint64_t descA, uint64_t descB) {
  asm volatile("wgmma.mma_async.sync.aligned.m64n80k16.f32.bf16.bf16 {"
      "%0, %1, %2, %3, %4, %5, %6, %7, %8, %9, %10, %11, %12, %13, %14, %15, "
      "%16, %17, %18, %19, %20, %21, %22, %23, %24, %25, %26, %27, %28, %29, %30, %31, "
      "%32, %33, %34, %35, %36, %37, %38, %39"
      "}, %40, %41, 1, 1, 1, 1, 1;\n"
      : "+f"(d[0]), "+f"(d[1]), "+f"(d[2]), "+f"(d[3]), "+f"(d[4]), "+f"(d[5]), "+f"(d[6]), "+f"(d[7]),
        "+f"(d[8]), "+f"(d[9]), "+f"(d[10]), "+f"(d[11]), "+f"(d[12]), "+f"(d[13]), "+f"(d[14]), "+f"(d[15]),
        "+f"(d[16]), "+f"(d[17]), "+f"(d[18]), "+f"(d[19]), "+f"(d[20]), "+f"(d[21]), "+f"(d[22]), "+f"(d[23]),
        "+f"(d[24]), "+f"(d[25]), "+f"(d[26]), "+f"(d[27]), "+f"(d[28]), "+f"(d[29]), "+f"(d[30]), "+f"(d[31]),
        "+f"(d[32]), "+f"(d[33]), "+f"(d[34]), "+f"(d[35]), "+f"(d[36]), "+f"(d[37]), "+f"(d[38]), "+f"(d[39])
      : "l"(descA), "l"(descB));
}
__device__ __forceinline__ void mma_ss80_tt_z(float (&d)[40], uint64_t descA, uint64_t descB) {
  asm volatile("wgmma.mma_async.sync.aligned.m64n80k16.f32.bf16.bf16 {"
      "%0, %1, %2, %3, %4, %5, %6, %7, %8, %9, %10, %11, %12, %13, %14, %15, "
      "%16, %17, %18, %19, %20, %21, %22, %23, %24, %25, %26, %27, %28, %29, %30, %31, "
      "%32, %33, %34, %35, %36, %37, %38, %39"
      "}, %40, %41, 0, 1, 1, 1, 1;\n"
      : "=f"(d[0]), "=f"(d[1]), "=f"(d[2]), "=f"(d[3]), "=f"(d[4]), "=f"(d[5]), "=f"(d[6]), "=f"(d[7]),
        "=f"(d[8]), "=f"(d[9]), "=f"(d[10]), "=f"(d[11]), "=f"(d[12]), "=f"(d[13]), "=f"(d[14]), "=f"(d[15]),
        "=f"(d[16]), "=f"(d[17]), "=f"(d[18]), "=f"(d[19]), "=f"(d[20]), "=f"(d[21]), "=f"(d[22]), "=f"(d[23]),
        "=f"(d[24]), "=f"(d[25]), "=f"(d[26]), "=f"(d[27]), "=f"(d[28]), "=f"(d[29]), "=f"(d[30]), "=f"(d[31]),
        "=f"(d[32]), "=f"(d[33]), "=f"(d[34]), "=f"(d[35]), "=f"(d[36]), "=f"(d[37]), "=f"(d[38]), "=f"(d[39])
      : "l"(descA), "l"(descB));
}

__device__ __forceinline__ void mma_rs80_k(float (&d)[40], const uint32_t (&a)[4], uint64_t descB) {
  asm volatile("wgmma.mma_async.sync.aligned.m64n80k16.f32.bf16.bf16 {"
      "%0, %1, %2, %3, %4, %5, %6, %7, %8, %9, %10, %11, %12, %13, %14, %15, "
      "%16, %17, %18, %19, %20, %21, %22, %23, %24, %25, %26, %27, %28, %29, %30, %31, "
      "%32, %33, %34, %35, %36, %37, %38, %39"
      "}, {%40, %41, %42, %43}, %44, 1, 1, 1, 0;\n"
      : "+f"(d[0]), "+f"(d[1]), "+f"(d[2]), "+f"(d[3]), "+f"(d[4]), "+f"(d[5]), "+f"(d[6]), "+f"(d[7]),
        "+f"(d[8]), "+f"(d[9]), "+f"(d[10]), "+f"(d[11]), "+f"(d[12]), "+f"(d[13]), "+f"(d[14]), "+f"(d[15]),
        "+f"(d[16]), "+f"(d[17]), "+f"(d[18]), "+f"(d[19]), "+f"(d[20]), "+f"(d[21]), "+f"(d[22]), "+f"(d[23]),
        "+f"(d[24]), "+f"(d[25]), "+f"(d[26]), "+f"(d[27]), "+f"(d[28]), "+f"(d[29]), "+f"(d[30]), "+f"(d[31]),
        "+f"(d[32]), "+f"(d[33]), "+f"(d[34]), "+f"(d[35]), "+f"(d[36]), "+f"(d[37]), "+f"(d[38]), "+f"(d[39])
      : "r"(a[0]), "r"(a[1]), "r"(a[2]), "r"(a[3]), "l"(descB));
}
__device__ __forceinline__ void mma_rs80_k_z(float (&d)[40], const uint32_t (&a)[4], uint64_t descB) {
  asm volatile("wgmma.mma_async.sync.aligned.m64n80k16.f32.bf16.bf16 {"
      "%0, %1, %2, %3, %4, %5, %6, %7, %8, %9, %10, %11, %12, %13, %14, %15, "
      "%16, %17, %18, %19, %20, %21, %22, %23, %24, %25, %26, %27, %28, %29, %30, %31, "
      "%32, %33, %34, %35, %36, %37, %38, %39"
      "}, {%40, %41, %42, %43}, %44, 0, 1, 1, 0;\n"
      : "=f"(d[0]), "=f"(d[1]), "=f"(d[2]), "=f"(d[3]), "=f"(d[4]), "=f"(d[5]), "=f"(d[6]), "=f"(d[7]),
        "=f"(d[8]), "=f"(d[9]), "=f"(d[10]), "=f"(d[11]), "=f"(d[12]), "=f"(d[13]), "=f"(d[14]), "=f"(d[15]),
        "=f"(d[16]), "=f"(d[17]), "=f"(d[18]), "=f"(d[19]), "=f"(d[20]), "=f"(d[21]), "=f"(d[22]), "=f"(d[23]),
        "=f"(d[24]), "=f"(d[25]), "=f"(d[26]), "=f"(d[27]), "=f"(d[28]), "=f"(d[29]), "=f"(d[30]), "=f"(d[31]),
        "=f"(d[32]), "=f"(d[33]), "=f"(d[34]), "=f"(d[35]), "=f"(d[36]), "=f"(d[37]), "=f"(d[38]), "=f"(d[39])
      : "r"(a[0]), "r"(a[1]), "r"(a[2]), "r"(a[3]), "l"(descB));
}

__device__ __forceinline__ void mma_rs48_k(float (&d)[24], const uint32_t (&a)[4], uint64_t descB) {
  asm volatile("wgmma.mma_async.sync.aligned.m64n48k16.f32.bf16.bf16 {"
      "%0, %1, %2, %3, %4, %5, %6, %7, %8, %9, %10, %11, %12, %13, %14, %15, "
      "%16, %17, %18, %19, %20, %21, %22, %23"
      "}, {%24, %25, %26, %27}, %28, 1, 1, 1, 0;\n"
      : "+f"(d[0]), "+f"(d[1]), "+f"(d[2]), "+f"(d[3]), "+f"(d[4]), "+f"(d[5]), "+f"(d[6]), "+f"(d[7]),
        "+f"(d[8]), "+f"(d[9]), "+f"(d[10]), "+f"(d[11]), "+f"(d[12]), "+f"(d[13]), "+f"(d[14]), "+f"(d[15]),
        "+f"(d[16]), "+f"(d[17]), "+f"(d[18]), "+f"(d[19]), "+f"(d[20]), "+f"(d[21]), "+f"(d[22]), "+f"(d[23])
      : "r"(a[0]), "r"(a[1]), "r"(a[2]), "r"(a[3]), "l"(descB));
}
__device__ __forceinline__ void mma_rs48_k_z(float (&d)[24], const uint32_t (&a)[4], uint64_t descB) {
  asm volatile("wgmma.mma_async.sync.aligned.m64n48k16.f32.bf16.bf16 {"
      "%0, %1, %2, %3, %4, %5, %6, %7, %8, %9, %10, %11, %12, %13, %14, %15, "
      "%16, %17, %18, %19, %20, %21, %22, %23"
      "}, {%24, %25, %26, %27}, %28, 0, 1, 1, 0;\n"
      : "=f"(d[0]), "=f"(d[1]), "=f"(d[2]), "=f"(d[3]), "=f"(d[4]), "=f"(d[5]), "=f"(d[6]), "=f"(d[7]),
        "=f"(d[8]), "=f"(d[9]), "=f"(d[10]), "=f"(d[11]), "=f"(d[12]), "=f"(d[13]), "=f"(d[14]), "=f"(d[15]),
        "=f"(d[16]), "=f"(d[17]), "=f"(d[18]), "=f"(d[19]), "=f"(d[20]), "=f"(d[21]), "=f"(d[22]), "=f"(d[23])
      : "r"(a[0]), "r"(a[1]), "r"(a[2]), "r"(a[3]), "l"(descB));
}

__device__ __forceinline__ void mma_rs80_n(float (&d)[40], const uint32_t (&a)[4], uint64_t descB) {
  asm volatile("wgmma.mma_async.sync.aligned.m64n80k16.f32.bf16.bf16 {"
      "%0, %1, %2, %3, %4, %5, %6, %7, %8, %9, %10, %11, %12, %13, %14, %15, "
      "%16, %17, %18, %19, %20, %21, %22, %23, %24, %25, %26, %27, %28, %29, %30, %31, "
      "%32, %33, %34, %35, %36, %37, %38, %39"
      "}, {%40, %41, %42, %43}, %44, 1, 1, 1, 1;\n"
      : "+f"(d[0]), "+f"(d[1]), "+f"(d[2]), "+f"(d[3]), "+f"(d[4]), "+f"(d[5]), "+f"(d[6]), "+f"(d[7]),
        "+f"(d[8]), "+f"(d[9]), "+f"(d[10]), "+f"(d[11]), "+f"(d[12]), "+f"(d[13]), "+f"(d[14]), "+f"(d[15]),
        "+f"(d[16]), "+f"(d[17]), "+f"(d[18]), "+f"(d[19]), "+f"(d[20]), "+f"(d[21]), "+f"(d[22]), "+f"(d[23]),
        "+f"(d[24]), "+f"(d[25]), "+f"(d[26]), "+f"(d[27]), "+f"(d[28]), "+f"(d[29]), "+f"(d[30]), "+f"(d[31]),
        "+f"(d[32]), "+f"(d[33]), "+f"(d[34]), "+f"(d[35]), "+f"(d[36]), "+f"(d[37]), "+f"(d[38]), "+f"(d[39])
      : "r"(a[0]), "r"(a[1]), "r"(a[2]), "r"(a[3]), "l"(descB));
}
__device__ __forceinline__ void mma_rs80_n_z(float (&d)[40], const uint32_t (&a)[4], uint64_t descB) {
  asm volatile("wgmma.mma_async.sync.aligned.m64n80k16.f32.bf16.bf16 {"
      "%0, %1, %2, %3, %4, %5, %6, %7, %8, %9, %10, %11, %12, %13, %14, %15, "
      "%16, %17, %18, %19, %20, %21, %22, %23, %24, %25, %26, %27, %28, %29, %30, %31, "
      "%32, %33, %34, %35, %36, %37, %38, %39"
      "}, {%40, %41, %42, %43}, %44, 0, 1, 1, 1;\n"
      : "=f"(d[0]), "=f"(d[1]), "=f"(d[2]), "=f"(d[3]), "=f"(d[4]), "=f"(d[5]), "=f"(d[6]), "=f"(d[7]),
        "=f"(d[8]), "=f"(d[9]), "=f"(d[10]), "=f"(d[11]), "=f"(d[12]), "=f"(d[13]), "=f"(d[14]), "=f"(d[15]),
        "=f"(d[16]), "=f"(d[17]), "=f"(d[18]), "=f"(d[19]), "=f"(d[20]), "=f"(d[21]), "=f"(d[22]), "=f"(d[23]),
        "=f"(d[24]), "=f"(d[25]), "=f"(d[26]), "=f"(d[27]), "=f"(d[28]), "=f"(d[29]), "=f"(d[30]), "=f"(d[31]),
        "=f"(d[32]), "=f"(d[33]), "=f"(d[34]), "=f"(d[35]), "=f"(d[36]), "=f"(d[37]), "=f"(d[38]), "=f"(d[39])
      : "r"(a[0]), "r"(a[1]), "r"(a[2]), "r"(a[3]), "l"(descB));
}

__device__ __forceinline__ void feature_map(const uint32_t (&P)[2][10], uint32_t (&fr)[10][4]) {
  constexpr float L2E = 1.4426950408889634f;
#pragma unroll
  for (int p = 0; p < 2; p++) {
#pragma unroll
    for (int r = 0; r < 2; r++) {
      uint32_t mx = P[r][5 * p], mn = mx;
#pragma unroll
      for (int g = 1; g < 5; g++) { mx = max_bf2(mx, P[r][5 * p + g]); mn = min_bf2(mn, P[r][5 * p + g]); }
      mx = max_bf2(mx, __shfl_xor_sync(0xffffffffu, mx, 1));
      mn = min_bf2(mn, __shfl_xor_sync(0xffffffffu, mn, 1));
      mx = max_bf2(mx, __shfl_xor_sync(0xffffffffu, mx, 2));
      mn = min_bf2(mn, __shfl_xor_sync(0xffffffffu, mn, 2));
      float mx0 = -bf_lo(mx) * L2E, mx1 = -bf_hi(mx) * L2E, mn0 = bf_lo(mn) * L2E, mn1 = bf_hi(mn) * L2E;
      float ep0[5], ep1[5], en0[5], en1[5];
      float sp0 = 0.f, sp1 = 0.f, sn0 = 0.f, sn1 = 0.f;
#pragma unroll
      for (int g = 0; g < 5; g++) {
        float x0 = bf_lo(P[r][5 * p + g]), x1 = bf_hi(P[r][5 * p + g]);
        ep0[g] = ex2(fmaf(x0, L2E, mx0)); ep1[g] = ex2(fmaf(x1, L2E, mx1));
        en0[g] = ex2(fmaf(x0, -L2E, mn0)); en1[g] = ex2(fmaf(x1, -L2E, mn1));
        sp0 += ep0[g]; sp1 += ep1[g]; sn0 += en0[g]; sn1 += en1[g];
      }
      sp0 += __shfl_xor_sync(0xffffffffu, sp0, 1); sp1 += __shfl_xor_sync(0xffffffffu, sp1, 1);
      sn0 += __shfl_xor_sync(0xffffffffu, sn0, 1); sn1 += __shfl_xor_sync(0xffffffffu, sn1, 1);
      sp0 += __shfl_xor_sync(0xffffffffu, sp0, 2); sp1 += __shfl_xor_sync(0xffffffffu, sp1, 2);
      sn0 += __shfl_xor_sync(0xffffffffu, sn0, 2); sn1 += __shfl_xor_sync(0xffffffffu, sn1, 2);
      sp0 = rcp(sp0); sp1 = rcp(sp1); sn0 = rcp(sn0); sn1 = rcp(sn1);
#pragma unroll
      for (int g = 0; g < 5; g++) {
        fr[5 * p + g][r] = pack_bf16(ep0[g] * sp0, ep1[g] * sp1);
        fr[5 * p + g][2 + r] = pack_bf16(en0[g] * sn0, en1[g] * sn1);
      }
    }
  }
}

struct Ring {
  uint32_t idx, phase;
  template <int N> __device__ __forceinline__ void next() { if (++idx == N) { idx = 0; phase ^= 1; } }
};

}

__global__ void __cluster_dims__(2, 1, 1) __launch_bounds__(384, 1)
fused_kernel(const __grid_constant__ Maps maps, const __nv_bfloat16* __restrict__ x, const __nv_bfloat16* __restrict__ wqkv,
             const __nv_bfloat16* __restrict__ wphi, const __nv_bfloat16* __restrict__ w1, const __nv_bfloat16* __restrict__ w2,
             const __nv_bfloat16* __restrict__ w3, const __nv_bfloat16* __restrict__ w4, const __nv_bfloat16* __restrict__ wo,
             const __nv_bfloat16* __restrict__ gate_w) {
  extern __shared__ __align__(1024) uint8_t sgen[];
  const uint32_t sb = smem_u32(sgen);
  const uint32_t sb16 = (sb & 0x3FFFFu) >> 4;
  const uint32_t bars = sb + OFF_BAR;
  const uint32_t fullA = bars + 8 * B_FULLA, emptyA = bars + 8 * B_EMPTYA, fullB = bars + 8 * B_FULLB, emptyB = bars + 8 * B_EMPTYB;

  const int tid = threadIdx.x;
  const int rank = blockIdx.x & 1;
  const int pairIdx = blockIdx.x >> 1;
  const int I = pairIdx >> 3, j = pairIdx & 7;
  const int i = 2 * I + rank;
  const int i2 = 2 * I + (j >> 2);
  const int j2 = 2 * (j & 3) + rank;

  TSTAMP(0);
  uint4 pre = make_uint4(0, 0, 0, 0), pre2 = make_uint4(0, 0, 0, 0);
  if (tid < 200) pre = __ldg(reinterpret_cast<const uint4*>(wphi + (size_t)j * 1600) + tid);
  if (tid < 80) pre2 = __ldg(reinterpret_cast<const uint4*>(gate_w) + tid);
  const unsigned done_cnt = *reinterpret_cast<volatile unsigned*>(g_flags + FL_DONE * 32);
  if (tid >= 320 && tid < 320 + NBAR) {
    const int b = tid - 320;
    const int cnt = (b >= B_EMPTYA && b < B_FULLB) || (b >= B_EMPTYB && b < B_SIGH) ? 16
                    : (b >= B_SEND && b < B_CS) ? 4 : (b >= B_SIGH && b < B_SEND) ? 8 : 1;
    mbar_init(bars + 8 * b, cnt);
    asm volatile("fence.mbarrier_init.release.cluster;" ::: "memory");
  }
  if (tid == 256) { prefetch_tmap(&maps.x); }
  if (tid == 288) { prefetch_tmap(&maps.qm); prefetch_tmap(&maps.w1m); prefetch_tmap(&maps.qr); prefetch_tmap(&maps.w1r); }
  if (tid < 256) {
#pragma unroll 1
    for (int e = tid; e < 800; e += 256) sts128(sb + OFF_MISC + e * 16, make_uint4(0, 0, 0, 0));
  }
  asm volatile("barrier.cluster.arrive.aligned;\nbarrier.cluster.wait.aligned;" ::: "memory");
  TSTAMP(16);

  if (tid >= 256) {
    asm volatile("setmaxnreg.dec.sync.aligned.u32 56;");
    const int lane = tid & 31, pw = (tid >> 5) & 3;
    auto send_stream = [&](int w) {
      const unsigned ep1 = done_cnt / NCTA + 1;
#pragma unroll 1
      for (int c = 0; c < 8; c++) {
        if (c < 7) {
          mbar_wait(bars + 8 * (B_SEND + 2 * c + w), 0);
          bulk_store(g_part + (size_t)(((i * 8 + ((j + c + 1) & 7)) * 8 + j) * 2 + w) * 640,
                     sb + OFF_A + (c % 3) * 20480 + w * 10240, 10240);
        }
        bulk_commit();
        if (c > 0) {
          bulk_wait<1>();
          asm volatile("st.release.gpu.global.u32 [%0], %1;"
                       ::"l"(g_flags + (FL_PART + i * 8 + ((j + c) & 7)) * 32 + 2 * (c - 1) + w), "r"(ep1) : "memory");
          if (c - 1 < 4) mbar_arrive(bars + 8 * (B_SDONE + 2 * (c - 1) + w));
        }
      }
    };
    if (pw == 0) {
      Ring r{0, 1};
      const unsigned tgt = (done_cnt / NCTA + 1) * 8u;
#pragma unroll 1
      for (int k = 0; k < 30; k++) {
        if (k == 10 || k == 20) {
          if (lane < (k == 10 ? 3 : 1)) flag_wait(k == 10 ? FL_H + ((i2 - 1 + lane) & 15) : FL_X1 + i, tgt);
          __syncwarp();
          fence_async_all();
          if (lane == 0) TSTAMPX(k == 10 ? 29 : 30);
        }
        if (lane == 0) {
          if (k == 22) mbar_wait(bars + 8 * B_STG, 0);
          mbar_wait(emptyA + 8 * r.idx, r.phase);
          const uint32_t bar = fullA + 8 * r.idx, slot = sb + OFF_A + r.idx * SLOT_A;
          mbar_expect_tx(bar, SLOT_A);
          if (k >= 10 && k < 20) tma2d_mc(slot + rank * 8192, &maps.hs, bar, 64 * (k - 10), 128 * i2 + 64 * rank);
          else tma2d(slot, k < 10 ? &maps.x : &maps.x1, bar, 64 * (k < 10 ? k : k - 20), 128 * i);
          if (k == 3) { prefetch_tmap(&maps.hs); prefetch_tmap(&maps.x1); }
        }
        r.next<NA>();
      }
      if (lane == 0) send_stream(1);
    } else if (pw == 1) {
      if (lane == 0) {
        Ring r{0, 1};
#pragma unroll 1
        for (int k = 0; k < 26; k++) {
          mbar_wait(emptyB + 8 * r.idx, r.phase);
          const uint32_t bar = fullB + 8 * r.idx, slot = sb + OFF_B + r.idx * SLOT_B;
          if (k < 10) {
            mbar_expect_tx(bar, 40960);
            const int k0 = 64 * k + 32 * rank;
            tma4d_mc(slot + rank * 16384 + 4096, &maps.qm, bar, 0, k0, 0, j);
            tma3d_mc(slot + rank * 16384, &maps.w1m, bar, 0, k0, j);
            tma4d_mc(slot + 32768 + rank * 4096 + 1024, &maps.qr, bar, 64, k0, 0, j);
            tma3d_mc(slot + 32768 + rank * 4096, &maps.w1r, bar, 64, k0, j);
            if (k == 2) { prefetch_tmap(&maps.w2); prefetch_tmap(&maps.w3); prefetch_tmap(&maps.w4); prefetch_tmap(&maps.wo); }
          } else if (k < 13) {
            const int s = k - 10;
            mbar_expect_tx(bar, s < 2 ? 40960 : 20480);
            tma3d(slot, &maps.w2, bar, 0, 256 * s, 5 * j2);
            if (s < 2) tma3d(slot + 20480, &maps.w2, bar, 0, 256 * s + 128, 5 * j2);
          } else if (k < 18) {
            mbar_expect_tx(bar, 49152);
            tma3d_mc(slot + rank * 24576, &maps.w3, bar, 0, 128 * (k - 13) + 64 * rank, 3 * j);
          } else {
            const int d = (j + k - 17) & 7;
            mbar_expect_tx(bar, 43520);
            tma3d_mc(slot + rank * 10240, &maps.w4, bar, 0, 192 * j + 64 * rank, 5 * d);
            tma3d_mc(slot + (rank ? 20480 : 30720), rank ? &maps.w4 : &maps.wo, bar, 0, rank ? 192 * j + 128 : 80 * j, 5 * d);
          }
          r.next<NB>();
        }
      }
    } else {
      const int hw = pw & 1;
      if (lane == 0 && hw == 0) {
        l2_prefetch(x + (size_t)blockIdx.x * (S_ * D_ / NCTA), S_ * D_ * 2 / NCTA);
        l2_prefetch(wqkv + (size_t)blockIdx.x * (D_ * 3 * D_ / NCTA), D_ * 3 * D_ * 2 / NCTA);
        l2_prefetch(w1 + (size_t)blockIdx.x * (D_ * D_ / NCTA), D_ * D_ * 2 / NCTA);
      }
      const unsigned epoch = done_cnt / NCTA;
      float* accg = g_acc[epoch & 1];
#pragma unroll 1
      for (int m = 0; m < 5; m++) {
        const int ch = lane & 7, row = 40 * i + (hw * 4 + (lane >> 3)) * 5;
        const int col = m < 2 ? 80 * j + 64 * m + 8 * ch : 192 * j + 64 * (m - 2) + 8 * ch;
        const __nv_bfloat16* p = m < 2 ? w1 + (size_t)row * D_ + col : w3 + (size_t)row * F_ + col;
        const int ld = m < 2 ? D_ : F_;
        const bool act = m != 1 || ch < 2;
        float a[8];
#pragma unroll
        for (int e = 0; e < 8; e++) a[e] = 0.f;
        if (act) {
#pragma unroll
          for (int it = 0; it < 5; it++) {
            const uint4 v = __ldg(reinterpret_cast<const uint4*>(p + (size_t)it * ld));
            a[0] += bf_lo(v.x); a[1] += bf_hi(v.x); a[2] += bf_lo(v.y); a[3] += bf_hi(v.y);
            a[4] += bf_lo(v.z); a[5] += bf_hi(v.z); a[6] += bf_lo(v.w); a[7] += bf_hi(v.w);
          }
        }
#pragma unroll
        for (int e = 0; e < 4; e++) {
          const float snd = (lane & 8) ? a[e] : a[e + 4], keep = (lane & 8) ? a[e + 4] : a[e];
          a[e] = keep + __shfl_xor_sync(0xffffffffu, snd, 8);
          a[e] += __shfl_xor_sync(0xffffffffu, a[e], 16);
        }
        if (act && lane < 16) red_add4(accg + 8 * KV_J + (m < 2 ? 0 : D_) + col + (lane >> 3) * 4, a[0], a[1], a[2], a[3]);
      }
      __syncwarp();
      if (lane == 0) flag_add(FL_CS + j);
      if (hw == 0) {
        if (lane == 0) {
          TSTAMPX(20);
          l2_prefetch(w2 + (size_t)blockIdx.x * (D_ * D_ / NCTA), D_ * D_ * 2 / NCTA);
          l2_prefetch(w4 + (size_t)blockIdx.x * (F_ * D_ / NCTA), F_ * D_ * 2 / NCTA);
          l2_prefetch(wo + (size_t)blockIdx.x * (D_ * D_ / NCTA), D_ * D_ * 2 / NCTA);
        }
        {
          float* nxt = g_acc[(epoch + 1) & 1];
          constexpr int PER = ACC_FLOATS / NCTA;
#pragma unroll 1
          for (int e = lane; e < PER; e += 32) nxt[blockIdx.x * PER + e] = 0.f;
        }
        if (lane == 0) {
          flag_wait(FL_CS + j, (epoch + 1) * 32u);
          fence_async_all();
          mbar_expect_tx(bars + 8 * B_CS, 1088);
          bulk_load(sb + OFF_CS, accg + 8 * KV_J + 80 * j, 320, bars + 8 * B_CS);
          bulk_load(sb + OFF_CS + 320, accg + 8 * KV_J + D_ + 192 * j, 768, bars + 8 * B_CS);
          TSTAMPX(21);
          flag_wait(FL_KV + j, (epoch + 1) * 16u);
          fence_async_all();
          mbar_expect_tx(bars + 8 * B_KV, KV_J * 4);
          bulk_load(sb + OFF_MISC, accg + j * KV_J, KV_J * 4, bars + 8 * B_KV);
          TSTAMPX(22);
        }
        __syncwarp();
        const unsigned* fp = g_flags + (FL_PART + i * 8 + j) * 32 + lane;
        bool seen = lane >= 14;
        uint32_t n = 0;
        while (!__all_sync(0xffffffffu, seen) && ++n < (WAIT_LIMIT >> 4)) {
          if (!seen && ld_acquire(fp) == epoch + 1) { seen = true; mbar_arrive(bars + 8 * (B_RDY + lane)); }
        }
      } else if (lane == 0) {
        prefetch_tmap(&maps.st_h); prefetch_tmap(&maps.st_x1);
        const int shift = (j < 2) ? 1 : (j < 4) ? -1 : (j < 6) ? 2 : -2;
        if ((shift > 0 && i == 0) || (shift < 0 && i == 15)) {
          const int nz = shift > 0 ? shift : -shift, zr = shift > 0 ? 0 : S_ - nz;
#pragma unroll 1
          for (int e = 0; e < nz * 10; e++)
            reinterpret_cast<uint4*>(g_Hs + (size_t)(2 + zr + e / 10) * D_ + 80 * j)[e % 10] = make_uint4(0, 0, 0, 0);
        }
        mbar_wait(bars + 8 * B_SIGH, 0);
        TSTAMPX(23);
        tma2d_store(&maps.st_h, sb + OFF_STG, 80 * j, 128 * i + 2 + shift);
        tma2d_store(&maps.st_h, sb + OFF_STG + 10240, 80 * j, 128 * i + 66 + shift);
        bulk_commit(); bulk_wait<0>();
        flag_add(FL_H + i);
        TSTAMPX(24);
        mbar_wait(bars + 8 * B_SIGKV, 0);
        TSTAMPX(25);
        flag_add(FL_KV + j);
        TSTAMPX(26);
        mbar_wait(bars + 8 * B_SIGX1, 0);
        TSTAMPX(27);
        tma2d_store(&maps.st_x1, sb + OFF_STG, 80 * j2, 128 * i2);
        tma2d_store(&maps.st_x1, sb + OFF_STG + 10240, 80 * j2, 128 * i2 + 64);
        bulk_commit(); bulk_wait<0>();
        flag_add(FL_X1 + i2);
        mbar_arrive(bars + 8 * B_STG);
        TSTAMPX(28);
        send_stream(0);
      }
    }
    __syncwarp();
    asm volatile("barrier.cluster.arrive;\nbarrier.cluster.wait;" ::: "memory");
  } else {
    asm volatile("setmaxnreg.inc.sync.aligned.u32 224;");
    const int wg = tid >> 7, warp = tid >> 5, lane = tid & 31, t = lane & 3;
    const int rloc = warp * 16 + (lane >> 2);
    const float* s_cs = reinterpret_cast<const float*>(sgen + OFF_CS);
    auto signal = [&](int b) {
      __syncwarp();
      if (lane == 0) mbar_arrive(bars + 8 * b);
    };
    auto release = [&](uint32_t bar) {
      __syncwarp();
      if (lane < 2) mbar_arrive_cta(bar, lane);
    };
    const uint32_t stg_lane = (warp * 16 + ((lane >> 3) & 1) * 8 + (lane & 7)) * 160 + (lane >> 4) * 16;

    if (tid < 80) sts128(sb + OFF_GATE + tid * 16, pre2);
    if (tid < 200) {
      const uint32_t ww[4] = {pre.x, pre.y, pre.z, pre.w};
      const int h = tid / 50;
#pragma unroll
      for (int e = 0; e < 8; e++) {
        const int idx = tid * 8 + e, k = idx / 20, ff = idx - 20 * k;
        const int n = 40 * (h >> 1) + 8 * (ff >> 2) + 2 * (ff & 3) + (h & 1);
        const int off = (k >> 4) * 2560 + n * 32 + ((((k >> 3) ^ (n >> 2)) & 1) << 4) + (k & 7) * 2;
        *reinterpret_cast<unsigned short*>(sgen + OFF_MISC + off) = (unsigned short)(ww[e >> 1] >> ((e & 1) * 16));
      }
      fence_async_smem();
    }
    bar_sync(1, 256);
    TSTAMP(1);

    Ring ra{0, 0}, rb{0, 0};
    uint32_t qp[2][10], P[2][10];
    float st_g[2];
    {
      float accM[128], accR[32];
      zero_regs(accM); zero_regs(accR);
      float piv[2] = {0.f, 0.f}, ssum[2] = {0.f, 0.f}, ssq[2] = {0.f, 0.f}, sg[2] = {0.f, 0.f};
      const int par = (lane >> 2) & 1;
      const uint32_t xoff = rloc * 128;
      uint32_t pa = 0, pb = 0;
#pragma unroll 1
      for (int k = 0; k < 10; k++) {
        mbar_wait(fullA + 8 * ra.idx, ra.phase);
        mbar_wait(fullB + 8 * rb.idx, rb.phase);
        if (k == 0) TSTAMP(2);
        const uint32_t a0 = sb16 + ((OFF_A + ra.idx * SLOT_A + wg * 8192) >> 4), b0 = sb16 + ((OFF_B + rb.idx * SLOT_B) >> 4);
        wg_fence();
#pragma unroll
        for (int kk = 0; kk < 4; kk++) {
          const uint64_t da = make_desc(a0, kk * 32, 16, 1024, 1);
          mma_ss256(accM, da, make_desc(b0, (kk >> 1) * 16384 + (kk & 1) * 2048, 4096, 1024, 1));
          mma_ss64(accR, da, make_desc(b0, 32768 + (kk >> 1) * 4096 + (kk & 1) * 512, 1024, 256, 3));
        }
        wg_commit();
        if (k > 0) {
          wg_wait<1>();
          if (k - 1 < 8) release(emptyA + 8 * pa);
          release(emptyB + 8 * pb);
        }
#pragma unroll
        for (int u = 0; u < 2; u++) {
          const int ch = t + 4 * (u ^ par);
          const uint4 gw = lds128(sb + OFF_GATE + k * 128 + ch * 16);
          const uint32_t gg[4] = {gw.x, gw.y, gw.z, gw.w};
#pragma unroll
          for (int r = 0; r < 2; r++) {
            const uint4 xv = lds128(sb + OFF_A + ra.idx * SLOT_A + xoff + r * 1024 + ((ch ^ (rloc & 7)) << 4));
            const uint32_t xx[4] = {xv.x, xv.y, xv.z, xv.w};
            if (u == 0 && k == 0) piv[r] = bf_lo(xx[0]);
#pragma unroll
            for (int e = 0; e < 4; e++) {
              const float x0 = bf_lo(xx[e]), x1 = bf_hi(xx[e]);
              const float d0 = x0 - piv[r], d1 = x1 - piv[r];
              ssum[r] += d0 + d1;
              ssq[r] = fmaf(d0, d0, ssq[r]); ssq[r] = fmaf(d1, d1, ssq[r]);
              sg[r] = fmaf(x0, bf_lo(gg[e]), sg[r]); sg[r] = fmaf(x1, bf_hi(gg[e]), sg[r]);
            }
          }
        }
        pa = ra.idx; pb = rb.idx;
        ra.next<NA>(); rb.next<NB>();
      }
      TSTAMP(18);
      float st_rstd[2], st_mr[2];
#pragma unroll
      for (int r = 0; r < 2; r++) {
        const float dm = ssum[r] * (1.f / 160.f), ml = piv[r] + dm;
        float m2 = fmaf(-ssum[r], dm, ssq[r]);
        float mu = ml + __shfl_xor_sync(0xffffffffu, ml, 1);
        mu += __shfl_xor_sync(0xffffffffu, mu, 2);
        mu *= 0.25f;
        m2 = fmaf(160.f * (ml - mu), ml - mu, m2);
        m2 += __shfl_xor_sync(0xffffffffu, m2, 1); m2 += __shfl_xor_sync(0xffffffffu, m2, 2);
        float gl = sg[r] + __shfl_xor_sync(0xffffffffu, sg[r], 1);
        gl += __shfl_xor_sync(0xffffffffu, gl, 2);
        st_rstd[r] = rsqrtf(fmaxf(m2, 0.f) * (1.f / D_) + 1e-5f);
        st_mr[r] = -mu * st_rstd[r];
        st_g[r] = rcp(1.f + __expf(-gl));
      }
      mbar_wait(bars + 8 * B_CS, 0);
      TSTAMP(19);
      wg_wait<0>();
      fence_regs(accM); fence_regs(accR);
      TSTAMP(3);
#define ACC(P_, G, I_) ((G) < 8 ? accM[(P_) * 32 + ((G) & 7) * 4 + (I_)] : accR[(P_) * 8 + ((G) & 1) * 4 + (I_)])
      {
        const int mat = lane >> 3;
        const int tok = warp * 16 + (mat & 1) * 8 + (lane & 7);
        const uint32_t ones = (t == 0) ? 0x00003f80u : 0u;
        __syncwarp();
#pragma unroll
        for (int p = 0; p < 2; p++) {
          const uint32_t rowa = sb + OFF_A + p * SLOT_A + tok * 128;
#pragma unroll
          for (int gg = 0; gg < 3; gg++) {
            const int g0 = 5 * p + 2 * gg;
            uint32_t r0 = pack_bf16(ACC(3, g0, 0), ACC(3, g0, 1)), r1 = pack_bf16(ACC(3, g0, 2), ACC(3, g0, 3));
            uint32_t r2 = ones, r3 = ones;
            if (gg < 2) { r2 = pack_bf16(ACC(3, g0 + 1, 0), ACC(3, g0 + 1, 1)); r3 = pack_bf16(ACC(3, g0 + 1, 2), ACC(3, g0 + 1, 3)); }
            stsm4(rowa + (((2 * gg + (mat >> 1)) ^ (tok & 7)) << 4), r0, r1, r2, r3);
          }
        }
      }
      uint32_t kf[5][4], qf[5][4];
#pragma unroll
      for (int s = 0; s < 5; s++) {
        kf[s][0] = pack_bf16(ACC(2, 2 * s, 0), ACC(2, 2 * s, 1)); kf[s][1] = pack_bf16(ACC(2, 2 * s, 2), ACC(2, 2 * s, 3));
        kf[s][2] = pack_bf16(ACC(2, 2 * s + 1, 0), ACC(2, 2 * s + 1, 1)); kf[s][3] = pack_bf16(ACC(2, 2 * s + 1, 2), ACC(2, 2 * s + 1, 3));
        qf[s][0] = pack_bf16(ACC(1, 2 * s, 0), ACC(1, 2 * s, 1)); qf[s][1] = pack_bf16(ACC(1, 2 * s, 2), ACC(1, 2 * s, 3));
        qf[s][2] = pack_bf16(ACC(1, 2 * s + 1, 0), ACC(1, 2 * s + 1, 1)); qf[s][3] = pack_bf16(ACC(1, 2 * s + 1, 2), ACC(1, 2 * s + 1, 3));
      }
      float pk[40], pq[40];
      wg_fence();
#pragma unroll
      for (int s = 0; s < 5; s++) {
        if (s == 0) mma_rs80_k_z(pk, kf[s], make_desc(sb16, OFF_MISC, 16, 256, 3));
        else mma_rs80_k(pk, kf[s], make_desc(sb16, OFF_MISC + s * 2560, 16, 256, 3));
      }
#pragma unroll
      for (int s = 0; s < 5; s++) {
        if (s == 0) mma_rs80_k_z(pq, qf[s], make_desc(sb16, OFF_MISC, 16, 256, 3));
        else mma_rs80_k(pq, qf[s], make_desc(sb16, OFF_MISC + s * 2560, 16, 256, 3));
      }
      wg_commit();
      bar_sync(1, 256);

      {
        uint32_t hv[10][2];
#pragma unroll
        for (int g = 0; g < 10; g++) {
          const float2 cs = *reinterpret_cast<const float2*>(s_cs + 8 * g + 2 * t);
          const float v0 = gelu_s(fmaf(ACC(0, g, 0), st_rstd[0], st_mr[0] * cs.x), 0.5f), v1 = gelu_s(fmaf(ACC(0, g, 1), st_rstd[0], st_mr[0] * cs.y), 0.5f);
          const float v2 = gelu_s(fmaf(ACC(0, g, 2), st_rstd[1], st_mr[1] * cs.x), 0.5f), v3 = gelu_s(fmaf(ACC(0, g, 3), st_rstd[1], st_mr[1] * cs.y), 0.5f);
          hv[g][0] = pack_bf16(v0, v1); hv[g][1] = pack_bf16(v2, v3);
        }
#pragma unroll
        for (int s = 0; s < 5; s++) stsm4(sb + OFF_STG + stg_lane + s * 32, hv[2 * s][0], hv[2 * s][1], hv[2 * s + 1][0], hv[2 * s + 1][1]);
        fence_async_smem();
        signal(B_SIGH);
      }
#undef ACC
      TSTAMP(4);
      wg_wait<0>();
      fence_regs(pk); fence_regs(pq);
#pragma unroll
      for (int G = 0; G < 10; G++) {
        P[0][G] = pack_bf16(pk[4 * G], pk[4 * G + 1]); P[1][G] = pack_bf16(pk[4 * G + 2], pk[4 * G + 3]);
        qp[0][G] = pack_bf16(pq[4 * G], pq[4 * G + 1]); qp[1][G] = pack_bf16(pq[4 * G + 2], pq[4 * G + 3]);
      }
    }

    uint32_t fr[10][4];
    {
      feature_map(P, fr);
      const int mat = lane >> 3;
      const int tok = warp * 16 + (mat & 1) * 8 + (lane & 7);
      const uint32_t base = sb + OFF_B + tok * 32 + (((mat >> 1) ^ ((tok >> 2) & 1)) << 4);
#pragma unroll
      for (int G = 0; G < 10; G++) stsm4(base + G * 4096, fr[G][0], fr[G][1], fr[G][2], fr[G][3]);
      fence_async_smem();
      bar_sync(1, 256);
      float kv[40];
      const uint32_t a0 = sb16 + ((OFF_A + wg * SLOT_A) >> 4), b0 = sb16 + ((OFF_B + wg * 20480) >> 4);
      wg_fence();
#pragma unroll
      for (int ks = 0; ks < 8; ks++) {
        if (ks == 0) mma_ss80_tt_z(kv, make_desc(a0, 0, 16, 1024, 1), make_desc(b0, 0, 4096, 256, 3));
        else mma_ss80_tt(kv, make_desc(a0, ks * 2048, 16, 1024, 1), make_desc(b0, ks * 512, 4096, 256, 3));
      }
      wg_commit();
      wg_wait<0>();
      fence_regs(kv);
      release(emptyA); release(emptyA + 8); release(emptyB);
      float* dst = g_acc[(done_cnt / NCTA) & 1] + j * KV_J + wg * KV_PAIR;
      const int m0 = (warp & 3) * 16 + (lane >> 2);
#pragma unroll
      for (int r = 0; r < 2; r++) {
        const int m = m0 + 8 * r;
        const bool hi = m >= 20;
        float v[10];
#pragma unroll
        for (int G = 0; G < 10; G++) v[G] = hi ? kv[4 * G + 2 * r + 1] : kv[4 * G + 2 * r];
        float* p = dst + (m < 40 ? m * 48 + t * 12 : 1920 + t * 24 + 12);
        if (m <= 40) { red_add4(p, v[0], v[1], v[2], v[3]); red_add4(p + 4, v[4], v[5], v[6], v[7]); red_add2(p + 8, v[8], v[9]); }
      }
      if (m0 == 32) {
        float* p = dst + 1920 + t * 24;
        red_add4(p, kv[2], kv[6], kv[10], kv[14]); red_add4(p + 4, kv[18], kv[22], kv[26], kv[30]); red_add2(p + 8, kv[34], kv[38]);
      }
      signal(B_SIGKV);
    }
    TSTAMP(5);

    {
      uint32_t xv[2][10];
      {
        const uint32_t* xp = reinterpret_cast<const uint32_t*>(x + (size_t)(128 * i2 + rloc) * D_ + 80 * j2 + 2 * t);
#pragma unroll
        for (int g = 0; g < 10; g++) { xv[0][g] = __ldg(xp + 4 * g); xv[1][g] = __ldg(xp + 8 * (D_ / 2) + 4 * g); }
      }
      float acc[40];
      zero_regs(acc);
      uint32_t pa = 0, pb = 0;
#pragma unroll 1
      for (int k = 0; k < 10; k++) {
        mbar_wait(fullA + 8 * ra.idx, ra.phase);
        if ((k & 3) == 0) mbar_wait(fullB + 8 * rb.idx, rb.phase);
        if (k == 0) TSTAMP(6);
        const uint32_t a0 = sb16 + ((OFF_A + ra.idx * SLOT_A + wg * 8192) >> 4);
        const uint32_t b0 = sb16 + ((OFF_B + rb.idx * SLOT_B + ((k >> 1) & 1) * 20480 + (k & 1) * 2048) >> 4);
        wg_fence();
#pragma unroll
        for (int kk = 0; kk < 4; kk++)
          mma_ss80(acc, make_desc(a0, kk * 32, 16, 1024, 1), make_desc(b0, kk * 512, 4096, 256, 3));
        wg_commit();
        if (k > 0) {
          wg_wait<1>();
          release(emptyA + 8 * pa);
          if ((k & 3) == 0) release(emptyB + 8 * pb);
        }
        pa = ra.idx; pb = rb.idx;
        ra.next<NA>();
        if ((k & 3) == 3 || k == 9) rb.next<NB>();
      }
      wg_wait<0>();
      fence_regs(acc);
      release(emptyA + 8 * pa); release(emptyB + 8 * pb);
      TSTAMP(7);
#pragma unroll
      for (int r = 0; r < 2; r++) {
#pragma unroll
        for (int g = 0; g < 10; g++)
          xv[r][g] = pack_bf16(bf_lo(xv[r][g]) + acc[4 * g + 2 * r], bf_hi(xv[r][g]) + acc[4 * g + 2 * r + 1]);
      }
      bar_sync(1, 256);
#pragma unroll
      for (int s = 0; s < 5; s++) stsm4(sb + OFF_STG + stg_lane + s * 32, xv[0][2 * s], xv[1][2 * s], xv[0][2 * s + 1], xv[1][2 * s + 1]);
      fence_async_smem();
#pragma unroll
      for (int r = 0; r < 2; r++) {
        float s = 0.f;
#pragma unroll
        for (int g = 0; g < 10; g++) s += bf_lo(xv[r][g]) + bf_hi(xv[r][g]);
        s += __shfl_xor_sync(0xffffffffu, s, 1); s += __shfl_xor_sync(0xffffffffu, s, 2);
        const float mu = s * (1.f / 80.f);
        float q = 0.f;
#pragma unroll
        for (int g = 0; g < 10; g++) {
          const float d0 = bf_lo(xv[r][g]) - mu, d1 = bf_hi(xv[r][g]) - mu;
          q = fmaf(d0, d0, q); q = fmaf(d1, d1, q);
        }
        q += __shfl_xor_sync(0xffffffffu, q, 1); q += __shfl_xor_sync(0xffffffffu, q, 2);
        if (t == 0) g_st1[(128 * i2 + rloc + 8 * r) * 8 + j2] = make_float2(mu, q);
      }
      signal(B_SIGX1);
    }
    TSTAMP(8);

    uint32_t of[5][4];
    {
      feature_map(qp, fr);
      mbar_wait(bars + 8 * B_KV, 0);
      uint4 kvr[2][3];
#pragma unroll
      for (int u = 0; u < 2; u++) {
        const int it = tid + 256 * u, p = it / 192, rem = it - 192 * p, n = rem >> 2, tq = rem & 3;
        const uint32_t sp = sb + OFF_MISC + 4 * (p * KV_PAIR + (n < 40 ? n * 48 + tq * 12 : 1920 + tq * 24 + (n & 1) * 12));
        if (it < 384) { kvr[u][0] = lds128(sp); kvr[u][1] = lds128(sp + 16); kvr[u][2] = lds128(sp + 32); }
      }
      bar_sync(1, 256);
#pragma unroll
      for (int u = 0; u < 2; u++) {
        const int it = tid + 256 * u, p = it / 192, rem = it - 192 * p, n = rem >> 2, tq = rem & 3;
        const int sh = (n < 40 ? (n >= 20) : (n & 1)) * 16;
        const uint32_t v[10] = {kvr[u][0].x, kvr[u][0].y, kvr[u][0].z, kvr[u][0].w, kvr[u][1].x, kvr[u][1].y, kvr[u][1].z, kvr[u][1].w, kvr[u][2].x, kvr[u][2].y};
        uint8_t* dst = sgen + OFF_MISC + p * 7680 + n * 32 + tq * 4;
        const int sw = ((n >> 2) & 1) << 4;
        if (it < 384) {
#pragma unroll
          for (int G = 0; G < 10; G++)
            *reinterpret_cast<uint32_t*>(dst + (G >> 1) * 1536 + (((G & 1) << 4) ^ sw)) = pack_bf16(__uint_as_float(v[G]), 0.f) << sh;
        }
      }
      fence_async_smem();
      bar_sync(1, 256);
      float o0[24], o1[24];
      wg_fence();
#pragma unroll
      for (int g = 0; g < 5; g++) {
        if (g == 0) mma_rs48_k_z(o0, fr[g], make_desc(sb16, OFF_MISC, 16, 256, 3));
        else mma_rs48_k(o0, fr[g], make_desc(sb16, OFF_MISC + g * 1536, 16, 256, 3));
      }
#pragma unroll
      for (int g = 0; g < 5; g++) {
        if (g == 0) mma_rs48_k_z(o1, fr[5], make_desc(sb16, OFF_MISC + 7680, 16, 256, 3));
        else mma_rs48_k(o1, fr[5 + g], make_desc(sb16, OFF_MISC + 7680 + g * 1536, 16, 256, 3));
      }
      wg_commit();
      wg_wait<0>();
      fence_regs(o0); fence_regs(o1);
#pragma unroll
      for (int r = 0; r < 2; r++) {
        const float a0 = __fdividef(st_g[r], o0[20 + 2 * r] + 1e-6f), a1 = __fdividef(st_g[r], o0[21 + 2 * r] + 1e-6f);
        const float b0 = __fdividef(st_g[r], o1[20 + 2 * r] + 1e-6f), b1 = __fdividef(st_g[r], o1[21 + 2 * r] + 1e-6f);
        const float am = t < 2 ? a0 : a1, bm = t < 2 ? b0 : b1;
#pragma unroll
        for (int g = 0; g < 5; g++) {
          const float sa = g < 2 ? a0 : (g == 2 ? am : a1), sb2 = g < 2 ? b0 : (g == 2 ? bm : b1);
          of[g >> 1][(g & 1) * 2 + r] = pack_bf16(o0[4 * g + 2 * r] * sa, o0[4 * g + 2 * r + 1] * sa);
          of[(5 + g) >> 1][((5 + g) & 1) * 2 + r] = pack_bf16(o1[4 * g + 2 * r] * sb2, o1[4 * g + 2 * r + 1] * sb2);
        }
      }
    }
    TSTAMP(9);

    uint32_t hf[12][4];
    float sum[40];
    {
      float acc[96];
      zero_regs(acc);
      float4 sv[2];
      uint32_t x1v[2][10];
      uint32_t pa = 0, pb = 0;
#pragma unroll 1
      for (int k = 0; k < 10; k++) {
        mbar_wait(fullA + 8 * ra.idx, ra.phase);
        if ((k & 1) == 0) mbar_wait(fullB + 8 * rb.idx, rb.phase);
        if (k == 0) TSTAMP(10);
        const uint32_t a0 = sb16 + ((OFF_A + ra.idx * SLOT_A + wg * 8192) >> 4);
        const uint32_t b0 = sb16 + ((OFF_B + rb.idx * SLOT_B + (k & 1) * 24576) >> 4);
        wg_fence();
#pragma unroll
        for (int kk = 0; kk < 4; kk++)
          mma_ss192(acc, make_desc(a0, kk * 32, 16, 1024, 1), make_desc(b0, kk * 2048, 8192, 1024, 1));
        wg_commit();
        if (k > 0) {
          wg_wait<1>();
          release(emptyA + 8 * pa);
          if ((k & 1) == 0) release(emptyB + 8 * pb);
        }
        if (k == 6) {
#pragma unroll
          for (int r = 0; r < 2; r++) sv[r] = __ldcg(reinterpret_cast<const float4*>(g_st1 + (128 * i + rloc + 8 * r) * 8) + t);
          const uint32_t* xp = reinterpret_cast<const uint32_t*>(g_X1 + (size_t)(128 * i + rloc) * D_ + 80 * j + 2 * t);
#pragma unroll
          for (int g = 0; g < 10; g++) { x1v[0][g] = __ldcg(xp + 4 * g); x1v[1][g] = __ldcg(xp + 8 * (D_ / 2) + 4 * g); }
        }
        pa = ra.idx; pb = rb.idx;
        ra.next<NA>();
        if (k & 1) rb.next<NB>();
      }
      float rs[2], mm[2];
#pragma unroll
      for (int r = 0; r < 2; r++) {
        float mu = sv[r].x + sv[r].z;
        mu += __shfl_xor_sync(0xffffffffu, mu, 1); mu += __shfl_xor_sync(0xffffffffu, mu, 2);
        mu *= 0.125f;
        const float d0 = sv[r].x - mu, d1 = sv[r].z - mu;
        float q = sv[r].y + sv[r].w + 80.f * (d0 * d0 + d1 * d1);
        q += __shfl_xor_sync(0xffffffffu, q, 1); q += __shfl_xor_sync(0xffffffffu, q, 2);
        rs[r] = rsqrtf(q * (1.f / D_) + 1e-5f);
        mm[r] = -mu * rs[r];
      }
      wg_wait<0>();
      fence_regs(acc);
      release(emptyB + 8 * pb);
      if (wg == 1) bar_arrive(2, 256);
      TSTAMP(11);
      const float w0 = 1.f - st_g[0], w1s = 1.f - st_g[1];
      const float hs0 = 0.5f * w0, hs1 = 0.5f * w1s;
#pragma unroll
      for (int g = 0; g < 24; g++) {
        const float2 cs = *reinterpret_cast<const float2*>(s_cs + 80 + 8 * g + 2 * t);
        const float v0 = gelu_s(fmaf(acc[4 * g], rs[0], mm[0] * cs.x), hs0), v1 = gelu_s(fmaf(acc[4 * g + 1], rs[0], mm[0] * cs.y), hs0);
        const float v2 = gelu_s(fmaf(acc[4 * g + 2], rs[1], mm[1] * cs.x), hs1), v3 = gelu_s(fmaf(acc[4 * g + 3], rs[1], mm[1] * cs.y), hs1);
        hf[g >> 1][(g & 1) * 2] = pack_bf16(v0, v1);
        hf[g >> 1][(g & 1) * 2 + 1] = pack_bf16(v2, v3);
      }
#pragma unroll
      for (int g = 0; g < 10; g++) {
        sum[4 * g] = w0 * bf_lo(x1v[0][g]); sum[4 * g + 1] = w0 * bf_hi(x1v[0][g]);
        sum[4 * g + 2] = w1s * bf_lo(x1v[1][g]); sum[4 * g + 3] = w1s * bf_hi(x1v[1][g]);
      }
    }
    TSTAMP(12);

    {
      float acc[40];
      uint4 nx[5];
      const int wt = tid & 127;
      auto issue = [&](bool pass_turn) {
        mbar_wait(fullB + 8 * rb.idx, rb.phase);
        const uint32_t b0 = sb16 + ((OFF_B + rb.idx * SLOT_B) >> 4);
        bar_sync(2 + wg, 256);
        wg_fence();
#pragma unroll
        for (int s = 0; s < 12; s++) {
          if (s == 0) mma_rs80_n_z(acc, hf[s], make_desc(b0, 0, 2048, 256, 3));
          else mma_rs80_n(acc, hf[s], make_desc(b0, (s >> 2) * 10240 + (s & 3) * 512, 2048, 256, 3));
        }
#pragma unroll
        for (int s = 0; s < 5; s++) mma_rs80_n(acc, of[s], make_desc(b0, 30720 + s * 512, 2560, 256, 3));
        wg_commit();
        if (pass_turn) bar_arrive(3 - wg, 256);
      };
      auto fetch = [&](int c) {
        mbar_wait(bars + 8 * (B_RDY + 2 * c + wg), 0);
        const uint4* sp = g_part + (size_t)(((i * 8 + j) * 8 + ((j - 1 - c) & 7)) * 2 + wg) * 640 + wt;
#pragma unroll
        for (int q = 0; q < 5; q++) nx[q] = __ldcg(sp + q * 128);
      };
      auto accum = [&]() {
#pragma unroll
        for (int q = 0; q < 5; q++) {
          const uint4 v = nx[q];
          sum[8 * q] += bf_lo(v.x); sum[8 * q + 1] += bf_hi(v.x); sum[8 * q + 2] += bf_lo(v.y); sum[8 * q + 3] += bf_hi(v.y);
          sum[8 * q + 4] += bf_lo(v.z); sum[8 * q + 5] += bf_hi(v.z); sum[8 * q + 6] += bf_lo(v.w); sum[8 * q + 7] += bf_hi(v.w);
        }
      };
#pragma unroll 1
      for (int c = 0; c < 7; c++) {
        issue(true);
        if (c >= 4) accum();
        if (c >= 3) { fetch(c - 3); mbar_wait(bars + 8 * (B_SDONE + 2 * (c - 3) + wg), 0); }
        wg_wait<0>();
        fence_regs(acc);
        release(emptyB + 8 * rb.idx);
        rb.next<NB>();
        const uint32_t dst = sb + OFF_A + (c % 3) * 20480 + wg * 10240 + wt * 16;
#pragma unroll
        for (int q = 0; q < 5; q++)
          sts128(dst + q * 2048, make_uint4(pack_bf16(acc[8 * q], acc[8 * q + 1]), pack_bf16(acc[8 * q + 2], acc[8 * q + 3]),
                                            pack_bf16(acc[8 * q + 4], acc[8 * q + 5]), pack_bf16(acc[8 * q + 6], acc[8 * q + 7])));
        fence_async_smem();
        signal(B_SEND + 2 * c + wg);
      }
      issue(wg == 0);
      TSTAMP(13);
#pragma unroll 1
      for (int c = 4; c < 7; c++) { accum(); fetch(c); }
      TSTAMP(14);
      accum();
      wg_wait<0>(); fence_regs(acc);
      uint32_t ov[10][2];
#pragma unroll
      for (int g = 0; g < 10; g++) {
        ov[g][0] = pack_bf16(sum[4 * g] + acc[4 * g], sum[4 * g + 1] + acc[4 * g + 1]);
        ov[g][1] = pack_bf16(sum[4 * g + 2] + acc[4 * g + 2], sum[4 * g + 3] + acc[4 * g + 3]);
      }
      const uint32_t ostg = sb + OFF_B + ((rb.idx + 1) % NB) * SLOT_B;
#pragma unroll
      for (int s = 0; s < 5; s++) stsm4(ostg + stg_lane + s * 32, ov[2 * s][0], ov[2 * s][1], ov[2 * s + 1][0], ov[2 * s + 1][1]);
      fence_async_smem();
      bar_sync(4 + wg, 128);
      if (wt == 0) {
        tma2d_store(&maps.st_out, ostg + wg * 10240, 80 * j, 128 * i + 64 * wg);
        bulk_commit(); bulk_wait_read();
      }
    }
    TSTAMP(15);
    if (tid == 0) asm volatile("red.relaxed.gpu.global.add.u32 [%0], 1;" ::"l"(g_flags + FL_DONE * 32) : "memory");
    asm volatile("barrier.cluster.arrive;\nbarrier.cluster.wait;" ::: "memory");
  }
}

namespace {
typedef CUresult (*EncodeFn)(CUtensorMap*, CUtensorMapDataType, cuuint32_t, void*, const cuuint64_t*, const cuuint64_t*,
                             const cuuint32_t*, const cuuint32_t*, CUtensorMapInterleave, CUtensorMapSwizzle,
                             CUtensorMapL2promotion, CUtensorMapFloatOOBfill);

void encode(EncodeFn fn, CUtensorMap* m, const void* ptr, int rank, const cuuint64_t* dims, const cuuint64_t* strides,
            const cuuint32_t* box, CUtensorMapSwizzle swz) {
  cuuint32_t es[5] = {1, 1, 1, 1, 1};
  fn(m, CU_TENSOR_MAP_DATA_TYPE_BFLOAT16, rank, const_cast<void*>(ptr), dims, strides, box, es, CU_TENSOR_MAP_INTERLEAVE_NONE,
     swz, CU_TENSOR_MAP_L2_PROMOTION_L2_128B, CU_TENSOR_MAP_FLOAT_OOB_FILL_NONE);
}
}

extern "C" void kernel_launch(void* const* d_in, const int* in_sizes, int n_in, void* d_out, int out_size) {
  (void)in_sizes; (void)n_in; (void)out_size;
  const __nv_bfloat16* x = (const __nv_bfloat16*)d_in[0];
  const __nv_bfloat16* wqkv = (const __nv_bfloat16*)d_in[1];
  const __nv_bfloat16* wphi = (const __nv_bfloat16*)d_in[2];
  const __nv_bfloat16* wo = (const __nv_bfloat16*)d_in[3];
  const __nv_bfloat16* w1 = (const __nv_bfloat16*)d_in[5];
  const __nv_bfloat16* w2 = (const __nv_bfloat16*)d_in[6];
  const __nv_bfloat16* w3 = (const __nv_bfloat16*)d_in[7];
  const __nv_bfloat16* w4 = (const __nv_bfloat16*)d_in[8];
  const __nv_bfloat16* gate_w = (const __nv_bfloat16*)d_in[9];

  static EncodeFn enc = nullptr;
  static void *pHs = nullptr, *pX1 = nullptr;
  if (!enc) {
    cudaDriverEntryPointQueryResult qr;
    cudaGetDriverEntryPoint("cuTensorMapEncodeTiled", (void**)&enc, cudaEnableDefault, &qr);
    cudaGetSymbolAddress(&pHs, g_Hs);
    cudaGetSymbolAddress(&pX1, g_X1);
    cudaFuncSetAttribute(fused_kernel, cudaFuncAttributeMaxDynamicSharedMemorySize, SMEM_BYTES);
  }
  Maps m;
  {
    cuuint64_t dims[2] = {D_, S_}, str[1] = {D_ * 2};
    cuuint32_t box[2] = {64, 128}, boxh[2] = {64, 64};
    encode(enc, &m.x, x, 2, dims, str, box, CU_TENSOR_MAP_SWIZZLE_128B);
    encode(enc, &m.hs, (const char*)pHs + 2 * D_ * 2, 2, dims, str, boxh, CU_TENSOR_MAP_SWIZZLE_128B);
    encode(enc, &m.x1, pX1, 2, dims, str, box, CU_TENSOR_MAP_SWIZZLE_128B);
    cuuint32_t boxs[2] = {80, 64};
    cuuint64_t dimsp[2] = {D_, S_ + 4};
    encode(enc, &m.st_h, pHs, 2, dimsp, str, boxs, CU_TENSOR_MAP_SWIZZLE_NONE);
    encode(enc, &m.st_x1, pX1, 2, dims, str, boxs, CU_TENSOR_MAP_SWIZZLE_NONE);
    encode(enc, &m.st_out, d_out, 2, dims, str, boxs, CU_TENSOR_MAP_SWIZZLE_NONE);
  }
  {
    cuuint64_t dims[3] = {80, D_, 8}, str[2] = {D_ * 2, 160};
    cuuint32_t boxm[3] = {64, 32, 1}, boxr[3] = {16, 32, 1};
    encode(enc, &m.w1m, w1, 3, dims, str, boxm, CU_TENSOR_MAP_SWIZZLE_128B);
    encode(enc, &m.w1r, w1, 3, dims, str, boxr, CU_TENSOR_MAP_SWIZZLE_32B);
  }
  {
    cuuint64_t dims[4] = {80, D_, 3, 8}, str[3] = {3 * D_ * 2, D_ * 2, 160};
    cuuint32_t boxm[4] = {64, 32, 3, 1}, boxr[4] = {16, 32, 3, 1};
    encode(enc, &m.qm, wqkv, 4, dims, str, boxm, CU_TENSOR_MAP_SWIZZLE_128B);
    encode(enc, &m.qr, wqkv, 4, dims, str, boxr, CU_TENSOR_MAP_SWIZZLE_32B);
  }
  {
    cuuint64_t dims[3] = {16, D_, 40}, dims4[3] = {16, F_, 40}, str[2] = {D_ * 2, 32};
    cuuint32_t box2[3] = {16, 128, 5}, box4[3] = {16, 64, 5}, boxo[3] = {16, 80, 5};
    encode(enc, &m.w2, w2, 3, dims, str, box2, CU_TENSOR_MAP_SWIZZLE_32B);
    encode(enc, &m.w4, w4, 3, dims4, str, box4, CU_TENSOR_MAP_SWIZZLE_32B);
    encode(enc, &m.wo, wo, 3, dims, str, boxo, CU_TENSOR_MAP_SWIZZLE_32B);
  }
  {
    cuuint64_t dims[3] = {64, D_, 24}, str[2] = {F_ * 2, 128};
    cuuint32_t box[3] = {64, 64, 3};
    encode(enc, &m.w3, w3, 3, dims, str, box, CU_TENSOR_MAP_SWIZZLE_128B);
  }
  fused_kernel<<<NCTA, 384, SMEM_BYTES, cudaStreamPerThread>>>(m, x, wqkv, wphi, w1, w2, w3, w4, wo, gate_w);
}
```

```cpp
#include <cuda_runtime.h>
#include <cuda_bf16.h>
#include <cuda.h>
#include <stdint.h>

namespace {

constexpr int S_ = 2048, D_ = 640, F_ = 1536;
constexpr int NCTA = 128;
constexpr int KV_PAIR = 40 * 48 + 96;
constexpr int KV_J = 2 * KV_PAIR;

constexpr int SLOT_B = 49152, NB = 3;
constexpr int SLOT_A = 16384, NA = 4;
constexpr int OFF_B = 0;
constexpr int OFF_A = OFF_B + NB * SLOT_B;
constexpr int OFF_STG = OFF_A + 2 * SLOT_A;
constexpr int OFF_MISC = OFF_A + NA * SLOT_A;
constexpr int OFF_XST = OFF_MISC + 13312;
constexpr int OFF_CS = OFF_MISC + 16384;
constexpr int OFF_BAR = OFF_CS + 1088;
constexpr int SMEM_BYTES = OFF_BAR + 512;
constexpr int B_FULLA = 0, B_EMPTYA = 4, B_FULLB = 8, B_EMPTYB = 11,
              B_SIGP = 14, B_SIGH = 15, B_SIGKV = 16, B_SIGX1 = 17, B_MFREE = 18, B_SEND = 19  , B_RFREE = 26  ,
              B_CS = 31, B_KV = 32, B_STG = 33, B_ST1 = 34, B_SDONE = 35  , B_RDY = 40  , NBAR = 47;
constexpr int OFF_SEND = OFF_A, OFF_RECV = OFF_A + 40960;

constexpr int FL_DONE = 0, FL_H = 1, FL_X1 = FL_H + 16, FL_KV = FL_X1 + 16, FL_CS = FL_KV + 8, FL_ST = FL_CS + 8, FL_PART = FL_ST + 16;
constexpr int FL_COUNT = FL_PART + 16 * 8;
constexpr int ACC_FLOATS = 8 * KV_J + D_ + F_;

struct Maps {
  CUtensorMap x, w1m, w1r, qm, qr, hs, w2, x1, w3, w4, wo, st_h, st_x1, st_out, xr;
};

}

__device__ __align__(1024) __nv_bfloat16 g_Hs[(S_ + 4) * D_];
__device__ __align__(1024) __nv_bfloat16 g_X1[S_ * D_];
__device__ __align__(128) float g_acc[2][ACC_FLOATS];
__device__ __align__(128) float4 g_xstat[S_];
__device__ __align__(128) float2 g_st1[S_ * 8];
__device__ __align__(128) uint4 g_part[16 * 8 * 8 * 5 * 256];
__device__ __align__(128) unsigned g_flags[FL_COUNT * 32];
#define TSTAMP(n) do {} while (0)
#define TSTAMPX(n) do {} while (0)
#define TRACE(n) do {} while (0)

namespace {

__device__ __forceinline__ long long gtime() { long long t; asm volatile("mov.u64 %0, %%globaltimer;" : "=l"(t)); return t; }
__device__ __forceinline__ uint32_t smem_u32(const void* p) { return (uint32_t)__cvta_generic_to_shared(p); }
__device__ __forceinline__ void mbar_init(uint32_t bar, int cnt) {
  asm volatile("mbarrier.init.shared::cta.b64 [%0], %1;" ::"r"(bar), "r"(cnt) : "memory");
}
__device__ __forceinline__ void mbar_expect_tx(uint32_t bar, int bytes) {
  asm volatile("mbarrier.arrive.expect_tx.shared::cta.b64 _, [%0], %1;" ::"r"(bar), "r"(bytes) : "memory");
}
__device__ __forceinline__ void mbar_arrive_cta(uint32_t bar, uint32_t cta) {
  asm volatile("{\n.reg .b32 ra;\nmapa.shared::cluster.u32 ra, %0, %1;\nmbarrier.arrive.shared::cluster.b64 _, [ra];\n}"
               ::"r"(bar), "r"(cta) : "memory");
}
__device__ __forceinline__ uint32_t mbar_try(uint32_t bar, uint32_t parity) {
  uint32_t ok;
  asm volatile("{\n.reg .pred p;\nmbarrier.try_wait.parity.shared::cta.b64 p, [%1], %2;\nselp.u32 %0, 1, 0, p;\n}"
               : "=r"(ok) : "r"(bar), "r"(parity) : "memory");
  return ok;
}
constexpr uint32_t WAIT_LIMIT = 1u << 22;
__device__ __forceinline__ void mbar_wait(uint32_t bar, uint32_t parity) {
  uint32_t n = 0;
  while (!mbar_try(bar, parity) && ++n < WAIT_LIMIT) {}
}
__device__ __forceinline__ unsigned ld_acquire(const unsigned* p) {
  unsigned v;
  asm volatile("ld.acquire.gpu.global.u32 %0, [%1];" : "=r"(v) : "l"(p) : "memory");
  return v;
}
__device__ __forceinline__ void flag_wait(int idx, unsigned target) {
  const unsigned* p = g_flags + idx * 32;
  uint32_t n = 0;
  while ((int)(ld_acquire(p) - target) < 0 && ++n < (WAIT_LIMIT >> 4)) {}
}
__device__ __forceinline__ void flag_add(int idx) {
  asm volatile("red.release.gpu.global.add.u32 [%0], 1;" ::"l"(g_flags + idx * 32) : "memory");
}
__device__ __forceinline__ void flag_add_relaxed(int idx) {
  asm volatile("red.relaxed.gpu.global.add.u32 [%0], 1;" ::"l"(g_flags + idx * 32) : "memory");
}
__device__ __forceinline__ uint32_t mbar_test(uint32_t bar, uint32_t parity) {
  uint32_t ok;
  asm volatile("{\n.reg .pred p;\nmbarrier.test_wait.parity.shared::cta.b64 p, [%1], %2;\nselp.u32 %0, 1, 0, p;\n}"
               : "=r"(ok) : "r"(bar), "r"(parity) : "memory");
  return ok;
}
__device__ __forceinline__ uint32_t lds32(uint32_t a) {
  uint32_t v;
  asm volatile("ld.shared.u32 %0, [%1];" : "=r"(v) : "r"(a) : "memory");
  return v;
}
__device__ __forceinline__ void mbar_arrive(uint32_t bar) {
  asm volatile("mbarrier.arrive.shared::cta.b64 _, [%0];" ::"r"(bar) : "memory");
}
__device__ __forceinline__ void fence_async_all() { asm volatile("fence.proxy.async;" ::: "memory"); }
__device__ __forceinline__ void fence_async_smem() { asm volatile("fence.proxy.async.shared::cta;" ::: "memory"); }
__device__ __forceinline__ void bar_sync(int id, int n) { asm volatile("bar.sync %0, %1;" ::"r"(id), "r"(n) : "memory"); }

__device__ __forceinline__ void tma2d(uint32_t dst, const CUtensorMap* m, uint32_t bar, int c0, int c1) {
  asm volatile("cp.async.bulk.tensor.2d.shared::cluster.global.mbarrier::complete_tx::bytes [%0], [%1, {%3, %4}], [%2];"
               ::"r"(dst), "l"(m), "r"(bar), "r"(c0), "r"(c1) : "memory");
}
__device__ __forceinline__ void tma2d_mc(uint32_t dst, const CUtensorMap* m, uint32_t bar, int c0, int c1) {
  asm volatile("cp.async.bulk.tensor.2d.shared::cluster.global.mbarrier::complete_tx::bytes.multicast::cluster"
               " [%0], [%1, {%3, %4}], [%2], %5;"
               ::"r"(dst), "l"(m), "r"(bar), "r"(c0), "r"(c1), "h"((uint16_t)3) : "memory");
}
__device__ __forceinline__ void tma3d(uint32_t dst, const CUtensorMap* m, uint32_t bar, int c0, int c1, int c2) {
  asm volatile("cp.async.bulk.tensor.3d.shared::cluster.global.mbarrier::complete_tx::bytes [%0], [%1, {%3, %4, %5}], [%2];"
               ::"r"(dst), "l"(m), "r"(bar), "r"(c0), "r"(c1), "r"(c2) : "memory");
}
__device__ __forceinline__ void tma3d_mc(uint32_t dst, const CUtensorMap* m, uint32_t bar, int c0, int c1, int c2) {
  asm volatile("cp.async.bulk.tensor.3d.shared::cluster.global.mbarrier::complete_tx::bytes.multicast::cluster"
               " [%0], [%1, {%3, %4, %5}], [%2], %6;"
               ::"r"(dst), "l"(m), "r"(bar), "r"(c0), "r"(c1), "r"(c2), "h"((uint16_t)3) : "memory");
}
__device__ __forceinline__ void tma4d_mc(uint32_t dst, const CUtensorMap* m, uint32_t bar, int c0, int c1, int c2, int c3) {
  asm volatile("cp.async.bulk.tensor.4d.shared::cluster.global.mbarrier::complete_tx::bytes.multicast::cluster"
               " [%0], [%1, {%3, %4, %5, %6}], [%2], %7;"
               ::"r"(dst), "l"(m), "r"(bar), "r"(c0), "r"(c1), "r"(c2), "r"(c3), "h"((uint16_t)3) : "memory");
}
__device__ __forceinline__ void tma2d_store(const CUtensorMap* m, uint32_t src, int c0, int c1) {
  asm volatile("cp.async.bulk.tensor.2d.global.shared::cta.bulk_group [%0, {%2, %3}], [%1];"
               ::"l"(m), "r"(src), "r"(c0), "r"(c1) : "memory");
}
__device__ __forceinline__ void bulk_store(void* dst, uint32_t src, uint32_t bytes) {
  asm volatile("cp.async.bulk.global.shared::cta.bulk_group [%0], [%1], %2;" ::"l"(dst), "r"(src), "r"(bytes) : "memory");
}
__device__ __forceinline__ void bulk_load(uint32_t dst, const void* src, uint32_t bytes, uint32_t bar) {
  asm volatile("cp.async.bulk.shared::cluster.global.mbarrier::complete_tx::bytes [%0], [%1], %2, [%3];"
               ::"r"(dst), "l"(src), "r"(bytes), "r"(bar) : "memory");
}
__device__ __forceinline__ void bulk_commit() { asm volatile("cp.async.bulk.commit_group;" ::: "memory"); }
template <int N> __device__ __forceinline__ void bulk_wait() { asm volatile("cp.async.bulk.wait_group %0;" ::"n"(N) : "memory"); }
__device__ __forceinline__ void bulk_wait_read() { asm volatile("cp.async.bulk.wait_group.read 0;" ::: "memory"); }
__device__ __forceinline__ void bar_arrive(int id, int n) { asm volatile("bar.arrive %0, %1;" ::"r"(id), "r"(n) : "memory"); }
__device__ __forceinline__ uint4 lds128(uint32_t a) {
  uint4 v;
  asm volatile("ld.shared.v4.u32 {%0, %1, %2, %3}, [%4];" : "=r"(v.x), "=r"(v.y), "=r"(v.z), "=r"(v.w) : "r"(a) : "memory");
  return v;
}
__device__ __forceinline__ void sts128(uint32_t a, uint4 v) {
  asm volatile("st.shared.v4.u32 [%0], {%1, %2, %3, %4};" ::"r"(a), "r"(v.x), "r"(v.y), "r"(v.z), "r"(v.w) : "memory");
}
__device__ __forceinline__ void l2_prefetch(const void* p, uint32_t bytes) {
  asm volatile("cp.async.bulk.prefetch.L2.global [%0], %1;" ::"l"(p), "r"(bytes) : "memory");
}
__device__ __forceinline__ void prefetch_tmap(const CUtensorMap* m) {
  asm volatile("prefetch.tensormap [%0];" ::"l"(m) : "memory");
}
__device__ __forceinline__ uint64_t make_desc(uint32_t a16, uint32_t off, uint32_t lbo, uint32_t sbo, uint32_t swz) {
  const uint32_t lo = a16 + ((off >> 4) + ((lbo >> 4) << 16)), hi = (sbo >> 4) | (swz << 30);
  uint64_t d;
  asm("mov.b64 %0, {%1, %2};" : "=l"(d) : "r"(lo), "r"(hi));
  return d;
}
__device__ __forceinline__ void wg_fence() { asm volatile("wgmma.fence.sync.aligned;" ::: "memory"); }
__device__ __forceinline__ void wg_commit() { asm volatile("wgmma.commit_group.sync.aligned;" ::: "memory"); }
template <int N> __device__ __forceinline__ void wg_wait() { asm volatile("wgmma.wait_group.sync.aligned %0;" ::"n"(N) : "memory"); }
template <int N> __device__ __forceinline__ void fence_regs(float (&d)[N]) {
#pragma unroll
  for (int i = 0; i < N; i++) asm volatile("" : "+f"(d[i])::"memory");
}
template <int N> __device__ __forceinline__ void zero_regs(float (&d)[N]) {
#pragma unroll
  for (int i = 0; i < N; i++) d[i] = 0.f;
}
__device__ __forceinline__ uint32_t pack_bf16(float lo, float hi) {
  uint32_t r;
  asm("cvt.rn.bf16x2.f32 %0, %1, %2;" : "=r"(r) : "f"(hi), "f"(lo));
  return r;
}
__device__ __forceinline__ float bf_lo(uint32_t v) { return __uint_as_float(v << 16); }
__device__ __forceinline__ float bf_hi(uint32_t v) { return __uint_as_float(v & 0xffff0000u); }
__device__ __forceinline__ uint32_t max_bf2(uint32_t a, uint32_t b) {
  uint32_t r; asm("max.bf16x2 %0, %1, %2;" : "=r"(r) : "r"(a), "r"(b)); return r;
}
__device__ __forceinline__ uint32_t min_bf2(uint32_t a, uint32_t b) {
  uint32_t r; asm("min.bf16x2 %0, %1, %2;" : "=r"(r) : "r"(a), "r"(b)); return r;
}
__device__ __forceinline__ float ex2(float x) { float r; asm("ex2.approx.ftz.f32 %0, %1;" : "=f"(r) : "f"(x)); return r; }
__device__ __forceinline__ float rcp(float x) { float r; asm("rcp.approx.ftz.f32 %0, %1;" : "=f"(r) : "f"(x)); return r; }
__device__ __forceinline__ float tanh_ap(float x) { float r; asm("tanh.approx.f32 %0, %1;" : "=f"(r) : "f"(x)); return r; }
__device__ __forceinline__ float gelu_s(float x, float hs) {
  float u = x * fmaf(x * x, 0.0356774081f, 0.7978845608f);
  float hx = x * hs;
  return fmaf(hx, tanh_ap(u), hx);
}
__device__ __forceinline__ void stsm4(uint32_t addr, uint32_t r0, uint32_t r1, uint32_t r2, uint32_t r3) {
  asm volatile("stmatrix.sync.aligned.m8n8.x4.shared.b16 [%0], {%1, %2, %3, %4};"
               ::"r"(addr), "r"(r0), "r"(r1), "r"(r2), "r"(r3) : "memory");
}
__device__ __forceinline__ void red_add4(float* p, float a, float b, float c, float d) {
  asm volatile("red.global.add.v4.f32 [%0], {%1, %2, %3, %4};" ::"l"(p), "f"(a), "f"(b), "f"(c), "f"(d) : "memory");
}
__device__ __forceinline__ void red_add2(float* p, float a, float b) {
  asm volatile("red.global.add.v2.f32 [%0], {%1, %2};" ::"l"(p), "f"(a), "f"(b) : "memory");
}

__device__ __forceinline__ void mma_ss256(float (&d)[128], uint64_t descA, uint64_t descB) {
  asm volatile("wgmma.mma_async.sync.aligned.m64n256k16.f32.bf16.bf16 {"
      "%0, %1, %2, %3, %4, %5, %6, %7, %8, %9, %10, %11, %12, %13, %14, %15, "
      "%16, %17, %18, %19, %20, %21, %22, %23, %24, %25, %26, %27, %28, %29, %30, %31, "
      "%32, %33, %34, %35, %36, %37, %38, %39, %40, %41, %42, %43, %44, %45, %46, %47, "
      "%48, %49, %50, %51, %52, %53, %54, %55, %56, %57, %58, %59, %60, %61, %62, %63, "
      "%64, %65, %66, %67, %68, %69, %70, %71, %72, %73, %74, %75, %76, %77, %78, %79, "
      "%80, %81, %82, %83, %84, %85, %86, %87, %88, %89, %90, %91, %92, %93, %94, %95, "
      "%96, %97, %98, %99, %100, %101, %102, %103, %104, %105, %106, %107, %108, %109, %110, %111, "
      "%112, %113, %114, %115, %116, %117, %118, %119, %120, %121, %122, %123, %124, %125, %126, %127"
      "}, %128, %129, 1, 1, 1, 0, 1;\n"
      : "+f"(d[0]), "+f"(d[1]), "+f"(d[2]), "+f"(d[3]), "+f"(d[4]), "+f"(d[5]), "+f"(d[6]), "+f"(d[7]),
        "+f"(d[8]), "+f"(d[9]), "+f"(d[10]), "+f"(d[11]), "+f"(d[12]), "+f"(d[13]), "+f"(d[14]), "+f"(d[15]),
        "+f"(d[16]), "+f"(d[17]), "+f"(d[18]), "+f"(d[19]), "+f"(d[20]), "+f"(d[21]), "+f"(d[22]), "+f"(d[23]),
        "+f"(d[24]), "+f"(d[25]), "+f"(d[26]), "+f"(d[27]), "+f"(d[28]), "+f"(d[29]), "+f"(d[30]), "+f"(d[31]),
        "+f"(d[32]), "+f"(d[33]), "+f"(d[34]), "+f"(d[35]), "+f"(d[36]), "+f"(d[37]), "+f"(d[38]), "+f"(d[39]),
        "+f"(d[40]), "+f"(d[41]), "+f"(d[42]), "+f"(d[43]), "+f"(d[44]), "+f"(d[45]), "+f"(d[46]), "+f"(d[47]),
        "+f"(d[48]), "+f"(d[49]), "+f"(d[50]), "+f"(d[51]), "+f"(d[52]), "+f"(d[53]), "+f"(d[54]), "+f"(d[55]),
        "+f"(d[56]), "+f"(d[57]), "+f"(d[58]), "+f"(d[59]), "+f"(d[60]), "+f"(d[61]), "+f"(d[62]), "+f"(d[63]),
        "+f"(d[64]), "+f"(d[65]), "+f"(d[66]), "+f"(d[67]), "+f"(d[68]), "+f"(d[69]), "+f"(d[70]), "+f"(d[71]),
        "+f"(d[72]), "+f"(d[73]), "+f"(d[74]), "+f"(d[75]), "+f"(d[76]), "+f"(d[77]), "+f"(d[78]), "+f"(d[79]),
        "+f"(d[80]), "+f"(d[81]), "+f"(d[82]), "+f"(d[83]), "+f"(d[84]), "+f"(d[85]), "+f"(d[86]), "+f"(d[87]),
        "+f"(d[88]), "+f"(d[89]), "+f"(d[90]), "+f"(d[91]), "+f"(d[92]), "+f"(d[93]), "+f"(d[94]), "+f"(d[95]),
        "+f"(d[96]), "+f"(d[97]), "+f"(d[98]), "+f"(d[99]), "+f"(d[100]), "+f"(d[101]), "+f"(d[102]), "+f"(d[103]),
        "+f"(d[104]), "+f"(d[105]), "+f"(d[106]), "+f"(d[107]), "+f"(d[108]), "+f"(d[109]), "+f"(d[110]), "+f"(d[111]),
        "+f"(d[112]), "+f"(d[113]), "+f"(d[114]), "+f"(d[115]), "+f"(d[116]), "+f"(d[117]), "+f"(d[118]), "+f"(d[119]),
        "+f"(d[120]), "+f"(d[121]), "+f"(d[122]), "+f"(d[123]), "+f"(d[124]), "+f"(d[125]), "+f"(d[126]), "+f"(d[127])
      : "l"(descA), "l"(descB));
}

__device__ __forceinline__ void mma_ss64(float (&d)[32], uint64_t descA, uint64_t descB) {
  asm volatile("wgmma.mma_async.sync.aligned.m64n64k16.f32.bf16.bf16 {"
      "%0, %1, %2, %3, %4, %5, %6, %7, %8, %9, %10, %11, %12, %13, %14, %15, "
      "%16, %17, %18, %19, %20, %21, %22, %23, %24, %25, %26, %27, %28, %29, %30, %31"
      "}, %32, %33, 1, 1, 1, 0, 1;\n"
      : "+f"(d[0]), "+f"(d[1]), "+f"(d[2]), "+f"(d[3]), "+f"(d[4]), "+f"(d[5]), "+f"(d[6]), "+f"(d[7]),
        "+f"(d[8]), "+f"(d[9]), "+f"(d[10]), "+f"(d[11]), "+f"(d[12]), "+f"(d[13]), "+f"(d[14]), "+f"(d[15]),
        "+f"(d[16]), "+f"(d[17]), "+f"(d[18]), "+f"(d[19]), "+f"(d[20]), "+f"(d[21]), "+f"(d[22]), "+f"(d[23]),
        "+f"(d[24]), "+f"(d[25]), "+f"(d[26]), "+f"(d[27]), "+f"(d[28]), "+f"(d[29]), "+f"(d[30]), "+f"(d[31])
      : "l"(descA), "l"(descB));
}

__device__ __forceinline__ void mma_ss80(float (&d)[40], uint64_t descA, uint64_t descB) {
  asm volatile("wgmma.mma_async.sync.aligned.m64n80k16.f32.bf16.bf16 {"
      "%0, %1, %2, %3, %4, %5, %6, %7, %8, %9, %10, %11, %12, %13, %14, %15, "
      "%16, %17, %18, %19, %20, %21, %22, %23, %24, %25, %26, %27, %28, %29, %30, %31, "
      "%32, %33, %34, %35, %36, %37, %38, %39"
      "}, %40, %41, 1, 1, 1, 0, 1;\n"
      : "+f"(d[0]), "+f"(d[1]), "+f"(d[2]), "+f"(d[3]), "+f"(d[4]), "+f"(d[5]), "+f"(d[6]), "+f"(d[7]),
        "+f"(d[8]), "+f"(d[9]), "+f"(d[10]), "+f"(d[11]), "+f"(d[12]), "+f"(d[13]), "+f"(d[14]), "+f"(d[15]),
        "+f"(d[16]), "+f"(d[17]), "+f"(d[18]), "+f"(d[19]), "+f"(d[20]), "+f"(d[21]), "+f"(d[22]), "+f"(d[23]),
        "+f"(d[24]), "+f"(d[25]), "+f"(d[26]), "+f"(d[27]), "+f"(d[28]), "+f"(d[29]), "+f"(d[30]), "+f"(d[31]),
        "+f"(d[32]), "+f"(d[33]), "+f"(d[34]), "+f"(d[35]), "+f"(d[36]), "+f"(d[37]), "+f"(d[38]), "+f"(d[39])
      : "l"(descA), "l"(descB));
}

__device__ __forceinline__ void mma_ss192(float (&d)[96], uint64_t descA, uint64_t descB) {
  asm volatile("wgmma.mma_async.sync.aligned.m64n192k16.f32.bf16.bf16 {"
      "%0, %1, %2, %3, %4, %5, %6, %7, %8, %9, %10, %11, %12, %13, %14, %15, "
      "%16, %17, %18, %19, %20, %21, %22, %23, %24, %25, %26, %27, %28, %29, %30, %31, "
      "%32, %33, %34, %35, %36, %37, %38, %39, %40, %41, %42, %43, %44, %45, %46, %47, "
      "%48, %49, %50, %51, %52, %53, %54, %55, %56, %57, %58, %59, %60, %61, %62, %63, "
      "%64, %65, %66, %67, %68, %69, %70, %71, %72, %73, %74, %75, %76, %77, %78, %79, "
      "%80, %81, %82, %83, %84, %85, %86, %87, %88, %89, %90, %91, %92, %93, %94, %95"
      "}, %96, %97, 1, 1, 1, 0, 1;\n"
      : "+f"(d[0]), "+f"(d[1]), "+f"(d[2]), "+f"(d[3]), "+f"(d[4]), "+f"(d[5]), "+f"(d[6]), "+f"(d[7]),
        "+f"(d[8]), "+f"(d[9]), "+f"(d[10]), "+f"(d[11]), "+f"(d[12]), "+f"(d[13]), "+f"(d[14]), "+f"(d[15]),
        "+f"(d[16]), "+f"(d[17]), "+f"(d[18]), "+f"(d[19]), "+f"(d[20]), "+f"(d[21]), "+f"(d[22]), "+f"(d[23]),
        "+f"(d[24]), "+f"(d[25]), "+f"(d[26]), "+f"(d[27]), "+f"(d[28]), "+f"(d[29]), "+f"(d[30]), "+f"(d[31]),
        "+f"(d[32]), "+f"(d[33]), "+f"(d[34]), "+f"(d[35]), "+f"(d[36]), "+f"(d[37]), "+f"(d[38]), "+f"(d[39]),
        "+f"(d[40]), "+f"(d[41]), "+f"(d[42]), "+f"(d[43]), "+f"(d[44]), "+f"(d[45]), "+f"(d[46]), "+f"(d[47]),
        "+f"(d[48]), "+f"(d[49]), "+f"(d[50]), "+f"(d[51]), "+f"(d[52]), "+f"(d[53]), "+f"(d[54]), "+f"(d[55]),
        "+f"(d[56]), "+f"(d[57]), "+f"(d[58]), "+f"(d[59]), "+f"(d[60]), "+f"(d[61]), "+f"(d[62]), "+f"(d[63]),
        "+f"(d[64]), "+f"(d[65]), "+f"(d[66]), "+f"(d[67]), "+f"(d[68]), "+f"(d[69]), "+f"(d[70]), "+f"(d[71]),
        "+f"(d[72]), "+f"(d[73]), "+f"(d[74]), "+f"(d[75]), "+f"(d[76]), "+f"(d[77]), "+f"(d[78]), "+f"(d[79]),
        "+f"(d[80]), "+f"(d[81]), "+f"(d[82]), "+f"(d[83]), "+f"(d[84]), "+f"(d[85]), "+f"(d[86]), "+f"(d[87]),
        "+f"(d[88]), "+f"(d[89]), "+f"(d[90]), "+f"(d[91]), "+f"(d[92]), "+f"(d[93]), "+f"(d[94]), "+f"(d[95])
      : "l"(descA), "l"(descB));
}

__device__ __forceinline__ void mma_ss80_tt(float (&d)[40], uint64_t descA, uint64_t descB) {
  asm volatile("wgmma.mma_async.sync.aligned.m64n80k16.f32.bf16.bf16 {"
      "%0, %1, %2, %3, %4, %5, %6, %7, %8, %9, %10, %11, %12, %13, %14, %15, "
      "%16, %17, %18, %19, %20, %21, %22, %23, %24, %25, %26, %27, %28, %29, %30, %31, "
      "%32, %33, %34, %35, %36, %37, %38, %39"
      "}, %40, %41, 1, 1, 1, 1, 1;\n"
      : "+f"(d[0]), "+f"(d[1]), "+f"(d[2]), "+f"(d[3]), "+f"(d[4]), "+f"(d[5]), "+f"(d[6]), "+f"(d[7]),
        "+f"(d[8]), "+f"(d[9]), "+f"(d[10]), "+f"(d[11]), "+f"(d[12]), "+f"(d[13]), "+f"(d[14]), "+f"(d[15]),
        "+f"(d[16]), "+f"(d[17]), "+f"(d[18]), "+f"(d[19]), "+f"(d[20]), "+f"(d[21]), "+f"(d[22]), "+f"(d[23]),
        "+f"(d[24]), "+f"(d[25]), "+f"(d[26]), "+f"(d[27]), "+f"(d[28]), "+f"(d[29]), "+f"(d[30]), "+f"(d[31]),
        "+f"(d[32]), "+f"(d[33]), "+f"(d[34]), "+f"(d[35]), "+f"(d[36]), "+f"(d[37]), "+f"(d[38]), "+f"(d[39])
      : "l"(descA), "l"(descB));
}
__device__ __forceinline__ void mma_ss80_tt_z(float (&d)[40], uint64_t descA, uint64_t descB) {
  asm volatile("wgmma.mma_async.sync.aligned.m64n80k16.f32.bf16.bf16 {"
      "%0, %1, %2, %3, %4, %5, %6, %7, %8, %9, %10, %11, %12, %13, %14, %15, "
      "%16, %17, %18, %19, %20, %21, %22, %23, %24, %25, %26, %27, %28, %29, %30, %31, "
      "%32, %33, %34, %35, %36, %37, %38, %39"
      "}, %40, %41, 0, 1, 1, 1, 1;\n"
      : "=f"(d[0]), "=f"(d[1]), "=f"(d[2]), "=f"(d[3]), "=f"(d[4]), "=f"(d[5]), "=f"(d[6]), "=f"(d[7]),
        "=f"(d[8]), "=f"(d[9]), "=f"(d[10]), "=f"(d[11]), "=f"(d[12]), "=f"(d[13]), "=f"(d[14]), "=f"(d[15]),
        "=f"(d[16]), "=f"(d[17]), "=f"(d[18]), "=f"(d[19]), "=f"(d[20]), "=f"(d[21]), "=f"(d[22]), "=f"(d[23]),
        "=f"(d[24]), "=f"(d[25]), "=f"(d[26]), "=f"(d[27]), "=f"(d[28]), "=f"(d[29]), "=f"(d[30]), "=f"(d[31]),
        "=f"(d[32]), "=f"(d[33]), "=f"(d[34]), "=f"(d[35]), "=f"(d[36]), "=f"(d[37]), "=f"(d[38]), "=f"(d[39])
      : "l"(descA), "l"(descB));
}

__device__ __forceinline__ void mma_rs80_k(float (&d)[40], const uint32_t (&a)[4], uint64_t descB) {
  asm volatile("wgmma.mma_async.sync.aligned.m64n80k16.f32.bf16.bf16 {"
      "%0, %1, %2, %3, %4, %5, %6, %7, %8, %9, %10, %11, %12, %13, %14, %15, "
      "%16, %17, %18, %19, %20, %21, %22, %23, %24, %25, %26, %27, %28, %29, %30, %31, "
      "%32, %33, %34, %35, %36, %37, %38, %39"
      "}, {%40, %41, %42, %43}, %44, 1, 1, 1, 0;\n"
      : "+f"(d[0]), "+f"(d[1]), "+f"(d[2]), "+f"(d[3]), "+f"(d[4]), "+f"(d[5]), "+f"(d[6]), "+f"(d[7]),
        "+f"(d[8]), "+f"(d[9]), "+f"(d[10]), "+f"(d[11]), "+f"(d[12]), "+f"(d[13]), "+f"(d[14]), "+f"(d[15]),
        "+f"(d[16]), "+f"(d[17]), "+f"(d[18]), "+f"(d[19]), "+f"(d[20]), "+f"(d[21]), "+f"(d[22]), "+f"(d[23]),
        "+f"(d[24]), "+f"(d[25]), "+f"(d[26]), "+f"(d[27]), "+f"(d[28]), "+f"(d[29]), "+f"(d[30]), "+f"(d[31]),
        "+f"(d[32]), "+f"(d[33]), "+f"(d[34]), "+f"(d[35]), "+f"(d[36]), "+f"(d[37]), "+f"(d[38]), "+f"(d[39])
      : "r"(a[0]), "r"(a[1]), "r"(a[2]), "r"(a[3]), "l"(descB));
}
__device__ __forceinline__ void mma_rs80_k_z(float (&d)[40], const uint32_t (&a)[4], uint64_t descB) {
  asm volatile("wgmma.mma_async.sync.aligned.m64n80k16.f32.bf16.bf16 {"
      "%0, %1, %2, %3, %4, %5, %6, %7, %8, %9, %10, %11, %12, %13, %14, %15, "
      "%16, %17, %18, %19, %20, %21, %22, %23, %24, %25, %26, %27, %28, %29, %30, %31, "
      "%32, %33, %34, %35, %36, %37, %38, %39"
      "}, {%40, %41, %42, %43}, %44, 0, 1, 1, 0;\n"
      : "=f"(d[0]), "=f"(d[1]), "=f"(d[2]), "=f"(d[3]), "=f"(d[4]), "=f"(d[5]), "=f"(d[6]), "=f"(d[7]),
        "=f"(d[8]), "=f"(d[9]), "=f"(d[10]), "=f"(d[11]), "=f"(d[12]), "=f"(d[13]), "=f"(d[14]), "=f"(d[15]),
        "=f"(d[16]), "=f"(d[17]), "=f"(d[18]), "=f"(d[19]), "=f"(d[20]), "=f"(d[21]), "=f"(d[22]), "=f"(d[23]),
        "=f"(d[24]), "=f"(d[25]), "=f"(d[26]), "=f"(d[27]), "=f"(d[28]), "=f"(d[29]), "=f"(d[30]), "=f"(d[31]),
        "=f"(d[32]), "=f"(d[33]), "=f"(d[34]), "=f"(d[35]), "=f"(d[36]), "=f"(d[37]), "=f"(d[38]), "=f"(d[39])
      : "r"(a[0]), "r"(a[1]), "r"(a[2]), "r"(a[3]), "l"(descB));
}

__device__ __forceinline__ void mma_rs48_k(float (&d)[24], const uint32_t (&a)[4], uint64_t descB) {
  asm volatile("wgmma.mma_async.sync.aligned.m64n48k16.f32.bf16.bf16 {"
      "%0, %1, %2, %3, %4, %5, %6, %7, %8, %9, %10, %11, %12, %13, %14, %15, "
      "%16, %17, %18, %19, %20, %21, %22, %23"
      "}, {%24, %25, %26, %27}, %28, 1, 1, 1, 0;\n"
      : "+f"(d[0]), "+f"(d[1]), "+f"(d[2]), "+f"(d[3]), "+f"(d[4]), "+f"(d[5]), "+f"(d[6]), "+f"(d[7]),
        "+f"(d[8]), "+f"(d[9]), "+f"(d[10]), "+f"(d[11]), "+f"(d[12]), "+f"(d[13]), "+f"(d[14]), "+f"(d[15]),
        "+f"(d[16]), "+f"(d[17]), "+f"(d[18]), "+f"(d[19]), "+f"(d[20]), "+f"(d[21]), "+f"(d[22]), "+f"(d[23])
      : "r"(a[0]), "r"(a[1]), "r"(a[2]), "r"(a[3]), "l"(descB));
}
__device__ __forceinline__ void mma_rs48_k_z(float (&d)[24], const uint32_t (&a)[4], uint64_t descB) {
  asm volatile("wgmma.mma_async.sync.aligned.m64n48k16.f32.bf16.bf16 {"
      "%0, %1, %2, %3, %4, %5, %6, %7, %8, %9, %10, %11, %12, %13, %14, %15, "
      "%16, %17, %18, %19, %20, %21, %22, %23"
      "}, {%24, %25, %26, %27}, %28, 0, 1, 1, 0;\n"
      : "=f"(d[0]), "=f"(d[1]), "=f"(d[2]), "=f"(d[3]), "=f"(d[4]), "=f"(d[5]), "=f"(d[6]), "=f"(d[7]),
        "=f"(d[8]), "=f"(d[9]), "=f"(d[10]), "=f"(d[11]), "=f"(d[12]), "=f"(d[13]), "=f"(d[14]), "=f"(d[15]),
        "=f"(d[16]), "=f"(d[17]), "=f"(d[18]), "=f"(d[19]), "=f"(d[20]), "=f"(d[21]), "=f"(d[22]), "=f"(d[23])
      : "r"(a[0]), "r"(a[1]), "r"(a[2]), "r"(a[3]), "l"(descB));
}

__device__ __forceinline__ void mma_rs80_n(float (&d)[40], const uint32_t (&a)[4], uint64_t descB) {
  asm volatile("wgmma.mma_async.sync.aligned.m64n80k16.f32.bf16.bf16 {"
      "%0, %1, %2, %3, %4, %5, %6, %7, %8, %9, %10, %11, %12, %13, %14, %15, "
      "%16, %17, %18, %19, %20, %21, %22, %23, %24, %25, %26, %27, %28, %29, %30, %31, "
      "%32, %33, %34, %35, %36, %37, %38, %39"
      "}, {%40, %41, %42, %43}, %44, 1, 1, 1, 1;\n"
      : "+f"(d[0]), "+f"(d[1]), "+f"(d[2]), "+f"(d[3]), "+f"(d[4]), "+f"(d[5]), "+f"(d[6]), "+f"(d[7]),
        "+f"(d[8]), "+f"(d[9]), "+f"(d[10]), "+f"(d[11]), "+f"(d[12]), "+f"(d[13]), "+f"(d[14]), "+f"(d[15]),
        "+f"(d[16]), "+f"(d[17]), "+f"(d[18]), "+f"(d[19]), "+f"(d[20]), "+f"(d[21]), "+f"(d[22]), "+f"(d[23]),
        "+f"(d[24]), "+f"(d[25]), "+f"(d[26]), "+f"(d[27]), "+f"(d[28]), "+f"(d[29]), "+f"(d[30]), "+f"(d[31]),
        "+f"(d[32]), "+f"(d[33]), "+f"(d[34]), "+f"(d[35]), "+f"(d[36]), "+f"(d[37]), "+f"(d[38]), "+f"(d[39])
      : "r"(a[0]), "r"(a[1]), "r"(a[2]), "r"(a[3]), "l"(descB));
}
__device__ __forceinline__ void mma_rs80_n_z(float (&d)[40], const uint32_t (&a)[4], uint64_t descB) {
  asm volatile("wgmma.mma_async.sync.aligned.m64n80k16.f32.bf16.bf16 {"
      "%0, %1, %2, %3, %4, %5, %6, %7, %8, %9, %10, %11, %12, %13, %14, %15, "
      "%16, %17, %18, %19, %20, %21, %22, %23, %24, %25, %26, %27, %28, %29, %30, %31, "
      "%32, %33, %34, %35, %36, %37, %38, %39"
      "}, {%40, %41, %42, %43}, %44, 0, 1, 1, 1;\n"
      : "=f"(d[0]), "=f"(d[1]), "=f"(d[2]), "=f"(d[3]), "=f"(d[4]), "=f"(d[5]), "=f"(d[6]), "=f"(d[7]),
        "=f"(d[8]), "=f"(d[9]), "=f"(d[10]), "=f"(d[11]), "=f"(d[12]), "=f"(d[13]), "=f"(d[14]), "=f"(d[15]),
        "=f"(d[16]), "=f"(d[17]), "=f"(d[18]), "=f"(d[19]), "=f"(d[20]), "=f"(d[21]), "=f"(d[22]), "=f"(d[23]),
        "=f"(d[24]), "=f"(d[25]), "=f"(d[26]), "=f"(d[27]), "=f"(d[28]), "=f"(d[29]), "=f"(d[30]), "=f"(d[31]),
        "=f"(d[32]), "=f"(d[33]), "=f"(d[34]), "=f"(d[35]), "=f"(d[36]), "=f"(d[37]), "=f"(d[38]), "=f"(d[39])
      : "r"(a[0]), "r"(a[1]), "r"(a[2]), "r"(a[3]), "l"(descB));
}

__device__ __forceinline__ void feature_map(const uint32_t (&P)[2][10], uint32_t (&fr)[10][4]) {
  constexpr float L2E = 1.4426950408889634f;
#pragma unroll
  for (int p = 0; p < 2; p++) {
#pragma unroll
    for (int r = 0; r < 2; r++) {
      uint32_t mx = P[r][5 * p], mn = mx;
#pragma unroll
      for (int g = 1; g < 5; g++) { mx = max_bf2(mx, P[r][5 * p + g]); mn = min_bf2(mn, P[r][5 * p + g]); }
      mx = max_bf2(mx, __shfl_xor_sync(0xffffffffu, mx, 1));
      mn = min_bf2(mn, __shfl_xor_sync(0xffffffffu, mn, 1));
      mx = max_bf2(mx, __shfl_xor_sync(0xffffffffu, mx, 2));
      mn = min_bf2(mn, __shfl_xor_sync(0xffffffffu, mn, 2));
      float mx0 = -bf_lo(mx) * L2E, mx1 = -bf_hi(mx) * L2E, mn0 = bf_lo(mn) * L2E, mn1 = bf_hi(mn) * L2E;
      float ep0[5], ep1[5], en0[5], en1[5];
      float sp0 = 0.f, sp1 = 0.f, sn0 = 0.f, sn1 = 0.f;
#pragma unroll
      for (int g = 0; g < 5; g++) {
        float x0 = bf_lo(P[r][5 * p + g]), x1 = bf_hi(P[r][5 * p + g]);
        ep0[g] = ex2(fmaf(x0, L2E, mx0)); ep1[g] = ex2(fmaf(x1, L2E, mx1));
        en0[g] = ex2(fmaf(x0, -L2E, mn0)); en1[g] = ex2(fmaf(x1, -L2E, mn1));
        sp0 += ep0[g]; sp1 += ep1[g]; sn0 += en0[g]; sn1 += en1[g];
      }
      sp0 += __shfl_xor_sync(0xffffffffu, sp0, 1); sp1 += __shfl_xor_sync(0xffffffffu, sp1, 1);
      sn0 += __shfl_xor_sync(0xffffffffu, sn0, 1); sn1 += __shfl_xor_sync(0xffffffffu, sn1, 1);
      sp0 += __shfl_xor_sync(0xffffffffu, sp0, 2); sp1 += __shfl_xor_sync(0xffffffffu, sp1, 2);
      sn0 += __shfl_xor_sync(0xffffffffu, sn0, 2); sn1 += __shfl_xor_sync(0xffffffffu, sn1, 2);
      sp0 = rcp(sp0); sp1 = rcp(sp1); sn0 = rcp(sn0); sn1 = rcp(sn1);
#pragma unroll
      for (int g = 0; g < 5; g++) {
        fr[5 * p + g][r] = pack_bf16(ep0[g] * sp0, ep1[g] * sp1);
        fr[5 * p + g][2 + r] = pack_bf16(en0[g] * sn0, en1[g] * sn1);
      }
    }
  }
}

struct Ring {
  uint32_t idx, phase;
  template <int N> __device__ __forceinline__ void next() { if (++idx == N) { idx = 0; phase ^= 1; } }
};

}

__global__ void __cluster_dims__(2, 1, 1) __launch_bounds__(384, 1)
fused_kernel(const __grid_constant__ Maps maps, const __nv_bfloat16* __restrict__ x, const __nv_bfloat16* __restrict__ wqkv,
             const __nv_bfloat16* __restrict__ wphi, const __nv_bfloat16* __restrict__ w1, const __nv_bfloat16* __restrict__ w2,
             const __nv_bfloat16* __restrict__ w3, const __nv_bfloat16* __restrict__ w4, const __nv_bfloat16* __restrict__ wo,
             const __nv_bfloat16* __restrict__ gate_w) {
  extern __shared__ __align__(1024) uint8_t sgen[];
  const uint32_t sb = smem_u32(sgen);
  const uint32_t sb16 = (sb & 0x3FFFFu) >> 4;
  const uint32_t bars = sb + OFF_BAR;
  const uint32_t fullA = bars + 8 * B_FULLA, emptyA = bars + 8 * B_EMPTYA, fullB = bars + 8 * B_FULLB, emptyB = bars + 8 * B_EMPTYB;

  const int tid = threadIdx.x;
  const int rank = blockIdx.x & 1;
  const int pairIdx = blockIdx.x >> 1;
  const int I = pairIdx >> 3, j = pairIdx & 7;
  const int i = 2 * I + rank;
  const int i2 = 2 * I + (j >> 2);
  const int j2 = 2 * (j & 3) + rank;

  TSTAMP(0);
  if ((tid & 31) == 0) {
#pragma unroll 1
    for (int b = tid >> 5; b < NBAR; b += 12) {
      const int cnt = (b >= B_EMPTYA && b < B_FULLB) || (b >= B_EMPTYB && b < B_SIGP) ? 16 : (b >= B_SIGP && b < B_CS) ? 8 : 1;
      mbar_init(bars + 8 * b, cnt);
    }
    asm volatile("fence.mbarrier_init.release.cluster;" ::: "memory");
  }
  if (tid == 352) { prefetch_tmap(&maps.x); prefetch_tmap(&maps.qm); prefetch_tmap(&maps.w1m); prefetch_tmap(&maps.qr); prefetch_tmap(&maps.w1r); }
  asm volatile("barrier.cluster.arrive.relaxed.aligned;" ::: "memory");

  if (tid >= 256) {
    asm volatile("setmaxnreg.dec.sync.aligned.u32 40;");
    asm volatile("barrier.cluster.wait.aligned;" ::: "memory");
    auto get_epoch = [&]() { return *reinterpret_cast<volatile unsigned*>(g_flags + FL_DONE * 32) / NCTA; };
    const int lane = tid & 31, pw = (tid >> 5) & 3;
    auto send_stream = [&](int c0, unsigned ep1) {
#pragma unroll 1
      for (int c = c0; c < 7; c += 2) {
        mbar_wait(bars + 8 * (B_SEND + c), 0);
        bulk_store(g_part + (size_t)((i * 8 + ((j + c + 1) & 7)) * 8 + j) * 1280, sb + OFF_SEND + c0 * 20480, 20480);
        bulk_commit();
        if (c < 5) { bulk_wait_read(); mbar_arrive(bars + 8 * (B_SDONE + c)); }
        bulk_wait<0>();
        asm volatile("st.release.gpu.global.u32 [%0], %1;"
                     ::"l"(g_flags + (FL_PART + i * 8 + ((j + c + 1) & 7)) * 32 + c), "r"(ep1) : "memory");
      }
    };
    if (pw == 0) {
      if (lane == 0) {
        Ring r{0, 1};
        unsigned ep1 = 0;
#pragma unroll 1
        for (int k = 0; k < 30; k++) {
          if (k == 4) ep1 = get_epoch() + 1;
          if (k == 10 || k == 20) {
            const unsigned tgt = ep1 * 8u;
            const unsigned* f0 = g_flags + (k == 10 ? FL_H + ((i2 - 1) & 15) : FL_X1 + i) * 32;
            const unsigned* f1 = g_flags + (k == 10 ? FL_H + i2 : FL_X1 + i) * 32;
            const unsigned* f2 = g_flags + (k == 10 ? FL_H + ((i2 + 1) & 15) : FL_X1 + i) * 32;
            uint32_t n = 0;
            while (++n < (WAIT_LIMIT >> 4)) {
              unsigned v0, v1, v2;
              asm volatile("ld.relaxed.gpu.global.u32 %0, [%3];\nld.relaxed.gpu.global.u32 %1, [%4];\nld.acquire.gpu.global.u32 %2, [%5];"
                           : "=r"(v0), "=r"(v1), "=r"(v2) : "l"(f0), "l"(f1), "l"(f2) : "memory");
              if ((int)((v0 - tgt) | (v1 - tgt) | (v2 - tgt)) >= 0) break;
            }
            TSTAMPX(k == 10 ? 29 : 30);
          }
          if (k == 22) mbar_wait(bars + 8 * B_STG, 0);
          mbar_wait(emptyA + 8 * r.idx, r.phase);
          const uint32_t bar = fullA + 8 * r.idx, slot = sb + OFF_A + r.idx * SLOT_A;
          TRACE(k);
          mbar_expect_tx(bar, SLOT_A);
          if (k >= 10 && k < 20) tma2d_mc(slot + rank * 8192, &maps.hs, bar, 64 * (k - 10), 128 * i2 + 64 * rank);
          else tma2d(slot, k < 10 ? &maps.x : &maps.x1, bar, 64 * (k < 10 ? k : k - 20), 128 * i);
          r.next<NA>();
        }
        send_stream(1, ep1);
      }
    } else if (pw == 1) {
      if (lane == 0) {
        Ring r{0, 1};
#pragma unroll 1
        for (int k = 0; k < 26; k++) {
          mbar_wait(emptyB + 8 * r.idx, r.phase);
          const uint32_t bar = fullB + 8 * r.idx, slot = sb + OFF_B + r.idx * SLOT_B;
          TRACE(96 + k);
          if (k < 10) {
            mbar_expect_tx(bar, 40960);
            const int k0 = 64 * k + 32 * rank;
            tma4d_mc(slot + rank * 16384 + 4096, &maps.qm, bar, 0, k0, 0, j);
            tma3d_mc(slot + rank * 16384, &maps.w1m, bar, 0, k0, j);
            tma4d_mc(slot + 32768 + rank * 4096 + 1024, &maps.qr, bar, 64, k0, 0, j);
            tma3d_mc(slot + 32768 + rank * 4096, &maps.w1r, bar, 64, k0, j);
          } else if (k < 13) {
            const int s = k - 10;
            mbar_expect_tx(bar, 40960);
            tma3d(slot, &maps.w2, bar, 0, 256 * s, 5 * j2);
            if (s < 2) tma3d(slot + 20480, &maps.w2, bar, 0, 256 * s + 128, 5 * j2);
            else tma2d(slot + 20480, &maps.xr, bar, 80 * j2, 128 * i2);
          } else if (k < 18) {
            mbar_expect_tx(bar, 49152);
            tma3d_mc(slot + rank * 24576, &maps.w3, bar, 0, 128 * (k - 13) + 64 * rank, 3 * j);
          } else {
            const int d = (j + k - 17) & 7;
            mbar_expect_tx(bar, 43520);
            tma3d_mc(slot + rank * 10240, &maps.w4, bar, 0, 192 * j + 64 * rank, 5 * d);
            tma3d_mc(slot + (rank ? 20480 : 30720), rank ? &maps.w4 : &maps.wo, bar, 0, rank ? 192 * j + 128 : 80 * j, 5 * d);
          }
          r.next<NB>();
        }
      }
    } else {
      const unsigned epoch = get_epoch();
      float* accg = g_acc[epoch & 1];
      if (pw == 2) {
        {
          float* nxt = g_acc[(epoch + 1) & 1];
          constexpr int PER = ACC_FLOATS / NCTA;
#pragma unroll 1
          for (int e = lane; e < PER; e += 32) nxt[blockIdx.x * PER + e] = 0.f;
        }
        if (lane == 0) {
          flag_wait(FL_CS + j, (epoch + 1) * 16u);
          flag_wait(FL_ST + i, (epoch + 1) * 8u);
          fence_async_all();
          mbar_expect_tx(bars + 8 * B_CS, 1088 + 2048);
          bulk_load(sb + OFF_CS, accg + 8 * KV_J + 80 * j, 320, bars + 8 * B_CS);
          bulk_load(sb + OFF_CS + 320, accg + 8 * KV_J + D_ + 192 * j, 768, bars + 8 * B_CS);
          bulk_load(sb + OFF_XST, g_xstat + 128 * i, 2048, bars + 8 * B_CS);
          TSTAMPX(21);
          l2_prefetch(w2 + (size_t)blockIdx.x * (D_ * D_ / NCTA), D_ * D_ * 2 / NCTA);
          l2_prefetch(w4 + (size_t)blockIdx.x * (F_ * D_ / NCTA), F_ * D_ * 2 / NCTA);
          l2_prefetch(wo + (size_t)blockIdx.x * (D_ * D_ / NCTA), D_ * D_ * 2 / NCTA);
          flag_wait(FL_KV + j, (epoch + 1) * 16u);
          fence_async_all();
          mbar_expect_tx(bars + 8 * B_KV, KV_J * 4);
          bulk_load(sb + OFF_MISC, accg + j * KV_J, KV_J * 4, bars + 8 * B_KV);
          TSTAMPX(22);
          mbar_wait(bars + 8 * B_MFREE, 0);
          flag_wait(FL_X1 + i, (epoch + 1) * 8u);
          fence_async_all();
          mbar_expect_tx(bars + 8 * B_ST1, 8192);
          bulk_load(sb + OFF_MISC, g_st1 + 128 * i * 8, 8192, bars + 8 * B_ST1);
        }
        __syncwarp();
        mbar_wait(bars + 8 * B_SEND, 0);
        const unsigned* fp = g_flags + (FL_PART + i * 8 + j) * 32 + lane;
        bool seen = lane >= 7;
        uint32_t n = 0;
        while (!__all_sync(0xffffffffu, seen) && ++n < (WAIT_LIMIT >> 4)) {
          if (!seen && ld_acquire(fp) == epoch + 1 && (lane < 2 || mbar_test(bars + 8 * (B_RFREE + lane - 2), 0))) {
            seen = true;
            mbar_expect_tx(bars + 8 * (B_RDY + lane), 20480);
            bulk_load(sb + OFF_RECV + (lane & 1) * 20480, g_part + (size_t)((i * 8 + j) * 8 + ((j - 1 - lane) & 7)) * 1280, 20480,
                      bars + 8 * (B_RDY + lane));
          }
        }
      } else if (lane == 0) {
        const int shift = (j < 2) ? 1 : (j < 4) ? -1 : (j < 6) ? 2 : -2;
        if ((shift > 0 && i == 0) || (shift < 0 && i == 15)) {
          const int nz = shift > 0 ? shift : -shift, zr = shift > 0 ? 0 : S_ - nz;
#pragma unroll 1
          for (int e = 0; e < nz * 10; e++)
            reinterpret_cast<uint4*>(g_Hs + (size_t)(2 + zr + e / 10) * D_ + 80 * j)[e % 10] = make_uint4(0, 0, 0, 0);
          fence_async_all();
        }
        mbar_wait(bars + 8 * B_SIGP, 0);
        flag_add(FL_CS + j);
        flag_add_relaxed(FL_ST + i);
        TSTAMPX(20);
        prefetch_tmap(&maps.st_h); prefetch_tmap(&maps.st_x1); prefetch_tmap(&maps.hs); prefetch_tmap(&maps.x1); prefetch_tmap(&maps.xr);
        prefetch_tmap(&maps.w2); prefetch_tmap(&maps.w3); prefetch_tmap(&maps.w4); prefetch_tmap(&maps.wo); prefetch_tmap(&maps.st_out);
        mbar_wait(bars + 8 * B_SIGH, 0);
        TSTAMPX(23);
        tma2d_store(&maps.st_h, sb + OFF_STG, 80 * j, 128 * i + 2 + shift);
        tma2d_store(&maps.st_h, sb + OFF_STG + 10240, 80 * j, 128 * i + 66 + shift);
        bulk_commit(); bulk_wait<0>();
        flag_add(FL_H + i);
        TSTAMPX(24);
        mbar_wait(bars + 8 * B_SIGKV, 0);
        TSTAMPX(25);
        flag_add(FL_KV + j);
        TSTAMPX(26);
        mbar_wait(bars + 8 * B_SIGX1, 0);
        TSTAMPX(27);
        tma2d_store(&maps.st_x1, sb + OFF_STG, 80 * j2, 128 * i2);
        tma2d_store(&maps.st_x1, sb + OFF_STG + 10240, 80 * j2, 128 * i2 + 64);
        bulk_commit(); bulk_wait<0>();
        flag_add(FL_X1 + i2);
        mbar_arrive(bars + 8 * B_STG);
        TSTAMPX(28);
        send_stream(0, epoch + 1);
      }
    }
    __syncwarp();
    asm volatile("barrier.cluster.arrive;\nbarrier.cluster.wait;" ::: "memory");
  } else {
    asm volatile("setmaxnreg.inc.sync.aligned.u32 232;");
    const int wg = tid >> 7, warp = tid >> 5, lane = tid & 31, t = lane & 3;
    const int rloc = warp * 16 + (lane >> 2);
    const float* s_cs = reinterpret_cast<const float*>(sgen + OFF_CS);
    auto signal = [&](int b) {
      __syncwarp();
      if (lane == 0) mbar_arrive(bars + 8 * b);
    };
    auto release = [&](uint32_t bar) {
      __syncwarp();
      if (lane < 2) mbar_arrive_cta(bar, lane);
    };
    const uint32_t stg_lane = (warp * 16 + ((lane >> 3) & 1) * 8 + (lane & 7)) * 160 + (lane >> 4) * 16;

    unsigned epoch;
    {
      const int row = 128 * i + 16 * j + warp * 2 + (lane >> 4), l16 = lane & 15;
      uint4 v[5], w[5], cv[5], cw[5];
      const int crow = 40 * i + 5 * warp;
      const __nv_bfloat16* cp = lane < 10 ? w1 + (size_t)crow * D_ + 80 * j + 8 * lane : w3 + (size_t)crow * F_ + 192 * j + 8 * (lane - 10);
      const int cld = lane < 10 ? D_ : F_;
#pragma unroll
      for (int c = 0; c < 5; c++) {
        v[c] = __ldg(reinterpret_cast<const uint4*>(x + (size_t)row * D_ + c * 128 + l16 * 8));
        w[c] = __ldg(reinterpret_cast<const uint4*>(gate_w + c * 128 + l16 * 8));
        cv[c] = __ldg(reinterpret_cast<const uint4*>(cp + (size_t)c * cld));
        cw[c] = make_uint4(0, 0, 0, 0);
        if (lane >= 30) cw[c] = __ldg(reinterpret_cast<const uint4*>(cp + (size_t)c * cld + 16));
      }
      uint4 pre = make_uint4(0, 0, 0, 0);
      if (tid < 200) pre = __ldg(reinterpret_cast<const uint4*>(wphi + (size_t)j * 1600) + tid);
      epoch = *reinterpret_cast<volatile unsigned*>(g_flags + FL_DONE * 32) / NCTA;
#pragma unroll 1
      for (int e = tid; e < 800; e += 256) sts128(sb + OFF_MISC + e * 16, make_uint4(0, 0, 0, 0));
      bar_sync(1, 256);
      if (tid < 200) {
        const uint32_t ww[4] = {pre.x, pre.y, pre.z, pre.w};
        const int h = tid / 50;
#pragma unroll
        for (int e = 0; e < 8; e++) {
          const int idx = tid * 8 + e, k = idx / 20, ff = idx - 20 * k;
          const int n = 40 * (h >> 1) + 8 * (ff >> 2) + 2 * (ff & 3) + (h & 1);
          const int off = (k >> 4) * 2560 + n * 32 + ((((k >> 3) ^ (n >> 2)) & 1) << 4) + (k & 7) * 2;
          *reinterpret_cast<unsigned short*>(sgen + OFF_MISC + off) = (unsigned short)(ww[e >> 1] >> ((e & 1) * 16));
        }
      }
      float f[40];
      float s = 0.f, gs = 0.f;
#pragma unroll
      for (int c = 0; c < 5; c++) {
        const uint32_t vv[4] = {v[c].x, v[c].y, v[c].z, v[c].w}, ww[4] = {w[c].x, w[c].y, w[c].z, w[c].w};
#pragma unroll
        for (int e = 0; e < 4; e++) {
          f[8 * c + 2 * e] = bf_lo(vv[e]); f[8 * c + 2 * e + 1] = bf_hi(vv[e]);
          s += f[8 * c + 2 * e] + f[8 * c + 2 * e + 1];
          gs = fmaf(f[8 * c + 2 * e], bf_lo(ww[e]), gs); gs = fmaf(f[8 * c + 2 * e + 1], bf_hi(ww[e]), gs);
        }
      }
#pragma unroll
      for (int o = 1; o < 16; o <<= 1) { s += __shfl_xor_sync(0xffffffffu, s, o); gs += __shfl_xor_sync(0xffffffffu, gs, o); }
      const float mean = s * (1.f / D_);
      float q = 0.f;
#pragma unroll
      for (int e = 0; e < 40; e++) { const float d = f[e] - mean; q = fmaf(d, d, q); }
#pragma unroll
      for (int o = 1; o < 16; o <<= 1) q += __shfl_xor_sync(0xffffffffu, q, o);
      const float rstd = rsqrtf(q * (1.f / D_) + 1e-5f);
      if (l16 == 0) g_xstat[row] = make_float4(rstd, -mean * rstd, rcp(1.f + __expf(-gs)), 0.f);
      float* cd = g_acc[epoch & 1] + 8 * KV_J + (lane < 10 ? 80 * j + 8 * lane : D_ + 192 * j + 8 * (lane - 10));
#pragma unroll 1
      for (int hh = 0; hh < 2; hh++) {
        float a[8];
#pragma unroll
        for (int e = 0; e < 8; e++) a[e] = 0.f;
#pragma unroll
        for (int c = 0; c < 5; c++) {
          a[0] += bf_lo(cv[c].x); a[1] += bf_hi(cv[c].x); a[2] += bf_lo(cv[c].y); a[3] += bf_hi(cv[c].y);
          a[4] += bf_lo(cv[c].z); a[5] += bf_hi(cv[c].z); a[6] += bf_lo(cv[c].w); a[7] += bf_hi(cv[c].w);
          cv[c] = cw[c];
        }
        if (hh == 0 || lane >= 30) { red_add4(cd, a[0], a[1], a[2], a[3]); red_add4(cd + 4, a[4], a[5], a[6], a[7]); }
        cd += 16;
      }
      fence_async_smem();
      asm volatile("barrier.cluster.wait.aligned;" ::: "memory");
      signal(B_SIGP);
    }
    TSTAMP(1);

    Ring ra{0, 0}, rb{0, 0};
    const uint32_t xoff = rloc * 128;
    uint32_t qp[2][10], P[2][10];
    float st_g[2];
    {
      float accM[128], accR[32];
      zero_regs(accM); zero_regs(accR);
      uint32_t pa = 0, pb = 0;
#pragma unroll 1
      for (int k = 0; k < 10; k++) {
        mbar_wait(fullA + 8 * ra.idx, ra.phase);
        if (tid == 0) TRACE(32 + k);
        mbar_wait(fullB + 8 * rb.idx, rb.phase);
        if (tid == 0) TRACE(64 + k);
        if (k == 0) TSTAMP(2);
        const uint32_t a0 = sb16 + ((OFF_A + ra.idx * SLOT_A + wg * 8192) >> 4), b0 = sb16 + ((OFF_B + rb.idx * SLOT_B) >> 4);
        wg_fence();
#pragma unroll
        for (int kk = 0; kk < 4; kk++) {
          const uint64_t da = make_desc(a0, kk * 32, 16, 1024, 1);
          mma_ss256(accM, da, make_desc(b0, (kk >> 1) * 16384 + (kk & 1) * 2048, 4096, 1024, 1));
          mma_ss64(accR, da, make_desc(b0, 32768 + (kk >> 1) * 4096 + (kk & 1) * 512, 1024, 256, 3));
          if (kk == 0) {
            wg_commit();
            if (k > 0) {
              wg_wait<1>();
              if (k - 1 < 8) release(emptyA + 8 * pa);
              release(emptyB + 8 * pb);
            }
          }
        }
        wg_commit();
        pa = ra.idx; pb = rb.idx;
        ra.next<NA>(); rb.next<NB>();
      }
      TSTAMP(18);
      float st_rstd[2], st_mr[2];
      mbar_wait(bars + 8 * B_CS, 0);
#pragma unroll
      for (int r = 0; r < 2; r++) {
        const uint4 st = lds128(sb + OFF_XST + (rloc + 8 * r) * 16);
        st_rstd[r] = __uint_as_float(st.x); st_mr[r] = __uint_as_float(st.y); st_g[r] = __uint_as_float(st.z);
      }
      TSTAMP(19);
      wg_wait<0>();
      fence_regs(accM); fence_regs(accR);
      TSTAMP(3);
#define ACC(P_, G, I_) ((G) < 8 ? accM[(P_) * 32 + ((G) & 7) * 4 + (I_)] : accR[(P_) * 8 + ((G) & 1) * 4 + (I_)])
      {
        const int mat = lane >> 3;
        const int tok = warp * 16 + (mat & 1) * 8 + (lane & 7);
        const uint32_t ones = (t == 0) ? 0x00003f80u : 0u;
        __syncwarp();
#pragma unroll
        for (int p = 0; p < 2; p++) {
          const uint32_t rowa = sb + OFF_A + p * SLOT_A + tok * 128;
#pragma unroll
          for (int gg = 0; gg < 3; gg++) {
            const int g0 = 5 * p + 2 * gg;
            uint32_t r0 = pack_bf16(ACC(3, g0, 0), ACC(3, g0, 1)), r1 = pack_bf16(ACC(3, g0, 2), ACC(3, g0, 3));
            uint32_t r2 = ones, r3 = ones;
            if (gg < 2) { r2 = pack_bf16(ACC(3, g0 + 1, 0), ACC(3, g0 + 1, 1)); r3 = pack_bf16(ACC(3, g0 + 1, 2), ACC(3, g0 + 1, 3)); }
            stsm4(rowa + (((2 * gg + (mat >> 1)) ^ (tok & 7)) << 4), r0, r1, r2, r3);
          }
        }
      }
      uint32_t kf[5][4], qf[5][4];
#pragma unroll
      for (int s = 0; s < 5; s++) {
        kf[s][0] = pack_bf16(ACC(2, 2 * s, 0), ACC(2, 2 * s, 1)); kf[s][1] = pack_bf16(ACC(2, 2 * s, 2), ACC(2, 2 * s, 3));
        kf[s][2] = pack_bf16(ACC(2, 2 * s + 1, 0), ACC(2, 2 * s + 1, 1)); kf[s][3] = pack_bf16(ACC(2, 2 * s + 1, 2), ACC(2, 2 * s + 1, 3));
        qf[s][0] = pack_bf16(ACC(1, 2 * s, 0), ACC(1, 2 * s, 1)); qf[s][1] = pack_bf16(ACC(1, 2 * s, 2), ACC(1, 2 * s, 3));
        qf[s][2] = pack_bf16(ACC(1, 2 * s + 1, 0), ACC(1, 2 * s + 1, 1)); qf[s][3] = pack_bf16(ACC(1, 2 * s + 1, 2), ACC(1, 2 * s + 1, 3));
      }
      bar_sync(1, 256);
      float pk[40], pq[40];
      wg_fence();
#pragma unroll
      for (int s = 0; s < 5; s++) {
        if (s == 0) mma_rs80_k_z(pk, kf[s], make_desc(sb16, OFF_MISC, 16, 256, 3));
        else mma_rs80_k(pk, kf[s], make_desc(sb16, OFF_MISC + s * 2560, 16, 256, 3));
      }
#pragma unroll
      for (int s = 0; s < 5; s++) {
        if (s == 0) mma_rs80_k_z(pq, qf[s], make_desc(sb16, OFF_MISC, 16, 256, 3));
        else mma_rs80_k(pq, qf[s], make_desc(sb16, OFF_MISC + s * 2560, 16, 256, 3));
      }
      wg_commit();

      {
        uint32_t hv[10][2];
#pragma unroll
        for (int g = 0; g < 10; g++) {
          const float2 cs = *reinterpret_cast<const float2*>(s_cs + 8 * g + 2 * t);
          const float v0 = gelu_s(fmaf(ACC(0, g, 0), st_rstd[0], st_mr[0] * cs.x), 0.5f), v1 = gelu_s(fmaf(ACC(0, g, 1), st_rstd[0], st_mr[0] * cs.y), 0.5f);
          const float v2 = gelu_s(fmaf(ACC(0, g, 2), st_rstd[1], st_mr[1] * cs.x), 0.5f), v3 = gelu_s(fmaf(ACC(0, g, 3), st_rstd[1], st_mr[1] * cs.y), 0.5f);
          hv[g][0] = pack_bf16(v0, v1); hv[g][1] = pack_bf16(v2, v3);
        }
#pragma unroll
        for (int s = 0; s < 5; s++) stsm4(sb + OFF_STG + stg_lane + s * 32, hv[2 * s][0], hv[2 * s][1], hv[2 * s + 1][0], hv[2 * s + 1][1]);
        fence_async_smem();
        signal(B_SIGH);
      }
#undef ACC
      TSTAMP(4);
      wg_wait<0>();
      fence_regs(pk); fence_regs(pq);
#pragma unroll
      for (int G = 0; G < 10; G++) {
        P[0][G] = pack_bf16(pk[4 * G], pk[4 * G + 1]); P[1][G] = pack_bf16(pk[4 * G + 2], pk[4 * G + 3]);
        qp[0][G] = pack_bf16(pq[4 * G], pq[4 * G + 1]); qp[1][G] = pack_bf16(pq[4 * G + 2], pq[4 * G + 3]);
      }
    }

    uint32_t fr[10][4];
    {
      feature_map(P, fr);
      const int mat = lane >> 3;
      const int tok = warp * 16 + (mat & 1) * 8 + (lane & 7);
      const uint32_t base = sb + OFF_B + tok * 32 + (((mat >> 1) ^ ((tok >> 2) & 1)) << 4);
#pragma unroll
      for (int G = 0; G < 10; G++) stsm4(base + G * 4096, fr[G][0], fr[G][1], fr[G][2], fr[G][3]);
      fence_async_smem();
      bar_sync(1, 256);
      float kv[40];
      const uint32_t a0 = sb16 + ((OFF_A + wg * SLOT_A) >> 4), b0 = sb16 + ((OFF_B + wg * 20480) >> 4);
      wg_fence();
#pragma unroll
      for (int ks = 0; ks < 8; ks++) {
        if (ks == 0) mma_ss80_tt_z(kv, make_desc(a0, 0, 16, 1024, 1), make_desc(b0, 0, 4096, 256, 3));
        else mma_ss80_tt(kv, make_desc(a0, ks * 2048, 16, 1024, 1), make_desc(b0, ks * 512, 4096, 256, 3));
      }
      wg_commit();
      wg_wait<0>();
      fence_regs(kv);
      release(emptyA); release(emptyA + 8); release(emptyB);
      float* dst = g_acc[epoch & 1] + j * KV_J + wg * KV_PAIR;
      const int m0 = (warp & 3) * 16 + (lane >> 2);
#pragma unroll
      for (int r = 0; r < 2; r++) {
        const int m = m0 + 8 * r;
        const bool hi = m >= 20;
        float v[10];
#pragma unroll
        for (int G = 0; G < 10; G++) v[G] = hi ? kv[4 * G + 2 * r + 1] : kv[4 * G + 2 * r];
        float* p = dst + (m < 40 ? m * 48 + t * 12 : 1920 + t * 24 + 12);
        if (m <= 40) { red_add4(p, v[0], v[1], v[2], v[3]); red_add4(p + 4, v[4], v[5], v[6], v[7]); red_add2(p + 8, v[8], v[9]); }
      }
      if (m0 == 32) {
        float* p = dst + 1920 + t * 24;
        red_add4(p, kv[2], kv[6], kv[10], kv[14]); red_add4(p + 4, kv[18], kv[22], kv[26], kv[30]); red_add2(p + 8, kv[34], kv[38]);
      }
      signal(B_SIGKV);
    }
    TSTAMP(5);

    {
      float acc[40];
      zero_regs(acc);
      uint32_t pa = 0, pb = 0;
#pragma unroll 1
      for (int k = 0; k < 10; k++) {
        mbar_wait(fullA + 8 * ra.idx, ra.phase);
        if (tid == 0) TRACE(42 + k);
        if ((k & 3) == 0) mbar_wait(fullB + 8 * rb.idx, rb.phase);
        if (tid == 0) TRACE(74 + k);
        if (k == 0) TSTAMP(6);
        const uint32_t a0 = sb16 + ((OFF_A + ra.idx * SLOT_A + wg * 8192) >> 4);
        const uint32_t b0 = sb16 + ((OFF_B + rb.idx * SLOT_B + ((k >> 1) & 1) * 20480 + (k & 1) * 2048) >> 4);
        wg_fence();
#pragma unroll
        for (int kk = 0; kk < 4; kk++) {
          mma_ss80(acc, make_desc(a0, kk * 32, 16, 1024, 1), make_desc(b0, kk * 512, 4096, 256, 3));
          if (kk == 1) {
            wg_commit();
            if (k > 0) {
              wg_wait<1>();
              release(emptyA + 8 * pa);
              if ((k & 3) == 0) release(emptyB + 8 * pb);
            }
          }
        }
        wg_commit();
        pa = ra.idx; pb = rb.idx;
        ra.next<NA>();
        if ((k & 3) == 3 || k == 9) rb.next<NB>();
      }
      uint32_t xv[2][10];
      {
        const uint32_t xa = sb + OFF_B + pb * SLOT_B + 20480 + rloc * 160 + t * 4;
#pragma unroll
        for (int g = 0; g < 10; g++) { xv[0][g] = lds32(xa + g * 16); xv[1][g] = lds32(xa + 1280 + g * 16); }
      }
      wg_wait<0>();
      fence_regs(acc);
      release(emptyA + 8 * pa); release(emptyB + 8 * pb);
      TSTAMP(7);
#pragma unroll
      for (int r = 0; r < 2; r++) {
#pragma unroll
        for (int g = 0; g < 10; g++)
          xv[r][g] = pack_bf16(bf_lo(xv[r][g]) + acc[4 * g + 2 * r], bf_hi(xv[r][g]) + acc[4 * g + 2 * r + 1]);
      }
      bar_sync(1, 256);
#pragma unroll
      for (int s = 0; s < 5; s++) stsm4(sb + OFF_STG + stg_lane + s * 32, xv[0][2 * s], xv[1][2 * s], xv[0][2 * s + 1], xv[1][2 * s + 1]);
#pragma unroll
      for (int r = 0; r < 2; r++) {
        float s = 0.f;
#pragma unroll
        for (int g = 0; g < 10; g++) {
          acc[4 * g + 2 * r] = bf_lo(xv[r][g]); acc[4 * g + 2 * r + 1] = bf_hi(xv[r][g]);
          s += acc[4 * g + 2 * r] + acc[4 * g + 2 * r + 1];
        }
        s += __shfl_xor_sync(0xffffffffu, s, 1); s += __shfl_xor_sync(0xffffffffu, s, 2);
        const float mu = s * (1.f / 80.f);
        float q = 0.f;
#pragma unroll
        for (int g = 0; g < 10; g++) {
          const float d0 = acc[4 * g + 2 * r] - mu, d1 = acc[4 * g + 2 * r + 1] - mu;
          q = fmaf(d0, d0, q); q = fmaf(d1, d1, q);
        }
        q += __shfl_xor_sync(0xffffffffu, q, 1); q += __shfl_xor_sync(0xffffffffu, q, 2);
        if (t == 0) g_st1[(128 * i2 + rloc + 8 * r) * 8 + j2] = make_float2(mu, q);
      }
      fence_async_smem();
      signal(B_SIGX1);
    }
    TSTAMP(8);

    uint32_t of[5][4];
    {
      feature_map(qp, fr);
      mbar_wait(bars + 8 * B_KV, 0);
      uint4 kvr[2][3];
#pragma unroll
      for (int u = 0; u < 2; u++) {
        const int it = tid + 256 * u, p = it / 192, rem = it - 192 * p, n = rem >> 2, tq = rem & 3;
        const uint32_t sp = sb + OFF_MISC + 4 * (p * KV_PAIR + (n < 40 ? n * 48 + tq * 12 : 1920 + tq * 24 + (n & 1) * 12));
        if (it < 384) { kvr[u][0] = lds128(sp); kvr[u][1] = lds128(sp + 16); kvr[u][2] = lds128(sp + 32); }
      }
      bar_sync(1, 256);
#pragma unroll
      for (int u = 0; u < 2; u++) {
        const int it = tid + 256 * u, p = it / 192, rem = it - 192 * p, n = rem >> 2, tq = rem & 3;
        const int sh = (n < 40 ? (n >= 20) : (n & 1)) * 16;
        const uint32_t v[10] = {kvr[u][0].x, kvr[u][0].y, kvr[u][0].z, kvr[u][0].w, kvr[u][1].x, kvr[u][1].y, kvr[u][1].z, kvr[u][1].w, kvr[u][2].x, kvr[u][2].y};
        uint8_t* dst = sgen + OFF_MISC + p * 7680 + n * 32 + tq * 4;
        const int sw = ((n >> 2) & 1) << 4;
        if (it < 384) {
#pragma unroll
          for (int G = 0; G < 10; G++)
            *reinterpret_cast<uint32_t*>(dst + (G >> 1) * 1536 + (((G & 1) << 4) ^ sw)) = pack_bf16(__uint_as_float(v[G]), 0.f) << sh;
        }
      }
      fence_async_smem();
      bar_sync(1, 256);
      float o0[24], o1[24];
      wg_fence();
#pragma unroll
      for (int g = 0; g < 5; g++) {
        if (g == 0) mma_rs48_k_z(o0, fr[g], make_desc(sb16, OFF_MISC, 16, 256, 3));
        else mma_rs48_k(o0, fr[g], make_desc(sb16, OFF_MISC + g * 1536, 16, 256, 3));
      }
#pragma unroll
      for (int g = 0; g < 5; g++) {
        if (g == 0) mma_rs48_k_z(o1, fr[5], make_desc(sb16, OFF_MISC + 7680, 16, 256, 3));
        else mma_rs48_k(o1, fr[5 + g], make_desc(sb16, OFF_MISC + 7680 + g * 1536, 16, 256, 3));
      }
      wg_commit();
      wg_wait<0>();
      fence_regs(o0); fence_regs(o1);
      signal(B_MFREE);
#pragma unroll
      for (int r = 0; r < 2; r++) {
        const float a0 = __fdividef(st_g[r], o0[20 + 2 * r] + 1e-6f), a1 = __fdividef(st_g[r], o0[21 + 2 * r] + 1e-6f);
        const float b0 = __fdividef(st_g[r], o1[20 + 2 * r] + 1e-6f), b1 = __fdividef(st_g[r], o1[21 + 2 * r] + 1e-6f);
        const float am = t < 2 ? a0 : a1, bm = t < 2 ? b0 : b1;
#pragma unroll
        for (int g = 0; g < 5; g++) {
          const float sa = g < 2 ? a0 : (g == 2 ? am : a1), sb2 = g < 2 ? b0 : (g == 2 ? bm : b1);
          of[g >> 1][(g & 1) * 2 + r] = pack_bf16(o0[4 * g + 2 * r] * sa, o0[4 * g + 2 * r + 1] * sa);
          of[(5 + g) >> 1][((5 + g) & 1) * 2 + r] = pack_bf16(o1[4 * g + 2 * r] * sb2, o1[4 * g + 2 * r + 1] * sb2);
        }
      }
    }
    TSTAMP(9);

    uint32_t hf[12][4];
    float sum[40];
    {
      float acc[96];
      zero_regs(acc);
      uint32_t x1v[2][10];
      uint32_t pa = 0, pb = 0;
#pragma unroll 1
      for (int k = 0; k < 10; k++) {
        mbar_wait(fullA + 8 * ra.idx, ra.phase);
        if (tid == 0) TRACE(52 + k);
        if ((k & 1) == 0) mbar_wait(fullB + 8 * rb.idx, rb.phase);
        if (tid == 0) TRACE(84 + k);
        if (k == 0) TSTAMP(10);
        const uint32_t a0 = sb16 + ((OFF_A + ra.idx * SLOT_A + wg * 8192) >> 4);
        const uint32_t b0 = sb16 + ((OFF_B + rb.idx * SLOT_B + (k & 1) * 24576) >> 4);
        const uint32_t trow = sb + OFF_A + ra.idx * SLOT_A + xoff;
        wg_fence();
#pragma unroll
        for (int kk = 0; kk < 4; kk++) {
          mma_ss192(acc, make_desc(a0, kk * 32, 16, 1024, 1), make_desc(b0, kk * 2048, 8192, 1024, 1));
          if (kk == 0) {
            wg_commit();
            if (k > 0) {
              wg_wait<1>();
              release(emptyA + 8 * pa);
              if ((k & 1) == 0) release(emptyB + 8 * pb);
            }
          }
        }
        wg_commit();
        if ((unsigned)(k - ((10 * j) >> 3)) < 2u) {
#pragma unroll
          for (int g = 0; g < 10; g++) {
            const int cg = 10 * j + g;
            if ((cg >> 3) == k) {
              const uint32_t ad = trow + (((cg & 7) ^ (rloc & 7)) << 4) + t * 4;
              x1v[0][g] = lds32(ad); x1v[1][g] = lds32(ad + 1024);
            }
          }
        }
        pa = ra.idx; pb = rb.idx;
        ra.next<NA>();
        if (k & 1) rb.next<NB>();
      }
      float rs[2], mm[2];
      mbar_wait(bars + 8 * B_ST1, 0);
#pragma unroll
      for (int r = 0; r < 2; r++) {
        const uint4 su = lds128(sb + OFF_MISC + (rloc + 8 * r) * 64 + t * 16);
        const float m0 = __uint_as_float(su.x), m1 = __uint_as_float(su.z);
        float mu = m0 + m1;
        mu += __shfl_xor_sync(0xffffffffu, mu, 1); mu += __shfl_xor_sync(0xffffffffu, mu, 2);
        mu *= 0.125f;
        const float d0 = m0 - mu, d1 = m1 - mu;
        float q = __uint_as_float(su.y) + __uint_as_float(su.w) + 80.f * (d0 * d0 + d1 * d1);
        q += __shfl_xor_sync(0xffffffffu, q, 1); q += __shfl_xor_sync(0xffffffffu, q, 2);
        rs[r] = rsqrtf(q * (1.f / D_) + 1e-5f);
        mm[r] = -mu * rs[r];
      }
      wg_wait<0>();
      fence_regs(acc);
      release(emptyB + 8 * pb);
      if (wg == 1) bar_arrive(2, 256);
      TSTAMP(11);
      const float w0 = 1.f - st_g[0], w1s = 1.f - st_g[1];
      const float hs0 = 0.5f * w0, hs1 = 0.5f * w1s;
#pragma unroll
      for (int g = 0; g < 24; g++) {
        const float2 cs = *reinterpret_cast<const float2*>(s_cs + 80 + 8 * g + 2 * t);
        const float v0 = gelu_s(fmaf(acc[4 * g], rs[0], mm[0] * cs.x), hs0), v1 = gelu_s(fmaf(acc[4 * g + 1], rs[0], mm[0] * cs.y), hs0);
        const float v2 = gelu_s(fmaf(acc[4 * g + 2], rs[1], mm[1] * cs.x), hs1), v3 = gelu_s(fmaf(acc[4 * g + 3], rs[1], mm[1] * cs.y), hs1);
        hf[g >> 1][(g & 1) * 2] = pack_bf16(v0, v1);
        hf[g >> 1][(g & 1) * 2 + 1] = pack_bf16(v2, v3);
      }
#pragma unroll
      for (int g = 0; g < 10; g++) {
        sum[4 * g] = w0 * bf_lo(x1v[0][g]); sum[4 * g + 1] = w0 * bf_hi(x1v[0][g]);
        sum[4 * g + 2] = w1s * bf_lo(x1v[1][g]); sum[4 * g + 3] = w1s * bf_hi(x1v[1][g]);
      }
    }
    TSTAMP(12);

    {
      float acc[40];
      const int wt = tid & 127;
      auto issue = [&](bool pass_turn) {
        mbar_wait(fullB + 8 * rb.idx, rb.phase);
        const uint32_t b0 = sb16 + ((OFF_B + rb.idx * SLOT_B) >> 4);
        bar_sync(2 + wg, 256);
        wg_fence();
#pragma unroll
        for (int s = 0; s < 12; s++) {
          if (s == 0) mma_rs80_n_z(acc, hf[s], make_desc(b0, 0, 2048, 256, 3));
          else mma_rs80_n(acc, hf[s], make_desc(b0, (s >> 2) * 10240 + (s & 3) * 512, 2048, 256, 3));
        }
#pragma unroll
        for (int s = 0; s < 5; s++) mma_rs80_n(acc, of[s], make_desc(b0, 30720 + s * 512, 2560, 256, 3));
        wg_commit();
        if (pass_turn) bar_arrive(3 - wg, 256);
      };
      auto gather = [&](int c) {
        const uint32_t src = sb + OFF_RECV + (c & 1) * 20480 + tid * 16;
#pragma unroll
        for (int q = 0; q < 5; q++) {
          const uint4 v = lds128(src + q * 4096);
          sum[8 * q] += bf_lo(v.x); sum[8 * q + 1] += bf_hi(v.x); sum[8 * q + 2] += bf_lo(v.y); sum[8 * q + 3] += bf_hi(v.y);
          sum[8 * q + 4] += bf_lo(v.z); sum[8 * q + 5] += bf_hi(v.z); sum[8 * q + 6] += bf_lo(v.w); sum[8 * q + 7] += bf_hi(v.w);
        }
        if (c < 5) signal(B_RFREE + c);
      };
      int ng = 0;
#pragma unroll 1
      for (int c = 0; c < 7; c++) {
        issue(true);
        if (__all_sync(0xffffffffu, mbar_test(bars + 8 * (B_RDY + ng), 0))) gather(ng++);
        if (c >= 2) mbar_wait(bars + 8 * (B_SDONE + c - 2), 0);
        wg_wait<0>();
        fence_regs(acc);
        release(emptyB + 8 * rb.idx);
        rb.next<NB>();
        const uint32_t dst = sb + OFF_SEND + (c & 1) * 20480 + tid * 16;
#pragma unroll
        for (int q = 0; q < 5; q++)
          sts128(dst + q * 4096, make_uint4(pack_bf16(acc[8 * q], acc[8 * q + 1]), pack_bf16(acc[8 * q + 2], acc[8 * q + 3]),
                                            pack_bf16(acc[8 * q + 4], acc[8 * q + 5]), pack_bf16(acc[8 * q + 6], acc[8 * q + 7])));
        fence_async_smem();
        signal(B_SEND + c);
      }
      issue(wg == 0);
      TSTAMP(13);
#pragma unroll 1
      for (; ng < 7; ng++) { mbar_wait(bars + 8 * (B_RDY + ng), 0); gather(ng); }
      TSTAMP(14);
      wg_wait<0>(); fence_regs(acc);
      uint32_t ov[10][2];
#pragma unroll
      for (int g = 0; g < 10; g++) {
        ov[g][0] = pack_bf16(sum[4 * g] + acc[4 * g], sum[4 * g + 1] + acc[4 * g + 1]);
        ov[g][1] = pack_bf16(sum[4 * g + 2] + acc[4 * g + 2], sum[4 * g + 3] + acc[4 * g + 3]);
      }
      const uint32_t ostg = sb + OFF_B + ((rb.idx + 1) % NB) * SLOT_B;
#pragma unroll
      for (int s = 0; s < 5; s++) stsm4(ostg + stg_lane + s * 32, ov[2 * s][0], ov[2 * s][1], ov[2 * s + 1][0], ov[2 * s + 1][1]);
      fence_async_smem();
      bar_sync(4 + wg, 128);
      if (wt == 0) {
        tma2d_store(&maps.st_out, ostg + wg * 10240, 80 * j, 128 * i + 64 * wg);
        bulk_commit(); bulk_wait_read();
      }
    }
    TSTAMP(15);
    if (tid == 0) asm volatile("red.relaxed.gpu.global.add.u32 [%0], 1;" ::"l"(g_flags + FL_DONE * 32) : "memory");
    asm volatile("barrier.cluster.arrive;\nbarrier.cluster.wait;" ::: "memory");
  }
}

namespace {
typedef CUresult (*EncodeFn)(CUtensorMap*, CUtensorMapDataType, cuuint32_t, void*, const cuuint64_t*, const cuuint64_t*,
                             const cuuint32_t*, const cuuint32_t*, CUtensorMapInterleave, CUtensorMapSwizzle,
                             CUtensorMapL2promotion, CUtensorMapFloatOOBfill);

void encode(EncodeFn fn, CUtensorMap* m, const void* ptr, int rank, const cuuint64_t* dims, const cuuint64_t* strides,
            const cuuint32_t* box, CUtensorMapSwizzle swz) {
  cuuint32_t es[5] = {1, 1, 1, 1, 1};
  fn(m, CU_TENSOR_MAP_DATA_TYPE_BFLOAT16, rank, const_cast<void*>(ptr), dims, strides, box, es, CU_TENSOR_MAP_INTERLEAVE_NONE,
     swz, CU_TENSOR_MAP_L2_PROMOTION_L2_128B, CU_TENSOR_MAP_FLOAT_OOB_FILL_NONE);
}
}

extern "C" void kernel_launch(void* const* d_in, const int* in_sizes, int n_in, void* d_out, int out_size) {
  (void)in_sizes; (void)n_in; (void)out_size;
  const __nv_bfloat16* x = (const __nv_bfloat16*)d_in[0];
  const __nv_bfloat16* wqkv = (const __nv_bfloat16*)d_in[1];
  const __nv_bfloat16* wphi = (const __nv_bfloat16*)d_in[2];
  const __nv_bfloat16* wo = (const __nv_bfloat16*)d_in[3];
  const __nv_bfloat16* w1 = (const __nv_bfloat16*)d_in[5];
  const __nv_bfloat16* w2 = (const __nv_bfloat16*)d_in[6];
  const __nv_bfloat16* w3 = (const __nv_bfloat16*)d_in[7];
  const __nv_bfloat16* w4 = (const __nv_bfloat16*)d_in[8];
  const __nv_bfloat16* gate_w = (const __nv_bfloat16*)d_in[9];

  static EncodeFn enc = nullptr;
  static void *pHs = nullptr, *pX1 = nullptr;
  if (!enc) {
    cudaDriverEntryPointQueryResult qr;
    cudaGetDriverEntryPoint("cuTensorMapEncodeTiled", (void**)&enc, cudaEnableDefault, &qr);
    cudaGetSymbolAddress(&pHs, g_Hs);
    cudaGetSymbolAddress(&pX1, g_X1);
    cudaFuncSetAttribute(fused_kernel, cudaFuncAttributeMaxDynamicSharedMemorySize, SMEM_BYTES);
  }
  Maps m;
  {
    cuuint64_t dims[2] = {D_, S_}, str[1] = {D_ * 2};
    cuuint32_t box[2] = {64, 128}, boxh[2] = {64, 64};
    encode(enc, &m.x, x, 2, dims, str, box, CU_TENSOR_MAP_SWIZZLE_128B);
    encode(enc, &m.hs, (const char*)pHs + 2 * D_ * 2, 2, dims, str, boxh, CU_TENSOR_MAP_SWIZZLE_128B);
    encode(enc, &m.x1, pX1, 2, dims, str, box, CU_TENSOR_MAP_SWIZZLE_128B);
    cuuint32_t boxs[2] = {80, 64};
    cuuint64_t dimsp[2] = {D_, S_ + 4};
    encode(enc, &m.st_h, pHs, 2, dimsp, str, boxs, CU_TENSOR_MAP_SWIZZLE_NONE);
    encode(enc, &m.st_x1, pX1, 2, dims, str, boxs, CU_TENSOR_MAP_SWIZZLE_NONE);
    encode(enc, &m.st_out, d_out, 2, dims, str, boxs, CU_TENSOR_MAP_SWIZZLE_NONE);
    cuuint32_t boxr[2] = {80, 128};
    encode(enc, &m.xr, x, 2, dims, str, boxr, CU_TENSOR_MAP_SWIZZLE_NONE);
  }
  {
    cuuint64_t dims[3] = {80, D_, 8}, str[2] = {D_ * 2, 160};
    cuuint32_t boxm[3] = {64, 32, 1}, boxr[3] = {16, 32, 1};
    encode(enc, &m.w1m, w1, 3, dims, str, boxm, CU_TENSOR_MAP_SWIZZLE_128B);
    encode(enc, &m.w1r, w1, 3, dims, str, boxr, CU_TENSOR_MAP_SWIZZLE_32B);
  }
  {
    cuuint64_t dims[4] = {80, D_, 3, 8}, str[3] = {3 * D_ * 2, D_ * 2, 160};
    cuuint32_t boxm[4] = {64, 32, 3, 1}, boxr[4] = {16, 32, 3, 1};
    encode(enc, &m.qm, wqkv, 4, dims, str, boxm, CU_TENSOR_MAP_SWIZZLE_128B);
    encode(enc, &m.qr, wqkv, 4, dims, str, boxr, CU_TENSOR_MAP_SWIZZLE_32B);
  }
  {
    cuuint64_t dims[3] = {16, D_, 40}, dims4[3] = {16, F_, 40}, str[2] = {D_ * 2, 32};
    cuuint32_t box2[3] = {16, 128, 5}, box4[3] = {16, 64, 5}, boxo[3] = {16, 80, 5};
    encode(enc, &m.w2, w2, 3, dims, str, box2, CU_TENSOR_MAP_SWIZZLE_32B);
    encode(enc, &m.w4, w4, 3, dims4, str, box4, CU_TENSOR_MAP_SWIZZLE_32B);
    encode(enc, &m.wo, wo, 3, dims, str, boxo, CU_TENSOR_MAP_SWIZZLE_32B);
  }
  {
    cuuint64_t dims[3] = {64, D_, 24}, str[2] = {F_ * 2, 128};
    cuuint32_t box[3] = {64, 64, 3};
    encode(enc, &m.w3, w3, 3, dims, str, box, CU_TENSOR_MAP_SWIZZLE_128B);
  }
  fused_kernel<<<NCTA, 384, SMEM_BYTES, cudaStreamPerThread>>>(m, x, wqkv, wphi, w1, w2, w3, w4, wo, gate_w);
}
```

```cpp
#include <cuda_runtime.h>
#include <cuda_bf16.h>
#include <cuda.h>
#include <stdint.h>

namespace {

constexpr int S_ = 2048, D_ = 640, F_ = 1536;
constexpr int NCTA = 128;
constexpr int KV_PAIR = 40 * 48 + 96;
constexpr int KV_J = 2 * KV_PAIR;

constexpr int SLOT_B = 49152, NB = 3;
constexpr int SLOT_A = 16384, NA = 4;
constexpr int OFF_B = 0;
constexpr int OFF_A = OFF_B + NB * SLOT_B;
constexpr int OFF_STG = OFF_A + 2 * SLOT_A;
constexpr int OFF_MISC = OFF_A + NA * SLOT_A;
constexpr int OFF_XST = OFF_MISC + 13312;
constexpr int OFF_CS = OFF_MISC + 16384;
constexpr int OFF_BAR = OFF_CS + 1088;
constexpr int SMEM_BYTES = OFF_BAR + 512;
constexpr int B_FULLA = 0, B_FULLB = 4, B_CS = 7, B_CS3 = 8, B_KV = 9, B_ST1 = 10, B_SDONE = 11  , B_RDY = 15  ,
              B_DSR = 21  , B_SEND = 29  , B_EMPTYB = 35  , B_SIGP = 38, B_SIGH = 39,
              B_SIGKV = 40, B_SIGX1 = 41, B_MFREE = 42, B_PEER = 43, B_EMPTYA = 44  , NBAR = 48;
constexpr int OFF_DS = OFF_A, OFF_SEND = OFF_A + 40960, OFF_G0 = OFF_A + 61440, OFF_G1 = OFF_B + 2 * SLOT_B;

constexpr int FL_DONE = 0, FL_H = 1, FL_X1 = FL_H + 16, FL_KV = FL_X1 + 16, FL_CS = FL_KV + 8, FL_CS3 = FL_CS + 8, FL_ST = FL_CS3 + 8, FL_PART = FL_ST + 16;
constexpr int FL_COUNT = FL_PART + 16 * 8;
constexpr int ACC_FLOATS = 8 * KV_J + D_ + F_;

struct Maps {
  CUtensorMap x, w1m, w1r, qm, qr, hs, w2, x1, w3, w4m, w4r, wom, wor, st_h, st_x1, st_out, xr;
};

}

__device__ __align__(1024) __nv_bfloat16 g_Hs[(S_ + 4) * D_];
__device__ __align__(1024) __nv_bfloat16 g_X1[S_ * D_];
__device__ __align__(128) float g_acc[2][ACC_FLOATS];
__device__ __align__(128) float4 g_xstat[S_];
__device__ __align__(128) float2 g_st1[S_ * 8];
__device__ __align__(128) uint4 g_part[16 * 8 * 3 * 1280];
__device__ __align__(128) unsigned g_flags[FL_COUNT * 32];
#define TSTAMP(n) do {} while (0)
#define TSTAMPX(n) do {} while (0)
#define TRACE(n) do {} while (0)
#define TR4(n) do {} while (0)

namespace {

__device__ __forceinline__ long long gtime() { long long t; asm volatile("mov.u64 %0, %%globaltimer;" : "=l"(t)); return t; }
__device__ __forceinline__ uint32_t smem_u32(const void* p) { return (uint32_t)__cvta_generic_to_shared(p); }
__device__ __forceinline__ void mbar_init(uint32_t bar, int cnt) {
  asm volatile("mbarrier.init.shared::cta.b64 [%0], %1;" ::"r"(bar), "r"(cnt) : "memory");
}
__device__ __forceinline__ void mbar_expect_tx(uint32_t bar, int bytes) {
  asm volatile("mbarrier.arrive.expect_tx.shared::cta.b64 _, [%0], %1;" ::"r"(bar), "r"(bytes) : "memory");
}
__device__ __forceinline__ void mbar_arrive_cta(uint32_t bar, uint32_t cta) {
  asm volatile("{\n.reg .b32 ra;\nmapa.shared::cluster.u32 ra, %0, %1;\nmbarrier.arrive.shared::cluster.b64 _, [ra];\n}"
               ::"r"(bar), "r"(cta) : "memory");
}
__device__ __forceinline__ uint32_t mbar_try(uint32_t bar, uint32_t parity) {
  uint32_t ok;
  asm volatile("{\n.reg .pred p;\nmbarrier.try_wait.parity.shared::cta.b64 p, [%1], %2;\nselp.u32 %0, 1, 0, p;\n}"
               : "=r"(ok) : "r"(bar), "r"(parity) : "memory");
  return ok;
}
constexpr uint32_t WAIT_LIMIT = 1u << 22;
__device__ __forceinline__ void mbar_wait(uint32_t bar, uint32_t parity) {
  uint32_t n = 0;
  while (!mbar_try(bar, parity) && ++n < WAIT_LIMIT) {}
}
__device__ __forceinline__ unsigned ld_acquire(const unsigned* p) {
  unsigned v;
  asm volatile("ld.acquire.gpu.global.u32 %0, [%1];" : "=r"(v) : "l"(p) : "memory");
  return v;
}
__device__ __forceinline__ void flag_wait(int idx, unsigned target) {
  const unsigned* p = g_flags + idx * 32;
  uint32_t n = 0;
  while ((int)(ld_acquire(p) - target) < 0 && ++n < (WAIT_LIMIT >> 4)) {}
}
__device__ __forceinline__ void flag_add(int idx) {
  asm volatile("red.release.gpu.global.add.u32 [%0], 1;" ::"l"(g_flags + idx * 32) : "memory");
}
__device__ __forceinline__ void flag_add_relaxed(int idx) {
  asm volatile("red.relaxed.gpu.global.add.u32 [%0], 1;" ::"l"(g_flags + idx * 32) : "memory");
}
__device__ __forceinline__ uint32_t mbar_test(uint32_t bar, uint32_t parity) {
  uint32_t ok;
  asm volatile("{\n.reg .pred p;\nmbarrier.test_wait.parity.shared::cta.b64 p, [%1], %2;\nselp.u32 %0, 1, 0, p;\n}"
               : "=r"(ok) : "r"(bar), "r"(parity) : "memory");
  return ok;
}
__device__ __forceinline__ uint32_t lds32(uint32_t a) {
  uint32_t v;
  asm volatile("ld.shared.u32 %0, [%1];" : "=r"(v) : "r"(a) : "memory");
  return v;
}
__device__ __forceinline__ void mbar_arrive(uint32_t bar) {
  asm volatile("mbarrier.arrive.shared::cta.b64 _, [%0];" ::"r"(bar) : "memory");
}
__device__ __forceinline__ void fence_async_all() { asm volatile("fence.proxy.async;" ::: "memory"); }
__device__ __forceinline__ void fence_async_smem() { asm volatile("fence.proxy.async.shared::cta;" ::: "memory"); }
__device__ __forceinline__ void bar_sync(int id, int n) { asm volatile("bar.sync %0, %1;" ::"r"(id), "r"(n) : "memory"); }

__device__ __forceinline__ void tma2d(uint32_t dst, const CUtensorMap* m, uint32_t bar, int c0, int c1) {
  asm volatile("cp.async.bulk.tensor.2d.shared::cluster.global.mbarrier::complete_tx::bytes [%0], [%1, {%3, %4}], [%2];"
               ::"r"(dst), "l"(m), "r"(bar), "r"(c0), "r"(c1) : "memory");
}
__device__ __forceinline__ void tma2d_mc(uint32_t dst, const CUtensorMap* m, uint32_t bar, int c0, int c1) {
  asm volatile("cp.async.bulk.tensor.2d.shared::cluster.global.mbarrier::complete_tx::bytes.multicast::cluster"
               " [%0], [%1, {%3, %4}], [%2], %5;"
               ::"r"(dst), "l"(m), "r"(bar), "r"(c0), "r"(c1), "h"((uint16_t)3) : "memory");
}
__device__ __forceinline__ void tma3d(uint32_t dst, const CUtensorMap* m, uint32_t bar, int c0, int c1, int c2) {
  asm volatile("cp.async.bulk.tensor.3d.shared::cluster.global.mbarrier::complete_tx::bytes [%0], [%1, {%3, %4, %5}], [%2];"
               ::"r"(dst), "l"(m), "r"(bar), "r"(c0), "r"(c1), "r"(c2) : "memory");
}
__device__ __forceinline__ void tma4d(uint32_t dst, const CUtensorMap* m, uint32_t bar, int c0, int c1, int c2, int c3) {
  asm volatile("cp.async.bulk.tensor.4d.shared::cluster.global.mbarrier::complete_tx::bytes [%0], [%1, {%3, %4, %5, %6}], [%2];"
               ::"r"(dst), "l"(m), "r"(bar), "r"(c0), "r"(c1), "r"(c2), "r"(c3) : "memory");
}
__device__ __forceinline__ void tma2d_store(const CUtensorMap* m, uint32_t src, int c0, int c1) {
  asm volatile("cp.async.bulk.tensor.2d.global.shared::cta.bulk_group [%0, {%2, %3}], [%1];"
               ::"l"(m), "r"(src), "r"(c0), "r"(c1) : "memory");
}
__device__ __forceinline__ void bulk_store(void* dst, uint32_t src, uint32_t bytes) {
  asm volatile("cp.async.bulk.global.shared::cta.bulk_group [%0], [%1], %2;" ::"l"(dst), "r"(src), "r"(bytes) : "memory");
}
__device__ __forceinline__ void bulk_load(uint32_t dst, const void* src, uint32_t bytes, uint32_t bar) {
  asm volatile("cp.async.bulk.shared::cluster.global.mbarrier::complete_tx::bytes [%0], [%1], %2, [%3];"
               ::"r"(dst), "l"(src), "r"(bytes), "r"(bar) : "memory");
}
__device__ __forceinline__ void bulk_commit() { asm volatile("cp.async.bulk.commit_group;" ::: "memory"); }
template <int N> __device__ __forceinline__ void bulk_wait() { asm volatile("cp.async.bulk.wait_group %0;" ::"n"(N) : "memory"); }
__device__ __forceinline__ void bulk_wait_read() { asm volatile("cp.async.bulk.wait_group.read 0;" ::: "memory"); }
__device__ __forceinline__ void bar_arrive(int id, int n) { asm volatile("bar.arrive %0, %1;" ::"r"(id), "r"(n) : "memory"); }
__device__ __forceinline__ uint4 lds128(uint32_t a) {
  uint4 v;
  asm volatile("ld.shared.v4.u32 {%0, %1, %2, %3}, [%4];" : "=r"(v.x), "=r"(v.y), "=r"(v.z), "=r"(v.w) : "r"(a) : "memory");
  return v;
}
__device__ __forceinline__ void sts128(uint32_t a, uint4 v) {
  asm volatile("st.shared.v4.u32 [%0], {%1, %2, %3, %4};" ::"r"(a), "r"(v.x), "r"(v.y), "r"(v.z), "r"(v.w) : "memory");
}
__device__ __forceinline__ uint32_t map_peer(uint32_t addr, uint32_t cta) {
  uint32_t r;
  asm("mapa.shared::cluster.u32 %0, %1, %2;" : "=r"(r) : "r"(addr), "r"(cta));
  return r;
}
__device__ __forceinline__ void st_async16(uint32_t addr, uint32_t a, uint32_t b, uint32_t c, uint32_t d, uint32_t bar) {
  asm volatile("st.async.weak.shared::cluster.mbarrier::complete_tx::bytes.v4.b32 [%0], {%1, %2, %3, %4}, [%5];"
               ::"r"(addr), "r"(a), "r"(b), "r"(c), "r"(d), "r"(bar) : "memory");
}
__device__ __forceinline__ void l2_prefetch(const void* p, uint32_t bytes) {
  asm volatile("cp.async.bulk.prefetch.L2.global [%0], %1;" ::"l"(p), "r"(bytes) : "memory");
}
__device__ __forceinline__ void prefetch_tmap(const CUtensorMap* m) {
  asm volatile("prefetch.tensormap [%0];" ::"l"(m) : "memory");
}
__device__ __forceinline__ uint64_t make_desc(uint32_t a16, uint32_t off, uint32_t lbo, uint32_t sbo, uint32_t swz) {
  const uint32_t lo = a16 + ((off >> 4) + ((lbo >> 4) << 16)), hi = (sbo >> 4) | (swz << 30);
  uint64_t d;
  asm("mov.b64 %0, {%1, %2};" : "=l"(d) : "r"(lo), "r"(hi));
  return d;
}
__device__ __forceinline__ void wg_fence() { asm volatile("wgmma.fence.sync.aligned;" ::: "memory"); }
__device__ __forceinline__ void wg_commit() { asm volatile("wgmma.commit_group.sync.aligned;" ::: "memory"); }
template <int N> __device__ __forceinline__ void wg_wait() { asm volatile("wgmma.wait_group.sync.aligned %0;" ::"n"(N) : "memory"); }
template <int N> __device__ __forceinline__ void fence_regs(float (&d)[N]) {
#pragma unroll
  for (int i = 0; i < N; i++) asm volatile("" : "+f"(d[i])::"memory");
}
template <int N> __device__ __forceinline__ void zero_regs(float (&d)[N]) {
#pragma unroll
  for (int i = 0; i < N; i++) d[i] = 0.f;
}
__device__ __forceinline__ uint32_t pack_bf16(float lo, float hi) {
  uint32_t r;
  asm("cvt.rn.bf16x2.f32 %0, %1, %2;" : "=r"(r) : "f"(hi), "f"(lo));
  return r;
}
__device__ __forceinline__ float bf_lo(uint32_t v) { return __uint_as_float(v << 16); }
__device__ __forceinline__ float bf_hi(uint32_t v) { return __uint_as_float(v & 0xffff0000u); }
__device__ __forceinline__ uint32_t max_bf2(uint32_t a, uint32_t b) {
  uint32_t r; asm("max.bf16x2 %0, %1, %2;" : "=r"(r) : "r"(a), "r"(b)); return r;
}
__device__ __forceinline__ uint32_t min_bf2(uint32_t a, uint32_t b) {
  uint32_t r; asm("min.bf16x2 %0, %1, %2;" : "=r"(r) : "r"(a), "r"(b)); return r;
}
__device__ __forceinline__ float ex2(float x) { float r; asm("ex2.approx.ftz.f32 %0, %1;" : "=f"(r) : "f"(x)); return r; }
__device__ __forceinline__ float rcp(float x) { float r; asm("rcp.approx.ftz.f32 %0, %1;" : "=f"(r) : "f"(x)); return r; }
__device__ __forceinline__ float tanh_ap(float x) { float r; asm("tanh.approx.f32 %0, %1;" : "=f"(r) : "f"(x)); return r; }
__device__ __forceinline__ float gelu_s(float x, float hs) {
  float u = x * fmaf(x * x, 0.0356774081f, 0.7978845608f);
  float hx = x * hs;
  return fmaf(hx, tanh_ap(u), hx);
}
__device__ __forceinline__ void stsm4(uint32_t addr, uint32_t r0, uint32_t r1, uint32_t r2, uint32_t r3) {
  asm volatile("stmatrix.sync.aligned.m8n8.x4.shared.b16 [%0], {%1, %2, %3, %4};"
               ::"r"(addr), "r"(r0), "r"(r1), "r"(r2), "r"(r3) : "memory");
}
__device__ __forceinline__ void red_add4(float* p, float a, float b, float c, float d) {
  asm volatile("red.global.add.v4.f32 [%0], {%1, %2, %3, %4};" ::"l"(p), "f"(a), "f"(b), "f"(c), "f"(d) : "memory");
}
__device__ __forceinline__ void red_add2(float* p, float a, float b) {
  asm volatile("red.global.add.v2.f32 [%0], {%1, %2};" ::"l"(p), "f"(a), "f"(b) : "memory");
}

__device__ __forceinline__ void mma_ss256(float (&d)[128], uint64_t descA, uint64_t descB) {
  asm volatile("wgmma.mma_async.sync.aligned.m64n256k16.f32.bf16.bf16 {"
      "%0, %1, %2, %3, %4, %5, %6, %7, %8, %9, %10, %11, %12, %13, %14, %15, "
      "%16, %17, %18, %19, %20, %21, %22, %23, %24, %25, %26, %27, %28, %29, %30, %31, "
      "%32, %33, %34, %35, %36, %37, %38, %39, %40, %41, %42, %43, %44, %45, %46, %47, "
      "%48, %49, %50, %51, %52, %53, %54, %55, %56, %57, %58, %59, %60, %61, %62, %63, "
      "%64, %65, %66, %67, %68, %69, %70, %71, %72, %73, %74, %75, %76, %77, %78, %79, "
      "%80, %81, %82, %83, %84, %85, %86, %87, %88, %89, %90, %91, %92, %93, %94, %95, "
      "%96, %97, %98, %99, %100, %101, %102, %103, %104, %105, %106, %107, %108, %109, %110, %111, "
      "%112, %113, %114, %115, %116, %117, %118, %119, %120, %121, %122, %123, %124, %125, %126, %127"
      "}, %128, %129, 1, 1, 1, 0, 1;\n"
      : "+f"(d[0]), "+f"(d[1]), "+f"(d[2]), "+f"(d[3]), "+f"(d[4]), "+f"(d[5]), "+f"(d[6]), "+f"(d[7]),
        "+f"(d[8]), "+f"(d[9]), "+f"(d[10]), "+f"(d[11]), "+f"(d[12]), "+f"(d[13]), "+f"(d[14]), "+f"(d[15]),
        "+f"(d[16]), "+f"(d[17]), "+f"(d[18]), "+f"(d[19]), "+f"(d[20]), "+f"(d[21]), "+f"(d[22]), "+f"(d[23]),
        "+f"(d[24]), "+f"(d[25]), "+f"(d[26]), "+f"(d[27]), "+f"(d[28]), "+f"(d[29]), "+f"(d[30]), "+f"(d[31]),
        "+f"(d[32]), "+f"(d[33]), "+f"(d[34]), "+f"(d[35]), "+f"(d[36]), "+f"(d[37]), "+f"(d[38]), "+f"(d[39]),
        "+f"(d[40]), "+f"(d[41]), "+f"(d[42]), "+f"(d[43]), "+f"(d[44]), "+f"(d[45]), "+f"(d[46]), "+f"(d[47]),
        "+f"(d[48]), "+f"(d[49]), "+f"(d[50]), "+f"(d[51]), "+f"(d[52]), "+f"(d[53]), "+f"(d[54]), "+f"(d[55]),
        "+f"(d[56]), "+f"(d[57]), "+f"(d[58]), "+f"(d[59]), "+f"(d[60]), "+f"(d[61]), "+f"(d[62]), "+f"(d[63]),
        "+f"(d[64]), "+f"(d[65]), "+f"(d[66]), "+f"(d[67]), "+f"(d[68]), "+f"(d[69]), "+f"(d[70]), "+f"(d[71]),
        "+f"(d[72]), "+f"(d[73]), "+f"(d[74]), "+f"(d[75]), "+f"(d[76]), "+f"(d[77]), "+f"(d[78]), "+f"(d[79]),
        "+f"(d[80]), "+f"(d[81]), "+f"(d[82]), "+f"(d[83]), "+f"(d[84]), "+f"(d[85]), "+f"(d[86]), "+f"(d[87]),
        "+f"(d[88]), "+f"(d[89]), "+f"(d[90]), "+f"(d[91]), "+f"(d[92]), "+f"(d[93]), "+f"(d[94]), "+f"(d[95]),
        "+f"(d[96]), "+f"(d[97]), "+f"(d[98]), "+f"(d[99]), "+f"(d[100]), "+f"(d[101]), "+f"(d[102]), "+f"(d[103]),
        "+f"(d[104]), "+f"(d[105]), "+f"(d[106]), "+f"(d[107]), "+f"(d[108]), "+f"(d[109]), "+f"(d[110]), "+f"(d[111]),
        "+f"(d[112]), "+f"(d[113]), "+f"(d[114]), "+f"(d[115]), "+f"(d[116]), "+f"(d[117]), "+f"(d[118]), "+f"(d[119]),
        "+f"(d[120]), "+f"(d[121]), "+f"(d[122]), "+f"(d[123]), "+f"(d[124]), "+f"(d[125]), "+f"(d[126]), "+f"(d[127])
      : "l"(descA), "l"(descB));
}

__device__ __forceinline__ void mma_ss64(float (&d)[32], uint64_t descA, uint64_t descB) {
  asm volatile("wgmma.mma_async.sync.aligned.m64n64k16.f32.bf16.bf16 {"
      "%0, %1, %2, %3, %4, %5, %6, %7, %8, %9, %10, %11, %12, %13, %14, %15, "
      "%16, %17, %18, %19, %20, %21, %22, %23, %24, %25, %26, %27, %28, %29, %30, %31"
      "}, %32, %33, 1, 1, 1, 0, 1;\n"
      : "+f"(d[0]), "+f"(d[1]), "+f"(d[2]), "+f"(d[3]), "+f"(d[4]), "+f"(d[5]), "+f"(d[6]), "+f"(d[7]),
        "+f"(d[8]), "+f"(d[9]), "+f"(d[10]), "+f"(d[11]), "+f"(d[12]), "+f"(d[13]), "+f"(d[14]), "+f"(d[15]),
        "+f"(d[16]), "+f"(d[17]), "+f"(d[18]), "+f"(d[19]), "+f"(d[20]), "+f"(d[21]), "+f"(d[22]), "+f"(d[23]),
        "+f"(d[24]), "+f"(d[25]), "+f"(d[26]), "+f"(d[27]), "+f"(d[28]), "+f"(d[29]), "+f"(d[30]), "+f"(d[31])
      : "l"(descA), "l"(descB));
}

__device__ __forceinline__ void mma_ss80(float (&d)[40], uint64_t descA, uint64_t descB) {
  asm volatile("wgmma.mma_async.sync.aligned.m64n80k16.f32.bf16.bf16 {"
      "%0, %1, %2, %3, %4, %5, %6, %7, %8, %9, %10, %11, %12, %13, %14, %15, "
      "%16, %17, %18, %19, %20, %21, %22, %23, %24, %25, %26, %27, %28, %29, %30, %31, "
      "%32, %33, %34, %35, %36, %37, %38, %39"
      "}, %40, %41, 1, 1, 1, 0, 1;\n"
      : "+f"(d[0]), "+f"(d[1]), "+f"(d[2]), "+f"(d[3]), "+f"(d[4]), "+f"(d[5]), "+f"(d[6]), "+f"(d[7]),
        "+f"(d[8]), "+f"(d[9]), "+f"(d[10]), "+f"(d[11]), "+f"(d[12]), "+f"(d[13]), "+f"(d[14]), "+f"(d[15]),
        "+f"(d[16]), "+f"(d[17]), "+f"(d[18]), "+f"(d[19]), "+f"(d[20]), "+f"(d[21]), "+f"(d[22]), "+f"(d[23]),
        "+f"(d[24]), "+f"(d[25]), "+f"(d[26]), "+f"(d[27]), "+f"(d[28]), "+f"(d[29]), "+f"(d[30]), "+f"(d[31]),
        "+f"(d[32]), "+f"(d[33]), "+f"(d[34]), "+f"(d[35]), "+f"(d[36]), "+f"(d[37]), "+f"(d[38]), "+f"(d[39])
      : "l"(descA), "l"(descB));
}

__device__ __forceinline__ void mma_ss192(float (&d)[96], uint64_t descA, uint64_t descB) {
  asm volatile("wgmma.mma_async.sync.aligned.m64n192k16.f32.bf16.bf16 {"
      "%0, %1, %2, %3, %4, %5, %6, %7, %8, %9, %10, %11, %12, %13, %14, %15, "
      "%16, %17, %18, %19, %20, %21, %22, %23, %24, %25, %26, %27, %28, %29, %30, %31, "
      "%32, %33, %34, %35, %36, %37, %38, %39, %40, %41, %42, %43, %44, %45, %46, %47, "
      "%48, %49, %50, %51, %52, %53, %54, %55, %56, %57, %58, %59, %60, %61, %62, %63, "
      "%64, %65, %66, %67, %68, %69, %70, %71, %72, %73, %74, %75, %76, %77, %78, %79, "
      "%80, %81, %82, %83, %84, %85, %86, %87, %88, %89, %90, %91, %92, %93, %94, %95"
      "}, %96, %97, 1, 1, 1, 0, 1;\n"
      : "+f"(d[0]), "+f"(d[1]), "+f"(d[2]), "+f"(d[3]), "+f"(d[4]), "+f"(d[5]), "+f"(d[6]), "+f"(d[7]),
        "+f"(d[8]), "+f"(d[9]), "+f"(d[10]), "+f"(d[11]), "+f"(d[12]), "+f"(d[13]), "+f"(d[14]), "+f"(d[15]),
        "+f"(d[16]), "+f"(d[17]), "+f"(d[18]), "+f"(d[19]), "+f"(d[20]), "+f"(d[21]), "+f"(d[22]), "+f"(d[23]),
        "+f"(d[24]), "+f"(d[25]), "+f"(d[26]), "+f"(d[27]), "+f"(d[28]), "+f"(d[29]), "+f"(d[30]), "+f"(d[31]),
        "+f"(d[32]), "+f"(d[33]), "+f"(d[34]), "+f"(d[35]), "+f"(d[36]), "+f"(d[37]), "+f"(d[38]), "+f"(d[39]),
        "+f"(d[40]), "+f"(d[41]), "+f"(d[42]), "+f"(d[43]), "+f"(d[44]), "+f"(d[45]), "+f"(d[46]), "+f"(d[47]),
        "+f"(d[48]), "+f"(d[49]), "+f"(d[50]), "+f"(d[51]), "+f"(d[52]), "+f"(d[53]), "+f"(d[54]), "+f"(d[55]),
        "+f"(d[56]), "+f"(d[57]), "+f"(d[58]), "+f"(d[59]), "+f"(d[60]), "+f"(d[61]), "+f"(d[62]), "+f"(d[63]),
        "+f"(d[64]), "+f"(d[65]), "+f"(d[66]), "+f"(d[67]), "+f"(d[68]), "+f"(d[69]), "+f"(d[70]), "+f"(d[71]),
        "+f"(d[72]), "+f"(d[73]), "+f"(d[74]), "+f"(d[75]), "+f"(d[76]), "+f"(d[77]), "+f"(d[78]), "+f"(d[79]),
        "+f"(d[80]), "+f"(d[81]), "+f"(d[82]), "+f"(d[83]), "+f"(d[84]), "+f"(d[85]), "+f"(d[86]), "+f"(d[87]),
        "+f"(d[88]), "+f"(d[89]), "+f"(d[90]), "+f"(d[91]), "+f"(d[92]), "+f"(d[93]), "+f"(d[94]), "+f"(d[95])
      : "l"(descA), "l"(descB));
}

__device__ __forceinline__ void mma_ss80_tt(float (&d)[40], uint64_t descA, uint64_t descB) {
  asm volatile("wgmma.mma_async.sync.aligned.m64n80k16.f32.bf16.bf16 {"
      "%0, %1, %2, %3, %4, %5, %6, %7, %8, %9, %10, %11, %12, %13, %14, %15, "
      "%16, %17, %18, %19, %20, %21, %22, %23, %24, %25, %26, %27, %28, %29, %30, %31, "
      "%32, %33, %34, %35, %36, %37, %38, %39"
      "}, %40, %41, 1, 1, 1, 1, 1;\n"
      : "+f"(d[0]), "+f"(d[1]), "+f"(d[2]), "+f"(d[3]), "+f"(d[4]), "+f"(d[5]), "+f"(d[6]), "+f"(d[7]),
        "+f"(d[8]), "+f"(d[9]), "+f"(d[10]), "+f"(d[11]), "+f"(d[12]), "+f"(d[13]), "+f"(d[14]), "+f"(d[15]),
        "+f"(d[16]), "+f"(d[17]), "+f"(d[18]), "+f"(d[19]), "+f"(d[20]), "+f"(d[21]), "+f"(d[22]), "+f"(d[23]),
        "+f"(d[24]), "+f"(d[25]), "+f"(d[26]), "+f"(d[27]), "+f"(d[28]), "+f"(d[29]), "+f"(d[30]), "+f"(d[31]),
        "+f"(d[32]), "+f"(d[33]), "+f"(d[34]), "+f"(d[35]), "+f"(d[36]), "+f"(d[37]), "+f"(d[38]), "+f"(d[39])
      : "l"(descA), "l"(descB));
}
__device__ __forceinline__ void mma_ss80_tt_z(float (&d)[40], uint64_t descA, uint64_t descB) {
  asm volatile("wgmma.mma_async.sync.aligned.m64n80k16.f32.bf16.bf16 {"
      "%0, %1, %2, %3, %4, %5, %6, %7, %8, %9, %10, %11, %12, %13, %14, %15, "
      "%16, %17, %18, %19, %20, %21, %22, %23, %24, %25, %26, %27, %28, %29, %30, %31, "
      "%32, %33, %34, %35, %36, %37, %38, %39"
      "}, %40, %41, 0, 1, 1, 1, 1;\n"
      : "=f"(d[0]), "=f"(d[1]), "=f"(d[2]), "=f"(d[3]), "=f"(d[4]), "=f"(d[5]), "=f"(d[6]), "=f"(d[7]),
        "=f"(d[8]), "=f"(d[9]), "=f"(d[10]), "=f"(d[11]), "=f"(d[12]), "=f"(d[13]), "=f"(d[14]), "=f"(d[15]),
        "=f"(d[16]), "=f"(d[17]), "=f"(d[18]), "=f"(d[19]), "=f"(d[20]), "=f"(d[21]), "=f"(d[22]), "=f"(d[23]),
        "=f"(d[24]), "=f"(d[25]), "=f"(d[26]), "=f"(d[27]), "=f"(d[28]), "=f"(d[29]), "=f"(d[30]), "=f"(d[31]),
        "=f"(d[32]), "=f"(d[33]), "=f"(d[34]), "=f"(d[35]), "=f"(d[36]), "=f"(d[37]), "=f"(d[38]), "=f"(d[39])
      : "l"(descA), "l"(descB));
}

__device__ __forceinline__ void mma_rs80_k(float (&d)[40], const uint32_t (&a)[4], uint64_t descB) {
  asm volatile("wgmma.mma_async.sync.aligned.m64n80k16.f32.bf16.bf16 {"
      "%0, %1, %2, %3, %4, %5, %6, %7, %8, %9, %10, %11, %12, %13, %14, %15, "
      "%16, %17, %18, %19, %20, %21, %22, %23, %24, %25, %26, %27, %28, %29, %30, %31, "
      "%32, %33, %34, %35, %36, %37, %38, %39"
      "}, {%40, %41, %42, %43}, %44, 1, 1, 1, 0;\n"
      : "+f"(d[0]), "+f"(d[1]), "+f"(d[2]), "+f"(d[3]), "+f"(d[4]), "+f"(d[5]), "+f"(d[6]), "+f"(d[7]),
        "+f"(d[8]), "+f"(d[9]), "+f"(d[10]), "+f"(d[11]), "+f"(d[12]), "+f"(d[13]), "+f"(d[14]), "+f"(d[15]),
        "+f"(d[16]), "+f"(d[17]), "+f"(d[18]), "+f"(d[19]), "+f"(d[20]), "+f"(d[21]), "+f"(d[22]), "+f"(d[23]),
        "+f"(d[24]), "+f"(d[25]), "+f"(d[26]), "+f"(d[27]), "+f"(d[28]), "+f"(d[29]), "+f"(d[30]), "+f"(d[31]),
        "+f"(d[32]), "+f"(d[33]), "+f"(d[34]), "+f"(d[35]), "+f"(d[36]), "+f"(d[37]), "+f"(d[38]), "+f"(d[39])
      : "r"(a[0]), "r"(a[1]), "r"(a[2]), "r"(a[3]), "l"(descB));
}
__device__ __forceinline__ void mma_rs80_k_z(float (&d)[40], const uint32_t (&a)[4], uint64_t descB) {
  asm volatile("wgmma.mma_async.sync.aligned.m64n80k16.f32.bf16.bf16 {"
      "%0, %1, %2, %3, %4, %5, %6, %7, %8, %9, %10, %11, %12, %13, %14, %15, "
      "%16, %17, %18, %19, %20, %21, %22, %23, %24, %25, %26, %27, %28, %29, %30, %31, "
      "%32, %33, %34, %35, %36, %37, %38, %39"
      "}, {%40, %41, %42, %43}, %44, 0, 1, 1, 0;\n"
      : "=f"(d[0]), "=f"(d[1]), "=f"(d[2]), "=f"(d[3]), "=f"(d[4]), "=f"(d[5]), "=f"(d[6]), "=f"(d[7]),
        "=f"(d[8]), "=f"(d[9]), "=f"(d[10]), "=f"(d[11]), "=f"(d[12]), "=f"(d[13]), "=f"(d[14]), "=f"(d[15]),
        "=f"(d[16]), "=f"(d[17]), "=f"(d[18]), "=f"(d[19]), "=f"(d[20]), "=f"(d[21]), "=f"(d[22]), "=f"(d[23]),
        "=f"(d[24]), "=f"(d[25]), "=f"(d[26]), "=f"(d[27]), "=f"(d[28]), "=f"(d[29]), "=f"(d[30]), "=f"(d[31]),
        "=f"(d[32]), "=f"(d[33]), "=f"(d[34]), "=f"(d[35]), "=f"(d[36]), "=f"(d[37]), "=f"(d[38]), "=f"(d[39])
      : "r"(a[0]), "r"(a[1]), "r"(a[2]), "r"(a[3]), "l"(descB));
}

__device__ __forceinline__ void mma_rs48_k(float (&d)[24], const uint32_t (&a)[4], uint64_t descB) {
  asm volatile("wgmma.mma_async.sync.aligned.m64n48k16.f32.bf16.bf16 {"
      "%0, %1, %2, %3, %4, %5, %6, %7, %8, %9, %10, %11, %12, %13, %14, %15, "
      "%16, %17, %18, %19, %20, %21, %22, %23"
      "}, {%24, %25, %26, %27}, %28, 1, 1, 1, 0;\n"
      : "+f"(d[0]), "+f"(d[1]), "+f"(d[2]), "+f"(d[3]), "+f"(d[4]), "+f"(d[5]), "+f"(d[6]), "+f"(d[7]),
        "+f"(d[8]), "+f"(d[9]), "+f"(d[10]), "+f"(d[11]), "+f"(d[12]), "+f"(d[13]), "+f"(d[14]), "+f"(d[15]),
        "+f"(d[16]), "+f"(d[17]), "+f"(d[18]), "+f"(d[19]), "+f"(d[20]), "+f"(d[21]), "+f"(d[22]), "+f"(d[23])
      : "r"(a[0]), "r"(a[1]), "r"(a[2]), "r"(a[3]), "l"(descB));
}
__device__ __forceinline__ void mma_rs48_k_z(float (&d)[24], const uint32_t (&a)[4], uint64_t descB) {
  asm volatile("wgmma.mma_async.sync.aligned.m64n48k16.f32.bf16.bf16 {"
      "%0, %1, %2, %3, %4, %5, %6, %7, %8, %9, %10, %11, %12, %13, %14, %15, "
      "%16, %17, %18, %19, %20, %21, %22, %23"
      "}, {%24, %25, %26, %27}, %28, 0, 1, 1, 0;\n"
      : "=f"(d[0]), "=f"(d[1]), "=f"(d[2]), "=f"(d[3]), "=f"(d[4]), "=f"(d[5]), "=f"(d[6]), "=f"(d[7]),
        "=f"(d[8]), "=f"(d[9]), "=f"(d[10]), "=f"(d[11]), "=f"(d[12]), "=f"(d[13]), "=f"(d[14]), "=f"(d[15]),
        "=f"(d[16]), "=f"(d[17]), "=f"(d[18]), "=f"(d[19]), "=f"(d[20]), "=f"(d[21]), "=f"(d[22]), "=f"(d[23])
      : "r"(a[0]), "r"(a[1]), "r"(a[2]), "r"(a[3]), "l"(descB));
}

__device__ __forceinline__ void mma_rs128_n(float (&d)[64], const uint32_t (&a)[4], uint64_t descB) {
  asm volatile("wgmma.mma_async.sync.aligned.m64n128k16.f32.bf16.bf16 {"
      "%0, %1, %2, %3, %4, %5, %6, %7, %8, %9, %10, %11, %12, %13, %14, %15, "
      "%16, %17, %18, %19, %20, %21, %22, %23, %24, %25, %26, %27, %28, %29, %30, %31, "
      "%32, %33, %34, %35, %36, %37, %38, %39, %40, %41, %42, %43, %44, %45, %46, %47, "
      "%48, %49, %50, %51, %52, %53, %54, %55, %56, %57, %58, %59, %60, %61, %62, %63"
      "}, {%64, %65, %66, %67}, %68, 1, 1, 1, 1;\n"
      : "+f"(d[0]), "+f"(d[1]), "+f"(d[2]), "+f"(d[3]), "+f"(d[4]), "+f"(d[5]), "+f"(d[6]), "+f"(d[7]),
        "+f"(d[8]), "+f"(d[9]), "+f"(d[10]), "+f"(d[11]), "+f"(d[12]), "+f"(d[13]), "+f"(d[14]), "+f"(d[15]),
        "+f"(d[16]), "+f"(d[17]), "+f"(d[18]), "+f"(d[19]), "+f"(d[20]), "+f"(d[21]), "+f"(d[22]), "+f"(d[23]),
        "+f"(d[24]), "+f"(d[25]), "+f"(d[26]), "+f"(d[27]), "+f"(d[28]), "+f"(d[29]), "+f"(d[30]), "+f"(d[31]),
        "+f"(d[32]), "+f"(d[33]), "+f"(d[34]), "+f"(d[35]), "+f"(d[36]), "+f"(d[37]), "+f"(d[38]), "+f"(d[39]),
        "+f"(d[40]), "+f"(d[41]), "+f"(d[42]), "+f"(d[43]), "+f"(d[44]), "+f"(d[45]), "+f"(d[46]), "+f"(d[47]),
        "+f"(d[48]), "+f"(d[49]), "+f"(d[50]), "+f"(d[51]), "+f"(d[52]), "+f"(d[53]), "+f"(d[54]), "+f"(d[55]),
        "+f"(d[56]), "+f"(d[57]), "+f"(d[58]), "+f"(d[59]), "+f"(d[60]), "+f"(d[61]), "+f"(d[62]), "+f"(d[63])
      : "r"(a[0]), "r"(a[1]), "r"(a[2]), "r"(a[3]), "l"(descB));
}
__device__ __forceinline__ void mma_rs128_n_z(float (&d)[64], const uint32_t (&a)[4], uint64_t descB) {
  asm volatile("wgmma.mma_async.sync.aligned.m64n128k16.f32.bf16.bf16 {"
      "%0, %1, %2, %3, %4, %5, %6, %7, %8, %9, %10, %11, %12, %13, %14, %15, "
      "%16, %17, %18, %19, %20, %21, %22, %23, %24, %25, %26, %27, %28, %29, %30, %31, "
      "%32, %33, %34, %35, %36, %37, %38, %39, %40, %41, %42, %43, %44, %45, %46, %47, "
      "%48, %49, %50, %51, %52, %53, %54, %55, %56, %57, %58, %59, %60, %61, %62, %63"
      "}, {%64, %65, %66, %67}, %68, 0, 1, 1, 1;\n"
      : "=f"(d[0]), "=f"(d[1]), "=f"(d[2]), "=f"(d[3]), "=f"(d[4]), "=f"(d[5]), "=f"(d[6]), "=f"(d[7]),
        "=f"(d[8]), "=f"(d[9]), "=f"(d[10]), "=f"(d[11]), "=f"(d[12]), "=f"(d[13]), "=f"(d[14]), "=f"(d[15]),
        "=f"(d[16]), "=f"(d[17]), "=f"(d[18]), "=f"(d[19]), "=f"(d[20]), "=f"(d[21]), "=f"(d[22]), "=f"(d[23]),
        "=f"(d[24]), "=f"(d[25]), "=f"(d[26]), "=f"(d[27]), "=f"(d[28]), "=f"(d[29]), "=f"(d[30]), "=f"(d[31]),
        "=f"(d[32]), "=f"(d[33]), "=f"(d[34]), "=f"(d[35]), "=f"(d[36]), "=f"(d[37]), "=f"(d[38]), "=f"(d[39]),
        "=f"(d[40]), "=f"(d[41]), "=f"(d[42]), "=f"(d[43]), "=f"(d[44]), "=f"(d[45]), "=f"(d[46]), "=f"(d[47]),
        "=f"(d[48]), "=f"(d[49]), "=f"(d[50]), "=f"(d[51]), "=f"(d[52]), "=f"(d[53]), "=f"(d[54]), "=f"(d[55]),
        "=f"(d[56]), "=f"(d[57]), "=f"(d[58]), "=f"(d[59]), "=f"(d[60]), "=f"(d[61]), "=f"(d[62]), "=f"(d[63])
      : "r"(a[0]), "r"(a[1]), "r"(a[2]), "r"(a[3]), "l"(descB));
}

__device__ __forceinline__ void mma_rs32_n(float (&d)[16], const uint32_t (&a)[4], uint64_t descB) {
  asm volatile("wgmma.mma_async.sync.aligned.m64n32k16.f32.bf16.bf16 {"
      "%0, %1, %2, %3, %4, %5, %6, %7, %8, %9, %10, %11, %12, %13, %14, %15"
      "}, {%16, %17, %18, %19}, %20, 1, 1, 1, 1;\n"
      : "+f"(d[0]), "+f"(d[1]), "+f"(d[2]), "+f"(d[3]), "+f"(d[4]), "+f"(d[5]), "+f"(d[6]), "+f"(d[7]),
        "+f"(d[8]), "+f"(d[9]), "+f"(d[10]), "+f"(d[11]), "+f"(d[12]), "+f"(d[13]), "+f"(d[14]), "+f"(d[15])
      : "r"(a[0]), "r"(a[1]), "r"(a[2]), "r"(a[3]), "l"(descB));
}
__device__ __forceinline__ void mma_rs32_n_z(float (&d)[16], const uint32_t (&a)[4], uint64_t descB) {
  asm volatile("wgmma.mma_async.sync.aligned.m64n32k16.f32.bf16.bf16 {"
      "%0, %1, %2, %3, %4, %5, %6, %7, %8, %9, %10, %11, %12, %13, %14, %15"
      "}, {%16, %17, %18, %19}, %20, 0, 1, 1, 1;\n"
      : "=f"(d[0]), "=f"(d[1]), "=f"(d[2]), "=f"(d[3]), "=f"(d[4]), "=f"(d[5]), "=f"(d[6]), "=f"(d[7]),
        "=f"(d[8]), "=f"(d[9]), "=f"(d[10]), "=f"(d[11]), "=f"(d[12]), "=f"(d[13]), "=f"(d[14]), "=f"(d[15])
      : "r"(a[0]), "r"(a[1]), "r"(a[2]), "r"(a[3]), "l"(descB));
}

__device__ __forceinline__ void feature_map(const uint32_t (&P)[2][10], uint32_t (&fr)[10][4]) {
  constexpr float L2E = 1.4426950408889634f;
#pragma unroll
  for (int p = 0; p < 2; p++) {
#pragma unroll
    for (int r = 0; r < 2; r++) {
      uint32_t mx = P[r][5 * p], mn = mx;
#pragma unroll
      for (int g = 1; g < 5; g++) { mx = max_bf2(mx, P[r][5 * p + g]); mn = min_bf2(mn, P[r][5 * p + g]); }
      mx = max_bf2(mx, __shfl_xor_sync(0xffffffffu, mx, 1));
      mn = min_bf2(mn, __shfl_xor_sync(0xffffffffu, mn, 1));
      mx = max_bf2(mx, __shfl_xor_sync(0xffffffffu, mx, 2));
      mn = min_bf2(mn, __shfl_xor_sync(0xffffffffu, mn, 2));
      float mx0 = -bf_lo(mx) * L2E, mx1 = -bf_hi(mx) * L2E, mn0 = bf_lo(mn) * L2E, mn1 = bf_hi(mn) * L2E;
      float ep0[5], ep1[5], en0[5], en1[5];
      float sp0 = 0.f, sp1 = 0.f, sn0 = 0.f, sn1 = 0.f;
#pragma unroll
      for (int g = 0; g < 5; g++) {
        float x0 = bf_lo(P[r][5 * p + g]), x1 = bf_hi(P[r][5 * p + g]);
        ep0[g] = ex2(fmaf(x0, L2E, mx0)); ep1[g] = ex2(fmaf(x1, L2E, mx1));
        en0[g] = ex2(fmaf(x0, -L2E, mn0)); en1[g] = ex2(fmaf(x1, -L2E, mn1));
        sp0 += ep0[g]; sp1 += ep1[g]; sn0 += en0[g]; sn1 += en1[g];
      }
      sp0 += __shfl_xor_sync(0xffffffffu, sp0, 1); sp1 += __shfl_xor_sync(0xffffffffu, sp1, 1);
      sn0 += __shfl_xor_sync(0xffffffffu, sn0, 1); sn1 += __shfl_xor_sync(0xffffffffu, sn1, 1);
      sp0 += __shfl_xor_sync(0xffffffffu, sp0, 2); sp1 += __shfl_xor_sync(0xffffffffu, sp1, 2);
      sn0 += __shfl_xor_sync(0xffffffffu, sn0, 2); sn1 += __shfl_xor_sync(0xffffffffu, sn1, 2);
      sp0 = rcp(sp0); sp1 = rcp(sp1); sn0 = rcp(sn0); sn1 = rcp(sn1);
#pragma unroll
      for (int g = 0; g < 5; g++) {
        fr[5 * p + g][r] = pack_bf16(ep0[g] * sp0, ep1[g] * sp1);
        fr[5 * p + g][2 + r] = pack_bf16(en0[g] * sn0, en1[g] * sn1);
      }
    }
  }
}

struct Ring {
  uint32_t idx, phase;
  template <int N> __device__ __forceinline__ void next() { if (++idx == N) { idx = 0; phase ^= 1; } }
};

}

__global__ void __cluster_dims__(2, 1, 1) __launch_bounds__(384, 1)
fused_kernel(const __grid_constant__ Maps maps, const __nv_bfloat16* __restrict__ x, const __nv_bfloat16* __restrict__ wqkv,
             const __nv_bfloat16* __restrict__ wphi, const __nv_bfloat16* __restrict__ w1, const __nv_bfloat16* __restrict__ w2,
             const __nv_bfloat16* __restrict__ w3, const __nv_bfloat16* __restrict__ w4, const __nv_bfloat16* __restrict__ wo,
             const __nv_bfloat16* __restrict__ gate_w) {
  extern __shared__ __align__(1024) uint8_t sgen[];
  const uint32_t sb = smem_u32(sgen);
  const uint32_t sb16 = (sb & 0x3FFFFu) >> 4;
  const uint32_t bars = sb + OFF_BAR;
  const uint32_t fullA = bars + 8 * B_FULLA, emptyA = bars + 8 * B_EMPTYA, fullB = bars + 8 * B_FULLB, emptyB = bars + 8 * B_EMPTYB;

  const int tid = threadIdx.x;
  const int rank = blockIdx.x & 1;
  const int pairIdx = blockIdx.x >> 1;
  const int i = pairIdx >> 2, j = 2 * (pairIdx & 3) + rank;

  TSTAMP(0);
  if ((tid & 31) == 0) {
#pragma unroll 1
    for (int b = tid >> 5; b < NBAR; b += 12) {
      mbar_init(bars + 8 * b, b < B_SEND ? 1 : b < B_EMPTYB ? 4 : b < B_EMPTYA ? 8 : 16);
      if (b >= B_DSR && b < B_SEND) mbar_expect_tx(bars + 8 * b, 10240);
    }
    asm volatile("fence.mbarrier_init.release.cluster;" ::: "memory");
  }
  if (tid == 352) { prefetch_tmap(&maps.x); prefetch_tmap(&maps.qm); prefetch_tmap(&maps.w1m); prefetch_tmap(&maps.qr); prefetch_tmap(&maps.w1r); }
  asm volatile("barrier.cluster.arrive.relaxed.aligned;" ::: "memory");

  if (tid >= 256) {
    asm volatile("setmaxnreg.dec.sync.aligned.u32 40;");
    asm volatile("barrier.cluster.wait.aligned;" ::: "memory");
    auto get_epoch = [&]() { return *reinterpret_cast<volatile unsigned*>(g_flags + FL_DONE * 32) / NCTA; };
    const int lane = tid & 31, pw = (tid >> 5) & 3;
    auto send_stream = [&](int w, unsigned ep1) {
#pragma unroll 1
      for (int c = 0; c < 3; c++) {
        const int d = (j + 2 * c + 2) & 7;
        mbar_wait(bars + 8 * (B_SEND + 2 * c + w), 0);
        if (w) TR4(c * 16 + 7);
        bulk_store(g_part + (size_t)((i * 8 + d) * 3 + c) * 1280 + w * 640, sb + OFF_SEND + w * 10240, 10240);
        bulk_commit();
        bulk_wait<0>();
        if (c < 2) mbar_arrive(bars + 8 * (B_SDONE + 2 * c + w));
        if (w) TR4(c * 16 + 9);
        asm volatile("st.release.gpu.global.u32 [%0], %1;"
                     ::"l"(g_flags + (FL_PART + i * 8 + d) * 32 + 2 * c + w), "r"(ep1) : "memory");
        if (w) TR4(c * 16 + 10);
      }
    };
    if (pw == 0) {
      if (lane == 0) {
        Ring r{0, 1};
        unsigned ep1 = 0;
#pragma unroll 1
        for (int k = 0; k < 30; k++) {
          if (k == 4) ep1 = get_epoch() + 1;
          if (k == 10 || k == 20) {
            const unsigned tgt = ep1 * 8u;
            const unsigned* f0 = g_flags + (k == 10 ? FL_H + ((i - 1) & 15) : FL_X1 + i) * 32;
            const unsigned* f1 = g_flags + (k == 10 ? FL_H + i : FL_X1 + i) * 32;
            const unsigned* f2 = g_flags + (k == 10 ? FL_H + ((i + 1) & 15) : FL_X1 + i) * 32;
            uint32_t n = 0;
            while (++n < (WAIT_LIMIT >> 4)) {
              unsigned v0, v1, v2;
              asm volatile("ld.relaxed.gpu.global.u32 %0, [%3];\nld.relaxed.gpu.global.u32 %1, [%4];\nld.acquire.gpu.global.u32 %2, [%5];"
                           : "=r"(v0), "=r"(v1), "=r"(v2) : "l"(f0), "l"(f1), "l"(f2) : "memory");
              if ((int)((v0 - tgt) | (v1 - tgt) | (v2 - tgt)) >= 0) break;
            }
            TSTAMPX(k == 10 ? 29 : 30);
          }
          mbar_wait(emptyA + 8 * r.idx, r.phase);
          const uint32_t bar = fullA + 8 * r.idx, slot = sb + OFF_A + r.idx * SLOT_A;
          TRACE(k);
          mbar_expect_tx(bar, SLOT_A);
          tma2d_mc(slot + rank * 8192, k < 10 ? &maps.x : k < 20 ? &maps.hs : &maps.x1, bar, 64 * (k % 10), 128 * i + 64 * rank);
          r.next<NA>();
        }
        send_stream(1, ep1);
      }
    } else if (pw == 1) {
      if (lane == 0) {
        Ring r{0, 1};
#pragma unroll 1
        for (int k = 0; k < 26; k++) {
          mbar_wait(emptyB + 8 * r.idx, r.phase);
          const uint32_t bar = fullB + 8 * r.idx, slot = sb + OFF_B + r.idx * SLOT_B;
          TRACE(96 + k);
          if (k < 10) {
            mbar_expect_tx(bar, 40960);
            tma4d(slot + 8192, &maps.qm, bar, 0, 64 * k, 0, j);
            tma3d(slot, &maps.w1m, bar, 0, 64 * k, j);
            tma4d(slot + 32768 + 2048, &maps.qr, bar, 64, 64 * k, 0, j);
            tma3d(slot + 32768, &maps.w1r, bar, 64, 64 * k, j);
          } else if (k < 13) {
            const int s = k - 10;
            mbar_expect_tx(bar, 40960);
            tma3d(slot, &maps.w2, bar, 0, 256 * s, 5 * j);
            if (s < 2) tma3d(slot + 20480, &maps.w2, bar, 0, 256 * s + 128, 5 * j);
            else tma2d(slot + 20480, &maps.xr, bar, 80 * j, 128 * i);
          } else if (k < 18) {
            mbar_expect_tx(bar, 49152);
            tma3d(slot, &maps.w3, bar, 0, 128 * (k - 13), 3 * j);
            tma3d(slot + 24576, &maps.w3, bar, 0, 128 * (k - 13) + 64, 3 * j);
          } else {
            const int hb = k & 1, d = (j + (k - 16 - hb)) & 7;
            mbar_expect_tx(bar, hb ? 46080 : 40960);
#pragma unroll 1
            for (int u = 0; u < 4; u++) {
              const int g = u >> 1, sl = d ^ (u & 1);
              if (hb && g) {
                tma3d(slot + 20480 + (u & 1) * 10240, &maps.wom, bar, 0, 80 * j, sl);
                tma3d(slot + 40960 + (u & 1) * 2560, &maps.wor, bar, 64, 80 * j, sl);
              } else {
                const int k0 = 192 * j + 128 * hb + 64 * g;
                tma3d(slot + g * 20480 + (u & 1) * 8192, &maps.w4m, bar, 0, k0, sl);
                tma3d(slot + g * 20480 + 16384 + (u & 1) * 2048, &maps.w4r, bar, 64, k0, sl);
              }
            }
          }
          r.next<NB>();
        }
      }
    } else {
      const unsigned epoch = get_epoch();
      float* accg = g_acc[epoch & 1];
      if (pw == 2) {
        {
          float* nxt = g_acc[(epoch + 1) & 1];
          constexpr int PER = ACC_FLOATS / NCTA;
#pragma unroll 1
          for (int e = lane; e < PER; e += 32) nxt[blockIdx.x * PER + e] = 0.f;
        }
        if (lane == 0) {
          flag_wait(FL_CS + j, (epoch + 1) * 16u);
          flag_wait(FL_ST + i, (epoch + 1) * 8u);
          fence_async_all();
          mbar_expect_tx(bars + 8 * B_CS, 320 + 2048);
          bulk_load(sb + OFF_CS, accg + 8 * KV_J + 80 * j, 320, bars + 8 * B_CS);
          bulk_load(sb + OFF_XST, g_xstat + 128 * i, 2048, bars + 8 * B_CS);
          TSTAMPX(21);
          l2_prefetch(w2 + (size_t)blockIdx.x * (D_ * D_ / NCTA), D_ * D_ * 2 / NCTA);
          l2_prefetch(w4 + (size_t)blockIdx.x * (F_ * D_ / NCTA), F_ * D_ * 2 / NCTA);
          l2_prefetch(wo + (size_t)blockIdx.x * (D_ * D_ / NCTA), D_ * D_ * 2 / NCTA);
        }
        __syncwarp();
#pragma unroll 1
        for (int m = 0; m < 6; m++) {
          const int col = 192 * j + 32 * m + 8 * (lane & 3);
          const __nv_bfloat16* p = w3 + (size_t)(40 * i + (lane >> 2) * 5) * F_ + col;
          float a[8];
#pragma unroll
          for (int e = 0; e < 8; e++) a[e] = 0.f;
#pragma unroll
          for (int it = 0; it < 5; it++) {
            const uint4 v = __ldg(reinterpret_cast<const uint4*>(p + (size_t)it * F_));
            a[0] += bf_lo(v.x); a[1] += bf_hi(v.x); a[2] += bf_lo(v.y); a[3] += bf_hi(v.y);
            a[4] += bf_lo(v.z); a[5] += bf_hi(v.z); a[6] += bf_lo(v.w); a[7] += bf_hi(v.w);
          }
#pragma unroll
          for (int e = 0; e < 4; e++) {
            const float snd = (lane & 4) ? a[e] : a[e + 4], keep = (lane & 4) ? a[e + 4] : a[e];
            a[e] = keep + __shfl_xor_sync(0xffffffffu, snd, 4);
            a[e] += __shfl_xor_sync(0xffffffffu, a[e], 8);
            a[e] += __shfl_xor_sync(0xffffffffu, a[e], 16);
          }
          if (lane < 8) red_add4(accg + 8 * KV_J + D_ + col + (lane >> 2) * 4, a[0], a[1], a[2], a[3]);
        }
        __syncwarp();
        if (lane == 0) {
          flag_add(FL_CS3 + j);
          flag_wait(FL_KV + j, (epoch + 1) * 16u);
          fence_async_all();
          mbar_expect_tx(bars + 8 * B_KV, KV_J * 4);
          bulk_load(sb + OFF_MISC, accg + j * KV_J, KV_J * 4, bars + 8 * B_KV);
          TSTAMPX(22);
          mbar_wait(bars + 8 * B_MFREE, 0);
          flag_wait(FL_X1 + i, (epoch + 1) * 8u);
          flag_wait(FL_CS3 + j, (epoch + 1) * 16u);
          fence_async_all();
          mbar_expect_tx(bars + 8 * B_ST1, 8192 + 768);
          bulk_load(sb + OFF_CS + 320, accg + 8 * KV_J + D_ + 192 * j, 768, bars + 8 * B_ST1);
          bulk_load(sb + OFF_MISC, g_st1 + 128 * i * 8, 8192, bars + 8 * B_ST1);
        }
        __syncwarp();
        mbar_wait(bars + 8 * (B_SEND + 1), 0);
        const unsigned* fp = g_flags + (FL_PART + i * 8 + j) * 32 + lane;
        bool seen = lane >= 6;
        uint32_t n = 0;
        while (!__all_sync(0xffffffffu, seen) && ++n < (WAIT_LIMIT >> 4)) {
          if (!seen && ld_acquire(fp) == epoch + 1 && (lane < 2 || mbar_test(bars + 8 * (B_SEND + 5), 0))) {
            seen = true;
            if (lane & 1) TR4((lane >> 1) * 16 + 11);
            mbar_expect_tx(bars + 8 * (B_RDY + lane), 10240);
            bulk_load(sb + (lane < 2 ? OFF_G0 : OFF_G1 - 20480) + lane * 10240, g_part + (size_t)(i * 8 + j) * 3840 + lane * 640, 10240,
                      bars + 8 * (B_RDY + lane));
          }
        }
      } else if (lane == 0) {
        const int shift = (j < 2) ? 1 : (j < 4) ? -1 : (j < 6) ? 2 : -2;
        if ((shift > 0 && i == 0) || (shift < 0 && i == 15)) {
          const int nz = shift > 0 ? shift : -shift, zr = shift > 0 ? 0 : S_ - nz;
#pragma unroll 1
          for (int e = 0; e < nz * 10; e++)
            reinterpret_cast<uint4*>(g_Hs + (size_t)(2 + zr + e / 10) * D_ + 80 * j)[e % 10] = make_uint4(0, 0, 0, 0);
          fence_async_all();
        }
        mbar_wait(bars + 8 * B_SIGP, 0);
        flag_add(FL_CS + j);
        flag_add_relaxed(FL_ST + i);
        TSTAMPX(20);
        prefetch_tmap(&maps.st_h); prefetch_tmap(&maps.st_x1); prefetch_tmap(&maps.hs); prefetch_tmap(&maps.x1); prefetch_tmap(&maps.xr);
        prefetch_tmap(&maps.w2); prefetch_tmap(&maps.w3); prefetch_tmap(&maps.w4m); prefetch_tmap(&maps.w4r); prefetch_tmap(&maps.wom); prefetch_tmap(&maps.wor); prefetch_tmap(&maps.st_out);
        mbar_wait(bars + 8 * B_SIGH, 0);
        TSTAMPX(23);
        tma2d_store(&maps.st_h, sb + OFF_STG, 80 * j, 128 * i + 2 + shift);
        tma2d_store(&maps.st_h, sb + OFF_STG + 10240, 80 * j, 128 * i + 66 + shift);
        bulk_commit(); bulk_wait<0>();
        flag_add(FL_H + i);
        TSTAMPX(24);
        mbar_wait(bars + 8 * B_SIGKV, 0);
        TSTAMPX(25);
        flag_add(FL_KV + j);
        TSTAMPX(26);
        mbar_wait(bars + 8 * B_SIGX1, 0);
        TSTAMPX(27);
        tma2d_store(&maps.st_x1, sb + OFF_STG, 80 * j, 128 * i);
        tma2d_store(&maps.st_x1, sb + OFF_STG + 10240, 80 * j, 128 * i + 64);
        bulk_commit(); bulk_wait<0>();
        flag_add(FL_X1 + i);
        TSTAMPX(28);
        send_stream(0, epoch + 1);
      }
    }
    __syncwarp();
    asm volatile("barrier.cluster.arrive;\nbarrier.cluster.wait;" ::: "memory");
  } else {
    asm volatile("setmaxnreg.inc.sync.aligned.u32 232;");
    const int wg = tid >> 7, warp = tid >> 5, lane = tid & 31, t = lane & 3;
    const int rloc = warp * 16 + (lane >> 2);
    const float* s_cs = reinterpret_cast<const float*>(sgen + OFF_CS);
    auto signal = [&](int b) {
      __syncwarp();
      if (lane == 0) mbar_arrive(bars + 8 * b);
    };
    auto releaseB = [&](uint32_t bar) {
      __syncwarp();
      if (lane == 0) mbar_arrive(bar);
    };
    auto release = [&](uint32_t bar) {
      __syncwarp();
      if (lane < 2) mbar_arrive_cta(bar, lane);
    };
    const uint32_t stg_lane = (warp * 16 + ((lane >> 3) & 1) * 8 + (lane & 7)) * 160 + (lane >> 4) * 16;

    unsigned epoch;
    {
      const int row = 128 * i + 16 * j + warp * 2 + (lane >> 4), l16 = lane & 15;
      uint4 v[5], w[5], cv[2];
#pragma unroll
      for (int c = 0; c < 5; c++) {
        v[c] = __ldg(reinterpret_cast<const uint4*>(x + (size_t)row * D_ + c * 128 + l16 * 8));
        w[c] = __ldg(reinterpret_cast<const uint4*>(gate_w + c * 128 + l16 * 8));
      }
      const int cch = tid % 10, crw = tid / 10;
      if (tid < 200) {
        const __nv_bfloat16* cp = w1 + (size_t)(40 * i + crw) * D_ + 80 * j + 8 * cch;
        cv[0] = __ldg(reinterpret_cast<const uint4*>(cp)); cv[1] = __ldg(reinterpret_cast<const uint4*>(cp + 20 * D_));
      }
      uint4 pre = make_uint4(0, 0, 0, 0);
      if (tid < 200) pre = __ldg(reinterpret_cast<const uint4*>(wphi + (size_t)j * 1600) + tid);
      epoch = *reinterpret_cast<volatile unsigned*>(g_flags + FL_DONE * 32) / NCTA;
#pragma unroll 1
      for (int e = tid; e < 800; e += 256) sts128(sb + OFF_MISC + e * 16, make_uint4(0, 0, 0, 0));
      bar_sync(1, 256);
      if (tid < 200) {
        const uint32_t ww[4] = {pre.x, pre.y, pre.z, pre.w};
        const int h = tid / 50;
#pragma unroll
        for (int e = 0; e < 8; e++) {
          const int idx = tid * 8 + e, k = idx / 20, ff = idx - 20 * k;
          const int n = 40 * (h >> 1) + 8 * (ff >> 2) + 2 * (ff & 3) + (h & 1);
          const int off = (k >> 4) * 2560 + n * 32 + ((((k >> 3) ^ (n >> 2)) & 1) << 4) + (k & 7) * 2;
          *reinterpret_cast<unsigned short*>(sgen + OFF_MISC + off) = (unsigned short)(ww[e >> 1] >> ((e & 1) * 16));
        }
      }
      fence_async_smem();
      asm volatile("barrier.cluster.wait.aligned;" ::: "memory");
      TSTAMP(16);
      float f[40];
      float s = 0.f, gs = 0.f;
#pragma unroll
      for (int c = 0; c < 5; c++) {
        const uint32_t vv[4] = {v[c].x, v[c].y, v[c].z, v[c].w}, ww[4] = {w[c].x, w[c].y, w[c].z, w[c].w};
#pragma unroll
        for (int e = 0; e < 4; e++) {
          f[8 * c + 2 * e] = bf_lo(vv[e]); f[8 * c + 2 * e + 1] = bf_hi(vv[e]);
          s += f[8 * c + 2 * e] + f[8 * c + 2 * e + 1];
          gs = fmaf(f[8 * c + 2 * e], bf_lo(ww[e]), gs); gs = fmaf(f[8 * c + 2 * e + 1], bf_hi(ww[e]), gs);
        }
      }
#pragma unroll
      for (int o = 1; o < 16; o <<= 1) { s += __shfl_xor_sync(0xffffffffu, s, o); gs += __shfl_xor_sync(0xffffffffu, gs, o); }
      const float mean = s * (1.f / D_);
      float q = 0.f;
#pragma unroll
      for (int e = 0; e < 40; e++) { const float d = f[e] - mean; q = fmaf(d, d, q); }
#pragma unroll
      for (int o = 1; o < 16; o <<= 1) q += __shfl_xor_sync(0xffffffffu, q, o);
      const float rstd = rsqrtf(q * (1.f / D_) + 1e-5f);
      if (l16 == 0) g_xstat[row] = make_float4(rstd, -mean * rstd, rcp(1.f + __expf(-gs)), 0.f);
      TSTAMP(17);
      if (tid < 200) {
        float* cd = g_acc[epoch & 1] + 8 * KV_J + 80 * j + 8 * cch;
        red_add4(cd, bf_lo(cv[0].x) + bf_lo(cv[1].x), bf_hi(cv[0].x) + bf_hi(cv[1].x), bf_lo(cv[0].y) + bf_lo(cv[1].y), bf_hi(cv[0].y) + bf_hi(cv[1].y));
        red_add4(cd + 4, bf_lo(cv[0].z) + bf_lo(cv[1].z), bf_hi(cv[0].z) + bf_hi(cv[1].z), bf_lo(cv[0].w) + bf_lo(cv[1].w), bf_hi(cv[0].w) + bf_hi(cv[1].w));
      }
      signal(B_SIGP);
    }
    TSTAMP(1);

    Ring ra{0, 0}, rb{0, 0};
    uint32_t qp[2][10], P[2][10];
    float st_g[2];
    {
      float accM[128], accR[32];
      zero_regs(accM); zero_regs(accR);
      uint32_t pa = 0, pb = 0;
#pragma unroll 1
      for (int k = 0; k < 10; k++) {
        mbar_wait(fullA + 8 * ra.idx, ra.phase);
        if (tid == 0) TRACE(32 + k);
        mbar_wait(fullB + 8 * rb.idx, rb.phase);
        if (tid == 0) TRACE(64 + k);
        if (k == 0) TSTAMP(2);
        const uint32_t a0 = sb16 + ((OFF_A + ra.idx * SLOT_A + wg * 8192) >> 4), b0 = sb16 + ((OFF_B + rb.idx * SLOT_B) >> 4);
        wg_fence();
#pragma unroll
        for (int kk = 0; kk < 4; kk++) {
          const uint64_t da = make_desc(a0, kk * 32, 16, 1024, 1);
          mma_ss256(accM, da, make_desc(b0, kk * 2048, 8192, 1024, 1));
          mma_ss64(accR, da, make_desc(b0, 32768 + kk * 512, 2048, 256, 3));
          if (kk == 0) {
            wg_commit();
            if (k > 0) {
              wg_wait<1>();
              if (k - 1 < 8) release(emptyA + 8 * pa);
              releaseB(emptyB + 8 * pb);
            }
          }
        }
        wg_commit();
        pa = ra.idx; pb = rb.idx;
        ra.next<NA>(); rb.next<NB>();
      }
      TSTAMP(18);
      float st_rstd[2], st_mr[2];
      mbar_wait(bars + 8 * B_CS, 0);
#pragma unroll
      for (int r = 0; r < 2; r++) {
        const uint4 st = lds128(sb + OFF_XST + (rloc + 8 * r) * 16);
        st_rstd[r] = __uint_as_float(st.x); st_mr[r] = __uint_as_float(st.y); st_g[r] = __uint_as_float(st.z);
      }
      TSTAMP(19);
      wg_wait<0>();
      fence_regs(accM); fence_regs(accR);
      TSTAMP(3);
#define ACC(P_, G, I_) ((G) < 8 ? accM[(P_) * 32 + ((G) & 7) * 4 + (I_)] : accR[(P_) * 8 + ((G) & 1) * 4 + (I_)])
      {
        const int mat = lane >> 3;
        const int tok = warp * 16 + (mat & 1) * 8 + (lane & 7);
        const uint32_t ones = (t == 0) ? 0x00003f80u : 0u;
        __syncwarp();
#pragma unroll
        for (int p = 0; p < 2; p++) {
          const uint32_t rowa = sb + OFF_A + p * SLOT_A + tok * 128;
#pragma unroll
          for (int gg = 0; gg < 3; gg++) {
            const int g0 = 5 * p + 2 * gg;
            uint32_t r0 = pack_bf16(ACC(3, g0, 0), ACC(3, g0, 1)), r1 = pack_bf16(ACC(3, g0, 2), ACC(3, g0, 3));
            uint32_t r2 = ones, r3 = ones;
            if (gg < 2) { r2 = pack_bf16(ACC(3, g0 + 1, 0), ACC(3, g0 + 1, 1)); r3 = pack_bf16(ACC(3, g0 + 1, 2), ACC(3, g0 + 1, 3)); }
            stsm4(rowa + (((2 * gg + (mat >> 1)) ^ (tok & 7)) << 4), r0, r1, r2, r3);
          }
        }
      }
      uint32_t kf[5][4], qf[5][4];
#pragma unroll
      for (int s = 0; s < 5; s++) {
        kf[s][0] = pack_bf16(ACC(2, 2 * s, 0), ACC(2, 2 * s, 1)); kf[s][1] = pack_bf16(ACC(2, 2 * s, 2), ACC(2, 2 * s, 3));
        kf[s][2] = pack_bf16(ACC(2, 2 * s + 1, 0), ACC(2, 2 * s + 1, 1)); kf[s][3] = pack_bf16(ACC(2, 2 * s + 1, 2), ACC(2, 2 * s + 1, 3));
        qf[s][0] = pack_bf16(ACC(1, 2 * s, 0), ACC(1, 2 * s, 1)); qf[s][1] = pack_bf16(ACC(1, 2 * s, 2), ACC(1, 2 * s, 3));
        qf[s][2] = pack_bf16(ACC(1, 2 * s + 1, 0), ACC(1, 2 * s + 1, 1)); qf[s][3] = pack_bf16(ACC(1, 2 * s + 1, 2), ACC(1, 2 * s + 1, 3));
      }
      bar_sync(1, 256);
      float pk[40], pq[40];
      wg_fence();
#pragma unroll
      for (int s = 0; s < 5; s++) {
        if (s == 0) mma_rs80_k_z(pk, kf[s], make_desc(sb16, OFF_MISC, 16, 256, 3));
        else mma_rs80_k(pk, kf[s], make_desc(sb16, OFF_MISC + s * 2560, 16, 256, 3));
      }
#pragma unroll
      for (int s = 0; s < 5; s++) {
        if (s == 0) mma_rs80_k_z(pq, qf[s], make_desc(sb16, OFF_MISC, 16, 256, 3));
        else mma_rs80_k(pq, qf[s], make_desc(sb16, OFF_MISC + s * 2560, 16, 256, 3));
      }
      wg_commit();

      {
        uint32_t hv[10][2];
#pragma unroll
        for (int g = 0; g < 10; g++) {
          const float2 cs = *reinterpret_cast<const float2*>(s_cs + 8 * g + 2 * t);
          const float v0 = gelu_s(fmaf(ACC(0, g, 0), st_rstd[0], st_mr[0] * cs.x), 0.5f), v1 = gelu_s(fmaf(ACC(0, g, 1), st_rstd[0], st_mr[0] * cs.y), 0.5f);
          const float v2 = gelu_s(fmaf(ACC(0, g, 2), st_rstd[1], st_mr[1] * cs.x), 0.5f), v3 = gelu_s(fmaf(ACC(0, g, 3), st_rstd[1], st_mr[1] * cs.y), 0.5f);
          hv[g][0] = pack_bf16(v0, v1); hv[g][1] = pack_bf16(v2, v3);
        }
#pragma unroll
        for (int s = 0; s < 5; s++) stsm4(sb + OFF_STG + stg_lane + s * 32, hv[2 * s][0], hv[2 * s][1], hv[2 * s + 1][0], hv[2 * s + 1][1]);
        fence_async_smem();
        signal(B_SIGH);
      }
#undef ACC
      TSTAMP(4);
      wg_wait<0>();
      fence_regs(pk); fence_regs(pq);
#pragma unroll
      for (int G = 0; G < 10; G++) {
        P[0][G] = pack_bf16(pk[4 * G], pk[4 * G + 1]); P[1][G] = pack_bf16(pk[4 * G + 2], pk[4 * G + 3]);
        qp[0][G] = pack_bf16(pq[4 * G], pq[4 * G + 1]); qp[1][G] = pack_bf16(pq[4 * G + 2], pq[4 * G + 3]);
      }
    }

    uint32_t fr[10][4];
    {
      feature_map(P, fr);
      const int mat = lane >> 3;
      const int tok = warp * 16 + (mat & 1) * 8 + (lane & 7);
      const uint32_t base = sb + OFF_B + tok * 32 + (((mat >> 1) ^ ((tok >> 2) & 1)) << 4);
#pragma unroll
      for (int G = 0; G < 10; G++) stsm4(base + G * 4096, fr[G][0], fr[G][1], fr[G][2], fr[G][3]);
      fence_async_smem();
      bar_sync(1, 256);
      float kv[40];
      const uint32_t a0 = sb16 + ((OFF_A + wg * SLOT_A) >> 4), b0 = sb16 + ((OFF_B + wg * 20480) >> 4);
      wg_fence();
#pragma unroll
      for (int ks = 0; ks < 8; ks++) {
        if (ks == 0) mma_ss80_tt_z(kv, make_desc(a0, 0, 16, 1024, 1), make_desc(b0, 0, 4096, 256, 3));
        else mma_ss80_tt(kv, make_desc(a0, ks * 2048, 16, 1024, 1), make_desc(b0, ks * 512, 4096, 256, 3));
      }
      wg_commit();
      wg_wait<0>();
      fence_regs(kv);
      release(emptyA); release(emptyA + 8); releaseB(emptyB);
      float* dst = g_acc[epoch & 1] + j * KV_J + wg * KV_PAIR;
      const int m0 = (warp & 3) * 16 + (lane >> 2);
#pragma unroll
      for (int r = 0; r < 2; r++) {
        const int m = m0 + 8 * r;
        const bool hi = m >= 20;
        float v[10];
#pragma unroll
        for (int G = 0; G < 10; G++) v[G] = hi ? kv[4 * G + 2 * r + 1] : kv[4 * G + 2 * r];
        float* p = dst + (m < 40 ? m * 48 + t * 12 : 1920 + t * 24 + 12);
        if (m <= 40) { red_add4(p, v[0], v[1], v[2], v[3]); red_add4(p + 4, v[4], v[5], v[6], v[7]); red_add2(p + 8, v[8], v[9]); }
      }
      if (m0 == 32) {
        float* p = dst + 1920 + t * 24;
        red_add4(p, kv[2], kv[6], kv[10], kv[14]); red_add4(p + 4, kv[18], kv[22], kv[26], kv[30]); red_add2(p + 8, kv[34], kv[38]);
      }
      signal(B_SIGKV);
    }
    TSTAMP(5);

    uint32_t xv[2][10];
    {
      float acc[40];
      zero_regs(acc);
      uint32_t pa = 0, pb = 0;
#pragma unroll 1
      for (int k = 0; k < 10; k++) {
        mbar_wait(fullA + 8 * ra.idx, ra.phase);
        if (tid == 0) TRACE(42 + k);
        if ((k & 3) == 0) mbar_wait(fullB + 8 * rb.idx, rb.phase);
        if (tid == 0) TRACE(74 + k);
        if (k == 0) TSTAMP(6);
        const uint32_t a0 = sb16 + ((OFF_A + ra.idx * SLOT_A + wg * 8192) >> 4);
        const uint32_t b0 = sb16 + ((OFF_B + rb.idx * SLOT_B + ((k >> 1) & 1) * 20480 + (k & 1) * 2048) >> 4);
        wg_fence();
#pragma unroll
        for (int kk = 0; kk < 4; kk++) {
          mma_ss80(acc, make_desc(a0, kk * 32, 16, 1024, 1), make_desc(b0, kk * 512, 4096, 256, 3));
          if (kk == 1) {
            wg_commit();
            if (k > 0) {
              wg_wait<1>();
              release(emptyA + 8 * pa);
              if ((k & 3) == 0) releaseB(emptyB + 8 * pb);
            }
          }
        }
        wg_commit();
        pa = ra.idx; pb = rb.idx;
        ra.next<NA>();
        if ((k & 3) == 3 || k == 9) rb.next<NB>();
      }
      {
        const uint32_t xa = sb + OFF_B + pb * SLOT_B + 20480 + rloc * 160 + t * 4;
#pragma unroll
        for (int g = 0; g < 10; g++) { xv[0][g] = lds32(xa + g * 16); xv[1][g] = lds32(xa + 1280 + g * 16); }
      }
      wg_wait<0>();
      fence_regs(acc);
      release(emptyA + 8 * pa); releaseB(emptyB + 8 * pb);
      TSTAMP(7);
#pragma unroll
      for (int r = 0; r < 2; r++) {
#pragma unroll
        for (int g = 0; g < 10; g++)
          xv[r][g] = pack_bf16(bf_lo(xv[r][g]) + acc[4 * g + 2 * r], bf_hi(xv[r][g]) + acc[4 * g + 2 * r + 1]);
      }
      bar_sync(1, 256);
#pragma unroll
      for (int s = 0; s < 5; s++) stsm4(sb + OFF_STG + stg_lane + s * 32, xv[0][2 * s], xv[1][2 * s], xv[0][2 * s + 1], xv[1][2 * s + 1]);
#pragma unroll
      for (int r = 0; r < 2; r++) {
        float s = 0.f;
#pragma unroll
        for (int g = 0; g < 10; g++) {
          acc[4 * g + 2 * r] = bf_lo(xv[r][g]); acc[4 * g + 2 * r + 1] = bf_hi(xv[r][g]);
          s += acc[4 * g + 2 * r] + acc[4 * g + 2 * r + 1];
        }
        s += __shfl_xor_sync(0xffffffffu, s, 1); s += __shfl_xor_sync(0xffffffffu, s, 2);
        const float mu = s * (1.f / 80.f);
        float q = 0.f;
#pragma unroll
        for (int g = 0; g < 10; g++) {
          const float d0 = acc[4 * g + 2 * r] - mu, d1 = acc[4 * g + 2 * r + 1] - mu;
          q = fmaf(d0, d0, q); q = fmaf(d1, d1, q);
        }
        q += __shfl_xor_sync(0xffffffffu, q, 1); q += __shfl_xor_sync(0xffffffffu, q, 2);
        if (t == 0) g_st1[(128 * i + rloc + 8 * r) * 8 + j] = make_float2(mu, q);
      }
      fence_async_smem();
      signal(B_SIGX1);
    }
    TSTAMP(8);

    uint32_t of[5][4];
    {
      feature_map(qp, fr);
      mbar_wait(bars + 8 * B_KV, 0);
      uint4 kvr[2][3];
#pragma unroll
      for (int u = 0; u < 2; u++) {
        const int it = tid + 256 * u, p = it / 192, rem = it - 192 * p, n = rem >> 2, tq = rem & 3;
        const uint32_t sp = sb + OFF_MISC + 4 * (p * KV_PAIR + (n < 40 ? n * 48 + tq * 12 : 1920 + tq * 24 + (n & 1) * 12));
        if (it < 384) { kvr[u][0] = lds128(sp); kvr[u][1] = lds128(sp + 16); kvr[u][2] = lds128(sp + 32); }
      }
      bar_sync(1, 256);
#pragma unroll
      for (int u = 0; u < 2; u++) {
        const int it = tid + 256 * u, p = it / 192, rem = it - 192 * p, n = rem >> 2, tq = rem & 3;
        const int sh = (n < 40 ? (n >= 20) : (n & 1)) * 16;
        const uint32_t v[10] = {kvr[u][0].x, kvr[u][0].y, kvr[u][0].z, kvr[u][0].w, kvr[u][1].x, kvr[u][1].y, kvr[u][1].z, kvr[u][1].w, kvr[u][2].x, kvr[u][2].y};
        uint8_t* dst = sgen + OFF_MISC + p * 7680 + n * 32 + tq * 4;
        const int sw = ((n >> 2) & 1) << 4;
        if (it < 384) {
#pragma unroll
          for (int G = 0; G < 10; G++)
            *reinterpret_cast<uint32_t*>(dst + (G >> 1) * 1536 + (((G & 1) << 4) ^ sw)) = pack_bf16(__uint_as_float(v[G]), 0.f) << sh;
        }
      }
      fence_async_smem();
      bar_sync(1, 256);
      float o0[24], o1[24];
      wg_fence();
#pragma unroll
      for (int g = 0; g < 5; g++) {
        if (g == 0) mma_rs48_k_z(o0, fr[g], make_desc(sb16, OFF_MISC, 16, 256, 3));
        else mma_rs48_k(o0, fr[g], make_desc(sb16, OFF_MISC + g * 1536, 16, 256, 3));
      }
#pragma unroll
      for (int g = 0; g < 5; g++) {
        if (g == 0) mma_rs48_k_z(o1, fr[5], make_desc(sb16, OFF_MISC + 7680, 16, 256, 3));
        else mma_rs48_k(o1, fr[5 + g], make_desc(sb16, OFF_MISC + 7680 + g * 1536, 16, 256, 3));
      }
      wg_commit();
      wg_wait<0>();
      fence_regs(o0); fence_regs(o1);
      signal(B_MFREE);
#pragma unroll
      for (int r = 0; r < 2; r++) {
        const float a0 = __fdividef(st_g[r], o0[20 + 2 * r] + 1e-6f), a1 = __fdividef(st_g[r], o0[21 + 2 * r] + 1e-6f);
        const float b0 = __fdividef(st_g[r], o1[20 + 2 * r] + 1e-6f), b1 = __fdividef(st_g[r], o1[21 + 2 * r] + 1e-6f);
        const float am = t < 2 ? a0 : a1, bm = t < 2 ? b0 : b1;
#pragma unroll
        for (int g = 0; g < 5; g++) {
          const float sa = g < 2 ? a0 : (g == 2 ? am : a1), sb2 = g < 2 ? b0 : (g == 2 ? bm : b1);
          of[g >> 1][(g & 1) * 2 + r] = pack_bf16(o0[4 * g + 2 * r] * sa, o0[4 * g + 2 * r + 1] * sa);
          of[(5 + g) >> 1][((5 + g) & 1) * 2 + r] = pack_bf16(o1[4 * g + 2 * r] * sb2, o1[4 * g + 2 * r + 1] * sb2);
        }
      }
    }
    TSTAMP(9);

    uint32_t hf[12][4];
    {
      float acc[96];
      zero_regs(acc);
      uint32_t pa = 0, pb = 0;
#pragma unroll 1
      for (int k = 0; k < 10; k++) {
        mbar_wait(fullA + 8 * ra.idx, ra.phase);
        if (tid == 0) TRACE(52 + k);
        if ((k & 1) == 0) mbar_wait(fullB + 8 * rb.idx, rb.phase);
        if (tid == 0) TRACE(84 + k);
        if (k == 0) TSTAMP(10);
        const uint32_t a0 = sb16 + ((OFF_A + ra.idx * SLOT_A + wg * 8192) >> 4);
        const uint32_t b0 = sb16 + ((OFF_B + rb.idx * SLOT_B + (k & 1) * 24576) >> 4);
        wg_fence();
#pragma unroll
        for (int kk = 0; kk < 4; kk++) {
          mma_ss192(acc, make_desc(a0, kk * 32, 16, 1024, 1), make_desc(b0, kk * 2048, 8192, 1024, 1));
          if (kk == 0) {
            wg_commit();
            if (k > 0) {
              wg_wait<1>();
              release(emptyA + 8 * pa);
              if ((k & 1) == 0) releaseB(emptyB + 8 * pb);
            }
          }
        }
        wg_commit();
        pa = ra.idx; pb = rb.idx;
        ra.next<NA>();
        if (k & 1) rb.next<NB>();
      }
      float rs[2], mm[2];
      mbar_wait(bars + 8 * B_ST1, 0);
#pragma unroll
      for (int r = 0; r < 2; r++) {
        const uint4 su = lds128(sb + OFF_MISC + (rloc + 8 * r) * 64 + t * 16);
        const float m0 = __uint_as_float(su.x), m1 = __uint_as_float(su.z);
        float mu = m0 + m1;
        mu += __shfl_xor_sync(0xffffffffu, mu, 1); mu += __shfl_xor_sync(0xffffffffu, mu, 2);
        mu *= 0.125f;
        const float d0 = m0 - mu, d1 = m1 - mu;
        float q = __uint_as_float(su.y) + __uint_as_float(su.w) + 80.f * (d0 * d0 + d1 * d1);
        q += __shfl_xor_sync(0xffffffffu, q, 1); q += __shfl_xor_sync(0xffffffffu, q, 2);
        rs[r] = rsqrtf(q * (1.f / D_) + 1e-5f);
        mm[r] = -mu * rs[r];
      }
      wg_wait<0>();
      fence_regs(acc);
      releaseB(emptyB + 8 * pb);
      if (lane == 0) mbar_arrive_cta(bars + 8 * B_PEER, rank ^ 1);
      if (wg == 1) bar_arrive(2, 256);
      TSTAMP(11);
      const float hs0 = 0.5f - 0.5f * st_g[0], hs1 = 0.5f - 0.5f * st_g[1];
#pragma unroll
      for (int g = 0; g < 24; g++) {
        const float2 cs = *reinterpret_cast<const float2*>(s_cs + 80 + 8 * g + 2 * t);
        const float v0 = gelu_s(fmaf(acc[4 * g], rs[0], mm[0] * cs.x), hs0), v1 = gelu_s(fmaf(acc[4 * g + 1], rs[0], mm[0] * cs.y), hs0);
        const float v2 = gelu_s(fmaf(acc[4 * g + 2], rs[1], mm[1] * cs.x), hs1), v3 = gelu_s(fmaf(acc[4 * g + 3], rs[1], mm[1] * cs.y), hs1);
        hf[g >> 1][(g & 1) * 2] = pack_bf16(v0, v1);
        hf[g >> 1][(g & 1) * 2 + 1] = pack_bf16(v2, v3);
      }
    }
    TSTAMP(12);

    {
      float aM[64], aR[16];
      const int wt = tid & 127;
      const uint32_t peer = map_peer(sb, rank ^ 1);
      auto add16 = [&](uint32_t src) {
#pragma unroll
        for (int q = 0; q < 5; q++) {
          const uint4 v = lds128(src + q * 2048);
          float* d = q < 4 ? &aM[8 * q] : &aR[0];
          d[0] += bf_lo(v.x); d[1] += bf_hi(v.x); d[2] += bf_lo(v.y); d[3] += bf_hi(v.y);
          d[4] += bf_lo(v.z); d[5] += bf_hi(v.z); d[6] += bf_lo(v.w); d[7] += bf_hi(v.w);
        }
      };
#pragma unroll 1
      for (int c = 0; c < 4; c++) {
        mbar_wait(fullB + 8 * rb.idx, rb.phase);
        const uint32_t s0 = rb.idx, b0 = sb16 + ((OFF_B + rb.idx * SLOT_B) >> 4);
        rb.next<NB>();
        const uint32_t b1 = sb16 + ((OFF_B + rb.idx * SLOT_B) >> 4);
        if (tid == 128) TR4(c * 16 + 0);
        bar_sync(2 + wg, 256);
        wg_fence();
#pragma unroll
        for (int s = 0; s < 8; s++) {
          const uint64_t dm = make_desc(b0, (s >> 2) * 20480 + (s & 3) * 2048, 8192, 1024, 1);
          const uint64_t dr = make_desc(b0, (s >> 2) * 20480 + 16384 + (s & 3) * 512, 2048, 256, 3);
          if (s == 0) { mma_rs128_n_z(aM, hf[s], dm); mma_rs32_n_z(aR, hf[s], dr); }
          else { mma_rs128_n(aM, hf[s], dm); mma_rs32_n(aR, hf[s], dr); }
        }
        wg_commit();
        mbar_wait(fullB + 8 * rb.idx, rb.phase);
        wg_fence();
#pragma unroll
        for (int s = 0; s < 4; s++) {
          mma_rs128_n(aM, hf[8 + s], make_desc(b1, s * 2048, 8192, 1024, 1));
          mma_rs32_n(aR, hf[8 + s], make_desc(b1, 16384 + s * 512, 2048, 256, 3));
        }
#pragma unroll
        for (int s = 0; s < 5; s++) {
          mma_rs128_n(aM, of[s], make_desc(b1, 20480 + s * 2048, 10240, 1024, 1));
          mma_rs32_n(aR, of[s], make_desc(b1, 40960 + s * 512, 2560, 256, 3));
        }
        wg_commit();
        if (c < 3 || wg == 0) bar_arrive(3 - wg, 256);
        if (tid == 128) TR4(c * 16 + 2);
        wg_wait<1>();
        releaseB(emptyB + 8 * s0);
        if (c == 0) mbar_wait(bars + 8 * B_PEER, 0);
        wg_wait<0>();
        fence_regs(aM); fence_regs(aR);
        releaseB(emptyB + 8 * rb.idx);
        rb.next<NB>();
        if (tid == 128) TR4(c * 16 + 5);
        const uint32_t dso = OFF_DS + (c & 1) * 20480 + wg * 10240 + wt * 16, dsb = OFF_BAR + 8 * (B_DSR + 2 * c + wg);
#pragma unroll
        for (int q = 0; q < 5; q++) {
          const float* d = q < 4 ? &aM[32 + 8 * q] : &aR[8];
          st_async16(peer + dso + q * 2048, pack_bf16(d[0], d[1]), pack_bf16(d[2], d[3]), pack_bf16(d[4], d[5]), pack_bf16(d[6], d[7]),
                     peer + dsb);
        }
        if (c > 0 && c < 3) mbar_wait(bars + 8 * (B_SDONE + 2 * (c - 1) + wg), 0);
        mbar_wait(sb + dsb, 0);
        if (tid == 128) TR4(c * 16 + 3);
        add16(sb + dso);
        if (c < 3) {
          const uint32_t dst = sb + OFF_SEND + wg * 10240 + wt * 16;
#pragma unroll
          for (int q = 0; q < 5; q++) {
            const float* d = q < 4 ? &aM[8 * q] : &aR[0];
            sts128(dst + q * 2048, make_uint4(pack_bf16(d[0], d[1]), pack_bf16(d[2], d[3]), pack_bf16(d[4], d[5]), pack_bf16(d[6], d[7])));
          }
          fence_async_smem();
          signal(B_SEND + 2 * c + wg);
          if (tid == 128) TR4(c * 16 + 6);
        }
      }
      TSTAMP(13);
#pragma unroll 1
      for (int c = 0; c < 3; c++) {
        mbar_wait(bars + 8 * (B_RDY + 2 * c + wg), 0);
        add16(sb + (c == 0 ? OFF_G0 : OFF_G1 - 20480) + c * 20480 + wg * 10240 + wt * 16);
        if (tid == 128) TR4(c * 16 + 12);
      }
      TSTAMP(14);
      const float w0 = 1.f - st_g[0], w1s = 1.f - st_g[1];
      uint32_t ov[10][2];
#pragma unroll
      for (int g = 0; g < 10; g++) {
        const float* d = g < 8 ? &aM[4 * g] : &aR[4 * (g - 8)];
        ov[g][0] = pack_bf16(fmaf(w0, bf_lo(xv[0][g]), d[0]), fmaf(w0, bf_hi(xv[0][g]), d[1]));
        ov[g][1] = pack_bf16(fmaf(w1s, bf_lo(xv[1][g]), d[2]), fmaf(w1s, bf_hi(xv[1][g]), d[3]));
      }
      bar_sync(4 + wg, 128);
#pragma unroll
      for (int s = 0; s < 5; s++) stsm4(sb + OFF_DS + stg_lane + s * 32, ov[2 * s][0], ov[2 * s][1], ov[2 * s + 1][0], ov[2 * s + 1][1]);
      fence_async_smem();
      bar_sync(4 + wg, 128);
      if (wt == 0) {
        tma2d_store(&maps.st_out, sb + OFF_DS + wg * 10240, 80 * j, 128 * i + 64 * wg);
        bulk_commit(); bulk_wait_read();
      }
    }
    TSTAMP(15);
    if (tid == 0) asm volatile("red.relaxed.gpu.global.add.u32 [%0], 1;" ::"l"(g_flags + FL_DONE * 32) : "memory");
    asm volatile("barrier.cluster.arrive;\nbarrier.cluster.wait;" ::: "memory");
  }
}

namespace {
typedef CUresult (*EncodeFn)(CUtensorMap*, CUtensorMapDataType, cuuint32_t, void*, const cuuint64_t*, const cuuint64_t*,
                             const cuuint32_t*, const cuuint32_t*, CUtensorMapInterleave, CUtensorMapSwizzle,
                             CUtensorMapL2promotion, CUtensorMapFloatOOBfill);

void encode(EncodeFn fn, CUtensorMap* m, const void* ptr, int rank, const cuuint64_t* dims, const cuuint64_t* strides,
            const cuuint32_t* box, CUtensorMapSwizzle swz) {
  cuuint32_t es[5] = {1, 1, 1, 1, 1};
  fn(m, CU_TENSOR_MAP_DATA_TYPE_BFLOAT16, rank, const_cast<void*>(ptr), dims, strides, box, es, CU_TENSOR_MAP_INTERLEAVE_NONE,
     swz, CU_TENSOR_MAP_L2_PROMOTION_L2_128B, CU_TENSOR_MAP_FLOAT_OOB_FILL_NONE);
}
}

extern "C" void kernel_launch(void* const* d_in, const int* in_sizes, int n_in, void* d_out, int out_size) {
  (void)in_sizes; (void)n_in; (void)out_size;
  const __nv_bfloat16* x = (const __nv_bfloat16*)d_in[0];
  const __nv_bfloat16* wqkv = (const __nv_bfloat16*)d_in[1];
  const __nv_bfloat16* wphi = (const __nv_bfloat16*)d_in[2];
  const __nv_bfloat16* wo = (const __nv_bfloat16*)d_in[3];
  const __nv_bfloat16* w1 = (const __nv_bfloat16*)d_in[5];
  const __nv_bfloat16* w2 = (const __nv_bfloat16*)d_in[6];
  const __nv_bfloat16* w3 = (const __nv_bfloat16*)d_in[7];
  const __nv_bfloat16* w4 = (const __nv_bfloat16*)d_in[8];
  const __nv_bfloat16* gate_w = (const __nv_bfloat16*)d_in[9];

  static EncodeFn enc = nullptr;
  static void *pHs = nullptr, *pX1 = nullptr;
  if (!enc) {
    cudaDriverEntryPointQueryResult qr;
    cudaGetDriverEntryPoint("cuTensorMapEncodeTiled", (void**)&enc, cudaEnableDefault, &qr);
    cudaGetSymbolAddress(&pHs, g_Hs);
    cudaGetSymbolAddress(&pX1, g_X1);
    cudaFuncSetAttribute(fused_kernel, cudaFuncAttributeMaxDynamicSharedMemorySize, SMEM_BYTES);
  }
  Maps m;
  {
    cuuint64_t dims[2] = {D_, S_}, str[1] = {D_ * 2};
    cuuint32_t boxh[2] = {64, 64};
    encode(enc, &m.x, x, 2, dims, str, boxh, CU_TENSOR_MAP_SWIZZLE_128B);
    encode(enc, &m.hs, (const char*)pHs + 2 * D_ * 2, 2, dims, str, boxh, CU_TENSOR_MAP_SWIZZLE_128B);
    encode(enc, &m.x1, pX1, 2, dims, str, boxh, CU_TENSOR_MAP_SWIZZLE_128B);
    cuuint32_t boxs[2] = {80, 64};
    cuuint64_t dimsp[2] = {D_, S_ + 4};
    encode(enc, &m.st_h, pHs, 2, dimsp, str, boxs, CU_TENSOR_MAP_SWIZZLE_NONE);
    encode(enc, &m.st_x1, pX1, 2, dims, str, boxs, CU_TENSOR_MAP_SWIZZLE_NONE);
    encode(enc, &m.st_out, d_out, 2, dims, str, boxs, CU_TENSOR_MAP_SWIZZLE_NONE);
    cuuint32_t boxr[2] = {80, 128};
    encode(enc, &m.xr, x, 2, dims, str, boxr, CU_TENSOR_MAP_SWIZZLE_NONE);
  }
  {
    cuuint64_t dims[3] = {80, D_, 8}, str[2] = {D_ * 2, 160};
    cuuint32_t boxm[3] = {64, 64, 1}, boxr[3] = {16, 64, 1}, boxom[3] = {64, 80, 1}, boxor[3] = {16, 80, 1};
    cuuint64_t dims4[3] = {80, F_, 8};
    encode(enc, &m.w1m, w1, 3, dims, str, boxm, CU_TENSOR_MAP_SWIZZLE_128B);
    encode(enc, &m.w1r, w1, 3, dims, str, boxr, CU_TENSOR_MAP_SWIZZLE_32B);
    encode(enc, &m.w4m, w4, 3, dims4, str, boxm, CU_TENSOR_MAP_SWIZZLE_128B);
    encode(enc, &m.w4r, w4, 3, dims4, str, boxr, CU_TENSOR_MAP_SWIZZLE_32B);
    encode(enc, &m.wom, wo, 3, dims, str, boxom, CU_TENSOR_MAP_SWIZZLE_128B);
    encode(enc, &m.wor, wo, 3, dims, str, boxor, CU_TENSOR_MAP_SWIZZLE_32B);
  }
  {
    cuuint64_t dims[4] = {80, D_, 3, 8}, str[3] = {3 * D_ * 2, D_ * 2, 160};
    cuuint32_t boxm[4] = {64, 64, 3, 1}, boxr[4] = {16, 64, 3, 1};
    encode(enc, &m.qm, wqkv, 4, dims, str, boxm, CU_TENSOR_MAP_SWIZZLE_128B);
    encode(enc, &m.qr, wqkv, 4, dims, str, boxr, CU_TENSOR_MAP_SWIZZLE_32B);
  }
  {
    cuuint64_t dims[3] = {16, D_, 40}, str[2] = {D_ * 2, 32};
    cuuint32_t box2[3] = {16, 128, 5};
    encode(enc, &m.w2, w2, 3, dims, str, box2, CU_TENSOR_MAP_SWIZZLE_32B);
  }
  {
    cuuint64_t dims[3] = {64, D_, 24}, str[2] = {F_ * 2, 128};
    cuuint32_t box[3] = {64, 64, 3};
    encode(enc, &m.w3, w3, 3, dims, str, box, CU_TENSOR_MAP_SWIZZLE_128B);
  }
  fused_kernel<<<NCTA, 384, SMEM_BYTES, cudaStreamPerThread>>>(m, x, wqkv, wphi, w1, w2, w3, w4, wo, gate_w);
}
```

```cpp
#include <cuda_runtime.h>
#include <cuda_bf16.h>
#include <cuda.h>
#include <stdint.h>

namespace {

constexpr int S_ = 2048, D_ = 640, F_ = 1536;
constexpr int NCTA = 128;
constexpr int KV_PAIR = 40 * 48 + 96;
constexpr int KV_J = 2 * KV_PAIR;

constexpr int SLOT_B = 49152, NB = 3;
constexpr int SLOT_A = 16384, NA = 4;
constexpr int OFF_B = 0;
constexpr int OFF_A = OFF_B + NB * SLOT_B;
constexpr int OFF_STG = OFF_A + 2 * SLOT_A;
constexpr int OFF_MISC = OFF_A + NA * SLOT_A;
constexpr int OFF_XST = OFF_MISC + 13312;
constexpr int OFF_CS = OFF_MISC + 16384;
constexpr int OFF_BAR = OFF_CS + 1088;
constexpr int SMEM_BYTES = OFF_BAR + 512;
constexpr int B_FULLA = 0, B_FULLB = 4, B_CS = 7, B_CS3 = 8, B_KV = 9, B_ST1 = 10, B_SDONE = 11  , B_RDY = 15  ,
              B_DSR = 21  , B_SEND = 29  , B_EMPTYB = 35  , B_SIGP = 38, B_SIGH = 39,
              B_SIGKV = 40, B_SIGX1 = 41, B_MFREE = 42, B_PEER = 43, B_EMPTYA = 44  , NBAR = 48;
constexpr int OFF_DS = OFF_A, OFF_SEND = OFF_A + 40960, OFF_G0 = OFF_A + 61440, OFF_G1 = OFF_B + 2 * SLOT_B;

constexpr int FL_DONE = 0, FL_H = 1, FL_X1 = FL_H + 16, FL_KV = FL_X1 + 16, FL_CS = FL_KV + 8, FL_CS3 = FL_CS + 8, FL_ST = FL_CS3 + 8, FL_PART = FL_ST + 16;
constexpr int FL_COUNT = FL_PART + 16 * 8;
constexpr int ACC_FLOATS = 8 * KV_J + D_ + F_;

struct Maps {
  CUtensorMap x, w1m, w1r, qm, qr, hs, w2, x1, w3, w4m, w4r, wom, wor, st_h, st_x1, st_out, xr;
};

}

__device__ __align__(1024) __nv_bfloat16 g_Hs[(S_ + 4) * D_];
__device__ __align__(1024) __nv_bfloat16 g_X1[S_ * D_];
__device__ __align__(128) float g_acc[2][ACC_FLOATS];
__device__ __align__(128) float4 g_xstat[S_];
__device__ __align__(128) float2 g_st1[S_ * 8];
__device__ __align__(128) uint4 g_part[16 * 8 * 3 * 1280];
__device__ __align__(128) unsigned g_flags[FL_COUNT * 32];
#define TSTAMP(n) do {} while (0)
#define TSTAMPX(n) do {} while (0)
#define TRACE(n) do {} while (0)
#define TR4(n) do {} while (0)

namespace {

__device__ __forceinline__ long long gtime() { long long t; asm volatile("mov.u64 %0, %%globaltimer;" : "=l"(t)); return t; }
__device__ __forceinline__ uint32_t smem_u32(const void* p) { return (uint32_t)__cvta_generic_to_shared(p); }
__device__ __forceinline__ void mbar_init(uint32_t bar, int cnt) {
  asm volatile("mbarrier.init.shared::cta.b64 [%0], %1;" ::"r"(bar), "r"(cnt) : "memory");
}
__device__ __forceinline__ void mbar_expect_tx(uint32_t bar, int bytes) {
  asm volatile("mbarrier.arrive.expect_tx.shared::cta.b64 _, [%0], %1;" ::"r"(bar), "r"(bytes) : "memory");
}
__device__ __forceinline__ void mbar_arrive_cta(uint32_t bar, uint32_t cta) {
  asm volatile("{\n.reg .b32 ra;\nmapa.shared::cluster.u32 ra, %0, %1;\nmbarrier.arrive.shared::cluster.b64 _, [ra];\n}"
               ::"r"(bar), "r"(cta) : "memory");
}
__device__ __forceinline__ uint32_t mbar_try(uint32_t bar, uint32_t parity) {
  uint32_t ok;
  asm volatile("{\n.reg .pred p;\nmbarrier.try_wait.parity.shared::cta.b64 p, [%1], %2;\nselp.u32 %0, 1, 0, p;\n}"
               : "=r"(ok) : "r"(bar), "r"(parity) : "memory");
  return ok;
}
constexpr uint32_t WAIT_LIMIT = 1u << 22;
__device__ __forceinline__ void mbar_wait(uint32_t bar, uint32_t parity) {
  uint32_t n = 0;
  while (!mbar_try(bar, parity) && ++n < WAIT_LIMIT) {}
}
__device__ __forceinline__ unsigned ld_acquire(const unsigned* p) {
  unsigned v;
  asm volatile("ld.acquire.gpu.global.u32 %0, [%1];" : "=r"(v) : "l"(p) : "memory");
  return v;
}
__device__ __forceinline__ void flag_wait(int idx, unsigned target) {
  const unsigned* p = g_flags + idx * 32;
  uint32_t n = 0;
  while ((int)(ld_acquire(p) - target) < 0 && ++n < (WAIT_LIMIT >> 4)) {}
}
__device__ __forceinline__ void flag_add(int idx) {
  asm volatile("red.release.gpu.global.add.u32 [%0], 1;" ::"l"(g_flags + idx * 32) : "memory");
}
__device__ __forceinline__ void flag_add_relaxed(int idx) {
  asm volatile("red.relaxed.gpu.global.add.u32 [%0], 1;" ::"l"(g_flags + idx * 32) : "memory");
}
__device__ __forceinline__ uint32_t mbar_test(uint32_t bar, uint32_t parity) {
  uint32_t ok;
  asm volatile("{\n.reg .pred p;\nmbarrier.test_wait.parity.shared::cta.b64 p, [%1], %2;\nselp.u32 %0, 1, 0, p;\n}"
               : "=r"(ok) : "r"(bar), "r"(parity) : "memory");
  return ok;
}
__device__ __forceinline__ uint32_t lds32(uint32_t a) {
  uint32_t v;
  asm volatile("ld.shared.u32 %0, [%1];" : "=r"(v) : "r"(a) : "memory");
  return v;
}
__device__ __forceinline__ void mbar_arrive(uint32_t bar) {
  asm volatile("mbarrier.arrive.shared::cta.b64 _, [%0];" ::"r"(bar) : "memory");
}
__device__ __forceinline__ void fence_async_all() { asm volatile("fence.proxy.async;" ::: "memory"); }
__device__ __forceinline__ void fence_async_smem() { asm volatile("fence.proxy.async.shared::cta;" ::: "memory"); }
__device__ __forceinline__ void bar_sync(int id, int n) { asm volatile("bar.sync %0, %1;" ::"r"(id), "r"(n) : "memory"); }

__device__ __forceinline__ void tma2d(uint32_t dst, const CUtensorMap* m, uint32_t bar, int c0, int c1) {
  asm volatile("cp.async.bulk.tensor.2d.shared::cluster.global.mbarrier::complete_tx::bytes [%0], [%1, {%3, %4}], [%2];"
               ::"r"(dst), "l"(m), "r"(bar), "r"(c0), "r"(c1) : "memory");
}
__device__ __forceinline__ void tma2d_mc(uint32_t dst, const CUtensorMap* m, uint32_t bar, int c0, int c1) {
  asm volatile("cp.async.bulk.tensor.2d.shared::cluster.global.mbarrier::complete_tx::bytes.multicast::cluster"
               " [%0], [%1, {%3, %4}], [%2], %5;"
               ::"r"(dst), "l"(m), "r"(bar), "r"(c0), "r"(c1), "h"((uint16_t)3) : "memory");
}
__device__ __forceinline__ void tma3d(uint32_t dst, const CUtensorMap* m, uint32_t bar, int c0, int c1, int c2) {
  asm volatile("cp.async.bulk.tensor.3d.shared::cluster.global.mbarrier::complete_tx::bytes [%0], [%1, {%3, %4, %5}], [%2];"
               ::"r"(dst), "l"(m), "r"(bar), "r"(c0), "r"(c1), "r"(c2) : "memory");
}
__device__ __forceinline__ void tma4d(uint32_t dst, const CUtensorMap* m, uint32_t bar, int c0, int c1, int c2, int c3) {
  asm volatile("cp.async.bulk.tensor.4d.shared::cluster.global.mbarrier::complete_tx::bytes [%0], [%1, {%3, %4, %5, %6}], [%2];"
               ::"r"(dst), "l"(m), "r"(bar), "r"(c0), "r"(c1), "r"(c2), "r"(c3) : "memory");
}
__device__ __forceinline__ void tma2d_store(const CUtensorMap* m, uint32_t src, int c0, int c1) {
  asm volatile("cp.async.bulk.tensor.2d.global.shared::cta.bulk_group [%0, {%2, %3}], [%1];"
               ::"l"(m), "r"(src), "r"(c0), "r"(c1) : "memory");
}
__device__ __forceinline__ void bulk_store(void* dst, uint32_t src, uint32_t bytes) {
  asm volatile("cp.async.bulk.global.shared::cta.bulk_group [%0], [%1], %2;" ::"l"(dst), "r"(src), "r"(bytes) : "memory");
}
__device__ __forceinline__ void bulk_load(uint32_t dst, const void* src, uint32_t bytes, uint32_t bar) {
  asm volatile("cp.async.bulk.shared::cluster.global.mbarrier::complete_tx::bytes [%0], [%1], %2, [%3];"
               ::"r"(dst), "l"(src), "r"(bytes), "r"(bar) : "memory");
}
__device__ __forceinline__ void bulk_commit() { asm volatile("cp.async.bulk.commit_group;" ::: "memory"); }
template <int N> __device__ __forceinline__ void bulk_wait() { asm volatile("cp.async.bulk.wait_group %0;" ::"n"(N) : "memory"); }
__device__ __forceinline__ void bulk_wait_read() { asm volatile("cp.async.bulk.wait_group.read 0;" ::: "memory"); }
__device__ __forceinline__ void bar_arrive(int id, int n) { asm volatile("bar.arrive %0, %1;" ::"r"(id), "r"(n) : "memory"); }
__device__ __forceinline__ uint4 lds128(uint32_t a) {
  uint4 v;
  asm volatile("ld.shared.v4.u32 {%0, %1, %2, %3}, [%4];" : "=r"(v.x), "=r"(v.y), "=r"(v.z), "=r"(v.w) : "r"(a) : "memory");
  return v;
}
__device__ __forceinline__ void sts128(uint32_t a, uint4 v) {
  asm volatile("st.shared.v4.u32 [%0], {%1, %2, %3, %4};" ::"r"(a), "r"(v.x), "r"(v.y), "r"(v.z), "r"(v.w) : "memory");
}
__device__ __forceinline__ uint32_t map_peer(uint32_t addr, uint32_t cta) {
  uint32_t r;
  asm("mapa.shared::cluster.u32 %0, %1, %2;" : "=r"(r) : "r"(addr), "r"(cta));
  return r;
}
__device__ __forceinline__ void st_async16(uint32_t addr, uint32_t a, uint32_t b, uint32_t c, uint32_t d, uint32_t bar) {
  asm volatile("st.async.weak.shared::cluster.mbarrier::complete_tx::bytes.v4.b32 [%0], {%1, %2, %3, %4}, [%5];"
               ::"r"(addr), "r"(a), "r"(b), "r"(c), "r"(d), "r"(bar) : "memory");
}
__device__ __forceinline__ void l2_prefetch(const void* p, uint32_t bytes) {
  asm volatile("cp.async.bulk.prefetch.L2.global [%0], %1;" ::"l"(p), "r"(bytes) : "memory");
}
__device__ __forceinline__ void prefetch_tmap(const CUtensorMap* m) {
  asm volatile("prefetch.tensormap [%0];" ::"l"(m) : "memory");
}
__device__ __forceinline__ uint64_t make_desc(uint32_t a16, uint32_t off, uint32_t lbo, uint32_t sbo, uint32_t swz) {
  const uint32_t lo = a16 + ((off >> 4) + ((lbo >> 4) << 16)), hi = (sbo >> 4) | (swz << 30);
  uint64_t d;
  asm("mov.b64 %0, {%1, %2};" : "=l"(d) : "r"(lo), "r"(hi));
  return d;
}
__device__ __forceinline__ void wg_fence() { asm volatile("wgmma.fence.sync.aligned;" ::: "memory"); }
__device__ __forceinline__ void wg_commit() { asm volatile("wgmma.commit_group.sync.aligned;" ::: "memory"); }
template <int N> __device__ __forceinline__ void wg_wait() { asm volatile("wgmma.wait_group.sync.aligned %0;" ::"n"(N) : "memory"); }
template <int N> __device__ __forceinline__ void fence_regs(float (&d)[N]) {
#pragma unroll
  for (int i = 0; i < N; i++) asm volatile("" : "+f"(d[i])::"memory");
}
template <int N> __device__ __forceinline__ void zero_regs(float (&d)[N]) {
#pragma unroll
  for (int i = 0; i < N; i++) d[i] = 0.f;
}
__device__ __forceinline__ uint32_t pack_bf16(float lo, float hi) {
  uint32_t r;
  asm("cvt.rn.bf16x2.f32 %0, %1, %2;" : "=r"(r) : "f"(hi), "f"(lo));
  return r;
}
__device__ __forceinline__ float bf_lo(uint32_t v) { return __uint_as_float(v << 16); }
__device__ __forceinline__ float bf_hi(uint32_t v) { return __uint_as_float(v & 0xffff0000u); }
__device__ __forceinline__ uint32_t max_bf2(uint32_t a, uint32_t b) {
  uint32_t r; asm("max.bf16x2 %0, %1, %2;" : "=r"(r) : "r"(a), "r"(b)); return r;
}
__device__ __forceinline__ uint32_t min_bf2(uint32_t a, uint32_t b) {
  uint32_t r; asm("min.bf16x2 %0, %1, %2;" : "=r"(r) : "r"(a), "r"(b)); return r;
}
__device__ __forceinline__ float ex2(float x) { float r; asm("ex2.approx.ftz.f32 %0, %1;" : "=f"(r) : "f"(x)); return r; }
__device__ __forceinline__ float rcp(float x) { float r; asm("rcp.approx.ftz.f32 %0, %1;" : "=f"(r) : "f"(x)); return r; }
__device__ __forceinline__ float tanh_ap(float x) { float r; asm("tanh.approx.f32 %0, %1;" : "=f"(r) : "f"(x)); return r; }
__device__ __forceinline__ float gelu_s(float x, float hs) {
  float u = x * fmaf(x * x, 0.0356774081f, 0.7978845608f);
  float hx = x * hs;
  return fmaf(hx, tanh_ap(u), hx);
}
__device__ __forceinline__ void stsm4(uint32_t addr, uint32_t r0, uint32_t r1, uint32_t r2, uint32_t r3) {
  asm volatile("stmatrix.sync.aligned.m8n8.x4.shared.b16 [%0], {%1, %2, %3, %4};"
               ::"r"(addr), "r"(r0), "r"(r1), "r"(r2), "r"(r3) : "memory");
}
__device__ __forceinline__ void red_add4(float* p, float a, float b, float c, float d) {
  asm volatile("red.global.add.v4.f32 [%0], {%1, %2, %3, %4};" ::"l"(p), "f"(a), "f"(b), "f"(c), "f"(d) : "memory");
}
__device__ __forceinline__ void red_add2(float* p, float a, float b) {
  asm volatile("red.global.add.v2.f32 [%0], {%1, %2};" ::"l"(p), "f"(a), "f"(b) : "memory");
}

__device__ __forceinline__ void mma_ss256(float (&d)[128], uint64_t descA, uint64_t descB) {
  asm volatile("wgmma.mma_async.sync.aligned.m64n256k16.f32.bf16.bf16 {"
      "%0, %1, %2, %3, %4, %5, %6, %7, %8, %9, %10, %11, %12, %13, %14, %15, "
      "%16, %17, %18, %19, %20, %21, %22, %23, %24, %25, %26, %27, %28, %29, %30, %31, "
      "%32, %33, %34, %35, %36, %37, %38, %39, %40, %41, %42, %43, %44, %45, %46, %47, "
      "%48, %49, %50, %51, %52, %53, %54, %55, %56, %57, %58, %59, %60, %61, %62, %63, "
      "%64, %65, %66, %67, %68, %69, %70, %71, %72, %73, %74, %75, %76, %77, %78, %79, "
      "%80, %81, %82, %83, %84, %85, %86, %87, %88, %89, %90, %91, %92, %93, %94, %95, "
      "%96, %97, %98, %99, %100, %101, %102, %103, %104, %105, %106, %107, %108, %109, %110, %111, "
      "%112, %113, %114, %115, %116, %117, %118, %119, %120, %121, %122, %123, %124, %125, %126, %127"
      "}, %128, %129, 1, 1, 1, 0, 1;\n"
      : "+f"(d[0]), "+f"(d[1]), "+f"(d[2]), "+f"(d[3]), "+f"(d[4]), "+f"(d[5]), "+f"(d[6]), "+f"(d[7]),
        "+f"(d[8]), "+f"(d[9]), "+f"(d[10]), "+f"(d[11]), "+f"(d[12]), "+f"(d[13]), "+f"(d[14]), "+f"(d[15]),
        "+f"(d[16]), "+f"(d[17]), "+f"(d[18]), "+f"(d[19]), "+f"(d[20]), "+f"(d[21]), "+f"(d[22]), "+f"(d[23]),
        "+f"(d[24]), "+f"(d[25]), "+f"(d[26]), "+f"(d[27]), "+f"(d[28]), "+f"(d[29]), "+f"(d[30]), "+f"(d[31]),
        "+f"(d[32]), "+f"(d[33]), "+f"(d[34]), "+f"(d[35]), "+f"(d[36]), "+f"(d[37]), "+f"(d[38]), "+f"(d[39]),
        "+f"(d[40]), "+f"(d[41]), "+f"(d[42]), "+f"(d[43]), "+f"(d[44]), "+f"(d[45]), "+f"(d[46]), "+f"(d[47]),
        "+f"(d[48]), "+f"(d[49]), "+f"(d[50]), "+f"(d[51]), "+f"(d[52]), "+f"(d[53]), "+f"(d[54]), "+f"(d[55]),
        "+f"(d[56]), "+f"(d[57]), "+f"(d[58]), "+f"(d[59]), "+f"(d[60]), "+f"(d[61]), "+f"(d[62]), "+f"(d[63]),
        "+f"(d[64]), "+f"(d[65]), "+f"(d[66]), "+f"(d[67]), "+f"(d[68]), "+f"(d[69]), "+f"(d[70]), "+f"(d[71]),
        "+f"(d[72]), "+f"(d[73]), "+f"(d[74]), "+f"(d[75]), "+f"(d[76]), "+f"(d[77]), "+f"(d[78]), "+f"(d[79]),
        "+f"(d[80]), "+f"(d[81]), "+f"(d[82]), "+f"(d[83]), "+f"(d[84]), "+f"(d[85]), "+f"(d[86]), "+f"(d[87]),
        "+f"(d[88]), "+f"(d[89]), "+f"(d[90]), "+f"(d[91]), "+f"(d[92]), "+f"(d[93]), "+f"(d[94]), "+f"(d[95]),
        "+f"(d[96]), "+f"(d[97]), "+f"(d[98]), "+f"(d[99]), "+f"(d[100]), "+f"(d[101]), "+f"(d[102]), "+f"(d[103]),
        "+f"(d[104]), "+f"(d[105]), "+f"(d[106]), "+f"(d[107]), "+f"(d[108]), "+f"(d[109]), "+f"(d[110]), "+f"(d[111]),
        "+f"(d[112]), "+f"(d[113]), "+f"(d[114]), "+f"(d[115]), "+f"(d[116]), "+f"(d[117]), "+f"(d[118]), "+f"(d[119]),
        "+f"(d[120]), "+f"(d[121]), "+f"(d[122]), "+f"(d[123]), "+f"(d[124]), "+f"(d[125]), "+f"(d[126]), "+f"(d[127])
      : "l"(descA), "l"(descB));
}

__device__ __forceinline__ void mma_ss64(float (&d)[32], uint64_t descA, uint64_t descB) {
  asm volatile("wgmma.mma_async.sync.aligned.m64n64k16.f32.bf16.bf16 {"
      "%0, %1, %2, %3, %4, %5, %6, %7, %8, %9, %10, %11, %12, %13, %14, %15, "
      "%16, %17, %18, %19, %20, %21, %22, %23, %24, %25, %26, %27, %28, %29, %30, %31"
      "}, %32, %33, 1, 1, 1, 0, 1;\n"
      : "+f"(d[0]), "+f"(d[1]), "+f"(d[2]), "+f"(d[3]), "+f"(d[4]), "+f"(d[5]), "+f"(d[6]), "+f"(d[7]),
        "+f"(d[8]), "+f"(d[9]), "+f"(d[10]), "+f"(d[11]), "+f"(d[12]), "+f"(d[13]), "+f"(d[14]), "+f"(d[15]),
        "+f"(d[16]), "+f"(d[17]), "+f"(d[18]), "+f"(d[19]), "+f"(d[20]), "+f"(d[21]), "+f"(d[22]), "+f"(d[23]),
        "+f"(d[24]), "+f"(d[25]), "+f"(d[26]), "+f"(d[27]), "+f"(d[28]), "+f"(d[29]), "+f"(d[30]), "+f"(d[31])
      : "l"(descA), "l"(descB));
}

__device__ __forceinline__ void mma_ss80(float (&d)[40], uint64_t descA, uint64_t descB) {
  asm volatile("wgmma.mma_async.sync.aligned.m64n80k16.f32.bf16.bf16 {"
      "%0, %1, %2, %3, %4, %5, %6, %7, %8, %9, %10, %11, %12, %13, %14, %15, "
      "%16, %17, %18, %19, %20, %21, %22, %23, %24, %25, %26, %27, %28, %29, %30, %31, "
      "%32, %33, %34, %35, %36, %37, %38, %39"
      "}, %40, %41, 1, 1, 1, 0, 1;\n"
      : "+f"(d[0]), "+f"(d[1]), "+f"(d[2]), "+f"(d[3]), "+f"(d[4]), "+f"(d[5]), "+f"(d[6]), "+f"(d[7]),
        "+f"(d[8]), "+f"(d[9]), "+f"(d[10]), "+f"(d[11]), "+f"(d[12]), "+f"(d[13]), "+f"(d[14]), "+f"(d[15]),
        "+f"(d[16]), "+f"(d[17]), "+f"(d[18]), "+f"(d[19]), "+f"(d[20]), "+f"(d[21]), "+f"(d[22]), "+f"(d[23]),
        "+f"(d[24]), "+f"(d[25]), "+f"(d[26]), "+f"(d[27]), "+f"(d[28]), "+f"(d[29]), "+f"(d[30]), "+f"(d[31]),
        "+f"(d[32]), "+f"(d[33]), "+f"(d[34]), "+f"(d[35]), "+f"(d[36]), "+f"(d[37]), "+f"(d[38]), "+f"(d[39])
      : "l"(descA), "l"(descB));
}

__device__ __forceinline__ void mma_ss192(float (&d)[96], uint64_t descA, uint64_t descB) {
  asm volatile("wgmma.mma_async.sync.aligned.m64n192k16.f32.bf16.bf16 {"
      "%0, %1, %2, %3, %4, %5, %6, %7, %8, %9, %10, %11, %12, %13, %14, %15, "
      "%16, %17, %18, %19, %20, %21, %22, %23, %24, %25, %26, %27, %28, %29, %30, %31, "
      "%32, %33, %34, %35, %36, %37, %38, %39, %40, %41, %42, %43, %44, %45, %46, %47, "
      "%48, %49, %50, %51, %52, %53, %54, %55, %56, %57, %58, %59, %60, %61, %62, %63, "
      "%64, %65, %66, %67, %68, %69, %70, %71, %72, %73, %74, %75, %76, %77, %78, %79, "
      "%80, %81, %82, %83, %84, %85, %86, %87, %88, %89, %90, %91, %92, %93, %94, %95"
      "}, %96, %97, 1, 1, 1, 0, 1;\n"
      : "+f"(d[0]), "+f"(d[1]), "+f"(d[2]), "+f"(d[3]), "+f"(d[4]), "+f"(d[5]), "+f"(d[6]), "+f"(d[7]),
        "+f"(d[8]), "+f"(d[9]), "+f"(d[10]), "+f"(d[11]), "+f"(d[12]), "+f"(d[13]), "+f"(d[14]), "+f"(d[15]),
        "+f"(d[16]), "+f"(d[17]), "+f"(d[18]), "+f"(d[19]), "+f"(d[20]), "+f"(d[21]), "+f"(d[22]), "+f"(d[23]),
        "+f"(d[24]), "+f"(d[25]), "+f"(d[26]), "+f"(d[27]), "+f"(d[28]), "+f"(d[29]), "+f"(d[30]), "+f"(d[31]),
        "+f"(d[32]), "+f"(d[33]), "+f"(d[34]), "+f"(d[35]), "+f"(d[36]), "+f"(d[37]), "+f"(d[38]), "+f"(d[39]),
        "+f"(d[40]), "+f"(d[41]), "+f"(d[42]), "+f"(d[43]), "+f"(d[44]), "+f"(d[45]), "+f"(d[46]), "+f"(d[47]),
        "+f"(d[48]), "+f"(d[49]), "+f"(d[50]), "+f"(d[51]), "+f"(d[52]), "+f"(d[53]), "+f"(d[54]), "+f"(d[55]),
        "+f"(d[56]), "+f"(d[57]), "+f"(d[58]), "+f"(d[59]), "+f"(d[60]), "+f"(d[61]), "+f"(d[62]), "+f"(d[63]),
        "+f"(d[64]), "+f"(d[65]), "+f"(d[66]), "+f"(d[67]), "+f"(d[68]), "+f"(d[69]), "+f"(d[70]), "+f"(d[71]),
        "+f"(d[72]), "+f"(d[73]), "+f"(d[74]), "+f"(d[75]), "+f"(d[76]), "+f"(d[77]), "+f"(d[78]), "+f"(d[79]),
        "+f"(d[80]), "+f"(d[81]), "+f"(d[82]), "+f"(d[83]), "+f"(d[84]), "+f"(d[85]), "+f"(d[86]), "+f"(d[87]),
        "+f"(d[88]), "+f"(d[89]), "+f"(d[90]), "+f"(d[91]), "+f"(d[92]), "+f"(d[93]), "+f"(d[94]), "+f"(d[95])
      : "l"(descA), "l"(descB));
}

__device__ __forceinline__ void mma_ss80_tt(float (&d)[40], uint64_t descA, uint64_t descB) {
  asm volatile("wgmma.mma_async.sync.aligned.m64n80k16.f32.bf16.bf16 {"
      "%0, %1, %2, %3, %4, %5, %6, %7, %8, %9, %10, %11, %12, %13, %14, %15, "
      "%16, %17, %18, %19, %20, %21, %22, %23, %24, %25, %26, %27, %28, %29, %30, %31, "
      "%32, %33, %34, %35, %36, %37, %38, %39"
      "}, %40, %41, 1, 1, 1, 1, 1;\n"
      : "+f"(d[0]), "+f"(d[1]), "+f"(d[2]), "+f"(d[3]), "+f"(d[4]), "+f"(d[5]), "+f"(d[6]), "+f"(d[7]),
        "+f"(d[8]), "+f"(d[9]), "+f"(d[10]), "+f"(d[11]), "+f"(d[12]), "+f"(d[13]), "+f"(d[14]), "+f"(d[15]),
        "+f"(d[16]), "+f"(d[17]), "+f"(d[18]), "+f"(d[19]), "+f"(d[20]), "+f"(d[21]), "+f"(d[22]), "+f"(d[23]),
        "+f"(d[24]), "+f"(d[25]), "+f"(d[26]), "+f"(d[27]), "+f"(d[28]), "+f"(d[29]), "+f"(d[30]), "+f"(d[31]),
        "+f"(d[32]), "+f"(d[33]), "+f"(d[34]), "+f"(d[35]), "+f"(d[36]), "+f"(d[37]), "+f"(d[38]), "+f"(d[39])
      : "l"(descA), "l"(descB));
}
__device__ __forceinline__ void mma_ss80_tt_z(float (&d)[40], uint64_t descA, uint64_t descB) {
  asm volatile("wgmma.mma_async.sync.aligned.m64n80k16.f32.bf16.bf16 {"
      "%0, %1, %2, %3, %4, %5, %6, %7, %8, %9, %10, %11, %12, %13, %14, %15, "
      "%16, %17, %18, %19, %20, %21, %22, %23, %24, %25, %26, %27, %28, %29, %30, %31, "
      "%32, %33, %34, %35, %36, %37, %38, %39"
      "}, %40, %41, 0, 1, 1, 1, 1;\n"
      : "=f"(d[0]), "=f"(d[1]), "=f"(d[2]), "=f"(d[3]), "=f"(d[4]), "=f"(d[5]), "=f"(d[6]), "=f"(d[7]),
        "=f"(d[8]), "=f"(d[9]), "=f"(d[10]), "=f"(d[11]), "=f"(d[12]), "=f"(d[13]), "=f"(d[14]), "=f"(d[15]),
        "=f"(d[16]), "=f"(d[17]), "=f"(d[18]), "=f"(d[19]), "=f"(d[20]), "=f"(d[21]), "=f"(d[22]), "=f"(d[23]),
        "=f"(d[24]), "=f"(d[25]), "=f"(d[26]), "=f"(d[27]), "=f"(d[28]), "=f"(d[29]), "=f"(d[30]), "=f"(d[31]),
        "=f"(d[32]), "=f"(d[33]), "=f"(d[34]), "=f"(d[35]), "=f"(d[36]), "=f"(d[37]), "=f"(d[38]), "=f"(d[39])
      : "l"(descA), "l"(descB));
}

__device__ __forceinline__ void mma_rs80_k(float (&d)[40], const uint32_t (&a)[4], uint64_t descB) {
  asm volatile("wgmma.mma_async.sync.aligned.m64n80k16.f32.bf16.bf16 {"
      "%0, %1, %2, %3, %4, %5, %6, %7, %8, %9, %10, %11, %12, %13, %14, %15, "
      "%16, %17, %18, %19, %20, %21, %22, %23, %24, %25, %26, %27, %28, %29, %30, %31, "
      "%32, %33, %34, %35, %36, %37, %38, %39"
      "}, {%40, %41, %42, %43}, %44, 1, 1, 1, 0;\n"
      : "+f"(d[0]), "+f"(d[1]), "+f"(d[2]), "+f"(d[3]), "+f"(d[4]), "+f"(d[5]), "+f"(d[6]), "+f"(d[7]),
        "+f"(d[8]), "+f"(d[9]), "+f"(d[10]), "+f"(d[11]), "+f"(d[12]), "+f"(d[13]), "+f"(d[14]), "+f"(d[15]),
        "+f"(d[16]), "+f"(d[17]), "+f"(d[18]), "+f"(d[19]), "+f"(d[20]), "+f"(d[21]), "+f"(d[22]), "+f"(d[23]),
        "+f"(d[24]), "+f"(d[25]), "+f"(d[26]), "+f"(d[27]), "+f"(d[28]), "+f"(d[29]), "+f"(d[30]), "+f"(d[31]),
        "+f"(d[32]), "+f"(d[33]), "+f"(d[34]), "+f"(d[35]), "+f"(d[36]), "+f"(d[37]), "+f"(d[38]), "+f"(d[39])
      : "r"(a[0]), "r"(a[1]), "r"(a[2]), "r"(a[3]), "l"(descB));
}
__device__ __forceinline__ void mma_rs80_k_z(float (&d)[40], const uint32_t (&a)[4], uint64_t descB) {
  asm volatile("wgmma.mma_async.sync.aligned.m64n80k16.f32.bf16.bf16 {"
      "%0, %1, %2, %3, %4, %5, %6, %7, %8, %9, %10, %11, %12, %13, %14, %15, "
      "%16, %17, %18, %19, %20, %21, %22, %23, %24, %25, %26, %27, %28, %29, %30, %31, "
      "%32, %33, %34, %35, %36, %37, %38, %39"
      "}, {%40, %41, %42, %43}, %44, 0, 1, 1, 0;\n"
      : "=f"(d[0]), "=f"(d[1]), "=f"(d[2]), "=f"(d[3]), "=f"(d[4]), "=f"(d[5]), "=f"(d[6]), "=f"(d[7]),
        "=f"(d[8]), "=f"(d[9]), "=f"(d[10]), "=f"(d[11]), "=f"(d[12]), "=f"(d[13]), "=f"(d[14]), "=f"(d[15]),
        "=f"(d[16]), "=f"(d[17]), "=f"(d[18]), "=f"(d[19]), "=f"(d[20]), "=f"(d[21]), "=f"(d[22]), "=f"(d[23]),
        "=f"(d[24]), "=f"(d[25]), "=f"(d[26]), "=f"(d[27]), "=f"(d[28]), "=f"(d[29]), "=f"(d[30]), "=f"(d[31]),
        "=f"(d[32]), "=f"(d[33]), "=f"(d[34]), "=f"(d[35]), "=f"(d[36]), "=f"(d[37]), "=f"(d[38]), "=f"(d[39])
      : "r"(a[0]), "r"(a[1]), "r"(a[2]), "r"(a[3]), "l"(descB));
}

__device__ __forceinline__ void mma_rs48_k(float (&d)[24], const uint32_t (&a)[4], uint64_t descB) {
  asm volatile("wgmma.mma_async.sync.aligned.m64n48k16.f32.bf16.bf16 {"
      "%0, %1, %2, %3, %4, %5, %6, %7, %8, %9, %10, %11, %12, %13, %14, %15, "
      "%16, %17, %18, %19, %20, %21, %22, %23"
      "}, {%24, %25, %26, %27}, %28, 1, 1, 1, 0;\n"
      : "+f"(d[0]), "+f"(d[1]), "+f"(d[2]), "+f"(d[3]), "+f"(d[4]), "+f"(d[5]), "+f"(d[6]), "+f"(d[7]),
        "+f"(d[8]), "+f"(d[9]), "+f"(d[10]), "+f"(d[11]), "+f"(d[12]), "+f"(d[13]), "+f"(d[14]), "+f"(d[15]),
        "+f"(d[16]), "+f"(d[17]), "+f"(d[18]), "+f"(d[19]), "+f"(d[20]), "+f"(d[21]), "+f"(d[22]), "+f"(d[23])
      : "r"(a[0]), "r"(a[1]), "r"(a[2]), "r"(a[3]), "l"(descB));
}
__device__ __forceinline__ void mma_rs48_k_z(float (&d)[24], const uint32_t (&a)[4], uint64_t descB) {
  asm volatile("wgmma.mma_async.sync.aligned.m64n48k16.f32.bf16.bf16 {"
      "%0, %1, %2, %3, %4, %5, %6, %7, %8, %9, %10, %11, %12, %13, %14, %15, "
      "%16, %17, %18, %19, %20, %21, %22, %23"
      "}, {%24, %25, %26, %27}, %28, 0, 1, 1, 0;\n"
      : "=f"(d[0]), "=f"(d[1]), "=f"(d[2]), "=f"(d[3]), "=f"(d[4]), "=f"(d[5]), "=f"(d[6]), "=f"(d[7]),
        "=f"(d[8]), "=f"(d[9]), "=f"(d[10]), "=f"(d[11]), "=f"(d[12]), "=f"(d[13]), "=f"(d[14]), "=f"(d[15]),
        "=f"(d[16]), "=f"(d[17]), "=f"(d[18]), "=f"(d[19]), "=f"(d[20]), "=f"(d[21]), "=f"(d[22]), "=f"(d[23])
      : "r"(a[0]), "r"(a[1]), "r"(a[2]), "r"(a[3]), "l"(descB));
}

__device__ __forceinline__ void mma_rs128_n(float (&d)[64], const uint32_t (&a)[4], uint64_t descB) {
  asm volatile("wgmma.mma_async.sync.aligned.m64n128k16.f32.bf16.bf16 {"
      "%0, %1, %2, %3, %4, %5, %6, %7, %8, %9, %10, %11, %12, %13, %14, %15, "
      "%16, %17, %18, %19, %20, %21, %22, %23, %24, %25, %26, %27, %28, %29, %30, %31, "
      "%32, %33, %34, %35, %36, %37, %38, %39, %40, %41, %42, %43, %44, %45, %46, %47, "
      "%48, %49, %50, %51, %52, %53, %54, %55, %56, %57, %58, %59, %60, %61, %62, %63"
      "}, {%64, %65, %66, %67}, %68, 1, 1, 1, 1;\n"
      : "+f"(d[0]), "+f"(d[1]), "+f"(d[2]), "+f"(d[3]), "+f"(d[4]), "+f"(d[5]), "+f"(d[6]), "+f"(d[7]),
        "+f"(d[8]), "+f"(d[9]), "+f"(d[10]), "+f"(d[11]), "+f"(d[12]), "+f"(d[13]), "+f"(d[14]), "+f"(d[15]),
        "+f"(d[16]), "+f"(d[17]), "+f"(d[18]), "+f"(d[19]), "+f"(d[20]), "+f"(d[21]), "+f"(d[22]), "+f"(d[23]),
        "+f"(d[24]), "+f"(d[25]), "+f"(d[26]), "+f"(d[27]), "+f"(d[28]), "+f"(d[29]), "+f"(d[30]), "+f"(d[31]),
        "+f"(d[32]), "+f"(d[33]), "+f"(d[34]), "+f"(d[35]), "+f"(d[36]), "+f"(d[37]), "+f"(d[38]), "+f"(d[39]),
        "+f"(d[40]), "+f"(d[41]), "+f"(d[42]), "+f"(d[43]), "+f"(d[44]), "+f"(d[45]), "+f"(d[46]), "+f"(d[47]),
        "+f"(d[48]), "+f"(d[49]), "+f"(d[50]), "+f"(d[51]), "+f"(d[52]), "+f"(d[53]), "+f"(d[54]), "+f"(d[55]),
        "+f"(d[56]), "+f"(d[57]), "+f"(d[58]), "+f"(d[59]), "+f"(d[60]), "+f"(d[61]), "+f"(d[62]), "+f"(d[63])
      : "r"(a[0]), "r"(a[1]), "r"(a[2]), "r"(a[3]), "l"(descB));
}
__device__ __forceinline__ void mma_rs128_n_z(float (&d)[64], const uint32_t (&a)[4], uint64_t descB) {
  asm volatile("wgmma.mma_async.sync.aligned.m64n128k16.f32.bf16.bf16 {"
      "%0, %1, %2, %3, %4, %5, %6, %7, %8, %9, %10, %11, %12, %13, %14, %15, "
      "%16, %17, %18, %19, %20, %21, %22, %23, %24, %25, %26, %27, %28, %29, %30, %31, "
      "%32, %33, %34, %35, %36, %37, %38, %39, %40, %41, %42, %43, %44, %45, %46, %47, "
      "%48, %49, %50, %51, %52, %53, %54, %55, %56, %57, %58, %59, %60, %61, %62, %63"
      "}, {%64, %65, %66, %67}, %68, 0, 1, 1, 1;\n"
      : "=f"(d[0]), "=f"(d[1]), "=f"(d[2]), "=f"(d[3]), "=f"(d[4]), "=f"(d[5]), "=f"(d[6]), "=f"(d[7]),
        "=f"(d[8]), "=f"(d[9]), "=f"(d[10]), "=f"(d[11]), "=f"(d[12]), "=f"(d[13]), "=f"(d[14]), "=f"(d[15]),
        "=f"(d[16]), "=f"(d[17]), "=f"(d[18]), "=f"(d[19]), "=f"(d[20]), "=f"(d[21]), "=f"(d[22]), "=f"(d[23]),
        "=f"(d[24]), "=f"(d[25]), "=f"(d[26]), "=f"(d[27]), "=f"(d[28]), "=f"(d[29]), "=f"(d[30]), "=f"(d[31]),
        "=f"(d[32]), "=f"(d[33]), "=f"(d[34]), "=f"(d[35]), "=f"(d[36]), "=f"(d[37]), "=f"(d[38]), "=f"(d[39]),
        "=f"(d[40]), "=f"(d[41]), "=f"(d[42]), "=f"(d[43]), "=f"(d[44]), "=f"(d[45]), "=f"(d[46]), "=f"(d[47]),
        "=f"(d[48]), "=f"(d[49]), "=f"(d[50]), "=f"(d[51]), "=f"(d[52]), "=f"(d[53]), "=f"(d[54]), "=f"(d[55]),
        "=f"(d[56]), "=f"(d[57]), "=f"(d[58]), "=f"(d[59]), "=f"(d[60]), "=f"(d[61]), "=f"(d[62]), "=f"(d[63])
      : "r"(a[0]), "r"(a[1]), "r"(a[2]), "r"(a[3]), "l"(descB));
}

__device__ __forceinline__ void mma_rs32_n(float (&d)[16], const uint32_t (&a)[4], uint64_t descB) {
  asm volatile("wgmma.mma_async.sync.aligned.m64n32k16.f32.bf16.bf16 {"
      "%0, %1, %2, %3, %4, %5, %6, %7, %8, %9, %10, %11, %12, %13, %14, %15"
      "}, {%16, %17, %18, %19}, %20, 1, 1, 1, 1;\n"
      : "+f"(d[0]), "+f"(d[1]), "+f"(d[2]), "+f"(d[3]), "+f"(d[4]), "+f"(d[5]), "+f"(d[6]), "+f"(d[7]),
        "+f"(d[8]), "+f"(d[9]), "+f"(d[10]), "+f"(d[11]), "+f"(d[12]), "+f"(d[13]), "+f"(d[14]), "+f"(d[15])
      : "r"(a[0]), "r"(a[1]), "r"(a[2]), "r"(a[3]), "l"(descB));
}
__device__ __forceinline__ void mma_rs32_n_z(float (&d)[16], const uint32_t (&a)[4], uint64_t descB) {
  asm volatile("wgmma.mma_async.sync.aligned.m64n32k16.f32.bf16.bf16 {"
      "%0, %1, %2, %3, %4, %5, %6, %7, %8, %9, %10, %11, %12, %13, %14, %15"
      "}, {%16, %17, %18, %19}, %20, 0, 1, 1, 1;\n"
      : "=f"(d[0]), "=f"(d[1]), "=f"(d[2]), "=f"(d[3]), "=f"(d[4]), "=f"(d[5]), "=f"(d[6]), "=f"(d[7]),
        "=f"(d[8]), "=f"(d[9]), "=f"(d[10]), "=f"(d[11]), "=f"(d[12]), "=f"(d[13]), "=f"(d[14]), "=f"(d[15])
      : "r"(a[0]), "r"(a[1]), "r"(a[2]), "r"(a[3]), "l"(descB));
}

__device__ __forceinline__ void feature_map(const uint32_t (&P)[2][10], uint32_t (&fr)[10][4]) {
  constexpr float L2E = 1.4426950408889634f;
#pragma unroll
  for (int p = 0; p < 2; p++) {
#pragma unroll
    for (int r = 0; r < 2; r++) {
      uint32_t mx = P[r][5 * p], mn = mx;
#pragma unroll
      for (int g = 1; g < 5; g++) { mx = max_bf2(mx, P[r][5 * p + g]); mn = min_bf2(mn, P[r][5 * p + g]); }
      mx = max_bf2(mx, __shfl_xor_sync(0xffffffffu, mx, 1));
      mn = min_bf2(mn, __shfl_xor_sync(0xffffffffu, mn, 1));
      mx = max_bf2(mx, __shfl_xor_sync(0xffffffffu, mx, 2));
      mn = min_bf2(mn, __shfl_xor_sync(0xffffffffu, mn, 2));
      float mx0 = -bf_lo(mx) * L2E, mx1 = -bf_hi(mx) * L2E, mn0 = bf_lo(mn) * L2E, mn1 = bf_hi(mn) * L2E;
      float ep0[5], ep1[5], en0[5], en1[5];
      float sp0 = 0.f, sp1 = 0.f, sn0 = 0.f, sn1 = 0.f;
#pragma unroll
      for (int g = 0; g < 5; g++) {
        float x0 = bf_lo(P[r][5 * p + g]), x1 = bf_hi(P[r][5 * p + g]);
        ep0[g] = ex2(fmaf(x0, L2E, mx0)); ep1[g] = ex2(fmaf(x1, L2E, mx1));
        en0[g] = ex2(fmaf(x0, -L2E, mn0)); en1[g] = ex2(fmaf(x1, -L2E, mn1));
        sp0 += ep0[g]; sp1 += ep1[g]; sn0 += en0[g]; sn1 += en1[g];
      }
      sp0 += __shfl_xor_sync(0xffffffffu, sp0, 1); sp1 += __shfl_xor_sync(0xffffffffu, sp1, 1);
      sn0 += __shfl_xor_sync(0xffffffffu, sn0, 1); sn1 += __shfl_xor_sync(0xffffffffu, sn1, 1);
      sp0 += __shfl_xor_sync(0xffffffffu, sp0, 2); sp1 += __shfl_xor_sync(0xffffffffu, sp1, 2);
      sn0 += __shfl_xor_sync(0xffffffffu, sn0, 2); sn1 += __shfl_xor_sync(0xffffffffu, sn1, 2);
      sp0 = rcp(sp0); sp1 = rcp(sp1); sn0 = rcp(sn0); sn1 = rcp(sn1);
#pragma unroll
      for (int g = 0; g < 5; g++) {
        fr[5 * p + g][r] = pack_bf16(ep0[g] * sp0, ep1[g] * sp1);
        fr[5 * p + g][2 + r] = pack_bf16(en0[g] * sn0, en1[g] * sn1);
      }
    }
  }
}

struct Ring {
  uint32_t idx, phase;
  template <int N> __device__ __forceinline__ void next() { if (++idx == N) { idx = 0; phase ^= 1; } }
};

}

__global__ void __cluster_dims__(2, 1, 1) __launch_bounds__(384, 1)
fused_kernel(const __grid_constant__ Maps maps, const __nv_bfloat16* __restrict__ x, const __nv_bfloat16* __restrict__ wqkv,
             const __nv_bfloat16* __restrict__ wphi, const __nv_bfloat16* __restrict__ w1, const __nv_bfloat16* __restrict__ w2,
             const __nv_bfloat16* __restrict__ w3, const __nv_bfloat16* __restrict__ w4, const __nv_bfloat16* __restrict__ wo,
             const __nv_bfloat16* __restrict__ gate_w) {
  extern __shared__ __align__(1024) uint8_t sgen[];
  const uint32_t sb = smem_u32(sgen);
  const uint32_t sb16 = (sb & 0x3FFFFu) >> 4;
  const uint32_t bars = sb + OFF_BAR;
  const uint32_t fullA = bars + 8 * B_FULLA, emptyA = bars + 8 * B_EMPTYA, fullB = bars + 8 * B_FULLB, emptyB = bars + 8 * B_EMPTYB;

  const int tid = threadIdx.x;
  const int rank = blockIdx.x & 1;
  const int pairIdx = blockIdx.x >> 1;
  const int i = pairIdx >> 2, j = 2 * (pairIdx & 3) + rank;

  TSTAMP(0);
  if ((tid & 31) == 0) {
#pragma unroll 1
    for (int b = tid >> 5; b < NBAR; b += 12) {
      mbar_init(bars + 8 * b, b == B_CS ? 2 : b < B_SEND ? 1 : b < B_EMPTYB ? 4 : b < B_EMPTYA ? 8 : 16);
      if (b >= B_DSR && b < B_SEND) mbar_expect_tx(bars + 8 * b, 10240);
    }
    asm volatile("fence.mbarrier_init.release.cluster;" ::: "memory");
  }
  if (tid == 352) { prefetch_tmap(&maps.x); prefetch_tmap(&maps.qm); prefetch_tmap(&maps.w1m); prefetch_tmap(&maps.qr); prefetch_tmap(&maps.w1r); }
  asm volatile("barrier.cluster.arrive.relaxed.aligned;" ::: "memory");

  if (tid >= 256) {
    asm volatile("setmaxnreg.dec.sync.aligned.u32 56;");
    asm volatile("barrier.cluster.wait.aligned;" ::: "memory");
    auto get_epoch = [&]() { return *reinterpret_cast<volatile unsigned*>(g_flags + FL_DONE * 32) / NCTA; };
    const int lane = tid & 31, pw = (tid >> 5) & 3;
    auto send_stream = [&](int w, unsigned ep1) {
#pragma unroll 1
      for (int c = 0; c < 3; c++) {
        const int d = (j + 2 * c + 2) & 7;
        mbar_wait(bars + 8 * (B_SEND + 2 * c + w), 0);
        if (w) TR4(c * 16 + 7);
        bulk_store(g_part + (size_t)((i * 8 + d) * 3 + c) * 1280 + w * 640, sb + OFF_SEND + w * 10240, 10240);
        bulk_commit();
        bulk_wait<0>();
        if (c < 2) mbar_arrive(bars + 8 * (B_SDONE + 2 * c + w));
        if (w) TR4(c * 16 + 9);
        asm volatile("st.release.gpu.global.u32 [%0], %1;"
                     ::"l"(g_flags + (FL_PART + i * 8 + d) * 32 + 2 * c + w), "r"(ep1) : "memory");
        if (w) TR4(c * 16 + 10);
      }
    };
    if (pw == 0) {
      if (lane == 0) {
        Ring r{0, 1};
        unsigned ep1 = 0;
#pragma unroll 1
        for (int k = 0; k < 30; k++) {
          if (k == 4) ep1 = get_epoch() + 1;
          if (k == 10 || k == 20) {
            const unsigned tgt = ep1 * 8u;
            const unsigned* f0 = g_flags + (k == 10 ? FL_H + ((i - 1) & 15) : FL_X1 + i) * 32;
            const unsigned* f1 = g_flags + (k == 10 ? FL_H + i : FL_X1 + i) * 32;
            const unsigned* f2 = g_flags + (k == 10 ? FL_H + ((i + 1) & 15) : FL_X1 + i) * 32;
            uint32_t n = 0;
            while (++n < (WAIT_LIMIT >> 4)) {
              unsigned v0, v1, v2;
              asm volatile("ld.relaxed.gpu.global.u32 %0, [%3];\nld.relaxed.gpu.global.u32 %1, [%4];\nld.acquire.gpu.global.u32 %2, [%5];"
                           : "=r"(v0), "=r"(v1), "=r"(v2) : "l"(f0), "l"(f1), "l"(f2) : "memory");
              if ((int)((v0 - tgt) | (v1 - tgt) | (v2 - tgt)) >= 0) break;
            }
            TSTAMPX(k == 10 ? 29 : 30);
          }
          mbar_wait(emptyA + 8 * r.idx, r.phase);
          const uint32_t bar = fullA + 8 * r.idx, slot = sb + OFF_A + r.idx * SLOT_A;
          TRACE(k);
          mbar_expect_tx(bar, SLOT_A);
          tma2d_mc(slot + rank * 8192, k < 10 ? &maps.x : k < 20 ? &maps.hs : &maps.x1, bar, 64 * (k % 10), 128 * i + 64 * rank);
          r.next<NA>();
        }
        send_stream(1, ep1);
      }
    } else if (pw == 1) {
      if (lane == 0) {
        Ring r{0, 1};
#pragma unroll 1
        for (int k = 0; k < 26; k++) {
          mbar_wait(emptyB + 8 * r.idx, r.phase);
          const uint32_t bar = fullB + 8 * r.idx, slot = sb + OFF_B + r.idx * SLOT_B;
          TRACE(96 + k);
          if (k < 10) {
            mbar_expect_tx(bar, 40960);
            tma4d(slot + 8192, &maps.qm, bar, 0, 64 * k, 0, j);
            tma3d(slot, &maps.w1m, bar, 0, 64 * k, j);
            tma4d(slot + 32768 + 2048, &maps.qr, bar, 64, 64 * k, 0, j);
            tma3d(slot + 32768, &maps.w1r, bar, 64, 64 * k, j);
          } else if (k < 13) {
            const int s = k - 10;
            mbar_expect_tx(bar, 40960);
            tma3d(slot, &maps.w2, bar, 0, 256 * s, 5 * j);
            if (s < 2) tma3d(slot + 20480, &maps.w2, bar, 0, 256 * s + 128, 5 * j);
            else tma2d(slot + 20480, &maps.xr, bar, 80 * j, 128 * i);
          } else if (k < 18) {
            mbar_expect_tx(bar, 49152);
            tma3d(slot, &maps.w3, bar, 0, 128 * (k - 13), 3 * j);
            tma3d(slot + 24576, &maps.w3, bar, 0, 128 * (k - 13) + 64, 3 * j);
          } else {
            const int hb = k & 1, d = (j + (k - 16 - hb)) & 7;
            mbar_expect_tx(bar, hb ? 46080 : 40960);
#pragma unroll 1
            for (int u = 0; u < 4; u++) {
              const int g = u >> 1, sl = d ^ (u & 1);
              if (hb && g) {
                tma3d(slot + 20480 + (u & 1) * 10240, &maps.wom, bar, 0, 80 * j, sl);
                tma3d(slot + 40960 + (u & 1) * 2560, &maps.wor, bar, 64, 80 * j, sl);
              } else {
                const int k0 = 192 * j + 128 * hb + 64 * g;
                tma3d(slot + g * 20480 + (u & 1) * 8192, &maps.w4m, bar, 0, k0, sl);
                tma3d(slot + g * 20480 + 16384 + (u & 1) * 2048, &maps.w4r, bar, 64, k0, sl);
              }
            }
          }
          r.next<NB>();
        }
      }
    } else {
      const unsigned epoch = get_epoch();
      float* accg = g_acc[epoch & 1];
      const int hw = pw & 1;
      {
        const int ch = lane % 10, rg = lane / 10;
        const __nv_bfloat16* p = w1 + (size_t)(40 * i + 20 * hw + rg) * D_ + 80 * j + 8 * ch;
        float a[8];
#pragma unroll
        for (int e = 0; e < 8; e++) a[e] = 0.f;
#pragma unroll
        for (int it = 0; it < 7; it++) {
          uint4 v = make_uint4(0, 0, 0, 0);
          if (lane < 30 && 3 * it + rg < 20) v = __ldg(reinterpret_cast<const uint4*>(p + (size_t)it * 3 * D_));
          a[0] += bf_lo(v.x); a[1] += bf_hi(v.x); a[2] += bf_lo(v.y); a[3] += bf_hi(v.y);
          a[4] += bf_lo(v.z); a[5] += bf_hi(v.z); a[6] += bf_lo(v.w); a[7] += bf_hi(v.w);
        }
#pragma unroll
        for (int e = 0; e < 8; e++) a[e] += __shfl_down_sync(0xffffffffu, a[e], 10) + __shfl_down_sync(0xffffffffu, a[e], 20);
        if (lane < 10) {
          float* cd = accg + 8 * KV_J + 80 * j + 8 * ch;
          red_add4(cd, a[0], a[1], a[2], a[3]); red_add4(cd + 4, a[4], a[5], a[6], a[7]);
        }
      }
#pragma unroll 1
      for (int it = 0; it < 4; it++) {
        const int row = 128 * i + 16 * j + 8 * hw + 2 * it + (lane >> 4), l16 = lane & 15;
        uint4 v[5];
#pragma unroll
        for (int c = 0; c < 5; c++) v[c] = __ldg(reinterpret_cast<const uint4*>(x + (size_t)row * D_ + c * 128 + l16 * 8));
        float s = 0.f, gs = 0.f;
#pragma unroll
        for (int c = 0; c < 5; c++) {
          const uint4 w = __ldg(reinterpret_cast<const uint4*>(gate_w + c * 128 + l16 * 8));
          const uint32_t vv[4] = {v[c].x, v[c].y, v[c].z, v[c].w}, ww[4] = {w.x, w.y, w.z, w.w};
#pragma unroll
          for (int e = 0; e < 4; e++) {
            s += bf_lo(vv[e]) + bf_hi(vv[e]);
            gs = fmaf(bf_lo(vv[e]), bf_lo(ww[e]), gs); gs = fmaf(bf_hi(vv[e]), bf_hi(ww[e]), gs);
          }
        }
#pragma unroll
        for (int o = 1; o < 16; o <<= 1) { s += __shfl_xor_sync(0xffffffffu, s, o); gs += __shfl_xor_sync(0xffffffffu, gs, o); }
        const float mean = s * (1.f / D_);
        float q = 0.f;
#pragma unroll
        for (int c = 0; c < 5; c++) {
          const uint32_t vv[4] = {v[c].x, v[c].y, v[c].z, v[c].w};
#pragma unroll
          for (int e = 0; e < 4; e++) {
            const float d0 = bf_lo(vv[e]) - mean, d1 = bf_hi(vv[e]) - mean;
            q = fmaf(d0, d0, q); q = fmaf(d1, d1, q);
          }
        }
#pragma unroll
        for (int o = 1; o < 16; o <<= 1) q += __shfl_xor_sync(0xffffffffu, q, o);
        const float rstd = rsqrtf(q * (1.f / D_) + 1e-5f);
        if (l16 == 0) g_xstat[row] = make_float4(rstd, -mean * rstd, rcp(1.f + __expf(-gs)), __uint_as_float(epoch & 1));
      }
      __syncwarp();
      if (lane == 0) { flag_add(FL_CS + j); flag_add_relaxed(FL_ST + i); TSTAMPX(20); }
      if (pw == 2) {
        {
          float* nxt = g_acc[(epoch + 1) & 1];
          constexpr int PER = ACC_FLOATS / NCTA;
#pragma unroll 1
          for (int e = lane; e < PER; e += 32) nxt[blockIdx.x * PER + e] = 0.f;
        }
        if (lane == 0) {
          flag_wait(FL_CS + j, (epoch + 1) * 32u);
          flag_wait(FL_ST + i, (epoch + 1) * 16u);
          fence_async_all();
          mbar_expect_tx(bars + 8 * B_CS, 320 + 2048);
          bulk_load(sb + OFF_CS, accg + 8 * KV_J + 80 * j, 320, bars + 8 * B_CS);
          bulk_load(sb + OFF_XST, g_xstat + 128 * i, 2048, bars + 8 * B_CS);
          TSTAMPX(21);
          l2_prefetch(w2 + (size_t)blockIdx.x * (D_ * D_ / NCTA), D_ * D_ * 2 / NCTA);
          l2_prefetch(w4 + (size_t)blockIdx.x * (F_ * D_ / NCTA), F_ * D_ * 2 / NCTA);
          l2_prefetch(wo + (size_t)blockIdx.x * (D_ * D_ / NCTA), D_ * D_ * 2 / NCTA);
        }
        __syncwarp();
#pragma unroll 1
        for (int m = 0; m < 6; m++) {
          const int col = 192 * j + 32 * m + 8 * (lane & 3);
          const __nv_bfloat16* p = w3 + (size_t)(40 * i + (lane >> 2) * 5) * F_ + col;
          float a[8];
#pragma unroll
          for (int e = 0; e < 8; e++) a[e] = 0.f;
#pragma unroll
          for (int it = 0; it < 5; it++) {
            const uint4 v = __ldg(reinterpret_cast<const uint4*>(p + (size_t)it * F_));
            a[0] += bf_lo(v.x); a[1] += bf_hi(v.x); a[2] += bf_lo(v.y); a[3] += bf_hi(v.y);
            a[4] += bf_lo(v.z); a[5] += bf_hi(v.z); a[6] += bf_lo(v.w); a[7] += bf_hi(v.w);
          }
#pragma unroll
          for (int e = 0; e < 4; e++) {
            const float snd = (lane & 4) ? a[e] : a[e + 4], keep = (lane & 4) ? a[e + 4] : a[e];
            a[e] = keep + __shfl_xor_sync(0xffffffffu, snd, 4);
            a[e] += __shfl_xor_sync(0xffffffffu, a[e], 8);
            a[e] += __shfl_xor_sync(0xffffffffu, a[e], 16);
          }
          if (lane < 8) red_add4(accg + 8 * KV_J + D_ + col + (lane >> 2) * 4, a[0], a[1], a[2], a[3]);
        }
        __syncwarp();
        if (lane == 0) {
          flag_add(FL_CS3 + j);
          flag_wait(FL_KV + j, (epoch + 1) * 16u);
          fence_async_all();
          mbar_expect_tx(bars + 8 * B_KV, KV_J * 4);
          bulk_load(sb + OFF_MISC, accg + j * KV_J, KV_J * 4, bars + 8 * B_KV);
          TSTAMPX(22);
          mbar_wait(bars + 8 * B_MFREE, 0);
          flag_wait(FL_X1 + i, (epoch + 1) * 8u);
          flag_wait(FL_CS3 + j, (epoch + 1) * 16u);
          fence_async_all();
          mbar_expect_tx(bars + 8 * B_ST1, 8192 + 768);
          bulk_load(sb + OFF_CS + 320, accg + 8 * KV_J + D_ + 192 * j, 768, bars + 8 * B_ST1);
          bulk_load(sb + OFF_MISC, g_st1 + 128 * i * 8, 8192, bars + 8 * B_ST1);
        }
        __syncwarp();
        mbar_wait(bars + 8 * (B_SEND + 1), 0);
        const unsigned* fp = g_flags + (FL_PART + i * 8 + j) * 32 + lane;
        bool seen = lane >= 6;
        uint32_t n = 0;
        while (!__all_sync(0xffffffffu, seen) && ++n < (WAIT_LIMIT >> 4)) {
          if (!seen && ld_acquire(fp) == epoch + 1 && (lane < 2 || mbar_test(bars + 8 * (B_SEND + 5), 0))) {
            seen = true;
            if (lane & 1) TR4((lane >> 1) * 16 + 11);
            mbar_expect_tx(bars + 8 * (B_RDY + lane), 10240);
            bulk_load(sb + (lane < 2 ? OFF_G0 : OFF_G1 - 20480) + lane * 10240, g_part + (size_t)(i * 8 + j) * 3840 + lane * 640, 10240,
                      bars + 8 * (B_RDY + lane));
          }
        }
      } else {
        mbar_wait(bars + 8 * B_SIGP, 0);
#pragma unroll 1
        for (int q = lane; q < 200; q += 32) {
          const uint4 pre = __ldg(reinterpret_cast<const uint4*>(wphi + (size_t)j * 1600) + q);
          const uint32_t ww[4] = {pre.x, pre.y, pre.z, pre.w};
          const int h = q / 50;
#pragma unroll
          for (int e = 0; e < 8; e++) {
            const int idx = q * 8 + e, k = idx / 20, ff = idx - 20 * k;
            const int n = 40 * (h >> 1) + 8 * (ff >> 2) + 2 * (ff & 3) + (h & 1);
            const int off = (k >> 4) * 2560 + n * 32 + ((((k >> 3) ^ (n >> 2)) & 1) << 4) + (k & 7) * 2;
            *reinterpret_cast<unsigned short*>(sgen + OFF_MISC + off) = (unsigned short)(ww[e >> 1] >> ((e & 1) * 16));
          }
        }
        fence_async_smem();
        __syncwarp();
      }
      if (pw == 3 && lane == 0) {
        mbar_arrive(bars + 8 * B_CS);
        TSTAMPX(17);
        const int shift = (j < 2) ? 1 : (j < 4) ? -1 : (j < 6) ? 2 : -2;
        if ((shift > 0 && i == 0) || (shift < 0 && i == 15)) {
          const int nz = shift > 0 ? shift : -shift, zr = shift > 0 ? 0 : S_ - nz;
#pragma unroll 1
          for (int e = 0; e < nz * 10; e++)
            reinterpret_cast<uint4*>(g_Hs + (size_t)(2 + zr + e / 10) * D_ + 80 * j)[e % 10] = make_uint4(0, 0, 0, 0);
          fence_async_all();
        }
        prefetch_tmap(&maps.st_h); prefetch_tmap(&maps.st_x1); prefetch_tmap(&maps.hs); prefetch_tmap(&maps.x1); prefetch_tmap(&maps.xr);
        prefetch_tmap(&maps.w2); prefetch_tmap(&maps.w3); prefetch_tmap(&maps.w4m); prefetch_tmap(&maps.w4r); prefetch_tmap(&maps.wom); prefetch_tmap(&maps.wor); prefetch_tmap(&maps.st_out);
        mbar_wait(bars + 8 * B_SIGH, 0);
        TSTAMPX(23);
        tma2d_store(&maps.st_h, sb + OFF_STG, 80 * j, 128 * i + 2 + shift);
        tma2d_store(&maps.st_h, sb + OFF_STG + 10240, 80 * j, 128 * i + 66 + shift);
        bulk_commit(); bulk_wait<0>();
        flag_add(FL_H + i);
        TSTAMPX(24);
        mbar_wait(bars + 8 * B_SIGKV, 0);
        TSTAMPX(25);
        flag_add(FL_KV + j);
        TSTAMPX(26);
        mbar_wait(bars + 8 * B_SIGX1, 0);
        TSTAMPX(27);
        tma2d_store(&maps.st_x1, sb + OFF_STG, 80 * j, 128 * i);
        tma2d_store(&maps.st_x1, sb + OFF_STG + 10240, 80 * j, 128 * i + 64);
        bulk_commit(); bulk_wait<0>();
        flag_add(FL_X1 + i);
        TSTAMPX(28);
        send_stream(0, epoch + 1);
      }
    }
    __syncwarp();
    asm volatile("barrier.cluster.arrive;\nbarrier.cluster.wait;" ::: "memory");
  } else {
    asm volatile("setmaxnreg.inc.sync.aligned.u32 224;");
    const int wg = tid >> 7, warp = tid >> 5, lane = tid & 31, t = lane & 3;
    const int rloc = warp * 16 + (lane >> 2);
    const float* s_cs = reinterpret_cast<const float*>(sgen + OFF_CS);
    auto signal = [&](int b) {
      __syncwarp();
      if (lane == 0) mbar_arrive(bars + 8 * b);
    };
    auto releaseB = [&](uint32_t bar) {
      __syncwarp();
      if (lane == 0) mbar_arrive(bar);
    };
    auto release = [&](uint32_t bar) {
      __syncwarp();
      if (lane < 2) mbar_arrive_cta(bar, lane);
    };
    const uint32_t stg_lane = (warp * 16 + ((lane >> 3) & 1) * 8 + (lane & 7)) * 160 + (lane >> 4) * 16;

#pragma unroll 1
    for (int e = tid; e < 800; e += 256) sts128(sb + OFF_MISC + e * 16, make_uint4(0, 0, 0, 0));
    asm volatile("barrier.cluster.wait.aligned;" ::: "memory");
    signal(B_SIGP);
    TSTAMP(1);

    Ring ra{0, 0}, rb{0, 0};
    uint32_t qp[2][10], P[2][10];
    float st_g[2];
    uint32_t par;
    {
      float accM[128], accR[32];
      zero_regs(accM); zero_regs(accR);
      uint32_t pa = 0, pb = 0;
#pragma unroll 1
      for (int k = 0; k < 10; k++) {
        mbar_wait(fullA + 8 * ra.idx, ra.phase);
        if (tid == 0) TRACE(32 + k);
        mbar_wait(fullB + 8 * rb.idx, rb.phase);
        if (tid == 0) TRACE(64 + k);
        if (k == 0) TSTAMP(2);
        const uint32_t a0 = sb16 + ((OFF_A + ra.idx * SLOT_A + wg * 8192) >> 4), b0 = sb16 + ((OFF_B + rb.idx * SLOT_B) >> 4);
        wg_fence();
#pragma unroll
        for (int kk = 0; kk < 4; kk++) {
          const uint64_t da = make_desc(a0, kk * 32, 16, 1024, 1);
          mma_ss256(accM, da, make_desc(b0, kk * 2048, 8192, 1024, 1));
          mma_ss64(accR, da, make_desc(b0, 32768 + kk * 512, 2048, 256, 3));
          if (kk == 0) {
            wg_commit();
            if (k > 0) {
              wg_wait<1>();
              if (k - 1 < 8) release(emptyA + 8 * pa);
              releaseB(emptyB + 8 * pb);
            }
          }
        }
        wg_commit();
        pa = ra.idx; pb = rb.idx;
        ra.next<NA>(); rb.next<NB>();
      }
      TSTAMP(18);
      float st_rstd[2], st_mr[2];
      mbar_wait(bars + 8 * B_CS, 0);
#pragma unroll
      for (int r = 0; r < 2; r++) {
        const uint4 st = lds128(sb + OFF_XST + (rloc + 8 * r) * 16);
        st_rstd[r] = __uint_as_float(st.x); st_mr[r] = __uint_as_float(st.y); st_g[r] = __uint_as_float(st.z);
        par = st.w;
      }
      TSTAMP(19);
      wg_wait<0>();
      fence_regs(accM); fence_regs(accR);
      TSTAMP(3);
#define ACC(P_, G, I_) ((G) < 8 ? accM[(P_) * 32 + ((G) & 7) * 4 + (I_)] : accR[(P_) * 8 + ((G) & 1) * 4 + (I_)])
      {
        const int mat = lane >> 3;
        const int tok = warp * 16 + (mat & 1) * 8 + (lane & 7);
        const uint32_t ones = (t == 0) ? 0x00003f80u : 0u;
        __syncwarp();
#pragma unroll
        for (int p = 0; p < 2; p++) {
          const uint32_t rowa = sb + OFF_A + p * SLOT_A + tok * 128;
#pragma unroll
          for (int gg = 0; gg < 3; gg++) {
            const int g0 = 5 * p + 2 * gg;
            uint32_t r0 = pack_bf16(ACC(3, g0, 0), ACC(3, g0, 1)), r1 = pack_bf16(ACC(3, g0, 2), ACC(3, g0, 3));
            uint32_t r2 = ones, r3 = ones;
            if (gg < 2) { r2 = pack_bf16(ACC(3, g0 + 1, 0), ACC(3, g0 + 1, 1)); r3 = pack_bf16(ACC(3, g0 + 1, 2), ACC(3, g0 + 1, 3)); }
            stsm4(rowa + (((2 * gg + (mat >> 1)) ^ (tok & 7)) << 4), r0, r1, r2, r3);
          }
        }
      }
      uint32_t kf[5][4], qf[5][4];
#pragma unroll
      for (int s = 0; s < 5; s++) {
        kf[s][0] = pack_bf16(ACC(2, 2 * s, 0), ACC(2, 2 * s, 1)); kf[s][1] = pack_bf16(ACC(2, 2 * s, 2), ACC(2, 2 * s, 3));
        kf[s][2] = pack_bf16(ACC(2, 2 * s + 1, 0), ACC(2, 2 * s + 1, 1)); kf[s][3] = pack_bf16(ACC(2, 2 * s + 1, 2), ACC(2, 2 * s + 1, 3));
        qf[s][0] = pack_bf16(ACC(1, 2 * s, 0), ACC(1, 2 * s, 1)); qf[s][1] = pack_bf16(ACC(1, 2 * s, 2), ACC(1, 2 * s, 3));
        qf[s][2] = pack_bf16(ACC(1, 2 * s + 1, 0), ACC(1, 2 * s + 1, 1)); qf[s][3] = pack_bf16(ACC(1, 2 * s + 1, 2), ACC(1, 2 * s + 1, 3));
      }
      bar_sync(1, 256);
      float pk[40], pq[40];
      wg_fence();
#pragma unroll
      for (int s = 0; s < 5; s++) {
        if (s == 0) mma_rs80_k_z(pk, kf[s], make_desc(sb16, OFF_MISC, 16, 256, 3));
        else mma_rs80_k(pk, kf[s], make_desc(sb16, OFF_MISC + s * 2560, 16, 256, 3));
      }
#pragma unroll
      for (int s = 0; s < 5; s++) {
        if (s == 0) mma_rs80_k_z(pq, qf[s], make_desc(sb16, OFF_MISC, 16, 256, 3));
        else mma_rs80_k(pq, qf[s], make_desc(sb16, OFF_MISC + s * 2560, 16, 256, 3));
      }
      wg_commit();

      {
        uint32_t hv[10][2];
#pragma unroll
        for (int g = 0; g < 10; g++) {
          const float2 cs = *reinterpret_cast<const float2*>(s_cs + 8 * g + 2 * t);
          const float v0 = gelu_s(fmaf(ACC(0, g, 0), st_rstd[0], st_mr[0] * cs.x), 0.5f), v1 = gelu_s(fmaf(ACC(0, g, 1), st_rstd[0], st_mr[0] * cs.y), 0.5f);
          const float v2 = gelu_s(fmaf(ACC(0, g, 2), st_rstd[1], st_mr[1] * cs.x), 0.5f), v3 = gelu_s(fmaf(ACC(0, g, 3), st_rstd[1], st_mr[1] * cs.y), 0.5f);
          hv[g][0] = pack_bf16(v0, v1); hv[g][1] = pack_bf16(v2, v3);
        }
#pragma unroll
        for (int s = 0; s < 5; s++) stsm4(sb + OFF_STG + stg_lane + s * 32, hv[2 * s][0], hv[2 * s][1], hv[2 * s + 1][0], hv[2 * s + 1][1]);
        fence_async_smem();
        signal(B_SIGH);
      }
#undef ACC
      TSTAMP(4);
      wg_wait<0>();
      fence_regs(pk); fence_regs(pq);
#pragma unroll
      for (int G = 0; G < 10; G++) {
        P[0][G] = pack_bf16(pk[4 * G], pk[4 * G + 1]); P[1][G] = pack_bf16(pk[4 * G + 2], pk[4 * G + 3]);
        qp[0][G] = pack_bf16(pq[4 * G], pq[4 * G + 1]); qp[1][G] = pack_bf16(pq[4 * G + 2], pq[4 * G + 3]);
      }
    }

    uint32_t fr[10][4];
    {
      feature_map(P, fr);
      const int mat = lane >> 3;
      const int tok = warp * 16 + (mat & 1) * 8 + (lane & 7);
      const uint32_t base = sb + OFF_B + tok * 32 + (((mat >> 1) ^ ((tok >> 2) & 1)) << 4);
#pragma unroll
      for (int G = 0; G < 10; G++) stsm4(base + G * 4096, fr[G][0], fr[G][1], fr[G][2], fr[G][3]);
      fence_async_smem();
      bar_sync(1, 256);
      float kv[40];
      const uint32_t a0 = sb16 + ((OFF_A + wg * SLOT_A) >> 4), b0 = sb16 + ((OFF_B + wg * 20480) >> 4);
      wg_fence();
#pragma unroll
      for (int ks = 0; ks < 8; ks++) {
        if (ks == 0) mma_ss80_tt_z(kv, make_desc(a0, 0, 16, 1024, 1), make_desc(b0, 0, 4096, 256, 3));
        else mma_ss80_tt(kv, make_desc(a0, ks * 2048, 16, 1024, 1), make_desc(b0, ks * 512, 4096, 256, 3));
      }
      wg_commit();
      wg_wait<0>();
      fence_regs(kv);
      release(emptyA); release(emptyA + 8); releaseB(emptyB);
      float* dst = g_acc[par] + j * KV_J + wg * KV_PAIR;
      const int m0 = (warp & 3) * 16 + (lane >> 2);
#pragma unroll
      for (int r = 0; r < 2; r++) {
        const int m = m0 + 8 * r;
        const bool hi = m >= 20;
        float v[10];
#pragma unroll
        for (int G = 0; G < 10; G++) v[G] = hi ? kv[4 * G + 2 * r + 1] : kv[4 * G + 2 * r];
        float* p = dst + (m < 40 ? m * 48 + t * 12 : 1920 + t * 24 + 12);
        if (m <= 40) { red_add4(p, v[0], v[1], v[2], v[3]); red_add4(p + 4, v[4], v[5], v[6], v[7]); red_add2(p + 8, v[8], v[9]); }
      }
      if (m0 == 32) {
        float* p = dst + 1920 + t * 24;
        red_add4(p, kv[2], kv[6], kv[10], kv[14]); red_add4(p + 4, kv[18], kv[22], kv[26], kv[30]); red_add2(p + 8, kv[34], kv[38]);
      }
      signal(B_SIGKV);
    }
    TSTAMP(5);

    uint32_t xv[2][10];
    {
      float acc[40];
      zero_regs(acc);
      uint32_t pa = 0, pb = 0;
#pragma unroll 1
      for (int k = 0; k < 10; k++) {
        mbar_wait(fullA + 8 * ra.idx, ra.phase);
        if (tid == 0) TRACE(42 + k);
        if ((k & 3) == 0) mbar_wait(fullB + 8 * rb.idx, rb.phase);
        if (tid == 0) TRACE(74 + k);
        if (k == 0) TSTAMP(6);
        const uint32_t a0 = sb16 + ((OFF_A + ra.idx * SLOT_A + wg * 8192) >> 4);
        const uint32_t b0 = sb16 + ((OFF_B + rb.idx * SLOT_B + ((k >> 1) & 1) * 20480 + (k & 1) * 2048) >> 4);
        wg_fence();
#pragma unroll
        for (int kk = 0; kk < 4; kk++) {
          mma_ss80(acc, make_desc(a0, kk * 32, 16, 1024, 1), make_desc(b0, kk * 512, 4096, 256, 3));
          if (kk == 1) {
            wg_commit();
            if (k > 0) {
              wg_wait<1>();
              release(emptyA + 8 * pa);
              if ((k & 3) == 0) releaseB(emptyB + 8 * pb);
            }
          }
        }
        wg_commit();
        pa = ra.idx; pb = rb.idx;
        ra.next<NA>();
        if ((k & 3) == 3 || k == 9) rb.next<NB>();
      }
      {
        const uint32_t xa = sb + OFF_B + pb * SLOT_B + 20480 + rloc * 160 + t * 4;
#pragma unroll
        for (int g = 0; g < 10; g++) { xv[0][g] = lds32(xa + g * 16); xv[1][g] = lds32(xa + 1280 + g * 16); }
      }
      wg_wait<0>();
      fence_regs(acc);
      release(emptyA + 8 * pa); releaseB(emptyB + 8 * pb);
      TSTAMP(7);
#pragma unroll
      for (int r = 0; r < 2; r++) {
#pragma unroll
        for (int g = 0; g < 10; g++)
          xv[r][g] = pack_bf16(bf_lo(xv[r][g]) + acc[4 * g + 2 * r], bf_hi(xv[r][g]) + acc[4 * g + 2 * r + 1]);
      }
      bar_sync(1, 256);
#pragma unroll
      for (int s = 0; s < 5; s++) stsm4(sb + OFF_STG + stg_lane + s * 32, xv[0][2 * s], xv[1][2 * s], xv[0][2 * s + 1], xv[1][2 * s + 1]);
#pragma unroll
      for (int r = 0; r < 2; r++) {
        float s = 0.f;
#pragma unroll
        for (int g = 0; g < 10; g++) {
          acc[4 * g + 2 * r] = bf_lo(xv[r][g]); acc[4 * g + 2 * r + 1] = bf_hi(xv[r][g]);
          s += acc[4 * g + 2 * r] + acc[4 * g + 2 * r + 1];
        }
        s += __shfl_xor_sync(0xffffffffu, s, 1); s += __shfl_xor_sync(0xffffffffu, s, 2);
        const float mu = s * (1.f / 80.f);
        float q = 0.f;
#pragma unroll
        for (int g = 0; g < 10; g++) {
          const float d0 = acc[4 * g + 2 * r] - mu, d1 = acc[4 * g + 2 * r + 1] - mu;
          q = fmaf(d0, d0, q); q = fmaf(d1, d1, q);
        }
        q += __shfl_xor_sync(0xffffffffu, q, 1); q += __shfl_xor_sync(0xffffffffu, q, 2);
        if (t == 0) g_st1[(128 * i + rloc + 8 * r) * 8 + j] = make_float2(mu, q);
      }
      fence_async_smem();
      signal(B_SIGX1);
    }
    TSTAMP(8);

    uint32_t of[5][4];
    {
      feature_map(qp, fr);
      mbar_wait(bars + 8 * B_KV, 0);
      uint4 kvr[2][3];
#pragma unroll
      for (int u = 0; u < 2; u++) {
        const int it = tid + 256 * u, p = it / 192, rem = it - 192 * p, n = rem >> 2, tq = rem & 3;
        const uint32_t sp = sb + OFF_MISC + 4 * (p * KV_PAIR + (n < 40 ? n * 48 + tq * 12 : 1920 + tq * 24 + (n & 1) * 12));
        if (it < 384) { kvr[u][0] = lds128(sp); kvr[u][1] = lds128(sp + 16); kvr[u][2] = lds128(sp + 32); }
      }
      bar_sync(1, 256);
#pragma unroll
      for (int u = 0; u < 2; u++) {
        const int it = tid + 256 * u, p = it / 192, rem = it - 192 * p, n = rem >> 2, tq = rem & 3;
        const int sh = (n < 40 ? (n >= 20) : (n & 1)) * 16;
        const uint32_t v[10] = {kvr[u][0].x, kvr[u][0].y, kvr[u][0].z, kvr[u][0].w, kvr[u][1].x, kvr[u][1].y, kvr[u][1].z, kvr[u][1].w, kvr[u][2].x, kvr[u][2].y};
        uint8_t* dst = sgen + OFF_MISC + p * 7680 + n * 32 + tq * 4;
        const int sw = ((n >> 2) & 1) << 4;
        if (it < 384) {
#pragma unroll
          for (int G = 0; G < 10; G++)
            *reinterpret_cast<uint32_t*>(dst + (G >> 1) * 1536 + (((G & 1) << 4) ^ sw)) = pack_bf16(__uint_as_float(v[G]), 0.f) << sh;
        }
      }
      fence_async_smem();
      bar_sync(1, 256);
      float o0[24], o1[24];
      wg_fence();
#pragma unroll
      for (int g = 0; g < 5; g++) {
        if (g == 0) mma_rs48_k_z(o0, fr[g], make_desc(sb16, OFF_MISC, 16, 256, 3));
        else mma_rs48_k(o0, fr[g], make_desc(sb16, OFF_MISC + g * 1536, 16, 256, 3));
      }
#pragma unroll
      for (int g = 0; g < 5; g++) {
        if (g == 0) mma_rs48_k_z(o1, fr[5], make_desc(sb16, OFF_MISC + 7680, 16, 256, 3));
        else mma_rs48_k(o1, fr[5 + g], make_desc(sb16, OFF_MISC + 7680 + g * 1536, 16, 256, 3));
      }
      wg_commit();
      wg_wait<0>();
      fence_regs(o0); fence_regs(o1);
      signal(B_MFREE);
#pragma unroll
      for (int r = 0; r < 2; r++) {
        const float a0 = __fdividef(st_g[r], o0[20 + 2 * r] + 1e-6f), a1 = __fdividef(st_g[r], o0[21 + 2 * r] + 1e-6f);
        const float b0 = __fdividef(st_g[r], o1[20 + 2 * r] + 1e-6f), b1 = __fdividef(st_g[r], o1[21 + 2 * r] + 1e-6f);
        const float am = t < 2 ? a0 : a1, bm = t < 2 ? b0 : b1;
#pragma unroll
        for (int g = 0; g < 5; g++) {
          const float sa = g < 2 ? a0 : (g == 2 ? am : a1), sb2 = g < 2 ? b0 : (g == 2 ? bm : b1);
          of[g >> 1][(g & 1) * 2 + r] = pack_bf16(o0[4 * g + 2 * r] * sa, o0[4 * g + 2 * r + 1] * sa);
          of[(5 + g) >> 1][((5 + g) & 1) * 2 + r] = pack_bf16(o1[4 * g + 2 * r] * sb2, o1[4 * g + 2 * r + 1] * sb2);
        }
      }
    }
    TSTAMP(9);

    uint32_t hf[12][4];
    {
      float acc[96];
      zero_regs(acc);
      uint32_t pa = 0, pb = 0;
#pragma unroll 1
      for (int k = 0; k < 10; k++) {
        mbar_wait(fullA + 8 * ra.idx, ra.phase);
        if (tid == 0) TRACE(52 + k);
        if ((k & 1) == 0) mbar_wait(fullB + 8 * rb.idx, rb.phase);
        if (tid == 0) TRACE(84 + k);
        if (k == 0) TSTAMP(10);
        const uint32_t a0 = sb16 + ((OFF_A + ra.idx * SLOT_A + wg * 8192) >> 4);
        const uint32_t b0 = sb16 + ((OFF_B + rb.idx * SLOT_B + (k & 1) * 24576) >> 4);
        wg_fence();
#pragma unroll
        for (int kk = 0; kk < 4; kk++) {
          mma_ss192(acc, make_desc(a0, kk * 32, 16, 1024, 1), make_desc(b0, kk * 2048, 8192, 1024, 1));
          if (kk == 0) {
            wg_commit();
            if (k > 0) {
              wg_wait<1>();
              release(emptyA + 8 * pa);
              if ((k & 1) == 0) releaseB(emptyB + 8 * pb);
            }
          }
        }
        wg_commit();
        pa = ra.idx; pb = rb.idx;
        ra.next<NA>();
        if (k & 1) rb.next<NB>();
      }
      float rs[2], mm[2];
      mbar_wait(bars + 8 * B_ST1, 0);
#pragma unroll
      for (int r = 0; r < 2; r++) {
        const uint4 su = lds128(sb + OFF_MISC + (rloc + 8 * r) * 64 + t * 16);
        const float m0 = __uint_as_float(su.x), m1 = __uint_as_float(su.z);
        float mu = m0 + m1;
        mu += __shfl_xor_sync(0xffffffffu, mu, 1); mu += __shfl_xor_sync(0xffffffffu, mu, 2);
        mu *= 0.125f;
        const float d0 = m0 - mu, d1 = m1 - mu;
        float q = __uint_as_float(su.y) + __uint_as_float(su.w) + 80.f * (d0 * d0 + d1 * d1);
        q += __shfl_xor_sync(0xffffffffu, q, 1); q += __shfl_xor_sync(0xffffffffu, q, 2);
        rs[r] = rsqrtf(q * (1.f / D_) + 1e-5f);
        mm[r] = -mu * rs[r];
      }
      wg_wait<0>();
      fence_regs(acc);
      releaseB(emptyB + 8 * pb);
      if (lane == 0) mbar_arrive_cta(bars + 8 * B_PEER, rank ^ 1);
      if (wg == 1) bar_arrive(2, 256);
      TSTAMP(11);
      const float hs0 = 0.5f - 0.5f * st_g[0], hs1 = 0.5f - 0.5f * st_g[1];
#pragma unroll
      for (int g = 0; g < 24; g++) {
        const float2 cs = *reinterpret_cast<const float2*>(s_cs + 80 + 8 * g + 2 * t);
        const float v0 = gelu_s(fmaf(acc[4 * g], rs[0], mm[0] * cs.x), hs0), v1 = gelu_s(fmaf(acc[4 * g + 1], rs[0], mm[0] * cs.y), hs0);
        const float v2 = gelu_s(fmaf(acc[4 * g + 2], rs[1], mm[1] * cs.x), hs1), v3 = gelu_s(fmaf(acc[4 * g + 3], rs[1], mm[1] * cs.y), hs1);
        hf[g >> 1][(g & 1) * 2] = pack_bf16(v0, v1);
        hf[g >> 1][(g & 1) * 2 + 1] = pack_bf16(v2, v3);
      }
    }
    TSTAMP(12);

    {
      float aM[64], aR[16];
      const int wt = tid & 127;
      const uint32_t peer = map_peer(sb, rank ^ 1);
      auto add16 = [&](uint32_t src) {
#pragma unroll
        for (int q = 0; q < 5; q++) {
          const uint4 v = lds128(src + q * 2048);
          float* d = q < 4 ? &aM[8 * q] : &aR[0];
          d[0] += bf_lo(v.x); d[1] += bf_hi(v.x); d[2] += bf_lo(v.y); d[3] += bf_hi(v.y);
          d[4] += bf_lo(v.z); d[5] += bf_hi(v.z); d[6] += bf_lo(v.w); d[7] += bf_hi(v.w);
        }
      };
#pragma unroll 1
      for (int c = 0; c < 4; c++) {
        mbar_wait(fullB + 8 * rb.idx, rb.phase);
        const uint32_t s0 = rb.idx, b0 = sb16 + ((OFF_B + rb.idx * SLOT_B) >> 4);
        rb.next<NB>();
        const uint32_t b1 = sb16 + ((OFF_B + rb.idx * SLOT_B) >> 4);
        if (tid == 128) TR4(c * 16 + 0);
        bar_sync(2 + wg, 256);
        wg_fence();
#pragma unroll
        for (int s = 0; s < 8; s++) {
          const uint64_t dm = make_desc(b0, (s >> 2) * 20480 + (s & 3) * 2048, 8192, 1024, 1);
          const uint64_t dr = make_desc(b0, (s >> 2) * 20480 + 16384 + (s & 3) * 512, 2048, 256, 3);
          if (s == 0) { mma_rs128_n_z(aM, hf[s], dm); mma_rs32_n_z(aR, hf[s], dr); }
          else { mma_rs128_n(aM, hf[s], dm); mma_rs32_n(aR, hf[s], dr); }
        }
        wg_commit();
        mbar_wait(fullB + 8 * rb.idx, rb.phase);
        wg_fence();
#pragma unroll
        for (int s = 0; s < 4; s++) {
          mma_rs128_n(aM, hf[8 + s], make_desc(b1, s * 2048, 8192, 1024, 1));
          mma_rs32_n(aR, hf[8 + s], make_desc(b1, 16384 + s * 512, 2048, 256, 3));
          if (s == 1) { wg_commit(); wg_wait<1>(); releaseB(emptyB + 8 * s0); }
        }
#pragma unroll
        for (int s = 0; s < 5; s++) {
          mma_rs128_n(aM, of[s], make_desc(b1, 20480 + s * 2048, 10240, 1024, 1));
          mma_rs32_n(aR, of[s], make_desc(b1, 40960 + s * 512, 2560, 256, 3));
        }
        wg_commit();
        if (c < 3 || wg == 0) bar_arrive(3 - wg, 256);
        if (tid == 128) TR4(c * 16 + 2);
        if (c == 0) mbar_wait(bars + 8 * B_PEER, 0);
        wg_wait<0>();
        fence_regs(aM); fence_regs(aR);
        releaseB(emptyB + 8 * rb.idx);
        rb.next<NB>();
        if (tid == 128) TR4(c * 16 + 5);
        const uint32_t dso = OFF_DS + (c & 1) * 20480 + wg * 10240 + wt * 16, dsb = OFF_BAR + 8 * (B_DSR + 2 * c + wg);
#pragma unroll
        for (int q = 0; q < 5; q++) {
          const float* d = q < 4 ? &aM[32 + 8 * q] : &aR[8];
          st_async16(peer + dso + q * 2048, pack_bf16(d[0], d[1]), pack_bf16(d[2], d[3]), pack_bf16(d[4], d[5]), pack_bf16(d[6], d[7]),
                     peer + dsb);
        }
        if (c > 0 && c < 3) mbar_wait(bars + 8 * (B_SDONE + 2 * (c - 1) + wg), 0);
        mbar_wait(sb + dsb, 0);
        if (tid == 128) TR4(c * 16 + 3);
        add16(sb + dso);
        if (c < 3) {
          const uint32_t dst = sb + OFF_SEND + wg * 10240 + wt * 16;
#pragma unroll
          for (int q = 0; q < 5; q++) {
            const float* d = q < 4 ? &aM[8 * q] : &aR[0];
            sts128(dst + q * 2048, make_uint4(pack_bf16(d[0], d[1]), pack_bf16(d[2], d[3]), pack_bf16(d[4], d[5]), pack_bf16(d[6], d[7])));
          }
          fence_async_smem();
          signal(B_SEND + 2 * c + wg);
          if (tid == 128) TR4(c * 16 + 6);
        }
      }
      TSTAMP(13);
#pragma unroll 1
      for (int c = 0; c < 3; c++) {
        mbar_wait(bars + 8 * (B_RDY + 2 * c + wg), 0);
        add16(sb + (c == 0 ? OFF_G0 : OFF_G1 - 20480) + c * 20480 + wg * 10240 + wt * 16);
        if (tid == 128) TR4(c * 16 + 12);
      }
      TSTAMP(14);
      const float w0 = 1.f - st_g[0], w1s = 1.f - st_g[1];
      uint32_t ov[10][2];
#pragma unroll
      for (int g = 0; g < 10; g++) {
        const float* d = g < 8 ? &aM[4 * g] : &aR[4 * (g - 8)];
        ov[g][0] = pack_bf16(fmaf(w0, bf_lo(xv[0][g]), d[0]), fmaf(w0, bf_hi(xv[0][g]), d[1]));
        ov[g][1] = pack_bf16(fmaf(w1s, bf_lo(xv[1][g]), d[2]), fmaf(w1s, bf_hi(xv[1][g]), d[3]));
      }
      bar_sync(4 + wg, 128);
#pragma unroll
      for (int s = 0; s < 5; s++) stsm4(sb + OFF_DS + stg_lane + s * 32, ov[2 * s][0], ov[2 * s][1], ov[2 * s + 1][0], ov[2 * s + 1][1]);
      fence_async_smem();
      bar_sync(4 + wg, 128);
      if (wt == 0) {
        tma2d_store(&maps.st_out, sb + OFF_DS + wg * 10240, 80 * j, 128 * i + 64 * wg);
        bulk_commit(); bulk_wait_read();
      }
    }
    TSTAMP(15);
    if (tid == 0) asm volatile("red.relaxed.gpu.global.add.u32 [%0], 1;" ::"l"(g_flags + FL_DONE * 32) : "memory");
    asm volatile("barrier.cluster.arrive;\nbarrier.cluster.wait;" ::: "memory");
  }
}

namespace {
typedef CUresult (*EncodeFn)(CUtensorMap*, CUtensorMapDataType, cuuint32_t, void*, const cuuint64_t*, const cuuint64_t*,
                             const cuuint32_t*, const cuuint32_t*, CUtensorMapInterleave, CUtensorMapSwizzle,
                             CUtensorMapL2promotion, CUtensorMapFloatOOBfill);

void encode(EncodeFn fn, CUtensorMap* m, const void* ptr, int rank, const cuuint64_t* dims, const cuuint64_t* strides,
            const cuuint32_t* box, CUtensorMapSwizzle swz) {
  cuuint32_t es[5] = {1, 1, 1, 1, 1};
  fn(m, CU_TENSOR_MAP_DATA_TYPE_BFLOAT16, rank, const_cast<void*>(ptr), dims, strides, box, es, CU_TENSOR_MAP_INTERLEAVE_NONE,
     swz, CU_TENSOR_MAP_L2_PROMOTION_L2_128B, CU_TENSOR_MAP_FLOAT_OOB_FILL_NONE);
}
}

extern "C" void kernel_launch(void* const* d_in, const int* in_sizes, int n_in, void* d_out, int out_size) {
  (void)in_sizes; (void)n_in; (void)out_size;
  const __nv_bfloat16* x = (const __nv_bfloat16*)d_in[0];
  const __nv_bfloat16* wqkv = (const __nv_bfloat16*)d_in[1];
  const __nv_bfloat16* wphi = (const __nv_bfloat16*)d_in[2];
  const __nv_bfloat16* wo = (const __nv_bfloat16*)d_in[3];
  const __nv_bfloat16* w1 = (const __nv_bfloat16*)d_in[5];
  const __nv_bfloat16* w2 = (const __nv_bfloat16*)d_in[6];
  const __nv_bfloat16* w3 = (const __nv_bfloat16*)d_in[7];
  const __nv_bfloat16* w4 = (const __nv_bfloat16*)d_in[8];
  const __nv_bfloat16* gate_w = (const __nv_bfloat16*)d_in[9];

  static EncodeFn enc = nullptr;
  static void *pHs = nullptr, *pX1 = nullptr;
  if (!enc) {
    cudaDriverEntryPointQueryResult qr;
    cudaGetDriverEntryPoint("cuTensorMapEncodeTiled", (void**)&enc, cudaEnableDefault, &qr);
    cudaGetSymbolAddress(&pHs, g_Hs);
    cudaGetSymbolAddress(&pX1, g_X1);
    cudaFuncSetAttribute(fused_kernel, cudaFuncAttributeMaxDynamicSharedMemorySize, SMEM_BYTES);
  }
  Maps m;
  {
    cuuint64_t dims[2] = {D_, S_}, str[1] = {D_ * 2};
    cuuint32_t boxh[2] = {64, 64};
    encode(enc, &m.x, x, 2, dims, str, boxh, CU_TENSOR_MAP_SWIZZLE_128B);
    encode(enc, &m.hs, (const char*)pHs + 2 * D_ * 2, 2, dims, str, boxh, CU_TENSOR_MAP_SWIZZLE_128B);
    encode(enc, &m.x1, pX1, 2, dims, str, boxh, CU_TENSOR_MAP_SWIZZLE_128B);
    cuuint32_t boxs[2] = {80, 64};
    cuuint64_t dimsp[2] = {D_, S_ + 4};
    encode(enc, &m.st_h, pHs, 2, dimsp, str, boxs, CU_TENSOR_MAP_SWIZZLE_NONE);
    encode(enc, &m.st_x1, pX1, 2, dims, str, boxs, CU_TENSOR_MAP_SWIZZLE_NONE);
    encode(enc, &m.st_out, d_out, 2, dims, str, boxs, CU_TENSOR_MAP_SWIZZLE_NONE);
    cuuint32_t boxr[2] = {80, 128};
    encode(enc, &m.xr, x, 2, dims, str, boxr, CU_TENSOR_MAP_SWIZZLE_NONE);
  }
  {
    cuuint64_t dims[3] = {80, D_, 8}, str[2] = {D_ * 2, 160};
    cuuint32_t boxm[3] = {64, 64, 1}, boxr[3] = {16, 64, 1}, boxom[3] = {64, 80, 1}, boxor[3] = {16, 80, 1};
    cuuint64_t dims4[3] = {80, F_, 8};
    encode(enc, &m.w1m, w1, 3, dims, str, boxm, CU_TENSOR_MAP_SWIZZLE_128B);
    encode(enc, &m.w1r, w1, 3, dims, str, boxr, CU_TENSOR_MAP_SWIZZLE_32B);
    encode(enc, &m.w4m, w4, 3, dims4, str, boxm, CU_TENSOR_MAP_SWIZZLE_128B);
    encode(enc, &m.w4r, w4, 3, dims4, str, boxr, CU_TENSOR_MAP_SWIZZLE_32B);
    encode(enc, &m.wom, wo, 3, dims, str, boxom, CU_TENSOR_MAP_SWIZZLE_128B);
    encode(enc, &m.wor, wo, 3, dims, str, boxor, CU_TENSOR_MAP_SWIZZLE_32B);
  }
  {
    cuuint64_t dims[4] = {80, D_, 3, 8}, str[3] = {3 * D_ * 2, D_ * 2, 160};
    cuuint32_t boxm[4] = {64, 64, 3, 1}, boxr[4] = {16, 64, 3, 1};
    encode(enc, &m.qm, wqkv, 4, dims, str, boxm, CU_TENSOR_MAP_SWIZZLE_128B);
    encode(enc, &m.qr, wqkv, 4, dims, str, boxr, CU_TENSOR_MAP_SWIZZLE_32B);
  }
  {
    cuuint64_t dims[3] = {16, D_, 40}, str[2] = {D_ * 2, 32};
    cuuint32_t box2[3] = {16, 128, 5};
    encode(enc, &m.w2, w2, 3, dims, str, box2, CU_TENSOR_MAP_SWIZZLE_32B);
  }
  {
    cuuint64_t dims[3] = {64, D_, 24}, str[2] = {F_ * 2, 128};
    cuuint32_t box[3] = {64, 64, 3};
    encode(enc, &m.w3, w3, 3, dims, str, box, CU_TENSOR_MAP_SWIZZLE_128B);
  }
  fused_kernel<<<NCTA, 384, SMEM_BYTES, cudaStreamPerThread>>>(m, x, wqkv, wphi, w1, w2, w3, w4, wo, gate_w);
}
```

```cpp
#include <cuda_runtime.h>
#include <cuda_bf16.h>
#include <cuda.h>
#include <stdint.h>

namespace {

constexpr int S_ = 2048, D_ = 640, F_ = 1536;
constexpr int NCTA = 128;
constexpr int KV_PAIR = 40 * 48 + 96;
constexpr int KV_J = 2 * KV_PAIR;

constexpr int SLOT_B = 49152, NB = 3;
constexpr int SLOT_A = 16384, NA = 4;
constexpr int OFF_B = 0;
constexpr int OFF_A = OFF_B + NB * SLOT_B;
constexpr int OFF_STG = OFF_A + 2 * SLOT_A;
constexpr int OFF_MISC = OFF_A + NA * SLOT_A;
constexpr int OFF_XST = OFF_MISC + 13312;
constexpr int OFF_CS = OFF_MISC + 16384;
constexpr int OFF_BAR = OFF_CS + 1088;
constexpr int SMEM_BYTES = OFF_BAR + 512;
constexpr int B_FULLA = 0, B_FULLB = 4, B_CS = 7, B_XR = 8, B_KV = 9, B_ST1 = 10, B_SDONE = 11  , B_RDY = 17  ,
              B_FULL4 = 23  , B_DSR = 28  , B_SEND = 36  , B_EMPTYB = 42  ,
              B_SIGP = 45, B_SIGH = 46, B_SIGKV = 47, B_SIGX1 = 48, B_MFREE = 49, B_PEER = 50, B_EMPTY4 = 51  ,
              B_EMPTYA = 56  , NBAR = 60;
constexpr int SPARE = 40960;
constexpr int UNIT4 = 25600, NU4 = 5;
constexpr int OFF_DS = OFF_A, OFF_SEND = OFF_A + 40960, OFF_G0 = OFF_A + 61440, OFF_G1 = OFF_B + UNIT4;

constexpr int FL_DONE = 0, FL_H = 1, FL_X1 = FL_H + 16, FL_KV = FL_X1 + 16, FL_CS = FL_KV + 8, FL_CS3 = FL_CS + 8, FL_ST = FL_CS3 + 8, FL_PART = FL_ST + 16;
constexpr int FL_COUNT = FL_PART + 16 * 8;
constexpr int ACC_FLOATS = 8 * KV_J + D_ + F_;

struct Maps {
  CUtensorMap x, w1m, w1r, qm, qr, hs, w2, x1, w3, w4m, w4r, wom, wor, st_h, st_x1, st_out, xr;
};

}

__device__ __align__(1024) __nv_bfloat16 g_Hs[(S_ + 4) * D_];
__device__ __align__(1024) __nv_bfloat16 g_X1[S_ * D_];
__device__ __align__(128) float g_acc[2][ACC_FLOATS];
__device__ __align__(128) float4 g_xstat[S_];
__device__ __align__(128) float2 g_st1[S_ * 8];
__device__ __align__(128) uint4 g_part[16 * 8 * 3 * 1280];
__device__ __align__(128) unsigned g_flags[FL_COUNT * 32];
#define TSTAMP(n) do {} while (0)
#define TSTAMPX(n) do {} while (0)
#define TRACE(n) do {} while (0)
#define TR4(n) do {} while (0)

namespace {

__device__ __forceinline__ long long gtime() { long long t; asm volatile("mov.u64 %0, %%globaltimer;" : "=l"(t)); return t; }
__device__ __forceinline__ uint32_t smem_u32(const void* p) { return (uint32_t)__cvta_generic_to_shared(p); }
__device__ __forceinline__ void mbar_init(uint32_t bar, int cnt) {
  asm volatile("mbarrier.init.shared::cta.b64 [%0], %1;" ::"r"(bar), "r"(cnt) : "memory");
}
__device__ __forceinline__ void mbar_expect_tx(uint32_t bar, int bytes) {
  asm volatile("mbarrier.arrive.expect_tx.shared::cta.b64 _, [%0], %1;" ::"r"(bar), "r"(bytes) : "memory");
}
__device__ __forceinline__ void mbar_arrive_cta(uint32_t bar, uint32_t cta) {
  asm volatile("{\n.reg .b32 ra;\nmapa.shared::cluster.u32 ra, %0, %1;\nmbarrier.arrive.shared::cluster.b64 _, [ra];\n}"
               ::"r"(bar), "r"(cta) : "memory");
}
__device__ __forceinline__ uint32_t mbar_try(uint32_t bar, uint32_t parity) {
  uint32_t ok;
  asm volatile("{\n.reg .pred p;\nmbarrier.try_wait.parity.shared::cta.b64 p, [%1], %2;\nselp.u32 %0, 1, 0, p;\n}"
               : "=r"(ok) : "r"(bar), "r"(parity) : "memory");
  return ok;
}
constexpr uint32_t WAIT_LIMIT = 1u << 22;
__device__ __forceinline__ void mbar_wait(uint32_t bar, uint32_t parity) {
  uint32_t n = 0;
  while (!mbar_try(bar, parity) && ++n < WAIT_LIMIT) {}
}
__device__ __forceinline__ unsigned ld_acquire(const unsigned* p) {
  unsigned v;
  asm volatile("ld.acquire.gpu.global.u32 %0, [%1];" : "=r"(v) : "l"(p) : "memory");
  return v;
}
__device__ __forceinline__ void flag_wait(int idx, unsigned target) {
  const unsigned* p = g_flags + idx * 32;
  uint32_t n = 0;
  while ((int)(ld_acquire(p) - target) < 0 && ++n < (WAIT_LIMIT >> 4)) {}
}
__device__ __forceinline__ void flag_add(int idx) {
  asm volatile("red.release.gpu.global.add.u32 [%0], 1;" ::"l"(g_flags + idx * 32) : "memory");
}
__device__ __forceinline__ void flag_add_relaxed(int idx) {
  asm volatile("red.relaxed.gpu.global.add.u32 [%0], 1;" ::"l"(g_flags + idx * 32) : "memory");
}
__device__ __forceinline__ uint32_t mbar_test(uint32_t bar, uint32_t parity) {
  uint32_t ok;
  asm volatile("{\n.reg .pred p;\nmbarrier.test_wait.parity.shared::cta.b64 p, [%1], %2;\nselp.u32 %0, 1, 0, p;\n}"
               : "=r"(ok) : "r"(bar), "r"(parity) : "memory");
  return ok;
}
__device__ __forceinline__ uint32_t lds32(uint32_t a) {
  uint32_t v;
  asm volatile("ld.shared.u32 %0, [%1];" : "=r"(v) : "r"(a) : "memory");
  return v;
}
__device__ __forceinline__ void mbar_arrive(uint32_t bar) {
  asm volatile("mbarrier.arrive.shared::cta.b64 _, [%0];" ::"r"(bar) : "memory");
}
__device__ __forceinline__ void fence_async_all() { asm volatile("fence.proxy.async;" ::: "memory"); }
__device__ __forceinline__ void fence_async_smem() { asm volatile("fence.proxy.async.shared::cta;" ::: "memory"); }
__device__ __forceinline__ void bar_sync(int id, int n) { asm volatile("bar.sync %0, %1;" ::"r"(id), "r"(n) : "memory"); }

__device__ __forceinline__ void tma2d(uint32_t dst, const CUtensorMap* m, uint32_t bar, int c0, int c1) {
  asm volatile("cp.async.bulk.tensor.2d.shared::cluster.global.mbarrier::complete_tx::bytes [%0], [%1, {%3, %4}], [%2];"
               ::"r"(dst), "l"(m), "r"(bar), "r"(c0), "r"(c1) : "memory");
}
__device__ __forceinline__ void tma2d_mc(uint32_t dst, const CUtensorMap* m, uint32_t bar, int c0, int c1) {
  asm volatile("cp.async.bulk.tensor.2d.shared::cluster.global.mbarrier::complete_tx::bytes.multicast::cluster"
               " [%0], [%1, {%3, %4}], [%2], %5;"
               ::"r"(dst), "l"(m), "r"(bar), "r"(c0), "r"(c1), "h"((uint16_t)3) : "memory");
}
__device__ __forceinline__ void tma3d(uint32_t dst, const CUtensorMap* m, uint32_t bar, int c0, int c1, int c2) {
  asm volatile("cp.async.bulk.tensor.3d.shared::cluster.global.mbarrier::complete_tx::bytes [%0], [%1, {%3, %4, %5}], [%2];"
               ::"r"(dst), "l"(m), "r"(bar), "r"(c0), "r"(c1), "r"(c2) : "memory");
}
__device__ __forceinline__ void tma4d(uint32_t dst, const CUtensorMap* m, uint32_t bar, int c0, int c1, int c2, int c3) {
  asm volatile("cp.async.bulk.tensor.4d.shared::cluster.global.mbarrier::complete_tx::bytes [%0], [%1, {%3, %4, %5, %6}], [%2];"
               ::"r"(dst), "l"(m), "r"(bar), "r"(c0), "r"(c1), "r"(c2), "r"(c3) : "memory");
}
__device__ __forceinline__ void tma2d_store(const CUtensorMap* m, uint32_t src, int c0, int c1) {
  asm volatile("cp.async.bulk.tensor.2d.global.shared::cta.bulk_group [%0, {%2, %3}], [%1];"
               ::"l"(m), "r"(src), "r"(c0), "r"(c1) : "memory");
}
__device__ __forceinline__ void bulk_store(void* dst, uint32_t src, uint32_t bytes) {
  asm volatile("cp.async.bulk.global.shared::cta.bulk_group [%0], [%1], %2;" ::"l"(dst), "r"(src), "r"(bytes) : "memory");
}
__device__ __forceinline__ void bulk_load(uint32_t dst, const void* src, uint32_t bytes, uint32_t bar) {
  asm volatile("cp.async.bulk.shared::cluster.global.mbarrier::complete_tx::bytes [%0], [%1], %2, [%3];"
               ::"r"(dst), "l"(src), "r"(bytes), "r"(bar) : "memory");
}
__device__ __forceinline__ void bulk_commit() { asm volatile("cp.async.bulk.commit_group;" ::: "memory"); }
template <int N> __device__ __forceinline__ void bulk_wait() { asm volatile("cp.async.bulk.wait_group %0;" ::"n"(N) : "memory"); }
__device__ __forceinline__ void bulk_wait_read() { asm volatile("cp.async.bulk.wait_group.read 0;" ::: "memory"); }
__device__ __forceinline__ void bar_arrive(int id, int n) { asm volatile("bar.arrive %0, %1;" ::"r"(id), "r"(n) : "memory"); }
__device__ __forceinline__ uint4 lds128(uint32_t a) {
  uint4 v;
  asm volatile("ld.shared.v4.u32 {%0, %1, %2, %3}, [%4];" : "=r"(v.x), "=r"(v.y), "=r"(v.z), "=r"(v.w) : "r"(a) : "memory");
  return v;
}
__device__ __forceinline__ void sts128(uint32_t a, uint4 v) {
  asm volatile("st.shared.v4.u32 [%0], {%1, %2, %3, %4};" ::"r"(a), "r"(v.x), "r"(v.y), "r"(v.z), "r"(v.w) : "memory");
}
__device__ __forceinline__ uint32_t map_peer(uint32_t addr, uint32_t cta) {
  uint32_t r;
  asm("mapa.shared::cluster.u32 %0, %1, %2;" : "=r"(r) : "r"(addr), "r"(cta));
  return r;
}
__device__ __forceinline__ void st_async16(uint32_t addr, uint32_t a, uint32_t b, uint32_t c, uint32_t d, uint32_t bar) {
  asm volatile("st.async.weak.shared::cluster.mbarrier::complete_tx::bytes.v4.b32 [%0], {%1, %2, %3, %4}, [%5];"
               ::"r"(addr), "r"(a), "r"(b), "r"(c), "r"(d), "r"(bar) : "memory");
}
__device__ __forceinline__ void l2_prefetch(const void* p, uint32_t bytes) {
  asm volatile("cp.async.bulk.prefetch.L2.global [%0], %1;" ::"l"(p), "r"(bytes) : "memory");
}
__device__ __forceinline__ void prefetch_tmap(const CUtensorMap* m) {
  asm volatile("prefetch.tensormap [%0];" ::"l"(m) : "memory");
}
__device__ __forceinline__ uint64_t make_desc(uint32_t a16, uint32_t off, uint32_t lbo, uint32_t sbo, uint32_t swz) {
  const uint32_t lo = a16 + ((off >> 4) + ((lbo >> 4) << 16)), hi = (sbo >> 4) | (swz << 30);
  uint64_t d;
  asm("mov.b64 %0, {%1, %2};" : "=l"(d) : "r"(lo), "r"(hi));
  return d;
}
__device__ __forceinline__ void wg_fence() { asm volatile("wgmma.fence.sync.aligned;" ::: "memory"); }
__device__ __forceinline__ void wg_commit() { asm volatile("wgmma.commit_group.sync.aligned;" ::: "memory"); }
template <int N> __device__ __forceinline__ void wg_wait() { asm volatile("wgmma.wait_group.sync.aligned %0;" ::"n"(N) : "memory"); }
template <int N> __device__ __forceinline__ void fence_regs(float (&d)[N]) {
#pragma unroll
  for (int i = 0; i < N; i++) asm volatile("" : "+f"(d[i])::"memory");
}
template <int N> __device__ __forceinline__ void zero_regs(float (&d)[N]) {
#pragma unroll
  for (int i = 0; i < N; i++) d[i] = 0.f;
}
__device__ __forceinline__ uint32_t pack_bf16(float lo, float hi) {
  uint32_t r;
  asm("cvt.rn.bf16x2.f32 %0, %1, %2;" : "=r"(r) : "f"(hi), "f"(lo));
  return r;
}
__device__ __forceinline__ float bf_lo(uint32_t v) { return __uint_as_float(v << 16); }
__device__ __forceinline__ float bf_hi(uint32_t v) { return __uint_as_float(v & 0xffff0000u); }
__device__ __forceinline__ uint32_t max_bf2(uint32_t a, uint32_t b) {
  uint32_t r; asm("max.bf16x2 %0, %1, %2;" : "=r"(r) : "r"(a), "r"(b)); return r;
}
__device__ __forceinline__ uint32_t min_bf2(uint32_t a, uint32_t b) {
  uint32_t r; asm("min.bf16x2 %0, %1, %2;" : "=r"(r) : "r"(a), "r"(b)); return r;
}
__device__ __forceinline__ float ex2(float x) { float r; asm("ex2.approx.ftz.f32 %0, %1;" : "=f"(r) : "f"(x)); return r; }
__device__ __forceinline__ float rcp(float x) { float r; asm("rcp.approx.ftz.f32 %0, %1;" : "=f"(r) : "f"(x)); return r; }
__device__ __forceinline__ float tanh_ap(float x) { float r; asm("tanh.approx.f32 %0, %1;" : "=f"(r) : "f"(x)); return r; }
__device__ __forceinline__ float gelu_s(float x, float hs) {
  float u = x * fmaf(x * x, 0.0356774081f, 0.7978845608f);
  float hx = x * hs;
  return fmaf(hx, tanh_ap(u), hx);
}
__device__ __forceinline__ void stsm4(uint32_t addr, uint32_t r0, uint32_t r1, uint32_t r2, uint32_t r3) {
  asm volatile("stmatrix.sync.aligned.m8n8.x4.shared.b16 [%0], {%1, %2, %3, %4};"
               ::"r"(addr), "r"(r0), "r"(r1), "r"(r2), "r"(r3) : "memory");
}
__device__ __forceinline__ void red_add4(float* p, float a, float b, float c, float d) {
  asm volatile("red.global.add.v4.f32 [%0], {%1, %2, %3, %4};" ::"l"(p), "f"(a), "f"(b), "f"(c), "f"(d) : "memory");
}
__device__ __forceinline__ void red_add2(float* p, float a, float b) {
  asm volatile("red.global.add.v2.f32 [%0], {%1, %2};" ::"l"(p), "f"(a), "f"(b) : "memory");
}

__device__ __forceinline__ void mma_ss256(float (&d)[128], uint64_t descA, uint64_t descB) {
  asm volatile("wgmma.mma_async.sync.aligned.m64n256k16.f32.bf16.bf16 {"
      "%0, %1, %2, %3, %4, %5, %6, %7, %8, %9, %10, %11, %12, %13, %14, %15, "
      "%16, %17, %18, %19, %20, %21, %22, %23, %24, %25, %26, %27, %28, %29, %30, %31, "
      "%32, %33, %34, %35, %36, %37, %38, %39, %40, %41, %42, %43, %44, %45, %46, %47, "
      "%48, %49, %50, %51, %52, %53, %54, %55, %56, %57, %58, %59, %60, %61, %62, %63, "
      "%64, %65, %66, %67, %68, %69, %70, %71, %72, %73, %74, %75, %76, %77, %78, %79, "
      "%80, %81, %82, %83, %84, %85, %86, %87, %88, %89, %90, %91, %92, %93, %94, %95, "
      "%96, %97, %98, %99, %100, %101, %102, %103, %104, %105, %106, %107, %108, %109, %110, %111, "
      "%112, %113, %114, %115, %116, %117, %118, %119, %120, %121, %122, %123, %124, %125, %126, %127"
      "}, %128, %129, 1, 1, 1, 0, 1;\n"
      : "+f"(d[0]), "+f"(d[1]), "+f"(d[2]), "+f"(d[3]), "+f"(d[4]), "+f"(d[5]), "+f"(d[6]), "+f"(d[7]),
        "+f"(d[8]), "+f"(d[9]), "+f"(d[10]), "+f"(d[11]), "+f"(d[12]), "+f"(d[13]), "+f"(d[14]), "+f"(d[15]),
        "+f"(d[16]), "+f"(d[17]), "+f"(d[18]), "+f"(d[19]), "+f"(d[20]), "+f"(d[21]), "+f"(d[22]), "+f"(d[23]),
        "+f"(d[24]), "+f"(d[25]), "+f"(d[26]), "+f"(d[27]), "+f"(d[28]), "+f"(d[29]), "+f"(d[30]), "+f"(d[31]),
        "+f"(d[32]), "+f"(d[33]), "+f"(d[34]), "+f"(d[35]), "+f"(d[36]), "+f"(d[37]), "+f"(d[38]), "+f"(d[39]),
        "+f"(d[40]), "+f"(d[41]), "+f"(d[42]), "+f"(d[43]), "+f"(d[44]), "+f"(d[45]), "+f"(d[46]), "+f"(d[47]),
        "+f"(d[48]), "+f"(d[49]), "+f"(d[50]), "+f"(d[51]), "+f"(d[52]), "+f"(d[53]), "+f"(d[54]), "+f"(d[55]),
        "+f"(d[56]), "+f"(d[57]), "+f"(d[58]), "+f"(d[59]), "+f"(d[60]), "+f"(d[61]), "+f"(d[62]), "+f"(d[63]),
        "+f"(d[64]), "+f"(d[65]), "+f"(d[66]), "+f"(d[67]), "+f"(d[68]), "+f"(d[69]), "+f"(d[70]), "+f"(d[71]),
        "+f"(d[72]), "+f"(d[73]), "+f"(d[74]), "+f"(d[75]), "+f"(d[76]), "+f"(d[77]), "+f"(d[78]), "+f"(d[79]),
        "+f"(d[80]), "+f"(d[81]), "+f"(d[82]), "+f"(d[83]), "+f"(d[84]), "+f"(d[85]), "+f"(d[86]), "+f"(d[87]),
        "+f"(d[88]), "+f"(d[89]), "+f"(d[90]), "+f"(d[91]), "+f"(d[92]), "+f"(d[93]), "+f"(d[94]), "+f"(d[95]),
        "+f"(d[96]), "+f"(d[97]), "+f"(d[98]), "+f"(d[99]), "+f"(d[100]), "+f"(d[101]), "+f"(d[102]), "+f"(d[103]),
        "+f"(d[104]), "+f"(d[105]), "+f"(d[106]), "+f"(d[107]), "+f"(d[108]), "+f"(d[109]), "+f"(d[110]), "+f"(d[111]),
        "+f"(d[112]), "+f"(d[113]), "+f"(d[114]), "+f"(d[115]), "+f"(d[116]), "+f"(d[117]), "+f"(d[118]), "+f"(d[119]),
        "+f"(d[120]), "+f"(d[121]), "+f"(d[122]), "+f"(d[123]), "+f"(d[124]), "+f"(d[125]), "+f"(d[126]), "+f"(d[127])
      : "l"(descA), "l"(descB));
}

__device__ __forceinline__ void mma_ss64(float (&d)[32], uint64_t descA, uint64_t descB) {
  asm volatile("wgmma.mma_async.sync.aligned.m64n64k16.f32.bf16.bf16 {"
      "%0, %1, %2, %3, %4, %5, %6, %7, %8, %9, %10, %11, %12, %13, %14, %15, "
      "%16, %17, %18, %19, %20, %21, %22, %23, %24, %25, %26, %27, %28, %29, %30, %31"
      "}, %32, %33, 1, 1, 1, 0, 1;\n"
      : "+f"(d[0]), "+f"(d[1]), "+f"(d[2]), "+f"(d[3]), "+f"(d[4]), "+f"(d[5]), "+f"(d[6]), "+f"(d[7]),
        "+f"(d[8]), "+f"(d[9]), "+f"(d[10]), "+f"(d[11]), "+f"(d[12]), "+f"(d[13]), "+f"(d[14]), "+f"(d[15]),
        "+f"(d[16]), "+f"(d[17]), "+f"(d[18]), "+f"(d[19]), "+f"(d[20]), "+f"(d[21]), "+f"(d[22]), "+f"(d[23]),
        "+f"(d[24]), "+f"(d[25]), "+f"(d[26]), "+f"(d[27]), "+f"(d[28]), "+f"(d[29]), "+f"(d[30]), "+f"(d[31])
      : "l"(descA), "l"(descB));
}

__device__ __forceinline__ void mma_ss80(float (&d)[40], uint64_t descA, uint64_t descB) {
  asm volatile("wgmma.mma_async.sync.aligned.m64n80k16.f32.bf16.bf16 {"
      "%0, %1, %2, %3, %4, %5, %6, %7, %8, %9, %10, %11, %12, %13, %14, %15, "
      "%16, %17, %18, %19, %20, %21, %22, %23, %24, %25, %26, %27, %28, %29, %30, %31, "
      "%32, %33, %34, %35, %36, %37, %38, %39"
      "}, %40, %41, 1, 1, 1, 0, 1;\n"
      : "+f"(d[0]), "+f"(d[1]), "+f"(d[2]), "+f"(d[3]), "+f"(d[4]), "+f"(d[5]), "+f"(d[6]), "+f"(d[7]),
        "+f"(d[8]), "+f"(d[9]), "+f"(d[10]), "+f"(d[11]), "+f"(d[12]), "+f"(d[13]), "+f"(d[14]), "+f"(d[15]),
        "+f"(d[16]), "+f"(d[17]), "+f"(d[18]), "+f"(d[19]), "+f"(d[20]), "+f"(d[21]), "+f"(d[22]), "+f"(d[23]),
        "+f"(d[24]), "+f"(d[25]), "+f"(d[26]), "+f"(d[27]), "+f"(d[28]), "+f"(d[29]), "+f"(d[30]), "+f"(d[31]),
        "+f"(d[32]), "+f"(d[33]), "+f"(d[34]), "+f"(d[35]), "+f"(d[36]), "+f"(d[37]), "+f"(d[38]), "+f"(d[39])
      : "l"(descA), "l"(descB));
}

__device__ __forceinline__ void mma_ss192(float (&d)[96], uint64_t descA, uint64_t descB) {
  asm volatile("wgmma.mma_async.sync.aligned.m64n192k16.f32.bf16.bf16 {"
      "%0, %1, %2, %3, %4, %5, %6, %7, %8, %9, %10, %11, %12, %13, %14, %15, "
      "%16, %17, %18, %19, %20, %21, %22, %23, %24, %25, %26, %27, %28, %29, %30, %31, "
      "%32, %33, %34, %35, %36, %37, %38, %39, %40, %41, %42, %43, %44, %45, %46, %47, "
      "%48, %49, %50, %51, %52, %53, %54, %55, %56, %57, %58, %59, %60, %61, %62, %63, "
      "%64, %65, %66, %67, %68, %69, %70, %71, %72, %73, %74, %75, %76, %77, %78, %79, "
      "%80, %81, %82, %83, %84, %85, %86, %87, %88, %89, %90, %91, %92, %93, %94, %95"
      "}, %96, %97, 1, 1, 1, 0, 1;\n"
      : "+f"(d[0]), "+f"(d[1]), "+f"(d[2]), "+f"(d[3]), "+f"(d[4]), "+f"(d[5]), "+f"(d[6]), "+f"(d[7]),
        "+f"(d[8]), "+f"(d[9]), "+f"(d[10]), "+f"(d[11]), "+f"(d[12]), "+f"(d[13]), "+f"(d[14]), "+f"(d[15]),
        "+f"(d[16]), "+f"(d[17]), "+f"(d[18]), "+f"(d[19]), "+f"(d[20]), "+f"(d[21]), "+f"(d[22]), "+f"(d[23]),
        "+f"(d[24]), "+f"(d[25]), "+f"(d[26]), "+f"(d[27]), "+f"(d[28]), "+f"(d[29]), "+f"(d[30]), "+f"(d[31]),
        "+f"(d[32]), "+f"(d[33]), "+f"(d[34]), "+f"(d[35]), "+f"(d[36]), "+f"(d[37]), "+f"(d[38]), "+f"(d[39]),
        "+f"(d[40]), "+f"(d[41]), "+f"(d[42]), "+f"(d[43]), "+f"(d[44]), "+f"(d[45]), "+f"(d[46]), "+f"(d[47]),
        "+f"(d[48]), "+f"(d[49]), "+f"(d[50]), "+f"(d[51]), "+f"(d[52]), "+f"(d[53]), "+f"(d[54]), "+f"(d[55]),
        "+f"(d[56]), "+f"(d[57]), "+f"(d[58]), "+f"(d[59]), "+f"(d[60]), "+f"(d[61]), "+f"(d[62]), "+f"(d[63]),
        "+f"(d[64]), "+f"(d[65]), "+f"(d[66]), "+f"(d[67]), "+f"(d[68]), "+f"(d[69]), "+f"(d[70]), "+f"(d[71]),
        "+f"(d[72]), "+f"(d[73]), "+f"(d[74]), "+f"(d[75]), "+f"(d[76]), "+f"(d[77]), "+f"(d[78]), "+f"(d[79]),
        "+f"(d[80]), "+f"(d[81]), "+f"(d[82]), "+f"(d[83]), "+f"(d[84]), "+f"(d[85]), "+f"(d[86]), "+f"(d[87]),
        "+f"(d[88]), "+f"(d[89]), "+f"(d[90]), "+f"(d[91]), "+f"(d[92]), "+f"(d[93]), "+f"(d[94]), "+f"(d[95])
      : "l"(descA), "l"(descB));
}

__device__ __forceinline__ void mma_ss80_tt(float (&d)[40], uint64_t descA, uint64_t descB) {
  asm volatile("wgmma.mma_async.sync.aligned.m64n80k16.f32.bf16.bf16 {"
      "%0, %1, %2, %3, %4, %5, %6, %7, %8, %9, %10, %11, %12, %13, %14, %15, "
      "%16, %17, %18, %19, %20, %21, %22, %23, %24, %25, %26, %27, %28, %29, %30, %31, "
      "%32, %33, %34, %35, %36, %37, %38, %39"
      "}, %40, %41, 1, 1, 1, 1, 1;\n"
      : "+f"(d[0]), "+f"(d[1]), "+f"(d[2]), "+f"(d[3]), "+f"(d[4]), "+f"(d[5]), "+f"(d[6]), "+f"(d[7]),
        "+f"(d[8]), "+f"(d[9]), "+f"(d[10]), "+f"(d[11]), "+f"(d[12]), "+f"(d[13]), "+f"(d[14]), "+f"(d[15]),
        "+f"(d[16]), "+f"(d[17]), "+f"(d[18]), "+f"(d[19]), "+f"(d[20]), "+f"(d[21]), "+f"(d[22]), "+f"(d[23]),
        "+f"(d[24]), "+f"(d[25]), "+f"(d[26]), "+f"(d[27]), "+f"(d[28]), "+f"(d[29]), "+f"(d[30]), "+f"(d[31]),
        "+f"(d[32]), "+f"(d[33]), "+f"(d[34]), "+f"(d[35]), "+f"(d[36]), "+f"(d[37]), "+f"(d[38]), "+f"(d[39])
      : "l"(descA), "l"(descB));
}
__device__ __forceinline__ void mma_ss80_tt_z(float (&d)[40], uint64_t descA, uint64_t descB) {
  asm volatile("wgmma.mma_async.sync.aligned.m64n80k16.f32.bf16.bf16 {"
      "%0, %1, %2, %3, %4, %5, %6, %7, %8, %9, %10, %11, %12, %13, %14, %15, "
      "%16, %17, %18, %19, %20, %21, %22, %23, %24, %25, %26, %27, %28, %29, %30, %31, "
      "%32, %33, %34, %35, %36, %37, %38, %39"
      "}, %40, %41, 0, 1, 1, 1, 1;\n"
      : "=f"(d[0]), "=f"(d[1]), "=f"(d[2]), "=f"(d[3]), "=f"(d[4]), "=f"(d[5]), "=f"(d[6]), "=f"(d[7]),
        "=f"(d[8]), "=f"(d[9]), "=f"(d[10]), "=f"(d[11]), "=f"(d[12]), "=f"(d[13]), "=f"(d[14]), "=f"(d[15]),
        "=f"(d[16]), "=f"(d[17]), "=f"(d[18]), "=f"(d[19]), "=f"(d[20]), "=f"(d[21]), "=f"(d[22]), "=f"(d[23]),
        "=f"(d[24]), "=f"(d[25]), "=f"(d[26]), "=f"(d[27]), "=f"(d[28]), "=f"(d[29]), "=f"(d[30]), "=f"(d[31]),
        "=f"(d[32]), "=f"(d[33]), "=f"(d[34]), "=f"(d[35]), "=f"(d[36]), "=f"(d[37]), "=f"(d[38]), "=f"(d[39])
      : "l"(descA), "l"(descB));
}

__device__ __forceinline__ void mma_rs80_k(float (&d)[40], const uint32_t (&a)[4], uint64_t descB) {
  asm volatile("wgmma.mma_async.sync.aligned.m64n80k16.f32.bf16.bf16 {"
      "%0, %1, %2, %3, %4, %5, %6, %7, %8, %9, %10, %11, %12, %13, %14, %15, "
      "%16, %17, %18, %19, %20, %21, %22, %23, %24, %25, %26, %27, %28, %29, %30, %31, "
      "%32, %33, %34, %35, %36, %37, %38, %39"
      "}, {%40, %41, %42, %43}, %44, 1, 1, 1, 0;\n"
      : "+f"(d[0]), "+f"(d[1]), "+f"(d[2]), "+f"(d[3]), "+f"(d[4]), "+f"(d[5]), "+f"(d[6]), "+f"(d[7]),
        "+f"(d[8]), "+f"(d[9]), "+f"(d[10]), "+f"(d[11]), "+f"(d[12]), "+f"(d[13]), "+f"(d[14]), "+f"(d[15]),
        "+f"(d[16]), "+f"(d[17]), "+f"(d[18]), "+f"(d[19]), "+f"(d[20]), "+f"(d[21]), "+f"(d[22]), "+f"(d[23]),
        "+f"(d[24]), "+f"(d[25]), "+f"(d[26]), "+f"(d[27]), "+f"(d[28]), "+f"(d[29]), "+f"(d[30]), "+f"(d[31]),
        "+f"(d[32]), "+f"(d[33]), "+f"(d[34]), "+f"(d[35]), "+f"(d[36]), "+f"(d[37]), "+f"(d[38]), "+f"(d[39])
      : "r"(a[0]), "r"(a[1]), "r"(a[2]), "r"(a[3]), "l"(descB));
}
__device__ __forceinline__ void mma_rs80_k_z(float (&d)[40], const uint32_t (&a)[4], uint64_t descB) {
  asm volatile("wgmma.mma_async.sync.aligned.m64n80k16.f32.bf16.bf16 {"
      "%0, %1, %2, %3, %4, %5, %6, %7, %8, %9, %10, %11, %12, %13, %14, %15, "
      "%16, %17, %18, %19, %20, %21, %22, %23, %24, %25, %26, %27, %28, %29, %30, %31, "
      "%32, %33, %34, %35, %36, %37, %38, %39"
      "}, {%40, %41, %42, %43}, %44, 0, 1, 1, 0;\n"
      : "=f"(d[0]), "=f"(d[1]), "=f"(d[2]), "=f"(d[3]), "=f"(d[4]), "=f"(d[5]), "=f"(d[6]), "=f"(d[7]),
        "=f"(d[8]), "=f"(d[9]), "=f"(d[10]), "=f"(d[11]), "=f"(d[12]), "=f"(d[13]), "=f"(d[14]), "=f"(d[15]),
        "=f"(d[16]), "=f"(d[17]), "=f"(d[18]), "=f"(d[19]), "=f"(d[20]), "=f"(d[21]), "=f"(d[22]), "=f"(d[23]),
        "=f"(d[24]), "=f"(d[25]), "=f"(d[26]), "=f"(d[27]), "=f"(d[28]), "=f"(d[29]), "=f"(d[30]), "=f"(d[31]),
        "=f"(d[32]), "=f"(d[33]), "=f"(d[34]), "=f"(d[35]), "=f"(d[36]), "=f"(d[37]), "=f"(d[38]), "=f"(d[39])
      : "r"(a[0]), "r"(a[1]), "r"(a[2]), "r"(a[3]), "l"(descB));
}

__device__ __forceinline__ void mma_rs48_k(float (&d)[24], const uint32_t (&a)[4], uint64_t descB) {
  asm volatile("wgmma.mma_async.sync.aligned.m64n48k16.f32.bf16.bf16 {"
      "%0, %1, %2, %3, %4, %5, %6, %7, %8, %9, %10, %11, %12, %13, %14, %15, "
      "%16, %17, %18, %19, %20, %21, %22, %23"
      "}, {%24, %25, %26, %27}, %28, 1, 1, 1, 0;\n"
      : "+f"(d[0]), "+f"(d[1]), "+f"(d[2]), "+f"(d[3]), "+f"(d[4]), "+f"(d[5]), "+f"(d[6]), "+f"(d[7]),
        "+f"(d[8]), "+f"(d[9]), "+f"(d[10]), "+f"(d[11]), "+f"(d[12]), "+f"(d[13]), "+f"(d[14]), "+f"(d[15]),
        "+f"(d[16]), "+f"(d[17]), "+f"(d[18]), "+f"(d[19]), "+f"(d[20]), "+f"(d[21]), "+f"(d[22]), "+f"(d[23])
      : "r"(a[0]), "r"(a[1]), "r"(a[2]), "r"(a[3]), "l"(descB));
}
__device__ __forceinline__ void mma_rs48_k_z(float (&d)[24], const uint32_t (&a)[4], uint64_t descB) {
  asm volatile("wgmma.mma_async.sync.aligned.m64n48k16.f32.bf16.bf16 {"
      "%0, %1, %2, %3, %4, %5, %6, %7, %8, %9, %10, %11, %12, %13, %14, %15, "
      "%16, %17, %18, %19, %20, %21, %22, %23"
      "}, {%24, %25, %26, %27}, %28, 0, 1, 1, 0;\n"
      : "=f"(d[0]), "=f"(d[1]), "=f"(d[2]), "=f"(d[3]), "=f"(d[4]), "=f"(d[5]), "=f"(d[6]), "=f"(d[7]),
        "=f"(d[8]), "=f"(d[9]), "=f"(d[10]), "=f"(d[11]), "=f"(d[12]), "=f"(d[13]), "=f"(d[14]), "=f"(d[15]),
        "=f"(d[16]), "=f"(d[17]), "=f"(d[18]), "=f"(d[19]), "=f"(d[20]), "=f"(d[21]), "=f"(d[22]), "=f"(d[23])
      : "r"(a[0]), "r"(a[1]), "r"(a[2]), "r"(a[3]), "l"(descB));
}

__device__ __forceinline__ void mma_rs128_n(float (&d)[64], const uint32_t (&a)[4], uint64_t descB) {
  asm volatile("wgmma.mma_async.sync.aligned.m64n128k16.f32.bf16.bf16 {"
      "%0, %1, %2, %3, %4, %5, %6, %7, %8, %9, %10, %11, %12, %13, %14, %15, "
      "%16, %17, %18, %19, %20, %21, %22, %23, %24, %25, %26, %27, %28, %29, %30, %31, "
      "%32, %33, %34, %35, %36, %37, %38, %39, %40, %41, %42, %43, %44, %45, %46, %47, "
      "%48, %49, %50, %51, %52, %53, %54, %55, %56, %57, %58, %59, %60, %61, %62, %63"
      "}, {%64, %65, %66, %67}, %68, 1, 1, 1, 1;\n"
      : "+f"(d[0]), "+f"(d[1]), "+f"(d[2]), "+f"(d[3]), "+f"(d[4]), "+f"(d[5]), "+f"(d[6]), "+f"(d[7]),
        "+f"(d[8]), "+f"(d[9]), "+f"(d[10]), "+f"(d[11]), "+f"(d[12]), "+f"(d[13]), "+f"(d[14]), "+f"(d[15]),
        "+f"(d[16]), "+f"(d[17]), "+f"(d[18]), "+f"(d[19]), "+f"(d[20]), "+f"(d[21]), "+f"(d[22]), "+f"(d[23]),
        "+f"(d[24]), "+f"(d[25]), "+f"(d[26]), "+f"(d[27]), "+f"(d[28]), "+f"(d[29]), "+f"(d[30]), "+f"(d[31]),
        "+f"(d[32]), "+f"(d[33]), "+f"(d[34]), "+f"(d[35]), "+f"(d[36]), "+f"(d[37]), "+f"(d[38]), "+f"(d[39]),
        "+f"(d[40]), "+f"(d[41]), "+f"(d[42]), "+f"(d[43]), "+f"(d[44]), "+f"(d[45]), "+f"(d[46]), "+f"(d[47]),
        "+f"(d[48]), "+f"(d[49]), "+f"(d[50]), "+f"(d[51]), "+f"(d[52]), "+f"(d[53]), "+f"(d[54]), "+f"(d[55]),
        "+f"(d[56]), "+f"(d[57]), "+f"(d[58]), "+f"(d[59]), "+f"(d[60]), "+f"(d[61]), "+f"(d[62]), "+f"(d[63])
      : "r"(a[0]), "r"(a[1]), "r"(a[2]), "r"(a[3]), "l"(descB));
}
__device__ __forceinline__ void mma_rs128_n_z(float (&d)[64], const uint32_t (&a)[4], uint64_t descB) {
  asm volatile("wgmma.mma_async.sync.aligned.m64n128k16.f32.bf16.bf16 {"
      "%0, %1, %2, %3, %4, %5, %6, %7, %8, %9, %10, %11, %12, %13, %14, %15, "
      "%16, %17, %18, %19, %20, %21, %22, %23, %24, %25, %26, %27, %28, %29, %30, %31, "
      "%32, %33, %34, %35, %36, %37, %38, %39, %40, %41, %42, %43, %44, %45, %46, %47, "
      "%48, %49, %50, %51, %52, %53, %54, %55, %56, %57, %58, %59, %60, %61, %62, %63"
      "}, {%64, %65, %66, %67}, %68, 0, 1, 1, 1;\n"
      : "=f"(d[0]), "=f"(d[1]), "=f"(d[2]), "=f"(d[3]), "=f"(d[4]), "=f"(d[5]), "=f"(d[6]), "=f"(d[7]),
        "=f"(d[8]), "=f"(d[9]), "=f"(d[10]), "=f"(d[11]), "=f"(d[12]), "=f"(d[13]), "=f"(d[14]), "=f"(d[15]),
        "=f"(d[16]), "=f"(d[17]), "=f"(d[18]), "=f"(d[19]), "=f"(d[20]), "=f"(d[21]), "=f"(d[22]), "=f"(d[23]),
        "=f"(d[24]), "=f"(d[25]), "=f"(d[26]), "=f"(d[27]), "=f"(d[28]), "=f"(d[29]), "=f"(d[30]), "=f"(d[31]),
        "=f"(d[32]), "=f"(d[33]), "=f"(d[34]), "=f"(d[35]), "=f"(d[36]), "=f"(d[37]), "=f"(d[38]), "=f"(d[39]),
        "=f"(d[40]), "=f"(d[41]), "=f"(d[42]), "=f"(d[43]), "=f"(d[44]), "=f"(d[45]), "=f"(d[46]), "=f"(d[47]),
        "=f"(d[48]), "=f"(d[49]), "=f"(d[50]), "=f"(d[51]), "=f"(d[52]), "=f"(d[53]), "=f"(d[54]), "=f"(d[55]),
        "=f"(d[56]), "=f"(d[57]), "=f"(d[58]), "=f"(d[59]), "=f"(d[60]), "=f"(d[61]), "=f"(d[62]), "=f"(d[63])
      : "r"(a[0]), "r"(a[1]), "r"(a[2]), "r"(a[3]), "l"(descB));
}

__device__ __forceinline__ void mma_rs32_n(float (&d)[16], const uint32_t (&a)[4], uint64_t descB) {
  asm volatile("wgmma.mma_async.sync.aligned.m64n32k16.f32.bf16.bf16 {"
      "%0, %1, %2, %3, %4, %5, %6, %7, %8, %9, %10, %11, %12, %13, %14, %15"
      "}, {%16, %17, %18, %19}, %20, 1, 1, 1, 1;\n"
      : "+f"(d[0]), "+f"(d[1]), "+f"(d[2]), "+f"(d[3]), "+f"(d[4]), "+f"(d[5]), "+f"(d[6]), "+f"(d[7]),
        "+f"(d[8]), "+f"(d[9]), "+f"(d[10]), "+f"(d[11]), "+f"(d[12]), "+f"(d[13]), "+f"(d[14]), "+f"(d[15])
      : "r"(a[0]), "r"(a[1]), "r"(a[2]), "r"(a[3]), "l"(descB));
}
__device__ __forceinline__ void mma_rs32_n_z(float (&d)[16], const uint32_t (&a)[4], uint64_t descB) {
  asm volatile("wgmma.mma_async.sync.aligned.m64n32k16.f32.bf16.bf16 {"
      "%0, %1, %2, %3, %4, %5, %6, %7, %8, %9, %10, %11, %12, %13, %14, %15"
      "}, {%16, %17, %18, %19}, %20, 0, 1, 1, 1;\n"
      : "=f"(d[0]), "=f"(d[1]), "=f"(d[2]), "=f"(d[3]), "=f"(d[4]), "=f"(d[5]), "=f"(d[6]), "=f"(d[7]),
        "=f"(d[8]), "=f"(d[9]), "=f"(d[10]), "=f"(d[11]), "=f"(d[12]), "=f"(d[13]), "=f"(d[14]), "=f"(d[15])
      : "r"(a[0]), "r"(a[1]), "r"(a[2]), "r"(a[3]), "l"(descB));
}

__device__ __forceinline__ void feature_map(const uint32_t (&P)[2][10], uint32_t (&fr)[10][4]) {
  constexpr float L2E = 1.4426950408889634f;
#pragma unroll
  for (int p = 0; p < 2; p++) {
#pragma unroll
    for (int r = 0; r < 2; r++) {
      uint32_t mx = P[r][5 * p], mn = mx;
#pragma unroll
      for (int g = 1; g < 5; g++) { mx = max_bf2(mx, P[r][5 * p + g]); mn = min_bf2(mn, P[r][5 * p + g]); }
      mx = max_bf2(mx, __shfl_xor_sync(0xffffffffu, mx, 1));
      mn = min_bf2(mn, __shfl_xor_sync(0xffffffffu, mn, 1));
      mx = max_bf2(mx, __shfl_xor_sync(0xffffffffu, mx, 2));
      mn = min_bf2(mn, __shfl_xor_sync(0xffffffffu, mn, 2));
      float mx0 = -bf_lo(mx) * L2E, mx1 = -bf_hi(mx) * L2E, mn0 = bf_lo(mn) * L2E, mn1 = bf_hi(mn) * L2E;
      float ep0[5], ep1[5], en0[5], en1[5];
      float sp0 = 0.f, sp1 = 0.f, sn0 = 0.f, sn1 = 0.f;
#pragma unroll
      for (int g = 0; g < 5; g++) {
        float x0 = bf_lo(P[r][5 * p + g]), x1 = bf_hi(P[r][5 * p + g]);
        ep0[g] = ex2(fmaf(x0, L2E, mx0)); ep1[g] = ex2(fmaf(x1, L2E, mx1));
        en0[g] = ex2(fmaf(x0, -L2E, mn0)); en1[g] = ex2(fmaf(x1, -L2E, mn1));
        sp0 += ep0[g]; sp1 += ep1[g]; sn0 += en0[g]; sn1 += en1[g];
      }
      sp0 += __shfl_xor_sync(0xffffffffu, sp0, 1); sp1 += __shfl_xor_sync(0xffffffffu, sp1, 1);
      sn0 += __shfl_xor_sync(0xffffffffu, sn0, 1); sn1 += __shfl_xor_sync(0xffffffffu, sn1, 1);
      sp0 += __shfl_xor_sync(0xffffffffu, sp0, 2); sp1 += __shfl_xor_sync(0xffffffffu, sp1, 2);
      sn0 += __shfl_xor_sync(0xffffffffu, sn0, 2); sn1 += __shfl_xor_sync(0xffffffffu, sn1, 2);
      sp0 = rcp(sp0); sp1 = rcp(sp1); sn0 = rcp(sn0); sn1 = rcp(sn1);
#pragma unroll
      for (int g = 0; g < 5; g++) {
        fr[5 * p + g][r] = pack_bf16(ep0[g] * sp0, ep1[g] * sp1);
        fr[5 * p + g][2 + r] = pack_bf16(en0[g] * sn0, en1[g] * sn1);
      }
    }
  }
}

struct Ring {
  uint32_t idx, phase;
  template <int N> __device__ __forceinline__ void next() { if (++idx == N) { idx = 0; phase ^= 1; } }
};

}

__global__ void __cluster_dims__(2, 1, 1) __launch_bounds__(384, 1)
fused_kernel(const __grid_constant__ Maps maps, const __nv_bfloat16* __restrict__ x, const __nv_bfloat16* __restrict__ wqkv,
             const __nv_bfloat16* __restrict__ wphi, const __nv_bfloat16* __restrict__ w1, const __nv_bfloat16* __restrict__ w2,
             const __nv_bfloat16* __restrict__ w3, const __nv_bfloat16* __restrict__ w4, const __nv_bfloat16* __restrict__ wo,
             const __nv_bfloat16* __restrict__ gate_w) {
  extern __shared__ __align__(1024) uint8_t sgen[];
  const uint32_t sb = smem_u32(sgen);
  const uint32_t sb16 = (sb & 0x3FFFFu) >> 4;
  const uint32_t bars = sb + OFF_BAR;
  const uint32_t fullA = bars + 8 * B_FULLA, emptyA = bars + 8 * B_EMPTYA, fullB = bars + 8 * B_FULLB, emptyB = bars + 8 * B_EMPTYB;

  const int tid = threadIdx.x;
  const int rank = blockIdx.x & 1;
  const int pairIdx = blockIdx.x >> 1;
  const int i = pairIdx >> 2, j = 2 * (pairIdx & 3) + rank;

  TSTAMP(0);
  uint4 pv[5], pw_[5], pc[2], pre;
  if (tid < 256) {
    const int row = 128 * i + 16 * j + (tid >> 4), l16 = tid & 15;
#pragma unroll
    for (int c = 0; c < 5; c++) pv[c] = __ldg(reinterpret_cast<const uint4*>(x + (size_t)row * D_ + c * 128 + l16 * 8));
    const int tq = tid < 200 ? tid : 0;
    const __nv_bfloat16* cp = w1 + (size_t)(40 * i + tq / 10) * D_ + 80 * j + 8 * (tq % 10);
    pc[0] = __ldg(reinterpret_cast<const uint4*>(cp)); pc[1] = __ldg(reinterpret_cast<const uint4*>(cp + 20 * D_));
    pre = __ldg(reinterpret_cast<const uint4*>(wphi + (size_t)j * 1600) + tq);
#pragma unroll
    for (int c = 0; c < 5; c++) pw_[c] = __ldg(reinterpret_cast<const uint4*>(gate_w + c * 128 + l16 * 8));
  }
  if ((tid & 31) == 0) {
#pragma unroll 1
    for (int b = tid >> 5; b < NBAR; b += 12) {
      mbar_init(bars + 8 * b, b < B_SEND ? 1 : b < B_EMPTYB ? 4 : b < B_EMPTYA ? 8 : 16);
      if (b >= B_DSR && b < B_SEND) mbar_expect_tx(bars + 8 * b, 10240);
    }
    asm volatile("fence.mbarrier_init.release.cluster;" ::: "memory");
  }
  if (tid == 352) { prefetch_tmap(&maps.x); prefetch_tmap(&maps.qm); prefetch_tmap(&maps.w1m); prefetch_tmap(&maps.qr); prefetch_tmap(&maps.w1r); }
  asm volatile("barrier.cluster.arrive.relaxed.aligned;" ::: "memory");

  if (tid >= 256) {
    asm volatile("setmaxnreg.dec.sync.aligned.u32 40;");
    asm volatile("barrier.cluster.wait.aligned;" ::: "memory");
    auto get_epoch = [&]() { return *reinterpret_cast<volatile unsigned*>(g_flags + FL_DONE * 32) / NCTA; };
    const int lane = tid & 31, pw = (tid >> 5) & 3;
    auto send_stream = [&](int w, unsigned ep1) {
#pragma unroll 1
      for (int c = 0; c < 3; c++) {
        const int d = (j + 2 * c + 2) & 7;
        mbar_wait(bars + 8 * (B_SEND + 2 * c + w), 0);
        if (w) TR4(c * 16 + 7);
        bulk_store(g_part + (size_t)((i * 8 + d) * 3 + c) * 1280 + w * 640, sb + OFF_SEND + w * 10240, 10240);
        bulk_commit();
        bulk_wait<0>();
        mbar_arrive(bars + 8 * (B_SDONE + 2 * c + w));
        if (w) TR4(c * 16 + 9);
        asm volatile("st.release.gpu.global.u32 [%0], %1;"
                     ::"l"(g_flags + (FL_PART + i * 8 + d) * 32 + 2 * c + w), "r"(ep1) : "memory");
        if (w) TR4(c * 16 + 10);
      }
    };
    if (pw == 0) {
      if (lane == 0) {
        Ring r{0, 1};
        unsigned ep1 = 0;
#pragma unroll 1
        for (int k = 0; k < 30; k++) {
          if (k == 4) ep1 = get_epoch() + 1;
          if (k == 10 || k == 20) {
            const unsigned tgt = ep1 * 8u;
            const unsigned* f0 = g_flags + (k == 10 ? FL_H + ((i - 1) & 15) : FL_X1 + i) * 32;
            const unsigned* f1 = g_flags + (k == 10 ? FL_H + i : FL_X1 + i) * 32;
            const unsigned* f2 = g_flags + (k == 10 ? FL_H + ((i + 1) & 15) : FL_X1 + i) * 32;
            uint32_t n = 0;
            while (++n < (WAIT_LIMIT >> 4)) {
              unsigned v0, v1, v2;
              asm volatile("ld.relaxed.gpu.global.u32 %0, [%3];\nld.relaxed.gpu.global.u32 %1, [%4];\nld.acquire.gpu.global.u32 %2, [%5];"
                           : "=r"(v0), "=r"(v1), "=r"(v2) : "l"(f0), "l"(f1), "l"(f2) : "memory");
              if ((int)((v0 - tgt) | (v1 - tgt) | (v2 - tgt)) >= 0) break;
            }
            TSTAMPX(k == 10 ? 29 : 30);
          }
          mbar_wait(emptyA + 8 * r.idx, r.phase);
          const uint32_t bar = fullA + 8 * r.idx, slot = sb + OFF_A + r.idx * SLOT_A;
          TRACE(k);
          mbar_expect_tx(bar, SLOT_A);
          tma2d_mc(slot + rank * 8192, k < 10 ? &maps.x : k < 20 ? &maps.hs : &maps.x1, bar, 64 * (k % 10), 128 * i + 64 * rank);
          r.next<NA>();
        }
        send_stream(1, ep1);
      }
    } else if (pw == 1) {
      if (lane == 0) {
        Ring r{0, 1};
#pragma unroll 1
        for (int k = 0; k < 18; k++) {
          mbar_wait(emptyB + 8 * r.idx, r.phase);
          const uint32_t bar = fullB + 8 * r.idx, slot = sb + OFF_B + r.idx * SLOT_B;
          if (k < 10) {
            mbar_expect_tx(bar, 40960);
            tma4d(slot + 8192, &maps.qm, bar, 0, 64 * k, 0, j);
            tma3d(slot, &maps.w1m, bar, 0, 64 * k, j);
            tma4d(slot + 32768 + 2048, &maps.qr, bar, 64, 64 * k, 0, j);
            tma3d(slot + 32768, &maps.w1r, bar, 64, 64 * k, j);
          } else if (k < 13) {
            if (k == 12) mbar_wait(fullA + 8 * 2, 0);
            mbar_expect_tx(bar, k < 12 ? 40960 : 20480);
#pragma unroll 1
            for (int u = 0; u < (k < 12 ? 4 : 2); u++) tma3d(slot + u * 10240, &maps.w2, bar, 0, 256 * (k - 10) + 64 * u, 5 * j);
          } else {
            mbar_expect_tx(bar, 49152);
            tma3d(slot, &maps.w3, bar, 0, 128 * (k - 13), 3 * j);
            tma3d(slot + 24576, &maps.w3, bar, 0, 128 * (k - 13) + 64, 3 * j);
          }
          r.next<NB>();
        }
        Ring r4{0, 1};
#pragma unroll 1
        for (int n = 0; n < 16; n++) {
          if (n == 0 || n == 1 || n == 3) { mbar_wait(emptyB + 8 * r.idx, r.phase); r.next<NB>(); }
          mbar_wait(bars + 8 * (B_EMPTY4 + r4.idx), r4.phase);
          const uint32_t bar = bars + 8 * (B_FULL4 + r4.idx), slot = sb + OFF_B + r4.idx * UNIT4;
          const int u = n & 3, d = (j + 2 + (n >> 2) * 2) & 7;
          const bool isw = u == 3;
          const int k0 = isw ? 80 * j : 192 * j + 64 * u, ms = isw ? 10240 : 8192;
          const CUtensorMap* mm = isw ? &maps.wom : &maps.w4m;
          const CUtensorMap* mr = isw ? &maps.wor : &maps.w4r;
          mbar_expect_tx(bar, isw ? 25600 : 20480);
          tma3d(slot, mm, bar, 0, k0, d);
          tma3d(slot + ms, mm, bar, 0, k0, d ^ 1);
          tma3d(slot + 2 * ms, mr, bar, 64, k0, d);
          tma3d(slot + 2 * ms + (ms >> 2), mr, bar, 64, k0, d ^ 1);
          r4.next<NU4>();
        }
      }
    } else {
      const unsigned epoch = get_epoch();
      float* accg = g_acc[epoch & 1];
      if (pw == 2) {
        {
          float* nxt = g_acc[(epoch + 1) & 1];
          constexpr int PER = ACC_FLOATS / NCTA;
#pragma unroll 1
          for (int e = lane; e < PER; e += 32) nxt[blockIdx.x * PER + e] = 0.f;
        }
        if (lane == 0) {
          flag_wait(FL_CS + j, (epoch + 1) * 16u);
          flag_wait(FL_ST + i, (epoch + 1) * 8u);
          fence_async_all();
          mbar_expect_tx(bars + 8 * B_CS, 320 + 2048);
          bulk_load(sb + OFF_CS, accg + 8 * KV_J + 80 * j, 320, bars + 8 * B_CS);
          bulk_load(sb + OFF_XST, g_xstat + 128 * i, 2048, bars + 8 * B_CS);
          TSTAMPX(21);
          l2_prefetch(w2 + (size_t)blockIdx.x * (D_ * D_ / NCTA), D_ * D_ * 2 / NCTA);
          l2_prefetch(w4 + (size_t)blockIdx.x * (F_ * D_ / NCTA), F_ * D_ * 2 / NCTA);
          l2_prefetch(wo + (size_t)blockIdx.x * (D_ * D_ / NCTA), D_ * D_ * 2 / NCTA);
        }
        __syncwarp();
#pragma unroll 1
        for (int m = 0; m < 6; m++) {
          const int col = 192 * j + 32 * m + 8 * (lane & 3);
          const __nv_bfloat16* p = w3 + (size_t)(40 * i + (lane >> 2) * 5) * F_ + col;
          float a[8];
#pragma unroll
          for (int e = 0; e < 8; e++) a[e] = 0.f;
#pragma unroll
          for (int it = 0; it < 5; it++) {
            const uint4 v = __ldg(reinterpret_cast<const uint4*>(p + (size_t)it * F_));
            a[0] += bf_lo(v.x); a[1] += bf_hi(v.x); a[2] += bf_lo(v.y); a[3] += bf_hi(v.y);
            a[4] += bf_lo(v.z); a[5] += bf_hi(v.z); a[6] += bf_lo(v.w); a[7] += bf_hi(v.w);
          }
#pragma unroll
          for (int e = 0; e < 4; e++) {
            const float snd = (lane & 4) ? a[e] : a[e + 4], keep = (lane & 4) ? a[e + 4] : a[e];
            a[e] = keep + __shfl_xor_sync(0xffffffffu, snd, 4);
            a[e] += __shfl_xor_sync(0xffffffffu, a[e], 8);
            a[e] += __shfl_xor_sync(0xffffffffu, a[e], 16);
          }
          if (lane < 8) red_add4(accg + 8 * KV_J + D_ + col + (lane >> 2) * 4, a[0], a[1], a[2], a[3]);
        }
        __syncwarp();
        if (lane == 0) {
          flag_add(FL_CS3 + j);
          flag_wait(FL_KV + j, (epoch + 1) * 16u);
          fence_async_all();
          mbar_expect_tx(bars + 8 * B_KV, KV_J * 4);
          bulk_load(sb + OFF_MISC, accg + j * KV_J, KV_J * 4, bars + 8 * B_KV);
          TSTAMPX(22);
          mbar_wait(bars + 8 * B_MFREE, 0);
          flag_wait(FL_X1 + i, (epoch + 1) * 8u);
          flag_wait(FL_CS3 + j, (epoch + 1) * 16u);
          fence_async_all();
          mbar_expect_tx(bars + 8 * B_ST1, 8192 + 768);
          bulk_load(sb + OFF_CS + 320, accg + 8 * KV_J + D_ + 192 * j, 768, bars + 8 * B_ST1);
          bulk_load(sb + OFF_MISC, g_st1 + 128 * i * 8, 8192, bars + 8 * B_ST1);
        }
        __syncwarp();
        mbar_wait(bars + 8 * (B_SEND + 1), 0);
        const unsigned* fp = g_flags + (FL_PART + i * 8 + j) * 32 + lane;
        bool seen = lane >= 6;
        uint32_t n = 0;
        while (!__all_sync(0xffffffffu, seen) && ++n < (WAIT_LIMIT >> 4)) {
          if (!seen && ld_acquire(fp) == epoch + 1 && (lane < 2 || mbar_test(bars + 8 * (lane < 4 ? B_SEND + 5 : B_SDONE + lane), 0))) {
            seen = true;
            if (lane & 1) TR4((lane >> 1) * 16 + 11);
            mbar_expect_tx(bars + 8 * (B_RDY + lane), 10240);
            bulk_load(sb + (lane < 2 ? OFF_G0 : lane < 4 ? OFF_G1 : OFF_SEND) + (lane & 1) * 10240, g_part + (size_t)(i * 8 + j) * 3840 + lane * 640, 10240,
                      bars + 8 * (B_RDY + lane));
          }
        }
      } else {
        mbar_wait(bars + 8 * B_SIGP, 0);
        if (lane < 20) {
          float a0 = 0.f, a1 = 0.f, a2 = 0.f, a3 = 0.f;
#pragma unroll 4
          for (int r = 0; r < 20; r++) {
            const uint4 v = lds128(sb + OFF_B + SPARE + r * 320 + lane * 16);
            a0 += __uint_as_float(v.x); a1 += __uint_as_float(v.y); a2 += __uint_as_float(v.z); a3 += __uint_as_float(v.w);
          }
          red_add4(accg + 8 * KV_J + 80 * j + 4 * lane, a0, a1, a2, a3);
        }
        __syncwarp();
      }
      if (pw == 3 && lane == 0) {
        flag_add(FL_CS + j); flag_add_relaxed(FL_ST + i);
        TSTAMPX(20);
        mbar_expect_tx(bars + 8 * B_XR, 20480);
#pragma unroll 1
        for (int u = 0; u < 8; u++)
          tma2d(sb + OFF_B + (u / 3) * SLOT_B + SPARE + (u % 3) * 2560, &maps.xr, bars + 8 * B_XR, 80 * j, 128 * i + 16 * u);
        const int shift = (j < 2) ? 1 : (j < 4) ? -1 : (j < 6) ? 2 : -2;
        if ((shift > 0 && i == 0) || (shift < 0 && i == 15)) {
          const int nz = shift > 0 ? shift : -shift, zr = shift > 0 ? 0 : S_ - nz;
#pragma unroll 1
          for (int e = 0; e < nz * 10; e++)
            reinterpret_cast<uint4*>(g_Hs + (size_t)(2 + zr + e / 10) * D_ + 80 * j)[e % 10] = make_uint4(0, 0, 0, 0);
          fence_async_all();
        }
        prefetch_tmap(&maps.st_h); prefetch_tmap(&maps.st_x1); prefetch_tmap(&maps.hs); prefetch_tmap(&maps.x1); prefetch_tmap(&maps.xr);
        prefetch_tmap(&maps.w2); prefetch_tmap(&maps.w3); prefetch_tmap(&maps.w4m); prefetch_tmap(&maps.w4r); prefetch_tmap(&maps.wom); prefetch_tmap(&maps.wor); prefetch_tmap(&maps.st_out);
        mbar_wait(bars + 8 * B_SIGH, 0);
        TSTAMPX(23);
        tma2d_store(&maps.st_h, sb + OFF_STG, 80 * j, 128 * i + 2 + shift);
        tma2d_store(&maps.st_h, sb + OFF_STG + 10240, 80 * j, 128 * i + 66 + shift);
        bulk_commit(); bulk_wait<0>();
        flag_add(FL_H + i);
        TSTAMPX(24);
        mbar_wait(bars + 8 * B_SIGKV, 0);
        TSTAMPX(25);
        flag_add(FL_KV + j);
        TSTAMPX(26);
        mbar_wait(bars + 8 * B_SIGX1, 0);
        TSTAMPX(27);
        tma2d_store(&maps.st_x1, sb + OFF_STG, 80 * j, 128 * i);
        tma2d_store(&maps.st_x1, sb + OFF_STG + 10240, 80 * j, 128 * i + 64);
        bulk_commit(); bulk_wait<0>();
        flag_add(FL_X1 + i);
        TSTAMPX(28);
        send_stream(0, epoch + 1);
      }
    }
    __syncwarp();
    asm volatile("barrier.cluster.arrive;\nbarrier.cluster.wait;" ::: "memory");
  } else {
    asm volatile("setmaxnreg.inc.sync.aligned.u32 232;");
    const int wg = tid >> 7, warp = tid >> 5, lane = tid & 31, t = lane & 3;
    const int rloc = warp * 16 + (lane >> 2);
    const float* s_cs = reinterpret_cast<const float*>(sgen + OFF_CS);
    auto signal = [&](int b) {
      __syncwarp();
      if (lane == 0) mbar_arrive(bars + 8 * b);
    };
    auto releaseB = [&](uint32_t bar) {
      __syncwarp();
      if (lane == 0) mbar_arrive(bar);
    };
    auto release = [&](uint32_t bar) {
      __syncwarp();
      if (lane < 2) mbar_arrive_cta(bar, lane);
    };
    uint32_t par;
    const uint32_t stg_lane = (warp * 16 + ((lane >> 3) & 1) * 8 + (lane & 7)) * 160 + (lane >> 4) * 16;

    {
      const unsigned done_cnt = *reinterpret_cast<volatile unsigned*>(g_flags + FL_DONE * 32);
#pragma unroll 1
      for (int e = tid; e < 800; e += 256) sts128(sb + OFF_MISC + e * 16, make_uint4(0, 0, 0, 0));
      bar_sync(1, 256);
      float f[40];
      float s = 0.f, gs = 0.f;
#pragma unroll
      for (int c = 0; c < 5; c++) {
        const uint32_t vv[4] = {pv[c].x, pv[c].y, pv[c].z, pv[c].w}, ww[4] = {pw_[c].x, pw_[c].y, pw_[c].z, pw_[c].w};
#pragma unroll
        for (int e = 0; e < 4; e++) {
          f[8 * c + 2 * e] = bf_lo(vv[e]); f[8 * c + 2 * e + 1] = bf_hi(vv[e]);
          s += f[8 * c + 2 * e] + f[8 * c + 2 * e + 1];
          gs = fmaf(f[8 * c + 2 * e], bf_lo(ww[e]), gs); gs = fmaf(f[8 * c + 2 * e + 1], bf_hi(ww[e]), gs);
        }
      }
#pragma unroll
      for (int o = 1; o < 16; o <<= 1) { s += __shfl_xor_sync(0xffffffffu, s, o); gs += __shfl_xor_sync(0xffffffffu, gs, o); }
      const float mean = s * (1.f / D_);
      float q = 0.f;
#pragma unroll
      for (int e = 0; e < 40; e++) { const float d = f[e] - mean; q = fmaf(d, d, q); }
#pragma unroll
      for (int o = 1; o < 16; o <<= 1) q += __shfl_xor_sync(0xffffffffu, q, o);
      const float rstd = rsqrtf(q * (1.f / D_) + 1e-5f);
      par = (done_cnt / NCTA) & 1;
      if (tid < 200) {
        const uint32_t cd = sb + OFF_B + SPARE + tid * 32;
        sts128(cd, make_uint4(__float_as_uint(bf_lo(pc[0].x) + bf_lo(pc[1].x)), __float_as_uint(bf_hi(pc[0].x) + bf_hi(pc[1].x)),
                              __float_as_uint(bf_lo(pc[0].y) + bf_lo(pc[1].y)), __float_as_uint(bf_hi(pc[0].y) + bf_hi(pc[1].y))));
        sts128(cd + 16, make_uint4(__float_as_uint(bf_lo(pc[0].z) + bf_lo(pc[1].z)), __float_as_uint(bf_hi(pc[0].z) + bf_hi(pc[1].z)),
                                   __float_as_uint(bf_lo(pc[0].w) + bf_lo(pc[1].w)), __float_as_uint(bf_hi(pc[0].w) + bf_hi(pc[1].w))));
        const uint32_t ww[4] = {pre.x, pre.y, pre.z, pre.w};
        const int h = tid / 50;
#pragma unroll
        for (int e = 0; e < 8; e++) {
          const int idx = tid * 8 + e, k = idx / 20, ff = idx - 20 * k;
          const int n = 40 * (h >> 1) + 8 * (ff >> 2) + 2 * (ff & 3) + (h & 1);
          const int off = (k >> 4) * 2560 + n * 32 + ((((k >> 3) ^ (n >> 2)) & 1) << 4) + (k & 7) * 2;
          *reinterpret_cast<unsigned short*>(sgen + OFF_MISC + off) = (unsigned short)(ww[e >> 1] >> ((e & 1) * 16));
        }
      }
      fence_async_smem();
      asm volatile("barrier.cluster.wait.aligned;" ::: "memory");
      if ((tid & 15) == 0) g_xstat[128 * i + 16 * j + (tid >> 4)] = make_float4(rstd, -mean * rstd, rcp(1.f + __expf(-gs)), 0.f);
      signal(B_SIGP);
    }
    TSTAMP(1);

    Ring ra{0, 0}, rb{0, 0};
    uint32_t qp[2][10], P[2][10];
    float st_g[2];
    {
      float accM[128], accR[32];
      zero_regs(accM); zero_regs(accR);
      uint32_t pa = 0, pb = 0;
#pragma unroll 1
      for (int k = 0; k < 10; k++) {
        mbar_wait(fullA + 8 * ra.idx, ra.phase);
        if (tid == 0) TRACE(32 + k);
        mbar_wait(fullB + 8 * rb.idx, rb.phase);
        if (tid == 0) TRACE(64 + k);
        if (k == 0) TSTAMP(2);
        const uint32_t a0 = sb16 + ((OFF_A + ra.idx * SLOT_A + wg * 8192) >> 4), b0 = sb16 + ((OFF_B + rb.idx * SLOT_B) >> 4);
        wg_fence();
#pragma unroll
        for (int kk = 0; kk < 4; kk++) {
          const uint64_t da = make_desc(a0, kk * 32, 16, 1024, 1);
          mma_ss256(accM, da, make_desc(b0, kk * 2048, 8192, 1024, 1));
          mma_ss64(accR, da, make_desc(b0, 32768 + kk * 512, 2048, 256, 3));
          if (kk == 0) {
            wg_commit();
            if (k > 0) {
              wg_wait<1>();
              if (k - 1 < 8) release(emptyA + 8 * pa);
              releaseB(emptyB + 8 * pb);
            }
          }
        }
        wg_commit();
        pa = ra.idx; pb = rb.idx;
        ra.next<NA>(); rb.next<NB>();
      }
      TSTAMP(18);
      float st_rstd[2], st_mr[2];
      mbar_wait(bars + 8 * B_CS, 0);
#pragma unroll
      for (int r = 0; r < 2; r++) {
        const uint4 st = lds128(sb + OFF_XST + (rloc + 8 * r) * 16);
        st_rstd[r] = __uint_as_float(st.x); st_mr[r] = __uint_as_float(st.y); st_g[r] = __uint_as_float(st.z);
      }
      TSTAMP(19);
      wg_wait<0>();
      fence_regs(accM); fence_regs(accR);
      TSTAMP(3);
#define ACC(P_, G, I_) ((G) < 8 ? accM[(P_) * 32 + ((G) & 7) * 4 + (I_)] : accR[(P_) * 8 + ((G) & 1) * 4 + (I_)])
      {
        const int mat = lane >> 3;
        const int tok = warp * 16 + (mat & 1) * 8 + (lane & 7);
        const uint32_t ones = (t == 0) ? 0x00003f80u : 0u;
        __syncwarp();
#pragma unroll
        for (int p = 0; p < 2; p++) {
          const uint32_t rowa = sb + OFF_A + p * SLOT_A + tok * 128;
#pragma unroll
          for (int gg = 0; gg < 3; gg++) {
            const int g0 = 5 * p + 2 * gg;
            uint32_t r0 = pack_bf16(ACC(3, g0, 0), ACC(3, g0, 1)), r1 = pack_bf16(ACC(3, g0, 2), ACC(3, g0, 3));
            uint32_t r2 = ones, r3 = ones;
            if (gg < 2) { r2 = pack_bf16(ACC(3, g0 + 1, 0), ACC(3, g0 + 1, 1)); r3 = pack_bf16(ACC(3, g0 + 1, 2), ACC(3, g0 + 1, 3)); }
            stsm4(rowa + (((2 * gg + (mat >> 1)) ^ (tok & 7)) << 4), r0, r1, r2, r3);
          }
        }
      }
      uint32_t kf[5][4], qf[5][4];
#pragma unroll
      for (int s = 0; s < 5; s++) {
        kf[s][0] = pack_bf16(ACC(2, 2 * s, 0), ACC(2, 2 * s, 1)); kf[s][1] = pack_bf16(ACC(2, 2 * s, 2), ACC(2, 2 * s, 3));
        kf[s][2] = pack_bf16(ACC(2, 2 * s + 1, 0), ACC(2, 2 * s + 1, 1)); kf[s][3] = pack_bf16(ACC(2, 2 * s + 1, 2), ACC(2, 2 * s + 1, 3));
        qf[s][0] = pack_bf16(ACC(1, 2 * s, 0), ACC(1, 2 * s, 1)); qf[s][1] = pack_bf16(ACC(1, 2 * s, 2), ACC(1, 2 * s, 3));
        qf[s][2] = pack_bf16(ACC(1, 2 * s + 1, 0), ACC(1, 2 * s + 1, 1)); qf[s][3] = pack_bf16(ACC(1, 2 * s + 1, 2), ACC(1, 2 * s + 1, 3));
      }
      bar_sync(1, 256);
      float pk[40], pq[40];
      wg_fence();
#pragma unroll
      for (int s = 0; s < 5; s++) {
        if (s == 0) mma_rs80_k_z(pk, kf[s], make_desc(sb16, OFF_MISC, 16, 256, 3));
        else mma_rs80_k(pk, kf[s], make_desc(sb16, OFF_MISC + s * 2560, 16, 256, 3));
      }
#pragma unroll
      for (int s = 0; s < 5; s++) {
        if (s == 0) mma_rs80_k_z(pq, qf[s], make_desc(sb16, OFF_MISC, 16, 256, 3));
        else mma_rs80_k(pq, qf[s], make_desc(sb16, OFF_MISC + s * 2560, 16, 256, 3));
      }
      wg_commit();

      {
        uint32_t hv[10][2];
#pragma unroll
        for (int g = 0; g < 10; g++) {
          const float2 cs = *reinterpret_cast<const float2*>(s_cs + 8 * g + 2 * t);
          const float v0 = gelu_s(fmaf(ACC(0, g, 0), st_rstd[0], st_mr[0] * cs.x), 0.5f), v1 = gelu_s(fmaf(ACC(0, g, 1), st_rstd[0], st_mr[0] * cs.y), 0.5f);
          const float v2 = gelu_s(fmaf(ACC(0, g, 2), st_rstd[1], st_mr[1] * cs.x), 0.5f), v3 = gelu_s(fmaf(ACC(0, g, 3), st_rstd[1], st_mr[1] * cs.y), 0.5f);
          hv[g][0] = pack_bf16(v0, v1); hv[g][1] = pack_bf16(v2, v3);
        }
#pragma unroll
        for (int s = 0; s < 5; s++) stsm4(sb + OFF_STG + stg_lane + s * 32, hv[2 * s][0], hv[2 * s][1], hv[2 * s + 1][0], hv[2 * s + 1][1]);
        fence_async_smem();
        signal(B_SIGH);
      }
#undef ACC
      TSTAMP(4);
      wg_wait<0>();
      fence_regs(pk); fence_regs(pq);
#pragma unroll
      for (int G = 0; G < 10; G++) {
        P[0][G] = pack_bf16(pk[4 * G], pk[4 * G + 1]); P[1][G] = pack_bf16(pk[4 * G + 2], pk[4 * G + 3]);
        qp[0][G] = pack_bf16(pq[4 * G], pq[4 * G + 1]); qp[1][G] = pack_bf16(pq[4 * G + 2], pq[4 * G + 3]);
      }
    }

    uint32_t fr[10][4];
    {
      feature_map(P, fr);
      const int mat = lane >> 3;
      const int tok = warp * 16 + (mat & 1) * 8 + (lane & 7);
      const uint32_t base = sb + OFF_B + tok * 32 + (((mat >> 1) ^ ((tok >> 2) & 1)) << 4);
#pragma unroll
      for (int G = 0; G < 10; G++) stsm4(base + G * 4096, fr[G][0], fr[G][1], fr[G][2], fr[G][3]);
      fence_async_smem();
      bar_sync(1, 256);
      float kv[40];
      const uint32_t a0 = sb16 + ((OFF_A + wg * SLOT_A) >> 4), b0 = sb16 + ((OFF_B + wg * 20480) >> 4);
      wg_fence();
#pragma unroll
      for (int ks = 0; ks < 8; ks++) {
        if (ks == 0) mma_ss80_tt_z(kv, make_desc(a0, 0, 16, 1024, 1), make_desc(b0, 0, 4096, 256, 3));
        else mma_ss80_tt(kv, make_desc(a0, ks * 2048, 16, 1024, 1), make_desc(b0, ks * 512, 4096, 256, 3));
      }
      wg_commit();
      wg_wait<0>();
      fence_regs(kv);
      release(emptyA); release(emptyA + 8); releaseB(emptyB);
      float* dst = g_acc[par] + j * KV_J + wg * KV_PAIR;
      const int m0 = (warp & 3) * 16 + (lane >> 2);
#pragma unroll
      for (int r = 0; r < 2; r++) {
        const int m = m0 + 8 * r;
        const bool hi = m >= 20;
        float v[10];
#pragma unroll
        for (int G = 0; G < 10; G++) v[G] = hi ? kv[4 * G + 2 * r + 1] : kv[4 * G + 2 * r];
        float* p = dst + (m < 40 ? m * 48 + t * 12 : 1920 + t * 24 + 12);
        if (m <= 40) { red_add4(p, v[0], v[1], v[2], v[3]); red_add4(p + 4, v[4], v[5], v[6], v[7]); red_add2(p + 8, v[8], v[9]); }
      }
      if (m0 == 32) {
        float* p = dst + 1920 + t * 24;
        red_add4(p, kv[2], kv[6], kv[10], kv[14]); red_add4(p + 4, kv[18], kv[22], kv[26], kv[30]); red_add2(p + 8, kv[34], kv[38]);
      }
      signal(B_SIGKV);
    }
    TSTAMP(5);

    uint32_t xv[2][10];
    {
      {
        mbar_wait(bars + 8 * B_XR, 0);
        const uint32_t xa = sb + OFF_B + (warp / 3) * SLOT_B + SPARE + (warp % 3) * 2560 + (lane >> 2) * 160 + t * 4;
#pragma unroll
        for (int g = 0; g < 10; g++) { xv[0][g] = lds32(xa + g * 16); xv[1][g] = lds32(xa + 1280 + g * 16); }
      }
      float acc[40];
      zero_regs(acc);
      uint32_t pa = 0, pb = 0;
#pragma unroll 1
      for (int k = 0; k < 10; k++) {
        mbar_wait(fullA + 8 * ra.idx, ra.phase);
        if (tid == 0) TRACE(42 + k);
        if ((k & 3) == 0) mbar_wait(fullB + 8 * rb.idx, rb.phase);
        if (tid == 0) TRACE(74 + k);
        if (k == 0) TSTAMP(6);
        const uint32_t a0 = sb16 + ((OFF_A + ra.idx * SLOT_A + wg * 8192) >> 4);
        const uint32_t b0 = sb16 + ((OFF_B + rb.idx * SLOT_B + (k & 3) * 10240) >> 4);
        wg_fence();
#pragma unroll
        for (int kk = 0; kk < 4; kk++) {
          mma_ss80(acc, make_desc(a0, kk * 32, 16, 1024, 1), make_desc(b0, kk * 512, 2048, 256, 3));
          if (kk == 1) {
            wg_commit();
            if (k > 0) {
              wg_wait<1>();
              release(emptyA + 8 * pa);
              if ((k & 3) == 0) releaseB(emptyB + 8 * pb);
            }
          }
        }
        wg_commit();
        pa = ra.idx; pb = rb.idx;
        ra.next<NA>();
        if ((k & 3) == 3 || k == 9) rb.next<NB>();
      }
      wg_wait<0>();
      fence_regs(acc);
      release(emptyA + 8 * pa); releaseB(emptyB + 8 * pb);
      TSTAMP(7);
#pragma unroll
      for (int r = 0; r < 2; r++) {
#pragma unroll
        for (int g = 0; g < 10; g++)
          xv[r][g] = pack_bf16(bf_lo(xv[r][g]) + acc[4 * g + 2 * r], bf_hi(xv[r][g]) + acc[4 * g + 2 * r + 1]);
      }
      bar_sync(1, 256);
#pragma unroll
      for (int s = 0; s < 5; s++) stsm4(sb + OFF_STG + stg_lane + s * 32, xv[0][2 * s], xv[1][2 * s], xv[0][2 * s + 1], xv[1][2 * s + 1]);
#pragma unroll
      for (int r = 0; r < 2; r++) {
        float s = 0.f;
#pragma unroll
        for (int g = 0; g < 10; g++) {
          acc[4 * g + 2 * r] = bf_lo(xv[r][g]); acc[4 * g + 2 * r + 1] = bf_hi(xv[r][g]);
          s += acc[4 * g + 2 * r] + acc[4 * g + 2 * r + 1];
        }
        s += __shfl_xor_sync(0xffffffffu, s, 1); s += __shfl_xor_sync(0xffffffffu, s, 2);
        const float mu = s * (1.f / 80.f);
        float q = 0.f;
#pragma unroll
        for (int g = 0; g < 10; g++) {
          const float d0 = acc[4 * g + 2 * r] - mu, d1 = acc[4 * g + 2 * r + 1] - mu;
          q = fmaf(d0, d0, q); q = fmaf(d1, d1, q);
        }
        q += __shfl_xor_sync(0xffffffffu, q, 1); q += __shfl_xor_sync(0xffffffffu, q, 2);
        if (t == 0) g_st1[(128 * i + rloc + 8 * r) * 8 + j] = make_float2(mu, q);
      }
      fence_async_smem();
      signal(B_SIGX1);
    }
    TSTAMP(8);

    uint32_t of[5][4];
    {
      feature_map(qp, fr);
      mbar_wait(bars + 8 * B_KV, 0);
      uint4 kvr[2][3];
#pragma unroll
      for (int u = 0; u < 2; u++) {
        const int it = tid + 256 * u, p = it / 192, rem = it - 192 * p, n = rem >> 2, tq = rem & 3;
        const uint32_t sp = sb + OFF_MISC + 4 * (p * KV_PAIR + (n < 40 ? n * 48 + tq * 12 : 1920 + tq * 24 + (n & 1) * 12));
        if (it < 384) { kvr[u][0] = lds128(sp); kvr[u][1] = lds128(sp + 16); kvr[u][2] = lds128(sp + 32); }
      }
      bar_sync(1, 256);
#pragma unroll
      for (int u = 0; u < 2; u++) {
        const int it = tid + 256 * u, p = it / 192, rem = it - 192 * p, n = rem >> 2, tq = rem & 3;
        const int sh = (n < 40 ? (n >= 20) : (n & 1)) * 16;
        const uint32_t v[10] = {kvr[u][0].x, kvr[u][0].y, kvr[u][0].z, kvr[u][0].w, kvr[u][1].x, kvr[u][1].y, kvr[u][1].z, kvr[u][1].w, kvr[u][2].x, kvr[u][2].y};
        uint8_t* dst = sgen + OFF_MISC + p * 7680 + n * 32 + tq * 4;
        const int sw = ((n >> 2) & 1) << 4;
        if (it < 384) {
#pragma unroll
          for (int G = 0; G < 10; G++)
            *reinterpret_cast<uint32_t*>(dst + (G >> 1) * 1536 + (((G & 1) << 4) ^ sw)) = pack_bf16(__uint_as_float(v[G]), 0.f) << sh;
        }
      }
      fence_async_smem();
      bar_sync(1, 256);
      float o0[24], o1[24];
      wg_fence();
#pragma unroll
      for (int g = 0; g < 5; g++) {
        if (g == 0) mma_rs48_k_z(o0, fr[g], make_desc(sb16, OFF_MISC, 16, 256, 3));
        else mma_rs48_k(o0, fr[g], make_desc(sb16, OFF_MISC + g * 1536, 16, 256, 3));
      }
#pragma unroll
      for (int g = 0; g < 5; g++) {
        if (g == 0) mma_rs48_k_z(o1, fr[5], make_desc(sb16, OFF_MISC + 7680, 16, 256, 3));
        else mma_rs48_k(o1, fr[5 + g], make_desc(sb16, OFF_MISC + 7680 + g * 1536, 16, 256, 3));
      }
      wg_commit();
      wg_wait<0>();
      fence_regs(o0); fence_regs(o1);
      signal(B_MFREE);
#pragma unroll
      for (int r = 0; r < 2; r++) {
        const float a0 = __fdividef(st_g[r], o0[20 + 2 * r] + 1e-6f), a1 = __fdividef(st_g[r], o0[21 + 2 * r] + 1e-6f);
        const float b0 = __fdividef(st_g[r], o1[20 + 2 * r] + 1e-6f), b1 = __fdividef(st_g[r], o1[21 + 2 * r] + 1e-6f);
        const float am = t < 2 ? a0 : a1, bm = t < 2 ? b0 : b1;
#pragma unroll
        for (int g = 0; g < 5; g++) {
          const float sa = g < 2 ? a0 : (g == 2 ? am : a1), sb2 = g < 2 ? b0 : (g == 2 ? bm : b1);
          of[g >> 1][(g & 1) * 2 + r] = pack_bf16(o0[4 * g + 2 * r] * sa, o0[4 * g + 2 * r + 1] * sa);
          of[(5 + g) >> 1][((5 + g) & 1) * 2 + r] = pack_bf16(o1[4 * g + 2 * r] * sb2, o1[4 * g + 2 * r + 1] * sb2);
        }
      }
    }
    TSTAMP(9);

    uint32_t hf[12][4];
    {
      float acc[96];
      zero_regs(acc);
      uint32_t pa = 0, pb = 0;
#pragma unroll 1
      for (int k = 0; k < 10; k++) {
        mbar_wait(fullA + 8 * ra.idx, ra.phase);
        if (tid == 0) TRACE(52 + k);
        if ((k & 1) == 0) mbar_wait(fullB + 8 * rb.idx, rb.phase);
        if (tid == 0) TRACE(84 + k);
        if (k == 0) TSTAMP(10);
        const uint32_t a0 = sb16 + ((OFF_A + ra.idx * SLOT_A + wg * 8192) >> 4);
        const uint32_t b0 = sb16 + ((OFF_B + rb.idx * SLOT_B + (k & 1) * 24576) >> 4);
        wg_fence();
#pragma unroll
        for (int kk = 0; kk < 4; kk++) {
          mma_ss192(acc, make_desc(a0, kk * 32, 16, 1024, 1), make_desc(b0, kk * 2048, 8192, 1024, 1));
          if (kk == 0) {
            wg_commit();
            if (k > 0) {
              wg_wait<1>();
              release(emptyA + 8 * pa);
              if ((k & 1) == 0) releaseB(emptyB + 8 * pb);
            }
          }
        }
        wg_commit();
        pa = ra.idx; pb = rb.idx;
        ra.next<NA>();
        if (k & 1) rb.next<NB>();
      }
      float rs[2], mm[2];
      mbar_wait(bars + 8 * B_ST1, 0);
#pragma unroll
      for (int r = 0; r < 2; r++) {
        const uint4 su = lds128(sb + OFF_MISC + (rloc + 8 * r) * 64 + t * 16);
        const float m0 = __uint_as_float(su.x), m1 = __uint_as_float(su.z);
        float mu = m0 + m1;
        mu += __shfl_xor_sync(0xffffffffu, mu, 1); mu += __shfl_xor_sync(0xffffffffu, mu, 2);
        mu *= 0.125f;
        const float d0 = m0 - mu, d1 = m1 - mu;
        float q = __uint_as_float(su.y) + __uint_as_float(su.w) + 80.f * (d0 * d0 + d1 * d1);
        q += __shfl_xor_sync(0xffffffffu, q, 1); q += __shfl_xor_sync(0xffffffffu, q, 2);
        rs[r] = rsqrtf(q * (1.f / D_) + 1e-5f);
        mm[r] = -mu * rs[r];
      }
      wg_wait<0>();
      fence_regs(acc);
      releaseB(emptyB + 8 * pb);
      if (lane == 0) mbar_arrive_cta(bars + 8 * B_PEER, rank ^ 1);
      if (wg == 1) bar_arrive(2, 256);
      TSTAMP(11);
      const float hs0 = 0.5f - 0.5f * st_g[0], hs1 = 0.5f - 0.5f * st_g[1];
#pragma unroll
      for (int g = 0; g < 24; g++) {
        const float2 cs = *reinterpret_cast<const float2*>(s_cs + 80 + 8 * g + 2 * t);
        const float v0 = gelu_s(fmaf(acc[4 * g], rs[0], mm[0] * cs.x), hs0), v1 = gelu_s(fmaf(acc[4 * g + 1], rs[0], mm[0] * cs.y), hs0);
        const float v2 = gelu_s(fmaf(acc[4 * g + 2], rs[1], mm[1] * cs.x), hs1), v3 = gelu_s(fmaf(acc[4 * g + 3], rs[1], mm[1] * cs.y), hs1);
        hf[g >> 1][(g & 1) * 2] = pack_bf16(v0, v1);
        hf[g >> 1][(g & 1) * 2 + 1] = pack_bf16(v2, v3);
      }
    }
    TSTAMP(12);

    {
      float aM[64], aR[16];
      const int wt = tid & 127;
      const uint32_t peer = map_peer(sb, rank ^ 1);
      Ring r4{0, 0};
      auto add16 = [&](uint32_t src) {
#pragma unroll
        for (int q = 0; q < 5; q++) {
          const uint4 v = lds128(src + q * 2048);
          float* d = q < 4 ? &aM[8 * q] : &aR[0];
          d[0] += bf_lo(v.x); d[1] += bf_hi(v.x); d[2] += bf_lo(v.y); d[3] += bf_hi(v.y);
          d[4] += bf_lo(v.z); d[5] += bf_hi(v.z); d[6] += bf_lo(v.w); d[7] += bf_hi(v.w);
        }
      };
#pragma unroll 1
      for (int c = 0; c < 4; c++) {
        uint32_t prev = 0;
#pragma unroll
        for (int u = 0; u < 4; u++) {
          mbar_wait(bars + 8 * (B_FULL4 + r4.idx), r4.phase);
          const uint32_t b0 = sb16 + ((OFF_B + r4.idx * UNIT4) >> 4);
          if (u == 0) {
            if (tid == 128) TR4(c * 16 + 0);
            bar_sync(2 + wg, 256);
          }
          wg_fence();
#pragma unroll
          for (int s = 0; s < (u < 3 ? 4 : 5); s++) {
            const uint64_t dm = make_desc(b0, s * 2048, u < 3 ? 8192 : 10240, 1024, 1);
            const uint64_t dr = make_desc(b0, (u < 3 ? 16384 : 20480) + s * 512, u < 3 ? 2048 : 2560, 256, 3);
            if (u == 0 && s == 0) { mma_rs128_n_z(aM, hf[0], dm); mma_rs32_n_z(aR, hf[0], dr); }
            else if (u < 3) { mma_rs128_n(aM, hf[(4 * u + s) % 12], dm); mma_rs32_n(aR, hf[(4 * u + s) % 12], dr); }
            else { mma_rs128_n(aM, of[s], dm); mma_rs32_n(aR, of[s], dr); }
            if (s == 1 && u > 0) { wg_commit(); wg_wait<1>(); releaseB(bars + 8 * (B_EMPTY4 + prev)); }
          }
          wg_commit();
          prev = r4.idx;
          r4.next<NU4>();
        }
        if (c < 3 || wg == 0) bar_arrive(3 - wg, 256);
        if (tid == 128) TR4(c * 16 + 2);
        if (c == 0) mbar_wait(bars + 8 * B_PEER, 0);
        wg_wait<0>();
        fence_regs(aM); fence_regs(aR);
        releaseB(bars + 8 * (B_EMPTY4 + prev));
        if (tid == 128) TR4(c * 16 + 5);
        const uint32_t dso = OFF_DS + (c & 1) * 20480 + wg * 10240 + wt * 16, dsb = OFF_BAR + 8 * (B_DSR + 2 * c + wg);
#pragma unroll
        for (int q = 0; q < 5; q++) {
          const float* d = q < 4 ? &aM[32 + 8 * q] : &aR[8];
          st_async16(peer + dso + q * 2048, pack_bf16(d[0], d[1]), pack_bf16(d[2], d[3]), pack_bf16(d[4], d[5]), pack_bf16(d[6], d[7]),
                     peer + dsb);
        }
        if (c > 0 && c < 3) mbar_wait(bars + 8 * (B_SDONE + 2 * (c - 1) + wg), 0);
        mbar_wait(sb + dsb, 0);
        if (tid == 128) TR4(c * 16 + 3);
        add16(sb + dso);
        if (c < 3) {
          const uint32_t dst = sb + OFF_SEND + wg * 10240 + wt * 16;
#pragma unroll
          for (int q = 0; q < 5; q++) {
            const float* d = q < 4 ? &aM[8 * q] : &aR[0];
            sts128(dst + q * 2048, make_uint4(pack_bf16(d[0], d[1]), pack_bf16(d[2], d[3]), pack_bf16(d[4], d[5]), pack_bf16(d[6], d[7])));
          }
          fence_async_smem();
          signal(B_SEND + 2 * c + wg);
          if (tid == 128) TR4(c * 16 + 6);
        }
      }
      TSTAMP(13);
#pragma unroll 1
      for (int c = 0; c < 3; c++) {
        mbar_wait(bars + 8 * (B_RDY + 2 * c + wg), 0);
        add16(sb + (c == 0 ? OFF_G0 : c == 1 ? OFF_G1 : OFF_SEND) + wg * 10240 + wt * 16);
        if (tid == 128) TR4(c * 16 + 12);
      }
      TSTAMP(14);
      const float w0 = 1.f - st_g[0], w1s = 1.f - st_g[1];
      uint32_t ov[10][2];
#pragma unroll
      for (int g = 0; g < 10; g++) {
        const float* d = g < 8 ? &aM[4 * g] : &aR[4 * (g - 8)];
        ov[g][0] = pack_bf16(fmaf(w0, bf_lo(xv[0][g]), d[0]), fmaf(w0, bf_hi(xv[0][g]), d[1]));
        ov[g][1] = pack_bf16(fmaf(w1s, bf_lo(xv[1][g]), d[2]), fmaf(w1s, bf_hi(xv[1][g]), d[3]));
      }
      bar_sync(4 + wg, 128);
#pragma unroll
      for (int s = 0; s < 5; s++) stsm4(sb + OFF_DS + stg_lane + s * 32, ov[2 * s][0], ov[2 * s][1], ov[2 * s + 1][0], ov[2 * s + 1][1]);
      fence_async_smem();
      bar_sync(4 + wg, 128);
      if (wt == 0) {
        tma2d_store(&maps.st_out, sb + OFF_DS + wg * 10240, 80 * j, 128 * i + 64 * wg);
        bulk_commit(); bulk_wait_read();
      }
    }
    TSTAMP(15);
    if (tid == 0) asm volatile("red.relaxed.gpu.global.add.u32 [%0], 1;" ::"l"(g_flags + FL_DONE * 32) : "memory");
    asm volatile("barrier.cluster.arrive;\nbarrier.cluster.wait;" ::: "memory");
  }
}

namespace {
typedef CUresult (*EncodeFn)(CUtensorMap*, CUtensorMapDataType, cuuint32_t, void*, const cuuint64_t*, const cuuint64_t*,
                             const cuuint32_t*, const cuuint32_t*, CUtensorMapInterleave, CUtensorMapSwizzle,
                             CUtensorMapL2promotion, CUtensorMapFloatOOBfill);

void encode(EncodeFn fn, CUtensorMap* m, const void* ptr, int rank, const cuuint64_t* dims, const cuuint64_t* strides,
            const cuuint32_t* box, CUtensorMapSwizzle swz) {
  cuuint32_t es[5] = {1, 1, 1, 1, 1};
  fn(m, CU_TENSOR_MAP_DATA_TYPE_BFLOAT16, rank, const_cast<void*>(ptr), dims, strides, box, es, CU_TENSOR_MAP_INTERLEAVE_NONE,
     swz, CU_TENSOR_MAP_L2_PROMOTION_L2_128B, CU_TENSOR_MAP_FLOAT_OOB_FILL_NONE);
}
}

extern "C" void kernel_launch(void* const* d_in, const int* in_sizes, int n_in, void* d_out, int out_size) {
  (void)in_sizes; (void)n_in; (void)out_size;
  const __nv_bfloat16* x = (const __nv_bfloat16*)d_in[0];
  const __nv_bfloat16* wqkv = (const __nv_bfloat16*)d_in[1];
  const __nv_bfloat16* wphi = (const __nv_bfloat16*)d_in[2];
  const __nv_bfloat16* wo = (const __nv_bfloat16*)d_in[3];
  const __nv_bfloat16* w1 = (const __nv_bfloat16*)d_in[5];
  const __nv_bfloat16* w2 = (const __nv_bfloat16*)d_in[6];
  const __nv_bfloat16* w3 = (const __nv_bfloat16*)d_in[7];
  const __nv_bfloat16* w4 = (const __nv_bfloat16*)d_in[8];
  const __nv_bfloat16* gate_w = (const __nv_bfloat16*)d_in[9];

  static EncodeFn enc = nullptr;
  static void *pHs = nullptr, *pX1 = nullptr;
  if (!enc) {
    cudaDriverEntryPointQueryResult qr;
    cudaGetDriverEntryPoint("cuTensorMapEncodeTiled", (void**)&enc, cudaEnableDefault, &qr);
    cudaGetSymbolAddress(&pHs, g_Hs);
    cudaGetSymbolAddress(&pX1, g_X1);
    cudaFuncSetAttribute(fused_kernel, cudaFuncAttributeMaxDynamicSharedMemorySize, SMEM_BYTES);
  }
  Maps m;
  {
    cuuint64_t dims[2] = {D_, S_}, str[1] = {D_ * 2};
    cuuint32_t boxh[2] = {64, 64};
    encode(enc, &m.x, x, 2, dims, str, boxh, CU_TENSOR_MAP_SWIZZLE_128B);
    encode(enc, &m.hs, (const char*)pHs + 2 * D_ * 2, 2, dims, str, boxh, CU_TENSOR_MAP_SWIZZLE_128B);
    encode(enc, &m.x1, pX1, 2, dims, str, boxh, CU_TENSOR_MAP_SWIZZLE_128B);
    cuuint32_t boxs[2] = {80, 64};
    cuuint64_t dimsp[2] = {D_, S_ + 4};
    encode(enc, &m.st_h, pHs, 2, dimsp, str, boxs, CU_TENSOR_MAP_SWIZZLE_NONE);
    encode(enc, &m.st_x1, pX1, 2, dims, str, boxs, CU_TENSOR_MAP_SWIZZLE_NONE);
    encode(enc, &m.st_out, d_out, 2, dims, str, boxs, CU_TENSOR_MAP_SWIZZLE_NONE);
    cuuint32_t boxr[2] = {80, 16};
    encode(enc, &m.xr, x, 2, dims, str, boxr, CU_TENSOR_MAP_SWIZZLE_NONE);
  }
  {
    cuuint64_t dims[3] = {80, D_, 8}, str[2] = {D_ * 2, 160};
    cuuint32_t boxm[3] = {64, 64, 1}, boxr[3] = {16, 64, 1}, boxom[3] = {64, 80, 1}, boxor[3] = {16, 80, 1};
    cuuint64_t dims4[3] = {80, F_, 8};
    encode(enc, &m.w1m, w1, 3, dims, str, boxm, CU_TENSOR_MAP_SWIZZLE_128B);
    encode(enc, &m.w1r, w1, 3, dims, str, boxr, CU_TENSOR_MAP_SWIZZLE_32B);
    encode(enc, &m.w4m, w4, 3, dims4, str, boxm, CU_TENSOR_MAP_SWIZZLE_128B);
    encode(enc, &m.w4r, w4, 3, dims4, str, boxr, CU_TENSOR_MAP_SWIZZLE_32B);
    encode(enc, &m.wom, wo, 3, dims, str, boxom, CU_TENSOR_MAP_SWIZZLE_128B);
    encode(enc, &m.wor, wo, 3, dims, str, boxor, CU_TENSOR_MAP_SWIZZLE_32B);
  }
  {
    cuuint64_t dims[4] = {80, D_, 3, 8}, str[3] = {3 * D_ * 2, D_ * 2, 160};
    cuuint32_t boxm[4] = {64, 64, 3, 1}, boxr[4] = {16, 64, 3, 1};
    encode(enc, &m.qm, wqkv, 4, dims, str, boxm, CU_TENSOR_MAP_SWIZZLE_128B);
    encode(enc, &m.qr, wqkv, 4, dims, str, boxr, CU_TENSOR_MAP_SWIZZLE_32B);
  }
  {
    cuuint64_t dims[3] = {16, D_, 40}, str[2] = {D_ * 2, 32};
    cuuint32_t box2[3] = {16, 64, 5};
    encode(enc, &m.w2, w2, 3, dims, str, box2, CU_TENSOR_MAP_SWIZZLE_32B);
  }
  {
    cuuint64_t dims[3] = {64, D_, 24}, str[2] = {F_ * 2, 128};
    cuuint32_t box[3] = {64, 64, 3};
    encode(enc, &m.w3, w3, 3, dims, str, box, CU_TENSOR_MAP_SWIZZLE_128B);
  }
  fused_kernel<<<NCTA, 384, SMEM_BYTES, cudaStreamPerThread>>>(m, x, wqkv, wphi, w1, w2, w3, w4, wo, gate_w);
}
```

```cpp
#include <cuda_runtime.h>
#include <cuda_bf16.h>
#include <cuda.h>
#include <stdint.h>

namespace {

constexpr int S_ = 2048, D_ = 640, F_ = 1536;
constexpr int NCTA = 128;
constexpr int KV_PAIR = 40 * 48 + 96;
constexpr int KV_J = 2 * KV_PAIR;

constexpr int SLOT_B = 49152, NB = 3;
constexpr int SLOT_A = 16384, NA = 4;
constexpr int OFF_B = 0;
constexpr int OFF_A = OFF_B + NB * SLOT_B;
constexpr int OFF_STG = OFF_A + 2 * SLOT_A;
constexpr int OFF_MISC = OFF_A + NA * SLOT_A;
constexpr int OFF_XST = OFF_MISC + 13312;
constexpr int OFF_CS = OFF_MISC + 16384;
constexpr int OFF_BAR = OFF_CS + 1088;
constexpr int SMEM_BYTES = OFF_BAR + 512;
constexpr int B_FULLA = 0, B_FULLB = 4, B_CS = 7, B_XR = 8, B_KV = 9, B_ST1 = 10, B_SDONE = 11  , B_RDY = 17  ,
              B_FULL4 = 23  , B_DSR = 28  , B_SEND = 36  , B_EMPTYB = 42  ,
              B_SIGP = 45, B_SIGH = 46, B_SIGKV = 47, B_SIGX1 = 48, B_MFREE = 49, B_PEER = 50, B_EMPTY4 = 51  ,
              B_EMPTYA = 56  , NBAR = 60;
constexpr int SPARE = 40960;
constexpr int UNIT4 = 25600, NU4 = 5;
constexpr int OFF_DS = OFF_A, OFF_SEND = OFF_A + 40960, OFF_G0 = OFF_A + 61440, OFF_G1 = OFF_B + UNIT4;

constexpr int FL_DONE = 0, FL_H = 1, FL_X1 = FL_H + 16, FL_KV = FL_X1 + 16, FL_CS = FL_KV + 8, FL_CS3 = FL_CS + 8, FL_ST = FL_CS3 + 8, FL_PART = FL_ST + 16;
constexpr int FL_COUNT = FL_PART + 16 * 8;
constexpr int ACC_FLOATS = 8 * KV_J + D_ + F_;

struct Maps {
  CUtensorMap x, w1m, w1r, qm, qr, hs, w2, x1, w3, w4, wo, st_h, st_x1, st_out, xr;
};

}

__device__ __align__(1024) __nv_bfloat16 g_Hs[(S_ + 4) * D_];
__device__ __align__(1024) __nv_bfloat16 g_X1[S_ * D_];
__device__ __align__(128) float g_acc[2][ACC_FLOATS];
__device__ __align__(128) float4 g_xstat[S_];
__device__ __align__(128) float2 g_st1[S_ * 8];
__device__ __align__(128) uint4 g_part[16 * 8 * 3 * 1280];
__device__ __align__(128) unsigned g_flags[FL_COUNT * 32];
#define TSTAMP(n) do {} while (0)
#define TSTAMPX(n) do {} while (0)
#define TRACE(n) do {} while (0)
#define TR4(n) do {} while (0)

namespace {

__device__ __forceinline__ long long gtime() { long long t; asm volatile("mov.u64 %0, %%globaltimer;" : "=l"(t)); return t; }
__device__ __forceinline__ uint32_t smem_u32(const void* p) { return (uint32_t)__cvta_generic_to_shared(p); }
__device__ __forceinline__ void mbar_init(uint32_t bar, int cnt) {
  asm volatile("mbarrier.init.shared::cta.b64 [%0], %1;" ::"r"(bar), "r"(cnt) : "memory");
}
__device__ __forceinline__ void mbar_expect_tx(uint32_t bar, int bytes) {
  asm volatile("mbarrier.arrive.expect_tx.shared::cta.b64 _, [%0], %1;" ::"r"(bar), "r"(bytes) : "memory");
}
__device__ __forceinline__ void mbar_arrive_cta(uint32_t bar, uint32_t cta) {
  asm volatile("{\n.reg .b32 ra;\nmapa.shared::cluster.u32 ra, %0, %1;\nmbarrier.arrive.shared::cluster.b64 _, [ra];\n}"
               ::"r"(bar), "r"(cta) : "memory");
}
__device__ __forceinline__ uint32_t mbar_try(uint32_t bar, uint32_t parity) {
  uint32_t ok;
  asm volatile("{\n.reg .pred p;\nmbarrier.try_wait.parity.shared::cta.b64 p, [%1], %2;\nselp.u32 %0, 1, 0, p;\n}"
               : "=r"(ok) : "r"(bar), "r"(parity) : "memory");
  return ok;
}
constexpr uint32_t WAIT_LIMIT = 1u << 22;
__device__ __forceinline__ void mbar_wait(uint32_t bar, uint32_t parity) {
  uint32_t n = 0;
  while (!mbar_try(bar, parity) && ++n < WAIT_LIMIT) {}
}
__device__ __forceinline__ unsigned ld_acquire(const unsigned* p) {
  unsigned v;
  asm volatile("ld.acquire.gpu.global.u32 %0, [%1];" : "=r"(v) : "l"(p) : "memory");
  return v;
}
__device__ __forceinline__ void flag_wait(int idx, unsigned target) {
  const unsigned* p = g_flags + idx * 32;
  uint32_t n = 0;
  while ((int)(ld_acquire(p) - target) < 0 && ++n < (WAIT_LIMIT >> 4)) {}
}
__device__ __forceinline__ void flag_add(int idx) {
  asm volatile("red.release.gpu.global.add.u32 [%0], 1;" ::"l"(g_flags + idx * 32) : "memory");
}
__device__ __forceinline__ void flag_add_relaxed(int idx) {
  asm volatile("red.relaxed.gpu.global.add.u32 [%0], 1;" ::"l"(g_flags + idx * 32) : "memory");
}
__device__ __forceinline__ uint32_t mbar_test(uint32_t bar, uint32_t parity) {
  uint32_t ok;
  asm volatile("{\n.reg .pred p;\nmbarrier.test_wait.parity.shared::cta.b64 p, [%1], %2;\nselp.u32 %0, 1, 0, p;\n}"
               : "=r"(ok) : "r"(bar), "r"(parity) : "memory");
  return ok;
}
__device__ __forceinline__ uint32_t lds32(uint32_t a) {
  uint32_t v;
  asm volatile("ld.shared.u32 %0, [%1];" : "=r"(v) : "r"(a) : "memory");
  return v;
}
__device__ __forceinline__ void mbar_arrive(uint32_t bar) {
  asm volatile("mbarrier.arrive.shared::cta.b64 _, [%0];" ::"r"(bar) : "memory");
}
__device__ __forceinline__ void fence_async_all() { asm volatile("fence.proxy.async;" ::: "memory"); }
__device__ __forceinline__ void fence_async_smem() { asm volatile("fence.proxy.async.shared::cta;" ::: "memory"); }
__device__ __forceinline__ void bar_sync(int id, int n) { asm volatile("bar.sync %0, %1;" ::"r"(id), "r"(n) : "memory"); }

__device__ __forceinline__ void tma2d(uint32_t dst, const CUtensorMap* m, uint32_t bar, int c0, int c1) {
  asm volatile("cp.async.bulk.tensor.2d.shared::cluster.global.mbarrier::complete_tx::bytes [%0], [%1, {%3, %4}], [%2];"
               ::"r"(dst), "l"(m), "r"(bar), "r"(c0), "r"(c1) : "memory");
}
__device__ __forceinline__ void tma2d_mc(uint32_t dst, const CUtensorMap* m, uint32_t bar, int c0, int c1) {
  asm volatile("cp.async.bulk.tensor.2d.shared::cluster.global.mbarrier::complete_tx::bytes.multicast::cluster"
               " [%0], [%1, {%3, %4}], [%2], %5;"
               ::"r"(dst), "l"(m), "r"(bar), "r"(c0), "r"(c1), "h"((uint16_t)3) : "memory");
}
__device__ __forceinline__ void tma3d(uint32_t dst, const CUtensorMap* m, uint32_t bar, int c0, int c1, int c2) {
  asm volatile("cp.async.bulk.tensor.3d.shared::cluster.global.mbarrier::complete_tx::bytes [%0], [%1, {%3, %4, %5}], [%2];"
               ::"r"(dst), "l"(m), "r"(bar), "r"(c0), "r"(c1), "r"(c2) : "memory");
}
__device__ __forceinline__ void tma4d(uint32_t dst, const CUtensorMap* m, uint32_t bar, int c0, int c1, int c2, int c3) {
  asm volatile("cp.async.bulk.tensor.4d.shared::cluster.global.mbarrier::complete_tx::bytes [%0], [%1, {%3, %4, %5, %6}], [%2];"
               ::"r"(dst), "l"(m), "r"(bar), "r"(c0), "r"(c1), "r"(c2), "r"(c3) : "memory");
}
__device__ __forceinline__ void tma2d_store(const CUtensorMap* m, uint32_t src, int c0, int c1) {
  asm volatile("cp.async.bulk.tensor.2d.global.shared::cta.bulk_group [%0, {%2, %3}], [%1];"
               ::"l"(m), "r"(src), "r"(c0), "r"(c1) : "memory");
}
__device__ __forceinline__ void bulk_store(void* dst, uint32_t src, uint32_t bytes) {
  asm volatile("cp.async.bulk.global.shared::cta.bulk_group [%0], [%1], %2;" ::"l"(dst), "r"(src), "r"(bytes) : "memory");
}
__device__ __forceinline__ void bulk_load(uint32_t dst, const void* src, uint32_t bytes, uint32_t bar) {
  asm volatile("cp.async.bulk.shared::cluster.global.mbarrier::complete_tx::bytes [%0], [%1], %2, [%3];"
               ::"r"(dst), "l"(src), "r"(bytes), "r"(bar) : "memory");
}
__device__ __forceinline__ void bulk_commit() { asm volatile("cp.async.bulk.commit_group;" ::: "memory"); }
template <int N> __device__ __forceinline__ void bulk_wait() { asm volatile("cp.async.bulk.wait_group %0;" ::"n"(N) : "memory"); }
__device__ __forceinline__ void bulk_wait_read() { asm volatile("cp.async.bulk.wait_group.read 0;" ::: "memory"); }
__device__ __forceinline__ void bar_arrive(int id, int n) { asm volatile("bar.arrive %0, %1;" ::"r"(id), "r"(n) : "memory"); }
__device__ __forceinline__ uint4 lds128(uint32_t a) {
  uint4 v;
  asm volatile("ld.shared.v4.u32 {%0, %1, %2, %3}, [%4];" : "=r"(v.x), "=r"(v.y), "=r"(v.z), "=r"(v.w) : "r"(a) : "memory");
  return v;
}
__device__ __forceinline__ void sts128(uint32_t a, uint4 v) {
  asm volatile("st.shared.v4.u32 [%0], {%1, %2, %3, %4};" ::"r"(a), "r"(v.x), "r"(v.y), "r"(v.z), "r"(v.w) : "memory");
}
__device__ __forceinline__ uint32_t map_peer(uint32_t addr, uint32_t cta) {
  uint32_t r;
  asm("mapa.shared::cluster.u32 %0, %1, %2;" : "=r"(r) : "r"(addr), "r"(cta));
  return r;
}
__device__ __forceinline__ void st_async16(uint32_t addr, uint32_t a, uint32_t b, uint32_t c, uint32_t d, uint32_t bar) {
  asm volatile("st.async.weak.shared::cluster.mbarrier::complete_tx::bytes.v4.b32 [%0], {%1, %2, %3, %4}, [%5];"
               ::"r"(addr), "r"(a), "r"(b), "r"(c), "r"(d), "r"(bar) : "memory");
}
__device__ __forceinline__ void l2_prefetch(const void* p, uint32_t bytes) {
  asm volatile("cp.async.bulk.prefetch.L2.global [%0], %1;" ::"l"(p), "r"(bytes) : "memory");
}
__device__ __forceinline__ void prefetch_tmap(const CUtensorMap* m) {
  asm volatile("prefetch.tensormap [%0];" ::"l"(m) : "memory");
}
__device__ __forceinline__ uint64_t make_desc(uint32_t a16, uint32_t off, uint32_t lbo, uint32_t sbo, uint32_t swz) {
  const uint32_t lo = a16 + ((off >> 4) + ((lbo >> 4) << 16)), hi = (sbo >> 4) | (swz << 30);
  uint64_t d;
  asm("mov.b64 %0, {%1, %2};" : "=l"(d) : "r"(lo), "r"(hi));
  return d;
}
__device__ __forceinline__ void wg_fence() { asm volatile("wgmma.fence.sync.aligned;" ::: "memory"); }
__device__ __forceinline__ void wg_commit() { asm volatile("wgmma.commit_group.sync.aligned;" ::: "memory"); }
template <int N> __device__ __forceinline__ void wg_wait() { asm volatile("wgmma.wait_group.sync.aligned %0;" ::"n"(N) : "memory"); }
template <int N> __device__ __forceinline__ void fence_regs(float (&d)[N]) {
#pragma unroll
  for (int i = 0; i < N; i++) asm volatile("" : "+f"(d[i])::"memory");
}
template <int N> __device__ __forceinline__ void zero_regs(float (&d)[N]) {
#pragma unroll
  for (int i = 0; i < N; i++) d[i] = 0.f;
}
__device__ __forceinline__ uint32_t pack_bf16(float lo, float hi) {
  uint32_t r;
  asm("cvt.rn.bf16x2.f32 %0, %1, %2;" : "=r"(r) : "f"(hi), "f"(lo));
  return r;
}
__device__ __forceinline__ float bf_lo(uint32_t v) { return __uint_as_float(v << 16); }
__device__ __forceinline__ float bf_hi(uint32_t v) { return __uint_as_float(v & 0xffff0000u); }
__device__ __forceinline__ uint32_t max_bf2(uint32_t a, uint32_t b) {
  uint32_t r; asm("max.bf16x2 %0, %1, %2;" : "=r"(r) : "r"(a), "r"(b)); return r;
}
__device__ __forceinline__ uint32_t min_bf2(uint32_t a, uint32_t b) {
  uint32_t r; asm("min.bf16x2 %0, %1, %2;" : "=r"(r) : "r"(a), "r"(b)); return r;
}
__device__ __forceinline__ float ex2(float x) { float r; asm("ex2.approx.ftz.f32 %0, %1;" : "=f"(r) : "f"(x)); return r; }
__device__ __forceinline__ float rcp(float x) { float r; asm("rcp.approx.ftz.f32 %0, %1;" : "=f"(r) : "f"(x)); return r; }
__device__ __forceinline__ float tanh_ap(float x) { float r; asm("tanh.approx.f32 %0, %1;" : "=f"(r) : "f"(x)); return r; }
__device__ __forceinline__ float gelu_s(float x, float hs) {
  float u = x * fmaf(x * x, 0.0356774081f, 0.7978845608f);
  float hx = x * hs;
  return fmaf(hx, tanh_ap(u), hx);
}
__device__ __forceinline__ void stsm4(uint32_t addr, uint32_t r0, uint32_t r1, uint32_t r2, uint32_t r3) {
  asm volatile("stmatrix.sync.aligned.m8n8.x4.shared.b16 [%0], {%1, %2, %3, %4};"
               ::"r"(addr), "r"(r0), "r"(r1), "r"(r2), "r"(r3) : "memory");
}
__device__ __forceinline__ void red_add4(float* p, float a, float b, float c, float d) {
  asm volatile("red.global.add.v4.f32 [%0], {%1, %2, %3, %4};" ::"l"(p), "f"(a), "f"(b), "f"(c), "f"(d) : "memory");
}
__device__ __forceinline__ void red_add2(float* p, float a, float b) {
  asm volatile("red.global.add.v2.f32 [%0], {%1, %2};" ::"l"(p), "f"(a), "f"(b) : "memory");
}

__device__ __forceinline__ void mma_ss256(float (&d)[128], uint64_t descA, uint64_t descB) {
  asm volatile("wgmma.mma_async.sync.aligned.m64n256k16.f32.bf16.bf16 {"
      "%0, %1, %2, %3, %4, %5, %6, %7, %8, %9, %10, %11, %12, %13, %14, %15, "
      "%16, %17, %18, %19, %20, %21, %22, %23, %24, %25, %26, %27, %28, %29, %30, %31, "
      "%32, %33, %34, %35, %36, %37, %38, %39, %40, %41, %42, %43, %44, %45, %46, %47, "
      "%48, %49, %50, %51, %52, %53, %54, %55, %56, %57, %58, %59, %60, %61, %62, %63, "
      "%64, %65, %66, %67, %68, %69, %70, %71, %72, %73, %74, %75, %76, %77, %78, %79, "
      "%80, %81, %82, %83, %84, %85, %86, %87, %88, %89, %90, %91, %92, %93, %94, %95, "
      "%96, %97, %98, %99, %100, %101, %102, %103, %104, %105, %106, %107, %108, %109, %110, %111, "
      "%112, %113, %114, %115, %116, %117, %118, %119, %120, %121, %122, %123, %124, %125, %126, %127"
      "}, %128, %129, 1, 1, 1, 0, 1;\n"
      : "+f"(d[0]), "+f"(d[1]), "+f"(d[2]), "+f"(d[3]), "+f"(d[4]), "+f"(d[5]), "+f"(d[6]), "+f"(d[7]),
        "+f"(d[8]), "+f"(d[9]), "+f"(d[10]), "+f"(d[11]), "+f"(d[12]), "+f"(d[13]), "+f"(d[14]), "+f"(d[15]),
        "+f"(d[16]), "+f"(d[17]), "+f"(d[18]), "+f"(d[19]), "+f"(d[20]), "+f"(d[21]), "+f"(d[22]), "+f"(d[23]),
        "+f"(d[24]), "+f"(d[25]), "+f"(d[26]), "+f"(d[27]), "+f"(d[28]), "+f"(d[29]), "+f"(d[30]), "+f"(d[31]),
        "+f"(d[32]), "+f"(d[33]), "+f"(d[34]), "+f"(d[35]), "+f"(d[36]), "+f"(d[37]), "+f"(d[38]), "+f"(d[39]),
        "+f"(d[40]), "+f"(d[41]), "+f"(d[42]), "+f"(d[43]), "+f"(d[44]), "+f"(d[45]), "+f"(d[46]), "+f"(d[47]),
        "+f"(d[48]), "+f"(d[49]), "+f"(d[50]), "+f"(d[51]), "+f"(d[52]), "+f"(d[53]), "+f"(d[54]), "+f"(d[55]),
        "+f"(d[56]), "+f"(d[57]), "+f"(d[58]), "+f"(d[59]), "+f"(d[60]), "+f"(d[61]), "+f"(d[62]), "+f"(d[63]),
        "+f"(d[64]), "+f"(d[65]), "+f"(d[66]), "+f"(d[67]), "+f"(d[68]), "+f"(d[69]), "+f"(d[70]), "+f"(d[71]),
        "+f"(d[72]), "+f"(d[73]), "+f"(d[74]), "+f"(d[75]), "+f"(d[76]), "+f"(d[77]), "+f"(d[78]), "+f"(d[79]),
        "+f"(d[80]), "+f"(d[81]), "+f"(d[82]), "+f"(d[83]), "+f"(d[84]), "+f"(d[85]), "+f"(d[86]), "+f"(d[87]),
        "+f"(d[88]), "+f"(d[89]), "+f"(d[90]), "+f"(d[91]), "+f"(d[92]), "+f"(d[93]), "+f"(d[94]), "+f"(d[95]),
        "+f"(d[96]), "+f"(d[97]), "+f"(d[98]), "+f"(d[99]), "+f"(d[100]), "+f"(d[101]), "+f"(d[102]), "+f"(d[103]),
        "+f"(d[104]), "+f"(d[105]), "+f"(d[106]), "+f"(d[107]), "+f"(d[108]), "+f"(d[109]), "+f"(d[110]), "+f"(d[111]),
        "+f"(d[112]), "+f"(d[113]), "+f"(d[114]), "+f"(d[115]), "+f"(d[116]), "+f"(d[117]), "+f"(d[118]), "+f"(d[119]),
        "+f"(d[120]), "+f"(d[121]), "+f"(d[122]), "+f"(d[123]), "+f"(d[124]), "+f"(d[125]), "+f"(d[126]), "+f"(d[127])
      : "l"(descA), "l"(descB));
}

__device__ __forceinline__ void mma_ss64(float (&d)[32], uint64_t descA, uint64_t descB) {
  asm volatile("wgmma.mma_async.sync.aligned.m64n64k16.f32.bf16.bf16 {"
      "%0, %1, %2, %3, %4, %5, %6, %7, %8, %9, %10, %11, %12, %13, %14, %15, "
      "%16, %17, %18, %19, %20, %21, %22, %23, %24, %25, %26, %27, %28, %29, %30, %31"
      "}, %32, %33, 1, 1, 1, 0, 1;\n"
      : "+f"(d[0]), "+f"(d[1]), "+f"(d[2]), "+f"(d[3]), "+f"(d[4]), "+f"(d[5]), "+f"(d[6]), "+f"(d[7]),
        "+f"(d[8]), "+f"(d[9]), "+f"(d[10]), "+f"(d[11]), "+f"(d[12]), "+f"(d[13]), "+f"(d[14]), "+f"(d[15]),
        "+f"(d[16]), "+f"(d[17]), "+f"(d[18]), "+f"(d[19]), "+f"(d[20]), "+f"(d[21]), "+f"(d[22]), "+f"(d[23]),
        "+f"(d[24]), "+f"(d[25]), "+f"(d[26]), "+f"(d[27]), "+f"(d[28]), "+f"(d[29]), "+f"(d[30]), "+f"(d[31])
      : "l"(descA), "l"(descB));
}

__device__ __forceinline__ void mma_ss80(float (&d)[40], uint64_t descA, uint64_t descB) {
  asm volatile("wgmma.mma_async.sync.aligned.m64n80k16.f32.bf16.bf16 {"
      "%0, %1, %2, %3, %4, %5, %6, %7, %8, %9, %10, %11, %12, %13, %14, %15, "
      "%16, %17, %18, %19, %20, %21, %22, %23, %24, %25, %26, %27, %28, %29, %30, %31, "
      "%32, %33, %34, %35, %36, %37, %38, %39"
      "}, %40, %41, 1, 1, 1, 0, 1;\n"
      : "+f"(d[0]), "+f"(d[1]), "+f"(d[2]), "+f"(d[3]), "+f"(d[4]), "+f"(d[5]), "+f"(d[6]), "+f"(d[7]),
        "+f"(d[8]), "+f"(d[9]), "+f"(d[10]), "+f"(d[11]), "+f"(d[12]), "+f"(d[13]), "+f"(d[14]), "+f"(d[15]),
        "+f"(d[16]), "+f"(d[17]), "+f"(d[18]), "+f"(d[19]), "+f"(d[20]), "+f"(d[21]), "+f"(d[22]), "+f"(d[23]),
        "+f"(d[24]), "+f"(d[25]), "+f"(d[26]), "+f"(d[27]), "+f"(d[28]), "+f"(d[29]), "+f"(d[30]), "+f"(d[31]),
        "+f"(d[32]), "+f"(d[33]), "+f"(d[34]), "+f"(d[35]), "+f"(d[36]), "+f"(d[37]), "+f"(d[38]), "+f"(d[39])
      : "l"(descA), "l"(descB));
}

__device__ __forceinline__ void mma_ss192(float (&d)[96], uint64_t descA, uint64_t descB) {
  asm volatile("wgmma.mma_async.sync.aligned.m64n192k16.f32.bf16.bf16 {"
      "%0, %1, %2, %3, %4, %5, %6, %7, %8, %9, %10, %11, %12, %13, %14, %15, "
      "%16, %17, %18, %19, %20, %21, %22, %23, %24, %25, %26, %27, %28, %29, %30, %31, "
      "%32, %33, %34, %35, %36, %37, %38, %39, %40, %41, %42, %43, %44, %45, %46, %47, "
      "%48, %49, %50, %51, %52, %53, %54, %55, %56, %57, %58, %59, %60, %61, %62, %63, "
      "%64, %65, %66, %67, %68, %69, %70, %71, %72, %73, %74, %75, %76, %77, %78, %79, "
      "%80, %81, %82, %83, %84, %85, %86, %87, %88, %89, %90, %91, %92, %93, %94, %95"
      "}, %96, %97, 1, 1, 1, 0, 1;\n"
      : "+f"(d[0]), "+f"(d[1]), "+f"(d[2]), "+f"(d[3]), "+f"(d[4]), "+f"(d[5]), "+f"(d[6]), "+f"(d[7]),
        "+f"(d[8]), "+f"(d[9]), "+f"(d[10]), "+f"(d[11]), "+f"(d[12]), "+f"(d[13]), "+f"(d[14]), "+f"(d[15]),
        "+f"(d[16]), "+f"(d[17]), "+f"(d[18]), "+f"(d[19]), "+f"(d[20]), "+f"(d[21]), "+f"(d[22]), "+f"(d[23]),
        "+f"(d[24]), "+f"(d[25]), "+f"(d[26]), "+f"(d[27]), "+f"(d[28]), "+f"(d[29]), "+f"(d[30]), "+f"(d[31]),
        "+f"(d[32]), "+f"(d[33]), "+f"(d[34]), "+f"(d[35]), "+f"(d[36]), "+f"(d[37]), "+f"(d[38]), "+f"(d[39]),
        "+f"(d[40]), "+f"(d[41]), "+f"(d[42]), "+f"(d[43]), "+f"(d[44]), "+f"(d[45]), "+f"(d[46]), "+f"(d[47]),
        "+f"(d[48]), "+f"(d[49]), "+f"(d[50]), "+f"(d[51]), "+f"(d[52]), "+f"(d[53]), "+f"(d[54]), "+f"(d[55]),
        "+f"(d[56]), "+f"(d[57]), "+f"(d[58]), "+f"(d[59]), "+f"(d[60]), "+f"(d[61]), "+f"(d[62]), "+f"(d[63]),
        "+f"(d[64]), "+f"(d[65]), "+f"(d[66]), "+f"(d[67]), "+f"(d[68]), "+f"(d[69]), "+f"(d[70]), "+f"(d[71]),
        "+f"(d[72]), "+f"(d[73]), "+f"(d[74]), "+f"(d[75]), "+f"(d[76]), "+f"(d[77]), "+f"(d[78]), "+f"(d[79]),
        "+f"(d[80]), "+f"(d[81]), "+f"(d[82]), "+f"(d[83]), "+f"(d[84]), "+f"(d[85]), "+f"(d[86]), "+f"(d[87]),
        "+f"(d[88]), "+f"(d[89]), "+f"(d[90]), "+f"(d[91]), "+f"(d[92]), "+f"(d[93]), "+f"(d[94]), "+f"(d[95])
      : "l"(descA), "l"(descB));
}

__device__ __forceinline__ void mma_ss80_tt(float (&d)[40], uint64_t descA, uint64_t descB) {
  asm volatile("wgmma.mma_async.sync.aligned.m64n80k16.f32.bf16.bf16 {"
      "%0, %1, %2, %3, %4, %5, %6, %7, %8, %9, %10, %11, %12, %13, %14, %15, "
      "%16, %17, %18, %19, %20, %21, %22, %23, %24, %25, %26, %27, %28, %29, %30, %31, "
      "%32, %33, %34, %35, %36, %37, %38, %39"
      "}, %40, %41, 1, 1, 1, 1, 1;\n"
      : "+f"(d[0]), "+f"(d[1]), "+f"(d[2]), "+f"(d[3]), "+f"(d[4]), "+f"(d[5]), "+f"(d[6]), "+f"(d[7]),
        "+f"(d[8]), "+f"(d[9]), "+f"(d[10]), "+f"(d[11]), "+f"(d[12]), "+f"(d[13]), "+f"(d[14]), "+f"(d[15]),
        "+f"(d[16]), "+f"(d[17]), "+f"(d[18]), "+f"(d[19]), "+f"(d[20]), "+f"(d[21]), "+f"(d[22]), "+f"(d[23]),
        "+f"(d[24]), "+f"(d[25]), "+f"(d[26]), "+f"(d[27]), "+f"(d[28]), "+f"(d[29]), "+f"(d[30]), "+f"(d[31]),
        "+f"(d[32]), "+f"(d[33]), "+f"(d[34]), "+f"(d[35]), "+f"(d[36]), "+f"(d[37]), "+f"(d[38]), "+f"(d[39])
      : "l"(descA), "l"(descB));
}
__device__ __forceinline__ void mma_ss80_tt_z(float (&d)[40], uint64_t descA, uint64_t descB) {
  asm volatile("wgmma.mma_async.sync.aligned.m64n80k16.f32.bf16.bf16 {"
      "%0, %1, %2, %3, %4, %5, %6, %7, %8, %9, %10, %11, %12, %13, %14, %15, "
      "%16, %17, %18, %19, %20, %21, %22, %23, %24, %25, %26, %27, %28, %29, %30, %31, "
      "%32, %33, %34, %35, %36, %37, %38, %39"
      "}, %40, %41, 0, 1, 1, 1, 1;\n"
      : "=f"(d[0]), "=f"(d[1]), "=f"(d[2]), "=f"(d[3]), "=f"(d[4]), "=f"(d[5]), "=f"(d[6]), "=f"(d[7]),
        "=f"(d[8]), "=f"(d[9]), "=f"(d[10]), "=f"(d[11]), "=f"(d[12]), "=f"(d[13]), "=f"(d[14]), "=f"(d[15]),
        "=f"(d[16]), "=f"(d[17]), "=f"(d[18]), "=f"(d[19]), "=f"(d[20]), "=f"(d[21]), "=f"(d[22]), "=f"(d[23]),
        "=f"(d[24]), "=f"(d[25]), "=f"(d[26]), "=f"(d[27]), "=f"(d[28]), "=f"(d[29]), "=f"(d[30]), "=f"(d[31]),
        "=f"(d[32]), "=f"(d[33]), "=f"(d[34]), "=f"(d[35]), "=f"(d[36]), "=f"(d[37]), "=f"(d[38]), "=f"(d[39])
      : "l"(descA), "l"(descB));
}

__device__ __forceinline__ void mma_rs80_k(float (&d)[40], const uint32_t (&a)[4], uint64_t descB) {
  asm volatile("wgmma.mma_async.sync.aligned.m64n80k16.f32.bf16.bf16 {"
      "%0, %1, %2, %3, %4, %5, %6, %7, %8, %9, %10, %11, %12, %13, %14, %15, "
      "%16, %17, %18, %19, %20, %21, %22, %23, %24, %25, %26, %27, %28, %29, %30, %31, "
      "%32, %33, %34, %35, %36, %37, %38, %39"
      "}, {%40, %41, %42, %43}, %44, 1, 1, 1, 0;\n"
      : "+f"(d[0]), "+f"(d[1]), "+f"(d[2]), "+f"(d[3]), "+f"(d[4]), "+f"(d[5]), "+f"(d[6]), "+f"(d[7]),
        "+f"(d[8]), "+f"(d[9]), "+f"(d[10]), "+f"(d[11]), "+f"(d[12]), "+f"(d[13]), "+f"(d[14]), "+f"(d[15]),
        "+f"(d[16]), "+f"(d[17]), "+f"(d[18]), "+f"(d[19]), "+f"(d[20]), "+f"(d[21]), "+f"(d[22]), "+f"(d[23]),
        "+f"(d[24]), "+f"(d[25]), "+f"(d[26]), "+f"(d[27]), "+f"(d[28]), "+f"(d[29]), "+f"(d[30]), "+f"(d[31]),
        "+f"(d[32]), "+f"(d[33]), "+f"(d[34]), "+f"(d[35]), "+f"(d[36]), "+f"(d[37]), "+f"(d[38]), "+f"(d[39])
      : "r"(a[0]), "r"(a[1]), "r"(a[2]), "r"(a[3]), "l"(descB));
}
__device__ __forceinline__ void mma_rs80_k_z(float (&d)[40], const uint32_t (&a)[4], uint64_t descB) {
  asm volatile("wgmma.mma_async.sync.aligned.m64n80k16.f32.bf16.bf16 {"
      "%0, %1, %2, %3, %4, %5, %6, %7, %8, %9, %10, %11, %12, %13, %14, %15, "
      "%16, %17, %18, %19, %20, %21, %22, %23, %24, %25, %26, %27, %28, %29, %30, %31, "
      "%32, %33, %34, %35, %36, %37, %38, %39"
      "}, {%40, %41, %42, %43}, %44, 0, 1, 1, 0;\n"
      : "=f"(d[0]), "=f"(d[1]), "=f"(d[2]), "=f"(d[3]), "=f"(d[4]), "=f"(d[5]), "=f"(d[6]), "=f"(d[7]),
        "=f"(d[8]), "=f"(d[9]), "=f"(d[10]), "=f"(d[11]), "=f"(d[12]), "=f"(d[13]), "=f"(d[14]), "=f"(d[15]),
        "=f"(d[16]), "=f"(d[17]), "=f"(d[18]), "=f"(d[19]), "=f"(d[20]), "=f"(d[21]), "=f"(d[22]), "=f"(d[23]),
        "=f"(d[24]), "=f"(d[25]), "=f"(d[26]), "=f"(d[27]), "=f"(d[28]), "=f"(d[29]), "=f"(d[30]), "=f"(d[31]),
        "=f"(d[32]), "=f"(d[33]), "=f"(d[34]), "=f"(d[35]), "=f"(d[36]), "=f"(d[37]), "=f"(d[38]), "=f"(d[39])
      : "r"(a[0]), "r"(a[1]), "r"(a[2]), "r"(a[3]), "l"(descB));
}

__device__ __forceinline__ void mma_rs48_k(float (&d)[24], const uint32_t (&a)[4], uint64_t descB) {
  asm volatile("wgmma.mma_async.sync.aligned.m64n48k16.f32.bf16.bf16 {"
      "%0, %1, %2, %3, %4, %5, %6, %7, %8, %9, %10, %11, %12, %13, %14, %15, "
      "%16, %17, %18, %19, %20, %21, %22, %23"
      "}, {%24, %25, %26, %27}, %28, 1, 1, 1, 0;\n"
      : "+f"(d[0]), "+f"(d[1]), "+f"(d[2]), "+f"(d[3]), "+f"(d[4]), "+f"(d[5]), "+f"(d[6]), "+f"(d[7]),
        "+f"(d[8]), "+f"(d[9]), "+f"(d[10]), "+f"(d[11]), "+f"(d[12]), "+f"(d[13]), "+f"(d[14]), "+f"(d[15]),
        "+f"(d[16]), "+f"(d[17]), "+f"(d[18]), "+f"(d[19]), "+f"(d[20]), "+f"(d[21]), "+f"(d[22]), "+f"(d[23])
      : "r"(a[0]), "r"(a[1]), "r"(a[2]), "r"(a[3]), "l"(descB));
}
__device__ __forceinline__ void mma_rs48_k_z(float (&d)[24], const uint32_t (&a)[4], uint64_t descB) {
  asm volatile("wgmma.mma_async.sync.aligned.m64n48k16.f32.bf16.bf16 {"
      "%0, %1, %2, %3, %4, %5, %6, %7, %8, %9, %10, %11, %12, %13, %14, %15, "
      "%16, %17, %18, %19, %20, %21, %22, %23"
      "}, {%24, %25, %26, %27}, %28, 0, 1, 1, 0;\n"
      : "=f"(d[0]), "=f"(d[1]), "=f"(d[2]), "=f"(d[3]), "=f"(d[4]), "=f"(d[5]), "=f"(d[6]), "=f"(d[7]),
        "=f"(d[8]), "=f"(d[9]), "=f"(d[10]), "=f"(d[11]), "=f"(d[12]), "=f"(d[13]), "=f"(d[14]), "=f"(d[15]),
        "=f"(d[16]), "=f"(d[17]), "=f"(d[18]), "=f"(d[19]), "=f"(d[20]), "=f"(d[21]), "=f"(d[22]), "=f"(d[23])
      : "r"(a[0]), "r"(a[1]), "r"(a[2]), "r"(a[3]), "l"(descB));
}

__device__ __forceinline__ void mma_rs160_n(float (&d)[80], const uint32_t (&a)[4], uint64_t descB) {
  asm volatile("wgmma.mma_async.sync.aligned.m64n160k16.f32.bf16.bf16 {"
      "%0, %1, %2, %3, %4, %5, %6, %7, %8, %9, %10, %11, %12, %13, %14, %15, "
      "%16, %17, %18, %19, %20, %21, %22, %23, %24, %25, %26, %27, %28, %29, %30, %31, "
      "%32, %33, %34, %35, %36, %37, %38, %39, %40, %41, %42, %43, %44, %45, %46, %47, "
      "%48, %49, %50, %51, %52, %53, %54, %55, %56, %57, %58, %59, %60, %61, %62, %63, "
      "%64, %65, %66, %67, %68, %69, %70, %71, %72, %73, %74, %75, %76, %77, %78, %79"
      "}, {%80, %81, %82, %83}, %84, 1, 1, 1, 1;\n"
      : "+f"(d[0]), "+f"(d[1]), "+f"(d[2]), "+f"(d[3]), "+f"(d[4]), "+f"(d[5]), "+f"(d[6]), "+f"(d[7]),
        "+f"(d[8]), "+f"(d[9]), "+f"(d[10]), "+f"(d[11]), "+f"(d[12]), "+f"(d[13]), "+f"(d[14]), "+f"(d[15]),
        "+f"(d[16]), "+f"(d[17]), "+f"(d[18]), "+f"(d[19]), "+f"(d[20]), "+f"(d[21]), "+f"(d[22]), "+f"(d[23]),
        "+f"(d[24]), "+f"(d[25]), "+f"(d[26]), "+f"(d[27]), "+f"(d[28]), "+f"(d[29]), "+f"(d[30]), "+f"(d[31]),
        "+f"(d[32]), "+f"(d[33]), "+f"(d[34]), "+f"(d[35]), "+f"(d[36]), "+f"(d[37]), "+f"(d[38]), "+f"(d[39]),
        "+f"(d[40]), "+f"(d[41]), "+f"(d[42]), "+f"(d[43]), "+f"(d[44]), "+f"(d[45]), "+f"(d[46]), "+f"(d[47]),
        "+f"(d[48]), "+f"(d[49]), "+f"(d[50]), "+f"(d[51]), "+f"(d[52]), "+f"(d[53]), "+f"(d[54]), "+f"(d[55]),
        "+f"(d[56]), "+f"(d[57]), "+f"(d[58]), "+f"(d[59]), "+f"(d[60]), "+f"(d[61]), "+f"(d[62]), "+f"(d[63]),
        "+f"(d[64]), "+f"(d[65]), "+f"(d[66]), "+f"(d[67]), "+f"(d[68]), "+f"(d[69]), "+f"(d[70]), "+f"(d[71]),
        "+f"(d[72]), "+f"(d[73]), "+f"(d[74]), "+f"(d[75]), "+f"(d[76]), "+f"(d[77]), "+f"(d[78]), "+f"(d[79])
      : "r"(a[0]), "r"(a[1]), "r"(a[2]), "r"(a[3]), "l"(descB));
}
__device__ __forceinline__ void mma_rs160_n_z(float (&d)[80], const uint32_t (&a)[4], uint64_t descB) {
  asm volatile("wgmma.mma_async.sync.aligned.m64n160k16.f32.bf16.bf16 {"
      "%0, %1, %2, %3, %4, %5, %6, %7, %8, %9, %10, %11, %12, %13, %14, %15, "
      "%16, %17, %18, %19, %20, %21, %22, %23, %24, %25, %26, %27, %28, %29, %30, %31, "
      "%32, %33, %34, %35, %36, %37, %38, %39, %40, %41, %42, %43, %44, %45, %46, %47, "
      "%48, %49, %50, %51, %52, %53, %54, %55, %56, %57, %58, %59, %60, %61, %62, %63, "
      "%64, %65, %66, %67, %68, %69, %70, %71, %72, %73, %74, %75, %76, %77, %78, %79"
      "}, {%80, %81, %82, %83}, %84, 0, 1, 1, 1;\n"
      : "=f"(d[0]), "=f"(d[1]), "=f"(d[2]), "=f"(d[3]), "=f"(d[4]), "=f"(d[5]), "=f"(d[6]), "=f"(d[7]),
        "=f"(d[8]), "=f"(d[9]), "=f"(d[10]), "=f"(d[11]), "=f"(d[12]), "=f"(d[13]), "=f"(d[14]), "=f"(d[15]),
        "=f"(d[16]), "=f"(d[17]), "=f"(d[18]), "=f"(d[19]), "=f"(d[20]), "=f"(d[21]), "=f"(d[22]), "=f"(d[23]),
        "=f"(d[24]), "=f"(d[25]), "=f"(d[26]), "=f"(d[27]), "=f"(d[28]), "=f"(d[29]), "=f"(d[30]), "=f"(d[31]),
        "=f"(d[32]), "=f"(d[33]), "=f"(d[34]), "=f"(d[35]), "=f"(d[36]), "=f"(d[37]), "=f"(d[38]), "=f"(d[39]),
        "=f"(d[40]), "=f"(d[41]), "=f"(d[42]), "=f"(d[43]), "=f"(d[44]), "=f"(d[45]), "=f"(d[46]), "=f"(d[47]),
        "=f"(d[48]), "=f"(d[49]), "=f"(d[50]), "=f"(d[51]), "=f"(d[52]), "=f"(d[53]), "=f"(d[54]), "=f"(d[55]),
        "=f"(d[56]), "=f"(d[57]), "=f"(d[58]), "=f"(d[59]), "=f"(d[60]), "=f"(d[61]), "=f"(d[62]), "=f"(d[63]),
        "=f"(d[64]), "=f"(d[65]), "=f"(d[66]), "=f"(d[67]), "=f"(d[68]), "=f"(d[69]), "=f"(d[70]), "=f"(d[71]),
        "=f"(d[72]), "=f"(d[73]), "=f"(d[74]), "=f"(d[75]), "=f"(d[76]), "=f"(d[77]), "=f"(d[78]), "=f"(d[79])
      : "r"(a[0]), "r"(a[1]), "r"(a[2]), "r"(a[3]), "l"(descB));
}

__device__ __forceinline__ void feature_map(const uint32_t (&P)[2][10], uint32_t (&fr)[10][4]) {
  constexpr float L2E = 1.4426950408889634f;
#pragma unroll
  for (int p = 0; p < 2; p++) {
#pragma unroll
    for (int r = 0; r < 2; r++) {
      uint32_t mx = P[r][5 * p], mn = mx;
#pragma unroll
      for (int g = 1; g < 5; g++) { mx = max_bf2(mx, P[r][5 * p + g]); mn = min_bf2(mn, P[r][5 * p + g]); }
      mx = max_bf2(mx, __shfl_xor_sync(0xffffffffu, mx, 1));
      mn = min_bf2(mn, __shfl_xor_sync(0xffffffffu, mn, 1));
      mx = max_bf2(mx, __shfl_xor_sync(0xffffffffu, mx, 2));
      mn = min_bf2(mn, __shfl_xor_sync(0xffffffffu, mn, 2));
      float mx0 = -bf_lo(mx) * L2E, mx1 = -bf_hi(mx) * L2E, mn0 = bf_lo(mn) * L2E, mn1 = bf_hi(mn) * L2E;
      float ep0[5], ep1[5], en0[5], en1[5];
      float sp0 = 0.f, sp1 = 0.f, sn0 = 0.f, sn1 = 0.f;
#pragma unroll
      for (int g = 0; g < 5; g++) {
        float x0 = bf_lo(P[r][5 * p + g]), x1 = bf_hi(P[r][5 * p + g]);
        ep0[g] = ex2(fmaf(x0, L2E, mx0)); ep1[g] = ex2(fmaf(x1, L2E, mx1));
        en0[g] = ex2(fmaf(x0, -L2E, mn0)); en1[g] = ex2(fmaf(x1, -L2E, mn1));
        sp0 += ep0[g]; sp1 += ep1[g]; sn0 += en0[g]; sn1 += en1[g];
      }
      sp0 += __shfl_xor_sync(0xffffffffu, sp0, 1); sp1 += __shfl_xor_sync(0xffffffffu, sp1, 1);
      sn0 += __shfl_xor_sync(0xffffffffu, sn0, 1); sn1 += __shfl_xor_sync(0xffffffffu, sn1, 1);
      sp0 += __shfl_xor_sync(0xffffffffu, sp0, 2); sp1 += __shfl_xor_sync(0xffffffffu, sp1, 2);
      sn0 += __shfl_xor_sync(0xffffffffu, sn0, 2); sn1 += __shfl_xor_sync(0xffffffffu, sn1, 2);
      sp0 = rcp(sp0); sp1 = rcp(sp1); sn0 = rcp(sn0); sn1 = rcp(sn1);
#pragma unroll
      for (int g = 0; g < 5; g++) {
        fr[5 * p + g][r] = pack_bf16(ep0[g] * sp0, ep1[g] * sp1);
        fr[5 * p + g][2 + r] = pack_bf16(en0[g] * sn0, en1[g] * sn1);
      }
    }
  }
}

struct Ring {
  uint32_t idx, phase;
  template <int N> __device__ __forceinline__ void next() { if (++idx == N) { idx = 0; phase ^= 1; } }
};

}

__global__ void __cluster_dims__(2, 1, 1) __launch_bounds__(384, 1)
fused_kernel(const __grid_constant__ Maps maps, const __nv_bfloat16* __restrict__ x, const __nv_bfloat16* __restrict__ wqkv,
             const __nv_bfloat16* __restrict__ wphi, const __nv_bfloat16* __restrict__ w1, const __nv_bfloat16* __restrict__ w2,
             const __nv_bfloat16* __restrict__ w3, const __nv_bfloat16* __restrict__ w4, const __nv_bfloat16* __restrict__ wo,
             const __nv_bfloat16* __restrict__ gate_w) {
  extern __shared__ __align__(1024) uint8_t sgen[];
  const uint32_t sb = smem_u32(sgen);
  const uint32_t sb16 = (sb & 0x3FFFFu) >> 4;
  const uint32_t bars = sb + OFF_BAR;
  const uint32_t fullA = bars + 8 * B_FULLA, emptyA = bars + 8 * B_EMPTYA, fullB = bars + 8 * B_FULLB, emptyB = bars + 8 * B_EMPTYB;

  const int tid = threadIdx.x;
  const int rank = blockIdx.x & 1;
  const int pairIdx = blockIdx.x >> 1;
  const int i = pairIdx >> 2, j = 2 * (pairIdx & 3) + rank;

  TSTAMP(0);
  uint4 pv[5], pw_[5], pc[2], pre;
  if (tid < 256) {
    const int row = 128 * i + 16 * j + (tid >> 4), l16 = tid & 15;
#pragma unroll
    for (int c = 0; c < 5; c++) pv[c] = __ldg(reinterpret_cast<const uint4*>(x + (size_t)row * D_ + c * 128 + l16 * 8));
    const int tq = tid < 200 ? tid : 0;
    const __nv_bfloat16* cp = w1 + (size_t)(40 * i + tq / 10) * D_ + 80 * j + 8 * (tq % 10);
    pc[0] = __ldg(reinterpret_cast<const uint4*>(cp)); pc[1] = __ldg(reinterpret_cast<const uint4*>(cp + 20 * D_));
    pre = __ldg(reinterpret_cast<const uint4*>(wphi + (size_t)j * 1600) + tq);
#pragma unroll
    for (int c = 0; c < 5; c++) pw_[c] = __ldg(reinterpret_cast<const uint4*>(gate_w + c * 128 + l16 * 8));
  }
  if ((tid & 31) == 0) {
#pragma unroll 1
    for (int b = tid >> 5; b < NBAR; b += 12) {
      mbar_init(bars + 8 * b, b < B_SEND ? 1 : b < B_EMPTYB ? 4 : b < B_EMPTYA ? 8 : 16);
      if (b >= B_DSR && b < B_SEND) mbar_expect_tx(bars + 8 * b, 10240);
    }
    asm volatile("fence.mbarrier_init.release.cluster;" ::: "memory");
  }
  if (tid == 352) { prefetch_tmap(&maps.x); prefetch_tmap(&maps.qm); prefetch_tmap(&maps.w1m); prefetch_tmap(&maps.qr); prefetch_tmap(&maps.w1r); }
  asm volatile("barrier.cluster.arrive.relaxed.aligned;" ::: "memory");

  if (tid >= 256) {
    asm volatile("setmaxnreg.dec.sync.aligned.u32 40;");
    asm volatile("barrier.cluster.wait.aligned;" ::: "memory");
    auto get_epoch = [&]() { return *reinterpret_cast<volatile unsigned*>(g_flags + FL_DONE * 32) / NCTA; };
    const int lane = tid & 31, pw = (tid >> 5) & 3;
    auto send_stream = [&](int w, unsigned ep1) {
#pragma unroll 1
      for (int c = 0; c < 3; c++) {
        const int d = (j + 2 * c + 2) & 7;
        mbar_wait(bars + 8 * (B_SEND + 2 * c + w), 0);
        if (w) TR4(c * 16 + 7);
        bulk_store(g_part + (size_t)((i * 8 + d) * 3 + c) * 1280 + w * 640, sb + OFF_SEND + w * 10240, 10240);
        bulk_commit();
        bulk_wait<0>();
        mbar_arrive(bars + 8 * (B_SDONE + 2 * c + w));
        if (w) TR4(c * 16 + 9);
        asm volatile("st.release.gpu.global.u32 [%0], %1;"
                     ::"l"(g_flags + (FL_PART + i * 8 + d) * 32 + 2 * c + w), "r"(ep1) : "memory");
        if (w) TR4(c * 16 + 10);
      }
    };
    if (pw == 0) {
      if (lane == 0) {
        Ring r{0, 1};
        unsigned ep1 = 0;
#pragma unroll 1
        for (int k = 0; k < 30; k++) {
          if (k == 4) ep1 = get_epoch() + 1;
          if (k == 10 || k == 20) {
            const unsigned tgt = ep1 * 8u;
            const unsigned* f0 = g_flags + (k == 10 ? FL_H + ((i - 1) & 15) : FL_X1 + i) * 32;
            const unsigned* f1 = g_flags + (k == 10 ? FL_H + i : FL_X1 + i) * 32;
            const unsigned* f2 = g_flags + (k == 10 ? FL_H + ((i + 1) & 15) : FL_X1 + i) * 32;
            uint32_t n = 0;
            while (++n < (WAIT_LIMIT >> 4)) {
              unsigned v0, v1, v2;
              asm volatile("ld.relaxed.gpu.global.u32 %0, [%3];\nld.relaxed.gpu.global.u32 %1, [%4];\nld.acquire.gpu.global.u32 %2, [%5];"
                           : "=r"(v0), "=r"(v1), "=r"(v2) : "l"(f0), "l"(f1), "l"(f2) : "memory");
              if ((int)((v0 - tgt) | (v1 - tgt) | (v2 - tgt)) >= 0) break;
            }
            TSTAMPX(k == 10 ? 29 : 30);
          }
          mbar_wait(emptyA + 8 * r.idx, r.phase);
          const uint32_t bar = fullA + 8 * r.idx, slot = sb + OFF_A + r.idx * SLOT_A;
          TRACE(k);
          mbar_expect_tx(bar, SLOT_A);
          tma2d_mc(slot + rank * 8192, k < 10 ? &maps.x : k < 20 ? &maps.hs : &maps.x1, bar, 64 * (k % 10), 128 * i + 64 * rank);
          r.next<NA>();
        }
        send_stream(1, ep1);
      }
    } else if (pw == 1) {
      if (lane == 0) {
        Ring r{0, 1};
#pragma unroll 1
        for (int k = 0; k < 18; k++) {
          mbar_wait(emptyB + 8 * r.idx, r.phase);
          const uint32_t bar = fullB + 8 * r.idx, slot = sb + OFF_B + r.idx * SLOT_B;
          if (k < 10) {
            mbar_expect_tx(bar, 40960);
            tma4d(slot + 8192, &maps.qm, bar, 0, 64 * k, 0, j);
            tma3d(slot, &maps.w1m, bar, 0, 64 * k, j);
            tma4d(slot + 32768 + 2048, &maps.qr, bar, 64, 64 * k, 0, j);
            tma3d(slot + 32768, &maps.w1r, bar, 64, 64 * k, j);
          } else if (k < 13) {
            if (k == 12) mbar_wait(fullA + 8 * 2, 0);
            mbar_expect_tx(bar, k < 12 ? 40960 : 20480);
#pragma unroll 1
            for (int u = 0; u < (k < 12 ? 4 : 2); u++) tma3d(slot + u * 10240, &maps.w2, bar, 0, 256 * (k - 10) + 64 * u, 5 * j);
          } else {
            mbar_expect_tx(bar, 49152);
            tma3d(slot, &maps.w3, bar, 0, 128 * (k - 13), 3 * j);
            tma3d(slot + 24576, &maps.w3, bar, 0, 128 * (k - 13) + 64, 3 * j);
          }
          r.next<NB>();
        }
        Ring r4{0, 1};
#pragma unroll 1
        for (int n = 0; n < 16; n++) {
          if (n == 0 || n == 1 || n == 3) { mbar_wait(emptyB + 8 * r.idx, r.phase); r.next<NB>(); }
          mbar_wait(bars + 8 * (B_EMPTY4 + r4.idx), r4.phase);
          const uint32_t bar = bars + 8 * (B_FULL4 + r4.idx), slot = sb + OFF_B + r4.idx * UNIT4;
          const int u = n & 3, m = ((j >> 1) + 1 + (n >> 2)) & 3;
          mbar_expect_tx(bar, u == 3 ? 25600 : 20480);
          tma3d(slot, u == 3 ? &maps.wo : &maps.w4, bar, 0, u == 3 ? 80 * j : 192 * j + 64 * u, 5 * m);
          r4.next<NU4>();
        }
      }
    } else {
      const unsigned epoch = get_epoch();
      float* accg = g_acc[epoch & 1];
      if (pw == 2) {
        {
          float* nxt = g_acc[(epoch + 1) & 1];
          constexpr int PER = ACC_FLOATS / NCTA;
#pragma unroll 1
          for (int e = lane; e < PER; e += 32) nxt[blockIdx.x * PER + e] = 0.f;
        }
        if (lane == 0) {
          flag_wait(FL_CS + j, (epoch + 1) * 16u);
          flag_wait(FL_ST + i, (epoch + 1) * 8u);
          fence_async_all();
          mbar_expect_tx(bars + 8 * B_CS, 320 + 2048);
          bulk_load(sb + OFF_CS, accg + 8 * KV_J + 80 * j, 320, bars + 8 * B_CS);
          bulk_load(sb + OFF_XST, g_xstat + 128 * i, 2048, bars + 8 * B_CS);
          TSTAMPX(21);
          l2_prefetch(w2 + (size_t)blockIdx.x * (D_ * D_ / NCTA), D_ * D_ * 2 / NCTA);
          l2_prefetch(w4 + (size_t)blockIdx.x * (F_ * D_ / NCTA), F_ * D_ * 2 / NCTA);
          l2_prefetch(wo + (size_t)blockIdx.x * (D_ * D_ / NCTA), D_ * D_ * 2 / NCTA);
        }
        __syncwarp();
#pragma unroll 1
        for (int m = 0; m < 6; m++) {
          const int col = 192 * j + 32 * m + 8 * (lane & 3);
          const __nv_bfloat16* p = w3 + (size_t)(40 * i + (lane >> 2) * 5) * F_ + col;
          float a[8];
#pragma unroll
          for (int e = 0; e < 8; e++) a[e] = 0.f;
#pragma unroll
          for (int it = 0; it < 5; it++) {
            const uint4 v = __ldg(reinterpret_cast<const uint4*>(p + (size_t)it * F_));
            a[0] += bf_lo(v.x); a[1] += bf_hi(v.x); a[2] += bf_lo(v.y); a[3] += bf_hi(v.y);
            a[4] += bf_lo(v.z); a[5] += bf_hi(v.z); a[6] += bf_lo(v.w); a[7] += bf_hi(v.w);
          }
#pragma unroll
          for (int e = 0; e < 4; e++) {
            const float snd = (lane & 4) ? a[e] : a[e + 4], keep = (lane & 4) ? a[e + 4] : a[e];
            a[e] = keep + __shfl_xor_sync(0xffffffffu, snd, 4);
            a[e] += __shfl_xor_sync(0xffffffffu, a[e], 8);
            a[e] += __shfl_xor_sync(0xffffffffu, a[e], 16);
          }
          if (lane < 8) red_add4(accg + 8 * KV_J + D_ + col + (lane >> 2) * 4, a[0], a[1], a[2], a[3]);
        }
        __syncwarp();
        if (lane == 0) {
          flag_add(FL_CS3 + j);
          flag_wait(FL_KV + j, (epoch + 1) * 16u);
          fence_async_all();
          mbar_expect_tx(bars + 8 * B_KV, KV_J * 4);
          bulk_load(sb + OFF_MISC, accg + j * KV_J, KV_J * 4, bars + 8 * B_KV);
          TSTAMPX(22);
          mbar_wait(bars + 8 * B_MFREE, 0);
          flag_wait(FL_X1 + i, (epoch + 1) * 8u);
          flag_wait(FL_CS3 + j, (epoch + 1) * 16u);
          fence_async_all();
          mbar_expect_tx(bars + 8 * B_ST1, 8192 + 768);
          bulk_load(sb + OFF_CS + 320, accg + 8 * KV_J + D_ + 192 * j, 768, bars + 8 * B_ST1);
          bulk_load(sb + OFF_MISC, g_st1 + 128 * i * 8, 8192, bars + 8 * B_ST1);
        }
        __syncwarp();
        mbar_wait(bars + 8 * (B_SEND + 1), 0);
        const unsigned* fp = g_flags + (FL_PART + i * 8 + j) * 32 + lane;
        bool seen = lane >= 6;
        uint32_t n = 0;
        while (!__all_sync(0xffffffffu, seen) && ++n < (WAIT_LIMIT >> 4)) {
          if (!seen && ld_acquire(fp) == epoch + 1 && (lane < 2 || mbar_test(bars + 8 * (lane < 4 ? B_SEND + 5 : B_SDONE + lane), 0))) {
            seen = true;
            if (lane & 1) TR4((lane >> 1) * 16 + 11);
            mbar_expect_tx(bars + 8 * (B_RDY + lane), 10240);
            bulk_load(sb + (lane < 2 ? OFF_G0 : lane < 4 ? OFF_G1 : OFF_SEND) + (lane & 1) * 10240, g_part + (size_t)(i * 8 + j) * 3840 + lane * 640, 10240,
                      bars + 8 * (B_RDY + lane));
          }
        }
      } else {
        mbar_wait(bars + 8 * B_SIGP, 0);
        if (lane < 20) {
          float a0 = 0.f, a1 = 0.f, a2 = 0.f, a3 = 0.f;
#pragma unroll 4
          for (int r = 0; r < 20; r++) {
            const uint4 v = lds128(sb + OFF_B + SPARE + r * 320 + lane * 16);
            a0 += __uint_as_float(v.x); a1 += __uint_as_float(v.y); a2 += __uint_as_float(v.z); a3 += __uint_as_float(v.w);
          }
          red_add4(accg + 8 * KV_J + 80 * j + 4 * lane, a0, a1, a2, a3);
        }
        __syncwarp();
      }
      if (pw == 3 && lane == 0) {
        flag_add(FL_CS + j); flag_add_relaxed(FL_ST + i);
        TSTAMPX(20);
        mbar_expect_tx(bars + 8 * B_XR, 20480);
#pragma unroll 1
        for (int u = 0; u < 8; u++)
          tma2d(sb + OFF_B + (u / 3) * SLOT_B + SPARE + (u % 3) * 2560, &maps.xr, bars + 8 * B_XR, 80 * j, 128 * i + 16 * u);
        const int shift = (j < 2) ? 1 : (j < 4) ? -1 : (j < 6) ? 2 : -2;
        if ((shift > 0 && i == 0) || (shift < 0 && i == 15)) {
          const int nz = shift > 0 ? shift : -shift, zr = shift > 0 ? 0 : S_ - nz;
#pragma unroll 1
          for (int e = 0; e < nz * 10; e++)
            reinterpret_cast<uint4*>(g_Hs + (size_t)(2 + zr + e / 10) * D_ + 80 * j)[e % 10] = make_uint4(0, 0, 0, 0);
          fence_async_all();
        }
        prefetch_tmap(&maps.st_h); prefetch_tmap(&maps.st_x1); prefetch_tmap(&maps.hs); prefetch_tmap(&maps.x1); prefetch_tmap(&maps.xr);
        prefetch_tmap(&maps.w2); prefetch_tmap(&maps.w3); prefetch_tmap(&maps.w4); prefetch_tmap(&maps.wo); prefetch_tmap(&maps.st_out);
        mbar_wait(bars + 8 * B_SIGH, 0);
        TSTAMPX(23);
        tma2d_store(&maps.st_h, sb + OFF_STG, 80 * j, 128 * i + 2 + shift);
        tma2d_store(&maps.st_h, sb + OFF_STG + 10240, 80 * j, 128 * i + 66 + shift);
        bulk_commit(); bulk_wait<0>();
        flag_add(FL_H + i);
        TSTAMPX(24);
        mbar_wait(bars + 8 * B_SIGKV, 0);
        TSTAMPX(25);
        flag_add(FL_KV + j);
        TSTAMPX(26);
        mbar_wait(bars + 8 * B_SIGX1, 0);
        TSTAMPX(27);
        tma2d_store(&maps.st_x1, sb + OFF_STG, 80 * j, 128 * i);
        tma2d_store(&maps.st_x1, sb + OFF_STG + 10240, 80 * j, 128 * i + 64);
        bulk_commit(); bulk_wait<0>();
        flag_add(FL_X1 + i);
        TSTAMPX(28);
        send_stream(0, epoch + 1);
      }
    }
    __syncwarp();
    asm volatile("barrier.cluster.arrive;\nbarrier.cluster.wait;" ::: "memory");
  } else {
    asm volatile("setmaxnreg.inc.sync.aligned.u32 232;");
    const int wg = tid >> 7, warp = tid >> 5, lane = tid & 31, t = lane & 3;
    const int rloc = warp * 16 + (lane >> 2);
    const float* s_cs = reinterpret_cast<const float*>(sgen + OFF_CS);
    auto signal = [&](int b) {
      __syncwarp();
      if (lane == 0) mbar_arrive(bars + 8 * b);
    };
    auto releaseB = [&](uint32_t bar) {
      __syncwarp();
      if (lane == 0) mbar_arrive(bar);
    };
    auto release = [&](uint32_t bar) {
      __syncwarp();
      if (lane < 2) mbar_arrive_cta(bar, lane);
    };
    uint32_t par;
    const uint32_t stg_lane = (warp * 16 + ((lane >> 3) & 1) * 8 + (lane & 7)) * 160 + (lane >> 4) * 16;

    {
      const unsigned done_cnt = *reinterpret_cast<volatile unsigned*>(g_flags + FL_DONE * 32);
#pragma unroll 1
      for (int e = tid; e < 800; e += 256) sts128(sb + OFF_MISC + e * 16, make_uint4(0, 0, 0, 0));
      bar_sync(1, 256);
      float f[40];
      float s = 0.f, gs = 0.f;
#pragma unroll
      for (int c = 0; c < 5; c++) {
        const uint32_t vv[4] = {pv[c].x, pv[c].y, pv[c].z, pv[c].w}, ww[4] = {pw_[c].x, pw_[c].y, pw_[c].z, pw_[c].w};
#pragma unroll
        for (int e = 0; e < 4; e++) {
          f[8 * c + 2 * e] = bf_lo(vv[e]); f[8 * c + 2 * e + 1] = bf_hi(vv[e]);
          s += f[8 * c + 2 * e] + f[8 * c + 2 * e + 1];
          gs = fmaf(f[8 * c + 2 * e], bf_lo(ww[e]), gs); gs = fmaf(f[8 * c + 2 * e + 1], bf_hi(ww[e]), gs);
        }
      }
#pragma unroll
      for (int o = 1; o < 16; o <<= 1) { s += __shfl_xor_sync(0xffffffffu, s, o); gs += __shfl_xor_sync(0xffffffffu, gs, o); }
      const float mean = s * (1.f / D_);
      float q = 0.f;
#pragma unroll
      for (int e = 0; e < 40; e++) { const float d = f[e] - mean; q = fmaf(d, d, q); }
#pragma unroll
      for (int o = 1; o < 16; o <<= 1) q += __shfl_xor_sync(0xffffffffu, q, o);
      const float rstd = rsqrtf(q * (1.f / D_) + 1e-5f);
      par = (done_cnt / NCTA) & 1;
      if (tid < 200) {
        const uint32_t cd = sb + OFF_B + SPARE + tid * 32;
        sts128(cd, make_uint4(__float_as_uint(bf_lo(pc[0].x) + bf_lo(pc[1].x)), __float_as_uint(bf_hi(pc[0].x) + bf_hi(pc[1].x)),
                              __float_as_uint(bf_lo(pc[0].y) + bf_lo(pc[1].y)), __float_as_uint(bf_hi(pc[0].y) + bf_hi(pc[1].y))));
        sts128(cd + 16, make_uint4(__float_as_uint(bf_lo(pc[0].z) + bf_lo(pc[1].z)), __float_as_uint(bf_hi(pc[0].z) + bf_hi(pc[1].z)),
                                   __float_as_uint(bf_lo(pc[0].w) + bf_lo(pc[1].w)), __float_as_uint(bf_hi(pc[0].w) + bf_hi(pc[1].w))));
        const uint32_t ww[4] = {pre.x, pre.y, pre.z, pre.w};
        const int h = tid / 50;
#pragma unroll
        for (int e = 0; e < 8; e++) {
          const int idx = tid * 8 + e, k = idx / 20, ff = idx - 20 * k;
          const int n = 40 * (h >> 1) + 8 * (ff >> 2) + 2 * (ff & 3) + (h & 1);
          const int off = (k >> 4) * 2560 + n * 32 + ((((k >> 3) ^ (n >> 2)) & 1) << 4) + (k & 7) * 2;
          *reinterpret_cast<unsigned short*>(sgen + OFF_MISC + off) = (unsigned short)(ww[e >> 1] >> ((e & 1) * 16));
        }
      }
      fence_async_smem();
      asm volatile("barrier.cluster.wait.aligned;" ::: "memory");
      if ((tid & 15) == 0) g_xstat[128 * i + 16 * j + (tid >> 4)] = make_float4(rstd, -mean * rstd, rcp(1.f + __expf(-gs)), 0.f);
      signal(B_SIGP);
    }
    TSTAMP(1);

    Ring ra{0, 0}, rb{0, 0};
    uint32_t qp[2][10], P[2][10];
    float st_g[2];
    {
      float accM[128], accR[32];
      zero_regs(accM); zero_regs(accR);
      uint32_t pa = 0, pb = 0;
#pragma unroll 1
      for (int k = 0; k < 10; k++) {
        mbar_wait(fullA + 8 * ra.idx, ra.phase);
        if (tid == 0) TRACE(32 + k);
        mbar_wait(fullB + 8 * rb.idx, rb.phase);
        if (tid == 0) TRACE(64 + k);
        if (k == 0) TSTAMP(2);
        const uint32_t a0 = sb16 + ((OFF_A + ra.idx * SLOT_A + wg * 8192) >> 4), b0 = sb16 + ((OFF_B + rb.idx * SLOT_B) >> 4);
        wg_fence();
#pragma unroll
        for (int kk = 0; kk < 4; kk++) {
          const uint64_t da = make_desc(a0, kk * 32, 16, 1024, 1);
          mma_ss256(accM, da, make_desc(b0, kk * 2048, 8192, 1024, 1));
          mma_ss64(accR, da, make_desc(b0, 32768 + kk * 512, 2048, 256, 3));
          if (kk == 0) {
            wg_commit();
            if (k > 0) {
              wg_wait<1>();
              if (k - 1 < 8) release(emptyA + 8 * pa);
              releaseB(emptyB + 8 * pb);
            }
          }
        }
        wg_commit();
        pa = ra.idx; pb = rb.idx;
        ra.next<NA>(); rb.next<NB>();
      }
      TSTAMP(18);
      float st_rstd[2], st_mr[2];
      mbar_wait(bars + 8 * B_CS, 0);
#pragma unroll
      for (int r = 0; r < 2; r++) {
        const uint4 st = lds128(sb + OFF_XST + (rloc + 8 * r) * 16);
        st_rstd[r] = __uint_as_float(st.x); st_mr[r] = __uint_as_float(st.y); st_g[r] = __uint_as_float(st.z);
      }
      TSTAMP(19);
      wg_wait<0>();
      fence_regs(accM); fence_regs(accR);
      TSTAMP(3);
#define ACC(P_, G, I_) ((G) < 8 ? accM[(P_) * 32 + ((G) & 7) * 4 + (I_)] : accR[(P_) * 8 + ((G) & 1) * 4 + (I_)])
      {
        const int mat = lane >> 3;
        const int tok = warp * 16 + (mat & 1) * 8 + (lane & 7);
        const uint32_t ones = (t == 0) ? 0x00003f80u : 0u;
        __syncwarp();
#pragma unroll
        for (int p = 0; p < 2; p++) {
          const uint32_t rowa = sb + OFF_A + p * SLOT_A + tok * 128;
#pragma unroll
          for (int gg = 0; gg < 3; gg++) {
            const int g0 = 5 * p + 2 * gg;
            uint32_t r0 = pack_bf16(ACC(3, g0, 0), ACC(3, g0, 1)), r1 = pack_bf16(ACC(3, g0, 2), ACC(3, g0, 3));
            uint32_t r2 = ones, r3 = ones;
            if (gg < 2) { r2 = pack_bf16(ACC(3, g0 + 1, 0), ACC(3, g0 + 1, 1)); r3 = pack_bf16(ACC(3, g0 + 1, 2), ACC(3, g0 + 1, 3)); }
            stsm4(rowa + (((2 * gg + (mat >> 1)) ^ (tok & 7)) << 4), r0, r1, r2, r3);
          }
        }
      }
      uint32_t kf[5][4], qf[5][4];
#pragma unroll
      for (int s = 0; s < 5; s++) {
        kf[s][0] = pack_bf16(ACC(2, 2 * s, 0), ACC(2, 2 * s, 1)); kf[s][1] = pack_bf16(ACC(2, 2 * s, 2), ACC(2, 2 * s, 3));
        kf[s][2] = pack_bf16(ACC(2, 2 * s + 1, 0), ACC(2, 2 * s + 1, 1)); kf[s][3] = pack_bf16(ACC(2, 2 * s + 1, 2), ACC(2, 2 * s + 1, 3));
        qf[s][0] = pack_bf16(ACC(1, 2 * s, 0), ACC(1, 2 * s, 1)); qf[s][1] = pack_bf16(ACC(1, 2 * s, 2), ACC(1, 2 * s, 3));
        qf[s][2] = pack_bf16(ACC(1, 2 * s + 1, 0), ACC(1, 2 * s + 1, 1)); qf[s][3] = pack_bf16(ACC(1, 2 * s + 1, 2), ACC(1, 2 * s + 1, 3));
      }
      bar_sync(1, 256);
      float pk[40], pq[40];
      wg_fence();
#pragma unroll
      for (int s = 0; s < 5; s++) {
        if (s == 0) mma_rs80_k_z(pk, kf[s], make_desc(sb16, OFF_MISC, 16, 256, 3));
        else mma_rs80_k(pk, kf[s], make_desc(sb16, OFF_MISC + s * 2560, 16, 256, 3));
      }
#pragma unroll
      for (int s = 0; s < 5; s++) {
        if (s == 0) mma_rs80_k_z(pq, qf[s], make_desc(sb16, OFF_MISC, 16, 256, 3));
        else mma_rs80_k(pq, qf[s], make_desc(sb16, OFF_MISC + s * 2560, 16, 256, 3));
      }
      wg_commit();

      {
        uint32_t hv[10][2];
#pragma unroll
        for (int g = 0; g < 10; g++) {
          const float2 cs = *reinterpret_cast<const float2*>(s_cs + 8 * g + 2 * t);
          const float v0 = gelu_s(fmaf(ACC(0, g, 0), st_rstd[0], st_mr[0] * cs.x), 0.5f), v1 = gelu_s(fmaf(ACC(0, g, 1), st_rstd[0], st_mr[0] * cs.y), 0.5f);
          const float v2 = gelu_s(fmaf(ACC(0, g, 2), st_rstd[1], st_mr[1] * cs.x), 0.5f), v3 = gelu_s(fmaf(ACC(0, g, 3), st_rstd[1], st_mr[1] * cs.y), 0.5f);
          hv[g][0] = pack_bf16(v0, v1); hv[g][1] = pack_bf16(v2, v3);
        }
#pragma unroll
        for (int s = 0; s < 5; s++) stsm4(sb + OFF_STG + stg_lane + s * 32, hv[2 * s][0], hv[2 * s][1], hv[2 * s + 1][0], hv[2 * s + 1][1]);
        fence_async_smem();
        signal(B_SIGH);
      }
#undef ACC
      TSTAMP(4);
      wg_wait<0>();
      fence_regs(pk); fence_regs(pq);
#pragma unroll
      for (int G = 0; G < 10; G++) {
        P[0][G] = pack_bf16(pk[4 * G], pk[4 * G + 1]); P[1][G] = pack_bf16(pk[4 * G + 2], pk[4 * G + 3]);
        qp[0][G] = pack_bf16(pq[4 * G], pq[4 * G + 1]); qp[1][G] = pack_bf16(pq[4 * G + 2], pq[4 * G + 3]);
      }
    }

    uint32_t fr[10][4];
    {
      feature_map(P, fr);
      const int mat = lane >> 3;
      const int tok = warp * 16 + (mat & 1) * 8 + (lane & 7);
      const uint32_t base = sb + OFF_B + tok * 32 + (((mat >> 1) ^ ((tok >> 2) & 1)) << 4);
#pragma unroll
      for (int G = 0; G < 10; G++) stsm4(base + G * 4096, fr[G][0], fr[G][1], fr[G][2], fr[G][3]);
      fence_async_smem();
      bar_sync(1, 256);
      float kv[40];
      const uint32_t a0 = sb16 + ((OFF_A + wg * SLOT_A) >> 4), b0 = sb16 + ((OFF_B + wg * 20480) >> 4);
      wg_fence();
#pragma unroll
      for (int ks = 0; ks < 8; ks++) {
        if (ks == 0) mma_ss80_tt_z(kv, make_desc(a0, 0, 16, 1024, 1), make_desc(b0, 0, 4096, 256, 3));
        else mma_ss80_tt(kv, make_desc(a0, ks * 2048, 16, 1024, 1), make_desc(b0, ks * 512, 4096, 256, 3));
      }
      wg_commit();
      wg_wait<0>();
      fence_regs(kv);
      release(emptyA); release(emptyA + 8); releaseB(emptyB);
      float* dst = g_acc[par] + j * KV_J + wg * KV_PAIR;
      const int m0 = (warp & 3) * 16 + (lane >> 2);
#pragma unroll
      for (int r = 0; r < 2; r++) {
        const int m = m0 + 8 * r;
        const bool hi = m >= 20;
        float v[10];
#pragma unroll
        for (int G = 0; G < 10; G++) v[G] = hi ? kv[4 * G + 2 * r + 1] : kv[4 * G + 2 * r];
        float* p = dst + (m < 40 ? m * 48 + t * 12 : 1920 + t * 24 + 12);
        if (m <= 40) { red_add4(p, v[0], v[1], v[2], v[3]); red_add4(p + 4, v[4], v[5], v[6], v[7]); red_add2(p + 8, v[8], v[9]); }
      }
      if (m0 == 32) {
        float* p = dst + 1920 + t * 24;
        red_add4(p, kv[2], kv[6], kv[10], kv[14]); red_add4(p + 4, kv[18], kv[22], kv[26], kv[30]); red_add2(p + 8, kv[34], kv[38]);
      }
      signal(B_SIGKV);
    }
    TSTAMP(5);

    uint32_t xv[2][10];
    {
      {
        mbar_wait(bars + 8 * B_XR, 0);
        const uint32_t xa = sb + OFF_B + (warp / 3) * SLOT_B + SPARE + (warp % 3) * 2560 + (lane >> 2) * 160 + t * 4;
#pragma unroll
        for (int g = 0; g < 10; g++) { xv[0][g] = lds32(xa + g * 16); xv[1][g] = lds32(xa + 1280 + g * 16); }
      }
      float acc[40];
      zero_regs(acc);
      uint32_t pa = 0, pb = 0;
#pragma unroll 1
      for (int k = 0; k < 10; k++) {
        mbar_wait(fullA + 8 * ra.idx, ra.phase);
        if (tid == 0) TRACE(42 + k);
        if ((k & 3) == 0) mbar_wait(fullB + 8 * rb.idx, rb.phase);
        if (tid == 0) TRACE(74 + k);
        if (k == 0) TSTAMP(6);
        const uint32_t a0 = sb16 + ((OFF_A + ra.idx * SLOT_A + wg * 8192) >> 4);
        const uint32_t b0 = sb16 + ((OFF_B + rb.idx * SLOT_B + (k & 3) * 10240) >> 4);
        wg_fence();
#pragma unroll
        for (int kk = 0; kk < 4; kk++) {
          mma_ss80(acc, make_desc(a0, kk * 32, 16, 1024, 1), make_desc(b0, kk * 512, 2048, 256, 3));
          if (kk == 1) {
            wg_commit();
            if (k > 0) {
              wg_wait<1>();
              release(emptyA + 8 * pa);
              if ((k & 3) == 0) releaseB(emptyB + 8 * pb);
            }
          }
        }
        wg_commit();
        pa = ra.idx; pb = rb.idx;
        ra.next<NA>();
        if ((k & 3) == 3 || k == 9) rb.next<NB>();
      }
      wg_wait<0>();
      fence_regs(acc);
      release(emptyA + 8 * pa); releaseB(emptyB + 8 * pb);
      TSTAMP(7);
#pragma unroll
      for (int r = 0; r < 2; r++) {
#pragma unroll
        for (int g = 0; g < 10; g++)
          xv[r][g] = pack_bf16(bf_lo(xv[r][g]) + acc[4 * g + 2 * r], bf_hi(xv[r][g]) + acc[4 * g + 2 * r + 1]);
      }
      bar_sync(1, 256);
#pragma unroll
      for (int s = 0; s < 5; s++) stsm4(sb + OFF_STG + stg_lane + s * 32, xv[0][2 * s], xv[1][2 * s], xv[0][2 * s + 1], xv[1][2 * s + 1]);
#pragma unroll
      for (int r = 0; r < 2; r++) {
        float s = 0.f;
#pragma unroll
        for (int g = 0; g < 10; g++) {
          acc[4 * g + 2 * r] = bf_lo(xv[r][g]); acc[4 * g + 2 * r + 1] = bf_hi(xv[r][g]);
          s += acc[4 * g + 2 * r] + acc[4 * g + 2 * r + 1];
        }
        s += __shfl_xor_sync(0xffffffffu, s, 1); s += __shfl_xor_sync(0xffffffffu, s, 2);
        const float mu = s * (1.f / 80.f);
        float q = 0.f;
#pragma unroll
        for (int g = 0; g < 10; g++) {
          const float d0 = acc[4 * g + 2 * r] - mu, d1 = acc[4 * g + 2 * r + 1] - mu;
          q = fmaf(d0, d0, q); q = fmaf(d1, d1, q);
        }
        q += __shfl_xor_sync(0xffffffffu, q, 1); q += __shfl_xor_sync(0xffffffffu, q, 2);
        if (t == 0) g_st1[(128 * i + rloc + 8 * r) * 8 + j] = make_float2(mu, q);
      }
      fence_async_smem();
      signal(B_SIGX1);
    }
    TSTAMP(8);

    uint32_t of[5][4];
    {
      feature_map(qp, fr);
      mbar_wait(bars + 8 * B_KV, 0);
      uint4 kvr[2][3];
#pragma unroll
      for (int u = 0; u < 2; u++) {
        const int it = tid + 256 * u, p = it / 192, rem = it - 192 * p, n = rem >> 2, tq = rem & 3;
        const uint32_t sp = sb + OFF_MISC + 4 * (p * KV_PAIR + (n < 40 ? n * 48 + tq * 12 : 1920 + tq * 24 + (n & 1) * 12));
        if (it < 384) { kvr[u][0] = lds128(sp); kvr[u][1] = lds128(sp + 16); kvr[u][2] = lds128(sp + 32); }
      }
      bar_sync(1, 256);
#pragma unroll
      for (int u = 0; u < 2; u++) {
        const int it = tid + 256 * u, p = it / 192, rem = it - 192 * p, n = rem >> 2, tq = rem & 3;
        const int sh = (n < 40 ? (n >= 20) : (n & 1)) * 16;
        const uint32_t v[10] = {kvr[u][0].x, kvr[u][0].y, kvr[u][0].z, kvr[u][0].w, kvr[u][1].x, kvr[u][1].y, kvr[u][1].z, kvr[u][1].w, kvr[u][2].x, kvr[u][2].y};
        uint8_t* dst = sgen + OFF_MISC + p * 7680 + n * 32 + tq * 4;
        const int sw = ((n >> 2) & 1) << 4;
        if (it < 384) {
#pragma unroll
          for (int G = 0; G < 10; G++)
            *reinterpret_cast<uint32_t*>(dst + (G >> 1) * 1536 + (((G & 1) << 4) ^ sw)) = pack_bf16(__uint_as_float(v[G]), 0.f) << sh;
        }
      }
      fence_async_smem();
      bar_sync(1, 256);
      float o0[24], o1[24];
      wg_fence();
#pragma unroll
      for (int g = 0; g < 5; g++) {
        if (g == 0) mma_rs48_k_z(o0, fr[g], make_desc(sb16, OFF_MISC, 16, 256, 3));
        else mma_rs48_k(o0, fr[g], make_desc(sb16, OFF_MISC + g * 1536, 16, 256, 3));
      }
#pragma unroll
      for (int g = 0; g < 5; g++) {
        if (g == 0) mma_rs48_k_z(o1, fr[5], make_desc(sb16, OFF_MISC + 7680, 16, 256, 3));
        else mma_rs48_k(o1, fr[5 + g], make_desc(sb16, OFF_MISC + 7680 + g * 1536, 16, 256, 3));
      }
      wg_commit();
      wg_wait<0>();
      fence_regs(o0); fence_regs(o1);
      signal(B_MFREE);
#pragma unroll
      for (int r = 0; r < 2; r++) {
        const float a0 = __fdividef(st_g[r], o0[20 + 2 * r] + 1e-6f), a1 = __fdividef(st_g[r], o0[21 + 2 * r] + 1e-6f);
        const float b0 = __fdividef(st_g[r], o1[20 + 2 * r] + 1e-6f), b1 = __fdividef(st_g[r], o1[21 + 2 * r] + 1e-6f);
        const float am = t < 2 ? a0 : a1, bm = t < 2 ? b0 : b1;
#pragma unroll
        for (int g = 0; g < 5; g++) {
          const float sa = g < 2 ? a0 : (g == 2 ? am : a1), sb2 = g < 2 ? b0 : (g == 2 ? bm : b1);
          of[g >> 1][(g & 1) * 2 + r] = pack_bf16(o0[4 * g + 2 * r] * sa, o0[4 * g + 2 * r + 1] * sa);
          of[(5 + g) >> 1][((5 + g) & 1) * 2 + r] = pack_bf16(o1[4 * g + 2 * r] * sb2, o1[4 * g + 2 * r + 1] * sb2);
        }
      }
    }
    TSTAMP(9);

    uint32_t hf[12][4];
    {
      float acc[96];
      zero_regs(acc);
      uint32_t pa = 0, pb = 0;
#pragma unroll 1
      for (int k = 0; k < 10; k++) {
        mbar_wait(fullA + 8 * ra.idx, ra.phase);
        if (tid == 0) TRACE(52 + k);
        if ((k & 1) == 0) mbar_wait(fullB + 8 * rb.idx, rb.phase);
        if (tid == 0) TRACE(84 + k);
        if (k == 0) TSTAMP(10);
        const uint32_t a0 = sb16 + ((OFF_A + ra.idx * SLOT_A + wg * 8192) >> 4);
        const uint32_t b0 = sb16 + ((OFF_B + rb.idx * SLOT_B + (k & 1) * 24576) >> 4);
        wg_fence();
#pragma unroll
        for (int kk = 0; kk < 4; kk++) {
          mma_ss192(acc, make_desc(a0, kk * 32, 16, 1024, 1), make_desc(b0, kk * 2048, 8192, 1024, 1));
          if (kk == 0) {
            wg_commit();
            if (k > 0) {
              wg_wait<1>();
              release(emptyA + 8 * pa);
              if ((k & 1) == 0) releaseB(emptyB + 8 * pb);
            }
          }
        }
        wg_commit();
        pa = ra.idx; pb = rb.idx;
        ra.next<NA>();
        if (k & 1) rb.next<NB>();
      }
      float rs[2], mm[2];
      mbar_wait(bars + 8 * B_ST1, 0);
#pragma unroll
      for (int r = 0; r < 2; r++) {
        const uint4 su = lds128(sb + OFF_MISC + (rloc + 8 * r) * 64 + t * 16);
        const float m0 = __uint_as_float(su.x), m1 = __uint_as_float(su.z);
        float mu = m0 + m1;
        mu += __shfl_xor_sync(0xffffffffu, mu, 1); mu += __shfl_xor_sync(0xffffffffu, mu, 2);
        mu *= 0.125f;
        const float d0 = m0 - mu, d1 = m1 - mu;
        float q = __uint_as_float(su.y) + __uint_as_float(su.w) + 80.f * (d0 * d0 + d1 * d1);
        q += __shfl_xor_sync(0xffffffffu, q, 1); q += __shfl_xor_sync(0xffffffffu, q, 2);
        rs[r] = rsqrtf(q * (1.f / D_) + 1e-5f);
        mm[r] = -mu * rs[r];
      }
      wg_wait<0>();
      fence_regs(acc);
      releaseB(emptyB + 8 * pb);
      if (lane == 0) mbar_arrive_cta(bars + 8 * B_PEER, rank ^ 1);
      if (wg == 1) bar_arrive(2, 256);
      TSTAMP(11);
      const float hs0 = 0.5f - 0.5f * st_g[0], hs1 = 0.5f - 0.5f * st_g[1];
#pragma unroll
      for (int g = 0; g < 24; g++) {
        const float2 cs = *reinterpret_cast<const float2*>(s_cs + 80 + 8 * g + 2 * t);
        const float v0 = gelu_s(fmaf(acc[4 * g], rs[0], mm[0] * cs.x), hs0), v1 = gelu_s(fmaf(acc[4 * g + 1], rs[0], mm[0] * cs.y), hs0);
        const float v2 = gelu_s(fmaf(acc[4 * g + 2], rs[1], mm[1] * cs.x), hs1), v3 = gelu_s(fmaf(acc[4 * g + 3], rs[1], mm[1] * cs.y), hs1);
        hf[g >> 1][(g & 1) * 2] = pack_bf16(v0, v1);
        hf[g >> 1][(g & 1) * 2 + 1] = pack_bf16(v2, v3);
      }
    }
    TSTAMP(12);

    {
      float acc[80];
      const int wt = tid & 127;
      const uint32_t peer = map_peer(sb, rank ^ 1);
      Ring r4{0, 0};
      auto add16 = [&](uint32_t src) {
#pragma unroll
        for (int q = 0; q < 5; q++) {
          const uint4 v = lds128(src + q * 2048);
          float* d = &acc[8 * q];
          d[0] += bf_lo(v.x); d[1] += bf_hi(v.x); d[2] += bf_lo(v.y); d[3] += bf_hi(v.y);
          d[4] += bf_lo(v.z); d[5] += bf_hi(v.z); d[6] += bf_lo(v.w); d[7] += bf_hi(v.w);
        }
      };
#pragma unroll 1
      for (int c = 0; c < 4; c++) {
        uint32_t prev = 0;
#pragma unroll
        for (int u = 0; u < 4; u++) {
          mbar_wait(bars + 8 * (B_FULL4 + r4.idx), r4.phase);
          const uint32_t b0 = sb16 + ((OFF_B + r4.idx * UNIT4) >> 4);
          if (u == 0) {
            if (tid == 128) TR4(c * 16 + 0);
            bar_sync(2 + wg, 256);
          }
          wg_fence();
#pragma unroll
          for (int s = 0; s < (u < 3 ? 4 : 5); s++) {
            const uint64_t db = make_desc(b0, s * 1024, u < 3 ? 4096 : 5120, 512, 2);
            if (u == 0 && s == 0) mma_rs160_n_z(acc, hf[0], db);
            else if (u < 3) mma_rs160_n(acc, hf[(4 * u + s) % 12], db);
            else mma_rs160_n(acc, of[s], db);
            if (s == 1 && u > 0) { wg_commit(); wg_wait<1>(); releaseB(bars + 8 * (B_EMPTY4 + prev)); }
          }
          wg_commit();
          prev = r4.idx;
          r4.next<NU4>();
        }
        if (c < 3 || wg == 0) bar_arrive(3 - wg, 256);
        if (tid == 128) TR4(c * 16 + 2);
        if (c == 0) mbar_wait(bars + 8 * B_PEER, 0);
        wg_wait<0>();
        fence_regs(acc);
        releaseB(bars + 8 * (B_EMPTY4 + prev));
        if (tid == 128) TR4(c * 16 + 5);
        const uint32_t dso = OFF_DS + (c & 1) * 20480 + wg * 10240 + wt * 16, dsb = OFF_BAR + 8 * (B_DSR + 2 * c + wg);
        uint32_t sn[20];
        if (rank) {
#pragma unroll
          for (int e = 0; e < 20; e++) sn[e] = pack_bf16(acc[2 * e], acc[2 * e + 1]);
#pragma unroll
          for (int e = 0; e < 40; e++) acc[e] = acc[40 + e];
        } else {
#pragma unroll
          for (int e = 0; e < 20; e++) sn[e] = pack_bf16(acc[40 + 2 * e], acc[41 + 2 * e]);
        }
#pragma unroll
        for (int q = 0; q < 5; q++) st_async16(peer + dso + q * 2048, sn[4 * q], sn[4 * q + 1], sn[4 * q + 2], sn[4 * q + 3], peer + dsb);
        if (c > 0 && c < 3) mbar_wait(bars + 8 * (B_SDONE + 2 * (c - 1) + wg), 0);
        mbar_wait(sb + dsb, 0);
        if (tid == 128) TR4(c * 16 + 3);
        add16(sb + dso);
        if (c < 3) {
          const uint32_t dst = sb + OFF_SEND + wg * 10240 + wt * 16;
#pragma unroll
          for (int q = 0; q < 5; q++) {
            const float* d = &acc[8 * q];
            sts128(dst + q * 2048, make_uint4(pack_bf16(d[0], d[1]), pack_bf16(d[2], d[3]), pack_bf16(d[4], d[5]), pack_bf16(d[6], d[7])));
          }
          fence_async_smem();
          signal(B_SEND + 2 * c + wg);
          if (tid == 128) TR4(c * 16 + 6);
        }
      }
      TSTAMP(13);
#pragma unroll 1
      for (int c = 0; c < 3; c++) {
        mbar_wait(bars + 8 * (B_RDY + 2 * c + wg), 0);
        add16(sb + (c == 0 ? OFF_G0 : c == 1 ? OFF_G1 : OFF_SEND) + wg * 10240 + wt * 16);
        if (tid == 128) TR4(c * 16 + 12);
      }
      TSTAMP(14);
      const float w0 = 1.f - st_g[0], w1s = 1.f - st_g[1];
      uint32_t ov[10][2];
#pragma unroll
      for (int g = 0; g < 10; g++) {
        const float* d = &acc[4 * g];
        ov[g][0] = pack_bf16(fmaf(w0, bf_lo(xv[0][g]), d[0]), fmaf(w0, bf_hi(xv[0][g]), d[1]));
        ov[g][1] = pack_bf16(fmaf(w1s, bf_lo(xv[1][g]), d[2]), fmaf(w1s, bf_hi(xv[1][g]), d[3]));
      }
      bar_sync(4 + wg, 128);
#pragma unroll
      for (int s = 0; s < 5; s++) stsm4(sb + OFF_DS + stg_lane + s * 32, ov[2 * s][0], ov[2 * s][1], ov[2 * s + 1][0], ov[2 * s + 1][1]);
      fence_async_smem();
      bar_sync(4 + wg, 128);
      if (wt == 0) {
        tma2d_store(&maps.st_out, sb + OFF_DS + wg * 10240, 80 * j, 128 * i + 64 * wg);
        bulk_commit(); bulk_wait_read();
      }
    }
    TSTAMP(15);
    if (tid == 0) asm volatile("red.relaxed.gpu.global.add.u32 [%0], 1;" ::"l"(g_flags + FL_DONE * 32) : "memory");
    asm volatile("barrier.cluster.arrive;\nbarrier.cluster.wait;" ::: "memory");
  }
}

namespace {
typedef CUresult (*EncodeFn)(CUtensorMap*, CUtensorMapDataType, cuuint32_t, void*, const cuuint64_t*, const cuuint64_t*,
                             const cuuint32_t*, const cuuint32_t*, CUtensorMapInterleave, CUtensorMapSwizzle,
                             CUtensorMapL2promotion, CUtensorMapFloatOOBfill);

void encode(EncodeFn fn, CUtensorMap* m, const void* ptr, int rank, const cuuint64_t* dims, const cuuint64_t* strides,
            const cuuint32_t* box, CUtensorMapSwizzle swz) {
  cuuint32_t es[5] = {1, 1, 1, 1, 1};
  fn(m, CU_TENSOR_MAP_DATA_TYPE_BFLOAT16, rank, const_cast<void*>(ptr), dims, strides, box, es, CU_TENSOR_MAP_INTERLEAVE_NONE,
     swz, CU_TENSOR_MAP_L2_PROMOTION_L2_128B, CU_TENSOR_MAP_FLOAT_OOB_FILL_NONE);
}
}

extern "C" void kernel_launch(void* const* d_in, const int* in_sizes, int n_in, void* d_out, int out_size) {
  (void)in_sizes; (void)n_in; (void)out_size;
  const __nv_bfloat16* x = (const __nv_bfloat16*)d_in[0];
  const __nv_bfloat16* wqkv = (const __nv_bfloat16*)d_in[1];
  const __nv_bfloat16* wphi = (const __nv_bfloat16*)d_in[2];
  const __nv_bfloat16* wo = (const __nv_bfloat16*)d_in[3];
  const __nv_bfloat16* w1 = (const __nv_bfloat16*)d_in[5];
  const __nv_bfloat16* w2 = (const __nv_bfloat16*)d_in[6];
  const __nv_bfloat16* w3 = (const __nv_bfloat16*)d_in[7];
  const __nv_bfloat16* w4 = (const __nv_bfloat16*)d_in[8];
  const __nv_bfloat16* gate_w = (const __nv_bfloat16*)d_in[9];

  static EncodeFn enc = nullptr;
  static void *pHs = nullptr, *pX1 = nullptr;
  if (!enc) {
    cudaDriverEntryPointQueryResult qr;
    cudaGetDriverEntryPoint("cuTensorMapEncodeTiled", (void**)&enc, cudaEnableDefault, &qr);
    cudaGetSymbolAddress(&pHs, g_Hs);
    cudaGetSymbolAddress(&pX1, g_X1);
    cudaFuncSetAttribute(fused_kernel, cudaFuncAttributeMaxDynamicSharedMemorySize, SMEM_BYTES);
  }
  Maps m;
  {
    cuuint64_t dims[2] = {D_, S_}, str[1] = {D_ * 2};
    cuuint32_t boxh[2] = {64, 64};
    encode(enc, &m.x, x, 2, dims, str, boxh, CU_TENSOR_MAP_SWIZZLE_128B);
    encode(enc, &m.hs, (const char*)pHs + 2 * D_ * 2, 2, dims, str, boxh, CU_TENSOR_MAP_SWIZZLE_128B);
    encode(enc, &m.x1, pX1, 2, dims, str, boxh, CU_TENSOR_MAP_SWIZZLE_128B);
    cuuint32_t boxs[2] = {80, 64};
    cuuint64_t dimsp[2] = {D_, S_ + 4};
    encode(enc, &m.st_h, pHs, 2, dimsp, str, boxs, CU_TENSOR_MAP_SWIZZLE_NONE);
    encode(enc, &m.st_x1, pX1, 2, dims, str, boxs, CU_TENSOR_MAP_SWIZZLE_NONE);
    encode(enc, &m.st_out, d_out, 2, dims, str, boxs, CU_TENSOR_MAP_SWIZZLE_NONE);
    cuuint32_t boxr[2] = {80, 16};
    encode(enc, &m.xr, x, 2, dims, str, boxr, CU_TENSOR_MAP_SWIZZLE_NONE);
  }
  {
    cuuint64_t dims[3] = {80, D_, 8}, str[2] = {D_ * 2, 160};
    cuuint32_t boxm[3] = {64, 64, 1}, boxr[3] = {16, 64, 1};
    encode(enc, &m.w1m, w1, 3, dims, str, boxm, CU_TENSOR_MAP_SWIZZLE_128B);
    encode(enc, &m.w1r, w1, 3, dims, str, boxr, CU_TENSOR_MAP_SWIZZLE_32B);
  }
  {
    cuuint64_t dims[4] = {80, D_, 3, 8}, str[3] = {3 * D_ * 2, D_ * 2, 160};
    cuuint32_t boxm[4] = {64, 64, 3, 1}, boxr[4] = {16, 64, 3, 1};
    encode(enc, &m.qm, wqkv, 4, dims, str, boxm, CU_TENSOR_MAP_SWIZZLE_128B);
    encode(enc, &m.qr, wqkv, 4, dims, str, boxr, CU_TENSOR_MAP_SWIZZLE_32B);
  }
  {
    cuuint64_t dims[3] = {16, D_, 40}, str[2] = {D_ * 2, 32};
    cuuint32_t box2[3] = {16, 64, 5};
    encode(enc, &m.w2, w2, 3, dims, str, box2, CU_TENSOR_MAP_SWIZZLE_32B);
  }
  {
    cuuint64_t dims[3] = {32, D_, 20}, dims4[3] = {32, F_, 20}, str[2] = {D_ * 2, 64};
    cuuint32_t box4[3] = {32, 64, 5}, boxo[3] = {32, 80, 5};
    encode(enc, &m.w4, w4, 3, dims4, str, box4, CU_TENSOR_MAP_SWIZZLE_64B);
    encode(enc, &m.wo, wo, 3, dims, str, boxo, CU_TENSOR_MAP_SWIZZLE_64B);
  }
  {
    cuuint64_t dims[3] = {64, D_, 24}, str[2] = {F_ * 2, 128};
    cuuint32_t box[3] = {64, 64, 3};
    encode(enc, &m.w3, w3, 3, dims, str, box, CU_TENSOR_MAP_SWIZZLE_128B);
  }
  fused_kernel<<<NCTA, 384, SMEM_BYTES, cudaStreamPerThread>>>(m, x, wqkv, wphi, w1, w2, w3, w4, wo, gate_w);
}
```

```cpp
#include <cuda_runtime.h>
#include <cuda_bf16.h>
#include <cuda.h>
#include <stdint.h>

namespace {

constexpr int S_ = 2048, D_ = 640, F_ = 1536;
constexpr int NCTA = 128;
constexpr int KV_PAIR = 40 * 48 + 96;
constexpr int KV_J = 2 * KV_PAIR;

constexpr int SLOT_B = 49152, NB = 3;
constexpr int SLOT_A = 16384, NA = 4;
constexpr int OFF_B = 0;
constexpr int OFF_A = OFF_B + NB * SLOT_B;
constexpr int OFF_STG = OFF_A + 2 * SLOT_A;
constexpr int OFF_MISC = OFF_A + NA * SLOT_A;
constexpr int OFF_XST = OFF_MISC + 13312;
constexpr int OFF_CS = OFF_MISC + 16384;
constexpr int OFF_BAR = OFF_CS + 1088;
constexpr int SMEM_BYTES = OFF_BAR + 512;
constexpr int B_FULLA = 0, B_FULLB = 4, B_CS = 7, B_XR = 8, B_KV = 9, B_ST1 = 10, B_SDONE = 11  , B_RDY = 17  ,
              B_FULL4 = 23  , B_DSR = 28  , B_SEND = 36  , B_EMPTYB = 42  ,
              B_SIGP = 45, B_SIGH = 46, B_SIGKV = 47, B_SIGX1 = 48, B_MFREE = 49, B_EMPTY4 = 50  ,
              B_EMPTYA = 55  , B_PEER = 59, NBAR = 60;
constexpr int SPARE = 40960;
constexpr int UNIT4 = 25600, NU4 = 5;
constexpr int OFF_DS = OFF_A, OFF_SEND = OFF_A + 40960, OFF_G0 = OFF_A + 61440, OFF_G1 = OFF_B + UNIT4;

constexpr int FL_DONE = 0, FL_H = 1, FL_X1 = FL_H + 16, FL_KV = FL_X1 + 16, FL_CS = FL_KV + 8, FL_CS3 = FL_CS + 8, FL_ST = FL_CS3 + 8, FL_PART = FL_ST + 16;
constexpr int FL_COUNT = FL_PART + 16 * 8;
constexpr int ACC_FLOATS = 8 * KV_J + D_ + F_;

struct Maps {
  CUtensorMap x, w1m, w1r, qm, qr, hs, w2, x1, w3, w4, wo, st_h, st_x1, st_out, xr;
};

}

__device__ __align__(1024) __nv_bfloat16 g_Hs[(S_ + 4) * D_];
__device__ __align__(1024) __nv_bfloat16 g_X1[S_ * D_];
__device__ __align__(128) float g_acc[2][ACC_FLOATS];
__device__ __align__(128) float4 g_xstat[S_];
__device__ __align__(128) float2 g_st1[S_ * 8];
__device__ __align__(128) uint4 g_part[16 * 8 * 3 * 1280];
__device__ __align__(128) unsigned g_flags[FL_COUNT * 32];
#define TSTAMP(n) do {} while (0)
#define TSTAMPX(n) do {} while (0)
#define TRACE(n) do {} while (0)
#define TR4(n) do {} while (0)

namespace {

__device__ __forceinline__ long long gtime() { long long t; asm volatile("mov.u64 %0, %%globaltimer;" : "=l"(t)); return t; }
__device__ __forceinline__ uint32_t smem_u32(const void* p) { return (uint32_t)__cvta_generic_to_shared(p); }
__device__ __forceinline__ void mbar_init(uint32_t bar, int cnt) {
  asm volatile("mbarrier.init.shared::cta.b64 [%0], %1;" ::"r"(bar), "r"(cnt) : "memory");
}
__device__ __forceinline__ void mbar_expect_tx(uint32_t bar, int bytes) {
  asm volatile("mbarrier.arrive.expect_tx.shared::cta.b64 _, [%0], %1;" ::"r"(bar), "r"(bytes) : "memory");
}
__device__ __forceinline__ void mbar_arrive_cta(uint32_t bar, uint32_t cta) {
  asm volatile("{\n.reg .b32 ra;\nmapa.shared::cluster.u32 ra, %0, %1;\nmbarrier.arrive.shared::cluster.b64 _, [ra];\n}"
               ::"r"(bar), "r"(cta) : "memory");
}
__device__ __forceinline__ uint32_t mbar_try(uint32_t bar, uint32_t parity) {
  uint32_t ok;
  asm volatile("{\n.reg .pred p;\nmbarrier.try_wait.parity.shared::cta.b64 p, [%1], %2;\nselp.u32 %0, 1, 0, p;\n}"
               : "=r"(ok) : "r"(bar), "r"(parity) : "memory");
  return ok;
}
constexpr uint32_t WAIT_LIMIT = 1u << 22;
__device__ __forceinline__ void mbar_wait(uint32_t bar, uint32_t parity) {
  uint32_t n = 0;
  while (!mbar_try(bar, parity) && ++n < WAIT_LIMIT) {}
}
__device__ __forceinline__ unsigned ld_acquire(const unsigned* p) {
  unsigned v;
  asm volatile("ld.acquire.gpu.global.u32 %0, [%1];" : "=r"(v) : "l"(p) : "memory");
  return v;
}
__device__ __forceinline__ void flag_wait(int idx, unsigned target) {
  const unsigned* p = g_flags + idx * 32;
  uint32_t n = 0;
  while ((int)(ld_acquire(p) - target) < 0 && ++n < (WAIT_LIMIT >> 4)) {}
}
__device__ __forceinline__ void flag_add(int idx) {
  asm volatile("red.release.gpu.global.add.u32 [%0], 1;" ::"l"(g_flags + idx * 32) : "memory");
}
__device__ __forceinline__ void flag_add_relaxed(int idx) {
  asm volatile("red.relaxed.gpu.global.add.u32 [%0], 1;" ::"l"(g_flags + idx * 32) : "memory");
}
__device__ __forceinline__ uint32_t mbar_test(uint32_t bar, uint32_t parity) {
  uint32_t ok;
  asm volatile("{\n.reg .pred p;\nmbarrier.test_wait.parity.shared::cta.b64 p, [%1], %2;\nselp.u32 %0, 1, 0, p;\n}"
               : "=r"(ok) : "r"(bar), "r"(parity) : "memory");
  return ok;
}
__device__ __forceinline__ uint32_t lds32(uint32_t a) {
  uint32_t v;
  asm volatile("ld.shared.u32 %0, [%1];" : "=r"(v) : "r"(a) : "memory");
  return v;
}
__device__ __forceinline__ void mbar_arrive(uint32_t bar) {
  asm volatile("mbarrier.arrive.shared::cta.b64 _, [%0];" ::"r"(bar) : "memory");
}
__device__ __forceinline__ void fence_async_all() { asm volatile("fence.proxy.async;" ::: "memory"); }
__device__ __forceinline__ void fence_async_smem() { asm volatile("fence.proxy.async.shared::cta;" ::: "memory"); }
__device__ __forceinline__ void bar_sync(int id, int n) { asm volatile("bar.sync %0, %1;" ::"r"(id), "r"(n) : "memory"); }

__device__ __forceinline__ void tma2d(uint32_t dst, const CUtensorMap* m, uint32_t bar, int c0, int c1) {
  asm volatile("cp.async.bulk.tensor.2d.shared::cluster.global.mbarrier::complete_tx::bytes [%0], [%1, {%3, %4}], [%2];"
               ::"r"(dst), "l"(m), "r"(bar), "r"(c0), "r"(c1) : "memory");
}
__device__ __forceinline__ void tma2d_mc(uint32_t dst, const CUtensorMap* m, uint32_t bar, int c0, int c1) {
  asm volatile("cp.async.bulk.tensor.2d.shared::cluster.global.mbarrier::complete_tx::bytes.multicast::cluster"
               " [%0], [%1, {%3, %4}], [%2], %5;"
               ::"r"(dst), "l"(m), "r"(bar), "r"(c0), "r"(c1), "h"((uint16_t)3) : "memory");
}
__device__ __forceinline__ void tma3d(uint32_t dst, const CUtensorMap* m, uint32_t bar, int c0, int c1, int c2) {
  asm volatile("cp.async.bulk.tensor.3d.shared::cluster.global.mbarrier::complete_tx::bytes [%0], [%1, {%3, %4, %5}], [%2];"
               ::"r"(dst), "l"(m), "r"(bar), "r"(c0), "r"(c1), "r"(c2) : "memory");
}
__device__ __forceinline__ void tma4d(uint32_t dst, const CUtensorMap* m, uint32_t bar, int c0, int c1, int c2, int c3) {
  asm volatile("cp.async.bulk.tensor.4d.shared::cluster.global.mbarrier::complete_tx::bytes [%0], [%1, {%3, %4, %5, %6}], [%2];"
               ::"r"(dst), "l"(m), "r"(bar), "r"(c0), "r"(c1), "r"(c2), "r"(c3) : "memory");
}
__device__ __forceinline__ void tma2d_store(const CUtensorMap* m, uint32_t src, int c0, int c1) {
  asm volatile("cp.async.bulk.tensor.2d.global.shared::cta.bulk_group [%0, {%2, %3}], [%1];"
               ::"l"(m), "r"(src), "r"(c0), "r"(c1) : "memory");
}
__device__ __forceinline__ void bulk_store(void* dst, uint32_t src, uint32_t bytes) {
  asm volatile("cp.async.bulk.global.shared::cta.bulk_group [%0], [%1], %2;" ::"l"(dst), "r"(src), "r"(bytes) : "memory");
}
__device__ __forceinline__ void bulk_load(uint32_t dst, const void* src, uint32_t bytes, uint32_t bar) {
  asm volatile("cp.async.bulk.shared::cluster.global.mbarrier::complete_tx::bytes [%0], [%1], %2, [%3];"
               ::"r"(dst), "l"(src), "r"(bytes), "r"(bar) : "memory");
}
__device__ __forceinline__ void bulk_commit() { asm volatile("cp.async.bulk.commit_group;" ::: "memory"); }
template <int N> __device__ __forceinline__ void bulk_wait() { asm volatile("cp.async.bulk.wait_group %0;" ::"n"(N) : "memory"); }
__device__ __forceinline__ void bulk_wait_read() { asm volatile("cp.async.bulk.wait_group.read 0;" ::: "memory"); }
__device__ __forceinline__ void bar_arrive(int id, int n) { asm volatile("bar.arrive %0, %1;" ::"r"(id), "r"(n) : "memory"); }
__device__ __forceinline__ uint4 lds128(uint32_t a) {
  uint4 v;
  asm volatile("ld.shared.v4.u32 {%0, %1, %2, %3}, [%4];" : "=r"(v.x), "=r"(v.y), "=r"(v.z), "=r"(v.w) : "r"(a) : "memory");
  return v;
}
__device__ __forceinline__ void sts128(uint32_t a, uint4 v) {
  asm volatile("st.shared.v4.u32 [%0], {%1, %2, %3, %4};" ::"r"(a), "r"(v.x), "r"(v.y), "r"(v.z), "r"(v.w) : "memory");
}
__device__ __forceinline__ uint32_t map_peer(uint32_t addr, uint32_t cta) {
  uint32_t r;
  asm("mapa.shared::cluster.u32 %0, %1, %2;" : "=r"(r) : "r"(addr), "r"(cta));
  return r;
}
__device__ __forceinline__ void st_async16(uint32_t addr, uint32_t a, uint32_t b, uint32_t c, uint32_t d, uint32_t bar) {
  asm volatile("st.async.weak.shared::cluster.mbarrier::complete_tx::bytes.v4.b32 [%0], {%1, %2, %3, %4}, [%5];"
               ::"r"(addr), "r"(a), "r"(b), "r"(c), "r"(d), "r"(bar) : "memory");
}
__device__ __forceinline__ void l2_prefetch(const void* p, uint32_t bytes) {
  asm volatile("cp.async.bulk.prefetch.L2.global [%0], %1;" ::"l"(p), "r"(bytes) : "memory");
}
__device__ __forceinline__ void prefetch_tmap(const CUtensorMap* m) {
  asm volatile("prefetch.tensormap [%0];" ::"l"(m) : "memory");
}
__device__ __forceinline__ uint64_t make_desc(uint32_t a16, uint32_t off, uint32_t lbo, uint32_t sbo, uint32_t swz) {
  const uint32_t lo = a16 + ((off >> 4) + ((lbo >> 4) << 16)), hi = (sbo >> 4) | (swz << 30);
  uint64_t d;
  asm("mov.b64 %0, {%1, %2};" : "=l"(d) : "r"(lo), "r"(hi));
  return d;
}
__device__ __forceinline__ void wg_fence() { asm volatile("wgmma.fence.sync.aligned;" ::: "memory"); }
__device__ __forceinline__ void wg_commit() { asm volatile("wgmma.commit_group.sync.aligned;" ::: "memory"); }
template <int N> __device__ __forceinline__ void wg_wait() { asm volatile("wgmma.wait_group.sync.aligned %0;" ::"n"(N) : "memory"); }
template <int N> __device__ __forceinline__ void fence_regs(float (&d)[N]) {
#pragma unroll
  for (int i = 0; i < N; i++) asm volatile("" : "+f"(d[i])::"memory");
}
template <int N> __device__ __forceinline__ void zero_regs(float (&d)[N]) {
#pragma unroll
  for (int i = 0; i < N; i++) d[i] = 0.f;
}
__device__ __forceinline__ uint32_t pack_bf16(float lo, float hi) {
  uint32_t r;
  asm("cvt.rn.bf16x2.f32 %0, %1, %2;" : "=r"(r) : "f"(hi), "f"(lo));
  return r;
}
__device__ __forceinline__ float bf_lo(uint32_t v) { return __uint_as_float(v << 16); }
__device__ __forceinline__ float bf_hi(uint32_t v) { return __uint_as_float(v & 0xffff0000u); }
__device__ __forceinline__ uint32_t max_bf2(uint32_t a, uint32_t b) {
  uint32_t r; asm("max.bf16x2 %0, %1, %2;" : "=r"(r) : "r"(a), "r"(b)); return r;
}
__device__ __forceinline__ uint32_t min_bf2(uint32_t a, uint32_t b) {
  uint32_t r; asm("min.bf16x2 %0, %1, %2;" : "=r"(r) : "r"(a), "r"(b)); return r;
}
__device__ __forceinline__ float ex2(float x) { float r; asm("ex2.approx.ftz.f32 %0, %1;" : "=f"(r) : "f"(x)); return r; }
__device__ __forceinline__ float rcp(float x) { float r; asm("rcp.approx.ftz.f32 %0, %1;" : "=f"(r) : "f"(x)); return r; }
__device__ __forceinline__ float tanh_ap(float x) { float r; asm("tanh.approx.f32 %0, %1;" : "=f"(r) : "f"(x)); return r; }
__device__ __forceinline__ float gelu_s(float x, float hs) {
  float u = x * fmaf(x * x, 0.0356774081f, 0.7978845608f);
  float hx = x * hs;
  return fmaf(hx, tanh_ap(u), hx);
}
__device__ __forceinline__ void stsm4(uint32_t addr, uint32_t r0, uint32_t r1, uint32_t r2, uint32_t r3) {
  asm volatile("stmatrix.sync.aligned.m8n8.x4.shared.b16 [%0], {%1, %2, %3, %4};"
               ::"r"(addr), "r"(r0), "r"(r1), "r"(r2), "r"(r3) : "memory");
}
__device__ __forceinline__ void red_add4(float* p, float a, float b, float c, float d) {
  asm volatile("red.global.add.v4.f32 [%0], {%1, %2, %3, %4};" ::"l"(p), "f"(a), "f"(b), "f"(c), "f"(d) : "memory");
}
__device__ __forceinline__ void red_add2(float* p, float a, float b) {
  asm volatile("red.global.add.v2.f32 [%0], {%1, %2};" ::"l"(p), "f"(a), "f"(b) : "memory");
}

__device__ __forceinline__ void mma_ss256(float (&d)[128], uint64_t descA, uint64_t descB) {
  asm volatile("wgmma.mma_async.sync.aligned.m64n256k16.f32.bf16.bf16 {"
      "%0, %1, %2, %3, %4, %5, %6, %7, %8, %9, %10, %11, %12, %13, %14, %15, "
      "%16, %17, %18, %19, %20, %21, %22, %23, %24, %25, %26, %27, %28, %29, %30, %31, "
      "%32, %33, %34, %35, %36, %37, %38, %39, %40, %41, %42, %43, %44, %45, %46, %47, "
      "%48, %49, %50, %51, %52, %53, %54, %55, %56, %57, %58, %59, %60, %61, %62, %63, "
      "%64, %65, %66, %67, %68, %69, %70, %71, %72, %73, %74, %75, %76, %77, %78, %79, "
      "%80, %81, %82, %83, %84, %85, %86, %87, %88, %89, %90, %91, %92, %93, %94, %95, "
      "%96, %97, %98, %99, %100, %101, %102, %103, %104, %105, %106, %107, %108, %109, %110, %111, "
      "%112, %113, %114, %115, %116, %117, %118, %119, %120, %121, %122, %123, %124, %125, %126, %127"
      "}, %128, %129, 1, 1, 1, 0, 1;\n"
      : "+f"(d[0]), "+f"(d[1]), "+f"(d[2]), "+f"(d[3]), "+f"(d[4]), "+f"(d[5]), "+f"(d[6]), "+f"(d[7]),
        "+f"(d[8]), "+f"(d[9]), "+f"(d[10]), "+f"(d[11]), "+f"(d[12]), "+f"(d[13]), "+f"(d[14]), "+f"(d[15]),
        "+f"(d[16]), "+f"(d[17]), "+f"(d[18]), "+f"(d[19]), "+f"(d[20]), "+f"(d[21]), "+f"(d[22]), "+f"(d[23]),
        "+f"(d[24]), "+f"(d[25]), "+f"(d[26]), "+f"(d[27]), "+f"(d[28]), "+f"(d[29]), "+f"(d[30]), "+f"(d[31]),
        "+f"(d[32]), "+f"(d[33]), "+f"(d[34]), "+f"(d[35]), "+f"(d[36]), "+f"(d[37]), "+f"(d[38]), "+f"(d[39]),
        "+f"(d[40]), "+f"(d[41]), "+f"(d[42]), "+f"(d[43]), "+f"(d[44]), "+f"(d[45]), "+f"(d[46]), "+f"(d[47]),
        "+f"(d[48]), "+f"(d[49]), "+f"(d[50]), "+f"(d[51]), "+f"(d[52]), "+f"(d[53]), "+f"(d[54]), "+f"(d[55]),
        "+f"(d[56]), "+f"(d[57]), "+f"(d[58]), "+f"(d[59]), "+f"(d[60]), "+f"(d[61]), "+f"(d[62]), "+f"(d[63]),
        "+f"(d[64]), "+f"(d[65]), "+f"(d[66]), "+f"(d[67]), "+f"(d[68]), "+f"(d[69]), "+f"(d[70]), "+f"(d[71]),
        "+f"(d[72]), "+f"(d[73]), "+f"(d[74]), "+f"(d[75]), "+f"(d[76]), "+f"(d[77]), "+f"(d[78]), "+f"(d[79]),
        "+f"(d[80]), "+f"(d[81]), "+f"(d[82]), "+f"(d[83]), "+f"(d[84]), "+f"(d[85]), "+f"(d[86]), "+f"(d[87]),
        "+f"(d[88]), "+f"(d[89]), "+f"(d[90]), "+f"(d[91]), "+f"(d[92]), "+f"(d[93]), "+f"(d[94]), "+f"(d[95]),
        "+f"(d[96]), "+f"(d[97]), "+f"(d[98]), "+f"(d[99]), "+f"(d[100]), "+f"(d[101]), "+f"(d[102]), "+f"(d[103]),
        "+f"(d[104]), "+f"(d[105]), "+f"(d[106]), "+f"(d[107]), "+f"(d[108]), "+f"(d[109]), "+f"(d[110]), "+f"(d[111]),
        "+f"(d[112]), "+f"(d[113]), "+f"(d[114]), "+f"(d[115]), "+f"(d[116]), "+f"(d[117]), "+f"(d[118]), "+f"(d[119]),
        "+f"(d[120]), "+f"(d[121]), "+f"(d[122]), "+f"(d[123]), "+f"(d[124]), "+f"(d[125]), "+f"(d[126]), "+f"(d[127])
      : "l"(descA), "l"(descB));
}

__device__ __forceinline__ void mma_ss64(float (&d)[32], uint64_t descA, uint64_t descB) {
  asm volatile("wgmma.mma_async.sync.aligned.m64n64k16.f32.bf16.bf16 {"
      "%0, %1, %2, %3, %4, %5, %6, %7, %8, %9, %10, %11, %12, %13, %14, %15, "
      "%16, %17, %18, %19, %20, %21, %22, %23, %24, %25, %26, %27, %28, %29, %30, %31"
      "}, %32, %33, 1, 1, 1, 0, 1;\n"
      : "+f"(d[0]), "+f"(d[1]), "+f"(d[2]), "+f"(d[3]), "+f"(d[4]), "+f"(d[5]), "+f"(d[6]), "+f"(d[7]),
        "+f"(d[8]), "+f"(d[9]), "+f"(d[10]), "+f"(d[11]), "+f"(d[12]), "+f"(d[13]), "+f"(d[14]), "+f"(d[15]),
        "+f"(d[16]), "+f"(d[17]), "+f"(d[18]), "+f"(d[19]), "+f"(d[20]), "+f"(d[21]), "+f"(d[22]), "+f"(d[23]),
        "+f"(d[24]), "+f"(d[25]), "+f"(d[26]), "+f"(d[27]), "+f"(d[28]), "+f"(d[29]), "+f"(d[30]), "+f"(d[31])
      : "l"(descA), "l"(descB));
}

__device__ __forceinline__ void mma_ss80(float (&d)[40], uint64_t descA, uint64_t descB) {
  asm volatile("wgmma.mma_async.sync.aligned.m64n80k16.f32.bf16.bf16 {"
      "%0, %1, %2, %3, %4, %5, %6, %7, %8, %9, %10, %11, %12, %13, %14, %15, "
      "%16, %17, %18, %19, %20, %21, %22, %23, %24, %25, %26, %27, %28, %29, %30, %31, "
      "%32, %33, %34, %35, %36, %37, %38, %39"
      "}, %40, %41, 1, 1, 1, 0, 1;\n"
      : "+f"(d[0]), "+f"(d[1]), "+f"(d[2]), "+f"(d[3]), "+f"(d[4]), "+f"(d[5]), "+f"(d[6]), "+f"(d[7]),
        "+f"(d[8]), "+f"(d[9]), "+f"(d[10]), "+f"(d[11]), "+f"(d[12]), "+f"(d[13]), "+f"(d[14]), "+f"(d[15]),
        "+f"(d[16]), "+f"(d[17]), "+f"(d[18]), "+f"(d[19]), "+f"(d[20]), "+f"(d[21]), "+f"(d[22]), "+f"(d[23]),
        "+f"(d[24]), "+f"(d[25]), "+f"(d[26]), "+f"(d[27]), "+f"(d[28]), "+f"(d[29]), "+f"(d[30]), "+f"(d[31]),
        "+f"(d[32]), "+f"(d[33]), "+f"(d[34]), "+f"(d[35]), "+f"(d[36]), "+f"(d[37]), "+f"(d[38]), "+f"(d[39])
      : "l"(descA), "l"(descB));
}

__device__ __forceinline__ void mma_ss192(float (&d)[96], uint64_t descA, uint64_t descB) {
  asm volatile("wgmma.mma_async.sync.aligned.m64n192k16.f32.bf16.bf16 {"
      "%0, %1, %2, %3, %4, %5, %6, %7, %8, %9, %10, %11, %12, %13, %14, %15, "
      "%16, %17, %18, %19, %20, %21, %22, %23, %24, %25, %26, %27, %28, %29, %30, %31, "
      "%32, %33, %34, %35, %36, %37, %38, %39, %40, %41, %42, %43, %44, %45, %46, %47, "
      "%48, %49, %50, %51, %52, %53, %54, %55, %56, %57, %58, %59, %60, %61, %62, %63, "
      "%64, %65, %66, %67, %68, %69, %70, %71, %72, %73, %74, %75, %76, %77, %78, %79, "
      "%80, %81, %82, %83, %84, %85, %86, %87, %88, %89, %90, %91, %92, %93, %94, %95"
      "}, %96, %97, 1, 1, 1, 0, 1;\n"
      : "+f"(d[0]), "+f"(d[1]), "+f"(d[2]), "+f"(d[3]), "+f"(d[4]), "+f"(d[5]), "+f"(d[6]), "+f"(d[7]),
        "+f"(d[8]), "+f"(d[9]), "+f"(d[10]), "+f"(d[11]), "+f"(d[12]), "+f"(d[13]), "+f"(d[14]), "+f"(d[15]),
        "+f"(d[16]), "+f"(d[17]), "+f"(d[18]), "+f"(d[19]), "+f"(d[20]), "+f"(d[21]), "+f"(d[22]), "+f"(d[23]),
        "+f"(d[24]), "+f"(d[25]), "+f"(d[26]), "+f"(d[27]), "+f"(d[28]), "+f"(d[29]), "+f"(d[30]), "+f"(d[31]),
        "+f"(d[32]), "+f"(d[33]), "+f"(d[34]), "+f"(d[35]), "+f"(d[36]), "+f"(d[37]), "+f"(d[38]), "+f"(d[39]),
        "+f"(d[40]), "+f"(d[41]), "+f"(d[42]), "+f"(d[43]), "+f"(d[44]), "+f"(d[45]), "+f"(d[46]), "+f"(d[47]),
        "+f"(d[48]), "+f"(d[49]), "+f"(d[50]), "+f"(d[51]), "+f"(d[52]), "+f"(d[53]), "+f"(d[54]), "+f"(d[55]),
        "+f"(d[56]), "+f"(d[57]), "+f"(d[58]), "+f"(d[59]), "+f"(d[60]), "+f"(d[61]), "+f"(d[62]), "+f"(d[63]),
        "+f"(d[64]), "+f"(d[65]), "+f"(d[66]), "+f"(d[67]), "+f"(d[68]), "+f"(d[69]), "+f"(d[70]), "+f"(d[71]),
        "+f"(d[72]), "+f"(d[73]), "+f"(d[74]), "+f"(d[75]), "+f"(d[76]), "+f"(d[77]), "+f"(d[78]), "+f"(d[79]),
        "+f"(d[80]), "+f"(d[81]), "+f"(d[82]), "+f"(d[83]), "+f"(d[84]), "+f"(d[85]), "+f"(d[86]), "+f"(d[87]),
        "+f"(d[88]), "+f"(d[89]), "+f"(d[90]), "+f"(d[91]), "+f"(d[92]), "+f"(d[93]), "+f"(d[94]), "+f"(d[95])
      : "l"(descA), "l"(descB));
}

__device__ __forceinline__ void mma_ss80_tt(float (&d)[40], uint64_t descA, uint64_t descB) {
  asm volatile("wgmma.mma_async.sync.aligned.m64n80k16.f32.bf16.bf16 {"
      "%0, %1, %2, %3, %4, %5, %6, %7, %8, %9, %10, %11, %12, %13, %14, %15, "
      "%16, %17, %18, %19, %20, %21, %22, %23, %24, %25, %26, %27, %28, %29, %30, %31, "
      "%32, %33, %34, %35, %36, %37, %38, %39"
      "}, %40, %41, 1, 1, 1, 1, 1;\n"
      : "+f"(d[0]), "+f"(d[1]), "+f"(d[2]), "+f"(d[3]), "+f"(d[4]), "+f"(d[5]), "+f"(d[6]), "+f"(d[7]),
        "+f"(d[8]), "+f"(d[9]), "+f"(d[10]), "+f"(d[11]), "+f"(d[12]), "+f"(d[13]), "+f"(d[14]), "+f"(d[15]),
        "+f"(d[16]), "+f"(d[17]), "+f"(d[18]), "+f"(d[19]), "+f"(d[20]), "+f"(d[21]), "+f"(d[22]), "+f"(d[23]),
        "+f"(d[24]), "+f"(d[25]), "+f"(d[26]), "+f"(d[27]), "+f"(d[28]), "+f"(d[29]), "+f"(d[30]), "+f"(d[31]),
        "+f"(d[32]), "+f"(d[33]), "+f"(d[34]), "+f"(d[35]), "+f"(d[36]), "+f"(d[37]), "+f"(d[38]), "+f"(d[39])
      : "l"(descA), "l"(descB));
}
__device__ __forceinline__ void mma_ss80_tt_z(float (&d)[40], uint64_t descA, uint64_t descB) {
  asm volatile("wgmma.mma_async.sync.aligned.m64n80k16.f32.bf16.bf16 {"
      "%0, %1, %2, %3, %4, %5, %6, %7, %8, %9, %10, %11, %12, %13, %14, %15, "
      "%16, %17, %18, %19, %20, %21, %22, %23, %24, %25, %26, %27, %28, %29, %30, %31, "
      "%32, %33, %34, %35, %36, %37, %38, %39"
      "}, %40, %41, 0, 1, 1, 1, 1;\n"
      : "=f"(d[0]), "=f"(d[1]), "=f"(d[2]), "=f"(d[3]), "=f"(d[4]), "=f"(d[5]), "=f"(d[6]), "=f"(d[7]),
        "=f"(d[8]), "=f"(d[9]), "=f"(d[10]), "=f"(d[11]), "=f"(d[12]), "=f"(d[13]), "=f"(d[14]), "=f"(d[15]),
        "=f"(d[16]), "=f"(d[17]), "=f"(d[18]), "=f"(d[19]), "=f"(d[20]), "=f"(d[21]), "=f"(d[22]), "=f"(d[23]),
        "=f"(d[24]), "=f"(d[25]), "=f"(d[26]), "=f"(d[27]), "=f"(d[28]), "=f"(d[29]), "=f"(d[30]), "=f"(d[31]),
        "=f"(d[32]), "=f"(d[33]), "=f"(d[34]), "=f"(d[35]), "=f"(d[36]), "=f"(d[37]), "=f"(d[38]), "=f"(d[39])
      : "l"(descA), "l"(descB));
}

__device__ __forceinline__ void mma_rs80_k(float (&d)[40], const uint32_t (&a)[4], uint64_t descB) {
  asm volatile("wgmma.mma_async.sync.aligned.m64n80k16.f32.bf16.bf16 {"
      "%0, %1, %2, %3, %4, %5, %6, %7, %8, %9, %10, %11, %12, %13, %14, %15, "
      "%16, %17, %18, %19, %20, %21, %22, %23, %24, %25, %26, %27, %28, %29, %30, %31, "
      "%32, %33, %34, %35, %36, %37, %38, %39"
      "}, {%40, %41, %42, %43}, %44, 1, 1, 1, 0;\n"
      : "+f"(d[0]), "+f"(d[1]), "+f"(d[2]), "+f"(d[3]), "+f"(d[4]), "+f"(d[5]), "+f"(d[6]), "+f"(d[7]),
        "+f"(d[8]), "+f"(d[9]), "+f"(d[10]), "+f"(d[11]), "+f"(d[12]), "+f"(d[13]), "+f"(d[14]), "+f"(d[15]),
        "+f"(d[16]), "+f"(d[17]), "+f"(d[18]), "+f"(d[19]), "+f"(d[20]), "+f"(d[21]), "+f"(d[22]), "+f"(d[23]),
        "+f"(d[24]), "+f"(d[25]), "+f"(d[26]), "+f"(d[27]), "+f"(d[28]), "+f"(d[29]), "+f"(d[30]), "+f"(d[31]),
        "+f"(d[32]), "+f"(d[33]), "+f"(d[34]), "+f"(d[35]), "+f"(d[36]), "+f"(d[37]), "+f"(d[38]), "+f"(d[39])
      : "r"(a[0]), "r"(a[1]), "r"(a[2]), "r"(a[3]), "l"(descB));
}
__device__ __forceinline__ void mma_rs80_k_z(float (&d)[40], const uint32_t (&a)[4], uint64_t descB) {
  asm volatile("wgmma.mma_async.sync.aligned.m64n80k16.f32.bf16.bf16 {"
      "%0, %1, %2, %3, %4, %5, %6, %7, %8, %9, %10, %11, %12, %13, %14, %15, "
      "%16, %17, %18, %19, %20, %21, %22, %23, %24, %25, %26, %27, %28, %29, %30, %31, "
      "%32, %33, %34, %35, %36, %37, %38, %39"
      "}, {%40, %41, %42, %43}, %44, 0, 1, 1, 0;\n"
      : "=f"(d[0]), "=f"(d[1]), "=f"(d[2]), "=f"(d[3]), "=f"(d[4]), "=f"(d[5]), "=f"(d[6]), "=f"(d[7]),
        "=f"(d[8]), "=f"(d[9]), "=f"(d[10]), "=f"(d[11]), "=f"(d[12]), "=f"(d[13]), "=f"(d[14]), "=f"(d[15]),
        "=f"(d[16]), "=f"(d[17]), "=f"(d[18]), "=f"(d[19]), "=f"(d[20]), "=f"(d[21]), "=f"(d[22]), "=f"(d[23]),
        "=f"(d[24]), "=f"(d[25]), "=f"(d[26]), "=f"(d[27]), "=f"(d[28]), "=f"(d[29]), "=f"(d[30]), "=f"(d[31]),
        "=f"(d[32]), "=f"(d[33]), "=f"(d[34]), "=f"(d[35]), "=f"(d[36]), "=f"(d[37]), "=f"(d[38]), "=f"(d[39])
      : "r"(a[0]), "r"(a[1]), "r"(a[2]), "r"(a[3]), "l"(descB));
}

__device__ __forceinline__ void mma_rs48_k(float (&d)[24], const uint32_t (&a)[4], uint64_t descB) {
  asm volatile("wgmma.mma_async.sync.aligned.m64n48k16.f32.bf16.bf16 {"
      "%0, %1, %2, %3, %4, %5, %6, %7, %8, %9, %10, %11, %12, %13, %14, %15, "
      "%16, %17, %18, %19, %20, %21, %22, %23"
      "}, {%24, %25, %26, %27}, %28, 1, 1, 1, 0;\n"
      : "+f"(d[0]), "+f"(d[1]), "+f"(d[2]), "+f"(d[3]), "+f"(d[4]), "+f"(d[5]), "+f"(d[6]), "+f"(d[7]),
        "+f"(d[8]), "+f"(d[9]), "+f"(d[10]), "+f"(d[11]), "+f"(d[12]), "+f"(d[13]), "+f"(d[14]), "+f"(d[15]),
        "+f"(d[16]), "+f"(d[17]), "+f"(d[18]), "+f"(d[19]), "+f"(d[20]), "+f"(d[21]), "+f"(d[22]), "+f"(d[23])
      : "r"(a[0]), "r"(a[1]), "r"(a[2]), "r"(a[3]), "l"(descB));
}
__device__ __forceinline__ void mma_rs48_k_z(float (&d)[24], const uint32_t (&a)[4], uint64_t descB) {
  asm volatile("wgmma.mma_async.sync.aligned.m64n48k16.f32.bf16.bf16 {"
      "%0, %1, %2, %3, %4, %5, %6, %7, %8, %9, %10, %11, %12, %13, %14, %15, "
      "%16, %17, %18, %19, %20, %21, %22, %23"
      "}, {%24, %25, %26, %27}, %28, 0, 1, 1, 0;\n"
      : "=f"(d[0]), "=f"(d[1]), "=f"(d[2]), "=f"(d[3]), "=f"(d[4]), "=f"(d[5]), "=f"(d[6]), "=f"(d[7]),
        "=f"(d[8]), "=f"(d[9]), "=f"(d[10]), "=f"(d[11]), "=f"(d[12]), "=f"(d[13]), "=f"(d[14]), "=f"(d[15]),
        "=f"(d[16]), "=f"(d[17]), "=f"(d[18]), "=f"(d[19]), "=f"(d[20]), "=f"(d[21]), "=f"(d[22]), "=f"(d[23])
      : "r"(a[0]), "r"(a[1]), "r"(a[2]), "r"(a[3]), "l"(descB));
}

__device__ __forceinline__ void mma_rs160_n(float (&d)[80], const uint32_t (&a)[4], uint64_t descB) {
  asm volatile("wgmma.mma_async.sync.aligned.m64n160k16.f32.bf16.bf16 {"
      "%0, %1, %2, %3, %4, %5, %6, %7, %8, %9, %10, %11, %12, %13, %14, %15, "
      "%16, %17, %18, %19, %20, %21, %22, %23, %24, %25, %26, %27, %28, %29, %30, %31, "
      "%32, %33, %34, %35, %36, %37, %38, %39, %40, %41, %42, %43, %44, %45, %46, %47, "
      "%48, %49, %50, %51, %52, %53, %54, %55, %56, %57, %58, %59, %60, %61, %62, %63, "
      "%64, %65, %66, %67, %68, %69, %70, %71, %72, %73, %74, %75, %76, %77, %78, %79"
      "}, {%80, %81, %82, %83}, %84, 1, 1, 1, 1;\n"
      : "+f"(d[0]), "+f"(d[1]), "+f"(d[2]), "+f"(d[3]), "+f"(d[4]), "+f"(d[5]), "+f"(d[6]), "+f"(d[7]),
        "+f"(d[8]), "+f"(d[9]), "+f"(d[10]), "+f"(d[11]), "+f"(d[12]), "+f"(d[13]), "+f"(d[14]), "+f"(d[15]),
        "+f"(d[16]), "+f"(d[17]), "+f"(d[18]), "+f"(d[19]), "+f"(d[20]), "+f"(d[21]), "+f"(d[22]), "+f"(d[23]),
        "+f"(d[24]), "+f"(d[25]), "+f"(d[26]), "+f"(d[27]), "+f"(d[28]), "+f"(d[29]), "+f"(d[30]), "+f"(d[31]),
        "+f"(d[32]), "+f"(d[33]), "+f"(d[34]), "+f"(d[35]), "+f"(d[36]), "+f"(d[37]), "+f"(d[38]), "+f"(d[39]),
        "+f"(d[40]), "+f"(d[41]), "+f"(d[42]), "+f"(d[43]), "+f"(d[44]), "+f"(d[45]), "+f"(d[46]), "+f"(d[47]),
        "+f"(d[48]), "+f"(d[49]), "+f"(d[50]), "+f"(d[51]), "+f"(d[52]), "+f"(d[53]), "+f"(d[54]), "+f"(d[55]),
        "+f"(d[56]), "+f"(d[57]), "+f"(d[58]), "+f"(d[59]), "+f"(d[60]), "+f"(d[61]), "+f"(d[62]), "+f"(d[63]),
        "+f"(d[64]), "+f"(d[65]), "+f"(d[66]), "+f"(d[67]), "+f"(d[68]), "+f"(d[69]), "+f"(d[70]), "+f"(d[71]),
        "+f"(d[72]), "+f"(d[73]), "+f"(d[74]), "+f"(d[75]), "+f"(d[76]), "+f"(d[77]), "+f"(d[78]), "+f"(d[79])
      : "r"(a[0]), "r"(a[1]), "r"(a[2]), "r"(a[3]), "l"(descB));
}
__device__ __forceinline__ void mma_rs160_n_z(float (&d)[80], const uint32_t (&a)[4], uint64_t descB) {
  asm volatile("wgmma.mma_async.sync.aligned.m64n160k16.f32.bf16.bf16 {"
      "%0, %1, %2, %3, %4, %5, %6, %7, %8, %9, %10, %11, %12, %13, %14, %15, "
      "%16, %17, %18, %19, %20, %21, %22, %23, %24, %25, %26, %27, %28, %29, %30, %31, "
      "%32, %33, %34, %35, %36, %37, %38, %39, %40, %41, %42, %43, %44, %45, %46, %47, "
      "%48, %49, %50, %51, %52, %53, %54, %55, %56, %57, %58, %59, %60, %61, %62, %63, "
      "%64, %65, %66, %67, %68, %69, %70, %71, %72, %73, %74, %75, %76, %77, %78, %79"
      "}, {%80, %81, %82, %83}, %84, 0, 1, 1, 1;\n"
      : "=f"(d[0]), "=f"(d[1]), "=f"(d[2]), "=f"(d[3]), "=f"(d[4]), "=f"(d[5]), "=f"(d[6]), "=f"(d[7]),
        "=f"(d[8]), "=f"(d[9]), "=f"(d[10]), "=f"(d[11]), "=f"(d[12]), "=f"(d[13]), "=f"(d[14]), "=f"(d[15]),
        "=f"(d[16]), "=f"(d[17]), "=f"(d[18]), "=f"(d[19]), "=f"(d[20]), "=f"(d[21]), "=f"(d[22]), "=f"(d[23]),
        "=f"(d[24]), "=f"(d[25]), "=f"(d[26]), "=f"(d[27]), "=f"(d[28]), "=f"(d[29]), "=f"(d[30]), "=f"(d[31]),
        "=f"(d[32]), "=f"(d[33]), "=f"(d[34]), "=f"(d[35]), "=f"(d[36]), "=f"(d[37]), "=f"(d[38]), "=f"(d[39]),
        "=f"(d[40]), "=f"(d[41]), "=f"(d[42]), "=f"(d[43]), "=f"(d[44]), "=f"(d[45]), "=f"(d[46]), "=f"(d[47]),
        "=f"(d[48]), "=f"(d[49]), "=f"(d[50]), "=f"(d[51]), "=f"(d[52]), "=f"(d[53]), "=f"(d[54]), "=f"(d[55]),
        "=f"(d[56]), "=f"(d[57]), "=f"(d[58]), "=f"(d[59]), "=f"(d[60]), "=f"(d[61]), "=f"(d[62]), "=f"(d[63]),
        "=f"(d[64]), "=f"(d[65]), "=f"(d[66]), "=f"(d[67]), "=f"(d[68]), "=f"(d[69]), "=f"(d[70]), "=f"(d[71]),
        "=f"(d[72]), "=f"(d[73]), "=f"(d[74]), "=f"(d[75]), "=f"(d[76]), "=f"(d[77]), "=f"(d[78]), "=f"(d[79])
      : "r"(a[0]), "r"(a[1]), "r"(a[2]), "r"(a[3]), "l"(descB));
}

__device__ __forceinline__ void feature_map(const uint32_t (&P)[2][10], uint32_t (&fr)[10][4]) {
  constexpr float L2E = 1.4426950408889634f;
#pragma unroll
  for (int p = 0; p < 2; p++) {
#pragma unroll
    for (int r = 0; r < 2; r++) {
      uint32_t mx = P[r][5 * p], mn = mx;
#pragma unroll
      for (int g = 1; g < 5; g++) { mx = max_bf2(mx, P[r][5 * p + g]); mn = min_bf2(mn, P[r][5 * p + g]); }
      mx = max_bf2(mx, __shfl_xor_sync(0xffffffffu, mx, 1));
      mn = min_bf2(mn, __shfl_xor_sync(0xffffffffu, mn, 1));
      mx = max_bf2(mx, __shfl_xor_sync(0xffffffffu, mx, 2));
      mn = min_bf2(mn, __shfl_xor_sync(0xffffffffu, mn, 2));
      float mx0 = -bf_lo(mx) * L2E, mx1 = -bf_hi(mx) * L2E, mn0 = bf_lo(mn) * L2E, mn1 = bf_hi(mn) * L2E;
      float ep0[5], ep1[5], en0[5], en1[5];
      float sp0 = 0.f, sp1 = 0.f, sn0 = 0.f, sn1 = 0.f;
#pragma unroll
      for (int g = 0; g < 5; g++) {
        float x0 = bf_lo(P[r][5 * p + g]), x1 = bf_hi(P[r][5 * p + g]);
        ep0[g] = ex2(fmaf(x0, L2E, mx0)); ep1[g] = ex2(fmaf(x1, L2E, mx1));
        en0[g] = ex2(fmaf(x0, -L2E, mn0)); en1[g] = ex2(fmaf(x1, -L2E, mn1));
        sp0 += ep0[g]; sp1 += ep1[g]; sn0 += en0[g]; sn1 += en1[g];
      }
      sp0 += __shfl_xor_sync(0xffffffffu, sp0, 1); sp1 += __shfl_xor_sync(0xffffffffu, sp1, 1);
      sn0 += __shfl_xor_sync(0xffffffffu, sn0, 1); sn1 += __shfl_xor_sync(0xffffffffu, sn1, 1);
      sp0 += __shfl_xor_sync(0xffffffffu, sp0, 2); sp1 += __shfl_xor_sync(0xffffffffu, sp1, 2);
      sn0 += __shfl_xor_sync(0xffffffffu, sn0, 2); sn1 += __shfl_xor_sync(0xffffffffu, sn1, 2);
      sp0 = rcp(sp0); sp1 = rcp(sp1); sn0 = rcp(sn0); sn1 = rcp(sn1);
#pragma unroll
      for (int g = 0; g < 5; g++) {
        fr[5 * p + g][r] = pack_bf16(ep0[g] * sp0, ep1[g] * sp1);
        fr[5 * p + g][2 + r] = pack_bf16(en0[g] * sn0, en1[g] * sn1);
      }
    }
  }
}

struct Ring {
  uint32_t idx, phase;
  template <int N> __device__ __forceinline__ void next() { if (++idx == N) { idx = 0; phase ^= 1; } }
};

}

__global__ void __cluster_dims__(2, 1, 1) __launch_bounds__(384, 1)
fused_kernel(const __grid_constant__ Maps maps, const __nv_bfloat16* __restrict__ x, const __nv_bfloat16* __restrict__ wqkv,
             const __nv_bfloat16* __restrict__ wphi, const __nv_bfloat16* __restrict__ w1, const __nv_bfloat16* __restrict__ w2,
             const __nv_bfloat16* __restrict__ w3, const __nv_bfloat16* __restrict__ w4, const __nv_bfloat16* __restrict__ wo,
             const __nv_bfloat16* __restrict__ gate_w) {
  extern __shared__ __align__(1024) uint8_t sgen[];
  const uint32_t sb = smem_u32(sgen);
  const uint32_t sb16 = (sb & 0x3FFFFu) >> 4;
  const uint32_t bars = sb + OFF_BAR;
  const uint32_t fullA = bars + 8 * B_FULLA, emptyA = bars + 8 * B_EMPTYA, fullB = bars + 8 * B_FULLB, emptyB = bars + 8 * B_EMPTYB;

  const int tid = threadIdx.x;
  const int rank = blockIdx.x & 1;
  const int pairIdx = blockIdx.x >> 1;
  const int i = pairIdx >> 2, j = 2 * (pairIdx & 3) + rank;

  TSTAMP(0);
  uint4 pv[5], pw_[5], pc[2], pre;
  if (tid < 256) {
    const int row = 128 * i + 16 * j + (tid >> 4), l16 = tid & 15;
#pragma unroll
    for (int c = 0; c < 5; c++) pv[c] = __ldg(reinterpret_cast<const uint4*>(x + (size_t)row * D_ + c * 128 + l16 * 8));
    const int tq = tid < 200 ? tid : 0;
    const __nv_bfloat16* cp = w1 + (size_t)(40 * i + tq / 10) * D_ + 80 * j + 8 * (tq % 10);
    pc[0] = __ldg(reinterpret_cast<const uint4*>(cp)); pc[1] = __ldg(reinterpret_cast<const uint4*>(cp + 20 * D_));
    pre = __ldg(reinterpret_cast<const uint4*>(wphi + (size_t)j * 1600) + tq);
#pragma unroll
    for (int c = 0; c < 5; c++) pw_[c] = __ldg(reinterpret_cast<const uint4*>(gate_w + c * 128 + l16 * 8));
  }
  if ((tid & 31) == 0) {
#pragma unroll 1
    for (int b = tid >> 5; b < NBAR; b += 12) {
      mbar_init(bars + 8 * b, b < B_SEND ? 1 : b < B_EMPTYB ? 4 : b < B_EMPTYA ? 8 : 16);
      if (b >= B_DSR && b < B_SEND) mbar_expect_tx(bars + 8 * b, 10240);
    }
    asm volatile("fence.mbarrier_init.release.cluster;" ::: "memory");
  }
  if (tid == 352) { prefetch_tmap(&maps.x); prefetch_tmap(&maps.qm); prefetch_tmap(&maps.w1m); prefetch_tmap(&maps.qr); prefetch_tmap(&maps.w1r); }
  asm volatile("barrier.cluster.arrive.relaxed.aligned;" ::: "memory");

  if (tid >= 256) {
    asm volatile("setmaxnreg.dec.sync.aligned.u32 40;");
    asm volatile("barrier.cluster.wait.aligned;" ::: "memory");
    auto get_epoch = [&]() { return *reinterpret_cast<volatile unsigned*>(g_flags + FL_DONE * 32) / NCTA; };
    const int lane = tid & 31, pw = (tid >> 5) & 3;
    auto send_stream = [&](int w, unsigned ep1) {
#pragma unroll 1
      for (int c = 0; c < 3; c++) {
        const int d = (j + 2 * c + 2) & 7;
        mbar_wait(bars + 8 * (B_SEND + 2 * c + w), 0);
        if (w) TR4(c * 16 + 7);
        bulk_store(g_part + (size_t)((i * 8 + d) * 3 + c) * 1280 + w * 640, sb + OFF_SEND + w * 10240, 10240);
        bulk_commit();
        bulk_wait<0>();
        mbar_arrive(bars + 8 * (B_SDONE + 2 * c + w));
        if (w) TR4(c * 16 + 9);
        asm volatile("st.release.gpu.global.u32 [%0], %1;"
                     ::"l"(g_flags + (FL_PART + i * 8 + d) * 32 + 2 * c + w), "r"(ep1) : "memory");
        if (w) TR4(c * 16 + 10);
      }
    };
    if (pw == 0) {
      if (lane == 0) {
        Ring r{0, 1};
        unsigned ep1 = 0;
#pragma unroll 1
        for (int k = 0; k < 30; k++) {
          if (k == 4) ep1 = get_epoch() + 1;
          if (k == 10 || k == 20) {
            const unsigned tgt = ep1 * 8u;
            const unsigned* f0 = g_flags + (k == 10 ? FL_H + ((i - 1) & 15) : FL_X1 + i) * 32;
            const unsigned* f1 = g_flags + (k == 10 ? FL_H + i : FL_X1 + i) * 32;
            const unsigned* f2 = g_flags + (k == 10 ? FL_H + ((i + 1) & 15) : FL_X1 + i) * 32;
            uint32_t n = 0;
            while (++n < (WAIT_LIMIT >> 4)) {
              unsigned v0, v1, v2;
              asm volatile("ld.relaxed.gpu.global.u32 %0, [%3];\nld.relaxed.gpu.global.u32 %1, [%4];\nld.acquire.gpu.global.u32 %2, [%5];"
                           : "=r"(v0), "=r"(v1), "=r"(v2) : "l"(f0), "l"(f1), "l"(f2) : "memory");
              if ((int)((v0 - tgt) | (v1 - tgt) | (v2 - tgt)) >= 0) break;
            }
            TSTAMPX(k == 10 ? 29 : 30);
          }
          mbar_wait(emptyA + 8 * r.idx, r.phase);
          const uint32_t bar = fullA + 8 * r.idx, slot = sb + OFF_A + r.idx * SLOT_A;
          TRACE(k);
          mbar_expect_tx(bar, SLOT_A);
          tma2d_mc(slot + rank * 8192, k < 10 ? &maps.x : k < 20 ? &maps.hs : &maps.x1, bar, 64 * (k % 10), 128 * i + 64 * rank);
          r.next<NA>();
        }
        send_stream(1, ep1);
      }
    } else if (pw == 1) {
      if (lane == 0) {
        Ring r{0, 1};
#pragma unroll 1
        for (int k = 0; k < 18; k++) {
          mbar_wait(emptyB + 8 * r.idx, r.phase);
          const uint32_t bar = fullB + 8 * r.idx, slot = sb + OFF_B + r.idx * SLOT_B;
          if (k < 10) {
            mbar_expect_tx(bar, 40960);
            tma4d(slot + 8192, &maps.qm, bar, 0, 64 * k, 0, j);
            tma3d(slot, &maps.w1m, bar, 0, 64 * k, j);
            tma4d(slot + 32768 + 2048, &maps.qr, bar, 64, 64 * k, 0, j);
            tma3d(slot + 32768, &maps.w1r, bar, 64, 64 * k, j);
          } else if (k < 13) {
            if (k == 12) mbar_wait(fullA + 8 * 2, 0);
            mbar_expect_tx(bar, k < 12 ? 40960 : 20480);
#pragma unroll 1
            for (int u = 0; u < (k < 12 ? 4 : 2); u++) tma3d(slot + u * 10240, &maps.w2, bar, 0, 256 * (k - 10) + 64 * u, 5 * j);
          } else {
            mbar_expect_tx(bar, 49152);
            tma3d(slot, &maps.w3, bar, 0, 128 * (k - 13), 3 * j);
            tma3d(slot + 24576, &maps.w3, bar, 0, 128 * (k - 13) + 64, 3 * j);
          }
          r.next<NB>();
        }
        Ring r4{0, 1};
#pragma unroll 1
        for (int n = 0; n < 16; n++) {
          if (n == 0 || n == 1 || n == 3) { mbar_wait(emptyB + 8 * r.idx, r.phase); r.next<NB>(); }
          mbar_wait(bars + 8 * (B_EMPTY4 + r4.idx), r4.phase);
          const uint32_t bar = bars + 8 * (B_FULL4 + r4.idx), slot = sb + OFF_B + r4.idx * UNIT4;
          const int u = n & 3, m = ((j >> 1) + 1 + (n >> 2)) & 3;
          mbar_expect_tx(bar, u == 3 ? 25600 : 20480);
          tma3d(slot, u == 3 ? &maps.wo : &maps.w4, bar, 0, u == 3 ? 80 * j : 192 * j + 64 * u, 5 * m);
          r4.next<NU4>();
        }
      }
    } else {
      const unsigned epoch = get_epoch();
      float* accg = g_acc[epoch & 1];
      if (pw == 2) {
        {
          float* nxt = g_acc[(epoch + 1) & 1];
          constexpr int PER = ACC_FLOATS / NCTA;
#pragma unroll 1
          for (int e = lane; e < PER; e += 32) nxt[blockIdx.x * PER + e] = 0.f;
        }
        if (lane == 0) {
          flag_wait(FL_CS + j, (epoch + 1) * 16u);
          flag_wait(FL_ST + i, (epoch + 1) * 8u);
          fence_async_all();
          mbar_expect_tx(bars + 8 * B_CS, 320 + 2048);
          bulk_load(sb + OFF_CS, accg + 8 * KV_J + 80 * j, 320, bars + 8 * B_CS);
          bulk_load(sb + OFF_XST, g_xstat + 128 * i, 2048, bars + 8 * B_CS);
          TSTAMPX(21);
          l2_prefetch(w2 + (size_t)blockIdx.x * (D_ * D_ / NCTA), D_ * D_ * 2 / NCTA);
          l2_prefetch(w4 + (size_t)blockIdx.x * (F_ * D_ / NCTA), F_ * D_ * 2 / NCTA);
          l2_prefetch(wo + (size_t)blockIdx.x * (D_ * D_ / NCTA), D_ * D_ * 2 / NCTA);
        }
        __syncwarp();
#pragma unroll 1
        for (int m = 0; m < 6; m++) {
          const int col = 192 * j + 32 * m + 8 * (lane & 3);
          const __nv_bfloat16* p = w3 + (size_t)(40 * i + (lane >> 2) * 5) * F_ + col;
          float a[8];
#pragma unroll
          for (int e = 0; e < 8; e++) a[e] = 0.f;
#pragma unroll
          for (int it = 0; it < 5; it++) {
            const uint4 v = __ldg(reinterpret_cast<const uint4*>(p + (size_t)it * F_));
            a[0] += bf_lo(v.x); a[1] += bf_hi(v.x); a[2] += bf_lo(v.y); a[3] += bf_hi(v.y);
            a[4] += bf_lo(v.z); a[5] += bf_hi(v.z); a[6] += bf_lo(v.w); a[7] += bf_hi(v.w);
          }
#pragma unroll
          for (int e = 0; e < 4; e++) {
            const float snd = (lane & 4) ? a[e] : a[e + 4], keep = (lane & 4) ? a[e + 4] : a[e];
            a[e] = keep + __shfl_xor_sync(0xffffffffu, snd, 4);
            a[e] += __shfl_xor_sync(0xffffffffu, a[e], 8);
            a[e] += __shfl_xor_sync(0xffffffffu, a[e], 16);
          }
          if (lane < 8) red_add4(accg + 8 * KV_J + D_ + col + (lane >> 2) * 4, a[0], a[1], a[2], a[3]);
        }
        __syncwarp();
        if (lane == 0) {
          flag_add(FL_CS3 + j);
          flag_wait(FL_KV + j, (epoch + 1) * 16u);
          fence_async_all();
          mbar_expect_tx(bars + 8 * B_KV, KV_J * 4);
          bulk_load(sb + OFF_MISC, accg + j * KV_J, KV_J * 4, bars + 8 * B_KV);
          TSTAMPX(22);
          mbar_wait(bars + 8 * B_MFREE, 0);
          flag_wait(FL_X1 + i, (epoch + 1) * 8u);
          flag_wait(FL_CS3 + j, (epoch + 1) * 16u);
          fence_async_all();
          mbar_expect_tx(bars + 8 * B_ST1, 8192 + 768);
          bulk_load(sb + OFF_CS + 320, accg + 8 * KV_J + D_ + 192 * j, 768, bars + 8 * B_ST1);
          bulk_load(sb + OFF_MISC, g_st1 + 128 * i * 8, 8192, bars + 8 * B_ST1);
        }
        __syncwarp();
        mbar_wait(bars + 8 * B_PEER, 0);
        const unsigned* fp = g_flags + (FL_PART + i * 8 + j) * 32 + lane;
        bool seen = lane >= 6;
        uint32_t n = 0;
        while (!__all_sync(0xffffffffu, seen) && ++n < (WAIT_LIMIT >> 4)) {
          if (!seen && ld_acquire(fp) == epoch + 1 && (lane < 2 || (lane < 4 ? mbar_test(bars + 8 * (B_SEND + 2), 0) && mbar_test(bars + 8 * (B_SEND + 3), 0) && mbar_test(bars + 8 * (B_EMPTY4 + 1), 0) : mbar_test(bars + 8 * (B_SDONE + lane), 0)))) {
            seen = true;
            if (lane & 1) TR4((lane >> 1) * 16 + 11);
            mbar_expect_tx(bars + 8 * (B_RDY + lane), 10240);
            bulk_load(sb + (lane < 2 ? OFF_G0 : lane < 4 ? OFF_G1 : OFF_SEND) + (lane & 1) * 10240, g_part + (size_t)(i * 8 + j) * 3840 + lane * 640, 10240,
                      bars + 8 * (B_RDY + lane));
          }
        }
      } else {
        mbar_wait(bars + 8 * B_SIGP, 0);
        if (lane < 20) {
          float a0 = 0.f, a1 = 0.f, a2 = 0.f, a3 = 0.f;
#pragma unroll 4
          for (int r = 0; r < 20; r++) {
            const uint4 v = lds128(sb + OFF_B + SPARE + r * 320 + lane * 16);
            a0 += __uint_as_float(v.x); a1 += __uint_as_float(v.y); a2 += __uint_as_float(v.z); a3 += __uint_as_float(v.w);
          }
          red_add4(accg + 8 * KV_J + 80 * j + 4 * lane, a0, a1, a2, a3);
        }
        __syncwarp();
      }
      if (pw == 3 && lane == 0) {
        flag_add(FL_CS + j); flag_add_relaxed(FL_ST + i);
        TSTAMPX(20);
        mbar_expect_tx(bars + 8 * B_XR, 20480);
#pragma unroll 1
        for (int u = 0; u < 8; u++)
          tma2d(sb + OFF_B + (u / 3) * SLOT_B + SPARE + (u % 3) * 2560, &maps.xr, bars + 8 * B_XR, 80 * j, 128 * i + 16 * u);
        const int shift = (j < 2) ? 1 : (j < 4) ? -1 : (j < 6) ? 2 : -2;
        if ((shift > 0 && i == 0) || (shift < 0 && i == 15)) {
          const int nz = shift > 0 ? shift : -shift, zr = shift > 0 ? 0 : S_ - nz;
#pragma unroll 1
          for (int e = 0; e < nz * 10; e++)
            reinterpret_cast<uint4*>(g_Hs + (size_t)(2 + zr + e / 10) * D_ + 80 * j)[e % 10] = make_uint4(0, 0, 0, 0);
          fence_async_all();
        }
        prefetch_tmap(&maps.st_h); prefetch_tmap(&maps.st_x1); prefetch_tmap(&maps.hs); prefetch_tmap(&maps.x1); prefetch_tmap(&maps.xr);
        prefetch_tmap(&maps.w2); prefetch_tmap(&maps.w3); prefetch_tmap(&maps.w4); prefetch_tmap(&maps.wo); prefetch_tmap(&maps.st_out);
        mbar_wait(bars + 8 * B_SIGH, 0);
        TSTAMPX(23);
        tma2d_store(&maps.st_h, sb + OFF_STG, 80 * j, 128 * i + 2 + shift);
        tma2d_store(&maps.st_h, sb + OFF_STG + 10240, 80 * j, 128 * i + 66 + shift);
        bulk_commit(); bulk_wait<0>();
        flag_add(FL_H + i);
        TSTAMPX(24);
        mbar_wait(bars + 8 * B_SIGKV, 0);
        TSTAMPX(25);
        flag_add(FL_KV + j);
        TSTAMPX(26);
        mbar_wait(bars + 8 * B_SIGX1, 0);
        TSTAMPX(27);
        tma2d_store(&maps.st_x1, sb + OFF_STG, 80 * j, 128 * i);
        tma2d_store(&maps.st_x1, sb + OFF_STG + 10240, 80 * j, 128 * i + 64);
        bulk_commit(); bulk_wait<0>();
        flag_add(FL_X1 + i);
        TSTAMPX(28);
        send_stream(0, epoch + 1);
      }
    }
    __syncwarp();
    asm volatile("barrier.cluster.arrive;\nbarrier.cluster.wait;" ::: "memory");
  } else {
    asm volatile("setmaxnreg.inc.sync.aligned.u32 232;");
    const int wg = tid >> 7, warp = tid >> 5, lane = tid & 31, t = lane & 3;
    const int rloc = warp * 16 + (lane >> 2);
    const float* s_cs = reinterpret_cast<const float*>(sgen + OFF_CS);
    auto signal = [&](int b) {
      __syncwarp();
      if (lane == 0) mbar_arrive(bars + 8 * b);
    };
    auto releaseB = [&](uint32_t bar) {
      __syncwarp();
      if (lane == 0) mbar_arrive(bar);
    };
    auto release = [&](uint32_t bar) {
      __syncwarp();
      if (lane < 2) mbar_arrive_cta(bar, lane);
    };
    uint32_t par;
    const uint32_t stg_lane = (warp * 16 + ((lane >> 3) & 1) * 8 + (lane & 7)) * 160 + (lane >> 4) * 16;

    {
      const unsigned done_cnt = *reinterpret_cast<volatile unsigned*>(g_flags + FL_DONE * 32);
#pragma unroll 1
      for (int e = tid; e < 800; e += 256) sts128(sb + OFF_MISC + e * 16, make_uint4(0, 0, 0, 0));
      bar_sync(1, 256);
      float f[40];
      float s = 0.f, gs = 0.f;
#pragma unroll
      for (int c = 0; c < 5; c++) {
        const uint32_t vv[4] = {pv[c].x, pv[c].y, pv[c].z, pv[c].w}, ww[4] = {pw_[c].x, pw_[c].y, pw_[c].z, pw_[c].w};
#pragma unroll
        for (int e = 0; e < 4; e++) {
          f[8 * c + 2 * e] = bf_lo(vv[e]); f[8 * c + 2 * e + 1] = bf_hi(vv[e]);
          s += f[8 * c + 2 * e] + f[8 * c + 2 * e + 1];
          gs = fmaf(f[8 * c + 2 * e], bf_lo(ww[e]), gs); gs = fmaf(f[8 * c + 2 * e + 1], bf_hi(ww[e]), gs);
        }
      }
#pragma unroll
      for (int o = 1; o < 16; o <<= 1) { s += __shfl_xor_sync(0xffffffffu, s, o); gs += __shfl_xor_sync(0xffffffffu, gs, o); }
      const float mean = s * (1.f / D_);
      float q = 0.f;
#pragma unroll
      for (int e = 0; e < 40; e++) { const float d = f[e] - mean; q = fmaf(d, d, q); }
#pragma unroll
      for (int o = 1; o < 16; o <<= 1) q += __shfl_xor_sync(0xffffffffu, q, o);
      const float rstd = rsqrtf(q * (1.f / D_) + 1e-5f);
      par = (done_cnt / NCTA) & 1;
      if (tid < 200) {
        const uint32_t cd = sb + OFF_B + SPARE + tid * 32;
        sts128(cd, make_uint4(__float_as_uint(bf_lo(pc[0].x) + bf_lo(pc[1].x)), __float_as_uint(bf_hi(pc[0].x) + bf_hi(pc[1].x)),
                              __float_as_uint(bf_lo(pc[0].y) + bf_lo(pc[1].y)), __float_as_uint(bf_hi(pc[0].y) + bf_hi(pc[1].y))));
        sts128(cd + 16, make_uint4(__float_as_uint(bf_lo(pc[0].z) + bf_lo(pc[1].z)), __float_as_uint(bf_hi(pc[0].z) + bf_hi(pc[1].z)),
                                   __float_as_uint(bf_lo(pc[0].w) + bf_lo(pc[1].w)), __float_as_uint(bf_hi(pc[0].w) + bf_hi(pc[1].w))));
        const uint32_t ww[4] = {pre.x, pre.y, pre.z, pre.w};
        const int h = tid / 50;
#pragma unroll
        for (int e = 0; e < 8; e++) {
          const int idx = tid * 8 + e, k = idx / 20, ff = idx - 20 * k;
          const int n = 40 * (h >> 1) + 8 * (ff >> 2) + 2 * (ff & 3) + (h & 1);
          const int off = (k >> 4) * 2560 + n * 32 + ((((k >> 3) ^ (n >> 2)) & 1) << 4) + (k & 7) * 2;
          *reinterpret_cast<unsigned short*>(sgen + OFF_MISC + off) = (unsigned short)(ww[e >> 1] >> ((e & 1) * 16));
        }
      }
      fence_async_smem();
      asm volatile("barrier.cluster.wait.aligned;" ::: "memory");
      if ((tid & 15) == 0) g_xstat[128 * i + 16 * j + (tid >> 4)] = make_float4(rstd, -mean * rstd, rcp(1.f + __expf(-gs)), 0.f);
      signal(B_SIGP);
    }
    TSTAMP(1);

    Ring ra{0, 0}, rb{0, 0};
    uint32_t qp[2][10], P[2][10];
    float st_g[2];
    {
      float accM[128], accR[32];
      zero_regs(accM); zero_regs(accR);
      uint32_t pa = 0, pb = 0;
#pragma unroll 1
      for (int k = 0; k < 10; k++) {
        mbar_wait(fullA + 8 * ra.idx, ra.phase);
        if (tid == 0) TRACE(32 + k);
        mbar_wait(fullB + 8 * rb.idx, rb.phase);
        if (tid == 0) TRACE(64 + k);
        if (k == 0) TSTAMP(2);
        const uint32_t a0 = sb16 + ((OFF_A + ra.idx * SLOT_A + wg * 8192) >> 4), b0 = sb16 + ((OFF_B + rb.idx * SLOT_B) >> 4);
        wg_fence();
#pragma unroll
        for (int kk = 0; kk < 4; kk++) {
          const uint64_t da = make_desc(a0, kk * 32, 16, 1024, 1);
          mma_ss256(accM, da, make_desc(b0, kk * 2048, 8192, 1024, 1));
          mma_ss64(accR, da, make_desc(b0, 32768 + kk * 512, 2048, 256, 3));
          if (kk == 0) {
            wg_commit();
            if (k > 0) {
              wg_wait<1>();
              if (k - 1 < 8) release(emptyA + 8 * pa);
              releaseB(emptyB + 8 * pb);
            }
          }
        }
        wg_commit();
        pa = ra.idx; pb = rb.idx;
        ra.next<NA>(); rb.next<NB>();
      }
      TSTAMP(18);
      float st_rstd[2], st_mr[2];
      mbar_wait(bars + 8 * B_CS, 0);
#pragma unroll
      for (int r = 0; r < 2; r++) {
        const uint4 st = lds128(sb + OFF_XST + (rloc + 8 * r) * 16);
        st_rstd[r] = __uint_as_float(st.x); st_mr[r] = __uint_as_float(st.y); st_g[r] = __uint_as_float(st.z);
      }
      TSTAMP(19);
      wg_wait<0>();
      fence_regs(accM); fence_regs(accR);
      TSTAMP(3);
#define ACC(P_, G, I_) ((G) < 8 ? accM[(P_) * 32 + ((G) & 7) * 4 + (I_)] : accR[(P_) * 8 + ((G) & 1) * 4 + (I_)])
      {
        const int mat = lane >> 3;
        const int tok = warp * 16 + (mat & 1) * 8 + (lane & 7);
        const uint32_t ones = (t == 0) ? 0x00003f80u : 0u;
        __syncwarp();
#pragma unroll
        for (int p = 0; p < 2; p++) {
          const uint32_t rowa = sb + OFF_A + p * SLOT_A + tok * 128;
#pragma unroll
          for (int gg = 0; gg < 3; gg++) {
            const int g0 = 5 * p + 2 * gg;
            uint32_t r0 = pack_bf16(ACC(3, g0, 0), ACC(3, g0, 1)), r1 = pack_bf16(ACC(3, g0, 2), ACC(3, g0, 3));
            uint32_t r2 = ones, r3 = ones;
            if (gg < 2) { r2 = pack_bf16(ACC(3, g0 + 1, 0), ACC(3, g0 + 1, 1)); r3 = pack_bf16(ACC(3, g0 + 1, 2), ACC(3, g0 + 1, 3)); }
            stsm4(rowa + (((2 * gg + (mat >> 1)) ^ (tok & 7)) << 4), r0, r1, r2, r3);
          }
        }
      }
      uint32_t kf[5][4], qf[5][4];
#pragma unroll
      for (int s = 0; s < 5; s++) {
        kf[s][0] = pack_bf16(ACC(2, 2 * s, 0), ACC(2, 2 * s, 1)); kf[s][1] = pack_bf16(ACC(2, 2 * s, 2), ACC(2, 2 * s, 3));
        kf[s][2] = pack_bf16(ACC(2, 2 * s + 1, 0), ACC(2, 2 * s + 1, 1)); kf[s][3] = pack_bf16(ACC(2, 2 * s + 1, 2), ACC(2, 2 * s + 1, 3));
        qf[s][0] = pack_bf16(ACC(1, 2 * s, 0), ACC(1, 2 * s, 1)); qf[s][1] = pack_bf16(ACC(1, 2 * s, 2), ACC(1, 2 * s, 3));
        qf[s][2] = pack_bf16(ACC(1, 2 * s + 1, 0), ACC(1, 2 * s + 1, 1)); qf[s][3] = pack_bf16(ACC(1, 2 * s + 1, 2), ACC(1, 2 * s + 1, 3));
      }
      bar_sync(1, 256);
      float pk[40], pq[40];
      wg_fence();
#pragma unroll
      for (int s = 0; s < 5; s++) {
        if (s == 0) mma_rs80_k_z(pk, kf[s], make_desc(sb16, OFF_MISC, 16, 256, 3));
        else mma_rs80_k(pk, kf[s], make_desc(sb16, OFF_MISC + s * 2560, 16, 256, 3));
      }
#pragma unroll
      for (int s = 0; s < 5; s++) {
        if (s == 0) mma_rs80_k_z(pq, qf[s], make_desc(sb16, OFF_MISC, 16, 256, 3));
        else mma_rs80_k(pq, qf[s], make_desc(sb16, OFF_MISC + s * 2560, 16, 256, 3));
      }
      wg_commit();

      {
        uint32_t hv[10][2];
#pragma unroll
        for (int g = 0; g < 10; g++) {
          const float2 cs = *reinterpret_cast<const float2*>(s_cs + 8 * g + 2 * t);
          const float v0 = gelu_s(fmaf(ACC(0, g, 0), st_rstd[0], st_mr[0] * cs.x), 0.5f), v1 = gelu_s(fmaf(ACC(0, g, 1), st_rstd[0], st_mr[0] * cs.y), 0.5f);
          const float v2 = gelu_s(fmaf(ACC(0, g, 2), st_rstd[1], st_mr[1] * cs.x), 0.5f), v3 = gelu_s(fmaf(ACC(0, g, 3), st_rstd[1], st_mr[1] * cs.y), 0.5f);
          hv[g][0] = pack_bf16(v0, v1); hv[g][1] = pack_bf16(v2, v3);
        }
#pragma unroll
        for (int s = 0; s < 5; s++) stsm4(sb + OFF_STG + stg_lane + s * 32, hv[2 * s][0], hv[2 * s][1], hv[2 * s + 1][0], hv[2 * s + 1][1]);
        fence_async_smem();
        signal(B_SIGH);
      }
#undef ACC
      TSTAMP(4);
      wg_wait<0>();
      fence_regs(pk); fence_regs(pq);
#pragma unroll
      for (int G = 0; G < 10; G++) {
        P[0][G] = pack_bf16(pk[4 * G], pk[4 * G + 1]); P[1][G] = pack_bf16(pk[4 * G + 2], pk[4 * G + 3]);
        qp[0][G] = pack_bf16(pq[4 * G], pq[4 * G + 1]); qp[1][G] = pack_bf16(pq[4 * G + 2], pq[4 * G + 3]);
      }
    }

    uint32_t fr[10][4];
    {
      feature_map(P, fr);
      const int mat = lane >> 3;
      const int tok = warp * 16 + (mat & 1) * 8 + (lane & 7);
      const uint32_t base = sb + OFF_B + tok * 32 + (((mat >> 1) ^ ((tok >> 2) & 1)) << 4);
#pragma unroll
      for (int G = 0; G < 10; G++) stsm4(base + G * 4096, fr[G][0], fr[G][1], fr[G][2], fr[G][3]);
      fence_async_smem();
      bar_sync(1, 256);
      float kv[40];
      const uint32_t a0 = sb16 + ((OFF_A + wg * SLOT_A) >> 4), b0 = sb16 + ((OFF_B + wg * 20480) >> 4);
      wg_fence();
#pragma unroll
      for (int ks = 0; ks < 8; ks++) {
        if (ks == 0) mma_ss80_tt_z(kv, make_desc(a0, 0, 16, 1024, 1), make_desc(b0, 0, 4096, 256, 3));
        else mma_ss80_tt(kv, make_desc(a0, ks * 2048, 16, 1024, 1), make_desc(b0, ks * 512, 4096, 256, 3));
      }
      wg_commit();
      wg_wait<0>();
      fence_regs(kv);
      release(emptyA); release(emptyA + 8); releaseB(emptyB);
      float* dst = g_acc[par] + j * KV_J + wg * KV_PAIR;
      const int m0 = (warp & 3) * 16 + (lane >> 2);
#pragma unroll
      for (int r = 0; r < 2; r++) {
        const int m = m0 + 8 * r;
        const bool hi = m >= 20;
        float v[10];
#pragma unroll
        for (int G = 0; G < 10; G++) v[G] = hi ? kv[4 * G + 2 * r + 1] : kv[4 * G + 2 * r];
        float* p = dst + (m < 40 ? m * 48 + t * 12 : 1920 + t * 24 + 12);
        if (m <= 40) { red_add4(p, v[0], v[1], v[2], v[3]); red_add4(p + 4, v[4], v[5], v[6], v[7]); red_add2(p + 8, v[8], v[9]); }
      }
      if (m0 == 32) {
        float* p = dst + 1920 + t * 24;
        red_add4(p, kv[2], kv[6], kv[10], kv[14]); red_add4(p + 4, kv[18], kv[22], kv[26], kv[30]); red_add2(p + 8, kv[34], kv[38]);
      }
      signal(B_SIGKV);
    }
    TSTAMP(5);

    uint32_t xv[2][10];
    {
      {
        mbar_wait(bars + 8 * B_XR, 0);
        const uint32_t xa = sb + OFF_B + (warp / 3) * SLOT_B + SPARE + (warp % 3) * 2560 + (lane >> 2) * 160 + t * 4;
#pragma unroll
        for (int g = 0; g < 10; g++) { xv[0][g] = lds32(xa + g * 16); xv[1][g] = lds32(xa + 1280 + g * 16); }
      }
      float acc[40];
      zero_regs(acc);
      uint32_t pa = 0, pb = 0;
#pragma unroll 1
      for (int k = 0; k < 10; k++) {
        mbar_wait(fullA + 8 * ra.idx, ra.phase);
        if (tid == 0) TRACE(42 + k);
        if ((k & 3) == 0) mbar_wait(fullB + 8 * rb.idx, rb.phase);
        if (tid == 0) TRACE(74 + k);
        if (k == 0) TSTAMP(6);
        const uint32_t a0 = sb16 + ((OFF_A + ra.idx * SLOT_A + wg * 8192) >> 4);
        const uint32_t b0 = sb16 + ((OFF_B + rb.idx * SLOT_B + (k & 3) * 10240) >> 4);
        wg_fence();
#pragma unroll
        for (int kk = 0; kk < 4; kk++) {
          mma_ss80(acc, make_desc(a0, kk * 32, 16, 1024, 1), make_desc(b0, kk * 512, 2048, 256, 3));
          if (kk == 1) {
            wg_commit();
            if (k > 0) {
              wg_wait<1>();
              release(emptyA + 8 * pa);
              if ((k & 3) == 0) releaseB(emptyB + 8 * pb);
            }
          }
        }
        wg_commit();
        pa = ra.idx; pb = rb.idx;
        ra.next<NA>();
        if ((k & 3) == 3 || k == 9) rb.next<NB>();
      }
      wg_wait<0>();
      fence_regs(acc);
      release(emptyA + 8 * pa); releaseB(emptyB + 8 * pb);
      TSTAMP(7);
#pragma unroll
      for (int r = 0; r < 2; r++) {
#pragma unroll
        for (int g = 0; g < 10; g++)
          xv[r][g] = pack_bf16(bf_lo(xv[r][g]) + acc[4 * g + 2 * r], bf_hi(xv[r][g]) + acc[4 * g + 2 * r + 1]);
      }
      bar_sync(1, 256);
#pragma unroll
      for (int s = 0; s < 5; s++) stsm4(sb + OFF_STG + stg_lane + s * 32, xv[0][2 * s], xv[1][2 * s], xv[0][2 * s + 1], xv[1][2 * s + 1]);
#pragma unroll
      for (int r = 0; r < 2; r++) {
        float s = 0.f;
#pragma unroll
        for (int g = 0; g < 10; g++) {
          acc[4 * g + 2 * r] = bf_lo(xv[r][g]); acc[4 * g + 2 * r + 1] = bf_hi(xv[r][g]);
          s += acc[4 * g + 2 * r] + acc[4 * g + 2 * r + 1];
        }
        s += __shfl_xor_sync(0xffffffffu, s, 1); s += __shfl_xor_sync(0xffffffffu, s, 2);
        const float mu = s * (1.f / 80.f);
        float q = 0.f;
#pragma unroll
        for (int g = 0; g < 10; g++) {
          const float d0 = acc[4 * g + 2 * r] - mu, d1 = acc[4 * g + 2 * r + 1] - mu;
          q = fmaf(d0, d0, q); q = fmaf(d1, d1, q);
        }
        q += __shfl_xor_sync(0xffffffffu, q, 1); q += __shfl_xor_sync(0xffffffffu, q, 2);
        if (t == 0) g_st1[(128 * i + rloc + 8 * r) * 8 + j] = make_float2(mu, q);
      }
      fence_async_smem();
      signal(B_SIGX1);
    }
    TSTAMP(8);

    uint32_t of[5][4];
    {
      feature_map(qp, fr);
      mbar_wait(bars + 8 * B_KV, 0);
      uint4 kvr[2][3];
#pragma unroll
      for (int u = 0; u < 2; u++) {
        const int it = tid + 256 * u, p = it / 192, rem = it - 192 * p, n = rem >> 2, tq = rem & 3;
        const uint32_t sp = sb + OFF_MISC + 4 * (p * KV_PAIR + (n < 40 ? n * 48 + tq * 12 : 1920 + tq * 24 + (n & 1) * 12));
        if (it < 384) { kvr[u][0] = lds128(sp); kvr[u][1] = lds128(sp + 16); kvr[u][2] = lds128(sp + 32); }
      }
      bar_sync(1, 256);
#pragma unroll
      for (int u = 0; u < 2; u++) {
        const int it = tid + 256 * u, p = it / 192, rem = it - 192 * p, n = rem >> 2, tq = rem & 3;
        const int sh = (n < 40 ? (n >= 20) : (n & 1)) * 16;
        const uint32_t v[10] = {kvr[u][0].x, kvr[u][0].y, kvr[u][0].z, kvr[u][0].w, kvr[u][1].x, kvr[u][1].y, kvr[u][1].z, kvr[u][1].w, kvr[u][2].x, kvr[u][2].y};
        uint8_t* dst = sgen + OFF_MISC + p * 7680 + n * 32 + tq * 4;
        const int sw = ((n >> 2) & 1) << 4;
        if (it < 384) {
#pragma unroll
          for (int G = 0; G < 10; G++)
            *reinterpret_cast<uint32_t*>(dst + (G >> 1) * 1536 + (((G & 1) << 4) ^ sw)) = pack_bf16(__uint_as_float(v[G]), 0.f) << sh;
        }
      }
      fence_async_smem();
      bar_sync(1, 256);
      float o0[24], o1[24];
      wg_fence();
#pragma unroll
      for (int g = 0; g < 5; g++) {
        if (g == 0) mma_rs48_k_z(o0, fr[g], make_desc(sb16, OFF_MISC, 16, 256, 3));
        else mma_rs48_k(o0, fr[g], make_desc(sb16, OFF_MISC + g * 1536, 16, 256, 3));
      }
#pragma unroll
      for (int g = 0; g < 5; g++) {
        if (g == 0) mma_rs48_k_z(o1, fr[5], make_desc(sb16, OFF_MISC + 7680, 16, 256, 3));
        else mma_rs48_k(o1, fr[5 + g], make_desc(sb16, OFF_MISC + 7680 + g * 1536, 16, 256, 3));
      }
      wg_commit();
      wg_wait<0>();
      fence_regs(o0); fence_regs(o1);
      signal(B_MFREE);
#pragma unroll
      for (int r = 0; r < 2; r++) {
        const float a0 = __fdividef(st_g[r], o0[20 + 2 * r] + 1e-6f), a1 = __fdividef(st_g[r], o0[21 + 2 * r] + 1e-6f);
        const float b0 = __fdividef(st_g[r], o1[20 + 2 * r] + 1e-6f), b1 = __fdividef(st_g[r], o1[21 + 2 * r] + 1e-6f);
        const float am = t < 2 ? a0 : a1, bm = t < 2 ? b0 : b1;
#pragma unroll
        for (int g = 0; g < 5; g++) {
          const float sa = g < 2 ? a0 : (g == 2 ? am : a1), sb2 = g < 2 ? b0 : (g == 2 ? bm : b1);
          of[g >> 1][(g & 1) * 2 + r] = pack_bf16(o0[4 * g + 2 * r] * sa, o0[4 * g + 2 * r + 1] * sa);
          of[(5 + g) >> 1][((5 + g) & 1) * 2 + r] = pack_bf16(o1[4 * g + 2 * r] * sb2, o1[4 * g + 2 * r + 1] * sb2);
        }
      }
    }
    TSTAMP(9);

    uint32_t hf[12][4];
    {
      float acc[96];
      zero_regs(acc);
      uint32_t pa = 0, pb = 0;
#pragma unroll 1
      for (int k = 0; k < 10; k++) {
        mbar_wait(fullA + 8 * ra.idx, ra.phase);
        if (tid == 0) TRACE(52 + k);
        if ((k & 1) == 0) mbar_wait(fullB + 8 * rb.idx, rb.phase);
        if (tid == 0) TRACE(84 + k);
        if (k == 0) TSTAMP(10);
        const uint32_t a0 = sb16 + ((OFF_A + ra.idx * SLOT_A + wg * 8192) >> 4);
        const uint32_t b0 = sb16 + ((OFF_B + rb.idx * SLOT_B + (k & 1) * 24576) >> 4);
        wg_fence();
#pragma unroll
        for (int kk = 0; kk < 4; kk++) {
          mma_ss192(acc, make_desc(a0, kk * 32, 16, 1024, 1), make_desc(b0, kk * 2048, 8192, 1024, 1));
          if (kk == 0) {
            wg_commit();
            if (k > 0) {
              wg_wait<1>();
              release(emptyA + 8 * pa);
              if ((k & 1) == 0) releaseB(emptyB + 8 * pb);
            }
          }
        }
        wg_commit();
        pa = ra.idx; pb = rb.idx;
        ra.next<NA>();
        if (k & 1) rb.next<NB>();
      }
      float rs[2], mm[2];
      mbar_wait(bars + 8 * B_ST1, 0);
#pragma unroll
      for (int r = 0; r < 2; r++) {
        const uint4 su = lds128(sb + OFF_MISC + (rloc + 8 * r) * 64 + t * 16);
        const float m0 = __uint_as_float(su.x), m1 = __uint_as_float(su.z);
        float mu = m0 + m1;
        mu += __shfl_xor_sync(0xffffffffu, mu, 1); mu += __shfl_xor_sync(0xffffffffu, mu, 2);
        mu *= 0.125f;
        const float d0 = m0 - mu, d1 = m1 - mu;
        float q = __uint_as_float(su.y) + __uint_as_float(su.w) + 80.f * (d0 * d0 + d1 * d1);
        q += __shfl_xor_sync(0xffffffffu, q, 1); q += __shfl_xor_sync(0xffffffffu, q, 2);
        rs[r] = rsqrtf(q * (1.f / D_) + 1e-5f);
        mm[r] = -mu * rs[r];
      }
      wg_wait<0>();
      fence_regs(acc);
      releaseB(emptyB + 8 * pb);
      release(bars + 8 * B_PEER);
      TSTAMP(11);
      const float hs0 = 0.5f - 0.5f * st_g[0], hs1 = 0.5f - 0.5f * st_g[1];
#pragma unroll
      for (int g = 0; g < 24; g++) {
        const float2 cs = *reinterpret_cast<const float2*>(s_cs + 80 + 8 * g + 2 * t);
        const float v0 = gelu_s(fmaf(acc[4 * g], rs[0], mm[0] * cs.x), hs0), v1 = gelu_s(fmaf(acc[4 * g + 1], rs[0], mm[0] * cs.y), hs0);
        const float v2 = gelu_s(fmaf(acc[4 * g + 2], rs[1], mm[1] * cs.x), hs1), v3 = gelu_s(fmaf(acc[4 * g + 3], rs[1], mm[1] * cs.y), hs1);
        hf[g >> 1][(g & 1) * 2] = pack_bf16(v0, v1);
        hf[g >> 1][(g & 1) * 2 + 1] = pack_bf16(v2, v3);
      }
    }
    TSTAMP(12);

    {
      float acc[80], kp[40];
      const int wt = tid & 127;
      const uint32_t peer = map_peer(sb, rank ^ 1);
      Ring r4{0, 0};
      auto add16 = [&](uint32_t src) {
#pragma unroll
        for (int q = 0; q < 5; q++) {
          const uint4 v = lds128(src + q * 2048);
          float* d = &kp[8 * q];
          d[0] += bf_lo(v.x); d[1] += bf_hi(v.x); d[2] += bf_lo(v.y); d[3] += bf_hi(v.y);
          d[4] += bf_lo(v.z); d[5] += bf_hi(v.z); d[6] += bf_lo(v.w); d[7] += bf_hi(v.w);
        }
      };
      zero_regs(kp);
#pragma unroll 1
      for (int c = 0; c < 4; c++) {
        uint32_t prev = 0;
#pragma unroll
        for (int u = 0; u < 4; u++) {
          mbar_wait(bars + 8 * (B_FULL4 + r4.idx), r4.phase);
          const uint32_t b0 = sb16 + ((OFF_B + r4.idx * UNIT4) >> 4);
          if (u == 0 && tid == 128) TR4(c * 16 + 0);
          wg_fence();
#pragma unroll
          for (int s = 0; s < (u < 3 ? 4 : 5); s++) {
            const uint64_t db = make_desc(b0, s * 1024, u < 3 ? 4096 : 5120, 512, 2);
            if (u == 0 && s == 0) mma_rs160_n_z(acc, hf[0], db);
            else if (u < 3) mma_rs160_n(acc, hf[(4 * u + s) % 12], db);
            else mma_rs160_n(acc, of[s], db);
            if (s == 1 && u > 0) { wg_commit(); wg_wait<1>(); releaseB(bars + 8 * (B_EMPTY4 + prev)); }
          }
          wg_commit();
          prev = r4.idx;
          r4.next<NU4>();
          if (u == 0 && c > 0) {
            if (c > 1) mbar_wait(bars + 8 * (B_SDONE + 2 * (c - 2) + wg), 0);
            mbar_wait(bars + 8 * (B_DSR + 2 * (c - 1) + wg), 0);
            if (tid == 128) TR4((c - 1) * 16 + 3);
            add16(sb + OFF_DS + ((c - 1) & 1) * 20480 + wg * 10240 + wt * 16);
            const uint32_t dst = sb + OFF_SEND + wg * 10240 + wt * 16;
#pragma unroll
            for (int q = 0; q < 5; q++) {
              const float* d = &kp[8 * q];
              sts128(dst + q * 2048, make_uint4(pack_bf16(d[0], d[1]), pack_bf16(d[2], d[3]), pack_bf16(d[4], d[5]), pack_bf16(d[6], d[7])));
            }
            fence_async_smem();
            signal(B_SEND + 2 * (c - 1) + wg);
            if (tid == 128) TR4((c - 1) * 16 + 6);
          }
        }
        if (tid == 128) TR4(c * 16 + 2);
        if (c == 0) mbar_wait(bars + 8 * B_PEER, 0);
        wg_wait<0>();
        fence_regs(acc);
        releaseB(bars + 8 * (B_EMPTY4 + prev));
        if (tid == 128) TR4(c * 16 + 5);
        uint32_t sn[20];
        if (rank) {
#pragma unroll
          for (int e = 0; e < 20; e++) sn[e] = pack_bf16(acc[2 * e], acc[2 * e + 1]);
#pragma unroll
          for (int e = 0; e < 40; e++) kp[e] = acc[40 + e];
        } else {
#pragma unroll
          for (int e = 0; e < 20; e++) sn[e] = pack_bf16(acc[40 + 2 * e], acc[41 + 2 * e]);
#pragma unroll
          for (int e = 0; e < 40; e++) kp[e] = acc[e];
        }
        fence_regs(kp);
        const uint32_t dso = peer + OFF_DS + (c & 1) * 20480 + wg * 10240 + wt * 16, dsb = peer + OFF_BAR + 8 * (B_DSR + 2 * c + wg);
#pragma unroll
        for (int q = 0; q < 5; q++) st_async16(dso + q * 2048, sn[4 * q], sn[4 * q + 1], sn[4 * q + 2], sn[4 * q + 3], dsb);
      }
      TSTAMP(13);
#pragma unroll 1
      for (int c = 0; c < 4; c++) {
        mbar_wait(bars + 8 * ((c == 2 ? B_DSR + 6 : B_RDY + (c == 3 ? 4 : 2 * c)) + wg), 0);
        add16(sb + (c == 0 ? OFF_G0 : c == 1 ? OFF_G1 : c == 2 ? OFF_DS + 20480 : OFF_SEND) + wg * 10240 + wt * 16);
        if (tid == 128) TR4(c * 16 + 12);
      }
      TSTAMP(14);
      const float w0 = 1.f - st_g[0], w1s = 1.f - st_g[1];
      uint32_t ov[10][2];
#pragma unroll
      for (int g = 0; g < 10; g++) {
        const float* d = &kp[4 * g];
        ov[g][0] = pack_bf16(fmaf(w0, bf_lo(xv[0][g]), d[0]), fmaf(w0, bf_hi(xv[0][g]), d[1]));
        ov[g][1] = pack_bf16(fmaf(w1s, bf_lo(xv[1][g]), d[2]), fmaf(w1s, bf_hi(xv[1][g]), d[3]));
      }
      bar_sync(4 + wg, 128);
#pragma unroll
      for (int s = 0; s < 5; s++) stsm4(sb + OFF_DS + stg_lane + s * 32, ov[2 * s][0], ov[2 * s][1], ov[2 * s + 1][0], ov[2 * s + 1][1]);
      fence_async_smem();
      bar_sync(4 + wg, 128);
      if (wt == 0) {
        tma2d_store(&maps.st_out, sb + OFF_DS + wg * 10240, 80 * j, 128 * i + 64 * wg);
        bulk_commit(); bulk_wait_read();
      }
    }
    TSTAMP(15);
    if (tid == 0) asm volatile("red.relaxed.gpu.global.add.u32 [%0], 1;" ::"l"(g_flags + FL_DONE * 32) : "memory");
    asm volatile("barrier.cluster.arrive;\nbarrier.cluster.wait;" ::: "memory");
  }
}

namespace {
typedef CUresult (*EncodeFn)(CUtensorMap*, CUtensorMapDataType, cuuint32_t, void*, const cuuint64_t*, const cuuint64_t*,
                             const cuuint32_t*, const cuuint32_t*, CUtensorMapInterleave, CUtensorMapSwizzle,
                             CUtensorMapL2promotion, CUtensorMapFloatOOBfill);

void encode(EncodeFn fn, CUtensorMap* m, const void* ptr, int rank, const cuuint64_t* dims, const cuuint64_t* strides,
            const cuuint32_t* box, CUtensorMapSwizzle swz) {
  cuuint32_t es[5] = {1, 1, 1, 1, 1};
  fn(m, CU_TENSOR_MAP_DATA_TYPE_BFLOAT16, rank, const_cast<void*>(ptr), dims, strides, box, es, CU_TENSOR_MAP_INTERLEAVE_NONE,
     swz, CU_TENSOR_MAP_L2_PROMOTION_L2_128B, CU_TENSOR_MAP_FLOAT_OOB_FILL_NONE);
}
}

extern "C" void kernel_launch(void* const* d_in, const int* in_sizes, int n_in, void* d_out, int out_size) {
  (void)in_sizes; (void)n_in; (void)out_size;
  const __nv_bfloat16* x = (const __nv_bfloat16*)d_in[0];
  const __nv_bfloat16* wqkv = (const __nv_bfloat16*)d_in[1];
  const __nv_bfloat16* wphi = (const __nv_bfloat16*)d_in[2];
  const __nv_bfloat16* wo = (const __nv_bfloat16*)d_in[3];
  const __nv_bfloat16* w1 = (const __nv_bfloat16*)d_in[5];
  const __nv_bfloat16* w2 = (const __nv_bfloat16*)d_in[6];
  const __nv_bfloat16* w3 = (const __nv_bfloat16*)d_in[7];
  const __nv_bfloat16* w4 = (const __nv_bfloat16*)d_in[8];
  const __nv_bfloat16* gate_w = (const __nv_bfloat16*)d_in[9];

  static EncodeFn enc = nullptr;
  static void *pHs = nullptr, *pX1 = nullptr;
  if (!enc) {
    cudaDriverEntryPointQueryResult qr;
    cudaGetDriverEntryPoint("cuTensorMapEncodeTiled", (void**)&enc, cudaEnableDefault, &qr);
    cudaGetSymbolAddress(&pHs, g_Hs);
    cudaGetSymbolAddress(&pX1, g_X1);
    cudaFuncSetAttribute(fused_kernel, cudaFuncAttributeMaxDynamicSharedMemorySize, SMEM_BYTES);
  }
  Maps m;
  {
    cuuint64_t dims[2] = {D_, S_}, str[1] = {D_ * 2};
    cuuint32_t boxh[2] = {64, 64};
    encode(enc, &m.x, x, 2, dims, str, boxh, CU_TENSOR_MAP_SWIZZLE_128B);
    encode(enc, &m.hs, (const char*)pHs + 2 * D_ * 2, 2, dims, str, boxh, CU_TENSOR_MAP_SWIZZLE_128B);
    encode(enc, &m.x1, pX1, 2, dims, str, boxh, CU_TENSOR_MAP_SWIZZLE_128B);
    cuuint32_t boxs[2] = {80, 64};
    cuuint64_t dimsp[2] = {D_, S_ + 4};
    encode(enc, &m.st_h, pHs, 2, dimsp, str, boxs, CU_TENSOR_MAP_SWIZZLE_NONE);
    encode(enc, &m.st_x1, pX1, 2, dims, str, boxs, CU_TENSOR_MAP_SWIZZLE_NONE);
    encode(enc, &m.st_out, d_out, 2, dims, str, boxs, CU_TENSOR_MAP_SWIZZLE_NONE);
    cuuint32_t boxr[2] = {80, 16};
    encode(enc, &m.xr, x, 2, dims, str, boxr, CU_TENSOR_MAP_SWIZZLE_NONE);
  }
  {
    cuuint64_t dims[3] = {80, D_, 8}, str[2] = {D_ * 2, 160};
    cuuint32_t boxm[3] = {64, 64, 1}, boxr[3] = {16, 64, 1};
    encode(enc, &m.w1m, w1, 3, dims, str, boxm, CU_TENSOR_MAP_SWIZZLE_128B);
    encode(enc, &m.w1r, w1, 3, dims, str, boxr, CU_TENSOR_MAP_SWIZZLE_32B);
  }
  {
    cuuint64_t dims[4] = {80, D_, 3, 8}, str[3] = {3 * D_ * 2, D_ * 2, 160};
    cuuint32_t boxm[4] = {64, 64, 3, 1}, boxr[4] = {16, 64, 3, 1};
    encode(enc, &m.qm, wqkv, 4, dims, str, boxm, CU_TENSOR_MAP_SWIZZLE_128B);
    encode(enc, &m.qr, wqkv, 4, dims, str, boxr, CU_TENSOR_MAP_SWIZZLE_32B);
  }
  {
    cuuint64_t dims[3] = {16, D_, 40}, str[2] = {D_ * 2, 32};
    cuuint32_t box2[3] = {16, 64, 5};
    encode(enc, &m.w2, w2, 3, dims, str, box2, CU_TENSOR_MAP_SWIZZLE_32B);
  }
  {
    cuuint64_t dims[3] = {32, D_, 20}, dims4[3] = {32, F_, 20}, str[2] = {D_ * 2, 64};
    cuuint32_t box4[3] = {32, 64, 5}, boxo[3] = {32, 80, 5};
    encode(enc, &m.w4, w4, 3, dims4, str, box4, CU_TENSOR_MAP_SWIZZLE_64B);
    encode(enc, &m.wo, wo, 3, dims, str, boxo, CU_TENSOR_MAP_SWIZZLE_64B);
  }
  {
    cuuint64_t dims[3] = {64, D_, 24}, str[2] = {F_ * 2, 128};
    cuuint32_t box[3] = {64, 64, 3};
    encode(enc, &m.w3, w3, 3, dims, str, box, CU_TENSOR_MAP_SWIZZLE_128B);
  }
  fused_kernel<<<NCTA, 384, SMEM_BYTES, cudaStreamPerThread>>>(m, x, wqkv, wphi, w1, w2, w3, w4, wo, gate_w);
}
```

```cpp
#include <cuda_runtime.h>
#include <cuda_bf16.h>
#include <cuda.h>
#include <stdint.h>

namespace {

constexpr int S_ = 2048, D_ = 640, F_ = 1536;
constexpr int NCTA = 128;
constexpr int KV_PAIR = 40 * 48 + 96;
constexpr int KV_J = 2 * KV_PAIR;

constexpr int SLOT_B = 49152, NB = 3;
constexpr int SLOT_A = 16384, NA = 4;
constexpr int OFF_B = 0;
constexpr int OFF_A = OFF_B + NB * SLOT_B;
constexpr int OFF_STG = OFF_A + 2 * SLOT_A;
constexpr int OFF_MISC = OFF_A + NA * SLOT_A;
constexpr int OFF_XST = OFF_MISC + 13312;
constexpr int OFF_CS = OFF_MISC + 16384;
constexpr int OFF_BAR = OFF_CS + 1088;
constexpr int SMEM_BYTES = OFF_BAR + 512;
constexpr int B_FULLA = 0, B_FULLB = 4, B_CS = 7, B_XR = 8, B_KV = 9, B_ST1 = 10, B_SDONE = 11  , B_RDY = 17  ,
              B_FULL4 = 23  , B_DSR = 28  , B_SEND = 36  , B_EMPTYB = 42  ,
              B_SIGP = 45, B_SIGH = 46, B_SIGKV = 47, B_SIGX1 = 48, B_MFREE = 49, B_EMPTY4 = 50  ,
              B_EMPTYA = 55  , B_PEER = 59, NBAR = 60;
constexpr int SPARE = 40960;
constexpr int UNIT4 = 25600, NU4 = 5;
constexpr int OFF_DS = OFF_A, OFF_SEND = OFF_A + 40960, OFF_G0 = OFF_A + 61440, OFF_G1 = OFF_B + UNIT4;

constexpr int FL_DONE = 0, FL_H = 1, FL_X1 = FL_H + 16, FL_KV = FL_X1 + 16, FL_CS = FL_KV + 8, FL_CS3 = FL_CS + 8, FL_ST = FL_CS3 + 8, FL_PART = FL_ST + 16;
constexpr int FL_COUNT = FL_PART + 16 * 8;
constexpr int ACC_FLOATS = 8 * KV_J + D_ + F_;

struct Maps {
  CUtensorMap x, w1m, w1r, qm, qr, hs, w2, x1, w3, w4, wo, st_h, st_x1, st_out, xr;
};

}

__device__ __align__(1024) __nv_bfloat16 g_Hs[(S_ + 4) * D_];
__device__ __align__(1024) __nv_bfloat16 g_X1[S_ * D_];
__device__ __align__(128) float g_acc[2][ACC_FLOATS];
__device__ __align__(128) float4 g_xstat[S_];
__device__ __align__(128) float2 g_st1[S_ * 8];
__device__ __align__(128) uint4 g_part[16 * 8 * 3 * 1280];
__device__ __align__(128) unsigned g_flags[FL_COUNT * 32];
#define TSTAMP(n) do {} while (0)
#define TSTAMPX(n) do {} while (0)
#define TRACE(n) do {} while (0)
#define TR4(n) do {} while (0)

namespace {

__device__ __forceinline__ long long gtime() { long long t; asm volatile("mov.u64 %0, %%globaltimer;" : "=l"(t)); return t; }
__device__ __forceinline__ uint32_t smem_u32(const void* p) { return (uint32_t)__cvta_generic_to_shared(p); }
__device__ __forceinline__ void mbar_init(uint32_t bar, int cnt) {
  asm volatile("mbarrier.init.shared::cta.b64 [%0], %1;" ::"r"(bar), "r"(cnt) : "memory");
}
__device__ __forceinline__ void mbar_expect_tx(uint32_t bar, int bytes) {
  asm volatile("mbarrier.arrive.expect_tx.shared::cta.b64 _, [%0], %1;" ::"r"(bar), "r"(bytes) : "memory");
}
__device__ __forceinline__ void mbar_arrive_cta(uint32_t bar, uint32_t cta) {
  asm volatile("{\n.reg .b32 ra;\nmapa.shared::cluster.u32 ra, %0, %1;\nmbarrier.arrive.shared::cluster.b64 _, [ra];\n}"
               ::"r"(bar), "r"(cta) : "memory");
}
__device__ __forceinline__ uint32_t mbar_try(uint32_t bar, uint32_t parity) {
  uint32_t ok;
  asm volatile("{\n.reg .pred p;\nmbarrier.try_wait.parity.shared::cta.b64 p, [%1], %2;\nselp.u32 %0, 1, 0, p;\n}"
               : "=r"(ok) : "r"(bar), "r"(parity) : "memory");
  return ok;
}
constexpr uint32_t WAIT_LIMIT = 1u << 22;
__device__ __forceinline__ void mbar_wait(uint32_t bar, uint32_t parity) {
  uint32_t n = 0;
  while (!mbar_try(bar, parity) && ++n < WAIT_LIMIT) {}
}
__device__ __forceinline__ unsigned ld_acquire(const unsigned* p) {
  unsigned v;
  asm volatile("ld.acquire.gpu.global.u32 %0, [%1];" : "=r"(v) : "l"(p) : "memory");
  return v;
}
__device__ __forceinline__ void flag_wait(int idx, unsigned target) {
  const unsigned* p = g_flags + idx * 32;
  uint32_t n = 0;
  while ((int)(ld_acquire(p) - target) < 0 && ++n < (WAIT_LIMIT >> 4)) {}
}
__device__ __forceinline__ void flag_add(int idx) {
  asm volatile("red.release.gpu.global.add.u32 [%0], 1;" ::"l"(g_flags + idx * 32) : "memory");
}
__device__ __forceinline__ void flag_add_relaxed(int idx) {
  asm volatile("red.relaxed.gpu.global.add.u32 [%0], 1;" ::"l"(g_flags + idx * 32) : "memory");
}
__device__ __forceinline__ uint32_t mbar_test(uint32_t bar, uint32_t parity) {
  uint32_t ok;
  asm volatile("{\n.reg .pred p;\nmbarrier.test_wait.parity.shared::cta.b64 p, [%1], %2;\nselp.u32 %0, 1, 0, p;\n}"
               : "=r"(ok) : "r"(bar), "r"(parity) : "memory");
  return ok;
}
__device__ __forceinline__ uint32_t lds32(uint32_t a) {
  uint32_t v;
  asm volatile("ld.shared.u32 %0, [%1];" : "=r"(v) : "r"(a) : "memory");
  return v;
}
__device__ __forceinline__ void mbar_arrive(uint32_t bar) {
  asm volatile("mbarrier.arrive.shared::cta.b64 _, [%0];" ::"r"(bar) : "memory");
}
__device__ __forceinline__ void fence_async_all() { asm volatile("fence.proxy.async;" ::: "memory"); }
__device__ __forceinline__ void fence_async_smem() { asm volatile("fence.proxy.async.shared::cta;" ::: "memory"); }
__device__ __forceinline__ void bar_sync(int id, int n) { asm volatile("bar.sync %0, %1;" ::"r"(id), "r"(n) : "memory"); }

__device__ __forceinline__ void tma2d(uint32_t dst, const CUtensorMap* m, uint32_t bar, int c0, int c1) {
  asm volatile("cp.async.bulk.tensor.2d.shared::cluster.global.mbarrier::complete_tx::bytes [%0], [%1, {%3, %4}], [%2];"
               ::"r"(dst), "l"(m), "r"(bar), "r"(c0), "r"(c1) : "memory");
}
__device__ __forceinline__ void tma2d_mc(uint32_t dst, const CUtensorMap* m, uint32_t bar, int c0, int c1) {
  asm volatile("cp.async.bulk.tensor.2d.shared::cluster.global.mbarrier::complete_tx::bytes.multicast::cluster"
               " [%0], [%1, {%3, %4}], [%2], %5;"
               ::"r"(dst), "l"(m), "r"(bar), "r"(c0), "r"(c1), "h"((uint16_t)3) : "memory");
}
__device__ __forceinline__ void tma3d(uint32_t dst, const CUtensorMap* m, uint32_t bar, int c0, int c1, int c2) {
  asm volatile("cp.async.bulk.tensor.3d.shared::cluster.global.mbarrier::complete_tx::bytes [%0], [%1, {%3, %4, %5}], [%2];"
               ::"r"(dst), "l"(m), "r"(bar), "r"(c0), "r"(c1), "r"(c2) : "memory");
}
__device__ __forceinline__ void tma4d(uint32_t dst, const CUtensorMap* m, uint32_t bar, int c0, int c1, int c2, int c3) {
  asm volatile("cp.async.bulk.tensor.4d.shared::cluster.global.mbarrier::complete_tx::bytes [%0], [%1, {%3, %4, %5, %6}], [%2];"
               ::"r"(dst), "l"(m), "r"(bar), "r"(c0), "r"(c1), "r"(c2), "r"(c3) : "memory");
}
__device__ __forceinline__ void tma2d_store(const CUtensorMap* m, uint32_t src, int c0, int c1) {
  asm volatile("cp.async.bulk.tensor.2d.global.shared::cta.bulk_group [%0, {%2, %3}], [%1];"
               ::"l"(m), "r"(src), "r"(c0), "r"(c1) : "memory");
}
__device__ __forceinline__ void bulk_store(void* dst, uint32_t src, uint32_t bytes) {
  asm volatile("cp.async.bulk.global.shared::cta.bulk_group [%0], [%1], %2;" ::"l"(dst), "r"(src), "r"(bytes) : "memory");
}
__device__ __forceinline__ void bulk_load(uint32_t dst, const void* src, uint32_t bytes, uint32_t bar) {
  asm volatile("cp.async.bulk.shared::cluster.global.mbarrier::complete_tx::bytes [%0], [%1], %2, [%3];"
               ::"r"(dst), "l"(src), "r"(bytes), "r"(bar) : "memory");
}
__device__ __forceinline__ void bulk_commit() { asm volatile("cp.async.bulk.commit_group;" ::: "memory"); }
template <int N> __device__ __forceinline__ void bulk_wait() { asm volatile("cp.async.bulk.wait_group %0;" ::"n"(N) : "memory"); }
__device__ __forceinline__ void bulk_wait_read() { asm volatile("cp.async.bulk.wait_group.read 0;" ::: "memory"); }
__device__ __forceinline__ void bar_arrive(int id, int n) { asm volatile("bar.arrive %0, %1;" ::"r"(id), "r"(n) : "memory"); }
__device__ __forceinline__ uint4 lds128(uint32_t a) {
  uint4 v;
  asm volatile("ld.shared.v4.u32 {%0, %1, %2, %3}, [%4];" : "=r"(v.x), "=r"(v.y), "=r"(v.z), "=r"(v.w) : "r"(a) : "memory");
  return v;
}
__device__ __forceinline__ void sts128(uint32_t a, uint4 v) {
  asm volatile("st.shared.v4.u32 [%0], {%1, %2, %3, %4};" ::"r"(a), "r"(v.x), "r"(v.y), "r"(v.z), "r"(v.w) : "memory");
}
__device__ __forceinline__ uint32_t map_peer(uint32_t addr, uint32_t cta) {
  uint32_t r;
  asm("mapa.shared::cluster.u32 %0, %1, %2;" : "=r"(r) : "r"(addr), "r"(cta));
  return r;
}
__device__ __forceinline__ void st_async16(uint32_t addr, uint32_t a, uint32_t b, uint32_t c, uint32_t d, uint32_t bar) {
  asm volatile("st.async.weak.shared::cluster.mbarrier::complete_tx::bytes.v4.b32 [%0], {%1, %2, %3, %4}, [%5];"
               ::"r"(addr), "r"(a), "r"(b), "r"(c), "r"(d), "r"(bar) : "memory");
}
__device__ __forceinline__ void l2_prefetch(const void* p, uint32_t bytes) {
  asm volatile("cp.async.bulk.prefetch.L2.global [%0], %1;" ::"l"(p), "r"(bytes) : "memory");
}
__device__ __forceinline__ void prefetch_tmap(const CUtensorMap* m) {
  asm volatile("prefetch.tensormap [%0];" ::"l"(m) : "memory");
}
__device__ __forceinline__ uint64_t make_desc(uint32_t a16, uint32_t off, uint32_t lbo, uint32_t sbo, uint32_t swz) {
  const uint32_t lo = a16 + ((off >> 4) + ((lbo >> 4) << 16)), hi = (sbo >> 4) | (swz << 30);
  uint64_t d;
  asm("mov.b64 %0, {%1, %2};" : "=l"(d) : "r"(lo), "r"(hi));
  return d;
}
__device__ __forceinline__ void wg_fence() { asm volatile("wgmma.fence.sync.aligned;" ::: "memory"); }
__device__ __forceinline__ void wg_commit() { asm volatile("wgmma.commit_group.sync.aligned;" ::: "memory"); }
template <int N> __device__ __forceinline__ void wg_wait() { asm volatile("wgmma.wait_group.sync.aligned %0;" ::"n"(N) : "memory"); }
template <int N> __device__ __forceinline__ void fence_regs(float (&d)[N]) {
#pragma unroll
  for (int i = 0; i < N; i++) asm volatile("" : "+f"(d[i])::"memory");
}
template <int N> __device__ __forceinline__ void zero_regs(float (&d)[N]) {
#pragma unroll
  for (int i = 0; i < N; i++) d[i] = 0.f;
}
__device__ __forceinline__ uint32_t pack_bf16(float lo, float hi) {
  uint32_t r;
  asm("cvt.rn.bf16x2.f32 %0, %1, %2;" : "=r"(r) : "f"(hi), "f"(lo));
  return r;
}
__device__ __forceinline__ float bf_lo(uint32_t v) { return __uint_as_float(v << 16); }
__device__ __forceinline__ float bf_hi(uint32_t v) { return __uint_as_float(v & 0xffff0000u); }
__device__ __forceinline__ uint32_t max_bf2(uint32_t a, uint32_t b) {
  uint32_t r; asm("max.bf16x2 %0, %1, %2;" : "=r"(r) : "r"(a), "r"(b)); return r;
}
__device__ __forceinline__ uint32_t min_bf2(uint32_t a, uint32_t b) {
  uint32_t r; asm("min.bf16x2 %0, %1, %2;" : "=r"(r) : "r"(a), "r"(b)); return r;
}
__device__ __forceinline__ float ex2(float x) { float r; asm("ex2.approx.ftz.f32 %0, %1;" : "=f"(r) : "f"(x)); return r; }
__device__ __forceinline__ float rcp(float x) { float r; asm("rcp.approx.ftz.f32 %0, %1;" : "=f"(r) : "f"(x)); return r; }
__device__ __forceinline__ float tanh_ap(float x) { float r; asm("tanh.approx.f32 %0, %1;" : "=f"(r) : "f"(x)); return r; }
__device__ __forceinline__ float gelu_s(float x, float hs) {
  float u = x * fmaf(x * x, 0.0356774081f, 0.7978845608f);
  float hx = x * hs;
  return fmaf(hx, tanh_ap(u), hx);
}
__device__ __forceinline__ void stsm4(uint32_t addr, uint32_t r0, uint32_t r1, uint32_t r2, uint32_t r3) {
  asm volatile("stmatrix.sync.aligned.m8n8.x4.shared.b16 [%0], {%1, %2, %3, %4};"
               ::"r"(addr), "r"(r0), "r"(r1), "r"(r2), "r"(r3) : "memory");
}
__device__ __forceinline__ void red_add4(float* p, float a, float b, float c, float d) {
  asm volatile("red.global.add.v4.f32 [%0], {%1, %2, %3, %4};" ::"l"(p), "f"(a), "f"(b), "f"(c), "f"(d) : "memory");
}
__device__ __forceinline__ void red_add2(float* p, float a, float b) {
  asm volatile("red.global.add.v2.f32 [%0], {%1, %2};" ::"l"(p), "f"(a), "f"(b) : "memory");
}

__device__ __forceinline__ void mma_ss256(float (&d)[128], uint64_t descA, uint64_t descB) {
  asm volatile("wgmma.mma_async.sync.aligned.m64n256k16.f32.bf16.bf16 {"
      "%0, %1, %2, %3, %4, %5, %6, %7, %8, %9, %10, %11, %12, %13, %14, %15, "
      "%16, %17, %18, %19, %20, %21, %22, %23, %24, %25, %26, %27, %28, %29, %30, %31, "
      "%32, %33, %34, %35, %36, %37, %38, %39, %40, %41, %42, %43, %44, %45, %46, %47, "
      "%48, %49, %50, %51, %52, %53, %54, %55, %56, %57, %58, %59, %60, %61, %62, %63, "
      "%64, %65, %66, %67, %68, %69, %70, %71, %72, %73, %74, %75, %76, %77, %78, %79, "
      "%80, %81, %82, %83, %84, %85, %86, %87, %88, %89, %90, %91, %92, %93, %94, %95, "
      "%96, %97, %98, %99, %100, %101, %102, %103, %104, %105, %106, %107, %108, %109, %110, %111, "
      "%112, %113, %114, %115, %116, %117, %118, %119, %120, %121, %122, %123, %124, %125, %126, %127"
      "}, %128, %129, 1, 1, 1, 0, 1;\n"
      : "+f"(d[0]), "+f"(d[1]), "+f"(d[2]), "+f"(d[3]), "+f"(d[4]), "+f"(d[5]), "+f"(d[6]), "+f"(d[7]),
        "+f"(d[8]), "+f"(d[9]), "+f"(d[10]), "+f"(d[11]), "+f"(d[12]), "+f"(d[13]), "+f"(d[14]), "+f"(d[15]),
        "+f"(d[16]), "+f"(d[17]), "+f"(d[18]), "+f"(d[19]), "+f"(d[20]), "+f"(d[21]), "+f"(d[22]), "+f"(d[23]),
        "+f"(d[24]), "+f"(d[25]), "+f"(d[26]), "+f"(d[27]), "+f"(d[28]), "+f"(d[29]), "+f"(d[30]), "+f"(d[31]),
        "+f"(d[32]), "+f"(d[33]), "+f"(d[34]), "+f"(d[35]), "+f"(d[36]), "+f"(d[37]), "+f"(d[38]), "+f"(d[39]),
        "+f"(d[40]), "+f"(d[41]), "+f"(d[42]), "+f"(d[43]), "+f"(d[44]), "+f"(d[45]), "+f"(d[46]), "+f"(d[47]),
        "+f"(d[48]), "+f"(d[49]), "+f"(d[50]), "+f"(d[51]), "+f"(d[52]), "+f"(d[53]), "+f"(d[54]), "+f"(d[55]),
        "+f"(d[56]), "+f"(d[57]), "+f"(d[58]), "+f"(d[59]), "+f"(d[60]), "+f"(d[61]), "+f"(d[62]), "+f"(d[63]),
        "+f"(d[64]), "+f"(d[65]), "+f"(d[66]), "+f"(d[67]), "+f"(d[68]), "+f"(d[69]), "+f"(d[70]), "+f"(d[71]),
        "+f"(d[72]), "+f"(d[73]), "+f"(d[74]), "+f"(d[75]), "+f"(d[76]), "+f"(d[77]), "+f"(d[78]), "+f"(d[79]),
        "+f"(d[80]), "+f"(d[81]), "+f"(d[82]), "+f"(d[83]), "+f"(d[84]), "+f"(d[85]), "+f"(d[86]), "+f"(d[87]),
        "+f"(d[88]), "+f"(d[89]), "+f"(d[90]), "+f"(d[91]), "+f"(d[92]), "+f"(d[93]), "+f"(d[94]), "+f"(d[95]),
        "+f"(d[96]), "+f"(d[97]), "+f"(d[98]), "+f"(d[99]), "+f"(d[100]), "+f"(d[101]), "+f"(d[102]), "+f"(d[103]),
        "+f"(d[104]), "+f"(d[105]), "+f"(d[106]), "+f"(d[107]), "+f"(d[108]), "+f"(d[109]), "+f"(d[110]), "+f"(d[111]),
        "+f"(d[112]), "+f"(d[113]), "+f"(d[114]), "+f"(d[115]), "+f"(d[116]), "+f"(d[117]), "+f"(d[118]), "+f"(d[119]),
        "+f"(d[120]), "+f"(d[121]), "+f"(d[122]), "+f"(d[123]), "+f"(d[124]), "+f"(d[125]), "+f"(d[126]), "+f"(d[127])
      : "l"(descA), "l"(descB));
}

__device__ __forceinline__ void mma_ss64(float (&d)[32], uint64_t descA, uint64_t descB) {
  asm volatile("wgmma.mma_async.sync.aligned.m64n64k16.f32.bf16.bf16 {"
      "%0, %1, %2, %3, %4, %5, %6, %7, %8, %9, %10, %11, %12, %13, %14, %15, "
      "%16, %17, %18, %19, %20, %21, %22, %23, %24, %25, %26, %27, %28, %29, %30, %31"
      "}, %32, %33, 1, 1, 1, 0, 1;\n"
      : "+f"(d[0]), "+f"(d[1]), "+f"(d[2]), "+f"(d[3]), "+f"(d[4]), "+f"(d[5]), "+f"(d[6]), "+f"(d[7]),
        "+f"(d[8]), "+f"(d[9]), "+f"(d[10]), "+f"(d[11]), "+f"(d[12]), "+f"(d[13]), "+f"(d[14]), "+f"(d[15]),
        "+f"(d[16]), "+f"(d[17]), "+f"(d[18]), "+f"(d[19]), "+f"(d[20]), "+f"(d[21]), "+f"(d[22]), "+f"(d[23]),
        "+f"(d[24]), "+f"(d[25]), "+f"(d[26]), "+f"(d[27]), "+f"(d[28]), "+f"(d[29]), "+f"(d[30]), "+f"(d[31])
      : "l"(descA), "l"(descB));
}

__device__ __forceinline__ void mma_ss80(float (&d)[40], uint64_t descA, uint64_t descB) {
  asm volatile("wgmma.mma_async.sync.aligned.m64n80k16.f32.bf16.bf16 {"
      "%0, %1, %2, %3, %4, %5, %6, %7, %8, %9, %10, %11, %12, %13, %14, %15, "
      "%16, %17, %18, %19, %20, %21, %22, %23, %24, %25, %26, %27, %28, %29, %30, %31, "
      "%32, %33, %34, %35, %36, %37, %38, %39"
      "}, %40, %41, 1, 1, 1, 0, 1;\n"
      : "+f"(d[0]), "+f"(d[1]), "+f"(d[2]), "+f"(d[3]), "+f"(d[4]), "+f"(d[5]), "+f"(d[6]), "+f"(d[7]),
        "+f"(d[8]), "+f"(d[9]), "+f"(d[10]), "+f"(d[11]), "+f"(d[12]), "+f"(d[13]), "+f"(d[14]), "+f"(d[15]),
        "+f"(d[16]), "+f"(d[17]), "+f"(d[18]), "+f"(d[19]), "+f"(d[20]), "+f"(d[21]), "+f"(d[22]), "+f"(d[23]),
        "+f"(d[24]), "+f"(d[25]), "+f"(d[26]), "+f"(d[27]), "+f"(d[28]), "+f"(d[29]), "+f"(d[30]), "+f"(d[31]),
        "+f"(d[32]), "+f"(d[33]), "+f"(d[34]), "+f"(d[35]), "+f"(d[36]), "+f"(d[37]), "+f"(d[38]), "+f"(d[39])
      : "l"(descA), "l"(descB));
}

__device__ __forceinline__ void mma_ss192(float (&d)[96], uint64_t descA, uint64_t descB) {
  asm volatile("wgmma.mma_async.sync.aligned.m64n192k16.f32.bf16.bf16 {"
      "%0, %1, %2, %3, %4, %5, %6, %7, %8, %9, %10, %11, %12, %13, %14, %15, "
      "%16, %17, %18, %19, %20, %21, %22, %23, %24, %25, %26, %27, %28, %29, %30, %31, "
      "%32, %33, %34, %35, %36, %37, %38, %39, %40, %41, %42, %43, %44, %45, %46, %47, "
      "%48, %49, %50, %51, %52, %53, %54, %55, %56, %57, %58, %59, %60, %61, %62, %63, "
      "%64, %65, %66, %67, %68, %69, %70, %71, %72, %73, %74, %75, %76, %77, %78, %79, "
      "%80, %81, %82, %83, %84, %85, %86, %87, %88, %89, %90, %91, %92, %93, %94, %95"
      "}, %96, %97, 1, 1, 1, 0, 1;\n"
      : "+f"(d[0]), "+f"(d[1]), "+f"(d[2]), "+f"(d[3]), "+f"(d[4]), "+f"(d[5]), "+f"(d[6]), "+f"(d[7]),
        "+f"(d[8]), "+f"(d[9]), "+f"(d[10]), "+f"(d[11]), "+f"(d[12]), "+f"(d[13]), "+f"(d[14]), "+f"(d[15]),
        "+f"(d[16]), "+f"(d[17]), "+f"(d[18]), "+f"(d[19]), "+f"(d[20]), "+f"(d[21]), "+f"(d[22]), "+f"(d[23]),
        "+f"(d[24]), "+f"(d[25]), "+f"(d[26]), "+f"(d[27]), "+f"(d[28]), "+f"(d[29]), "+f"(d[30]), "+f"(d[31]),
        "+f"(d[32]), "+f"(d[33]), "+f"(d[34]), "+f"(d[35]), "+f"(d[36]), "+f"(d[37]), "+f"(d[38]), "+f"(d[39]),
        "+f"(d[40]), "+f"(d[41]), "+f"(d[42]), "+f"(d[43]), "+f"(d[44]), "+f"(d[45]), "+f"(d[46]), "+f"(d[47]),
        "+f"(d[48]), "+f"(d[49]), "+f"(d[50]), "+f"(d[51]), "+f"(d[52]), "+f"(d[53]), "+f"(d[54]), "+f"(d[55]),
        "+f"(d[56]), "+f"(d[57]), "+f"(d[58]), "+f"(d[59]), "+f"(d[60]), "+f"(d[61]), "+f"(d[62]), "+f"(d[63]),
        "+f"(d[64]), "+f"(d[65]), "+f"(d[66]), "+f"(d[67]), "+f"(d[68]), "+f"(d[69]), "+f"(d[70]), "+f"(d[71]),
        "+f"(d[72]), "+f"(d[73]), "+f"(d[74]), "+f"(d[75]), "+f"(d[76]), "+f"(d[77]), "+f"(d[78]), "+f"(d[79]),
        "+f"(d[80]), "+f"(d[81]), "+f"(d[82]), "+f"(d[83]), "+f"(d[84]), "+f"(d[85]), "+f"(d[86]), "+f"(d[87]),
        "+f"(d[88]), "+f"(d[89]), "+f"(d[90]), "+f"(d[91]), "+f"(d[92]), "+f"(d[93]), "+f"(d[94]), "+f"(d[95])
      : "l"(descA), "l"(descB));
}

__device__ __forceinline__ void mma_ss80_tt(float (&d)[40], uint64_t descA, uint64_t descB) {
  asm volatile("wgmma.mma_async.sync.aligned.m64n80k16.f32.bf16.bf16 {"
      "%0, %1, %2, %3, %4, %5, %6, %7, %8, %9, %10, %11, %12, %13, %14, %15, "
      "%16, %17, %18, %19, %20, %21, %22, %23, %24, %25, %26, %27, %28, %29, %30, %31, "
      "%32, %33, %34, %35, %36, %37, %38, %39"
      "}, %40, %41, 1, 1, 1, 1, 1;\n"
      : "+f"(d[0]), "+f"(d[1]), "+f"(d[2]), "+f"(d[3]), "+f"(d[4]), "+f"(d[5]), "+f"(d[6]), "+f"(d[7]),
        "+f"(d[8]), "+f"(d[9]), "+f"(d[10]), "+f"(d[11]), "+f"(d[12]), "+f"(d[13]), "+f"(d[14]), "+f"(d[15]),
        "+f"(d[16]), "+f"(d[17]), "+f"(d[18]), "+f"(d[19]), "+f"(d[20]), "+f"(d[21]), "+f"(d[22]), "+f"(d[23]),
        "+f"(d[24]), "+f"(d[25]), "+f"(d[26]), "+f"(d[27]), "+f"(d[28]), "+f"(d[29]), "+f"(d[30]), "+f"(d[31]),
        "+f"(d[32]), "+f"(d[33]), "+f"(d[34]), "+f"(d[35]), "+f"(d[36]), "+f"(d[37]), "+f"(d[38]), "+f"(d[39])
      : "l"(descA), "l"(descB));
}
__device__ __forceinline__ void mma_ss80_tt_z(float (&d)[40], uint64_t descA, uint64_t descB) {
  asm volatile("wgmma.mma_async.sync.aligned.m64n80k16.f32.bf16.bf16 {"
      "%0, %1, %2, %3, %4, %5, %6, %7, %8, %9, %10, %11, %12, %13, %14, %15, "
      "%16, %17, %18, %19, %20, %21, %22, %23, %24, %25, %26, %27, %28, %29, %30, %31, "
      "%32, %33, %34, %35, %36, %37, %38, %39"
      "}, %40, %41, 0, 1, 1, 1, 1;\n"
      : "=f"(d[0]), "=f"(d[1]), "=f"(d[2]), "=f"(d[3]), "=f"(d[4]), "=f"(d[5]), "=f"(d[6]), "=f"(d[7]),
        "=f"(d[8]), "=f"(d[9]), "=f"(d[10]), "=f"(d[11]), "=f"(d[12]), "=f"(d[13]), "=f"(d[14]), "=f"(d[15]),
        "=f"(d[16]), "=f"(d[17]), "=f"(d[18]), "=f"(d[19]), "=f"(d[20]), "=f"(d[21]), "=f"(d[22]), "=f"(d[23]),
        "=f"(d[24]), "=f"(d[25]), "=f"(d[26]), "=f"(d[27]), "=f"(d[28]), "=f"(d[29]), "=f"(d[30]), "=f"(d[31]),
        "=f"(d[32]), "=f"(d[33]), "=f"(d[34]), "=f"(d[35]), "=f"(d[36]), "=f"(d[37]), "=f"(d[38]), "=f"(d[39])
      : "l"(descA), "l"(descB));
}

__device__ __forceinline__ void mma_rs80_k(float (&d)[40], const uint32_t (&a)[4], uint64_t descB) {
  asm volatile("wgmma.mma_async.sync.aligned.m64n80k16.f32.bf16.bf16 {"
      "%0, %1, %2, %3, %4, %5, %6, %7, %8, %9, %10, %11, %12, %13, %14, %15, "
      "%16, %17, %18, %19, %20, %21, %22, %23, %24, %25, %26, %27, %28, %29, %30, %31, "
      "%32, %33, %34, %35, %36, %37, %38, %39"
      "}, {%40, %41, %42, %43}, %44, 1, 1, 1, 0;\n"
      : "+f"(d[0]), "+f"(d[1]), "+f"(d[2]), "+f"(d[3]), "+f"(d[4]), "+f"(d[5]), "+f"(d[6]), "+f"(d[7]),
        "+f"(d[8]), "+f"(d[9]), "+f"(d[10]), "+f"(d[11]), "+f"(d[12]), "+f"(d[13]), "+f"(d[14]), "+f"(d[15]),
        "+f"(d[16]), "+f"(d[17]), "+f"(d[18]), "+f"(d[19]), "+f"(d[20]), "+f"(d[21]), "+f"(d[22]), "+f"(d[23]),
        "+f"(d[24]), "+f"(d[25]), "+f"(d[26]), "+f"(d[27]), "+f"(d[28]), "+f"(d[29]), "+f"(d[30]), "+f"(d[31]),
        "+f"(d[32]), "+f"(d[33]), "+f"(d[34]), "+f"(d[35]), "+f"(d[36]), "+f"(d[37]), "+f"(d[38]), "+f"(d[39])
      : "r"(a[0]), "r"(a[1]), "r"(a[2]), "r"(a[3]), "l"(descB));
}
__device__ __forceinline__ void mma_rs80_k_z(float (&d)[40], const uint32_t (&a)[4], uint64_t descB) {
  asm volatile("wgmma.mma_async.sync.aligned.m64n80k16.f32.bf16.bf16 {"
      "%0, %1, %2, %3, %4, %5, %6, %7, %8, %9, %10, %11, %12, %13, %14, %15, "
      "%16, %17, %18, %19, %20, %21, %22, %23, %24, %25, %26, %27, %28, %29, %30, %31, "
      "%32, %33, %34, %35, %36, %37, %38, %39"
      "}, {%40, %41, %42, %43}, %44, 0, 1, 1, 0;\n"
      : "=f"(d[0]), "=f"(d[1]), "=f"(d[2]), "=f"(d[3]), "=f"(d[4]), "=f"(d[5]), "=f"(d[6]), "=f"(d[7]),
        "=f"(d[8]), "=f"(d[9]), "=f"(d[10]), "=f"(d[11]), "=f"(d[12]), "=f"(d[13]), "=f"(d[14]), "=f"(d[15]),
        "=f"(d[16]), "=f"(d[17]), "=f"(d[18]), "=f"(d[19]), "=f"(d[20]), "=f"(d[21]), "=f"(d[22]), "=f"(d[23]),
        "=f"(d[24]), "=f"(d[25]), "=f"(d[26]), "=f"(d[27]), "=f"(d[28]), "=f"(d[29]), "=f"(d[30]), "=f"(d[31]),
        "=f"(d[32]), "=f"(d[33]), "=f"(d[34]), "=f"(d[35]), "=f"(d[36]), "=f"(d[37]), "=f"(d[38]), "=f"(d[39])
      : "r"(a[0]), "r"(a[1]), "r"(a[2]), "r"(a[3]), "l"(descB));
}

__device__ __forceinline__ void mma_rs48_k(float (&d)[24], const uint32_t (&a)[4], uint64_t descB) {
  asm volatile("wgmma.mma_async.sync.aligned.m64n48k16.f32.bf16.bf16 {"
      "%0, %1, %2, %3, %4, %5, %6, %7, %8, %9, %10, %11, %12, %13, %14, %15, "
      "%16, %17, %18, %19, %20, %21, %22, %23"
      "}, {%24, %25, %26, %27}, %28, 1, 1, 1, 0;\n"
      : "+f"(d[0]), "+f"(d[1]), "+f"(d[2]), "+f"(d[3]), "+f"(d[4]), "+f"(d[5]), "+f"(d[6]), "+f"(d[7]),
        "+f"(d[8]), "+f"(d[9]), "+f"(d[10]), "+f"(d[11]), "+f"(d[12]), "+f"(d[13]), "+f"(d[14]), "+f"(d[15]),
        "+f"(d[16]), "+f"(d[17]), "+f"(d[18]), "+f"(d[19]), "+f"(d[20]), "+f"(d[21]), "+f"(d[22]), "+f"(d[23])
      : "r"(a[0]), "r"(a[1]), "r"(a[2]), "r"(a[3]), "l"(descB));
}
__device__ __forceinline__ void mma_rs48_k_z(float (&d)[24], const uint32_t (&a)[4], uint64_t descB) {
  asm volatile("wgmma.mma_async.sync.aligned.m64n48k16.f32.bf16.bf16 {"
      "%0, %1, %2, %3, %4, %5, %6, %7, %8, %9, %10, %11, %12, %13, %14, %15, "
      "%16, %17, %18, %19, %20, %21, %22, %23"
      "}, {%24, %25, %26, %27}, %28, 0, 1, 1, 0;\n"
      : "=f"(d[0]), "=f"(d[1]), "=f"(d[2]), "=f"(d[3]), "=f"(d[4]), "=f"(d[5]), "=f"(d[6]), "=f"(d[7]),
        "=f"(d[8]), "=f"(d[9]), "=f"(d[10]), "=f"(d[11]), "=f"(d[12]), "=f"(d[13]), "=f"(d[14]), "=f"(d[15]),
        "=f"(d[16]), "=f"(d[17]), "=f"(d[18]), "=f"(d[19]), "=f"(d[20]), "=f"(d[21]), "=f"(d[22]), "=f"(d[23])
      : "r"(a[0]), "r"(a[1]), "r"(a[2]), "r"(a[3]), "l"(descB));
}

__device__ __forceinline__ void mma_rs160_n(float (&d)[80], const uint32_t (&a)[4], uint64_t descB) {
  asm volatile("wgmma.mma_async.sync.aligned.m64n160k16.f32.bf16.bf16 {"
      "%0, %1, %2, %3, %4, %5, %6, %7, %8, %9, %10, %11, %12, %13, %14, %15, "
      "%16, %17, %18, %19, %20, %21, %22, %23, %24, %25, %26, %27, %28, %29, %30, %31, "
      "%32, %33, %34, %35, %36, %37, %38, %39, %40, %41, %42, %43, %44, %45, %46, %47, "
      "%48, %49, %50, %51, %52, %53, %54, %55, %56, %57, %58, %59, %60, %61, %62, %63, "
      "%64, %65, %66, %67, %68, %69, %70, %71, %72, %73, %74, %75, %76, %77, %78, %79"
      "}, {%80, %81, %82, %83}, %84, 1, 1, 1, 1;\n"
      : "+f"(d[0]), "+f"(d[1]), "+f"(d[2]), "+f"(d[3]), "+f"(d[4]), "+f"(d[5]), "+f"(d[6]), "+f"(d[7]),
        "+f"(d[8]), "+f"(d[9]), "+f"(d[10]), "+f"(d[11]), "+f"(d[12]), "+f"(d[13]), "+f"(d[14]), "+f"(d[15]),
        "+f"(d[16]), "+f"(d[17]), "+f"(d[18]), "+f"(d[19]), "+f"(d[20]), "+f"(d[21]), "+f"(d[22]), "+f"(d[23]),
        "+f"(d[24]), "+f"(d[25]), "+f"(d[26]), "+f"(d[27]), "+f"(d[28]), "+f"(d[29]), "+f"(d[30]), "+f"(d[31]),
        "+f"(d[32]), "+f"(d[33]), "+f"(d[34]), "+f"(d[35]), "+f"(d[36]), "+f"(d[37]), "+f"(d[38]), "+f"(d[39]),
        "+f"(d[40]), "+f"(d[41]), "+f"(d[42]), "+f"(d[43]), "+f"(d[44]), "+f"(d[45]), "+f"(d[46]), "+f"(d[47]),
        "+f"(d[48]), "+f"(d[49]), "+f"(d[50]), "+f"(d[51]), "+f"(d[52]), "+f"(d[53]), "+f"(d[54]), "+f"(d[55]),
        "+f"(d[56]), "+f"(d[57]), "+f"(d[58]), "+f"(d[59]), "+f"(d[60]), "+f"(d[61]), "+f"(d[62]), "+f"(d[63]),
        "+f"(d[64]), "+f"(d[65]), "+f"(d[66]), "+f"(d[67]), "+f"(d[68]), "+f"(d[69]), "+f"(d[70]), "+f"(d[71]),
        "+f"(d[72]), "+f"(d[73]), "+f"(d[74]), "+f"(d[75]), "+f"(d[76]), "+f"(d[77]), "+f"(d[78]), "+f"(d[79])
      : "r"(a[0]), "r"(a[1]), "r"(a[2]), "r"(a[3]), "l"(descB));
}
__device__ __forceinline__ void mma_rs160_n_z(float (&d)[80], const uint32_t (&a)[4], uint64_t descB) {
  asm volatile("wgmma.mma_async.sync.aligned.m64n160k16.f32.bf16.bf16 {"
      "%0, %1, %2, %3, %4, %5, %6, %7, %8, %9, %10, %11, %12, %13, %14, %15, "
      "%16, %17, %18, %19, %20, %21, %22, %23, %24, %25, %26, %27, %28, %29, %30, %31, "
      "%32, %33, %34, %35, %36, %37, %38, %39, %40, %41, %42, %43, %44, %45, %46, %47, "
      "%48, %49, %50, %51, %52, %53, %54, %55, %56, %57, %58, %59, %60, %61, %62, %63, "
      "%64, %65, %66, %67, %68, %69, %70, %71, %72, %73, %74, %75, %76, %77, %78, %79"
      "}, {%80, %81, %82, %83}, %84, 0, 1, 1, 1;\n"
      : "=f"(d[0]), "=f"(d[1]), "=f"(d[2]), "=f"(d[3]), "=f"(d[4]), "=f"(d[5]), "=f"(d[6]), "=f"(d[7]),
        "=f"(d[8]), "=f"(d[9]), "=f"(d[10]), "=f"(d[11]), "=f"(d[12]), "=f"(d[13]), "=f"(d[14]), "=f"(d[15]),
        "=f"(d[16]), "=f"(d[17]), "=f"(d[18]), "=f"(d[19]), "=f"(d[20]), "=f"(d[21]), "=f"(d[22]), "=f"(d[23]),
        "=f"(d[24]), "=f"(d[25]), "=f"(d[26]), "=f"(d[27]), "=f"(d[28]), "=f"(d[29]), "=f"(d[30]), "=f"(d[31]),
        "=f"(d[32]), "=f"(d[33]), "=f"(d[34]), "=f"(d[35]), "=f"(d[36]), "=f"(d[37]), "=f"(d[38]), "=f"(d[39]),
        "=f"(d[40]), "=f"(d[41]), "=f"(d[42]), "=f"(d[43]), "=f"(d[44]), "=f"(d[45]), "=f"(d[46]), "=f"(d[47]),
        "=f"(d[48]), "=f"(d[49]), "=f"(d[50]), "=f"(d[51]), "=f"(d[52]), "=f"(d[53]), "=f"(d[54]), "=f"(d[55]),
        "=f"(d[56]), "=f"(d[57]), "=f"(d[58]), "=f"(d[59]), "=f"(d[60]), "=f"(d[61]), "=f"(d[62]), "=f"(d[63]),
        "=f"(d[64]), "=f"(d[65]), "=f"(d[66]), "=f"(d[67]), "=f"(d[68]), "=f"(d[69]), "=f"(d[70]), "=f"(d[71]),
        "=f"(d[72]), "=f"(d[73]), "=f"(d[74]), "=f"(d[75]), "=f"(d[76]), "=f"(d[77]), "=f"(d[78]), "=f"(d[79])
      : "r"(a[0]), "r"(a[1]), "r"(a[2]), "r"(a[3]), "l"(descB));
}

__device__ __forceinline__ void feature_map(const uint32_t (&P)[2][10], uint32_t (&fr)[10][4]) {
  constexpr float L2E = 1.4426950408889634f;
#pragma unroll
  for (int p = 0; p < 2; p++) {
#pragma unroll
    for (int r = 0; r < 2; r++) {
      uint32_t mx = P[r][5 * p], mn = mx;
#pragma unroll
      for (int g = 1; g < 5; g++) { mx = max_bf2(mx, P[r][5 * p + g]); mn = min_bf2(mn, P[r][5 * p + g]); }
      mx = max_bf2(mx, __shfl_xor_sync(0xffffffffu, mx, 1));
      mn = min_bf2(mn, __shfl_xor_sync(0xffffffffu, mn, 1));
      mx = max_bf2(mx, __shfl_xor_sync(0xffffffffu, mx, 2));
      mn = min_bf2(mn, __shfl_xor_sync(0xffffffffu, mn, 2));
      float mx0 = -bf_lo(mx) * L2E, mx1 = -bf_hi(mx) * L2E, mn0 = bf_lo(mn) * L2E, mn1 = bf_hi(mn) * L2E;
      float ep0[5], ep1[5], en0[5], en1[5];
      float sp0 = 0.f, sp1 = 0.f, sn0 = 0.f, sn1 = 0.f;
#pragma unroll
      for (int g = 0; g < 5; g++) {
        float x0 = bf_lo(P[r][5 * p + g]), x1 = bf_hi(P[r][5 * p + g]);
        ep0[g] = ex2(fmaf(x0, L2E, mx0)); ep1[g] = ex2(fmaf(x1, L2E, mx1));
        en0[g] = ex2(fmaf(x0, -L2E, mn0)); en1[g] = ex2(fmaf(x1, -L2E, mn1));
        sp0 += ep0[g]; sp1 += ep1[g]; sn0 += en0[g]; sn1 += en1[g];
      }
      sp0 += __shfl_xor_sync(0xffffffffu, sp0, 1); sp1 += __shfl_xor_sync(0xffffffffu, sp1, 1);
      sn0 += __shfl_xor_sync(0xffffffffu, sn0, 1); sn1 += __shfl_xor_sync(0xffffffffu, sn1, 1);
      sp0 += __shfl_xor_sync(0xffffffffu, sp0, 2); sp1 += __shfl_xor_sync(0xffffffffu, sp1, 2);
      sn0 += __shfl_xor_sync(0xffffffffu, sn0, 2); sn1 += __shfl_xor_sync(0xffffffffu, sn1, 2);
      sp0 = rcp(sp0); sp1 = rcp(sp1); sn0 = rcp(sn0); sn1 = rcp(sn1);
#pragma unroll
      for (int g = 0; g < 5; g++) {
        fr[5 * p + g][r] = pack_bf16(ep0[g] * sp0, ep1[g] * sp1);
        fr[5 * p + g][2 + r] = pack_bf16(en0[g] * sn0, en1[g] * sn1);
      }
    }
  }
}

struct Ring {
  uint32_t idx, phase;
  template <int N> __device__ __forceinline__ void next() { if (++idx == N) { idx = 0; phase ^= 1; } }
};

}

__global__ void __cluster_dims__(2, 1, 1) __launch_bounds__(384, 1)
fused_kernel(const __grid_constant__ Maps maps, const __nv_bfloat16* __restrict__ x, const __nv_bfloat16* __restrict__ wqkv,
             const __nv_bfloat16* __restrict__ wphi, const __nv_bfloat16* __restrict__ w1, const __nv_bfloat16* __restrict__ w2,
             const __nv_bfloat16* __restrict__ w3, const __nv_bfloat16* __restrict__ w4, const __nv_bfloat16* __restrict__ wo,
             const __nv_bfloat16* __restrict__ gate_w) {
  extern __shared__ __align__(1024) uint8_t sgen[];
  const uint32_t sb = smem_u32(sgen);
  const uint32_t sb16 = (sb & 0x3FFFFu) >> 4;
  const uint32_t bars = sb + OFF_BAR;
  const uint32_t fullA = bars + 8 * B_FULLA, emptyA = bars + 8 * B_EMPTYA, fullB = bars + 8 * B_FULLB, emptyB = bars + 8 * B_EMPTYB;

  const int tid = threadIdx.x;
  const int rank = blockIdx.x & 1;
  const int pairIdx = blockIdx.x >> 1;
  const int i = pairIdx >> 2, j = 2 * (pairIdx & 3) + rank;

  TSTAMP(0);
  uint4 pv[5], pw_[5], pc[2], pre;
  if (tid < 256) {
    const int row = 128 * i + 16 * j + (tid >> 4), l16 = tid & 15;
#pragma unroll
    for (int c = 0; c < 5; c++) pv[c] = __ldg(reinterpret_cast<const uint4*>(x + (size_t)row * D_ + c * 128 + l16 * 8));
    const int tq = tid < 200 ? tid : 0;
    const __nv_bfloat16* cp = w1 + (size_t)(40 * i + tq / 10) * D_ + 80 * j + 8 * (tq % 10);
    pc[0] = __ldg(reinterpret_cast<const uint4*>(cp)); pc[1] = __ldg(reinterpret_cast<const uint4*>(cp + 20 * D_));
    pre = __ldg(reinterpret_cast<const uint4*>(wphi + (size_t)j * 1600) + tq);
#pragma unroll
    for (int c = 0; c < 5; c++) pw_[c] = __ldg(reinterpret_cast<const uint4*>(gate_w + c * 128 + l16 * 8));
  }
  if ((tid & 31) == 0) {
#pragma unroll 1
    for (int b = tid >> 5; b < NBAR; b += 12) {
      mbar_init(bars + 8 * b, b < B_SEND ? 1 : b < B_EMPTYB ? 4 : b < B_EMPTYA ? 8 : 16);
      if (b >= B_DSR && b < B_SEND) mbar_expect_tx(bars + 8 * b, 10240);
    }
    asm volatile("fence.mbarrier_init.release.cluster;" ::: "memory");
  }
  if (tid == 352) { prefetch_tmap(&maps.x); prefetch_tmap(&maps.qm); prefetch_tmap(&maps.w1m); prefetch_tmap(&maps.qr); prefetch_tmap(&maps.w1r); }
  asm volatile("barrier.cluster.arrive.relaxed.aligned;" ::: "memory");

  if (tid >= 256) {
    asm volatile("setmaxnreg.dec.sync.aligned.u32 40;");
    asm volatile("barrier.cluster.wait.aligned;" ::: "memory");
    auto get_epoch = [&]() { return *reinterpret_cast<volatile unsigned*>(g_flags + FL_DONE * 32) / NCTA; };
    const int lane = tid & 31, pw = (tid >> 5) & 3;
    auto send_stream = [&](int w, unsigned ep1) {
#pragma unroll 1
      for (int c = 0; c < 3; c++) {
        const int d = (j + 2 * c + 2) & 7;
        mbar_wait(bars + 8 * (B_SEND + 2 * c + w), 0);
        if (w) TR4(c * 16 + 7);
        bulk_store(g_part + (size_t)((i * 8 + d) * 3 + c) * 1280 + w * 640, sb + OFF_SEND + w * 10240, 10240);
        bulk_commit();
        bulk_wait<0>();
        mbar_arrive(bars + 8 * (B_SDONE + 2 * c + w));
        if (w) TR4(c * 16 + 9);
        asm volatile("st.release.gpu.global.u32 [%0], %1;"
                     ::"l"(g_flags + (FL_PART + i * 8 + d) * 32 + 2 * c + w), "r"(ep1) : "memory");
        if (w) TR4(c * 16 + 10);
      }
    };
    if (pw == 0) {
      if (lane == 0) {
        Ring r{0, 1};
        unsigned ep1 = 0;
#pragma unroll 1
        for (int k = 0; k < 30; k++) {
          if (k == 4) ep1 = get_epoch() + 1;
          if (k == 10 || k == 20) {
            const unsigned tgt = ep1 * 8u;
            const unsigned* f0 = g_flags + (k == 10 ? FL_H + ((i - 1) & 15) : FL_X1 + i) * 32;
            const unsigned* f1 = g_flags + (k == 10 ? FL_H + i : FL_X1 + i) * 32;
            const unsigned* f2 = g_flags + (k == 10 ? FL_H + ((i + 1) & 15) : FL_X1 + i) * 32;
            uint32_t n = 0;
            while (++n < (WAIT_LIMIT >> 4)) {
              unsigned v0, v1, v2;
              asm volatile("ld.relaxed.gpu.global.u32 %0, [%3];\nld.relaxed.gpu.global.u32 %1, [%4];\nld.acquire.gpu.global.u32 %2, [%5];"
                           : "=r"(v0), "=r"(v1), "=r"(v2) : "l"(f0), "l"(f1), "l"(f2) : "memory");
              if ((int)((v0 - tgt) | (v1 - tgt) | (v2 - tgt)) >= 0) break;
            }
            TSTAMPX(k == 10 ? 29 : 30);
          }
          mbar_wait(emptyA + 8 * r.idx, r.phase);
          const uint32_t bar = fullA + 8 * r.idx, slot = sb + OFF_A + r.idx * SLOT_A;
          TRACE(k);
          mbar_expect_tx(bar, SLOT_A);
          tma2d_mc(slot + rank * 8192, k < 10 ? &maps.x : k < 20 ? &maps.hs : &maps.x1, bar, 64 * (k % 10), 128 * i + 64 * rank);
          r.next<NA>();
        }
        send_stream(1, ep1);
      }
    } else if (pw == 1) {
      if (lane == 0) {
        Ring r{0, 1};
#pragma unroll 1
        for (int k = 0; k < 18; k++) {
          mbar_wait(emptyB + 8 * r.idx, r.phase);
          const uint32_t bar = fullB + 8 * r.idx, slot = sb + OFF_B + r.idx * SLOT_B;
          if (k < 10) {
            mbar_expect_tx(bar, 40960);
            tma4d(slot + 8192, &maps.qm, bar, 0, 64 * k, 0, j);
            tma3d(slot, &maps.w1m, bar, 0, 64 * k, j);
            tma4d(slot + 32768 + 2048, &maps.qr, bar, 64, 64 * k, 0, j);
            tma3d(slot + 32768, &maps.w1r, bar, 64, 64 * k, j);
          } else if (k < 13) {
            if (k == 12) mbar_wait(fullA + 8 * 2, 0);
            mbar_expect_tx(bar, k < 12 ? 40960 : 20480);
#pragma unroll 1
            for (int u = 0; u < (k < 12 ? 4 : 2); u++) tma3d(slot + u * 10240, &maps.w2, bar, 0, 256 * (k - 10) + 64 * u, 5 * j);
          } else {
            mbar_expect_tx(bar, 49152);
            tma3d(slot, &maps.w3, bar, 0, 128 * (k - 13), 3 * j);
            tma3d(slot + 24576, &maps.w3, bar, 0, 128 * (k - 13) + 64, 3 * j);
          }
          r.next<NB>();
        }
        Ring r4{0, 1};
#pragma unroll 1
        for (int n = 0; n < 16; n++) {
          if (n == 0 || n == 1 || n == 3) { mbar_wait(emptyB + 8 * r.idx, r.phase); r.next<NB>(); }
          mbar_wait(bars + 8 * (B_EMPTY4 + r4.idx), r4.phase);
          const uint32_t bar = bars + 8 * (B_FULL4 + r4.idx), slot = sb + OFF_B + r4.idx * UNIT4;
          const int u = n & 3, m = ((j >> 1) + 1 + (n >> 2)) & 3;
          mbar_expect_tx(bar, u == 3 ? 25600 : 20480);
          tma3d(slot, u == 3 ? &maps.wo : &maps.w4, bar, 0, u == 3 ? 80 * j : 192 * j + 64 * u, 5 * m);
          r4.next<NU4>();
        }
      }
    } else {
      const unsigned epoch = get_epoch();
      float* accg = g_acc[epoch & 1];
      if (pw == 2) {
        {
          float* nxt = g_acc[(epoch + 1) & 1];
          constexpr int PER = ACC_FLOATS / NCTA;
#pragma unroll 1
          for (int e = lane; e < PER; e += 32) nxt[blockIdx.x * PER + e] = 0.f;
        }
        if (lane == 0) {
          flag_wait(FL_CS + j, (epoch + 1) * 16u);
          flag_wait(FL_ST + i, (epoch + 1) * 8u);
          fence_async_all();
          mbar_expect_tx(bars + 8 * B_CS, 320 + 2048);
          bulk_load(sb + OFF_CS, accg + 8 * KV_J + 80 * j, 320, bars + 8 * B_CS);
          bulk_load(sb + OFF_XST, g_xstat + 128 * i, 2048, bars + 8 * B_CS);
          TSTAMPX(21);
          l2_prefetch(w2 + (size_t)blockIdx.x * (D_ * D_ / NCTA), D_ * D_ * 2 / NCTA);
          l2_prefetch(w4 + (size_t)blockIdx.x * (F_ * D_ / NCTA), F_ * D_ * 2 / NCTA);
          l2_prefetch(wo + (size_t)blockIdx.x * (D_ * D_ / NCTA), D_ * D_ * 2 / NCTA);
        }
        __syncwarp();
#pragma unroll 1
        for (int m = 0; m < 6; m++) {
          const int col = 192 * j + 32 * m + 8 * (lane & 3);
          const __nv_bfloat16* p = w3 + (size_t)(40 * i + (lane >> 2) * 5) * F_ + col;
          float a[8];
#pragma unroll
          for (int e = 0; e < 8; e++) a[e] = 0.f;
#pragma unroll
          for (int it = 0; it < 5; it++) {
            const uint4 v = __ldg(reinterpret_cast<const uint4*>(p + (size_t)it * F_));
            a[0] += bf_lo(v.x); a[1] += bf_hi(v.x); a[2] += bf_lo(v.y); a[3] += bf_hi(v.y);
            a[4] += bf_lo(v.z); a[5] += bf_hi(v.z); a[6] += bf_lo(v.w); a[7] += bf_hi(v.w);
          }
#pragma unroll
          for (int e = 0; e < 4; e++) {
            const float snd = (lane & 4) ? a[e] : a[e + 4], keep = (lane & 4) ? a[e + 4] : a[e];
            a[e] = keep + __shfl_xor_sync(0xffffffffu, snd, 4);
            a[e] += __shfl_xor_sync(0xffffffffu, a[e], 8);
            a[e] += __shfl_xor_sync(0xffffffffu, a[e], 16);
          }
          if (lane < 8) red_add4(accg + 8 * KV_J + D_ + col + (lane >> 2) * 4, a[0], a[1], a[2], a[3]);
        }
        __syncwarp();
        if (lane == 0) {
          flag_add(FL_CS3 + j);
          flag_wait(FL_KV + j, (epoch + 1) * 16u);
          fence_async_all();
          mbar_expect_tx(bars + 8 * B_KV, KV_J * 4);
          bulk_load(sb + OFF_MISC, accg + j * KV_J, KV_J * 4, bars + 8 * B_KV);
          TSTAMPX(22);
          mbar_wait(bars + 8 * B_MFREE, 0);
          flag_wait(FL_X1 + i, (epoch + 1) * 8u);
          flag_wait(FL_CS3 + j, (epoch + 1) * 16u);
          fence_async_all();
          mbar_expect_tx(bars + 8 * B_ST1, 8192 + 768);
          bulk_load(sb + OFF_CS + 320, accg + 8 * KV_J + D_ + 192 * j, 768, bars + 8 * B_ST1);
          bulk_load(sb + OFF_MISC, g_st1 + 128 * i * 8, 8192, bars + 8 * B_ST1);
        }
        __syncwarp();
        mbar_wait(bars + 8 * B_PEER, 0);
        const unsigned* fp = g_flags + (FL_PART + i * 8 + j) * 32 + lane;
        bool seen = lane >= 6;
        uint32_t n = 0;
        while (!__all_sync(0xffffffffu, seen) && ++n < (WAIT_LIMIT >> 4)) {
          if (!seen && ld_acquire(fp) == epoch + 1 && (lane < 2 || (lane < 4 ? mbar_test(bars + 8 * (B_SEND + 2), 0) && mbar_test(bars + 8 * (B_SEND + 3), 0) && mbar_test(bars + 8 * (B_EMPTY4 + 1), 0) : mbar_test(bars + 8 * (B_SDONE + lane), 0)))) {
            seen = true;
            if (lane & 1) TR4((lane >> 1) * 16 + 11);
            mbar_expect_tx(bars + 8 * (B_RDY + lane), 10240);
            bulk_load(sb + (lane < 2 ? OFF_G0 : lane < 4 ? OFF_G1 : OFF_SEND) + (lane & 1) * 10240, g_part + (size_t)(i * 8 + j) * 3840 + lane * 640, 10240,
                      bars + 8 * (B_RDY + lane));
          }
        }
      } else {
        mbar_wait(bars + 8 * B_SIGP, 0);
        if (lane < 20) {
          float a0 = 0.f, a1 = 0.f, a2 = 0.f, a3 = 0.f;
#pragma unroll 4
          for (int r = 0; r < 20; r++) {
            const uint4 v = lds128(sb + OFF_B + SPARE + r * 320 + lane * 16);
            a0 += __uint_as_float(v.x); a1 += __uint_as_float(v.y); a2 += __uint_as_float(v.z); a3 += __uint_as_float(v.w);
          }
          red_add4(accg + 8 * KV_J + 80 * j + 4 * lane, a0, a1, a2, a3);
        }
        __syncwarp();
      }
      if (pw == 3 && lane == 0) {
        flag_add(FL_CS + j); flag_add_relaxed(FL_ST + i);
        TSTAMPX(20);
        mbar_expect_tx(bars + 8 * B_XR, 20480);
#pragma unroll 1
        for (int u = 0; u < 8; u++)
          tma2d(sb + OFF_B + (u / 3) * SLOT_B + SPARE + (u % 3) * 2560, &maps.xr, bars + 8 * B_XR, 80 * j, 128 * i + 16 * u);
        const int shift = (j < 2) ? 1 : (j < 4) ? -1 : (j < 6) ? 2 : -2;
        if ((shift > 0 && i == 0) || (shift < 0 && i == 15)) {
          const int nz = shift > 0 ? shift : -shift, zr = shift > 0 ? 0 : S_ - nz;
#pragma unroll 1
          for (int e = 0; e < nz * 10; e++)
            reinterpret_cast<uint4*>(g_Hs + (size_t)(2 + zr + e / 10) * D_ + 80 * j)[e % 10] = make_uint4(0, 0, 0, 0);
          fence_async_all();
        }
        prefetch_tmap(&maps.st_h); prefetch_tmap(&maps.st_x1); prefetch_tmap(&maps.hs); prefetch_tmap(&maps.x1); prefetch_tmap(&maps.xr);
        prefetch_tmap(&maps.w2); prefetch_tmap(&maps.w3); prefetch_tmap(&maps.w4); prefetch_tmap(&maps.wo); prefetch_tmap(&maps.st_out);
        mbar_wait(bars + 8 * B_SIGH, 0);
        TSTAMPX(23);
        tma2d_store(&maps.st_h, sb + OFF_STG, 80 * j, 128 * i + 2 + shift);
        tma2d_store(&maps.st_h, sb + OFF_STG + 10240, 80 * j, 128 * i + 66 + shift);
        bulk_commit(); bulk_wait<0>();
        flag_add(FL_H + i);
        TSTAMPX(24);
        mbar_wait(bars + 8 * B_SIGKV, 0);
        TSTAMPX(25);
        flag_add(FL_KV + j);
        TSTAMPX(26);
        mbar_wait(bars + 8 * B_SIGX1, 0);
        TSTAMPX(27);
        tma2d_store(&maps.st_x1, sb + OFF_STG, 80 * j, 128 * i);
        tma2d_store(&maps.st_x1, sb + OFF_STG + 10240, 80 * j, 128 * i + 64);
        bulk_commit(); bulk_wait<0>();
        flag_add(FL_X1 + i);
        TSTAMPX(28);
        send_stream(0, epoch + 1);
      }
    }
  } else {
    asm volatile("setmaxnreg.inc.sync.aligned.u32 232;");
    const int wg = tid >> 7, warp = tid >> 5, lane = tid & 31, t = lane & 3;
    const int rloc = warp * 16 + (lane >> 2);
    const float* s_cs = reinterpret_cast<const float*>(sgen + OFF_CS);
    auto signal = [&](int b) {
      __syncwarp();
      if (lane == 0) mbar_arrive(bars + 8 * b);
    };
    auto releaseB = [&](uint32_t bar) {
      __syncwarp();
      if (lane == 0) mbar_arrive(bar);
    };
    auto release = [&](uint32_t bar) {
      __syncwarp();
      if (lane < 2) mbar_arrive_cta(bar, lane);
    };
    uint32_t par;
    const uint32_t stg_lane = (warp * 16 + ((lane >> 3) & 1) * 8 + (lane & 7)) * 160 + (lane >> 4) * 16;

    {
      const unsigned done_cnt = *reinterpret_cast<volatile unsigned*>(g_flags + FL_DONE * 32);
#pragma unroll 1
      for (int e = tid; e < 800; e += 256) sts128(sb + OFF_MISC + e * 16, make_uint4(0, 0, 0, 0));
      bar_sync(1, 256);
      float f[40];
      float s = 0.f, gs = 0.f;
#pragma unroll
      for (int c = 0; c < 5; c++) {
        const uint32_t vv[4] = {pv[c].x, pv[c].y, pv[c].z, pv[c].w}, ww[4] = {pw_[c].x, pw_[c].y, pw_[c].z, pw_[c].w};
#pragma unroll
        for (int e = 0; e < 4; e++) {
          f[8 * c + 2 * e] = bf_lo(vv[e]); f[8 * c + 2 * e + 1] = bf_hi(vv[e]);
          s += f[8 * c + 2 * e] + f[8 * c + 2 * e + 1];
          gs = fmaf(f[8 * c + 2 * e], bf_lo(ww[e]), gs); gs = fmaf(f[8 * c + 2 * e + 1], bf_hi(ww[e]), gs);
        }
      }
#pragma unroll
      for (int o = 1; o < 16; o <<= 1) { s += __shfl_xor_sync(0xffffffffu, s, o); gs += __shfl_xor_sync(0xffffffffu, gs, o); }
      const float mean = s * (1.f / D_);
      float q = 0.f;
#pragma unroll
      for (int e = 0; e < 40; e++) { const float d = f[e] - mean; q = fmaf(d, d, q); }
#pragma unroll
      for (int o = 1; o < 16; o <<= 1) q += __shfl_xor_sync(0xffffffffu, q, o);
      const float rstd = rsqrtf(q * (1.f / D_) + 1e-5f);
      par = (done_cnt / NCTA) & 1;
      if (tid < 200) {
        const uint32_t cd = sb + OFF_B + SPARE + tid * 32;
        sts128(cd, make_uint4(__float_as_uint(bf_lo(pc[0].x) + bf_lo(pc[1].x)), __float_as_uint(bf_hi(pc[0].x) + bf_hi(pc[1].x)),
                              __float_as_uint(bf_lo(pc[0].y) + bf_lo(pc[1].y)), __float_as_uint(bf_hi(pc[0].y) + bf_hi(pc[1].y))));
        sts128(cd + 16, make_uint4(__float_as_uint(bf_lo(pc[0].z) + bf_lo(pc[1].z)), __float_as_uint(bf_hi(pc[0].z) + bf_hi(pc[1].z)),
                                   __float_as_uint(bf_lo(pc[0].w) + bf_lo(pc[1].w)), __float_as_uint(bf_hi(pc[0].w) + bf_hi(pc[1].w))));
        const uint32_t ww[4] = {pre.x, pre.y, pre.z, pre.w};
        const int h = tid / 50;
#pragma unroll
        for (int e = 0; e < 8; e++) {
          const int idx = tid * 8 + e, k = idx / 20, ff = idx - 20 * k;
          const int n = 40 * (h >> 1) + 8 * (ff >> 2) + 2 * (ff & 3) + (h & 1);
          const int off = (k >> 4) * 2560 + n * 32 + ((((k >> 3) ^ (n >> 2)) & 1) << 4) + (k & 7) * 2;
          *reinterpret_cast<unsigned short*>(sgen + OFF_MISC + off) = (unsigned short)(ww[e >> 1] >> ((e & 1) * 16));
        }
      }
      fence_async_smem();
      asm volatile("barrier.cluster.wait.aligned;" ::: "memory");
      if ((tid & 15) == 0) g_xstat[128 * i + 16 * j + (tid >> 4)] = make_float4(rstd, -mean * rstd, rcp(1.f + __expf(-gs)), 0.f);
      signal(B_SIGP);
    }
    TSTAMP(1);

    Ring ra{0, 0}, rb{0, 0};
    uint32_t qp[2][10], P[2][10];
    float st_g[2];
    {
      float accM[128], accR[32];
      zero_regs(accM); zero_regs(accR);
      uint32_t pa = 0, pb = 0;
#pragma unroll 1
      for (int k = 0; k < 10; k++) {
        mbar_wait(fullA + 8 * ra.idx, ra.phase);
        if (tid == 0) TRACE(32 + k);
        mbar_wait(fullB + 8 * rb.idx, rb.phase);
        if (tid == 0) TRACE(64 + k);
        if (k == 0) TSTAMP(2);
        const uint32_t a0 = sb16 + ((OFF_A + ra.idx * SLOT_A + wg * 8192) >> 4), b0 = sb16 + ((OFF_B + rb.idx * SLOT_B) >> 4);
        wg_fence();
#pragma unroll
        for (int kk = 0; kk < 4; kk++) {
          const uint64_t da = make_desc(a0, kk * 32, 16, 1024, 1);
          mma_ss256(accM, da, make_desc(b0, kk * 2048, 8192, 1024, 1));
          mma_ss64(accR, da, make_desc(b0, 32768 + kk * 512, 2048, 256, 3));
          if (kk == 0) {
            wg_commit();
            if (k > 0) {
              wg_wait<1>();
              if (k - 1 < 8) release(emptyA + 8 * pa);
              releaseB(emptyB + 8 * pb);
            }
          }
        }
        wg_commit();
        pa = ra.idx; pb = rb.idx;
        ra.next<NA>(); rb.next<NB>();
      }
      TSTAMP(18);
      float st_rstd[2], st_mr[2];
      mbar_wait(bars + 8 * B_CS, 0);
#pragma unroll
      for (int r = 0; r < 2; r++) {
        const uint4 st = lds128(sb + OFF_XST + (rloc + 8 * r) * 16);
        st_rstd[r] = __uint_as_float(st.x); st_mr[r] = __uint_as_float(st.y); st_g[r] = __uint_as_float(st.z);
      }
      TSTAMP(19);
      wg_wait<0>();
      fence_regs(accM); fence_regs(accR);
      TSTAMP(3);
#define ACC(P_, G, I_) ((G) < 8 ? accM[(P_) * 32 + ((G) & 7) * 4 + (I_)] : accR[(P_) * 8 + ((G) & 1) * 4 + (I_)])
      {
        const int mat = lane >> 3;
        const int tok = warp * 16 + (mat & 1) * 8 + (lane & 7);
        const uint32_t ones = (t == 0) ? 0x00003f80u : 0u;
        __syncwarp();
#pragma unroll
        for (int p = 0; p < 2; p++) {
          const uint32_t rowa = sb + OFF_A + p * SLOT_A + tok * 128;
#pragma unroll
          for (int gg = 0; gg < 3; gg++) {
            const int g0 = 5 * p + 2 * gg;
            uint32_t r0 = pack_bf16(ACC(3, g0, 0), ACC(3, g0, 1)), r1 = pack_bf16(ACC(3, g0, 2), ACC(3, g0, 3));
            uint32_t r2 = ones, r3 = ones;
            if (gg < 2) { r2 = pack_bf16(ACC(3, g0 + 1, 0), ACC(3, g0 + 1, 1)); r3 = pack_bf16(ACC(3, g0 + 1, 2), ACC(3, g0 + 1, 3)); }
            stsm4(rowa + (((2 * gg + (mat >> 1)) ^ (tok & 7)) << 4), r0, r1, r2, r3);
          }
        }
      }
      uint32_t kf[5][4], qf[5][4];
#pragma unroll
      for (int s = 0; s < 5; s++) {
        kf[s][0] = pack_bf16(ACC(2, 2 * s, 0), ACC(2, 2 * s, 1)); kf[s][1] = pack_bf16(ACC(2, 2 * s, 2), ACC(2, 2 * s, 3));
        kf[s][2] = pack_bf16(ACC(2, 2 * s + 1, 0), ACC(2, 2 * s + 1, 1)); kf[s][3] = pack_bf16(ACC(2, 2 * s + 1, 2), ACC(2, 2 * s + 1, 3));
        qf[s][0] = pack_bf16(ACC(1, 2 * s, 0), ACC(1, 2 * s, 1)); qf[s][1] = pack_bf16(ACC(1, 2 * s, 2), ACC(1, 2 * s, 3));
        qf[s][2] = pack_bf16(ACC(1, 2 * s + 1, 0), ACC(1, 2 * s + 1, 1)); qf[s][3] = pack_bf16(ACC(1, 2 * s + 1, 2), ACC(1, 2 * s + 1, 3));
      }
      bar_sync(1, 256);
      float pk[40], pq[40];
      wg_fence();
#pragma unroll
      for (int s = 0; s < 5; s++) {
        if (s == 0) mma_rs80_k_z(pk, kf[s], make_desc(sb16, OFF_MISC, 16, 256, 3));
        else mma_rs80_k(pk, kf[s], make_desc(sb16, OFF_MISC + s * 2560, 16, 256, 3));
      }
#pragma unroll
      for (int s = 0; s < 5; s++) {
        if (s == 0) mma_rs80_k_z(pq, qf[s], make_desc(sb16, OFF_MISC, 16, 256, 3));
        else mma_rs80_k(pq, qf[s], make_desc(sb16, OFF_MISC + s * 2560, 16, 256, 3));
      }
      wg_commit();

      {
        uint32_t hv[10][2];
#pragma unroll
        for (int g = 0; g < 10; g++) {
          const float2 cs = *reinterpret_cast<const float2*>(s_cs + 8 * g + 2 * t);
          const float v0 = gelu_s(fmaf(ACC(0, g, 0), st_rstd[0], st_mr[0] * cs.x), 0.5f), v1 = gelu_s(fmaf(ACC(0, g, 1), st_rstd[0], st_mr[0] * cs.y), 0.5f);
          const float v2 = gelu_s(fmaf(ACC(0, g, 2), st_rstd[1], st_mr[1] * cs.x), 0.5f), v3 = gelu_s(fmaf(ACC(0, g, 3), st_rstd[1], st_mr[1] * cs.y), 0.5f);
          hv[g][0] = pack_bf16(v0, v1); hv[g][1] = pack_bf16(v2, v3);
        }
#pragma unroll
        for (int s = 0; s < 5; s++) stsm4(sb + OFF_STG + stg_lane + s * 32, hv[2 * s][0], hv[2 * s][1], hv[2 * s + 1][0], hv[2 * s + 1][1]);
        fence_async_smem();
        signal(B_SIGH);
      }
#undef ACC
      TSTAMP(4);
      wg_wait<0>();
      fence_regs(pk); fence_regs(pq);
#pragma unroll
      for (int G = 0; G < 10; G++) {
        P[0][G] = pack_bf16(pk[4 * G], pk[4 * G + 1]); P[1][G] = pack_bf16(pk[4 * G + 2], pk[4 * G + 3]);
        qp[0][G] = pack_bf16(pq[4 * G], pq[4 * G + 1]); qp[1][G] = pack_bf16(pq[4 * G + 2], pq[4 * G + 3]);
      }
    }

    uint32_t fr[10][4];
    {
      TSTAMP(16);
      feature_map(P, fr);
      TSTAMP(17);
      const int mat = lane >> 3;
      const int tok = warp * 16 + (mat & 1) * 8 + (lane & 7);
      const uint32_t base = sb + OFF_B + tok * 32 + (((mat >> 1) ^ ((tok >> 2) & 1)) << 4);
#pragma unroll
      for (int G = 0; G < 10; G++) stsm4(base + G * 4096, fr[G][0], fr[G][1], fr[G][2], fr[G][3]);
      fence_async_smem();
      bar_sync(1, 256);
      float kv[40];
      const uint32_t a0 = sb16 + ((OFF_A + wg * SLOT_A) >> 4), b0 = sb16 + ((OFF_B + wg * 20480) >> 4);
      wg_fence();
#pragma unroll
      for (int ks = 0; ks < 8; ks++) {
        if (ks == 0) mma_ss80_tt_z(kv, make_desc(a0, 0, 16, 1024, 1), make_desc(b0, 0, 4096, 256, 3));
        else mma_ss80_tt(kv, make_desc(a0, ks * 2048, 16, 1024, 1), make_desc(b0, ks * 512, 4096, 256, 3));
      }
      wg_commit();
      wg_wait<0>();
      fence_regs(kv);
      TSTAMP(31);
      release(emptyA); release(emptyA + 8); releaseB(emptyB);
      float* dst = g_acc[par] + j * KV_J + wg * KV_PAIR;
      const int m0 = (warp & 3) * 16 + (lane >> 2);
#pragma unroll
      for (int r = 0; r < 2; r++) {
        const int m = m0 + 8 * r;
        const bool hi = m >= 20;
        float v[10];
#pragma unroll
        for (int G = 0; G < 10; G++) v[G] = hi ? kv[4 * G + 2 * r + 1] : kv[4 * G + 2 * r];
        float* p = dst + (m < 40 ? m * 48 + t * 12 : 1920 + t * 24 + 12);
        if (m <= 40) { red_add4(p, v[0], v[1], v[2], v[3]); red_add4(p + 4, v[4], v[5], v[6], v[7]); red_add2(p + 8, v[8], v[9]); }
      }
      if (m0 == 32) {
        float* p = dst + 1920 + t * 24;
        red_add4(p, kv[2], kv[6], kv[10], kv[14]); red_add4(p + 4, kv[18], kv[22], kv[26], kv[30]); red_add2(p + 8, kv[34], kv[38]);
      }
      signal(B_SIGKV);
    }
    TSTAMP(5);

    uint32_t xv[2][10];
    {
      {
        mbar_wait(bars + 8 * B_XR, 0);
        const uint32_t xa = sb + OFF_B + (warp / 3) * SLOT_B + SPARE + (warp % 3) * 2560 + (lane >> 2) * 160 + t * 4;
#pragma unroll
        for (int g = 0; g < 10; g++) { xv[0][g] = lds32(xa + g * 16); xv[1][g] = lds32(xa + 1280 + g * 16); }
      }
      float acc[40];
      zero_regs(acc);
      uint32_t pa = 0, pb = 0;
#pragma unroll 1
      for (int k = 0; k < 10; k++) {
        mbar_wait(fullA + 8 * ra.idx, ra.phase);
        if (tid == 0) TRACE(42 + k);
        if ((k & 3) == 0) mbar_wait(fullB + 8 * rb.idx, rb.phase);
        if (tid == 0) TRACE(74 + k);
        if (k == 0) TSTAMP(6);
        const uint32_t a0 = sb16 + ((OFF_A + ra.idx * SLOT_A + wg * 8192) >> 4);
        const uint32_t b0 = sb16 + ((OFF_B + rb.idx * SLOT_B + (k & 3) * 10240) >> 4);
        wg_fence();
#pragma unroll
        for (int kk = 0; kk < 4; kk++) {
          mma_ss80(acc, make_desc(a0, kk * 32, 16, 1024, 1), make_desc(b0, kk * 512, 2048, 256, 3));
          if (kk == 1) {
            wg_commit();
            if (k > 0) {
              wg_wait<1>();
              release(emptyA + 8 * pa);
              if ((k & 3) == 0) releaseB(emptyB + 8 * pb);
            }
          }
        }
        wg_commit();
        pa = ra.idx; pb = rb.idx;
        ra.next<NA>();
        if ((k & 3) == 3 || k == 9) rb.next<NB>();
      }
      wg_wait<0>();
      fence_regs(acc);
      release(emptyA + 8 * pa); releaseB(emptyB + 8 * pb);
      TSTAMP(7);
#pragma unroll
      for (int r = 0; r < 2; r++) {
#pragma unroll
        for (int g = 0; g < 10; g++)
          xv[r][g] = pack_bf16(bf_lo(xv[r][g]) + acc[4 * g + 2 * r], bf_hi(xv[r][g]) + acc[4 * g + 2 * r + 1]);
      }
      bar_sync(1, 256);
#pragma unroll
      for (int s = 0; s < 5; s++) stsm4(sb + OFF_STG + stg_lane + s * 32, xv[0][2 * s], xv[1][2 * s], xv[0][2 * s + 1], xv[1][2 * s + 1]);
#pragma unroll
      for (int r = 0; r < 2; r++) {
        float s = 0.f;
#pragma unroll
        for (int g = 0; g < 10; g++) {
          acc[4 * g + 2 * r] = bf_lo(xv[r][g]); acc[4 * g + 2 * r + 1] = bf_hi(xv[r][g]);
          s += acc[4 * g + 2 * r] + acc[4 * g + 2 * r + 1];
        }
        s += __shfl_xor_sync(0xffffffffu, s, 1); s += __shfl_xor_sync(0xffffffffu, s, 2);
        const float mu = s * (1.f / 80.f);
        float q = 0.f;
#pragma unroll
        for (int g = 0; g < 10; g++) {
          const float d0 = acc[4 * g + 2 * r] - mu, d1 = acc[4 * g + 2 * r + 1] - mu;
          q = fmaf(d0, d0, q); q = fmaf(d1, d1, q);
        }
        q += __shfl_xor_sync(0xffffffffu, q, 1); q += __shfl_xor_sync(0xffffffffu, q, 2);
        if (t == 0) g_st1[(128 * i + rloc + 8 * r) * 8 + j] = make_float2(mu, q);
      }
      fence_async_smem();
      signal(B_SIGX1);
    }
    TSTAMP(8);

    uint32_t of[5][4];
    {
      feature_map(qp, fr);
      mbar_wait(bars + 8 * B_KV, 0);
      uint4 kvr[2][3];
#pragma unroll
      for (int u = 0; u < 2; u++) {
        const int it = tid + 256 * u, p = it / 192, rem = it - 192 * p, n = rem >> 2, tq = rem & 3;
        const uint32_t sp = sb + OFF_MISC + 4 * (p * KV_PAIR + (n < 40 ? n * 48 + tq * 12 : 1920 + tq * 24 + (n & 1) * 12));
        if (it < 384) { kvr[u][0] = lds128(sp); kvr[u][1] = lds128(sp + 16); kvr[u][2] = lds128(sp + 32); }
      }
      bar_sync(1, 256);
#pragma unroll
      for (int u = 0; u < 2; u++) {
        const int it = tid + 256 * u, p = it / 192, rem = it - 192 * p, n = rem >> 2, tq = rem & 3;
        const int sh = (n < 40 ? (n >= 20) : (n & 1)) * 16;
        const uint32_t v[10] = {kvr[u][0].x, kvr[u][0].y, kvr[u][0].z, kvr[u][0].w, kvr[u][1].x, kvr[u][1].y, kvr[u][1].z, kvr[u][1].w, kvr[u][2].x, kvr[u][2].y};
        uint8_t* dst = sgen + OFF_MISC + p * 7680 + n * 32 + tq * 4;
        const int sw = ((n >> 2) & 1) << 4;
        if (it < 384) {
#pragma unroll
          for (int G = 0; G < 10; G++)
            *reinterpret_cast<uint32_t*>(dst + (G >> 1) * 1536 + (((G & 1) << 4) ^ sw)) = pack_bf16(__uint_as_float(v[G]), 0.f) << sh;
        }
      }
      fence_async_smem();
      bar_sync(1, 256);
      float o0[24], o1[24];
      wg_fence();
#pragma unroll
      for (int g = 0; g < 5; g++) {
        if (g == 0) mma_rs48_k_z(o0, fr[g], make_desc(sb16, OFF_MISC, 16, 256, 3));
        else mma_rs48_k(o0, fr[g], make_desc(sb16, OFF_MISC + g * 1536, 16, 256, 3));
      }
#pragma unroll
      for (int g = 0; g < 5; g++) {
        if (g == 0) mma_rs48_k_z(o1, fr[5], make_desc(sb16, OFF_MISC + 7680, 16, 256, 3));
        else mma_rs48_k(o1, fr[5 + g], make_desc(sb16, OFF_MISC + 7680 + g * 1536, 16, 256, 3));
      }
      wg_commit();
      wg_wait<0>();
      fence_regs(o0); fence_regs(o1);
      signal(B_MFREE);
#pragma unroll
      for (int r = 0; r < 2; r++) {
        const float a0 = __fdividef(st_g[r], o0[20 + 2 * r] + 1e-6f), a1 = __fdividef(st_g[r], o0[21 + 2 * r] + 1e-6f);
        const float b0 = __fdividef(st_g[r], o1[20 + 2 * r] + 1e-6f), b1 = __fdividef(st_g[r], o1[21 + 2 * r] + 1e-6f);
        const float am = t < 2 ? a0 : a1, bm = t < 2 ? b0 : b1;
#pragma unroll
        for (int g = 0; g < 5; g++) {
          const float sa = g < 2 ? a0 : (g == 2 ? am : a1), sb2 = g < 2 ? b0 : (g == 2 ? bm : b1);
          of[g >> 1][(g & 1) * 2 + r] = pack_bf16(o0[4 * g + 2 * r] * sa, o0[4 * g + 2 * r + 1] * sa);
          of[(5 + g) >> 1][((5 + g) & 1) * 2 + r] = pack_bf16(o1[4 * g + 2 * r] * sb2, o1[4 * g + 2 * r + 1] * sb2);
        }
      }
    }
    TSTAMP(9);

    uint32_t hf[12][4];
    {
      float acc[96];
      zero_regs(acc);
      uint32_t pa = 0, pb = 0;
#pragma unroll 1
      for (int k = 0; k < 10; k++) {
        mbar_wait(fullA + 8 * ra.idx, ra.phase);
        if (tid == 0) TRACE(52 + k);
        if ((k & 1) == 0) mbar_wait(fullB + 8 * rb.idx, rb.phase);
        if (tid == 0) TRACE(84 + k);
        if (k == 0) TSTAMP(10);
        const uint32_t a0 = sb16 + ((OFF_A + ra.idx * SLOT_A + wg * 8192) >> 4);
        const uint32_t b0 = sb16 + ((OFF_B + rb.idx * SLOT_B + (k & 1) * 24576) >> 4);
        wg_fence();
#pragma unroll
        for (int kk = 0; kk < 4; kk++) {
          mma_ss192(acc, make_desc(a0, kk * 32, 16, 1024, 1), make_desc(b0, kk * 2048, 8192, 1024, 1));
          if (kk == 0) {
            wg_commit();
            if (k > 0) {
              wg_wait<1>();
              release(emptyA + 8 * pa);
              if ((k & 1) == 0) releaseB(emptyB + 8 * pb);
            }
          }
        }
        wg_commit();
        pa = ra.idx; pb = rb.idx;
        ra.next<NA>();
        if (k & 1) rb.next<NB>();
      }
      float rs[2], mm[2];
      mbar_wait(bars + 8 * B_ST1, 0);
#pragma unroll
      for (int r = 0; r < 2; r++) {
        const uint4 su = lds128(sb + OFF_MISC + (rloc + 8 * r) * 64 + t * 16);
        const float m0 = __uint_as_float(su.x), m1 = __uint_as_float(su.z);
        float mu = m0 + m1;
        mu += __shfl_xor_sync(0xffffffffu, mu, 1); mu += __shfl_xor_sync(0xffffffffu, mu, 2);
        mu *= 0.125f;
        const float d0 = m0 - mu, d1 = m1 - mu;
        float q = __uint_as_float(su.y) + __uint_as_float(su.w) + 80.f * (d0 * d0 + d1 * d1);
        q += __shfl_xor_sync(0xffffffffu, q, 1); q += __shfl_xor_sync(0xffffffffu, q, 2);
        rs[r] = rsqrtf(q * (1.f / D_) + 1e-5f);
        mm[r] = -mu * rs[r];
      }
      wg_wait<0>();
      fence_regs(acc);
      releaseB(emptyB + 8 * pb);
      release(bars + 8 * B_PEER);
      TSTAMP(11);
      const float hs0 = 0.5f - 0.5f * st_g[0], hs1 = 0.5f - 0.5f * st_g[1];
#pragma unroll
      for (int g = 0; g < 24; g++) {
        const float2 cs = *reinterpret_cast<const float2*>(s_cs + 80 + 8 * g + 2 * t);
        const float v0 = gelu_s(fmaf(acc[4 * g], rs[0], mm[0] * cs.x), hs0), v1 = gelu_s(fmaf(acc[4 * g + 1], rs[0], mm[0] * cs.y), hs0);
        const float v2 = gelu_s(fmaf(acc[4 * g + 2], rs[1], mm[1] * cs.x), hs1), v3 = gelu_s(fmaf(acc[4 * g + 3], rs[1], mm[1] * cs.y), hs1);
        hf[g >> 1][(g & 1) * 2] = pack_bf16(v0, v1);
        hf[g >> 1][(g & 1) * 2 + 1] = pack_bf16(v2, v3);
      }
    }
    TSTAMP(12);

    {
      float acc[80], kp[40];
      const int wt = tid & 127;
      const uint32_t peer = map_peer(sb, rank ^ 1);
      Ring r4{0, 0};
      auto add16 = [&](uint32_t src) {
#pragma unroll
        for (int q = 0; q < 5; q++) {
          const uint4 v = lds128(src + q * 2048);
          float* d = &kp[8 * q];
          d[0] += bf_lo(v.x); d[1] += bf_hi(v.x); d[2] += bf_lo(v.y); d[3] += bf_hi(v.y);
          d[4] += bf_lo(v.z); d[5] += bf_hi(v.z); d[6] += bf_lo(v.w); d[7] += bf_hi(v.w);
        }
      };
      auto finish = [&](int c) {
        if (c > 1) mbar_wait(bars + 8 * (B_SDONE + 2 * (c - 2) + wg), 0);
        mbar_wait(bars + 8 * (B_DSR + 2 * (c - 1) + wg), 0);
        if (tid == 128) TR4((c - 1) * 16 + 3);
        add16(sb + OFF_DS + ((c - 1) & 1) * 20480 + wg * 10240 + wt * 16);
        const uint32_t dst = sb + OFF_SEND + wg * 10240 + wt * 16;
#pragma unroll
        for (int q = 0; q < 5; q++) {
          const float* d = &kp[8 * q];
          sts128(dst + q * 2048, make_uint4(pack_bf16(d[0], d[1]), pack_bf16(d[2], d[3]), pack_bf16(d[4], d[5]), pack_bf16(d[6], d[7])));
        }
        fence_async_smem();
        signal(B_SEND + 2 * (c - 1) + wg);
        if (tid == 128) TR4((c - 1) * 16 + 6);
      };
      zero_regs(kp);
      if (wg == 1) bar_sync(2, 256);
#pragma unroll 1
      for (int c = 0; c < 4; c++) {
        uint32_t prev = 0;
#pragma unroll
        for (int u = 0; u < 4; u++) {
          mbar_wait(bars + 8 * (B_FULL4 + r4.idx), r4.phase);
          const uint32_t b0 = sb16 + ((OFF_B + r4.idx * UNIT4) >> 4);
          if (u == 0 && tid == 128) TR4(c * 16 + 0);
          wg_fence();
#pragma unroll
          for (int s = 0; s < (u < 3 ? 4 : 5); s++) {
            const uint64_t db = make_desc(b0, s * 1024, u < 3 ? 4096 : 5120, 512, 2);
            if (u == 0 && s == 0) mma_rs160_n_z(acc, hf[0], db);
            else if (u < 3) mma_rs160_n(acc, hf[(4 * u + s) % 12], db);
            else mma_rs160_n(acc, of[s], db);
            if (s == 1 && u > 0) { wg_commit(); wg_wait<1>(); releaseB(bars + 8 * (B_EMPTY4 + prev)); }
          }
          wg_commit();
          prev = r4.idx;
          r4.next<NU4>();
          if (u == 1 && c == 0 && wg == 0) bar_arrive(2, 256);
          if (u == 0 && c > 0) finish(c);
          if (u == 2) {
            if (c == 3) {
              const float w0 = 1.f - st_g[0], w1s = 1.f - st_g[1];
#pragma unroll
              for (int g = 0; g < 10; g++) {
                kp[4 * g] = w0 * bf_lo(xv[0][g]); kp[4 * g + 1] = w0 * bf_hi(xv[0][g]);
                kp[4 * g + 2] = w1s * bf_lo(xv[1][g]); kp[4 * g + 3] = w1s * bf_hi(xv[1][g]);
              }
#pragma unroll 1
              for (int e = 0; e < 2; e++) {
                mbar_wait(bars + 8 * (B_RDY + 2 * e + wg), 0);
                add16(sb + (e == 0 ? OFF_G0 : OFF_G1) + wg * 10240 + wt * 16);
              }
            } else {
              zero_regs(kp);
            }
          }
        }
        if (tid == 128) TR4(c * 16 + 2);
        if (c == 0) mbar_wait(bars + 8 * B_PEER, 0);
        wg_wait<0>();
        fence_regs(acc);
        releaseB(bars + 8 * (B_EMPTY4 + prev));
        if (tid == 128) TR4(c * 16 + 5);
        uint32_t sn[20];
        if (rank) {
#pragma unroll
          for (int e = 0; e < 20; e++) sn[e] = pack_bf16(acc[2 * e], acc[2 * e + 1]);
#pragma unroll
          for (int e = 0; e < 40; e++) kp[e] += acc[40 + e];
        } else {
#pragma unroll
          for (int e = 0; e < 20; e++) sn[e] = pack_bf16(acc[40 + 2 * e], acc[41 + 2 * e]);
#pragma unroll
          for (int e = 0; e < 40; e++) kp[e] += acc[e];
        }
        fence_regs(kp);
        const uint32_t dso = peer + OFF_DS + (c & 1) * 20480 + wg * 10240 + wt * 16, dsb = peer + OFF_BAR + 8 * (B_DSR + 2 * c + wg);
#pragma unroll
        for (int q = 0; q < 5; q++) st_async16(dso + q * 2048, sn[4 * q], sn[4 * q + 1], sn[4 * q + 2], sn[4 * q + 3], dsb);
      }
      TSTAMP(13);
#pragma unroll 1
      for (int c = 0; c < 2; c++) {
        mbar_wait(bars + 8 * ((c == 0 ? B_DSR + 6 : B_RDY + 4) + wg), 0);
        add16(sb + (c == 0 ? OFF_DS + 20480 : OFF_SEND) + wg * 10240 + wt * 16);
      }
      TSTAMP(14);
#pragma unroll
      for (int s = 0; s < 5; s++)
        stsm4(sb + OFF_DS + stg_lane + s * 32, pack_bf16(kp[8 * s], kp[8 * s + 1]), pack_bf16(kp[8 * s + 2], kp[8 * s + 3]),
              pack_bf16(kp[8 * s + 4], kp[8 * s + 5]), pack_bf16(kp[8 * s + 6], kp[8 * s + 7]));
      fence_async_smem();
      __syncwarp();
      if (lane == 0) {
        tma2d_store(&maps.st_out, sb + OFF_DS + warp * 2560, 80 * j, 128 * i + 16 * warp);
        bulk_commit(); bulk_wait_read();
      }
    }
    TSTAMP(15);
    if (tid == 0) asm volatile("red.relaxed.gpu.global.add.u32 [%0], 1;" ::"l"(g_flags + FL_DONE * 32) : "memory");
  }
}

namespace {
typedef CUresult (*EncodeFn)(CUtensorMap*, CUtensorMapDataType, cuuint32_t, void*, const cuuint64_t*, const cuuint64_t*,
                             const cuuint32_t*, const cuuint32_t*, CUtensorMapInterleave, CUtensorMapSwizzle,
                             CUtensorMapL2promotion, CUtensorMapFloatOOBfill);

void encode(EncodeFn fn, CUtensorMap* m, const void* ptr, int rank, const cuuint64_t* dims, const cuuint64_t* strides,
            const cuuint32_t* box, CUtensorMapSwizzle swz) {
  cuuint32_t es[5] = {1, 1, 1, 1, 1};
  fn(m, CU_TENSOR_MAP_DATA_TYPE_BFLOAT16, rank, const_cast<void*>(ptr), dims, strides, box, es, CU_TENSOR_MAP_INTERLEAVE_NONE,
     swz, CU_TENSOR_MAP_L2_PROMOTION_L2_128B, CU_TENSOR_MAP_FLOAT_OOB_FILL_NONE);
}
}

extern "C" void kernel_launch(void* const* d_in, const int* in_sizes, int n_in, void* d_out, int out_size) {
  (void)in_sizes; (void)n_in; (void)out_size;
  const __nv_bfloat16* x = (const __nv_bfloat16*)d_in[0];
  const __nv_bfloat16* wqkv = (const __nv_bfloat16*)d_in[1];
  const __nv_bfloat16* wphi = (const __nv_bfloat16*)d_in[2];
  const __nv_bfloat16* wo = (const __nv_bfloat16*)d_in[3];
  const __nv_bfloat16* w1 = (const __nv_bfloat16*)d_in[5];
  const __nv_bfloat16* w2 = (const __nv_bfloat16*)d_in[6];
  const __nv_bfloat16* w3 = (const __nv_bfloat16*)d_in[7];
  const __nv_bfloat16* w4 = (const __nv_bfloat16*)d_in[8];
  const __nv_bfloat16* gate_w = (const __nv_bfloat16*)d_in[9];

  static EncodeFn enc = nullptr;
  static void *pHs = nullptr, *pX1 = nullptr;
  if (!enc) {
    cudaDriverEntryPointQueryResult qr;
    cudaGetDriverEntryPoint("cuTensorMapEncodeTiled", (void**)&enc, cudaEnableDefault, &qr);
    cudaGetSymbolAddress(&pHs, g_Hs);
    cudaGetSymbolAddress(&pX1, g_X1);
    cudaFuncSetAttribute(fused_kernel, cudaFuncAttributeMaxDynamicSharedMemorySize, SMEM_BYTES);
  }
  Maps m;
  {
    cuuint64_t dims[2] = {D_, S_}, str[1] = {D_ * 2};
    cuuint32_t boxh[2] = {64, 64};
    encode(enc, &m.x, x, 2, dims, str, boxh, CU_TENSOR_MAP_SWIZZLE_128B);
    encode(enc, &m.hs, (const char*)pHs + 2 * D_ * 2, 2, dims, str, boxh, CU_TENSOR_MAP_SWIZZLE_128B);
    encode(enc, &m.x1, pX1, 2, dims, str, boxh, CU_TENSOR_MAP_SWIZZLE_128B);
    cuuint32_t boxs[2] = {80, 64};
    cuuint64_t dimsp[2] = {D_, S_ + 4};
    encode(enc, &m.st_h, pHs, 2, dimsp, str, boxs, CU_TENSOR_MAP_SWIZZLE_NONE);
    encode(enc, &m.st_x1, pX1, 2, dims, str, boxs, CU_TENSOR_MAP_SWIZZLE_NONE);
    cuuint32_t boxr[2] = {80, 16};
    encode(enc, &m.st_out, d_out, 2, dims, str, boxr, CU_TENSOR_MAP_SWIZZLE_NONE);
    encode(enc, &m.xr, x, 2, dims, str, boxr, CU_TENSOR_MAP_SWIZZLE_NONE);
  }
  {
    cuuint64_t dims[3] = {80, D_, 8}, str[2] = {D_ * 2, 160};
    cuuint32_t boxm[3] = {64, 64, 1}, boxr[3] = {16, 64, 1};
    encode(enc, &m.w1m, w1, 3, dims, str, boxm, CU_TENSOR_MAP_SWIZZLE_128B);
    encode(enc, &m.w1r, w1, 3, dims, str, boxr, CU_TENSOR_MAP_SWIZZLE_32B);
  }
  {
    cuuint64_t dims[4] = {80, D_, 3, 8}, str[3] = {3 * D_ * 2, D_ * 2, 160};
    cuuint32_t boxm[4] = {64, 64, 3, 1}, boxr[4] = {16, 64, 3, 1};
    encode(enc, &m.qm, wqkv, 4, dims, str, boxm, CU_TENSOR_MAP_SWIZZLE_128B);
    encode(enc, &m.qr, wqkv, 4, dims, str, boxr, CU_TENSOR_MAP_SWIZZLE_32B);
  }
  {
    cuuint64_t dims[3] = {16, D_, 40}, str[2] = {D_ * 2, 32};
    cuuint32_t box2[3] = {16, 64, 5};
    encode(enc, &m.w2, w2, 3, dims, str, box2, CU_TENSOR_MAP_SWIZZLE_32B);
  }
  {
    cuuint64_t dims[3] = {32, D_, 20}, dims4[3] = {32, F_, 20}, str[2] = {D_ * 2, 64};
    cuuint32_t box4[3] = {32, 64, 5}, boxo[3] = {32, 80, 5};
    encode(enc, &m.w4, w4, 3, dims4, str, box4, CU_TENSOR_MAP_SWIZZLE_64B);
    encode(enc, &m.wo, wo, 3, dims, str, boxo, CU_TENSOR_MAP_SWIZZLE_64B);
  }
  {
    cuuint64_t dims[3] = {64, D_, 24}, str[2] = {F_ * 2, 128};
    cuuint32_t box[3] = {64, 64, 3};
    encode(enc, &m.w3, w3, 3, dims, str, box, CU_TENSOR_MAP_SWIZZLE_128B);
  }
  fused_kernel<<<NCTA, 384, SMEM_BYTES, cudaStreamPerThread>>>(m, x, wqkv, wphi, w1, w2, w3, w4, wo, gate_w);
}
```

```cpp
#include <cuda_runtime.h>
#include <cuda_bf16.h>
#include <cuda.h>
#include <stdint.h>

namespace {

constexpr int S_ = 2048, D_ = 640, F_ = 1536;
constexpr int NCTA = 128;
constexpr int KV_PAIR = 40 * 48 + 96;
constexpr int KV_J = 2 * KV_PAIR;

constexpr int SLOT_B = 49152, NB = 3;
constexpr int SLOT_A = 16384, NA = 4;
constexpr int OFF_B = 0;
constexpr int OFF_A = OFF_B + NB * SLOT_B;
constexpr int OFF_STG = OFF_A + 2 * SLOT_A;
constexpr int OFF_MISC = OFF_A + NA * SLOT_A;
constexpr int OFF_XST = OFF_MISC + 13312;
constexpr int OFF_CS = OFF_MISC + 16384;
constexpr int OFF_BAR = OFF_CS + 1088;
constexpr int SMEM_BYTES = OFF_BAR + 512;
constexpr int B_FULLA = 0, B_FULLB = 4, B_CS = 7, B_XR = 8, B_KV = 9, B_ST1 = 10, B_SDONE = 11  , B_RDY = 17  ,
              B_FULL4 = 23  , B_DSR = 28  , B_SEND = 36  , B_EMPTYB = 42  ,
              B_SIGP = 45, B_SIGH = 46, B_SIGKV = 47, B_SIGX1 = 48, B_MFREE = 49, B_EMPTY4 = 50  ,
              B_EMPTYA = 55  , B_PEER = 59, NBAR = 60;
constexpr int SPARE = 40960;
constexpr int UNIT4 = 25600, NU4 = 5;
constexpr int OFF_DS = OFF_A, OFF_SEND = OFF_A + 40960, OFF_G0 = OFF_A + 61440, OFF_G1 = OFF_B + UNIT4;

constexpr int FL_DONE = 0, FL_H = 1, FL_X1 = FL_H + 16, FL_KV = FL_X1 + 16, FL_CS = FL_KV + 8, FL_CS3 = FL_CS + 8, FL_ST = FL_CS3 + 8, FL_PART = FL_ST + 16;
constexpr int FL_COUNT = FL_PART + 16 * 8;
constexpr int ACC_FLOATS = 8 * KV_J + D_ + F_;

struct Maps {
  CUtensorMap x, w1m, w1r, qm, qr, hs, w2, x1, w3, w4, wo, st_h, st_x1, st_out, xr;
};

}

__device__ __align__(1024) __nv_bfloat16 g_Hs[(S_ + 4) * D_];
__device__ __align__(1024) __nv_bfloat16 g_X1[S_ * D_];
__device__ __align__(128) float g_acc[2][ACC_FLOATS];
__device__ __align__(128) float4 g_xstat[S_];
__device__ __align__(128) float2 g_st1[S_ * 8];
__device__ __align__(128) uint4 g_part[16 * 8 * 3 * 1280];
__device__ __align__(128) unsigned g_flags[FL_COUNT * 32];
#define TSTAMP(n) do {} while (0)
#define TSTAMPX(n) do {} while (0)
#define TRACE(n) do {} while (0)
#define TR4(n) do {} while (0)

namespace {

__device__ __forceinline__ long long gtime() { long long t; asm volatile("mov.u64 %0, %%globaltimer;" : "=l"(t)); return t; }
__device__ __forceinline__ uint32_t smem_u32(const void* p) { return (uint32_t)__cvta_generic_to_shared(p); }
__device__ __forceinline__ void mbar_init(uint32_t bar, int cnt) {
  asm volatile("mbarrier.init.shared::cta.b64 [%0], %1;" ::"r"(bar), "r"(cnt) : "memory");
}
__device__ __forceinline__ void mbar_expect_tx(uint32_t bar, int bytes) {
  asm volatile("mbarrier.arrive.expect_tx.shared::cta.b64 _, [%0], %1;" ::"r"(bar), "r"(bytes) : "memory");
}
__device__ __forceinline__ void mbar_arrive_cta(uint32_t bar, uint32_t cta) {
  asm volatile("{\n.reg .b32 ra;\nmapa.shared::cluster.u32 ra, %0, %1;\nmbarrier.arrive.shared::cluster.b64 _, [ra];\n}"
               ::"r"(bar), "r"(cta) : "memory");
}
__device__ __forceinline__ uint32_t mbar_try(uint32_t bar, uint32_t parity) {
  uint32_t ok;
  asm volatile("{\n.reg .pred p;\nmbarrier.try_wait.parity.shared::cta.b64 p, [%1], %2;\nselp.u32 %0, 1, 0, p;\n}"
               : "=r"(ok) : "r"(bar), "r"(parity) : "memory");
  return ok;
}
constexpr uint32_t WAIT_LIMIT = 1u << 22;
__device__ __forceinline__ void mbar_wait(uint32_t bar, uint32_t parity) {
  uint32_t n = 0;
  while (!mbar_try(bar, parity) && ++n < WAIT_LIMIT) {}
}
__device__ __forceinline__ unsigned ld_acquire(const unsigned* p) {
  unsigned v;
  asm volatile("ld.acquire.gpu.global.u32 %0, [%1];" : "=r"(v) : "l"(p) : "memory");
  return v;
}
__device__ __forceinline__ void flag_wait(int idx, unsigned target) {
  const unsigned* p = g_flags + idx * 32;
  uint32_t n = 0;
  while ((int)(ld_acquire(p) - target) < 0 && ++n < (WAIT_LIMIT >> 4)) {}
}
__device__ __forceinline__ void flag_add(int idx) {
  asm volatile("red.release.gpu.global.add.u32 [%0], 1;" ::"l"(g_flags + idx * 32) : "memory");
}
__device__ __forceinline__ void flag_add_relaxed(int idx) {
  asm volatile("red.relaxed.gpu.global.add.u32 [%0], 1;" ::"l"(g_flags + idx * 32) : "memory");
}
__device__ __forceinline__ uint32_t mbar_test(uint32_t bar, uint32_t parity) {
  uint32_t ok;
  asm volatile("{\n.reg .pred p;\nmbarrier.test_wait.parity.shared::cta.b64 p, [%1], %2;\nselp.u32 %0, 1, 0, p;\n}"
               : "=r"(ok) : "r"(bar), "r"(parity) : "memory");
  return ok;
}
__device__ __forceinline__ uint32_t lds32(uint32_t a) {
  uint32_t v;
  asm volatile("ld.shared.u32 %0, [%1];" : "=r"(v) : "r"(a) : "memory");
  return v;
}
__device__ __forceinline__ void mbar_arrive(uint32_t bar) {
  asm volatile("mbarrier.arrive.shared::cta.b64 _, [%0];" ::"r"(bar) : "memory");
}
__device__ __forceinline__ void fence_async_all() { asm volatile("fence.proxy.async;" ::: "memory"); }
__device__ __forceinline__ void fence_async_smem() { asm volatile("fence.proxy.async.shared::cta;" ::: "memory"); }
__device__ __forceinline__ void bar_sync(int id, int n) { asm volatile("bar.sync %0, %1;" ::"r"(id), "r"(n) : "memory"); }

__device__ __forceinline__ void tma2d(uint32_t dst, const CUtensorMap* m, uint32_t bar, int c0, int c1) {
  asm volatile("cp.async.bulk.tensor.2d.shared::cluster.global.mbarrier::complete_tx::bytes [%0], [%1, {%3, %4}], [%2];"
               ::"r"(dst), "l"(m), "r"(bar), "r"(c0), "r"(c1) : "memory");
}
__device__ __forceinline__ void tma2d_mc(uint32_t dst, const CUtensorMap* m, uint32_t bar, int c0, int c1) {
  asm volatile("cp.async.bulk.tensor.2d.shared::cluster.global.mbarrier::complete_tx::bytes.multicast::cluster"
               " [%0], [%1, {%3, %4}], [%2], %5;"
               ::"r"(dst), "l"(m), "r"(bar), "r"(c0), "r"(c1), "h"((uint16_t)3) : "memory");
}
__device__ __forceinline__ void tma3d(uint32_t dst, const CUtensorMap* m, uint32_t bar, int c0, int c1, int c2) {
  asm volatile("cp.async.bulk.tensor.3d.shared::cluster.global.mbarrier::complete_tx::bytes [%0], [%1, {%3, %4, %5}], [%2];"
               ::"r"(dst), "l"(m), "r"(bar), "r"(c0), "r"(c1), "r"(c2) : "memory");
}
__device__ __forceinline__ void tma4d(uint32_t dst, const CUtensorMap* m, uint32_t bar, int c0, int c1, int c2, int c3) {
  asm volatile("cp.async.bulk.tensor.4d.shared::cluster.global.mbarrier::complete_tx::bytes [%0], [%1, {%3, %4, %5, %6}], [%2];"
               ::"r"(dst), "l"(m), "r"(bar), "r"(c0), "r"(c1), "r"(c2), "r"(c3) : "memory");
}
__device__ __forceinline__ void tma2d_store(const CUtensorMap* m, uint32_t src, int c0, int c1) {
  asm volatile("cp.async.bulk.tensor.2d.global.shared::cta.bulk_group [%0, {%2, %3}], [%1];"
               ::"l"(m), "r"(src), "r"(c0), "r"(c1) : "memory");
}
__device__ __forceinline__ void bulk_store(void* dst, uint32_t src, uint32_t bytes) {
  asm volatile("cp.async.bulk.global.shared::cta.bulk_group [%0], [%1], %2;" ::"l"(dst), "r"(src), "r"(bytes) : "memory");
}
__device__ __forceinline__ void bulk_load(uint32_t dst, const void* src, uint32_t bytes, uint32_t bar) {
  asm volatile("cp.async.bulk.shared::cluster.global.mbarrier::complete_tx::bytes [%0], [%1], %2, [%3];"
               ::"r"(dst), "l"(src), "r"(bytes), "r"(bar) : "memory");
}
__device__ __forceinline__ void bulk_commit() { asm volatile("cp.async.bulk.commit_group;" ::: "memory"); }
template <int N> __device__ __forceinline__ void bulk_wait() { asm volatile("cp.async.bulk.wait_group %0;" ::"n"(N) : "memory"); }
__device__ __forceinline__ void bulk_wait_read() { asm volatile("cp.async.bulk.wait_group.read 0;" ::: "memory"); }
__device__ __forceinline__ void bar_arrive(int id, int n) { asm volatile("bar.arrive %0, %1;" ::"r"(id), "r"(n) : "memory"); }
__device__ __forceinline__ uint4 lds128(uint32_t a) {
  uint4 v;
  asm volatile("ld.shared.v4.u32 {%0, %1, %2, %3}, [%4];" : "=r"(v.x), "=r"(v.y), "=r"(v.z), "=r"(v.w) : "r"(a) : "memory");
  return v;
}
__device__ __forceinline__ void sts128(uint32_t a, uint4 v) {
  asm volatile("st.shared.v4.u32 [%0], {%1, %2, %3, %4};" ::"r"(a), "r"(v.x), "r"(v.y), "r"(v.z), "r"(v.w) : "memory");
}
__device__ __forceinline__ uint32_t map_peer(uint32_t addr, uint32_t cta) {
  uint32_t r;
  asm("mapa.shared::cluster.u32 %0, %1, %2;" : "=r"(r) : "r"(addr), "r"(cta));
  return r;
}
__device__ __forceinline__ void st_async16(uint32_t addr, uint32_t a, uint32_t b, uint32_t c, uint32_t d, uint32_t bar) {
  asm volatile("st.async.weak.shared::cluster.mbarrier::complete_tx::bytes.v4.b32 [%0], {%1, %2, %3, %4}, [%5];"
               ::"r"(addr), "r"(a), "r"(b), "r"(c), "r"(d), "r"(bar) : "memory");
}
__device__ __forceinline__ void l2_prefetch(const void* p, uint32_t bytes) {
  asm volatile("cp.async.bulk.prefetch.L2.global [%0], %1;" ::"l"(p), "r"(bytes) : "memory");
}
__device__ __forceinline__ void prefetch_tmap(const CUtensorMap* m) {
  asm volatile("prefetch.tensormap [%0];" ::"l"(m) : "memory");
}
__device__ __forceinline__ uint64_t make_desc(uint32_t a16, uint32_t off, uint32_t lbo, uint32_t sbo, uint32_t swz) {
  const uint32_t lo = a16 + ((off >> 4) + ((lbo >> 4) << 16)), hi = (sbo >> 4) | (swz << 30);
  uint64_t d;
  asm("mov.b64 %0, {%1, %2};" : "=l"(d) : "r"(lo), "r"(hi));
  return d;
}
__device__ __forceinline__ void wg_fence() { asm volatile("wgmma.fence.sync.aligned;" ::: "memory"); }
__device__ __forceinline__ void wg_commit() { asm volatile("wgmma.commit_group.sync.aligned;" ::: "memory"); }
template <int N> __device__ __forceinline__ void wg_wait() { asm volatile("wgmma.wait_group.sync.aligned %0;" ::"n"(N) : "memory"); }
template <int N> __device__ __forceinline__ void fence_regs(float (&d)[N]) {
#pragma unroll
  for (int i = 0; i < N; i++) asm volatile("" : "+f"(d[i])::"memory");
}
template <int N> __device__ __forceinline__ void zero_regs(float (&d)[N]) {
#pragma unroll
  for (int i = 0; i < N; i++) d[i] = 0.f;
}
__device__ __forceinline__ uint32_t pack_bf16(float lo, float hi) {
  uint32_t r;
  asm("cvt.rn.bf16x2.f32 %0, %1, %2;" : "=r"(r) : "f"(hi), "f"(lo));
  return r;
}
__device__ __forceinline__ float bf_lo(uint32_t v) { return __uint_as_float(v << 16); }
__device__ __forceinline__ float bf_hi(uint32_t v) { return __uint_as_float(v & 0xffff0000u); }
__device__ __forceinline__ uint32_t max_bf2(uint32_t a, uint32_t b) {
  uint32_t r; asm("max.bf16x2 %0, %1, %2;" : "=r"(r) : "r"(a), "r"(b)); return r;
}
__device__ __forceinline__ uint32_t min_bf2(uint32_t a, uint32_t b) {
  uint32_t r; asm("min.bf16x2 %0, %1, %2;" : "=r"(r) : "r"(a), "r"(b)); return r;
}
__device__ __forceinline__ float ex2(float x) { float r; asm("ex2.approx.ftz.f32 %0, %1;" : "=f"(r) : "f"(x)); return r; }
__device__ __forceinline__ float rcp(float x) { float r; asm("rcp.approx.ftz.f32 %0, %1;" : "=f"(r) : "f"(x)); return r; }
__device__ __forceinline__ float tanh_ap(float x) { float r; asm("tanh.approx.f32 %0, %1;" : "=f"(r) : "f"(x)); return r; }
__device__ __forceinline__ float gelu_s(float x, float hs) {
  float u = x * fmaf(x * x, 0.0356774081f, 0.7978845608f);
  float hx = x * hs;
  return fmaf(hx, tanh_ap(u), hx);
}
__device__ __forceinline__ void stsm4(uint32_t addr, uint32_t r0, uint32_t r1, uint32_t r2, uint32_t r3) {
  asm volatile("stmatrix.sync.aligned.m8n8.x4.shared.b16 [%0], {%1, %2, %3, %4};"
               ::"r"(addr), "r"(r0), "r"(r1), "r"(r2), "r"(r3) : "memory");
}
__device__ __forceinline__ void red_add4(float* p, float a, float b, float c, float d) {
  asm volatile("red.global.add.v4.f32 [%0], {%1, %2, %3, %4};" ::"l"(p), "f"(a), "f"(b), "f"(c), "f"(d) : "memory");
}

__device__ __forceinline__ void mma_ss256(float (&d)[128], uint64_t descA, uint64_t descB) {
  asm volatile("wgmma.mma_async.sync.aligned.m64n256k16.f32.bf16.bf16 {"
      "%0, %1, %2, %3, %4, %5, %6, %7, %8, %9, %10, %11, %12, %13, %14, %15, "
      "%16, %17, %18, %19, %20, %21, %22, %23, %24, %25, %26, %27, %28, %29, %30, %31, "
      "%32, %33, %34, %35, %36, %37, %38, %39, %40, %41, %42, %43, %44, %45, %46, %47, "
      "%48, %49, %50, %51, %52, %53, %54, %55, %56, %57, %58, %59, %60, %61, %62, %63, "
      "%64, %65, %66, %67, %68, %69, %70, %71, %72, %73, %74, %75, %76, %77, %78, %79, "
      "%80, %81, %82, %83, %84, %85, %86, %87, %88, %89, %90, %91, %92, %93, %94, %95, "
      "%96, %97, %98, %99, %100, %101, %102, %103, %104, %105, %106, %107, %108, %109, %110, %111, "
      "%112, %113, %114, %115, %116, %117, %118, %119, %120, %121, %122, %123, %124, %125, %126, %127"
      "}, %128, %129, 1, 1, 1, 0, 1;\n"
      : "+f"(d[0]), "+f"(d[1]), "+f"(d[2]), "+f"(d[3]), "+f"(d[4]), "+f"(d[5]), "+f"(d[6]), "+f"(d[7]),
        "+f"(d[8]), "+f"(d[9]), "+f"(d[10]), "+f"(d[11]), "+f"(d[12]), "+f"(d[13]), "+f"(d[14]), "+f"(d[15]),
        "+f"(d[16]), "+f"(d[17]), "+f"(d[18]), "+f"(d[19]), "+f"(d[20]), "+f"(d[21]), "+f"(d[22]), "+f"(d[23]),
        "+f"(d[24]), "+f"(d[25]), "+f"(d[26]), "+f"(d[27]), "+f"(d[28]), "+f"(d[29]), "+f"(d[30]), "+f"(d[31]),
        "+f"(d[32]), "+f"(d[33]), "+f"(d[34]), "+f"(d[35]), "+f"(d[36]), "+f"(d[37]), "+f"(d[38]), "+f"(d[39]),
        "+f"(d[40]), "+f"(d[41]), "+f"(d[42]), "+f"(d[43]), "+f"(d[44]), "+f"(d[45]), "+f"(d[46]), "+f"(d[47]),
        "+f"(d[48]), "+f"(d[49]), "+f"(d[50]), "+f"(d[51]), "+f"(d[52]), "+f"(d[53]), "+f"(d[54]), "+f"(d[55]),
        "+f"(d[56]), "+f"(d[57]), "+f"(d[58]), "+f"(d[59]), "+f"(d[60]), "+f"(d[61]), "+f"(d[62]), "+f"(d[63]),
        "+f"(d[64]), "+f"(d[65]), "+f"(d[66]), "+f"(d[67]), "+f"(d[68]), "+f"(d[69]), "+f"(d[70]), "+f"(d[71]),
        "+f"(d[72]), "+f"(d[73]), "+f"(d[74]), "+f"(d[75]), "+f"(d[76]), "+f"(d[77]), "+f"(d[78]), "+f"(d[79]),
        "+f"(d[80]), "+f"(d[81]), "+f"(d[82]), "+f"(d[83]), "+f"(d[84]), "+f"(d[85]), "+f"(d[86]), "+f"(d[87]),
        "+f"(d[88]), "+f"(d[89]), "+f"(d[90]), "+f"(d[91]), "+f"(d[92]), "+f"(d[93]), "+f"(d[94]), "+f"(d[95]),
        "+f"(d[96]), "+f"(d[97]), "+f"(d[98]), "+f"(d[99]), "+f"(d[100]), "+f"(d[101]), "+f"(d[102]), "+f"(d[103]),
        "+f"(d[104]), "+f"(d[105]), "+f"(d[106]), "+f"(d[107]), "+f"(d[108]), "+f"(d[109]), "+f"(d[110]), "+f"(d[111]),
        "+f"(d[112]), "+f"(d[113]), "+f"(d[114]), "+f"(d[115]), "+f"(d[116]), "+f"(d[117]), "+f"(d[118]), "+f"(d[119]),
        "+f"(d[120]), "+f"(d[121]), "+f"(d[122]), "+f"(d[123]), "+f"(d[124]), "+f"(d[125]), "+f"(d[126]), "+f"(d[127])
      : "l"(descA), "l"(descB));
}

__device__ __forceinline__ void mma_ss64(float (&d)[32], uint64_t descA, uint64_t descB) {
  asm volatile("wgmma.mma_async.sync.aligned.m64n64k16.f32.bf16.bf16 {"
      "%0, %1, %2, %3, %4, %5, %6, %7, %8, %9, %10, %11, %12, %13, %14, %15, "
      "%16, %17, %18, %19, %20, %21, %22, %23, %24, %25, %26, %27, %28, %29, %30, %31"
      "}, %32, %33, 1, 1, 1, 0, 1;\n"
      : "+f"(d[0]), "+f"(d[1]), "+f"(d[2]), "+f"(d[3]), "+f"(d[4]), "+f"(d[5]), "+f"(d[6]), "+f"(d[7]),
        "+f"(d[8]), "+f"(d[9]), "+f"(d[10]), "+f"(d[11]), "+f"(d[12]), "+f"(d[13]), "+f"(d[14]), "+f"(d[15]),
        "+f"(d[16]), "+f"(d[17]), "+f"(d[18]), "+f"(d[19]), "+f"(d[20]), "+f"(d[21]), "+f"(d[22]), "+f"(d[23]),
        "+f"(d[24]), "+f"(d[25]), "+f"(d[26]), "+f"(d[27]), "+f"(d[28]), "+f"(d[29]), "+f"(d[30]), "+f"(d[31])
      : "l"(descA), "l"(descB));
}

__device__ __forceinline__ void mma_ss80(float (&d)[40], uint64_t descA, uint64_t descB) {
  asm volatile("wgmma.mma_async.sync.aligned.m64n80k16.f32.bf16.bf16 {"
      "%0, %1, %2, %3, %4, %5, %6, %7, %8, %9, %10, %11, %12, %13, %14, %15, "
      "%16, %17, %18, %19, %20, %21, %22, %23, %24, %25, %26, %27, %28, %29, %30, %31, "
      "%32, %33, %34, %35, %36, %37, %38, %39"
      "}, %40, %41, 1, 1, 1, 0, 1;\n"
      : "+f"(d[0]), "+f"(d[1]), "+f"(d[2]), "+f"(d[3]), "+f"(d[4]), "+f"(d[5]), "+f"(d[6]), "+f"(d[7]),
        "+f"(d[8]), "+f"(d[9]), "+f"(d[10]), "+f"(d[11]), "+f"(d[12]), "+f"(d[13]), "+f"(d[14]), "+f"(d[15]),
        "+f"(d[16]), "+f"(d[17]), "+f"(d[18]), "+f"(d[19]), "+f"(d[20]), "+f"(d[21]), "+f"(d[22]), "+f"(d[23]),
        "+f"(d[24]), "+f"(d[25]), "+f"(d[26]), "+f"(d[27]), "+f"(d[28]), "+f"(d[29]), "+f"(d[30]), "+f"(d[31]),
        "+f"(d[32]), "+f"(d[33]), "+f"(d[34]), "+f"(d[35]), "+f"(d[36]), "+f"(d[37]), "+f"(d[38]), "+f"(d[39])
      : "l"(descA), "l"(descB));
}

__device__ __forceinline__ void mma_ss192(float (&d)[96], uint64_t descA, uint64_t descB) {
  asm volatile("wgmma.mma_async.sync.aligned.m64n192k16.f32.bf16.bf16 {"
      "%0, %1, %2, %3, %4, %5, %6, %7, %8, %9, %10, %11, %12, %13, %14, %15, "
      "%16, %17, %18, %19, %20, %21, %22, %23, %24, %25, %26, %27, %28, %29, %30, %31, "
      "%32, %33, %34, %35, %36, %37, %38, %39, %40, %41, %42, %43, %44, %45, %46, %47, "
      "%48, %49, %50, %51, %52, %53, %54, %55, %56, %57, %58, %59, %60, %61, %62, %63, "
      "%64, %65, %66, %67, %68, %69, %70, %71, %72, %73, %74, %75, %76, %77, %78, %79, "
      "%80, %81, %82, %83, %84, %85, %86, %87, %88, %89, %90, %91, %92, %93, %94, %95"
      "}, %96, %97, 1, 1, 1, 0, 1;\n"
      : "+f"(d[0]), "+f"(d[1]), "+f"(d[2]), "+f"(d[3]), "+f"(d[4]), "+f"(d[5]), "+f"(d[6]), "+f"(d[7]),
        "+f"(d[8]), "+f"(d[9]), "+f"(d[10]), "+f"(d[11]), "+f"(d[12]), "+f"(d[13]), "+f"(d[14]), "+f"(d[15]),
        "+f"(d[16]), "+f"(d[17]), "+f"(d[18]), "+f"(d[19]), "+f"(d[20]), "+f"(d[21]), "+f"(d[22]), "+f"(d[23]),
        "+f"(d[24]), "+f"(d[25]), "+f"(d[26]), "+f"(d[27]), "+f"(d[28]), "+f"(d[29]), "+f"(d[30]), "+f"(d[31]),
        "+f"(d[32]), "+f"(d[33]), "+f"(d[34]), "+f"(d[35]), "+f"(d[36]), "+f"(d[37]), "+f"(d[38]), "+f"(d[39]),
        "+f"(d[40]), "+f"(d[41]), "+f"(d[42]), "+f"(d[43]), "+f"(d[44]), "+f"(d[45]), "+f"(d[46]), "+f"(d[47]),
        "+f"(d[48]), "+f"(d[49]), "+f"(d[50]), "+f"(d[51]), "+f"(d[52]), "+f"(d[53]), "+f"(d[54]), "+f"(d[55]),
        "+f"(d[56]), "+f"(d[57]), "+f"(d[58]), "+f"(d[59]), "+f"(d[60]), "+f"(d[61]), "+f"(d[62]), "+f"(d[63]),
        "+f"(d[64]), "+f"(d[65]), "+f"(d[66]), "+f"(d[67]), "+f"(d[68]), "+f"(d[69]), "+f"(d[70]), "+f"(d[71]),
        "+f"(d[72]), "+f"(d[73]), "+f"(d[74]), "+f"(d[75]), "+f"(d[76]), "+f"(d[77]), "+f"(d[78]), "+f"(d[79]),
        "+f"(d[80]), "+f"(d[81]), "+f"(d[82]), "+f"(d[83]), "+f"(d[84]), "+f"(d[85]), "+f"(d[86]), "+f"(d[87]),
        "+f"(d[88]), "+f"(d[89]), "+f"(d[90]), "+f"(d[91]), "+f"(d[92]), "+f"(d[93]), "+f"(d[94]), "+f"(d[95])
      : "l"(descA), "l"(descB));
}

__device__ __forceinline__ void mma_ss80_tt(float (&d)[40], uint64_t descA, uint64_t descB) {
  asm volatile("wgmma.mma_async.sync.aligned.m64n80k16.f32.bf16.bf16 {"
      "%0, %1, %2, %3, %4, %5, %6, %7, %8, %9, %10, %11, %12, %13, %14, %15, "
      "%16, %17, %18, %19, %20, %21, %22, %23, %24, %25, %26, %27, %28, %29, %30, %31, "
      "%32, %33, %34, %35, %36, %37, %38, %39"
      "}, %40, %41, 1, 1, 1, 1, 1;\n"
      : "+f"(d[0]), "+f"(d[1]), "+f"(d[2]), "+f"(d[3]), "+f"(d[4]), "+f"(d[5]), "+f"(d[6]), "+f"(d[7]),
        "+f"(d[8]), "+f"(d[9]), "+f"(d[10]), "+f"(d[11]), "+f"(d[12]), "+f"(d[13]), "+f"(d[14]), "+f"(d[15]),
        "+f"(d[16]), "+f"(d[17]), "+f"(d[18]), "+f"(d[19]), "+f"(d[20]), "+f"(d[21]), "+f"(d[22]), "+f"(d[23]),
        "+f"(d[24]), "+f"(d[25]), "+f"(d[26]), "+f"(d[27]), "+f"(d[28]), "+f"(d[29]), "+f"(d[30]), "+f"(d[31]),
        "+f"(d[32]), "+f"(d[33]), "+f"(d[34]), "+f"(d[35]), "+f"(d[36]), "+f"(d[37]), "+f"(d[38]), "+f"(d[39])
      : "l"(descA), "l"(descB));
}
__device__ __forceinline__ void mma_ss80_tt_z(float (&d)[40], uint64_t descA, uint64_t descB) {
  asm volatile("wgmma.mma_async.sync.aligned.m64n80k16.f32.bf16.bf16 {"
      "%0, %1, %2, %3, %4, %5, %6, %7, %8, %9, %10, %11, %12, %13, %14, %15, "
      "%16, %17, %18, %19, %20, %21, %22, %23, %24, %25, %26, %27, %28, %29, %30, %31, "
      "%32, %33, %34, %35, %36, %37, %38, %39"
      "}, %40, %41, 0, 1, 1, 1, 1;\n"
      : "=f"(d[0]), "=f"(d[1]), "=f"(d[2]), "=f"(d[3]), "=f"(d[4]), "=f"(d[5]), "=f"(d[6]), "=f"(d[7]),
        "=f"(d[8]), "=f"(d[9]), "=f"(d[10]), "=f"(d[11]), "=f"(d[12]), "=f"(d[13]), "=f"(d[14]), "=f"(d[15]),
        "=f"(d[16]), "=f"(d[17]), "=f"(d[18]), "=f"(d[19]), "=f"(d[20]), "=f"(d[21]), "=f"(d[22]), "=f"(d[23]),
        "=f"(d[24]), "=f"(d[25]), "=f"(d[26]), "=f"(d[27]), "=f"(d[28]), "=f"(d[29]), "=f"(d[30]), "=f"(d[31]),
        "=f"(d[32]), "=f"(d[33]), "=f"(d[34]), "=f"(d[35]), "=f"(d[36]), "=f"(d[37]), "=f"(d[38]), "=f"(d[39])
      : "l"(descA), "l"(descB));
}

__device__ __forceinline__ void mma_rs80_k(float (&d)[40], const uint32_t (&a)[4], uint64_t descB) {
  asm volatile("wgmma.mma_async.sync.aligned.m64n80k16.f32.bf16.bf16 {"
      "%0, %1, %2, %3, %4, %5, %6, %7, %8, %9, %10, %11, %12, %13, %14, %15, "
      "%16, %17, %18, %19, %20, %21, %22, %23, %24, %25, %26, %27, %28, %29, %30, %31, "
      "%32, %33, %34, %35, %36, %37, %38, %39"
      "}, {%40, %41, %42, %43}, %44, 1, 1, 1, 0;\n"
      : "+f"(d[0]), "+f"(d[1]), "+f"(d[2]), "+f"(d[3]), "+f"(d[4]), "+f"(d[5]), "+f"(d[6]), "+f"(d[7]),
        "+f"(d[8]), "+f"(d[9]), "+f"(d[10]), "+f"(d[11]), "+f"(d[12]), "+f"(d[13]), "+f"(d[14]), "+f"(d[15]),
        "+f"(d[16]), "+f"(d[17]), "+f"(d[18]), "+f"(d[19]), "+f"(d[20]), "+f"(d[21]), "+f"(d[22]), "+f"(d[23]),
        "+f"(d[24]), "+f"(d[25]), "+f"(d[26]), "+f"(d[27]), "+f"(d[28]), "+f"(d[29]), "+f"(d[30]), "+f"(d[31]),
        "+f"(d[32]), "+f"(d[33]), "+f"(d[34]), "+f"(d[35]), "+f"(d[36]), "+f"(d[37]), "+f"(d[38]), "+f"(d[39])
      : "r"(a[0]), "r"(a[1]), "r"(a[2]), "r"(a[3]), "l"(descB));
}
__device__ __forceinline__ void mma_rs80_k_z(float (&d)[40], const uint32_t (&a)[4], uint64_t descB) {
  asm volatile("wgmma.mma_async.sync.aligned.m64n80k16.f32.bf16.bf16 {"
      "%0, %1, %2, %3, %4, %5, %6, %7, %8, %9, %10, %11, %12, %13, %14, %15, "
      "%16, %17, %18, %19, %20, %21, %22, %23, %24, %25, %26, %27, %28, %29, %30, %31, "
      "%32, %33, %34, %35, %36, %37, %38, %39"
      "}, {%40, %41, %42, %43}, %44, 0, 1, 1, 0;\n"
      : "=f"(d[0]), "=f"(d[1]), "=f"(d[2]), "=f"(d[3]), "=f"(d[4]), "=f"(d[5]), "=f"(d[6]), "=f"(d[7]),
        "=f"(d[8]), "=f"(d[9]), "=f"(d[10]), "=f"(d[11]), "=f"(d[12]), "=f"(d[13]), "=f"(d[14]), "=f"(d[15]),
        "=f"(d[16]), "=f"(d[17]), "=f"(d[18]), "=f"(d[19]), "=f"(d[20]), "=f"(d[21]), "=f"(d[22]), "=f"(d[23]),
        "=f"(d[24]), "=f"(d[25]), "=f"(d[26]), "=f"(d[27]), "=f"(d[28]), "=f"(d[29]), "=f"(d[30]), "=f"(d[31]),
        "=f"(d[32]), "=f"(d[33]), "=f"(d[34]), "=f"(d[35]), "=f"(d[36]), "=f"(d[37]), "=f"(d[38]), "=f"(d[39])
      : "r"(a[0]), "r"(a[1]), "r"(a[2]), "r"(a[3]), "l"(descB));
}

__device__ __forceinline__ void mma_rs48_k(float (&d)[24], const uint32_t (&a)[4], uint64_t descB) {
  asm volatile("wgmma.mma_async.sync.aligned.m64n48k16.f32.bf16.bf16 {"
      "%0, %1, %2, %3, %4, %5, %6, %7, %8, %9, %10, %11, %12, %13, %14, %15, "
      "%16, %17, %18, %19, %20, %21, %22, %23"
      "}, {%24, %25, %26, %27}, %28, 1, 1, 1, 0;\n"
      : "+f"(d[0]), "+f"(d[1]), "+f"(d[2]), "+f"(d[3]), "+f"(d[4]), "+f"(d[5]), "+f"(d[6]), "+f"(d[7]),
        "+f"(d[8]), "+f"(d[9]), "+f"(d[10]), "+f"(d[11]), "+f"(d[12]), "+f"(d[13]), "+f"(d[14]), "+f"(d[15]),
        "+f"(d[16]), "+f"(d[17]), "+f"(d[18]), "+f"(d[19]), "+f"(d[20]), "+f"(d[21]), "+f"(d[22]), "+f"(d[23])
      : "r"(a[0]), "r"(a[1]), "r"(a[2]), "r"(a[3]), "l"(descB));
}
__device__ __forceinline__ void mma_rs48_k_z(float (&d)[24], const uint32_t (&a)[4], uint64_t descB) {
  asm volatile("wgmma.mma_async.sync.aligned.m64n48k16.f32.bf16.bf16 {"
      "%0, %1, %2, %3, %4, %5, %6, %7, %8, %9, %10, %11, %12, %13, %14, %15, "
      "%16, %17, %18, %19, %20, %21, %22, %23"
      "}, {%24, %25, %26, %27}, %28, 0, 1, 1, 0;\n"
      : "=f"(d[0]), "=f"(d[1]), "=f"(d[2]), "=f"(d[3]), "=f"(d[4]), "=f"(d[5]), "=f"(d[6]), "=f"(d[7]),
        "=f"(d[8]), "=f"(d[9]), "=f"(d[10]), "=f"(d[11]), "=f"(d[12]), "=f"(d[13]), "=f"(d[14]), "=f"(d[15]),
        "=f"(d[16]), "=f"(d[17]), "=f"(d[18]), "=f"(d[19]), "=f"(d[20]), "=f"(d[21]), "=f"(d[22]), "=f"(d[23])
      : "r"(a[0]), "r"(a[1]), "r"(a[2]), "r"(a[3]), "l"(descB));
}

__device__ __forceinline__ void mma_rs160_n(float (&d)[80], const uint32_t (&a)[4], uint64_t descB) {
  asm volatile("wgmma.mma_async.sync.aligned.m64n160k16.f32.bf16.bf16 {"
      "%0, %1, %2, %3, %4, %5, %6, %7, %8, %9, %10, %11, %12, %13, %14, %15, "
      "%16, %17, %18, %19, %20, %21, %22, %23, %24, %25, %26, %27, %28, %29, %30, %31, "
      "%32, %33, %34, %35, %36, %37, %38, %39, %40, %41, %42, %43, %44, %45, %46, %47, "
      "%48, %49, %50, %51, %52, %53, %54, %55, %56, %57, %58, %59, %60, %61, %62, %63, "
      "%64, %65, %66, %67, %68, %69, %70, %71, %72, %73, %74, %75, %76, %77, %78, %79"
      "}, {%80, %81, %82, %83}, %84, 1, 1, 1, 1;\n"
      : "+f"(d[0]), "+f"(d[1]), "+f"(d[2]), "+f"(d[3]), "+f"(d[4]), "+f"(d[5]), "+f"(d[6]), "+f"(d[7]),
        "+f"(d[8]), "+f"(d[9]), "+f"(d[10]), "+f"(d[11]), "+f"(d[12]), "+f"(d[13]), "+f"(d[14]), "+f"(d[15]),
        "+f"(d[16]), "+f"(d[17]), "+f"(d[18]), "+f"(d[19]), "+f"(d[20]), "+f"(d[21]), "+f"(d[22]), "+f"(d[23]),
        "+f"(d[24]), "+f"(d[25]), "+f"(d[26]), "+f"(d[27]), "+f"(d[28]), "+f"(d[29]), "+f"(d[30]), "+f"(d[31]),
        "+f"(d[32]), "+f"(d[33]), "+f"(d[34]), "+f"(d[35]), "+f"(d[36]), "+f"(d[37]), "+f"(d[38]), "+f"(d[39]),
        "+f"(d[40]), "+f"(d[41]), "+f"(d[42]), "+f"(d[43]), "+f"(d[44]), "+f"(d[45]), "+f"(d[46]), "+f"(d[47]),
        "+f"(d[48]), "+f"(d[49]), "+f"(d[50]), "+f"(d[51]), "+f"(d[52]), "+f"(d[53]), "+f"(d[54]), "+f"(d[55]),
        "+f"(d[56]), "+f"(d[57]), "+f"(d[58]), "+f"(d[59]), "+f"(d[60]), "+f"(d[61]), "+f"(d[62]), "+f"(d[63]),
        "+f"(d[64]), "+f"(d[65]), "+f"(d[66]), "+f"(d[67]), "+f"(d[68]), "+f"(d[69]), "+f"(d[70]), "+f"(d[71]),
        "+f"(d[72]), "+f"(d[73]), "+f"(d[74]), "+f"(d[75]), "+f"(d[76]), "+f"(d[77]), "+f"(d[78]), "+f"(d[79])
      : "r"(a[0]), "r"(a[1]), "r"(a[2]), "r"(a[3]), "l"(descB));
}
__device__ __forceinline__ void mma_rs160_n_z(float (&d)[80], const uint32_t (&a)[4], uint64_t descB) {
  asm volatile("wgmma.mma_async.sync.aligned.m64n160k16.f32.bf16.bf16 {"
      "%0, %1, %2, %3, %4, %5, %6, %7, %8, %9, %10, %11, %12, %13, %14, %15, "
      "%16, %17, %18, %19, %20, %21, %22, %23, %24, %25, %26, %27, %28, %29, %30, %31, "
      "%32, %33, %34, %35, %36, %37, %38, %39, %40, %41, %42, %43, %44, %45, %46, %47, "
      "%48, %49, %50, %51, %52, %53, %54, %55, %56, %57, %58, %59, %60, %61, %62, %63, "
      "%64, %65, %66, %67, %68, %69, %70, %71, %72, %73, %74, %75, %76, %77, %78, %79"
      "}, {%80, %81, %82, %83}, %84, 0, 1, 1, 1;\n"
      : "=f"(d[0]), "=f"(d[1]), "=f"(d[2]), "=f"(d[3]), "=f"(d[4]), "=f"(d[5]), "=f"(d[6]), "=f"(d[7]),
        "=f"(d[8]), "=f"(d[9]), "=f"(d[10]), "=f"(d[11]), "=f"(d[12]), "=f"(d[13]), "=f"(d[14]), "=f"(d[15]),
        "=f"(d[16]), "=f"(d[17]), "=f"(d[18]), "=f"(d[19]), "=f"(d[20]), "=f"(d[21]), "=f"(d[22]), "=f"(d[23]),
        "=f"(d[24]), "=f"(d[25]), "=f"(d[26]), "=f"(d[27]), "=f"(d[28]), "=f"(d[29]), "=f"(d[30]), "=f"(d[31]),
        "=f"(d[32]), "=f"(d[33]), "=f"(d[34]), "=f"(d[35]), "=f"(d[36]), "=f"(d[37]), "=f"(d[38]), "=f"(d[39]),
        "=f"(d[40]), "=f"(d[41]), "=f"(d[42]), "=f"(d[43]), "=f"(d[44]), "=f"(d[45]), "=f"(d[46]), "=f"(d[47]),
        "=f"(d[48]), "=f"(d[49]), "=f"(d[50]), "=f"(d[51]), "=f"(d[52]), "=f"(d[53]), "=f"(d[54]), "=f"(d[55]),
        "=f"(d[56]), "=f"(d[57]), "=f"(d[58]), "=f"(d[59]), "=f"(d[60]), "=f"(d[61]), "=f"(d[62]), "=f"(d[63]),
        "=f"(d[64]), "=f"(d[65]), "=f"(d[66]), "=f"(d[67]), "=f"(d[68]), "=f"(d[69]), "=f"(d[70]), "=f"(d[71]),
        "=f"(d[72]), "=f"(d[73]), "=f"(d[74]), "=f"(d[75]), "=f"(d[76]), "=f"(d[77]), "=f"(d[78]), "=f"(d[79])
      : "r"(a[0]), "r"(a[1]), "r"(a[2]), "r"(a[3]), "l"(descB));
}

__device__ __forceinline__ void feature_map(const uint32_t (&P)[2][10], uint32_t (&fr)[10][4]) {
  constexpr float L2E = 1.4426950408889634f;
#pragma unroll
  for (int p = 0; p < 2; p++) {
#pragma unroll
    for (int r = 0; r < 2; r++) {
      uint32_t mx = P[r][5 * p], mn = mx;
#pragma unroll
      for (int g = 1; g < 5; g++) { mx = max_bf2(mx, P[r][5 * p + g]); mn = min_bf2(mn, P[r][5 * p + g]); }
      mx = max_bf2(mx, __shfl_xor_sync(0xffffffffu, mx, 1));
      mn = min_bf2(mn, __shfl_xor_sync(0xffffffffu, mn, 1));
      mx = max_bf2(mx, __shfl_xor_sync(0xffffffffu, mx, 2));
      mn = min_bf2(mn, __shfl_xor_sync(0xffffffffu, mn, 2));
      float mx0 = -bf_lo(mx) * L2E, mx1 = -bf_hi(mx) * L2E, mn0 = bf_lo(mn) * L2E, mn1 = bf_hi(mn) * L2E;
      float ep0[5], ep1[5], en0[5], en1[5];
      float sp0 = 0.f, sp1 = 0.f, sn0 = 0.f, sn1 = 0.f;
#pragma unroll
      for (int g = 0; g < 5; g++) {
        float x0 = bf_lo(P[r][5 * p + g]), x1 = bf_hi(P[r][5 * p + g]);
        ep0[g] = ex2(fmaf(x0, L2E, mx0)); ep1[g] = ex2(fmaf(x1, L2E, mx1));
        en0[g] = ex2(fmaf(x0, -L2E, mn0)); en1[g] = ex2(fmaf(x1, -L2E, mn1));
        sp0 += ep0[g]; sp1 += ep1[g]; sn0 += en0[g]; sn1 += en1[g];
      }
      sp0 += __shfl_xor_sync(0xffffffffu, sp0, 1); sp1 += __shfl_xor_sync(0xffffffffu, sp1, 1);
      sn0 += __shfl_xor_sync(0xffffffffu, sn0, 1); sn1 += __shfl_xor_sync(0xffffffffu, sn1, 1);
      sp0 += __shfl_xor_sync(0xffffffffu, sp0, 2); sp1 += __shfl_xor_sync(0xffffffffu, sp1, 2);
      sn0 += __shfl_xor_sync(0xffffffffu, sn0, 2); sn1 += __shfl_xor_sync(0xffffffffu, sn1, 2);
      sp0 = rcp(sp0); sp1 = rcp(sp1); sn0 = rcp(sn0); sn1 = rcp(sn1);
#pragma unroll
      for (int g = 0; g < 5; g++) {
        fr[5 * p + g][r] = pack_bf16(ep0[g] * sp0, ep1[g] * sp1);
        fr[5 * p + g][2 + r] = pack_bf16(en0[g] * sn0, en1[g] * sn1);
      }
    }
  }
}

struct Ring {
  uint32_t idx, phase;
  template <int N> __device__ __forceinline__ void next() { if (++idx == N) { idx = 0; phase ^= 1; } }
};

}

__global__ void __cluster_dims__(2, 1, 1) __launch_bounds__(384, 1)
fused_kernel(const __grid_constant__ Maps maps, const __nv_bfloat16* __restrict__ x, const __nv_bfloat16* __restrict__ wqkv,
             const __nv_bfloat16* __restrict__ wphi, const __nv_bfloat16* __restrict__ w1, const __nv_bfloat16* __restrict__ w2,
             const __nv_bfloat16* __restrict__ w3, const __nv_bfloat16* __restrict__ w4, const __nv_bfloat16* __restrict__ wo,
             const __nv_bfloat16* __restrict__ gate_w) {
  extern __shared__ __align__(1024) uint8_t sgen[];
  const uint32_t sb = smem_u32(sgen);
  const uint32_t sb16 = (sb & 0x3FFFFu) >> 4;
  const uint32_t bars = sb + OFF_BAR;
  const uint32_t fullA = bars + 8 * B_FULLA, emptyA = bars + 8 * B_EMPTYA, fullB = bars + 8 * B_FULLB, emptyB = bars + 8 * B_EMPTYB;

  const int tid = threadIdx.x;
  const int rank = blockIdx.x & 1;
  const int pairIdx = blockIdx.x >> 1;
  const int i = pairIdx >> 2, j = 2 * (pairIdx & 3) + rank;

  TSTAMP(0);
  auto load_p1_b = [&](int k, uint32_t slot, uint32_t bar) {
    mbar_expect_tx(bar, 40960);
    tma4d(slot + 8192, &maps.qm, bar, 0, 64 * k, 0, j);
    tma3d(slot, &maps.w1m, bar, 0, 64 * k, j);
    tma4d(slot + 32768 + 2048, &maps.qr, bar, 64, 64 * k, 0, j);
    tma3d(slot + 32768, &maps.w1r, bar, 64, 64 * k, j);
  };
  if (tid == 256) {
#pragma unroll
    for (int s = 0; s < NA; s++) mbar_init(fullA + 8 * s, 1);
    asm volatile("fence.mbarrier_init.release.cluster;" ::: "memory");
#pragma unroll 1
    for (int u = 0; u < 4; u++) {
      if ((u & 1) == 0) mbar_expect_tx(fullA + 4 * u, SLOT_A);
      tma2d(sb + OFF_A + u * 8192, &maps.x, fullA + 8 * (u >> 1), 64 * (u >> 1), 128 * i + 64 * (u & 1));
    }
  } else if (tid == 288) {
#pragma unroll
    for (int s = 0; s < NB; s++) mbar_init(fullB + 8 * s, 1);
    asm volatile("fence.mbarrier_init.release.cluster;" ::: "memory");
    load_p1_b(0, sb + OFF_B, fullB);
  } else if ((tid & 31) == 0) {
    const int w = tid >> 5;
#pragma unroll 1
    for (int b = B_CS + (w < 8 ? w : w - 2); b < NBAR; b += 10) {
      mbar_init(bars + 8 * b, b < B_SEND ? 1 : b < B_EMPTYB ? 4 : b < B_EMPTYA ? 8 : 16);
      if (b >= B_DSR && b < B_SEND) mbar_expect_tx(bars + 8 * b, 10240);
    }
    asm volatile("fence.mbarrier_init.release.cluster;" ::: "memory");
  }
  __syncwarp();
  asm volatile("barrier.cluster.arrive.relaxed.aligned;" ::: "memory");
  uint4 pv[5], pw_[5], pc[2], pre;
  if (tid < 256) {
    const int row = 128 * i + 16 * j + (tid >> 4), l16 = tid & 15;
#pragma unroll
    for (int c = 0; c < 5; c++) pv[c] = __ldg(reinterpret_cast<const uint4*>(x + (size_t)row * D_ + c * 128 + l16 * 8));
    const int tq = tid < 200 ? tid : 0;
    const __nv_bfloat16* cp = w1 + (size_t)(40 * i + tq / 10) * D_ + 80 * j + 8 * (tq % 10);
    pc[0] = __ldg(reinterpret_cast<const uint4*>(cp)); pc[1] = __ldg(reinterpret_cast<const uint4*>(cp + 20 * D_));
    pre = __ldg(reinterpret_cast<const uint4*>(wphi + (size_t)j * 1600) + tq);
#pragma unroll
    for (int c = 0; c < 5; c++) pw_[c] = __ldg(reinterpret_cast<const uint4*>(gate_w + c * 128 + l16 * 8));
  }

  if (tid >= 256) {
    asm volatile("setmaxnreg.dec.sync.aligned.u32 40;");
    asm volatile("barrier.cluster.wait.aligned;" ::: "memory");
    auto get_epoch = [&]() { return *reinterpret_cast<volatile unsigned*>(g_flags + FL_DONE * 32) / NCTA; };
    const int lane = tid & 31, pw = (tid >> 5) & 3;
    auto send_stream = [&](int w, unsigned ep1) {
#pragma unroll 1
      for (int c = 0; c < 3; c++) {
        const int d = (j + 2 * c + 2) & 7;
        mbar_wait(bars + 8 * (B_SEND + 2 * c + w), 0);
        if (w) TR4(c * 16 + 7);
        bulk_store(g_part + (size_t)((i * 8 + d) * 3 + c) * 1280 + w * 640, sb + OFF_SEND + w * 10240, 10240);
        bulk_commit();
        bulk_wait<0>();
        mbar_arrive(bars + 8 * (B_SDONE + 2 * c + w));
        if (w) TR4(c * 16 + 9);
        asm volatile("st.release.gpu.global.u32 [%0], %1;"
                     ::"l"(g_flags + (FL_PART + i * 8 + d) * 32 + 2 * c + w), "r"(ep1) : "memory");
        if (w) TR4(c * 16 + 10);
      }
    };
    if (pw == 0) {
      if (lane == 0) {
        Ring r{2, 1};
        unsigned ep1 = 0;
#pragma unroll 1
        for (int k = 2; k < 30; k++) {
          if (k == 4) ep1 = get_epoch() + 1;
          if (k == 10 || k == 20) {
            const unsigned tgt = ep1 * 8u;
            const unsigned* f0 = g_flags + (k == 10 ? FL_H + ((i - 1) & 15) : FL_X1 + i) * 32;
            const unsigned* f1 = g_flags + (k == 10 ? FL_H + i : FL_X1 + i) * 32;
            const unsigned* f2 = g_flags + (k == 10 ? FL_H + ((i + 1) & 15) : FL_X1 + i) * 32;
            uint32_t n = 0;
            while (++n < (WAIT_LIMIT >> 4)) {
              unsigned v0, v1, v2;
              asm volatile("ld.relaxed.gpu.global.u32 %0, [%3];\nld.relaxed.gpu.global.u32 %1, [%4];\nld.acquire.gpu.global.u32 %2, [%5];"
                           : "=r"(v0), "=r"(v1), "=r"(v2) : "l"(f0), "l"(f1), "l"(f2) : "memory");
              if ((int)((v0 - tgt) | (v1 - tgt) | (v2 - tgt)) >= 0) break;
            }
            TSTAMPX(k == 10 ? 29 : 30);
          }
          mbar_wait(emptyA + 8 * r.idx, r.phase);
          const uint32_t bar = fullA + 8 * r.idx, slot = sb + OFF_A + r.idx * SLOT_A;
          TRACE(k);
          mbar_expect_tx(bar, SLOT_A);
          tma2d_mc(slot + rank * 8192, k < 10 ? &maps.x : k < 20 ? &maps.hs : &maps.x1, bar, 64 * (k % 10), 128 * i + 64 * rank);
          r.next<NA>();
        }
        send_stream(1, ep1);
      }
    } else if (pw == 1) {
      if (lane == 0) {
        Ring r{1, 1};
#pragma unroll 1
        for (int k = 1; k < 18; k++) {
          mbar_wait(emptyB + 8 * r.idx, r.phase);
          const uint32_t bar = fullB + 8 * r.idx, slot = sb + OFF_B + r.idx * SLOT_B;
          if (k < 10) {
            load_p1_b(k, slot, bar);
          } else if (k < 13) {
            if (k == 12) mbar_wait(fullA + 8 * 2, 0);
            mbar_expect_tx(bar, k < 12 ? 40960 : 20480);
#pragma unroll 1
            for (int u = 0; u < (k < 12 ? 4 : 2); u++) tma3d(slot + u * 10240, &maps.w2, bar, 0, 256 * (k - 10) + 64 * u, 5 * j);
          } else {
            mbar_expect_tx(bar, 49152);
            tma3d(slot, &maps.w3, bar, 0, 128 * (k - 13), 3 * j);
            tma3d(slot + 24576, &maps.w3, bar, 0, 128 * (k - 13) + 64, 3 * j);
          }
          r.next<NB>();
        }
        Ring r4{0, 1};
#pragma unroll 1
        for (int n = 0; n < 16; n++) {
          if (n == 0 || n == 1 || n == 3) { mbar_wait(emptyB + 8 * r.idx, r.phase); r.next<NB>(); }
          mbar_wait(bars + 8 * (B_EMPTY4 + r4.idx), r4.phase);
          const uint32_t bar = bars + 8 * (B_FULL4 + r4.idx), slot = sb + OFF_B + r4.idx * UNIT4;
          const int u = n & 3, m = ((j >> 1) + 1 + (n >> 2)) & 3;
          mbar_expect_tx(bar, u == 3 ? 25600 : 20480);
          tma3d(slot, u == 3 ? &maps.wo : &maps.w4, bar, 0, u == 3 ? 80 * j : 192 * j + 64 * u, 5 * m);
          r4.next<NU4>();
        }
      }
    } else {
      const unsigned epoch = get_epoch();
      float* accg = g_acc[epoch & 1];
      if (pw == 2) {
        {
          float* nxt = g_acc[(epoch + 1) & 1];
          constexpr int PER = ACC_FLOATS / NCTA;
#pragma unroll 1
          for (int e = lane; e < PER; e += 32) nxt[blockIdx.x * PER + e] = 0.f;
        }
        if (lane == 0) {
          flag_wait(FL_CS + j, (epoch + 1) * 16u);
          flag_wait(FL_ST + i, (epoch + 1) * 8u);
          fence_async_all();
          mbar_expect_tx(bars + 8 * B_CS, 320 + 2048);
          bulk_load(sb + OFF_CS, accg + 8 * KV_J + 80 * j, 320, bars + 8 * B_CS);
          bulk_load(sb + OFF_XST, g_xstat + 128 * i, 2048, bars + 8 * B_CS);
          TSTAMPX(21);
          l2_prefetch(w2 + (size_t)blockIdx.x * (D_ * D_ / NCTA), D_ * D_ * 2 / NCTA);
          mbar_wait(bars + 8 * B_SIGH, 0);
          l2_prefetch(w3 + (size_t)blockIdx.x * (F_ * D_ / NCTA), F_ * D_ * 2 / NCTA);
          l2_prefetch(w4 + (size_t)blockIdx.x * (F_ * D_ / NCTA), F_ * D_ * 2 / NCTA);
          l2_prefetch(wo + (size_t)blockIdx.x * (D_ * D_ / NCTA), D_ * D_ * 2 / NCTA);
          flag_wait(FL_KV + j, (epoch + 1) * 16u);
          mbar_expect_tx(bars + 8 * B_KV, KV_J * 4);
          bulk_load(sb + OFF_MISC, accg + j * KV_J, KV_J * 4, bars + 8 * B_KV);
          TSTAMPX(22);
        }
        __syncwarp();
#pragma unroll 1
        for (int m = 0; m < 6; m++) {
          const int col = 192 * j + 32 * m + 8 * (lane & 3);
          const __nv_bfloat16* p = w3 + (size_t)(40 * i + (lane >> 2) * 5) * F_ + col;
          float a[8];
#pragma unroll
          for (int e = 0; e < 8; e++) a[e] = 0.f;
#pragma unroll
          for (int it = 0; it < 5; it++) {
            const uint4 v = __ldg(reinterpret_cast<const uint4*>(p + (size_t)it * F_));
            a[0] += bf_lo(v.x); a[1] += bf_hi(v.x); a[2] += bf_lo(v.y); a[3] += bf_hi(v.y);
            a[4] += bf_lo(v.z); a[5] += bf_hi(v.z); a[6] += bf_lo(v.w); a[7] += bf_hi(v.w);
          }
#pragma unroll
          for (int e = 0; e < 4; e++) {
            const float snd = (lane & 4) ? a[e] : a[e + 4], keep = (lane & 4) ? a[e + 4] : a[e];
            a[e] = keep + __shfl_xor_sync(0xffffffffu, snd, 4);
            a[e] += __shfl_xor_sync(0xffffffffu, a[e], 8);
            a[e] += __shfl_xor_sync(0xffffffffu, a[e], 16);
          }
          if (lane < 8) red_add4(accg + 8 * KV_J + D_ + col + (lane >> 2) * 4, a[0], a[1], a[2], a[3]);
        }
        __syncwarp();
        if (lane == 0) {
          flag_add(FL_CS3 + j);
          mbar_wait(bars + 8 * B_MFREE, 0);
          flag_wait(FL_X1 + i, (epoch + 1) * 8u);
          flag_wait(FL_CS3 + j, (epoch + 1) * 16u);
          fence_async_all();
          mbar_expect_tx(bars + 8 * B_ST1, 8192 + 768);
          bulk_load(sb + OFF_CS + 320, accg + 8 * KV_J + D_ + 192 * j, 768, bars + 8 * B_ST1);
          bulk_load(sb + OFF_MISC, g_st1 + 128 * i * 8, 8192, bars + 8 * B_ST1);
        }
        __syncwarp();
        mbar_wait(bars + 8 * B_PEER, 0);
        const unsigned* fp = g_flags + (FL_PART + i * 8 + j) * 32 + lane;
        bool seen = lane >= 6;
        uint32_t n = 0;
        while (!__all_sync(0xffffffffu, seen) && ++n < (WAIT_LIMIT >> 4)) {
          if (!seen && ld_acquire(fp) == epoch + 1 && (lane < 2 || (lane < 4 ? mbar_test(bars + 8 * (B_SEND + 2), 0) && mbar_test(bars + 8 * (B_SEND + 3), 0) && mbar_test(bars + 8 * (B_EMPTY4 + 1), 0) : mbar_test(bars + 8 * (B_SDONE + lane), 0)))) {
            seen = true;
            if (lane & 1) TR4((lane >> 1) * 16 + 11);
            mbar_expect_tx(bars + 8 * (B_RDY + lane), 10240);
            bulk_load(sb + (lane < 2 ? OFF_G0 : lane < 4 ? OFF_G1 : OFF_SEND) + (lane & 1) * 10240, g_part + (size_t)(i * 8 + j) * 3840 + lane * 640, 10240,
                      bars + 8 * (B_RDY + lane));
          }
        }
      } else {
        mbar_wait(bars + 8 * B_SIGP, 0);
        if (lane < 20) {
          float a0 = 0.f, a1 = 0.f, a2 = 0.f, a3 = 0.f;
#pragma unroll 4
          for (int r = 0; r < 20; r++) {
            const uint4 v = lds128(sb + OFF_B + SPARE + r * 320 + lane * 16);
            a0 += __uint_as_float(v.x); a1 += __uint_as_float(v.y); a2 += __uint_as_float(v.z); a3 += __uint_as_float(v.w);
          }
          red_add4(accg + 8 * KV_J + 80 * j + 4 * lane, a0, a1, a2, a3);
        }
        __syncwarp();
      }
      if (pw == 3 && lane == 0) {
        flag_add(FL_CS + j); flag_add_relaxed(FL_ST + i);
        TSTAMPX(20);
        mbar_expect_tx(bars + 8 * B_XR, 20480);
#pragma unroll 1
        for (int u = 0; u < 8; u++)
          tma2d(sb + OFF_B + (u / 3) * SLOT_B + SPARE + (u % 3) * 2560, &maps.xr, bars + 8 * B_XR, 80 * j, 128 * i + 16 * u);
        const int shift = (j < 2) ? 1 : (j < 4) ? -1 : (j < 6) ? 2 : -2;
        if ((shift > 0 && i == 0) || (shift < 0 && i == 15)) {
          const int nz = shift > 0 ? shift : -shift, zr = shift > 0 ? 0 : S_ - nz;
#pragma unroll 1
          for (int e = 0; e < nz * 10; e++)
            reinterpret_cast<uint4*>(g_Hs + (size_t)(2 + zr + e / 10) * D_ + 80 * j)[e % 10] = make_uint4(0, 0, 0, 0);
          fence_async_all();
        }
        prefetch_tmap(&maps.st_h); prefetch_tmap(&maps.st_x1); prefetch_tmap(&maps.hs); prefetch_tmap(&maps.x1); prefetch_tmap(&maps.xr);
        prefetch_tmap(&maps.w2); prefetch_tmap(&maps.w3); prefetch_tmap(&maps.w4); prefetch_tmap(&maps.wo); prefetch_tmap(&maps.st_out);
        mbar_wait(bars + 8 * B_SIGH, 0);
        TSTAMPX(23);
        tma2d_store(&maps.st_h, sb + OFF_STG, 80 * j, 128 * i + 2 + shift);
        tma2d_store(&maps.st_h, sb + OFF_STG + 10240, 80 * j, 128 * i + 66 + shift);
        bulk_commit(); bulk_wait<0>();
        flag_add(FL_H + i);
        TSTAMPX(24);
        mbar_wait(bars + 8 * B_SIGKV, 0);
        TSTAMPX(25);
        asm volatile("cp.reduce.async.bulk.global.shared::cta.bulk_group.add.f32 [%0], [%1], %2;"
                     ::"l"(accg + j * KV_J), "r"(sb + OFF_MISC), "r"(KV_J * 4) : "memory");
        bulk_commit(); bulk_wait<0>();
        flag_add(FL_KV + j);
        TSTAMPX(26);
        mbar_wait(bars + 8 * B_SIGX1, 0);
        TSTAMPX(27);
        tma2d_store(&maps.st_x1, sb + OFF_STG, 80 * j, 128 * i);
        tma2d_store(&maps.st_x1, sb + OFF_STG + 10240, 80 * j, 128 * i + 64);
        bulk_commit(); bulk_wait<0>();
        flag_add(FL_X1 + i);
        TSTAMPX(28);
        send_stream(0, epoch + 1);
      }
    }
  } else {
    asm volatile("setmaxnreg.inc.sync.aligned.u32 232;");
    const int wg = tid >> 7, warp = tid >> 5, lane = tid & 31, t = lane & 3;
    const int rloc = warp * 16 + (lane >> 2);
    const float* s_cs = reinterpret_cast<const float*>(sgen + OFF_CS);
    auto signal = [&](int b) {
      __syncwarp();
      if (lane == 0) mbar_arrive(bars + 8 * b);
    };
    auto releaseB = [&](uint32_t bar) {
      __syncwarp();
      if (lane == 0) mbar_arrive(bar);
    };
    auto release = [&](uint32_t bar) {
      __syncwarp();
      if (lane < 2) mbar_arrive_cta(bar, lane);
    };
    const uint32_t stg_lane = (warp * 16 + ((lane >> 3) & 1) * 8 + (lane & 7)) * 160 + (lane >> 4) * 16;

    {
#pragma unroll 1
      for (int e = tid; e < 800; e += 256) sts128(sb + OFF_MISC + e * 16, make_uint4(0, 0, 0, 0));
      bar_sync(1, 256);
      float f[40];
      float s = 0.f, gs = 0.f;
#pragma unroll
      for (int c = 0; c < 5; c++) {
        const uint32_t vv[4] = {pv[c].x, pv[c].y, pv[c].z, pv[c].w}, ww[4] = {pw_[c].x, pw_[c].y, pw_[c].z, pw_[c].w};
#pragma unroll
        for (int e = 0; e < 4; e++) {
          f[8 * c + 2 * e] = bf_lo(vv[e]); f[8 * c + 2 * e + 1] = bf_hi(vv[e]);
          s += f[8 * c + 2 * e] + f[8 * c + 2 * e + 1];
          gs = fmaf(f[8 * c + 2 * e], bf_lo(ww[e]), gs); gs = fmaf(f[8 * c + 2 * e + 1], bf_hi(ww[e]), gs);
        }
      }
#pragma unroll
      for (int o = 1; o < 16; o <<= 1) { s += __shfl_xor_sync(0xffffffffu, s, o); gs += __shfl_xor_sync(0xffffffffu, gs, o); }
      const float mean = s * (1.f / D_);
      float q = 0.f;
#pragma unroll
      for (int e = 0; e < 40; e++) { const float d = f[e] - mean; q = fmaf(d, d, q); }
#pragma unroll
      for (int o = 1; o < 16; o <<= 1) q += __shfl_xor_sync(0xffffffffu, q, o);
      const float rstd = rsqrtf(q * (1.f / D_) + 1e-5f);
      if (tid < 200) {
        const uint32_t cd = sb + OFF_B + SPARE + tid * 32;
        sts128(cd, make_uint4(__float_as_uint(bf_lo(pc[0].x) + bf_lo(pc[1].x)), __float_as_uint(bf_hi(pc[0].x) + bf_hi(pc[1].x)),
                              __float_as_uint(bf_lo(pc[0].y) + bf_lo(pc[1].y)), __float_as_uint(bf_hi(pc[0].y) + bf_hi(pc[1].y))));
        sts128(cd + 16, make_uint4(__float_as_uint(bf_lo(pc[0].z) + bf_lo(pc[1].z)), __float_as_uint(bf_hi(pc[0].z) + bf_hi(pc[1].z)),
                                   __float_as_uint(bf_lo(pc[0].w) + bf_lo(pc[1].w)), __float_as_uint(bf_hi(pc[0].w) + bf_hi(pc[1].w))));
        const uint32_t ww[4] = {pre.x, pre.y, pre.z, pre.w};
        const int h = tid / 50;
#pragma unroll
        for (int e = 0; e < 8; e++) {
          const int idx = tid * 8 + e, k = idx / 20, ff = idx - 20 * k;
          const int n = 40 * (h >> 1) + 8 * (ff >> 2) + 2 * (ff & 3) + (h & 1);
          const int off = (k >> 4) * 2560 + n * 32 + ((((k >> 3) ^ (n >> 2)) & 1) << 4) + (k & 7) * 2;
          *reinterpret_cast<unsigned short*>(sgen + OFF_MISC + off) = (unsigned short)(ww[e >> 1] >> ((e & 1) * 16));
        }
      }
      fence_async_smem();
      asm volatile("barrier.cluster.wait.aligned;" ::: "memory");
      if ((tid & 15) == 0) g_xstat[128 * i + 16 * j + (tid >> 4)] = make_float4(rstd, -mean * rstd, rcp(1.f + __expf(-gs)), 0.f);
      signal(B_SIGP);
      bar_sync(1, 256);
    }
    TSTAMP(1);

    Ring ra{0, 0}, rb{0, 0};
    uint32_t qp[2][10], P[2][10];
    float st_g[2];
    {
      float accM[128], accR[32];
      zero_regs(accM); zero_regs(accR);
      uint32_t pa = 0, pb = 0;
#pragma unroll 1
      for (int k = 0; k < 10; k++) {
        mbar_wait(fullA + 8 * ra.idx, ra.phase);
        if (tid == 0) TRACE(32 + k);
        mbar_wait(fullB + 8 * rb.idx, rb.phase);
        if (tid == 0) TRACE(64 + k);
        if (k == 0) TSTAMP(2);
        const uint32_t a0 = sb16 + ((OFF_A + ra.idx * SLOT_A + wg * 8192) >> 4), b0 = sb16 + ((OFF_B + rb.idx * SLOT_B) >> 4);
        wg_fence();
#pragma unroll
        for (int kk = 0; kk < 4; kk++) {
          const uint64_t da = make_desc(a0, kk * 32, 16, 1024, 1);
          mma_ss256(accM, da, make_desc(b0, kk * 2048, 8192, 1024, 1));
          mma_ss64(accR, da, make_desc(b0, 32768 + kk * 512, 2048, 256, 3));
          if (kk == 0) {
            wg_commit();
            if (k > 0) {
              wg_wait<1>();
              if (k - 1 < 8) release(emptyA + 8 * pa);
              releaseB(emptyB + 8 * pb);
            }
          }
        }
        wg_commit();
        pa = ra.idx; pb = rb.idx;
        ra.next<NA>(); rb.next<NB>();
      }
      TSTAMP(18);
      float st_rstd[2], st_mr[2];
      mbar_wait(bars + 8 * B_CS, 0);
#pragma unroll
      for (int r = 0; r < 2; r++) {
        const uint4 st = lds128(sb + OFF_XST + (rloc + 8 * r) * 16);
        st_rstd[r] = __uint_as_float(st.x); st_mr[r] = __uint_as_float(st.y); st_g[r] = __uint_as_float(st.z);
      }
      TSTAMP(19);
      wg_wait<0>();
      fence_regs(accM); fence_regs(accR);
      TSTAMP(3);
#define ACC(P_, G, I_) ((G) < 8 ? accM[(P_) * 32 + ((G) & 7) * 4 + (I_)] : accR[(P_) * 8 + ((G) & 1) * 4 + (I_)])
      uint32_t kf[5][4];
#pragma unroll
      for (int s = 0; s < 5; s++) {
        kf[s][0] = pack_bf16(ACC(2, 2 * s, 0), ACC(2, 2 * s, 1)); kf[s][1] = pack_bf16(ACC(2, 2 * s, 2), ACC(2, 2 * s, 3));
        kf[s][2] = pack_bf16(ACC(2, 2 * s + 1, 0), ACC(2, 2 * s + 1, 1)); kf[s][3] = pack_bf16(ACC(2, 2 * s + 1, 2), ACC(2, 2 * s + 1, 3));
      }
      float pk[40], pq[40];
      wg_fence();
#pragma unroll
      for (int s = 0; s < 5; s++) {
        if (s == 0) mma_rs80_k_z(pk, kf[s], make_desc(sb16, OFF_MISC, 16, 256, 3));
        else mma_rs80_k(pk, kf[s], make_desc(sb16, OFF_MISC + s * 2560, 16, 256, 3));
      }
      wg_commit();

      {
        uint32_t hv[10][2];
#pragma unroll
        for (int g = 0; g < 10; g++) {
          const float2 cs = *reinterpret_cast<const float2*>(s_cs + 8 * g + 2 * t);
          const float v0 = gelu_s(fmaf(ACC(0, g, 0), st_rstd[0], st_mr[0] * cs.x), 0.5f), v1 = gelu_s(fmaf(ACC(0, g, 1), st_rstd[0], st_mr[0] * cs.y), 0.5f);
          const float v2 = gelu_s(fmaf(ACC(0, g, 2), st_rstd[1], st_mr[1] * cs.x), 0.5f), v3 = gelu_s(fmaf(ACC(0, g, 3), st_rstd[1], st_mr[1] * cs.y), 0.5f);
          hv[g][0] = pack_bf16(v0, v1); hv[g][1] = pack_bf16(v2, v3);
        }
        bar_sync(1, 256);
#pragma unroll
        for (int s = 0; s < 5; s++) stsm4(sb + OFF_STG + stg_lane + s * 32, hv[2 * s][0], hv[2 * s][1], hv[2 * s + 1][0], hv[2 * s + 1][1]);
        fence_async_smem();
        signal(B_SIGH);
      }
      TSTAMP(4);
      uint32_t qf[5][4];
#pragma unroll
      for (int s = 0; s < 5; s++) {
        qf[s][0] = pack_bf16(ACC(1, 2 * s, 0), ACC(1, 2 * s, 1)); qf[s][1] = pack_bf16(ACC(1, 2 * s, 2), ACC(1, 2 * s, 3));
        qf[s][2] = pack_bf16(ACC(1, 2 * s + 1, 0), ACC(1, 2 * s + 1, 1)); qf[s][3] = pack_bf16(ACC(1, 2 * s + 1, 2), ACC(1, 2 * s + 1, 3));
      }
      wg_fence();
#pragma unroll
      for (int s = 0; s < 5; s++) {
        if (s == 0) mma_rs80_k_z(pq, qf[s], make_desc(sb16, OFF_MISC, 16, 256, 3));
        else mma_rs80_k(pq, qf[s], make_desc(sb16, OFF_MISC + s * 2560, 16, 256, 3));
      }
      wg_commit();
      {
        const int mat = lane >> 3;
        const int tok = warp * 16 + (mat & 1) * 8 + (lane & 7);
        const uint32_t ones = (t == 0) ? 0x00003f80u : 0u;
        __syncwarp();
#pragma unroll
        for (int p = 0; p < 2; p++) {
          const uint32_t rowa = sb + OFF_A + p * SLOT_A + tok * 128;
#pragma unroll
          for (int gg = 0; gg < 3; gg++) {
            const int g0 = 5 * p + 2 * gg;
            uint32_t r0 = pack_bf16(ACC(3, g0, 0), ACC(3, g0, 1)), r1 = pack_bf16(ACC(3, g0, 2), ACC(3, g0, 3));
            uint32_t r2 = ones, r3 = ones;
            if (gg < 2) { r2 = pack_bf16(ACC(3, g0 + 1, 0), ACC(3, g0 + 1, 1)); r3 = pack_bf16(ACC(3, g0 + 1, 2), ACC(3, g0 + 1, 3)); }
            stsm4(rowa + (((2 * gg + (mat >> 1)) ^ (tok & 7)) << 4), r0, r1, r2, r3);
          }
        }
      }
#undef ACC
      wg_wait<0>();
      fence_regs(pk); fence_regs(pq);
#pragma unroll
      for (int G = 0; G < 10; G++) {
        P[0][G] = pack_bf16(pk[4 * G], pk[4 * G + 1]); P[1][G] = pack_bf16(pk[4 * G + 2], pk[4 * G + 3]);
        qp[0][G] = pack_bf16(pq[4 * G], pq[4 * G + 1]); qp[1][G] = pack_bf16(pq[4 * G + 2], pq[4 * G + 3]);
      }
    }

    uint32_t fr[10][4];
    {
      TSTAMP(16);
      feature_map(P, fr);
      TSTAMP(17);
      const int mat = lane >> 3;
      const int tok = warp * 16 + (mat & 1) * 8 + (lane & 7);
      const uint32_t base = sb + OFF_B + tok * 32 + (((mat >> 1) ^ ((tok >> 2) & 1)) << 4);
#pragma unroll
      for (int G = 0; G < 10; G++) stsm4(base + G * 4096, fr[G][0], fr[G][1], fr[G][2], fr[G][3]);
      fence_async_smem();
      bar_sync(1, 256);
      float kv[40];
      const uint32_t a0 = sb16 + ((OFF_A + wg * SLOT_A) >> 4), b0 = sb16 + ((OFF_B + wg * 20480) >> 4);
      wg_fence();
#pragma unroll
      for (int ks = 0; ks < 8; ks++) {
        if (ks == 0) mma_ss80_tt_z(kv, make_desc(a0, 0, 16, 1024, 1), make_desc(b0, 0, 4096, 256, 3));
        else mma_ss80_tt(kv, make_desc(a0, ks * 2048, 16, 1024, 1), make_desc(b0, ks * 512, 4096, 256, 3));
      }
      wg_commit();
      wg_wait<0>();
      fence_regs(kv);
      TSTAMP(31);
      release(emptyA); release(emptyA + 8); releaseB(emptyB);
      const uint32_t dst = sb + OFF_MISC + wg * (KV_PAIR * 4);
      const int m0 = (warp & 3) * 16 + (lane >> 2);
#pragma unroll
      for (int r = 0; r < 2; r++) {
        const int m = m0 + 8 * r;
        const bool hi = m >= 20;
        uint32_t v[10];
#pragma unroll
        for (int G = 0; G < 10; G++) v[G] = __float_as_uint(hi ? kv[4 * G + 2 * r + 1] : kv[4 * G + 2 * r]);
        const uint32_t p = dst + 4 * (m < 40 ? m * 48 + t * 12 : 1920 + t * 24 + 12);
        if (m <= 40) {
          sts128(p, make_uint4(v[0], v[1], v[2], v[3])); sts128(p + 16, make_uint4(v[4], v[5], v[6], v[7]));
          sts128(p + 32, make_uint4(v[8], v[9], 0u, 0u));
        }
      }
      if (m0 == 32) {
        const uint32_t p = dst + 4 * (1920 + t * 24);
        sts128(p, make_uint4(__float_as_uint(kv[2]), __float_as_uint(kv[6]), __float_as_uint(kv[10]), __float_as_uint(kv[14])));
        sts128(p + 16, make_uint4(__float_as_uint(kv[18]), __float_as_uint(kv[22]), __float_as_uint(kv[26]), __float_as_uint(kv[30])));
        sts128(p + 32, make_uint4(__float_as_uint(kv[34]), __float_as_uint(kv[38]), 0u, 0u));
      }
      fence_async_smem();
      signal(B_SIGKV);
    }
    TSTAMP(5);

    uint32_t xv[2][10];
    {
      {
        mbar_wait(bars + 8 * B_XR, 0);
        const uint32_t xa = sb + OFF_B + (warp / 3) * SLOT_B + SPARE + (warp % 3) * 2560 + (lane >> 2) * 160 + t * 4;
#pragma unroll
        for (int g = 0; g < 10; g++) { xv[0][g] = lds32(xa + g * 16); xv[1][g] = lds32(xa + 1280 + g * 16); }
      }
      float acc[40];
      zero_regs(acc);
      uint32_t pa = 0, pb = 0;
#pragma unroll 1
      for (int k = 0; k < 10; k++) {
        mbar_wait(fullA + 8 * ra.idx, ra.phase);
        if (tid == 0) TRACE(42 + k);
        if ((k & 3) == 0) mbar_wait(fullB + 8 * rb.idx, rb.phase);
        if (tid == 0) TRACE(74 + k);
        if (k == 0) TSTAMP(6);
        const uint32_t a0 = sb16 + ((OFF_A + ra.idx * SLOT_A + wg * 8192) >> 4);
        const uint32_t b0 = sb16 + ((OFF_B + rb.idx * SLOT_B + (k & 3) * 10240) >> 4);
        wg_fence();
#pragma unroll
        for (int kk = 0; kk < 4; kk++) {
          mma_ss80(acc, make_desc(a0, kk * 32, 16, 1024, 1), make_desc(b0, kk * 512, 2048, 256, 3));
          if (kk == 1) {
            wg_commit();
            if (k > 0) {
              wg_wait<1>();
              release(emptyA + 8 * pa);
              if ((k & 3) == 0) releaseB(emptyB + 8 * pb);
            }
          }
        }
        wg_commit();
        pa = ra.idx; pb = rb.idx;
        ra.next<NA>();
        if ((k & 3) == 3 || k == 9) rb.next<NB>();
      }
      wg_wait<0>();
      fence_regs(acc);
      release(emptyA + 8 * pa); releaseB(emptyB + 8 * pb);
      TSTAMP(7);
#pragma unroll
      for (int r = 0; r < 2; r++) {
#pragma unroll
        for (int g = 0; g < 10; g++)
          xv[r][g] = pack_bf16(bf_lo(xv[r][g]) + acc[4 * g + 2 * r], bf_hi(xv[r][g]) + acc[4 * g + 2 * r + 1]);
      }
      bar_sync(1, 256);
#pragma unroll
      for (int s = 0; s < 5; s++) stsm4(sb + OFF_STG + stg_lane + s * 32, xv[0][2 * s], xv[1][2 * s], xv[0][2 * s + 1], xv[1][2 * s + 1]);
#pragma unroll
      for (int r = 0; r < 2; r++) {
        float s = 0.f;
#pragma unroll
        for (int g = 0; g < 10; g++) {
          acc[4 * g + 2 * r] = bf_lo(xv[r][g]); acc[4 * g + 2 * r + 1] = bf_hi(xv[r][g]);
          s += acc[4 * g + 2 * r] + acc[4 * g + 2 * r + 1];
        }
        s += __shfl_xor_sync(0xffffffffu, s, 1); s += __shfl_xor_sync(0xffffffffu, s, 2);
        const float mu = s * (1.f / 80.f);
        float q = 0.f;
#pragma unroll
        for (int g = 0; g < 10; g++) {
          const float d0 = acc[4 * g + 2 * r] - mu, d1 = acc[4 * g + 2 * r + 1] - mu;
          q = fmaf(d0, d0, q); q = fmaf(d1, d1, q);
        }
        q += __shfl_xor_sync(0xffffffffu, q, 1); q += __shfl_xor_sync(0xffffffffu, q, 2);
        if (t == 0) g_st1[(128 * i + rloc + 8 * r) * 8 + j] = make_float2(mu, q);
      }
      fence_async_smem();
      signal(B_SIGX1);
    }
    TSTAMP(8);

    uint32_t of[5][4];
    {
      feature_map(qp, fr);
      mbar_wait(bars + 8 * B_KV, 0);
      uint4 kvr[2][3];
#pragma unroll
      for (int u = 0; u < 2; u++) {
        const int it = tid + 256 * u, p = it / 192, rem = it - 192 * p, n = rem >> 2, tq = rem & 3;
        const uint32_t sp = sb + OFF_MISC + 4 * (p * KV_PAIR + (n < 40 ? n * 48 + tq * 12 : 1920 + tq * 24 + (n & 1) * 12));
        if (it < 384) { kvr[u][0] = lds128(sp); kvr[u][1] = lds128(sp + 16); kvr[u][2] = lds128(sp + 32); }
      }
      bar_sync(1, 256);
#pragma unroll
      for (int u = 0; u < 2; u++) {
        const int it = tid + 256 * u, p = it / 192, rem = it - 192 * p, n = rem >> 2, tq = rem & 3;
        const int sh = (n < 40 ? (n >= 20) : (n & 1)) * 16;
        const uint32_t v[10] = {kvr[u][0].x, kvr[u][0].y, kvr[u][0].z, kvr[u][0].w, kvr[u][1].x, kvr[u][1].y, kvr[u][1].z, kvr[u][1].w, kvr[u][2].x, kvr[u][2].y};
        uint8_t* dst = sgen + OFF_MISC + p * 7680 + n * 32 + tq * 4;
        const int sw = ((n >> 2) & 1) << 4;
        if (it < 384) {
#pragma unroll
          for (int G = 0; G < 10; G++)
            *reinterpret_cast<uint32_t*>(dst + (G >> 1) * 1536 + (((G & 1) << 4) ^ sw)) = pack_bf16(__uint_as_float(v[G]), 0.f) << sh;
        }
      }
      fence_async_smem();
      bar_sync(1, 256);
      float o0[24], o1[24];
      wg_fence();
#pragma unroll
      for (int g = 0; g < 5; g++) {
        if (g == 0) mma_rs48_k_z(o0, fr[g], make_desc(sb16, OFF_MISC, 16, 256, 3));
        else mma_rs48_k(o0, fr[g], make_desc(sb16, OFF_MISC + g * 1536, 16, 256, 3));
      }
#pragma unroll
      for (int g = 0; g < 5; g++) {
        if (g == 0) mma_rs48_k_z(o1, fr[5], make_desc(sb16, OFF_MISC + 7680, 16, 256, 3));
        else mma_rs48_k(o1, fr[5 + g], make_desc(sb16, OFF_MISC + 7680 + g * 1536, 16, 256, 3));
      }
      wg_commit();
      wg_wait<0>();
      fence_regs(o0); fence_regs(o1);
      signal(B_MFREE);
#pragma unroll
      for (int r = 0; r < 2; r++) {
        const float a0 = __fdividef(st_g[r], o0[20 + 2 * r] + 1e-6f), a1 = __fdividef(st_g[r], o0[21 + 2 * r] + 1e-6f);
        const float b0 = __fdividef(st_g[r], o1[20 + 2 * r] + 1e-6f), b1 = __fdividef(st_g[r], o1[21 + 2 * r] + 1e-6f);
        const float am = t < 2 ? a0 : a1, bm = t < 2 ? b0 : b1;
#pragma unroll
        for (int g = 0; g < 5; g++) {
          const float sa = g < 2 ? a0 : (g == 2 ? am : a1), sb2 = g < 2 ? b0 : (g == 2 ? bm : b1);
          of[g >> 1][(g & 1) * 2 + r] = pack_bf16(o0[4 * g + 2 * r] * sa, o0[4 * g + 2 * r + 1] * sa);
          of[(5 + g) >> 1][((5 + g) & 1) * 2 + r] = pack_bf16(o1[4 * g + 2 * r] * sb2, o1[4 * g + 2 * r + 1] * sb2);
        }
      }
    }
    TSTAMP(9);

    uint32_t hf[12][4];
    {
      float acc[96];
      zero_regs(acc);
      uint32_t pa = 0, pb = 0;
#pragma unroll 1
      for (int k = 0; k < 10; k++) {
        mbar_wait(fullA + 8 * ra.idx, ra.phase);
        if (tid == 0) TRACE(52 + k);
        if ((k & 1) == 0) mbar_wait(fullB + 8 * rb.idx, rb.phase);
        if (tid == 0) TRACE(84 + k);
        if (k == 0) TSTAMP(10);
        const uint32_t a0 = sb16 + ((OFF_A + ra.idx * SLOT_A + wg * 8192) >> 4);
        const uint32_t b0 = sb16 + ((OFF_B + rb.idx * SLOT_B + (k & 1) * 24576) >> 4);
        wg_fence();
#pragma unroll
        for (int kk = 0; kk < 4; kk++) {
          mma_ss192(acc, make_desc(a0, kk * 32, 16, 1024, 1), make_desc(b0, kk * 2048, 8192, 1024, 1));
          if (kk == 0) {
            wg_commit();
            if (k > 0) {
              wg_wait<1>();
              release(emptyA + 8 * pa);
              if ((k & 1) == 0) releaseB(emptyB + 8 * pb);
            }
          }
        }
        wg_commit();
        pa = ra.idx; pb = rb.idx;
        ra.next<NA>();
        if (k & 1) rb.next<NB>();
      }
      float rs[2], mm[2];
      mbar_wait(bars + 8 * B_ST1, 0);
#pragma unroll
      for (int r = 0; r < 2; r++) {
        const uint4 su = lds128(sb + OFF_MISC + (rloc + 8 * r) * 64 + t * 16);
        const float m0 = __uint_as_float(su.x), m1 = __uint_as_float(su.z);
        float mu = m0 + m1;
        mu += __shfl_xor_sync(0xffffffffu, mu, 1); mu += __shfl_xor_sync(0xffffffffu, mu, 2);
        mu *= 0.125f;
        const float d0 = m0 - mu, d1 = m1 - mu;
        float q = __uint_as_float(su.y) + __uint_as_float(su.w) + 80.f * (d0 * d0 + d1 * d1);
        q += __shfl_xor_sync(0xffffffffu, q, 1); q += __shfl_xor_sync(0xffffffffu, q, 2);
        rs[r] = rsqrtf(q * (1.f / D_) + 1e-5f);
        mm[r] = -mu * rs[r];
      }
      wg_wait<0>();
      fence_regs(acc);
      releaseB(emptyB + 8 * pb);
      release(bars + 8 * B_PEER);
      TSTAMP(11);
      const float hs0 = 0.5f - 0.5f * st_g[0], hs1 = 0.5f - 0.5f * st_g[1];
#pragma unroll
      for (int g = 0; g < 24; g++) {
        const float2 cs = *reinterpret_cast<const float2*>(s_cs + 80 + 8 * g + 2 * t);
        const float v0 = gelu_s(fmaf(acc[4 * g], rs[0], mm[0] * cs.x), hs0), v1 = gelu_s(fmaf(acc[4 * g + 1], rs[0], mm[0] * cs.y), hs0);
        const float v2 = gelu_s(fmaf(acc[4 * g + 2], rs[1], mm[1] * cs.x), hs1), v3 = gelu_s(fmaf(acc[4 * g + 3], rs[1], mm[1] * cs.y), hs1);
        hf[g >> 1][(g & 1) * 2] = pack_bf16(v0, v1);
        hf[g >> 1][(g & 1) * 2 + 1] = pack_bf16(v2, v3);
      }
    }
    TSTAMP(12);

    {
      float acc[80], kp[40];
      const int wt = tid & 127;
      const uint32_t peer = map_peer(sb, rank ^ 1);
      Ring r4{0, 0};
      auto add16 = [&](uint32_t src) {
#pragma unroll
        for (int q = 0; q < 5; q++) {
          const uint4 v = lds128(src + q * 2048);
          float* d = &kp[8 * q];
          d[0] += bf_lo(v.x); d[1] += bf_hi(v.x); d[2] += bf_lo(v.y); d[3] += bf_hi(v.y);
          d[4] += bf_lo(v.z); d[5] += bf_hi(v.z); d[6] += bf_lo(v.w); d[7] += bf_hi(v.w);
        }
      };
      auto finish = [&](int c) {
        if (c > 1) mbar_wait(bars + 8 * (B_SDONE + 2 * (c - 2) + wg), 0);
        mbar_wait(bars + 8 * (B_DSR + 2 * (c - 1) + wg), 0);
        if (tid == 128) TR4((c - 1) * 16 + 3);
        add16(sb + OFF_DS + ((c - 1) & 1) * 20480 + wg * 10240 + wt * 16);
        const uint32_t dst = sb + OFF_SEND + wg * 10240 + wt * 16;
#pragma unroll
        for (int q = 0; q < 5; q++) {
          const float* d = &kp[8 * q];
          sts128(dst + q * 2048, make_uint4(pack_bf16(d[0], d[1]), pack_bf16(d[2], d[3]), pack_bf16(d[4], d[5]), pack_bf16(d[6], d[7])));
        }
        fence_async_smem();
        signal(B_SEND + 2 * (c - 1) + wg);
        if (tid == 128) TR4((c - 1) * 16 + 6);
      };
      zero_regs(kp);
      if (wg == 1) bar_sync(2, 256);
#pragma unroll 1
      for (int c = 0; c < 4; c++) {
        uint32_t prev = 0;
#pragma unroll
        for (int u = 0; u < 4; u++) {
          mbar_wait(bars + 8 * (B_FULL4 + r4.idx), r4.phase);
          const uint32_t b0 = sb16 + ((OFF_B + r4.idx * UNIT4) >> 4);
          if (u == 0 && tid == 128) TR4(c * 16 + 0);
          wg_fence();
#pragma unroll
          for (int s = 0; s < (u < 3 ? 4 : 5); s++) {
            const uint64_t db = make_desc(b0, s * 1024, u < 3 ? 4096 : 5120, 512, 2);
            if (u == 0 && s == 0) mma_rs160_n_z(acc, hf[0], db);
            else if (u < 3) mma_rs160_n(acc, hf[(4 * u + s) % 12], db);
            else mma_rs160_n(acc, of[s], db);
            if (s == 1 && u > 0) { wg_commit(); wg_wait<1>(); releaseB(bars + 8 * (B_EMPTY4 + prev)); }
          }
          wg_commit();
          prev = r4.idx;
          r4.next<NU4>();
          if (u == 1 && c == 0 && wg == 0) bar_arrive(2, 256);
          if (u == 0 && c > 0) finish(c);
          if (u == 2) {
            if (c == 3) {
              const float w0 = 1.f - st_g[0], w1s = 1.f - st_g[1];
#pragma unroll
              for (int g = 0; g < 10; g++) {
                kp[4 * g] = w0 * bf_lo(xv[0][g]); kp[4 * g + 1] = w0 * bf_hi(xv[0][g]);
                kp[4 * g + 2] = w1s * bf_lo(xv[1][g]); kp[4 * g + 3] = w1s * bf_hi(xv[1][g]);
              }
#pragma unroll 1
              for (int e = 0; e < 2; e++) {
                mbar_wait(bars + 8 * (B_RDY + 2 * e + wg), 0);
                add16(sb + (e == 0 ? OFF_G0 : OFF_G1) + wg * 10240 + wt * 16);
              }
            } else {
              zero_regs(kp);
            }
          }
        }
        if (tid == 128) TR4(c * 16 + 2);
        if (c == 0) mbar_wait(bars + 8 * B_PEER, 0);
        wg_wait<0>();
        fence_regs(acc);
        releaseB(bars + 8 * (B_EMPTY4 + prev));
        if (tid == 128) TR4(c * 16 + 5);
        uint32_t sn[20];
        if (rank) {
#pragma unroll
          for (int e = 0; e < 20; e++) sn[e] = pack_bf16(acc[2 * e], acc[2 * e + 1]);
#pragma unroll
          for (int e = 0; e < 40; e++) kp[e] += acc[40 + e];
        } else {
#pragma unroll
          for (int e = 0; e < 20; e++) sn[e] = pack_bf16(acc[40 + 2 * e], acc[41 + 2 * e]);
#pragma unroll
          for (int e = 0; e < 40; e++) kp[e] += acc[e];
        }
        fence_regs(kp);
        const uint32_t dso = peer + OFF_DS + (c & 1) * 20480 + wg * 10240 + wt * 16, dsb = peer + OFF_BAR + 8 * (B_DSR + 2 * c + wg);
#pragma unroll
        for (int q = 0; q < 5; q++) st_async16(dso + q * 2048, sn[4 * q], sn[4 * q + 1], sn[4 * q + 2], sn[4 * q + 3], dsb);
      }
      TSTAMP(13);
#pragma unroll 1
      for (int c = 0; c < 2; c++) {
        mbar_wait(bars + 8 * ((c == 0 ? B_DSR + 6 : B_RDY + 4) + wg), 0);
        add16(sb + (c == 0 ? OFF_DS + 20480 : OFF_SEND) + wg * 10240 + wt * 16);
      }
      TSTAMP(14);
#pragma unroll
      for (int s = 0; s < 5; s++)
        stsm4(sb + OFF_DS + stg_lane + s * 32, pack_bf16(kp[8 * s], kp[8 * s + 1]), pack_bf16(kp[8 * s + 2], kp[8 * s + 3]),
              pack_bf16(kp[8 * s + 4], kp[8 * s + 5]), pack_bf16(kp[8 * s + 6], kp[8 * s + 7]));
      fence_async_smem();
      __syncwarp();
      if (lane == 0) {
        tma2d_store(&maps.st_out, sb + OFF_DS + warp * 2560, 80 * j, 128 * i + 16 * warp);
        bulk_commit(); bulk_wait_read();
      }
    }
    TSTAMP(15);
    if (tid == 0) asm volatile("red.relaxed.gpu.global.add.u32 [%0], 1;" ::"l"(g_flags + FL_DONE * 32) : "memory");
  }
}

namespace {
typedef CUresult (*EncodeFn)(CUtensorMap*, CUtensorMapDataType, cuuint32_t, void*, const cuuint64_t*, const cuuint64_t*,
                             const cuuint32_t*, const cuuint32_t*, CUtensorMapInterleave, CUtensorMapSwizzle,
                             CUtensorMapL2promotion, CUtensorMapFloatOOBfill);

void encode(EncodeFn fn, CUtensorMap* m, const void* ptr, int rank, const cuuint64_t* dims, const cuuint64_t* strides,
            const cuuint32_t* box, CUtensorMapSwizzle swz) {
  cuuint32_t es[5] = {1, 1, 1, 1, 1};
  fn(m, CU_TENSOR_MAP_DATA_TYPE_BFLOAT16, rank, const_cast<void*>(ptr), dims, strides, box, es, CU_TENSOR_MAP_INTERLEAVE_NONE,
     swz, CU_TENSOR_MAP_L2_PROMOTION_L2_128B, CU_TENSOR_MAP_FLOAT_OOB_FILL_NONE);
}
}

extern "C" void kernel_launch(void* const* d_in, const int* in_sizes, int n_in, void* d_out, int out_size) {
  (void)in_sizes; (void)n_in; (void)out_size;
  const __nv_bfloat16* x = (const __nv_bfloat16*)d_in[0];
  const __nv_bfloat16* wqkv = (const __nv_bfloat16*)d_in[1];
  const __nv_bfloat16* wphi = (const __nv_bfloat16*)d_in[2];
  const __nv_bfloat16* wo = (const __nv_bfloat16*)d_in[3];
  const __nv_bfloat16* w1 = (const __nv_bfloat16*)d_in[5];
  const __nv_bfloat16* w2 = (const __nv_bfloat16*)d_in[6];
  const __nv_bfloat16* w3 = (const __nv_bfloat16*)d_in[7];
  const __nv_bfloat16* w4 = (const __nv_bfloat16*)d_in[8];
  const __nv_bfloat16* gate_w = (const __nv_bfloat16*)d_in[9];

  static EncodeFn enc = nullptr;
  static void *pHs = nullptr, *pX1 = nullptr;
  if (!enc) {
    cudaDriverEntryPointQueryResult qr;
    cudaGetDriverEntryPoint("cuTensorMapEncodeTiled", (void**)&enc, cudaEnableDefault, &qr);
    cudaGetSymbolAddress(&pHs, g_Hs);
    cudaGetSymbolAddress(&pX1, g_X1);
    cudaFuncSetAttribute(fused_kernel, cudaFuncAttributeMaxDynamicSharedMemorySize, SMEM_BYTES);
  }
  Maps m;
  {
    cuuint64_t dims[2] = {D_, S_}, str[1] = {D_ * 2};
    cuuint32_t boxh[2] = {64, 64};
    encode(enc, &m.x, x, 2, dims, str, boxh, CU_TENSOR_MAP_SWIZZLE_128B);
    encode(enc, &m.hs, (const char*)pHs + 2 * D_ * 2, 2, dims, str, boxh, CU_TENSOR_MAP_SWIZZLE_128B);
    encode(enc, &m.x1, pX1, 2, dims, str, boxh, CU_TENSOR_MAP_SWIZZLE_128B);
    cuuint32_t boxs[2] = {80, 64};
    cuuint64_t dimsp[2] = {D_, S_ + 4};
    encode(enc, &m.st_h, pHs, 2, dimsp, str, boxs, CU_TENSOR_MAP_SWIZZLE_NONE);
    encode(enc, &m.st_x1, pX1, 2, dims, str, boxs, CU_TENSOR_MAP_SWIZZLE_NONE);
    cuuint32_t boxr[2] = {80, 16};
    encode(enc, &m.st_out, d_out, 2, dims, str, boxr, CU_TENSOR_MAP_SWIZZLE_NONE);
    encode(enc, &m.xr, x, 2, dims, str, boxr, CU_TENSOR_MAP_SWIZZLE_NONE);
  }
  {
    cuuint64_t dims[3] = {80, D_, 8}, str[2] = {D_ * 2, 160};
    cuuint32_t boxm[3] = {64, 64, 1}, boxr[3] = {16, 64, 1};
    encode(enc, &m.w1m, w1, 3, dims, str, boxm, CU_TENSOR_MAP_SWIZZLE_128B);
    encode(enc, &m.w1r, w1, 3, dims, str, boxr, CU_TENSOR_MAP_SWIZZLE_32B);
  }
  {
    cuuint64_t dims[4] = {80, D_, 3, 8}, str[3] = {3 * D_ * 2, D_ * 2, 160};
    cuuint32_t boxm[4] = {64, 64, 3, 1}, boxr[4] = {16, 64, 3, 1};
    encode(enc, &m.qm, wqkv, 4, dims, str, boxm, CU_TENSOR_MAP_SWIZZLE_128B);
    encode(enc, &m.qr, wqkv, 4, dims, str, boxr, CU_TENSOR_MAP_SWIZZLE_32B);
  }
  {
    cuuint64_t dims[3] = {16, D_, 40}, str[2] = {D_ * 2, 32};
    cuuint32_t box2[3] = {16, 64, 5};
    encode(enc, &m.w2, w2, 3, dims, str, box2, CU_TENSOR_MAP_SWIZZLE_32B);
  }
  {
    cuuint64_t dims[3] = {32, D_, 20}, dims4[3] = {32, F_, 20}, str[2] = {D_ * 2, 64};
    cuuint32_t box4[3] = {32, 64, 5}, boxo[3] = {32, 80, 5};
    encode(enc, &m.w4, w4, 3, dims4, str, box4, CU_TENSOR_MAP_SWIZZLE_64B);
    encode(enc, &m.wo, wo, 3, dims, str, boxo, CU_TENSOR_MAP_SWIZZLE_64B);
  }
  {
    cuuint64_t dims[3] = {64, D_, 24}, str[2] = {F_ * 2, 128};
    cuuint32_t box[3] = {64, 64, 3};
    encode(enc, &m.w3, w3, 3, dims, str, box, CU_TENSOR_MAP_SWIZZLE_128B);
  }
  fused_kernel<<<NCTA, 384, SMEM_BYTES, cudaStreamPerThread>>>(m, x, wqkv, wphi, w1, w2, w3, w4, wo, gate_w);
}
```

```cpp
#include <cuda_runtime.h>
#include <cuda_bf16.h>
#include <cuda.h>
#include <stdint.h>

namespace {

constexpr int S_ = 2048, D_ = 640, F_ = 1536;
constexpr int NCTA = 128;
constexpr int KV_PAIR = 40 * 48 + 96;
constexpr int KV_J = 2 * KV_PAIR;

constexpr int SLOT_B = 49152, NB = 3;
constexpr int SLOT_A = 16384, NA = 4;
constexpr int OFF_B = 0;
constexpr int OFF_A = OFF_B + NB * SLOT_B;
constexpr int OFF_STG = OFF_A + 2 * SLOT_A;
constexpr int OFF_MISC = OFF_A + NA * SLOT_A;
constexpr int OFF_XST = OFF_MISC + 13312;
constexpr int OFF_CS = OFF_MISC + 16384;
constexpr int OFF_BAR = OFF_CS + 1088;
constexpr int SMEM_BYTES = OFF_BAR + 512;
constexpr int B_FULLA = 0, B_FULLB = 4, B_CS = 7, B_XR = 8, B_KV = 9, B_ST1 = 10, B_SDONE = 11  , B_RDY = 17  ,
              B_FULL4 = 23  , B_DSR = 28  , B_SEND = 36  , B_EMPTYB = 42  ,
              B_SIGP = 45, B_SIGH = 46, B_SIGKV = 47, B_SIGX1 = 48, B_MFREE = 49, B_EMPTY4 = 50  ,
              B_EMPTYA = 55  , B_PEER = 59, NBAR = 60;
constexpr int SPARE = 40960;
constexpr int UNIT4 = 25600, NU4 = 5;
constexpr int OFF_DS = OFF_A, OFF_SEND = OFF_A + 40960, OFF_G0 = OFF_A + 61440, OFF_G1 = OFF_B + UNIT4;

constexpr int FL_DONE = 0, FL_H = 1, FL_X1 = FL_H + 16, FL_KV = FL_X1 + 16, FL_CS = FL_KV + 8, FL_CS3 = FL_CS + 8, FL_ST = FL_CS3 + 8, FL_PART = FL_ST + 16;
constexpr int FL_COUNT = FL_PART + 16 * 8;
constexpr int ACC_FLOATS = 8 * KV_J + D_ + F_;

struct Maps {
  CUtensorMap x, w1m, w1r, qm, qr, hs, w2, x1, w3, w4, wo, st_h, st_x1, st_out, xr;
};

}

__device__ __align__(1024) __nv_bfloat16 g_Hs[(S_ + 4) * D_];
__device__ __align__(1024) __nv_bfloat16 g_X1[S_ * D_];
__device__ __align__(128) float g_acc[2][ACC_FLOATS];
__device__ __align__(128) float4 g_xstat[S_];
__device__ __align__(128) float2 g_st1[S_ * 8];
__device__ __align__(128) uint4 g_part[16 * 8 * 3 * 1280];
__device__ __align__(128) unsigned g_flags[FL_COUNT * 32];
#define TSTAMP(n) do {} while (0)
#define TSTAMPX(n) do {} while (0)
#define TRACE(n) do {} while (0)
#define TR4(n) do {} while (0)

namespace {

__device__ __forceinline__ long long gtime() { long long t; asm volatile("mov.u64 %0, %%globaltimer;" : "=l"(t)); return t; }
__device__ __forceinline__ uint32_t smem_u32(const void* p) { return (uint32_t)__cvta_generic_to_shared(p); }
__device__ __forceinline__ void mbar_init(uint32_t bar, int cnt) {
  asm volatile("mbarrier.init.shared::cta.b64 [%0], %1;" ::"r"(bar), "r"(cnt) : "memory");
}
__device__ __forceinline__ void mbar_expect_tx(uint32_t bar, int bytes) {
  asm volatile("mbarrier.arrive.expect_tx.shared::cta.b64 _, [%0], %1;" ::"r"(bar), "r"(bytes) : "memory");
}
__device__ __forceinline__ void mbar_arrive_cta(uint32_t bar, uint32_t cta) {
  asm volatile("{\n.reg .b32 ra;\nmapa.shared::cluster.u32 ra, %0, %1;\nmbarrier.arrive.shared::cluster.b64 _, [ra];\n}"
               ::"r"(bar), "r"(cta) : "memory");
}
__device__ __forceinline__ uint32_t mbar_try(uint32_t bar, uint32_t parity) {
  uint32_t ok;
  asm volatile("{\n.reg .pred p;\nmbarrier.try_wait.parity.shared::cta.b64 p, [%1], %2;\nselp.u32 %0, 1, 0, p;\n}"
               : "=r"(ok) : "r"(bar), "r"(parity) : "memory");
  return ok;
}
constexpr uint32_t WAIT_LIMIT = 1u << 22;
__device__ __forceinline__ void mbar_wait(uint32_t bar, uint32_t parity) {
  uint32_t n = 0;
  while (!mbar_try(bar, parity) && ++n < WAIT_LIMIT) {}
}
__device__ __forceinline__ unsigned ld_acquire(const unsigned* p) {
  unsigned v;
  asm volatile("ld.acquire.gpu.global.u32 %0, [%1];" : "=r"(v) : "l"(p) : "memory");
  return v;
}
__device__ __forceinline__ void flag_wait(int idx, unsigned target) {
  const unsigned* p = g_flags + idx * 32;
  uint32_t n = 0;
  while ((int)(ld_acquire(p) - target) < 0 && ++n < (WAIT_LIMIT >> 4)) {}
}
__device__ __forceinline__ void flag_add(int idx) {
  asm volatile("red.release.gpu.global.add.u32 [%0], 1;" ::"l"(g_flags + idx * 32) : "memory");
}
__device__ __forceinline__ void flag_add_relaxed(int idx) {
  asm volatile("red.relaxed.gpu.global.add.u32 [%0], 1;" ::"l"(g_flags + idx * 32) : "memory");
}
__device__ __forceinline__ uint32_t mbar_test(uint32_t bar, uint32_t parity) {
  uint32_t ok;
  asm volatile("{\n.reg .pred p;\nmbarrier.test_wait.parity.shared::cta.b64 p, [%1], %2;\nselp.u32 %0, 1, 0, p;\n}"
               : "=r"(ok) : "r"(bar), "r"(parity) : "memory");
  return ok;
}
__device__ __forceinline__ uint32_t lds32(uint32_t a) {
  uint32_t v;
  asm volatile("ld.shared.u32 %0, [%1];" : "=r"(v) : "r"(a) : "memory");
  return v;
}
__device__ __forceinline__ void mbar_arrive(uint32_t bar) {
  asm volatile("mbarrier.arrive.shared::cta.b64 _, [%0];" ::"r"(bar) : "memory");
}
__device__ __forceinline__ void fence_async_all() { asm volatile("fence.proxy.async;" ::: "memory"); }
__device__ __forceinline__ void fence_async_smem() { asm volatile("fence.proxy.async.shared::cta;" ::: "memory"); }
__device__ __forceinline__ void bar_sync(int id, int n) { asm volatile("bar.sync %0, %1;" ::"r"(id), "r"(n) : "memory"); }

__device__ __forceinline__ void tma2d(uint32_t dst, const CUtensorMap* m, uint32_t bar, int c0, int c1) {
  asm volatile("cp.async.bulk.tensor.2d.shared::cluster.global.mbarrier::complete_tx::bytes [%0], [%1, {%3, %4}], [%2];"
               ::"r"(dst), "l"(m), "r"(bar), "r"(c0), "r"(c1) : "memory");
}
__device__ __forceinline__ void tma2d_mc(uint32_t dst, const CUtensorMap* m, uint32_t bar, int c0, int c1) {
  asm volatile("cp.async.bulk.tensor.2d.shared::cluster.global.mbarrier::complete_tx::bytes.multicast::cluster"
               " [%0], [%1, {%3, %4}], [%2], %5;"
               ::"r"(dst), "l"(m), "r"(bar), "r"(c0), "r"(c1), "h"((uint16_t)3) : "memory");
}
__device__ __forceinline__ void tma3d(uint32_t dst, const CUtensorMap* m, uint32_t bar, int c0, int c1, int c2) {
  asm volatile("cp.async.bulk.tensor.3d.shared::cluster.global.mbarrier::complete_tx::bytes [%0], [%1, {%3, %4, %5}], [%2];"
               ::"r"(dst), "l"(m), "r"(bar), "r"(c0), "r"(c1), "r"(c2) : "memory");
}
__device__ __forceinline__ void tma4d(uint32_t dst, const CUtensorMap* m, uint32_t bar, int c0, int c1, int c2, int c3) {
  asm volatile("cp.async.bulk.tensor.4d.shared::cluster.global.mbarrier::complete_tx::bytes [%0], [%1, {%3, %4, %5, %6}], [%2];"
               ::"r"(dst), "l"(m), "r"(bar), "r"(c0), "r"(c1), "r"(c2), "r"(c3) : "memory");
}
__device__ __forceinline__ void tma2d_store(const CUtensorMap* m, uint32_t src, int c0, int c1) {
  asm volatile("cp.async.bulk.tensor.2d.global.shared::cta.bulk_group [%0, {%2, %3}], [%1];"
               ::"l"(m), "r"(src), "r"(c0), "r"(c1) : "memory");
}
__device__ __forceinline__ void bulk_store(void* dst, uint32_t src, uint32_t bytes) {
  asm volatile("cp.async.bulk.global.shared::cta.bulk_group [%0], [%1], %2;" ::"l"(dst), "r"(src), "r"(bytes) : "memory");
}
__device__ __forceinline__ void bulk_load(uint32_t dst, const void* src, uint32_t bytes, uint32_t bar) {
  asm volatile("cp.async.bulk.shared::cluster.global.mbarrier::complete_tx::bytes [%0], [%1], %2, [%3];"
               ::"r"(dst), "l"(src), "r"(bytes), "r"(bar) : "memory");
}
__device__ __forceinline__ void bulk_commit() { asm volatile("cp.async.bulk.commit_group;" ::: "memory"); }
template <int N> __device__ __forceinline__ void bulk_wait() { asm volatile("cp.async.bulk.wait_group %0;" ::"n"(N) : "memory"); }
__device__ __forceinline__ void bulk_wait_read() { asm volatile("cp.async.bulk.wait_group.read 0;" ::: "memory"); }
__device__ __forceinline__ void bar_arrive(int id, int n) { asm volatile("bar.arrive %0, %1;" ::"r"(id), "r"(n) : "memory"); }
__device__ __forceinline__ uint4 lds128(uint32_t a) {
  uint4 v;
  asm volatile("ld.shared.v4.u32 {%0, %1, %2, %3}, [%4];" : "=r"(v.x), "=r"(v.y), "=r"(v.z), "=r"(v.w) : "r"(a) : "memory");
  return v;
}
__device__ __forceinline__ void sts128(uint32_t a, uint4 v) {
  asm volatile("st.shared.v4.u32 [%0], {%1, %2, %3, %4};" ::"r"(a), "r"(v.x), "r"(v.y), "r"(v.z), "r"(v.w) : "memory");
}
__device__ __forceinline__ uint32_t map_peer(uint32_t addr, uint32_t cta) {
  uint32_t r;
  asm("mapa.shared::cluster.u32 %0, %1, %2;" : "=r"(r) : "r"(addr), "r"(cta));
  return r;
}
__device__ __forceinline__ void st_async16(uint32_t addr, uint32_t a, uint32_t b, uint32_t c, uint32_t d, uint32_t bar) {
  asm volatile("st.async.weak.shared::cluster.mbarrier::complete_tx::bytes.v4.b32 [%0], {%1, %2, %3, %4}, [%5];"
               ::"r"(addr), "r"(a), "r"(b), "r"(c), "r"(d), "r"(bar) : "memory");
}
__device__ __forceinline__ void l2_prefetch(const void* p, uint32_t bytes) {
  asm volatile("cp.async.bulk.prefetch.L2.global [%0], %1;" ::"l"(p), "r"(bytes) : "memory");
}
__device__ __forceinline__ void prefetch_tmap(const CUtensorMap* m) {
  asm volatile("prefetch.tensormap [%0];" ::"l"(m) : "memory");
}
__device__ __forceinline__ uint64_t make_desc(uint32_t a16, uint32_t off, uint32_t lbo, uint32_t sbo, uint32_t swz) {
  const uint32_t lo = a16 + ((off >> 4) + ((lbo >> 4) << 16)), hi = (sbo >> 4) | (swz << 30);
  uint64_t d;
  asm("mov.b64 %0, {%1, %2};" : "=l"(d) : "r"(lo), "r"(hi));
  return d;
}
__device__ __forceinline__ void wg_fence() { asm volatile("wgmma.fence.sync.aligned;" ::: "memory"); }
__device__ __forceinline__ void wg_commit() { asm volatile("wgmma.commit_group.sync.aligned;" ::: "memory"); }
template <int N> __device__ __forceinline__ void wg_wait() { asm volatile("wgmma.wait_group.sync.aligned %0;" ::"n"(N) : "memory"); }
template <int N> __device__ __forceinline__ void fence_regs(float (&d)[N]) {
#pragma unroll
  for (int i = 0; i < N; i++) asm volatile("" : "+f"(d[i])::"memory");
}
template <int N> __device__ __forceinline__ void zero_regs(float (&d)[N]) {
#pragma unroll
  for (int i = 0; i < N; i++) d[i] = 0.f;
}
__device__ __forceinline__ uint32_t pack_bf16(float lo, float hi) {
  uint32_t r;
  asm("cvt.rn.bf16x2.f32 %0, %1, %2;" : "=r"(r) : "f"(hi), "f"(lo));
  return r;
}
__device__ __forceinline__ float bf_lo(uint32_t v) { return __uint_as_float(v << 16); }
__device__ __forceinline__ float bf_hi(uint32_t v) { return __uint_as_float(v & 0xffff0000u); }
__device__ __forceinline__ uint32_t max_bf2(uint32_t a, uint32_t b) {
  uint32_t r; asm("max.bf16x2 %0, %1, %2;" : "=r"(r) : "r"(a), "r"(b)); return r;
}
__device__ __forceinline__ uint32_t min_bf2(uint32_t a, uint32_t b) {
  uint32_t r; asm("min.bf16x2 %0, %1, %2;" : "=r"(r) : "r"(a), "r"(b)); return r;
}
__device__ __forceinline__ float ex2(float x) { float r; asm("ex2.approx.ftz.f32 %0, %1;" : "=f"(r) : "f"(x)); return r; }
__device__ __forceinline__ float rcp(float x) { float r; asm("rcp.approx.ftz.f32 %0, %1;" : "=f"(r) : "f"(x)); return r; }
__device__ __forceinline__ float tanh_ap(float x) { float r; asm("tanh.approx.f32 %0, %1;" : "=f"(r) : "f"(x)); return r; }
__device__ __forceinline__ float gelu_s(float x, float hs) {
  float u = x * fmaf(x * x, 0.0356774081f, 0.7978845608f);
  float hx = x * hs;
  return fmaf(hx, tanh_ap(u), hx);
}
__device__ __forceinline__ void stsm4(uint32_t addr, uint32_t r0, uint32_t r1, uint32_t r2, uint32_t r3) {
  asm volatile("stmatrix.sync.aligned.m8n8.x4.shared.b16 [%0], {%1, %2, %3, %4};"
               ::"r"(addr), "r"(r0), "r"(r1), "r"(r2), "r"(r3) : "memory");
}
__device__ __forceinline__ void red_add4(float* p, float a, float b, float c, float d) {
  asm volatile("red.global.add.v4.f32 [%0], {%1, %2, %3, %4};" ::"l"(p), "f"(a), "f"(b), "f"(c), "f"(d) : "memory");
}

__device__ __forceinline__ void mma_ss256(float (&d)[128], uint64_t descA, uint64_t descB) {
  asm volatile("wgmma.mma_async.sync.aligned.m64n256k16.f32.bf16.bf16 {"
      "%0, %1, %2, %3, %4, %5, %6, %7, %8, %9, %10, %11, %12, %13, %14, %15, "
      "%16, %17, %18, %19, %20, %21, %22, %23, %24, %25, %26, %27, %28, %29, %30, %31, "
      "%32, %33, %34, %35, %36, %37, %38, %39, %40, %41, %42, %43, %44, %45, %46, %47, "
      "%48, %49, %50, %51, %52, %53, %54, %55, %56, %57, %58, %59, %60, %61, %62, %63, "
      "%64, %65, %66, %67, %68, %69, %70, %71, %72, %73, %74, %75, %76, %77, %78, %79, "
      "%80, %81, %82, %83, %84, %85, %86, %87, %88, %89, %90, %91, %92, %93, %94, %95, "
      "%96, %97, %98, %99, %100, %101, %102, %103, %104, %105, %106, %107, %108, %109, %110, %111, "
      "%112, %113, %114, %115, %116, %117, %118, %119, %120, %121, %122, %123, %124, %125, %126, %127"
      "}, %128, %129, 1, 1, 1, 0, 1;\n"
      : "+f"(d[0]), "+f"(d[1]), "+f"(d[2]), "+f"(d[3]), "+f"(d[4]), "+f"(d[5]), "+f"(d[6]), "+f"(d[7]),
        "+f"(d[8]), "+f"(d[9]), "+f"(d[10]), "+f"(d[11]), "+f"(d[12]), "+f"(d[13]), "+f"(d[14]), "+f"(d[15]),
        "+f"(d[16]), "+f"(d[17]), "+f"(d[18]), "+f"(d[19]), "+f"(d[20]), "+f"(d[21]), "+f"(d[22]), "+f"(d[23]),
        "+f"(d[24]), "+f"(d[25]), "+f"(d[26]), "+f"(d[27]), "+f"(d[28]), "+f"(d[29]), "+f"(d[30]), "+f"(d[31]),
        "+f"(d[32]), "+f"(d[33]), "+f"(d[34]), "+f"(d[35]), "+f"(d[36]), "+f"(d[37]), "+f"(d[38]), "+f"(d[39]),
        "+f"(d[40]), "+f"(d[41]), "+f"(d[42]), "+f"(d[43]), "+f"(d[44]), "+f"(d[45]), "+f"(d[46]), "+f"(d[47]),
        "+f"(d[48]), "+f"(d[49]), "+f"(d[50]), "+f"(d[51]), "+f"(d[52]), "+f"(d[53]), "+f"(d[54]), "+f"(d[55]),
        "+f"(d[56]), "+f"(d[57]), "+f"(d[58]), "+f"(d[59]), "+f"(d[60]), "+f"(d[61]), "+f"(d[62]), "+f"(d[63]),
        "+f"(d[64]), "+f"(d[65]), "+f"(d[66]), "+f"(d[67]), "+f"(d[68]), "+f"(d[69]), "+f"(d[70]), "+f"(d[71]),
        "+f"(d[72]), "+f"(d[73]), "+f"(d[74]), "+f"(d[75]), "+f"(d[76]), "+f"(d[77]), "+f"(d[78]), "+f"(d[79]),
        "+f"(d[80]), "+f"(d[81]), "+f"(d[82]), "+f"(d[83]), "+f"(d[84]), "+f"(d[85]), "+f"(d[86]), "+f"(d[87]),
        "+f"(d[88]), "+f"(d[89]), "+f"(d[90]), "+f"(d[91]), "+f"(d[92]), "+f"(d[93]), "+f"(d[94]), "+f"(d[95]),
        "+f"(d[96]), "+f"(d[97]), "+f"(d[98]), "+f"(d[99]), "+f"(d[100]), "+f"(d[101]), "+f"(d[102]), "+f"(d[103]),
        "+f"(d[104]), "+f"(d[105]), "+f"(d[106]), "+f"(d[107]), "+f"(d[108]), "+f"(d[109]), "+f"(d[110]), "+f"(d[111]),
        "+f"(d[112]), "+f"(d[113]), "+f"(d[114]), "+f"(d[115]), "+f"(d[116]), "+f"(d[117]), "+f"(d[118]), "+f"(d[119]),
        "+f"(d[120]), "+f"(d[121]), "+f"(d[122]), "+f"(d[123]), "+f"(d[124]), "+f"(d[125]), "+f"(d[126]), "+f"(d[127])
      : "l"(descA), "l"(descB));
}

__device__ __forceinline__ void mma_ss64(float (&d)[32], uint64_t descA, uint64_t descB) {
  asm volatile("wgmma.mma_async.sync.aligned.m64n64k16.f32.bf16.bf16 {"
      "%0, %1, %2, %3, %4, %5, %6, %7, %8, %9, %10, %11, %12, %13, %14, %15, "
      "%16, %17, %18, %19, %20, %21, %22, %23, %24, %25, %26, %27, %28, %29, %30, %31"
      "}, %32, %33, 1, 1, 1, 0, 1;\n"
      : "+f"(d[0]), "+f"(d[1]), "+f"(d[2]), "+f"(d[3]), "+f"(d[4]), "+f"(d[5]), "+f"(d[6]), "+f"(d[7]),
        "+f"(d[8]), "+f"(d[9]), "+f"(d[10]), "+f"(d[11]), "+f"(d[12]), "+f"(d[13]), "+f"(d[14]), "+f"(d[15]),
        "+f"(d[16]), "+f"(d[17]), "+f"(d[18]), "+f"(d[19]), "+f"(d[20]), "+f"(d[21]), "+f"(d[22]), "+f"(d[23]),
        "+f"(d[24]), "+f"(d[25]), "+f"(d[26]), "+f"(d[27]), "+f"(d[28]), "+f"(d[29]), "+f"(d[30]), "+f"(d[31])
      : "l"(descA), "l"(descB));
}

__device__ __forceinline__ void mma_ss80(float (&d)[40], uint64_t descA, uint64_t descB) {
  asm volatile("wgmma.mma_async.sync.aligned.m64n80k16.f32.bf16.bf16 {"
      "%0, %1, %2, %3, %4, %5, %6, %7, %8, %9, %10, %11, %12, %13, %14, %15, "
      "%16, %17, %18, %19, %20, %21, %22, %23, %24, %25, %26, %27, %28, %29, %30, %31, "
      "%32, %33, %34, %35, %36, %37, %38, %39"
      "}, %40, %41, 1, 1, 1, 0, 1;\n"
      : "+f"(d[0]), "+f"(d[1]), "+f"(d[2]), "+f"(d[3]), "+f"(d[4]), "+f"(d[5]), "+f"(d[6]), "+f"(d[7]),
        "+f"(d[8]), "+f"(d[9]), "+f"(d[10]), "+f"(d[11]), "+f"(d[12]), "+f"(d[13]), "+f"(d[14]), "+f"(d[15]),
        "+f"(d[16]), "+f"(d[17]), "+f"(d[18]), "+f"(d[19]), "+f"(d[20]), "+f"(d[21]), "+f"(d[22]), "+f"(d[23]),
        "+f"(d[24]), "+f"(d[25]), "+f"(d[26]), "+f"(d[27]), "+f"(d[28]), "+f"(d[29]), "+f"(d[30]), "+f"(d[31]),
        "+f"(d[32]), "+f"(d[33]), "+f"(d[34]), "+f"(d[35]), "+f"(d[36]), "+f"(d[37]), "+f"(d[38]), "+f"(d[39])
      : "l"(descA), "l"(descB));
}

__device__ __forceinline__ void mma_ss192(float (&d)[96], uint64_t descA, uint64_t descB) {
  asm volatile("wgmma.mma_async.sync.aligned.m64n192k16.f32.bf16.bf16 {"
      "%0, %1, %2, %3, %4, %5, %6, %7, %8, %9, %10, %11, %12, %13, %14, %15, "
      "%16, %17, %18, %19, %20, %21, %22, %23, %24, %25, %26, %27, %28, %29, %30, %31, "
      "%32, %33, %34, %35, %36, %37, %38, %39, %40, %41, %42, %43, %44, %45, %46, %47, "
      "%48, %49, %50, %51, %52, %53, %54, %55, %56, %57, %58, %59, %60, %61, %62, %63, "
      "%64, %65, %66, %67, %68, %69, %70, %71, %72, %73, %74, %75, %76, %77, %78, %79, "
      "%80, %81, %82, %83, %84, %85, %86, %87, %88, %89, %90, %91, %92, %93, %94, %95"
      "}, %96, %97, 1, 1, 1, 0, 1;\n"
      : "+f"(d[0]), "+f"(d[1]), "+f"(d[2]), "+f"(d[3]), "+f"(d[4]), "+f"(d[5]), "+f"(d[6]), "+f"(d[7]),
        "+f"(d[8]), "+f"(d[9]), "+f"(d[10]), "+f"(d[11]), "+f"(d[12]), "+f"(d[13]), "+f"(d[14]), "+f"(d[15]),
        "+f"(d[16]), "+f"(d[17]), "+f"(d[18]), "+f"(d[19]), "+f"(d[20]), "+f"(d[21]), "+f"(d[22]), "+f"(d[23]),
        "+f"(d[24]), "+f"(d[25]), "+f"(d[26]), "+f"(d[27]), "+f"(d[28]), "+f"(d[29]), "+f"(d[30]), "+f"(d[31]),
        "+f"(d[32]), "+f"(d[33]), "+f"(d[34]), "+f"(d[35]), "+f"(d[36]), "+f"(d[37]), "+f"(d[38]), "+f"(d[39]),
        "+f"(d[40]), "+f"(d[41]), "+f"(d[42]), "+f"(d[43]), "+f"(d[44]), "+f"(d[45]), "+f"(d[46]), "+f"(d[47]),
        "+f"(d[48]), "+f"(d[49]), "+f"(d[50]), "+f"(d[51]), "+f"(d[52]), "+f"(d[53]), "+f"(d[54]), "+f"(d[55]),
        "+f"(d[56]), "+f"(d[57]), "+f"(d[58]), "+f"(d[59]), "+f"(d[60]), "+f"(d[61]), "+f"(d[62]), "+f"(d[63]),
        "+f"(d[64]), "+f"(d[65]), "+f"(d[66]), "+f"(d[67]), "+f"(d[68]), "+f"(d[69]), "+f"(d[70]), "+f"(d[71]),
        "+f"(d[72]), "+f"(d[73]), "+f"(d[74]), "+f"(d[75]), "+f"(d[76]), "+f"(d[77]), "+f"(d[78]), "+f"(d[79]),
        "+f"(d[80]), "+f"(d[81]), "+f"(d[82]), "+f"(d[83]), "+f"(d[84]), "+f"(d[85]), "+f"(d[86]), "+f"(d[87]),
        "+f"(d[88]), "+f"(d[89]), "+f"(d[90]), "+f"(d[91]), "+f"(d[92]), "+f"(d[93]), "+f"(d[94]), "+f"(d[95])
      : "l"(descA), "l"(descB));
}

__device__ __forceinline__ void mma_ss80_tt(float (&d)[40], uint64_t descA, uint64_t descB) {
  asm volatile("wgmma.mma_async.sync.aligned.m64n80k16.f32.bf16.bf16 {"
      "%0, %1, %2, %3, %4, %5, %6, %7, %8, %9, %10, %11, %12, %13, %14, %15, "
      "%16, %17, %18, %19, %20, %21, %22, %23, %24, %25, %26, %27, %28, %29, %30, %31, "
      "%32, %33, %34, %35, %36, %37, %38, %39"
      "}, %40, %41, 1, 1, 1, 1, 1;\n"
      : "+f"(d[0]), "+f"(d[1]), "+f"(d[2]), "+f"(d[3]), "+f"(d[4]), "+f"(d[5]), "+f"(d[6]), "+f"(d[7]),
        "+f"(d[8]), "+f"(d[9]), "+f"(d[10]), "+f"(d[11]), "+f"(d[12]), "+f"(d[13]), "+f"(d[14]), "+f"(d[15]),
        "+f"(d[16]), "+f"(d[17]), "+f"(d[18]), "+f"(d[19]), "+f"(d[20]), "+f"(d[21]), "+f"(d[22]), "+f"(d[23]),
        "+f"(d[24]), "+f"(d[25]), "+f"(d[26]), "+f"(d[27]), "+f"(d[28]), "+f"(d[29]), "+f"(d[30]), "+f"(d[31]),
        "+f"(d[32]), "+f"(d[33]), "+f"(d[34]), "+f"(d[35]), "+f"(d[36]), "+f"(d[37]), "+f"(d[38]), "+f"(d[39])
      : "l"(descA), "l"(descB));
}
__device__ __forceinline__ void mma_ss80_tt_z(float (&d)[40], uint64_t descA, uint64_t descB) {
  asm volatile("wgmma.mma_async.sync.aligned.m64n80k16.f32.bf16.bf16 {"
      "%0, %1, %2, %3, %4, %5, %6, %7, %8, %9, %10, %11, %12, %13, %14, %15, "
      "%16, %17, %18, %19, %20, %21, %22, %23, %24, %25, %26, %27, %28, %29, %30, %31, "
      "%32, %33, %34, %35, %36, %37, %38, %39"
      "}, %40, %41, 0, 1, 1, 1, 1;\n"
      : "=f"(d[0]), "=f"(d[1]), "=f"(d[2]), "=f"(d[3]), "=f"(d[4]), "=f"(d[5]), "=f"(d[6]), "=f"(d[7]),
        "=f"(d[8]), "=f"(d[9]), "=f"(d[10]), "=f"(d[11]), "=f"(d[12]), "=f"(d[13]), "=f"(d[14]), "=f"(d[15]),
        "=f"(d[16]), "=f"(d[17]), "=f"(d[18]), "=f"(d[19]), "=f"(d[20]), "=f"(d[21]), "=f"(d[22]), "=f"(d[23]),
        "=f"(d[24]), "=f"(d[25]), "=f"(d[26]), "=f"(d[27]), "=f"(d[28]), "=f"(d[29]), "=f"(d[30]), "=f"(d[31]),
        "=f"(d[32]), "=f"(d[33]), "=f"(d[34]), "=f"(d[35]), "=f"(d[36]), "=f"(d[37]), "=f"(d[38]), "=f"(d[39])
      : "l"(descA), "l"(descB));
}

__device__ __forceinline__ void mma_rs80_k(float (&d)[40], const uint32_t (&a)[4], uint64_t descB) {
  asm volatile("wgmma.mma_async.sync.aligned.m64n80k16.f32.bf16.bf16 {"
      "%0, %1, %2, %3, %4, %5, %6, %7, %8, %9, %10, %11, %12, %13, %14, %15, "
      "%16, %17, %18, %19, %20, %21, %22, %23, %24, %25, %26, %27, %28, %29, %30, %31, "
      "%32, %33, %34, %35, %36, %37, %38, %39"
      "}, {%40, %41, %42, %43}, %44, 1, 1, 1, 0;\n"
      : "+f"(d[0]), "+f"(d[1]), "+f"(d[2]), "+f"(d[3]), "+f"(d[4]), "+f"(d[5]), "+f"(d[6]), "+f"(d[7]),
        "+f"(d[8]), "+f"(d[9]), "+f"(d[10]), "+f"(d[11]), "+f"(d[12]), "+f"(d[13]), "+f"(d[14]), "+f"(d[15]),
        "+f"(d[16]), "+f"(d[17]), "+f"(d[18]), "+f"(d[19]), "+f"(d[20]), "+f"(d[21]), "+f"(d[22]), "+f"(d[23]),
        "+f"(d[24]), "+f"(d[25]), "+f"(d[26]), "+f"(d[27]), "+f"(d[28]), "+f"(d[29]), "+f"(d[30]), "+f"(d[31]),
        "+f"(d[32]), "+f"(d[33]), "+f"(d[34]), "+f"(d[35]), "+f"(d[36]), "+f"(d[37]), "+f"(d[38]), "+f"(d[39])
      : "r"(a[0]), "r"(a[1]), "r"(a[2]), "r"(a[3]), "l"(descB));
}
__device__ __forceinline__ void mma_rs80_k_z(float (&d)[40], const uint32_t (&a)[4], uint64_t descB) {
  asm volatile("wgmma.mma_async.sync.aligned.m64n80k16.f32.bf16.bf16 {"
      "%0, %1, %2, %3, %4, %5, %6, %7, %8, %9, %10, %11, %12, %13, %14, %15, "
      "%16, %17, %18, %19, %20, %21, %22, %23, %24, %25, %26, %27, %28, %29, %30, %31, "
      "%32, %33, %34, %35, %36, %37, %38, %39"
      "}, {%40, %41, %42, %43}, %44, 0, 1, 1, 0;\n"
      : "=f"(d[0]), "=f"(d[1]), "=f"(d[2]), "=f"(d[3]), "=f"(d[4]), "=f"(d[5]), "=f"(d[6]), "=f"(d[7]),
        "=f"(d[8]), "=f"(d[9]), "=f"(d[10]), "=f"(d[11]), "=f"(d[12]), "=f"(d[13]), "=f"(d[14]), "=f"(d[15]),
        "=f"(d[16]), "=f"(d[17]), "=f"(d[18]), "=f"(d[19]), "=f"(d[20]), "=f"(d[21]), "=f"(d[22]), "=f"(d[23]),
        "=f"(d[24]), "=f"(d[25]), "=f"(d[26]), "=f"(d[27]), "=f"(d[28]), "=f"(d[29]), "=f"(d[30]), "=f"(d[31]),
        "=f"(d[32]), "=f"(d[33]), "=f"(d[34]), "=f"(d[35]), "=f"(d[36]), "=f"(d[37]), "=f"(d[38]), "=f"(d[39])
      : "r"(a[0]), "r"(a[1]), "r"(a[2]), "r"(a[3]), "l"(descB));
}

__device__ __forceinline__ void mma_rs48_k(float (&d)[24], const uint32_t (&a)[4], uint64_t descB) {
  asm volatile("wgmma.mma_async.sync.aligned.m64n48k16.f32.bf16.bf16 {"
      "%0, %1, %2, %3, %4, %5, %6, %7, %8, %9, %10, %11, %12, %13, %14, %15, "
      "%16, %17, %18, %19, %20, %21, %22, %23"
      "}, {%24, %25, %26, %27}, %28, 1, 1, 1, 0;\n"
      : "+f"(d[0]), "+f"(d[1]), "+f"(d[2]), "+f"(d[3]), "+f"(d[4]), "+f"(d[5]), "+f"(d[6]), "+f"(d[7]),
        "+f"(d[8]), "+f"(d[9]), "+f"(d[10]), "+f"(d[11]), "+f"(d[12]), "+f"(d[13]), "+f"(d[14]), "+f"(d[15]),
        "+f"(d[16]), "+f"(d[17]), "+f"(d[18]), "+f"(d[19]), "+f"(d[20]), "+f"(d[21]), "+f"(d[22]), "+f"(d[23])
      : "r"(a[0]), "r"(a[1]), "r"(a[2]), "r"(a[3]), "l"(descB));
}
__device__ __forceinline__ void mma_rs48_k_z(float (&d)[24], const uint32_t (&a)[4], uint64_t descB) {
  asm volatile("wgmma.mma_async.sync.aligned.m64n48k16.f32.bf16.bf16 {"
      "%0, %1, %2, %3, %4, %5, %6, %7, %8, %9, %10, %11, %12, %13, %14, %15, "
      "%16, %17, %18, %19, %20, %21, %22, %23"
      "}, {%24, %25, %26, %27}, %28, 0, 1, 1, 0;\n"
      : "=f"(d[0]), "=f"(d[1]), "=f"(d[2]), "=f"(d[3]), "=f"(d[4]), "=f"(d[5]), "=f"(d[6]), "=f"(d[7]),
        "=f"(d[8]), "=f"(d[9]), "=f"(d[10]), "=f"(d[11]), "=f"(d[12]), "=f"(d[13]), "=f"(d[14]), "=f"(d[15]),
        "=f"(d[16]), "=f"(d[17]), "=f"(d[18]), "=f"(d[19]), "=f"(d[20]), "=f"(d[21]), "=f"(d[22]), "=f"(d[23])
      : "r"(a[0]), "r"(a[1]), "r"(a[2]), "r"(a[3]), "l"(descB));
}

__device__ __forceinline__ void mma_rs160_n(float (&d)[80], const uint32_t (&a)[4], uint64_t descB) {
  asm volatile("wgmma.mma_async.sync.aligned.m64n160k16.f32.bf16.bf16 {"
      "%0, %1, %2, %3, %4, %5, %6, %7, %8, %9, %10, %11, %12, %13, %14, %15, "
      "%16, %17, %18, %19, %20, %21, %22, %23, %24, %25, %26, %27, %28, %29, %30, %31, "
      "%32, %33, %34, %35, %36, %37, %38, %39, %40, %41, %42, %43, %44, %45, %46, %47, "
      "%48, %49, %50, %51, %52, %53, %54, %55, %56, %57, %58, %59, %60, %61, %62, %63, "
      "%64, %65, %66, %67, %68, %69, %70, %71, %72, %73, %74, %75, %76, %77, %78, %79"
      "}, {%80, %81, %82, %83}, %84, 1, 1, 1, 1;\n"
      : "+f"(d[0]), "+f"(d[1]), "+f"(d[2]), "+f"(d[3]), "+f"(d[4]), "+f"(d[5]), "+f"(d[6]), "+f"(d[7]),
        "+f"(d[8]), "+f"(d[9]), "+f"(d[10]), "+f"(d[11]), "+f"(d[12]), "+f"(d[13]), "+f"(d[14]), "+f"(d[15]),
        "+f"(d[16]), "+f"(d[17]), "+f"(d[18]), "+f"(d[19]), "+f"(d[20]), "+f"(d[21]), "+f"(d[22]), "+f"(d[23]),
        "+f"(d[24]), "+f"(d[25]), "+f"(d[26]), "+f"(d[27]), "+f"(d[28]), "+f"(d[29]), "+f"(d[30]), "+f"(d[31]),
        "+f"(d[32]), "+f"(d[33]), "+f"(d[34]), "+f"(d[35]), "+f"(d[36]), "+f"(d[37]), "+f"(d[38]), "+f"(d[39]),
        "+f"(d[40]), "+f"(d[41]), "+f"(d[42]), "+f"(d[43]), "+f"(d[44]), "+f"(d[45]), "+f"(d[46]), "+f"(d[47]),
        "+f"(d[48]), "+f"(d[49]), "+f"(d[50]), "+f"(d[51]), "+f"(d[52]), "+f"(d[53]), "+f"(d[54]), "+f"(d[55]),
        "+f"(d[56]), "+f"(d[57]), "+f"(d[58]), "+f"(d[59]), "+f"(d[60]), "+f"(d[61]), "+f"(d[62]), "+f"(d[63]),
        "+f"(d[64]), "+f"(d[65]), "+f"(d[66]), "+f"(d[67]), "+f"(d[68]), "+f"(d[69]), "+f"(d[70]), "+f"(d[71]),
        "+f"(d[72]), "+f"(d[73]), "+f"(d[74]), "+f"(d[75]), "+f"(d[76]), "+f"(d[77]), "+f"(d[78]), "+f"(d[79])
      : "r"(a[0]), "r"(a[1]), "r"(a[2]), "r"(a[3]), "l"(descB));
}
__device__ __forceinline__ void mma_rs160_n_z(float (&d)[80], const uint32_t (&a)[4], uint64_t descB) {
  asm volatile("wgmma.mma_async.sync.aligned.m64n160k16.f32.bf16.bf16 {"
      "%0, %1, %2, %3, %4, %5, %6, %7, %8, %9, %10, %11, %12, %13, %14, %15, "
      "%16, %17, %18, %19, %20, %21, %22, %23, %24, %25, %26, %27, %28, %29, %30, %31, "
      "%32, %33, %34, %35, %36, %37, %38, %39, %40, %41, %42, %43, %44, %45, %46, %47, "
      "%48, %49, %50, %51, %52, %53, %54, %55, %56, %57, %58, %59, %60, %61, %62, %63, "
      "%64, %65, %66, %67, %68, %69, %70, %71, %72, %73, %74, %75, %76, %77, %78, %79"
      "}, {%80, %81, %82, %83}, %84, 0, 1, 1, 1;\n"
      : "=f"(d[0]), "=f"(d[1]), "=f"(d[2]), "=f"(d[3]), "=f"(d[4]), "=f"(d[5]), "=f"(d[6]), "=f"(d[7]),
        "=f"(d[8]), "=f"(d[9]), "=f"(d[10]), "=f"(d[11]), "=f"(d[12]), "=f"(d[13]), "=f"(d[14]), "=f"(d[15]),
        "=f"(d[16]), "=f"(d[17]), "=f"(d[18]), "=f"(d[19]), "=f"(d[20]), "=f"(d[21]), "=f"(d[22]), "=f"(d[23]),
        "=f"(d[24]), "=f"(d[25]), "=f"(d[26]), "=f"(d[27]), "=f"(d[28]), "=f"(d[29]), "=f"(d[30]), "=f"(d[31]),
        "=f"(d[32]), "=f"(d[33]), "=f"(d[34]), "=f"(d[35]), "=f"(d[36]), "=f"(d[37]), "=f"(d[38]), "=f"(d[39]),
        "=f"(d[40]), "=f"(d[41]), "=f"(d[42]), "=f"(d[43]), "=f"(d[44]), "=f"(d[45]), "=f"(d[46]), "=f"(d[47]),
        "=f"(d[48]), "=f"(d[49]), "=f"(d[50]), "=f"(d[51]), "=f"(d[52]), "=f"(d[53]), "=f"(d[54]), "=f"(d[55]),
        "=f"(d[56]), "=f"(d[57]), "=f"(d[58]), "=f"(d[59]), "=f"(d[60]), "=f"(d[61]), "=f"(d[62]), "=f"(d[63]),
        "=f"(d[64]), "=f"(d[65]), "=f"(d[66]), "=f"(d[67]), "=f"(d[68]), "=f"(d[69]), "=f"(d[70]), "=f"(d[71]),
        "=f"(d[72]), "=f"(d[73]), "=f"(d[74]), "=f"(d[75]), "=f"(d[76]), "=f"(d[77]), "=f"(d[78]), "=f"(d[79])
      : "r"(a[0]), "r"(a[1]), "r"(a[2]), "r"(a[3]), "l"(descB));
}

__device__ __forceinline__ void feature_map(const uint32_t (&P)[2][10], uint32_t (&fr)[10][4]) {
  constexpr float L2E = 1.4426950408889634f;
#pragma unroll
  for (int p = 0; p < 2; p++) {
#pragma unroll
    for (int r = 0; r < 2; r++) {
      uint32_t mx = P[r][5 * p], mn = mx;
#pragma unroll
      for (int g = 1; g < 5; g++) { mx = max_bf2(mx, P[r][5 * p + g]); mn = min_bf2(mn, P[r][5 * p + g]); }
      mx = max_bf2(mx, __shfl_xor_sync(0xffffffffu, mx, 1));
      mn = min_bf2(mn, __shfl_xor_sync(0xffffffffu, mn, 1));
      mx = max_bf2(mx, __shfl_xor_sync(0xffffffffu, mx, 2));
      mn = min_bf2(mn, __shfl_xor_sync(0xffffffffu, mn, 2));
      float mx0 = -bf_lo(mx) * L2E, mx1 = -bf_hi(mx) * L2E, mn0 = bf_lo(mn) * L2E, mn1 = bf_hi(mn) * L2E;
      float ep0[5], ep1[5], en0[5], en1[5];
      float sp0 = 0.f, sp1 = 0.f, sn0 = 0.f, sn1 = 0.f;
#pragma unroll
      for (int g = 0; g < 5; g++) {
        float x0 = bf_lo(P[r][5 * p + g]), x1 = bf_hi(P[r][5 * p + g]);
        ep0[g] = ex2(fmaf(x0, L2E, mx0)); ep1[g] = ex2(fmaf(x1, L2E, mx1));
        en0[g] = ex2(fmaf(x0, -L2E, mn0)); en1[g] = ex2(fmaf(x1, -L2E, mn1));
        sp0 += ep0[g]; sp1 += ep1[g]; sn0 += en0[g]; sn1 += en1[g];
      }
      sp0 += __shfl_xor_sync(0xffffffffu, sp0, 1); sp1 += __shfl_xor_sync(0xffffffffu, sp1, 1);
      sn0 += __shfl_xor_sync(0xffffffffu, sn0, 1); sn1 += __shfl_xor_sync(0xffffffffu, sn1, 1);
      sp0 += __shfl_xor_sync(0xffffffffu, sp0, 2); sp1 += __shfl_xor_sync(0xffffffffu, sp1, 2);
      sn0 += __shfl_xor_sync(0xffffffffu, sn0, 2); sn1 += __shfl_xor_sync(0xffffffffu, sn1, 2);
      sp0 = rcp(sp0); sp1 = rcp(sp1); sn0 = rcp(sn0); sn1 = rcp(sn1);
#pragma unroll
      for (int g = 0; g < 5; g++) {
        fr[5 * p + g][r] = pack_bf16(ep0[g] * sp0, ep1[g] * sp1);
        fr[5 * p + g][2 + r] = pack_bf16(en0[g] * sn0, en1[g] * sn1);
      }
    }
  }
}

struct Ring {
  uint32_t idx, phase;
  template <int N> __device__ __forceinline__ void next() { if (++idx == N) { idx = 0; phase ^= 1; } }
};

}

__global__ void __cluster_dims__(2, 1, 1) __launch_bounds__(384, 1)
fused_kernel(const __grid_constant__ Maps maps, const __nv_bfloat16* __restrict__ x, const __nv_bfloat16* __restrict__ wqkv,
             const __nv_bfloat16* __restrict__ wphi, const __nv_bfloat16* __restrict__ w1, const __nv_bfloat16* __restrict__ w2,
             const __nv_bfloat16* __restrict__ w3, const __nv_bfloat16* __restrict__ w4, const __nv_bfloat16* __restrict__ wo,
             const __nv_bfloat16* __restrict__ gate_w) {
  extern __shared__ __align__(1024) uint8_t sgen[];
  const uint32_t sb = smem_u32(sgen);
  const uint32_t sb16 = (sb & 0x3FFFFu) >> 4;
  const uint32_t bars = sb + OFF_BAR;
  const uint32_t fullA = bars + 8 * B_FULLA, emptyA = bars + 8 * B_EMPTYA, fullB = bars + 8 * B_FULLB, emptyB = bars + 8 * B_EMPTYB;

  const int tid = threadIdx.x;
  const int rank = blockIdx.x & 1;
  const int pairIdx = blockIdx.x >> 1;
  const int i = pairIdx >> 2, j = 2 * (pairIdx & 3) + rank;

  TSTAMP(0);
  uint4 pv[5], pw_[5], pc[2], pre;
  if (tid < 256) {
    const int row = 128 * i + 16 * j + (tid >> 4), l16 = tid & 15;
#pragma unroll
    for (int c = 0; c < 5; c++) pv[c] = __ldg(reinterpret_cast<const uint4*>(x + (size_t)row * D_ + c * 128 + l16 * 8));
    const int tq = tid < 200 ? tid : 0;
    const __nv_bfloat16* cp = w1 + (size_t)(40 * i + tq / 10) * D_ + 80 * j + 8 * (tq % 10);
    pc[0] = __ldg(reinterpret_cast<const uint4*>(cp)); pc[1] = __ldg(reinterpret_cast<const uint4*>(cp + 20 * D_));
    pre = __ldg(reinterpret_cast<const uint4*>(wphi + (size_t)j * 1600) + tq);
#pragma unroll
    for (int c = 0; c < 5; c++) pw_[c] = __ldg(reinterpret_cast<const uint4*>(gate_w + c * 128 + l16 * 8));
  }
  auto load_p1_b = [&](int k, uint32_t slot, uint32_t bar) {
    mbar_expect_tx(bar, 40960);
    tma4d(slot + 8192, &maps.qm, bar, 0, 64 * k, 0, j);
    tma3d(slot, &maps.w1m, bar, 0, 64 * k, j);
    tma4d(slot + 32768 + 2048, &maps.qr, bar, 64, 64 * k, 0, j);
    tma3d(slot + 32768, &maps.w1r, bar, 64, 64 * k, j);
  };
  if (tid == 256) {
#pragma unroll
    for (int s = 0; s < NA; s++) mbar_init(fullA + 8 * s, 1);
    asm volatile("fence.mbarrier_init.release.cluster;" ::: "memory");
#pragma unroll 1
    for (int u = 0; u < 4; u++) {
      if ((u & 1) == 0) mbar_expect_tx(fullA + 4 * u, SLOT_A);
      tma2d(sb + OFF_A + u * 8192, &maps.x, fullA + 8 * (u >> 1), 64 * (u >> 1), 128 * i + 64 * (u & 1));
    }
  } else if (tid == 288) {
#pragma unroll
    for (int s = 0; s < NB; s++) mbar_init(fullB + 8 * s, 1);
    asm volatile("fence.mbarrier_init.release.cluster;" ::: "memory");
#pragma unroll 1
    for (int k = 0; k < 2; k++) load_p1_b(k, sb + OFF_B + k * SLOT_B, fullB + 8 * k);
  } else if (tid == 320 || tid == 352) {
#pragma unroll 1
    for (int b = B_CS + (tid == 352); b < NBAR; b += 2) {
      mbar_init(bars + 8 * b, b < B_SEND ? 1 : b < B_EMPTYB ? 4 : b < B_EMPTYA ? 8 : 16);
      if (b >= B_DSR && b < B_SEND) mbar_expect_tx(bars + 8 * b, 10240);
    }
    asm volatile("fence.mbarrier_init.release.cluster;" ::: "memory");
  }
  __syncwarp();
  asm volatile("barrier.cluster.arrive.relaxed.aligned;" ::: "memory");

  if (tid >= 256) {
    asm volatile("setmaxnreg.dec.sync.aligned.u32 40;");
    asm volatile("barrier.cluster.wait.aligned;" ::: "memory");
    auto get_epoch = [&]() { return *reinterpret_cast<volatile unsigned*>(g_flags + FL_DONE * 32) / NCTA; };
    const int lane = tid & 31, pw = (tid >> 5) & 3;
    auto send_stream = [&](int w, unsigned ep1) {
#pragma unroll 1
      for (int c = 0; c < 3; c++) {
        const int d = (j + 2 * c + 2) & 7;
        mbar_wait(bars + 8 * (B_SEND + 2 * c + w), 0);
        if (w) TR4(c * 16 + 7);
        bulk_store(g_part + (size_t)((i * 8 + d) * 3 + c) * 1280 + w * 640, sb + OFF_SEND + w * 10240, 10240);
        bulk_commit();
        bulk_wait<0>();
        mbar_arrive(bars + 8 * (B_SDONE + 2 * c + w));
        if (w) TR4(c * 16 + 9);
        asm volatile("st.release.gpu.global.u32 [%0], %1;"
                     ::"l"(g_flags + (FL_PART + i * 8 + d) * 32 + 2 * c + w), "r"(ep1) : "memory");
        if (w) TR4(c * 16 + 10);
      }
    };
    if (pw == 0) {
      if (lane == 0) {
        Ring r{2, 1};
        unsigned ep1 = 0;
#pragma unroll 1
        for (int k = 2; k < 30; k++) {
          if (k == 4) ep1 = get_epoch() + 1;
          if (k == 10 || k == 20) {
            const unsigned tgt = ep1 * 8u;
            const unsigned* f0 = g_flags + (k == 10 ? FL_H + ((i - 1) & 15) : FL_X1 + i) * 32;
            const unsigned* f1 = g_flags + (k == 10 ? FL_H + i : FL_X1 + i) * 32;
            const unsigned* f2 = g_flags + (k == 10 ? FL_H + ((i + 1) & 15) : FL_X1 + i) * 32;
            uint32_t n = 0;
            while (++n < (WAIT_LIMIT >> 4)) {
              unsigned v0, v1, v2;
              asm volatile("ld.relaxed.gpu.global.u32 %0, [%3];\nld.relaxed.gpu.global.u32 %1, [%4];\nld.acquire.gpu.global.u32 %2, [%5];"
                           : "=r"(v0), "=r"(v1), "=r"(v2) : "l"(f0), "l"(f1), "l"(f2) : "memory");
              if ((int)((v0 - tgt) | (v1 - tgt) | (v2 - tgt)) >= 0) break;
            }
            TSTAMPX(k == 10 ? 29 : 30);
          }
          mbar_wait(emptyA + 8 * r.idx, r.phase);
          const uint32_t bar = fullA + 8 * r.idx, slot = sb + OFF_A + r.idx * SLOT_A;
          TRACE(k);
          mbar_expect_tx(bar, SLOT_A);
          tma2d_mc(slot + rank * 8192, k < 10 ? &maps.x : k < 20 ? &maps.hs : &maps.x1, bar, 64 * (k % 10), 128 * i + 64 * rank);
          r.next<NA>();
        }
        send_stream(1, ep1);
      }
    } else if (pw == 1) {
      if (lane == 0) {
        Ring r{2, 1};
#pragma unroll 1
        for (int k = 2; k < 18; k++) {
          mbar_wait(emptyB + 8 * r.idx, r.phase);
          const uint32_t bar = fullB + 8 * r.idx, slot = sb + OFF_B + r.idx * SLOT_B;
          if (k < 10) {
            load_p1_b(k, slot, bar);
          } else if (k < 13) {
            if (k == 12) mbar_wait(fullA + 8 * 2, 0);
            mbar_expect_tx(bar, k < 12 ? 40960 : 20480);
#pragma unroll 1
            for (int u = 0; u < (k < 12 ? 4 : 2); u++) tma3d(slot + u * 10240, &maps.w2, bar, 0, 256 * (k - 10) + 64 * u, 5 * j);
          } else {
            mbar_expect_tx(bar, 49152);
            tma3d(slot, &maps.w3, bar, 0, 128 * (k - 13), 3 * j);
            tma3d(slot + 24576, &maps.w3, bar, 0, 128 * (k - 13) + 64, 3 * j);
          }
          r.next<NB>();
        }
        Ring r4{0, 1};
#pragma unroll 1
        for (int n = 0; n < 16; n++) {
          if (n == 0 || n == 1 || n == 3) { mbar_wait(emptyB + 8 * r.idx, r.phase); r.next<NB>(); }
          mbar_wait(bars + 8 * (B_EMPTY4 + r4.idx), r4.phase);
          const uint32_t bar = bars + 8 * (B_FULL4 + r4.idx), slot = sb + OFF_B + r4.idx * UNIT4;
          const int u = n & 3, m = ((j >> 1) + 1 + (n >> 2)) & 3;
          mbar_expect_tx(bar, u == 3 ? 25600 : 20480);
          tma3d(slot, u == 3 ? &maps.wo : &maps.w4, bar, 0, u == 3 ? 80 * j : 192 * j + 64 * u, 5 * m);
          r4.next<NU4>();
        }
      }
    } else {
      const unsigned epoch = get_epoch();
      float* accg = g_acc[epoch & 1];
      if (pw == 2) {
        {
          float* nxt = g_acc[(epoch + 1) & 1];
          constexpr int PER = ACC_FLOATS / NCTA;
#pragma unroll 1
          for (int e = lane; e < PER; e += 32) nxt[blockIdx.x * PER + e] = 0.f;
        }
        if (lane == 0) {
          flag_wait(FL_CS + j, (epoch + 1) * 16u);
          flag_wait(FL_ST + i, (epoch + 1) * 8u);
          fence_async_all();
          mbar_expect_tx(bars + 8 * B_CS, 320 + 2048);
          bulk_load(sb + OFF_CS, accg + 8 * KV_J + 80 * j, 320, bars + 8 * B_CS);
          bulk_load(sb + OFF_XST, g_xstat + 128 * i, 2048, bars + 8 * B_CS);
          TSTAMPX(21);
          l2_prefetch(w2 + (size_t)blockIdx.x * (D_ * D_ / NCTA), D_ * D_ * 2 / NCTA);
          mbar_wait(bars + 8 * B_SIGH, 0);
          l2_prefetch(w3 + (size_t)blockIdx.x * (F_ * D_ / NCTA), F_ * D_ * 2 / NCTA);
          l2_prefetch(w4 + (size_t)blockIdx.x * (F_ * D_ / NCTA), F_ * D_ * 2 / NCTA);
          l2_prefetch(wo + (size_t)blockIdx.x * (D_ * D_ / NCTA), D_ * D_ * 2 / NCTA);
          flag_wait(FL_KV + j, (epoch + 1) * 16u);
          mbar_expect_tx(bars + 8 * B_KV, KV_J * 4);
          bulk_load(sb + OFF_MISC, accg + j * KV_J, KV_J * 4, bars + 8 * B_KV);
          TSTAMPX(22);
        }
        __syncwarp();
#pragma unroll 1
        for (int m = 0; m < 6; m++) {
          const int col = 192 * j + 32 * m + 8 * (lane & 3);
          const __nv_bfloat16* p = w3 + (size_t)(40 * i + (lane >> 2) * 5) * F_ + col;
          float a[8];
#pragma unroll
          for (int e = 0; e < 8; e++) a[e] = 0.f;
#pragma unroll
          for (int it = 0; it < 5; it++) {
            const uint4 v = __ldg(reinterpret_cast<const uint4*>(p + (size_t)it * F_));
            a[0] += bf_lo(v.x); a[1] += bf_hi(v.x); a[2] += bf_lo(v.y); a[3] += bf_hi(v.y);
            a[4] += bf_lo(v.z); a[5] += bf_hi(v.z); a[6] += bf_lo(v.w); a[7] += bf_hi(v.w);
          }
#pragma unroll
          for (int e = 0; e < 4; e++) {
            const float snd = (lane & 4) ? a[e] : a[e + 4], keep = (lane & 4) ? a[e + 4] : a[e];
            a[e] = keep + __shfl_xor_sync(0xffffffffu, snd, 4);
            a[e] += __shfl_xor_sync(0xffffffffu, a[e], 8);
            a[e] += __shfl_xor_sync(0xffffffffu, a[e], 16);
          }
          if (lane < 8) red_add4(accg + 8 * KV_J + D_ + col + (lane >> 2) * 4, a[0], a[1], a[2], a[3]);
        }
        __syncwarp();
        if (lane == 0) {
          flag_add(FL_CS3 + j);
          mbar_wait(bars + 8 * B_MFREE, 0);
          flag_wait(FL_X1 + i, (epoch + 1) * 8u);
          flag_wait(FL_CS3 + j, (epoch + 1) * 16u);
          fence_async_all();
          mbar_expect_tx(bars + 8 * B_ST1, 8192 + 768);
          bulk_load(sb + OFF_CS + 320, accg + 8 * KV_J + D_ + 192 * j, 768, bars + 8 * B_ST1);
          bulk_load(sb + OFF_MISC, g_st1 + 128 * i * 8, 8192, bars + 8 * B_ST1);
        }
        __syncwarp();
        mbar_wait(bars + 8 * B_PEER, 0);
        const unsigned* fp = g_flags + (FL_PART + i * 8 + j) * 32 + lane;
        bool seen = lane >= 6;
        uint32_t n = 0;
        while (!__all_sync(0xffffffffu, seen) && ++n < (WAIT_LIMIT >> 4)) {
          if (!seen && ld_acquire(fp) == epoch + 1 && (lane < 2 || (lane < 4 ? mbar_test(bars + 8 * (B_SEND + 2), 0) && mbar_test(bars + 8 * (B_SEND + 3), 0) && mbar_test(bars + 8 * (B_EMPTY4 + 1), 0) : mbar_test(bars + 8 * (B_SDONE + lane), 0)))) {
            seen = true;
            if (lane & 1) TR4((lane >> 1) * 16 + 11);
            mbar_expect_tx(bars + 8 * (B_RDY + lane), 10240);
            bulk_load(sb + (lane < 2 ? OFF_G0 : lane < 4 ? OFF_G1 : OFF_SEND) + (lane & 1) * 10240, g_part + (size_t)(i * 8 + j) * 3840 + lane * 640, 10240,
                      bars + 8 * (B_RDY + lane));
          }
        }
      } else {
        mbar_wait(bars + 8 * B_SIGP, 0);
        if (lane < 20) {
          float a0 = 0.f, a1 = 0.f, a2 = 0.f, a3 = 0.f;
#pragma unroll 4
          for (int r = 0; r < 20; r++) {
            const uint4 v = lds128(sb + OFF_B + SPARE + r * 320 + lane * 16);
            a0 += __uint_as_float(v.x); a1 += __uint_as_float(v.y); a2 += __uint_as_float(v.z); a3 += __uint_as_float(v.w);
          }
          red_add4(accg + 8 * KV_J + 80 * j + 4 * lane, a0, a1, a2, a3);
        }
        __syncwarp();
      }
      if (pw == 3 && lane == 0) {
        flag_add(FL_CS + j); flag_add_relaxed(FL_ST + i);
        TSTAMPX(20);
        mbar_expect_tx(bars + 8 * B_XR, 20480);
#pragma unroll 1
        for (int u = 0; u < 8; u++)
          tma2d(sb + OFF_B + (u / 3) * SLOT_B + SPARE + (u % 3) * 2560, &maps.xr, bars + 8 * B_XR, 80 * j, 128 * i + 16 * u);
        const int shift = (j < 2) ? 1 : (j < 4) ? -1 : (j < 6) ? 2 : -2;
        if ((shift > 0 && i == 0) || (shift < 0 && i == 15)) {
          const int nz = shift > 0 ? shift : -shift, zr = shift > 0 ? 0 : S_ - nz;
#pragma unroll 1
          for (int e = 0; e < nz * 10; e++)
            reinterpret_cast<uint4*>(g_Hs + (size_t)(2 + zr + e / 10) * D_ + 80 * j)[e % 10] = make_uint4(0, 0, 0, 0);
          fence_async_all();
        }
        prefetch_tmap(&maps.st_h); prefetch_tmap(&maps.st_x1); prefetch_tmap(&maps.hs); prefetch_tmap(&maps.x1); prefetch_tmap(&maps.xr);
        prefetch_tmap(&maps.w2); prefetch_tmap(&maps.w3); prefetch_tmap(&maps.w4); prefetch_tmap(&maps.wo); prefetch_tmap(&maps.st_out);
        mbar_wait(bars + 8 * B_SIGH, 0);
        TSTAMPX(23);
        tma2d_store(&maps.st_h, sb + OFF_STG, 80 * j, 128 * i + 2 + shift);
        tma2d_store(&maps.st_h, sb + OFF_STG + 10240, 80 * j, 128 * i + 66 + shift);
        bulk_commit(); bulk_wait<0>();
        flag_add(FL_H + i);
        TSTAMPX(24);
        mbar_wait(bars + 8 * B_SIGKV, 0);
        TSTAMPX(25);
        asm volatile("cp.reduce.async.bulk.global.shared::cta.bulk_group.add.f32 [%0], [%1], %2;"
                     ::"l"(accg + j * KV_J), "r"(sb + OFF_MISC), "r"(KV_J * 4) : "memory");
        bulk_commit(); bulk_wait<0>();
        flag_add(FL_KV + j);
        TSTAMPX(26);
        mbar_wait(bars + 8 * B_SIGX1, 0);
        TSTAMPX(27);
        tma2d_store(&maps.st_x1, sb + OFF_STG, 80 * j, 128 * i);
        tma2d_store(&maps.st_x1, sb + OFF_STG + 10240, 80 * j, 128 * i + 64);
        bulk_commit(); bulk_wait<0>();
        flag_add(FL_X1 + i);
        TSTAMPX(28);
        send_stream(0, epoch + 1);
      }
    }
  } else {
    asm volatile("setmaxnreg.inc.sync.aligned.u32 232;");
    const int wg = tid >> 7, warp = tid >> 5, lane = tid & 31, t = lane & 3;
    const int rloc = warp * 16 + (lane >> 2);
    const float* s_cs = reinterpret_cast<const float*>(sgen + OFF_CS);
    auto signal = [&](int b) {
      __syncwarp();
      if (lane == 0) mbar_arrive(bars + 8 * b);
    };
    auto releaseB = [&](uint32_t bar) {
      __syncwarp();
      if (lane == 0) mbar_arrive(bar);
    };
    auto release = [&](uint32_t bar) {
      __syncwarp();
      if (lane < 2) mbar_arrive_cta(bar, lane);
    };
    const uint32_t stg_lane = (warp * 16 + ((lane >> 3) & 1) * 8 + (lane & 7)) * 160 + (lane >> 4) * 16;

    {
#pragma unroll 1
      for (int e = tid; e < 800; e += 256) sts128(sb + OFF_MISC + e * 16, make_uint4(0, 0, 0, 0));
      bar_sync(1, 256);
      float f[40];
      float s = 0.f, gs = 0.f;
#pragma unroll
      for (int c = 0; c < 5; c++) {
        const uint32_t vv[4] = {pv[c].x, pv[c].y, pv[c].z, pv[c].w}, ww[4] = {pw_[c].x, pw_[c].y, pw_[c].z, pw_[c].w};
#pragma unroll
        for (int e = 0; e < 4; e++) {
          f[8 * c + 2 * e] = bf_lo(vv[e]); f[8 * c + 2 * e + 1] = bf_hi(vv[e]);
          s += f[8 * c + 2 * e] + f[8 * c + 2 * e + 1];
          gs = fmaf(f[8 * c + 2 * e], bf_lo(ww[e]), gs); gs = fmaf(f[8 * c + 2 * e + 1], bf_hi(ww[e]), gs);
        }
      }
#pragma unroll
      for (int o = 1; o < 16; o <<= 1) { s += __shfl_xor_sync(0xffffffffu, s, o); gs += __shfl_xor_sync(0xffffffffu, gs, o); }
      const float mean = s * (1.f / D_);
      float q = 0.f;
#pragma unroll
      for (int e = 0; e < 40; e++) { const float d = f[e] - mean; q = fmaf(d, d, q); }
#pragma unroll
      for (int o = 1; o < 16; o <<= 1) q += __shfl_xor_sync(0xffffffffu, q, o);
      const float rstd = rsqrtf(q * (1.f / D_) + 1e-5f);
      if (tid < 200) {
        const uint32_t cd = sb + OFF_B + SPARE + tid * 32;
        sts128(cd, make_uint4(__float_as_uint(bf_lo(pc[0].x) + bf_lo(pc[1].x)), __float_as_uint(bf_hi(pc[0].x) + bf_hi(pc[1].x)),
                              __float_as_uint(bf_lo(pc[0].y) + bf_lo(pc[1].y)), __float_as_uint(bf_hi(pc[0].y) + bf_hi(pc[1].y))));
        sts128(cd + 16, make_uint4(__float_as_uint(bf_lo(pc[0].z) + bf_lo(pc[1].z)), __float_as_uint(bf_hi(pc[0].z) + bf_hi(pc[1].z)),
                                   __float_as_uint(bf_lo(pc[0].w) + bf_lo(pc[1].w)), __float_as_uint(bf_hi(pc[0].w) + bf_hi(pc[1].w))));
        const uint32_t ww[4] = {pre.x, pre.y, pre.z, pre.w};
        const int h = tid / 50;
#pragma unroll
        for (int e = 0; e < 8; e++) {
          const int idx = tid * 8 + e, k = idx / 20, ff = idx - 20 * k;
          const int n = 40 * (h >> 1) + 8 * (ff >> 2) + 2 * (ff & 3) + (h & 1);
          const int off = (k >> 4) * 2560 + n * 32 + ((((k >> 3) ^ (n >> 2)) & 1) << 4) + (k & 7) * 2;
          *reinterpret_cast<unsigned short*>(sgen + OFF_MISC + off) = (unsigned short)(ww[e >> 1] >> ((e & 1) * 16));
        }
      }
      fence_async_smem();
      asm volatile("barrier.cluster.wait.aligned;" ::: "memory");
      if ((tid & 15) == 0) g_xstat[128 * i + 16 * j + (tid >> 4)] = make_float4(rstd, -mean * rstd, rcp(1.f + __expf(-gs)), 0.f);
      signal(B_SIGP);
    }
    TSTAMP(1);

    Ring ra{0, 0}, rb{0, 0};
    uint32_t qp[2][10], P[2][10];
    float st_g[2];
    {
      float accM[128], accR[32];
      zero_regs(accM); zero_regs(accR);
      uint32_t pa = 0, pb = 0;
#pragma unroll 1
      for (int k = 0; k < 10; k++) {
        mbar_wait(fullA + 8 * ra.idx, ra.phase);
        if (tid == 0) TRACE(32 + k);
        mbar_wait(fullB + 8 * rb.idx, rb.phase);
        if (tid == 0) TRACE(64 + k);
        if (k == 0) TSTAMP(2);
        const uint32_t a0 = sb16 + ((OFF_A + ra.idx * SLOT_A + wg * 8192) >> 4), b0 = sb16 + ((OFF_B + rb.idx * SLOT_B) >> 4);
        wg_fence();
#pragma unroll
        for (int kk = 0; kk < 4; kk++) {
          const uint64_t da = make_desc(a0, kk * 32, 16, 1024, 1);
          mma_ss256(accM, da, make_desc(b0, kk * 2048, 8192, 1024, 1));
          mma_ss64(accR, da, make_desc(b0, 32768 + kk * 512, 2048, 256, 3));
          if (kk == 0) {
            wg_commit();
            if (k > 0) {
              wg_wait<1>();
              if (k - 1 < 8) release(emptyA + 8 * pa);
              releaseB(emptyB + 8 * pb);
            }
          }
        }
        wg_commit();
        pa = ra.idx; pb = rb.idx;
        ra.next<NA>(); rb.next<NB>();
      }
      TSTAMP(18);
      float st_rstd[2], st_mr[2];
      mbar_wait(bars + 8 * B_CS, 0);
#pragma unroll
      for (int r = 0; r < 2; r++) {
        const uint4 st = lds128(sb + OFF_XST + (rloc + 8 * r) * 16);
        st_rstd[r] = __uint_as_float(st.x); st_mr[r] = __uint_as_float(st.y); st_g[r] = __uint_as_float(st.z);
      }
      TSTAMP(19);
      wg_wait<0>();
      fence_regs(accM); fence_regs(accR);
      TSTAMP(3);
#define ACC(P_, G, I_) ((G) < 8 ? accM[(P_) * 32 + ((G) & 7) * 4 + (I_)] : accR[(P_) * 8 + ((G) & 1) * 4 + (I_)])
      {
        uint32_t hv[10][2];
#pragma unroll
        for (int g = 0; g < 10; g++) {
          const float2 cs = *reinterpret_cast<const float2*>(s_cs + 8 * g + 2 * t);
          const float v0 = gelu_s(fmaf(ACC(0, g, 0), st_rstd[0], st_mr[0] * cs.x), 0.5f), v1 = gelu_s(fmaf(ACC(0, g, 1), st_rstd[0], st_mr[0] * cs.y), 0.5f);
          const float v2 = gelu_s(fmaf(ACC(0, g, 2), st_rstd[1], st_mr[1] * cs.x), 0.5f), v3 = gelu_s(fmaf(ACC(0, g, 3), st_rstd[1], st_mr[1] * cs.y), 0.5f);
          hv[g][0] = pack_bf16(v0, v1); hv[g][1] = pack_bf16(v2, v3);
        }
        bar_sync(1, 256);
#pragma unroll
        for (int s = 0; s < 5; s++) stsm4(sb + OFF_STG + stg_lane + s * 32, hv[2 * s][0], hv[2 * s][1], hv[2 * s + 1][0], hv[2 * s + 1][1]);
        fence_async_smem();
        signal(B_SIGH);
      }
      TSTAMP(4);
      uint32_t kf[5][4], qf[5][4];
#pragma unroll
      for (int s = 0; s < 5; s++) {
        kf[s][0] = pack_bf16(ACC(2, 2 * s, 0), ACC(2, 2 * s, 1)); kf[s][1] = pack_bf16(ACC(2, 2 * s, 2), ACC(2, 2 * s, 3));
        kf[s][2] = pack_bf16(ACC(2, 2 * s + 1, 0), ACC(2, 2 * s + 1, 1)); kf[s][3] = pack_bf16(ACC(2, 2 * s + 1, 2), ACC(2, 2 * s + 1, 3));
        qf[s][0] = pack_bf16(ACC(1, 2 * s, 0), ACC(1, 2 * s, 1)); qf[s][1] = pack_bf16(ACC(1, 2 * s, 2), ACC(1, 2 * s, 3));
        qf[s][2] = pack_bf16(ACC(1, 2 * s + 1, 0), ACC(1, 2 * s + 1, 1)); qf[s][3] = pack_bf16(ACC(1, 2 * s + 1, 2), ACC(1, 2 * s + 1, 3));
      }
      float pk[40], pq[40];
      wg_fence();
#pragma unroll
      for (int s = 0; s < 5; s++) {
        if (s == 0) mma_rs80_k_z(pk, kf[s], make_desc(sb16, OFF_MISC, 16, 256, 3));
        else mma_rs80_k(pk, kf[s], make_desc(sb16, OFF_MISC + s * 2560, 16, 256, 3));
      }
#pragma unroll
      for (int s = 0; s < 5; s++) {
        if (s == 0) mma_rs80_k_z(pq, qf[s], make_desc(sb16, OFF_MISC, 16, 256, 3));
        else mma_rs80_k(pq, qf[s], make_desc(sb16, OFF_MISC + s * 2560, 16, 256, 3));
      }
      wg_commit();
      {
        const int mat = lane >> 3;
        const int tok = warp * 16 + (mat & 1) * 8 + (lane & 7);
        const uint32_t ones = (t == 0) ? 0x00003f80u : 0u;
        __syncwarp();
#pragma unroll
        for (int p = 0; p < 2; p++) {
          const uint32_t rowa = sb + OFF_A + p * SLOT_A + tok * 128;
#pragma unroll
          for (int gg = 0; gg < 3; gg++) {
            const int g0 = 5 * p + 2 * gg;
            uint32_t r0 = pack_bf16(ACC(3, g0, 0), ACC(3, g0, 1)), r1 = pack_bf16(ACC(3, g0, 2), ACC(3, g0, 3));
            uint32_t r2 = ones, r3 = ones;
            if (gg < 2) { r2 = pack_bf16(ACC(3, g0 + 1, 0), ACC(3, g0 + 1, 1)); r3 = pack_bf16(ACC(3, g0 + 1, 2), ACC(3, g0 + 1, 3)); }
            stsm4(rowa + (((2 * gg + (mat >> 1)) ^ (tok & 7)) << 4), r0, r1, r2, r3);
          }
        }
      }
#undef ACC
      wg_wait<0>();
      fence_regs(pk); fence_regs(pq);
#pragma unroll
      for (int G = 0; G < 10; G++) {
        P[0][G] = pack_bf16(pk[4 * G], pk[4 * G + 1]); P[1][G] = pack_bf16(pk[4 * G + 2], pk[4 * G + 3]);
        qp[0][G] = pack_bf16(pq[4 * G], pq[4 * G + 1]); qp[1][G] = pack_bf16(pq[4 * G + 2], pq[4 * G + 3]);
      }
    }

    uint32_t fr[10][4];
    {
      TSTAMP(16);
      feature_map(P, fr);
      TSTAMP(17);
      const int mat = lane >> 3;
      const int tok = warp * 16 + (mat & 1) * 8 + (lane & 7);
      const uint32_t base = sb + OFF_B + tok * 32 + (((mat >> 1) ^ ((tok >> 2) & 1)) << 4);
#pragma unroll
      for (int G = 0; G < 10; G++) stsm4(base + G * 4096, fr[G][0], fr[G][1], fr[G][2], fr[G][3]);
      fence_async_smem();
      bar_sync(1, 256);
      float kv[40];
      const uint32_t a0 = sb16 + ((OFF_A + wg * SLOT_A) >> 4), b0 = sb16 + ((OFF_B + wg * 20480) >> 4);
      wg_fence();
#pragma unroll
      for (int ks = 0; ks < 8; ks++) {
        if (ks == 0) mma_ss80_tt_z(kv, make_desc(a0, 0, 16, 1024, 1), make_desc(b0, 0, 4096, 256, 3));
        else mma_ss80_tt(kv, make_desc(a0, ks * 2048, 16, 1024, 1), make_desc(b0, ks * 512, 4096, 256, 3));
      }
      wg_commit();
      wg_wait<0>();
      fence_regs(kv);
      TSTAMP(31);
      release(emptyA); release(emptyA + 8); releaseB(emptyB);
      const uint32_t dst = sb + OFF_MISC + wg * (KV_PAIR * 4);
      const int m0 = (warp & 3) * 16 + (lane >> 2);
#pragma unroll
      for (int r = 0; r < 2; r++) {
        const int m = m0 + 8 * r;
        const bool hi = m >= 20;
        uint32_t v[10];
#pragma unroll
        for (int G = 0; G < 10; G++) v[G] = __float_as_uint(hi ? kv[4 * G + 2 * r + 1] : kv[4 * G + 2 * r]);
        const uint32_t p = dst + 4 * (m < 40 ? m * 48 + t * 12 : 1920 + t * 24 + 12);
        if (m <= 40) {
          sts128(p, make_uint4(v[0], v[1], v[2], v[3])); sts128(p + 16, make_uint4(v[4], v[5], v[6], v[7]));
          sts128(p + 32, make_uint4(v[8], v[9], 0u, 0u));
        }
      }
      if (m0 == 32) {
        const uint32_t p = dst + 4 * (1920 + t * 24);
        sts128(p, make_uint4(__float_as_uint(kv[2]), __float_as_uint(kv[6]), __float_as_uint(kv[10]), __float_as_uint(kv[14])));
        sts128(p + 16, make_uint4(__float_as_uint(kv[18]), __float_as_uint(kv[22]), __float_as_uint(kv[26]), __float_as_uint(kv[30])));
        sts128(p + 32, make_uint4(__float_as_uint(kv[34]), __float_as_uint(kv[38]), 0u, 0u));
      }
      fence_async_smem();
      signal(B_SIGKV);
    }
    TSTAMP(5);

    uint32_t xv[2][10];
    {
      {
        mbar_wait(bars + 8 * B_XR, 0);
        const uint32_t xa = sb + OFF_B + (warp / 3) * SLOT_B + SPARE + (warp % 3) * 2560 + (lane >> 2) * 160 + t * 4;
#pragma unroll
        for (int g = 0; g < 10; g++) { xv[0][g] = lds32(xa + g * 16); xv[1][g] = lds32(xa + 1280 + g * 16); }
      }
      float acc[40];
      zero_regs(acc);
      uint32_t pa = 0, pb = 0;
#pragma unroll 1
      for (int k = 0; k < 10; k++) {
        mbar_wait(fullA + 8 * ra.idx, ra.phase);
        if (tid == 0) TRACE(42 + k);
        if ((k & 3) == 0) mbar_wait(fullB + 8 * rb.idx, rb.phase);
        if (tid == 0) TRACE(74 + k);
        if (k == 0) TSTAMP(6);
        const uint32_t a0 = sb16 + ((OFF_A + ra.idx * SLOT_A + wg * 8192) >> 4);
        const uint32_t b0 = sb16 + ((OFF_B + rb.idx * SLOT_B + (k & 3) * 10240) >> 4);
        wg_fence();
#pragma unroll
        for (int kk = 0; kk < 4; kk++) {
          mma_ss80(acc, make_desc(a0, kk * 32, 16, 1024, 1), make_desc(b0, kk * 512, 2048, 256, 3));
          if (kk == 1) {
            wg_commit();
            if (k > 0) {
              wg_wait<1>();
              release(emptyA + 8 * pa);
              if ((k & 3) == 0) releaseB(emptyB + 8 * pb);
            }
          }
        }
        wg_commit();
        pa = ra.idx; pb = rb.idx;
        ra.next<NA>();
        if ((k & 3) == 3 || k == 9) rb.next<NB>();
      }
      wg_wait<0>();
      fence_regs(acc);
      release(emptyA + 8 * pa); releaseB(emptyB + 8 * pb);
      TSTAMP(7);
#pragma unroll
      for (int r = 0; r < 2; r++) {
#pragma unroll
        for (int g = 0; g < 10; g++)
          xv[r][g] = pack_bf16(bf_lo(xv[r][g]) + acc[4 * g + 2 * r], bf_hi(xv[r][g]) + acc[4 * g + 2 * r + 1]);
      }
      bar_sync(1, 256);
#pragma unroll
      for (int s = 0; s < 5; s++) stsm4(sb + OFF_STG + stg_lane + s * 32, xv[0][2 * s], xv[1][2 * s], xv[0][2 * s + 1], xv[1][2 * s + 1]);
#pragma unroll
      for (int r = 0; r < 2; r++) {
        float s = 0.f;
#pragma unroll
        for (int g = 0; g < 10; g++) {
          acc[4 * g + 2 * r] = bf_lo(xv[r][g]); acc[4 * g + 2 * r + 1] = bf_hi(xv[r][g]);
          s += acc[4 * g + 2 * r] + acc[4 * g + 2 * r + 1];
        }
        s += __shfl_xor_sync(0xffffffffu, s, 1); s += __shfl_xor_sync(0xffffffffu, s, 2);
        const float mu = s * (1.f / 80.f);
        float q = 0.f;
#pragma unroll
        for (int g = 0; g < 10; g++) {
          const float d0 = acc[4 * g + 2 * r] - mu, d1 = acc[4 * g + 2 * r + 1] - mu;
          q = fmaf(d0, d0, q); q = fmaf(d1, d1, q);
        }
        q += __shfl_xor_sync(0xffffffffu, q, 1); q += __shfl_xor_sync(0xffffffffu, q, 2);
        if (t == 0) g_st1[(128 * i + rloc + 8 * r) * 8 + j] = make_float2(mu, q);
      }
      fence_async_smem();
      signal(B_SIGX1);
    }
    TSTAMP(8);

    uint32_t of[5][4];
    {
      feature_map(qp, fr);
      mbar_wait(bars + 8 * B_KV, 0);
      uint4 kvr[2][3];
#pragma unroll
      for (int u = 0; u < 2; u++) {
        const int it = tid + 256 * u, p = it / 192, rem = it - 192 * p, n = rem >> 2, tq = rem & 3;
        const uint32_t sp = sb + OFF_MISC + 4 * (p * KV_PAIR + (n < 40 ? n * 48 + tq * 12 : 1920 + tq * 24 + (n & 1) * 12));
        if (it < 384) { kvr[u][0] = lds128(sp); kvr[u][1] = lds128(sp + 16); kvr[u][2] = lds128(sp + 32); }
      }
      bar_sync(1, 256);
#pragma unroll
      for (int u = 0; u < 2; u++) {
        const int it = tid + 256 * u, p = it / 192, rem = it - 192 * p, n = rem >> 2, tq = rem & 3;
        const int sh = (n < 40 ? (n >= 20) : (n & 1)) * 16;
        const uint32_t v[10] = {kvr[u][0].x, kvr[u][0].y, kvr[u][0].z, kvr[u][0].w, kvr[u][1].x, kvr[u][1].y, kvr[u][1].z, kvr[u][1].w, kvr[u][2].x, kvr[u][2].y};
        uint8_t* dst = sgen + OFF_MISC + p * 7680 + n * 32 + tq * 4;
        const int sw = ((n >> 2) & 1) << 4;
        if (it < 384) {
#pragma unroll
          for (int G = 0; G < 10; G++)
            *reinterpret_cast<uint32_t*>(dst + (G >> 1) * 1536 + (((G & 1) << 4) ^ sw)) = pack_bf16(__uint_as_float(v[G]), 0.f) << sh;
        }
      }
      fence_async_smem();
      bar_sync(1, 256);
      float o0[24], o1[24];
      wg_fence();
#pragma unroll
      for (int g = 0; g < 5; g++) {
        if (g == 0) mma_rs48_k_z(o0, fr[g], make_desc(sb16, OFF_MISC, 16, 256, 3));
        else mma_rs48_k(o0, fr[g], make_desc(sb16, OFF_MISC + g * 1536, 16, 256, 3));
      }
#pragma unroll
      for (int g = 0; g < 5; g++) {
        if (g == 0) mma_rs48_k_z(o1, fr[5], make_desc(sb16, OFF_MISC + 7680, 16, 256, 3));
        else mma_rs48_k(o1, fr[5 + g], make_desc(sb16, OFF_MISC + 7680 + g * 1536, 16, 256, 3));
      }
      wg_commit();
      wg_wait<0>();
      fence_regs(o0); fence_regs(o1);
      signal(B_MFREE);
#pragma unroll
      for (int r = 0; r < 2; r++) {
        const float a0 = __fdividef(st_g[r], o0[20 + 2 * r] + 1e-6f), a1 = __fdividef(st_g[r], o0[21 + 2 * r] + 1e-6f);
        const float b0 = __fdividef(st_g[r], o1[20 + 2 * r] + 1e-6f), b1 = __fdividef(st_g[r], o1[21 + 2 * r] + 1e-6f);
        const float am = t < 2 ? a0 : a1, bm = t < 2 ? b0 : b1;
#pragma unroll
        for (int g = 0; g < 5; g++) {
          const float sa = g < 2 ? a0 : (g == 2 ? am : a1), sb2 = g < 2 ? b0 : (g == 2 ? bm : b1);
          of[g >> 1][(g & 1) * 2 + r] = pack_bf16(o0[4 * g + 2 * r] * sa, o0[4 * g + 2 * r + 1] * sa);
          of[(5 + g) >> 1][((5 + g) & 1) * 2 + r] = pack_bf16(o1[4 * g + 2 * r] * sb2, o1[4 * g + 2 * r + 1] * sb2);
        }
      }
    }
    TSTAMP(9);

    uint32_t hf[12][4];
    {
      float acc[96];
      zero_regs(acc);
      uint32_t pa = 0, pb = 0;
#pragma unroll 1
      for (int k = 0; k < 10; k++) {
        mbar_wait(fullA + 8 * ra.idx, ra.phase);
        if (tid == 0) TRACE(52 + k);
        if ((k & 1) == 0) mbar_wait(fullB + 8 * rb.idx, rb.phase);
        if (tid == 0) TRACE(84 + k);
        if (k == 0) TSTAMP(10);
        const uint32_t a0 = sb16 + ((OFF_A + ra.idx * SLOT_A + wg * 8192) >> 4);
        const uint32_t b0 = sb16 + ((OFF_B + rb.idx * SLOT_B + (k & 1) * 24576) >> 4);
        wg_fence();
#pragma unroll
        for (int kk = 0; kk < 4; kk++) {
          mma_ss192(acc, make_desc(a0, kk * 32, 16, 1024, 1), make_desc(b0, kk * 2048, 8192, 1024, 1));
          if (kk == 0) {
            wg_commit();
            if (k > 0) {
              wg_wait<1>();
              release(emptyA + 8 * pa);
              if ((k & 1) == 0) releaseB(emptyB + 8 * pb);
            }
          }
        }
        wg_commit();
        pa = ra.idx; pb = rb.idx;
        ra.next<NA>();
        if (k & 1) rb.next<NB>();
      }
      float rs[2], mm[2];
      mbar_wait(bars + 8 * B_ST1, 0);
#pragma unroll
      for (int r = 0; r < 2; r++) {
        const uint4 su = lds128(sb + OFF_MISC + (rloc + 8 * r) * 64 + t * 16);
        const float m0 = __uint_as_float(su.x), m1 = __uint_as_float(su.z);
        float mu = m0 + m1;
        mu += __shfl_xor_sync(0xffffffffu, mu, 1); mu += __shfl_xor_sync(0xffffffffu, mu, 2);
        mu *= 0.125f;
        const float d0 = m0 - mu, d1 = m1 - mu;
        float q = __uint_as_float(su.y) + __uint_as_float(su.w) + 80.f * (d0 * d0 + d1 * d1);
        q += __shfl_xor_sync(0xffffffffu, q, 1); q += __shfl_xor_sync(0xffffffffu, q, 2);
        rs[r] = rsqrtf(q * (1.f / D_) + 1e-5f);
        mm[r] = -mu * rs[r];
      }
      wg_wait<0>();
      fence_regs(acc);
      releaseB(emptyB + 8 * pb);
      release(bars + 8 * B_PEER);
      TSTAMP(11);
      const float hs0 = 0.5f - 0.5f * st_g[0], hs1 = 0.5f - 0.5f * st_g[1];
#pragma unroll
      for (int g = 0; g < 24; g++) {
        const float2 cs = *reinterpret_cast<const float2*>(s_cs + 80 + 8 * g + 2 * t);
        const float v0 = gelu_s(fmaf(acc[4 * g], rs[0], mm[0] * cs.x), hs0), v1 = gelu_s(fmaf(acc[4 * g + 1], rs[0], mm[0] * cs.y), hs0);
        const float v2 = gelu_s(fmaf(acc[4 * g + 2], rs[1], mm[1] * cs.x), hs1), v3 = gelu_s(fmaf(acc[4 * g + 3], rs[1], mm[1] * cs.y), hs1);
        hf[g >> 1][(g & 1) * 2] = pack_bf16(v0, v1);
        hf[g >> 1][(g & 1) * 2 + 1] = pack_bf16(v2, v3);
      }
    }
    TSTAMP(12);

    {
      float acc[80], kp[40];
      const int wt = tid & 127;
      const uint32_t peer = map_peer(sb, rank ^ 1);
      Ring r4{0, 0};
      auto add16 = [&](uint32_t src) {
#pragma unroll
        for (int q = 0; q < 5; q++) {
          const uint4 v = lds128(src + q * 2048);
          float* d = &kp[8 * q];
          d[0] += bf_lo(v.x); d[1] += bf_hi(v.x); d[2] += bf_lo(v.y); d[3] += bf_hi(v.y);
          d[4] += bf_lo(v.z); d[5] += bf_hi(v.z); d[6] += bf_lo(v.w); d[7] += bf_hi(v.w);
        }
      };
      auto finish = [&](int c) {
        if (c > 1) mbar_wait(bars + 8 * (B_SDONE + 2 * (c - 2) + wg), 0);
        mbar_wait(bars + 8 * (B_DSR + 2 * (c - 1) + wg), 0);
        if (tid == 128) TR4((c - 1) * 16 + 3);
        add16(sb + OFF_DS + ((c - 1) & 1) * 20480 + wg * 10240 + wt * 16);
        const uint32_t dst = sb + OFF_SEND + wg * 10240 + wt * 16;
#pragma unroll
        for (int q = 0; q < 5; q++) {
          const float* d = &kp[8 * q];
          sts128(dst + q * 2048, make_uint4(pack_bf16(d[0], d[1]), pack_bf16(d[2], d[3]), pack_bf16(d[4], d[5]), pack_bf16(d[6], d[7])));
        }
        fence_async_smem();
        signal(B_SEND + 2 * (c - 1) + wg);
        if (tid == 128) TR4((c - 1) * 16 + 6);
      };
      zero_regs(kp);
      if (wg == 1) bar_sync(2, 256);
#pragma unroll 1
      for (int c = 0; c < 4; c++) {
        uint32_t prev = 0;
#pragma unroll
        for (int u = 0; u < 4; u++) {
          mbar_wait(bars + 8 * (B_FULL4 + r4.idx), r4.phase);
          const uint32_t b0 = sb16 + ((OFF_B + r4.idx * UNIT4) >> 4);
          if (u == 0 && tid == 128) TR4(c * 16 + 0);
          wg_fence();
#pragma unroll
          for (int s = 0; s < (u < 3 ? 4 : 5); s++) {
            const uint64_t db = make_desc(b0, s * 1024, u < 3 ? 4096 : 5120, 512, 2);
            if (u == 0 && s == 0) mma_rs160_n_z(acc, hf[0], db);
            else if (u < 3) mma_rs160_n(acc, hf[(4 * u + s) % 12], db);
            else mma_rs160_n(acc, of[s], db);
            if (s == 1 && u > 0) { wg_commit(); wg_wait<1>(); releaseB(bars + 8 * (B_EMPTY4 + prev)); }
          }
          wg_commit();
          prev = r4.idx;
          r4.next<NU4>();
          if (u == 1 && c == 0 && wg == 0) bar_arrive(2, 256);
          if (u == 0 && c > 0) finish(c);
          if (u == 2) {
            if (c == 3) {
              const float w0 = 1.f - st_g[0], w1s = 1.f - st_g[1];
#pragma unroll
              for (int g = 0; g < 10; g++) {
                kp[4 * g] = w0 * bf_lo(xv[0][g]); kp[4 * g + 1] = w0 * bf_hi(xv[0][g]);
                kp[4 * g + 2] = w1s * bf_lo(xv[1][g]); kp[4 * g + 3] = w1s * bf_hi(xv[1][g]);
              }
#pragma unroll 1
              for (int e = 0; e < 2; e++) {
                mbar_wait(bars + 8 * (B_RDY + 2 * e + wg), 0);
                add16(sb + (e == 0 ? OFF_G0 : OFF_G1) + wg * 10240 + wt * 16);
              }
            } else {
              zero_regs(kp);
            }
          }
        }
        if (tid == 128) TR4(c * 16 + 2);
        if (c == 0) mbar_wait(bars + 8 * B_PEER, 0);
        wg_wait<0>();
        fence_regs(acc);
        releaseB(bars + 8 * (B_EMPTY4 + prev));
        if (tid == 128) TR4(c * 16 + 5);
        uint32_t sn[20];
        if (rank) {
#pragma unroll
          for (int e = 0; e < 20; e++) sn[e] = pack_bf16(acc[2 * e], acc[2 * e + 1]);
#pragma unroll
          for (int e = 0; e < 40; e++) kp[e] += acc[40 + e];
        } else {
#pragma unroll
          for (int e = 0; e < 20; e++) sn[e] = pack_bf16(acc[40 + 2 * e], acc[41 + 2 * e]);
#pragma unroll
          for (int e = 0; e < 40; e++) kp[e] += acc[e];
        }
        fence_regs(kp);
        const uint32_t dso = peer + OFF_DS + (c & 1) * 20480 + wg * 10240 + wt * 16, dsb = peer + OFF_BAR + 8 * (B_DSR + 2 * c + wg);
#pragma unroll
        for (int q = 0; q < 5; q++) st_async16(dso + q * 2048, sn[4 * q], sn[4 * q + 1], sn[4 * q + 2], sn[4 * q + 3], dsb);
      }
      TSTAMP(13);
#pragma unroll 1
      for (int c = 0; c < 2; c++) {
        mbar_wait(bars + 8 * ((c == 0 ? B_DSR + 6 : B_RDY + 4) + wg), 0);
        add16(sb + (c == 0 ? OFF_DS + 20480 : OFF_SEND) + wg * 10240 + wt * 16);
      }
      TSTAMP(14);
#pragma unroll
      for (int s = 0; s < 5; s++)
        stsm4(sb + OFF_DS + stg_lane + s * 32, pack_bf16(kp[8 * s], kp[8 * s + 1]), pack_bf16(kp[8 * s + 2], kp[8 * s + 3]),
              pack_bf16(kp[8 * s + 4], kp[8 * s + 5]), pack_bf16(kp[8 * s + 6], kp[8 * s + 7]));
      fence_async_smem();
      __syncwarp();
      if (lane == 0) {
        tma2d_store(&maps.st_out, sb + OFF_DS + warp * 2560, 80 * j, 128 * i + 16 * warp);
        bulk_commit(); bulk_wait_read();
      }
    }
    TSTAMP(15);
    if (tid == 0) asm volatile("red.relaxed.gpu.global.add.u32 [%0], 1;" ::"l"(g_flags + FL_DONE * 32) : "memory");
  }
}

namespace {
typedef CUresult (*EncodeFn)(CUtensorMap*, CUtensorMapDataType, cuuint32_t, void*, const cuuint64_t*, const cuuint64_t*,
                             const cuuint32_t*, const cuuint32_t*, CUtensorMapInterleave, CUtensorMapSwizzle,
                             CUtensorMapL2promotion, CUtensorMapFloatOOBfill);

void encode(EncodeFn fn, CUtensorMap* m, const void* ptr, int rank, const cuuint64_t* dims, const cuuint64_t* strides,
            const cuuint32_t* box, CUtensorMapSwizzle swz) {
  cuuint32_t es[5] = {1, 1, 1, 1, 1};
  fn(m, CU_TENSOR_MAP_DATA_TYPE_BFLOAT16, rank, const_cast<void*>(ptr), dims, strides, box, es, CU_TENSOR_MAP_INTERLEAVE_NONE,
     swz, CU_TENSOR_MAP_L2_PROMOTION_L2_128B, CU_TENSOR_MAP_FLOAT_OOB_FILL_NONE);
}
}

extern "C" void kernel_launch(void* const* d_in, const int* in_sizes, int n_in, void* d_out, int out_size) {
  (void)in_sizes; (void)n_in; (void)out_size;
  const __nv_bfloat16* x = (const __nv_bfloat16*)d_in[0];
  const __nv_bfloat16* wqkv = (const __nv_bfloat16*)d_in[1];
  const __nv_bfloat16* wphi = (const __nv_bfloat16*)d_in[2];
  const __nv_bfloat16* wo = (const __nv_bfloat16*)d_in[3];
  const __nv_bfloat16* w1 = (const __nv_bfloat16*)d_in[5];
  const __nv_bfloat16* w2 = (const __nv_bfloat16*)d_in[6];
  const __nv_bfloat16* w3 = (const __nv_bfloat16*)d_in[7];
  const __nv_bfloat16* w4 = (const __nv_bfloat16*)d_in[8];
  const __nv_bfloat16* gate_w = (const __nv_bfloat16*)d_in[9];

  static EncodeFn enc = nullptr;
  static void *pHs = nullptr, *pX1 = nullptr;
  if (!enc) {
    cudaDriverEntryPointQueryResult qr;
    cudaGetDriverEntryPoint("cuTensorMapEncodeTiled", (void**)&enc, cudaEnableDefault, &qr);
    cudaGetSymbolAddress(&pHs, g_Hs);
    cudaGetSymbolAddress(&pX1, g_X1);
    cudaFuncSetAttribute(fused_kernel, cudaFuncAttributeMaxDynamicSharedMemorySize, SMEM_BYTES);
  }
  Maps m;
  {
    cuuint64_t dims[2] = {D_, S_}, str[1] = {D_ * 2};
    cuuint32_t boxh[2] = {64, 64};
    encode(enc, &m.x, x, 2, dims, str, boxh, CU_TENSOR_MAP_SWIZZLE_128B);
    encode(enc, &m.hs, (const char*)pHs + 2 * D_ * 2, 2, dims, str, boxh, CU_TENSOR_MAP_SWIZZLE_128B);
    encode(enc, &m.x1, pX1, 2, dims, str, boxh, CU_TENSOR_MAP_SWIZZLE_128B);
    cuuint32_t boxs[2] = {80, 64};
    cuuint64_t dimsp[2] = {D_, S_ + 4};
    encode(enc, &m.st_h, pHs, 2, dimsp, str, boxs, CU_TENSOR_MAP_SWIZZLE_NONE);
    encode(enc, &m.st_x1, pX1, 2, dims, str, boxs, CU_TENSOR_MAP_SWIZZLE_NONE);
    cuuint32_t boxr[2] = {80, 16};
    encode(enc, &m.st_out, d_out, 2, dims, str, boxr, CU_TENSOR_MAP_SWIZZLE_NONE);
    encode(enc, &m.xr, x, 2, dims, str, boxr, CU_TENSOR_MAP_SWIZZLE_NONE);
  }
  {
    cuuint64_t dims[3] = {80, D_, 8}, str[2] = {D_ * 2, 160};
    cuuint32_t boxm[3] = {64, 64, 1}, boxr[3] = {16, 64, 1};
    encode(enc, &m.w1m, w1, 3, dims, str, boxm, CU_TENSOR_MAP_SWIZZLE_128B);
    encode(enc, &m.w1r, w1, 3, dims, str, boxr, CU_TENSOR_MAP_SWIZZLE_32B);
  }
  {
    cuuint64_t dims[4] = {80, D_, 3, 8}, str[3] = {3 * D_ * 2, D_ * 2, 160};
    cuuint32_t boxm[4] = {64, 64, 3, 1}, boxr[4] = {16, 64, 3, 1};
    encode(enc, &m.qm, wqkv, 4, dims, str, boxm, CU_TENSOR_MAP_SWIZZLE_128B);
    encode(enc, &m.qr, wqkv, 4, dims, str, boxr, CU_TENSOR_MAP_SWIZZLE_32B);
  }
  {
    cuuint64_t dims[3] = {16, D_, 40}, str[2] = {D_ * 2, 32};
    cuuint32_t box2[3] = {16, 64, 5};
    encode(enc, &m.w2, w2, 3, dims, str, box2, CU_TENSOR_MAP_SWIZZLE_32B);
  }
  {
    cuuint64_t dims[3] = {32, D_, 20}, dims4[3] = {32, F_, 20}, str[2] = {D_ * 2, 64};
    cuuint32_t box4[3] = {32, 64, 5}, boxo[3] = {32, 80, 5};
    encode(enc, &m.w4, w4, 3, dims4, str, box4, CU_TENSOR_MAP_SWIZZLE_64B);
    encode(enc, &m.wo, wo, 3, dims, str, boxo, CU_TENSOR_MAP_SWIZZLE_64B);
  }
  {
    cuuint64_t dims[3] = {64, D_, 24}, str[2] = {F_ * 2, 128};
    cuuint32_t box[3] = {64, 64, 3};
    encode(enc, &m.w3, w3, 3, dims, str, box, CU_TENSOR_MAP_SWIZZLE_128B);
  }
  fused_kernel<<<NCTA, 384, SMEM_BYTES, cudaStreamPerThread>>>(m, x, wqkv, wphi, w1, w2, w3, w4, wo, gate_w);
}
```

```cpp
#include <cuda_runtime.h>
#include <cuda_bf16.h>
#include <cuda.h>
#include <stdint.h>

namespace {

constexpr int S_ = 2048, D_ = 640, F_ = 1536;
constexpr int NCTA = 128;
constexpr int KV_PAIR = 40 * 48 + 96;
constexpr int KV_J = 2 * KV_PAIR;

constexpr int SLOT_B = 49152, NB = 3;
constexpr int SLOT_A = 16384, NA = 4;
constexpr int OFF_B = 0;
constexpr int OFF_A = OFF_B + NB * SLOT_B;
constexpr int OFF_STG = OFF_A + 2 * SLOT_A;
constexpr int OFF_MISC = OFF_A + NA * SLOT_A;
constexpr int OFF_XST = OFF_MISC + 13312;
constexpr int OFF_CS = OFF_MISC + 16384;
constexpr int OFF_BAR = OFF_CS + 1088;
constexpr int SMEM_BYTES = OFF_BAR + 512;
constexpr int B_FULLA = 0, B_FULLB = 4, B_CS = 7, B_XR = 8, B_KV = 9, B_ST1 = 10, B_SDONE = 11  , B_RDY = 17  ,
              B_FULL4 = 23  , B_DSR = 28  , B_SEND = 36  , B_EMPTYB = 42  ,
              B_SIGP = 45, B_SIGH = 46, B_SIGKV = 47, B_SIGX1 = 48, B_MFREE = 49, B_EMPTY4 = 50  ,
              B_EMPTYA = 55  , B_PEER = 59, NBAR = 60;
constexpr int SPARE = 40960;
constexpr int UNIT4 = 25600, NU4 = 5;
constexpr int OFF_DS = OFF_A, OFF_SEND = OFF_A + 40960, OFF_G0 = OFF_A + 61440, OFF_G1 = OFF_B + UNIT4;

constexpr int FL_DONE = 0, FL_H = 1, FL_X1 = FL_H + 16, FL_KV = FL_X1 + 16, FL_CS = FL_KV + 8, FL_CS3 = FL_CS + 8, FL_ST = FL_CS3 + 8, FL_PART = FL_ST + 16;
constexpr int FL_COUNT = FL_PART + 16 * 8;
constexpr int ACC_FLOATS = 8 * KV_J + D_ + F_;

struct Maps {
  CUtensorMap x, w1m, w1r, qm, qr, hs, w2, x1, w3, w4, wo, st_h, st_x1, st_out, xr;
};

}

__device__ __align__(1024) __nv_bfloat16 g_Hs[(S_ + 4) * D_];
__device__ __align__(1024) __nv_bfloat16 g_X1[S_ * D_];
__device__ __align__(128) float g_acc[2][ACC_FLOATS];
__device__ __align__(128) float4 g_xstat[S_];
__device__ __align__(128) float2 g_st1[S_ * 8];
__device__ __align__(128) uint4 g_part[16 * 8 * 3 * 1280];
__device__ __align__(128) unsigned g_flags[FL_COUNT * 32];
#define TSTAMP(n) do {} while (0)
#define TSTAMPX(n) do {} while (0)
#define TRACE(n) do {} while (0)
#define TR4(n) do {} while (0)

namespace {

__device__ __forceinline__ long long gtime() { long long t; asm volatile("mov.u64 %0, %%globaltimer;" : "=l"(t)); return t; }
__device__ __forceinline__ uint32_t smem_u32(const void* p) { return (uint32_t)__cvta_generic_to_shared(p); }
__device__ __forceinline__ void mbar_init(uint32_t bar, int cnt) {
  asm volatile("mbarrier.init.shared::cta.b64 [%0], %1;" ::"r"(bar), "r"(cnt) : "memory");
}
__device__ __forceinline__ void mbar_expect_tx(uint32_t bar, int bytes) {
  asm volatile("mbarrier.arrive.expect_tx.shared::cta.b64 _, [%0], %1;" ::"r"(bar), "r"(bytes) : "memory");
}
__device__ __forceinline__ void mbar_arrive_cta(uint32_t bar, uint32_t cta) {
  asm volatile("{\n.reg .b32 ra;\nmapa.shared::cluster.u32 ra, %0, %1;\nmbarrier.arrive.shared::cluster.b64 _, [ra];\n}"
               ::"r"(bar), "r"(cta) : "memory");
}
__device__ __forceinline__ uint32_t mbar_try(uint32_t bar, uint32_t parity) {
  uint32_t ok;
  asm volatile("{\n.reg .pred p;\nmbarrier.try_wait.parity.shared::cta.b64 p, [%1], %2;\nselp.u32 %0, 1, 0, p;\n}"
               : "=r"(ok) : "r"(bar), "r"(parity) : "memory");
  return ok;
}
constexpr uint32_t WAIT_LIMIT = 1u << 22;
__device__ __forceinline__ void mbar_wait(uint32_t bar, uint32_t parity) {
  uint32_t n = 0;
  while (!mbar_try(bar, parity) && ++n < WAIT_LIMIT) {}
}
__device__ __forceinline__ unsigned ld_acquire(const unsigned* p) {
  unsigned v;
  asm volatile("ld.acquire.gpu.global.u32 %0, [%1];" : "=r"(v) : "l"(p) : "memory");
  return v;
}
__device__ __forceinline__ void flag_wait(int idx, unsigned target) {
  const unsigned* p = g_flags + idx * 32;
  uint32_t n = 0;
  while ((int)(ld_acquire(p) - target) < 0 && ++n < (WAIT_LIMIT >> 4)) {}
}
__device__ __forceinline__ void flag_add(int idx) {
  asm volatile("red.release.gpu.global.add.u32 [%0], 1;" ::"l"(g_flags + idx * 32) : "memory");
}
__device__ __forceinline__ void flag_add_relaxed(int idx) {
  asm volatile("red.relaxed.gpu.global.add.u32 [%0], 1;" ::"l"(g_flags + idx * 32) : "memory");
}
__device__ __forceinline__ uint32_t mbar_test(uint32_t bar, uint32_t parity) {
  uint32_t ok;
  asm volatile("{\n.reg .pred p;\nmbarrier.test_wait.parity.shared::cta.b64 p, [%1], %2;\nselp.u32 %0, 1, 0, p;\n}"
               : "=r"(ok) : "r"(bar), "r"(parity) : "memory");
  return ok;
}
__device__ __forceinline__ uint32_t lds32(uint32_t a) {
  uint32_t v;
  asm volatile("ld.shared.u32 %0, [%1];" : "=r"(v) : "r"(a) : "memory");
  return v;
}
__device__ __forceinline__ void mbar_arrive(uint32_t bar) {
  asm volatile("mbarrier.arrive.shared::cta.b64 _, [%0];" ::"r"(bar) : "memory");
}
__device__ __forceinline__ void fence_async_all() { asm volatile("fence.proxy.async;" ::: "memory"); }
__device__ __forceinline__ void fence_async_smem() { asm volatile("fence.proxy.async.shared::cta;" ::: "memory"); }
__device__ __forceinline__ void bar_sync(int id, int n) { asm volatile("bar.sync %0, %1;" ::"r"(id), "r"(n) : "memory"); }

__device__ __forceinline__ void tma2d(uint32_t dst, const CUtensorMap* m, uint32_t bar, int c0, int c1) {
  asm volatile("cp.async.bulk.tensor.2d.shared::cluster.global.mbarrier::complete_tx::bytes [%0], [%1, {%3, %4}], [%2];"
               ::"r"(dst), "l"(m), "r"(bar), "r"(c0), "r"(c1) : "memory");
}
__device__ __forceinline__ void tma2d_mc(uint32_t dst, const CUtensorMap* m, uint32_t bar, int c0, int c1) {
  asm volatile("cp.async.bulk.tensor.2d.shared::cluster.global.mbarrier::complete_tx::bytes.multicast::cluster"
               " [%0], [%1, {%3, %4}], [%2], %5;"
               ::"r"(dst), "l"(m), "r"(bar), "r"(c0), "r"(c1), "h"((uint16_t)3) : "memory");
}
__device__ __forceinline__ void tma3d(uint32_t dst, const CUtensorMap* m, uint32_t bar, int c0, int c1, int c2) {
  asm volatile("cp.async.bulk.tensor.3d.shared::cluster.global.mbarrier::complete_tx::bytes [%0], [%1, {%3, %4, %5}], [%2];"
               ::"r"(dst), "l"(m), "r"(bar), "r"(c0), "r"(c1), "r"(c2) : "memory");
}
__device__ __forceinline__ void tma4d(uint32_t dst, const CUtensorMap* m, uint32_t bar, int c0, int c1, int c2, int c3) {
  asm volatile("cp.async.bulk.tensor.4d.shared::cluster.global.mbarrier::complete_tx::bytes [%0], [%1, {%3, %4, %5, %6}], [%2];"
               ::"r"(dst), "l"(m), "r"(bar), "r"(c0), "r"(c1), "r"(c2), "r"(c3) : "memory");
}
__device__ __forceinline__ void tma2d_store(const CUtensorMap* m, uint32_t src, int c0, int c1) {
  asm volatile("cp.async.bulk.tensor.2d.global.shared::cta.bulk_group [%0, {%2, %3}], [%1];"
               ::"l"(m), "r"(src), "r"(c0), "r"(c1) : "memory");
}
__device__ __forceinline__ void bulk_store(void* dst, uint32_t src, uint32_t bytes) {
  asm volatile("cp.async.bulk.global.shared::cta.bulk_group [%0], [%1], %2;" ::"l"(dst), "r"(src), "r"(bytes) : "memory");
}
__device__ __forceinline__ void bulk_load(uint32_t dst, const void* src, uint32_t bytes, uint32_t bar) {
  asm volatile("cp.async.bulk.shared::cluster.global.mbarrier::complete_tx::bytes [%0], [%1], %2, [%3];"
               ::"r"(dst), "l"(src), "r"(bytes), "r"(bar) : "memory");
}
__device__ __forceinline__ void bulk_commit() { asm volatile("cp.async.bulk.commit_group;" ::: "memory"); }
template <int N> __device__ __forceinline__ void bulk_wait() { asm volatile("cp.async.bulk.wait_group %0;" ::"n"(N) : "memory"); }
__device__ __forceinline__ void bulk_wait_read() { asm volatile("cp.async.bulk.wait_group.read 0;" ::: "memory"); }
__device__ __forceinline__ void bar_arrive(int id, int n) { asm volatile("bar.arrive %0, %1;" ::"r"(id), "r"(n) : "memory"); }
__device__ __forceinline__ uint4 lds128(uint32_t a) {
  uint4 v;
  asm volatile("ld.shared.v4.u32 {%0, %1, %2, %3}, [%4];" : "=r"(v.x), "=r"(v.y), "=r"(v.z), "=r"(v.w) : "r"(a) : "memory");
  return v;
}
__device__ __forceinline__ void sts128(uint32_t a, uint4 v) {
  asm volatile("st.shared.v4.u32 [%0], {%1, %2, %3, %4};" ::"r"(a), "r"(v.x), "r"(v.y), "r"(v.z), "r"(v.w) : "memory");
}
__device__ __forceinline__ uint32_t map_peer(uint32_t addr, uint32_t cta) {
  uint32_t r;
  asm("mapa.shared::cluster.u32 %0, %1, %2;" : "=r"(r) : "r"(addr), "r"(cta));
  return r;
}
__device__ __forceinline__ void st_async16(uint32_t addr, uint32_t a, uint32_t b, uint32_t c, uint32_t d, uint32_t bar) {
  asm volatile("st.async.weak.shared::cluster.mbarrier::complete_tx::bytes.v4.b32 [%0], {%1, %2, %3, %4}, [%5];"
               ::"r"(addr), "r"(a), "r"(b), "r"(c), "r"(d), "r"(bar) : "memory");
}
__device__ __forceinline__ void l2_prefetch(const void* p, uint32_t bytes) {
  asm volatile("cp.async.bulk.prefetch.L2.global [%0], %1;" ::"l"(p), "r"(bytes) : "memory");
}
__device__ __forceinline__ void prefetch_tmap(const CUtensorMap* m) {
  asm volatile("prefetch.tensormap [%0];" ::"l"(m) : "memory");
}
__device__ __forceinline__ uint64_t make_desc(uint32_t a16, uint32_t off, uint32_t lbo, uint32_t sbo, uint32_t swz) {
  const uint32_t lo = a16 + ((off >> 4) + ((lbo >> 4) << 16)), hi = (sbo >> 4) | (swz << 30);
  uint64_t d;
  asm("mov.b64 %0, {%1, %2};" : "=l"(d) : "r"(lo), "r"(hi));
  return d;
}
__device__ __forceinline__ void wg_fence() { asm volatile("wgmma.fence.sync.aligned;" ::: "memory"); }
__device__ __forceinline__ void wg_commit() { asm volatile("wgmma.commit_group.sync.aligned;" ::: "memory"); }
template <int N> __device__ __forceinline__ void wg_wait() { asm volatile("wgmma.wait_group.sync.aligned %0;" ::"n"(N) : "memory"); }
template <int N> __device__ __forceinline__ void fence_regs(float (&d)[N]) {
#pragma unroll
  for (int i = 0; i < N; i++) asm volatile("" : "+f"(d[i])::"memory");
}
template <int N> __device__ __forceinline__ void zero_regs(float (&d)[N]) {
#pragma unroll
  for (int i = 0; i < N; i++) d[i] = 0.f;
}
__device__ __forceinline__ uint32_t pack_bf16(float lo, float hi) {
  uint32_t r;
  asm("cvt.rn.bf16x2.f32 %0, %1, %2;" : "=r"(r) : "f"(hi), "f"(lo));
  return r;
}
__device__ __forceinline__ float bf_lo(uint32_t v) { return __uint_as_float(v << 16); }
__device__ __forceinline__ float bf_hi(uint32_t v) { return __uint_as_float(v & 0xffff0000u); }
__device__ __forceinline__ uint32_t max_bf2(uint32_t a, uint32_t b) {
  uint32_t r; asm("max.bf16x2 %0, %1, %2;" : "=r"(r) : "r"(a), "r"(b)); return r;
}
__device__ __forceinline__ uint32_t min_bf2(uint32_t a, uint32_t b) {
  uint32_t r; asm("min.bf16x2 %0, %1, %2;" : "=r"(r) : "r"(a), "r"(b)); return r;
}
__device__ __forceinline__ float ex2(float x) { float r; asm("ex2.approx.ftz.f32 %0, %1;" : "=f"(r) : "f"(x)); return r; }
__device__ __forceinline__ float rcp(float x) { float r; asm("rcp.approx.ftz.f32 %0, %1;" : "=f"(r) : "f"(x)); return r; }
__device__ __forceinline__ float tanh_ap(float x) { float r; asm("tanh.approx.f32 %0, %1;" : "=f"(r) : "f"(x)); return r; }
__device__ __forceinline__ float gelu_s(float x, float hs) {
  float u = x * fmaf(x * x, 0.0356774081f, 0.7978845608f);
  float hx = x * hs;
  return fmaf(hx, tanh_ap(u), hx);
}
__device__ __forceinline__ void stsm4(uint32_t addr, uint32_t r0, uint32_t r1, uint32_t r2, uint32_t r3) {
  asm volatile("stmatrix.sync.aligned.m8n8.x4.shared.b16 [%0], {%1, %2, %3, %4};"
               ::"r"(addr), "r"(r0), "r"(r1), "r"(r2), "r"(r3) : "memory");
}
__device__ __forceinline__ void red_add4(float* p, float a, float b, float c, float d) {
  asm volatile("red.global.add.v4.f32 [%0], {%1, %2, %3, %4};" ::"l"(p), "f"(a), "f"(b), "f"(c), "f"(d) : "memory");
}

__device__ __forceinline__ void mma_ss256(float (&d)[128], uint64_t descA, uint64_t descB) {
  asm volatile("wgmma.mma_async.sync.aligned.m64n256k16.f32.bf16.bf16 {"
      "%0, %1, %2, %3, %4, %5, %6, %7, %8, %9, %10, %11, %12, %13, %14, %15, "
      "%16, %17, %18, %19, %20, %21, %22, %23, %24, %25, %26, %27, %28, %29, %30, %31, "
      "%32, %33, %34, %35, %36, %37, %38, %39, %40, %41, %42, %43, %44, %45, %46, %47, "
      "%48, %49, %50, %51, %52, %53, %54, %55, %56, %57, %58, %59, %60, %61, %62, %63, "
      "%64, %65, %66, %67, %68, %69, %70, %71, %72, %73, %74, %75, %76, %77, %78, %79, "
      "%80, %81, %82, %83, %84, %85, %86, %87, %88, %89, %90, %91, %92, %93, %94, %95, "
      "%96, %97, %98, %99, %100, %101, %102, %103, %104, %105, %106, %107, %108, %109, %110, %111, "
      "%112, %113, %114, %115, %116, %117, %118, %119, %120, %121, %122, %123, %124, %125, %126, %127"
      "}, %128, %129, 1, 1, 1, 0, 1;\n"
      : "+f"(d[0]), "+f"(d[1]), "+f"(d[2]), "+f"(d[3]), "+f"(d[4]), "+f"(d[5]), "+f"(d[6]), "+f"(d[7]),
        "+f"(d[8]), "+f"(d[9]), "+f"(d[10]), "+f"(d[11]), "+f"(d[12]), "+f"(d[13]), "+f"(d[14]), "+f"(d[15]),
        "+f"(d[16]), "+f"(d[17]), "+f"(d[18]), "+f"(d[19]), "+f"(d[20]), "+f"(d[21]), "+f"(d[22]), "+f"(d[23]),
        "+f"(d[24]), "+f"(d[25]), "+f"(d[26]), "+f"(d[27]), "+f"(d[28]), "+f"(d[29]), "+f"(d[30]), "+f"(d[31]),
        "+f"(d[32]), "+f"(d[33]), "+f"(d[34]), "+f"(d[35]), "+f"(d[36]), "+f"(d[37]), "+f"(d[38]), "+f"(d[39]),
        "+f"(d[40]), "+f"(d[41]), "+f"(d[42]), "+f"(d[43]), "+f"(d[44]), "+f"(d[45]), "+f"(d[46]), "+f"(d[47]),
        "+f"(d[48]), "+f"(d[49]), "+f"(d[50]), "+f"(d[51]), "+f"(d[52]), "+f"(d[53]), "+f"(d[54]), "+f"(d[55]),
        "+f"(d[56]), "+f"(d[57]), "+f"(d[58]), "+f"(d[59]), "+f"(d[60]), "+f"(d[61]), "+f"(d[62]), "+f"(d[63]),
        "+f"(d[64]), "+f"(d[65]), "+f"(d[66]), "+f"(d[67]), "+f"(d[68]), "+f"(d[69]), "+f"(d[70]), "+f"(d[71]),
        "+f"(d[72]), "+f"(d[73]), "+f"(d[74]), "+f"(d[75]), "+f"(d[76]), "+f"(d[77]), "+f"(d[78]), "+f"(d[79]),
        "+f"(d[80]), "+f"(d[81]), "+f"(d[82]), "+f"(d[83]), "+f"(d[84]), "+f"(d[85]), "+f"(d[86]), "+f"(d[87]),
        "+f"(d[88]), "+f"(d[89]), "+f"(d[90]), "+f"(d[91]), "+f"(d[92]), "+f"(d[93]), "+f"(d[94]), "+f"(d[95]),
        "+f"(d[96]), "+f"(d[97]), "+f"(d[98]), "+f"(d[99]), "+f"(d[100]), "+f"(d[101]), "+f"(d[102]), "+f"(d[103]),
        "+f"(d[104]), "+f"(d[105]), "+f"(d[106]), "+f"(d[107]), "+f"(d[108]), "+f"(d[109]), "+f"(d[110]), "+f"(d[111]),
        "+f"(d[112]), "+f"(d[113]), "+f"(d[114]), "+f"(d[115]), "+f"(d[116]), "+f"(d[117]), "+f"(d[118]), "+f"(d[119]),
        "+f"(d[120]), "+f"(d[121]), "+f"(d[122]), "+f"(d[123]), "+f"(d[124]), "+f"(d[125]), "+f"(d[126]), "+f"(d[127])
      : "l"(descA), "l"(descB));
}

__device__ __forceinline__ void mma_ss64(float (&d)[32], uint64_t descA, uint64_t descB) {
  asm volatile("wgmma.mma_async.sync.aligned.m64n64k16.f32.bf16.bf16 {"
      "%0, %1, %2, %3, %4, %5, %6, %7, %8, %9, %10, %11, %12, %13, %14, %15, "
      "%16, %17, %18, %19, %20, %21, %22, %23, %24, %25, %26, %27, %28, %29, %30, %31"
      "}, %32, %33, 1, 1, 1, 0, 1;\n"
      : "+f"(d[0]), "+f"(d[1]), "+f"(d[2]), "+f"(d[3]), "+f"(d[4]), "+f"(d[5]), "+f"(d[6]), "+f"(d[7]),
        "+f"(d[8]), "+f"(d[9]), "+f"(d[10]), "+f"(d[11]), "+f"(d[12]), "+f"(d[13]), "+f"(d[14]), "+f"(d[15]),
        "+f"(d[16]), "+f"(d[17]), "+f"(d[18]), "+f"(d[19]), "+f"(d[20]), "+f"(d[21]), "+f"(d[22]), "+f"(d[23]),
        "+f"(d[24]), "+f"(d[25]), "+f"(d[26]), "+f"(d[27]), "+f"(d[28]), "+f"(d[29]), "+f"(d[30]), "+f"(d[31])
      : "l"(descA), "l"(descB));
}

__device__ __forceinline__ void mma_ss80(float (&d)[40], uint64_t descA, uint64_t descB) {
  asm volatile("wgmma.mma_async.sync.aligned.m64n80k16.f32.bf16.bf16 {"
      "%0, %1, %2, %3, %4, %5, %6, %7, %8, %9, %10, %11, %12, %13, %14, %15, "
      "%16, %17, %18, %19, %20, %21, %22, %23, %24, %25, %26, %27, %28, %29, %30, %31, "
      "%32, %33, %34, %35, %36, %37, %38, %39"
      "}, %40, %41, 1, 1, 1, 0, 1;\n"
      : "+f"(d[0]), "+f"(d[1]), "+f"(d[2]), "+f"(d[3]), "+f"(d[4]), "+f"(d[5]), "+f"(d[6]), "+f"(d[7]),
        "+f"(d[8]), "+f"(d[9]), "+f"(d[10]), "+f"(d[11]), "+f"(d[12]), "+f"(d[13]), "+f"(d[14]), "+f"(d[15]),
        "+f"(d[16]), "+f"(d[17]), "+f"(d[18]), "+f"(d[19]), "+f"(d[20]), "+f"(d[21]), "+f"(d[22]), "+f"(d[23]),
        "+f"(d[24]), "+f"(d[25]), "+f"(d[26]), "+f"(d[27]), "+f"(d[28]), "+f"(d[29]), "+f"(d[30]), "+f"(d[31]),
        "+f"(d[32]), "+f"(d[33]), "+f"(d[34]), "+f"(d[35]), "+f"(d[36]), "+f"(d[37]), "+f"(d[38]), "+f"(d[39])
      : "l"(descA), "l"(descB));
}

__device__ __forceinline__ void mma_ss192(float (&d)[96], uint64_t descA, uint64_t descB) {
  asm volatile("wgmma.mma_async.sync.aligned.m64n192k16.f32.bf16.bf16 {"
      "%0, %1, %2, %3, %4, %5, %6, %7, %8, %9, %10, %11, %12, %13, %14, %15, "
      "%16, %17, %18, %19, %20, %21, %22, %23, %24, %25, %26, %27, %28, %29, %30, %31, "
      "%32, %33, %34, %35, %36, %37, %38, %39, %40, %41, %42, %43, %44, %45, %46, %47, "
      "%48, %49, %50, %51, %52, %53, %54, %55, %56, %57, %58, %59, %60, %61, %62, %63, "
      "%64, %65, %66, %67, %68, %69, %70, %71, %72, %73, %74, %75, %76, %77, %78, %79, "
      "%80, %81, %82, %83, %84, %85, %86, %87, %88, %89, %90, %91, %92, %93, %94, %95"
      "}, %96, %97, 1, 1, 1, 0, 1;\n"
      : "+f"(d[0]), "+f"(d[1]), "+f"(d[2]), "+f"(d[3]), "+f"(d[4]), "+f"(d[5]), "+f"(d[6]), "+f"(d[7]),
        "+f"(d[8]), "+f"(d[9]), "+f"(d[10]), "+f"(d[11]), "+f"(d[12]), "+f"(d[13]), "+f"(d[14]), "+f"(d[15]),
        "+f"(d[16]), "+f"(d[17]), "+f"(d[18]), "+f"(d[19]), "+f"(d[20]), "+f"(d[21]), "+f"(d[22]), "+f"(d[23]),
        "+f"(d[24]), "+f"(d[25]), "+f"(d[26]), "+f"(d[27]), "+f"(d[28]), "+f"(d[29]), "+f"(d[30]), "+f"(d[31]),
        "+f"(d[32]), "+f"(d[33]), "+f"(d[34]), "+f"(d[35]), "+f"(d[36]), "+f"(d[37]), "+f"(d[38]), "+f"(d[39]),
        "+f"(d[40]), "+f"(d[41]), "+f"(d[42]), "+f"(d[43]), "+f"(d[44]), "+f"(d[45]), "+f"(d[46]), "+f"(d[47]),
        "+f"(d[48]), "+f"(d[49]), "+f"(d[50]), "+f"(d[51]), "+f"(d[52]), "+f"(d[53]), "+f"(d[54]), "+f"(d[55]),
        "+f"(d[56]), "+f"(d[57]), "+f"(d[58]), "+f"(d[59]), "+f"(d[60]), "+f"(d[61]), "+f"(d[62]), "+f"(d[63]),
        "+f"(d[64]), "+f"(d[65]), "+f"(d[66]), "+f"(d[67]), "+f"(d[68]), "+f"(d[69]), "+f"(d[70]), "+f"(d[71]),
        "+f"(d[72]), "+f"(d[73]), "+f"(d[74]), "+f"(d[75]), "+f"(d[76]), "+f"(d[77]), "+f"(d[78]), "+f"(d[79]),
        "+f"(d[80]), "+f"(d[81]), "+f"(d[82]), "+f"(d[83]), "+f"(d[84]), "+f"(d[85]), "+f"(d[86]), "+f"(d[87]),
        "+f"(d[88]), "+f"(d[89]), "+f"(d[90]), "+f"(d[91]), "+f"(d[92]), "+f"(d[93]), "+f"(d[94]), "+f"(d[95])
      : "l"(descA), "l"(descB));
}

__device__ __forceinline__ void mma_ss80_tt(float (&d)[40], uint64_t descA, uint64_t descB) {
  asm volatile("wgmma.mma_async.sync.aligned.m64n80k16.f32.bf16.bf16 {"
      "%0, %1, %2, %3, %4, %5, %6, %7, %8, %9, %10, %11, %12, %13, %14, %15, "
      "%16, %17, %18, %19, %20, %21, %22, %23, %24, %25, %26, %27, %28, %29, %30, %31, "
      "%32, %33, %34, %35, %36, %37, %38, %39"
      "}, %40, %41, 1, 1, 1, 1, 1;\n"
      : "+f"(d[0]), "+f"(d[1]), "+f"(d[2]), "+f"(d[3]), "+f"(d[4]), "+f"(d[5]), "+f"(d[6]), "+f"(d[7]),
        "+f"(d[8]), "+f"(d[9]), "+f"(d[10]), "+f"(d[11]), "+f"(d[12]), "+f"(d[13]), "+f"(d[14]), "+f"(d[15]),
        "+f"(d[16]), "+f"(d[17]), "+f"(d[18]), "+f"(d[19]), "+f"(d[20]), "+f"(d[21]), "+f"(d[22]), "+f"(d[23]),
        "+f"(d[24]), "+f"(d[25]), "+f"(d[26]), "+f"(d[27]), "+f"(d[28]), "+f"(d[29]), "+f"(d[30]), "+f"(d[31]),
        "+f"(d[32]), "+f"(d[33]), "+f"(d[34]), "+f"(d[35]), "+f"(d[36]), "+f"(d[37]), "+f"(d[38]), "+f"(d[39])
      : "l"(descA), "l"(descB));
}
__device__ __forceinline__ void mma_ss80_tt_z(float (&d)[40], uint64_t descA, uint64_t descB) {
  asm volatile("wgmma.mma_async.sync.aligned.m64n80k16.f32.bf16.bf16 {"
      "%0, %1, %2, %3, %4, %5, %6, %7, %8, %9, %10, %11, %12, %13, %14, %15, "
      "%16, %17, %18, %19, %20, %21, %22, %23, %24, %25, %26, %27, %28, %29, %30, %31, "
      "%32, %33, %34, %35, %36, %37, %38, %39"
      "}, %40, %41, 0, 1, 1, 1, 1;\n"
      : "=f"(d[0]), "=f"(d[1]), "=f"(d[2]), "=f"(d[3]), "=f"(d[4]), "=f"(d[5]), "=f"(d[6]), "=f"(d[7]),
        "=f"(d[8]), "=f"(d[9]), "=f"(d[10]), "=f"(d[11]), "=f"(d[12]), "=f"(d[13]), "=f"(d[14]), "=f"(d[15]),
        "=f"(d[16]), "=f"(d[17]), "=f"(d[18]), "=f"(d[19]), "=f"(d[20]), "=f"(d[21]), "=f"(d[22]), "=f"(d[23]),
        "=f"(d[24]), "=f"(d[25]), "=f"(d[26]), "=f"(d[27]), "=f"(d[28]), "=f"(d[29]), "=f"(d[30]), "=f"(d[31]),
        "=f"(d[32]), "=f"(d[33]), "=f"(d[34]), "=f"(d[35]), "=f"(d[36]), "=f"(d[37]), "=f"(d[38]), "=f"(d[39])
      : "l"(descA), "l"(descB));
}

__device__ __forceinline__ void mma_rs80_k(float (&d)[40], const uint32_t (&a)[4], uint64_t descB) {
  asm volatile("wgmma.mma_async.sync.aligned.m64n80k16.f32.bf16.bf16 {"
      "%0, %1, %2, %3, %4, %5, %6, %7, %8, %9, %10, %11, %12, %13, %14, %15, "
      "%16, %17, %18, %19, %20, %21, %22, %23, %24, %25, %26, %27, %28, %29, %30, %31, "
      "%32, %33, %34, %35, %36, %37, %38, %39"
      "}, {%40, %41, %42, %43}, %44, 1, 1, 1, 0;\n"
      : "+f"(d[0]), "+f"(d[1]), "+f"(d[2]), "+f"(d[3]), "+f"(d[4]), "+f"(d[5]), "+f"(d[6]), "+f"(d[7]),
        "+f"(d[8]), "+f"(d[9]), "+f"(d[10]), "+f"(d[11]), "+f"(d[12]), "+f"(d[13]), "+f"(d[14]), "+f"(d[15]),
        "+f"(d[16]), "+f"(d[17]), "+f"(d[18]), "+f"(d[19]), "+f"(d[20]), "+f"(d[21]), "+f"(d[22]), "+f"(d[23]),
        "+f"(d[24]), "+f"(d[25]), "+f"(d[26]), "+f"(d[27]), "+f"(d[28]), "+f"(d[29]), "+f"(d[30]), "+f"(d[31]),
        "+f"(d[32]), "+f"(d[33]), "+f"(d[34]), "+f"(d[35]), "+f"(d[36]), "+f"(d[37]), "+f"(d[38]), "+f"(d[39])
      : "r"(a[0]), "r"(a[1]), "r"(a[2]), "r"(a[3]), "l"(descB));
}
__device__ __forceinline__ void mma_rs80_k_z(float (&d)[40], const uint32_t (&a)[4], uint64_t descB) {
  asm volatile("wgmma.mma_async.sync.aligned.m64n80k16.f32.bf16.bf16 {"
      "%0, %1, %2, %3, %4, %5, %6, %7, %8, %9, %10, %11, %12, %13, %14, %15, "
      "%16, %17, %18, %19, %20, %21, %22, %23, %24, %25, %26, %27, %28, %29, %30, %31, "
      "%32, %33, %34, %35, %36, %37, %38, %39"
      "}, {%40, %41, %42, %43}, %44, 0, 1, 1, 0;\n"
      : "=f"(d[0]), "=f"(d[1]), "=f"(d[2]), "=f"(d[3]), "=f"(d[4]), "=f"(d[5]), "=f"(d[6]), "=f"(d[7]),
        "=f"(d[8]), "=f"(d[9]), "=f"(d[10]), "=f"(d[11]), "=f"(d[12]), "=f"(d[13]), "=f"(d[14]), "=f"(d[15]),
        "=f"(d[16]), "=f"(d[17]), "=f"(d[18]), "=f"(d[19]), "=f"(d[20]), "=f"(d[21]), "=f"(d[22]), "=f"(d[23]),
        "=f"(d[24]), "=f"(d[25]), "=f"(d[26]), "=f"(d[27]), "=f"(d[28]), "=f"(d[29]), "=f"(d[30]), "=f"(d[31]),
        "=f"(d[32]), "=f"(d[33]), "=f"(d[34]), "=f"(d[35]), "=f"(d[36]), "=f"(d[37]), "=f"(d[38]), "=f"(d[39])
      : "r"(a[0]), "r"(a[1]), "r"(a[2]), "r"(a[3]), "l"(descB));
}

__device__ __forceinline__ void mma_rs48_k(float (&d)[24], const uint32_t (&a)[4], uint64_t descB) {
  asm volatile("wgmma.mma_async.sync.aligned.m64n48k16.f32.bf16.bf16 {"
      "%0, %1, %2, %3, %4, %5, %6, %7, %8, %9, %10, %11, %12, %13, %14, %15, "
      "%16, %17, %18, %19, %20, %21, %22, %23"
      "}, {%24, %25, %26, %27}, %28, 1, 1, 1, 0;\n"
      : "+f"(d[0]), "+f"(d[1]), "+f"(d[2]), "+f"(d[3]), "+f"(d[4]), "+f"(d[5]), "+f"(d[6]), "+f"(d[7]),
        "+f"(d[8]), "+f"(d[9]), "+f"(d[10]), "+f"(d[11]), "+f"(d[12]), "+f"(d[13]), "+f"(d[14]), "+f"(d[15]),
        "+f"(d[16]), "+f"(d[17]), "+f"(d[18]), "+f"(d[19]), "+f"(d[20]), "+f"(d[21]), "+f"(d[22]), "+f"(d[23])
      : "r"(a[0]), "r"(a[1]), "r"(a[2]), "r"(a[3]), "l"(descB));
}
__device__ __forceinline__ void mma_rs48_k_z(float (&d)[24], const uint32_t (&a)[4], uint64_t descB) {
  asm volatile("wgmma.mma_async.sync.aligned.m64n48k16.f32.bf16.bf16 {"
      "%0, %1, %2, %3, %4, %5, %6, %7, %8, %9, %10, %11, %12, %13, %14, %15, "
      "%16, %17, %18, %19, %20, %21, %22, %23"
      "}, {%24, %25, %26, %27}, %28, 0, 1, 1, 0;\n"
      : "=f"(d[0]), "=f"(d[1]), "=f"(d[2]), "=f"(d[3]), "=f"(d[4]), "=f"(d[5]), "=f"(d[6]), "=f"(d[7]),
        "=f"(d[8]), "=f"(d[9]), "=f"(d[10]), "=f"(d[11]), "=f"(d[12]), "=f"(d[13]), "=f"(d[14]), "=f"(d[15]),
        "=f"(d[16]), "=f"(d[17]), "=f"(d[18]), "=f"(d[19]), "=f"(d[20]), "=f"(d[21]), "=f"(d[22]), "=f"(d[23])
      : "r"(a[0]), "r"(a[1]), "r"(a[2]), "r"(a[3]), "l"(descB));
}

__device__ __forceinline__ void mma_rs160_n(float (&d)[80], const uint32_t (&a)[4], uint64_t descB) {
  asm volatile("wgmma.mma_async.sync.aligned.m64n160k16.f32.bf16.bf16 {"
      "%0, %1, %2, %3, %4, %5, %6, %7, %8, %9, %10, %11, %12, %13, %14, %15, "
      "%16, %17, %18, %19, %20, %21, %22, %23, %24, %25, %26, %27, %28, %29, %30, %31, "
      "%32, %33, %34, %35, %36, %37, %38, %39, %40, %41, %42, %43, %44, %45, %46, %47, "
      "%48, %49, %50, %51, %52, %53, %54, %55, %56, %57, %58, %59, %60, %61, %62, %63, "
      "%64, %65, %66, %67, %68, %69, %70, %71, %72, %73, %74, %75, %76, %77, %78, %79"
      "}, {%80, %81, %82, %83}, %84, 1, 1, 1, 1;\n"
      : "+f"(d[0]), "+f"(d[1]), "+f"(d[2]), "+f"(d[3]), "+f"(d[4]), "+f"(d[5]), "+f"(d[6]), "+f"(d[7]),
        "+f"(d[8]), "+f"(d[9]), "+f"(d[10]), "+f"(d[11]), "+f"(d[12]), "+f"(d[13]), "+f"(d[14]), "+f"(d[15]),
        "+f"(d[16]), "+f"(d[17]), "+f"(d[18]), "+f"(d[19]), "+f"(d[20]), "+f"(d[21]), "+f"(d[22]), "+f"(d[23]),
        "+f"(d[24]), "+f"(d[25]), "+f"(d[26]), "+f"(d[27]), "+f"(d[28]), "+f"(d[29]), "+f"(d[30]), "+f"(d[31]),
        "+f"(d[32]), "+f"(d[33]), "+f"(d[34]), "+f"(d[35]), "+f"(d[36]), "+f"(d[37]), "+f"(d[38]), "+f"(d[39]),
        "+f"(d[40]), "+f"(d[41]), "+f"(d[42]), "+f"(d[43]), "+f"(d[44]), "+f"(d[45]), "+f"(d[46]), "+f"(d[47]),
        "+f"(d[48]), "+f"(d[49]), "+f"(d[50]), "+f"(d[51]), "+f"(d[52]), "+f"(d[53]), "+f"(d[54]), "+f"(d[55]),
        "+f"(d[56]), "+f"(d[57]), "+f"(d[58]), "+f"(d[59]), "+f"(d[60]), "+f"(d[61]), "+f"(d[62]), "+f"(d[63]),
        "+f"(d[64]), "+f"(d[65]), "+f"(d[66]), "+f"(d[67]), "+f"(d[68]), "+f"(d[69]), "+f"(d[70]), "+f"(d[71]),
        "+f"(d[72]), "+f"(d[73]), "+f"(d[74]), "+f"(d[75]), "+f"(d[76]), "+f"(d[77]), "+f"(d[78]), "+f"(d[79])
      : "r"(a[0]), "r"(a[1]), "r"(a[2]), "r"(a[3]), "l"(descB));
}
__device__ __forceinline__ void mma_rs160_n_z(float (&d)[80], const uint32_t (&a)[4], uint64_t descB) {
  asm volatile("wgmma.mma_async.sync.aligned.m64n160k16.f32.bf16.bf16 {"
      "%0, %1, %2, %3, %4, %5, %6, %7, %8, %9, %10, %11, %12, %13, %14, %15, "
      "%16, %17, %18, %19, %20, %21, %22, %23, %24, %25, %26, %27, %28, %29, %30, %31, "
      "%32, %33, %34, %35, %36, %37, %38, %39, %40, %41, %42, %43, %44, %45, %46, %47, "
      "%48, %49, %50, %51, %52, %53, %54, %55, %56, %57, %58, %59, %60, %61, %62, %63, "
      "%64, %65, %66, %67, %68, %69, %70, %71, %72, %73, %74, %75, %76, %77, %78, %79"
      "}, {%80, %81, %82, %83}, %84, 0, 1, 1, 1;\n"
      : "=f"(d[0]), "=f"(d[1]), "=f"(d[2]), "=f"(d[3]), "=f"(d[4]), "=f"(d[5]), "=f"(d[6]), "=f"(d[7]),
        "=f"(d[8]), "=f"(d[9]), "=f"(d[10]), "=f"(d[11]), "=f"(d[12]), "=f"(d[13]), "=f"(d[14]), "=f"(d[15]),
        "=f"(d[16]), "=f"(d[17]), "=f"(d[18]), "=f"(d[19]), "=f"(d[20]), "=f"(d[21]), "=f"(d[22]), "=f"(d[23]),
        "=f"(d[24]), "=f"(d[25]), "=f"(d[26]), "=f"(d[27]), "=f"(d[28]), "=f"(d[29]), "=f"(d[30]), "=f"(d[31]),
        "=f"(d[32]), "=f"(d[33]), "=f"(d[34]), "=f"(d[35]), "=f"(d[36]), "=f"(d[37]), "=f"(d[38]), "=f"(d[39]),
        "=f"(d[40]), "=f"(d[41]), "=f"(d[42]), "=f"(d[43]), "=f"(d[44]), "=f"(d[45]), "=f"(d[46]), "=f"(d[47]),
        "=f"(d[48]), "=f"(d[49]), "=f"(d[50]), "=f"(d[51]), "=f"(d[52]), "=f"(d[53]), "=f"(d[54]), "=f"(d[55]),
        "=f"(d[56]), "=f"(d[57]), "=f"(d[58]), "=f"(d[59]), "=f"(d[60]), "=f"(d[61]), "=f"(d[62]), "=f"(d[63]),
        "=f"(d[64]), "=f"(d[65]), "=f"(d[66]), "=f"(d[67]), "=f"(d[68]), "=f"(d[69]), "=f"(d[70]), "=f"(d[71]),
        "=f"(d[72]), "=f"(d[73]), "=f"(d[74]), "=f"(d[75]), "=f"(d[76]), "=f"(d[77]), "=f"(d[78]), "=f"(d[79])
      : "r"(a[0]), "r"(a[1]), "r"(a[2]), "r"(a[3]), "l"(descB));
}

__device__ __forceinline__ void feature_map(const uint32_t (&P)[2][10], uint32_t (&fr)[10][4]) {
  constexpr float L2E = 1.4426950408889634f;
#pragma unroll
  for (int p = 0; p < 2; p++) {
#pragma unroll
    for (int r = 0; r < 2; r++) {
      uint32_t mx = P[r][5 * p], mn = mx;
#pragma unroll
      for (int g = 1; g < 5; g++) { mx = max_bf2(mx, P[r][5 * p + g]); mn = min_bf2(mn, P[r][5 * p + g]); }
      mx = max_bf2(mx, __shfl_xor_sync(0xffffffffu, mx, 1));
      mn = min_bf2(mn, __shfl_xor_sync(0xffffffffu, mn, 1));
      mx = max_bf2(mx, __shfl_xor_sync(0xffffffffu, mx, 2));
      mn = min_bf2(mn, __shfl_xor_sync(0xffffffffu, mn, 2));
      float mx0 = -bf_lo(mx) * L2E, mx1 = -bf_hi(mx) * L2E, mn0 = bf_lo(mn) * L2E, mn1 = bf_hi(mn) * L2E;
      float ep0[5], ep1[5], en0[5], en1[5];
      float sp0 = 0.f, sp1 = 0.f, sn0 = 0.f, sn1 = 0.f;
#pragma unroll
      for (int g = 0; g < 5; g++) {
        float x0 = bf_lo(P[r][5 * p + g]), x1 = bf_hi(P[r][5 * p + g]);
        ep0[g] = ex2(fmaf(x0, L2E, mx0)); ep1[g] = ex2(fmaf(x1, L2E, mx1));
        en0[g] = ex2(fmaf(x0, -L2E, mn0)); en1[g] = ex2(fmaf(x1, -L2E, mn1));
        sp0 += ep0[g]; sp1 += ep1[g]; sn0 += en0[g]; sn1 += en1[g];
      }
      sp0 += __shfl_xor_sync(0xffffffffu, sp0, 1); sp1 += __shfl_xor_sync(0xffffffffu, sp1, 1);
      sn0 += __shfl_xor_sync(0xffffffffu, sn0, 1); sn1 += __shfl_xor_sync(0xffffffffu, sn1, 1);
      sp0 += __shfl_xor_sync(0xffffffffu, sp0, 2); sp1 += __shfl_xor_sync(0xffffffffu, sp1, 2);
      sn0 += __shfl_xor_sync(0xffffffffu, sn0, 2); sn1 += __shfl_xor_sync(0xffffffffu, sn1, 2);
      sp0 = rcp(sp0); sp1 = rcp(sp1); sn0 = rcp(sn0); sn1 = rcp(sn1);
#pragma unroll
      for (int g = 0; g < 5; g++) {
        fr[5 * p + g][r] = pack_bf16(ep0[g] * sp0, ep1[g] * sp1);
        fr[5 * p + g][2 + r] = pack_bf16(en0[g] * sn0, en1[g] * sn1);
      }
    }
  }
}

struct Ring {
  uint32_t idx, phase;
  template <int N> __device__ __forceinline__ void next() { if (++idx == N) { idx = 0; phase ^= 1; } }
};

}

__global__ void __cluster_dims__(2, 1, 1) __launch_bounds__(384, 1)
fused_kernel(const __grid_constant__ Maps maps, const __nv_bfloat16* __restrict__ x, const __nv_bfloat16* __restrict__ wqkv,
             const __nv_bfloat16* __restrict__ wphi, const __nv_bfloat16* __restrict__ w1, const __nv_bfloat16* __restrict__ w2,
             const __nv_bfloat16* __restrict__ w3, const __nv_bfloat16* __restrict__ w4, const __nv_bfloat16* __restrict__ wo,
             const __nv_bfloat16* __restrict__ gate_w) {
  extern __shared__ __align__(1024) uint8_t sgen[];
  const uint32_t sb = smem_u32(sgen);
  const uint32_t sb16 = (sb & 0x3FFFFu) >> 4;
  const uint32_t bars = sb + OFF_BAR;
  const uint32_t fullA = bars + 8 * B_FULLA, emptyA = bars + 8 * B_EMPTYA, fullB = bars + 8 * B_FULLB, emptyB = bars + 8 * B_EMPTYB;

  const int tid = threadIdx.x;
  const int rank = blockIdx.x & 1;
  const int pairIdx = blockIdx.x >> 1;
  const int i = pairIdx >> 2, j = 2 * (pairIdx & 3) + rank;

  TSTAMP(0);
  auto load_p1_b = [&](int k, uint32_t slot, uint32_t bar) {
    mbar_expect_tx(bar, 40960);
    tma4d(slot + 8192, &maps.qm, bar, 0, 64 * k, 0, j);
    tma3d(slot, &maps.w1m, bar, 0, 64 * k, j);
    tma4d(slot + 32768 + 2048, &maps.qr, bar, 64, 64 * k, 0, j);
    tma3d(slot + 32768, &maps.w1r, bar, 64, 64 * k, j);
  };
  if (tid >= 256) {
    asm volatile("setmaxnreg.dec.sync.aligned.u32 40;");
    if (tid == 256) {
#pragma unroll
      for (int s = 0; s < NA; s++) mbar_init(fullA + 8 * s, 1);
      asm volatile("fence.mbarrier_init.release.cluster;" ::: "memory");
#pragma unroll 1
      for (int u = 0; u < 4; u++) {
        if ((u & 1) == 0) mbar_expect_tx(fullA + 4 * u, SLOT_A);
        tma2d(sb + OFF_A + u * 8192, &maps.x, fullA + 8 * (u >> 1), 64 * (u >> 1), 128 * i + 64 * (u & 1));
      }
    } else if (tid == 288) {
#pragma unroll
      for (int s = 0; s < NB; s++) mbar_init(fullB + 8 * s, 1);
      asm volatile("fence.mbarrier_init.release.cluster;" ::: "memory");
#pragma unroll 1
      for (int k = 0; k < 2; k++) load_p1_b(k, sb + OFF_B + k * SLOT_B, fullB + 8 * k);
    } else if (tid == 320) {
#pragma unroll
      for (int b = B_CS; b < NBAR; b++) mbar_init(bars + 8 * b, b < B_SEND ? 1 : b < B_EMPTYB ? 4 : b < B_EMPTYA ? 8 : 16);
#pragma unroll
      for (int b = B_DSR; b < B_SEND; b++) mbar_expect_tx(bars + 8 * b, 10240);
      asm volatile("fence.mbarrier_init.release.cluster;" ::: "memory");
    }
    __syncwarp();
    asm volatile("barrier.cluster.arrive.relaxed.aligned;\nbarrier.cluster.wait.aligned;" ::: "memory");
    auto get_epoch = [&]() { return *reinterpret_cast<volatile unsigned*>(g_flags + FL_DONE * 32) / NCTA; };
    const int lane = tid & 31, pw = (tid >> 5) & 3;
    auto send_stream = [&](int w, unsigned ep1) {
#pragma unroll 1
      for (int c = 0; c < 3; c++) {
        const int d = (j + 2 * c + 2) & 7;
        mbar_wait(bars + 8 * (B_SEND + 2 * c + w), 0);
        if (w) TR4(c * 16 + 7);
        bulk_store(g_part + (size_t)((i * 8 + d) * 3 + c) * 1280 + w * 640, sb + OFF_SEND + w * 10240, 10240);
        bulk_commit();
        bulk_wait<0>();
        mbar_arrive(bars + 8 * (B_SDONE + 2 * c + w));
        if (w) TR4(c * 16 + 9);
        asm volatile("st.release.gpu.global.u32 [%0], %1;"
                     ::"l"(g_flags + (FL_PART + i * 8 + d) * 32 + 2 * c + w), "r"(ep1) : "memory");
        if (w) TR4(c * 16 + 10);
      }
    };
    if (pw == 0) {
      if (tid == 256) {
        Ring r{2, 1};
        unsigned ep1 = 0;
#pragma unroll 1
        for (int k = 2; k < 30; k++) {
          if (k == 4) ep1 = get_epoch() + 1;
          if (k == 10 || k == 20) {
            const unsigned tgt = ep1 * 8u;
            const unsigned* f0 = g_flags + (k == 10 ? FL_H + ((i - 1) & 15) : FL_X1 + i) * 32;
            const unsigned* f1 = g_flags + (k == 10 ? FL_H + i : FL_X1 + i) * 32;
            const unsigned* f2 = g_flags + (k == 10 ? FL_H + ((i + 1) & 15) : FL_X1 + i) * 32;
            uint32_t n = 0;
            while (++n < (WAIT_LIMIT >> 4)) {
              unsigned v0, v1, v2;
              asm volatile("ld.relaxed.gpu.global.u32 %0, [%3];\nld.relaxed.gpu.global.u32 %1, [%4];\nld.acquire.gpu.global.u32 %2, [%5];"
                           : "=r"(v0), "=r"(v1), "=r"(v2) : "l"(f0), "l"(f1), "l"(f2) : "memory");
              if ((int)((v0 - tgt) | (v1 - tgt) | (v2 - tgt)) >= 0) break;
            }
            TSTAMPX(k == 10 ? 29 : 30);
          }
          mbar_wait(emptyA + 8 * r.idx, r.phase);
          const uint32_t bar = fullA + 8 * r.idx, slot = sb + OFF_A + r.idx * SLOT_A;
          TRACE(k);
          mbar_expect_tx(bar, SLOT_A);
          tma2d_mc(slot + rank * 8192, k < 10 ? &maps.x : k < 20 ? &maps.hs : &maps.x1, bar, 64 * (k % 10), 128 * i + 64 * rank);
          r.next<NA>();
        }
        send_stream(1, ep1);
      }
    } else if (pw == 1) {
      if (tid == 288) {
        Ring r{2, 1};
#pragma unroll 1
        for (int k = 2; k < 18; k++) {
          mbar_wait(emptyB + 8 * r.idx, r.phase);
          const uint32_t bar = fullB + 8 * r.idx, slot = sb + OFF_B + r.idx * SLOT_B;
          if (k < 10) {
            load_p1_b(k, slot, bar);
          } else if (k < 13) {
            if (k == 12) mbar_wait(fullA + 8 * 2, 0);
            mbar_expect_tx(bar, k < 12 ? 40960 : 20480);
#pragma unroll 1
            for (int u = 0; u < (k < 12 ? 4 : 2); u++) tma3d(slot + u * 10240, &maps.w2, bar, 0, 256 * (k - 10) + 64 * u, 5 * j);
          } else {
            mbar_expect_tx(bar, 49152);
            tma3d(slot, &maps.w3, bar, 0, 128 * (k - 13), 3 * j);
            tma3d(slot + 24576, &maps.w3, bar, 0, 128 * (k - 13) + 64, 3 * j);
          }
          r.next<NB>();
        }
        Ring r4{0, 1};
#pragma unroll 1
        for (int n = 0; n < 16; n++) {
          if (n == 0 || n == 1 || n == 3) { mbar_wait(emptyB + 8 * r.idx, r.phase); r.next<NB>(); }
          mbar_wait(bars + 8 * (B_EMPTY4 + r4.idx), r4.phase);
          const uint32_t bar = bars + 8 * (B_FULL4 + r4.idx), slot = sb + OFF_B + r4.idx * UNIT4;
          const int u = n & 3, m = ((j >> 1) + 1 + (n >> 2)) & 3;
          mbar_expect_tx(bar, u == 3 ? 25600 : 20480);
          tma3d(slot, u == 3 ? &maps.wo : &maps.w4, bar, 0, u == 3 ? 80 * j : 192 * j + 64 * u, 5 * m);
          r4.next<NU4>();
        }
      }
    } else {
      const unsigned epoch = get_epoch();
      float* accg = g_acc[epoch & 1];
      if (pw == 2) {
        {
          float* nxt = g_acc[(epoch + 1) & 1];
          constexpr int PER = ACC_FLOATS / NCTA;
#pragma unroll 1
          for (int e = lane; e < PER; e += 32) nxt[blockIdx.x * PER + e] = 0.f;
        }
        if (tid == 320) {
          flag_wait(FL_CS + j, (epoch + 1) * 16u);
          flag_wait(FL_ST + i, (epoch + 1) * 8u);
          fence_async_all();
          mbar_expect_tx(bars + 8 * B_CS, 320 + 2048);
          bulk_load(sb + OFF_CS, accg + 8 * KV_J + 80 * j, 320, bars + 8 * B_CS);
          bulk_load(sb + OFF_XST, g_xstat + 128 * i, 2048, bars + 8 * B_CS);
          TSTAMPX(21);
          l2_prefetch(w2 + (size_t)blockIdx.x * (D_ * D_ / NCTA), D_ * D_ * 2 / NCTA);
          mbar_wait(bars + 8 * B_SIGH, 0);
          l2_prefetch(w3 + (size_t)blockIdx.x * (F_ * D_ / NCTA), F_ * D_ * 2 / NCTA);
          l2_prefetch(w4 + (size_t)blockIdx.x * (F_ * D_ / NCTA), F_ * D_ * 2 / NCTA);
          l2_prefetch(wo + (size_t)blockIdx.x * (D_ * D_ / NCTA), D_ * D_ * 2 / NCTA);
          flag_wait(FL_KV + j, (epoch + 1) * 16u);
          mbar_expect_tx(bars + 8 * B_KV, KV_J * 4);
          bulk_load(sb + OFF_MISC, accg + j * KV_J, KV_J * 4, bars + 8 * B_KV);
          TSTAMPX(22);
        }
        __syncwarp();
#pragma unroll 1
        for (int m = 0; m < 6; m++) {
          const int col = 192 * j + 32 * m + 8 * (lane & 3);
          const __nv_bfloat16* p = w3 + (size_t)(40 * i + (lane >> 2) * 5) * F_ + col;
          float a[8];
#pragma unroll
          for (int e = 0; e < 8; e++) a[e] = 0.f;
#pragma unroll
          for (int it = 0; it < 5; it++) {
            const uint4 v = __ldg(reinterpret_cast<const uint4*>(p + (size_t)it * F_));
            a[0] += bf_lo(v.x); a[1] += bf_hi(v.x); a[2] += bf_lo(v.y); a[3] += bf_hi(v.y);
            a[4] += bf_lo(v.z); a[5] += bf_hi(v.z); a[6] += bf_lo(v.w); a[7] += bf_hi(v.w);
          }
#pragma unroll
          for (int e = 0; e < 4; e++) {
            const float snd = (lane & 4) ? a[e] : a[e + 4], keep = (lane & 4) ? a[e + 4] : a[e];
            a[e] = keep + __shfl_xor_sync(0xffffffffu, snd, 4);
            a[e] += __shfl_xor_sync(0xffffffffu, a[e], 8);
            a[e] += __shfl_xor_sync(0xffffffffu, a[e], 16);
          }
          if (lane < 8) red_add4(accg + 8 * KV_J + D_ + col + (lane >> 2) * 4, a[0], a[1], a[2], a[3]);
        }
        __syncwarp();
        if (tid == 320) {
          flag_add(FL_CS3 + j);
          mbar_wait(bars + 8 * B_MFREE, 0);
          flag_wait(FL_X1 + i, (epoch + 1) * 8u);
          flag_wait(FL_CS3 + j, (epoch + 1) * 16u);
          fence_async_all();
          mbar_expect_tx(bars + 8 * B_ST1, 8192 + 768);
          bulk_load(sb + OFF_CS + 320, accg + 8 * KV_J + D_ + 192 * j, 768, bars + 8 * B_ST1);
          bulk_load(sb + OFF_MISC, g_st1 + 128 * i * 8, 8192, bars + 8 * B_ST1);
        }
        __syncwarp();
        mbar_wait(bars + 8 * B_PEER, 0);
        const unsigned* fp = g_flags + (FL_PART + i * 8 + j) * 32 + lane;
        bool seen = lane >= 6;
        uint32_t n = 0;
        while (!__all_sync(0xffffffffu, seen) && ++n < (WAIT_LIMIT >> 4)) {
          if (!seen && ld_acquire(fp) == epoch + 1 && (lane < 2 || (lane < 4 ? mbar_test(bars + 8 * (B_SEND + 2), 0) && mbar_test(bars + 8 * (B_SEND + 3), 0) && mbar_test(bars + 8 * (B_EMPTY4 + 1), 0) : mbar_test(bars + 8 * (B_SDONE + lane), 0)))) {
            seen = true;
            if (lane & 1) TR4((lane >> 1) * 16 + 11);
            mbar_expect_tx(bars + 8 * (B_RDY + lane), 10240);
            bulk_load(sb + (lane < 2 ? OFF_G0 : lane < 4 ? OFF_G1 : OFF_SEND) + (lane & 1) * 10240, g_part + (size_t)(i * 8 + j) * 3840 + lane * 640, 10240,
                      bars + 8 * (B_RDY + lane));
          }
        }
      } else {
        mbar_wait(bars + 8 * B_SIGP, 0);
        if (lane < 20) {
          float a0 = 0.f, a1 = 0.f, a2 = 0.f, a3 = 0.f;
#pragma unroll 4
          for (int r = 0; r < 20; r++) {
            const uint4 v = lds128(sb + OFF_B + SPARE + r * 320 + lane * 16);
            a0 += __uint_as_float(v.x); a1 += __uint_as_float(v.y); a2 += __uint_as_float(v.z); a3 += __uint_as_float(v.w);
          }
          red_add4(accg + 8 * KV_J + 80 * j + 4 * lane, a0, a1, a2, a3);
        }
        __syncwarp();
      }
      if (tid == 352) {
        flag_add(FL_CS + j); flag_add_relaxed(FL_ST + i);
        TSTAMPX(20);
        mbar_expect_tx(bars + 8 * B_XR, 20480);
#pragma unroll 1
        for (int u = 0; u < 8; u++)
          tma2d(sb + OFF_B + (u / 3) * SLOT_B + SPARE + (u % 3) * 2560, &maps.xr, bars + 8 * B_XR, 80 * j, 128 * i + 16 * u);
        const int shift = (j < 2) ? 1 : (j < 4) ? -1 : (j < 6) ? 2 : -2;
        if ((shift > 0 && i == 0) || (shift < 0 && i == 15)) {
          const int nz = shift > 0 ? shift : -shift, zr = shift > 0 ? 0 : S_ - nz;
#pragma unroll 1
          for (int e = 0; e < nz * 10; e++)
            reinterpret_cast<uint4*>(g_Hs + (size_t)(2 + zr + e / 10) * D_ + 80 * j)[e % 10] = make_uint4(0, 0, 0, 0);
          fence_async_all();
        }
        prefetch_tmap(&maps.st_h); prefetch_tmap(&maps.st_x1); prefetch_tmap(&maps.hs); prefetch_tmap(&maps.x1); prefetch_tmap(&maps.xr);
        prefetch_tmap(&maps.w2); prefetch_tmap(&maps.w3); prefetch_tmap(&maps.w4); prefetch_tmap(&maps.wo); prefetch_tmap(&maps.st_out);
        mbar_wait(bars + 8 * B_SIGH, 0);
        TSTAMPX(23);
        tma2d_store(&maps.st_h, sb + OFF_STG, 80 * j, 128 * i + 2 + shift);
        tma2d_store(&maps.st_h, sb + OFF_STG + 10240, 80 * j, 128 * i + 66 + shift);
        bulk_commit(); bulk_wait<0>();
        flag_add(FL_H + i);
        TSTAMPX(24);
        mbar_wait(bars + 8 * B_SIGKV, 0);
        TSTAMPX(25);
        asm volatile("cp.reduce.async.bulk.global.shared::cta.bulk_group.add.f32 [%0], [%1], %2;"
                     ::"l"(accg + j * KV_J), "r"(sb + OFF_MISC), "r"(KV_J * 4) : "memory");
        bulk_commit(); bulk_wait<0>();
        flag_add(FL_KV + j);
        TSTAMPX(26);
        mbar_wait(bars + 8 * B_SIGX1, 0);
        TSTAMPX(27);
        tma2d_store(&maps.st_x1, sb + OFF_STG, 80 * j, 128 * i);
        tma2d_store(&maps.st_x1, sb + OFF_STG + 10240, 80 * j, 128 * i + 64);
        bulk_commit(); bulk_wait<0>();
        flag_add(FL_X1 + i);
        TSTAMPX(28);
        send_stream(0, epoch + 1);
      }
    }
  } else {
    uint4 pv[5], pw_[5], pc[2], pre;
    {
      const int row = 128 * i + 16 * j + (tid >> 4), l16 = tid & 15;
#pragma unroll
      for (int c = 0; c < 5; c++) pv[c] = __ldg(reinterpret_cast<const uint4*>(x + (size_t)row * D_ + c * 128 + l16 * 8));
      const int tq = tid < 200 ? tid : 0;
      const __nv_bfloat16* cp = w1 + (size_t)(40 * i + tq / 10) * D_ + 80 * j + 8 * (tq % 10);
      pc[0] = __ldg(reinterpret_cast<const uint4*>(cp)); pc[1] = __ldg(reinterpret_cast<const uint4*>(cp + 20 * D_));
      pre = __ldg(reinterpret_cast<const uint4*>(wphi + (size_t)j * 1600) + tq);
#pragma unroll
      for (int c = 0; c < 5; c++) pw_[c] = __ldg(reinterpret_cast<const uint4*>(gate_w + c * 128 + l16 * 8));
    }
    asm volatile("barrier.cluster.arrive.relaxed.aligned;" ::: "memory");
    asm volatile("setmaxnreg.inc.sync.aligned.u32 232;");
    const int wg = tid >> 7, warp = tid >> 5, lane = tid & 31, t = lane & 3;
    const int rloc = warp * 16 + (lane >> 2);
    const float* s_cs = reinterpret_cast<const float*>(sgen + OFF_CS);
    auto signal = [&](int b) {
      __syncwarp();
      if (lane == 0) mbar_arrive(bars + 8 * b);
    };
    auto releaseB = [&](uint32_t bar) {
      __syncwarp();
      if (lane == 0) mbar_arrive(bar);
    };
    auto release = [&](uint32_t bar) {
      __syncwarp();
      if (lane < 2) mbar_arrive_cta(bar, lane);
    };
    const uint32_t stg_lane = (warp * 16 + ((lane >> 3) & 1) * 8 + (lane & 7)) * 160 + (lane >> 4) * 16;

    {
#pragma unroll 1
      for (int e = tid; e < 800; e += 256) sts128(sb + OFF_MISC + e * 16, make_uint4(0, 0, 0, 0));
      bar_sync(1, 256);
      float f[40];
      float s = 0.f, gs = 0.f;
#pragma unroll
      for (int c = 0; c < 5; c++) {
        const uint32_t vv[4] = {pv[c].x, pv[c].y, pv[c].z, pv[c].w}, ww[4] = {pw_[c].x, pw_[c].y, pw_[c].z, pw_[c].w};
#pragma unroll
        for (int e = 0; e < 4; e++) {
          f[8 * c + 2 * e] = bf_lo(vv[e]); f[8 * c + 2 * e + 1] = bf_hi(vv[e]);
          s += f[8 * c + 2 * e] + f[8 * c + 2 * e + 1];
          gs = fmaf(f[8 * c + 2 * e], bf_lo(ww[e]), gs); gs = fmaf(f[8 * c + 2 * e + 1], bf_hi(ww[e]), gs);
        }
      }
#pragma unroll
      for (int o = 1; o < 16; o <<= 1) { s += __shfl_xor_sync(0xffffffffu, s, o); gs += __shfl_xor_sync(0xffffffffu, gs, o); }
      const float mean = s * (1.f / D_);
      float q = 0.f;
#pragma unroll
      for (int e = 0; e < 40; e++) { const float d = f[e] - mean; q = fmaf(d, d, q); }
#pragma unroll
      for (int o = 1; o < 16; o <<= 1) q += __shfl_xor_sync(0xffffffffu, q, o);
      const float rstd = rsqrtf(q * (1.f / D_) + 1e-5f);
      if (tid < 200) {
        const uint32_t cd = sb + OFF_B + SPARE + tid * 32;
        sts128(cd, make_uint4(__float_as_uint(bf_lo(pc[0].x) + bf_lo(pc[1].x)), __float_as_uint(bf_hi(pc[0].x) + bf_hi(pc[1].x)),
                              __float_as_uint(bf_lo(pc[0].y) + bf_lo(pc[1].y)), __float_as_uint(bf_hi(pc[0].y) + bf_hi(pc[1].y))));
        sts128(cd + 16, make_uint4(__float_as_uint(bf_lo(pc[0].z) + bf_lo(pc[1].z)), __float_as_uint(bf_hi(pc[0].z) + bf_hi(pc[1].z)),
                                   __float_as_uint(bf_lo(pc[0].w) + bf_lo(pc[1].w)), __float_as_uint(bf_hi(pc[0].w) + bf_hi(pc[1].w))));
        const uint32_t ww[4] = {pre.x, pre.y, pre.z, pre.w};
        const int h = tid / 50;
#pragma unroll
        for (int e = 0; e < 8; e++) {
          const int idx = tid * 8 + e, k = idx / 20, ff = idx - 20 * k;
          const int n = 40 * (h >> 1) + 8 * (ff >> 2) + 2 * (ff & 3) + (h & 1);
          const int off = (k >> 4) * 2560 + n * 32 + ((((k >> 3) ^ (n >> 2)) & 1) << 4) + (k & 7) * 2;
          *reinterpret_cast<unsigned short*>(sgen + OFF_MISC + off) = (unsigned short)(ww[e >> 1] >> ((e & 1) * 16));
        }
      }
      fence_async_smem();
      asm volatile("barrier.cluster.wait.aligned;" ::: "memory");
      if ((tid & 15) == 0) g_xstat[128 * i + 16 * j + (tid >> 4)] = make_float4(rstd, -mean * rstd, rcp(1.f + __expf(-gs)), 0.f);
      signal(B_SIGP);
    }
    TSTAMP(1);

    Ring ra{0, 0}, rb{0, 0};
    uint32_t qp[2][10], P[2][10];
    float st_g[2];
    {
      float accM[128], accR[32];
      zero_regs(accM); zero_regs(accR);
      uint32_t pa = 0, pb = 0;
#pragma unroll 1
      for (int k = 0; k < 10; k++) {
        mbar_wait(fullA + 8 * ra.idx, ra.phase);
        if (tid == 0) TRACE(32 + k);
        mbar_wait(fullB + 8 * rb.idx, rb.phase);
        if (tid == 0) TRACE(64 + k);
        if (k == 0) TSTAMP(2);
        const uint32_t a0 = sb16 + ((OFF_A + ra.idx * SLOT_A + wg * 8192) >> 4), b0 = sb16 + ((OFF_B + rb.idx * SLOT_B) >> 4);
        wg_fence();
#pragma unroll
        for (int kk = 0; kk < 4; kk++) {
          const uint64_t da = make_desc(a0, kk * 32, 16, 1024, 1);
          mma_ss256(accM, da, make_desc(b0, kk * 2048, 8192, 1024, 1));
          mma_ss64(accR, da, make_desc(b0, 32768 + kk * 512, 2048, 256, 3));
          if (kk == 0) {
            wg_commit();
            if (k > 0) {
              wg_wait<1>();
              if (k - 1 < 8) release(emptyA + 8 * pa);
              releaseB(emptyB + 8 * pb);
            }
          }
        }
        wg_commit();
        pa = ra.idx; pb = rb.idx;
        ra.next<NA>(); rb.next<NB>();
      }
      TSTAMP(18);
      float st_rstd[2], st_mr[2];
      mbar_wait(bars + 8 * B_CS, 0);
#pragma unroll
      for (int r = 0; r < 2; r++) {
        const uint4 st = lds128(sb + OFF_XST + (rloc + 8 * r) * 16);
        st_rstd[r] = __uint_as_float(st.x); st_mr[r] = __uint_as_float(st.y); st_g[r] = __uint_as_float(st.z);
      }
      TSTAMP(19);
      wg_wait<0>();
      fence_regs(accM); fence_regs(accR);
      TSTAMP(3);
#define ACC(P_, G, I_) ((G) < 8 ? accM[(P_) * 32 + ((G) & 7) * 4 + (I_)] : accR[(P_) * 8 + ((G) & 1) * 4 + (I_)])
      {
        uint32_t hv[10][2];
#pragma unroll
        for (int g = 0; g < 10; g++) {
          const float2 cs = *reinterpret_cast<const float2*>(s_cs + 8 * g + 2 * t);
          const float v0 = gelu_s(fmaf(ACC(0, g, 0), st_rstd[0], st_mr[0] * cs.x), 0.5f), v1 = gelu_s(fmaf(ACC(0, g, 1), st_rstd[0], st_mr[0] * cs.y), 0.5f);
          const float v2 = gelu_s(fmaf(ACC(0, g, 2), st_rstd[1], st_mr[1] * cs.x), 0.5f), v3 = gelu_s(fmaf(ACC(0, g, 3), st_rstd[1], st_mr[1] * cs.y), 0.5f);
          hv[g][0] = pack_bf16(v0, v1); hv[g][1] = pack_bf16(v2, v3);
        }
        bar_sync(1, 256);
#pragma unroll
        for (int s = 0; s < 5; s++) stsm4(sb + OFF_STG + stg_lane + s * 32, hv[2 * s][0], hv[2 * s][1], hv[2 * s + 1][0], hv[2 * s + 1][1]);
        fence_async_smem();
        signal(B_SIGH);
      }
      TSTAMP(4);
      uint32_t kf[5][4], qf[5][4];
#pragma unroll
      for (int s = 0; s < 5; s++) {
        kf[s][0] = pack_bf16(ACC(2, 2 * s, 0), ACC(2, 2 * s, 1)); kf[s][1] = pack_bf16(ACC(2, 2 * s, 2), ACC(2, 2 * s, 3));
        kf[s][2] = pack_bf16(ACC(2, 2 * s + 1, 0), ACC(2, 2 * s + 1, 1)); kf[s][3] = pack_bf16(ACC(2, 2 * s + 1, 2), ACC(2, 2 * s + 1, 3));
        qf[s][0] = pack_bf16(ACC(1, 2 * s, 0), ACC(1, 2 * s, 1)); qf[s][1] = pack_bf16(ACC(1, 2 * s, 2), ACC(1, 2 * s, 3));
        qf[s][2] = pack_bf16(ACC(1, 2 * s + 1, 0), ACC(1, 2 * s + 1, 1)); qf[s][3] = pack_bf16(ACC(1, 2 * s + 1, 2), ACC(1, 2 * s + 1, 3));
      }
      float pk[40], pq[40];
      wg_fence();
#pragma unroll
      for (int s = 0; s < 5; s++) {
        if (s == 0) mma_rs80_k_z(pk, kf[s], make_desc(sb16, OFF_MISC, 16, 256, 3));
        else mma_rs80_k(pk, kf[s], make_desc(sb16, OFF_MISC + s * 2560, 16, 256, 3));
      }
#pragma unroll
      for (int s = 0; s < 5; s++) {
        if (s == 0) mma_rs80_k_z(pq, qf[s], make_desc(sb16, OFF_MISC, 16, 256, 3));
        else mma_rs80_k(pq, qf[s], make_desc(sb16, OFF_MISC + s * 2560, 16, 256, 3));
      }
      wg_commit();
      {
        const int mat = lane >> 3;
        const int tok = warp * 16 + (mat & 1) * 8 + (lane & 7);
        const uint32_t ones = (t == 0) ? 0x00003f80u : 0u;
        __syncwarp();
#pragma unroll
        for (int p = 0; p < 2; p++) {
          const uint32_t rowa = sb + OFF_A + p * SLOT_A + tok * 128;
#pragma unroll
          for (int gg = 0; gg < 3; gg++) {
            const int g0 = 5 * p + 2 * gg;
            uint32_t r0 = pack_bf16(ACC(3, g0, 0), ACC(3, g0, 1)), r1 = pack_bf16(ACC(3, g0, 2), ACC(3, g0, 3));
            uint32_t r2 = ones, r3 = ones;
            if (gg < 2) { r2 = pack_bf16(ACC(3, g0 + 1, 0), ACC(3, g0 + 1, 1)); r3 = pack_bf16(ACC(3, g0 + 1, 2), ACC(3, g0 + 1, 3)); }
            stsm4(rowa + (((2 * gg + (mat >> 1)) ^ (tok & 7)) << 4), r0, r1, r2, r3);
          }
        }
      }
#undef ACC
      wg_wait<0>();
      fence_regs(pk); fence_regs(pq);
#pragma unroll
      for (int G = 0; G < 10; G++) {
        P[0][G] = pack_bf16(pk[4 * G], pk[4 * G + 1]); P[1][G] = pack_bf16(pk[4 * G + 2], pk[4 * G + 3]);
        qp[0][G] = pack_bf16(pq[4 * G], pq[4 * G + 1]); qp[1][G] = pack_bf16(pq[4 * G + 2], pq[4 * G + 3]);
      }
    }

    uint32_t fr[10][4];
    uint32_t xv[2][10];
#pragma unroll
    for (int g = 0; g < 10; g++) xv[0][g] = xv[1][g] = 0u;
    int pass;
    asm volatile("mov.u32 %0, 1;" : "=r"(pass));
#pragma unroll 1
    for (;; pass--) {
    feature_map(P, fr);
    if (pass == 0) break;
    {
      const int mat = lane >> 3;
      const int tok = warp * 16 + (mat & 1) * 8 + (lane & 7);
      const uint32_t base = sb + OFF_B + tok * 32 + (((mat >> 1) ^ ((tok >> 2) & 1)) << 4);
#pragma unroll
      for (int G = 0; G < 10; G++) stsm4(base + G * 4096, fr[G][0], fr[G][1], fr[G][2], fr[G][3]);
      fence_async_smem();
      bar_sync(1, 256);
      float kv[40];
      const uint32_t a0 = sb16 + ((OFF_A + wg * SLOT_A) >> 4), b0 = sb16 + ((OFF_B + wg * 20480) >> 4);
      wg_fence();
#pragma unroll
      for (int ks = 0; ks < 8; ks++) {
        if (ks == 0) mma_ss80_tt_z(kv, make_desc(a0, 0, 16, 1024, 1), make_desc(b0, 0, 4096, 256, 3));
        else mma_ss80_tt(kv, make_desc(a0, ks * 2048, 16, 1024, 1), make_desc(b0, ks * 512, 4096, 256, 3));
      }
      wg_commit();
      wg_wait<0>();
      fence_regs(kv);
      TSTAMP(31);
      release(emptyA); release(emptyA + 8); releaseB(emptyB);
      const uint32_t dst = sb + OFF_MISC + wg * (KV_PAIR * 4);
      const int m0 = (warp & 3) * 16 + (lane >> 2);
#pragma unroll
      for (int r = 0; r < 2; r++) {
        const int m = m0 + 8 * r;
        const bool hi = m >= 20;
        uint32_t v[10];
#pragma unroll
        for (int G = 0; G < 10; G++) v[G] = __float_as_uint(hi ? kv[4 * G + 2 * r + 1] : kv[4 * G + 2 * r]);
        const uint32_t p = dst + 4 * (m < 40 ? m * 48 + t * 12 : 1920 + t * 24 + 12);
        if (m <= 40) {
          sts128(p, make_uint4(v[0], v[1], v[2], v[3])); sts128(p + 16, make_uint4(v[4], v[5], v[6], v[7]));
          sts128(p + 32, make_uint4(v[8], v[9], 0u, 0u));
        }
      }
      if (m0 == 32) {
        const uint32_t p = dst + 4 * (1920 + t * 24);
        sts128(p, make_uint4(__float_as_uint(kv[2]), __float_as_uint(kv[6]), __float_as_uint(kv[10]), __float_as_uint(kv[14])));
        sts128(p + 16, make_uint4(__float_as_uint(kv[18]), __float_as_uint(kv[22]), __float_as_uint(kv[26]), __float_as_uint(kv[30])));
        sts128(p + 32, make_uint4(__float_as_uint(kv[34]), __float_as_uint(kv[38]), 0u, 0u));
      }
      fence_async_smem();
      signal(B_SIGKV);
    }
    TSTAMP(5);

    {
      {
        mbar_wait(bars + 8 * B_XR, 0);
        const uint32_t xa = sb + OFF_B + (warp / 3) * SLOT_B + SPARE + (warp % 3) * 2560 + (lane >> 2) * 160 + t * 4;
#pragma unroll
        for (int g = 0; g < 10; g++) { xv[0][g] = lds32(xa + g * 16); xv[1][g] = lds32(xa + 1280 + g * 16); }
      }
      float acc[40];
      zero_regs(acc);
      uint32_t pa = 0, pb = 0;
#pragma unroll 1
      for (int k = 0; k < 10; k++) {
        mbar_wait(fullA + 8 * ra.idx, ra.phase);
        if (tid == 0) TRACE(42 + k);
        if ((k & 3) == 0) mbar_wait(fullB + 8 * rb.idx, rb.phase);
        if (tid == 0) TRACE(74 + k);
        if (k == 0) TSTAMP(6);
        const uint32_t a0 = sb16 + ((OFF_A + ra.idx * SLOT_A + wg * 8192) >> 4);
        const uint32_t b0 = sb16 + ((OFF_B + rb.idx * SLOT_B + (k & 3) * 10240) >> 4);
        wg_fence();
#pragma unroll
        for (int kk = 0; kk < 4; kk++) {
          mma_ss80(acc, make_desc(a0, kk * 32, 16, 1024, 1), make_desc(b0, kk * 512, 2048, 256, 3));
          if (kk == 1) {
            wg_commit();
            if (k > 0) {
              wg_wait<1>();
              release(emptyA + 8 * pa);
              if ((k & 3) == 0) releaseB(emptyB + 8 * pb);
            }
          }
        }
        wg_commit();
        pa = ra.idx; pb = rb.idx;
        ra.next<NA>();
        if ((k & 3) == 3 || k == 9) rb.next<NB>();
      }
      wg_wait<0>();
      fence_regs(acc);
      release(emptyA + 8 * pa); releaseB(emptyB + 8 * pb);
      TSTAMP(7);
#pragma unroll
      for (int r = 0; r < 2; r++) {
#pragma unroll
        for (int g = 0; g < 10; g++)
          xv[r][g] = pack_bf16(bf_lo(xv[r][g]) + acc[4 * g + 2 * r], bf_hi(xv[r][g]) + acc[4 * g + 2 * r + 1]);
      }
      bar_sync(1, 256);
#pragma unroll
      for (int s = 0; s < 5; s++) stsm4(sb + OFF_STG + stg_lane + s * 32, xv[0][2 * s], xv[1][2 * s], xv[0][2 * s + 1], xv[1][2 * s + 1]);
#pragma unroll
      for (int r = 0; r < 2; r++) {
        float s = 0.f;
#pragma unroll
        for (int g = 0; g < 10; g++) {
          acc[4 * g + 2 * r] = bf_lo(xv[r][g]); acc[4 * g + 2 * r + 1] = bf_hi(xv[r][g]);
          s += acc[4 * g + 2 * r] + acc[4 * g + 2 * r + 1];
        }
        s += __shfl_xor_sync(0xffffffffu, s, 1); s += __shfl_xor_sync(0xffffffffu, s, 2);
        const float mu = s * (1.f / 80.f);
        float q = 0.f;
#pragma unroll
        for (int g = 0; g < 10; g++) {
          const float d0 = acc[4 * g + 2 * r] - mu, d1 = acc[4 * g + 2 * r + 1] - mu;
          q = fmaf(d0, d0, q); q = fmaf(d1, d1, q);
        }
        q += __shfl_xor_sync(0xffffffffu, q, 1); q += __shfl_xor_sync(0xffffffffu, q, 2);
        if (t == 0) g_st1[(128 * i + rloc + 8 * r) * 8 + j] = make_float2(mu, q);
      }
      fence_async_smem();
      signal(B_SIGX1);
    }
    TSTAMP(8);
#pragma unroll
    for (int G = 0; G < 10; G++) { P[0][G] = qp[0][G]; P[1][G] = qp[1][G]; }
    }

    uint32_t of[5][4];
    {
      mbar_wait(bars + 8 * B_KV, 0);
      uint4 kvr[2][3];
#pragma unroll
      for (int u = 0; u < 2; u++) {
        const int it = tid + 256 * u, p = it / 192, rem = it - 192 * p, n = rem >> 2, tq = rem & 3;
        const uint32_t sp = sb + OFF_MISC + 4 * (p * KV_PAIR + (n < 40 ? n * 48 + tq * 12 : 1920 + tq * 24 + (n & 1) * 12));
        if (it < 384) { kvr[u][0] = lds128(sp); kvr[u][1] = lds128(sp + 16); kvr[u][2] = lds128(sp + 32); }
      }
      bar_sync(1, 256);
#pragma unroll
      for (int u = 0; u < 2; u++) {
        const int it = tid + 256 * u, p = it / 192, rem = it - 192 * p, n = rem >> 2, tq = rem & 3;
        const int sh = (n < 40 ? (n >= 20) : (n & 1)) * 16;
        const uint32_t v[10] = {kvr[u][0].x, kvr[u][0].y, kvr[u][0].z, kvr[u][0].w, kvr[u][1].x, kvr[u][1].y, kvr[u][1].z, kvr[u][1].w, kvr[u][2].x, kvr[u][2].y};
        uint8_t* dst = sgen + OFF_MISC + p * 7680 + n * 32 + tq * 4;
        const int sw = ((n >> 2) & 1) << 4;
        if (it < 384) {
#pragma unroll
          for (int G = 0; G < 10; G++)
            *reinterpret_cast<uint32_t*>(dst + (G >> 1) * 1536 + (((G & 1) << 4) ^ sw)) = pack_bf16(__uint_as_float(v[G]), 0.f) << sh;
        }
      }
      fence_async_smem();
      bar_sync(1, 256);
      float o0[24], o1[24];
      wg_fence();
#pragma unroll
      for (int g = 0; g < 5; g++) {
        if (g == 0) mma_rs48_k_z(o0, fr[g], make_desc(sb16, OFF_MISC, 16, 256, 3));
        else mma_rs48_k(o0, fr[g], make_desc(sb16, OFF_MISC + g * 1536, 16, 256, 3));
      }
#pragma unroll
      for (int g = 0; g < 5; g++) {
        if (g == 0) mma_rs48_k_z(o1, fr[5], make_desc(sb16, OFF_MISC + 7680, 16, 256, 3));
        else mma_rs48_k(o1, fr[5 + g], make_desc(sb16, OFF_MISC + 7680 + g * 1536, 16, 256, 3));
      }
      wg_commit();
      wg_wait<0>();
      fence_regs(o0); fence_regs(o1);
      signal(B_MFREE);
#pragma unroll
      for (int r = 0; r < 2; r++) {
        const float a0 = __fdividef(st_g[r], o0[20 + 2 * r] + 1e-6f), a1 = __fdividef(st_g[r], o0[21 + 2 * r] + 1e-6f);
        const float b0 = __fdividef(st_g[r], o1[20 + 2 * r] + 1e-6f), b1 = __fdividef(st_g[r], o1[21 + 2 * r] + 1e-6f);
        const float am = t < 2 ? a0 : a1, bm = t < 2 ? b0 : b1;
#pragma unroll
        for (int g = 0; g < 5; g++) {
          const float sa = g < 2 ? a0 : (g == 2 ? am : a1), sb2 = g < 2 ? b0 : (g == 2 ? bm : b1);
          of[g >> 1][(g & 1) * 2 + r] = pack_bf16(o0[4 * g + 2 * r] * sa, o0[4 * g + 2 * r + 1] * sa);
          of[(5 + g) >> 1][((5 + g) & 1) * 2 + r] = pack_bf16(o1[4 * g + 2 * r] * sb2, o1[4 * g + 2 * r + 1] * sb2);
        }
      }
    }
    TSTAMP(9);

    uint32_t hf[12][4];
    {
      float acc[96];
      zero_regs(acc);
      uint32_t pa = 0, pb = 0;
#pragma unroll 1
      for (int k = 0; k < 10; k++) {
        mbar_wait(fullA + 8 * ra.idx, ra.phase);
        if (tid == 0) TRACE(52 + k);
        if ((k & 1) == 0) mbar_wait(fullB + 8 * rb.idx, rb.phase);
        if (tid == 0) TRACE(84 + k);
        if (k == 0) TSTAMP(10);
        const uint32_t a0 = sb16 + ((OFF_A + ra.idx * SLOT_A + wg * 8192) >> 4);
        const uint32_t b0 = sb16 + ((OFF_B + rb.idx * SLOT_B + (k & 1) * 24576) >> 4);
        wg_fence();
#pragma unroll
        for (int kk = 0; kk < 4; kk++) {
          mma_ss192(acc, make_desc(a0, kk * 32, 16, 1024, 1), make_desc(b0, kk * 2048, 8192, 1024, 1));
          if (kk == 0) {
            wg_commit();
            if (k > 0) {
              wg_wait<1>();
              release(emptyA + 8 * pa);
              if ((k & 1) == 0) releaseB(emptyB + 8 * pb);
            }
          }
        }
        wg_commit();
        pa = ra.idx; pb = rb.idx;
        ra.next<NA>();
        if (k & 1) rb.next<NB>();
      }
      float rs[2], mm[2];
      mbar_wait(bars + 8 * B_ST1, 0);
#pragma unroll
      for (int r = 0; r < 2; r++) {
        const uint4 su = lds128(sb + OFF_MISC + (rloc + 8 * r) * 64 + t * 16);
        const float m0 = __uint_as_float(su.x), m1 = __uint_as_float(su.z);
        float mu = m0 + m1;
        mu += __shfl_xor_sync(0xffffffffu, mu, 1); mu += __shfl_xor_sync(0xffffffffu, mu, 2);
        mu *= 0.125f;
        const float d0 = m0 - mu, d1 = m1 - mu;
        float q = __uint_as_float(su.y) + __uint_as_float(su.w) + 80.f * (d0 * d0 + d1 * d1);
        q += __shfl_xor_sync(0xffffffffu, q, 1); q += __shfl_xor_sync(0xffffffffu, q, 2);
        rs[r] = rsqrtf(q * (1.f / D_) + 1e-5f);
        mm[r] = -mu * rs[r];
      }
      wg_wait<0>();
      fence_regs(acc);
      releaseB(emptyB + 8 * pb);
      release(bars + 8 * B_PEER);
      TSTAMP(11);
      const float hs0 = 0.5f - 0.5f * st_g[0], hs1 = 0.5f - 0.5f * st_g[1];
#pragma unroll
      for (int g = 0; g < 24; g++) {
        const float2 cs = *reinterpret_cast<const float2*>(s_cs + 80 + 8 * g + 2 * t);
        const float v0 = gelu_s(fmaf(acc[4 * g], rs[0], mm[0] * cs.x), hs0), v1 = gelu_s(fmaf(acc[4 * g + 1], rs[0], mm[0] * cs.y), hs0);
        const float v2 = gelu_s(fmaf(acc[4 * g + 2], rs[1], mm[1] * cs.x), hs1), v3 = gelu_s(fmaf(acc[4 * g + 3], rs[1], mm[1] * cs.y), hs1);
        hf[g >> 1][(g & 1) * 2] = pack_bf16(v0, v1);
        hf[g >> 1][(g & 1) * 2 + 1] = pack_bf16(v2, v3);
      }
    }
    TSTAMP(12);

    {
      float acc[80], kp[40];
      const int wt = tid & 127;
      const uint32_t peer = map_peer(sb, rank ^ 1);
      Ring r4{0, 0};
      auto add16 = [&](uint32_t src) {
#pragma unroll
        for (int q = 0; q < 5; q++) {
          const uint4 v = lds128(src + q * 2048);
          float* d = &kp[8 * q];
          d[0] += bf_lo(v.x); d[1] += bf_hi(v.x); d[2] += bf_lo(v.y); d[3] += bf_hi(v.y);
          d[4] += bf_lo(v.z); d[5] += bf_hi(v.z); d[6] += bf_lo(v.w); d[7] += bf_hi(v.w);
        }
      };
      auto finish = [&](int c) {
        if (c > 1) mbar_wait(bars + 8 * (B_SDONE + 2 * (c - 2) + wg), 0);
        mbar_wait(bars + 8 * (B_DSR + 2 * (c - 1) + wg), 0);
        if (tid == 128) TR4((c - 1) * 16 + 3);
        add16(sb + OFF_DS + ((c - 1) & 1) * 20480 + wg * 10240 + wt * 16);
        const uint32_t dst = sb + OFF_SEND + wg * 10240 + wt * 16;
#pragma unroll
        for (int q = 0; q < 5; q++) {
          const float* d = &kp[8 * q];
          sts128(dst + q * 2048, make_uint4(pack_bf16(d[0], d[1]), pack_bf16(d[2], d[3]), pack_bf16(d[4], d[5]), pack_bf16(d[6], d[7])));
        }
        fence_async_smem();
        signal(B_SEND + 2 * (c - 1) + wg);
        if (tid == 128) TR4((c - 1) * 16 + 6);
      };
      zero_regs(kp);
      if (wg == 1) bar_sync(2, 256);
#pragma unroll 1
      for (int c = 0; c < 4; c++) {
        uint32_t prev = 0;
#pragma unroll
        for (int u = 0; u < 4; u++) {
          mbar_wait(bars + 8 * (B_FULL4 + r4.idx), r4.phase);
          const uint32_t b0 = sb16 + ((OFF_B + r4.idx * UNIT4) >> 4);
          if (u == 0 && tid == 128) TR4(c * 16 + 0);
          wg_fence();
#pragma unroll
          for (int s = 0; s < (u < 3 ? 4 : 5); s++) {
            const uint64_t db = make_desc(b0, s * 1024, u < 3 ? 4096 : 5120, 512, 2);
            if (u == 0 && s == 0) mma_rs160_n_z(acc, hf[0], db);
            else if (u < 3) mma_rs160_n(acc, hf[(4 * u + s) % 12], db);
            else mma_rs160_n(acc, of[s], db);
            if (s == 1 && u > 0) { wg_commit(); wg_wait<1>(); releaseB(bars + 8 * (B_EMPTY4 + prev)); }
          }
          wg_commit();
          prev = r4.idx;
          r4.next<NU4>();
          if (u == 1 && c == 0 && wg == 0) bar_arrive(2, 256);
          if (u == 0 && c > 0) finish(c);
          if (u == 2) {
            if (c == 3) {
              const float w0 = 1.f - st_g[0], w1s = 1.f - st_g[1];
#pragma unroll
              for (int g = 0; g < 10; g++) {
                kp[4 * g] = w0 * bf_lo(xv[0][g]); kp[4 * g + 1] = w0 * bf_hi(xv[0][g]);
                kp[4 * g + 2] = w1s * bf_lo(xv[1][g]); kp[4 * g + 3] = w1s * bf_hi(xv[1][g]);
              }
#pragma unroll 1
              for (int e = 0; e < 2; e++) {
                mbar_wait(bars + 8 * (B_RDY + 2 * e + wg), 0);
                add16(sb + (e == 0 ? OFF_G0 : OFF_G1) + wg * 10240 + wt * 16);
              }
            } else {
              zero_regs(kp);
            }
          }
        }
        if (tid == 128) TR4(c * 16 + 2);
        if (c == 0) mbar_wait(bars + 8 * B_PEER, 0);
        wg_wait<0>();
        fence_regs(acc);
        releaseB(bars + 8 * (B_EMPTY4 + prev));
        if (tid == 128) TR4(c * 16 + 5);
        uint32_t sn[20];
        if (rank) {
#pragma unroll
          for (int e = 0; e < 20; e++) sn[e] = pack_bf16(acc[2 * e], acc[2 * e + 1]);
#pragma unroll
          for (int e = 0; e < 40; e++) kp[e] += acc[40 + e];
        } else {
#pragma unroll
          for (int e = 0; e < 20; e++) sn[e] = pack_bf16(acc[40 + 2 * e], acc[41 + 2 * e]);
#pragma unroll
          for (int e = 0; e < 40; e++) kp[e] += acc[e];
        }
        fence_regs(kp);
        const uint32_t dso = peer + OFF_DS + (c & 1) * 20480 + wg * 10240 + wt * 16, dsb = peer + OFF_BAR + 8 * (B_DSR + 2 * c + wg);
#pragma unroll
        for (int q = 0; q < 5; q++) st_async16(dso + q * 2048, sn[4 * q], sn[4 * q + 1], sn[4 * q + 2], sn[4 * q + 3], dsb);
      }
      TSTAMP(13);
#pragma unroll 1
      for (int c = 0; c < 2; c++) {
        mbar_wait(bars + 8 * ((c == 0 ? B_DSR + 6 : B_RDY + 4) + wg), 0);
        add16(sb + (c == 0 ? OFF_DS + 20480 : OFF_SEND) + wg * 10240 + wt * 16);
      }
      TSTAMP(14);
#pragma unroll
      for (int s = 0; s < 5; s++)
        stsm4(sb + OFF_DS + stg_lane + s * 32, pack_bf16(kp[8 * s], kp[8 * s + 1]), pack_bf16(kp[8 * s + 2], kp[8 * s + 3]),
              pack_bf16(kp[8 * s + 4], kp[8 * s + 5]), pack_bf16(kp[8 * s + 6], kp[8 * s + 7]));
      fence_async_smem();
      __syncwarp();
      if (lane == 0) {
        tma2d_store(&maps.st_out, sb + OFF_DS + warp * 2560, 80 * j, 128 * i + 16 * warp);
        bulk_commit(); bulk_wait_read();
      }
    }
    TSTAMP(15);
    if (tid == 0) asm volatile("red.relaxed.gpu.global.add.u32 [%0], 1;" ::"l"(g_flags + FL_DONE * 32) : "memory");
  }
}

namespace {
typedef CUresult (*EncodeFn)(CUtensorMap*, CUtensorMapDataType, cuuint32_t, void*, const cuuint64_t*, const cuuint64_t*,
                             const cuuint32_t*, const cuuint32_t*, CUtensorMapInterleave, CUtensorMapSwizzle,
                             CUtensorMapL2promotion, CUtensorMapFloatOOBfill);

void encode(EncodeFn fn, CUtensorMap* m, const void* ptr, int rank, const cuuint64_t* dims, const cuuint64_t* strides,
            const cuuint32_t* box, CUtensorMapSwizzle swz) {
  cuuint32_t es[5] = {1, 1, 1, 1, 1};
  fn(m, CU_TENSOR_MAP_DATA_TYPE_BFLOAT16, rank, const_cast<void*>(ptr), dims, strides, box, es, CU_TENSOR_MAP_INTERLEAVE_NONE,
     swz, CU_TENSOR_MAP_L2_PROMOTION_L2_128B, CU_TENSOR_MAP_FLOAT_OOB_FILL_NONE);
}
}

extern "C" void kernel_launch(void* const* d_in, const int* in_sizes, int n_in, void* d_out, int out_size) {
  (void)in_sizes; (void)n_in; (void)out_size;
  const __nv_bfloat16* x = (const __nv_bfloat16*)d_in[0];
  const __nv_bfloat16* wqkv = (const __nv_bfloat16*)d_in[1];
  const __nv_bfloat16* wphi = (const __nv_bfloat16*)d_in[2];
  const __nv_bfloat16* wo = (const __nv_bfloat16*)d_in[3];
  const __nv_bfloat16* w1 = (const __nv_bfloat16*)d_in[5];
  const __nv_bfloat16* w2 = (const __nv_bfloat16*)d_in[6];
  const __nv_bfloat16* w3 = (const __nv_bfloat16*)d_in[7];
  const __nv_bfloat16* w4 = (const __nv_bfloat16*)d_in[8];
  const __nv_bfloat16* gate_w = (const __nv_bfloat16*)d_in[9];

  static EncodeFn enc = nullptr;
  static void *pHs = nullptr, *pX1 = nullptr;
  if (!enc) {
    cudaDriverEntryPointQueryResult qr;
    cudaGetDriverEntryPoint("cuTensorMapEncodeTiled", (void**)&enc, cudaEnableDefault, &qr);
    cudaGetSymbolAddress(&pHs, g_Hs);
    cudaGetSymbolAddress(&pX1, g_X1);
    cudaFuncSetAttribute(fused_kernel, cudaFuncAttributeMaxDynamicSharedMemorySize, SMEM_BYTES);
  }
  Maps m;
  {
    cuuint64_t dims[2] = {D_, S_}, str[1] = {D_ * 2};
    cuuint32_t boxh[2] = {64, 64};
    encode(enc, &m.x, x, 2, dims, str, boxh, CU_TENSOR_MAP_SWIZZLE_128B);
    encode(enc, &m.hs, (const char*)pHs + 2 * D_ * 2, 2, dims, str, boxh, CU_TENSOR_MAP_SWIZZLE_128B);
    encode(enc, &m.x1, pX1, 2, dims, str, boxh, CU_TENSOR_MAP_SWIZZLE_128B);
    cuuint32_t boxs[2] = {80, 64};
    cuuint64_t dimsp[2] = {D_, S_ + 4};
    encode(enc, &m.st_h, pHs, 2, dimsp, str, boxs, CU_TENSOR_MAP_SWIZZLE_NONE);
    encode(enc, &m.st_x1, pX1, 2, dims, str, boxs, CU_TENSOR_MAP_SWIZZLE_NONE);
    cuuint32_t boxr[2] = {80, 16};
    encode(enc, &m.st_out, d_out, 2, dims, str, boxr, CU_TENSOR_MAP_SWIZZLE_NONE);
    encode(enc, &m.xr, x, 2, dims, str, boxr, CU_TENSOR_MAP_SWIZZLE_NONE);
  }
  {
    cuuint64_t dims[3] = {80, D_, 8}, str[2] = {D_ * 2, 160};
    cuuint32_t boxm[3] = {64, 64, 1}, boxr[3] = {16, 64, 1};
    encode(enc, &m.w1m, w1, 3, dims, str, boxm, CU_TENSOR_MAP_SWIZZLE_128B);
    encode(enc, &m.w1r, w1, 3, dims, str, boxr, CU_TENSOR_MAP_SWIZZLE_32B);
  }
  {
    cuuint64_t dims[4] = {80, D_, 3, 8}, str[3] = {3 * D_ * 2, D_ * 2, 160};
    cuuint32_t boxm[4] = {64, 64, 3, 1}, boxr[4] = {16, 64, 3, 1};
    encode(enc, &m.qm, wqkv, 4, dims, str, boxm, CU_TENSOR_MAP_SWIZZLE_128B);
    encode(enc, &m.qr, wqkv, 4, dims, str, boxr, CU_TENSOR_MAP_SWIZZLE_32B);
  }
  {
    cuuint64_t dims[3] = {16, D_, 40}, str[2] = {D_ * 2, 32};
    cuuint32_t box2[3] = {16, 64, 5};
    encode(enc, &m.w2, w2, 3, dims, str, box2, CU_TENSOR_MAP_SWIZZLE_32B);
  }
  {
    cuuint64_t dims[3] = {32, D_, 20}, dims4[3] = {32, F_, 20}, str[2] = {D_ * 2, 64};
    cuuint32_t box4[3] = {32, 64, 5}, boxo[3] = {32, 80, 5};
    encode(enc, &m.w4, w4, 3, dims4, str, box4, CU_TENSOR_MAP_SWIZZLE_64B);
    encode(enc, &m.wo, wo, 3, dims, str, boxo, CU_TENSOR_MAP_SWIZZLE_64B);
  }
  {
    cuuint64_t dims[3] = {64, D_, 24}, str[2] = {F_ * 2, 128};
    cuuint32_t box[3] = {64, 64, 3};
    encode(enc, &m.w3, w3, 3, dims, str, box, CU_TENSOR_MAP_SWIZZLE_128B);
  }
  fused_kernel<<<NCTA, 384, SMEM_BYTES, cudaStreamPerThread>>>(m, x, wqkv, wphi, w1, w2, w3, w4, wo, gate_w);
}
```

```cpp
#include <cuda_runtime.h>
#include <cuda_bf16.h>
#include <cuda.h>
#include <stdint.h>

namespace {

constexpr int S_ = 2048, D_ = 640, F_ = 1536;
constexpr int NCTA = 128;
constexpr int KV_PAIR = 40 * 48 + 96;
constexpr int KV_J = 2 * KV_PAIR;

constexpr int SLOT_B = 49152, NB = 3;
constexpr int SLOT_A = 16384, NA = 4;
constexpr int OFF_B = 0;
constexpr int OFF_A = OFF_B + NB * SLOT_B;
constexpr int OFF_STG = OFF_A + 2 * SLOT_A;
constexpr int OFF_MISC = OFF_A + NA * SLOT_A;
constexpr int OFF_XST = OFF_MISC + 13312;
constexpr int OFF_CS = OFF_MISC + 16384;
constexpr int OFF_BAR = OFF_CS + 1088;
constexpr int SMEM_BYTES = OFF_BAR + 512;
constexpr int B_FULLA = 0, B_FULLB = 4, B_CS = 7, B_XR = 8, B_KV = 9, B_ST1 = 10, B_SDONE = 11  , B_RDY = 17  ,
              B_FULL4 = 23  , B_DSR = 28  , B_SEND = 36  , B_EMPTYB = 42  ,
              B_SIGP = 45, B_SIGH = 46, B_SIGKV = 47, B_SIGX1 = 48, B_MFREE = 49, B_EMPTY4 = 50  ,
              B_EMPTYA = 55  , B_PEER = 59, NBAR = 60;
constexpr int SPARE = 40960;
constexpr int UNIT4 = 25600, NU4 = 5;
constexpr int OFF_DS = OFF_A, OFF_SEND = OFF_A + 40960, OFF_G0 = OFF_A + 61440, OFF_G1 = OFF_B + UNIT4;

constexpr int FL_DONE = 0, FL_H = 1, FL_X1 = FL_H + 16, FL_KV = FL_X1 + 16, FL_CS = FL_KV + 8, FL_CS3 = FL_CS + 8, FL_ST = FL_CS3 + 8, FL_PART = FL_ST + 16;
constexpr int FL_COUNT = FL_PART + 16 * 8;
constexpr int ACC_FLOATS = 8 * KV_J + D_ + F_;

struct Maps {
  CUtensorMap x, w1m, w1r, qm, qr, hs, w2, x1, w3, w4, wo, st_h, st_x1, st_out, xr;
};

}

__device__ __align__(1024) __nv_bfloat16 g_Hs[(S_ + 4) * D_];
__device__ __align__(1024) __nv_bfloat16 g_X1[S_ * D_];
__device__ __align__(128) float g_acc[2][ACC_FLOATS];
__device__ __align__(128) float4 g_xstat[S_];
__device__ __align__(128) float2 g_st1[S_ * 8];
__device__ __align__(128) uint4 g_part[16 * 8 * 3 * 1280];
__device__ __align__(128) unsigned g_flags[FL_COUNT * 32];
#define TSTAMP(n) do {} while (0)
#define TSTAMPX(n) do {} while (0)
#define TRACE(n) do {} while (0)
#define TR4(n) do {} while (0)

namespace {

__device__ __forceinline__ long long gtime() { long long t; asm volatile("mov.u64 %0, %%globaltimer;" : "=l"(t)); return t; }
__device__ __forceinline__ uint32_t smem_u32(const void* p) { return (uint32_t)__cvta_generic_to_shared(p); }
__device__ __forceinline__ void mbar_init(uint32_t bar, int cnt) {
  asm volatile("mbarrier.init.shared::cta.b64 [%0], %1;" ::"r"(bar), "r"(cnt) : "memory");
}
__device__ __forceinline__ void mbar_expect_tx(uint32_t bar, int bytes) {
  asm volatile("mbarrier.arrive.expect_tx.shared::cta.b64 _, [%0], %1;" ::"r"(bar), "r"(bytes) : "memory");
}
__device__ __forceinline__ void mbar_arrive_cta(uint32_t bar, uint32_t cta) {
  asm volatile("{\n.reg .b32 ra;\nmapa.shared::cluster.u32 ra, %0, %1;\nmbarrier.arrive.shared::cluster.b64 _, [ra];\n}"
               ::"r"(bar), "r"(cta) : "memory");
}
__device__ __forceinline__ uint32_t mbar_try(uint32_t bar, uint32_t parity) {
  uint32_t ok;
  asm volatile("{\n.reg .pred p;\nmbarrier.try_wait.parity.shared::cta.b64 p, [%1], %2;\nselp.u32 %0, 1, 0, p;\n}"
               : "=r"(ok) : "r"(bar), "r"(parity) : "memory");
  return ok;
}
constexpr uint32_t WAIT_LIMIT = 1u << 22;
__device__ __forceinline__ void mbar_wait(uint32_t bar, uint32_t parity) {
  uint32_t n = 0;
  while (!mbar_try(bar, parity) && ++n < WAIT_LIMIT) {}
}
__device__ __forceinline__ unsigned ld_acquire(const unsigned* p) {
  unsigned v;
  asm volatile("ld.acquire.gpu.global.u32 %0, [%1];" : "=r"(v) : "l"(p) : "memory");
  return v;
}
__device__ __forceinline__ void flag_wait(int idx, unsigned target) {
  const unsigned* p = g_flags + idx * 32;
  uint32_t n = 0;
  while ((int)(ld_acquire(p) - target) < 0 && ++n < (WAIT_LIMIT >> 4)) {}
}
__device__ __forceinline__ void flag_add(int idx) {
  asm volatile("red.release.gpu.global.add.u32 [%0], 1;" ::"l"(g_flags + idx * 32) : "memory");
}
__device__ __forceinline__ void flag_add_relaxed(int idx) {
  asm volatile("red.relaxed.gpu.global.add.u32 [%0], 1;" ::"l"(g_flags + idx * 32) : "memory");
}
__device__ __forceinline__ uint32_t mbar_test(uint32_t bar, uint32_t parity) {
  uint32_t ok;
  asm volatile("{\n.reg .pred p;\nmbarrier.test_wait.parity.shared::cta.b64 p, [%1], %2;\nselp.u32 %0, 1, 0, p;\n}"
               : "=r"(ok) : "r"(bar), "r"(parity) : "memory");
  return ok;
}
__device__ __forceinline__ uint32_t lds32(uint32_t a) {
  uint32_t v;
  asm volatile("ld.shared.u32 %0, [%1];" : "=r"(v) : "r"(a) : "memory");
  return v;
}
__device__ __forceinline__ void mbar_arrive(uint32_t bar) {
  asm volatile("mbarrier.arrive.shared::cta.b64 _, [%0];" ::"r"(bar) : "memory");
}
__device__ __forceinline__ void fence_async_all() { asm volatile("fence.proxy.async;" ::: "memory"); }
__device__ __forceinline__ void fence_async_smem() { asm volatile("fence.proxy.async.shared::cta;" ::: "memory"); }
__device__ __forceinline__ void bar_sync(int id, int n) { asm volatile("bar.sync %0, %1;" ::"r"(id), "r"(n) : "memory"); }

__device__ __forceinline__ void tma2d(uint32_t dst, const CUtensorMap* m, uint32_t bar, int c0, int c1) {
  asm volatile("cp.async.bulk.tensor.2d.shared::cluster.global.mbarrier::complete_tx::bytes [%0], [%1, {%3, %4}], [%2];"
               ::"r"(dst), "l"(m), "r"(bar), "r"(c0), "r"(c1) : "memory");
}
__device__ __forceinline__ void tma2d_mc(uint32_t dst, const CUtensorMap* m, uint32_t bar, int c0, int c1) {
  asm volatile("cp.async.bulk.tensor.2d.shared::cluster.global.mbarrier::complete_tx::bytes.multicast::cluster"
               " [%0], [%1, {%3, %4}], [%2], %5;"
               ::"r"(dst), "l"(m), "r"(bar), "r"(c0), "r"(c1), "h"((uint16_t)3) : "memory");
}
__device__ __forceinline__ void tma3d(uint32_t dst, const CUtensorMap* m, uint32_t bar, int c0, int c1, int c2) {
  asm volatile("cp.async.bulk.tensor.3d.shared::cluster.global.mbarrier::complete_tx::bytes [%0], [%1, {%3, %4, %5}], [%2];"
               ::"r"(dst), "l"(m), "r"(bar), "r"(c0), "r"(c1), "r"(c2) : "memory");
}
__device__ __forceinline__ void tma4d(uint32_t dst, const CUtensorMap* m, uint32_t bar, int c0, int c1, int c2, int c3) {
  asm volatile("cp.async.bulk.tensor.4d.shared::cluster.global.mbarrier::complete_tx::bytes [%0], [%1, {%3, %4, %5, %6}], [%2];"
               ::"r"(dst), "l"(m), "r"(bar), "r"(c0), "r"(c1), "r"(c2), "r"(c3) : "memory");
}
__device__ __forceinline__ void tma2d_store(const CUtensorMap* m, uint32_t src, int c0, int c1) {
  asm volatile("cp.async.bulk.tensor.2d.global.shared::cta.bulk_group [%0, {%2, %3}], [%1];"
               ::"l"(m), "r"(src), "r"(c0), "r"(c1) : "memory");
}
__device__ __forceinline__ void bulk_store(void* dst, uint32_t src, uint32_t bytes) {
  asm volatile("cp.async.bulk.global.shared::cta.bulk_group [%0], [%1], %2;" ::"l"(dst), "r"(src), "r"(bytes) : "memory");
}
__device__ __forceinline__ void bulk_load(uint32_t dst, const void* src, uint32_t bytes, uint32_t bar) {
  asm volatile("cp.async.bulk.shared::cluster.global.mbarrier::complete_tx::bytes [%0], [%1], %2, [%3];"
               ::"r"(dst), "l"(src), "r"(bytes), "r"(bar) : "memory");
}
__device__ __forceinline__ void bulk_commit() { asm volatile("cp.async.bulk.commit_group;" ::: "memory"); }
template <int N> __device__ __forceinline__ void bulk_wait() { asm volatile("cp.async.bulk.wait_group %0;" ::"n"(N) : "memory"); }
__device__ __forceinline__ void bulk_wait_read() { asm volatile("cp.async.bulk.wait_group.read 0;" ::: "memory"); }
__device__ __forceinline__ void bar_arrive(int id, int n) { asm volatile("bar.arrive %0, %1;" ::"r"(id), "r"(n) : "memory"); }
__device__ __forceinline__ uint4 lds128(uint32_t a) {
  uint4 v;
  asm volatile("ld.shared.v4.u32 {%0, %1, %2, %3}, [%4];" : "=r"(v.x), "=r"(v.y), "=r"(v.z), "=r"(v.w) : "r"(a) : "memory");
  return v;
}
__device__ __forceinline__ void sts128(uint32_t a, uint4 v) {
  asm volatile("st.shared.v4.u32 [%0], {%1, %2, %3, %4};" ::"r"(a), "r"(v.x), "r"(v.y), "r"(v.z), "r"(v.w) : "memory");
}
__device__ __forceinline__ uint32_t map_peer(uint32_t addr, uint32_t cta) {
  uint32_t r;
  asm("mapa.shared::cluster.u32 %0, %1, %2;" : "=r"(r) : "r"(addr), "r"(cta));
  return r;
}
__device__ __forceinline__ void st_async16(uint32_t addr, uint32_t a, uint32_t b, uint32_t c, uint32_t d, uint32_t bar) {
  asm volatile("st.async.weak.shared::cluster.mbarrier::complete_tx::bytes.v4.b32 [%0], {%1, %2, %3, %4}, [%5];"
               ::"r"(addr), "r"(a), "r"(b), "r"(c), "r"(d), "r"(bar) : "memory");
}
__device__ __forceinline__ void l2_prefetch(const void* p, uint32_t bytes) {
  asm volatile("cp.async.bulk.prefetch.L2.global [%0], %1;" ::"l"(p), "r"(bytes) : "memory");
}
__device__ __forceinline__ void prefetch_tmap(const CUtensorMap* m) {
  asm volatile("prefetch.tensormap [%0];" ::"l"(m) : "memory");
}
__device__ __forceinline__ uint64_t make_desc(uint32_t a16, uint32_t off, uint32_t lbo, uint32_t sbo, uint32_t swz) {
  const uint32_t lo = a16 + ((off >> 4) + ((lbo >> 4) << 16)), hi = (sbo >> 4) | (swz << 30);
  uint64_t d;
  asm("mov.b64 %0, {%1, %2};" : "=l"(d) : "r"(lo), "r"(hi));
  return d;
}
__device__ __forceinline__ void wg_fence() { asm volatile("wgmma.fence.sync.aligned;" ::: "memory"); }
__device__ __forceinline__ void wg_commit() { asm volatile("wgmma.commit_group.sync.aligned;" ::: "memory"); }
template <int N> __device__ __forceinline__ void wg_wait() { asm volatile("wgmma.wait_group.sync.aligned %0;" ::"n"(N) : "memory"); }
template <int N> __device__ __forceinline__ void fence_regs(float (&d)[N]) {
#pragma unroll
  for (int i = 0; i < N; i++) asm volatile("" : "+f"(d[i])::"memory");
}
template <int N> __device__ __forceinline__ void zero_regs(float (&d)[N]) {
#pragma unroll
  for (int i = 0; i < N; i++) d[i] = 0.f;
}
__device__ __forceinline__ uint32_t pack_bf16(float lo, float hi) {
  uint32_t r;
  asm("cvt.rn.bf16x2.f32 %0, %1, %2;" : "=r"(r) : "f"(hi), "f"(lo));
  return r;
}
__device__ __forceinline__ float bf_lo(uint32_t v) { return __uint_as_float(v << 16); }
__device__ __forceinline__ float bf_hi(uint32_t v) { return __uint_as_float(v & 0xffff0000u); }
__device__ __forceinline__ uint32_t max_bf2(uint32_t a, uint32_t b) {
  uint32_t r; asm("max.bf16x2 %0, %1, %2;" : "=r"(r) : "r"(a), "r"(b)); return r;
}
__device__ __forceinline__ uint32_t min_bf2(uint32_t a, uint32_t b) {
  uint32_t r; asm("min.bf16x2 %0, %1, %2;" : "=r"(r) : "r"(a), "r"(b)); return r;
}
__device__ __forceinline__ float ex2(float x) { float r; asm("ex2.approx.ftz.f32 %0, %1;" : "=f"(r) : "f"(x)); return r; }
__device__ __forceinline__ float rcp(float x) { float r; asm("rcp.approx.ftz.f32 %0, %1;" : "=f"(r) : "f"(x)); return r; }
__device__ __forceinline__ float tanh_ap(float x) { float r; asm("tanh.approx.f32 %0, %1;" : "=f"(r) : "f"(x)); return r; }
__device__ __forceinline__ float gelu_s(float x, float hs) {
  float u = x * fmaf(x * x, 0.0356774081f, 0.7978845608f);
  float hx = x * hs;
  return fmaf(hx, tanh_ap(u), hx);
}
__device__ __forceinline__ void stsm4(uint32_t addr, uint32_t r0, uint32_t r1, uint32_t r2, uint32_t r3) {
  asm volatile("stmatrix.sync.aligned.m8n8.x4.shared.b16 [%0], {%1, %2, %3, %4};"
               ::"r"(addr), "r"(r0), "r"(r1), "r"(r2), "r"(r3) : "memory");
}
__device__ __forceinline__ void red_add4(float* p, float a, float b, float c, float d) {
  asm volatile("red.global.add.v4.f32 [%0], {%1, %2, %3, %4};" ::"l"(p), "f"(a), "f"(b), "f"(c), "f"(d) : "memory");
}

__device__ __forceinline__ void mma_ss256(float (&d)[128], uint64_t descA, uint64_t descB) {
  asm volatile("wgmma.mma_async.sync.aligned.m64n256k16.f32.bf16.bf16 {"
      "%0, %1, %2, %3, %4, %5, %6, %7, %8, %9, %10, %11, %12, %13, %14, %15, "
      "%16, %17, %18, %19, %20, %21, %22, %23, %24, %25, %26, %27, %28, %29, %30, %31, "
      "%32, %33, %34, %35, %36, %37, %38, %39, %40, %41, %42, %43, %44, %45, %46, %47, "
      "%48, %49, %50, %51, %52, %53, %54, %55, %56, %57, %58, %59, %60, %61, %62, %63, "
      "%64, %65, %66, %67, %68, %69, %70, %71, %72, %73, %74, %75, %76, %77, %78, %79, "
      "%80, %81, %82, %83, %84, %85, %86, %87, %88, %89, %90, %91, %92, %93, %94, %95, "
      "%96, %97, %98, %99, %100, %101, %102, %103, %104, %105, %106, %107, %108, %109, %110, %111, "
      "%112, %113, %114, %115, %116, %117, %118, %119, %120, %121, %122, %123, %124, %125, %126, %127"
      "}, %128, %129, 1, 1, 1, 0, 1;\n"
      : "+f"(d[0]), "+f"(d[1]), "+f"(d[2]), "+f"(d[3]), "+f"(d[4]), "+f"(d[5]), "+f"(d[6]), "+f"(d[7]),
        "+f"(d[8]), "+f"(d[9]), "+f"(d[10]), "+f"(d[11]), "+f"(d[12]), "+f"(d[13]), "+f"(d[14]), "+f"(d[15]),
        "+f"(d[16]), "+f"(d[17]), "+f"(d[18]), "+f"(d[19]), "+f"(d[20]), "+f"(d[21]), "+f"(d[22]), "+f"(d[23]),
        "+f"(d[24]), "+f"(d[25]), "+f"(d[26]), "+f"(d[27]), "+f"(d[28]), "+f"(d[29]), "+f"(d[30]), "+f"(d[31]),
        "+f"(d[32]), "+f"(d[33]), "+f"(d[34]), "+f"(d[35]), "+f"(d[36]), "+f"(d[37]), "+f"(d[38]), "+f"(d[39]),
        "+f"(d[40]), "+f"(d[41]), "+f"(d[42]), "+f"(d[43]), "+f"(d[44]), "+f"(d[45]), "+f"(d[46]), "+f"(d[47]),
        "+f"(d[48]), "+f"(d[49]), "+f"(d[50]), "+f"(d[51]), "+f"(d[52]), "+f"(d[53]), "+f"(d[54]), "+f"(d[55]),
        "+f"(d[56]), "+f"(d[57]), "+f"(d[58]), "+f"(d[59]), "+f"(d[60]), "+f"(d[61]), "+f"(d[62]), "+f"(d[63]),
        "+f"(d[64]), "+f"(d[65]), "+f"(d[66]), "+f"(d[67]), "+f"(d[68]), "+f"(d[69]), "+f"(d[70]), "+f"(d[71]),
        "+f"(d[72]), "+f"(d[73]), "+f"(d[74]), "+f"(d[75]), "+f"(d[76]), "+f"(d[77]), "+f"(d[78]), "+f"(d[79]),
        "+f"(d[80]), "+f"(d[81]), "+f"(d[82]), "+f"(d[83]), "+f"(d[84]), "+f"(d[85]), "+f"(d[86]), "+f"(d[87]),
        "+f"(d[88]), "+f"(d[89]), "+f"(d[90]), "+f"(d[91]), "+f"(d[92]), "+f"(d[93]), "+f"(d[94]), "+f"(d[95]),
        "+f"(d[96]), "+f"(d[97]), "+f"(d[98]), "+f"(d[99]), "+f"(d[100]), "+f"(d[101]), "+f"(d[102]), "+f"(d[103]),
        "+f"(d[104]), "+f"(d[105]), "+f"(d[106]), "+f"(d[107]), "+f"(d[108]), "+f"(d[109]), "+f"(d[110]), "+f"(d[111]),
        "+f"(d[112]), "+f"(d[113]), "+f"(d[114]), "+f"(d[115]), "+f"(d[116]), "+f"(d[117]), "+f"(d[118]), "+f"(d[119]),
        "+f"(d[120]), "+f"(d[121]), "+f"(d[122]), "+f"(d[123]), "+f"(d[124]), "+f"(d[125]), "+f"(d[126]), "+f"(d[127])
      : "l"(descA), "l"(descB));
}

__device__ __forceinline__ void mma_ss64(float (&d)[32], uint64_t descA, uint64_t descB) {
  asm volatile("wgmma.mma_async.sync.aligned.m64n64k16.f32.bf16.bf16 {"
      "%0, %1, %2, %3, %4, %5, %6, %7, %8, %9, %10, %11, %12, %13, %14, %15, "
      "%16, %17, %18, %19, %20, %21, %22, %23, %24, %25, %26, %27, %28, %29, %30, %31"
      "}, %32, %33, 1, 1, 1, 0, 1;\n"
      : "+f"(d[0]), "+f"(d[1]), "+f"(d[2]), "+f"(d[3]), "+f"(d[4]), "+f"(d[5]), "+f"(d[6]), "+f"(d[7]),
        "+f"(d[8]), "+f"(d[9]), "+f"(d[10]), "+f"(d[11]), "+f"(d[12]), "+f"(d[13]), "+f"(d[14]), "+f"(d[15]),
        "+f"(d[16]), "+f"(d[17]), "+f"(d[18]), "+f"(d[19]), "+f"(d[20]), "+f"(d[21]), "+f"(d[22]), "+f"(d[23]),
        "+f"(d[24]), "+f"(d[25]), "+f"(d[26]), "+f"(d[27]), "+f"(d[28]), "+f"(d[29]), "+f"(d[30]), "+f"(d[31])
      : "l"(descA), "l"(descB));
}

__device__ __forceinline__ void mma_ss80(float (&d)[40], uint64_t descA, uint64_t descB) {
  asm volatile("wgmma.mma_async.sync.aligned.m64n80k16.f32.bf16.bf16 {"
      "%0, %1, %2, %3, %4, %5, %6, %7, %8, %9, %10, %11, %12, %13, %14, %15, "
      "%16, %17, %18, %19, %20, %21, %22, %23, %24, %25, %26, %27, %28, %29, %30, %31, "
      "%32, %33, %34, %35, %36, %37, %38, %39"
      "}, %40, %41, 1, 1, 1, 0, 1;\n"
      : "+f"(d[0]), "+f"(d[1]), "+f"(d[2]), "+f"(d[3]), "+f"(d[4]), "+f"(d[5]), "+f"(d[6]), "+f"(d[7]),
        "+f"(d[8]), "+f"(d[9]), "+f"(d[10]), "+f"(d[11]), "+f"(d[12]), "+f"(d[13]), "+f"(d[14]), "+f"(d[15]),
        "+f"(d[16]), "+f"(d[17]), "+f"(d[18]), "+f"(d[19]), "+f"(d[20]), "+f"(d[21]), "+f"(d[22]), "+f"(d[23]),
        "+f"(d[24]), "+f"(d[25]), "+f"(d[26]), "+f"(d[27]), "+f"(d[28]), "+f"(d[29]), "+f"(d[30]), "+f"(d[31]),
        "+f"(d[32]), "+f"(d[33]), "+f"(d[34]), "+f"(d[35]), "+f"(d[36]), "+f"(d[37]), "+f"(d[38]), "+f"(d[39])
      : "l"(descA), "l"(descB));
}

__device__ __forceinline__ void mma_ss192(float (&d)[96], uint64_t descA, uint64_t descB) {
  asm volatile("wgmma.mma_async.sync.aligned.m64n192k16.f32.bf16.bf16 {"
      "%0, %1, %2, %3, %4, %5, %6, %7, %8, %9, %10, %11, %12, %13, %14, %15, "
      "%16, %17, %18, %19, %20, %21, %22, %23, %24, %25, %26, %27, %28, %29, %30, %31, "
      "%32, %33, %34, %35, %36, %37, %38, %39, %40, %41, %42, %43, %44, %45, %46, %47, "
      "%48, %49, %50, %51, %52, %53, %54, %55, %56, %57, %58, %59, %60, %61, %62, %63, "
      "%64, %65, %66, %67, %68, %69, %70, %71, %72, %73, %74, %75, %76, %77, %78, %79, "
      "%80, %81, %82, %83, %84, %85, %86, %87, %88, %89, %90, %91, %92, %93, %94, %95"
      "}, %96, %97, 1, 1, 1, 0, 1;\n"
      : "+f"(d[0]), "+f"(d[1]), "+f"(d[2]), "+f"(d[3]), "+f"(d[4]), "+f"(d[5]), "+f"(d[6]), "+f"(d[7]),
        "+f"(d[8]), "+f"(d[9]), "+f"(d[10]), "+f"(d[11]), "+f"(d[12]), "+f"(d[13]), "+f"(d[14]), "+f"(d[15]),
        "+f"(d[16]), "+f"(d[17]), "+f"(d[18]), "+f"(d[19]), "+f"(d[20]), "+f"(d[21]), "+f"(d[22]), "+f"(d[23]),
        "+f"(d[24]), "+f"(d[25]), "+f"(d[26]), "+f"(d[27]), "+f"(d[28]), "+f"(d[29]), "+f"(d[30]), "+f"(d[31]),
        "+f"(d[32]), "+f"(d[33]), "+f"(d[34]), "+f"(d[35]), "+f"(d[36]), "+f"(d[37]), "+f"(d[38]), "+f"(d[39]),
        "+f"(d[40]), "+f"(d[41]), "+f"(d[42]), "+f"(d[43]), "+f"(d[44]), "+f"(d[45]), "+f"(d[46]), "+f"(d[47]),
        "+f"(d[48]), "+f"(d[49]), "+f"(d[50]), "+f"(d[51]), "+f"(d[52]), "+f"(d[53]), "+f"(d[54]), "+f"(d[55]),
        "+f"(d[56]), "+f"(d[57]), "+f"(d[58]), "+f"(d[59]), "+f"(d[60]), "+f"(d[61]), "+f"(d[62]), "+f"(d[63]),
        "+f"(d[64]), "+f"(d[65]), "+f"(d[66]), "+f"(d[67]), "+f"(d[68]), "+f"(d[69]), "+f"(d[70]), "+f"(d[71]),
        "+f"(d[72]), "+f"(d[73]), "+f"(d[74]), "+f"(d[75]), "+f"(d[76]), "+f"(d[77]), "+f"(d[78]), "+f"(d[79]),
        "+f"(d[80]), "+f"(d[81]), "+f"(d[82]), "+f"(d[83]), "+f"(d[84]), "+f"(d[85]), "+f"(d[86]), "+f"(d[87]),
        "+f"(d[88]), "+f"(d[89]), "+f"(d[90]), "+f"(d[91]), "+f"(d[92]), "+f"(d[93]), "+f"(d[94]), "+f"(d[95])
      : "l"(descA), "l"(descB));
}

__device__ __forceinline__ void mma_ss80_tt(float (&d)[40], uint64_t descA, uint64_t descB) {
  asm volatile("wgmma.mma_async.sync.aligned.m64n80k16.f32.bf16.bf16 {"
      "%0, %1, %2, %3, %4, %5, %6, %7, %8, %9, %10, %11, %12, %13, %14, %15, "
      "%16, %17, %18, %19, %20, %21, %22, %23, %24, %25, %26, %27, %28, %29, %30, %31, "
      "%32, %33, %34, %35, %36, %37, %38, %39"
      "}, %40, %41, 1, 1, 1, 1, 1;\n"
      : "+f"(d[0]), "+f"(d[1]), "+f"(d[2]), "+f"(d[3]), "+f"(d[4]), "+f"(d[5]), "+f"(d[6]), "+f"(d[7]),
        "+f"(d[8]), "+f"(d[9]), "+f"(d[10]), "+f"(d[11]), "+f"(d[12]), "+f"(d[13]), "+f"(d[14]), "+f"(d[15]),
        "+f"(d[16]), "+f"(d[17]), "+f"(d[18]), "+f"(d[19]), "+f"(d[20]), "+f"(d[21]), "+f"(d[22]), "+f"(d[23]),
        "+f"(d[24]), "+f"(d[25]), "+f"(d[26]), "+f"(d[27]), "+f"(d[28]), "+f"(d[29]), "+f"(d[30]), "+f"(d[31]),
        "+f"(d[32]), "+f"(d[33]), "+f"(d[34]), "+f"(d[35]), "+f"(d[36]), "+f"(d[37]), "+f"(d[38]), "+f"(d[39])
      : "l"(descA), "l"(descB));
}
__device__ __forceinline__ void mma_ss80_tt_z(float (&d)[40], uint64_t descA, uint64_t descB) {
  asm volatile("wgmma.mma_async.sync.aligned.m64n80k16.f32.bf16.bf16 {"
      "%0, %1, %2, %3, %4, %5, %6, %7, %8, %9, %10, %11, %12, %13, %14, %15, "
      "%16, %17, %18, %19, %20, %21, %22, %23, %24, %25, %26, %27, %28, %29, %30, %31, "
      "%32, %33, %34, %35, %36, %37, %38, %39"
      "}, %40, %41, 0, 1, 1, 1, 1;\n"
      : "=f"(d[0]), "=f"(d[1]), "=f"(d[2]), "=f"(d[3]), "=f"(d[4]), "=f"(d[5]), "=f"(d[6]), "=f"(d[7]),
        "=f"(d[8]), "=f"(d[9]), "=f"(d[10]), "=f"(d[11]), "=f"(d[12]), "=f"(d[13]), "=f"(d[14]), "=f"(d[15]),
        "=f"(d[16]), "=f"(d[17]), "=f"(d[18]), "=f"(d[19]), "=f"(d[20]), "=f"(d[21]), "=f"(d[22]), "=f"(d[23]),
        "=f"(d[24]), "=f"(d[25]), "=f"(d[26]), "=f"(d[27]), "=f"(d[28]), "=f"(d[29]), "=f"(d[30]), "=f"(d[31]),
        "=f"(d[32]), "=f"(d[33]), "=f"(d[34]), "=f"(d[35]), "=f"(d[36]), "=f"(d[37]), "=f"(d[38]), "=f"(d[39])
      : "l"(descA), "l"(descB));
}

__device__ __forceinline__ void mma_rs80_k(float (&d)[40], const uint32_t (&a)[4], uint64_t descB) {
  asm volatile("wgmma.mma_async.sync.aligned.m64n80k16.f32.bf16.bf16 {"
      "%0, %1, %2, %3, %4, %5, %6, %7, %8, %9, %10, %11, %12, %13, %14, %15, "
      "%16, %17, %18, %19, %20, %21, %22, %23, %24, %25, %26, %27, %28, %29, %30, %31, "
      "%32, %33, %34, %35, %36, %37, %38, %39"
      "}, {%40, %41, %42, %43}, %44, 1, 1, 1, 0;\n"
      : "+f"(d[0]), "+f"(d[1]), "+f"(d[2]), "+f"(d[3]), "+f"(d[4]), "+f"(d[5]), "+f"(d[6]), "+f"(d[7]),
        "+f"(d[8]), "+f"(d[9]), "+f"(d[10]), "+f"(d[11]), "+f"(d[12]), "+f"(d[13]), "+f"(d[14]), "+f"(d[15]),
        "+f"(d[16]), "+f"(d[17]), "+f"(d[18]), "+f"(d[19]), "+f"(d[20]), "+f"(d[21]), "+f"(d[22]), "+f"(d[23]),
        "+f"(d[24]), "+f"(d[25]), "+f"(d[26]), "+f"(d[27]), "+f"(d[28]), "+f"(d[29]), "+f"(d[30]), "+f"(d[31]),
        "+f"(d[32]), "+f"(d[33]), "+f"(d[34]), "+f"(d[35]), "+f"(d[36]), "+f"(d[37]), "+f"(d[38]), "+f"(d[39])
      : "r"(a[0]), "r"(a[1]), "r"(a[2]), "r"(a[3]), "l"(descB));
}
__device__ __forceinline__ void mma_rs80_k_z(float (&d)[40], const uint32_t (&a)[4], uint64_t descB) {
  asm volatile("wgmma.mma_async.sync.aligned.m64n80k16.f32.bf16.bf16 {"
      "%0, %1, %2, %3, %4, %5, %6, %7, %8, %9, %10, %11, %12, %13, %14, %15, "
      "%16, %17, %18, %19, %20, %21, %22, %23, %24, %25, %26, %27, %28, %29, %30, %31, "
      "%32, %33, %34, %35, %36, %37, %38, %39"
      "}, {%40, %41, %42, %43}, %44, 0, 1, 1, 0;\n"
      : "=f"(d[0]), "=f"(d[1]), "=f"(d[2]), "=f"(d[3]), "=f"(d[4]), "=f"(d[5]), "=f"(d[6]), "=f"(d[7]),
        "=f"(d[8]), "=f"(d[9]), "=f"(d[10]), "=f"(d[11]), "=f"(d[12]), "=f"(d[13]), "=f"(d[14]), "=f"(d[15]),
        "=f"(d[16]), "=f"(d[17]), "=f"(d[18]), "=f"(d[19]), "=f"(d[20]), "=f"(d[21]), "=f"(d[22]), "=f"(d[23]),
        "=f"(d[24]), "=f"(d[25]), "=f"(d[26]), "=f"(d[27]), "=f"(d[28]), "=f"(d[29]), "=f"(d[30]), "=f"(d[31]),
        "=f"(d[32]), "=f"(d[33]), "=f"(d[34]), "=f"(d[35]), "=f"(d[36]), "=f"(d[37]), "=f"(d[38]), "=f"(d[39])
      : "r"(a[0]), "r"(a[1]), "r"(a[2]), "r"(a[3]), "l"(descB));
}

__device__ __forceinline__ void mma_rs48_k(float (&d)[24], const uint32_t (&a)[4], uint64_t descB) {
  asm volatile("wgmma.mma_async.sync.aligned.m64n48k16.f32.bf16.bf16 {"
      "%0, %1, %2, %3, %4, %5, %6, %7, %8, %9, %10, %11, %12, %13, %14, %15, "
      "%16, %17, %18, %19, %20, %21, %22, %23"
      "}, {%24, %25, %26, %27}, %28, 1, 1, 1, 0;\n"
      : "+f"(d[0]), "+f"(d[1]), "+f"(d[2]), "+f"(d[3]), "+f"(d[4]), "+f"(d[5]), "+f"(d[6]), "+f"(d[7]),
        "+f"(d[8]), "+f"(d[9]), "+f"(d[10]), "+f"(d[11]), "+f"(d[12]), "+f"(d[13]), "+f"(d[14]), "+f"(d[15]),
        "+f"(d[16]), "+f"(d[17]), "+f"(d[18]), "+f"(d[19]), "+f"(d[20]), "+f"(d[21]), "+f"(d[22]), "+f"(d[23])
      : "r"(a[0]), "r"(a[1]), "r"(a[2]), "r"(a[3]), "l"(descB));
}
__device__ __forceinline__ void mma_rs48_k_z(float (&d)[24], const uint32_t (&a)[4], uint64_t descB) {
  asm volatile("wgmma.mma_async.sync.aligned.m64n48k16.f32.bf16.bf16 {"
      "%0, %1, %2, %3, %4, %5, %6, %7, %8, %9, %10, %11, %12, %13, %14, %15, "
      "%16, %17, %18, %19, %20, %21, %22, %23"
      "}, {%24, %25, %26, %27}, %28, 0, 1, 1, 0;\n"
      : "=f"(d[0]), "=f"(d[1]), "=f"(d[2]), "=f"(d[3]), "=f"(d[4]), "=f"(d[5]), "=f"(d[6]), "=f"(d[7]),
        "=f"(d[8]), "=f"(d[9]), "=f"(d[10]), "=f"(d[11]), "=f"(d[12]), "=f"(d[13]), "=f"(d[14]), "=f"(d[15]),
        "=f"(d[16]), "=f"(d[17]), "=f"(d[18]), "=f"(d[19]), "=f"(d[20]), "=f"(d[21]), "=f"(d[22]), "=f"(d[23])
      : "r"(a[0]), "r"(a[1]), "r"(a[2]), "r"(a[3]), "l"(descB));
}

__device__ __forceinline__ void mma_rs160_n(float (&d)[80], const uint32_t (&a)[4], uint64_t descB) {
  asm volatile("wgmma.mma_async.sync.aligned.m64n160k16.f32.bf16.bf16 {"
      "%0, %1, %2, %3, %4, %5, %6, %7, %8, %9, %10, %11, %12, %13, %14, %15, "
      "%16, %17, %18, %19, %20, %21, %22, %23, %24, %25, %26, %27, %28, %29, %30, %31, "
      "%32, %33, %34, %35, %36, %37, %38, %39, %40, %41, %42, %43, %44, %45, %46, %47, "
      "%48, %49, %50, %51, %52, %53, %54, %55, %56, %57, %58, %59, %60, %61, %62, %63, "
      "%64, %65, %66, %67, %68, %69, %70, %71, %72, %73, %74, %75, %76, %77, %78, %79"
      "}, {%80, %81, %82, %83}, %84, 1, 1, 1, 1;\n"
      : "+f"(d[0]), "+f"(d[1]), "+f"(d[2]), "+f"(d[3]), "+f"(d[4]), "+f"(d[5]), "+f"(d[6]), "+f"(d[7]),
        "+f"(d[8]), "+f"(d[9]), "+f"(d[10]), "+f"(d[11]), "+f"(d[12]), "+f"(d[13]), "+f"(d[14]), "+f"(d[15]),
        "+f"(d[16]), "+f"(d[17]), "+f"(d[18]), "+f"(d[19]), "+f"(d[20]), "+f"(d[21]), "+f"(d[22]), "+f"(d[23]),
        "+f"(d[24]), "+f"(d[25]), "+f"(d[26]), "+f"(d[27]), "+f"(d[28]), "+f"(d[29]), "+f"(d[30]), "+f"(d[31]),
        "+f"(d[32]), "+f"(d[33]), "+f"(d[34]), "+f"(d[35]), "+f"(d[36]), "+f"(d[37]), "+f"(d[38]), "+f"(d[39]),
        "+f"(d[40]), "+f"(d[41]), "+f"(d[42]), "+f"(d[43]), "+f"(d[44]), "+f"(d[45]), "+f"(d[46]), "+f"(d[47]),
        "+f"(d[48]), "+f"(d[49]), "+f"(d[50]), "+f"(d[51]), "+f"(d[52]), "+f"(d[53]), "+f"(d[54]), "+f"(d[55]),
        "+f"(d[56]), "+f"(d[57]), "+f"(d[58]), "+f"(d[59]), "+f"(d[60]), "+f"(d[61]), "+f"(d[62]), "+f"(d[63]),
        "+f"(d[64]), "+f"(d[65]), "+f"(d[66]), "+f"(d[67]), "+f"(d[68]), "+f"(d[69]), "+f"(d[70]), "+f"(d[71]),
        "+f"(d[72]), "+f"(d[73]), "+f"(d[74]), "+f"(d[75]), "+f"(d[76]), "+f"(d[77]), "+f"(d[78]), "+f"(d[79])
      : "r"(a[0]), "r"(a[1]), "r"(a[2]), "r"(a[3]), "l"(descB));
}
__device__ __forceinline__ void mma_rs160_n_z(float (&d)[80], const uint32_t (&a)[4], uint64_t descB) {
  asm volatile("wgmma.mma_async.sync.aligned.m64n160k16.f32.bf16.bf16 {"
      "%0, %1, %2, %3, %4, %5, %6, %7, %8, %9, %10, %11, %12, %13, %14, %15, "
      "%16, %17, %18, %19, %20, %21, %22, %23, %24, %25, %26, %27, %28, %29, %30, %31, "
      "%32, %33, %34, %35, %36, %37, %38, %39, %40, %41, %42, %43, %44, %45, %46, %47, "
      "%48, %49, %50, %51, %52, %53, %54, %55, %56, %57, %58, %59, %60, %61, %62, %63, "
      "%64, %65, %66, %67, %68, %69, %70, %71, %72, %73, %74, %75, %76, %77, %78, %79"
      "}, {%80, %81, %82, %83}, %84, 0, 1, 1, 1;\n"
      : "=f"(d[0]), "=f"(d[1]), "=f"(d[2]), "=f"(d[3]), "=f"(d[4]), "=f"(d[5]), "=f"(d[6]), "=f"(d[7]),
        "=f"(d[8]), "=f"(d[9]), "=f"(d[10]), "=f"(d[11]), "=f"(d[12]), "=f"(d[13]), "=f"(d[14]), "=f"(d[15]),
        "=f"(d[16]), "=f"(d[17]), "=f"(d[18]), "=f"(d[19]), "=f"(d[20]), "=f"(d[21]), "=f"(d[22]), "=f"(d[23]),
        "=f"(d[24]), "=f"(d[25]), "=f"(d[26]), "=f"(d[27]), "=f"(d[28]), "=f"(d[29]), "=f"(d[30]), "=f"(d[31]),
        "=f"(d[32]), "=f"(d[33]), "=f"(d[34]), "=f"(d[35]), "=f"(d[36]), "=f"(d[37]), "=f"(d[38]), "=f"(d[39]),
        "=f"(d[40]), "=f"(d[41]), "=f"(d[42]), "=f"(d[43]), "=f"(d[44]), "=f"(d[45]), "=f"(d[46]), "=f"(d[47]),
        "=f"(d[48]), "=f"(d[49]), "=f"(d[50]), "=f"(d[51]), "=f"(d[52]), "=f"(d[53]), "=f"(d[54]), "=f"(d[55]),
        "=f"(d[56]), "=f"(d[57]), "=f"(d[58]), "=f"(d[59]), "=f"(d[60]), "=f"(d[61]), "=f"(d[62]), "=f"(d[63]),
        "=f"(d[64]), "=f"(d[65]), "=f"(d[66]), "=f"(d[67]), "=f"(d[68]), "=f"(d[69]), "=f"(d[70]), "=f"(d[71]),
        "=f"(d[72]), "=f"(d[73]), "=f"(d[74]), "=f"(d[75]), "=f"(d[76]), "=f"(d[77]), "=f"(d[78]), "=f"(d[79])
      : "r"(a[0]), "r"(a[1]), "r"(a[2]), "r"(a[3]), "l"(descB));
}

__device__ __forceinline__ void feature_map(const uint32_t (&P)[2][10], uint32_t (&fr)[10][4]) {
  constexpr float L2E = 1.4426950408889634f;
#pragma unroll
  for (int p = 0; p < 2; p++) {
#pragma unroll
    for (int r = 0; r < 2; r++) {
      uint32_t mx = P[r][5 * p], mn = mx;
#pragma unroll
      for (int g = 1; g < 5; g++) { mx = max_bf2(mx, P[r][5 * p + g]); mn = min_bf2(mn, P[r][5 * p + g]); }
      mx = max_bf2(mx, __shfl_xor_sync(0xffffffffu, mx, 1));
      mn = min_bf2(mn, __shfl_xor_sync(0xffffffffu, mn, 1));
      mx = max_bf2(mx, __shfl_xor_sync(0xffffffffu, mx, 2));
      mn = min_bf2(mn, __shfl_xor_sync(0xffffffffu, mn, 2));
      float mx0 = -bf_lo(mx) * L2E, mx1 = -bf_hi(mx) * L2E, mn0 = bf_lo(mn) * L2E, mn1 = bf_hi(mn) * L2E;
      float ep0[5], ep1[5], en0[5], en1[5];
      float sp0 = 0.f, sp1 = 0.f, sn0 = 0.f, sn1 = 0.f;
#pragma unroll
      for (int g = 0; g < 5; g++) {
        float x0 = bf_lo(P[r][5 * p + g]), x1 = bf_hi(P[r][5 * p + g]);
        ep0[g] = ex2(fmaf(x0, L2E, mx0)); ep1[g] = ex2(fmaf(x1, L2E, mx1));
        en0[g] = ex2(fmaf(x0, -L2E, mn0)); en1[g] = ex2(fmaf(x1, -L2E, mn1));
        sp0 += ep0[g]; sp1 += ep1[g]; sn0 += en0[g]; sn1 += en1[g];
      }
      sp0 += __shfl_xor_sync(0xffffffffu, sp0, 1); sp1 += __shfl_xor_sync(0xffffffffu, sp1, 1);
      sn0 += __shfl_xor_sync(0xffffffffu, sn0, 1); sn1 += __shfl_xor_sync(0xffffffffu, sn1, 1);
      sp0 += __shfl_xor_sync(0xffffffffu, sp0, 2); sp1 += __shfl_xor_sync(0xffffffffu, sp1, 2);
      sn0 += __shfl_xor_sync(0xffffffffu, sn0, 2); sn1 += __shfl_xor_sync(0xffffffffu, sn1, 2);
      sp0 = rcp(sp0); sp1 = rcp(sp1); sn0 = rcp(sn0); sn1 = rcp(sn1);
#pragma unroll
      for (int g = 0; g < 5; g++) {
        fr[5 * p + g][r] = pack_bf16(ep0[g] * sp0, ep1[g] * sp1);
        fr[5 * p + g][2 + r] = pack_bf16(en0[g] * sn0, en1[g] * sn1);
      }
    }
  }
}

struct Ring {
  uint32_t idx, phase;
  template <int N> __device__ __forceinline__ void next() { if (++idx == N) { idx = 0; phase ^= 1; } }
};

}

__global__ void __cluster_dims__(2, 1, 1) __launch_bounds__(384, 1)
fused_kernel(const __grid_constant__ Maps maps, const __nv_bfloat16* __restrict__ x, const __nv_bfloat16* __restrict__ wqkv,
             const __nv_bfloat16* __restrict__ wphi, const __nv_bfloat16* __restrict__ w1, const __nv_bfloat16* __restrict__ w2,
             const __nv_bfloat16* __restrict__ w3, const __nv_bfloat16* __restrict__ w4, const __nv_bfloat16* __restrict__ wo,
             const __nv_bfloat16* __restrict__ gate_w) {
  extern __shared__ __align__(1024) uint8_t sgen[];
  const uint32_t sb = smem_u32(sgen);
  const uint32_t sb16 = (sb & 0x3FFFFu) >> 4;
  const uint32_t bars = sb + OFF_BAR;
  const uint32_t fullA = bars + 8 * B_FULLA, emptyA = bars + 8 * B_EMPTYA, fullB = bars + 8 * B_FULLB, emptyB = bars + 8 * B_EMPTYB;

  const int tid = threadIdx.x;
  const int rank = blockIdx.x & 1;
  const int pairIdx = blockIdx.x >> 1;
  const int i = pairIdx >> 2, j = 2 * (pairIdx & 3) + rank;

  TSTAMP(0);
  auto load_p1_b = [&](int k, uint32_t slot, uint32_t bar) {
    mbar_expect_tx(bar, 40960);
    tma4d(slot + 8192, &maps.qm, bar, 0, 64 * k, 0, j);
    tma3d(slot, &maps.w1m, bar, 0, 64 * k, j);
    tma4d(slot + 32768 + 2048, &maps.qr, bar, 64, 64 * k, 0, j);
    tma3d(slot + 32768, &maps.w1r, bar, 64, 64 * k, j);
  };
  if (tid >= 256) {
    asm volatile("setmaxnreg.dec.sync.aligned.u32 40;");
    if (tid == 256) {
#pragma unroll
      for (int s = 0; s < NA; s++) mbar_init(fullA + 8 * s, 1);
      asm volatile("fence.mbarrier_init.release.cluster;" ::: "memory");
#pragma unroll 1
      for (int u = 0; u < 4; u++) {
        if ((u & 1) == 0) mbar_expect_tx(fullA + 4 * u, SLOT_A);
        tma2d(sb + OFF_A + u * 8192, &maps.x, fullA + 8 * (u >> 1), 64 * (u >> 1), 128 * i + 64 * (u & 1));
      }
    } else if (tid == 288) {
#pragma unroll
      for (int s = 0; s < NB; s++) mbar_init(fullB + 8 * s, 1);
      asm volatile("fence.mbarrier_init.release.cluster;" ::: "memory");
#pragma unroll 1
      for (int k = 0; k < 2; k++) load_p1_b(k, sb + OFF_B + k * SLOT_B, fullB + 8 * k);
    } else if (tid == 320) {
#pragma unroll
      for (int b = B_CS; b < NBAR; b++) mbar_init(bars + 8 * b, b == B_CS ? 2 : b < B_SEND ? 1 : b < B_EMPTYB ? 4 : b < B_EMPTYA ? 8 : 16);
#pragma unroll
      for (int b = B_DSR; b < B_SEND; b++) mbar_expect_tx(bars + 8 * b, 10240);
      asm volatile("fence.mbarrier_init.release.cluster;" ::: "memory");
    }
    __syncwarp();
    asm volatile("barrier.cluster.arrive.relaxed.aligned;\nbarrier.cluster.wait.aligned;" ::: "memory");
    auto get_epoch = [&]() { return *reinterpret_cast<volatile unsigned*>(g_flags + FL_DONE * 32) / NCTA; };
    const int lane = tid & 31, pw = (tid >> 5) & 3;
    auto send_stream = [&](int w, unsigned ep1) {
#pragma unroll 1
      for (int c = 0; c < 3; c++) {
        const int d = (j + 2 * c + 2) & 7;
        mbar_wait(bars + 8 * (B_SEND + 2 * c + w), 0);
        if (w) TR4(c * 16 + 7);
        bulk_store(g_part + (size_t)((i * 8 + d) * 3 + c) * 1280 + w * 640, sb + OFF_SEND + w * 10240, 10240);
        bulk_commit();
        bulk_wait<0>();
        mbar_arrive(bars + 8 * (B_SDONE + 2 * c + w));
        if (w) TR4(c * 16 + 9);
        asm volatile("st.release.gpu.global.u32 [%0], %1;"
                     ::"l"(g_flags + (FL_PART + i * 8 + d) * 32 + 2 * c + w), "r"(ep1) : "memory");
        if (w) TR4(c * 16 + 10);
      }
    };
    if (pw == 0) {
      if (tid == 256) {
        Ring r{2, 1};
        unsigned ep1 = 0;
#pragma unroll 1
        for (int k = 2; k < 30; k++) {
          if (k == 4) ep1 = get_epoch() + 1;
          if (k == 10 || k == 20) {
            const unsigned tgt = ep1 * 8u;
            const unsigned* f0 = g_flags + (k == 10 ? FL_H + ((i - 1) & 15) : FL_X1 + i) * 32;
            const unsigned* f1 = g_flags + (k == 10 ? FL_H + i : FL_X1 + i) * 32;
            const unsigned* f2 = g_flags + (k == 10 ? FL_H + ((i + 1) & 15) : FL_X1 + i) * 32;
            uint32_t n = 0;
            while (++n < (WAIT_LIMIT >> 4)) {
              unsigned v0, v1, v2;
              asm volatile("ld.relaxed.gpu.global.u32 %0, [%3];\nld.relaxed.gpu.global.u32 %1, [%4];\nld.acquire.gpu.global.u32 %2, [%5];"
                           : "=r"(v0), "=r"(v1), "=r"(v2) : "l"(f0), "l"(f1), "l"(f2) : "memory");
              if ((int)((v0 - tgt) | (v1 - tgt) | (v2 - tgt)) >= 0) break;
            }
            TSTAMPX(k == 10 ? 29 : 30);
          }
          mbar_wait(emptyA + 8 * r.idx, r.phase);
          const uint32_t bar = fullA + 8 * r.idx, slot = sb + OFF_A + r.idx * SLOT_A;
          TRACE(k);
          mbar_expect_tx(bar, SLOT_A);
          tma2d_mc(slot + rank * 8192, k < 10 ? &maps.x : k < 20 ? &maps.hs : &maps.x1, bar, 64 * (k % 10), 128 * i + 64 * rank);
          r.next<NA>();
        }
        send_stream(1, ep1);
      }
    } else if (pw == 1) {
      if (tid == 288) {
        Ring r{2, 1};
#pragma unroll 1
        for (int k = 2; k < 18; k++) {
          mbar_wait(emptyB + 8 * r.idx, r.phase);
          const uint32_t bar = fullB + 8 * r.idx, slot = sb + OFF_B + r.idx * SLOT_B;
          if (k < 10) {
            load_p1_b(k, slot, bar);
          } else if (k < 13) {
            if (k == 12) mbar_wait(fullA + 8 * 2, 0);
            mbar_expect_tx(bar, k < 12 ? 40960 : 20480);
#pragma unroll 1
            for (int u = 0; u < (k < 12 ? 4 : 2); u++) tma3d(slot + u * 10240, &maps.w2, bar, 0, 256 * (k - 10) + 64 * u, 5 * j);
          } else {
            mbar_expect_tx(bar, 49152);
            tma3d(slot, &maps.w3, bar, 0, 128 * (k - 13), 3 * j);
            tma3d(slot + 24576, &maps.w3, bar, 0, 128 * (k - 13) + 64, 3 * j);
          }
          r.next<NB>();
        }
        Ring r4{0, 1};
#pragma unroll 1
        for (int n = 0; n < 16; n++) {
          if (n == 0 || n == 1 || n == 3) { mbar_wait(emptyB + 8 * r.idx, r.phase); r.next<NB>(); }
          mbar_wait(bars + 8 * (B_EMPTY4 + r4.idx), r4.phase);
          const uint32_t bar = bars + 8 * (B_FULL4 + r4.idx), slot = sb + OFF_B + r4.idx * UNIT4;
          const int u = n & 3, m = ((j >> 1) + 1 + (n >> 2)) & 3;
          mbar_expect_tx(bar, u == 3 ? 25600 : 20480);
          tma3d(slot, u == 3 ? &maps.wo : &maps.w4, bar, 0, u == 3 ? 80 * j : 192 * j + 64 * u, 5 * m);
          r4.next<NU4>();
        }
      }
    } else {
      const unsigned epoch = get_epoch();
      float* accg = g_acc[epoch & 1];
      if (pw == 2) {
        {
          const int ch = lane % 10, rg = lane / 10;
          const __nv_bfloat16* p = w1 + (size_t)(40 * i + rg) * D_ + 80 * j + 8 * ch;
          float a[8];
#pragma unroll
          for (int e = 0; e < 8; e++) a[e] = 0.f;
#pragma unroll 5
          for (int it = 0; it < 15; it++) {
            uint4 v = make_uint4(0, 0, 0, 0);
            if (lane < 30 && 3 * it + rg < 40) v = __ldg(reinterpret_cast<const uint4*>(p + (size_t)it * 3 * D_));
            a[0] += bf_lo(v.x); a[1] += bf_hi(v.x); a[2] += bf_lo(v.y); a[3] += bf_hi(v.y);
            a[4] += bf_lo(v.z); a[5] += bf_hi(v.z); a[6] += bf_lo(v.w); a[7] += bf_hi(v.w);
          }
#pragma unroll
          for (int e = 0; e < 8; e++) a[e] += __shfl_down_sync(0xffffffffu, a[e], 10) + __shfl_down_sync(0xffffffffu, a[e], 20);
          if (lane < 10) {
            float* cd = accg + 8 * KV_J + 80 * j + 8 * ch;
            red_add4(cd, a[0], a[1], a[2], a[3]); red_add4(cd + 4, a[4], a[5], a[6], a[7]);
          }
          __syncwarp();
          if (tid == 320) flag_add(FL_CS + j);
        }
        {
          float* nxt = g_acc[(epoch + 1) & 1];
          constexpr int PER = ACC_FLOATS / NCTA;
#pragma unroll 1
          for (int e = lane; e < PER; e += 32) nxt[blockIdx.x * PER + e] = 0.f;
        }
        if (tid == 320) {
          flag_wait(FL_CS + j, (epoch + 1) * 16u);
          flag_wait(FL_ST + i, (epoch + 1) * 8u);
          fence_async_all();
          mbar_expect_tx(bars + 8 * B_CS, 320 + 2048);
          bulk_load(sb + OFF_CS, accg + 8 * KV_J + 80 * j, 320, bars + 8 * B_CS);
          bulk_load(sb + OFF_XST, g_xstat + 128 * i, 2048, bars + 8 * B_CS);
          TSTAMPX(21);
          l2_prefetch(w2 + (size_t)blockIdx.x * (D_ * D_ / NCTA), D_ * D_ * 2 / NCTA);
          flag_wait(FL_H + i, (epoch + 1) * 8u);
          l2_prefetch(w3 + (size_t)blockIdx.x * (F_ * D_ / NCTA), F_ * D_ * 2 / NCTA);
          l2_prefetch(w4 + (size_t)blockIdx.x * (F_ * D_ / NCTA), F_ * D_ * 2 / NCTA);
          l2_prefetch(wo + (size_t)blockIdx.x * (D_ * D_ / NCTA), D_ * D_ * 2 / NCTA);
          flag_wait(FL_KV + j, (epoch + 1) * 16u);
          mbar_expect_tx(bars + 8 * B_KV, KV_J * 4);
          bulk_load(sb + OFF_MISC, accg + j * KV_J, KV_J * 4, bars + 8 * B_KV);
          TSTAMPX(22);
        }
        __syncwarp();
#pragma unroll 1
        for (int m = 0; m < 6; m++) {
          const int col = 192 * j + 32 * m + 8 * (lane & 3);
          const __nv_bfloat16* p = w3 + (size_t)(40 * i + (lane >> 2) * 5) * F_ + col;
          float a[8];
#pragma unroll
          for (int e = 0; e < 8; e++) a[e] = 0.f;
#pragma unroll
          for (int it = 0; it < 5; it++) {
            const uint4 v = __ldg(reinterpret_cast<const uint4*>(p + (size_t)it * F_));
            a[0] += bf_lo(v.x); a[1] += bf_hi(v.x); a[2] += bf_lo(v.y); a[3] += bf_hi(v.y);
            a[4] += bf_lo(v.z); a[5] += bf_hi(v.z); a[6] += bf_lo(v.w); a[7] += bf_hi(v.w);
          }
#pragma unroll
          for (int e = 0; e < 4; e++) {
            const float snd = (lane & 4) ? a[e] : a[e + 4], keep = (lane & 4) ? a[e + 4] : a[e];
            a[e] = keep + __shfl_xor_sync(0xffffffffu, snd, 4);
            a[e] += __shfl_xor_sync(0xffffffffu, a[e], 8);
            a[e] += __shfl_xor_sync(0xffffffffu, a[e], 16);
          }
          if (lane < 8) red_add4(accg + 8 * KV_J + D_ + col + (lane >> 2) * 4, a[0], a[1], a[2], a[3]);
        }
        __syncwarp();
        if (tid == 320) {
          flag_add(FL_CS3 + j);
          mbar_wait(bars + 8 * B_MFREE, 0);
          flag_wait(FL_X1 + i, (epoch + 1) * 8u);
          flag_wait(FL_CS3 + j, (epoch + 1) * 16u);
          fence_async_all();
          mbar_expect_tx(bars + 8 * B_ST1, 8192 + 768);
          bulk_load(sb + OFF_CS + 320, accg + 8 * KV_J + D_ + 192 * j, 768, bars + 8 * B_ST1);
          bulk_load(sb + OFF_MISC, g_st1 + 128 * i * 8, 8192, bars + 8 * B_ST1);
        }
        __syncwarp();
        mbar_wait(bars + 8 * B_PEER, 0);
        const unsigned* fp = g_flags + (FL_PART + i * 8 + j) * 32 + lane;
        bool seen = lane >= 6;
        uint32_t n = 0;
        while (!__all_sync(0xffffffffu, seen) && ++n < (WAIT_LIMIT >> 4)) {
          if (!seen && ld_acquire(fp) == epoch + 1 && (lane < 2 || (lane < 4 ? mbar_test(bars + 8 * (B_SEND + 2), 0) && mbar_test(bars + 8 * (B_SEND + 3), 0) && mbar_test(bars + 8 * (B_EMPTY4 + 1), 0) : mbar_test(bars + 8 * (B_SDONE + lane), 0)))) {
            seen = true;
            if (lane & 1) TR4((lane >> 1) * 16 + 11);
            mbar_expect_tx(bars + 8 * (B_RDY + lane), 10240);
            bulk_load(sb + (lane < 2 ? OFF_G0 : lane < 4 ? OFF_G1 : OFF_SEND) + (lane & 1) * 10240, g_part + (size_t)(i * 8 + j) * 3840 + lane * 640, 10240,
                      bars + 8 * (B_RDY + lane));
          }
        }
      } else {
        if (tid == 352) l2_prefetch(wphi + (size_t)j * 1600, 3200);
#pragma unroll 1
        for (int e = lane; e < 800; e += 32) sts128(sb + OFF_MISC + e * 16, make_uint4(0, 0, 0, 0));
        if (tid == 352) { mbar_wait(bars + 8 * B_SIGP, 0); flag_add(FL_ST + i); }
        __syncwarp();
#pragma unroll 1
        for (int q = lane; q < 200; q += 32) {
          const uint4 pre = __ldg(reinterpret_cast<const uint4*>(wphi + (size_t)j * 1600) + q);
          const uint32_t ww[4] = {pre.x, pre.y, pre.z, pre.w};
          const int h = q / 50;
#pragma unroll
          for (int e = 0; e < 8; e++) {
            const int idx = q * 8 + e, k = idx / 20, ff = idx - 20 * k;
            const int n = 40 * (h >> 1) + 8 * (ff >> 2) + 2 * (ff & 3) + (h & 1);
            const int off = (k >> 4) * 2560 + n * 32 + ((((k >> 3) ^ (n >> 2)) & 1) << 4) + (k & 7) * 2;
            *reinterpret_cast<unsigned short*>(sgen + OFF_MISC + off) = (unsigned short)(ww[e >> 1] >> ((e & 1) * 16));
          }
        }
        fence_async_smem();
        __syncwarp();
      }
      if (tid == 352) {
        mbar_arrive(bars + 8 * B_CS);
        TSTAMPX(20);
        mbar_expect_tx(bars + 8 * B_XR, 20480);
#pragma unroll 1
        for (int u = 0; u < 8; u++)
          tma2d(sb + OFF_B + (u / 3) * SLOT_B + SPARE + (u % 3) * 2560, &maps.xr, bars + 8 * B_XR, 80 * j, 128 * i + 16 * u);
        const int shift = (j < 2) ? 1 : (j < 4) ? -1 : (j < 6) ? 2 : -2;
        if ((shift > 0 && i == 0) || (shift < 0 && i == 15)) {
          const int nz = shift > 0 ? shift : -shift, zr = shift > 0 ? 0 : S_ - nz;
#pragma unroll 1
          for (int e = 0; e < nz * 10; e++)
            reinterpret_cast<uint4*>(g_Hs + (size_t)(2 + zr + e / 10) * D_ + 80 * j)[e % 10] = make_uint4(0, 0, 0, 0);
          fence_async_all();
        }
        prefetch_tmap(&maps.st_h); prefetch_tmap(&maps.st_x1); prefetch_tmap(&maps.hs); prefetch_tmap(&maps.x1); prefetch_tmap(&maps.xr);
        prefetch_tmap(&maps.w2); prefetch_tmap(&maps.w3); prefetch_tmap(&maps.w4); prefetch_tmap(&maps.wo); prefetch_tmap(&maps.st_out);
        mbar_wait(bars + 8 * B_SIGH, 0);
        TSTAMPX(23);
        tma2d_store(&maps.st_h, sb + OFF_STG, 80 * j, 128 * i + 2 + shift);
        tma2d_store(&maps.st_h, sb + OFF_STG + 10240, 80 * j, 128 * i + 66 + shift);
        bulk_commit(); bulk_wait<0>();
        flag_add(FL_H + i);
        TSTAMPX(24);
        mbar_wait(bars + 8 * B_SIGKV, 0);
        TSTAMPX(25);
        asm volatile("cp.reduce.async.bulk.global.shared::cta.bulk_group.add.f32 [%0], [%1], %2;"
                     ::"l"(accg + j * KV_J), "r"(sb + OFF_MISC), "r"(KV_J * 4) : "memory");
        bulk_commit(); bulk_wait<0>();
        flag_add(FL_KV + j);
        TSTAMPX(26);
        mbar_wait(bars + 8 * B_SIGX1, 0);
        TSTAMPX(27);
        tma2d_store(&maps.st_x1, sb + OFF_STG, 80 * j, 128 * i);
        tma2d_store(&maps.st_x1, sb + OFF_STG + 10240, 80 * j, 128 * i + 64);
        bulk_commit(); bulk_wait<0>();
        flag_add(FL_X1 + i);
        TSTAMPX(28);
        send_stream(0, epoch + 1);
      }
    }
  } else {
    uint4 pv[5], pw_[5];
    {
      const int row = 128 * i + 16 * j + (tid >> 4), l16 = tid & 15;
#pragma unroll
      for (int c = 0; c < 5; c++) pv[c] = __ldg(reinterpret_cast<const uint4*>(x + (size_t)row * D_ + c * 128 + l16 * 8));
#pragma unroll
      for (int c = 0; c < 5; c++) pw_[c] = __ldg(reinterpret_cast<const uint4*>(gate_w + c * 128 + l16 * 8));
    }
    asm volatile("barrier.cluster.arrive.relaxed.aligned;" ::: "memory");
    asm volatile("setmaxnreg.inc.sync.aligned.u32 232;");
    const int wg = tid >> 7, warp = tid >> 5, lane = tid & 31, t = lane & 3;
    const int rloc = warp * 16 + (lane >> 2);
    const float* s_cs = reinterpret_cast<const float*>(sgen + OFF_CS);
    auto signal = [&](int b) {
      __syncwarp();
      if (lane == 0) mbar_arrive(bars + 8 * b);
    };
    auto releaseB = [&](uint32_t bar) {
      __syncwarp();
      if (lane == 0) mbar_arrive(bar);
    };
    auto release = [&](uint32_t bar) {
      __syncwarp();
      if (lane < 2) mbar_arrive_cta(bar, lane);
    };
    const uint32_t stg_lane = (warp * 16 + ((lane >> 3) & 1) * 8 + (lane & 7)) * 160 + (lane >> 4) * 16;

    {
      float f[40];
      float s = 0.f, gs = 0.f;
#pragma unroll
      for (int c = 0; c < 5; c++) {
        const uint32_t vv[4] = {pv[c].x, pv[c].y, pv[c].z, pv[c].w}, ww[4] = {pw_[c].x, pw_[c].y, pw_[c].z, pw_[c].w};
#pragma unroll
        for (int e = 0; e < 4; e++) {
          f[8 * c + 2 * e] = bf_lo(vv[e]); f[8 * c + 2 * e + 1] = bf_hi(vv[e]);
          s += f[8 * c + 2 * e] + f[8 * c + 2 * e + 1];
          gs = fmaf(f[8 * c + 2 * e], bf_lo(ww[e]), gs); gs = fmaf(f[8 * c + 2 * e + 1], bf_hi(ww[e]), gs);
        }
      }
#pragma unroll
      for (int o = 1; o < 16; o <<= 1) { s += __shfl_xor_sync(0xffffffffu, s, o); gs += __shfl_xor_sync(0xffffffffu, gs, o); }
      const float mean = s * (1.f / D_);
      float q = 0.f;
#pragma unroll
      for (int e = 0; e < 40; e++) { const float d = f[e] - mean; q = fmaf(d, d, q); }
#pragma unroll
      for (int o = 1; o < 16; o <<= 1) q += __shfl_xor_sync(0xffffffffu, q, o);
      const float rstd = rsqrtf(q * (1.f / D_) + 1e-5f);
      asm volatile("barrier.cluster.wait.aligned;" ::: "memory");
      if ((tid & 15) == 0) g_xstat[128 * i + 16 * j + (tid >> 4)] = make_float4(rstd, -mean * rstd, rcp(1.f + __expf(-gs)), 0.f);
      signal(B_SIGP);
    }
    TSTAMP(1);

    Ring ra{0, 0}, rb{0, 0};
    uint32_t qp[2][10], P[2][10];
    float st_g[2];
    {
      float accM[128], accR[32];
      zero_regs(accM); zero_regs(accR);
      uint32_t pa = 0, pb = 0;
#pragma unroll 1
      for (int k = 0; k < 10; k++) {
        mbar_wait(fullA + 8 * ra.idx, ra.phase);
        if (tid == 0) TRACE(32 + k);
        mbar_wait(fullB + 8 * rb.idx, rb.phase);
        if (tid == 0) TRACE(64 + k);
        if (k == 0) TSTAMP(2);
        const uint32_t a0 = sb16 + ((OFF_A + ra.idx * SLOT_A + wg * 8192) >> 4), b0 = sb16 + ((OFF_B + rb.idx * SLOT_B) >> 4);
        wg_fence();
#pragma unroll
        for (int kk = 0; kk < 4; kk++) {
          const uint64_t da = make_desc(a0, kk * 32, 16, 1024, 1);
          mma_ss256(accM, da, make_desc(b0, kk * 2048, 8192, 1024, 1));
          mma_ss64(accR, da, make_desc(b0, 32768 + kk * 512, 2048, 256, 3));
          if (kk == 0) {
            wg_commit();
            if (k > 0) {
              wg_wait<1>();
              if (k - 1 < 8) release(emptyA + 8 * pa);
              releaseB(emptyB + 8 * pb);
            }
          }
        }
        wg_commit();
        pa = ra.idx; pb = rb.idx;
        ra.next<NA>(); rb.next<NB>();
      }
      TSTAMP(18);
      float st_rstd[2], st_mr[2];
      mbar_wait(bars + 8 * B_CS, 0);
#pragma unroll
      for (int r = 0; r < 2; r++) {
        const uint4 st = lds128(sb + OFF_XST + (rloc + 8 * r) * 16);
        st_rstd[r] = __uint_as_float(st.x); st_mr[r] = __uint_as_float(st.y); st_g[r] = __uint_as_float(st.z);
      }
      TSTAMP(19);
      wg_wait<0>();
      fence_regs(accM); fence_regs(accR);
      TSTAMP(3);
#define ACC(P_, G, I_) ((G) < 8 ? accM[(P_) * 32 + ((G) & 7) * 4 + (I_)] : accR[(P_) * 8 + ((G) & 1) * 4 + (I_)])
      {
        uint32_t hv[10][2];
#pragma unroll
        for (int g = 0; g < 10; g++) {
          const float2 cs = *reinterpret_cast<const float2*>(s_cs + 8 * g + 2 * t);
          const float v0 = gelu_s(fmaf(ACC(0, g, 0), st_rstd[0], st_mr[0] * cs.x), 0.5f), v1 = gelu_s(fmaf(ACC(0, g, 1), st_rstd[0], st_mr[0] * cs.y), 0.5f);
          const float v2 = gelu_s(fmaf(ACC(0, g, 2), st_rstd[1], st_mr[1] * cs.x), 0.5f), v3 = gelu_s(fmaf(ACC(0, g, 3), st_rstd[1], st_mr[1] * cs.y), 0.5f);
          hv[g][0] = pack_bf16(v0, v1); hv[g][1] = pack_bf16(v2, v3);
        }
        bar_sync(1, 256);
#pragma unroll
        for (int s = 0; s < 5; s++) stsm4(sb + OFF_STG + stg_lane + s * 32, hv[2 * s][0], hv[2 * s][1], hv[2 * s + 1][0], hv[2 * s + 1][1]);
        fence_async_smem();
        signal(B_SIGH);
      }
      TSTAMP(4);
      uint32_t kf[5][4], qf[5][4];
#pragma unroll
      for (int s = 0; s < 5; s++) {
        kf[s][0] = pack_bf16(ACC(2, 2 * s, 0), ACC(2, 2 * s, 1)); kf[s][1] = pack_bf16(ACC(2, 2 * s, 2), ACC(2, 2 * s, 3));
        kf[s][2] = pack_bf16(ACC(2, 2 * s + 1, 0), ACC(2, 2 * s + 1, 1)); kf[s][3] = pack_bf16(ACC(2, 2 * s + 1, 2), ACC(2, 2 * s + 1, 3));
        qf[s][0] = pack_bf16(ACC(1, 2 * s, 0), ACC(1, 2 * s, 1)); qf[s][1] = pack_bf16(ACC(1, 2 * s, 2), ACC(1, 2 * s, 3));
        qf[s][2] = pack_bf16(ACC(1, 2 * s + 1, 0), ACC(1, 2 * s + 1, 1)); qf[s][3] = pack_bf16(ACC(1, 2 * s + 1, 2), ACC(1, 2 * s + 1, 3));
      }
      float pk[40], pq[40];
      wg_fence();
#pragma unroll
      for (int s = 0; s < 5; s++) {
        if (s == 0) mma_rs80_k_z(pk, kf[s], make_desc(sb16, OFF_MISC, 16, 256, 3));
        else mma_rs80_k(pk, kf[s], make_desc(sb16, OFF_MISC + s * 2560, 16, 256, 3));
      }
#pragma unroll
      for (int s = 0; s < 5; s++) {
        if (s == 0) mma_rs80_k_z(pq, qf[s], make_desc(sb16, OFF_MISC, 16, 256, 3));
        else mma_rs80_k(pq, qf[s], make_desc(sb16, OFF_MISC + s * 2560, 16, 256, 3));
      }
      wg_commit();
      {
        const int mat = lane >> 3;
        const int tok = warp * 16 + (mat & 1) * 8 + (lane & 7);
        const uint32_t ones = (t == 0) ? 0x00003f80u : 0u;
        __syncwarp();
#pragma unroll
        for (int p = 0; p < 2; p++) {
          const uint32_t rowa = sb + OFF_A + p * SLOT_A + tok * 128;
#pragma unroll
          for (int gg = 0; gg < 3; gg++) {
            const int g0 = 5 * p + 2 * gg;
            uint32_t r0 = pack_bf16(ACC(3, g0, 0), ACC(3, g0, 1)), r1 = pack_bf16(ACC(3, g0, 2), ACC(3, g0, 3));
            uint32_t r2 = ones, r3 = ones;
            if (gg < 2) { r2 = pack_bf16(ACC(3, g0 + 1, 0), ACC(3, g0 + 1, 1)); r3 = pack_bf16(ACC(3, g0 + 1, 2), ACC(3, g0 + 1, 3)); }
            stsm4(rowa + (((2 * gg + (mat >> 1)) ^ (tok & 7)) << 4), r0, r1, r2, r3);
          }
        }
      }
#undef ACC
      wg_wait<0>();
      fence_regs(pk); fence_regs(pq);
#pragma unroll
      for (int G = 0; G < 10; G++) {
        P[0][G] = pack_bf16(pk[4 * G], pk[4 * G + 1]); P[1][G] = pack_bf16(pk[4 * G + 2], pk[4 * G + 3]);
        qp[0][G] = pack_bf16(pq[4 * G], pq[4 * G + 1]); qp[1][G] = pack_bf16(pq[4 * G + 2], pq[4 * G + 3]);
      }
    }

    uint32_t fr[10][4];
    uint32_t xv[2][10];
#pragma unroll
    for (int g = 0; g < 10; g++) xv[0][g] = xv[1][g] = 0u;
    int pass;
    pass = gridDim.y;
#pragma unroll 1
    do {
    feature_map(P, fr);
    if (pass != 0) {
    {
      const int mat = lane >> 3;
      const int tok = warp * 16 + (mat & 1) * 8 + (lane & 7);
      const uint32_t base = sb + OFF_B + tok * 32 + (((mat >> 1) ^ ((tok >> 2) & 1)) << 4);
#pragma unroll
      for (int G = 0; G < 10; G++) stsm4(base + G * 4096, fr[G][0], fr[G][1], fr[G][2], fr[G][3]);
      fence_async_smem();
      bar_sync(1, 256);
      float kv[40];
      const uint32_t a0 = sb16 + ((OFF_A + wg * SLOT_A) >> 4), b0 = sb16 + ((OFF_B + wg * 20480) >> 4);
      wg_fence();
#pragma unroll
      for (int ks = 0; ks < 8; ks++) {
        if (ks == 0) mma_ss80_tt_z(kv, make_desc(a0, 0, 16, 1024, 1), make_desc(b0, 0, 4096, 256, 3));
        else mma_ss80_tt(kv, make_desc(a0, ks * 2048, 16, 1024, 1), make_desc(b0, ks * 512, 4096, 256, 3));
      }
      wg_commit();
      wg_wait<0>();
      fence_regs(kv);
      TSTAMP(31);
      release(emptyA); release(emptyA + 8); releaseB(emptyB);
      const uint32_t dst = sb + OFF_MISC + wg * (KV_PAIR * 4);
      const int m0 = (warp & 3) * 16 + (lane >> 2);
#pragma unroll
      for (int r = 0; r < 2; r++) {
        const int m = m0 + 8 * r;
        const bool hi = m >= 20;
        uint32_t v[10];
#pragma unroll
        for (int G = 0; G < 10; G++) v[G] = __float_as_uint(hi ? kv[4 * G + 2 * r + 1] : kv[4 * G + 2 * r]);
        const uint32_t p = dst + 4 * (m < 40 ? m * 48 + t * 12 : 1920 + t * 24 + 12);
        if (m <= 40) {
          sts128(p, make_uint4(v[0], v[1], v[2], v[3])); sts128(p + 16, make_uint4(v[4], v[5], v[6], v[7]));
          sts128(p + 32, make_uint4(v[8], v[9], 0u, 0u));
        }
      }
      if (m0 == 32) {
        const uint32_t p = dst + 4 * (1920 + t * 24);
        sts128(p, make_uint4(__float_as_uint(kv[2]), __float_as_uint(kv[6]), __float_as_uint(kv[10]), __float_as_uint(kv[14])));
        sts128(p + 16, make_uint4(__float_as_uint(kv[18]), __float_as_uint(kv[22]), __float_as_uint(kv[26]), __float_as_uint(kv[30])));
        sts128(p + 32, make_uint4(__float_as_uint(kv[34]), __float_as_uint(kv[38]), 0u, 0u));
      }
      fence_async_smem();
      signal(B_SIGKV);
    }
    TSTAMP(5);

    {
      {
        mbar_wait(bars + 8 * B_XR, 0);
        const uint32_t xa = sb + OFF_B + (warp / 3) * SLOT_B + SPARE + (warp % 3) * 2560 + (lane >> 2) * 160 + t * 4;
#pragma unroll
        for (int g = 0; g < 10; g++) { xv[0][g] = lds32(xa + g * 16); xv[1][g] = lds32(xa + 1280 + g * 16); }
      }
      float acc[40];
      zero_regs(acc);
      uint32_t pa = 0, pb = 0;
#pragma unroll 1
      for (int k = 0; k < 10; k++) {
        mbar_wait(fullA + 8 * ra.idx, ra.phase);
        if (tid == 0) TRACE(42 + k);
        if ((k & 3) == 0) mbar_wait(fullB + 8 * rb.idx, rb.phase);
        if (tid == 0) TRACE(74 + k);
        if (k == 0) TSTAMP(6);
        const uint32_t a0 = sb16 + ((OFF_A + ra.idx * SLOT_A + wg * 8192) >> 4);
        const uint32_t b0 = sb16 + ((OFF_B + rb.idx * SLOT_B + (k & 3) * 10240) >> 4);
        wg_fence();
#pragma unroll
        for (int kk = 0; kk < 4; kk++) {
          mma_ss80(acc, make_desc(a0, kk * 32, 16, 1024, 1), make_desc(b0, kk * 512, 2048, 256, 3));
          if (kk == 1) {
            wg_commit();
            if (k > 0) {
              wg_wait<1>();
              release(emptyA + 8 * pa);
              if ((k & 3) == 0) releaseB(emptyB + 8 * pb);
            }
          }
        }
        wg_commit();
        pa = ra.idx; pb = rb.idx;
        ra.next<NA>();
        if ((k & 3) == 3 || k == 9) rb.next<NB>();
      }
      wg_wait<0>();
      fence_regs(acc);
      release(emptyA + 8 * pa); releaseB(emptyB + 8 * pb);
      TSTAMP(7);
#pragma unroll
      for (int r = 0; r < 2; r++) {
#pragma unroll
        for (int g = 0; g < 10; g++)
          xv[r][g] = pack_bf16(bf_lo(xv[r][g]) + acc[4 * g + 2 * r], bf_hi(xv[r][g]) + acc[4 * g + 2 * r + 1]);
      }
      bar_sync(1, 256);
#pragma unroll
      for (int s = 0; s < 5; s++) stsm4(sb + OFF_STG + stg_lane + s * 32, xv[0][2 * s], xv[1][2 * s], xv[0][2 * s + 1], xv[1][2 * s + 1]);
#pragma unroll
      for (int r = 0; r < 2; r++) {
        float s = 0.f;
#pragma unroll
        for (int g = 0; g < 10; g++) {
          acc[4 * g + 2 * r] = bf_lo(xv[r][g]); acc[4 * g + 2 * r + 1] = bf_hi(xv[r][g]);
          s += acc[4 * g + 2 * r] + acc[4 * g + 2 * r + 1];
        }
        s += __shfl_xor_sync(0xffffffffu, s, 1); s += __shfl_xor_sync(0xffffffffu, s, 2);
        const float mu = s * (1.f / 80.f);
        float q = 0.f;
#pragma unroll
        for (int g = 0; g < 10; g++) {
          const float d0 = acc[4 * g + 2 * r] - mu, d1 = acc[4 * g + 2 * r + 1] - mu;
          q = fmaf(d0, d0, q); q = fmaf(d1, d1, q);
        }
        q += __shfl_xor_sync(0xffffffffu, q, 1); q += __shfl_xor_sync(0xffffffffu, q, 2);
        if (t == 0) g_st1[(128 * i + rloc + 8 * r) * 8 + j] = make_float2(mu, q);
      }
      fence_async_smem();
      signal(B_SIGX1);
    }
    TSTAMP(8);
#pragma unroll
    for (int G = 0; G < 10; G++) { P[0][G] = qp[0][G]; P[1][G] = qp[1][G]; }
    }
    asm volatile("" : "+r"(pass));
    } while (pass-- != 0);

    uint32_t of[5][4];
    {
      mbar_wait(bars + 8 * B_KV, 0);
      uint4 kvr[2][3];
#pragma unroll
      for (int u = 0; u < 2; u++) {
        const int it = tid + 256 * u, p = it / 192, rem = it - 192 * p, n = rem >> 2, tq = rem & 3;
        const uint32_t sp = sb + OFF_MISC + 4 * (p * KV_PAIR + (n < 40 ? n * 48 + tq * 12 : 1920 + tq * 24 + (n & 1) * 12));
        if (it < 384) { kvr[u][0] = lds128(sp); kvr[u][1] = lds128(sp + 16); kvr[u][2] = lds128(sp + 32); }
      }
      bar_sync(1, 256);
#pragma unroll
      for (int u = 0; u < 2; u++) {
        const int it = tid + 256 * u, p = it / 192, rem = it - 192 * p, n = rem >> 2, tq = rem & 3;
        const int sh = (n < 40 ? (n >= 20) : (n & 1)) * 16;
        const uint32_t v[10] = {kvr[u][0].x, kvr[u][0].y, kvr[u][0].z, kvr[u][0].w, kvr[u][1].x, kvr[u][1].y, kvr[u][1].z, kvr[u][1].w, kvr[u][2].x, kvr[u][2].y};
        uint8_t* dst = sgen + OFF_MISC + p * 7680 + n * 32 + tq * 4;
        const int sw = ((n >> 2) & 1) << 4;
        if (it < 384) {
#pragma unroll
          for (int G = 0; G < 10; G++)
            *reinterpret_cast<uint32_t*>(dst + (G >> 1) * 1536 + (((G & 1) << 4) ^ sw)) = pack_bf16(__uint_as_float(v[G]), 0.f) << sh;
        }
      }
      fence_async_smem();
      bar_sync(1, 256);
      float o0[24], o1[24];
      wg_fence();
#pragma unroll
      for (int g = 0; g < 5; g++) {
        if (g == 0) mma_rs48_k_z(o0, fr[g], make_desc(sb16, OFF_MISC, 16, 256, 3));
        else mma_rs48_k(o0, fr[g], make_desc(sb16, OFF_MISC + g * 1536, 16, 256, 3));
      }
#pragma unroll
      for (int g = 0; g < 5; g++) {
        if (g == 0) mma_rs48_k_z(o1, fr[5], make_desc(sb16, OFF_MISC + 7680, 16, 256, 3));
        else mma_rs48_k(o1, fr[5 + g], make_desc(sb16, OFF_MISC + 7680 + g * 1536, 16, 256, 3));
      }
      wg_commit();
      wg_wait<0>();
      fence_regs(o0); fence_regs(o1);
      signal(B_MFREE);
#pragma unroll
      for (int r = 0; r < 2; r++) {
        const float a0 = __fdividef(st_g[r], o0[20 + 2 * r] + 1e-6f), a1 = __fdividef(st_g[r], o0[21 + 2 * r] + 1e-6f);
        const float b0 = __fdividef(st_g[r], o1[20 + 2 * r] + 1e-6f), b1 = __fdividef(st_g[r], o1[21 + 2 * r] + 1e-6f);
        const float am = t < 2 ? a0 : a1, bm = t < 2 ? b0 : b1;
#pragma unroll
        for (int g = 0; g < 5; g++) {
          const float sa = g < 2 ? a0 : (g == 2 ? am : a1), sb2 = g < 2 ? b0 : (g == 2 ? bm : b1);
          of[g >> 1][(g & 1) * 2 + r] = pack_bf16(o0[4 * g + 2 * r] * sa, o0[4 * g + 2 * r + 1] * sa);
          of[(5 + g) >> 1][((5 + g) & 1) * 2 + r] = pack_bf16(o1[4 * g + 2 * r] * sb2, o1[4 * g + 2 * r + 1] * sb2);
        }
      }
    }
    TSTAMP(9);

    uint32_t hf[12][4];
    {
      float acc[96];
      zero_regs(acc);
      uint32_t pa = 0, pb = 0;
#pragma unroll 1
      for (int k = 0; k < 10; k++) {
        mbar_wait(fullA + 8 * ra.idx, ra.phase);
        if (tid == 0) TRACE(52 + k);
        if ((k & 1) == 0) mbar_wait(fullB + 8 * rb.idx, rb.phase);
        if (tid == 0) TRACE(84 + k);
        if (k == 0) TSTAMP(10);
        const uint32_t a0 = sb16 + ((OFF_A + ra.idx * SLOT_A + wg * 8192) >> 4);
        const uint32_t b0 = sb16 + ((OFF_B + rb.idx * SLOT_B + (k & 1) * 24576) >> 4);
        wg_fence();
#pragma unroll
        for (int kk = 0; kk < 4; kk++) {
          mma_ss192(acc, make_desc(a0, kk * 32, 16, 1024, 1), make_desc(b0, kk * 2048, 8192, 1024, 1));
          if (kk == 0) {
            wg_commit();
            if (k > 0) {
              wg_wait<1>();
              release(emptyA + 8 * pa);
              if ((k & 1) == 0) releaseB(emptyB + 8 * pb);
            }
          }
        }
        wg_commit();
        pa = ra.idx; pb = rb.idx;
        ra.next<NA>();
        if (k & 1) rb.next<NB>();
      }
      float rs[2], mm[2];
      mbar_wait(bars + 8 * B_ST1, 0);
#pragma unroll
      for (int r = 0; r < 2; r++) {
        const uint4 su = lds128(sb + OFF_MISC + (rloc + 8 * r) * 64 + t * 16);
        const float m0 = __uint_as_float(su.x), m1 = __uint_as_float(su.z);
        float mu = m0 + m1;
        mu += __shfl_xor_sync(0xffffffffu, mu, 1); mu += __shfl_xor_sync(0xffffffffu, mu, 2);
        mu *= 0.125f;
        const float d0 = m0 - mu, d1 = m1 - mu;
        float q = __uint_as_float(su.y) + __uint_as_float(su.w) + 80.f * (d0 * d0 + d1 * d1);
        q += __shfl_xor_sync(0xffffffffu, q, 1); q += __shfl_xor_sync(0xffffffffu, q, 2);
        rs[r] = rsqrtf(q * (1.f / D_) + 1e-5f);
        mm[r] = -mu * rs[r];
      }
      wg_wait<0>();
      fence_regs(acc);
      releaseB(emptyB + 8 * pb);
      release(bars + 8 * B_PEER);
      TSTAMP(11);
      const float hs0 = 0.5f - 0.5f * st_g[0], hs1 = 0.5f - 0.5f * st_g[1];
#pragma unroll
      for (int g = 0; g < 24; g++) {
        const float2 cs = *reinterpret_cast<const float2*>(s_cs + 80 + 8 * g + 2 * t);
        const float v0 = gelu_s(fmaf(acc[4 * g], rs[0], mm[0] * cs.x), hs0), v1 = gelu_s(fmaf(acc[4 * g + 1], rs[0], mm[0] * cs.y), hs0);
        const float v2 = gelu_s(fmaf(acc[4 * g + 2], rs[1], mm[1] * cs.x), hs1), v3 = gelu_s(fmaf(acc[4 * g + 3], rs[1], mm[1] * cs.y), hs1);
        hf[g >> 1][(g & 1) * 2] = pack_bf16(v0, v1);
        hf[g >> 1][(g & 1) * 2 + 1] = pack_bf16(v2, v3);
      }
    }
    TSTAMP(12);

    {
      float acc[80], kp[40];
      const int wt = tid & 127;
      const uint32_t peer = map_peer(sb, rank ^ 1);
      Ring r4{0, 0};
      auto add16 = [&](uint32_t src) {
#pragma unroll
        for (int q = 0; q < 5; q++) {
          const uint4 v = lds128(src + q * 2048);
          float* d = &kp[8 * q];
          d[0] += bf_lo(v.x); d[1] += bf_hi(v.x); d[2] += bf_lo(v.y); d[3] += bf_hi(v.y);
          d[4] += bf_lo(v.z); d[5] += bf_hi(v.z); d[6] += bf_lo(v.w); d[7] += bf_hi(v.w);
        }
      };
      auto finish = [&](int c) {
        if (c > 1) mbar_wait(bars + 8 * (B_SDONE + 2 * (c - 2) + wg), 0);
        mbar_wait(bars + 8 * (B_DSR + 2 * (c - 1) + wg), 0);
        if (tid == 128) TR4((c - 1) * 16 + 3);
        add16(sb + OFF_DS + ((c - 1) & 1) * 20480 + wg * 10240 + wt * 16);
        const uint32_t dst = sb + OFF_SEND + wg * 10240 + wt * 16;
#pragma unroll
        for (int q = 0; q < 5; q++) {
          const float* d = &kp[8 * q];
          sts128(dst + q * 2048, make_uint4(pack_bf16(d[0], d[1]), pack_bf16(d[2], d[3]), pack_bf16(d[4], d[5]), pack_bf16(d[6], d[7])));
        }
        fence_async_smem();
        signal(B_SEND + 2 * (c - 1) + wg);
        if (tid == 128) TR4((c - 1) * 16 + 6);
      };
      zero_regs(kp);
      if (wg == 1) bar_sync(2, 256);
#pragma unroll 1
      for (int c = 0; c < 4; c++) {
        uint32_t prev = 0;
#pragma unroll
        for (int u = 0; u < 4; u++) {
          mbar_wait(bars + 8 * (B_FULL4 + r4.idx), r4.phase);
          const uint32_t b0 = sb16 + ((OFF_B + r4.idx * UNIT4) >> 4);
          if (u == 0 && tid == 128) TR4(c * 16 + 0);
          wg_fence();
#pragma unroll
          for (int s = 0; s < (u < 3 ? 4 : 5); s++) {
            const uint64_t db = make_desc(b0, s * 1024, u < 3 ? 4096 : 5120, 512, 2);
            if (u == 0 && s == 0) mma_rs160_n_z(acc, hf[0], db);
            else if (u < 3) mma_rs160_n(acc, hf[(4 * u + s) % 12], db);
            else mma_rs160_n(acc, of[s], db);
            if (s == 1 && u > 0) { wg_commit(); wg_wait<1>(); releaseB(bars + 8 * (B_EMPTY4 + prev)); }
          }
          wg_commit();
          prev = r4.idx;
          r4.next<NU4>();
          if (u == 1 && c == 0 && wg == 0) bar_arrive(2, 256);
          if (u == 0 && c > 0) finish(c);
          if (u == 2) {
            if (c == 3) {
              const float w0 = 1.f - st_g[0], w1s = 1.f - st_g[1];
#pragma unroll
              for (int g = 0; g < 10; g++) {
                kp[4 * g] = w0 * bf_lo(xv[0][g]); kp[4 * g + 1] = w0 * bf_hi(xv[0][g]);
                kp[4 * g + 2] = w1s * bf_lo(xv[1][g]); kp[4 * g + 3] = w1s * bf_hi(xv[1][g]);
              }
#pragma unroll 1
              for (int e = 0; e < 2; e++) {
                mbar_wait(bars + 8 * (B_RDY + 2 * e + wg), 0);
                add16(sb + (e == 0 ? OFF_G0 : OFF_G1) + wg * 10240 + wt * 16);
              }
            } else {
              zero_regs(kp);
            }
          }
        }
        if (tid == 128) TR4(c * 16 + 2);
        if (c == 0) mbar_wait(bars + 8 * B_PEER, 0);
        wg_wait<0>();
        fence_regs(acc);
        releaseB(bars + 8 * (B_EMPTY4 + prev));
        if (tid == 128) TR4(c * 16 + 5);
        uint32_t sn[20];
        if (rank) {
#pragma unroll
          for (int e = 0; e < 20; e++) sn[e] = pack_bf16(acc[2 * e], acc[2 * e + 1]);
#pragma unroll
          for (int e = 0; e < 40; e++) kp[e] += acc[40 + e];
        } else {
#pragma unroll
          for (int e = 0; e < 20; e++) sn[e] = pack_bf16(acc[40 + 2 * e], acc[41 + 2 * e]);
#pragma unroll
          for (int e = 0; e < 40; e++) kp[e] += acc[e];
        }
        fence_regs(kp);
        const uint32_t dso = peer + OFF_DS + (c & 1) * 20480 + wg * 10240 + wt * 16, dsb = peer + OFF_BAR + 8 * (B_DSR + 2 * c + wg);
#pragma unroll
        for (int q = 0; q < 5; q++) st_async16(dso + q * 2048, sn[4 * q], sn[4 * q + 1], sn[4 * q + 2], sn[4 * q + 3], dsb);
      }
      TSTAMP(13);
#pragma unroll 1
      for (int c = 0; c < 2; c++) {
        mbar_wait(bars + 8 * ((c == 0 ? B_DSR + 6 : B_RDY + 4) + wg), 0);
        add16(sb + (c == 0 ? OFF_DS + 20480 : OFF_SEND) + wg * 10240 + wt * 16);
      }
      TSTAMP(14);
#pragma unroll
      for (int s = 0; s < 5; s++)
        stsm4(sb + OFF_DS + stg_lane + s * 32, pack_bf16(kp[8 * s], kp[8 * s + 1]), pack_bf16(kp[8 * s + 2], kp[8 * s + 3]),
              pack_bf16(kp[8 * s + 4], kp[8 * s + 5]), pack_bf16(kp[8 * s + 6], kp[8 * s + 7]));
      fence_async_smem();
      __syncwarp();
      if (lane == 0) {
        tma2d_store(&maps.st_out, sb + OFF_DS + warp * 2560, 80 * j, 128 * i + 16 * warp);
        bulk_commit(); bulk_wait_read();
      }
    }
    TSTAMP(15);
    if (tid == 0) asm volatile("red.relaxed.gpu.global.add.u32 [%0], 1;" ::"l"(g_flags + FL_DONE * 32) : "memory");
  }
}

namespace {
typedef CUresult (*EncodeFn)(CUtensorMap*, CUtensorMapDataType, cuuint32_t, void*, const cuuint64_t*, const cuuint64_t*,
                             const cuuint32_t*, const cuuint32_t*, CUtensorMapInterleave, CUtensorMapSwizzle,
                             CUtensorMapL2promotion, CUtensorMapFloatOOBfill);

void encode(EncodeFn fn, CUtensorMap* m, const void* ptr, int rank, const cuuint64_t* dims, const cuuint64_t* strides,
            const cuuint32_t* box, CUtensorMapSwizzle swz) {
  cuuint32_t es[5] = {1, 1, 1, 1, 1};
  fn(m, CU_TENSOR_MAP_DATA_TYPE_BFLOAT16, rank, const_cast<void*>(ptr), dims, strides, box, es, CU_TENSOR_MAP_INTERLEAVE_NONE,
     swz, CU_TENSOR_MAP_L2_PROMOTION_L2_128B, CU_TENSOR_MAP_FLOAT_OOB_FILL_NONE);
}
}

extern "C" void kernel_launch(void* const* d_in, const int* in_sizes, int n_in, void* d_out, int out_size) {
  (void)in_sizes; (void)n_in; (void)out_size;
  const __nv_bfloat16* x = (const __nv_bfloat16*)d_in[0];
  const __nv_bfloat16* wqkv = (const __nv_bfloat16*)d_in[1];
  const __nv_bfloat16* wphi = (const __nv_bfloat16*)d_in[2];
  const __nv_bfloat16* wo = (const __nv_bfloat16*)d_in[3];
  const __nv_bfloat16* w1 = (const __nv_bfloat16*)d_in[5];
  const __nv_bfloat16* w2 = (const __nv_bfloat16*)d_in[6];
  const __nv_bfloat16* w3 = (const __nv_bfloat16*)d_in[7];
  const __nv_bfloat16* w4 = (const __nv_bfloat16*)d_in[8];
  const __nv_bfloat16* gate_w = (const __nv_bfloat16*)d_in[9];

  static EncodeFn enc = nullptr;
  static void *pHs = nullptr, *pX1 = nullptr;
  if (!enc) {
    cudaDriverEntryPointQueryResult qr;
    cudaGetDriverEntryPoint("cuTensorMapEncodeTiled", (void**)&enc, cudaEnableDefault, &qr);
    cudaGetSymbolAddress(&pHs, g_Hs);
    cudaGetSymbolAddress(&pX1, g_X1);
    cudaFuncSetAttribute(fused_kernel, cudaFuncAttributeMaxDynamicSharedMemorySize, SMEM_BYTES);
  }
  Maps m;
  {
    cuuint64_t dims[2] = {D_, S_}, str[1] = {D_ * 2};
    cuuint32_t boxh[2] = {64, 64};
    encode(enc, &m.x, x, 2, dims, str, boxh, CU_TENSOR_MAP_SWIZZLE_128B);
    encode(enc, &m.hs, (const char*)pHs + 2 * D_ * 2, 2, dims, str, boxh, CU_TENSOR_MAP_SWIZZLE_128B);
    encode(enc, &m.x1, pX1, 2, dims, str, boxh, CU_TENSOR_MAP_SWIZZLE_128B);
    cuuint32_t boxs[2] = {80, 64};
    cuuint64_t dimsp[2] = {D_, S_ + 4};
    encode(enc, &m.st_h, pHs, 2, dimsp, str, boxs, CU_TENSOR_MAP_SWIZZLE_NONE);
    encode(enc, &m.st_x1, pX1, 2, dims, str, boxs, CU_TENSOR_MAP_SWIZZLE_NONE);
    cuuint32_t boxr[2] = {80, 16};
    encode(enc, &m.st_out, d_out, 2, dims, str, boxr, CU_TENSOR_MAP_SWIZZLE_NONE);
    encode(enc, &m.xr, x, 2, dims, str, boxr, CU_TENSOR_MAP_SWIZZLE_NONE);
  }
  {
    cuuint64_t dims[3] = {80, D_, 8}, str[2] = {D_ * 2, 160};
    cuuint32_t boxm[3] = {64, 64, 1}, boxr[3] = {16, 64, 1};
    encode(enc, &m.w1m, w1, 3, dims, str, boxm, CU_TENSOR_MAP_SWIZZLE_128B);
    encode(enc, &m.w1r, w1, 3, dims, str, boxr, CU_TENSOR_MAP_SWIZZLE_32B);
  }
  {
    cuuint64_t dims[4] = {80, D_, 3, 8}, str[3] = {3 * D_ * 2, D_ * 2, 160};
    cuuint32_t boxm[4] = {64, 64, 3, 1}, boxr[4] = {16, 64, 3, 1};
    encode(enc, &m.qm, wqkv, 4, dims, str, boxm, CU_TENSOR_MAP_SWIZZLE_128B);
    encode(enc, &m.qr, wqkv, 4, dims, str, boxr, CU_TENSOR_MAP_SWIZZLE_32B);
  }
  {
    cuuint64_t dims[3] = {16, D_, 40}, str[2] = {D_ * 2, 32};
    cuuint32_t box2[3] = {16, 64, 5};
    encode(enc, &m.w2, w2, 3, dims, str, box2, CU_TENSOR_MAP_SWIZZLE_32B);
  }
  {
    cuuint64_t dims[3] = {32, D_, 20}, dims4[3] = {32, F_, 20}, str[2] = {D_ * 2, 64};
    cuuint32_t box4[3] = {32, 64, 5}, boxo[3] = {32, 80, 5};
    encode(enc, &m.w4, w4, 3, dims4, str, box4, CU_TENSOR_MAP_SWIZZLE_64B);
    encode(enc, &m.wo, wo, 3, dims, str, boxo, CU_TENSOR_MAP_SWIZZLE_64B);
  }
  {
    cuuint64_t dims[3] = {64, D_, 24}, str[2] = {F_ * 2, 128};
    cuuint32_t box[3] = {64, 64, 3};
    encode(enc, &m.w3, w3, 3, dims, str, box, CU_TENSOR_MAP_SWIZZLE_128B);
  }
  fused_kernel<<<NCTA, 384, SMEM_BYTES, cudaStreamPerThread>>>(m, x, wqkv, wphi, w1, w2, w3, w4, wo, gate_w);
}
```

```cpp
#include <cuda_runtime.h>
#include <cuda_bf16.h>
#include <cuda.h>
#include <stdint.h>

namespace {

constexpr int S_ = 2048, D_ = 640, F_ = 1536;
constexpr int NCTA = 128;
constexpr int KV_PAIR = 40 * 48 + 96;
constexpr int KV_J = 2 * KV_PAIR;

constexpr int SLOT_B = 49152, NB = 3;
constexpr int SLOT_A = 16384, NA = 4;
constexpr int OFF_B = 0;
constexpr int OFF_A = OFF_B + NB * SLOT_B;
constexpr int OFF_STG = OFF_A + 2 * SLOT_A;
constexpr int OFF_MISC = OFF_A + NA * SLOT_A;
constexpr int OFF_XST = OFF_MISC + 13312;
constexpr int OFF_CS = OFF_MISC + 16384;
constexpr int OFF_BAR = OFF_CS + 1088;
constexpr int SMEM_BYTES = OFF_BAR + 512;
constexpr int B_FULLA = 0, B_FULLB = 4, B_CS = 7, B_XR = 8, B_KV = 9, B_ST1 = 10, B_SDONE = 11  , B_RDY = 17  ,
              B_FULL4 = 23  , B_DSR = 28  , B_SEND = 36  , B_EMPTYB = 42  ,
              B_SIGP = 45, B_SIGH = 46, B_SIGKV = 47, B_SIGX1 = 48, B_MFREE = 49, B_EMPTY4 = 50  ,
              B_EMPTYA = 55  , B_PEER = 59, NBAR = 60;
constexpr int SPARE = 40960;
constexpr int UNIT4 = 25600, NU4 = 5;
constexpr int OFF_DS = OFF_A, OFF_SEND = OFF_A + 40960, OFF_G0 = OFF_A + 61440, OFF_G1 = OFF_B + UNIT4;

constexpr int FL_DONE = 0, FL_H = 1, FL_X1 = FL_H + 16, FL_KV = FL_X1 + 16, FL_CS = FL_KV + 8, FL_CS3 = FL_CS + 8, FL_ST = FL_CS3 + 8, FL_PART = FL_ST + 16;
constexpr int FL_COUNT = FL_PART + 16 * 8;
constexpr int ACC_FLOATS = 8 * KV_J + D_ + F_;

struct Maps {
  CUtensorMap x, w1m, w1r, qm, qr, hs, w2, x1, w3, w4, wo, st_h, st_x1, st_out, xr;
};

}

__device__ __align__(1024) __nv_bfloat16 g_Hs[(S_ + 4) * D_];
__device__ __align__(1024) __nv_bfloat16 g_X1[S_ * D_];
__device__ __align__(128) float g_acc[2][ACC_FLOATS];
__device__ __align__(128) float4 g_xstat[S_];
__device__ __align__(128) float2 g_st1[S_ * 8];
__device__ __align__(128) uint4 g_part[16 * 8 * 3 * 1280];
__device__ __align__(128) unsigned g_flags[FL_COUNT * 32];
#define TSTAMP(n) do {} while (0)
#define TSTAMPX(n) do {} while (0)
#define TRACE(n) do {} while (0)
#define TR4(n) do {} while (0)

namespace {

__device__ __forceinline__ long long gtime() { long long t; asm volatile("mov.u64 %0, %%globaltimer;" : "=l"(t)); return t; }
__device__ __forceinline__ uint32_t smem_u32(const void* p) { return (uint32_t)__cvta_generic_to_shared(p); }
__device__ __forceinline__ void mbar_init(uint32_t bar, int cnt) {
  asm volatile("mbarrier.init.shared::cta.b64 [%0], %1;" ::"r"(bar), "r"(cnt) : "memory");
}
__device__ __forceinline__ void mbar_expect_tx(uint32_t bar, int bytes) {
  asm volatile("mbarrier.arrive.expect_tx.shared::cta.b64 _, [%0], %1;" ::"r"(bar), "r"(bytes) : "memory");
}
__device__ __forceinline__ void mbar_arrive_cta(uint32_t bar, uint32_t cta) {
  asm volatile("{\n.reg .b32 ra;\nmapa.shared::cluster.u32 ra, %0, %1;\nmbarrier.arrive.shared::cluster.b64 _, [ra];\n}"
               ::"r"(bar), "r"(cta) : "memory");
}
__device__ __forceinline__ uint32_t mbar_try(uint32_t bar, uint32_t parity) {
  uint32_t ok;
  asm volatile("{\n.reg .pred p;\nmbarrier.try_wait.parity.shared::cta.b64 p, [%1], %2;\nselp.u32 %0, 1, 0, p;\n}"
               : "=r"(ok) : "r"(bar), "r"(parity) : "memory");
  return ok;
}
constexpr uint32_t WAIT_LIMIT = 1u << 22;
__device__ __forceinline__ void mbar_wait(uint32_t bar, uint32_t parity) {
  uint32_t n = 0;
  while (!mbar_try(bar, parity) && ++n < WAIT_LIMIT) {}
}
__device__ __forceinline__ unsigned ld_acquire(const unsigned* p) {
  unsigned v;
  asm volatile("ld.acquire.gpu.global.u32 %0, [%1];" : "=r"(v) : "l"(p) : "memory");
  return v;
}
__device__ __forceinline__ void flag_wait(int idx, unsigned target) {
  const unsigned* p = g_flags + idx * 32;
  uint32_t n = 0;
  while ((int)(ld_acquire(p) - target) < 0 && ++n < (WAIT_LIMIT >> 4)) {}
}
__device__ __forceinline__ void flag_add(int idx) {
  asm volatile("red.release.gpu.global.add.u32 [%0], 1;" ::"l"(g_flags + idx * 32) : "memory");
}
__device__ __forceinline__ void flag_add_relaxed(int idx) {
  asm volatile("red.relaxed.gpu.global.add.u32 [%0], 1;" ::"l"(g_flags + idx * 32) : "memory");
}
__device__ __forceinline__ uint32_t mbar_test(uint32_t bar, uint32_t parity) {
  uint32_t ok;
  asm volatile("{\n.reg .pred p;\nmbarrier.test_wait.parity.shared::cta.b64 p, [%1], %2;\nselp.u32 %0, 1, 0, p;\n}"
               : "=r"(ok) : "r"(bar), "r"(parity) : "memory");
  return ok;
}
__device__ __forceinline__ uint32_t lds32(uint32_t a) {
  uint32_t v;
  asm volatile("ld.shared.u32 %0, [%1];" : "=r"(v) : "r"(a) : "memory");
  return v;
}
__device__ __forceinline__ void mbar_arrive(uint32_t bar) {
  asm volatile("mbarrier.arrive.shared::cta.b64 _, [%0];" ::"r"(bar) : "memory");
}
__device__ __forceinline__ void fence_async_all() { asm volatile("fence.proxy.async;" ::: "memory"); }
__device__ __forceinline__ void fence_async_smem() { asm volatile("fence.proxy.async.shared::cta;" ::: "memory"); }
__device__ __forceinline__ void bar_sync(int id, int n) { asm volatile("bar.sync %0, %1;" ::"r"(id), "r"(n) : "memory"); }

__device__ __forceinline__ void tma2d(uint32_t dst, const CUtensorMap* m, uint32_t bar, int c0, int c1) {
  asm volatile("cp.async.bulk.tensor.2d.shared::cluster.global.mbarrier::complete_tx::bytes [%0], [%1, {%3, %4}], [%2];"
               ::"r"(dst), "l"(m), "r"(bar), "r"(c0), "r"(c1) : "memory");
}
__device__ __forceinline__ void tma2d_mc(uint32_t dst, const CUtensorMap* m, uint32_t bar, int c0, int c1) {
  asm volatile("cp.async.bulk.tensor.2d.shared::cluster.global.mbarrier::complete_tx::bytes.multicast::cluster"
               " [%0], [%1, {%3, %4}], [%2], %5;"
               ::"r"(dst), "l"(m), "r"(bar), "r"(c0), "r"(c1), "h"((uint16_t)3) : "memory");
}
__device__ __forceinline__ void tma3d(uint32_t dst, const CUtensorMap* m, uint32_t bar, int c0, int c1, int c2) {
  asm volatile("cp.async.bulk.tensor.3d.shared::cluster.global.mbarrier::complete_tx::bytes [%0], [%1, {%3, %4, %5}], [%2];"
               ::"r"(dst), "l"(m), "r"(bar), "r"(c0), "r"(c1), "r"(c2) : "memory");
}
__device__ __forceinline__ void tma4d(uint32_t dst, const CUtensorMap* m, uint32_t bar, int c0, int c1, int c2, int c3) {
  asm volatile("cp.async.bulk.tensor.4d.shared::cluster.global.mbarrier::complete_tx::bytes [%0], [%1, {%3, %4, %5, %6}], [%2];"
               ::"r"(dst), "l"(m), "r"(bar), "r"(c0), "r"(c1), "r"(c2), "r"(c3) : "memory");
}
__device__ __forceinline__ void tma2d_store(const CUtensorMap* m, uint32_t src, int c0, int c1) {
  asm volatile("cp.async.bulk.tensor.2d.global.shared::cta.bulk_group [%0, {%2, %3}], [%1];"
               ::"l"(m), "r"(src), "r"(c0), "r"(c1) : "memory");
}
__device__ __forceinline__ void bulk_store(void* dst, uint32_t src, uint32_t bytes) {
  asm volatile("cp.async.bulk.global.shared::cta.bulk_group [%0], [%1], %2;" ::"l"(dst), "r"(src), "r"(bytes) : "memory");
}
__device__ __forceinline__ void bulk_load(uint32_t dst, const void* src, uint32_t bytes, uint32_t bar) {
  asm volatile("cp.async.bulk.shared::cluster.global.mbarrier::complete_tx::bytes [%0], [%1], %2, [%3];"
               ::"r"(dst), "l"(src), "r"(bytes), "r"(bar) : "memory");
}
__device__ __forceinline__ void bulk_commit() { asm volatile("cp.async.bulk.commit_group;" ::: "memory"); }
template <int N> __device__ __forceinline__ void bulk_wait() { asm volatile("cp.async.bulk.wait_group %0;" ::"n"(N) : "memory"); }
__device__ __forceinline__ void bulk_wait_read() { asm volatile("cp.async.bulk.wait_group.read 0;" ::: "memory"); }
__device__ __forceinline__ void bar_arrive(int id, int n) { asm volatile("bar.arrive %0, %1;" ::"r"(id), "r"(n) : "memory"); }
__device__ __forceinline__ uint4 lds128(uint32_t a) {
  uint4 v;
  asm volatile("ld.shared.v4.u32 {%0, %1, %2, %3}, [%4];" : "=r"(v.x), "=r"(v.y), "=r"(v.z), "=r"(v.w) : "r"(a) : "memory");
  return v;
}
__device__ __forceinline__ void sts128(uint32_t a, uint4 v) {
  asm volatile("st.shared.v4.u32 [%0], {%1, %2, %3, %4};" ::"r"(a), "r"(v.x), "r"(v.y), "r"(v.z), "r"(v.w) : "memory");
}
__device__ __forceinline__ uint32_t map_peer(uint32_t addr, uint32_t cta) {
  uint32_t r;
  asm("mapa.shared::cluster.u32 %0, %1, %2;" : "=r"(r) : "r"(addr), "r"(cta));
  return r;
}
__device__ __forceinline__ void st_async16(uint32_t addr, uint32_t a, uint32_t b, uint32_t c, uint32_t d, uint32_t bar) {
  asm volatile("st.async.weak.shared::cluster.mbarrier::complete_tx::bytes.v4.b32 [%0], {%1, %2, %3, %4}, [%5];"
               ::"r"(addr), "r"(a), "r"(b), "r"(c), "r"(d), "r"(bar) : "memory");
}
__device__ __forceinline__ void l2_prefetch(const void* p, uint32_t bytes) {
  asm volatile("cp.async.bulk.prefetch.L2.global [%0], %1;" ::"l"(p), "r"(bytes) : "memory");
}
__device__ __forceinline__ void prefetch_tmap(const CUtensorMap* m) {
  asm volatile("prefetch.tensormap [%0];" ::"l"(m) : "memory");
}
__device__ __forceinline__ uint64_t make_desc(uint32_t a16, uint32_t off, uint32_t lbo, uint32_t sbo, uint32_t swz) {
  const uint32_t lo = a16 + ((off >> 4) + ((lbo >> 4) << 16)), hi = (sbo >> 4) | (swz << 30);
  uint64_t d;
  asm("mov.b64 %0, {%1, %2};" : "=l"(d) : "r"(lo), "r"(hi));
  return d;
}
__device__ __forceinline__ void wg_fence() { asm volatile("wgmma.fence.sync.aligned;" ::: "memory"); }
__device__ __forceinline__ void wg_commit() { asm volatile("wgmma.commit_group.sync.aligned;" ::: "memory"); }
template <int N> __device__ __forceinline__ void wg_wait() { asm volatile("wgmma.wait_group.sync.aligned %0;" ::"n"(N) : "memory"); }
template <int N> __device__ __forceinline__ void fence_regs(float (&d)[N]) {
#pragma unroll
  for (int i = 0; i < N; i++) asm volatile("" : "+f"(d[i])::"memory");
}
template <int N> __device__ __forceinline__ void zero_regs(float (&d)[N]) {
#pragma unroll
  for (int i = 0; i < N; i++) d[i] = 0.f;
}
__device__ __forceinline__ uint32_t pack_bf16(float lo, float hi) {
  uint32_t r;
  asm("cvt.rn.bf16x2.f32 %0, %1, %2;" : "=r"(r) : "f"(hi), "f"(lo));
  return r;
}
__device__ __forceinline__ float bf_lo(uint32_t v) { return __uint_as_float(v << 16); }
__device__ __forceinline__ float bf_hi(uint32_t v) { return __uint_as_float(v & 0xffff0000u); }
__device__ __forceinline__ uint32_t max_bf2(uint32_t a, uint32_t b) {
  uint32_t r; asm("max.bf16x2 %0, %1, %2;" : "=r"(r) : "r"(a), "r"(b)); return r;
}
__device__ __forceinline__ uint32_t min_bf2(uint32_t a, uint32_t b) {
  uint32_t r; asm("min.bf16x2 %0, %1, %2;" : "=r"(r) : "r"(a), "r"(b)); return r;
}
__device__ __forceinline__ float ex2(float x) { float r; asm("ex2.approx.ftz.f32 %0, %1;" : "=f"(r) : "f"(x)); return r; }
__device__ __forceinline__ float rcp(float x) { float r; asm("rcp.approx.ftz.f32 %0, %1;" : "=f"(r) : "f"(x)); return r; }
__device__ __forceinline__ float tanh_ap(float x) { float r; asm("tanh.approx.f32 %0, %1;" : "=f"(r) : "f"(x)); return r; }
__device__ __forceinline__ float gelu_s(float x, float hs) {
  float u = x * fmaf(x * x, 0.0356774081f, 0.7978845608f);
  float hx = x * hs;
  return fmaf(hx, tanh_ap(u), hx);
}
__device__ __forceinline__ void stsm4(uint32_t addr, uint32_t r0, uint32_t r1, uint32_t r2, uint32_t r3) {
  asm volatile("stmatrix.sync.aligned.m8n8.x4.shared.b16 [%0], {%1, %2, %3, %4};"
               ::"r"(addr), "r"(r0), "r"(r1), "r"(r2), "r"(r3) : "memory");
}
__device__ __forceinline__ void red_add4(float* p, float a, float b, float c, float d) {
  asm volatile("red.global.add.v4.f32 [%0], {%1, %2, %3, %4};" ::"l"(p), "f"(a), "f"(b), "f"(c), "f"(d) : "memory");
}

__device__ __forceinline__ void mma_ss256(float (&d)[128], uint64_t descA, uint64_t descB) {
  asm volatile("wgmma.mma_async.sync.aligned.m64n256k16.f32.bf16.bf16 {"
      "%0, %1, %2, %3, %4, %5, %6, %7, %8, %9, %10, %11, %12, %13, %14, %15, "
      "%16, %17, %18, %19, %20, %21, %22, %23, %24, %25, %26, %27, %28, %29, %30, %31, "
      "%32, %33, %34, %35, %36, %37, %38, %39, %40, %41, %42, %43, %44, %45, %46, %47, "
      "%48, %49, %50, %51, %52, %53, %54, %55, %56, %57, %58, %59, %60, %61, %62, %63, "
      "%64, %65, %66, %67, %68, %69, %70, %71, %72, %73, %74, %75, %76, %77, %78, %79, "
      "%80, %81, %82, %83, %84, %85, %86, %87, %88, %89, %90, %91, %92, %93, %94, %95, "
      "%96, %97, %98, %99, %100, %101, %102, %103, %104, %105, %106, %107, %108, %109, %110, %111, "
      "%112, %113, %114, %115, %116, %117, %118, %119, %120, %121, %122, %123, %124, %125, %126, %127"
      "}, %128, %129, 1, 1, 1, 0, 1;\n"
      : "+f"(d[0]), "+f"(d[1]), "+f"(d[2]), "+f"(d[3]), "+f"(d[4]), "+f"(d[5]), "+f"(d[6]), "+f"(d[7]),
        "+f"(d[8]), "+f"(d[9]), "+f"(d[10]), "+f"(d[11]), "+f"(d[12]), "+f"(d[13]), "+f"(d[14]), "+f"(d[15]),
        "+f"(d[16]), "+f"(d[17]), "+f"(d[18]), "+f"(d[19]), "+f"(d[20]), "+f"(d[21]), "+f"(d[22]), "+f"(d[23]),
        "+f"(d[24]), "+f"(d[25]), "+f"(d[26]), "+f"(d[27]), "+f"(d[28]), "+f"(d[29]), "+f"(d[30]), "+f"(d[31]),
        "+f"(d[32]), "+f"(d[33]), "+f"(d[34]), "+f"(d[35]), "+f"(d[36]), "+f"(d[37]), "+f"(d[38]), "+f"(d[39]),
        "+f"(d[40]), "+f"(d[41]), "+f"(d[42]), "+f"(d[43]), "+f"(d[44]), "+f"(d[45]), "+f"(d[46]), "+f"(d[47]),
        "+f"(d[48]), "+f"(d[49]), "+f"(d[50]), "+f"(d[51]), "+f"(d[52]), "+f"(d[53]), "+f"(d[54]), "+f"(d[55]),
        "+f"(d[56]), "+f"(d[57]), "+f"(d[58]), "+f"(d[59]), "+f"(d[60]), "+f"(d[61]), "+f"(d[62]), "+f"(d[63]),
        "+f"(d[64]), "+f"(d[65]), "+f"(d[66]), "+f"(d[67]), "+f"(d[68]), "+f"(d[69]), "+f"(d[70]), "+f"(d[71]),
        "+f"(d[72]), "+f"(d[73]), "+f"(d[74]), "+f"(d[75]), "+f"(d[76]), "+f"(d[77]), "+f"(d[78]), "+f"(d[79]),
        "+f"(d[80]), "+f"(d[81]), "+f"(d[82]), "+f"(d[83]), "+f"(d[84]), "+f"(d[85]), "+f"(d[86]), "+f"(d[87]),
        "+f"(d[88]), "+f"(d[89]), "+f"(d[90]), "+f"(d[91]), "+f"(d[92]), "+f"(d[93]), "+f"(d[94]), "+f"(d[95]),
        "+f"(d[96]), "+f"(d[97]), "+f"(d[98]), "+f"(d[99]), "+f"(d[100]), "+f"(d[101]), "+f"(d[102]), "+f"(d[103]),
        "+f"(d[104]), "+f"(d[105]), "+f"(d[106]), "+f"(d[107]), "+f"(d[108]), "+f"(d[109]), "+f"(d[110]), "+f"(d[111]),
        "+f"(d[112]), "+f"(d[113]), "+f"(d[114]), "+f"(d[115]), "+f"(d[116]), "+f"(d[117]), "+f"(d[118]), "+f"(d[119]),
        "+f"(d[120]), "+f"(d[121]), "+f"(d[122]), "+f"(d[123]), "+f"(d[124]), "+f"(d[125]), "+f"(d[126]), "+f"(d[127])
      : "l"(descA), "l"(descB));
}

__device__ __forceinline__ void mma_ss64(float (&d)[32], uint64_t descA, uint64_t descB) {
  asm volatile("wgmma.mma_async.sync.aligned.m64n64k16.f32.bf16.bf16 {"
      "%0, %1, %2, %3, %4, %5, %6, %7, %8, %9, %10, %11, %12, %13, %14, %15, "
      "%16, %17, %18, %19, %20, %21, %22, %23, %24, %25, %26, %27, %28, %29, %30, %31"
      "}, %32, %33, 1, 1, 1, 0, 1;\n"
      : "+f"(d[0]), "+f"(d[1]), "+f"(d[2]), "+f"(d[3]), "+f"(d[4]), "+f"(d[5]), "+f"(d[6]), "+f"(d[7]),
        "+f"(d[8]), "+f"(d[9]), "+f"(d[10]), "+f"(d[11]), "+f"(d[12]), "+f"(d[13]), "+f"(d[14]), "+f"(d[15]),
        "+f"(d[16]), "+f"(d[17]), "+f"(d[18]), "+f"(d[19]), "+f"(d[20]), "+f"(d[21]), "+f"(d[22]), "+f"(d[23]),
        "+f"(d[24]), "+f"(d[25]), "+f"(d[26]), "+f"(d[27]), "+f"(d[28]), "+f"(d[29]), "+f"(d[30]), "+f"(d[31])
      : "l"(descA), "l"(descB));
}

__device__ __forceinline__ void mma_ss80(float (&d)[40], uint64_t descA, uint64_t descB) {
  asm volatile("wgmma.mma_async.sync.aligned.m64n80k16.f32.bf16.bf16 {"
      "%0, %1, %2, %3, %4, %5, %6, %7, %8, %9, %10, %11, %12, %13, %14, %15, "
      "%16, %17, %18, %19, %20, %21, %22, %23, %24, %25, %26, %27, %28, %29, %30, %31, "
      "%32, %33, %34, %35, %36, %37, %38, %39"
      "}, %40, %41, 1, 1, 1, 0, 1;\n"
      : "+f"(d[0]), "+f"(d[1]), "+f"(d[2]), "+f"(d[3]), "+f"(d[4]), "+f"(d[5]), "+f"(d[6]), "+f"(d[7]),
        "+f"(d[8]), "+f"(d[9]), "+f"(d[10]), "+f"(d[11]), "+f"(d[12]), "+f"(d[13]), "+f"(d[14]), "+f"(d[15]),
        "+f"(d[16]), "+f"(d[17]), "+f"(d[18]), "+f"(d[19]), "+f"(d[20]), "+f"(d[21]), "+f"(d[22]), "+f"(d[23]),
        "+f"(d[24]), "+f"(d[25]), "+f"(d[26]), "+f"(d[27]), "+f"(d[28]), "+f"(d[29]), "+f"(d[30]), "+f"(d[31]),
        "+f"(d[32]), "+f"(d[33]), "+f"(d[34]), "+f"(d[35]), "+f"(d[36]), "+f"(d[37]), "+f"(d[38]), "+f"(d[39])
      : "l"(descA), "l"(descB));
}

__device__ __forceinline__ void mma_ss192(float (&d)[96], uint64_t descA, uint64_t descB) {
  asm volatile("wgmma.mma_async.sync.aligned.m64n192k16.f32.bf16.bf16 {"
      "%0, %1, %2, %3, %4, %5, %6, %7, %8, %9, %10, %11, %12, %13, %14, %15, "
      "%16, %17, %18, %19, %20, %21, %22, %23, %24, %25, %26, %27, %28, %29, %30, %31, "
      "%32, %33, %34, %35, %36, %37, %38, %39, %40, %41, %42, %43, %44, %45, %46, %47, "
      "%48, %49, %50, %51, %52, %53, %54, %55, %56, %57, %58, %59, %60, %61, %62, %63, "
      "%64, %65, %66, %67, %68, %69, %70, %71, %72, %73, %74, %75, %76, %77, %78, %79, "
      "%80, %81, %82, %83, %84, %85, %86, %87, %88, %89, %90, %91, %92, %93, %94, %95"
      "}, %96, %97, 1, 1, 1, 0, 1;\n"
      : "+f"(d[0]), "+f"(d[1]), "+f"(d[2]), "+f"(d[3]), "+f"(d[4]), "+f"(d[5]), "+f"(d[6]), "+f"(d[7]),
        "+f"(d[8]), "+f"(d[9]), "+f"(d[10]), "+f"(d[11]), "+f"(d[12]), "+f"(d[13]), "+f"(d[14]), "+f"(d[15]),
        "+f"(d[16]), "+f"(d[17]), "+f"(d[18]), "+f"(d[19]), "+f"(d[20]), "+f"(d[21]), "+f"(d[22]), "+f"(d[23]),
        "+f"(d[24]), "+f"(d[25]), "+f"(d[26]), "+f"(d[27]), "+f"(d[28]), "+f"(d[29]), "+f"(d[30]), "+f"(d[31]),
        "+f"(d[32]), "+f"(d[33]), "+f"(d[34]), "+f"(d[35]), "+f"(d[36]), "+f"(d[37]), "+f"(d[38]), "+f"(d[39]),
        "+f"(d[40]), "+f"(d[41]), "+f"(d[42]), "+f"(d[43]), "+f"(d[44]), "+f"(d[45]), "+f"(d[46]), "+f"(d[47]),
        "+f"(d[48]), "+f"(d[49]), "+f"(d[50]), "+f"(d[51]), "+f"(d[52]), "+f"(d[53]), "+f"(d[54]), "+f"(d[55]),
        "+f"(d[56]), "+f"(d[57]), "+f"(d[58]), "+f"(d[59]), "+f"(d[60]), "+f"(d[61]), "+f"(d[62]), "+f"(d[63]),
        "+f"(d[64]), "+f"(d[65]), "+f"(d[66]), "+f"(d[67]), "+f"(d[68]), "+f"(d[69]), "+f"(d[70]), "+f"(d[71]),
        "+f"(d[72]), "+f"(d[73]), "+f"(d[74]), "+f"(d[75]), "+f"(d[76]), "+f"(d[77]), "+f"(d[78]), "+f"(d[79]),
        "+f"(d[80]), "+f"(d[81]), "+f"(d[82]), "+f"(d[83]), "+f"(d[84]), "+f"(d[85]), "+f"(d[86]), "+f"(d[87]),
        "+f"(d[88]), "+f"(d[89]), "+f"(d[90]), "+f"(d[91]), "+f"(d[92]), "+f"(d[93]), "+f"(d[94]), "+f"(d[95])
      : "l"(descA), "l"(descB));
}

__device__ __forceinline__ void mma_ss80_tt(float (&d)[40], uint64_t descA, uint64_t descB) {
  asm volatile("wgmma.mma_async.sync.aligned.m64n80k16.f32.bf16.bf16 {"
      "%0, %1, %2, %3, %4, %5, %6, %7, %8, %9, %10, %11, %12, %13, %14, %15, "
      "%16, %17, %18, %19, %20, %21, %22, %23, %24, %25, %26, %27, %28, %29, %30, %31, "
      "%32, %33, %34, %35, %36, %37, %38, %39"
      "}, %40, %41, 1, 1, 1, 1, 1;\n"
      : "+f"(d[0]), "+f"(d[1]), "+f"(d[2]), "+f"(d[3]), "+f"(d[4]), "+f"(d[5]), "+f"(d[6]), "+f"(d[7]),
        "+f"(d[8]), "+f"(d[9]), "+f"(d[10]), "+f"(d[11]), "+f"(d[12]), "+f"(d[13]), "+f"(d[14]), "+f"(d[15]),
        "+f"(d[16]), "+f"(d[17]), "+f"(d[18]), "+f"(d[19]), "+f"(d[20]), "+f"(d[21]), "+f"(d[22]), "+f"(d[23]),
        "+f"(d[24]), "+f"(d[25]), "+f"(d[26]), "+f"(d[27]), "+f"(d[28]), "+f"(d[29]), "+f"(d[30]), "+f"(d[31]),
        "+f"(d[32]), "+f"(d[33]), "+f"(d[34]), "+f"(d[35]), "+f"(d[36]), "+f"(d[37]), "+f"(d[38]), "+f"(d[39])
      : "l"(descA), "l"(descB));
}
__device__ __forceinline__ void mma_ss80_tt_z(float (&d)[40], uint64_t descA, uint64_t descB) {
  asm volatile("wgmma.mma_async.sync.aligned.m64n80k16.f32.bf16.bf16 {"
      "%0, %1, %2, %3, %4, %5, %6, %7, %8, %9, %10, %11, %12, %13, %14, %15, "
      "%16, %17, %18, %19, %20, %21, %22, %23, %24, %25, %26, %27, %28, %29, %30, %31, "
      "%32, %33, %34, %35, %36, %37, %38, %39"
      "}, %40, %41, 0, 1, 1, 1, 1;\n"
      : "=f"(d[0]), "=f"(d[1]), "=f"(d[2]), "=f"(d[3]), "=f"(d[4]), "=f"(d[5]), "=f"(d[6]), "=f"(d[7]),
        "=f"(d[8]), "=f"(d[9]), "=f"(d[10]), "=f"(d[11]), "=f"(d[12]), "=f"(d[13]), "=f"(d[14]), "=f"(d[15]),
        "=f"(d[16]), "=f"(d[17]), "=f"(d[18]), "=f"(d[19]), "=f"(d[20]), "=f"(d[21]), "=f"(d[22]), "=f"(d[23]),
        "=f"(d[24]), "=f"(d[25]), "=f"(d[26]), "=f"(d[27]), "=f"(d[28]), "=f"(d[29]), "=f"(d[30]), "=f"(d[31]),
        "=f"(d[32]), "=f"(d[33]), "=f"(d[34]), "=f"(d[35]), "=f"(d[36]), "=f"(d[37]), "=f"(d[38]), "=f"(d[39])
      : "l"(descA), "l"(descB));
}

__device__ __forceinline__ void mma_rs80_k(float (&d)[40], const uint32_t (&a)[4], uint64_t descB) {
  asm volatile("wgmma.mma_async.sync.aligned.m64n80k16.f32.bf16.bf16 {"
      "%0, %1, %2, %3, %4, %5, %6, %7, %8, %9, %10, %11, %12, %13, %14, %15, "
      "%16, %17, %18, %19, %20, %21, %22, %23, %24, %25, %26, %27, %28, %29, %30, %31, "
      "%32, %33, %34, %35, %36, %37, %38, %39"
      "}, {%40, %41, %42, %43}, %44, 1, 1, 1, 0;\n"
      : "+f"(d[0]), "+f"(d[1]), "+f"(d[2]), "+f"(d[3]), "+f"(d[4]), "+f"(d[5]), "+f"(d[6]), "+f"(d[7]),
        "+f"(d[8]), "+f"(d[9]), "+f"(d[10]), "+f"(d[11]), "+f"(d[12]), "+f"(d[13]), "+f"(d[14]), "+f"(d[15]),
        "+f"(d[16]), "+f"(d[17]), "+f"(d[18]), "+f"(d[19]), "+f"(d[20]), "+f"(d[21]), "+f"(d[22]), "+f"(d[23]),
        "+f"(d[24]), "+f"(d[25]), "+f"(d[26]), "+f"(d[27]), "+f"(d[28]), "+f"(d[29]), "+f"(d[30]), "+f"(d[31]),
        "+f"(d[32]), "+f"(d[33]), "+f"(d[34]), "+f"(d[35]), "+f"(d[36]), "+f"(d[37]), "+f"(d[38]), "+f"(d[39])
      : "r"(a[0]), "r"(a[1]), "r"(a[2]), "r"(a[3]), "l"(descB));
}
__device__ __forceinline__ void mma_rs80_k_z(float (&d)[40], const uint32_t (&a)[4], uint64_t descB) {
  asm volatile("wgmma.mma_async.sync.aligned.m64n80k16.f32.bf16.bf16 {"
      "%0, %1, %2, %3, %4, %5, %6, %7, %8, %9, %10, %11, %12, %13, %14, %15, "
      "%16, %17, %18, %19, %20, %21, %22, %23, %24, %25, %26, %27, %28, %29, %30, %31, "
      "%32, %33, %34, %35, %36, %37, %38, %39"
      "}, {%40, %41, %42, %43}, %44, 0, 1, 1, 0;\n"
      : "=f"(d[0]), "=f"(d[1]), "=f"(d[2]), "=f"(d[3]), "=f"(d[4]), "=f"(d[5]), "=f"(d[6]), "=f"(d[7]),
        "=f"(d[8]), "=f"(d[9]), "=f"(d[10]), "=f"(d[11]), "=f"(d[12]), "=f"(d[13]), "=f"(d[14]), "=f"(d[15]),
        "=f"(d[16]), "=f"(d[17]), "=f"(d[18]), "=f"(d[19]), "=f"(d[20]), "=f"(d[21]), "=f"(d[22]), "=f"(d[23]),
        "=f"(d[24]), "=f"(d[25]), "=f"(d[26]), "=f"(d[27]), "=f"(d[28]), "=f"(d[29]), "=f"(d[30]), "=f"(d[31]),
        "=f"(d[32]), "=f"(d[33]), "=f"(d[34]), "=f"(d[35]), "=f"(d[36]), "=f"(d[37]), "=f"(d[38]), "=f"(d[39])
      : "r"(a[0]), "r"(a[1]), "r"(a[2]), "r"(a[3]), "l"(descB));
}

__device__ __forceinline__ void mma_rs48_k(float (&d)[24], const uint32_t (&a)[4], uint64_t descB) {
  asm volatile("wgmma.mma_async.sync.aligned.m64n48k16.f32.bf16.bf16 {"
      "%0, %1, %2, %3, %4, %5, %6, %7, %8, %9, %10, %11, %12, %13, %14, %15, "
      "%16, %17, %18, %19, %20, %21, %22, %23"
      "}, {%24, %25, %26, %27}, %28, 1, 1, 1, 0;\n"
      : "+f"(d[0]), "+f"(d[1]), "+f"(d[2]), "+f"(d[3]), "+f"(d[4]), "+f"(d[5]), "+f"(d[6]), "+f"(d[7]),
        "+f"(d[8]), "+f"(d[9]), "+f"(d[10]), "+f"(d[11]), "+f"(d[12]), "+f"(d[13]), "+f"(d[14]), "+f"(d[15]),
        "+f"(d[16]), "+f"(d[17]), "+f"(d[18]), "+f"(d[19]), "+f"(d[20]), "+f"(d[21]), "+f"(d[22]), "+f"(d[23])
      : "r"(a[0]), "r"(a[1]), "r"(a[2]), "r"(a[3]), "l"(descB));
}
__device__ __forceinline__ void mma_rs48_k_z(float (&d)[24], const uint32_t (&a)[4], uint64_t descB) {
  asm volatile("wgmma.mma_async.sync.aligned.m64n48k16.f32.bf16.bf16 {"
      "%0, %1, %2, %3, %4, %5, %6, %7, %8, %9, %10, %11, %12, %13, %14, %15, "
      "%16, %17, %18, %19, %20, %21, %22, %23"
      "}, {%24, %25, %26, %27}, %28, 0, 1, 1, 0;\n"
      : "=f"(d[0]), "=f"(d[1]), "=f"(d[2]), "=f"(d[3]), "=f"(d[4]), "=f"(d[5]), "=f"(d[6]), "=f"(d[7]),
        "=f"(d[8]), "=f"(d[9]), "=f"(d[10]), "=f"(d[11]), "=f"(d[12]), "=f"(d[13]), "=f"(d[14]), "=f"(d[15]),
        "=f"(d[16]), "=f"(d[17]), "=f"(d[18]), "=f"(d[19]), "=f"(d[20]), "=f"(d[21]), "=f"(d[22]), "=f"(d[23])
      : "r"(a[0]), "r"(a[1]), "r"(a[2]), "r"(a[3]), "l"(descB));
}

__device__ __forceinline__ void mma_rs160_n(float (&d)[80], const uint32_t (&a)[4], uint64_t descB) {
  asm volatile("wgmma.mma_async.sync.aligned.m64n160k16.f32.bf16.bf16 {"
      "%0, %1, %2, %3, %4, %5, %6, %7, %8, %9, %10, %11, %12, %13, %14, %15, "
      "%16, %17, %18, %19, %20, %21, %22, %23, %24, %25, %26, %27, %28, %29, %30, %31, "
      "%32, %33, %34, %35, %36, %37, %38, %39, %40, %41, %42, %43, %44, %45, %46, %47, "
      "%48, %49, %50, %51, %52, %53, %54, %55, %56, %57, %58, %59, %60, %61, %62, %63, "
      "%64, %65, %66, %67, %68, %69, %70, %71, %72, %73, %74, %75, %76, %77, %78, %79"
      "}, {%80, %81, %82, %83}, %84, 1, 1, 1, 1;\n"
      : "+f"(d[0]), "+f"(d[1]), "+f"(d[2]), "+f"(d[3]), "+f"(d[4]), "+f"(d[5]), "+f"(d[6]), "+f"(d[7]),
        "+f"(d[8]), "+f"(d[9]), "+f"(d[10]), "+f"(d[11]), "+f"(d[12]), "+f"(d[13]), "+f"(d[14]), "+f"(d[15]),
        "+f"(d[16]), "+f"(d[17]), "+f"(d[18]), "+f"(d[19]), "+f"(d[20]), "+f"(d[21]), "+f"(d[22]), "+f"(d[23]),
        "+f"(d[24]), "+f"(d[25]), "+f"(d[26]), "+f"(d[27]), "+f"(d[28]), "+f"(d[29]), "+f"(d[30]), "+f"(d[31]),
        "+f"(d[32]), "+f"(d[33]), "+f"(d[34]), "+f"(d[35]), "+f"(d[36]), "+f"(d[37]), "+f"(d[38]), "+f"(d[39]),
        "+f"(d[40]), "+f"(d[41]), "+f"(d[42]), "+f"(d[43]), "+f"(d[44]), "+f"(d[45]), "+f"(d[46]), "+f"(d[47]),
        "+f"(d[48]), "+f"(d[49]), "+f"(d[50]), "+f"(d[51]), "+f"(d[52]), "+f"(d[53]), "+f"(d[54]), "+f"(d[55]),
        "+f"(d[56]), "+f"(d[57]), "+f"(d[58]), "+f"(d[59]), "+f"(d[60]), "+f"(d[61]), "+f"(d[62]), "+f"(d[63]),
        "+f"(d[64]), "+f"(d[65]), "+f"(d[66]), "+f"(d[67]), "+f"(d[68]), "+f"(d[69]), "+f"(d[70]), "+f"(d[71]),
        "+f"(d[72]), "+f"(d[73]), "+f"(d[74]), "+f"(d[75]), "+f"(d[76]), "+f"(d[77]), "+f"(d[78]), "+f"(d[79])
      : "r"(a[0]), "r"(a[1]), "r"(a[2]), "r"(a[3]), "l"(descB));
}
__device__ __forceinline__ void mma_rs160_n_z(float (&d)[80], const uint32_t (&a)[4], uint64_t descB) {
  asm volatile("wgmma.mma_async.sync.aligned.m64n160k16.f32.bf16.bf16 {"
      "%0, %1, %2, %3, %4, %5, %6, %7, %8, %9, %10, %11, %12, %13, %14, %15, "
      "%16, %17, %18, %19, %20, %21, %22, %23, %24, %25, %26, %27, %28, %29, %30, %31, "
      "%32, %33, %34, %35, %36, %37, %38, %39, %40, %41, %42, %43, %44, %45, %46, %47, "
      "%48, %49, %50, %51, %52, %53, %54, %55, %56, %57, %58, %59, %60, %61, %62, %63, "
      "%64, %65, %66, %67, %68, %69, %70, %71, %72, %73, %74, %75, %76, %77, %78, %79"
      "}, {%80, %81, %82, %83}, %84, 0, 1, 1, 1;\n"
      : "=f"(d[0]), "=f"(d[1]), "=f"(d[2]), "=f"(d[3]), "=f"(d[4]), "=f"(d[5]), "=f"(d[6]), "=f"(d[7]),
        "=f"(d[8]), "=f"(d[9]), "=f"(d[10]), "=f"(d[11]), "=f"(d[12]), "=f"(d[13]), "=f"(d[14]), "=f"(d[15]),
        "=f"(d[16]), "=f"(d[17]), "=f"(d[18]), "=f"(d[19]), "=f"(d[20]), "=f"(d[21]), "=f"(d[22]), "=f"(d[23]),
        "=f"(d[24]), "=f"(d[25]), "=f"(d[26]), "=f"(d[27]), "=f"(d[28]), "=f"(d[29]), "=f"(d[30]), "=f"(d[31]),
        "=f"(d[32]), "=f"(d[33]), "=f"(d[34]), "=f"(d[35]), "=f"(d[36]), "=f"(d[37]), "=f"(d[38]), "=f"(d[39]),
        "=f"(d[40]), "=f"(d[41]), "=f"(d[42]), "=f"(d[43]), "=f"(d[44]), "=f"(d[45]), "=f"(d[46]), "=f"(d[47]),
        "=f"(d[48]), "=f"(d[49]), "=f"(d[50]), "=f"(d[51]), "=f"(d[52]), "=f"(d[53]), "=f"(d[54]), "=f"(d[55]),
        "=f"(d[56]), "=f"(d[57]), "=f"(d[58]), "=f"(d[59]), "=f"(d[60]), "=f"(d[61]), "=f"(d[62]), "=f"(d[63]),
        "=f"(d[64]), "=f"(d[65]), "=f"(d[66]), "=f"(d[67]), "=f"(d[68]), "=f"(d[69]), "=f"(d[70]), "=f"(d[71]),
        "=f"(d[72]), "=f"(d[73]), "=f"(d[74]), "=f"(d[75]), "=f"(d[76]), "=f"(d[77]), "=f"(d[78]), "=f"(d[79])
      : "r"(a[0]), "r"(a[1]), "r"(a[2]), "r"(a[3]), "l"(descB));
}

__device__ __forceinline__ void feature_map(const uint32_t (&P)[2][10], uint32_t (&fr)[10][4]) {
  constexpr float L2E = 1.4426950408889634f;
#pragma unroll
  for (int p = 0; p < 2; p++) {
#pragma unroll
    for (int r = 0; r < 2; r++) {
      uint32_t mx = P[r][5 * p], mn = mx;
#pragma unroll
      for (int g = 1; g < 5; g++) { mx = max_bf2(mx, P[r][5 * p + g]); mn = min_bf2(mn, P[r][5 * p + g]); }
      mx = max_bf2(mx, __shfl_xor_sync(0xffffffffu, mx, 1));
      mn = min_bf2(mn, __shfl_xor_sync(0xffffffffu, mn, 1));
      mx = max_bf2(mx, __shfl_xor_sync(0xffffffffu, mx, 2));
      mn = min_bf2(mn, __shfl_xor_sync(0xffffffffu, mn, 2));
      float mx0 = -bf_lo(mx) * L2E, mx1 = -bf_hi(mx) * L2E, mn0 = bf_lo(mn) * L2E, mn1 = bf_hi(mn) * L2E;
      float ep0[5], ep1[5], en0[5], en1[5];
      float sp0 = 0.f, sp1 = 0.f, sn0 = 0.f, sn1 = 0.f;
#pragma unroll
      for (int g = 0; g < 5; g++) {
        float x0 = bf_lo(P[r][5 * p + g]), x1 = bf_hi(P[r][5 * p + g]);
        ep0[g] = ex2(fmaf(x0, L2E, mx0)); ep1[g] = ex2(fmaf(x1, L2E, mx1));
        en0[g] = ex2(fmaf(x0, -L2E, mn0)); en1[g] = ex2(fmaf(x1, -L2E, mn1));
        sp0 += ep0[g]; sp1 += ep1[g]; sn0 += en0[g]; sn1 += en1[g];
      }
      sp0 += __shfl_xor_sync(0xffffffffu, sp0, 1); sp1 += __shfl_xor_sync(0xffffffffu, sp1, 1);
      sn0 += __shfl_xor_sync(0xffffffffu, sn0, 1); sn1 += __shfl_xor_sync(0xffffffffu, sn1, 1);
      sp0 += __shfl_xor_sync(0xffffffffu, sp0, 2); sp1 += __shfl_xor_sync(0xffffffffu, sp1, 2);
      sn0 += __shfl_xor_sync(0xffffffffu, sn0, 2); sn1 += __shfl_xor_sync(0xffffffffu, sn1, 2);
      sp0 = rcp(sp0); sp1 = rcp(sp1); sn0 = rcp(sn0); sn1 = rcp(sn1);
#pragma unroll
      for (int g = 0; g < 5; g++) {
        fr[5 * p + g][r] = pack_bf16(ep0[g] * sp0, ep1[g] * sp1);
        fr[5 * p + g][2 + r] = pack_bf16(en0[g] * sn0, en1[g] * sn1);
      }
    }
  }
}

struct Ring {
  uint32_t idx, phase;
  template <int N> __device__ __forceinline__ void next() { if (++idx == N) { idx = 0; phase ^= 1; } }
};

}

__global__ void __cluster_dims__(2, 1, 1) __launch_bounds__(384, 1)
fused_kernel(const __grid_constant__ Maps maps, const __nv_bfloat16* __restrict__ x, const __nv_bfloat16* __restrict__ wqkv,
             const __nv_bfloat16* __restrict__ wphi, const __nv_bfloat16* __restrict__ w1, const __nv_bfloat16* __restrict__ w2,
             const __nv_bfloat16* __restrict__ w3, const __nv_bfloat16* __restrict__ w4, const __nv_bfloat16* __restrict__ wo,
             const __nv_bfloat16* __restrict__ gate_w) {
  extern __shared__ __align__(1024) uint8_t sgen[];
  const uint32_t sb = smem_u32(sgen);
  const uint32_t sb16 = (sb & 0x3FFFFu) >> 4;
  const uint32_t bars = sb + OFF_BAR;
  const uint32_t fullA = bars + 8 * B_FULLA, emptyA = bars + 8 * B_EMPTYA, fullB = bars + 8 * B_FULLB, emptyB = bars + 8 * B_EMPTYB;

  const int tid = threadIdx.x;
  const int rank = blockIdx.x & 1;
  const int pairIdx = blockIdx.x >> 1;
  const int i = pairIdx >> 2, j = 2 * (pairIdx & 3) + rank;

  TSTAMP(0);
  auto load_p1_b = [&](int k, uint32_t slot, uint32_t bar) {
    mbar_expect_tx(bar, 40960);
    tma4d(slot + 8192, &maps.qm, bar, 0, 64 * k, 0, j);
    tma3d(slot, &maps.w1m, bar, 0, 64 * k, j);
    tma4d(slot + 32768 + 2048, &maps.qr, bar, 64, 64 * k, 0, j);
    tma3d(slot + 32768, &maps.w1r, bar, 64, 64 * k, j);
  };
  if (tid >= 256) {
    asm volatile("setmaxnreg.dec.sync.aligned.u32 40;");
    if (tid == 256) {
#pragma unroll
      for (int s = 0; s < NA; s++) mbar_init(fullA + 8 * s, 1);
      asm volatile("fence.mbarrier_init.release.cluster;" ::: "memory");
#pragma unroll 1
      for (int u = 0; u < 4; u++) {
        if ((u & 1) == 0) mbar_expect_tx(fullA + 4 * u, SLOT_A);
        tma2d(sb + OFF_A + u * 8192, &maps.x, fullA + 8 * (u >> 1), 64 * (u >> 1), 128 * i + 64 * (u & 1));
      }
    } else if (tid == 288) {
#pragma unroll
      for (int s = 0; s < NB; s++) mbar_init(fullB + 8 * s, 1);
      asm volatile("fence.mbarrier_init.release.cluster;" ::: "memory");
#pragma unroll 1
      for (int k = 0; k < 2; k++) load_p1_b(k, sb + OFF_B + k * SLOT_B, fullB + 8 * k);
    } else if (tid == 320) {
#pragma unroll
      for (int b = B_CS; b < NBAR; b++) mbar_init(bars + 8 * b, b < B_SEND ? 1 : b < B_EMPTYB ? 4 : b < B_EMPTYA ? 8 : 16);
#pragma unroll
      for (int b = B_DSR; b < B_SEND; b++) mbar_expect_tx(bars + 8 * b, 10240);
      asm volatile("fence.mbarrier_init.release.cluster;" ::: "memory");
    }
    __syncwarp();
    asm volatile("barrier.cluster.arrive.relaxed.aligned;" ::: "memory");
    auto get_epoch = [&]() { return *reinterpret_cast<volatile unsigned*>(g_flags + FL_DONE * 32) / NCTA; };
    if (tid >= 320) {
      const int lane = tid & 31, ch = lane % 10, rg = lane / 10;
      const __nv_bfloat16* p = w1 + (size_t)(40 * i + (tid >= 352 ? 20 : 0) + rg) * D_ + 80 * j + 8 * ch;
      const unsigned par = get_epoch() & 1;
      float a[8];
#pragma unroll
      for (int e = 0; e < 8; e++) a[e] = 0.f;
#pragma unroll
      for (int it = 0; it < 7; it++) {
        uint4 v = make_uint4(0, 0, 0, 0);
        if (lane < 30 && 3 * it + rg < 20) v = __ldg(reinterpret_cast<const uint4*>(p + (size_t)it * 3 * D_));
        a[0] += bf_lo(v.x); a[1] += bf_hi(v.x); a[2] += bf_lo(v.y); a[3] += bf_hi(v.y);
        a[4] += bf_lo(v.z); a[5] += bf_hi(v.z); a[6] += bf_lo(v.w); a[7] += bf_hi(v.w);
      }
#pragma unroll
      for (int e = 0; e < 8; e++) a[e] += __shfl_down_sync(0xffffffffu, a[e], 10) + __shfl_down_sync(0xffffffffu, a[e], 20);
      if (lane < 10) {
        float* cd = g_acc[par] + 8 * KV_J + 80 * j + 8 * ch;
        red_add4(cd, a[0], a[1], a[2], a[3]); red_add4(cd + 4, a[4], a[5], a[6], a[7]);
      }
      __syncwarp();
      if (lane == 0) flag_add(FL_CS + j);
      __syncwarp();
    }
    asm volatile("barrier.cluster.wait.aligned;" ::: "memory");
    const int lane = tid & 31, pw = (tid >> 5) & 3;
    auto send_stream = [&](int w, unsigned ep1) {
#pragma unroll 1
      for (int c = 0; c < 3; c++) {
        const int d = (j + 2 * c + 2) & 7;
        mbar_wait(bars + 8 * (B_SEND + 2 * c + w), 0);
        if (w) TR4(c * 16 + 7);
        bulk_store(g_part + (size_t)((i * 8 + d) * 3 + c) * 1280 + w * 640, sb + OFF_SEND + w * 10240, 10240);
        bulk_commit();
        bulk_wait<0>();
        mbar_arrive(bars + 8 * (B_SDONE + 2 * c + w));
        if (w) TR4(c * 16 + 9);
        asm volatile("st.release.gpu.global.u32 [%0], %1;"
                     ::"l"(g_flags + (FL_PART + i * 8 + d) * 32 + 2 * c + w), "r"(ep1) : "memory");
        if (w) TR4(c * 16 + 10);
      }
    };
    if (pw == 0) {
      if (tid == 256) {
        Ring r{2, 1};
        unsigned ep1 = 0;
#pragma unroll 1
        for (int k = 2; k < 30; k++) {
          if (k == 4) ep1 = get_epoch() + 1;
          if (k == 10 || k == 20) {
            const unsigned tgt = ep1 * 8u;
            const unsigned* f0 = g_flags + (k == 10 ? FL_H + ((i - 1) & 15) : FL_X1 + i) * 32;
            const unsigned* f1 = g_flags + (k == 10 ? FL_H + i : FL_X1 + i) * 32;
            const unsigned* f2 = g_flags + (k == 10 ? FL_H + ((i + 1) & 15) : FL_X1 + i) * 32;
            uint32_t n = 0;
            while (++n < (WAIT_LIMIT >> 4)) {
              unsigned v0, v1, v2;
              asm volatile("ld.relaxed.gpu.global.u32 %0, [%3];\nld.relaxed.gpu.global.u32 %1, [%4];\nld.acquire.gpu.global.u32 %2, [%5];"
                           : "=r"(v0), "=r"(v1), "=r"(v2) : "l"(f0), "l"(f1), "l"(f2) : "memory");
              if ((int)((v0 - tgt) | (v1 - tgt) | (v2 - tgt)) >= 0) break;
            }
            TSTAMPX(k == 10 ? 29 : 30);
          }
          mbar_wait(emptyA + 8 * r.idx, r.phase);
          const uint32_t bar = fullA + 8 * r.idx, slot = sb + OFF_A + r.idx * SLOT_A;
          TRACE(k);
          mbar_expect_tx(bar, SLOT_A);
          tma2d_mc(slot + rank * 8192, k < 10 ? &maps.x : k < 20 ? &maps.hs : &maps.x1, bar, 64 * (k % 10), 128 * i + 64 * rank);
          r.next<NA>();
        }
        send_stream(1, ep1);
      }
    } else if (pw == 1) {
      if (tid == 288) {
        Ring r{2, 1};
#pragma unroll 1
        for (int k = 2; k < 18; k++) {
          mbar_wait(emptyB + 8 * r.idx, r.phase);
          const uint32_t bar = fullB + 8 * r.idx, slot = sb + OFF_B + r.idx * SLOT_B;
          if (k < 10) {
            load_p1_b(k, slot, bar);
          } else if (k < 13) {
            if (k == 12) mbar_wait(fullA + 8 * 2, 0);
            mbar_expect_tx(bar, k < 12 ? 40960 : 20480);
#pragma unroll 1
            for (int u = 0; u < (k < 12 ? 4 : 2); u++) tma3d(slot + u * 10240, &maps.w2, bar, 0, 256 * (k - 10) + 64 * u, 5 * j);
          } else {
            mbar_expect_tx(bar, 49152);
            tma3d(slot, &maps.w3, bar, 0, 128 * (k - 13), 3 * j);
            tma3d(slot + 24576, &maps.w3, bar, 0, 128 * (k - 13) + 64, 3 * j);
          }
          r.next<NB>();
        }
        Ring r4{0, 1};
#pragma unroll 1
        for (int n = 0; n < 16; n++) {
          if (n == 0 || n == 1 || n == 3) { mbar_wait(emptyB + 8 * r.idx, r.phase); r.next<NB>(); }
          mbar_wait(bars + 8 * (B_EMPTY4 + r4.idx), r4.phase);
          const uint32_t bar = bars + 8 * (B_FULL4 + r4.idx), slot = sb + OFF_B + r4.idx * UNIT4;
          const int u = n & 3, m = ((j >> 1) + 1 + (n >> 2)) & 3;
          mbar_expect_tx(bar, u == 3 ? 25600 : 20480);
          tma3d(slot, u == 3 ? &maps.wo : &maps.w4, bar, 0, u == 3 ? 80 * j : 192 * j + 64 * u, 5 * m);
          r4.next<NU4>();
        }
      }
    } else {
      const unsigned epoch = get_epoch();
      float* accg = g_acc[epoch & 1];
      if (pw == 2) {
        {
          float* nxt = g_acc[(epoch + 1) & 1];
          constexpr int PER = ACC_FLOATS / NCTA;
#pragma unroll 1
          for (int e = lane; e < PER; e += 32) nxt[blockIdx.x * PER + e] = 0.f;
        }
        if (tid == 320) {
          flag_wait(FL_CS + j, (epoch + 1) * 32u);
          flag_wait(FL_ST + i, (epoch + 1) * 8u);
          fence_async_all();
          mbar_expect_tx(bars + 8 * B_CS, 320 + 2048);
          bulk_load(sb + OFF_CS, accg + 8 * KV_J + 80 * j, 320, bars + 8 * B_CS);
          bulk_load(sb + OFF_XST, g_xstat + 128 * i, 2048, bars + 8 * B_CS);
          TSTAMPX(21);
          l2_prefetch(w2 + (size_t)blockIdx.x * (D_ * D_ / NCTA), D_ * D_ * 2 / NCTA);
          flag_wait(FL_H + i, (epoch + 1) * 8u);
          l2_prefetch(w3 + (size_t)blockIdx.x * (F_ * D_ / NCTA), F_ * D_ * 2 / NCTA);
          l2_prefetch(w4 + (size_t)blockIdx.x * (F_ * D_ / NCTA), F_ * D_ * 2 / NCTA);
          l2_prefetch(wo + (size_t)blockIdx.x * (D_ * D_ / NCTA), D_ * D_ * 2 / NCTA);
          flag_wait(FL_KV + j, (epoch + 1) * 16u);
          mbar_expect_tx(bars + 8 * B_KV, KV_J * 4);
          bulk_load(sb + OFF_MISC, accg + j * KV_J, KV_J * 4, bars + 8 * B_KV);
          TSTAMPX(22);
        }
        __syncwarp();
#pragma unroll 1
        for (int m = 0; m < 6; m++) {
          const int col = 192 * j + 32 * m + 8 * (lane & 3);
          const __nv_bfloat16* p = w3 + (size_t)(40 * i + (lane >> 2) * 5) * F_ + col;
          float a[8];
#pragma unroll
          for (int e = 0; e < 8; e++) a[e] = 0.f;
#pragma unroll
          for (int it = 0; it < 5; it++) {
            const uint4 v = __ldg(reinterpret_cast<const uint4*>(p + (size_t)it * F_));
            a[0] += bf_lo(v.x); a[1] += bf_hi(v.x); a[2] += bf_lo(v.y); a[3] += bf_hi(v.y);
            a[4] += bf_lo(v.z); a[5] += bf_hi(v.z); a[6] += bf_lo(v.w); a[7] += bf_hi(v.w);
          }
#pragma unroll
          for (int e = 0; e < 4; e++) {
            const float snd = (lane & 4) ? a[e] : a[e + 4], keep = (lane & 4) ? a[e + 4] : a[e];
            a[e] = keep + __shfl_xor_sync(0xffffffffu, snd, 4);
            a[e] += __shfl_xor_sync(0xffffffffu, a[e], 8);
            a[e] += __shfl_xor_sync(0xffffffffu, a[e], 16);
          }
          if (lane < 8) red_add4(accg + 8 * KV_J + D_ + col + (lane >> 2) * 4, a[0], a[1], a[2], a[3]);
        }
        __syncwarp();
        if (tid == 320) {
          flag_add(FL_CS3 + j);
          mbar_wait(bars + 8 * B_MFREE, 0);
          flag_wait(FL_X1 + i, (epoch + 1) * 8u);
          flag_wait(FL_CS3 + j, (epoch + 1) * 16u);
          fence_async_all();
          mbar_expect_tx(bars + 8 * B_ST1, 8192 + 768);
          bulk_load(sb + OFF_CS + 320, accg + 8 * KV_J + D_ + 192 * j, 768, bars + 8 * B_ST1);
          bulk_load(sb + OFF_MISC, g_st1 + 128 * i * 8, 8192, bars + 8 * B_ST1);
        }
        __syncwarp();
        mbar_wait(bars + 8 * B_PEER, 0);
        const unsigned* fp = g_flags + (FL_PART + i * 8 + j) * 32 + lane;
        bool seen = lane >= 6;
        uint32_t n = 0;
        while (!__all_sync(0xffffffffu, seen) && ++n < (WAIT_LIMIT >> 4)) {
          if (!seen && ld_acquire(fp) == epoch + 1 && (lane < 2 || (lane < 4 ? mbar_test(bars + 8 * (B_SEND + 2), 0) && mbar_test(bars + 8 * (B_SEND + 3), 0) && mbar_test(bars + 8 * (B_EMPTY4 + 1), 0) : mbar_test(bars + 8 * (B_SDONE + lane), 0)))) {
            seen = true;
            if (lane & 1) TR4((lane >> 1) * 16 + 11);
            mbar_expect_tx(bars + 8 * (B_RDY + lane), 10240);
            bulk_load(sb + (lane < 2 ? OFF_G0 : lane < 4 ? OFF_G1 : OFF_SEND) + (lane & 1) * 10240, g_part + (size_t)(i * 8 + j) * 3840 + lane * 640, 10240,
                      bars + 8 * (B_RDY + lane));
          }
        }
      }
      if (tid == 352) {
        mbar_wait(bars + 8 * B_SIGP, 0);
        flag_add(FL_ST + i);
        TSTAMPX(20);
        mbar_expect_tx(bars + 8 * B_XR, 20480);
#pragma unroll 1
        for (int u = 0; u < 8; u++)
          tma2d(sb + OFF_B + (u / 3) * SLOT_B + SPARE + (u % 3) * 2560, &maps.xr, bars + 8 * B_XR, 80 * j, 128 * i + 16 * u);
        const int shift = (j < 2) ? 1 : (j < 4) ? -1 : (j < 6) ? 2 : -2;
        if ((shift > 0 && i == 0) || (shift < 0 && i == 15)) {
          const int nz = shift > 0 ? shift : -shift, zr = shift > 0 ? 0 : S_ - nz;
#pragma unroll 1
          for (int e = 0; e < nz * 10; e++)
            reinterpret_cast<uint4*>(g_Hs + (size_t)(2 + zr + e / 10) * D_ + 80 * j)[e % 10] = make_uint4(0, 0, 0, 0);
          fence_async_all();
        }
        prefetch_tmap(&maps.st_h); prefetch_tmap(&maps.st_x1); prefetch_tmap(&maps.hs); prefetch_tmap(&maps.x1); prefetch_tmap(&maps.xr);
        prefetch_tmap(&maps.w2); prefetch_tmap(&maps.w3); prefetch_tmap(&maps.w4); prefetch_tmap(&maps.wo); prefetch_tmap(&maps.st_out);
        mbar_wait(bars + 8 * B_SIGH, 0);
        TSTAMPX(23);
        tma2d_store(&maps.st_h, sb + OFF_STG, 80 * j, 128 * i + 2 + shift);
        tma2d_store(&maps.st_h, sb + OFF_STG + 10240, 80 * j, 128 * i + 66 + shift);
        bulk_commit(); bulk_wait<0>();
        flag_add(FL_H + i);
        TSTAMPX(24);
        mbar_wait(bars + 8 * B_SIGKV, 0);
        TSTAMPX(25);
        asm volatile("cp.reduce.async.bulk.global.shared::cta.bulk_group.add.f32 [%0], [%1], %2;"
                     ::"l"(accg + j * KV_J), "r"(sb + OFF_MISC), "r"(KV_J * 4) : "memory");
        bulk_commit(); bulk_wait<0>();
        flag_add(FL_KV + j);
        TSTAMPX(26);
        mbar_wait(bars + 8 * B_SIGX1, 0);
        TSTAMPX(27);
        tma2d_store(&maps.st_x1, sb + OFF_STG, 80 * j, 128 * i);
        tma2d_store(&maps.st_x1, sb + OFF_STG + 10240, 80 * j, 128 * i + 64);
        bulk_commit(); bulk_wait<0>();
        flag_add(FL_X1 + i);
        TSTAMPX(28);
        send_stream(0, epoch + 1);
      }
    }
  } else {
    uint4 pv[5], pw_[5], pre;
    {
      const int row = 128 * i + 16 * j + (tid >> 4), l16 = tid & 15;
#pragma unroll
      for (int c = 0; c < 5; c++) pv[c] = __ldg(reinterpret_cast<const uint4*>(x + (size_t)row * D_ + c * 128 + l16 * 8));
      pre = __ldg(reinterpret_cast<const uint4*>(wphi + (size_t)j * 1600) + (tid < 200 ? tid : 0));
#pragma unroll
      for (int c = 0; c < 5; c++) pw_[c] = __ldg(reinterpret_cast<const uint4*>(gate_w + c * 128 + l16 * 8));
    }
    asm volatile("barrier.cluster.arrive.relaxed.aligned;" ::: "memory");
    asm volatile("setmaxnreg.inc.sync.aligned.u32 232;");
    const int wg = tid >> 7, warp = tid >> 5, lane = tid & 31, t = lane & 3;
    const int rloc = warp * 16 + (lane >> 2);
    const float* s_cs = reinterpret_cast<const float*>(sgen + OFF_CS);
    auto signal = [&](int b) {
      __syncwarp();
      if (lane == 0) mbar_arrive(bars + 8 * b);
    };
    auto releaseB = [&](uint32_t bar) {
      __syncwarp();
      if (lane == 0) mbar_arrive(bar);
    };
    auto release = [&](uint32_t bar) {
      __syncwarp();
      if (lane < 2) mbar_arrive_cta(bar, lane);
    };
    const uint32_t stg_lane = (warp * 16 + ((lane >> 3) & 1) * 8 + (lane & 7)) * 160 + (lane >> 4) * 16;

    {
#pragma unroll 1
      for (int e = tid; e < 800; e += 256) sts128(sb + OFF_MISC + e * 16, make_uint4(0, 0, 0, 0));
      bar_sync(1, 256);
      float f[40];
      float s = 0.f, gs = 0.f;
#pragma unroll
      for (int c = 0; c < 5; c++) {
        const uint32_t vv[4] = {pv[c].x, pv[c].y, pv[c].z, pv[c].w}, ww[4] = {pw_[c].x, pw_[c].y, pw_[c].z, pw_[c].w};
#pragma unroll
        for (int e = 0; e < 4; e++) {
          f[8 * c + 2 * e] = bf_lo(vv[e]); f[8 * c + 2 * e + 1] = bf_hi(vv[e]);
          s += f[8 * c + 2 * e] + f[8 * c + 2 * e + 1];
          gs = fmaf(f[8 * c + 2 * e], bf_lo(ww[e]), gs); gs = fmaf(f[8 * c + 2 * e + 1], bf_hi(ww[e]), gs);
        }
      }
#pragma unroll
      for (int o = 1; o < 16; o <<= 1) { s += __shfl_xor_sync(0xffffffffu, s, o); gs += __shfl_xor_sync(0xffffffffu, gs, o); }
      const float mean = s * (1.f / D_);
      float q = 0.f;
#pragma unroll
      for (int e = 0; e < 40; e++) { const float d = f[e] - mean; q = fmaf(d, d, q); }
#pragma unroll
      for (int o = 1; o < 16; o <<= 1) q += __shfl_xor_sync(0xffffffffu, q, o);
      const float rstd = rsqrtf(q * (1.f / D_) + 1e-5f);
      asm volatile("barrier.cluster.wait.aligned;" ::: "memory");
      if ((tid & 15) == 0) g_xstat[128 * i + 16 * j + (tid >> 4)] = make_float4(rstd, -mean * rstd, rcp(1.f + __expf(-gs)), 0.f);
      signal(B_SIGP);
      if (tid < 200) {
        const uint32_t ww[4] = {pre.x, pre.y, pre.z, pre.w};
        const int h = tid / 50;
#pragma unroll
        for (int e = 0; e < 8; e++) {
          const int idx = tid * 8 + e, k = idx / 20, ff = idx - 20 * k;
          const int n = 40 * (h >> 1) + 8 * (ff >> 2) + 2 * (ff & 3) + (h & 1);
          const int off = (k >> 4) * 2560 + n * 32 + ((((k >> 3) ^ (n >> 2)) & 1) << 4) + (k & 7) * 2;
          *reinterpret_cast<unsigned short*>(sgen + OFF_MISC + off) = (unsigned short)(ww[e >> 1] >> ((e & 1) * 16));
        }
      }
    }
    TSTAMP(1);

    Ring ra{0, 0}, rb{0, 0};
    uint32_t qp[2][10], P[2][10];
    float st_g[2];
    {
      float accM[128], accR[32];
      zero_regs(accM); zero_regs(accR);
      uint32_t pa = 0, pb = 0;
#pragma unroll 1
      for (int k = 0; k < 10; k++) {
        mbar_wait(fullA + 8 * ra.idx, ra.phase);
        if (tid == 0) TRACE(32 + k);
        mbar_wait(fullB + 8 * rb.idx, rb.phase);
        if (tid == 0) TRACE(64 + k);
        if (k == 0) TSTAMP(2);
        const uint32_t a0 = sb16 + ((OFF_A + ra.idx * SLOT_A + wg * 8192) >> 4), b0 = sb16 + ((OFF_B + rb.idx * SLOT_B) >> 4);
        wg_fence();
#pragma unroll
        for (int kk = 0; kk < 4; kk++) {
          const uint64_t da = make_desc(a0, kk * 32, 16, 1024, 1);
          mma_ss256(accM, da, make_desc(b0, kk * 2048, 8192, 1024, 1));
          mma_ss64(accR, da, make_desc(b0, 32768 + kk * 512, 2048, 256, 3));
          if (kk == 0) {
            wg_commit();
            if (k > 0) {
              wg_wait<1>();
              if (k - 1 < 8) release(emptyA + 8 * pa);
              releaseB(emptyB + 8 * pb);
            }
          }
        }
        wg_commit();
        pa = ra.idx; pb = rb.idx;
        ra.next<NA>(); rb.next<NB>();
      }
      TSTAMP(18);
      float st_rstd[2], st_mr[2];
      mbar_wait(bars + 8 * B_CS, 0);
#pragma unroll
      for (int r = 0; r < 2; r++) {
        const uint4 st = lds128(sb + OFF_XST + (rloc + 8 * r) * 16);
        st_rstd[r] = __uint_as_float(st.x); st_mr[r] = __uint_as_float(st.y); st_g[r] = __uint_as_float(st.z);
      }
      TSTAMP(19);
      wg_wait<0>();
      fence_regs(accM); fence_regs(accR);
      TSTAMP(3);
#define ACC(P_, G, I_) ((G) < 8 ? accM[(P_) * 32 + ((G) & 7) * 4 + (I_)] : accR[(P_) * 8 + ((G) & 1) * 4 + (I_)])
      {
        uint32_t hv[10][2];
#pragma unroll
        for (int g = 0; g < 10; g++) {
          const float2 cs = *reinterpret_cast<const float2*>(s_cs + 8 * g + 2 * t);
          const float v0 = gelu_s(fmaf(ACC(0, g, 0), st_rstd[0], st_mr[0] * cs.x), 0.5f), v1 = gelu_s(fmaf(ACC(0, g, 1), st_rstd[0], st_mr[0] * cs.y), 0.5f);
          const float v2 = gelu_s(fmaf(ACC(0, g, 2), st_rstd[1], st_mr[1] * cs.x), 0.5f), v3 = gelu_s(fmaf(ACC(0, g, 3), st_rstd[1], st_mr[1] * cs.y), 0.5f);
          hv[g][0] = pack_bf16(v0, v1); hv[g][1] = pack_bf16(v2, v3);
        }
        fence_async_smem();
        bar_sync(1, 256);
#pragma unroll
        for (int s = 0; s < 5; s++) stsm4(sb + OFF_STG + stg_lane + s * 32, hv[2 * s][0], hv[2 * s][1], hv[2 * s + 1][0], hv[2 * s + 1][1]);
        fence_async_smem();
        signal(B_SIGH);
      }
      TSTAMP(4);
      uint32_t kf[5][4], qf[5][4];
#pragma unroll
      for (int s = 0; s < 5; s++) {
        kf[s][0] = pack_bf16(ACC(2, 2 * s, 0), ACC(2, 2 * s, 1)); kf[s][1] = pack_bf16(ACC(2, 2 * s, 2), ACC(2, 2 * s, 3));
        kf[s][2] = pack_bf16(ACC(2, 2 * s + 1, 0), ACC(2, 2 * s + 1, 1)); kf[s][3] = pack_bf16(ACC(2, 2 * s + 1, 2), ACC(2, 2 * s + 1, 3));
        qf[s][0] = pack_bf16(ACC(1, 2 * s, 0), ACC(1, 2 * s, 1)); qf[s][1] = pack_bf16(ACC(1, 2 * s, 2), ACC(1, 2 * s, 3));
        qf[s][2] = pack_bf16(ACC(1, 2 * s + 1, 0), ACC(1, 2 * s + 1, 1)); qf[s][3] = pack_bf16(ACC(1, 2 * s + 1, 2), ACC(1, 2 * s + 1, 3));
      }
      float pk[40], pq[40];
      wg_fence();
#pragma unroll
      for (int s = 0; s < 5; s++) {
        if (s == 0) mma_rs80_k_z(pk, kf[s], make_desc(sb16, OFF_MISC, 16, 256, 3));
        else mma_rs80_k(pk, kf[s], make_desc(sb16, OFF_MISC + s * 2560, 16, 256, 3));
      }
#pragma unroll
      for (int s = 0; s < 5; s++) {
        if (s == 0) mma_rs80_k_z(pq, qf[s], make_desc(sb16, OFF_MISC, 16, 256, 3));
        else mma_rs80_k(pq, qf[s], make_desc(sb16, OFF_MISC + s * 2560, 16, 256, 3));
      }
      wg_commit();
      {
        const int mat = lane >> 3;
        const int tok = warp * 16 + (mat & 1) * 8 + (lane & 7);
        const uint32_t ones = (t == 0) ? 0x00003f80u : 0u;
        __syncwarp();
#pragma unroll
        for (int p = 0; p < 2; p++) {
          const uint32_t rowa = sb + OFF_A + p * SLOT_A + tok * 128;
#pragma unroll
          for (int gg = 0; gg < 3; gg++) {
            const int g0 = 5 * p + 2 * gg;
            uint32_t r0 = pack_bf16(ACC(3, g0, 0), ACC(3, g0, 1)), r1 = pack_bf16(ACC(3, g0, 2), ACC(3, g0, 3));
            uint32_t r2 = ones, r3 = ones;
            if (gg < 2) { r2 = pack_bf16(ACC(3, g0 + 1, 0), ACC(3, g0 + 1, 1)); r3 = pack_bf16(ACC(3, g0 + 1, 2), ACC(3, g0 + 1, 3)); }
            stsm4(rowa + (((2 * gg + (mat >> 1)) ^ (tok & 7)) << 4), r0, r1, r2, r3);
          }
        }
      }
#undef ACC
      wg_wait<0>();
      fence_regs(pk); fence_regs(pq);
#pragma unroll
      for (int G = 0; G < 10; G++) {
        P[0][G] = pack_bf16(pk[4 * G], pk[4 * G + 1]); P[1][G] = pack_bf16(pk[4 * G + 2], pk[4 * G + 3]);
        qp[0][G] = pack_bf16(pq[4 * G], pq[4 * G + 1]); qp[1][G] = pack_bf16(pq[4 * G + 2], pq[4 * G + 3]);
      }
    }

    uint32_t fr[10][4];
    uint32_t xv[2][10];
#pragma unroll
    for (int g = 0; g < 10; g++) xv[0][g] = xv[1][g] = 0u;
    int pass;
    pass = gridDim.y;
#pragma unroll 1
    do {
    feature_map(P, fr);
    if (pass != 0) {
    {
      const int mat = lane >> 3;
      const int tok = warp * 16 + (mat & 1) * 8 + (lane & 7);
      const uint32_t base = sb + OFF_B + tok * 32 + (((mat >> 1) ^ ((tok >> 2) & 1)) << 4);
#pragma unroll
      for (int G = 0; G < 10; G++) stsm4(base + G * 4096, fr[G][0], fr[G][1], fr[G][2], fr[G][3]);
      fence_async_smem();
      bar_sync(1, 256);
      float kv[40];
      const uint32_t a0 = sb16 + ((OFF_A + wg * SLOT_A) >> 4), b0 = sb16 + ((OFF_B + wg * 20480) >> 4);
      wg_fence();
#pragma unroll
      for (int ks = 0; ks < 8; ks++) {
        if (ks == 0) mma_ss80_tt_z(kv, make_desc(a0, 0, 16, 1024, 1), make_desc(b0, 0, 4096, 256, 3));
        else mma_ss80_tt(kv, make_desc(a0, ks * 2048, 16, 1024, 1), make_desc(b0, ks * 512, 4096, 256, 3));
      }
      wg_commit();
      wg_wait<0>();
      fence_regs(kv);
      TSTAMP(31);
      release(emptyA); release(emptyA + 8); releaseB(emptyB);
      const uint32_t dst = sb + OFF_MISC + wg * (KV_PAIR * 4);
      const int m0 = (warp & 3) * 16 + (lane >> 2);
#pragma unroll
      for (int r = 0; r < 2; r++) {
        const int m = m0 + 8 * r;
        const bool hi = m >= 20;
        uint32_t v[10];
#pragma unroll
        for (int G = 0; G < 10; G++) v[G] = __float_as_uint(hi ? kv[4 * G + 2 * r + 1] : kv[4 * G + 2 * r]);
        const uint32_t p = dst + 4 * (m < 40 ? m * 48 + t * 12 : 1920 + t * 24 + 12);
        if (m <= 40) {
          sts128(p, make_uint4(v[0], v[1], v[2], v[3])); sts128(p + 16, make_uint4(v[4], v[5], v[6], v[7]));
          sts128(p + 32, make_uint4(v[8], v[9], 0u, 0u));
        }
      }
      if (m0 == 32) {
        const uint32_t p = dst + 4 * (1920 + t * 24);
        sts128(p, make_uint4(__float_as_uint(kv[2]), __float_as_uint(kv[6]), __float_as_uint(kv[10]), __float_as_uint(kv[14])));
        sts128(p + 16, make_uint4(__float_as_uint(kv[18]), __float_as_uint(kv[22]), __float_as_uint(kv[26]), __float_as_uint(kv[30])));
        sts128(p + 32, make_uint4(__float_as_uint(kv[34]), __float_as_uint(kv[38]), 0u, 0u));
      }
      fence_async_smem();
      signal(B_SIGKV);
    }
    TSTAMP(5);

    {
      {
        mbar_wait(bars + 8 * B_XR, 0);
        const uint32_t xa = sb + OFF_B + (warp / 3) * SLOT_B + SPARE + (warp % 3) * 2560 + (lane >> 2) * 160 + t * 4;
#pragma unroll
        for (int g = 0; g < 10; g++) { xv[0][g] = lds32(xa + g * 16); xv[1][g] = lds32(xa + 1280 + g * 16); }
      }
      float acc[40];
      zero_regs(acc);
      uint32_t pa = 0, pb = 0;
#pragma unroll 1
      for (int k = 0; k < 10; k++) {
        mbar_wait(fullA + 8 * ra.idx, ra.phase);
        if (tid == 0) TRACE(42 + k);
        if ((k & 3) == 0) mbar_wait(fullB + 8 * rb.idx, rb.phase);
        if (tid == 0) TRACE(74 + k);
        if (k == 0) TSTAMP(6);
        const uint32_t a0 = sb16 + ((OFF_A + ra.idx * SLOT_A + wg * 8192) >> 4);
        const uint32_t b0 = sb16 + ((OFF_B + rb.idx * SLOT_B + (k & 3) * 10240) >> 4);
        wg_fence();
#pragma unroll
        for (int kk = 0; kk < 4; kk++) {
          mma_ss80(acc, make_desc(a0, kk * 32, 16, 1024, 1), make_desc(b0, kk * 512, 2048, 256, 3));
          if (kk == 1) {
            wg_commit();
            if (k > 0) {
              wg_wait<1>();
              release(emptyA + 8 * pa);
              if ((k & 3) == 0) releaseB(emptyB + 8 * pb);
            }
          }
        }
        wg_commit();
        pa = ra.idx; pb = rb.idx;
        ra.next<NA>();
        if ((k & 3) == 3 || k == 9) rb.next<NB>();
      }
      wg_wait<0>();
      fence_regs(acc);
      release(emptyA + 8 * pa); releaseB(emptyB + 8 * pb);
      TSTAMP(7);
#pragma unroll
      for (int r = 0; r < 2; r++) {
#pragma unroll
        for (int g = 0; g < 10; g++)
          xv[r][g] = pack_bf16(bf_lo(xv[r][g]) + acc[4 * g + 2 * r], bf_hi(xv[r][g]) + acc[4 * g + 2 * r + 1]);
      }
      bar_sync(1, 256);
#pragma unroll
      for (int s = 0; s < 5; s++) stsm4(sb + OFF_STG + stg_lane + s * 32, xv[0][2 * s], xv[1][2 * s], xv[0][2 * s + 1], xv[1][2 * s + 1]);
#pragma unroll
      for (int r = 0; r < 2; r++) {
        float s = 0.f;
#pragma unroll
        for (int g = 0; g < 10; g++) {
          acc[4 * g + 2 * r] = bf_lo(xv[r][g]); acc[4 * g + 2 * r + 1] = bf_hi(xv[r][g]);
          s += acc[4 * g + 2 * r] + acc[4 * g + 2 * r + 1];
        }
        s += __shfl_xor_sync(0xffffffffu, s, 1); s += __shfl_xor_sync(0xffffffffu, s, 2);
        const float mu = s * (1.f / 80.f);
        float q = 0.f;
#pragma unroll
        for (int g = 0; g < 10; g++) {
          const float d0 = acc[4 * g + 2 * r] - mu, d1 = acc[4 * g + 2 * r + 1] - mu;
          q = fmaf(d0, d0, q); q = fmaf(d1, d1, q);
        }
        q += __shfl_xor_sync(0xffffffffu, q, 1); q += __shfl_xor_sync(0xffffffffu, q, 2);
        if (t == 0) g_st1[(128 * i + rloc + 8 * r) * 8 + j] = make_float2(mu, q);
      }
      fence_async_smem();
      signal(B_SIGX1);
    }
    TSTAMP(8);
#pragma unroll
    for (int G = 0; G < 10; G++) { P[0][G] = qp[0][G]; P[1][G] = qp[1][G]; }
    }
    asm volatile("" : "+r"(pass));
    } while (pass-- != 0);

    uint32_t of[5][4];
    {
      mbar_wait(bars + 8 * B_KV, 0);
      uint4 kvr[2][3];
#pragma unroll
      for (int u = 0; u < 2; u++) {
        const int it = tid + 256 * u, p = it / 192, rem = it - 192 * p, n = rem >> 2, tq = rem & 3;
        const uint32_t sp = sb + OFF_MISC + 4 * (p * KV_PAIR + (n < 40 ? n * 48 + tq * 12 : 1920 + tq * 24 + (n & 1) * 12));
        if (it < 384) { kvr[u][0] = lds128(sp); kvr[u][1] = lds128(sp + 16); kvr[u][2] = lds128(sp + 32); }
      }
      bar_sync(1, 256);
#pragma unroll
      for (int u = 0; u < 2; u++) {
        const int it = tid + 256 * u, p = it / 192, rem = it - 192 * p, n = rem >> 2, tq = rem & 3;
        const int sh = (n < 40 ? (n >= 20) : (n & 1)) * 16;
        const uint32_t v[10] = {kvr[u][0].x, kvr[u][0].y, kvr[u][0].z, kvr[u][0].w, kvr[u][1].x, kvr[u][1].y, kvr[u][1].z, kvr[u][1].w, kvr[u][2].x, kvr[u][2].y};
        uint8_t* dst = sgen + OFF_MISC + p * 7680 + n * 32 + tq * 4;
        const int sw = ((n >> 2) & 1) << 4;
        if (it < 384) {
#pragma unroll
          for (int G = 0; G < 10; G++)
            *reinterpret_cast<uint32_t*>(dst + (G >> 1) * 1536 + (((G & 1) << 4) ^ sw)) = pack_bf16(__uint_as_float(v[G]), 0.f) << sh;
        }
      }
      fence_async_smem();
      bar_sync(1, 256);
      float o0[24], o1[24];
      wg_fence();
#pragma unroll
      for (int g = 0; g < 5; g++) {
        if (g == 0) mma_rs48_k_z(o0, fr[g], make_desc(sb16, OFF_MISC, 16, 256, 3));
        else mma_rs48_k(o0, fr[g], make_desc(sb16, OFF_MISC + g * 1536, 16, 256, 3));
      }
#pragma unroll
      for (int g = 0; g < 5; g++) {
        if (g == 0) mma_rs48_k_z(o1, fr[5], make_desc(sb16, OFF_MISC + 7680, 16, 256, 3));
        else mma_rs48_k(o1, fr[5 + g], make_desc(sb16, OFF_MISC + 7680 + g * 1536, 16, 256, 3));
      }
      wg_commit();
      wg_wait<0>();
      fence_regs(o0); fence_regs(o1);
      signal(B_MFREE);
#pragma unroll
      for (int r = 0; r < 2; r++) {
        const float a0 = __fdividef(st_g[r], o0[20 + 2 * r] + 1e-6f), a1 = __fdividef(st_g[r], o0[21 + 2 * r] + 1e-6f);
        const float b0 = __fdividef(st_g[r], o1[20 + 2 * r] + 1e-6f), b1 = __fdividef(st_g[r], o1[21 + 2 * r] + 1e-6f);
        const float am = t < 2 ? a0 : a1, bm = t < 2 ? b0 : b1;
#pragma unroll
        for (int g = 0; g < 5; g++) {
          const float sa = g < 2 ? a0 : (g == 2 ? am : a1), sb2 = g < 2 ? b0 : (g == 2 ? bm : b1);
          of[g >> 1][(g & 1) * 2 + r] = pack_bf16(o0[4 * g + 2 * r] * sa, o0[4 * g + 2 * r + 1] * sa);
          of[(5 + g) >> 1][((5 + g) & 1) * 2 + r] = pack_bf16(o1[4 * g + 2 * r] * sb2, o1[4 * g + 2 * r + 1] * sb2);
        }
      }
    }
    TSTAMP(9);

    uint32_t hf[12][4];
    {
      float acc[96];
      zero_regs(acc);
      uint32_t pa = 0, pb = 0;
#pragma unroll 1
      for (int k = 0; k < 10; k++) {
        mbar_wait(fullA + 8 * ra.idx, ra.phase);
        if (tid == 0) TRACE(52 + k);
        if ((k & 1) == 0) mbar_wait(fullB + 8 * rb.idx, rb.phase);
        if (tid == 0) TRACE(84 + k);
        if (k == 0) TSTAMP(10);
        const uint32_t a0 = sb16 + ((OFF_A + ra.idx * SLOT_A + wg * 8192) >> 4);
        const uint32_t b0 = sb16 + ((OFF_B + rb.idx * SLOT_B + (k & 1) * 24576) >> 4);
        wg_fence();
#pragma unroll
        for (int kk = 0; kk < 4; kk++) {
          mma_ss192(acc, make_desc(a0, kk * 32, 16, 1024, 1), make_desc(b0, kk * 2048, 8192, 1024, 1));
          if (kk == 0) {
            wg_commit();
            if (k > 0) {
              wg_wait<1>();
              release(emptyA + 8 * pa);
              if ((k & 1) == 0) releaseB(emptyB + 8 * pb);
            }
          }
        }
        wg_commit();
        pa = ra.idx; pb = rb.idx;
        ra.next<NA>();
        if (k & 1) rb.next<NB>();
      }
      float rs[2], mm[2];
      mbar_wait(bars + 8 * B_ST1, 0);
#pragma unroll
      for (int r = 0; r < 2; r++) {
        const uint4 su = lds128(sb + OFF_MISC + (rloc + 8 * r) * 64 + t * 16);
        const float m0 = __uint_as_float(su.x), m1 = __uint_as_float(su.z);
        float mu = m0 + m1;
        mu += __shfl_xor_sync(0xffffffffu, mu, 1); mu += __shfl_xor_sync(0xffffffffu, mu, 2);
        mu *= 0.125f;
        const float d0 = m0 - mu, d1 = m1 - mu;
        float q = __uint_as_float(su.y) + __uint_as_float(su.w) + 80.f * (d0 * d0 + d1 * d1);
        q += __shfl_xor_sync(0xffffffffu, q, 1); q += __shfl_xor_sync(0xffffffffu, q, 2);
        rs[r] = rsqrtf(q * (1.f / D_) + 1e-5f);
        mm[r] = -mu * rs[r];
      }
      wg_wait<0>();
      fence_regs(acc);
      releaseB(emptyB + 8 * pb);
      release(bars + 8 * B_PEER);
      TSTAMP(11);
      const float hs0 = 0.5f - 0.5f * st_g[0], hs1 = 0.5f - 0.5f * st_g[1];
#pragma unroll
      for (int g = 0; g < 24; g++) {
        const float2 cs = *reinterpret_cast<const float2*>(s_cs + 80 + 8 * g + 2 * t);
        const float v0 = gelu_s(fmaf(acc[4 * g], rs[0], mm[0] * cs.x), hs0), v1 = gelu_s(fmaf(acc[4 * g + 1], rs[0], mm[0] * cs.y), hs0);
        const float v2 = gelu_s(fmaf(acc[4 * g + 2], rs[1], mm[1] * cs.x), hs1), v3 = gelu_s(fmaf(acc[4 * g + 3], rs[1], mm[1] * cs.y), hs1);
        hf[g >> 1][(g & 1) * 2] = pack_bf16(v0, v1);
        hf[g >> 1][(g & 1) * 2 + 1] = pack_bf16(v2, v3);
      }
    }
    TSTAMP(12);

    {
      float acc[80], kp[40];
      const int wt = tid & 127;
      const uint32_t peer = map_peer(sb, rank ^ 1);
      Ring r4{0, 0};
      auto add16 = [&](uint32_t src) {
#pragma unroll
        for (int q = 0; q < 5; q++) {
          const uint4 v = lds128(src + q * 2048);
          float* d = &kp[8 * q];
          d[0] += bf_lo(v.x); d[1] += bf_hi(v.x); d[2] += bf_lo(v.y); d[3] += bf_hi(v.y);
          d[4] += bf_lo(v.z); d[5] += bf_hi(v.z); d[6] += bf_lo(v.w); d[7] += bf_hi(v.w);
        }
      };
      auto finish = [&](int c) {
        if (c > 1) mbar_wait(bars + 8 * (B_SDONE + 2 * (c - 2) + wg), 0);
        mbar_wait(bars + 8 * (B_DSR + 2 * (c - 1) + wg), 0);
        if (tid == 128) TR4((c - 1) * 16 + 3);
        add16(sb + OFF_DS + ((c - 1) & 1) * 20480 + wg * 10240 + wt * 16);
        const uint32_t dst = sb + OFF_SEND + wg * 10240 + wt * 16;
#pragma unroll
        for (int q = 0; q < 5; q++) {
          const float* d = &kp[8 * q];
          sts128(dst + q * 2048, make_uint4(pack_bf16(d[0], d[1]), pack_bf16(d[2], d[3]), pack_bf16(d[4], d[5]), pack_bf16(d[6], d[7])));
        }
        fence_async_smem();
        signal(B_SEND + 2 * (c - 1) + wg);
        if (tid == 128) TR4((c - 1) * 16 + 6);
      };
      zero_regs(kp);
      if (wg == 1) bar_sync(2, 256);
#pragma unroll 1
      for (int c = 0; c < 4; c++) {
        uint32_t prev = 0;
#pragma unroll
        for (int u = 0; u < 4; u++) {
          mbar_wait(bars + 8 * (B_FULL4 + r4.idx), r4.phase);
          const uint32_t b0 = sb16 + ((OFF_B + r4.idx * UNIT4) >> 4);
          if (u == 0 && tid == 128) TR4(c * 16 + 0);
          wg_fence();
#pragma unroll
          for (int s = 0; s < (u < 3 ? 4 : 5); s++) {
            const uint64_t db = make_desc(b0, s * 1024, u < 3 ? 4096 : 5120, 512, 2);
            if (u == 0 && s == 0) mma_rs160_n_z(acc, hf[0], db);
            else if (u < 3) mma_rs160_n(acc, hf[(4 * u + s) % 12], db);
            else mma_rs160_n(acc, of[s], db);
            if (s == 1 && u > 0) { wg_commit(); wg_wait<1>(); releaseB(bars + 8 * (B_EMPTY4 + prev)); }
          }
          wg_commit();
          prev = r4.idx;
          r4.next<NU4>();
          if (u == 1 && c == 0 && wg == 0) bar_arrive(2, 256);
          if (u == 0 && c > 0) finish(c);
          if (u == 2) {
            if (c == 3) {
              const float w0 = 1.f - st_g[0], w1s = 1.f - st_g[1];
#pragma unroll
              for (int g = 0; g < 10; g++) {
                kp[4 * g] = w0 * bf_lo(xv[0][g]); kp[4 * g + 1] = w0 * bf_hi(xv[0][g]);
                kp[4 * g + 2] = w1s * bf_lo(xv[1][g]); kp[4 * g + 3] = w1s * bf_hi(xv[1][g]);
              }
#pragma unroll 1
              for (int e = 0; e < 2; e++) {
                mbar_wait(bars + 8 * (B_RDY + 2 * e + wg), 0);
                add16(sb + (e == 0 ? OFF_G0 : OFF_G1) + wg * 10240 + wt * 16);
              }
            } else {
              zero_regs(kp);
            }
          }
        }
        if (tid == 128) TR4(c * 16 + 2);
        if (c == 0) mbar_wait(bars + 8 * B_PEER, 0);
        wg_wait<0>();
        fence_regs(acc);
        releaseB(bars + 8 * (B_EMPTY4 + prev));
        if (tid == 128) TR4(c * 16 + 5);
        uint32_t sn[20];
        if (rank) {
#pragma unroll
          for (int e = 0; e < 20; e++) sn[e] = pack_bf16(acc[2 * e], acc[2 * e + 1]);
#pragma unroll
          for (int e = 0; e < 40; e++) kp[e] += acc[40 + e];
        } else {
#pragma unroll
          for (int e = 0; e < 20; e++) sn[e] = pack_bf16(acc[40 + 2 * e], acc[41 + 2 * e]);
#pragma unroll
          for (int e = 0; e < 40; e++) kp[e] += acc[e];
        }
        fence_regs(kp);
        const uint32_t dso = peer + OFF_DS + (c & 1) * 20480 + wg * 10240 + wt * 16, dsb = peer + OFF_BAR + 8 * (B_DSR + 2 * c + wg);
#pragma unroll
        for (int q = 0; q < 5; q++) st_async16(dso + q * 2048, sn[4 * q], sn[4 * q + 1], sn[4 * q + 2], sn[4 * q + 3], dsb);
      }
      TSTAMP(13);
#pragma unroll 1
      for (int c = 0; c < 2; c++) {
        mbar_wait(bars + 8 * ((c == 0 ? B_DSR + 6 : B_RDY + 4) + wg), 0);
        add16(sb + (c == 0 ? OFF_DS + 20480 : OFF_SEND) + wg * 10240 + wt * 16);
      }
      TSTAMP(14);
#pragma unroll
      for (int s = 0; s < 5; s++)
        stsm4(sb + OFF_DS + stg_lane + s * 32, pack_bf16(kp[8 * s], kp[8 * s + 1]), pack_bf16(kp[8 * s + 2], kp[8 * s + 3]),
              pack_bf16(kp[8 * s + 4], kp[8 * s + 5]), pack_bf16(kp[8 * s + 6], kp[8 * s + 7]));
      fence_async_smem();
      __syncwarp();
      if (lane == 0) {
        tma2d_store(&maps.st_out, sb + OFF_DS + warp * 2560, 80 * j, 128 * i + 16 * warp);
        bulk_commit(); bulk_wait_read();
      }
    }
    TSTAMP(15);
    if (tid == 0) asm volatile("red.relaxed.gpu.global.add.u32 [%0], 1;" ::"l"(g_flags + FL_DONE * 32) : "memory");
  }
}

namespace {
typedef CUresult (*EncodeFn)(CUtensorMap*, CUtensorMapDataType, cuuint32_t, void*, const cuuint64_t*, const cuuint64_t*,
                             const cuuint32_t*, const cuuint32_t*, CUtensorMapInterleave, CUtensorMapSwizzle,
                             CUtensorMapL2promotion, CUtensorMapFloatOOBfill);

void encode(EncodeFn fn, CUtensorMap* m, const void* ptr, int rank, const cuuint64_t* dims, const cuuint64_t* strides,
            const cuuint32_t* box, CUtensorMapSwizzle swz) {
  cuuint32_t es[5] = {1, 1, 1, 1, 1};
  fn(m, CU_TENSOR_MAP_DATA_TYPE_BFLOAT16, rank, const_cast<void*>(ptr), dims, strides, box, es, CU_TENSOR_MAP_INTERLEAVE_NONE,
     swz, CU_TENSOR_MAP_L2_PROMOTION_L2_128B, CU_TENSOR_MAP_FLOAT_OOB_FILL_NONE);
}
}

extern "C" void kernel_launch(void* const* d_in, const int* in_sizes, int n_in, void* d_out, int out_size) {
  (void)in_sizes; (void)n_in; (void)out_size;
  const __nv_bfloat16* x = (const __nv_bfloat16*)d_in[0];
  const __nv_bfloat16* wqkv = (const __nv_bfloat16*)d_in[1];
  const __nv_bfloat16* wphi = (const __nv_bfloat16*)d_in[2];
  const __nv_bfloat16* wo = (const __nv_bfloat16*)d_in[3];
  const __nv_bfloat16* w1 = (const __nv_bfloat16*)d_in[5];
  const __nv_bfloat16* w2 = (const __nv_bfloat16*)d_in[6];
  const __nv_bfloat16* w3 = (const __nv_bfloat16*)d_in[7];
  const __nv_bfloat16* w4 = (const __nv_bfloat16*)d_in[8];
  const __nv_bfloat16* gate_w = (const __nv_bfloat16*)d_in[9];

  static EncodeFn enc = nullptr;
  static void *pHs = nullptr, *pX1 = nullptr;
  if (!enc) {
    cudaDriverEntryPointQueryResult qr;
    cudaGetDriverEntryPoint("cuTensorMapEncodeTiled", (void**)&enc, cudaEnableDefault, &qr);
    cudaGetSymbolAddress(&pHs, g_Hs);
    cudaGetSymbolAddress(&pX1, g_X1);
    cudaFuncSetAttribute(fused_kernel, cudaFuncAttributeMaxDynamicSharedMemorySize, SMEM_BYTES);
  }
  Maps m;
  {
    cuuint64_t dims[2] = {D_, S_}, str[1] = {D_ * 2};
    cuuint32_t boxh[2] = {64, 64};
    encode(enc, &m.x, x, 2, dims, str, boxh, CU_TENSOR_MAP_SWIZZLE_128B);
    encode(enc, &m.hs, (const char*)pHs + 2 * D_ * 2, 2, dims, str, boxh, CU_TENSOR_MAP_SWIZZLE_128B);
    encode(enc, &m.x1, pX1, 2, dims, str, boxh, CU_TENSOR_MAP_SWIZZLE_128B);
    cuuint32_t boxs[2] = {80, 64};
    cuuint64_t dimsp[2] = {D_, S_ + 4};
    encode(enc, &m.st_h, pHs, 2, dimsp, str, boxs, CU_TENSOR_MAP_SWIZZLE_NONE);
    encode(enc, &m.st_x1, pX1, 2, dims, str, boxs, CU_TENSOR_MAP_SWIZZLE_NONE);
    cuuint32_t boxr[2] = {80, 16};
    encode(enc, &m.st_out, d_out, 2, dims, str, boxr, CU_TENSOR_MAP_SWIZZLE_NONE);
    encode(enc, &m.xr, x, 2, dims, str, boxr, CU_TENSOR_MAP_SWIZZLE_NONE);
  }
  {
    cuuint64_t dims[3] = {80, D_, 8}, str[2] = {D_ * 2, 160};
    cuuint32_t boxm[3] = {64, 64, 1}, boxr[3] = {16, 64, 1};
    encode(enc, &m.w1m, w1, 3, dims, str, boxm, CU_TENSOR_MAP_SWIZZLE_128B);
    encode(enc, &m.w1r, w1, 3, dims, str, boxr, CU_TENSOR_MAP_SWIZZLE_32B);
  }
  {
    cuuint64_t dims[4] = {80, D_, 3, 8}, str[3] = {3 * D_ * 2, D_ * 2, 160};
    cuuint32_t boxm[4] = {64, 64, 3, 1}, boxr[4] = {16, 64, 3, 1};
    encode(enc, &m.qm, wqkv, 4, dims, str, boxm, CU_TENSOR_MAP_SWIZZLE_128B);
    encode(enc, &m.qr, wqkv, 4, dims, str, boxr, CU_TENSOR_MAP_SWIZZLE_32B);
  }
  {
    cuuint64_t dims[3] = {16, D_, 40}, str[2] = {D_ * 2, 32};
    cuuint32_t box2[3] = {16, 64, 5};
    encode(enc, &m.w2, w2, 3, dims, str, box2, CU_TENSOR_MAP_SWIZZLE_32B);
  }
  {
    cuuint64_t dims[3] = {32, D_, 20}, dims4[3] = {32, F_, 20}, str[2] = {D_ * 2, 64};
    cuuint32_t box4[3] = {32, 64, 5}, boxo[3] = {32, 80, 5};
    encode(enc, &m.w4, w4, 3, dims4, str, box4, CU_TENSOR_MAP_SWIZZLE_64B);
    encode(enc, &m.wo, wo, 3, dims, str, boxo, CU_TENSOR_MAP_SWIZZLE_64B);
  }
  {
    cuuint64_t dims[3] = {64, D_, 24}, str[2] = {F_ * 2, 128};
    cuuint32_t box[3] = {64, 64, 3};
    encode(enc, &m.w3, w3, 3, dims, str, box, CU_TENSOR_MAP_SWIZZLE_128B);
  }
  fused_kernel<<<NCTA, 384, SMEM_BYTES, cudaStreamPerThread>>>(m, x, wqkv, wphi, w1, w2, w3, w4, wo, gate_w);
}
```

```cpp
#include <cuda_runtime.h>
#include <cuda_bf16.h>
#include <cuda.h>
#include <stdint.h>

namespace {

constexpr int S_ = 2048, D_ = 640, F_ = 1536;
constexpr int NCTA = 128;
constexpr int KV_PAIR = 40 * 48 + 96;
constexpr int KV_J = 2 * KV_PAIR;

constexpr int SLOT_B = 49152, NB = 3;
constexpr int SLOT_A = 16384, NA = 4;
constexpr int OFF_B = 0;
constexpr int OFF_A = OFF_B + NB * SLOT_B;
constexpr int OFF_STG = OFF_A + 2 * SLOT_A;
constexpr int OFF_MISC = OFF_A + NA * SLOT_A;
constexpr int OFF_XST = OFF_MISC + 13312;
constexpr int OFF_CS = OFF_MISC + 16384;
constexpr int OFF_BAR = OFF_CS + 1088;
constexpr int SMEM_BYTES = OFF_BAR + 512 + 512;
constexpr int B_FULLA = 0, B_FULLB = 4, B_CS = 7, B_XR = 8, B_KV = 9, B_ST1 = 10, B_SDONE = 11  , B_RDY = 17  ,
              B_FULL4 = 23  , B_DSR = 28  , B_SEND = 36  , B_EMPTYB = 42  ,
              B_SIGP = 45, B_SIGH = 46, B_SIGKV = 47, B_SIGX1 = 48, B_MFREE = 49, B_EMPTY4 = 50  ,
              B_EMPTYA = 55  , B_PEER = 59, NBAR = 60;
constexpr int SPARE = 40960;
constexpr int UNIT4 = 25600, NU4 = 5;
constexpr int OFF_DS = OFF_A, OFF_SEND = OFF_A + 40960, OFF_G0 = OFF_A + 61440, OFF_G1 = OFF_B + UNIT4;

constexpr int FL_DONE = 0, FL_H = 1, FL_X1 = FL_H + 16, FL_KV = FL_X1 + 16, FL_CS = FL_KV + 8, FL_CS3 = FL_CS + 8, FL_ST = FL_CS3 + 8, FL_PART = FL_ST + 16;
constexpr int FL_COUNT = FL_PART + 16 * 8;
constexpr int ACC_FLOATS = 8 * KV_J + D_ + F_;

struct Maps {
  CUtensorMap x, w1m, w1r, qm, qr, hs, w2, x1, w3, w4, wo, st_h, st_x1, st_out, xr;
};

}

__device__ __align__(1024) __nv_bfloat16 g_Hs[(S_ + 4) * D_];
__device__ __align__(1024) __nv_bfloat16 g_X1[S_ * D_];
__device__ __align__(128) float g_acc[2][ACC_FLOATS];
__device__ __align__(128) float4 g_xstat[S_];
__device__ __align__(128) float2 g_st1[S_ * 8];
__device__ __align__(128) uint4 g_part[16 * 8 * 3 * 1280];
__device__ __align__(128) unsigned g_flags[FL_COUNT * 32];
#define TSTAMP(n) do {} while (0)
#define TSTAMPX(n) do {} while (0)
#define TRACE(n) do {} while (0)
#define TRS(n) do {} while (0)

namespace {

__device__ __forceinline__ long long gtime() { long long t; asm volatile("mov.u64 %0, %%globaltimer;" : "=l"(t)); return t; }
__device__ __forceinline__ uint32_t smem_u32(const void* p) { return (uint32_t)__cvta_generic_to_shared(p); }
__device__ __forceinline__ void mbar_init(uint32_t bar, int cnt) {
  asm volatile("mbarrier.init.shared::cta.b64 [%0], %1;" ::"r"(bar), "r"(cnt) : "memory");
}
__device__ __forceinline__ void mbar_expect_tx(uint32_t bar, int bytes) {
  asm volatile("mbarrier.arrive.expect_tx.shared::cta.b64 _, [%0], %1;" ::"r"(bar), "r"(bytes) : "memory");
}
__device__ __forceinline__ void mbar_arrive_cta(uint32_t bar, uint32_t cta) {
  asm volatile("{\n.reg .b32 ra;\nmapa.shared::cluster.u32 ra, %0, %1;\nmbarrier.arrive.shared::cluster.b64 _, [ra];\n}"
               ::"r"(bar), "r"(cta) : "memory");
}
__device__ __forceinline__ uint32_t mbar_try(uint32_t bar, uint32_t parity) {
  uint32_t ok;
  asm volatile("{\n.reg .pred p;\nmbarrier.try_wait.parity.shared::cta.b64 p, [%1], %2;\nselp.u32 %0, 1, 0, p;\n}"
               : "=r"(ok) : "r"(bar), "r"(parity) : "memory");
  return ok;
}
constexpr uint32_t WAIT_LIMIT = 1u << 22;
__device__ __forceinline__ void mbar_wait(uint32_t bar, uint32_t parity) {
  uint32_t n = 0;
  while (!mbar_try(bar, parity) && ++n < WAIT_LIMIT) {}
}
__device__ __forceinline__ unsigned ld_acquire(const unsigned* p) {
  unsigned v;
  asm volatile("ld.acquire.gpu.global.u32 %0, [%1];" : "=r"(v) : "l"(p) : "memory");
  return v;
}
__device__ __forceinline__ void flag_wait(int idx, unsigned target) {
  const unsigned* p = g_flags + idx * 32;
  uint32_t n = 0;
  while ((int)(ld_acquire(p) - target) < 0 && ++n < (WAIT_LIMIT >> 4)) {}
}
__device__ __forceinline__ void flag_add(int idx) {
  asm volatile("red.release.gpu.global.add.u32 [%0], 1;" ::"l"(g_flags + idx * 32) : "memory");
}
__device__ __forceinline__ void flag_add_relaxed(int idx) {
  asm volatile("red.relaxed.gpu.global.add.u32 [%0], 1;" ::"l"(g_flags + idx * 32) : "memory");
}
__device__ __forceinline__ uint32_t mbar_test(uint32_t bar, uint32_t parity) {
  uint32_t ok;
  asm volatile("{\n.reg .pred p;\nmbarrier.test_wait.parity.shared::cta.b64 p, [%1], %2;\nselp.u32 %0, 1, 0, p;\n}"
               : "=r"(ok) : "r"(bar), "r"(parity) : "memory");
  return ok;
}
__device__ __forceinline__ uint32_t lds32(uint32_t a) {
  uint32_t v;
  asm volatile("ld.shared.u32 %0, [%1];" : "=r"(v) : "r"(a) : "memory");
  return v;
}
__device__ __forceinline__ void mbar_arrive(uint32_t bar) {
  asm volatile("mbarrier.arrive.shared::cta.b64 _, [%0];" ::"r"(bar) : "memory");
}
__device__ __forceinline__ void fence_async_all() { asm volatile("fence.proxy.async;" ::: "memory"); }
__device__ __forceinline__ void fence_async_smem() { asm volatile("fence.proxy.async.shared::cta;" ::: "memory"); }
__device__ __forceinline__ void bar_sync(int id, int n) { asm volatile("bar.sync %0, %1;" ::"r"(id), "r"(n) : "memory"); }

__device__ __forceinline__ void tma2d(uint32_t dst, const CUtensorMap* m, uint32_t bar, int c0, int c1) {
  asm volatile("cp.async.bulk.tensor.2d.shared::cluster.global.mbarrier::complete_tx::bytes [%0], [%1, {%3, %4}], [%2];"
               ::"r"(dst), "l"(m), "r"(bar), "r"(c0), "r"(c1) : "memory");
}
__device__ __forceinline__ void tma2d_mc(uint32_t dst, const CUtensorMap* m, uint32_t bar, int c0, int c1) {
  asm volatile("cp.async.bulk.tensor.2d.shared::cluster.global.mbarrier::complete_tx::bytes.multicast::cluster"
               " [%0], [%1, {%3, %4}], [%2], %5;"
               ::"r"(dst), "l"(m), "r"(bar), "r"(c0), "r"(c1), "h"((uint16_t)3) : "memory");
}
__device__ __forceinline__ void tma3d(uint32_t dst, const CUtensorMap* m, uint32_t bar, int c0, int c1, int c2) {
  asm volatile("cp.async.bulk.tensor.3d.shared::cluster.global.mbarrier::complete_tx::bytes [%0], [%1, {%3, %4, %5}], [%2];"
               ::"r"(dst), "l"(m), "r"(bar), "r"(c0), "r"(c1), "r"(c2) : "memory");
}
__device__ __forceinline__ void tma4d(uint32_t dst, const CUtensorMap* m, uint32_t bar, int c0, int c1, int c2, int c3) {
  asm volatile("cp.async.bulk.tensor.4d.shared::cluster.global.mbarrier::complete_tx::bytes [%0], [%1, {%3, %4, %5, %6}], [%2];"
               ::"r"(dst), "l"(m), "r"(bar), "r"(c0), "r"(c1), "r"(c2), "r"(c3) : "memory");
}
__device__ __forceinline__ void tma2d_store(const CUtensorMap* m, uint32_t src, int c0, int c1) {
  asm volatile("cp.async.bulk.tensor.2d.global.shared::cta.bulk_group [%0, {%2, %3}], [%1];"
               ::"l"(m), "r"(src), "r"(c0), "r"(c1) : "memory");
}
__device__ __forceinline__ void bulk_store(void* dst, uint32_t src, uint32_t bytes) {
  asm volatile("cp.async.bulk.global.shared::cta.bulk_group [%0], [%1], %2;" ::"l"(dst), "r"(src), "r"(bytes) : "memory");
}
__device__ __forceinline__ void bulk_load(uint32_t dst, const void* src, uint32_t bytes, uint32_t bar) {
  asm volatile("cp.async.bulk.shared::cluster.global.mbarrier::complete_tx::bytes [%0], [%1], %2, [%3];"
               ::"r"(dst), "l"(src), "r"(bytes), "r"(bar) : "memory");
}
__device__ __forceinline__ void bulk_commit() { asm volatile("cp.async.bulk.commit_group;" ::: "memory"); }
template <int N> __device__ __forceinline__ void bulk_wait() { asm volatile("cp.async.bulk.wait_group %0;" ::"n"(N) : "memory"); }
__device__ __forceinline__ void bulk_wait_read() { asm volatile("cp.async.bulk.wait_group.read 0;" ::: "memory"); }
__device__ __forceinline__ void bar_arrive(int id, int n) { asm volatile("bar.arrive %0, %1;" ::"r"(id), "r"(n) : "memory"); }
__device__ __forceinline__ uint4 lds128(uint32_t a) {
  uint4 v;
  asm volatile("ld.shared.v4.u32 {%0, %1, %2, %3}, [%4];" : "=r"(v.x), "=r"(v.y), "=r"(v.z), "=r"(v.w) : "r"(a) : "memory");
  return v;
}
__device__ __forceinline__ void sts128(uint32_t a, uint4 v) {
  asm volatile("st.shared.v4.u32 [%0], {%1, %2, %3, %4};" ::"r"(a), "r"(v.x), "r"(v.y), "r"(v.z), "r"(v.w) : "memory");
}
__device__ __forceinline__ uint32_t map_peer(uint32_t addr, uint32_t cta) {
  uint32_t r;
  asm("mapa.shared::cluster.u32 %0, %1, %2;" : "=r"(r) : "r"(addr), "r"(cta));
  return r;
}
__device__ __forceinline__ void st_async16(uint32_t addr, uint32_t a, uint32_t b, uint32_t c, uint32_t d, uint32_t bar) {
  asm volatile("st.async.weak.shared::cluster.mbarrier::complete_tx::bytes.v4.b32 [%0], {%1, %2, %3, %4}, [%5];"
               ::"r"(addr), "r"(a), "r"(b), "r"(c), "r"(d), "r"(bar) : "memory");
}
__device__ __forceinline__ void l2_prefetch(const void* p, uint32_t bytes) {
  asm volatile("cp.async.bulk.prefetch.L2.global [%0], %1;" ::"l"(p), "r"(bytes) : "memory");
}
__device__ __forceinline__ void prefetch_tmap(const CUtensorMap* m) {
  asm volatile("prefetch.tensormap [%0];" ::"l"(m) : "memory");
}
__device__ __forceinline__ uint64_t make_desc(uint32_t a16, uint32_t off, uint32_t lbo, uint32_t sbo, uint32_t swz) {
  const uint32_t lo = a16 + ((off >> 4) + ((lbo >> 4) << 16)), hi = (sbo >> 4) | (swz << 30);
  uint64_t d;
  asm("mov.b64 %0, {%1, %2};" : "=l"(d) : "r"(lo), "r"(hi));
  return d;
}
__device__ __forceinline__ void wg_fence() { asm volatile("wgmma.fence.sync.aligned;" ::: "memory"); }
__device__ __forceinline__ void wg_commit() { asm volatile("wgmma.commit_group.sync.aligned;" ::: "memory"); }
template <int N> __device__ __forceinline__ void wg_wait() { asm volatile("wgmma.wait_group.sync.aligned %0;" ::"n"(N) : "memory"); }
template <int N> __device__ __forceinline__ void fence_regs(float (&d)[N]) {
#pragma unroll
  for (int i = 0; i < N; i++) asm volatile("" : "+f"(d[i])::"memory");
}
template <int N> __device__ __forceinline__ void zero_regs(float (&d)[N]) {
#pragma unroll
  for (int i = 0; i < N; i++) d[i] = 0.f;
}
__device__ __forceinline__ uint32_t pack_bf16(float lo, float hi) {
  uint32_t r;
  asm("cvt.rn.bf16x2.f32 %0, %1, %2;" : "=r"(r) : "f"(hi), "f"(lo));
  return r;
}
__device__ __forceinline__ float bf_lo(uint32_t v) { return __uint_as_float(v << 16); }
__device__ __forceinline__ float bf_hi(uint32_t v) { return __uint_as_float(v & 0xffff0000u); }
__device__ __forceinline__ uint32_t max_bf2(uint32_t a, uint32_t b) {
  uint32_t r; asm("max.bf16x2 %0, %1, %2;" : "=r"(r) : "r"(a), "r"(b)); return r;
}
__device__ __forceinline__ uint32_t min_bf2(uint32_t a, uint32_t b) {
  uint32_t r; asm("min.bf16x2 %0, %1, %2;" : "=r"(r) : "r"(a), "r"(b)); return r;
}
__device__ __forceinline__ uint32_t add_bf2(uint32_t a, uint32_t b) {
  uint32_t r; asm("add.rn.bf16x2 %0, %1, %2;" : "=r"(r) : "r"(a), "r"(b)); return r;
}
__device__ __forceinline__ float ex2(float x) { float r; asm("ex2.approx.ftz.f32 %0, %1;" : "=f"(r) : "f"(x)); return r; }
__device__ __forceinline__ float rcp(float x) { float r; asm("rcp.approx.ftz.f32 %0, %1;" : "=f"(r) : "f"(x)); return r; }
__device__ __forceinline__ float tanh_ap(float x) { float r; asm("tanh.approx.f32 %0, %1;" : "=f"(r) : "f"(x)); return r; }
__device__ __forceinline__ float gelu_s(float x, float hs) {
  float u = x * fmaf(x * x, 0.0356774081f, 0.7978845608f);
  float hx = x * hs;
  return fmaf(hx, tanh_ap(u), hx);
}
__device__ __forceinline__ void stsm4(uint32_t addr, uint32_t r0, uint32_t r1, uint32_t r2, uint32_t r3) {
  asm volatile("stmatrix.sync.aligned.m8n8.x4.shared.b16 [%0], {%1, %2, %3, %4};"
               ::"r"(addr), "r"(r0), "r"(r1), "r"(r2), "r"(r3) : "memory");
}
__device__ __forceinline__ void red_add4(float* p, float a, float b, float c, float d) {
  asm volatile("red.global.add.v4.f32 [%0], {%1, %2, %3, %4};" ::"l"(p), "f"(a), "f"(b), "f"(c), "f"(d) : "memory");
}

__device__ __forceinline__ void mma_ss256(float (&d)[128], uint64_t descA, uint64_t descB) {
  asm volatile("wgmma.mma_async.sync.aligned.m64n256k16.f32.bf16.bf16 {"
      "%0, %1, %2, %3, %4, %5, %6, %7, %8, %9, %10, %11, %12, %13, %14, %15, "
      "%16, %17, %18, %19, %20, %21, %22, %23, %24, %25, %26, %27, %28, %29, %30, %31, "
      "%32, %33, %34, %35, %36, %37, %38, %39, %40, %41, %42, %43, %44, %45, %46, %47, "
      "%48, %49, %50, %51, %52, %53, %54, %55, %56, %57, %58, %59, %60, %61, %62, %63, "
      "%64, %65, %66, %67, %68, %69, %70, %71, %72, %73, %74, %75, %76, %77, %78, %79, "
      "%80, %81, %82, %83, %84, %85, %86, %87, %88, %89, %90, %91, %92, %93, %94, %95, "
      "%96, %97, %98, %99, %100, %101, %102, %103, %104, %105, %106, %107, %108, %109, %110, %111, "
      "%112, %113, %114, %115, %116, %117, %118, %119, %120, %121, %122, %123, %124, %125, %126, %127"
      "}, %128, %129, 1, 1, 1, 0, 1;\n"
      : "+f"(d[0]), "+f"(d[1]), "+f"(d[2]), "+f"(d[3]), "+f"(d[4]), "+f"(d[5]), "+f"(d[6]), "+f"(d[7]),
        "+f"(d[8]), "+f"(d[9]), "+f"(d[10]), "+f"(d[11]), "+f"(d[12]), "+f"(d[13]), "+f"(d[14]), "+f"(d[15]),
        "+f"(d[16]), "+f"(d[17]), "+f"(d[18]), "+f"(d[19]), "+f"(d[20]), "+f"(d[21]), "+f"(d[22]), "+f"(d[23]),
        "+f"(d[24]), "+f"(d[25]), "+f"(d[26]), "+f"(d[27]), "+f"(d[28]), "+f"(d[29]), "+f"(d[30]), "+f"(d[31]),
        "+f"(d[32]), "+f"(d[33]), "+f"(d[34]), "+f"(d[35]), "+f"(d[36]), "+f"(d[37]), "+f"(d[38]), "+f"(d[39]),
        "+f"(d[40]), "+f"(d[41]), "+f"(d[42]), "+f"(d[43]), "+f"(d[44]), "+f"(d[45]), "+f"(d[46]), "+f"(d[47]),
        "+f"(d[48]), "+f"(d[49]), "+f"(d[50]), "+f"(d[51]), "+f"(d[52]), "+f"(d[53]), "+f"(d[54]), "+f"(d[55]),
        "+f"(d[56]), "+f"(d[57]), "+f"(d[58]), "+f"(d[59]), "+f"(d[60]), "+f"(d[61]), "+f"(d[62]), "+f"(d[63]),
        "+f"(d[64]), "+f"(d[65]), "+f"(d[66]), "+f"(d[67]), "+f"(d[68]), "+f"(d[69]), "+f"(d[70]), "+f"(d[71]),
        "+f"(d[72]), "+f"(d[73]), "+f"(d[74]), "+f"(d[75]), "+f"(d[76]), "+f"(d[77]), "+f"(d[78]), "+f"(d[79]),
        "+f"(d[80]), "+f"(d[81]), "+f"(d[82]), "+f"(d[83]), "+f"(d[84]), "+f"(d[85]), "+f"(d[86]), "+f"(d[87]),
        "+f"(d[88]), "+f"(d[89]), "+f"(d[90]), "+f"(d[91]), "+f"(d[92]), "+f"(d[93]), "+f"(d[94]), "+f"(d[95]),
        "+f"(d[96]), "+f"(d[97]), "+f"(d[98]), "+f"(d[99]), "+f"(d[100]), "+f"(d[101]), "+f"(d[102]), "+f"(d[103]),
        "+f"(d[104]), "+f"(d[105]), "+f"(d[106]), "+f"(d[107]), "+f"(d[108]), "+f"(d[109]), "+f"(d[110]), "+f"(d[111]),
        "+f"(d[112]), "+f"(d[113]), "+f"(d[114]), "+f"(d[115]), "+f"(d[116]), "+f"(d[117]), "+f"(d[118]), "+f"(d[119]),
        "+f"(d[120]), "+f"(d[121]), "+f"(d[122]), "+f"(d[123]), "+f"(d[124]), "+f"(d[125]), "+f"(d[126]), "+f"(d[127])
      : "l"(descA), "l"(descB));
}

__device__ __forceinline__ void mma_ss64(float (&d)[32], uint64_t descA, uint64_t descB) {
  asm volatile("wgmma.mma_async.sync.aligned.m64n64k16.f32.bf16.bf16 {"
      "%0, %1, %2, %3, %4, %5, %6, %7, %8, %9, %10, %11, %12, %13, %14, %15, "
      "%16, %17, %18, %19, %20, %21, %22, %23, %24, %25, %26, %27, %28, %29, %30, %31"
      "}, %32, %33, 1, 1, 1, 0, 1;\n"
      : "+f"(d[0]), "+f"(d[1]), "+f"(d[2]), "+f"(d[3]), "+f"(d[4]), "+f"(d[5]), "+f"(d[6]), "+f"(d[7]),
        "+f"(d[8]), "+f"(d[9]), "+f"(d[10]), "+f"(d[11]), "+f"(d[12]), "+f"(d[13]), "+f"(d[14]), "+f"(d[15]),
        "+f"(d[16]), "+f"(d[17]), "+f"(d[18]), "+f"(d[19]), "+f"(d[20]), "+f"(d[21]), "+f"(d[22]), "+f"(d[23]),
        "+f"(d[24]), "+f"(d[25]), "+f"(d[26]), "+f"(d[27]), "+f"(d[28]), "+f"(d[29]), "+f"(d[30]), "+f"(d[31])
      : "l"(descA), "l"(descB));
}

__device__ __forceinline__ void mma_ss80(float (&d)[40], uint64_t descA, uint64_t descB) {
  asm volatile("wgmma.mma_async.sync.aligned.m64n80k16.f32.bf16.bf16 {"
      "%0, %1, %2, %3, %4, %5, %6, %7, %8, %9, %10, %11, %12, %13, %14, %15, "
      "%16, %17, %18, %19, %20, %21, %22, %23, %24, %25, %26, %27, %28, %29, %30, %31, "
      "%32, %33, %34, %35, %36, %37, %38, %39"
      "}, %40, %41, 1, 1, 1, 0, 1;\n"
      : "+f"(d[0]), "+f"(d[1]), "+f"(d[2]), "+f"(d[3]), "+f"(d[4]), "+f"(d[5]), "+f"(d[6]), "+f"(d[7]),
        "+f"(d[8]), "+f"(d[9]), "+f"(d[10]), "+f"(d[11]), "+f"(d[12]), "+f"(d[13]), "+f"(d[14]), "+f"(d[15]),
        "+f"(d[16]), "+f"(d[17]), "+f"(d[18]), "+f"(d[19]), "+f"(d[20]), "+f"(d[21]), "+f"(d[22]), "+f"(d[23]),
        "+f"(d[24]), "+f"(d[25]), "+f"(d[26]), "+f"(d[27]), "+f"(d[28]), "+f"(d[29]), "+f"(d[30]), "+f"(d[31]),
        "+f"(d[32]), "+f"(d[33]), "+f"(d[34]), "+f"(d[35]), "+f"(d[36]), "+f"(d[37]), "+f"(d[38]), "+f"(d[39])
      : "l"(descA), "l"(descB));
}

__device__ __forceinline__ void mma_ss192(float (&d)[96], uint64_t descA, uint64_t descB) {
  asm volatile("wgmma.mma_async.sync.aligned.m64n192k16.f32.bf16.bf16 {"
      "%0, %1, %2, %3, %4, %5, %6, %7, %8, %9, %10, %11, %12, %13, %14, %15, "
      "%16, %17, %18, %19, %20, %21, %22, %23, %24, %25, %26, %27, %28, %29, %30, %31, "
      "%32, %33, %34, %35, %36, %37, %38, %39, %40, %41, %42, %43, %44, %45, %46, %47, "
      "%48, %49, %50, %51, %52, %53, %54, %55, %56, %57, %58, %59, %60, %61, %62, %63, "
      "%64, %65, %66, %67, %68, %69, %70, %71, %72, %73, %74, %75, %76, %77, %78, %79, "
      "%80, %81, %82, %83, %84, %85, %86, %87, %88, %89, %90, %91, %92, %93, %94, %95"
      "}, %96, %97, 1, 1, 1, 0, 1;\n"
      : "+f"(d[0]), "+f"(d[1]), "+f"(d[2]), "+f"(d[3]), "+f"(d[4]), "+f"(d[5]), "+f"(d[6]), "+f"(d[7]),
        "+f"(d[8]), "+f"(d[9]), "+f"(d[10]), "+f"(d[11]), "+f"(d[12]), "+f"(d[13]), "+f"(d[14]), "+f"(d[15]),
        "+f"(d[16]), "+f"(d[17]), "+f"(d[18]), "+f"(d[19]), "+f"(d[20]), "+f"(d[21]), "+f"(d[22]), "+f"(d[23]),
        "+f"(d[24]), "+f"(d[25]), "+f"(d[26]), "+f"(d[27]), "+f"(d[28]), "+f"(d[29]), "+f"(d[30]), "+f"(d[31]),
        "+f"(d[32]), "+f"(d[33]), "+f"(d[34]), "+f"(d[35]), "+f"(d[36]), "+f"(d[37]), "+f"(d[38]), "+f"(d[39]),
        "+f"(d[40]), "+f"(d[41]), "+f"(d[42]), "+f"(d[43]), "+f"(d[44]), "+f"(d[45]), "+f"(d[46]), "+f"(d[47]),
        "+f"(d[48]), "+f"(d[49]), "+f"(d[50]), "+f"(d[51]), "+f"(d[52]), "+f"(d[53]), "+f"(d[54]), "+f"(d[55]),
        "+f"(d[56]), "+f"(d[57]), "+f"(d[58]), "+f"(d[59]), "+f"(d[60]), "+f"(d[61]), "+f"(d[62]), "+f"(d[63]),
        "+f"(d[64]), "+f"(d[65]), "+f"(d[66]), "+f"(d[67]), "+f"(d[68]), "+f"(d[69]), "+f"(d[70]), "+f"(d[71]),
        "+f"(d[72]), "+f"(d[73]), "+f"(d[74]), "+f"(d[75]), "+f"(d[76]), "+f"(d[77]), "+f"(d[78]), "+f"(d[79]),
        "+f"(d[80]), "+f"(d[81]), "+f"(d[82]), "+f"(d[83]), "+f"(d[84]), "+f"(d[85]), "+f"(d[86]), "+f"(d[87]),
        "+f"(d[88]), "+f"(d[89]), "+f"(d[90]), "+f"(d[91]), "+f"(d[92]), "+f"(d[93]), "+f"(d[94]), "+f"(d[95])
      : "l"(descA), "l"(descB));
}

__device__ __forceinline__ void mma_ss80_tt(float (&d)[40], uint64_t descA, uint64_t descB) {
  asm volatile("wgmma.mma_async.sync.aligned.m64n80k16.f32.bf16.bf16 {"
      "%0, %1, %2, %3, %4, %5, %6, %7, %8, %9, %10, %11, %12, %13, %14, %15, "
      "%16, %17, %18, %19, %20, %21, %22, %23, %24, %25, %26, %27, %28, %29, %30, %31, "
      "%32, %33, %34, %35, %36, %37, %38, %39"
      "}, %40, %41, 1, 1, 1, 1, 1;\n"
      : "+f"(d[0]), "+f"(d[1]), "+f"(d[2]), "+f"(d[3]), "+f"(d[4]), "+f"(d[5]), "+f"(d[6]), "+f"(d[7]),
        "+f"(d[8]), "+f"(d[9]), "+f"(d[10]), "+f"(d[11]), "+f"(d[12]), "+f"(d[13]), "+f"(d[14]), "+f"(d[15]),
        "+f"(d[16]), "+f"(d[17]), "+f"(d[18]), "+f"(d[19]), "+f"(d[20]), "+f"(d[21]), "+f"(d[22]), "+f"(d[23]),
        "+f"(d[24]), "+f"(d[25]), "+f"(d[26]), "+f"(d[27]), "+f"(d[28]), "+f"(d[29]), "+f"(d[30]), "+f"(d[31]),
        "+f"(d[32]), "+f"(d[33]), "+f"(d[34]), "+f"(d[35]), "+f"(d[36]), "+f"(d[37]), "+f"(d[38]), "+f"(d[39])
      : "l"(descA), "l"(descB));
}
__device__ __forceinline__ void mma_ss80_tt_z(float (&d)[40], uint64_t descA, uint64_t descB) {
  asm volatile("wgmma.mma_async.sync.aligned.m64n80k16.f32.bf16.bf16 {"
      "%0, %1, %2, %3, %4, %5, %6, %7, %8, %9, %10, %11, %12, %13, %14, %15, "
      "%16, %17, %18, %19, %20, %21, %22, %23, %24, %25, %26, %27, %28, %29, %30, %31, "
      "%32, %33, %34, %35, %36, %37, %38, %39"
      "}, %40, %41, 0, 1, 1, 1, 1;\n"
      : "=f"(d[0]), "=f"(d[1]), "=f"(d[2]), "=f"(d[3]), "=f"(d[4]), "=f"(d[5]), "=f"(d[6]), "=f"(d[7]),
        "=f"(d[8]), "=f"(d[9]), "=f"(d[10]), "=f"(d[11]), "=f"(d[12]), "=f"(d[13]), "=f"(d[14]), "=f"(d[15]),
        "=f"(d[16]), "=f"(d[17]), "=f"(d[18]), "=f"(d[19]), "=f"(d[20]), "=f"(d[21]), "=f"(d[22]), "=f"(d[23]),
        "=f"(d[24]), "=f"(d[25]), "=f"(d[26]), "=f"(d[27]), "=f"(d[28]), "=f"(d[29]), "=f"(d[30]), "=f"(d[31]),
        "=f"(d[32]), "=f"(d[33]), "=f"(d[34]), "=f"(d[35]), "=f"(d[36]), "=f"(d[37]), "=f"(d[38]), "=f"(d[39])
      : "l"(descA), "l"(descB));
}

__device__ __forceinline__ void mma_rs80_k(float (&d)[40], const uint32_t (&a)[4], uint64_t descB) {
  asm volatile("wgmma.mma_async.sync.aligned.m64n80k16.f32.bf16.bf16 {"
      "%0, %1, %2, %3, %4, %5, %6, %7, %8, %9, %10, %11, %12, %13, %14, %15, "
      "%16, %17, %18, %19, %20, %21, %22, %23, %24, %25, %26, %27, %28, %29, %30, %31, "
      "%32, %33, %34, %35, %36, %37, %38, %39"
      "}, {%40, %41, %42, %43}, %44, 1, 1, 1, 0;\n"
      : "+f"(d[0]), "+f"(d[1]), "+f"(d[2]), "+f"(d[3]), "+f"(d[4]), "+f"(d[5]), "+f"(d[6]), "+f"(d[7]),
        "+f"(d[8]), "+f"(d[9]), "+f"(d[10]), "+f"(d[11]), "+f"(d[12]), "+f"(d[13]), "+f"(d[14]), "+f"(d[15]),
        "+f"(d[16]), "+f"(d[17]), "+f"(d[18]), "+f"(d[19]), "+f"(d[20]), "+f"(d[21]), "+f"(d[22]), "+f"(d[23]),
        "+f"(d[24]), "+f"(d[25]), "+f"(d[26]), "+f"(d[27]), "+f"(d[28]), "+f"(d[29]), "+f"(d[30]), "+f"(d[31]),
        "+f"(d[32]), "+f"(d[33]), "+f"(d[34]), "+f"(d[35]), "+f"(d[36]), "+f"(d[37]), "+f"(d[38]), "+f"(d[39])
      : "r"(a[0]), "r"(a[1]), "r"(a[2]), "r"(a[3]), "l"(descB));
}
__device__ __forceinline__ void mma_rs80_k_z(float (&d)[40], const uint32_t (&a)[4], uint64_t descB) {
  asm volatile("wgmma.mma_async.sync.aligned.m64n80k16.f32.bf16.bf16 {"
      "%0, %1, %2, %3, %4, %5, %6, %7, %8, %9, %10, %11, %12, %13, %14, %15, "
      "%16, %17, %18, %19, %20, %21, %22, %23, %24, %25, %26, %27, %28, %29, %30, %31, "
      "%32, %33, %34, %35, %36, %37, %38, %39"
      "}, {%40, %41, %42, %43}, %44, 0, 1, 1, 0;\n"
      : "=f"(d[0]), "=f"(d[1]), "=f"(d[2]), "=f"(d[3]), "=f"(d[4]), "=f"(d[5]), "=f"(d[6]), "=f"(d[7]),
        "=f"(d[8]), "=f"(d[9]), "=f"(d[10]), "=f"(d[11]), "=f"(d[12]), "=f"(d[13]), "=f"(d[14]), "=f"(d[15]),
        "=f"(d[16]), "=f"(d[17]), "=f"(d[18]), "=f"(d[19]), "=f"(d[20]), "=f"(d[21]), "=f"(d[22]), "=f"(d[23]),
        "=f"(d[24]), "=f"(d[25]), "=f"(d[26]), "=f"(d[27]), "=f"(d[28]), "=f"(d[29]), "=f"(d[30]), "=f"(d[31]),
        "=f"(d[32]), "=f"(d[33]), "=f"(d[34]), "=f"(d[35]), "=f"(d[36]), "=f"(d[37]), "=f"(d[38]), "=f"(d[39])
      : "r"(a[0]), "r"(a[1]), "r"(a[2]), "r"(a[3]), "l"(descB));
}

__device__ __forceinline__ void mma_rs48_k(float (&d)[24], const uint32_t (&a)[4], uint64_t descB) {
  asm volatile("wgmma.mma_async.sync.aligned.m64n48k16.f32.bf16.bf16 {"
      "%0, %1, %2, %3, %4, %5, %6, %7, %8, %9, %10, %11, %12, %13, %14, %15, "
      "%16, %17, %18, %19, %20, %21, %22, %23"
      "}, {%24, %25, %26, %27}, %28, 1, 1, 1, 0;\n"
      : "+f"(d[0]), "+f"(d[1]), "+f"(d[2]), "+f"(d[3]), "+f"(d[4]), "+f"(d[5]), "+f"(d[6]), "+f"(d[7]),
        "+f"(d[8]), "+f"(d[9]), "+f"(d[10]), "+f"(d[11]), "+f"(d[12]), "+f"(d[13]), "+f"(d[14]), "+f"(d[15]),
        "+f"(d[16]), "+f"(d[17]), "+f"(d[18]), "+f"(d[19]), "+f"(d[20]), "+f"(d[21]), "+f"(d[22]), "+f"(d[23])
      : "r"(a[0]), "r"(a[1]), "r"(a[2]), "r"(a[3]), "l"(descB));
}
__device__ __forceinline__ void mma_rs48_k_z(float (&d)[24], const uint32_t (&a)[4], uint64_t descB) {
  asm volatile("wgmma.mma_async.sync.aligned.m64n48k16.f32.bf16.bf16 {"
      "%0, %1, %2, %3, %4, %5, %6, %7, %8, %9, %10, %11, %12, %13, %14, %15, "
      "%16, %17, %18, %19, %20, %21, %22, %23"
      "}, {%24, %25, %26, %27}, %28, 0, 1, 1, 0;\n"
      : "=f"(d[0]), "=f"(d[1]), "=f"(d[2]), "=f"(d[3]), "=f"(d[4]), "=f"(d[5]), "=f"(d[6]), "=f"(d[7]),
        "=f"(d[8]), "=f"(d[9]), "=f"(d[10]), "=f"(d[11]), "=f"(d[12]), "=f"(d[13]), "=f"(d[14]), "=f"(d[15]),
        "=f"(d[16]), "=f"(d[17]), "=f"(d[18]), "=f"(d[19]), "=f"(d[20]), "=f"(d[21]), "=f"(d[22]), "=f"(d[23])
      : "r"(a[0]), "r"(a[1]), "r"(a[2]), "r"(a[3]), "l"(descB));
}

__device__ __forceinline__ void mma_rs160_n(float (&d)[80], const uint32_t (&a)[4], uint64_t descB) {
  asm volatile("wgmma.mma_async.sync.aligned.m64n160k16.f32.bf16.bf16 {"
      "%0, %1, %2, %3, %4, %5, %6, %7, %8, %9, %10, %11, %12, %13, %14, %15, "
      "%16, %17, %18, %19, %20, %21, %22, %23, %24, %25, %26, %27, %28, %29, %30, %31, "
      "%32, %33, %34, %35, %36, %37, %38, %39, %40, %41, %42, %43, %44, %45, %46, %47, "
      "%48, %49, %50, %51, %52, %53, %54, %55, %56, %57, %58, %59, %60, %61, %62, %63, "
      "%64, %65, %66, %67, %68, %69, %70, %71, %72, %73, %74, %75, %76, %77, %78, %79"
      "}, {%80, %81, %82, %83}, %84, 1, 1, 1, 1;\n"
      : "+f"(d[0]), "+f"(d[1]), "+f"(d[2]), "+f"(d[3]), "+f"(d[4]), "+f"(d[5]), "+f"(d[6]), "+f"(d[7]),
        "+f"(d[8]), "+f"(d[9]), "+f"(d[10]), "+f"(d[11]), "+f"(d[12]), "+f"(d[13]), "+f"(d[14]), "+f"(d[15]),
        "+f"(d[16]), "+f"(d[17]), "+f"(d[18]), "+f"(d[19]), "+f"(d[20]), "+f"(d[21]), "+f"(d[22]), "+f"(d[23]),
        "+f"(d[24]), "+f"(d[25]), "+f"(d[26]), "+f"(d[27]), "+f"(d[28]), "+f"(d[29]), "+f"(d[30]), "+f"(d[31]),
        "+f"(d[32]), "+f"(d[33]), "+f"(d[34]), "+f"(d[35]), "+f"(d[36]), "+f"(d[37]), "+f"(d[38]), "+f"(d[39]),
        "+f"(d[40]), "+f"(d[41]), "+f"(d[42]), "+f"(d[43]), "+f"(d[44]), "+f"(d[45]), "+f"(d[46]), "+f"(d[47]),
        "+f"(d[48]), "+f"(d[49]), "+f"(d[50]), "+f"(d[51]), "+f"(d[52]), "+f"(d[53]), "+f"(d[54]), "+f"(d[55]),
        "+f"(d[56]), "+f"(d[57]), "+f"(d[58]), "+f"(d[59]), "+f"(d[60]), "+f"(d[61]), "+f"(d[62]), "+f"(d[63]),
        "+f"(d[64]), "+f"(d[65]), "+f"(d[66]), "+f"(d[67]), "+f"(d[68]), "+f"(d[69]), "+f"(d[70]), "+f"(d[71]),
        "+f"(d[72]), "+f"(d[73]), "+f"(d[74]), "+f"(d[75]), "+f"(d[76]), "+f"(d[77]), "+f"(d[78]), "+f"(d[79])
      : "r"(a[0]), "r"(a[1]), "r"(a[2]), "r"(a[3]), "l"(descB));
}
__device__ __forceinline__ void mma_rs160_n_z(float (&d)[80], const uint32_t (&a)[4], uint64_t descB) {
  asm volatile("wgmma.mma_async.sync.aligned.m64n160k16.f32.bf16.bf16 {"
      "%0, %1, %2, %3, %4, %5, %6, %7, %8, %9, %10, %11, %12, %13, %14, %15, "
      "%16, %17, %18, %19, %20, %21, %22, %23, %24, %25, %26, %27, %28, %29, %30, %31, "
      "%32, %33, %34, %35, %36, %37, %38, %39, %40, %41, %42, %43, %44, %45, %46, %47, "
      "%48, %49, %50, %51, %52, %53, %54, %55, %56, %57, %58, %59, %60, %61, %62, %63, "
      "%64, %65, %66, %67, %68, %69, %70, %71, %72, %73, %74, %75, %76, %77, %78, %79"
      "}, {%80, %81, %82, %83}, %84, 0, 1, 1, 1;\n"
      : "=f"(d[0]), "=f"(d[1]), "=f"(d[2]), "=f"(d[3]), "=f"(d[4]), "=f"(d[5]), "=f"(d[6]), "=f"(d[7]),
        "=f"(d[8]), "=f"(d[9]), "=f"(d[10]), "=f"(d[11]), "=f"(d[12]), "=f"(d[13]), "=f"(d[14]), "=f"(d[15]),
        "=f"(d[16]), "=f"(d[17]), "=f"(d[18]), "=f"(d[19]), "=f"(d[20]), "=f"(d[21]), "=f"(d[22]), "=f"(d[23]),
        "=f"(d[24]), "=f"(d[25]), "=f"(d[26]), "=f"(d[27]), "=f"(d[28]), "=f"(d[29]), "=f"(d[30]), "=f"(d[31]),
        "=f"(d[32]), "=f"(d[33]), "=f"(d[34]), "=f"(d[35]), "=f"(d[36]), "=f"(d[37]), "=f"(d[38]), "=f"(d[39]),
        "=f"(d[40]), "=f"(d[41]), "=f"(d[42]), "=f"(d[43]), "=f"(d[44]), "=f"(d[45]), "=f"(d[46]), "=f"(d[47]),
        "=f"(d[48]), "=f"(d[49]), "=f"(d[50]), "=f"(d[51]), "=f"(d[52]), "=f"(d[53]), "=f"(d[54]), "=f"(d[55]),
        "=f"(d[56]), "=f"(d[57]), "=f"(d[58]), "=f"(d[59]), "=f"(d[60]), "=f"(d[61]), "=f"(d[62]), "=f"(d[63]),
        "=f"(d[64]), "=f"(d[65]), "=f"(d[66]), "=f"(d[67]), "=f"(d[68]), "=f"(d[69]), "=f"(d[70]), "=f"(d[71]),
        "=f"(d[72]), "=f"(d[73]), "=f"(d[74]), "=f"(d[75]), "=f"(d[76]), "=f"(d[77]), "=f"(d[78]), "=f"(d[79])
      : "r"(a[0]), "r"(a[1]), "r"(a[2]), "r"(a[3]), "l"(descB));
}

__device__ __forceinline__ void feature_map(const uint32_t (&P)[2][10], uint32_t (&fr)[10][4]) {
  constexpr float L2E = 1.4426950408889634f;
#pragma unroll
  for (int p = 0; p < 2; p++) {
#pragma unroll
    for (int r = 0; r < 2; r++) {
      uint32_t mx = P[r][5 * p], mn = mx;
#pragma unroll
      for (int g = 1; g < 5; g++) { mx = max_bf2(mx, P[r][5 * p + g]); mn = min_bf2(mn, P[r][5 * p + g]); }
      mx = max_bf2(mx, __shfl_xor_sync(0xffffffffu, mx, 1));
      mn = min_bf2(mn, __shfl_xor_sync(0xffffffffu, mn, 1));
      mx = max_bf2(mx, __shfl_xor_sync(0xffffffffu, mx, 2));
      mn = min_bf2(mn, __shfl_xor_sync(0xffffffffu, mn, 2));
      float mx0 = -bf_lo(mx) * L2E, mx1 = -bf_hi(mx) * L2E, mn0 = bf_lo(mn) * L2E, mn1 = bf_hi(mn) * L2E;
      float ep0[5], ep1[5], en0[5], en1[5];
      float sp0 = 0.f, sp1 = 0.f, sn0 = 0.f, sn1 = 0.f;
#pragma unroll
      for (int g = 0; g < 5; g++) {
        float x0 = bf_lo(P[r][5 * p + g]), x1 = bf_hi(P[r][5 * p + g]);
        ep0[g] = ex2(fmaf(x0, L2E, mx0)); ep1[g] = ex2(fmaf(x1, L2E, mx1));
        en0[g] = ex2(fmaf(x0, -L2E, mn0)); en1[g] = ex2(fmaf(x1, -L2E, mn1));
        sp0 += ep0[g]; sp1 += ep1[g]; sn0 += en0[g]; sn1 += en1[g];
      }
      sp0 += __shfl_xor_sync(0xffffffffu, sp0, 1); sp1 += __shfl_xor_sync(0xffffffffu, sp1, 1);
      sn0 += __shfl_xor_sync(0xffffffffu, sn0, 1); sn1 += __shfl_xor_sync(0xffffffffu, sn1, 1);
      sp0 += __shfl_xor_sync(0xffffffffu, sp0, 2); sp1 += __shfl_xor_sync(0xffffffffu, sp1, 2);
      sn0 += __shfl_xor_sync(0xffffffffu, sn0, 2); sn1 += __shfl_xor_sync(0xffffffffu, sn1, 2);
      sp0 = rcp(sp0); sp1 = rcp(sp1); sn0 = rcp(sn0); sn1 = rcp(sn1);
#pragma unroll
      for (int g = 0; g < 5; g++) {
        fr[5 * p + g][r] = pack_bf16(ep0[g] * sp0, ep1[g] * sp1);
        fr[5 * p + g][2 + r] = pack_bf16(en0[g] * sn0, en1[g] * sn1);
      }
    }
  }
}

template <bool V> struct BoolC { static constexpr bool value = V; };
struct Ring {
  uint32_t idx, phase;
  template <int N> __device__ __forceinline__ void next() { if (++idx == N) { idx = 0; phase ^= 1; } }
};

}

__global__ void __cluster_dims__(2, 1, 1) __launch_bounds__(384, 1)
fused_kernel(const __grid_constant__ Maps maps, const __nv_bfloat16* __restrict__ x, const __nv_bfloat16* __restrict__ wqkv,
             const __nv_bfloat16* __restrict__ wphi, const __nv_bfloat16* __restrict__ w1, const __nv_bfloat16* __restrict__ w2,
             const __nv_bfloat16* __restrict__ w3, const __nv_bfloat16* __restrict__ w4, const __nv_bfloat16* __restrict__ wo,
             const __nv_bfloat16* __restrict__ gate_w) {
  extern __shared__ __align__(1024) uint8_t sgen[];
  const uint32_t sb = smem_u32(sgen);
  const uint32_t sb16 = (sb & 0x3FFFFu) >> 4;
  const uint32_t bars = sb + OFF_BAR;
  const uint32_t fullA = bars + 8 * B_FULLA, emptyA = bars + 8 * B_EMPTYA, fullB = bars + 8 * B_FULLB, emptyB = bars + 8 * B_EMPTYB;

  const int tid = threadIdx.x;
  const int rank = blockIdx.x & 1;
  const int pairIdx = blockIdx.x >> 1;
  const int i = pairIdx >> 2, j = 2 * (pairIdx & 3) + rank;

  TSTAMP(0);
  auto load_p1_b = [&](int k, uint32_t slot, uint32_t bar) {
    mbar_expect_tx(bar, 40960);
    tma4d(slot + 8192, &maps.qm, bar, 0, 64 * k, 0, j);
    tma3d(slot, &maps.w1m, bar, 0, 64 * k, j);
    tma4d(slot + 32768 + 2048, &maps.qr, bar, 64, 64 * k, 0, j);
    tma3d(slot + 32768, &maps.w1r, bar, 64, 64 * k, j);
  };
  if (tid >= 256) {
    asm volatile("setmaxnreg.dec.sync.aligned.u32 40;");
    if (tid == 256) {
#pragma unroll
      for (int s = 0; s < NA; s++) mbar_init(fullA + 8 * s, 1);
      asm volatile("fence.mbarrier_init.release.cluster;" ::: "memory");
#pragma unroll 1
      for (int u = 0; u < 4; u++) {
        if ((u & 1) == 0) mbar_expect_tx(fullA + 4 * u, SLOT_A);
        tma2d(sb + OFF_A + u * 8192, &maps.x, fullA + 8 * (u >> 1), 64 * (u >> 1), 128 * i + 64 * (u & 1));
      }
    } else if (tid == 288) {
#pragma unroll
      for (int s = 0; s < NB; s++) mbar_init(fullB + 8 * s, 1);
      asm volatile("fence.mbarrier_init.release.cluster;" ::: "memory");
#pragma unroll 1
      for (int k = 0; k < 2; k++) load_p1_b(k, sb + OFF_B + k * SLOT_B, fullB + 8 * k);
    } else if (tid == 320) {
#pragma unroll
      for (int b = B_CS; b < NBAR; b++) mbar_init(bars + 8 * b, b < B_SEND ? 1 : b < B_EMPTYB ? 4 : b < B_EMPTYA ? 8 : 16);
#pragma unroll
      for (int b = B_DSR; b < B_SEND; b++) mbar_expect_tx(bars + 8 * b, 10240);
      asm volatile("fence.mbarrier_init.release.cluster;" ::: "memory");
    }
    __syncwarp();
    asm volatile("barrier.cluster.arrive.relaxed.aligned;" ::: "memory");
    auto get_epoch = [&]() { return *reinterpret_cast<volatile unsigned*>(g_flags + FL_DONE * 32) / NCTA; };
    if (tid >= 320) {
      const int lane = tid & 31, ch = lane % 10, rg = lane / 10;
      const __nv_bfloat16* p = w1 + (size_t)(40 * i + (tid >= 352 ? 20 : 0) + rg) * D_ + 80 * j + 8 * ch;
      const unsigned par = get_epoch() & 1;
      float a[8];
#pragma unroll
      for (int e = 0; e < 8; e++) a[e] = 0.f;
#pragma unroll
      for (int it = 0; it < 7; it++) {
        uint4 v = make_uint4(0, 0, 0, 0);
        if (lane < 30 && 3 * it + rg < 20) v = __ldg(reinterpret_cast<const uint4*>(p + (size_t)it * 3 * D_));
        a[0] += bf_lo(v.x); a[1] += bf_hi(v.x); a[2] += bf_lo(v.y); a[3] += bf_hi(v.y);
        a[4] += bf_lo(v.z); a[5] += bf_hi(v.z); a[6] += bf_lo(v.w); a[7] += bf_hi(v.w);
      }
#pragma unroll
      for (int e = 0; e < 8; e++) a[e] += __shfl_down_sync(0xffffffffu, a[e], 10) + __shfl_down_sync(0xffffffffu, a[e], 20);
      if (lane < 10) {
        float* cd = g_acc[par] + 8 * KV_J + 80 * j + 8 * ch;
        red_add4(cd, a[0], a[1], a[2], a[3]); red_add4(cd + 4, a[4], a[5], a[6], a[7]);
      }
      __syncwarp();
      if (lane == 0) flag_add(FL_CS + j);
      __syncwarp();
    }
    asm volatile("barrier.cluster.wait.aligned;" ::: "memory");
    const int lane = tid & 31, pw = (tid >> 5) & 3;
    auto send_stream = [&](int w, unsigned ep1) {
#pragma unroll 1
      for (int c = 0; c < 3; c++) {
        const int d = (j + 2 * c + 2) & 7;
        mbar_wait(bars + 8 * (B_SEND + 2 * c + w), 0);
        bulk_store(g_part + (size_t)((i * 8 + d) * 3 + c) * 1280 + w * 640, sb + OFF_SEND + w * 10240, 10240);
        bulk_commit();
        bulk_wait<0>();
        mbar_arrive(bars + 8 * (B_SDONE + 2 * c + w));
        asm volatile("st.release.gpu.global.u32 [%0], %1;"
                     ::"l"(g_flags + (FL_PART + i * 8 + d) * 32 + 2 * c + w), "r"(ep1) : "memory");
      }
    };
    if (pw == 0) {
      if (tid == 256) {
        Ring r{2, 1};
        unsigned ep1 = 0;
#pragma unroll 1
        for (int k = 2; k < 30; k++) {
          if (k == 4) ep1 = get_epoch() + 1;
          if (k == 10 || k == 20) {
            const unsigned tgt = ep1 * 8u;
            const unsigned* f0 = g_flags + (k == 10 ? FL_H + ((i - 1) & 15) : FL_X1 + i) * 32;
            const unsigned* f1 = g_flags + (k == 10 ? FL_H + i : FL_X1 + i) * 32;
            const unsigned* f2 = g_flags + (k == 10 ? FL_H + ((i + 1) & 15) : FL_X1 + i) * 32;
            uint32_t n = 0;
            while (++n < (WAIT_LIMIT >> 4)) {
              unsigned v0, v1, v2;
              asm volatile("ld.relaxed.gpu.global.u32 %0, [%3];\nld.relaxed.gpu.global.u32 %1, [%4];\nld.acquire.gpu.global.u32 %2, [%5];"
                           : "=r"(v0), "=r"(v1), "=r"(v2) : "l"(f0), "l"(f1), "l"(f2) : "memory");
              if ((int)((v0 - tgt) | (v1 - tgt) | (v2 - tgt)) >= 0) break;
            }
            TSTAMPX(k == 10 ? 29 : 30);
          }
          mbar_wait(emptyA + 8 * r.idx, r.phase);
          const uint32_t bar = fullA + 8 * r.idx, slot = sb + OFF_A + r.idx * SLOT_A;
          TRACE(k);
          mbar_expect_tx(bar, SLOT_A);
          tma2d_mc(slot + rank * 8192, k < 10 ? &maps.x : k < 20 ? &maps.hs : &maps.x1, bar, 64 * (k % 10), 128 * i + 64 * rank);
          r.next<NA>();
        }
        send_stream(1, ep1);
      }
    } else if (pw == 1) {
      if (tid == 288) {
        Ring r{2, 1};
#pragma unroll 1
        for (int k = 2; k < 18; k++) {
          mbar_wait(emptyB + 8 * r.idx, r.phase);
          const uint32_t bar = fullB + 8 * r.idx, slot = sb + OFF_B + r.idx * SLOT_B;
          if (k < 10) {
            load_p1_b(k, slot, bar);
          } else if (k < 13) {
            if (k == 12) mbar_wait(fullA + 8 * 2, 0);
            mbar_expect_tx(bar, k < 12 ? 40960 : 20480);
#pragma unroll 1
            for (int u = 0; u < (k < 12 ? 4 : 2); u++) tma3d(slot + u * 10240, &maps.w2, bar, 0, 256 * (k - 10) + 64 * u, 5 * j);
          } else {
            mbar_expect_tx(bar, 49152);
            tma3d(slot, &maps.w3, bar, 0, 128 * (k - 13), 3 * j);
            tma3d(slot + 24576, &maps.w3, bar, 0, 128 * (k - 13) + 64, 3 * j);
          }
          r.next<NB>();
        }
        Ring r4{0, 1};
#pragma unroll 1
        for (int n = 0; n < 16; n++) {
          if (n == 0 || n == 1 || n == 3) { mbar_wait(emptyB + 8 * r.idx, r.phase); r.next<NB>(); }
          mbar_wait(bars + 8 * (B_EMPTY4 + r4.idx), r4.phase);
          const uint32_t bar = bars + 8 * (B_FULL4 + r4.idx), slot = sb + OFF_B + r4.idx * UNIT4;
          const int u = n & 3, m = ((j >> 1) + 1 + (n >> 2)) & 3;
          mbar_expect_tx(bar, u == 3 ? 25600 : 20480);
          tma3d(slot, u == 3 ? &maps.wo : &maps.w4, bar, 0, u == 3 ? 80 * j : 192 * j + 64 * u, 5 * m);
          r4.next<NU4>();
        }
      }
    } else {
      const unsigned epoch = get_epoch();
      float* accg = g_acc[epoch & 1];
      if (pw == 2) {
        {
          float* nxt = g_acc[(epoch + 1) & 1];
          constexpr int PER = ACC_FLOATS / NCTA;
#pragma unroll 1
          for (int e = lane; e < PER; e += 32) nxt[blockIdx.x * PER + e] = 0.f;
        }
        if (tid == 320) {
          flag_wait(FL_CS + j, (epoch + 1) * 32u);
          flag_wait(FL_ST + i, (epoch + 1) * 8u);
          fence_async_all();
          mbar_expect_tx(bars + 8 * B_CS, 320 + 2048);
          bulk_load(sb + OFF_CS, accg + 8 * KV_J + 80 * j, 320, bars + 8 * B_CS);
          bulk_load(sb + OFF_XST, g_xstat + 128 * i, 2048, bars + 8 * B_CS);
          TSTAMPX(21);
          l2_prefetch(w2 + (size_t)blockIdx.x * (D_ * D_ / NCTA), D_ * D_ * 2 / NCTA);
          flag_wait(FL_H + i, (epoch + 1) * 8u);
          l2_prefetch(w3 + (size_t)blockIdx.x * (F_ * D_ / NCTA), F_ * D_ * 2 / NCTA);
          l2_prefetch(w4 + (size_t)blockIdx.x * (F_ * D_ / NCTA), F_ * D_ * 2 / NCTA);
          l2_prefetch(wo + (size_t)blockIdx.x * (D_ * D_ / NCTA), D_ * D_ * 2 / NCTA);
          flag_wait(FL_KV + j, (epoch + 1) * 16u);
          mbar_expect_tx(bars + 8 * B_KV, KV_J * 4);
          bulk_load(sb + OFF_MISC, accg + j * KV_J, KV_J * 4, bars + 8 * B_KV);
          TSTAMPX(22);
        }
        __syncwarp();
#pragma unroll 1
        for (int m = 0; m < 6; m++) {
          const int col = 192 * j + 32 * m + 8 * (lane & 3);
          const __nv_bfloat16* p = w3 + (size_t)(40 * i + (lane >> 2) * 5) * F_ + col;
          float a[8];
#pragma unroll
          for (int e = 0; e < 8; e++) a[e] = 0.f;
#pragma unroll
          for (int it = 0; it < 5; it++) {
            const uint4 v = __ldg(reinterpret_cast<const uint4*>(p + (size_t)it * F_));
            a[0] += bf_lo(v.x); a[1] += bf_hi(v.x); a[2] += bf_lo(v.y); a[3] += bf_hi(v.y);
            a[4] += bf_lo(v.z); a[5] += bf_hi(v.z); a[6] += bf_lo(v.w); a[7] += bf_hi(v.w);
          }
#pragma unroll
          for (int e = 0; e < 4; e++) {
            const float snd = (lane & 4) ? a[e] : a[e + 4], keep = (lane & 4) ? a[e + 4] : a[e];
            a[e] = keep + __shfl_xor_sync(0xffffffffu, snd, 4);
            a[e] += __shfl_xor_sync(0xffffffffu, a[e], 8);
            a[e] += __shfl_xor_sync(0xffffffffu, a[e], 16);
          }
          if (lane < 8) red_add4(accg + 8 * KV_J + D_ + col + (lane >> 2) * 4, a[0], a[1], a[2], a[3]);
        }
        __syncwarp();
        if (tid == 320) {
          flag_add(FL_CS3 + j);
          mbar_wait(bars + 8 * B_MFREE, 0);
          flag_wait(FL_X1 + i, (epoch + 1) * 8u);
          flag_wait(FL_CS3 + j, (epoch + 1) * 16u);
          fence_async_all();
          mbar_expect_tx(bars + 8 * B_ST1, 8192 + 768);
          bulk_load(sb + OFF_CS + 320, accg + 8 * KV_J + D_ + 192 * j, 768, bars + 8 * B_ST1);
          bulk_load(sb + OFF_MISC, g_st1 + 128 * i * 8, 8192, bars + 8 * B_ST1);
        }
        __syncwarp();
        mbar_wait(bars + 8 * B_PEER, 0);
        const unsigned* fp = g_flags + (FL_PART + i * 8 + j) * 32 + lane;
        bool seen = lane >= 6;
        uint32_t n = 0;
        while (!__all_sync(0xffffffffu, seen) && ++n < (WAIT_LIMIT >> 4)) {
          if (!seen && ld_acquire(fp) == epoch + 1 && (lane < 2 || (lane < 4 ? mbar_test(bars + 8 * (B_SEND + 2), 0) && mbar_test(bars + 8 * (B_SEND + 3), 0) && mbar_test(bars + 8 * (B_EMPTY4 + 1), 0) : mbar_test(bars + 8 * (B_SDONE + lane), 0)))) {
            seen = true;
            mbar_expect_tx(bars + 8 * (B_RDY + lane), 10240);
            bulk_load(sb + (lane < 2 ? OFF_G0 : lane < 4 ? OFF_G1 : OFF_SEND) + (lane & 1) * 10240, g_part + (size_t)(i * 8 + j) * 3840 + lane * 640, 10240,
                      bars + 8 * (B_RDY + lane));
          }
        }
      }
      if (tid == 352) {
        mbar_wait(bars + 8 * B_SIGP, 0);
        flag_add(FL_ST + i);
        TSTAMPX(20);
        mbar_expect_tx(bars + 8 * B_XR, 20480);
#pragma unroll 1
        for (int u = 0; u < 8; u++)
          tma2d(sb + OFF_B + (u / 3) * SLOT_B + SPARE + (u % 3) * 2560, &maps.xr, bars + 8 * B_XR, 80 * j, 128 * i + 16 * u);
        const int shift = (j < 2) ? 1 : (j < 4) ? -1 : (j < 6) ? 2 : -2;
        if ((shift > 0 && i == 0) || (shift < 0 && i == 15)) {
          const int nz = shift > 0 ? shift : -shift, zr = shift > 0 ? 0 : S_ - nz;
#pragma unroll 1
          for (int e = 0; e < nz * 10; e++)
            reinterpret_cast<uint4*>(g_Hs + (size_t)(2 + zr + e / 10) * D_ + 80 * j)[e % 10] = make_uint4(0, 0, 0, 0);
          fence_async_all();
        }
        prefetch_tmap(&maps.st_h); prefetch_tmap(&maps.st_x1); prefetch_tmap(&maps.hs); prefetch_tmap(&maps.x1); prefetch_tmap(&maps.xr);
        prefetch_tmap(&maps.w2); prefetch_tmap(&maps.w3); prefetch_tmap(&maps.w4); prefetch_tmap(&maps.wo); prefetch_tmap(&maps.st_out);
        mbar_wait(bars + 8 * B_SIGH, 0);
        TSTAMPX(23);
        tma2d_store(&maps.st_h, sb + OFF_STG, 80 * j, 128 * i + 2 + shift);
        tma2d_store(&maps.st_h, sb + OFF_STG + 10240, 80 * j, 128 * i + 66 + shift);
        bulk_commit(); bulk_wait<0>();
        flag_add(FL_H + i);
        TSTAMPX(24);
        mbar_wait(bars + 8 * B_SIGKV, 0);
        TSTAMPX(25);
        asm volatile("cp.reduce.async.bulk.global.shared::cta.bulk_group.add.f32 [%0], [%1], %2;"
                     ::"l"(accg + j * KV_J), "r"(sb + OFF_MISC), "r"(KV_J * 4) : "memory");
        bulk_commit(); bulk_wait<0>();
        flag_add(FL_KV + j);
        TSTAMPX(26);
        mbar_wait(bars + 8 * B_SIGX1, 0);
        TSTAMPX(27);
        tma2d_store(&maps.st_x1, sb + OFF_STG, 80 * j, 128 * i);
        tma2d_store(&maps.st_x1, sb + OFF_STG + 10240, 80 * j, 128 * i + 64);
        bulk_commit(); bulk_wait<0>();
        flag_add(FL_X1 + i);
        TSTAMPX(28);
        send_stream(0, epoch + 1);
      }
    }
  } else {
    uint4 pv[5], pw_[5], pre;
    {
      const int row = 128 * i + 16 * j + (tid >> 4), l16 = tid & 15;
#pragma unroll
      for (int c = 0; c < 5; c++) pv[c] = __ldg(reinterpret_cast<const uint4*>(x + (size_t)row * D_ + c * 128 + l16 * 8));
      pre = __ldg(reinterpret_cast<const uint4*>(wphi + (size_t)j * 1600) + (tid < 200 ? tid : 0));
#pragma unroll
      for (int c = 0; c < 5; c++) pw_[c] = __ldg(reinterpret_cast<const uint4*>(gate_w + c * 128 + l16 * 8));
    }
    asm volatile("barrier.cluster.arrive.relaxed.aligned;" ::: "memory");
    asm volatile("setmaxnreg.inc.sync.aligned.u32 232;");
    const int wg = tid >> 7, warp = tid >> 5, lane = tid & 31, t = lane & 3;
    const int rloc = warp * 16 + (lane >> 2);
    const float* s_cs = reinterpret_cast<const float*>(sgen + OFF_CS);
    auto signal = [&](int b) {
      __syncwarp();
      if (lane == 0) mbar_arrive(bars + 8 * b);
    };
    auto releaseB = [&](uint32_t bar) {
      __syncwarp();
      if (lane == 0) mbar_arrive(bar);
    };
    auto release = [&](uint32_t bar) {
      __syncwarp();
      if (lane < 2) mbar_arrive_cta(bar, lane);
    };
    const uint32_t stg_lane = (warp * 16 + ((lane >> 3) & 1) * 8 + (lane & 7)) * 160 + (lane >> 4) * 16;

    {
#pragma unroll 1
      for (int e = tid; e < 800; e += 256) sts128(sb + OFF_MISC + e * 16, make_uint4(0, 0, 0, 0));
      bar_sync(1, 256);
      float f[40];
      float s = 0.f, gs = 0.f;
#pragma unroll
      for (int c = 0; c < 5; c++) {
        const uint32_t vv[4] = {pv[c].x, pv[c].y, pv[c].z, pv[c].w}, ww[4] = {pw_[c].x, pw_[c].y, pw_[c].z, pw_[c].w};
#pragma unroll
        for (int e = 0; e < 4; e++) {
          f[8 * c + 2 * e] = bf_lo(vv[e]); f[8 * c + 2 * e + 1] = bf_hi(vv[e]);
          s += f[8 * c + 2 * e] + f[8 * c + 2 * e + 1];
          gs = fmaf(f[8 * c + 2 * e], bf_lo(ww[e]), gs); gs = fmaf(f[8 * c + 2 * e + 1], bf_hi(ww[e]), gs);
        }
      }
#pragma unroll
      for (int o = 1; o < 16; o <<= 1) { s += __shfl_xor_sync(0xffffffffu, s, o); gs += __shfl_xor_sync(0xffffffffu, gs, o); }
      const float mean = s * (1.f / D_);
      float q = 0.f;
#pragma unroll
      for (int e = 0; e < 40; e++) { const float d = f[e] - mean; q = fmaf(d, d, q); }
#pragma unroll
      for (int o = 1; o < 16; o <<= 1) q += __shfl_xor_sync(0xffffffffu, q, o);
      const float rstd = rsqrtf(q * (1.f / D_) + 1e-5f);
      asm volatile("barrier.cluster.wait.aligned;" ::: "memory");
      if ((tid & 15) == 0) g_xstat[128 * i + 16 * j + (tid >> 4)] = make_float4(rstd, -mean * rstd, rcp(1.f + __expf(-gs)), 0.f);
      signal(B_SIGP);
      if (tid < 200) {
        const uint32_t ww[4] = {pre.x, pre.y, pre.z, pre.w};
        const int h = tid / 50;
#pragma unroll
        for (int e = 0; e < 8; e++) {
          const int idx = tid * 8 + e, k = idx / 20, ff = idx - 20 * k;
          const int n = 40 * (h >> 1) + 8 * (ff >> 2) + 2 * (ff & 3) + (h & 1);
          const int off = (k >> 4) * 2560 + n * 32 + ((((k >> 3) ^ (n >> 2)) & 1) << 4) + (k & 7) * 2;
          *reinterpret_cast<unsigned short*>(sgen + OFF_MISC + off) = (unsigned short)(ww[e >> 1] >> ((e & 1) * 16));
        }
      }
    }
    TSTAMP(1);

    Ring ra{0, 0}, rb{0, 0};
    uint32_t qp[2][10], P[2][10];
    float st_g[2];
    {
      float accM[128], accR[32];
      zero_regs(accM); zero_regs(accR);
      uint32_t pa = 0, pb = 0;
#pragma unroll 1
      for (int k = 0; k < 10; k++) {
        mbar_wait(fullA + 8 * ra.idx, ra.phase);
        if (tid == 0) TRACE(32 + k);
        mbar_wait(fullB + 8 * rb.idx, rb.phase);
        if (tid == 0) TRACE(64 + k);
        if (k == 0) TSTAMP(2);
        const uint32_t a0 = sb16 + ((OFF_A + ra.idx * SLOT_A + wg * 8192) >> 4), b0 = sb16 + ((OFF_B + rb.idx * SLOT_B) >> 4);
        wg_fence();
#pragma unroll
        for (int kk = 0; kk < 4; kk++) {
          const uint64_t da = make_desc(a0, kk * 32, 16, 1024, 1);
          mma_ss256(accM, da, make_desc(b0, kk * 2048, 8192, 1024, 1));
          mma_ss64(accR, da, make_desc(b0, 32768 + kk * 512, 2048, 256, 3));
          if (kk == 0) {
            wg_commit();
            if (k > 0) {
              wg_wait<1>();
              if (k - 1 < 8) release(emptyA + 8 * pa);
              releaseB(emptyB + 8 * pb);
            }
          }
        }
        wg_commit();
        pa = ra.idx; pb = rb.idx;
        ra.next<NA>(); rb.next<NB>();
      }
      TSTAMP(18);
      float st_rstd[2], st_mr[2];
      mbar_wait(bars + 8 * B_CS, 0);
#pragma unroll
      for (int r = 0; r < 2; r++) {
        const uint4 st = lds128(sb + OFF_XST + (rloc + 8 * r) * 16);
        st_rstd[r] = __uint_as_float(st.x); st_mr[r] = __uint_as_float(st.y); st_g[r] = __uint_as_float(st.z);
      }
      TSTAMP(19);
      wg_wait<0>();
      fence_regs(accM); fence_regs(accR);
      TSTAMP(3);
#define ACC(P_, G, I_) ((G) < 8 ? accM[(P_) * 32 + ((G) & 7) * 4 + (I_)] : accR[(P_) * 8 + ((G) & 1) * 4 + (I_)])
      {
        uint32_t hv[10][2];
#pragma unroll
        for (int g = 0; g < 10; g++) {
          const float2 cs = *reinterpret_cast<const float2*>(s_cs + 8 * g + 2 * t);
          const float v0 = gelu_s(fmaf(ACC(0, g, 0), st_rstd[0], st_mr[0] * cs.x), 0.5f), v1 = gelu_s(fmaf(ACC(0, g, 1), st_rstd[0], st_mr[0] * cs.y), 0.5f);
          const float v2 = gelu_s(fmaf(ACC(0, g, 2), st_rstd[1], st_mr[1] * cs.x), 0.5f), v3 = gelu_s(fmaf(ACC(0, g, 3), st_rstd[1], st_mr[1] * cs.y), 0.5f);
          hv[g][0] = pack_bf16(v0, v1); hv[g][1] = pack_bf16(v2, v3);
        }
        fence_async_smem();
        bar_sync(1, 256);
#pragma unroll
        for (int s = 0; s < 5; s++) stsm4(sb + OFF_STG + stg_lane + s * 32, hv[2 * s][0], hv[2 * s][1], hv[2 * s + 1][0], hv[2 * s + 1][1]);
        fence_async_smem();
        signal(B_SIGH);
      }
      TSTAMP(4);
      uint32_t kf[5][4], qf[5][4];
#pragma unroll
      for (int s = 0; s < 5; s++) {
        kf[s][0] = pack_bf16(ACC(2, 2 * s, 0), ACC(2, 2 * s, 1)); kf[s][1] = pack_bf16(ACC(2, 2 * s, 2), ACC(2, 2 * s, 3));
        kf[s][2] = pack_bf16(ACC(2, 2 * s + 1, 0), ACC(2, 2 * s + 1, 1)); kf[s][3] = pack_bf16(ACC(2, 2 * s + 1, 2), ACC(2, 2 * s + 1, 3));
        qf[s][0] = pack_bf16(ACC(1, 2 * s, 0), ACC(1, 2 * s, 1)); qf[s][1] = pack_bf16(ACC(1, 2 * s, 2), ACC(1, 2 * s, 3));
        qf[s][2] = pack_bf16(ACC(1, 2 * s + 1, 0), ACC(1, 2 * s + 1, 1)); qf[s][3] = pack_bf16(ACC(1, 2 * s + 1, 2), ACC(1, 2 * s + 1, 3));
      }
      float pk[40], pq[40];
      wg_fence();
#pragma unroll
      for (int s = 0; s < 5; s++) {
        if (s == 0) mma_rs80_k_z(pk, kf[s], make_desc(sb16, OFF_MISC, 16, 256, 3));
        else mma_rs80_k(pk, kf[s], make_desc(sb16, OFF_MISC + s * 2560, 16, 256, 3));
      }
#pragma unroll
      for (int s = 0; s < 5; s++) {
        if (s == 0) mma_rs80_k_z(pq, qf[s], make_desc(sb16, OFF_MISC, 16, 256, 3));
        else mma_rs80_k(pq, qf[s], make_desc(sb16, OFF_MISC + s * 2560, 16, 256, 3));
      }
      wg_commit();
      {
        const int mat = lane >> 3;
        const int tok = warp * 16 + (mat & 1) * 8 + (lane & 7);
        const uint32_t ones = (t == 0) ? 0x00003f80u : 0u;
        __syncwarp();
#pragma unroll
        for (int p = 0; p < 2; p++) {
          const uint32_t rowa = sb + OFF_A + p * SLOT_A + tok * 128;
#pragma unroll
          for (int gg = 0; gg < 3; gg++) {
            const int g0 = 5 * p + 2 * gg;
            uint32_t r0 = pack_bf16(ACC(3, g0, 0), ACC(3, g0, 1)), r1 = pack_bf16(ACC(3, g0, 2), ACC(3, g0, 3));
            uint32_t r2 = ones, r3 = ones;
            if (gg < 2) { r2 = pack_bf16(ACC(3, g0 + 1, 0), ACC(3, g0 + 1, 1)); r3 = pack_bf16(ACC(3, g0 + 1, 2), ACC(3, g0 + 1, 3)); }
            stsm4(rowa + (((2 * gg + (mat >> 1)) ^ (tok & 7)) << 4), r0, r1, r2, r3);
          }
        }
      }
#undef ACC
      wg_wait<0>();
      fence_regs(pk); fence_regs(pq);
#pragma unroll
      for (int G = 0; G < 10; G++) {
        P[0][G] = pack_bf16(pk[4 * G], pk[4 * G + 1]); P[1][G] = pack_bf16(pk[4 * G + 2], pk[4 * G + 3]);
        qp[0][G] = pack_bf16(pq[4 * G], pq[4 * G + 1]); qp[1][G] = pack_bf16(pq[4 * G + 2], pq[4 * G + 3]);
      }
    }

    uint32_t fr[10][4];
    uint32_t xv[2][10];
#pragma unroll
    for (int g = 0; g < 10; g++) xv[0][g] = xv[1][g] = 0u;
    int pass;
    pass = gridDim.y;
#pragma unroll 1
    do {
    feature_map(P, fr);
    if (pass != 0) {
    {
      const int mat = lane >> 3;
      const int tok = warp * 16 + (mat & 1) * 8 + (lane & 7);
      const uint32_t base = sb + OFF_B + tok * 32 + (((mat >> 1) ^ ((tok >> 2) & 1)) << 4);
#pragma unroll
      for (int G = 0; G < 10; G++) stsm4(base + G * 4096, fr[G][0], fr[G][1], fr[G][2], fr[G][3]);
      fence_async_smem();
      bar_sync(1, 256);
      float kv[40];
      const uint32_t a0 = sb16 + ((OFF_A + wg * SLOT_A) >> 4), b0 = sb16 + ((OFF_B + wg * 20480) >> 4);
      wg_fence();
#pragma unroll
      for (int ks = 0; ks < 8; ks++) {
        if (ks == 0) mma_ss80_tt_z(kv, make_desc(a0, 0, 16, 1024, 1), make_desc(b0, 0, 4096, 256, 3));
        else mma_ss80_tt(kv, make_desc(a0, ks * 2048, 16, 1024, 1), make_desc(b0, ks * 512, 4096, 256, 3));
      }
      wg_commit();
      wg_wait<0>();
      fence_regs(kv);
      TSTAMP(31);
      release(emptyA); release(emptyA + 8); releaseB(emptyB);
      const uint32_t dst = sb + OFF_MISC + wg * (KV_PAIR * 4);
      const int m0 = (warp & 3) * 16 + (lane >> 2);
#pragma unroll
      for (int r = 0; r < 2; r++) {
        const int m = m0 + 8 * r;
        const bool hi = m >= 20;
        uint32_t v[10];
#pragma unroll
        for (int G = 0; G < 10; G++) v[G] = __float_as_uint(hi ? kv[4 * G + 2 * r + 1] : kv[4 * G + 2 * r]);
        const uint32_t p = dst + 4 * (m < 40 ? m * 48 + t * 12 : 1920 + t * 24 + 12);
        if (m <= 40) {
          sts128(p, make_uint4(v[0], v[1], v[2], v[3])); sts128(p + 16, make_uint4(v[4], v[5], v[6], v[7]));
          sts128(p + 32, make_uint4(v[8], v[9], 0u, 0u));
        }
      }
      if (m0 == 32) {
        const uint32_t p = dst + 4 * (1920 + t * 24);
        sts128(p, make_uint4(__float_as_uint(kv[2]), __float_as_uint(kv[6]), __float_as_uint(kv[10]), __float_as_uint(kv[14])));
        sts128(p + 16, make_uint4(__float_as_uint(kv[18]), __float_as_uint(kv[22]), __float_as_uint(kv[26]), __float_as_uint(kv[30])));
        sts128(p + 32, make_uint4(__float_as_uint(kv[34]), __float_as_uint(kv[38]), 0u, 0u));
      }
      fence_async_smem();
      signal(B_SIGKV);
    }
    TSTAMP(5);

    {
      {
        mbar_wait(bars + 8 * B_XR, 0);
        const uint32_t xa = sb + OFF_B + (warp / 3) * SLOT_B + SPARE + (warp % 3) * 2560 + (lane >> 2) * 160 + t * 4;
#pragma unroll
        for (int g = 0; g < 10; g++) { xv[0][g] = lds32(xa + g * 16); xv[1][g] = lds32(xa + 1280 + g * 16); }
      }
      float acc[40];
      zero_regs(acc);
      uint32_t pa = 0, pb = 0;
#pragma unroll 1
      for (int k = 0; k < 10; k++) {
        mbar_wait(fullA + 8 * ra.idx, ra.phase);
        if (tid == 0) TRACE(42 + k);
        if ((k & 3) == 0) mbar_wait(fullB + 8 * rb.idx, rb.phase);
        if (tid == 0) TRACE(74 + k);
        if (k == 0) TSTAMP(6);
        const uint32_t a0 = sb16 + ((OFF_A + ra.idx * SLOT_A + wg * 8192) >> 4);
        const uint32_t b0 = sb16 + ((OFF_B + rb.idx * SLOT_B + (k & 3) * 10240) >> 4);
        wg_fence();
#pragma unroll
        for (int kk = 0; kk < 4; kk++) {
          mma_ss80(acc, make_desc(a0, kk * 32, 16, 1024, 1), make_desc(b0, kk * 512, 2048, 256, 3));
          if (kk == 1) {
            wg_commit();
            if (k > 0) {
              wg_wait<1>();
              release(emptyA + 8 * pa);
              if ((k & 3) == 0) releaseB(emptyB + 8 * pb);
            }
          }
        }
        wg_commit();
        pa = ra.idx; pb = rb.idx;
        ra.next<NA>();
        if ((k & 3) == 3 || k == 9) rb.next<NB>();
      }
      wg_wait<0>();
      fence_regs(acc);
      release(emptyA + 8 * pa); releaseB(emptyB + 8 * pb);
      TSTAMP(7);
#pragma unroll
      for (int r = 0; r < 2; r++) {
#pragma unroll
        for (int g = 0; g < 10; g++)
          xv[r][g] = pack_bf16(bf_lo(xv[r][g]) + acc[4 * g + 2 * r], bf_hi(xv[r][g]) + acc[4 * g + 2 * r + 1]);
      }
      bar_sync(1, 256);
#pragma unroll
      for (int s = 0; s < 5; s++) stsm4(sb + OFF_STG + stg_lane + s * 32, xv[0][2 * s], xv[1][2 * s], xv[0][2 * s + 1], xv[1][2 * s + 1]);
#pragma unroll
      for (int r = 0; r < 2; r++) {
        float s = 0.f;
#pragma unroll
        for (int g = 0; g < 10; g++) {
          acc[4 * g + 2 * r] = bf_lo(xv[r][g]); acc[4 * g + 2 * r + 1] = bf_hi(xv[r][g]);
          s += acc[4 * g + 2 * r] + acc[4 * g + 2 * r + 1];
        }
        s += __shfl_xor_sync(0xffffffffu, s, 1); s += __shfl_xor_sync(0xffffffffu, s, 2);
        const float mu = s * (1.f / 80.f);
        float q = 0.f;
#pragma unroll
        for (int g = 0; g < 10; g++) {
          const float d0 = acc[4 * g + 2 * r] - mu, d1 = acc[4 * g + 2 * r + 1] - mu;
          q = fmaf(d0, d0, q); q = fmaf(d1, d1, q);
        }
        q += __shfl_xor_sync(0xffffffffu, q, 1); q += __shfl_xor_sync(0xffffffffu, q, 2);
        if (t == 0) g_st1[(128 * i + rloc + 8 * r) * 8 + j] = make_float2(mu, q);
      }
      fence_async_smem();
      signal(B_SIGX1);
    }
    TSTAMP(8);
#pragma unroll
    for (int G = 0; G < 10; G++) { P[0][G] = qp[0][G]; P[1][G] = qp[1][G]; }
    }
    asm volatile("" : "+r"(pass));
    } while (pass-- != 0);

    uint32_t of[5][4];
    {
      mbar_wait(bars + 8 * B_KV, 0);
      uint4 kvr[2][3];
#pragma unroll
      for (int u = 0; u < 2; u++) {
        const int it = tid + 256 * u, p = it / 192, rem = it - 192 * p, n = rem >> 2, tq = rem & 3;
        const uint32_t sp = sb + OFF_MISC + 4 * (p * KV_PAIR + (n < 40 ? n * 48 + tq * 12 : 1920 + tq * 24 + (n & 1) * 12));
        if (it < 384) { kvr[u][0] = lds128(sp); kvr[u][1] = lds128(sp + 16); kvr[u][2] = lds128(sp + 32); }
      }
      bar_sync(1, 256);
#pragma unroll
      for (int u = 0; u < 2; u++) {
        const int it = tid + 256 * u, p = it / 192, rem = it - 192 * p, n = rem >> 2, tq = rem & 3;
        const int sh = (n < 40 ? (n >= 20) : (n & 1)) * 16;
        const uint32_t v[10] = {kvr[u][0].x, kvr[u][0].y, kvr[u][0].z, kvr[u][0].w, kvr[u][1].x, kvr[u][1].y, kvr[u][1].z, kvr[u][1].w, kvr[u][2].x, kvr[u][2].y};
        uint8_t* dst = sgen + OFF_MISC + p * 7680 + n * 32 + tq * 4;
        const int sw = ((n >> 2) & 1) << 4;
        if (it < 384) {
#pragma unroll
          for (int G = 0; G < 10; G++)
            *reinterpret_cast<uint32_t*>(dst + (G >> 1) * 1536 + (((G & 1) << 4) ^ sw)) = pack_bf16(__uint_as_float(v[G]), 0.f) << sh;
        }
      }
      fence_async_smem();
      bar_sync(1, 256);
      float o0[24], o1[24];
      wg_fence();
#pragma unroll
      for (int g = 0; g < 5; g++) {
        if (g == 0) mma_rs48_k_z(o0, fr[g], make_desc(sb16, OFF_MISC, 16, 256, 3));
        else mma_rs48_k(o0, fr[g], make_desc(sb16, OFF_MISC + g * 1536, 16, 256, 3));
      }
#pragma unroll
      for (int g = 0; g < 5; g++) {
        if (g == 0) mma_rs48_k_z(o1, fr[5], make_desc(sb16, OFF_MISC + 7680, 16, 256, 3));
        else mma_rs48_k(o1, fr[5 + g], make_desc(sb16, OFF_MISC + 7680 + g * 1536, 16, 256, 3));
      }
      wg_commit();
      wg_wait<0>();
      fence_regs(o0); fence_regs(o1);
      signal(B_MFREE);
#pragma unroll
      for (int r = 0; r < 2; r++) {
        const float a0 = __fdividef(st_g[r], o0[20 + 2 * r] + 1e-6f), a1 = __fdividef(st_g[r], o0[21 + 2 * r] + 1e-6f);
        const float b0 = __fdividef(st_g[r], o1[20 + 2 * r] + 1e-6f), b1 = __fdividef(st_g[r], o1[21 + 2 * r] + 1e-6f);
        const float am = t < 2 ? a0 : a1, bm = t < 2 ? b0 : b1;
#pragma unroll
        for (int g = 0; g < 5; g++) {
          const float sa = g < 2 ? a0 : (g == 2 ? am : a1), sb2 = g < 2 ? b0 : (g == 2 ? bm : b1);
          of[g >> 1][(g & 1) * 2 + r] = pack_bf16(o0[4 * g + 2 * r] * sa, o0[4 * g + 2 * r + 1] * sa);
          of[(5 + g) >> 1][((5 + g) & 1) * 2 + r] = pack_bf16(o1[4 * g + 2 * r] * sb2, o1[4 * g + 2 * r + 1] * sb2);
        }
      }
    }
    TSTAMP(9);

    uint32_t hf[12][4];
    {
      float acc[96];
      zero_regs(acc);
      uint32_t pa = 0, pb = 0;
#pragma unroll 1
      for (int k = 0; k < 10; k++) {
        mbar_wait(fullA + 8 * ra.idx, ra.phase);
        if (tid == 0) TRACE(52 + k);
        if ((k & 1) == 0) mbar_wait(fullB + 8 * rb.idx, rb.phase);
        if (tid == 0) TRACE(84 + k);
        if (k == 0) TSTAMP(10);
        const uint32_t a0 = sb16 + ((OFF_A + ra.idx * SLOT_A + wg * 8192) >> 4);
        const uint32_t b0 = sb16 + ((OFF_B + rb.idx * SLOT_B + (k & 1) * 24576) >> 4);
        wg_fence();
#pragma unroll
        for (int kk = 0; kk < 4; kk++) {
          mma_ss192(acc, make_desc(a0, kk * 32, 16, 1024, 1), make_desc(b0, kk * 2048, 8192, 1024, 1));
          if (kk == 0) {
            wg_commit();
            if (k > 0) {
              wg_wait<1>();
              release(emptyA + 8 * pa);
              if ((k & 1) == 0) releaseB(emptyB + 8 * pb);
            }
          }
        }
        wg_commit();
        pa = ra.idx; pb = rb.idx;
        ra.next<NA>();
        if (k & 1) rb.next<NB>();
      }
      float rs[2], mm[2];
      mbar_wait(bars + 8 * B_ST1, 0);
#pragma unroll
      for (int r = 0; r < 2; r++) {
        const uint4 su = lds128(sb + OFF_MISC + (rloc + 8 * r) * 64 + t * 16);
        const float m0 = __uint_as_float(su.x), m1 = __uint_as_float(su.z);
        float mu = m0 + m1;
        mu += __shfl_xor_sync(0xffffffffu, mu, 1); mu += __shfl_xor_sync(0xffffffffu, mu, 2);
        mu *= 0.125f;
        const float d0 = m0 - mu, d1 = m1 - mu;
        float q = __uint_as_float(su.y) + __uint_as_float(su.w) + 80.f * (d0 * d0 + d1 * d1);
        q += __shfl_xor_sync(0xffffffffu, q, 1); q += __shfl_xor_sync(0xffffffffu, q, 2);
        rs[r] = rsqrtf(q * (1.f / D_) + 1e-5f);
        mm[r] = -mu * rs[r];
      }
      wg_wait<0>();
      fence_regs(acc);
      releaseB(emptyB + 8 * pb);
      release(bars + 8 * B_PEER);
      TSTAMP(11);
      const float hs0 = 0.5f - 0.5f * st_g[0], hs1 = 0.5f - 0.5f * st_g[1];
#pragma unroll
      for (int g = 0; g < 24; g++) {
        const float2 cs = *reinterpret_cast<const float2*>(s_cs + 80 + 8 * g + 2 * t);
        const float v0 = gelu_s(fmaf(acc[4 * g], rs[0], mm[0] * cs.x), hs0), v1 = gelu_s(fmaf(acc[4 * g + 1], rs[0], mm[0] * cs.y), hs0);
        const float v2 = gelu_s(fmaf(acc[4 * g + 2], rs[1], mm[1] * cs.x), hs1), v3 = gelu_s(fmaf(acc[4 * g + 3], rs[1], mm[1] * cs.y), hs1);
        hf[g >> 1][(g & 1) * 2] = pack_bf16(v0, v1);
        hf[g >> 1][(g & 1) * 2 + 1] = pack_bf16(v2, v3);
      }
    }
    TSTAMP(12);

    {
      float acc[80], kp[40];
      uint32_t sn[20], kb[20];
      const int wt = tid & 127;
      const uint32_t peer = map_peer(sb, rank ^ 1);
      const uint32_t lofs = wg * 10240 + wt * 16;
      Ring r4{0, 0};
      auto add16 = [&](uint32_t src) {
#pragma unroll
        for (int q = 0; q < 5; q++) {
          const uint4 v = lds128(src + q * 2048);
          float* d = &kp[8 * q];
          d[0] += bf_lo(v.x); d[1] += bf_hi(v.x); d[2] += bf_lo(v.y); d[3] += bf_hi(v.y);
          d[4] += bf_lo(v.z); d[5] += bf_hi(v.z); d[6] += bf_lo(v.w); d[7] += bf_hi(v.w);
        }
      };
      auto send = [&](int c) {
        const uint32_t dso = peer + OFF_DS + (c & 1) * 20480 + lofs, dsb = peer + OFF_BAR + 8 * (B_DSR + 2 * c + wg);
#pragma unroll
        for (int q = 0; q < 5; q++) st_async16(dso + q * 2048, sn[4 * q], sn[4 * q + 1], sn[4 * q + 2], sn[4 * q + 3], dsb);
      };
#pragma unroll
      for (int e = 0; e < 20; e++) sn[e] = kb[e] = 0u;
      auto chunk = [&](const int c, auto last_c) {
        constexpr bool LAST = decltype(last_c)::value;
        const uint32_t e0 = r4.idx;
        auto rel = [&](int u) { const uint32_t e = e0 + u; releaseB(bars + 8 * (B_EMPTY4 + (e >= NU4 ? e - NU4 : e))); };
#pragma unroll
        for (int u = 0; u < 4; u++) {
          mbar_wait(bars + 8 * (B_FULL4 + r4.idx), r4.phase);
          const uint32_t b0 = sb16 + ((OFF_B + r4.idx * UNIT4) >> 4);
          TRS(c * 16 + u * 3);
          wg_fence();
#pragma unroll
          for (int s = 0; s < (u < 3 ? 4 : 5); s++) {
            const uint64_t db = make_desc(b0, s * 1024, u < 3 ? 4096 : 5120, 512, 2);
            if (u == 0 && s == 0) mma_rs160_n_z(acc, hf[0], db);
            else if (u < 3) mma_rs160_n(acc, hf[(4 * u + s) % 12], db);
            else mma_rs160_n(acc, of[s], db);
          }
          wg_commit();
          TRS(c * 16 + u * 3 + 1);
          r4.next<NU4>();
          if (u == 1) {
            if (c == 0) { if (wg == 0) bar_arrive(2, 256); mbar_wait(bars + 8 * B_PEER, 0); }
            else send(c - 1);
          }
          if (u == 2 && c > 0) {
            if (c > 1) mbar_wait(bars + 8 * (B_SDONE + 2 * (c - 2) + wg), 0);
            mbar_wait(bars + 8 * (B_DSR + 2 * (c - 1) + wg), 0);
            TRS(c * 16 + 14);
#pragma unroll
            for (int q = 0; q < 5; q++) {
              const uint4 v = lds128(sb + OFF_DS + ((c - 1) & 1) * 20480 + lofs + q * 2048);
              sts128(sb + OFF_SEND + lofs + q * 2048,
                     make_uint4(add_bf2(v.x, kb[4 * q]), add_bf2(v.y, kb[4 * q + 1]), add_bf2(v.z, kb[4 * q + 2]), add_bf2(v.w, kb[4 * q + 3])));
            }
            fence_async_smem();
            signal(B_SEND + 2 * (c - 1) + wg);
          }
          if (u == 3 && LAST) {
            const float w0 = 1.f - st_g[0], w1s = 1.f - st_g[1];
#pragma unroll
            for (int g = 0; g < 10; g++) {
              kp[4 * g] = w0 * bf_lo(xv[0][g]); kp[4 * g + 1] = w0 * bf_hi(xv[0][g]);
              kp[4 * g + 2] = w1s * bf_lo(xv[1][g]); kp[4 * g + 3] = w1s * bf_hi(xv[1][g]);
            }
#pragma unroll 1
            for (int e = 0; e < 2; e++) {
              mbar_wait(bars + 8 * (B_RDY + 2 * e + wg), 0);
              add16(sb + (e == 0 ? OFF_G0 : OFF_G1) + lofs);
            }
          }
          TRS(c * 16 + u * 3 + 2);
          if (u > 0 && !LAST) { wg_wait<1>(); rel(u - 1); }
        }
        wg_wait<0>();
        fence_regs(acc);
        if (!LAST) rel(3);
        TRS(c * 16 + 12);
        if (rank) {
#pragma unroll
          for (int e = 0; e < 20; e++) { sn[e] = pack_bf16(acc[2 * e], acc[2 * e + 1]); kb[e] = pack_bf16(acc[40 + 2 * e], acc[41 + 2 * e]); }
        } else {
#pragma unroll
          for (int e = 0; e < 20; e++) { kb[e] = pack_bf16(acc[2 * e], acc[2 * e + 1]); sn[e] = pack_bf16(acc[40 + 2 * e], acc[41 + 2 * e]); }
        }
#pragma unroll
        for (int e = 0; e < 20; e++) asm volatile("" : "+r"(sn[e]), "+r"(kb[e]));
        TRS(c * 16 + 13);
      };
      if (wg == 1) bar_sync(2, 256);
#pragma unroll 1
      for (int c = 0; c < 3; c++) chunk(c, BoolC<false>{});
      chunk(3, BoolC<true>{});
      send(3);
      TSTAMP(13);
#pragma unroll
      for (int e = 0; e < 40; e++) kp[e] += rank ? acc[40 + e] : acc[e];
#pragma unroll 1
      for (int c = 0; c < 2; c++) {
        mbar_wait(bars + 8 * ((c == 0 ? B_DSR + 6 : B_RDY + 4) + wg), 0);
        add16(sb + (c == 0 ? OFF_DS + 20480 : OFF_SEND) + lofs);
      }
      TSTAMP(14);
#pragma unroll
      for (int s = 0; s < 5; s++)
        stsm4(sb + OFF_DS + stg_lane + s * 32, pack_bf16(kp[8 * s], kp[8 * s + 1]), pack_bf16(kp[8 * s + 2], kp[8 * s + 3]),
              pack_bf16(kp[8 * s + 4], kp[8 * s + 5]), pack_bf16(kp[8 * s + 6], kp[8 * s + 7]));
      fence_async_smem();
      __syncwarp();
      if (lane == 0) {
        tma2d_store(&maps.st_out, sb + OFF_DS + warp * 2560, 80 * j, 128 * i + 16 * warp);
        bulk_commit(); bulk_wait_read();
      }
    }
    TSTAMP(15);
    if (tid == 0) asm volatile("red.relaxed.gpu.global.add.u32 [%0], 1;" ::"l"(g_flags + FL_DONE * 32) : "memory");
  }
}

namespace {
typedef CUresult (*EncodeFn)(CUtensorMap*, CUtensorMapDataType, cuuint32_t, void*, const cuuint64_t*, const cuuint64_t*,
                             const cuuint32_t*, const cuuint32_t*, CUtensorMapInterleave, CUtensorMapSwizzle,
                             CUtensorMapL2promotion, CUtensorMapFloatOOBfill);

void encode(EncodeFn fn, CUtensorMap* m, const void* ptr, int rank, const cuuint64_t* dims, const cuuint64_t* strides,
            const cuuint32_t* box, CUtensorMapSwizzle swz) {
  cuuint32_t es[5] = {1, 1, 1, 1, 1};
  fn(m, CU_TENSOR_MAP_DATA_TYPE_BFLOAT16, rank, const_cast<void*>(ptr), dims, strides, box, es, CU_TENSOR_MAP_INTERLEAVE_NONE,
     swz, CU_TENSOR_MAP_L2_PROMOTION_L2_128B, CU_TENSOR_MAP_FLOAT_OOB_FILL_NONE);
}
}

extern "C" void kernel_launch(void* const* d_in, const int* in_sizes, int n_in, void* d_out, int out_size) {
  (void)in_sizes; (void)n_in; (void)out_size;
  const __nv_bfloat16* x = (const __nv_bfloat16*)d_in[0];
  const __nv_bfloat16* wqkv = (const __nv_bfloat16*)d_in[1];
  const __nv_bfloat16* wphi = (const __nv_bfloat16*)d_in[2];
  const __nv_bfloat16* wo = (const __nv_bfloat16*)d_in[3];
  const __nv_bfloat16* w1 = (const __nv_bfloat16*)d_in[5];
  const __nv_bfloat16* w2 = (const __nv_bfloat16*)d_in[6];
  const __nv_bfloat16* w3 = (const __nv_bfloat16*)d_in[7];
  const __nv_bfloat16* w4 = (const __nv_bfloat16*)d_in[8];
  const __nv_bfloat16* gate_w = (const __nv_bfloat16*)d_in[9];

  static EncodeFn enc = nullptr;
  static void *pHs = nullptr, *pX1 = nullptr;
  if (!enc) {
    cudaDriverEntryPointQueryResult qr;
    cudaGetDriverEntryPoint("cuTensorMapEncodeTiled", (void**)&enc, cudaEnableDefault, &qr);
    cudaGetSymbolAddress(&pHs, g_Hs);
    cudaGetSymbolAddress(&pX1, g_X1);
    cudaFuncSetAttribute(fused_kernel, cudaFuncAttributeMaxDynamicSharedMemorySize, SMEM_BYTES);
  }
  Maps m;
  {
    cuuint64_t dims[2] = {D_, S_}, str[1] = {D_ * 2};
    cuuint32_t boxh[2] = {64, 64};
    encode(enc, &m.x, x, 2, dims, str, boxh, CU_TENSOR_MAP_SWIZZLE_128B);
    encode(enc, &m.hs, (const char*)pHs + 2 * D_ * 2, 2, dims, str, boxh, CU_TENSOR_MAP_SWIZZLE_128B);
    encode(enc, &m.x1, pX1, 2, dims, str, boxh, CU_TENSOR_MAP_SWIZZLE_128B);
    cuuint32_t boxs[2] = {80, 64};
    cuuint64_t dimsp[2] = {D_, S_ + 4};
    encode(enc, &m.st_h, pHs, 2, dimsp, str, boxs, CU_TENSOR_MAP_SWIZZLE_NONE);
    encode(enc, &m.st_x1, pX1, 2, dims, str, boxs, CU_TENSOR_MAP_SWIZZLE_NONE);
    cuuint32_t boxr[2] = {80, 16};
    encode(enc, &m.st_out, d_out, 2, dims, str, boxr, CU_TENSOR_MAP_SWIZZLE_NONE);
    encode(enc, &m.xr, x, 2, dims, str, boxr, CU_TENSOR_MAP_SWIZZLE_NONE);
  }
  {
    cuuint64_t dims[3] = {80, D_, 8}, str[2] = {D_ * 2, 160};
    cuuint32_t boxm[3] = {64, 64, 1}, boxr[3] = {16, 64, 1};
    encode(enc, &m.w1m, w1, 3, dims, str, boxm, CU_TENSOR_MAP_SWIZZLE_128B);
    encode(enc, &m.w1r, w1, 3, dims, str, boxr, CU_TENSOR_MAP_SWIZZLE_32B);
  }
  {
    cuuint64_t dims[4] = {80, D_, 3, 8}, str[3] = {3 * D_ * 2, D_ * 2, 160};
    cuuint32_t boxm[4] = {64, 64, 3, 1}, boxr[4] = {16, 64, 3, 1};
    encode(enc, &m.qm, wqkv, 4, dims, str, boxm, CU_TENSOR_MAP_SWIZZLE_128B);
    encode(enc, &m.qr, wqkv, 4, dims, str, boxr, CU_TENSOR_MAP_SWIZZLE_32B);
  }
  {
    cuuint64_t dims[3] = {16, D_, 40}, str[2] = {D_ * 2, 32};
    cuuint32_t box2[3] = {16, 64, 5};
    encode(enc, &m.w2, w2, 3, dims, str, box2, CU_TENSOR_MAP_SWIZZLE_32B);
  }
  {
    cuuint64_t dims[3] = {32, D_, 20}, dims4[3] = {32, F_, 20}, str[2] = {D_ * 2, 64};
    cuuint32_t box4[3] = {32, 64, 5}, boxo[3] = {32, 80, 5};
    encode(enc, &m.w4, w4, 3, dims4, str, box4, CU_TENSOR_MAP_SWIZZLE_64B);
    encode(enc, &m.wo, wo, 3, dims, str, boxo, CU_TENSOR_MAP_SWIZZLE_64B);
  }
  {
    cuuint64_t dims[3] = {64, D_, 24}, str[2] = {F_ * 2, 128};
    cuuint32_t box[3] = {64, 64, 3};
    encode(enc, &m.w3, w3, 3, dims, str, box, CU_TENSOR_MAP_SWIZZLE_128B);
  }
  fused_kernel<<<NCTA, 384, SMEM_BYTES, cudaStreamPerThread>>>(m, x, wqkv, wphi, w1, w2, w3, w4, wo, gate_w);
}
```

```cpp
#include <cuda_runtime.h>
#include <cuda_bf16.h>
#include <cuda.h>
#include <stdint.h>

namespace {

constexpr int S_ = 2048, D_ = 640, F_ = 1536;
constexpr int NCTA = 128;
constexpr int KV_PAIR = 40 * 48 + 96;
constexpr int KV_J = 2 * KV_PAIR;

constexpr int SLOT_B = 49152, NB = 3;
constexpr int SLOT_A = 16384, NA = 4;
constexpr int OFF_B = 0;
constexpr int OFF_A = OFF_B + NB * SLOT_B;
constexpr int OFF_STG = OFF_A + 2 * SLOT_A;
constexpr int OFF_MISC = OFF_A + NA * SLOT_A;
constexpr int OFF_XST = OFF_MISC + 13312;
constexpr int OFF_CS = OFF_MISC + 16384;
constexpr int OFF_BAR = OFF_CS + 1088;
constexpr int SMEM_BYTES = OFF_BAR + 512 + 512;
constexpr int B_FULLA = 0, B_FULLB = 4, B_CS = 7, B_XR = 8, B_KV = 9, B_ST1 = 10, B_RDY = 11  ,
              B_FULL4 = 17  , B_DSR = 22  , B_SEND = 30  , B_EMPTYB = 36  ,
              B_SIGP = 39, B_SIGH = 40, B_SIGKV = 41, B_SIGX1 = 42, B_MFREE = 43, B_EMPTY4 = 44  ,
              B_EMPTYA = 49  , B_PEER = 53, NBAR = 54;
constexpr int SPARE = 40960;
constexpr int UNIT4 = 25600, NU4 = 5;
constexpr int OFF_DS = OFF_A, OFF_G0 = OFF_A + 40960, OFF_G2 = OFF_B + UNIT4;

constexpr int FL_DONE = 0, FL_H = 1, FL_X1 = FL_H + 16, FL_KV = FL_X1 + 16, FL_CS = FL_KV + 8, FL_CS3 = FL_CS + 8, FL_ST = FL_CS3 + 8, FL_PART = FL_ST + 16;
constexpr int FL_COUNT = FL_PART + 16 * 8;
constexpr int ACC_FLOATS = 8 * KV_J + D_ + F_;

struct Maps {
  CUtensorMap x, w1m, w1r, qm, qr, hs, w2, x1, w3, w4, wo, st_h, st_x1, st_out, xr;
};

}

__device__ __align__(1024) __nv_bfloat16 g_Hs[(S_ + 4) * D_];
__device__ __align__(1024) __nv_bfloat16 g_X1[S_ * D_];
__device__ __align__(128) float g_acc[2][ACC_FLOATS];
__device__ __align__(128) float4 g_xstat[S_];
__device__ __align__(128) float2 g_st1[S_ * 8];
__device__ __align__(128) uint4 g_part[16 * 8 * 3 * 1280];
__device__ __align__(128) unsigned g_flags[FL_COUNT * 32];
#define TSTAMP(n) do {} while (0)
#define TSTAMPX(n) do {} while (0)
#define TRACE(n) do {} while (0)
#define TRS(n) do {} while (0)

namespace {

__device__ __forceinline__ long long gtime() { long long t; asm volatile("mov.u64 %0, %%globaltimer;" : "=l"(t)); return t; }
__device__ __forceinline__ uint32_t smem_u32(const void* p) { return (uint32_t)__cvta_generic_to_shared(p); }
__device__ __forceinline__ void mbar_init(uint32_t bar, int cnt) {
  asm volatile("mbarrier.init.shared::cta.b64 [%0], %1;" ::"r"(bar), "r"(cnt) : "memory");
}
__device__ __forceinline__ void mbar_expect_tx(uint32_t bar, int bytes) {
  asm volatile("mbarrier.arrive.expect_tx.shared::cta.b64 _, [%0], %1;" ::"r"(bar), "r"(bytes) : "memory");
}
__device__ __forceinline__ void mbar_arrive_cta(uint32_t bar, uint32_t cta) {
  asm volatile("{\n.reg .b32 ra;\nmapa.shared::cluster.u32 ra, %0, %1;\nmbarrier.arrive.shared::cluster.b64 _, [ra];\n}"
               ::"r"(bar), "r"(cta) : "memory");
}
__device__ __forceinline__ uint32_t mbar_try(uint32_t bar, uint32_t parity) {
  uint32_t ok;
  asm volatile("{\n.reg .pred p;\nmbarrier.try_wait.parity.shared::cta.b64 p, [%1], %2;\nselp.u32 %0, 1, 0, p;\n}"
               : "=r"(ok) : "r"(bar), "r"(parity) : "memory");
  return ok;
}
constexpr uint32_t WAIT_LIMIT = 1u << 22;
__device__ __forceinline__ void mbar_wait(uint32_t bar, uint32_t parity) {
  uint32_t n = 0;
  while (!mbar_try(bar, parity) && ++n < WAIT_LIMIT) {}
}
__device__ __forceinline__ unsigned ld_acquire(const unsigned* p) {
  unsigned v;
  asm volatile("ld.acquire.gpu.global.u32 %0, [%1];" : "=r"(v) : "l"(p) : "memory");
  return v;
}
__device__ __forceinline__ void flag_wait(int idx, unsigned target) {
  const unsigned* p = g_flags + idx * 32;
  uint32_t n = 0;
  while ((int)(ld_acquire(p) - target) < 0 && ++n < (WAIT_LIMIT >> 4)) {}
}
__device__ __forceinline__ void flag_add(int idx) {
  asm volatile("red.release.gpu.global.add.u32 [%0], 1;" ::"l"(g_flags + idx * 32) : "memory");
}
__device__ __forceinline__ void flag_add_relaxed(int idx) {
  asm volatile("red.relaxed.gpu.global.add.u32 [%0], 1;" ::"l"(g_flags + idx * 32) : "memory");
}
__device__ __forceinline__ uint32_t mbar_test(uint32_t bar, uint32_t parity) {
  uint32_t ok;
  asm volatile("{\n.reg .pred p;\nmbarrier.test_wait.parity.shared::cta.b64 p, [%1], %2;\nselp.u32 %0, 1, 0, p;\n}"
               : "=r"(ok) : "r"(bar), "r"(parity) : "memory");
  return ok;
}
__device__ __forceinline__ uint32_t lds32(uint32_t a) {
  uint32_t v;
  asm volatile("ld.shared.u32 %0, [%1];" : "=r"(v) : "r"(a) : "memory");
  return v;
}
__device__ __forceinline__ void mbar_arrive(uint32_t bar) {
  asm volatile("mbarrier.arrive.shared::cta.b64 _, [%0];" ::"r"(bar) : "memory");
}
__device__ __forceinline__ void fence_async_all() { asm volatile("fence.proxy.async;" ::: "memory"); }
__device__ __forceinline__ void fence_async_smem() { asm volatile("fence.proxy.async.shared::cta;" ::: "memory"); }
__device__ __forceinline__ void bar_sync(int id, int n) { asm volatile("bar.sync %0, %1;" ::"r"(id), "r"(n) : "memory"); }

__device__ __forceinline__ void tma2d(uint32_t dst, const CUtensorMap* m, uint32_t bar, int c0, int c1) {
  asm volatile("cp.async.bulk.tensor.2d.shared::cluster.global.mbarrier::complete_tx::bytes [%0], [%1, {%3, %4}], [%2];"
               ::"r"(dst), "l"(m), "r"(bar), "r"(c0), "r"(c1) : "memory");
}
__device__ __forceinline__ void tma2d_mc(uint32_t dst, const CUtensorMap* m, uint32_t bar, int c0, int c1) {
  asm volatile("cp.async.bulk.tensor.2d.shared::cluster.global.mbarrier::complete_tx::bytes.multicast::cluster"
               " [%0], [%1, {%3, %4}], [%2], %5;"
               ::"r"(dst), "l"(m), "r"(bar), "r"(c0), "r"(c1), "h"((uint16_t)3) : "memory");
}
__device__ __forceinline__ void tma3d(uint32_t dst, const CUtensorMap* m, uint32_t bar, int c0, int c1, int c2) {
  asm volatile("cp.async.bulk.tensor.3d.shared::cluster.global.mbarrier::complete_tx::bytes [%0], [%1, {%3, %4, %5}], [%2];"
               ::"r"(dst), "l"(m), "r"(bar), "r"(c0), "r"(c1), "r"(c2) : "memory");
}
__device__ __forceinline__ void tma4d(uint32_t dst, const CUtensorMap* m, uint32_t bar, int c0, int c1, int c2, int c3) {
  asm volatile("cp.async.bulk.tensor.4d.shared::cluster.global.mbarrier::complete_tx::bytes [%0], [%1, {%3, %4, %5, %6}], [%2];"
               ::"r"(dst), "l"(m), "r"(bar), "r"(c0), "r"(c1), "r"(c2), "r"(c3) : "memory");
}
__device__ __forceinline__ void tma2d_store(const CUtensorMap* m, uint32_t src, int c0, int c1) {
  asm volatile("cp.async.bulk.tensor.2d.global.shared::cta.bulk_group [%0, {%2, %3}], [%1];"
               ::"l"(m), "r"(src), "r"(c0), "r"(c1) : "memory");
}
__device__ __forceinline__ void bulk_store(void* dst, uint32_t src, uint32_t bytes) {
  asm volatile("cp.async.bulk.global.shared::cta.bulk_group [%0], [%1], %2;" ::"l"(dst), "r"(src), "r"(bytes) : "memory");
}
__device__ __forceinline__ void bulk_load(uint32_t dst, const void* src, uint32_t bytes, uint32_t bar) {
  asm volatile("cp.async.bulk.shared::cluster.global.mbarrier::complete_tx::bytes [%0], [%1], %2, [%3];"
               ::"r"(dst), "l"(src), "r"(bytes), "r"(bar) : "memory");
}
__device__ __forceinline__ void bulk_commit() { asm volatile("cp.async.bulk.commit_group;" ::: "memory"); }
template <int N> __device__ __forceinline__ void bulk_wait() { asm volatile("cp.async.bulk.wait_group %0;" ::"n"(N) : "memory"); }
__device__ __forceinline__ void bulk_wait_read() { asm volatile("cp.async.bulk.wait_group.read 0;" ::: "memory"); }
__device__ __forceinline__ void bar_arrive(int id, int n) { asm volatile("bar.arrive %0, %1;" ::"r"(id), "r"(n) : "memory"); }
__device__ __forceinline__ uint4 lds128(uint32_t a) {
  uint4 v;
  asm volatile("ld.shared.v4.u32 {%0, %1, %2, %3}, [%4];" : "=r"(v.x), "=r"(v.y), "=r"(v.z), "=r"(v.w) : "r"(a) : "memory");
  return v;
}
__device__ __forceinline__ void sts128(uint32_t a, uint4 v) {
  asm volatile("st.shared.v4.u32 [%0], {%1, %2, %3, %4};" ::"r"(a), "r"(v.x), "r"(v.y), "r"(v.z), "r"(v.w) : "memory");
}
__device__ __forceinline__ uint32_t map_peer(uint32_t addr, uint32_t cta) {
  uint32_t r;
  asm("mapa.shared::cluster.u32 %0, %1, %2;" : "=r"(r) : "r"(addr), "r"(cta));
  return r;
}
__device__ __forceinline__ void st_async16(uint32_t addr, uint32_t a, uint32_t b, uint32_t c, uint32_t d, uint32_t bar) {
  asm volatile("st.async.weak.shared::cluster.mbarrier::complete_tx::bytes.v4.b32 [%0], {%1, %2, %3, %4}, [%5];"
               ::"r"(addr), "r"(a), "r"(b), "r"(c), "r"(d), "r"(bar) : "memory");
}
__device__ __forceinline__ void l2_prefetch(const void* p, uint32_t bytes) {
  asm volatile("cp.async.bulk.prefetch.L2.global [%0], %1;" ::"l"(p), "r"(bytes) : "memory");
}
__device__ __forceinline__ void prefetch_tmap(const CUtensorMap* m) {
  asm volatile("prefetch.tensormap [%0];" ::"l"(m) : "memory");
}
__device__ __forceinline__ uint64_t make_desc(uint32_t a16, uint32_t off, uint32_t lbo, uint32_t sbo, uint32_t swz) {
  const uint32_t lo = a16 + ((off >> 4) + ((lbo >> 4) << 16)), hi = (sbo >> 4) | (swz << 30);
  uint64_t d;
  asm("mov.b64 %0, {%1, %2};" : "=l"(d) : "r"(lo), "r"(hi));
  return d;
}
__device__ __forceinline__ void wg_fence() { asm volatile("wgmma.fence.sync.aligned;" ::: "memory"); }
__device__ __forceinline__ void wg_commit() { asm volatile("wgmma.commit_group.sync.aligned;" ::: "memory"); }
template <int N> __device__ __forceinline__ void wg_wait() { asm volatile("wgmma.wait_group.sync.aligned %0;" ::"n"(N) : "memory"); }
template <int N> __device__ __forceinline__ void fence_regs(float (&d)[N]) {
#pragma unroll
  for (int i = 0; i < N; i++) asm volatile("" : "+f"(d[i])::"memory");
}
template <int N> __device__ __forceinline__ void zero_regs(float (&d)[N]) {
#pragma unroll
  for (int i = 0; i < N; i++) d[i] = 0.f;
}
__device__ __forceinline__ uint32_t pack_bf16(float lo, float hi) {
  uint32_t r;
  asm("cvt.rn.bf16x2.f32 %0, %1, %2;" : "=r"(r) : "f"(hi), "f"(lo));
  return r;
}
__device__ __forceinline__ float bf_lo(uint32_t v) { return __uint_as_float(v << 16); }
__device__ __forceinline__ float bf_hi(uint32_t v) { return __uint_as_float(v & 0xffff0000u); }
__device__ __forceinline__ uint32_t max_bf2(uint32_t a, uint32_t b) {
  uint32_t r; asm("max.bf16x2 %0, %1, %2;" : "=r"(r) : "r"(a), "r"(b)); return r;
}
__device__ __forceinline__ uint32_t min_bf2(uint32_t a, uint32_t b) {
  uint32_t r; asm("min.bf16x2 %0, %1, %2;" : "=r"(r) : "r"(a), "r"(b)); return r;
}
__device__ __forceinline__ uint32_t add_bf2(uint32_t a, uint32_t b) {
  uint32_t r; asm("add.rn.bf16x2 %0, %1, %2;" : "=r"(r) : "r"(a), "r"(b)); return r;
}
__device__ __forceinline__ float ex2(float x) { float r; asm("ex2.approx.ftz.f32 %0, %1;" : "=f"(r) : "f"(x)); return r; }
__device__ __forceinline__ float rcp(float x) { float r; asm("rcp.approx.ftz.f32 %0, %1;" : "=f"(r) : "f"(x)); return r; }
__device__ __forceinline__ float tanh_ap(float x) { float r; asm("tanh.approx.f32 %0, %1;" : "=f"(r) : "f"(x)); return r; }
__device__ __forceinline__ float gelu_s(float x, float hs) {
  float u = x * fmaf(x * x, 0.0356774081f, 0.7978845608f);
  float hx = x * hs;
  return fmaf(hx, tanh_ap(u), hx);
}
__device__ __forceinline__ void stsm4(uint32_t addr, uint32_t r0, uint32_t r1, uint32_t r2, uint32_t r3) {
  asm volatile("stmatrix.sync.aligned.m8n8.x4.shared.b16 [%0], {%1, %2, %3, %4};"
               ::"r"(addr), "r"(r0), "r"(r1), "r"(r2), "r"(r3) : "memory");
}
__device__ __forceinline__ void red_add4(float* p, float a, float b, float c, float d) {
  asm volatile("red.global.add.v4.f32 [%0], {%1, %2, %3, %4};" ::"l"(p), "f"(a), "f"(b), "f"(c), "f"(d) : "memory");
}

__device__ __forceinline__ void mma_ss256(float (&d)[128], uint64_t descA, uint64_t descB) {
  asm volatile("wgmma.mma_async.sync.aligned.m64n256k16.f32.bf16.bf16 {"
      "%0, %1, %2, %3, %4, %5, %6, %7, %8, %9, %10, %11, %12, %13, %14, %15, "
      "%16, %17, %18, %19, %20, %21, %22, %23, %24, %25, %26, %27, %28, %29, %30, %31, "
      "%32, %33, %34, %35, %36, %37, %38, %39, %40, %41, %42, %43, %44, %45, %46, %47, "
      "%48, %49, %50, %51, %52, %53, %54, %55, %56, %57, %58, %59, %60, %61, %62, %63, "
      "%64, %65, %66, %67, %68, %69, %70, %71, %72, %73, %74, %75, %76, %77, %78, %79, "
      "%80, %81, %82, %83, %84, %85, %86, %87, %88, %89, %90, %91, %92, %93, %94, %95, "
      "%96, %97, %98, %99, %100, %101, %102, %103, %104, %105, %106, %107, %108, %109, %110, %111, "
      "%112, %113, %114, %115, %116, %117, %118, %119, %120, %121, %122, %123, %124, %125, %126, %127"
      "}, %128, %129, 1, 1, 1, 0, 1;\n"
      : "+f"(d[0]), "+f"(d[1]), "+f"(d[2]), "+f"(d[3]), "+f"(d[4]), "+f"(d[5]), "+f"(d[6]), "+f"(d[7]),
        "+f"(d[8]), "+f"(d[9]), "+f"(d[10]), "+f"(d[11]), "+f"(d[12]), "+f"(d[13]), "+f"(d[14]), "+f"(d[15]),
        "+f"(d[16]), "+f"(d[17]), "+f"(d[18]), "+f"(d[19]), "+f"(d[20]), "+f"(d[21]), "+f"(d[22]), "+f"(d[23]),
        "+f"(d[24]), "+f"(d[25]), "+f"(d[26]), "+f"(d[27]), "+f"(d[28]), "+f"(d[29]), "+f"(d[30]), "+f"(d[31]),
        "+f"(d[32]), "+f"(d[33]), "+f"(d[34]), "+f"(d[35]), "+f"(d[36]), "+f"(d[37]), "+f"(d[38]), "+f"(d[39]),
        "+f"(d[40]), "+f"(d[41]), "+f"(d[42]), "+f"(d[43]), "+f"(d[44]), "+f"(d[45]), "+f"(d[46]), "+f"(d[47]),
        "+f"(d[48]), "+f"(d[49]), "+f"(d[50]), "+f"(d[51]), "+f"(d[52]), "+f"(d[53]), "+f"(d[54]), "+f"(d[55]),
        "+f"(d[56]), "+f"(d[57]), "+f"(d[58]), "+f"(d[59]), "+f"(d[60]), "+f"(d[61]), "+f"(d[62]), "+f"(d[63]),
        "+f"(d[64]), "+f"(d[65]), "+f"(d[66]), "+f"(d[67]), "+f"(d[68]), "+f"(d[69]), "+f"(d[70]), "+f"(d[71]),
        "+f"(d[72]), "+f"(d[73]), "+f"(d[74]), "+f"(d[75]), "+f"(d[76]), "+f"(d[77]), "+f"(d[78]), "+f"(d[79]),
        "+f"(d[80]), "+f"(d[81]), "+f"(d[82]), "+f"(d[83]), "+f"(d[84]), "+f"(d[85]), "+f"(d[86]), "+f"(d[87]),
        "+f"(d[88]), "+f"(d[89]), "+f"(d[90]), "+f"(d[91]), "+f"(d[92]), "+f"(d[93]), "+f"(d[94]), "+f"(d[95]),
        "+f"(d[96]), "+f"(d[97]), "+f"(d[98]), "+f"(d[99]), "+f"(d[100]), "+f"(d[101]), "+f"(d[102]), "+f"(d[103]),
        "+f"(d[104]), "+f"(d[105]), "+f"(d[106]), "+f"(d[107]), "+f"(d[108]), "+f"(d[109]), "+f"(d[110]), "+f"(d[111]),
        "+f"(d[112]), "+f"(d[113]), "+f"(d[114]), "+f"(d[115]), "+f"(d[116]), "+f"(d[117]), "+f"(d[118]), "+f"(d[119]),
        "+f"(d[120]), "+f"(d[121]), "+f"(d[122]), "+f"(d[123]), "+f"(d[124]), "+f"(d[125]), "+f"(d[126]), "+f"(d[127])
      : "l"(descA), "l"(descB));
}

__device__ __forceinline__ void mma_ss64(float (&d)[32], uint64_t descA, uint64_t descB) {
  asm volatile("wgmma.mma_async.sync.aligned.m64n64k16.f32.bf16.bf16 {"
      "%0, %1, %2, %3, %4, %5, %6, %7, %8, %9, %10, %11, %12, %13, %14, %15, "
      "%16, %17, %18, %19, %20, %21, %22, %23, %24, %25, %26, %27, %28, %29, %30, %31"
      "}, %32, %33, 1, 1, 1, 0, 1;\n"
      : "+f"(d[0]), "+f"(d[1]), "+f"(d[2]), "+f"(d[3]), "+f"(d[4]), "+f"(d[5]), "+f"(d[6]), "+f"(d[7]),
        "+f"(d[8]), "+f"(d[9]), "+f"(d[10]), "+f"(d[11]), "+f"(d[12]), "+f"(d[13]), "+f"(d[14]), "+f"(d[15]),
        "+f"(d[16]), "+f"(d[17]), "+f"(d[18]), "+f"(d[19]), "+f"(d[20]), "+f"(d[21]), "+f"(d[22]), "+f"(d[23]),
        "+f"(d[24]), "+f"(d[25]), "+f"(d[26]), "+f"(d[27]), "+f"(d[28]), "+f"(d[29]), "+f"(d[30]), "+f"(d[31])
      : "l"(descA), "l"(descB));
}

__device__ __forceinline__ void mma_ss80(float (&d)[40], uint64_t descA, uint64_t descB) {
  asm volatile("wgmma.mma_async.sync.aligned.m64n80k16.f32.bf16.bf16 {"
      "%0, %1, %2, %3, %4, %5, %6, %7, %8, %9, %10, %11, %12, %13, %14, %15, "
      "%16, %17, %18, %19, %20, %21, %22, %23, %24, %25, %26, %27, %28, %29, %30, %31, "
      "%32, %33, %34, %35, %36, %37, %38, %39"
      "}, %40, %41, 1, 1, 1, 0, 1;\n"
      : "+f"(d[0]), "+f"(d[1]), "+f"(d[2]), "+f"(d[3]), "+f"(d[4]), "+f"(d[5]), "+f"(d[6]), "+f"(d[7]),
        "+f"(d[8]), "+f"(d[9]), "+f"(d[10]), "+f"(d[11]), "+f"(d[12]), "+f"(d[13]), "+f"(d[14]), "+f"(d[15]),
        "+f"(d[16]), "+f"(d[17]), "+f"(d[18]), "+f"(d[19]), "+f"(d[20]), "+f"(d[21]), "+f"(d[22]), "+f"(d[23]),
        "+f"(d[24]), "+f"(d[25]), "+f"(d[26]), "+f"(d[27]), "+f"(d[28]), "+f"(d[29]), "+f"(d[30]), "+f"(d[31]),
        "+f"(d[32]), "+f"(d[33]), "+f"(d[34]), "+f"(d[35]), "+f"(d[36]), "+f"(d[37]), "+f"(d[38]), "+f"(d[39])
      : "l"(descA), "l"(descB));
}

__device__ __forceinline__ void mma_ss192(float (&d)[96], uint64_t descA, uint64_t descB) {
  asm volatile("wgmma.mma_async.sync.aligned.m64n192k16.f32.bf16.bf16 {"
      "%0, %1, %2, %3, %4, %5, %6, %7, %8, %9, %10, %11, %12, %13, %14, %15, "
      "%16, %17, %18, %19, %20, %21, %22, %23, %24, %25, %26, %27, %28, %29, %30, %31, "
      "%32, %33, %34, %35, %36, %37, %38, %39, %40, %41, %42, %43, %44, %45, %46, %47, "
      "%48, %49, %50, %51, %52, %53, %54, %55, %56, %57, %58, %59, %60, %61, %62, %63, "
      "%64, %65, %66, %67, %68, %69, %70, %71, %72, %73, %74, %75, %76, %77, %78, %79, "
      "%80, %81, %82, %83, %84, %85, %86, %87, %88, %89, %90, %91, %92, %93, %94, %95"
      "}, %96, %97, 1, 1, 1, 0, 1;\n"
      : "+f"(d[0]), "+f"(d[1]), "+f"(d[2]), "+f"(d[3]), "+f"(d[4]), "+f"(d[5]), "+f"(d[6]), "+f"(d[7]),
        "+f"(d[8]), "+f"(d[9]), "+f"(d[10]), "+f"(d[11]), "+f"(d[12]), "+f"(d[13]), "+f"(d[14]), "+f"(d[15]),
        "+f"(d[16]), "+f"(d[17]), "+f"(d[18]), "+f"(d[19]), "+f"(d[20]), "+f"(d[21]), "+f"(d[22]), "+f"(d[23]),
        "+f"(d[24]), "+f"(d[25]), "+f"(d[26]), "+f"(d[27]), "+f"(d[28]), "+f"(d[29]), "+f"(d[30]), "+f"(d[31]),
        "+f"(d[32]), "+f"(d[33]), "+f"(d[34]), "+f"(d[35]), "+f"(d[36]), "+f"(d[37]), "+f"(d[38]), "+f"(d[39]),
        "+f"(d[40]), "+f"(d[41]), "+f"(d[42]), "+f"(d[43]), "+f"(d[44]), "+f"(d[45]), "+f"(d[46]), "+f"(d[47]),
        "+f"(d[48]), "+f"(d[49]), "+f"(d[50]), "+f"(d[51]), "+f"(d[52]), "+f"(d[53]), "+f"(d[54]), "+f"(d[55]),
        "+f"(d[56]), "+f"(d[57]), "+f"(d[58]), "+f"(d[59]), "+f"(d[60]), "+f"(d[61]), "+f"(d[62]), "+f"(d[63]),
        "+f"(d[64]), "+f"(d[65]), "+f"(d[66]), "+f"(d[67]), "+f"(d[68]), "+f"(d[69]), "+f"(d[70]), "+f"(d[71]),
        "+f"(d[72]), "+f"(d[73]), "+f"(d[74]), "+f"(d[75]), "+f"(d[76]), "+f"(d[77]), "+f"(d[78]), "+f"(d[79]),
        "+f"(d[80]), "+f"(d[81]), "+f"(d[82]), "+f"(d[83]), "+f"(d[84]), "+f"(d[85]), "+f"(d[86]), "+f"(d[87]),
        "+f"(d[88]), "+f"(d[89]), "+f"(d[90]), "+f"(d[91]), "+f"(d[92]), "+f"(d[93]), "+f"(d[94]), "+f"(d[95])
      : "l"(descA), "l"(descB));
}

__device__ __forceinline__ void mma_ss80_tt(float (&d)[40], uint64_t descA, uint64_t descB) {
  asm volatile("wgmma.mma_async.sync.aligned.m64n80k16.f32.bf16.bf16 {"
      "%0, %1, %2, %3, %4, %5, %6, %7, %8, %9, %10, %11, %12, %13, %14, %15, "
      "%16, %17, %18, %19, %20, %21, %22, %23, %24, %25, %26, %27, %28, %29, %30, %31, "
      "%32, %33, %34, %35, %36, %37, %38, %39"
      "}, %40, %41, 1, 1, 1, 1, 1;\n"
      : "+f"(d[0]), "+f"(d[1]), "+f"(d[2]), "+f"(d[3]), "+f"(d[4]), "+f"(d[5]), "+f"(d[6]), "+f"(d[7]),
        "+f"(d[8]), "+f"(d[9]), "+f"(d[10]), "+f"(d[11]), "+f"(d[12]), "+f"(d[13]), "+f"(d[14]), "+f"(d[15]),
        "+f"(d[16]), "+f"(d[17]), "+f"(d[18]), "+f"(d[19]), "+f"(d[20]), "+f"(d[21]), "+f"(d[22]), "+f"(d[23]),
        "+f"(d[24]), "+f"(d[25]), "+f"(d[26]), "+f"(d[27]), "+f"(d[28]), "+f"(d[29]), "+f"(d[30]), "+f"(d[31]),
        "+f"(d[32]), "+f"(d[33]), "+f"(d[34]), "+f"(d[35]), "+f"(d[36]), "+f"(d[37]), "+f"(d[38]), "+f"(d[39])
      : "l"(descA), "l"(descB));
}
__device__ __forceinline__ void mma_ss80_tt_z(float (&d)[40], uint64_t descA, uint64_t descB) {
  asm volatile("wgmma.mma_async.sync.aligned.m64n80k16.f32.bf16.bf16 {"
      "%0, %1, %2, %3, %4, %5, %6, %7, %8, %9, %10, %11, %12, %13, %14, %15, "
      "%16, %17, %18, %19, %20, %21, %22, %23, %24, %25, %26, %27, %28, %29, %30, %31, "
      "%32, %33, %34, %35, %36, %37, %38, %39"
      "}, %40, %41, 0, 1, 1, 1, 1;\n"
      : "=f"(d[0]), "=f"(d[1]), "=f"(d[2]), "=f"(d[3]), "=f"(d[4]), "=f"(d[5]), "=f"(d[6]), "=f"(d[7]),
        "=f"(d[8]), "=f"(d[9]), "=f"(d[10]), "=f"(d[11]), "=f"(d[12]), "=f"(d[13]), "=f"(d[14]), "=f"(d[15]),
        "=f"(d[16]), "=f"(d[17]), "=f"(d[18]), "=f"(d[19]), "=f"(d[20]), "=f"(d[21]), "=f"(d[22]), "=f"(d[23]),
        "=f"(d[24]), "=f"(d[25]), "=f"(d[26]), "=f"(d[27]), "=f"(d[28]), "=f"(d[29]), "=f"(d[30]), "=f"(d[31]),
        "=f"(d[32]), "=f"(d[33]), "=f"(d[34]), "=f"(d[35]), "=f"(d[36]), "=f"(d[37]), "=f"(d[38]), "=f"(d[39])
      : "l"(descA), "l"(descB));
}

__device__ __forceinline__ void mma_rs80_k(float (&d)[40], const uint32_t (&a)[4], uint64_t descB) {
  asm volatile("wgmma.mma_async.sync.aligned.m64n80k16.f32.bf16.bf16 {"
      "%0, %1, %2, %3, %4, %5, %6, %7, %8, %9, %10, %11, %12, %13, %14, %15, "
      "%16, %17, %18, %19, %20, %21, %22, %23, %24, %25, %26, %27, %28, %29, %30, %31, "
      "%32, %33, %34, %35, %36, %37, %38, %39"
      "}, {%40, %41, %42, %43}, %44, 1, 1, 1, 0;\n"
      : "+f"(d[0]), "+f"(d[1]), "+f"(d[2]), "+f"(d[3]), "+f"(d[4]), "+f"(d[5]), "+f"(d[6]), "+f"(d[7]),
        "+f"(d[8]), "+f"(d[9]), "+f"(d[10]), "+f"(d[11]), "+f"(d[12]), "+f"(d[13]), "+f"(d[14]), "+f"(d[15]),
        "+f"(d[16]), "+f"(d[17]), "+f"(d[18]), "+f"(d[19]), "+f"(d[20]), "+f"(d[21]), "+f"(d[22]), "+f"(d[23]),
        "+f"(d[24]), "+f"(d[25]), "+f"(d[26]), "+f"(d[27]), "+f"(d[28]), "+f"(d[29]), "+f"(d[30]), "+f"(d[31]),
        "+f"(d[32]), "+f"(d[33]), "+f"(d[34]), "+f"(d[35]), "+f"(d[36]), "+f"(d[37]), "+f"(d[38]), "+f"(d[39])
      : "r"(a[0]), "r"(a[1]), "r"(a[2]), "r"(a[3]), "l"(descB));
}
__device__ __forceinline__ void mma_rs80_k_z(float (&d)[40], const uint32_t (&a)[4], uint64_t descB) {
  asm volatile("wgmma.mma_async.sync.aligned.m64n80k16.f32.bf16.bf16 {"
      "%0, %1, %2, %3, %4, %5, %6, %7, %8, %9, %10, %11, %12, %13, %14, %15, "
      "%16, %17, %18, %19, %20, %21, %22, %23, %24, %25, %26, %27, %28, %29, %30, %31, "
      "%32, %33, %34, %35, %36, %37, %38, %39"
      "}, {%40, %41, %42, %43}, %44, 0, 1, 1, 0;\n"
      : "=f"(d[0]), "=f"(d[1]), "=f"(d[2]), "=f"(d[3]), "=f"(d[4]), "=f"(d[5]), "=f"(d[6]), "=f"(d[7]),
        "=f"(d[8]), "=f"(d[9]), "=f"(d[10]), "=f"(d[11]), "=f"(d[12]), "=f"(d[13]), "=f"(d[14]), "=f"(d[15]),
        "=f"(d[16]), "=f"(d[17]), "=f"(d[18]), "=f"(d[19]), "=f"(d[20]), "=f"(d[21]), "=f"(d[22]), "=f"(d[23]),
        "=f"(d[24]), "=f"(d[25]), "=f"(d[26]), "=f"(d[27]), "=f"(d[28]), "=f"(d[29]), "=f"(d[30]), "=f"(d[31]),
        "=f"(d[32]), "=f"(d[33]), "=f"(d[34]), "=f"(d[35]), "=f"(d[36]), "=f"(d[37]), "=f"(d[38]), "=f"(d[39])
      : "r"(a[0]), "r"(a[1]), "r"(a[2]), "r"(a[3]), "l"(descB));
}

__device__ __forceinline__ void mma_rs48_k(float (&d)[24], const uint32_t (&a)[4], uint64_t descB) {
  asm volatile("wgmma.mma_async.sync.aligned.m64n48k16.f32.bf16.bf16 {"
      "%0, %1, %2, %3, %4, %5, %6, %7, %8, %9, %10, %11, %12, %13, %14, %15, "
      "%16, %17, %18, %19, %20, %21, %22, %23"
      "}, {%24, %25, %26, %27}, %28, 1, 1, 1, 0;\n"
      : "+f"(d[0]), "+f"(d[1]), "+f"(d[2]), "+f"(d[3]), "+f"(d[4]), "+f"(d[5]), "+f"(d[6]), "+f"(d[7]),
        "+f"(d[8]), "+f"(d[9]), "+f"(d[10]), "+f"(d[11]), "+f"(d[12]), "+f"(d[13]), "+f"(d[14]), "+f"(d[15]),
        "+f"(d[16]), "+f"(d[17]), "+f"(d[18]), "+f"(d[19]), "+f"(d[20]), "+f"(d[21]), "+f"(d[22]), "+f"(d[23])
      : "r"(a[0]), "r"(a[1]), "r"(a[2]), "r"(a[3]), "l"(descB));
}
__device__ __forceinline__ void mma_rs48_k_z(float (&d)[24], const uint32_t (&a)[4], uint64_t descB) {
  asm volatile("wgmma.mma_async.sync.aligned.m64n48k16.f32.bf16.bf16 {"
      "%0, %1, %2, %3, %4, %5, %6, %7, %8, %9, %10, %11, %12, %13, %14, %15, "
      "%16, %17, %18, %19, %20, %21, %22, %23"
      "}, {%24, %25, %26, %27}, %28, 0, 1, 1, 0;\n"
      : "=f"(d[0]), "=f"(d[1]), "=f"(d[2]), "=f"(d[3]), "=f"(d[4]), "=f"(d[5]), "=f"(d[6]), "=f"(d[7]),
        "=f"(d[8]), "=f"(d[9]), "=f"(d[10]), "=f"(d[11]), "=f"(d[12]), "=f"(d[13]), "=f"(d[14]), "=f"(d[15]),
        "=f"(d[16]), "=f"(d[17]), "=f"(d[18]), "=f"(d[19]), "=f"(d[20]), "=f"(d[21]), "=f"(d[22]), "=f"(d[23])
      : "r"(a[0]), "r"(a[1]), "r"(a[2]), "r"(a[3]), "l"(descB));
}

__device__ __forceinline__ void mma_rs160_n(float (&d)[80], const uint32_t (&a)[4], uint64_t descB) {
  asm volatile("wgmma.mma_async.sync.aligned.m64n160k16.f32.bf16.bf16 {"
      "%0, %1, %2, %3, %4, %5, %6, %7, %8, %9, %10, %11, %12, %13, %14, %15, "
      "%16, %17, %18, %19, %20, %21, %22, %23, %24, %25, %26, %27, %28, %29, %30, %31, "
      "%32, %33, %34, %35, %36, %37, %38, %39, %40, %41, %42, %43, %44, %45, %46, %47, "
      "%48, %49, %50, %51, %52, %53, %54, %55, %56, %57, %58, %59, %60, %61, %62, %63, "
      "%64, %65, %66, %67, %68, %69, %70, %71, %72, %73, %74, %75, %76, %77, %78, %79"
      "}, {%80, %81, %82, %83}, %84, 1, 1, 1, 1;\n"
      : "+f"(d[0]), "+f"(d[1]), "+f"(d[2]), "+f"(d[3]), "+f"(d[4]), "+f"(d[5]), "+f"(d[6]), "+f"(d[7]),
        "+f"(d[8]), "+f"(d[9]), "+f"(d[10]), "+f"(d[11]), "+f"(d[12]), "+f"(d[13]), "+f"(d[14]), "+f"(d[15]),
        "+f"(d[16]), "+f"(d[17]), "+f"(d[18]), "+f"(d[19]), "+f"(d[20]), "+f"(d[21]), "+f"(d[22]), "+f"(d[23]),
        "+f"(d[24]), "+f"(d[25]), "+f"(d[26]), "+f"(d[27]), "+f"(d[28]), "+f"(d[29]), "+f"(d[30]), "+f"(d[31]),
        "+f"(d[32]), "+f"(d[33]), "+f"(d[34]), "+f"(d[35]), "+f"(d[36]), "+f"(d[37]), "+f"(d[38]), "+f"(d[39]),
        "+f"(d[40]), "+f"(d[41]), "+f"(d[42]), "+f"(d[43]), "+f"(d[44]), "+f"(d[45]), "+f"(d[46]), "+f"(d[47]),
        "+f"(d[48]), "+f"(d[49]), "+f"(d[50]), "+f"(d[51]), "+f"(d[52]), "+f"(d[53]), "+f"(d[54]), "+f"(d[55]),
        "+f"(d[56]), "+f"(d[57]), "+f"(d[58]), "+f"(d[59]), "+f"(d[60]), "+f"(d[61]), "+f"(d[62]), "+f"(d[63]),
        "+f"(d[64]), "+f"(d[65]), "+f"(d[66]), "+f"(d[67]), "+f"(d[68]), "+f"(d[69]), "+f"(d[70]), "+f"(d[71]),
        "+f"(d[72]), "+f"(d[73]), "+f"(d[74]), "+f"(d[75]), "+f"(d[76]), "+f"(d[77]), "+f"(d[78]), "+f"(d[79])
      : "r"(a[0]), "r"(a[1]), "r"(a[2]), "r"(a[3]), "l"(descB));
}
__device__ __forceinline__ void mma_rs160_n_z(float (&d)[80], const uint32_t (&a)[4], uint64_t descB) {
  asm volatile("wgmma.mma_async.sync.aligned.m64n160k16.f32.bf16.bf16 {"
      "%0, %1, %2, %3, %4, %5, %6, %7, %8, %9, %10, %11, %12, %13, %14, %15, "
      "%16, %17, %18, %19, %20, %21, %22, %23, %24, %25, %26, %27, %28, %29, %30, %31, "
      "%32, %33, %34, %35, %36, %37, %38, %39, %40, %41, %42, %43, %44, %45, %46, %47, "
      "%48, %49, %50, %51, %52, %53, %54, %55, %56, %57, %58, %59, %60, %61, %62, %63, "
      "%64, %65, %66, %67, %68, %69, %70, %71, %72, %73, %74, %75, %76, %77, %78, %79"
      "}, {%80, %81, %82, %83}, %84, 0, 1, 1, 1;\n"
      : "=f"(d[0]), "=f"(d[1]), "=f"(d[2]), "=f"(d[3]), "=f"(d[4]), "=f"(d[5]), "=f"(d[6]), "=f"(d[7]),
        "=f"(d[8]), "=f"(d[9]), "=f"(d[10]), "=f"(d[11]), "=f"(d[12]), "=f"(d[13]), "=f"(d[14]), "=f"(d[15]),
        "=f"(d[16]), "=f"(d[17]), "=f"(d[18]), "=f"(d[19]), "=f"(d[20]), "=f"(d[21]), "=f"(d[22]), "=f"(d[23]),
        "=f"(d[24]), "=f"(d[25]), "=f"(d[26]), "=f"(d[27]), "=f"(d[28]), "=f"(d[29]), "=f"(d[30]), "=f"(d[31]),
        "=f"(d[32]), "=f"(d[33]), "=f"(d[34]), "=f"(d[35]), "=f"(d[36]), "=f"(d[37]), "=f"(d[38]), "=f"(d[39]),
        "=f"(d[40]), "=f"(d[41]), "=f"(d[42]), "=f"(d[43]), "=f"(d[44]), "=f"(d[45]), "=f"(d[46]), "=f"(d[47]),
        "=f"(d[48]), "=f"(d[49]), "=f"(d[50]), "=f"(d[51]), "=f"(d[52]), "=f"(d[53]), "=f"(d[54]), "=f"(d[55]),
        "=f"(d[56]), "=f"(d[57]), "=f"(d[58]), "=f"(d[59]), "=f"(d[60]), "=f"(d[61]), "=f"(d[62]), "=f"(d[63]),
        "=f"(d[64]), "=f"(d[65]), "=f"(d[66]), "=f"(d[67]), "=f"(d[68]), "=f"(d[69]), "=f"(d[70]), "=f"(d[71]),
        "=f"(d[72]), "=f"(d[73]), "=f"(d[74]), "=f"(d[75]), "=f"(d[76]), "=f"(d[77]), "=f"(d[78]), "=f"(d[79])
      : "r"(a[0]), "r"(a[1]), "r"(a[2]), "r"(a[3]), "l"(descB));
}

__device__ __forceinline__ void feature_map(const uint32_t (&P)[2][10], uint32_t (&fr)[10][4]) {
  constexpr float L2E = 1.4426950408889634f;
#pragma unroll
  for (int p = 0; p < 2; p++) {
#pragma unroll
    for (int r = 0; r < 2; r++) {
      uint32_t mx = P[r][5 * p], mn = mx;
#pragma unroll
      for (int g = 1; g < 5; g++) { mx = max_bf2(mx, P[r][5 * p + g]); mn = min_bf2(mn, P[r][5 * p + g]); }
      mx = max_bf2(mx, __shfl_xor_sync(0xffffffffu, mx, 1));
      mn = min_bf2(mn, __shfl_xor_sync(0xffffffffu, mn, 1));
      mx = max_bf2(mx, __shfl_xor_sync(0xffffffffu, mx, 2));
      mn = min_bf2(mn, __shfl_xor_sync(0xffffffffu, mn, 2));
      float mx0 = -bf_lo(mx) * L2E, mx1 = -bf_hi(mx) * L2E, mn0 = bf_lo(mn) * L2E, mn1 = bf_hi(mn) * L2E;
      float ep0[5], ep1[5], en0[5], en1[5];
      float sp0 = 0.f, sp1 = 0.f, sn0 = 0.f, sn1 = 0.f;
#pragma unroll
      for (int g = 0; g < 5; g++) {
        float x0 = bf_lo(P[r][5 * p + g]), x1 = bf_hi(P[r][5 * p + g]);
        ep0[g] = ex2(fmaf(x0, L2E, mx0)); ep1[g] = ex2(fmaf(x1, L2E, mx1));
        en0[g] = ex2(fmaf(x0, -L2E, mn0)); en1[g] = ex2(fmaf(x1, -L2E, mn1));
        sp0 += ep0[g]; sp1 += ep1[g]; sn0 += en0[g]; sn1 += en1[g];
      }
      sp0 += __shfl_xor_sync(0xffffffffu, sp0, 1); sp1 += __shfl_xor_sync(0xffffffffu, sp1, 1);
      sn0 += __shfl_xor_sync(0xffffffffu, sn0, 1); sn1 += __shfl_xor_sync(0xffffffffu, sn1, 1);
      sp0 += __shfl_xor_sync(0xffffffffu, sp0, 2); sp1 += __shfl_xor_sync(0xffffffffu, sp1, 2);
      sn0 += __shfl_xor_sync(0xffffffffu, sn0, 2); sn1 += __shfl_xor_sync(0xffffffffu, sn1, 2);
      sp0 = rcp(sp0); sp1 = rcp(sp1); sn0 = rcp(sn0); sn1 = rcp(sn1);
#pragma unroll
      for (int g = 0; g < 5; g++) {
        fr[5 * p + g][r] = pack_bf16(ep0[g] * sp0, ep1[g] * sp1);
        fr[5 * p + g][2 + r] = pack_bf16(en0[g] * sn0, en1[g] * sn1);
      }
    }
  }
}

template <bool V> struct BoolC { static constexpr bool value = V; };
struct Ring {
  uint32_t idx, phase;
  template <int N> __device__ __forceinline__ void next() { if (++idx == N) { idx = 0; phase ^= 1; } }
};

}

__global__ void __cluster_dims__(2, 1, 1) __launch_bounds__(384, 1)
fused_kernel(const __grid_constant__ Maps maps, const __nv_bfloat16* __restrict__ x, const __nv_bfloat16* __restrict__ wqkv,
             const __nv_bfloat16* __restrict__ wphi, const __nv_bfloat16* __restrict__ w1, const __nv_bfloat16* __restrict__ w2,
             const __nv_bfloat16* __restrict__ w3, const __nv_bfloat16* __restrict__ w4, const __nv_bfloat16* __restrict__ wo,
             const __nv_bfloat16* __restrict__ gate_w) {
  extern __shared__ __align__(1024) uint8_t sgen[];
  const uint32_t sb = smem_u32(sgen);
  const uint32_t sb16 = (sb & 0x3FFFFu) >> 4;
  const uint32_t bars = sb + OFF_BAR;
  const uint32_t fullA = bars + 8 * B_FULLA, emptyA = bars + 8 * B_EMPTYA, fullB = bars + 8 * B_FULLB, emptyB = bars + 8 * B_EMPTYB;

  const int tid = threadIdx.x;
  const int rank = blockIdx.x & 1;
  const int pairIdx = blockIdx.x >> 1;
  const int i = pairIdx >> 2, j = 2 * (pairIdx & 3) + rank;

  TSTAMP(0);
  auto load_p1_b = [&](int k, uint32_t slot, uint32_t bar) {
    mbar_expect_tx(bar, 40960);
    tma4d(slot + 8192, &maps.qm, bar, 0, 64 * k, 0, j);
    tma3d(slot, &maps.w1m, bar, 0, 64 * k, j);
    tma4d(slot + 32768 + 2048, &maps.qr, bar, 64, 64 * k, 0, j);
    tma3d(slot + 32768, &maps.w1r, bar, 64, 64 * k, j);
  };
  if (tid >= 256) {
    asm volatile("setmaxnreg.dec.sync.aligned.u32 40;");
    if (tid == 256) {
#pragma unroll
      for (int s = 0; s < NA; s++) mbar_init(fullA + 8 * s, 1);
      asm volatile("fence.mbarrier_init.release.cluster;" ::: "memory");
#pragma unroll 1
      for (int u = 0; u < 4; u++) {
        if ((u & 1) == 0) mbar_expect_tx(fullA + 4 * u, SLOT_A);
        tma2d(sb + OFF_A + u * 8192, &maps.x, fullA + 8 * (u >> 1), 64 * (u >> 1), 128 * i + 64 * (u & 1));
      }
    } else if (tid == 288) {
#pragma unroll
      for (int s = 0; s < NB; s++) mbar_init(fullB + 8 * s, 1);
      asm volatile("fence.mbarrier_init.release.cluster;" ::: "memory");
#pragma unroll 1
      for (int k = 0; k < 2; k++) load_p1_b(k, sb + OFF_B + k * SLOT_B, fullB + 8 * k);
    } else if (tid == 320) {
#pragma unroll
      for (int b = B_CS; b < NBAR; b++) mbar_init(bars + 8 * b, b < B_SEND ? 1 : b < B_EMPTYB ? 4 : b < B_EMPTYA ? 8 : 16);
#pragma unroll
      for (int b = B_DSR; b < B_SEND; b++) mbar_expect_tx(bars + 8 * b, 10240);
      asm volatile("fence.mbarrier_init.release.cluster;" ::: "memory");
    }
    __syncwarp();
    asm volatile("barrier.cluster.arrive.relaxed.aligned;" ::: "memory");
    auto get_epoch = [&]() { return *reinterpret_cast<volatile unsigned*>(g_flags + FL_DONE * 32) / NCTA; };
    if (tid >= 320) {
      const int lane = tid & 31, ch = lane % 10, rg = lane / 10;
      const __nv_bfloat16* p = w1 + (size_t)(40 * i + (tid >= 352 ? 20 : 0) + rg) * D_ + 80 * j + 8 * ch;
      const unsigned par = get_epoch() & 1;
      float a[8];
#pragma unroll
      for (int e = 0; e < 8; e++) a[e] = 0.f;
#pragma unroll
      for (int it = 0; it < 7; it++) {
        uint4 v = make_uint4(0, 0, 0, 0);
        if (lane < 30 && 3 * it + rg < 20) v = __ldg(reinterpret_cast<const uint4*>(p + (size_t)it * 3 * D_));
        a[0] += bf_lo(v.x); a[1] += bf_hi(v.x); a[2] += bf_lo(v.y); a[3] += bf_hi(v.y);
        a[4] += bf_lo(v.z); a[5] += bf_hi(v.z); a[6] += bf_lo(v.w); a[7] += bf_hi(v.w);
      }
#pragma unroll
      for (int e = 0; e < 8; e++) a[e] += __shfl_down_sync(0xffffffffu, a[e], 10) + __shfl_down_sync(0xffffffffu, a[e], 20);
      if (lane < 10) {
        float* cd = g_acc[par] + 8 * KV_J + 80 * j + 8 * ch;
        red_add4(cd, a[0], a[1], a[2], a[3]); red_add4(cd + 4, a[4], a[5], a[6], a[7]);
      }
      __syncwarp();
      if (lane == 0) flag_add(FL_CS + j);
      __syncwarp();
    }
    asm volatile("barrier.cluster.wait.aligned;" ::: "memory");
    const int lane = tid & 31, pw = (tid >> 5) & 3;
    auto send_stream = [&](int w, unsigned ep1) {
#pragma unroll 1
      for (int c = 0; c < 3; c++) {
        mbar_wait(bars + 8 * (B_SEND + 2 * c + w), 0);
        fence_async_all();
        asm volatile("st.release.gpu.global.u32 [%0], %1;"
                     ::"l"(g_flags + (FL_PART + i * 8 + ((j + 2 * c + 2) & 7)) * 32 + 2 * c + w), "r"(ep1) : "memory");
      }
    };
    if (pw == 0) {
      if (tid == 256) {
        Ring r{2, 1};
        unsigned ep1 = 0;
#pragma unroll 1
        for (int k = 2; k < 30; k++) {
          if (k == 4) ep1 = get_epoch() + 1;
          if (k == 10 || k == 20) {
            const unsigned tgt = ep1 * 8u;
            const unsigned* f0 = g_flags + (k == 10 ? FL_H + ((i - 1) & 15) : FL_X1 + i) * 32;
            const unsigned* f1 = g_flags + (k == 10 ? FL_H + i : FL_X1 + i) * 32;
            const unsigned* f2 = g_flags + (k == 10 ? FL_H + ((i + 1) & 15) : FL_X1 + i) * 32;
            uint32_t n = 0;
            while (++n < (WAIT_LIMIT >> 4)) {
              unsigned v0, v1, v2;
              asm volatile("ld.relaxed.gpu.global.u32 %0, [%3];\nld.relaxed.gpu.global.u32 %1, [%4];\nld.acquire.gpu.global.u32 %2, [%5];"
                           : "=r"(v0), "=r"(v1), "=r"(v2) : "l"(f0), "l"(f1), "l"(f2) : "memory");
              if ((int)((v0 - tgt) | (v1 - tgt) | (v2 - tgt)) >= 0) break;
            }
            TSTAMPX(k == 10 ? 29 : 30);
          }
          mbar_wait(emptyA + 8 * r.idx, r.phase);
          const uint32_t bar = fullA + 8 * r.idx, slot = sb + OFF_A + r.idx * SLOT_A;
          TRACE(k);
          mbar_expect_tx(bar, SLOT_A);
          tma2d_mc(slot + rank * 8192, k < 10 ? &maps.x : k < 20 ? &maps.hs : &maps.x1, bar, 64 * (k % 10), 128 * i + 64 * rank);
          r.next<NA>();
        }
        send_stream(1, ep1);
      }
    } else if (pw == 1) {
      if (tid == 288) {
        Ring r{2, 1};
#pragma unroll 1
        for (int k = 2; k < 18; k++) {
          mbar_wait(emptyB + 8 * r.idx, r.phase);
          const uint32_t bar = fullB + 8 * r.idx, slot = sb + OFF_B + r.idx * SLOT_B;
          if (k < 10) {
            load_p1_b(k, slot, bar);
          } else if (k < 13) {
            if (k == 12) mbar_wait(fullA + 8 * 2, 0);
            mbar_expect_tx(bar, k < 12 ? 40960 : 20480);
#pragma unroll 1
            for (int u = 0; u < (k < 12 ? 4 : 2); u++) tma3d(slot + u * 10240, &maps.w2, bar, 0, 256 * (k - 10) + 64 * u, 5 * j);
          } else {
            mbar_expect_tx(bar, 49152);
            tma3d(slot, &maps.w3, bar, 0, 128 * (k - 13), 3 * j);
            tma3d(slot + 24576, &maps.w3, bar, 0, 128 * (k - 13) + 64, 3 * j);
          }
          r.next<NB>();
        }
        Ring r4{0, 1};
#pragma unroll 1
        for (int n = 0; n < 16; n++) {
          if (n == 0 || n == 1 || n == 3) { mbar_wait(emptyB + 8 * r.idx, r.phase); r.next<NB>(); }
          mbar_wait(bars + 8 * (B_EMPTY4 + r4.idx), r4.phase);
          const uint32_t bar = bars + 8 * (B_FULL4 + r4.idx), slot = sb + OFF_B + r4.idx * UNIT4;
          const int u = n & 3, m = ((j >> 1) + 1 + (n >> 2)) & 3;
          mbar_expect_tx(bar, u == 3 ? 25600 : 20480);
          tma3d(slot, u == 3 ? &maps.wo : &maps.w4, bar, 0, u == 3 ? 80 * j : 192 * j + 64 * u, 5 * m);
          r4.next<NU4>();
        }
      }
    } else {
      const unsigned epoch = get_epoch();
      float* accg = g_acc[epoch & 1];
      if (pw == 2) {
        {
          float* nxt = g_acc[(epoch + 1) & 1];
          constexpr int PER = ACC_FLOATS / NCTA;
#pragma unroll 1
          for (int e = lane; e < PER; e += 32) nxt[blockIdx.x * PER + e] = 0.f;
        }
        if (tid == 320) {
          flag_wait(FL_CS + j, (epoch + 1) * 32u);
          flag_wait(FL_ST + i, (epoch + 1) * 8u);
          fence_async_all();
          mbar_expect_tx(bars + 8 * B_CS, 320 + 2048);
          bulk_load(sb + OFF_CS, accg + 8 * KV_J + 80 * j, 320, bars + 8 * B_CS);
          bulk_load(sb + OFF_XST, g_xstat + 128 * i, 2048, bars + 8 * B_CS);
          TSTAMPX(21);
          l2_prefetch(w2 + (size_t)blockIdx.x * (D_ * D_ / NCTA), D_ * D_ * 2 / NCTA);
          flag_wait(FL_H + i, (epoch + 1) * 8u);
          l2_prefetch(w3 + (size_t)blockIdx.x * (F_ * D_ / NCTA), F_ * D_ * 2 / NCTA);
          l2_prefetch(w4 + (size_t)blockIdx.x * (F_ * D_ / NCTA), F_ * D_ * 2 / NCTA);
          l2_prefetch(wo + (size_t)blockIdx.x * (D_ * D_ / NCTA), D_ * D_ * 2 / NCTA);
          flag_wait(FL_KV + j, (epoch + 1) * 16u);
          mbar_expect_tx(bars + 8 * B_KV, KV_J * 4);
          bulk_load(sb + OFF_MISC, accg + j * KV_J, KV_J * 4, bars + 8 * B_KV);
          TSTAMPX(22);
        }
        __syncwarp();
#pragma unroll 1
        for (int m = 0; m < 6; m++) {
          const int col = 192 * j + 32 * m + 8 * (lane & 3);
          const __nv_bfloat16* p = w3 + (size_t)(40 * i + (lane >> 2) * 5) * F_ + col;
          float a[8];
#pragma unroll
          for (int e = 0; e < 8; e++) a[e] = 0.f;
#pragma unroll
          for (int it = 0; it < 5; it++) {
            const uint4 v = __ldg(reinterpret_cast<const uint4*>(p + (size_t)it * F_));
            a[0] += bf_lo(v.x); a[1] += bf_hi(v.x); a[2] += bf_lo(v.y); a[3] += bf_hi(v.y);
            a[4] += bf_lo(v.z); a[5] += bf_hi(v.z); a[6] += bf_lo(v.w); a[7] += bf_hi(v.w);
          }
#pragma unroll
          for (int e = 0; e < 4; e++) {
            const float snd = (lane & 4) ? a[e] : a[e + 4], keep = (lane & 4) ? a[e + 4] : a[e];
            a[e] = keep + __shfl_xor_sync(0xffffffffu, snd, 4);
            a[e] += __shfl_xor_sync(0xffffffffu, a[e], 8);
            a[e] += __shfl_xor_sync(0xffffffffu, a[e], 16);
          }
          if (lane < 8) red_add4(accg + 8 * KV_J + D_ + col + (lane >> 2) * 4, a[0], a[1], a[2], a[3]);
        }
        __syncwarp();
        if (tid == 320) {
          flag_add(FL_CS3 + j);
          mbar_wait(bars + 8 * B_MFREE, 0);
          flag_wait(FL_X1 + i, (epoch + 1) * 8u);
          flag_wait(FL_CS3 + j, (epoch + 1) * 16u);
          fence_async_all();
          mbar_expect_tx(bars + 8 * B_ST1, 8192 + 768);
          bulk_load(sb + OFF_CS + 320, accg + 8 * KV_J + D_ + 192 * j, 768, bars + 8 * B_ST1);
          bulk_load(sb + OFF_MISC, g_st1 + 128 * i * 8, 8192, bars + 8 * B_ST1);
        }
        __syncwarp();
        mbar_wait(bars + 8 * B_PEER, 0);
        const unsigned* fp = g_flags + (FL_PART + i * 8 + j) * 32 + lane;
        bool seen = lane >= 6;
        uint32_t n = 0;
        while (!__all_sync(0xffffffffu, seen) && ++n < (WAIT_LIMIT >> 4)) {
          if (!seen && ld_acquire(fp) == epoch + 1 && (lane < 4 || (mbar_test(bars + 8 * (B_SEND + 2), 0) && mbar_test(bars + 8 * (B_SEND + 3), 0) &&
                                                                  mbar_test(bars + 8 * (B_EMPTY4 + 1), 0)))) {
            seen = true;
            mbar_expect_tx(bars + 8 * (B_RDY + lane), 10240);
            bulk_load(sb + (lane < 4 ? OFF_G0 : OFF_G2 - 40960) + lane * 10240, g_part + (size_t)(i * 8 + j) * 3840 + lane * 640, 10240,
                      bars + 8 * (B_RDY + lane));
          }
        }
      }
      if (tid == 352) {
        mbar_wait(bars + 8 * B_SIGP, 0);
        flag_add(FL_ST + i);
        TSTAMPX(20);
        mbar_expect_tx(bars + 8 * B_XR, 20480);
#pragma unroll 1
        for (int u = 0; u < 8; u++)
          tma2d(sb + OFF_B + (u / 3) * SLOT_B + SPARE + (u % 3) * 2560, &maps.xr, bars + 8 * B_XR, 80 * j, 128 * i + 16 * u);
        const int shift = (j < 2) ? 1 : (j < 4) ? -1 : (j < 6) ? 2 : -2;
        if ((shift > 0 && i == 0) || (shift < 0 && i == 15)) {
          const int nz = shift > 0 ? shift : -shift, zr = shift > 0 ? 0 : S_ - nz;
#pragma unroll 1
          for (int e = 0; e < nz * 10; e++)
            reinterpret_cast<uint4*>(g_Hs + (size_t)(2 + zr + e / 10) * D_ + 80 * j)[e % 10] = make_uint4(0, 0, 0, 0);
          fence_async_all();
        }
        prefetch_tmap(&maps.st_h); prefetch_tmap(&maps.st_x1); prefetch_tmap(&maps.hs); prefetch_tmap(&maps.x1); prefetch_tmap(&maps.xr);
        prefetch_tmap(&maps.w2); prefetch_tmap(&maps.w3); prefetch_tmap(&maps.w4); prefetch_tmap(&maps.wo); prefetch_tmap(&maps.st_out);
        mbar_wait(bars + 8 * B_SIGH, 0);
        TSTAMPX(23);
        tma2d_store(&maps.st_h, sb + OFF_STG, 80 * j, 128 * i + 2 + shift);
        tma2d_store(&maps.st_h, sb + OFF_STG + 10240, 80 * j, 128 * i + 66 + shift);
        bulk_commit(); bulk_wait<0>();
        flag_add(FL_H + i);
        TSTAMPX(24);
        mbar_wait(bars + 8 * B_SIGKV, 0);
        TSTAMPX(25);
        asm volatile("cp.reduce.async.bulk.global.shared::cta.bulk_group.add.f32 [%0], [%1], %2;"
                     ::"l"(accg + j * KV_J), "r"(sb + OFF_MISC), "r"(KV_J * 4) : "memory");
        bulk_commit(); bulk_wait<0>();
        flag_add(FL_KV + j);
        TSTAMPX(26);
        mbar_wait(bars + 8 * B_SIGX1, 0);
        TSTAMPX(27);
        tma2d_store(&maps.st_x1, sb + OFF_STG, 80 * j, 128 * i);
        tma2d_store(&maps.st_x1, sb + OFF_STG + 10240, 80 * j, 128 * i + 64);
        bulk_commit(); bulk_wait<0>();
        flag_add(FL_X1 + i);
        TSTAMPX(28);
        send_stream(0, epoch + 1);
      }
    }
  } else {
    uint4 pv[5], pw_[5], pre;
    {
      const int row = 128 * i + 16 * j + (tid >> 4), l16 = tid & 15;
#pragma unroll
      for (int c = 0; c < 5; c++) pv[c] = __ldg(reinterpret_cast<const uint4*>(x + (size_t)row * D_ + c * 128 + l16 * 8));
      pre = __ldg(reinterpret_cast<const uint4*>(wphi + (size_t)j * 1600) + (tid < 200 ? tid : 0));
#pragma unroll
      for (int c = 0; c < 5; c++) pw_[c] = __ldg(reinterpret_cast<const uint4*>(gate_w + c * 128 + l16 * 8));
    }
    asm volatile("barrier.cluster.arrive.relaxed.aligned;" ::: "memory");
    asm volatile("setmaxnreg.inc.sync.aligned.u32 232;");
    const int wg = tid >> 7, warp = tid >> 5, lane = tid & 31, t = lane & 3;
    const int rloc = warp * 16 + (lane >> 2);
    const float* s_cs = reinterpret_cast<const float*>(sgen + OFF_CS);
    auto signal = [&](int b) {
      __syncwarp();
      if (lane == 0) mbar_arrive(bars + 8 * b);
    };
    auto releaseB = [&](uint32_t bar) {
      __syncwarp();
      if (lane == 0) mbar_arrive(bar);
    };
    auto release = [&](uint32_t bar) {
      __syncwarp();
      if (lane < 2) mbar_arrive_cta(bar, lane);
    };
    const uint32_t stg_lane = (warp * 16 + ((lane >> 3) & 1) * 8 + (lane & 7)) * 160 + (lane >> 4) * 16;

    {
#pragma unroll 1
      for (int e = tid; e < 800; e += 256) sts128(sb + OFF_MISC + e * 16, make_uint4(0, 0, 0, 0));
      bar_sync(1, 256);
      float f[40];
      float s = 0.f, gs = 0.f;
#pragma unroll
      for (int c = 0; c < 5; c++) {
        const uint32_t vv[4] = {pv[c].x, pv[c].y, pv[c].z, pv[c].w}, ww[4] = {pw_[c].x, pw_[c].y, pw_[c].z, pw_[c].w};
#pragma unroll
        for (int e = 0; e < 4; e++) {
          f[8 * c + 2 * e] = bf_lo(vv[e]); f[8 * c + 2 * e + 1] = bf_hi(vv[e]);
          s += f[8 * c + 2 * e] + f[8 * c + 2 * e + 1];
          gs = fmaf(f[8 * c + 2 * e], bf_lo(ww[e]), gs); gs = fmaf(f[8 * c + 2 * e + 1], bf_hi(ww[e]), gs);
        }
      }
#pragma unroll
      for (int o = 1; o < 16; o <<= 1) { s += __shfl_xor_sync(0xffffffffu, s, o); gs += __shfl_xor_sync(0xffffffffu, gs, o); }
      const float mean = s * (1.f / D_);
      float q = 0.f;
#pragma unroll
      for (int e = 0; e < 40; e++) { const float d = f[e] - mean; q = fmaf(d, d, q); }
#pragma unroll
      for (int o = 1; o < 16; o <<= 1) q += __shfl_xor_sync(0xffffffffu, q, o);
      const float rstd = rsqrtf(q * (1.f / D_) + 1e-5f);
      asm volatile("barrier.cluster.wait.aligned;" ::: "memory");
      if ((tid & 15) == 0) g_xstat[128 * i + 16 * j + (tid >> 4)] = make_float4(rstd, -mean * rstd, rcp(1.f + __expf(-gs)), 0.f);
      signal(B_SIGP);
      if (tid < 200) {
        const uint32_t ww[4] = {pre.x, pre.y, pre.z, pre.w};
        const int h = tid / 50;
#pragma unroll
        for (int e = 0; e < 8; e++) {
          const int idx = tid * 8 + e, k = idx / 20, ff = idx - 20 * k;
          const int n = 40 * (h >> 1) + 8 * (ff >> 2) + 2 * (ff & 3) + (h & 1);
          const int off = (k >> 4) * 2560 + n * 32 + ((((k >> 3) ^ (n >> 2)) & 1) << 4) + (k & 7) * 2;
          *reinterpret_cast<unsigned short*>(sgen + OFF_MISC + off) = (unsigned short)(ww[e >> 1] >> ((e & 1) * 16));
        }
      }
    }
    TSTAMP(1);

    Ring ra{0, 0}, rb{0, 0};
    uint32_t qp[2][10], P[2][10];
    float st_g[2];
    {
      float accM[128], accR[32];
      zero_regs(accM); zero_regs(accR);
      uint32_t pa = 0, pb = 0;
#pragma unroll 1
      for (int k = 0; k < 10; k++) {
        mbar_wait(fullA + 8 * ra.idx, ra.phase);
        if (tid == 0) TRACE(32 + k);
        mbar_wait(fullB + 8 * rb.idx, rb.phase);
        if (tid == 0) TRACE(64 + k);
        if (k == 0) TSTAMP(2);
        const uint32_t a0 = sb16 + ((OFF_A + ra.idx * SLOT_A + wg * 8192) >> 4), b0 = sb16 + ((OFF_B + rb.idx * SLOT_B) >> 4);
        wg_fence();
#pragma unroll
        for (int kk = 0; kk < 4; kk++) {
          const uint64_t da = make_desc(a0, kk * 32, 16, 1024, 1);
          mma_ss256(accM, da, make_desc(b0, kk * 2048, 8192, 1024, 1));
          mma_ss64(accR, da, make_desc(b0, 32768 + kk * 512, 2048, 256, 3));
          if (kk == 0) {
            wg_commit();
            if (k > 0) {
              wg_wait<1>();
              if (k - 1 < 8) release(emptyA + 8 * pa);
              releaseB(emptyB + 8 * pb);
            }
          }
        }
        wg_commit();
        pa = ra.idx; pb = rb.idx;
        ra.next<NA>(); rb.next<NB>();
      }
      TSTAMP(18);
      float st_rstd[2], st_mr[2];
      mbar_wait(bars + 8 * B_CS, 0);
#pragma unroll
      for (int r = 0; r < 2; r++) {
        const uint4 st = lds128(sb + OFF_XST + (rloc + 8 * r) * 16);
        st_rstd[r] = __uint_as_float(st.x); st_mr[r] = __uint_as_float(st.y); st_g[r] = __uint_as_float(st.z);
      }
      TSTAMP(19);
      wg_wait<0>();
      fence_regs(accM); fence_regs(accR);
      TSTAMP(3);
#define ACC(P_, G, I_) ((G) < 8 ? accM[(P_) * 32 + ((G) & 7) * 4 + (I_)] : accR[(P_) * 8 + ((G) & 1) * 4 + (I_)])
      {
        uint32_t hv[10][2];
#pragma unroll
        for (int g = 0; g < 10; g++) {
          const float2 cs = *reinterpret_cast<const float2*>(s_cs + 8 * g + 2 * t);
          const float v0 = gelu_s(fmaf(ACC(0, g, 0), st_rstd[0], st_mr[0] * cs.x), 0.5f), v1 = gelu_s(fmaf(ACC(0, g, 1), st_rstd[0], st_mr[0] * cs.y), 0.5f);
          const float v2 = gelu_s(fmaf(ACC(0, g, 2), st_rstd[1], st_mr[1] * cs.x), 0.5f), v3 = gelu_s(fmaf(ACC(0, g, 3), st_rstd[1], st_mr[1] * cs.y), 0.5f);
          hv[g][0] = pack_bf16(v0, v1); hv[g][1] = pack_bf16(v2, v3);
        }
        fence_async_smem();
        bar_sync(1, 256);
#pragma unroll
        for (int s = 0; s < 5; s++) stsm4(sb + OFF_STG + stg_lane + s * 32, hv[2 * s][0], hv[2 * s][1], hv[2 * s + 1][0], hv[2 * s + 1][1]);
        fence_async_smem();
        signal(B_SIGH);
      }
      TSTAMP(4);
      uint32_t kf[5][4], qf[5][4];
#pragma unroll
      for (int s = 0; s < 5; s++) {
        kf[s][0] = pack_bf16(ACC(2, 2 * s, 0), ACC(2, 2 * s, 1)); kf[s][1] = pack_bf16(ACC(2, 2 * s, 2), ACC(2, 2 * s, 3));
        kf[s][2] = pack_bf16(ACC(2, 2 * s + 1, 0), ACC(2, 2 * s + 1, 1)); kf[s][3] = pack_bf16(ACC(2, 2 * s + 1, 2), ACC(2, 2 * s + 1, 3));
        qf[s][0] = pack_bf16(ACC(1, 2 * s, 0), ACC(1, 2 * s, 1)); qf[s][1] = pack_bf16(ACC(1, 2 * s, 2), ACC(1, 2 * s, 3));
        qf[s][2] = pack_bf16(ACC(1, 2 * s + 1, 0), ACC(1, 2 * s + 1, 1)); qf[s][3] = pack_bf16(ACC(1, 2 * s + 1, 2), ACC(1, 2 * s + 1, 3));
      }
      float pk[40], pq[40];
      wg_fence();
#pragma unroll
      for (int s = 0; s < 5; s++) {
        if (s == 0) mma_rs80_k_z(pk, kf[s], make_desc(sb16, OFF_MISC, 16, 256, 3));
        else mma_rs80_k(pk, kf[s], make_desc(sb16, OFF_MISC + s * 2560, 16, 256, 3));
      }
#pragma unroll
      for (int s = 0; s < 5; s++) {
        if (s == 0) mma_rs80_k_z(pq, qf[s], make_desc(sb16, OFF_MISC, 16, 256, 3));
        else mma_rs80_k(pq, qf[s], make_desc(sb16, OFF_MISC + s * 2560, 16, 256, 3));
      }
      wg_commit();
      {
        const int mat = lane >> 3;
        const int tok = warp * 16 + (mat & 1) * 8 + (lane & 7);
        const uint32_t ones = (t == 0) ? 0x00003f80u : 0u;
        __syncwarp();
#pragma unroll
        for (int p = 0; p < 2; p++) {
          const uint32_t rowa = sb + OFF_A + p * SLOT_A + tok * 128;
#pragma unroll
          for (int gg = 0; gg < 3; gg++) {
            const int g0 = 5 * p + 2 * gg;
            uint32_t r0 = pack_bf16(ACC(3, g0, 0), ACC(3, g0, 1)), r1 = pack_bf16(ACC(3, g0, 2), ACC(3, g0, 3));
            uint32_t r2 = ones, r3 = ones;
            if (gg < 2) { r2 = pack_bf16(ACC(3, g0 + 1, 0), ACC(3, g0 + 1, 1)); r3 = pack_bf16(ACC(3, g0 + 1, 2), ACC(3, g0 + 1, 3)); }
            stsm4(rowa + (((2 * gg + (mat >> 1)) ^ (tok & 7)) << 4), r0, r1, r2, r3);
          }
        }
      }
#undef ACC
      wg_wait<0>();
      fence_regs(pk); fence_regs(pq);
#pragma unroll
      for (int G = 0; G < 10; G++) {
        P[0][G] = pack_bf16(pk[4 * G], pk[4 * G + 1]); P[1][G] = pack_bf16(pk[4 * G + 2], pk[4 * G + 3]);
        qp[0][G] = pack_bf16(pq[4 * G], pq[4 * G + 1]); qp[1][G] = pack_bf16(pq[4 * G + 2], pq[4 * G + 3]);
      }
    }

    uint32_t fr[10][4];
    uint32_t xv[2][10];
#pragma unroll
    for (int g = 0; g < 10; g++) xv[0][g] = xv[1][g] = 0u;
    int pass;
    pass = gridDim.y;
#pragma unroll 1
    do {
    feature_map(P, fr);
    if (pass != 0) {
    {
      const int mat = lane >> 3;
      const int tok = warp * 16 + (mat & 1) * 8 + (lane & 7);
      const uint32_t base = sb + OFF_B + tok * 32 + (((mat >> 1) ^ ((tok >> 2) & 1)) << 4);
#pragma unroll
      for (int G = 0; G < 10; G++) stsm4(base + G * 4096, fr[G][0], fr[G][1], fr[G][2], fr[G][3]);
      fence_async_smem();
      bar_sync(1, 256);
      float kv[40];
      const uint32_t a0 = sb16 + ((OFF_A + wg * SLOT_A) >> 4), b0 = sb16 + ((OFF_B + wg * 20480) >> 4);
      wg_fence();
#pragma unroll
      for (int ks = 0; ks < 8; ks++) {
        if (ks == 0) mma_ss80_tt_z(kv, make_desc(a0, 0, 16, 1024, 1), make_desc(b0, 0, 4096, 256, 3));
        else mma_ss80_tt(kv, make_desc(a0, ks * 2048, 16, 1024, 1), make_desc(b0, ks * 512, 4096, 256, 3));
      }
      wg_commit();
      wg_wait<0>();
      fence_regs(kv);
      TSTAMP(31);
      release(emptyA); release(emptyA + 8); releaseB(emptyB);
      const uint32_t dst = sb + OFF_MISC + wg * (KV_PAIR * 4);
      const int m0 = (warp & 3) * 16 + (lane >> 2);
#pragma unroll
      for (int r = 0; r < 2; r++) {
        const int m = m0 + 8 * r;
        const bool hi = m >= 20;
        uint32_t v[10];
#pragma unroll
        for (int G = 0; G < 10; G++) v[G] = __float_as_uint(hi ? kv[4 * G + 2 * r + 1] : kv[4 * G + 2 * r]);
        const uint32_t p = dst + 4 * (m < 40 ? m * 48 + t * 12 : 1920 + t * 24 + 12);
        if (m <= 40) {
          sts128(p, make_uint4(v[0], v[1], v[2], v[3])); sts128(p + 16, make_uint4(v[4], v[5], v[6], v[7]));
          sts128(p + 32, make_uint4(v[8], v[9], 0u, 0u));
        }
      }
      if (m0 == 32) {
        const uint32_t p = dst + 4 * (1920 + t * 24);
        sts128(p, make_uint4(__float_as_uint(kv[2]), __float_as_uint(kv[6]), __float_as_uint(kv[10]), __float_as_uint(kv[14])));
        sts128(p + 16, make_uint4(__float_as_uint(kv[18]), __float_as_uint(kv[22]), __float_as_uint(kv[26]), __float_as_uint(kv[30])));
        sts128(p + 32, make_uint4(__float_as_uint(kv[34]), __float_as_uint(kv[38]), 0u, 0u));
      }
      fence_async_smem();
      signal(B_SIGKV);
    }
    TSTAMP(5);

    {
      {
        mbar_wait(bars + 8 * B_XR, 0);
        const uint32_t xa = sb + OFF_B + (warp / 3) * SLOT_B + SPARE + (warp % 3) * 2560 + (lane >> 2) * 160 + t * 4;
#pragma unroll
        for (int g = 0; g < 10; g++) { xv[0][g] = lds32(xa + g * 16); xv[1][g] = lds32(xa + 1280 + g * 16); }
      }
      float acc[40];
      zero_regs(acc);
      uint32_t pa = 0, pb = 0;
#pragma unroll 1
      for (int k = 0; k < 10; k++) {
        mbar_wait(fullA + 8 * ra.idx, ra.phase);
        if (tid == 0) TRACE(42 + k);
        if ((k & 3) == 0) mbar_wait(fullB + 8 * rb.idx, rb.phase);
        if (tid == 0) TRACE(74 + k);
        if (k == 0) TSTAMP(6);
        const uint32_t a0 = sb16 + ((OFF_A + ra.idx * SLOT_A + wg * 8192) >> 4);
        const uint32_t b0 = sb16 + ((OFF_B + rb.idx * SLOT_B + (k & 3) * 10240) >> 4);
        wg_fence();
#pragma unroll
        for (int kk = 0; kk < 4; kk++) {
          mma_ss80(acc, make_desc(a0, kk * 32, 16, 1024, 1), make_desc(b0, kk * 512, 2048, 256, 3));
          if (kk == 1) {
            wg_commit();
            if (k > 0) {
              wg_wait<1>();
              release(emptyA + 8 * pa);
              if ((k & 3) == 0) releaseB(emptyB + 8 * pb);
            }
          }
        }
        wg_commit();
        pa = ra.idx; pb = rb.idx;
        ra.next<NA>();
        if ((k & 3) == 3 || k == 9) rb.next<NB>();
      }
      wg_wait<0>();
      fence_regs(acc);
      release(emptyA + 8 * pa); releaseB(emptyB + 8 * pb);
      TSTAMP(7);
#pragma unroll
      for (int r = 0; r < 2; r++) {
#pragma unroll
        for (int g = 0; g < 10; g++)
          xv[r][g] = pack_bf16(bf_lo(xv[r][g]) + acc[4 * g + 2 * r], bf_hi(xv[r][g]) + acc[4 * g + 2 * r + 1]);
      }
      bar_sync(1, 256);
#pragma unroll
      for (int s = 0; s < 5; s++) stsm4(sb + OFF_STG + stg_lane + s * 32, xv[0][2 * s], xv[1][2 * s], xv[0][2 * s + 1], xv[1][2 * s + 1]);
#pragma unroll
      for (int r = 0; r < 2; r++) {
        float s = 0.f;
#pragma unroll
        for (int g = 0; g < 10; g++) {
          acc[4 * g + 2 * r] = bf_lo(xv[r][g]); acc[4 * g + 2 * r + 1] = bf_hi(xv[r][g]);
          s += acc[4 * g + 2 * r] + acc[4 * g + 2 * r + 1];
        }
        s += __shfl_xor_sync(0xffffffffu, s, 1); s += __shfl_xor_sync(0xffffffffu, s, 2);
        const float mu = s * (1.f / 80.f);
        float q = 0.f;
#pragma unroll
        for (int g = 0; g < 10; g++) {
          const float d0 = acc[4 * g + 2 * r] - mu, d1 = acc[4 * g + 2 * r + 1] - mu;
          q = fmaf(d0, d0, q); q = fmaf(d1, d1, q);
        }
        q += __shfl_xor_sync(0xffffffffu, q, 1); q += __shfl_xor_sync(0xffffffffu, q, 2);
        if (t == 0) g_st1[(128 * i + rloc + 8 * r) * 8 + j] = make_float2(mu, q);
      }
      fence_async_smem();
      signal(B_SIGX1);
    }
    TSTAMP(8);
#pragma unroll
    for (int G = 0; G < 10; G++) { P[0][G] = qp[0][G]; P[1][G] = qp[1][G]; }
    }
    asm volatile("" : "+r"(pass));
    } while (pass-- != 0);

    uint32_t of[5][4];
    {
      mbar_wait(bars + 8 * B_KV, 0);
      uint4 kvr[2][3];
#pragma unroll
      for (int u = 0; u < 2; u++) {
        const int it = tid + 256 * u, p = it / 192, rem = it - 192 * p, n = rem >> 2, tq = rem & 3;
        const uint32_t sp = sb + OFF_MISC + 4 * (p * KV_PAIR + (n < 40 ? n * 48 + tq * 12 : 1920 + tq * 24 + (n & 1) * 12));
        if (it < 384) { kvr[u][0] = lds128(sp); kvr[u][1] = lds128(sp + 16); kvr[u][2] = lds128(sp + 32); }
      }
      bar_sync(1, 256);
#pragma unroll
      for (int u = 0; u < 2; u++) {
        const int it = tid + 256 * u, p = it / 192, rem = it - 192 * p, n = rem >> 2, tq = rem & 3;
        const int sh = (n < 40 ? (n >= 20) : (n & 1)) * 16;
        const uint32_t v[10] = {kvr[u][0].x, kvr[u][0].y, kvr[u][0].z, kvr[u][0].w, kvr[u][1].x, kvr[u][1].y, kvr[u][1].z, kvr[u][1].w, kvr[u][2].x, kvr[u][2].y};
        uint8_t* dst = sgen + OFF_MISC + p * 7680 + n * 32 + tq * 4;
        const int sw = ((n >> 2) & 1) << 4;
        if (it < 384) {
#pragma unroll
          for (int G = 0; G < 10; G++)
            *reinterpret_cast<uint32_t*>(dst + (G >> 1) * 1536 + (((G & 1) << 4) ^ sw)) = pack_bf16(__uint_as_float(v[G]), 0.f) << sh;
        }
      }
      fence_async_smem();
      bar_sync(1, 256);
      float o0[24], o1[24];
      wg_fence();
#pragma unroll
      for (int g = 0; g < 5; g++) {
        if (g == 0) mma_rs48_k_z(o0, fr[g], make_desc(sb16, OFF_MISC, 16, 256, 3));
        else mma_rs48_k(o0, fr[g], make_desc(sb16, OFF_MISC + g * 1536, 16, 256, 3));
      }
#pragma unroll
      for (int g = 0; g < 5; g++) {
        if (g == 0) mma_rs48_k_z(o1, fr[5], make_desc(sb16, OFF_MISC + 7680, 16, 256, 3));
        else mma_rs48_k(o1, fr[5 + g], make_desc(sb16, OFF_MISC + 7680 + g * 1536, 16, 256, 3));
      }
      wg_commit();
      wg_wait<0>();
      fence_regs(o0); fence_regs(o1);
      signal(B_MFREE);
#pragma unroll
      for (int r = 0; r < 2; r++) {
        const float a0 = __fdividef(st_g[r], o0[20 + 2 * r] + 1e-6f), a1 = __fdividef(st_g[r], o0[21 + 2 * r] + 1e-6f);
        const float b0 = __fdividef(st_g[r], o1[20 + 2 * r] + 1e-6f), b1 = __fdividef(st_g[r], o1[21 + 2 * r] + 1e-6f);
        const float am = t < 2 ? a0 : a1, bm = t < 2 ? b0 : b1;
#pragma unroll
        for (int g = 0; g < 5; g++) {
          const float sa = g < 2 ? a0 : (g == 2 ? am : a1), sb2 = g < 2 ? b0 : (g == 2 ? bm : b1);
          of[g >> 1][(g & 1) * 2 + r] = pack_bf16(o0[4 * g + 2 * r] * sa, o0[4 * g + 2 * r + 1] * sa);
          of[(5 + g) >> 1][((5 + g) & 1) * 2 + r] = pack_bf16(o1[4 * g + 2 * r] * sb2, o1[4 * g + 2 * r + 1] * sb2);
        }
      }
    }
    TSTAMP(9);

    uint32_t hf[12][4];
    {
      float acc[96];
      zero_regs(acc);
      uint32_t pa = 0, pb = 0;
#pragma unroll 1
      for (int k = 0; k < 10; k++) {
        mbar_wait(fullA + 8 * ra.idx, ra.phase);
        if (tid == 0) TRACE(52 + k);
        if ((k & 1) == 0) mbar_wait(fullB + 8 * rb.idx, rb.phase);
        if (tid == 0) TRACE(84 + k);
        if (k == 0) TSTAMP(10);
        const uint32_t a0 = sb16 + ((OFF_A + ra.idx * SLOT_A + wg * 8192) >> 4);
        const uint32_t b0 = sb16 + ((OFF_B + rb.idx * SLOT_B + (k & 1) * 24576) >> 4);
        wg_fence();
#pragma unroll
        for (int kk = 0; kk < 4; kk++) {
          mma_ss192(acc, make_desc(a0, kk * 32, 16, 1024, 1), make_desc(b0, kk * 2048, 8192, 1024, 1));
          if (kk == 0) {
            wg_commit();
            if (k > 0) {
              wg_wait<1>();
              release(emptyA + 8 * pa);
              if ((k & 1) == 0) releaseB(emptyB + 8 * pb);
            }
          }
        }
        wg_commit();
        pa = ra.idx; pb = rb.idx;
        ra.next<NA>();
        if (k & 1) rb.next<NB>();
      }
      float rs[2], mm[2];
      mbar_wait(bars + 8 * B_ST1, 0);
#pragma unroll
      for (int r = 0; r < 2; r++) {
        const uint4 su = lds128(sb + OFF_MISC + (rloc + 8 * r) * 64 + t * 16);
        const float m0 = __uint_as_float(su.x), m1 = __uint_as_float(su.z);
        float mu = m0 + m1;
        mu += __shfl_xor_sync(0xffffffffu, mu, 1); mu += __shfl_xor_sync(0xffffffffu, mu, 2);
        mu *= 0.125f;
        const float d0 = m0 - mu, d1 = m1 - mu;
        float q = __uint_as_float(su.y) + __uint_as_float(su.w) + 80.f * (d0 * d0 + d1 * d1);
        q += __shfl_xor_sync(0xffffffffu, q, 1); q += __shfl_xor_sync(0xffffffffu, q, 2);
        rs[r] = rsqrtf(q * (1.f / D_) + 1e-5f);
        mm[r] = -mu * rs[r];
      }
      wg_wait<0>();
      fence_regs(acc);
      releaseB(emptyB + 8 * pb);
      release(bars + 8 * B_PEER);
      TSTAMP(11);
      const float hs0 = 0.5f - 0.5f * st_g[0], hs1 = 0.5f - 0.5f * st_g[1];
#pragma unroll
      for (int g = 0; g < 24; g++) {
        const float2 cs = *reinterpret_cast<const float2*>(s_cs + 80 + 8 * g + 2 * t);
        const float v0 = gelu_s(fmaf(acc[4 * g], rs[0], mm[0] * cs.x), hs0), v1 = gelu_s(fmaf(acc[4 * g + 1], rs[0], mm[0] * cs.y), hs0);
        const float v2 = gelu_s(fmaf(acc[4 * g + 2], rs[1], mm[1] * cs.x), hs1), v3 = gelu_s(fmaf(acc[4 * g + 3], rs[1], mm[1] * cs.y), hs1);
        hf[g >> 1][(g & 1) * 2] = pack_bf16(v0, v1);
        hf[g >> 1][(g & 1) * 2 + 1] = pack_bf16(v2, v3);
      }
    }
    TSTAMP(12);

    {
      float acc[80], kp[40];
      uint32_t sn[20], kb[20];
      const int wt = tid & 127;
      const uint32_t peer = map_peer(sb, rank ^ 1);
      const uint32_t lofs = wg * 10240 + wt * 16;
      Ring r4{0, 0};
      auto add16 = [&](uint32_t src) {
#pragma unroll
        for (int q = 0; q < 5; q++) {
          const uint4 v = lds128(src + q * 2048);
          float* d = &kp[8 * q];
          d[0] += bf_lo(v.x); d[1] += bf_hi(v.x); d[2] += bf_lo(v.y); d[3] += bf_hi(v.y);
          d[4] += bf_lo(v.z); d[5] += bf_hi(v.z); d[6] += bf_lo(v.w); d[7] += bf_hi(v.w);
        }
      };
      auto send = [&](int c) {
        const uint32_t dso = peer + OFF_DS + (c & 1) * 20480 + lofs, dsb = peer + OFF_BAR + 8 * (B_DSR + 2 * c + wg);
#pragma unroll
        for (int q = 0; q < 5; q++) st_async16(dso + q * 2048, sn[4 * q], sn[4 * q + 1], sn[4 * q + 2], sn[4 * q + 3], dsb);
      };
#pragma unroll
      for (int e = 0; e < 20; e++) sn[e] = kb[e] = 0u;
      auto chunk = [&](const int c, auto last_c) {
        constexpr bool LAST = decltype(last_c)::value;
        const uint32_t e0 = r4.idx;
        auto rel = [&](int u) { const uint32_t e = e0 + u; releaseB(bars + 8 * (B_EMPTY4 + (e >= NU4 ? e - NU4 : e))); };
#pragma unroll
        for (int u = 0; u < 4; u++) {
          mbar_wait(bars + 8 * (B_FULL4 + r4.idx), r4.phase);
          const uint32_t b0 = sb16 + ((OFF_B + r4.idx * UNIT4) >> 4);
          TRS(c * 16 + u * 3);
          wg_fence();
#pragma unroll
          for (int s = 0; s < (u < 3 ? 4 : 5); s++) {
            const uint64_t db = make_desc(b0, s * 1024, u < 3 ? 4096 : 5120, 512, 2);
            if (u == 0 && s == 0) mma_rs160_n_z(acc, hf[0], db);
            else if (u < 3) mma_rs160_n(acc, hf[(4 * u + s) % 12], db);
            else mma_rs160_n(acc, of[s], db);
          }
          wg_commit();
          TRS(c * 16 + u * 3 + 1);
          r4.next<NU4>();
          if (u == 1) {
            if (c == 0) { if (wg == 0) bar_arrive(2, 256); mbar_wait(bars + 8 * B_PEER, 0); }
            else send(c - 1);
          }
          if (u == 2 && c > 0) {
            mbar_wait(bars + 8 * (B_DSR + 2 * (c - 1) + wg), 0);
            TRS(c * 16 + 14);
            uint4* dst = g_part + (size_t)((i * 8 + ((j + 2 * c) & 7)) * 3 + c - 1) * 1280 + wg * 640 + wt;
#pragma unroll
            for (int q = 0; q < 5; q++) {
              const uint4 v = lds128(sb + OFF_DS + ((c - 1) & 1) * 20480 + lofs + q * 2048);
              dst[q * 128] = make_uint4(add_bf2(v.x, kb[4 * q]), add_bf2(v.y, kb[4 * q + 1]), add_bf2(v.z, kb[4 * q + 2]), add_bf2(v.w, kb[4 * q + 3]));
            }
            signal(B_SEND + 2 * (c - 1) + wg);
          }
          if (u == 3 && LAST) {
            const float w0 = 1.f - st_g[0], w1s = 1.f - st_g[1];
#pragma unroll
            for (int g = 0; g < 10; g++) {
              kp[4 * g] = w0 * bf_lo(xv[0][g]); kp[4 * g + 1] = w0 * bf_hi(xv[0][g]);
              kp[4 * g + 2] = w1s * bf_lo(xv[1][g]); kp[4 * g + 3] = w1s * bf_hi(xv[1][g]);
            }
#pragma unroll 1
            for (int e = 0; e < 2; e++) {
              mbar_wait(bars + 8 * (B_RDY + 2 * e + wg), 0);
              add16(sb + OFF_G0 + e * 20480 + lofs);
            }
          }
          TRS(c * 16 + u * 3 + 2);
          if (u > 0 && !LAST) { wg_wait<1>(); rel(u - 1); }
        }
        wg_wait<0>();
        fence_regs(acc);
        if (!LAST) rel(3);
        TRS(c * 16 + 12);
        if (rank) {
#pragma unroll
          for (int e = 0; e < 20; e++) { sn[e] = pack_bf16(acc[2 * e], acc[2 * e + 1]); kb[e] = pack_bf16(acc[40 + 2 * e], acc[41 + 2 * e]); }
        } else {
#pragma unroll
          for (int e = 0; e < 20; e++) { kb[e] = pack_bf16(acc[2 * e], acc[2 * e + 1]); sn[e] = pack_bf16(acc[40 + 2 * e], acc[41 + 2 * e]); }
        }
#pragma unroll
        for (int e = 0; e < 20; e++) asm volatile("" : "+r"(sn[e]), "+r"(kb[e]));
        TRS(c * 16 + 13);
      };
      if (wg == 1) bar_sync(2, 256);
#pragma unroll 1
      for (int c = 0; c < 3; c++) chunk(c, BoolC<false>{});
      chunk(3, BoolC<true>{});
      send(3);
      TSTAMP(13);
#pragma unroll
      for (int e = 0; e < 40; e++) kp[e] += rank ? acc[40 + e] : acc[e];
#pragma unroll 1
      for (int c = 0; c < 2; c++) {
        mbar_wait(bars + 8 * ((c == 0 ? B_DSR + 6 : B_RDY + 4) + wg), 0);
        add16(sb + (c == 0 ? OFF_DS + 20480 : OFF_G2) + lofs);
      }
      TSTAMP(14);
      mbar_wait(bars + 8 * (B_SEND + 4 + wg), 0);
#pragma unroll
      for (int s = 0; s < 5; s++)
        stsm4(sb + OFF_DS + stg_lane + s * 32, pack_bf16(kp[8 * s], kp[8 * s + 1]), pack_bf16(kp[8 * s + 2], kp[8 * s + 3]),
              pack_bf16(kp[8 * s + 4], kp[8 * s + 5]), pack_bf16(kp[8 * s + 6], kp[8 * s + 7]));
      fence_async_smem();
      __syncwarp();
      if (lane == 0) {
        tma2d_store(&maps.st_out, sb + OFF_DS + warp * 2560, 80 * j, 128 * i + 16 * warp);
        bulk_commit(); bulk_wait_read();
      }
    }
    TSTAMP(15);
    if (tid == 0) asm volatile("red.relaxed.gpu.global.add.u32 [%0], 1;" ::"l"(g_flags + FL_DONE * 32) : "memory");
  }
}

namespace {
typedef CUresult (*EncodeFn)(CUtensorMap*, CUtensorMapDataType, cuuint32_t, void*, const cuuint64_t*, const cuuint64_t*,
                             const cuuint32_t*, const cuuint32_t*, CUtensorMapInterleave, CUtensorMapSwizzle,
                             CUtensorMapL2promotion, CUtensorMapFloatOOBfill);

void encode(EncodeFn fn, CUtensorMap* m, const void* ptr, int rank, const cuuint64_t* dims, const cuuint64_t* strides,
            const cuuint32_t* box, CUtensorMapSwizzle swz) {
  cuuint32_t es[5] = {1, 1, 1, 1, 1};
  fn(m, CU_TENSOR_MAP_DATA_TYPE_BFLOAT16, rank, const_cast<void*>(ptr), dims, strides, box, es, CU_TENSOR_MAP_INTERLEAVE_NONE,
     swz, CU_TENSOR_MAP_L2_PROMOTION_L2_128B, CU_TENSOR_MAP_FLOAT_OOB_FILL_NONE);
}
}

extern "C" void kernel_launch(void* const* d_in, const int* in_sizes, int n_in, void* d_out, int out_size) {
  (void)in_sizes; (void)n_in; (void)out_size;
  const __nv_bfloat16* x = (const __nv_bfloat16*)d_in[0];
  const __nv_bfloat16* wqkv = (const __nv_bfloat16*)d_in[1];
  const __nv_bfloat16* wphi = (const __nv_bfloat16*)d_in[2];
  const __nv_bfloat16* wo = (const __nv_bfloat16*)d_in[3];
  const __nv_bfloat16* w1 = (const __nv_bfloat16*)d_in[5];
  const __nv_bfloat16* w2 = (const __nv_bfloat16*)d_in[6];
  const __nv_bfloat16* w3 = (const __nv_bfloat16*)d_in[7];
  const __nv_bfloat16* w4 = (const __nv_bfloat16*)d_in[8];
  const __nv_bfloat16* gate_w = (const __nv_bfloat16*)d_in[9];

  static EncodeFn enc = nullptr;
  static void *pHs = nullptr, *pX1 = nullptr;
  if (!enc) {
    cudaDriverEntryPointQueryResult qr;
    cudaGetDriverEntryPoint("cuTensorMapEncodeTiled", (void**)&enc, cudaEnableDefault, &qr);
    cudaGetSymbolAddress(&pHs, g_Hs);
    cudaGetSymbolAddress(&pX1, g_X1);
    cudaFuncSetAttribute(fused_kernel, cudaFuncAttributeMaxDynamicSharedMemorySize, SMEM_BYTES);
  }
  Maps m;
  {
    cuuint64_t dims[2] = {D_, S_}, str[1] = {D_ * 2};
    cuuint32_t boxh[2] = {64, 64};
    encode(enc, &m.x, x, 2, dims, str, boxh, CU_TENSOR_MAP_SWIZZLE_128B);
    encode(enc, &m.hs, (const char*)pHs + 2 * D_ * 2, 2, dims, str, boxh, CU_TENSOR_MAP_SWIZZLE_128B);
    encode(enc, &m.x1, pX1, 2, dims, str, boxh, CU_TENSOR_MAP_SWIZZLE_128B);
    cuuint32_t boxs[2] = {80, 64};
    cuuint64_t dimsp[2] = {D_, S_ + 4};
    encode(enc, &m.st_h, pHs, 2, dimsp, str, boxs, CU_TENSOR_MAP_SWIZZLE_NONE);
    encode(enc, &m.st_x1, pX1, 2, dims, str, boxs, CU_TENSOR_MAP_SWIZZLE_NONE);
    cuuint32_t boxr[2] = {80, 16};
    encode(enc, &m.st_out, d_out, 2, dims, str, boxr, CU_TENSOR_MAP_SWIZZLE_NONE);
    encode(enc, &m.xr, x, 2, dims, str, boxr, CU_TENSOR_MAP_SWIZZLE_NONE);
  }
  {
    cuuint64_t dims[3] = {80, D_, 8}, str[2] = {D_ * 2, 160};
    cuuint32_t boxm[3] = {64, 64, 1}, boxr[3] = {16, 64, 1};
    encode(enc, &m.w1m, w1, 3, dims, str, boxm, CU_TENSOR_MAP_SWIZZLE_128B);
    encode(enc, &m.w1r, w1, 3, dims, str, boxr, CU_TENSOR_MAP_SWIZZLE_32B);
  }
  {
    cuuint64_t dims[4] = {80, D_, 3, 8}, str[3] = {3 * D_ * 2, D_ * 2, 160};
    cuuint32_t boxm[4] = {64, 64, 3, 1}, boxr[4] = {16, 64, 3, 1};
    encode(enc, &m.qm, wqkv, 4, dims, str, boxm, CU_TENSOR_MAP_SWIZZLE_128B);
    encode(enc, &m.qr, wqkv, 4, dims, str, boxr, CU_TENSOR_MAP_SWIZZLE_32B);
  }
  {
    cuuint64_t dims[3] = {16, D_, 40}, str[2] = {D_ * 2, 32};
    cuuint32_t box2[3] = {16, 64, 5};
    encode(enc, &m.w2, w2, 3, dims, str, box2, CU_TENSOR_MAP_SWIZZLE_32B);
  }
  {
    cuuint64_t dims[3] = {32, D_, 20}, dims4[3] = {32, F_, 20}, str[2] = {D_ * 2, 64};
    cuuint32_t box4[3] = {32, 64, 5}, boxo[3] = {32, 80, 5};
    encode(enc, &m.w4, w4, 3, dims4, str, box4, CU_TENSOR_MAP_SWIZZLE_64B);
    encode(enc, &m.wo, wo, 3, dims, str, boxo, CU_TENSOR_MAP_SWIZZLE_64B);
  }
  {
    cuuint64_t dims[3] = {64, D_, 24}, str[2] = {F_ * 2, 128};
    cuuint32_t box[3] = {64, 64, 3};
    encode(enc, &m.w3, w3, 3, dims, str, box, CU_TENSOR_MAP_SWIZZLE_128B);
  }
  fused_kernel<<<NCTA, 384, SMEM_BYTES, cudaStreamPerThread>>>(m, x, wqkv, wphi, w1, w2, w3, w4, wo, gate_w);
}
```

```cpp
#include <cuda_runtime.h>
#include <cuda_bf16.h>
#include <cuda.h>
#include <stdint.h>

namespace {

constexpr int S_ = 2048, D_ = 640, F_ = 1536;
constexpr int NCTA = 128;
constexpr int KV_PAIR = 40 * 48 + 96;
constexpr int KV_J = 2 * KV_PAIR;

constexpr int SLOT_B = 49152, NB = 3;
constexpr int SLOT_A = 16384, NA = 4;
constexpr int OFF_B = 0;
constexpr int OFF_A = OFF_B + NB * SLOT_B;
constexpr int OFF_STG = OFF_A + 2 * SLOT_A;
constexpr int OFF_MISC = OFF_A + NA * SLOT_A;
constexpr int OFF_XST = OFF_MISC + 13312;
constexpr int OFF_CS = OFF_MISC + 16384;
constexpr int OFF_BAR = OFF_CS + 1088;
constexpr int SMEM_BYTES = OFF_BAR + 512 + 512;
constexpr int B_FULLA = 0, B_FULLB = 4, B_CS = 7, B_XR = 8, B_KV = 9, B_ST1 = 10, B_FULL4 = 11  , B_DSR = 16  ,
              B_EMPTYB = 24  , B_SIGP = 27, B_SIGH = 28, B_SIGKV = 29, B_SIGX1 = 30, B_MFREE = 31, B_EMPTY4 = 32  ,
              B_EMPTYA = 37  , B_PEER = 41, NBAR = 42;
constexpr int SPARE = 40960;
constexpr int UNIT4 = 25600, NU4 = 5;
constexpr int OFF_DS = OFF_A, OFF_OUT = OFF_A + 40960;

constexpr int FL_DONE = 0, FL_H = 1, FL_X1 = FL_H + 16, FL_KV = FL_X1 + 16, FL_CS = FL_KV + 8, FL_CS3 = FL_CS + 8, FL_ST = FL_CS3 + 8;
constexpr int FL_COUNT = FL_ST + 16;
constexpr int ACC_FLOATS = 8 * KV_J + D_ + F_;

struct Maps {
  CUtensorMap x, w1m, w1r, qm, qr, hs, w2, x1, w3, w4, wo, st_h, st_x1, st_out, xr;
};

}

__device__ __align__(1024) __nv_bfloat16 g_Hs[(S_ + 4) * D_];
__device__ __align__(1024) __nv_bfloat16 g_X1[S_ * D_];
__device__ __align__(128) float g_acc[2][ACC_FLOATS];
__device__ __align__(128) float4 g_xstat[S_];
__device__ __align__(128) float2 g_st1[S_ * 8];
__device__ __align__(128) uint4 g_part[16 * 8 * 3 * 1280];
__device__ __align__(128) unsigned g_flags[FL_COUNT * 32];
#define TSTAMP(n) do {} while (0)
#define TSTAMPX(n) do {} while (0)
#define TRACE(n) do {} while (0)
#define TRS(n) do {} while (0)

namespace {

__device__ __forceinline__ long long gtime() { long long t; asm volatile("mov.u64 %0, %%globaltimer;" : "=l"(t)); return t; }
__device__ __forceinline__ uint32_t smem_u32(const void* p) { return (uint32_t)__cvta_generic_to_shared(p); }
__device__ __forceinline__ void mbar_init(uint32_t bar, int cnt) {
  asm volatile("mbarrier.init.shared::cta.b64 [%0], %1;" ::"r"(bar), "r"(cnt) : "memory");
}
__device__ __forceinline__ void mbar_expect_tx(uint32_t bar, int bytes) {
  asm volatile("mbarrier.arrive.expect_tx.shared::cta.b64 _, [%0], %1;" ::"r"(bar), "r"(bytes) : "memory");
}
__device__ __forceinline__ void mbar_arrive_cta(uint32_t bar, uint32_t cta) {
  asm volatile("{\n.reg .b32 ra;\nmapa.shared::cluster.u32 ra, %0, %1;\nmbarrier.arrive.shared::cluster.b64 _, [ra];\n}"
               ::"r"(bar), "r"(cta) : "memory");
}
__device__ __forceinline__ uint32_t mbar_try(uint32_t bar, uint32_t parity) {
  uint32_t ok;
  asm volatile("{\n.reg .pred p;\nmbarrier.try_wait.parity.shared::cta.b64 p, [%1], %2;\nselp.u32 %0, 1, 0, p;\n}"
               : "=r"(ok) : "r"(bar), "r"(parity) : "memory");
  return ok;
}
constexpr uint32_t WAIT_LIMIT = 1u << 22;
__device__ __forceinline__ void mbar_wait(uint32_t bar, uint32_t parity) {
  uint32_t n = 0;
  while (!mbar_try(bar, parity) && ++n < WAIT_LIMIT) {}
}
__device__ __forceinline__ unsigned ld_acquire(const unsigned* p) {
  unsigned v;
  asm volatile("ld.acquire.gpu.global.u32 %0, [%1];" : "=r"(v) : "l"(p) : "memory");
  return v;
}
__device__ __forceinline__ void flag_wait(int idx, unsigned target) {
  const unsigned* p = g_flags + idx * 32;
  uint32_t n = 0;
  while ((int)(ld_acquire(p) - target) < 0 && ++n < (WAIT_LIMIT >> 4)) {}
}
__device__ __forceinline__ void flag_add(int idx) {
  asm volatile("red.release.gpu.global.add.u32 [%0], 1;" ::"l"(g_flags + idx * 32) : "memory");
}
__device__ __forceinline__ void flag_add_relaxed(int idx) {
  asm volatile("red.relaxed.gpu.global.add.u32 [%0], 1;" ::"l"(g_flags + idx * 32) : "memory");
}
__device__ __forceinline__ uint32_t mbar_test(uint32_t bar, uint32_t parity) {
  uint32_t ok;
  asm volatile("{\n.reg .pred p;\nmbarrier.test_wait.parity.shared::cta.b64 p, [%1], %2;\nselp.u32 %0, 1, 0, p;\n}"
               : "=r"(ok) : "r"(bar), "r"(parity) : "memory");
  return ok;
}
__device__ __forceinline__ uint32_t lds32(uint32_t a) {
  uint32_t v;
  asm volatile("ld.shared.u32 %0, [%1];" : "=r"(v) : "r"(a) : "memory");
  return v;
}
__device__ __forceinline__ void mbar_arrive(uint32_t bar) {
  asm volatile("mbarrier.arrive.shared::cta.b64 _, [%0];" ::"r"(bar) : "memory");
}
__device__ __forceinline__ void fence_async_glb() { asm volatile("fence.proxy.async.global;" ::: "memory"); }
__device__ __forceinline__ void fence_async_smem() { asm volatile("fence.proxy.async.shared::cta;" ::: "memory"); }
__device__ __forceinline__ void bar_sync(int id, int n) { asm volatile("bar.sync %0, %1;" ::"r"(id), "r"(n) : "memory"); }

__device__ __forceinline__ void tma2d(uint32_t dst, const CUtensorMap* m, uint32_t bar, int c0, int c1) {
  asm volatile("cp.async.bulk.tensor.2d.shared::cluster.global.mbarrier::complete_tx::bytes [%0], [%1, {%3, %4}], [%2];"
               ::"r"(dst), "l"(m), "r"(bar), "r"(c0), "r"(c1) : "memory");
}
__device__ __forceinline__ void tma2d_mc(uint32_t dst, const CUtensorMap* m, uint32_t bar, int c0, int c1) {
  asm volatile("cp.async.bulk.tensor.2d.shared::cluster.global.mbarrier::complete_tx::bytes.multicast::cluster"
               " [%0], [%1, {%3, %4}], [%2], %5;"
               ::"r"(dst), "l"(m), "r"(bar), "r"(c0), "r"(c1), "h"((uint16_t)3) : "memory");
}
__device__ __forceinline__ void tma3d(uint32_t dst, const CUtensorMap* m, uint32_t bar, int c0, int c1, int c2) {
  asm volatile("cp.async.bulk.tensor.3d.shared::cluster.global.mbarrier::complete_tx::bytes [%0], [%1, {%3, %4, %5}], [%2];"
               ::"r"(dst), "l"(m), "r"(bar), "r"(c0), "r"(c1), "r"(c2) : "memory");
}
__device__ __forceinline__ void tma4d(uint32_t dst, const CUtensorMap* m, uint32_t bar, int c0, int c1, int c2, int c3) {
  asm volatile("cp.async.bulk.tensor.4d.shared::cluster.global.mbarrier::complete_tx::bytes [%0], [%1, {%3, %4, %5, %6}], [%2];"
               ::"r"(dst), "l"(m), "r"(bar), "r"(c0), "r"(c1), "r"(c2), "r"(c3) : "memory");
}
__device__ __forceinline__ void tma2d_store(const CUtensorMap* m, uint32_t src, int c0, int c1) {
  asm volatile("cp.async.bulk.tensor.2d.global.shared::cta.bulk_group [%0, {%2, %3}], [%1];"
               ::"l"(m), "r"(src), "r"(c0), "r"(c1) : "memory");
}
__device__ __forceinline__ void bulk_store(void* dst, uint32_t src, uint32_t bytes) {
  asm volatile("cp.async.bulk.global.shared::cta.bulk_group [%0], [%1], %2;" ::"l"(dst), "r"(src), "r"(bytes) : "memory");
}
__device__ __forceinline__ void bulk_load(uint32_t dst, const void* src, uint32_t bytes, uint32_t bar) {
  asm volatile("cp.async.bulk.shared::cluster.global.mbarrier::complete_tx::bytes [%0], [%1], %2, [%3];"
               ::"r"(dst), "l"(src), "r"(bytes), "r"(bar) : "memory");
}
__device__ __forceinline__ void bulk_commit() { asm volatile("cp.async.bulk.commit_group;" ::: "memory"); }
template <int N> __device__ __forceinline__ void bulk_wait() { asm volatile("cp.async.bulk.wait_group %0;" ::"n"(N) : "memory"); }
__device__ __forceinline__ void bulk_wait_read() { asm volatile("cp.async.bulk.wait_group.read 0;" ::: "memory"); }
__device__ __forceinline__ void bar_arrive(int id, int n) { asm volatile("bar.arrive %0, %1;" ::"r"(id), "r"(n) : "memory"); }
__device__ __forceinline__ uint4 lds128(uint32_t a) {
  uint4 v;
  asm volatile("ld.shared.v4.u32 {%0, %1, %2, %3}, [%4];" : "=r"(v.x), "=r"(v.y), "=r"(v.z), "=r"(v.w) : "r"(a) : "memory");
  return v;
}
__device__ __forceinline__ void sts128(uint32_t a, uint4 v) {
  asm volatile("st.shared.v4.u32 [%0], {%1, %2, %3, %4};" ::"r"(a), "r"(v.x), "r"(v.y), "r"(v.z), "r"(v.w) : "memory");
}
__device__ __forceinline__ uint4 ld_relaxed16(const uint4* p) {
  uint4 v;
  asm volatile("ld.relaxed.gpu.global.v4.u32 {%0, %1, %2, %3}, [%4];" : "=r"(v.x), "=r"(v.y), "=r"(v.z), "=r"(v.w) : "l"(p) : "memory");
  return v;
}
__device__ __forceinline__ void st_relaxed16(uint4* p, uint32_t a, uint32_t b, uint32_t c, uint32_t d) {
  asm volatile("st.relaxed.gpu.global.v4.u32 [%0], {%1, %2, %3, %4};" ::"l"(p), "r"(a), "r"(b), "r"(c), "r"(d) : "memory");
}
__device__ __forceinline__ uint32_t map_peer(uint32_t addr, uint32_t cta) {
  uint32_t r;
  asm("mapa.shared::cluster.u32 %0, %1, %2;" : "=r"(r) : "r"(addr), "r"(cta));
  return r;
}
__device__ __forceinline__ void st_async16(uint32_t addr, uint32_t a, uint32_t b, uint32_t c, uint32_t d, uint32_t bar) {
  asm volatile("st.async.weak.shared::cluster.mbarrier::complete_tx::bytes.v4.b32 [%0], {%1, %2, %3, %4}, [%5];"
               ::"r"(addr), "r"(a), "r"(b), "r"(c), "r"(d), "r"(bar) : "memory");
}
__device__ __forceinline__ void l2_prefetch(const void* p, uint32_t bytes) {
  asm volatile("cp.async.bulk.prefetch.L2.global [%0], %1;" ::"l"(p), "r"(bytes) : "memory");
}
__device__ __forceinline__ void prefetch_tmap(const CUtensorMap* m) {
  asm volatile("prefetch.tensormap [%0];" ::"l"(m) : "memory");
}
__device__ __forceinline__ uint64_t make_desc(uint32_t a16, uint32_t off, uint32_t lbo, uint32_t sbo, uint32_t swz) {
  const uint32_t lo = a16 + ((off >> 4) + ((lbo >> 4) << 16)), hi = (sbo >> 4) | (swz << 30);
  uint64_t d;
  asm("mov.b64 %0, {%1, %2};" : "=l"(d) : "r"(lo), "r"(hi));
  return d;
}
__device__ __forceinline__ void wg_fence() { asm volatile("wgmma.fence.sync.aligned;" ::: "memory"); }
__device__ __forceinline__ void wg_commit() { asm volatile("wgmma.commit_group.sync.aligned;" ::: "memory"); }
template <int N> __device__ __forceinline__ void wg_wait() { asm volatile("wgmma.wait_group.sync.aligned %0;" ::"n"(N) : "memory"); }
template <int N> __device__ __forceinline__ void fence_regs(float (&d)[N]) {
#pragma unroll
  for (int i = 0; i < N; i++) asm volatile("" : "+f"(d[i])::"memory");
}
template <int N> __device__ __forceinline__ void zero_regs(float (&d)[N]) {
#pragma unroll
  for (int i = 0; i < N; i++) d[i] = 0.f;
}
__device__ __forceinline__ uint32_t pack_bf16(float lo, float hi) {
  uint32_t r;
  asm("cvt.rn.bf16x2.f32 %0, %1, %2;" : "=r"(r) : "f"(hi), "f"(lo));
  return r;
}
__device__ __forceinline__ float bf_lo(uint32_t v) { return __uint_as_float(v << 16); }
__device__ __forceinline__ float bf_hi(uint32_t v) { return __uint_as_float(v & 0xffff0000u); }
__device__ __forceinline__ uint32_t max_bf2(uint32_t a, uint32_t b) {
  uint32_t r; asm("max.bf16x2 %0, %1, %2;" : "=r"(r) : "r"(a), "r"(b)); return r;
}
__device__ __forceinline__ uint32_t min_bf2(uint32_t a, uint32_t b) {
  uint32_t r; asm("min.bf16x2 %0, %1, %2;" : "=r"(r) : "r"(a), "r"(b)); return r;
}
__device__ __forceinline__ uint32_t add_bf2(uint32_t a, uint32_t b) {
  uint32_t r; asm("add.rn.bf16x2 %0, %1, %2;" : "=r"(r) : "r"(a), "r"(b)); return r;
}
__device__ __forceinline__ float ex2(float x) { float r; asm("ex2.approx.ftz.f32 %0, %1;" : "=f"(r) : "f"(x)); return r; }
__device__ __forceinline__ float rcp(float x) { float r; asm("rcp.approx.ftz.f32 %0, %1;" : "=f"(r) : "f"(x)); return r; }
__device__ __forceinline__ float tanh_ap(float x) { float r; asm("tanh.approx.f32 %0, %1;" : "=f"(r) : "f"(x)); return r; }
__device__ __forceinline__ float gelu_s(float x, float hs) {
  float u = x * fmaf(x * x, 0.0356774081f, 0.7978845608f);
  float hx = x * hs;
  return fmaf(hx, tanh_ap(u), hx);
}
__device__ __forceinline__ void stsm4(uint32_t addr, uint32_t r0, uint32_t r1, uint32_t r2, uint32_t r3) {
  asm volatile("stmatrix.sync.aligned.m8n8.x4.shared.b16 [%0], {%1, %2, %3, %4};"
               ::"r"(addr), "r"(r0), "r"(r1), "r"(r2), "r"(r3) : "memory");
}
__device__ __forceinline__ void red_add4(float* p, float a, float b, float c, float d) {
  asm volatile("red.global.add.v4.f32 [%0], {%1, %2, %3, %4};" ::"l"(p), "f"(a), "f"(b), "f"(c), "f"(d) : "memory");
}

__device__ __forceinline__ void mma_ss256(float (&d)[128], uint64_t descA, uint64_t descB) {
  asm volatile("wgmma.mma_async.sync.aligned.m64n256k16.f32.bf16.bf16 {"
      "%0, %1, %2, %3, %4, %5, %6, %7, %8, %9, %10, %11, %12, %13, %14, %15, "
      "%16, %17, %18, %19, %20, %21, %22, %23, %24, %25, %26, %27, %28, %29, %30, %31, "
      "%32, %33, %34, %35, %36, %37, %38, %39, %40, %41, %42, %43, %44, %45, %46, %47, "
      "%48, %49, %50, %51, %52, %53, %54, %55, %56, %57, %58, %59, %60, %61, %62, %63, "
      "%64, %65, %66, %67, %68, %69, %70, %71, %72, %73, %74, %75, %76, %77, %78, %79, "
      "%80, %81, %82, %83, %84, %85, %86, %87, %88, %89, %90, %91, %92, %93, %94, %95, "
      "%96, %97, %98, %99, %100, %101, %102, %103, %104, %105, %106, %107, %108, %109, %110, %111, "
      "%112, %113, %114, %115, %116, %117, %118, %119, %120, %121, %122, %123, %124, %125, %126, %127"
      "}, %128, %129, 1, 1, 1, 0, 1;\n"
      : "+f"(d[0]), "+f"(d[1]), "+f"(d[2]), "+f"(d[3]), "+f"(d[4]), "+f"(d[5]), "+f"(d[6]), "+f"(d[7]),
        "+f"(d[8]), "+f"(d[9]), "+f"(d[10]), "+f"(d[11]), "+f"(d[12]), "+f"(d[13]), "+f"(d[14]), "+f"(d[15]),
        "+f"(d[16]), "+f"(d[17]), "+f"(d[18]), "+f"(d[19]), "+f"(d[20]), "+f"(d[21]), "+f"(d[22]), "+f"(d[23]),
        "+f"(d[24]), "+f"(d[25]), "+f"(d[26]), "+f"(d[27]), "+f"(d[28]), "+f"(d[29]), "+f"(d[30]), "+f"(d[31]),
        "+f"(d[32]), "+f"(d[33]), "+f"(d[34]), "+f"(d[35]), "+f"(d[36]), "+f"(d[37]), "+f"(d[38]), "+f"(d[39]),
        "+f"(d[40]), "+f"(d[41]), "+f"(d[42]), "+f"(d[43]), "+f"(d[44]), "+f"(d[45]), "+f"(d[46]), "+f"(d[47]),
        "+f"(d[48]), "+f"(d[49]), "+f"(d[50]), "+f"(d[51]), "+f"(d[52]), "+f"(d[53]), "+f"(d[54]), "+f"(d[55]),
        "+f"(d[56]), "+f"(d[57]), "+f"(d[58]), "+f"(d[59]), "+f"(d[60]), "+f"(d[61]), "+f"(d[62]), "+f"(d[63]),
        "+f"(d[64]), "+f"(d[65]), "+f"(d[66]), "+f"(d[67]), "+f"(d[68]), "+f"(d[69]), "+f"(d[70]), "+f"(d[71]),
        "+f"(d[72]), "+f"(d[73]), "+f"(d[74]), "+f"(d[75]), "+f"(d[76]), "+f"(d[77]), "+f"(d[78]), "+f"(d[79]),
        "+f"(d[80]), "+f"(d[81]), "+f"(d[82]), "+f"(d[83]), "+f"(d[84]), "+f"(d[85]), "+f"(d[86]), "+f"(d[87]),
        "+f"(d[88]), "+f"(d[89]), "+f"(d[90]), "+f"(d[91]), "+f"(d[92]), "+f"(d[93]), "+f"(d[94]), "+f"(d[95]),
        "+f"(d[96]), "+f"(d[97]), "+f"(d[98]), "+f"(d[99]), "+f"(d[100]), "+f"(d[101]), "+f"(d[102]), "+f"(d[103]),
        "+f"(d[104]), "+f"(d[105]), "+f"(d[106]), "+f"(d[107]), "+f"(d[108]), "+f"(d[109]), "+f"(d[110]), "+f"(d[111]),
        "+f"(d[112]), "+f"(d[113]), "+f"(d[114]), "+f"(d[115]), "+f"(d[116]), "+f"(d[117]), "+f"(d[118]), "+f"(d[119]),
        "+f"(d[120]), "+f"(d[121]), "+f"(d[122]), "+f"(d[123]), "+f"(d[124]), "+f"(d[125]), "+f"(d[126]), "+f"(d[127])
      : "l"(descA), "l"(descB));
}

__device__ __forceinline__ void mma_ss64(float (&d)[32], uint64_t descA, uint64_t descB) {
  asm volatile("wgmma.mma_async.sync.aligned.m64n64k16.f32.bf16.bf16 {"
      "%0, %1, %2, %3, %4, %5, %6, %7, %8, %9, %10, %11, %12, %13, %14, %15, "
      "%16, %17, %18, %19, %20, %21, %22, %23, %24, %25, %26, %27, %28, %29, %30, %31"
      "}, %32, %33, 1, 1, 1, 0, 1;\n"
      : "+f"(d[0]), "+f"(d[1]), "+f"(d[2]), "+f"(d[3]), "+f"(d[4]), "+f"(d[5]), "+f"(d[6]), "+f"(d[7]),
        "+f"(d[8]), "+f"(d[9]), "+f"(d[10]), "+f"(d[11]), "+f"(d[12]), "+f"(d[13]), "+f"(d[14]), "+f"(d[15]),
        "+f"(d[16]), "+f"(d[17]), "+f"(d[18]), "+f"(d[19]), "+f"(d[20]), "+f"(d[21]), "+f"(d[22]), "+f"(d[23]),
        "+f"(d[24]), "+f"(d[25]), "+f"(d[26]), "+f"(d[27]), "+f"(d[28]), "+f"(d[29]), "+f"(d[30]), "+f"(d[31])
      : "l"(descA), "l"(descB));
}

__device__ __forceinline__ void mma_ss80(float (&d)[40], uint64_t descA, uint64_t descB) {
  asm volatile("wgmma.mma_async.sync.aligned.m64n80k16.f32.bf16.bf16 {"
      "%0, %1, %2, %3, %4, %5, %6, %7, %8, %9, %10, %11, %12, %13, %14, %15, "
      "%16, %17, %18, %19, %20, %21, %22, %23, %24, %25, %26, %27, %28, %29, %30, %31, "
      "%32, %33, %34, %35, %36, %37, %38, %39"
      "}, %40, %41, 1, 1, 1, 0, 1;\n"
      : "+f"(d[0]), "+f"(d[1]), "+f"(d[2]), "+f"(d[3]), "+f"(d[4]), "+f"(d[5]), "+f"(d[6]), "+f"(d[7]),
        "+f"(d[8]), "+f"(d[9]), "+f"(d[10]), "+f"(d[11]), "+f"(d[12]), "+f"(d[13]), "+f"(d[14]), "+f"(d[15]),
        "+f"(d[16]), "+f"(d[17]), "+f"(d[18]), "+f"(d[19]), "+f"(d[20]), "+f"(d[21]), "+f"(d[22]), "+f"(d[23]),
        "+f"(d[24]), "+f"(d[25]), "+f"(d[26]), "+f"(d[27]), "+f"(d[28]), "+f"(d[29]), "+f"(d[30]), "+f"(d[31]),
        "+f"(d[32]), "+f"(d[33]), "+f"(d[34]), "+f"(d[35]), "+f"(d[36]), "+f"(d[37]), "+f"(d[38]), "+f"(d[39])
      : "l"(descA), "l"(descB));
}

__device__ __forceinline__ void mma_ss192(float (&d)[96], uint64_t descA, uint64_t descB) {
  asm volatile("wgmma.mma_async.sync.aligned.m64n192k16.f32.bf16.bf16 {"
      "%0, %1, %2, %3, %4, %5, %6, %7, %8, %9, %10, %11, %12, %13, %14, %15, "
      "%16, %17, %18, %19, %20, %21, %22, %23, %24, %25, %26, %27, %28, %29, %30, %31, "
      "%32, %33, %34, %35, %36, %37, %38, %39, %40, %41, %42, %43, %44, %45, %46, %47, "
      "%48, %49, %50, %51, %52, %53, %54, %55, %56, %57, %58, %59, %60, %61, %62, %63, "
      "%64, %65, %66, %67, %68, %69, %70, %71, %72, %73, %74, %75, %76, %77, %78, %79, "
      "%80, %81, %82, %83, %84, %85, %86, %87, %88, %89, %90, %91, %92, %93, %94, %95"
      "}, %96, %97, 1, 1, 1, 0, 1;\n"
      : "+f"(d[0]), "+f"(d[1]), "+f"(d[2]), "+f"(d[3]), "+f"(d[4]), "+f"(d[5]), "+f"(d[6]), "+f"(d[7]),
        "+f"(d[8]), "+f"(d[9]), "+f"(d[10]), "+f"(d[11]), "+f"(d[12]), "+f"(d[13]), "+f"(d[14]), "+f"(d[15]),
        "+f"(d[16]), "+f"(d[17]), "+f"(d[18]), "+f"(d[19]), "+f"(d[20]), "+f"(d[21]), "+f"(d[22]), "+f"(d[23]),
        "+f"(d[24]), "+f"(d[25]), "+f"(d[26]), "+f"(d[27]), "+f"(d[28]), "+f"(d[29]), "+f"(d[30]), "+f"(d[31]),
        "+f"(d[32]), "+f"(d[33]), "+f"(d[34]), "+f"(d[35]), "+f"(d[36]), "+f"(d[37]), "+f"(d[38]), "+f"(d[39]),
        "+f"(d[40]), "+f"(d[41]), "+f"(d[42]), "+f"(d[43]), "+f"(d[44]), "+f"(d[45]), "+f"(d[46]), "+f"(d[47]),
        "+f"(d[48]), "+f"(d[49]), "+f"(d[50]), "+f"(d[51]), "+f"(d[52]), "+f"(d[53]), "+f"(d[54]), "+f"(d[55]),
        "+f"(d[56]), "+f"(d[57]), "+f"(d[58]), "+f"(d[59]), "+f"(d[60]), "+f"(d[61]), "+f"(d[62]), "+f"(d[63]),
        "+f"(d[64]), "+f"(d[65]), "+f"(d[66]), "+f"(d[67]), "+f"(d[68]), "+f"(d[69]), "+f"(d[70]), "+f"(d[71]),
        "+f"(d[72]), "+f"(d[73]), "+f"(d[74]), "+f"(d[75]), "+f"(d[76]), "+f"(d[77]), "+f"(d[78]), "+f"(d[79]),
        "+f"(d[80]), "+f"(d[81]), "+f"(d[82]), "+f"(d[83]), "+f"(d[84]), "+f"(d[85]), "+f"(d[86]), "+f"(d[87]),
        "+f"(d[88]), "+f"(d[89]), "+f"(d[90]), "+f"(d[91]), "+f"(d[92]), "+f"(d[93]), "+f"(d[94]), "+f"(d[95])
      : "l"(descA), "l"(descB));
}

__device__ __forceinline__ void mma_ss80_tt(float (&d)[40], uint64_t descA, uint64_t descB) {
  asm volatile("wgmma.mma_async.sync.aligned.m64n80k16.f32.bf16.bf16 {"
      "%0, %1, %2, %3, %4, %5, %6, %7, %8, %9, %10, %11, %12, %13, %14, %15, "
      "%16, %17, %18, %19, %20, %21, %22, %23, %24, %25, %26, %27, %28, %29, %30, %31, "
      "%32, %33, %34, %35, %36, %37, %38, %39"
      "}, %40, %41, 1, 1, 1, 1, 1;\n"
      : "+f"(d[0]), "+f"(d[1]), "+f"(d[2]), "+f"(d[3]), "+f"(d[4]), "+f"(d[5]), "+f"(d[6]), "+f"(d[7]),
        "+f"(d[8]), "+f"(d[9]), "+f"(d[10]), "+f"(d[11]), "+f"(d[12]), "+f"(d[13]), "+f"(d[14]), "+f"(d[15]),
        "+f"(d[16]), "+f"(d[17]), "+f"(d[18]), "+f"(d[19]), "+f"(d[20]), "+f"(d[21]), "+f"(d[22]), "+f"(d[23]),
        "+f"(d[24]), "+f"(d[25]), "+f"(d[26]), "+f"(d[27]), "+f"(d[28]), "+f"(d[29]), "+f"(d[30]), "+f"(d[31]),
        "+f"(d[32]), "+f"(d[33]), "+f"(d[34]), "+f"(d[35]), "+f"(d[36]), "+f"(d[37]), "+f"(d[38]), "+f"(d[39])
      : "l"(descA), "l"(descB));
}
__device__ __forceinline__ void mma_ss80_tt_z(float (&d)[40], uint64_t descA, uint64_t descB) {
  asm volatile("wgmma.mma_async.sync.aligned.m64n80k16.f32.bf16.bf16 {"
      "%0, %1, %2, %3, %4, %5, %6, %7, %8, %9, %10, %11, %12, %13, %14, %15, "
      "%16, %17, %18, %19, %20, %21, %22, %23, %24, %25, %26, %27, %28, %29, %30, %31, "
      "%32, %33, %34, %35, %36, %37, %38, %39"
      "}, %40, %41, 0, 1, 1, 1, 1;\n"
      : "=f"(d[0]), "=f"(d[1]), "=f"(d[2]), "=f"(d[3]), "=f"(d[4]), "=f"(d[5]), "=f"(d[6]), "=f"(d[7]),
        "=f"(d[8]), "=f"(d[9]), "=f"(d[10]), "=f"(d[11]), "=f"(d[12]), "=f"(d[13]), "=f"(d[14]), "=f"(d[15]),
        "=f"(d[16]), "=f"(d[17]), "=f"(d[18]), "=f"(d[19]), "=f"(d[20]), "=f"(d[21]), "=f"(d[22]), "=f"(d[23]),
        "=f"(d[24]), "=f"(d[25]), "=f"(d[26]), "=f"(d[27]), "=f"(d[28]), "=f"(d[29]), "=f"(d[30]), "=f"(d[31]),
        "=f"(d[32]), "=f"(d[33]), "=f"(d[34]), "=f"(d[35]), "=f"(d[36]), "=f"(d[37]), "=f"(d[38]), "=f"(d[39])
      : "l"(descA), "l"(descB));
}

__device__ __forceinline__ void mma_rs80_k(float (&d)[40], const uint32_t (&a)[4], uint64_t descB) {
  asm volatile("wgmma.mma_async.sync.aligned.m64n80k16.f32.bf16.bf16 {"
      "%0, %1, %2, %3, %4, %5, %6, %7, %8, %9, %10, %11, %12, %13, %14, %15, "
      "%16, %17, %18, %19, %20, %21, %22, %23, %24, %25, %26, %27, %28, %29, %30, %31, "
      "%32, %33, %34, %35, %36, %37, %38, %39"
      "}, {%40, %41, %42, %43}, %44, 1, 1, 1, 0;\n"
      : "+f"(d[0]), "+f"(d[1]), "+f"(d[2]), "+f"(d[3]), "+f"(d[4]), "+f"(d[5]), "+f"(d[6]), "+f"(d[7]),
        "+f"(d[8]), "+f"(d[9]), "+f"(d[10]), "+f"(d[11]), "+f"(d[12]), "+f"(d[13]), "+f"(d[14]), "+f"(d[15]),
        "+f"(d[16]), "+f"(d[17]), "+f"(d[18]), "+f"(d[19]), "+f"(d[20]), "+f"(d[21]), "+f"(d[22]), "+f"(d[23]),
        "+f"(d[24]), "+f"(d[25]), "+f"(d[26]), "+f"(d[27]), "+f"(d[28]), "+f"(d[29]), "+f"(d[30]), "+f"(d[31]),
        "+f"(d[32]), "+f"(d[33]), "+f"(d[34]), "+f"(d[35]), "+f"(d[36]), "+f"(d[37]), "+f"(d[38]), "+f"(d[39])
      : "r"(a[0]), "r"(a[1]), "r"(a[2]), "r"(a[3]), "l"(descB));
}
__device__ __forceinline__ void mma_rs80_k_z(float (&d)[40], const uint32_t (&a)[4], uint64_t descB) {
  asm volatile("wgmma.mma_async.sync.aligned.m64n80k16.f32.bf16.bf16 {"
      "%0, %1, %2, %3, %4, %5, %6, %7, %8, %9, %10, %11, %12, %13, %14, %15, "
      "%16, %17, %18, %19, %20, %21, %22, %23, %24, %25, %26, %27, %28, %29, %30, %31, "
      "%32, %33, %34, %35, %36, %37, %38, %39"
      "}, {%40, %41, %42, %43}, %44, 0, 1, 1, 0;\n"
      : "=f"(d[0]), "=f"(d[1]), "=f"(d[2]), "=f"(d[3]), "=f"(d[4]), "=f"(d[5]), "=f"(d[6]), "=f"(d[7]),
        "=f"(d[8]), "=f"(d[9]), "=f"(d[10]), "=f"(d[11]), "=f"(d[12]), "=f"(d[13]), "=f"(d[14]), "=f"(d[15]),
        "=f"(d[16]), "=f"(d[17]), "=f"(d[18]), "=f"(d[19]), "=f"(d[20]), "=f"(d[21]), "=f"(d[22]), "=f"(d[23]),
        "=f"(d[24]), "=f"(d[25]), "=f"(d[26]), "=f"(d[27]), "=f"(d[28]), "=f"(d[29]), "=f"(d[30]), "=f"(d[31]),
        "=f"(d[32]), "=f"(d[33]), "=f"(d[34]), "=f"(d[35]), "=f"(d[36]), "=f"(d[37]), "=f"(d[38]), "=f"(d[39])
      : "r"(a[0]), "r"(a[1]), "r"(a[2]), "r"(a[3]), "l"(descB));
}

__device__ __forceinline__ void mma_rs48_k(float (&d)[24], const uint32_t (&a)[4], uint64_t descB) {
  asm volatile("wgmma.mma_async.sync.aligned.m64n48k16.f32.bf16.bf16 {"
      "%0, %1, %2, %3, %4, %5, %6, %7, %8, %9, %10, %11, %12, %13, %14, %15, "
      "%16, %17, %18, %19, %20, %21, %22, %23"
      "}, {%24, %25, %26, %27}, %28, 1, 1, 1, 0;\n"
      : "+f"(d[0]), "+f"(d[1]), "+f"(d[2]), "+f"(d[3]), "+f"(d[4]), "+f"(d[5]), "+f"(d[6]), "+f"(d[7]),
        "+f"(d[8]), "+f"(d[9]), "+f"(d[10]), "+f"(d[11]), "+f"(d[12]), "+f"(d[13]), "+f"(d[14]), "+f"(d[15]),
        "+f"(d[16]), "+f"(d[17]), "+f"(d[18]), "+f"(d[19]), "+f"(d[20]), "+f"(d[21]), "+f"(d[22]), "+f"(d[23])
      : "r"(a[0]), "r"(a[1]), "r"(a[2]), "r"(a[3]), "l"(descB));
}
__device__ __forceinline__ void mma_rs48_k_z(float (&d)[24], const uint32_t (&a)[4], uint64_t descB) {
  asm volatile("wgmma.mma_async.sync.aligned.m64n48k16.f32.bf16.bf16 {"
      "%0, %1, %2, %3, %4, %5, %6, %7, %8, %9, %10, %11, %12, %13, %14, %15, "
      "%16, %17, %18, %19, %20, %21, %22, %23"
      "}, {%24, %25, %26, %27}, %28, 0, 1, 1, 0;\n"
      : "=f"(d[0]), "=f"(d[1]), "=f"(d[2]), "=f"(d[3]), "=f"(d[4]), "=f"(d[5]), "=f"(d[6]), "=f"(d[7]),
        "=f"(d[8]), "=f"(d[9]), "=f"(d[10]), "=f"(d[11]), "=f"(d[12]), "=f"(d[13]), "=f"(d[14]), "=f"(d[15]),
        "=f"(d[16]), "=f"(d[17]), "=f"(d[18]), "=f"(d[19]), "=f"(d[20]), "=f"(d[21]), "=f"(d[22]), "=f"(d[23])
      : "r"(a[0]), "r"(a[1]), "r"(a[2]), "r"(a[3]), "l"(descB));
}

__device__ __forceinline__ void mma_rs160_n(float (&d)[80], const uint32_t (&a)[4], uint64_t descB) {
  asm volatile("wgmma.mma_async.sync.aligned.m64n160k16.f32.bf16.bf16 {"
      "%0, %1, %2, %3, %4, %5, %6, %7, %8, %9, %10, %11, %12, %13, %14, %15, "
      "%16, %17, %18, %19, %20, %21, %22, %23, %24, %25, %26, %27, %28, %29, %30, %31, "
      "%32, %33, %34, %35, %36, %37, %38, %39, %40, %41, %42, %43, %44, %45, %46, %47, "
      "%48, %49, %50, %51, %52, %53, %54, %55, %56, %57, %58, %59, %60, %61, %62, %63, "
      "%64, %65, %66, %67, %68, %69, %70, %71, %72, %73, %74, %75, %76, %77, %78, %79"
      "}, {%80, %81, %82, %83}, %84, 1, 1, 1, 1;\n"
      : "+f"(d[0]), "+f"(d[1]), "+f"(d[2]), "+f"(d[3]), "+f"(d[4]), "+f"(d[5]), "+f"(d[6]), "+f"(d[7]),
        "+f"(d[8]), "+f"(d[9]), "+f"(d[10]), "+f"(d[11]), "+f"(d[12]), "+f"(d[13]), "+f"(d[14]), "+f"(d[15]),
        "+f"(d[16]), "+f"(d[17]), "+f"(d[18]), "+f"(d[19]), "+f"(d[20]), "+f"(d[21]), "+f"(d[22]), "+f"(d[23]),
        "+f"(d[24]), "+f"(d[25]), "+f"(d[26]), "+f"(d[27]), "+f"(d[28]), "+f"(d[29]), "+f"(d[30]), "+f"(d[31]),
        "+f"(d[32]), "+f"(d[33]), "+f"(d[34]), "+f"(d[35]), "+f"(d[36]), "+f"(d[37]), "+f"(d[38]), "+f"(d[39]),
        "+f"(d[40]), "+f"(d[41]), "+f"(d[42]), "+f"(d[43]), "+f"(d[44]), "+f"(d[45]), "+f"(d[46]), "+f"(d[47]),
        "+f"(d[48]), "+f"(d[49]), "+f"(d[50]), "+f"(d[51]), "+f"(d[52]), "+f"(d[53]), "+f"(d[54]), "+f"(d[55]),
        "+f"(d[56]), "+f"(d[57]), "+f"(d[58]), "+f"(d[59]), "+f"(d[60]), "+f"(d[61]), "+f"(d[62]), "+f"(d[63]),
        "+f"(d[64]), "+f"(d[65]), "+f"(d[66]), "+f"(d[67]), "+f"(d[68]), "+f"(d[69]), "+f"(d[70]), "+f"(d[71]),
        "+f"(d[72]), "+f"(d[73]), "+f"(d[74]), "+f"(d[75]), "+f"(d[76]), "+f"(d[77]), "+f"(d[78]), "+f"(d[79])
      : "r"(a[0]), "r"(a[1]), "r"(a[2]), "r"(a[3]), "l"(descB));
}
__device__ __forceinline__ void mma_rs160_n_z(float (&d)[80], const uint32_t (&a)[4], uint64_t descB) {
  asm volatile("wgmma.mma_async.sync.aligned.m64n160k16.f32.bf16.bf16 {"
      "%0, %1, %2, %3, %4, %5, %6, %7, %8, %9, %10, %11, %12, %13, %14, %15, "
      "%16, %17, %18, %19, %20, %21, %22, %23, %24, %25, %26, %27, %28, %29, %30, %31, "
      "%32, %33, %34, %35, %36, %37, %38, %39, %40, %41, %42, %43, %44, %45, %46, %47, "
      "%48, %49, %50, %51, %52, %53, %54, %55, %56, %57, %58, %59, %60, %61, %62, %63, "
      "%64, %65, %66, %67, %68, %69, %70, %71, %72, %73, %74, %75, %76, %77, %78, %79"
      "}, {%80, %81, %82, %83}, %84, 0, 1, 1, 1;\n"
      : "=f"(d[0]), "=f"(d[1]), "=f"(d[2]), "=f"(d[3]), "=f"(d[4]), "=f"(d[5]), "=f"(d[6]), "=f"(d[7]),
        "=f"(d[8]), "=f"(d[9]), "=f"(d[10]), "=f"(d[11]), "=f"(d[12]), "=f"(d[13]), "=f"(d[14]), "=f"(d[15]),
        "=f"(d[16]), "=f"(d[17]), "=f"(d[18]), "=f"(d[19]), "=f"(d[20]), "=f"(d[21]), "=f"(d[22]), "=f"(d[23]),
        "=f"(d[24]), "=f"(d[25]), "=f"(d[26]), "=f"(d[27]), "=f"(d[28]), "=f"(d[29]), "=f"(d[30]), "=f"(d[31]),
        "=f"(d[32]), "=f"(d[33]), "=f"(d[34]), "=f"(d[35]), "=f"(d[36]), "=f"(d[37]), "=f"(d[38]), "=f"(d[39]),
        "=f"(d[40]), "=f"(d[41]), "=f"(d[42]), "=f"(d[43]), "=f"(d[44]), "=f"(d[45]), "=f"(d[46]), "=f"(d[47]),
        "=f"(d[48]), "=f"(d[49]), "=f"(d[50]), "=f"(d[51]), "=f"(d[52]), "=f"(d[53]), "=f"(d[54]), "=f"(d[55]),
        "=f"(d[56]), "=f"(d[57]), "=f"(d[58]), "=f"(d[59]), "=f"(d[60]), "=f"(d[61]), "=f"(d[62]), "=f"(d[63]),
        "=f"(d[64]), "=f"(d[65]), "=f"(d[66]), "=f"(d[67]), "=f"(d[68]), "=f"(d[69]), "=f"(d[70]), "=f"(d[71]),
        "=f"(d[72]), "=f"(d[73]), "=f"(d[74]), "=f"(d[75]), "=f"(d[76]), "=f"(d[77]), "=f"(d[78]), "=f"(d[79])
      : "r"(a[0]), "r"(a[1]), "r"(a[2]), "r"(a[3]), "l"(descB));
}

__device__ __forceinline__ void feature_map(const uint32_t (&P)[2][10], uint32_t (&fr)[10][4]) {
  constexpr float L2E = 1.4426950408889634f;
#pragma unroll
  for (int p = 0; p < 2; p++) {
#pragma unroll
    for (int r = 0; r < 2; r++) {
      uint32_t mx = P[r][5 * p], mn = mx;
#pragma unroll
      for (int g = 1; g < 5; g++) { mx = max_bf2(mx, P[r][5 * p + g]); mn = min_bf2(mn, P[r][5 * p + g]); }
      mx = max_bf2(mx, __shfl_xor_sync(0xffffffffu, mx, 1));
      mn = min_bf2(mn, __shfl_xor_sync(0xffffffffu, mn, 1));
      mx = max_bf2(mx, __shfl_xor_sync(0xffffffffu, mx, 2));
      mn = min_bf2(mn, __shfl_xor_sync(0xffffffffu, mn, 2));
      float mx0 = -bf_lo(mx) * L2E, mx1 = -bf_hi(mx) * L2E, mn0 = bf_lo(mn) * L2E, mn1 = bf_hi(mn) * L2E;
      float ep0[5], ep1[5], en0[5], en1[5];
      float sp0 = 0.f, sp1 = 0.f, sn0 = 0.f, sn1 = 0.f;
#pragma unroll
      for (int g = 0; g < 5; g++) {
        float x0 = bf_lo(P[r][5 * p + g]), x1 = bf_hi(P[r][5 * p + g]);
        ep0[g] = ex2(fmaf(x0, L2E, mx0)); ep1[g] = ex2(fmaf(x1, L2E, mx1));
        en0[g] = ex2(fmaf(x0, -L2E, mn0)); en1[g] = ex2(fmaf(x1, -L2E, mn1));
        sp0 += ep0[g]; sp1 += ep1[g]; sn0 += en0[g]; sn1 += en1[g];
      }
      sp0 += __shfl_xor_sync(0xffffffffu, sp0, 1); sp1 += __shfl_xor_sync(0xffffffffu, sp1, 1);
      sn0 += __shfl_xor_sync(0xffffffffu, sn0, 1); sn1 += __shfl_xor_sync(0xffffffffu, sn1, 1);
      sp0 += __shfl_xor_sync(0xffffffffu, sp0, 2); sp1 += __shfl_xor_sync(0xffffffffu, sp1, 2);
      sn0 += __shfl_xor_sync(0xffffffffu, sn0, 2); sn1 += __shfl_xor_sync(0xffffffffu, sn1, 2);
      sp0 = rcp(sp0); sp1 = rcp(sp1); sn0 = rcp(sn0); sn1 = rcp(sn1);
#pragma unroll
      for (int g = 0; g < 5; g++) {
        fr[5 * p + g][r] = pack_bf16(ep0[g] * sp0, ep1[g] * sp1);
        fr[5 * p + g][2 + r] = pack_bf16(en0[g] * sn0, en1[g] * sn1);
      }
    }
  }
}

template <bool V> struct BoolC { static constexpr bool value = V; };
struct Ring {
  uint32_t idx, phase;
  template <int N> __device__ __forceinline__ void next() { if (++idx == N) { idx = 0; phase ^= 1; } }
};

}

__global__ void __cluster_dims__(2, 1, 1) __launch_bounds__(384, 1)
fused_kernel(const __grid_constant__ Maps maps, const __nv_bfloat16* __restrict__ x, const __nv_bfloat16* __restrict__ wqkv,
             const __nv_bfloat16* __restrict__ wphi, const __nv_bfloat16* __restrict__ w1, const __nv_bfloat16* __restrict__ w2,
             const __nv_bfloat16* __restrict__ w3, const __nv_bfloat16* __restrict__ w4, const __nv_bfloat16* __restrict__ wo,
             const __nv_bfloat16* __restrict__ gate_w) {
  extern __shared__ __align__(1024) uint8_t sgen[];
  const uint32_t sb = smem_u32(sgen);
  const uint32_t sb16 = (sb & 0x3FFFFu) >> 4;
  const uint32_t bars = sb + OFF_BAR;
  const uint32_t fullA = bars + 8 * B_FULLA, emptyA = bars + 8 * B_EMPTYA, fullB = bars + 8 * B_FULLB, emptyB = bars + 8 * B_EMPTYB;

  const int tid = threadIdx.x;
  const int rank = blockIdx.x & 1;
  const int pairIdx = blockIdx.x >> 1;
  const int i = pairIdx >> 2, j = 2 * (pairIdx & 3) + rank;

  TSTAMP(0);
  auto load_p1_b = [&](int k, uint32_t slot, uint32_t bar) {
    mbar_expect_tx(bar, 40960);
    tma4d(slot + 8192, &maps.qm, bar, 0, 64 * k, 0, j);
    tma3d(slot, &maps.w1m, bar, 0, 64 * k, j);
    tma4d(slot + 32768 + 2048, &maps.qr, bar, 64, 64 * k, 0, j);
    tma3d(slot + 32768, &maps.w1r, bar, 64, 64 * k, j);
  };
  if (tid >= 256) {
    asm volatile("setmaxnreg.dec.sync.aligned.u32 40;");
    if (tid == 256) {
#pragma unroll
      for (int s = 0; s < NA; s++) mbar_init(fullA + 8 * s, 1);
      asm volatile("fence.mbarrier_init.release.cluster;" ::: "memory");
#pragma unroll 1
      for (int u = 0; u < 4; u++) {
        if ((u & 1) == 0) mbar_expect_tx(fullA + 4 * u, SLOT_A);
        tma2d(sb + OFF_A + u * 8192, &maps.x, fullA + 8 * (u >> 1), 64 * (u >> 1), 128 * i + 64 * (u & 1));
      }
    } else if (tid == 288) {
#pragma unroll
      for (int s = 0; s < NB; s++) mbar_init(fullB + 8 * s, 1);
      asm volatile("fence.mbarrier_init.release.cluster;" ::: "memory");
#pragma unroll 1
      for (int k = 0; k < 2; k++) load_p1_b(k, sb + OFF_B + k * SLOT_B, fullB + 8 * k);
    } else if (tid == 320) {
#pragma unroll
      for (int b = B_CS; b < NBAR; b++) mbar_init(bars + 8 * b, b < B_EMPTYB ? 1 : b < B_EMPTYA ? 8 : 16);
#pragma unroll
      for (int b = B_DSR; b < B_EMPTYB; b++) mbar_expect_tx(bars + 8 * b, 10240);
      asm volatile("fence.mbarrier_init.release.cluster;" ::: "memory");
    }
    __syncwarp();
    asm volatile("barrier.cluster.arrive.relaxed.aligned;" ::: "memory");
    auto get_epoch = [&]() { return *reinterpret_cast<volatile unsigned*>(g_flags + FL_DONE * 32) / NCTA; };
    if (tid >= 320) {
      const int lane = tid & 31, ch = lane % 10, rg = lane / 10;
      const __nv_bfloat16* p = w1 + (size_t)(40 * i + (tid >= 352 ? 20 : 0) + rg) * D_ + 80 * j + 8 * ch;
      const unsigned par = get_epoch() & 1;
      float a[8];
#pragma unroll
      for (int e = 0; e < 8; e++) a[e] = 0.f;
#pragma unroll
      for (int it = 0; it < 7; it++) {
        uint4 v = make_uint4(0, 0, 0, 0);
        if (lane < 30 && 3 * it + rg < 20) v = __ldg(reinterpret_cast<const uint4*>(p + (size_t)it * 3 * D_));
        a[0] += bf_lo(v.x); a[1] += bf_hi(v.x); a[2] += bf_lo(v.y); a[3] += bf_hi(v.y);
        a[4] += bf_lo(v.z); a[5] += bf_hi(v.z); a[6] += bf_lo(v.w); a[7] += bf_hi(v.w);
      }
#pragma unroll
      for (int e = 0; e < 8; e++) a[e] += __shfl_down_sync(0xffffffffu, a[e], 10) + __shfl_down_sync(0xffffffffu, a[e], 20);
      if (lane < 10) {
        float* cd = g_acc[par] + 8 * KV_J + 80 * j + 8 * ch;
        red_add4(cd, a[0], a[1], a[2], a[3]); red_add4(cd + 4, a[4], a[5], a[6], a[7]);
      }
      __syncwarp();
      if (lane == 0) flag_add(FL_CS + j);
      __syncwarp();
    }
    asm volatile("barrier.cluster.wait.aligned;" ::: "memory");
    const int lane = tid & 31, pw = (tid >> 5) & 3;
    if (pw == 0) {
      if (tid == 256) {
        Ring r{2, 1};
        unsigned ep1 = 0;
#pragma unroll 1
        for (int k = 2; k < 30; k++) {
          if (k == 4) ep1 = get_epoch() + 1;
          if (k == 10 || k == 20) {
            const unsigned tgt = ep1 * 8u;
            const unsigned* f0 = g_flags + (k == 10 ? FL_H + ((i - 1) & 15) : FL_X1 + i) * 32;
            const unsigned* f1 = g_flags + (k == 10 ? FL_H + i : FL_X1 + i) * 32;
            const unsigned* f2 = g_flags + (k == 10 ? FL_H + ((i + 1) & 15) : FL_X1 + i) * 32;
            uint32_t n = 0;
            while (++n < (WAIT_LIMIT >> 4)) {
              unsigned v0, v1, v2;
              asm volatile("ld.relaxed.gpu.global.u32 %0, [%3];\nld.relaxed.gpu.global.u32 %1, [%4];\nld.acquire.gpu.global.u32 %2, [%5];"
                           : "=r"(v0), "=r"(v1), "=r"(v2) : "l"(f0), "l"(f1), "l"(f2) : "memory");
              if ((int)((v0 - tgt) | (v1 - tgt) | (v2 - tgt)) >= 0) break;
            }
            TSTAMPX(k == 10 ? 29 : 30);
          }
          mbar_wait(emptyA + 8 * r.idx, r.phase);
          const uint32_t bar = fullA + 8 * r.idx, slot = sb + OFF_A + r.idx * SLOT_A;
          TRACE(k);
          mbar_expect_tx(bar, SLOT_A);
          tma2d_mc(slot + rank * 8192, k < 10 ? &maps.x : k < 20 ? &maps.hs : &maps.x1, bar, 64 * (k % 10), 128 * i + 64 * rank);
          r.next<NA>();
        }
      }
    } else if (pw == 1) {
      if (tid == 288) {
        Ring r{2, 1};
#pragma unroll 1
        for (int k = 2; k < 18; k++) {
          mbar_wait(emptyB + 8 * r.idx, r.phase);
          const uint32_t bar = fullB + 8 * r.idx, slot = sb + OFF_B + r.idx * SLOT_B;
          if (k < 10) {
            load_p1_b(k, slot, bar);
          } else if (k < 13) {
            if (k == 12) mbar_wait(fullA + 8 * 2, 0);
            mbar_expect_tx(bar, k < 12 ? 40960 : 20480);
#pragma unroll 1
            for (int u = 0; u < (k < 12 ? 4 : 2); u++) tma3d(slot + u * 10240, &maps.w2, bar, 0, 256 * (k - 10) + 64 * u, 5 * j);
          } else {
            mbar_expect_tx(bar, 49152);
            tma3d(slot, &maps.w3, bar, 0, 128 * (k - 13), 3 * j);
            tma3d(slot + 24576, &maps.w3, bar, 0, 128 * (k - 13) + 64, 3 * j);
          }
          r.next<NB>();
        }
        Ring r4{0, 1};
#pragma unroll 1
        for (int n = 0; n < 16; n++) {
          if (n == 0 || n == 1 || n == 3) { mbar_wait(emptyB + 8 * r.idx, r.phase); r.next<NB>(); }
          mbar_wait(bars + 8 * (B_EMPTY4 + r4.idx), r4.phase);
          const uint32_t bar = bars + 8 * (B_FULL4 + r4.idx), slot = sb + OFF_B + r4.idx * UNIT4;
          const int u = n & 3, m = ((j >> 1) + 1 + (n >> 2)) & 3;
          mbar_expect_tx(bar, u == 3 ? 25600 : 20480);
          tma3d(slot, u == 3 ? &maps.wo : &maps.w4, bar, 0, u == 3 ? 80 * j : 192 * j + 64 * u, 5 * m);
          r4.next<NU4>();
        }
      }
    } else {
      const unsigned epoch = get_epoch();
      float* accg = g_acc[epoch & 1];
      if (pw == 2) {
        {
          float* nxt = g_acc[(epoch + 1) & 1];
          constexpr int PER = ACC_FLOATS / NCTA;
#pragma unroll 1
          for (int e = lane; e < PER; e += 32) nxt[blockIdx.x * PER + e] = 0.f;
        }
        if (tid == 320) {
          flag_wait(FL_CS + j, (epoch + 1) * 32u);
          flag_wait(FL_ST + i, (epoch + 1) * 8u);
          fence_async_glb();
          mbar_expect_tx(bars + 8 * B_CS, 320 + 2048);
          bulk_load(sb + OFF_CS, accg + 8 * KV_J + 80 * j, 320, bars + 8 * B_CS);
          bulk_load(sb + OFF_XST, g_xstat + 128 * i, 2048, bars + 8 * B_CS);
          TSTAMPX(21);
          l2_prefetch(w2 + (size_t)blockIdx.x * (D_ * D_ / NCTA), D_ * D_ * 2 / NCTA);
          flag_wait(FL_H + i, (epoch + 1) * 8u);
          l2_prefetch(w3 + (size_t)blockIdx.x * (F_ * D_ / NCTA), F_ * D_ * 2 / NCTA);
          l2_prefetch(w4 + (size_t)blockIdx.x * (F_ * D_ / NCTA), F_ * D_ * 2 / NCTA);
          l2_prefetch(wo + (size_t)blockIdx.x * (D_ * D_ / NCTA), D_ * D_ * 2 / NCTA);
          flag_wait(FL_KV + j, (epoch + 1) * 16u);
          mbar_expect_tx(bars + 8 * B_KV, KV_J * 4);
          bulk_load(sb + OFF_MISC, accg + j * KV_J, KV_J * 4, bars + 8 * B_KV);
          TSTAMPX(22);
        }
        __syncwarp();
#pragma unroll 1
        for (int m = 0; m < 6; m++) {
          const int col = 192 * j + 32 * m + 8 * (lane & 3);
          const __nv_bfloat16* p = w3 + (size_t)(40 * i + (lane >> 2) * 5) * F_ + col;
          float a[8];
#pragma unroll
          for (int e = 0; e < 8; e++) a[e] = 0.f;
#pragma unroll
          for (int it = 0; it < 5; it++) {
            const uint4 v = __ldg(reinterpret_cast<const uint4*>(p + (size_t)it * F_));
            a[0] += bf_lo(v.x); a[1] += bf_hi(v.x); a[2] += bf_lo(v.y); a[3] += bf_hi(v.y);
            a[4] += bf_lo(v.z); a[5] += bf_hi(v.z); a[6] += bf_lo(v.w); a[7] += bf_hi(v.w);
          }
#pragma unroll
          for (int e = 0; e < 4; e++) {
            const float snd = (lane & 4) ? a[e] : a[e + 4], keep = (lane & 4) ? a[e + 4] : a[e];
            a[e] = keep + __shfl_xor_sync(0xffffffffu, snd, 4);
            a[e] += __shfl_xor_sync(0xffffffffu, a[e], 8);
            a[e] += __shfl_xor_sync(0xffffffffu, a[e], 16);
          }
          if (lane < 8) red_add4(accg + 8 * KV_J + D_ + col + (lane >> 2) * 4, a[0], a[1], a[2], a[3]);
        }
        __syncwarp();
        if (tid == 320) {
          flag_add(FL_CS3 + j);
          mbar_wait(bars + 8 * B_MFREE, 0);
          flag_wait(FL_X1 + i, (epoch + 1) * 8u);
          flag_wait(FL_CS3 + j, (epoch + 1) * 16u);
          fence_async_glb();
          mbar_expect_tx(bars + 8 * B_ST1, 8192 + 768);
          bulk_load(sb + OFF_CS + 320, accg + 8 * KV_J + D_ + 192 * j, 768, bars + 8 * B_ST1);
          bulk_load(sb + OFF_MISC, g_st1 + 128 * i * 8, 8192, bars + 8 * B_ST1);
        }
      }
      if (tid == 352) {
        mbar_wait(bars + 8 * B_SIGP, 0);
        flag_add(FL_ST + i);
        TSTAMPX(20);
        mbar_expect_tx(bars + 8 * B_XR, 20480);
#pragma unroll 1
        for (int u = 0; u < 8; u++)
          tma2d(sb + OFF_B + (u / 3) * SLOT_B + SPARE + (u % 3) * 2560, &maps.xr, bars + 8 * B_XR, 80 * j, 128 * i + 16 * u);
        const int shift = (j < 2) ? 1 : (j < 4) ? -1 : (j < 6) ? 2 : -2;
        if ((shift > 0 && i == 0) || (shift < 0 && i == 15)) {
          const int nz = shift > 0 ? shift : -shift, zr = shift > 0 ? 0 : S_ - nz;
#pragma unroll 1
          for (int e = 0; e < nz * 10; e++)
            reinterpret_cast<uint4*>(g_Hs + (size_t)(2 + zr + e / 10) * D_ + 80 * j)[e % 10] = make_uint4(0, 0, 0, 0);
          fence_async_glb();
        }
        prefetch_tmap(&maps.st_h); prefetch_tmap(&maps.st_x1); prefetch_tmap(&maps.hs); prefetch_tmap(&maps.x1); prefetch_tmap(&maps.xr);
        prefetch_tmap(&maps.w2); prefetch_tmap(&maps.w3); prefetch_tmap(&maps.w4); prefetch_tmap(&maps.wo); prefetch_tmap(&maps.st_out);
        mbar_wait(bars + 8 * B_SIGH, 0);
        TSTAMPX(23);
        tma2d_store(&maps.st_h, sb + OFF_STG, 80 * j, 128 * i + 2 + shift);
        tma2d_store(&maps.st_h, sb + OFF_STG + 10240, 80 * j, 128 * i + 66 + shift);
        bulk_commit(); bulk_wait<0>();
        flag_add(FL_H + i);
        TSTAMPX(24);
        mbar_wait(bars + 8 * B_SIGKV, 0);
        TSTAMPX(25);
        asm volatile("cp.reduce.async.bulk.global.shared::cta.bulk_group.add.f32 [%0], [%1], %2;"
                     ::"l"(accg + j * KV_J), "r"(sb + OFF_MISC), "r"(KV_J * 4) : "memory");
        bulk_commit(); bulk_wait<0>();
        flag_add(FL_KV + j);
        TSTAMPX(26);
        mbar_wait(bars + 8 * B_SIGX1, 0);
        TSTAMPX(27);
        tma2d_store(&maps.st_x1, sb + OFF_STG, 80 * j, 128 * i);
        tma2d_store(&maps.st_x1, sb + OFF_STG + 10240, 80 * j, 128 * i + 64);
        bulk_commit(); bulk_wait<0>();
        flag_add(FL_X1 + i);
        TSTAMPX(28);
      }
    }
  } else {
    uint4 pv[5], pw_[5], pre;
    {
      const int row = 128 * i + 16 * j + (tid >> 4), l16 = tid & 15;
#pragma unroll
      for (int c = 0; c < 5; c++) pv[c] = __ldg(reinterpret_cast<const uint4*>(x + (size_t)row * D_ + c * 128 + l16 * 8));
      pre = __ldg(reinterpret_cast<const uint4*>(wphi + (size_t)j * 1600) + (tid < 200 ? tid : 0));
#pragma unroll
      for (int c = 0; c < 5; c++) pw_[c] = __ldg(reinterpret_cast<const uint4*>(gate_w + c * 128 + l16 * 8));
    }
    asm volatile("barrier.cluster.arrive.relaxed.aligned;" ::: "memory");
    asm volatile("setmaxnreg.inc.sync.aligned.u32 232;");
    const int wg = tid >> 7, warp = tid >> 5, lane = tid & 31, t = lane & 3;
    const int rloc = warp * 16 + (lane >> 2);
    const float* s_cs = reinterpret_cast<const float*>(sgen + OFF_CS);
    auto signal = [&](int b) {
      __syncwarp();
      if (lane == 0) mbar_arrive(bars + 8 * b);
    };
    auto releaseB = [&](uint32_t bar) {
      __syncwarp();
      if (lane == 0) mbar_arrive(bar);
    };
    auto release = [&](uint32_t bar) {
      __syncwarp();
      if (lane < 2) mbar_arrive_cta(bar, lane);
    };
    const uint32_t stg_lane = (warp * 16 + ((lane >> 3) & 1) * 8 + (lane & 7)) * 160 + (lane >> 4) * 16;

    {
#pragma unroll 1
      for (int e = tid; e < 800; e += 256) sts128(sb + OFF_MISC + e * 16, make_uint4(0, 0, 0, 0));
      bar_sync(1, 256);
      float f[40];
      float s = 0.f, gs = 0.f;
#pragma unroll
      for (int c = 0; c < 5; c++) {
        const uint32_t vv[4] = {pv[c].x, pv[c].y, pv[c].z, pv[c].w}, ww[4] = {pw_[c].x, pw_[c].y, pw_[c].z, pw_[c].w};
#pragma unroll
        for (int e = 0; e < 4; e++) {
          f[8 * c + 2 * e] = bf_lo(vv[e]); f[8 * c + 2 * e + 1] = bf_hi(vv[e]);
          s += f[8 * c + 2 * e] + f[8 * c + 2 * e + 1];
          gs = fmaf(f[8 * c + 2 * e], bf_lo(ww[e]), gs); gs = fmaf(f[8 * c + 2 * e + 1], bf_hi(ww[e]), gs);
        }
      }
#pragma unroll
      for (int o = 1; o < 16; o <<= 1) { s += __shfl_xor_sync(0xffffffffu, s, o); gs += __shfl_xor_sync(0xffffffffu, gs, o); }
      const float mean = s * (1.f / D_);
      float q = 0.f;
#pragma unroll
      for (int e = 0; e < 40; e++) { const float d = f[e] - mean; q = fmaf(d, d, q); }
#pragma unroll
      for (int o = 1; o < 16; o <<= 1) q += __shfl_xor_sync(0xffffffffu, q, o);
      const float rstd = rsqrtf(q * (1.f / D_) + 1e-5f);
      asm volatile("barrier.cluster.wait.aligned;" ::: "memory");
      if ((tid & 15) == 0) g_xstat[128 * i + 16 * j + (tid >> 4)] = make_float4(rstd, -mean * rstd, rcp(1.f + __expf(-gs)), 0.f);
      signal(B_SIGP);
      if (tid < 200) {
        const uint32_t ww[4] = {pre.x, pre.y, pre.z, pre.w};
        const int h = tid / 50;
#pragma unroll
        for (int e = 0; e < 8; e++) {
          const int idx = tid * 8 + e, k = idx / 20, ff = idx - 20 * k;
          const int n = 40 * (h >> 1) + 8 * (ff >> 2) + 2 * (ff & 3) + (h & 1);
          const int off = (k >> 4) * 2560 + n * 32 + ((((k >> 3) ^ (n >> 2)) & 1) << 4) + (k & 7) * 2;
          *reinterpret_cast<unsigned short*>(sgen + OFF_MISC + off) = (unsigned short)(ww[e >> 1] >> ((e & 1) * 16));
        }
      }
    }
    TSTAMP(1);

    Ring ra{0, 0}, rb{0, 0};
    uint32_t qp[2][10], P[2][10];
    float st_g[2];
    {
      float accM[128], accR[32];
      zero_regs(accM); zero_regs(accR);
      uint32_t pa = 0, pb = 0;
#pragma unroll 1
      for (int k = 0; k < 10; k++) {
        mbar_wait(fullA + 8 * ra.idx, ra.phase);
        if (tid == 0) TRACE(32 + k);
        mbar_wait(fullB + 8 * rb.idx, rb.phase);
        if (tid == 0) TRACE(64 + k);
        if (k == 0) TSTAMP(2);
        const uint32_t a0 = sb16 + ((OFF_A + ra.idx * SLOT_A + wg * 8192) >> 4), b0 = sb16 + ((OFF_B + rb.idx * SLOT_B) >> 4);
        wg_fence();
#pragma unroll
        for (int kk = 0; kk < 4; kk++) {
          const uint64_t da = make_desc(a0, kk * 32, 16, 1024, 1);
          mma_ss256(accM, da, make_desc(b0, kk * 2048, 8192, 1024, 1));
          mma_ss64(accR, da, make_desc(b0, 32768 + kk * 512, 2048, 256, 3));
          if (kk == 0) {
            wg_commit();
            if (k > 0) {
              wg_wait<1>();
              if (k - 1 < 8) release(emptyA + 8 * pa);
              releaseB(emptyB + 8 * pb);
            }
          }
        }
        wg_commit();
        pa = ra.idx; pb = rb.idx;
        ra.next<NA>(); rb.next<NB>();
      }
      TSTAMP(18);
      float st_rstd[2], st_mr[2];
      mbar_wait(bars + 8 * B_CS, 0);
#pragma unroll
      for (int r = 0; r < 2; r++) {
        const uint4 st = lds128(sb + OFF_XST + (rloc + 8 * r) * 16);
        st_rstd[r] = __uint_as_float(st.x); st_mr[r] = __uint_as_float(st.y); st_g[r] = __uint_as_float(st.z);
      }
      TSTAMP(19);
      wg_wait<0>();
      fence_regs(accM); fence_regs(accR);
      TSTAMP(3);
#define ACC(P_, G, I_) ((G) < 8 ? accM[(P_) * 32 + ((G) & 7) * 4 + (I_)] : accR[(P_) * 8 + ((G) & 1) * 4 + (I_)])
      {
        uint32_t hv[10][2];
#pragma unroll
        for (int g = 0; g < 10; g++) {
          const float2 cs = *reinterpret_cast<const float2*>(s_cs + 8 * g + 2 * t);
          const float v0 = gelu_s(fmaf(ACC(0, g, 0), st_rstd[0], st_mr[0] * cs.x), 0.5f), v1 = gelu_s(fmaf(ACC(0, g, 1), st_rstd[0], st_mr[0] * cs.y), 0.5f);
          const float v2 = gelu_s(fmaf(ACC(0, g, 2), st_rstd[1], st_mr[1] * cs.x), 0.5f), v3 = gelu_s(fmaf(ACC(0, g, 3), st_rstd[1], st_mr[1] * cs.y), 0.5f);
          hv[g][0] = pack_bf16(v0, v1); hv[g][1] = pack_bf16(v2, v3);
        }
        fence_async_smem();
        bar_sync(1, 256);
#pragma unroll
        for (int s = 0; s < 5; s++) stsm4(sb + OFF_STG + stg_lane + s * 32, hv[2 * s][0], hv[2 * s][1], hv[2 * s + 1][0], hv[2 * s + 1][1]);
        fence_async_smem();
        signal(B_SIGH);
      }
      TSTAMP(4);
      uint32_t kf[5][4], qf[5][4];
#pragma unroll
      for (int s = 0; s < 5; s++) {
        kf[s][0] = pack_bf16(ACC(2, 2 * s, 0), ACC(2, 2 * s, 1)); kf[s][1] = pack_bf16(ACC(2, 2 * s, 2), ACC(2, 2 * s, 3));
        kf[s][2] = pack_bf16(ACC(2, 2 * s + 1, 0), ACC(2, 2 * s + 1, 1)); kf[s][3] = pack_bf16(ACC(2, 2 * s + 1, 2), ACC(2, 2 * s + 1, 3));
        qf[s][0] = pack_bf16(ACC(1, 2 * s, 0), ACC(1, 2 * s, 1)); qf[s][1] = pack_bf16(ACC(1, 2 * s, 2), ACC(1, 2 * s, 3));
        qf[s][2] = pack_bf16(ACC(1, 2 * s + 1, 0), ACC(1, 2 * s + 1, 1)); qf[s][3] = pack_bf16(ACC(1, 2 * s + 1, 2), ACC(1, 2 * s + 1, 3));
      }
      float pk[40], pq[40];
      wg_fence();
#pragma unroll
      for (int s = 0; s < 5; s++) {
        if (s == 0) mma_rs80_k_z(pk, kf[s], make_desc(sb16, OFF_MISC, 16, 256, 3));
        else mma_rs80_k(pk, kf[s], make_desc(sb16, OFF_MISC + s * 2560, 16, 256, 3));
      }
#pragma unroll
      for (int s = 0; s < 5; s++) {
        if (s == 0) mma_rs80_k_z(pq, qf[s], make_desc(sb16, OFF_MISC, 16, 256, 3));
        else mma_rs80_k(pq, qf[s], make_desc(sb16, OFF_MISC + s * 2560, 16, 256, 3));
      }
      wg_commit();
      {
        const int mat = lane >> 3;
        const int tok = warp * 16 + (mat & 1) * 8 + (lane & 7);
        const uint32_t ones = (t == 0) ? 0x00003f80u : 0u;
        __syncwarp();
#pragma unroll
        for (int p = 0; p < 2; p++) {
          const uint32_t rowa = sb + OFF_A + p * SLOT_A + tok * 128;
#pragma unroll
          for (int gg = 0; gg < 3; gg++) {
            const int g0 = 5 * p + 2 * gg;
            uint32_t r0 = pack_bf16(ACC(3, g0, 0), ACC(3, g0, 1)), r1 = pack_bf16(ACC(3, g0, 2), ACC(3, g0, 3));
            uint32_t r2 = ones, r3 = ones;
            if (gg < 2) { r2 = pack_bf16(ACC(3, g0 + 1, 0), ACC(3, g0 + 1, 1)); r3 = pack_bf16(ACC(3, g0 + 1, 2), ACC(3, g0 + 1, 3)); }
            stsm4(rowa + (((2 * gg + (mat >> 1)) ^ (tok & 7)) << 4), r0, r1, r2, r3);
          }
        }
      }
#undef ACC
      wg_wait<0>();
      fence_regs(pk); fence_regs(pq);
#pragma unroll
      for (int G = 0; G < 10; G++) {
        P[0][G] = pack_bf16(pk[4 * G], pk[4 * G + 1]); P[1][G] = pack_bf16(pk[4 * G + 2], pk[4 * G + 3]);
        qp[0][G] = pack_bf16(pq[4 * G], pq[4 * G + 1]); qp[1][G] = pack_bf16(pq[4 * G + 2], pq[4 * G + 3]);
      }
    }

    uint32_t fr[10][4];
    uint32_t xv[2][10];
#pragma unroll
    for (int g = 0; g < 10; g++) xv[0][g] = xv[1][g] = 0u;
    int pass;
    pass = gridDim.y;
#pragma unroll 1
    do {
    feature_map(P, fr);
    if (pass != 0) {
    {
      const int mat = lane >> 3;
      const int tok = warp * 16 + (mat & 1) * 8 + (lane & 7);
      const uint32_t base = sb + OFF_B + tok * 32 + (((mat >> 1) ^ ((tok >> 2) & 1)) << 4);
#pragma unroll
      for (int G = 0; G < 10; G++) stsm4(base + G * 4096, fr[G][0], fr[G][1], fr[G][2], fr[G][3]);
      fence_async_smem();
      bar_sync(1, 256);
      float kv[40];
      const uint32_t a0 = sb16 + ((OFF_A + wg * SLOT_A) >> 4), b0 = sb16 + ((OFF_B + wg * 20480) >> 4);
      wg_fence();
#pragma unroll
      for (int ks = 0; ks < 8; ks++) {
        if (ks == 0) mma_ss80_tt_z(kv, make_desc(a0, 0, 16, 1024, 1), make_desc(b0, 0, 4096, 256, 3));
        else mma_ss80_tt(kv, make_desc(a0, ks * 2048, 16, 1024, 1), make_desc(b0, ks * 512, 4096, 256, 3));
      }
      wg_commit();
      wg_wait<0>();
      fence_regs(kv);
      TSTAMP(31);
      release(emptyA); release(emptyA + 8); releaseB(emptyB);
      const uint32_t dst = sb + OFF_MISC + wg * (KV_PAIR * 4);
      const int m0 = (warp & 3) * 16 + (lane >> 2);
#pragma unroll
      for (int r = 0; r < 2; r++) {
        const int m = m0 + 8 * r;
        const bool hi = m >= 20;
        uint32_t v[10];
#pragma unroll
        for (int G = 0; G < 10; G++) v[G] = __float_as_uint(hi ? kv[4 * G + 2 * r + 1] : kv[4 * G + 2 * r]);
        const uint32_t p = dst + 4 * (m < 40 ? m * 48 + t * 12 : 1920 + t * 24 + 12);
        if (m <= 40) {
          sts128(p, make_uint4(v[0], v[1], v[2], v[3])); sts128(p + 16, make_uint4(v[4], v[5], v[6], v[7]));
          sts128(p + 32, make_uint4(v[8], v[9], 0u, 0u));
        }
      }
      if (m0 == 32) {
        const uint32_t p = dst + 4 * (1920 + t * 24);
        sts128(p, make_uint4(__float_as_uint(kv[2]), __float_as_uint(kv[6]), __float_as_uint(kv[10]), __float_as_uint(kv[14])));
        sts128(p + 16, make_uint4(__float_as_uint(kv[18]), __float_as_uint(kv[22]), __float_as_uint(kv[26]), __float_as_uint(kv[30])));
        sts128(p + 32, make_uint4(__float_as_uint(kv[34]), __float_as_uint(kv[38]), 0u, 0u));
      }
      fence_async_smem();
      signal(B_SIGKV);
    }
    TSTAMP(5);

    {
      {
        mbar_wait(bars + 8 * B_XR, 0);
        const uint32_t xa = sb + OFF_B + (warp / 3) * SLOT_B + SPARE + (warp % 3) * 2560 + (lane >> 2) * 160 + t * 4;
#pragma unroll
        for (int g = 0; g < 10; g++) { xv[0][g] = lds32(xa + g * 16); xv[1][g] = lds32(xa + 1280 + g * 16); }
      }
      float acc[40];
      zero_regs(acc);
      uint32_t pa = 0, pb = 0;
#pragma unroll 1
      for (int k = 0; k < 10; k++) {
        mbar_wait(fullA + 8 * ra.idx, ra.phase);
        if (tid == 0) TRACE(42 + k);
        if ((k & 3) == 0) mbar_wait(fullB + 8 * rb.idx, rb.phase);
        if (tid == 0) TRACE(74 + k);
        if (k == 0) TSTAMP(6);
        const uint32_t a0 = sb16 + ((OFF_A + ra.idx * SLOT_A + wg * 8192) >> 4);
        const uint32_t b0 = sb16 + ((OFF_B + rb.idx * SLOT_B + (k & 3) * 10240) >> 4);
        wg_fence();
#pragma unroll
        for (int kk = 0; kk < 4; kk++) {
          mma_ss80(acc, make_desc(a0, kk * 32, 16, 1024, 1), make_desc(b0, kk * 512, 2048, 256, 3));
          if (kk == 1) {
            wg_commit();
            if (k > 0) {
              wg_wait<1>();
              release(emptyA + 8 * pa);
              if ((k & 3) == 0) releaseB(emptyB + 8 * pb);
            }
          }
        }
        wg_commit();
        pa = ra.idx; pb = rb.idx;
        ra.next<NA>();
        if ((k & 3) == 3 || k == 9) rb.next<NB>();
      }
      wg_wait<0>();
      fence_regs(acc);
      release(emptyA + 8 * pa); releaseB(emptyB + 8 * pb);
      TSTAMP(7);
#pragma unroll
      for (int r = 0; r < 2; r++) {
#pragma unroll
        for (int g = 0; g < 10; g++)
          xv[r][g] = pack_bf16(bf_lo(xv[r][g]) + acc[4 * g + 2 * r], bf_hi(xv[r][g]) + acc[4 * g + 2 * r + 1]);
      }
      bar_sync(1, 256);
#pragma unroll
      for (int s = 0; s < 5; s++) stsm4(sb + OFF_STG + stg_lane + s * 32, xv[0][2 * s], xv[1][2 * s], xv[0][2 * s + 1], xv[1][2 * s + 1]);
#pragma unroll
      for (int r = 0; r < 2; r++) {
        float s = 0.f;
#pragma unroll
        for (int g = 0; g < 10; g++) {
          acc[4 * g + 2 * r] = bf_lo(xv[r][g]); acc[4 * g + 2 * r + 1] = bf_hi(xv[r][g]);
          s += acc[4 * g + 2 * r] + acc[4 * g + 2 * r + 1];
        }
        s += __shfl_xor_sync(0xffffffffu, s, 1); s += __shfl_xor_sync(0xffffffffu, s, 2);
        const float mu = s * (1.f / 80.f);
        float q = 0.f;
#pragma unroll
        for (int g = 0; g < 10; g++) {
          const float d0 = acc[4 * g + 2 * r] - mu, d1 = acc[4 * g + 2 * r + 1] - mu;
          q = fmaf(d0, d0, q); q = fmaf(d1, d1, q);
        }
        q += __shfl_xor_sync(0xffffffffu, q, 1); q += __shfl_xor_sync(0xffffffffu, q, 2);
        if (t == 0) g_st1[(128 * i + rloc + 8 * r) * 8 + j] = make_float2(mu, q);
      }
      fence_async_smem();
      signal(B_SIGX1);
    }
    TSTAMP(8);
#pragma unroll
    for (int G = 0; G < 10; G++) { P[0][G] = qp[0][G]; P[1][G] = qp[1][G]; }
    }
    asm volatile("" : "+r"(pass));
    } while (pass-- != 0);

    uint32_t of[5][4];
    {
      mbar_wait(bars + 8 * B_KV, 0);
      uint4 kvr[2][3];
#pragma unroll
      for (int u = 0; u < 2; u++) {
        const int it = tid + 256 * u, p = it / 192, rem = it - 192 * p, n = rem >> 2, tq = rem & 3;
        const uint32_t sp = sb + OFF_MISC + 4 * (p * KV_PAIR + (n < 40 ? n * 48 + tq * 12 : 1920 + tq * 24 + (n & 1) * 12));
        if (it < 384) { kvr[u][0] = lds128(sp); kvr[u][1] = lds128(sp + 16); kvr[u][2] = lds128(sp + 32); }
      }
      bar_sync(1, 256);
#pragma unroll
      for (int u = 0; u < 2; u++) {
        const int it = tid + 256 * u, p = it / 192, rem = it - 192 * p, n = rem >> 2, tq = rem & 3;
        const int sh = (n < 40 ? (n >= 20) : (n & 1)) * 16;
        const uint32_t v[10] = {kvr[u][0].x, kvr[u][0].y, kvr[u][0].z, kvr[u][0].w, kvr[u][1].x, kvr[u][1].y, kvr[u][1].z, kvr[u][1].w, kvr[u][2].x, kvr[u][2].y};
        uint8_t* dst = sgen + OFF_MISC + p * 7680 + n * 32 + tq * 4;
        const int sw = ((n >> 2) & 1) << 4;
        if (it < 384) {
#pragma unroll
          for (int G = 0; G < 10; G++)
            *reinterpret_cast<uint32_t*>(dst + (G >> 1) * 1536 + (((G & 1) << 4) ^ sw)) = pack_bf16(__uint_as_float(v[G]), 0.f) << sh;
        }
      }
      fence_async_smem();
      bar_sync(1, 256);
      float o0[24], o1[24];
      wg_fence();
#pragma unroll
      for (int g = 0; g < 5; g++) {
        if (g == 0) mma_rs48_k_z(o0, fr[g], make_desc(sb16, OFF_MISC, 16, 256, 3));
        else mma_rs48_k(o0, fr[g], make_desc(sb16, OFF_MISC + g * 1536, 16, 256, 3));
      }
#pragma unroll
      for (int g = 0; g < 5; g++) {
        if (g == 0) mma_rs48_k_z(o1, fr[5], make_desc(sb16, OFF_MISC + 7680, 16, 256, 3));
        else mma_rs48_k(o1, fr[5 + g], make_desc(sb16, OFF_MISC + 7680 + g * 1536, 16, 256, 3));
      }
      wg_commit();
      wg_wait<0>();
      fence_regs(o0); fence_regs(o1);
      signal(B_MFREE);
#pragma unroll
      for (int r = 0; r < 2; r++) {
        const float a0 = __fdividef(st_g[r], o0[20 + 2 * r] + 1e-6f), a1 = __fdividef(st_g[r], o0[21 + 2 * r] + 1e-6f);
        const float b0 = __fdividef(st_g[r], o1[20 + 2 * r] + 1e-6f), b1 = __fdividef(st_g[r], o1[21 + 2 * r] + 1e-6f);
        const float am = t < 2 ? a0 : a1, bm = t < 2 ? b0 : b1;
#pragma unroll
        for (int g = 0; g < 5; g++) {
          const float sa = g < 2 ? a0 : (g == 2 ? am : a1), sb2 = g < 2 ? b0 : (g == 2 ? bm : b1);
          of[g >> 1][(g & 1) * 2 + r] = pack_bf16(o0[4 * g + 2 * r] * sa, o0[4 * g + 2 * r + 1] * sa);
          of[(5 + g) >> 1][((5 + g) & 1) * 2 + r] = pack_bf16(o1[4 * g + 2 * r] * sb2, o1[4 * g + 2 * r + 1] * sb2);
        }
      }
    }
    TSTAMP(9);

    uint32_t hf[12][4];
    {
      float acc[96];
      zero_regs(acc);
      uint32_t pa = 0, pb = 0;
#pragma unroll 1
      for (int k = 0; k < 10; k++) {
        mbar_wait(fullA + 8 * ra.idx, ra.phase);
        if (tid == 0) TRACE(52 + k);
        if ((k & 1) == 0) mbar_wait(fullB + 8 * rb.idx, rb.phase);
        if (tid == 0) TRACE(84 + k);
        if (k == 0) TSTAMP(10);
        const uint32_t a0 = sb16 + ((OFF_A + ra.idx * SLOT_A + wg * 8192) >> 4);
        const uint32_t b0 = sb16 + ((OFF_B + rb.idx * SLOT_B + (k & 1) * 24576) >> 4);
        wg_fence();
#pragma unroll
        for (int kk = 0; kk < 4; kk++) {
          mma_ss192(acc, make_desc(a0, kk * 32, 16, 1024, 1), make_desc(b0, kk * 2048, 8192, 1024, 1));
          if (kk == 0) {
            wg_commit();
            if (k > 0) {
              wg_wait<1>();
              release(emptyA + 8 * pa);
              if ((k & 1) == 0) releaseB(emptyB + 8 * pb);
            }
          }
        }
        wg_commit();
        pa = ra.idx; pb = rb.idx;
        ra.next<NA>();
        if (k & 1) rb.next<NB>();
      }
      float rs[2], mm[2];
      mbar_wait(bars + 8 * B_ST1, 0);
#pragma unroll
      for (int r = 0; r < 2; r++) {
        const uint4 su = lds128(sb + OFF_MISC + (rloc + 8 * r) * 64 + t * 16);
        const float m0 = __uint_as_float(su.x), m1 = __uint_as_float(su.z);
        float mu = m0 + m1;
        mu += __shfl_xor_sync(0xffffffffu, mu, 1); mu += __shfl_xor_sync(0xffffffffu, mu, 2);
        mu *= 0.125f;
        const float d0 = m0 - mu, d1 = m1 - mu;
        float q = __uint_as_float(su.y) + __uint_as_float(su.w) + 80.f * (d0 * d0 + d1 * d1);
        q += __shfl_xor_sync(0xffffffffu, q, 1); q += __shfl_xor_sync(0xffffffffu, q, 2);
        rs[r] = rsqrtf(q * (1.f / D_) + 1e-5f);
        mm[r] = -mu * rs[r];
      }
      wg_wait<0>();
      fence_regs(acc);
      releaseB(emptyB + 8 * pb);
      release(bars + 8 * B_PEER);
      TSTAMP(11);
      const float hs0 = 0.5f - 0.5f * st_g[0], hs1 = 0.5f - 0.5f * st_g[1];
#pragma unroll
      for (int g = 0; g < 24; g++) {
        const float2 cs = *reinterpret_cast<const float2*>(s_cs + 80 + 8 * g + 2 * t);
        const float v0 = gelu_s(fmaf(acc[4 * g], rs[0], mm[0] * cs.x), hs0), v1 = gelu_s(fmaf(acc[4 * g + 1], rs[0], mm[0] * cs.y), hs0);
        const float v2 = gelu_s(fmaf(acc[4 * g + 2], rs[1], mm[1] * cs.x), hs1), v3 = gelu_s(fmaf(acc[4 * g + 3], rs[1], mm[1] * cs.y), hs1);
        hf[g >> 1][(g & 1) * 2] = pack_bf16(v0, v1);
        hf[g >> 1][(g & 1) * 2 + 1] = pack_bf16(v2, v3);
      }
    }
    TSTAMP(12);

    {
      float acc[80], kp[40];
      uint32_t sn[20], kb[20];
      const uint32_t peer = map_peer(sb, rank ^ 1);
      Ring r4{0, 0};
      auto add8 = [&](int q, const uint4 v) {
        float* d = &kp[8 * q];
        d[0] += bf_lo(v.x); d[1] += bf_hi(v.x); d[2] += bf_lo(v.y); d[3] += bf_hi(v.y);
        d[4] += bf_lo(v.z); d[5] += bf_hi(v.z); d[6] += bf_lo(v.w); d[7] += bf_hi(v.w);
      };
      auto send = [&](int c) {
        const uint32_t dso = peer + OFF_DS + (c & 1) * 20480 + tid * 16, dsb = peer + OFF_BAR + 8 * (B_DSR + 2 * c + wg);
#pragma unroll
        for (int q = 0; q < 5; q++) st_async16(dso + q * 4096, sn[4 * q], sn[4 * q + 1], sn[4 * q + 2], sn[4 * q + 3], dsb);
      };
      auto finish = [&](int c) {
        mbar_wait(bars + 8 * (B_DSR + 2 * c + wg), 0);
        uint4* dst = g_part + (size_t)((i * 8 + ((j + 2 * c + 2) & 7)) * 3 + c) * 1280 + tid;
#pragma unroll
        for (int q = 0; q < 5; q++) {
          const uint4 v = lds128(sb + OFF_DS + (c & 1) * 20480 + tid * 16 + q * 4096);
          st_relaxed16(dst + q * 256, max(add_bf2(v.x, kb[4 * q]), 1u), max(add_bf2(v.y, kb[4 * q + 1]), 1u),
                       max(add_bf2(v.z, kb[4 * q + 2]), 1u), max(add_bf2(v.w, kb[4 * q + 3]), 1u));
        }
      };
#pragma unroll
      for (int e = 0; e < 20; e++) sn[e] = kb[e] = 0u;
      auto chunk = [&](const int c, auto last_c) {
        constexpr bool LAST = decltype(last_c)::value;
        const uint32_t e0 = r4.idx;
        auto rel = [&](int u) { const uint32_t e = e0 + u; releaseB(bars + 8 * (B_EMPTY4 + (e >= NU4 ? e - NU4 : e))); };
#pragma unroll
        for (int u = 0; u < 4; u++) {
          mbar_wait(bars + 8 * (B_FULL4 + r4.idx), r4.phase);
          const uint32_t b0 = sb16 + ((OFF_B + r4.idx * UNIT4) >> 4);
          TRS(c * 16 + u * 3);
          wg_fence();
#pragma unroll
          for (int s = 0; s < (u < 3 ? 4 : 5); s++) {
            const uint64_t db = make_desc(b0, s * 1024, u < 3 ? 4096 : 5120, 512, 2);
            if (u == 0 && s == 0) mma_rs160_n_z(acc, hf[0], db);
            else if (u < 3) mma_rs160_n(acc, hf[(4 * u + s) % 12], db);
            else mma_rs160_n(acc, of[s], db);
          }
          wg_commit();
          TRS(c * 16 + u * 3 + 1);
          r4.next<NU4>();
          if (u > 0 && !LAST) { wg_wait<1>(); rel(u - 1); }
          if (u == 0 && c > 0) send(c - 1);
          if (u == 1 && c == 0) { if (wg == 0) bar_arrive(2, 256); mbar_wait(bars + 8 * B_PEER, 0); }
          if (u == (LAST ? 1 : 2) && c > 0) finish(c - 1);
          TRS(c * 16 + u * 3 + 2);
        }
        if (LAST) {
          const float w0 = 1.f - st_g[0], w1s = 1.f - st_g[1];
#pragma unroll
          for (int g = 0; g < 10; g++) {
            kp[4 * g] = w0 * bf_lo(xv[0][g]); kp[4 * g + 1] = w0 * bf_hi(xv[0][g]);
            kp[4 * g + 2] = w1s * bf_lo(xv[1][g]); kp[4 * g + 3] = w1s * bf_hi(xv[1][g]);
          }
        }
        wg_wait<0>();
        fence_regs(acc);
        if (!LAST) rel(3);
        TRS(c * 16 + 12);
        if (rank) {
#pragma unroll
          for (int e = 0; e < 20; e++) { sn[e] = pack_bf16(acc[2 * e], acc[2 * e + 1]); kb[e] = pack_bf16(acc[40 + 2 * e], acc[41 + 2 * e]); }
        } else {
#pragma unroll
          for (int e = 0; e < 20; e++) { kb[e] = pack_bf16(acc[2 * e], acc[2 * e + 1]); sn[e] = pack_bf16(acc[40 + 2 * e], acc[41 + 2 * e]); }
        }
#pragma unroll
        for (int e = 0; e < 20; e++) asm volatile("" : "+r"(sn[e]), "+r"(kb[e]));
        TRS(c * 16 + 13);
      };
      if (wg == 1) bar_sync(2, 256);
#pragma unroll 1
      for (int c = 0; c < 3; c++) chunk(c, BoolC<false>{});
      chunk(3, BoolC<true>{});
      uint4* gp = g_part + (size_t)(i * 8 + j) * 3840 + tid;
      uint4 pv4[15];
#pragma unroll
      for (int q = 0; q < 15; q++) pv4[q] = ld_relaxed16(gp + q * 256);
      send(3);
      TSTAMP(13);
#pragma unroll
      for (int e = 0; e < 40; e++) kp[e] += rank ? acc[40 + e] : acc[e];
      mbar_wait(bars + 8 * (B_DSR + 6 + wg), 0);
#pragma unroll
      for (int q = 0; q < 5; q++) add8(q, lds128(sb + OFF_DS + 20480 + tid * 16 + q * 4096));
#pragma unroll 1
      for (uint32_t n = 0; n < (WAIT_LIMIT >> 4); n++) {
        uint32_t m = 0xffffffffu;
#pragma unroll
        for (int q = 0; q < 15; q++) m = min(min(min(m, pv4[q].x), min(pv4[q].y, pv4[q].z)), pv4[q].w);
        if (m != 0u) break;
#pragma unroll
        for (int q = 0; q < 15; q++) pv4[q] = ld_relaxed16(gp + q * 256);
      }
      TSTAMP(14);
#pragma unroll
      for (int q = 0; q < 15; q++) add8(q % 5, pv4[q]);
      __syncwarp();
#pragma unroll
      for (int s = 0; s < 5; s++)
        stsm4(sb + OFF_OUT + stg_lane + s * 32, pack_bf16(kp[8 * s], kp[8 * s + 1]), pack_bf16(kp[8 * s + 2], kp[8 * s + 3]),
              pack_bf16(kp[8 * s + 4], kp[8 * s + 5]), pack_bf16(kp[8 * s + 6], kp[8 * s + 7]));
      fence_async_smem();
      __syncwarp();
      if (lane == 0) {
        tma2d_store(&maps.st_out, sb + OFF_OUT + warp * 2560, 80 * j, 128 * i + 16 * warp);
        bulk_commit();
      }
#pragma unroll
      for (int q = 0; q < 15; q++) st_relaxed16(gp + q * 256, 0u, 0u, 0u, 0u);
      if (lane == 0) bulk_wait_read();
    }
    TSTAMP(15);
    if (tid == 0) asm volatile("red.relaxed.gpu.global.add.u32 [%0], 1;" ::"l"(g_flags + FL_DONE * 32) : "memory");
  }
}

namespace {
typedef CUresult (*EncodeFn)(CUtensorMap*, CUtensorMapDataType, cuuint32_t, void*, const cuuint64_t*, const cuuint64_t*,
                             const cuuint32_t*, const cuuint32_t*, CUtensorMapInterleave, CUtensorMapSwizzle,
                             CUtensorMapL2promotion, CUtensorMapFloatOOBfill);

void encode(EncodeFn fn, CUtensorMap* m, const void* ptr, int rank, const cuuint64_t* dims, const cuuint64_t* strides,
            const cuuint32_t* box, CUtensorMapSwizzle swz) {
  cuuint32_t es[5] = {1, 1, 1, 1, 1};
  fn(m, CU_TENSOR_MAP_DATA_TYPE_BFLOAT16, rank, const_cast<void*>(ptr), dims, strides, box, es, CU_TENSOR_MAP_INTERLEAVE_NONE,
     swz, CU_TENSOR_MAP_L2_PROMOTION_L2_128B, CU_TENSOR_MAP_FLOAT_OOB_FILL_NONE);
}
}

extern "C" void kernel_launch(void* const* d_in, const int* in_sizes, int n_in, void* d_out, int out_size) {
  (void)in_sizes; (void)n_in; (void)out_size;
  const __nv_bfloat16* x = (const __nv_bfloat16*)d_in[0];
  const __nv_bfloat16* wqkv = (const __nv_bfloat16*)d_in[1];
  const __nv_bfloat16* wphi = (const __nv_bfloat16*)d_in[2];
  const __nv_bfloat16* wo = (const __nv_bfloat16*)d_in[3];
  const __nv_bfloat16* w1 = (const __nv_bfloat16*)d_in[5];
  const __nv_bfloat16* w2 = (const __nv_bfloat16*)d_in[6];
  const __nv_bfloat16* w3 = (const __nv_bfloat16*)d_in[7];
  const __nv_bfloat16* w4 = (const __nv_bfloat16*)d_in[8];
  const __nv_bfloat16* gate_w = (const __nv_bfloat16*)d_in[9];

  static EncodeFn enc = nullptr;
  static void *pHs = nullptr, *pX1 = nullptr;
  if (!enc) {
    cudaDriverEntryPointQueryResult qr;
    cudaGetDriverEntryPoint("cuTensorMapEncodeTiled", (void**)&enc, cudaEnableDefault, &qr);
    cudaGetSymbolAddress(&pHs, g_Hs);
    cudaGetSymbolAddress(&pX1, g_X1);
    cudaFuncSetAttribute(fused_kernel, cudaFuncAttributeMaxDynamicSharedMemorySize, SMEM_BYTES);
  }
  Maps m;
  {
    cuuint64_t dims[2] = {D_, S_}, str[1] = {D_ * 2};
    cuuint32_t boxh[2] = {64, 64};
    encode(enc, &m.x, x, 2, dims, str, boxh, CU_TENSOR_MAP_SWIZZLE_128B);
    encode(enc, &m.hs, (const char*)pHs + 2 * D_ * 2, 2, dims, str, boxh, CU_TENSOR_MAP_SWIZZLE_128B);
    encode(enc, &m.x1, pX1, 2, dims, str, boxh, CU_TENSOR_MAP_SWIZZLE_128B);
    cuuint32_t boxs[2] = {80, 64};
    cuuint64_t dimsp[2] = {D_, S_ + 4};
    encode(enc, &m.st_h, pHs, 2, dimsp, str, boxs, CU_TENSOR_MAP_SWIZZLE_NONE);
    encode(enc, &m.st_x1, pX1, 2, dims, str, boxs, CU_TENSOR_MAP_SWIZZLE_NONE);
    cuuint32_t boxr[2] = {80, 16};
    encode(enc, &m.st_out, d_out, 2, dims, str, boxr, CU_TENSOR_MAP_SWIZZLE_NONE);
    encode(enc, &m.xr, x, 2, dims, str, boxr, CU_TENSOR_MAP_SWIZZLE_NONE);
  }
  {
    cuuint64_t dims[3] = {80, D_, 8}, str[2] = {D_ * 2, 160};
    cuuint32_t boxm[3] = {64, 64, 1}, boxr[3] = {16, 64, 1};
    encode(enc, &m.w1m, w1, 3, dims, str, boxm, CU_TENSOR_MAP_SWIZZLE_128B);
    encode(enc, &m.w1r, w1, 3, dims, str, boxr, CU_TENSOR_MAP_SWIZZLE_32B);
  }
  {
    cuuint64_t dims[4] = {80, D_, 3, 8}, str[3] = {3 * D_ * 2, D_ * 2, 160};
    cuuint32_t boxm[4] = {64, 64, 3, 1}, boxr[4] = {16, 64, 3, 1};
    encode(enc, &m.qm, wqkv, 4, dims, str, boxm, CU_TENSOR_MAP_SWIZZLE_128B);
    encode(enc, &m.qr, wqkv, 4, dims, str, boxr, CU_TENSOR_MAP_SWIZZLE_32B);
  }
  {
    cuuint64_t dims[3] = {16, D_, 40}, str[2] = {D_ * 2, 32};
    cuuint32_t box2[3] = {16, 64, 5};
    encode(enc, &m.w2, w2, 3, dims, str, box2, CU_TENSOR_MAP_SWIZZLE_32B);
  }
  {
    cuuint64_t dims[3] = {32, D_, 20}, dims4[3] = {32, F_, 20}, str[2] = {D_ * 2, 64};
    cuuint32_t box4[3] = {32, 64, 5}, boxo[3] = {32, 80, 5};
    encode(enc, &m.w4, w4, 3, dims4, str, box4, CU_TENSOR_MAP_SWIZZLE_64B);
    encode(enc, &m.wo, wo, 3, dims, str, boxo, CU_TENSOR_MAP_SWIZZLE_64B);
  }
  {
    cuuint64_t dims[3] = {64, D_, 24}, str[2] = {F_ * 2, 128};
    cuuint32_t box[3] = {64, 64, 3};
    encode(enc, &m.w3, w3, 3, dims, str, box, CU_TENSOR_MAP_SWIZZLE_128B);
  }
  fused_kernel<<<NCTA, 384, SMEM_BYTES, cudaStreamPerThread>>>(m, x, wqkv, wphi, w1, w2, w3, w4, wo, gate_w);
}
```

```cpp
#include <cuda_runtime.h>
#include <cuda_bf16.h>
#include <cuda.h>
#include <stdint.h>

namespace {

constexpr int S_ = 2048, D_ = 640, F_ = 1536;
constexpr int NCTA = 128;
constexpr int KV_PAIR = 40 * 48 + 96;
constexpr int KV_J = 2 * KV_PAIR;

constexpr int SLOT_B = 49152, NB = 3;
constexpr int SLOT_A = 16384, NA = 4;
constexpr int OFF_B = 0;
constexpr int OFF_A = OFF_B + NB * SLOT_B;
constexpr int OFF_STG = OFF_A + 2 * SLOT_A;
constexpr int OFF_MISC = OFF_A + NA * SLOT_A;
constexpr int OFF_XST = OFF_MISC + 13312;
constexpr int OFF_CS = OFF_MISC + 16384;
constexpr int OFF_BAR = OFF_CS + 1088;
constexpr int SMEM_BYTES = OFF_BAR + 512 + 512;
constexpr int B_FULLA = 0, B_FULLB = 4, B_CS = 7, B_XR = 8, B_KV = 9, B_ST1 = 10, B_FULL4 = 11  , B_DSR = 16  ,
              B_EMPTYB = 24  , B_SIGP = 27, B_SIGH = 28, B_SIGKV = 29, B_SIGX1 = 30, B_MFREE = 31, B_EMPTY4 = 32  ,
              B_EMPTYA = 37  , B_PEER = 41, NBAR = 42;
constexpr int SPARE = 40960;
constexpr int UNIT4 = 25600, NU4 = 5;
constexpr int OFF_DS = OFF_A, OFF_OUT = OFF_A + 40960;

constexpr int FL_DONE = 0, FL_H = 1, FL_X1 = FL_H + 16, FL_KV = FL_X1 + 16, FL_CS = FL_KV + 8, FL_CS3 = FL_CS + 8, FL_ST = FL_CS3 + 8;
constexpr int FL_COUNT = FL_ST + 16;
constexpr int ACC_FLOATS = 8 * KV_J + D_ + F_;

struct Maps {
  CUtensorMap x, w1m, w1r, qm, qr, hs, w2, x1, w3, w4, wo, st_h, st_x1, st_out, xr;
};

}

__device__ __align__(1024) __nv_bfloat16 g_Hs[(S_ + 4) * D_];
__device__ __align__(1024) __nv_bfloat16 g_X1[S_ * D_];
__device__ __align__(128) float g_acc[2][ACC_FLOATS];
__device__ __align__(128) float4 g_xstat[S_];
__device__ __align__(128) float2 g_st1[S_ * 8];
__device__ __align__(128) uint4 g_part[16 * 8 * 3 * 1280];
__device__ __align__(128) unsigned g_flags[FL_COUNT * 32];
#define TSTAMP(n) do {} while (0)
#define TSTAMPX(n) do {} while (0)
#define TRACE(n) do {} while (0)
#define TRS(n) do {} while (0)

namespace {

__device__ __forceinline__ long long gtime() { long long t; asm volatile("mov.u64 %0, %%globaltimer;" : "=l"(t)); return t; }
__device__ __forceinline__ uint32_t smem_u32(const void* p) { return (uint32_t)__cvta_generic_to_shared(p); }
__device__ __forceinline__ void mbar_init(uint32_t bar, int cnt) {
  asm volatile("mbarrier.init.shared::cta.b64 [%0], %1;" ::"r"(bar), "r"(cnt) : "memory");
}
__device__ __forceinline__ void mbar_expect_tx(uint32_t bar, int bytes) {
  asm volatile("mbarrier.arrive.expect_tx.shared::cta.b64 _, [%0], %1;" ::"r"(bar), "r"(bytes) : "memory");
}
__device__ __forceinline__ void mbar_arrive_cta(uint32_t bar, uint32_t cta) {
  asm volatile("{\n.reg .b32 ra;\nmapa.shared::cluster.u32 ra, %0, %1;\nmbarrier.arrive.shared::cluster.b64 _, [ra];\n}"
               ::"r"(bar), "r"(cta) : "memory");
}
__device__ __forceinline__ uint32_t mbar_try(uint32_t bar, uint32_t parity) {
  uint32_t ok;
  asm volatile("{\n.reg .pred p;\nmbarrier.try_wait.parity.shared::cta.b64 p, [%1], %2;\nselp.u32 %0, 1, 0, p;\n}"
               : "=r"(ok) : "r"(bar), "r"(parity) : "memory");
  return ok;
}
constexpr uint32_t WAIT_LIMIT = 1u << 22;
__device__ __forceinline__ void mbar_wait(uint32_t bar, uint32_t parity) {
  uint32_t n = 0;
  while (!mbar_try(bar, parity) && ++n < WAIT_LIMIT) {}
}
__device__ __forceinline__ unsigned ld_acquire(const unsigned* p) {
  unsigned v;
  asm volatile("ld.acquire.gpu.global.u32 %0, [%1];" : "=r"(v) : "l"(p) : "memory");
  return v;
}
__device__ __forceinline__ void flag_wait(int idx, unsigned target) {
  const unsigned* p = g_flags + idx * 32;
  uint32_t n = 0;
  while ((int)(ld_acquire(p) - target) < 0 && ++n < (WAIT_LIMIT >> 4)) {}
}
__device__ __forceinline__ void flag_add(int idx) {
  asm volatile("red.release.gpu.global.add.u32 [%0], 1;" ::"l"(g_flags + idx * 32) : "memory");
}
__device__ __forceinline__ void flag_add_relaxed(int idx) {
  asm volatile("red.relaxed.gpu.global.add.u32 [%0], 1;" ::"l"(g_flags + idx * 32) : "memory");
}
__device__ __forceinline__ uint32_t mbar_test(uint32_t bar, uint32_t parity) {
  uint32_t ok;
  asm volatile("{\n.reg .pred p;\nmbarrier.test_wait.parity.shared::cta.b64 p, [%1], %2;\nselp.u32 %0, 1, 0, p;\n}"
               : "=r"(ok) : "r"(bar), "r"(parity) : "memory");
  return ok;
}
__device__ __forceinline__ uint32_t lds32(uint32_t a) {
  uint32_t v;
  asm volatile("ld.shared.u32 %0, [%1];" : "=r"(v) : "r"(a) : "memory");
  return v;
}
__device__ __forceinline__ void mbar_arrive(uint32_t bar) {
  asm volatile("mbarrier.arrive.shared::cta.b64 _, [%0];" ::"r"(bar) : "memory");
}
__device__ __forceinline__ void fence_async_glb() { asm volatile("fence.proxy.async.global;" ::: "memory"); }
__device__ __forceinline__ void fence_async_smem() { asm volatile("fence.proxy.async.shared::cta;" ::: "memory"); }
__device__ __forceinline__ void bar_sync(int id, int n) { asm volatile("bar.sync %0, %1;" ::"r"(id), "r"(n) : "memory"); }

__device__ __forceinline__ void tma2d(uint32_t dst, const CUtensorMap* m, uint32_t bar, int c0, int c1) {
  asm volatile("cp.async.bulk.tensor.2d.shared::cluster.global.mbarrier::complete_tx::bytes [%0], [%1, {%3, %4}], [%2];"
               ::"r"(dst), "l"(m), "r"(bar), "r"(c0), "r"(c1) : "memory");
}
__device__ __forceinline__ void tma2d_mc(uint32_t dst, const CUtensorMap* m, uint32_t bar, int c0, int c1) {
  asm volatile("cp.async.bulk.tensor.2d.shared::cluster.global.mbarrier::complete_tx::bytes.multicast::cluster"
               " [%0], [%1, {%3, %4}], [%2], %5;"
               ::"r"(dst), "l"(m), "r"(bar), "r"(c0), "r"(c1), "h"((uint16_t)3) : "memory");
}
__device__ __forceinline__ void tma3d(uint32_t dst, const CUtensorMap* m, uint32_t bar, int c0, int c1, int c2) {
  asm volatile("cp.async.bulk.tensor.3d.shared::cluster.global.mbarrier::complete_tx::bytes [%0], [%1, {%3, %4, %5}], [%2];"
               ::"r"(dst), "l"(m), "r"(bar), "r"(c0), "r"(c1), "r"(c2) : "memory");
}
__device__ __forceinline__ void tma4d(uint32_t dst, const CUtensorMap* m, uint32_t bar, int c0, int c1, int c2, int c3) {
  asm volatile("cp.async.bulk.tensor.4d.shared::cluster.global.mbarrier::complete_tx::bytes [%0], [%1, {%3, %4, %5, %6}], [%2];"
               ::"r"(dst), "l"(m), "r"(bar), "r"(c0), "r"(c1), "r"(c2), "r"(c3) : "memory");
}
__device__ __forceinline__ void tma2d_store(const CUtensorMap* m, uint32_t src, int c0, int c1) {
  asm volatile("cp.async.bulk.tensor.2d.global.shared::cta.bulk_group [%0, {%2, %3}], [%1];"
               ::"l"(m), "r"(src), "r"(c0), "r"(c1) : "memory");
}
__device__ __forceinline__ void bulk_store(void* dst, uint32_t src, uint32_t bytes) {
  asm volatile("cp.async.bulk.global.shared::cta.bulk_group [%0], [%1], %2;" ::"l"(dst), "r"(src), "r"(bytes) : "memory");
}
__device__ __forceinline__ void bulk_load(uint32_t dst, const void* src, uint32_t bytes, uint32_t bar) {
  asm volatile("cp.async.bulk.shared::cluster.global.mbarrier::complete_tx::bytes [%0], [%1], %2, [%3];"
               ::"r"(dst), "l"(src), "r"(bytes), "r"(bar) : "memory");
}
__device__ __forceinline__ void bulk_commit() { asm volatile("cp.async.bulk.commit_group;" ::: "memory"); }
template <int N> __device__ __forceinline__ void bulk_wait() { asm volatile("cp.async.bulk.wait_group %0;" ::"n"(N) : "memory"); }
__device__ __forceinline__ void bulk_wait_read() { asm volatile("cp.async.bulk.wait_group.read 0;" ::: "memory"); }
__device__ __forceinline__ void bar_arrive(int id, int n) { asm volatile("bar.arrive %0, %1;" ::"r"(id), "r"(n) : "memory"); }
__device__ __forceinline__ uint4 lds128(uint32_t a) {
  uint4 v;
  asm volatile("ld.shared.v4.u32 {%0, %1, %2, %3}, [%4];" : "=r"(v.x), "=r"(v.y), "=r"(v.z), "=r"(v.w) : "r"(a) : "memory");
  return v;
}
__device__ __forceinline__ void sts128(uint32_t a, uint4 v) {
  asm volatile("st.shared.v4.u32 [%0], {%1, %2, %3, %4};" ::"r"(a), "r"(v.x), "r"(v.y), "r"(v.z), "r"(v.w) : "memory");
}
__device__ __forceinline__ uint4 ld_relaxed16(const uint4* p) {
  uint4 v;
  asm volatile("ld.relaxed.gpu.global.v4.u32 {%0, %1, %2, %3}, [%4];" : "=r"(v.x), "=r"(v.y), "=r"(v.z), "=r"(v.w) : "l"(p) : "memory");
  return v;
}
__device__ __forceinline__ void st_relaxed16(uint4* p, uint32_t a, uint32_t b, uint32_t c, uint32_t d) {
  asm volatile("st.relaxed.gpu.global.v4.u32 [%0], {%1, %2, %3, %4};" ::"l"(p), "r"(a), "r"(b), "r"(c), "r"(d) : "memory");
}
__device__ __forceinline__ uint32_t map_peer(uint32_t addr, uint32_t cta) {
  uint32_t r;
  asm("mapa.shared::cluster.u32 %0, %1, %2;" : "=r"(r) : "r"(addr), "r"(cta));
  return r;
}
__device__ __forceinline__ void st_async16(uint32_t addr, uint32_t a, uint32_t b, uint32_t c, uint32_t d, uint32_t bar) {
  asm volatile("st.async.weak.shared::cluster.mbarrier::complete_tx::bytes.v4.b32 [%0], {%1, %2, %3, %4}, [%5];"
               ::"r"(addr), "r"(a), "r"(b), "r"(c), "r"(d), "r"(bar) : "memory");
}
__device__ __forceinline__ void l2_prefetch(const void* p, uint32_t bytes) {
  asm volatile("cp.async.bulk.prefetch.L2.global [%0], %1;" ::"l"(p), "r"(bytes) : "memory");
}
__device__ __forceinline__ void prefetch_tmap(const CUtensorMap* m) {
  asm volatile("prefetch.tensormap [%0];" ::"l"(m) : "memory");
}
__device__ __forceinline__ uint64_t make_desc(uint32_t a16, uint32_t off, uint32_t lbo, uint32_t sbo, uint32_t swz) {
  const uint32_t lo = a16 + ((off >> 4) + ((lbo >> 4) << 16)), hi = (sbo >> 4) | (swz << 30);
  uint64_t d;
  asm("mov.b64 %0, {%1, %2};" : "=l"(d) : "r"(lo), "r"(hi));
  return d;
}
__device__ __forceinline__ void wg_fence() { asm volatile("wgmma.fence.sync.aligned;" ::: "memory"); }
__device__ __forceinline__ void wg_commit() { asm volatile("wgmma.commit_group.sync.aligned;" ::: "memory"); }
template <int N> __device__ __forceinline__ void wg_wait() { asm volatile("wgmma.wait_group.sync.aligned %0;" ::"n"(N) : "memory"); }
template <int N> __device__ __forceinline__ void fence_regs(float (&d)[N]) {
#pragma unroll
  for (int i = 0; i < N; i++) asm volatile("" : "+f"(d[i])::"memory");
}
template <int N> __device__ __forceinline__ void zero_regs(float (&d)[N]) {
#pragma unroll
  for (int i = 0; i < N; i++) d[i] = 0.f;
}
__device__ __forceinline__ uint32_t pack_bf16(float lo, float hi) {
  uint32_t r;
  asm("cvt.rn.bf16x2.f32 %0, %1, %2;" : "=r"(r) : "f"(hi), "f"(lo));
  return r;
}
__device__ __forceinline__ float bf_lo(uint32_t v) { return __uint_as_float(v << 16); }
__device__ __forceinline__ float bf_hi(uint32_t v) { return __uint_as_float(v & 0xffff0000u); }
__device__ __forceinline__ uint32_t max_bf2(uint32_t a, uint32_t b) {
  uint32_t r; asm("max.bf16x2 %0, %1, %2;" : "=r"(r) : "r"(a), "r"(b)); return r;
}
__device__ __forceinline__ uint32_t min_bf2(uint32_t a, uint32_t b) {
  uint32_t r; asm("min.bf16x2 %0, %1, %2;" : "=r"(r) : "r"(a), "r"(b)); return r;
}
__device__ __forceinline__ uint32_t add_bf2(uint32_t a, uint32_t b) {
  uint32_t r; asm("add.rn.bf16x2 %0, %1, %2;" : "=r"(r) : "r"(a), "r"(b)); return r;
}
__device__ __forceinline__ float ex2(float x) { float r; asm("ex2.approx.ftz.f32 %0, %1;" : "=f"(r) : "f"(x)); return r; }
__device__ __forceinline__ float rcp(float x) { float r; asm("rcp.approx.ftz.f32 %0, %1;" : "=f"(r) : "f"(x)); return r; }
__device__ __forceinline__ float tanh_ap(float x) { float r; asm("tanh.approx.f32 %0, %1;" : "=f"(r) : "f"(x)); return r; }
__device__ __forceinline__ float gelu_s(float x, float hs) {
  float u = x * fmaf(x * x, 0.0356774081f, 0.7978845608f);
  float hx = x * hs;
  return fmaf(hx, tanh_ap(u), hx);
}
__device__ __forceinline__ void stsm4(uint32_t addr, uint32_t r0, uint32_t r1, uint32_t r2, uint32_t r3) {
  asm volatile("stmatrix.sync.aligned.m8n8.x4.shared.b16 [%0], {%1, %2, %3, %4};"
               ::"r"(addr), "r"(r0), "r"(r1), "r"(r2), "r"(r3) : "memory");
}
__device__ __forceinline__ void red_add4(float* p, float a, float b, float c, float d) {
  asm volatile("red.global.add.v4.f32 [%0], {%1, %2, %3, %4};" ::"l"(p), "f"(a), "f"(b), "f"(c), "f"(d) : "memory");
}

__device__ __forceinline__ void mma_ss256(float (&d)[128], uint64_t descA, uint64_t descB) {
  asm volatile("wgmma.mma_async.sync.aligned.m64n256k16.f32.bf16.bf16 {"
      "%0, %1, %2, %3, %4, %5, %6, %7, %8, %9, %10, %11, %12, %13, %14, %15, "
      "%16, %17, %18, %19, %20, %21, %22, %23, %24, %25, %26, %27, %28, %29, %30, %31, "
      "%32, %33, %34, %35, %36, %37, %38, %39, %40, %41, %42, %43, %44, %45, %46, %47, "
      "%48, %49, %50, %51, %52, %53, %54, %55, %56, %57, %58, %59, %60, %61, %62, %63, "
      "%64, %65, %66, %67, %68, %69, %70, %71, %72, %73, %74, %75, %76, %77, %78, %79, "
      "%80, %81, %82, %83, %84, %85, %86, %87, %88, %89, %90, %91, %92, %93, %94, %95, "
      "%96, %97, %98, %99, %100, %101, %102, %103, %104, %105, %106, %107, %108, %109, %110, %111, "
      "%112, %113, %114, %115, %116, %117, %118, %119, %120, %121, %122, %123, %124, %125, %126, %127"
      "}, %128, %129, 1, 1, 1, 0, 1;\n"
      : "+f"(d[0]), "+f"(d[1]), "+f"(d[2]), "+f"(d[3]), "+f"(d[4]), "+f"(d[5]), "+f"(d[6]), "+f"(d[7]),
        "+f"(d[8]), "+f"(d[9]), "+f"(d[10]), "+f"(d[11]), "+f"(d[12]), "+f"(d[13]), "+f"(d[14]), "+f"(d[15]),
        "+f"(d[16]), "+f"(d[17]), "+f"(d[18]), "+f"(d[19]), "+f"(d[20]), "+f"(d[21]), "+f"(d[22]), "+f"(d[23]),
        "+f"(d[24]), "+f"(d[25]), "+f"(d[26]), "+f"(d[27]), "+f"(d[28]), "+f"(d[29]), "+f"(d[30]), "+f"(d[31]),
        "+f"(d[32]), "+f"(d[33]), "+f"(d[34]), "+f"(d[35]), "+f"(d[36]), "+f"(d[37]), "+f"(d[38]), "+f"(d[39]),
        "+f"(d[40]), "+f"(d[41]), "+f"(d[42]), "+f"(d[43]), "+f"(d[44]), "+f"(d[45]), "+f"(d[46]), "+f"(d[47]),
        "+f"(d[48]), "+f"(d[49]), "+f"(d[50]), "+f"(d[51]), "+f"(d[52]), "+f"(d[53]), "+f"(d[54]), "+f"(d[55]),
        "+f"(d[56]), "+f"(d[57]), "+f"(d[58]), "+f"(d[59]), "+f"(d[60]), "+f"(d[61]), "+f"(d[62]), "+f"(d[63]),
        "+f"(d[64]), "+f"(d[65]), "+f"(d[66]), "+f"(d[67]), "+f"(d[68]), "+f"(d[69]), "+f"(d[70]), "+f"(d[71]),
        "+f"(d[72]), "+f"(d[73]), "+f"(d[74]), "+f"(d[75]), "+f"(d[76]), "+f"(d[77]), "+f"(d[78]), "+f"(d[79]),
        "+f"(d[80]), "+f"(d[81]), "+f"(d[82]), "+f"(d[83]), "+f"(d[84]), "+f"(d[85]), "+f"(d[86]), "+f"(d[87]),
        "+f"(d[88]), "+f"(d[89]), "+f"(d[90]), "+f"(d[91]), "+f"(d[92]), "+f"(d[93]), "+f"(d[94]), "+f"(d[95]),
        "+f"(d[96]), "+f"(d[97]), "+f"(d[98]), "+f"(d[99]), "+f"(d[100]), "+f"(d[101]), "+f"(d[102]), "+f"(d[103]),
        "+f"(d[104]), "+f"(d[105]), "+f"(d[106]), "+f"(d[107]), "+f"(d[108]), "+f"(d[109]), "+f"(d[110]), "+f"(d[111]),
        "+f"(d[112]), "+f"(d[113]), "+f"(d[114]), "+f"(d[115]), "+f"(d[116]), "+f"(d[117]), "+f"(d[118]), "+f"(d[119]),
        "+f"(d[120]), "+f"(d[121]), "+f"(d[122]), "+f"(d[123]), "+f"(d[124]), "+f"(d[125]), "+f"(d[126]), "+f"(d[127])
      : "l"(descA), "l"(descB));
}

__device__ __forceinline__ void mma_ss64(float (&d)[32], uint64_t descA, uint64_t descB) {
  asm volatile("wgmma.mma_async.sync.aligned.m64n64k16.f32.bf16.bf16 {"
      "%0, %1, %2, %3, %4, %5, %6, %7, %8, %9, %10, %11, %12, %13, %14, %15, "
      "%16, %17, %18, %19, %20, %21, %22, %23, %24, %25, %26, %27, %28, %29, %30, %31"
      "}, %32, %33, 1, 1, 1, 0, 1;\n"
      : "+f"(d[0]), "+f"(d[1]), "+f"(d[2]), "+f"(d[3]), "+f"(d[4]), "+f"(d[5]), "+f"(d[6]), "+f"(d[7]),
        "+f"(d[8]), "+f"(d[9]), "+f"(d[10]), "+f"(d[11]), "+f"(d[12]), "+f"(d[13]), "+f"(d[14]), "+f"(d[15]),
        "+f"(d[16]), "+f"(d[17]), "+f"(d[18]), "+f"(d[19]), "+f"(d[20]), "+f"(d[21]), "+f"(d[22]), "+f"(d[23]),
        "+f"(d[24]), "+f"(d[25]), "+f"(d[26]), "+f"(d[27]), "+f"(d[28]), "+f"(d[29]), "+f"(d[30]), "+f"(d[31])
      : "l"(descA), "l"(descB));
}

__device__ __forceinline__ void mma_ss80(float (&d)[40], uint64_t descA, uint64_t descB) {
  asm volatile("wgmma.mma_async.sync.aligned.m64n80k16.f32.bf16.bf16 {"
      "%0, %1, %2, %3, %4, %5, %6, %7, %8, %9, %10, %11, %12, %13, %14, %15, "
      "%16, %17, %18, %19, %20, %21, %22, %23, %24, %25, %26, %27, %28, %29, %30, %31, "
      "%32, %33, %34, %35, %36, %37, %38, %39"
      "}, %40, %41, 1, 1, 1, 0, 1;\n"
      : "+f"(d[0]), "+f"(d[1]), "+f"(d[2]), "+f"(d[3]), "+f"(d[4]), "+f"(d[5]), "+f"(d[6]), "+f"(d[7]),
        "+f"(d[8]), "+f"(d[9]), "+f"(d[10]), "+f"(d[11]), "+f"(d[12]), "+f"(d[13]), "+f"(d[14]), "+f"(d[15]),
        "+f"(d[16]), "+f"(d[17]), "+f"(d[18]), "+f"(d[19]), "+f"(d[20]), "+f"(d[21]), "+f"(d[22]), "+f"(d[23]),
        "+f"(d[24]), "+f"(d[25]), "+f"(d[26]), "+f"(d[27]), "+f"(d[28]), "+f"(d[29]), "+f"(d[30]), "+f"(d[31]),
        "+f"(d[32]), "+f"(d[33]), "+f"(d[34]), "+f"(d[35]), "+f"(d[36]), "+f"(d[37]), "+f"(d[38]), "+f"(d[39])
      : "l"(descA), "l"(descB));
}

__device__ __forceinline__ void mma_ss192(float (&d)[96], uint64_t descA, uint64_t descB) {
  asm volatile("wgmma.mma_async.sync.aligned.m64n192k16.f32.bf16.bf16 {"
      "%0, %1, %2, %3, %4, %5, %6, %7, %8, %9, %10, %11, %12, %13, %14, %15, "
      "%16, %17, %18, %19, %20, %21, %22, %23, %24, %25, %26, %27, %28, %29, %30, %31, "
      "%32, %33, %34, %35, %36, %37, %38, %39, %40, %41, %42, %43, %44, %45, %46, %47, "
      "%48, %49, %50, %51, %52, %53, %54, %55, %56, %57, %58, %59, %60, %61, %62, %63, "
      "%64, %65, %66, %67, %68, %69, %70, %71, %72, %73, %74, %75, %76, %77, %78, %79, "
      "%80, %81, %82, %83, %84, %85, %86, %87, %88, %89, %90, %91, %92, %93, %94, %95"
      "}, %96, %97, 1, 1, 1, 0, 1;\n"
      : "+f"(d[0]), "+f"(d[1]), "+f"(d[2]), "+f"(d[3]), "+f"(d[4]), "+f"(d[5]), "+f"(d[6]), "+f"(d[7]),
        "+f"(d[8]), "+f"(d[9]), "+f"(d[10]), "+f"(d[11]), "+f"(d[12]), "+f"(d[13]), "+f"(d[14]), "+f"(d[15]),
        "+f"(d[16]), "+f"(d[17]), "+f"(d[18]), "+f"(d[19]), "+f"(d[20]), "+f"(d[21]), "+f"(d[22]), "+f"(d[23]),
        "+f"(d[24]), "+f"(d[25]), "+f"(d[26]), "+f"(d[27]), "+f"(d[28]), "+f"(d[29]), "+f"(d[30]), "+f"(d[31]),
        "+f"(d[32]), "+f"(d[33]), "+f"(d[34]), "+f"(d[35]), "+f"(d[36]), "+f"(d[37]), "+f"(d[38]), "+f"(d[39]),
        "+f"(d[40]), "+f"(d[41]), "+f"(d[42]), "+f"(d[43]), "+f"(d[44]), "+f"(d[45]), "+f"(d[46]), "+f"(d[47]),
        "+f"(d[48]), "+f"(d[49]), "+f"(d[50]), "+f"(d[51]), "+f"(d[52]), "+f"(d[53]), "+f"(d[54]), "+f"(d[55]),
        "+f"(d[56]), "+f"(d[57]), "+f"(d[58]), "+f"(d[59]), "+f"(d[60]), "+f"(d[61]), "+f"(d[62]), "+f"(d[63]),
        "+f"(d[64]), "+f"(d[65]), "+f"(d[66]), "+f"(d[67]), "+f"(d[68]), "+f"(d[69]), "+f"(d[70]), "+f"(d[71]),
        "+f"(d[72]), "+f"(d[73]), "+f"(d[74]), "+f"(d[75]), "+f"(d[76]), "+f"(d[77]), "+f"(d[78]), "+f"(d[79]),
        "+f"(d[80]), "+f"(d[81]), "+f"(d[82]), "+f"(d[83]), "+f"(d[84]), "+f"(d[85]), "+f"(d[86]), "+f"(d[87]),
        "+f"(d[88]), "+f"(d[89]), "+f"(d[90]), "+f"(d[91]), "+f"(d[92]), "+f"(d[93]), "+f"(d[94]), "+f"(d[95])
      : "l"(descA), "l"(descB));
}

__device__ __forceinline__ void mma_ss80_tt(float (&d)[40], uint64_t descA, uint64_t descB) {
  asm volatile("wgmma.mma_async.sync.aligned.m64n80k16.f32.bf16.bf16 {"
      "%0, %1, %2, %3, %4, %5, %6, %7, %8, %9, %10, %11, %12, %13, %14, %15, "
      "%16, %17, %18, %19, %20, %21, %22, %23, %24, %25, %26, %27, %28, %29, %30, %31, "
      "%32, %33, %34, %35, %36, %37, %38, %39"
      "}, %40, %41, 1, 1, 1, 1, 1;\n"
      : "+f"(d[0]), "+f"(d[1]), "+f"(d[2]), "+f"(d[3]), "+f"(d[4]), "+f"(d[5]), "+f"(d[6]), "+f"(d[7]),
        "+f"(d[8]), "+f"(d[9]), "+f"(d[10]), "+f"(d[11]), "+f"(d[12]), "+f"(d[13]), "+f"(d[14]), "+f"(d[15]),
        "+f"(d[16]), "+f"(d[17]), "+f"(d[18]), "+f"(d[19]), "+f"(d[20]), "+f"(d[21]), "+f"(d[22]), "+f"(d[23]),
        "+f"(d[24]), "+f"(d[25]), "+f"(d[26]), "+f"(d[27]), "+f"(d[28]), "+f"(d[29]), "+f"(d[30]), "+f"(d[31]),
        "+f"(d[32]), "+f"(d[33]), "+f"(d[34]), "+f"(d[35]), "+f"(d[36]), "+f"(d[37]), "+f"(d[38]), "+f"(d[39])
      : "l"(descA), "l"(descB));
}
__device__ __forceinline__ void mma_ss80_tt_z(float (&d)[40], uint64_t descA, uint64_t descB) {
  asm volatile("wgmma.mma_async.sync.aligned.m64n80k16.f32.bf16.bf16 {"
      "%0, %1, %2, %3, %4, %5, %6, %7, %8, %9, %10, %11, %12, %13, %14, %15, "
      "%16, %17, %18, %19, %20, %21, %22, %23, %24, %25, %26, %27, %28, %29, %30, %31, "
      "%32, %33, %34, %35, %36, %37, %38, %39"
      "}, %40, %41, 0, 1, 1, 1, 1;\n"
      : "=f"(d[0]), "=f"(d[1]), "=f"(d[2]), "=f"(d[3]), "=f"(d[4]), "=f"(d[5]), "=f"(d[6]), "=f"(d[7]),
        "=f"(d[8]), "=f"(d[9]), "=f"(d[10]), "=f"(d[11]), "=f"(d[12]), "=f"(d[13]), "=f"(d[14]), "=f"(d[15]),
        "=f"(d[16]), "=f"(d[17]), "=f"(d[18]), "=f"(d[19]), "=f"(d[20]), "=f"(d[21]), "=f"(d[22]), "=f"(d[23]),
        "=f"(d[24]), "=f"(d[25]), "=f"(d[26]), "=f"(d[27]), "=f"(d[28]), "=f"(d[29]), "=f"(d[30]), "=f"(d[31]),
        "=f"(d[32]), "=f"(d[33]), "=f"(d[34]), "=f"(d[35]), "=f"(d[36]), "=f"(d[37]), "=f"(d[38]), "=f"(d[39])
      : "l"(descA), "l"(descB));
}

__device__ __forceinline__ void mma_rs80_k(float (&d)[40], const uint32_t (&a)[4], uint64_t descB) {
  asm volatile("wgmma.mma_async.sync.aligned.m64n80k16.f32.bf16.bf16 {"
      "%0, %1, %2, %3, %4, %5, %6, %7, %8, %9, %10, %11, %12, %13, %14, %15, "
      "%16, %17, %18, %19, %20, %21, %22, %23, %24, %25, %26, %27, %28, %29, %30, %31, "
      "%32, %33, %34, %35, %36, %37, %38, %39"
      "}, {%40, %41, %42, %43}, %44, 1, 1, 1, 0;\n"
      : "+f"(d[0]), "+f"(d[1]), "+f"(d[2]), "+f"(d[3]), "+f"(d[4]), "+f"(d[5]), "+f"(d[6]), "+f"(d[7]),
        "+f"(d[8]), "+f"(d[9]), "+f"(d[10]), "+f"(d[11]), "+f"(d[12]), "+f"(d[13]), "+f"(d[14]), "+f"(d[15]),
        "+f"(d[16]), "+f"(d[17]), "+f"(d[18]), "+f"(d[19]), "+f"(d[20]), "+f"(d[21]), "+f"(d[22]), "+f"(d[23]),
        "+f"(d[24]), "+f"(d[25]), "+f"(d[26]), "+f"(d[27]), "+f"(d[28]), "+f"(d[29]), "+f"(d[30]), "+f"(d[31]),
        "+f"(d[32]), "+f"(d[33]), "+f"(d[34]), "+f"(d[35]), "+f"(d[36]), "+f"(d[37]), "+f"(d[38]), "+f"(d[39])
      : "r"(a[0]), "r"(a[1]), "r"(a[2]), "r"(a[3]), "l"(descB));
}
__device__ __forceinline__ void mma_rs80_k_z(float (&d)[40], const uint32_t (&a)[4], uint64_t descB) {
  asm volatile("wgmma.mma_async.sync.aligned.m64n80k16.f32.bf16.bf16 {"
      "%0, %1, %2, %3, %4, %5, %6, %7, %8, %9, %10, %11, %12, %13, %14, %15, "
      "%16, %17, %18, %19, %20, %21, %22, %23, %24, %25, %26, %27, %28, %29, %30, %31, "
      "%32, %33, %34, %35, %36, %37, %38, %39"
      "}, {%40, %41, %42, %43}, %44, 0, 1, 1, 0;\n"
      : "=f"(d[0]), "=f"(d[1]), "=f"(d[2]), "=f"(d[3]), "=f"(d[4]), "=f"(d[5]), "=f"(d[6]), "=f"(d[7]),
        "=f"(d[8]), "=f"(d[9]), "=f"(d[10]), "=f"(d[11]), "=f"(d[12]), "=f"(d[13]), "=f"(d[14]), "=f"(d[15]),
        "=f"(d[16]), "=f"(d[17]), "=f"(d[18]), "=f"(d[19]), "=f"(d[20]), "=f"(d[21]), "=f"(d[22]), "=f"(d[23]),
        "=f"(d[24]), "=f"(d[25]), "=f"(d[26]), "=f"(d[27]), "=f"(d[28]), "=f"(d[29]), "=f"(d[30]), "=f"(d[31]),
        "=f"(d[32]), "=f"(d[33]), "=f"(d[34]), "=f"(d[35]), "=f"(d[36]), "=f"(d[37]), "=f"(d[38]), "=f"(d[39])
      : "r"(a[0]), "r"(a[1]), "r"(a[2]), "r"(a[3]), "l"(descB));
}

__device__ __forceinline__ void mma_rs48_k(float (&d)[24], const uint32_t (&a)[4], uint64_t descB) {
  asm volatile("wgmma.mma_async.sync.aligned.m64n48k16.f32.bf16.bf16 {"
      "%0, %1, %2, %3, %4, %5, %6, %7, %8, %9, %10, %11, %12, %13, %14, %15, "
      "%16, %17, %18, %19, %20, %21, %22, %23"
      "}, {%24, %25, %26, %27}, %28, 1, 1, 1, 0;\n"
      : "+f"(d[0]), "+f"(d[1]), "+f"(d[2]), "+f"(d[3]), "+f"(d[4]), "+f"(d[5]), "+f"(d[6]), "+f"(d[7]),
        "+f"(d[8]), "+f"(d[9]), "+f"(d[10]), "+f"(d[11]), "+f"(d[12]), "+f"(d[13]), "+f"(d[14]), "+f"(d[15]),
        "+f"(d[16]), "+f"(d[17]), "+f"(d[18]), "+f"(d[19]), "+f"(d[20]), "+f"(d[21]), "+f"(d[22]), "+f"(d[23])
      : "r"(a[0]), "r"(a[1]), "r"(a[2]), "r"(a[3]), "l"(descB));
}
__device__ __forceinline__ void mma_rs48_k_z(float (&d)[24], const uint32_t (&a)[4], uint64_t descB) {
  asm volatile("wgmma.mma_async.sync.aligned.m64n48k16.f32.bf16.bf16 {"
      "%0, %1, %2, %3, %4, %5, %6, %7, %8, %9, %10, %11, %12, %13, %14, %15, "
      "%16, %17, %18, %19, %20, %21, %22, %23"
      "}, {%24, %25, %26, %27}, %28, 0, 1, 1, 0;\n"
      : "=f"(d[0]), "=f"(d[1]), "=f"(d[2]), "=f"(d[3]), "=f"(d[4]), "=f"(d[5]), "=f"(d[6]), "=f"(d[7]),
        "=f"(d[8]), "=f"(d[9]), "=f"(d[10]), "=f"(d[11]), "=f"(d[12]), "=f"(d[13]), "=f"(d[14]), "=f"(d[15]),
        "=f"(d[16]), "=f"(d[17]), "=f"(d[18]), "=f"(d[19]), "=f"(d[20]), "=f"(d[21]), "=f"(d[22]), "=f"(d[23])
      : "r"(a[0]), "r"(a[1]), "r"(a[2]), "r"(a[3]), "l"(descB));
}

__device__ __forceinline__ void mma_rs160_n(float (&d)[80], const uint32_t (&a)[4], uint64_t descB) {
  asm volatile("wgmma.mma_async.sync.aligned.m64n160k16.f32.bf16.bf16 {"
      "%0, %1, %2, %3, %4, %5, %6, %7, %8, %9, %10, %11, %12, %13, %14, %15, "
      "%16, %17, %18, %19, %20, %21, %22, %23, %24, %25, %26, %27, %28, %29, %30, %31, "
      "%32, %33, %34, %35, %36, %37, %38, %39, %40, %41, %42, %43, %44, %45, %46, %47, "
      "%48, %49, %50, %51, %52, %53, %54, %55, %56, %57, %58, %59, %60, %61, %62, %63, "
      "%64, %65, %66, %67, %68, %69, %70, %71, %72, %73, %74, %75, %76, %77, %78, %79"
      "}, {%80, %81, %82, %83}, %84, 1, 1, 1, 1;\n"
      : "+f"(d[0]), "+f"(d[1]), "+f"(d[2]), "+f"(d[3]), "+f"(d[4]), "+f"(d[5]), "+f"(d[6]), "+f"(d[7]),
        "+f"(d[8]), "+f"(d[9]), "+f"(d[10]), "+f"(d[11]), "+f"(d[12]), "+f"(d[13]), "+f"(d[14]), "+f"(d[15]),
        "+f"(d[16]), "+f"(d[17]), "+f"(d[18]), "+f"(d[19]), "+f"(d[20]), "+f"(d[21]), "+f"(d[22]), "+f"(d[23]),
        "+f"(d[24]), "+f"(d[25]), "+f"(d[26]), "+f"(d[27]), "+f"(d[28]), "+f"(d[29]), "+f"(d[30]), "+f"(d[31]),
        "+f"(d[32]), "+f"(d[33]), "+f"(d[34]), "+f"(d[35]), "+f"(d[36]), "+f"(d[37]), "+f"(d[38]), "+f"(d[39]),
        "+f"(d[40]), "+f"(d[41]), "+f"(d[42]), "+f"(d[43]), "+f"(d[44]), "+f"(d[45]), "+f"(d[46]), "+f"(d[47]),
        "+f"(d[48]), "+f"(d[49]), "+f"(d[50]), "+f"(d[51]), "+f"(d[52]), "+f"(d[53]), "+f"(d[54]), "+f"(d[55]),
        "+f"(d[56]), "+f"(d[57]), "+f"(d[58]), "+f"(d[59]), "+f"(d[60]), "+f"(d[61]), "+f"(d[62]), "+f"(d[63]),
        "+f"(d[64]), "+f"(d[65]), "+f"(d[66]), "+f"(d[67]), "+f"(d[68]), "+f"(d[69]), "+f"(d[70]), "+f"(d[71]),
        "+f"(d[72]), "+f"(d[73]), "+f"(d[74]), "+f"(d[75]), "+f"(d[76]), "+f"(d[77]), "+f"(d[78]), "+f"(d[79])
      : "r"(a[0]), "r"(a[1]), "r"(a[2]), "r"(a[3]), "l"(descB));
}
__device__ __forceinline__ void mma_rs160_n_z(float (&d)[80], const uint32_t (&a)[4], uint64_t descB) {
  asm volatile("wgmma.mma_async.sync.aligned.m64n160k16.f32.bf16.bf16 {"
      "%0, %1, %2, %3, %4, %5, %6, %7, %8, %9, %10, %11, %12, %13, %14, %15, "
      "%16, %17, %18, %19, %20, %21, %22, %23, %24, %25, %26, %27, %28, %29, %30, %31, "
      "%32, %33, %34, %35, %36, %37, %38, %39, %40, %41, %42, %43, %44, %45, %46, %47, "
      "%48, %49, %50, %51, %52, %53, %54, %55, %56, %57, %58, %59, %60, %61, %62, %63, "
      "%64, %65, %66, %67, %68, %69, %70, %71, %72, %73, %74, %75, %76, %77, %78, %79"
      "}, {%80, %81, %82, %83}, %84, 0, 1, 1, 1;\n"
      : "=f"(d[0]), "=f"(d[1]), "=f"(d[2]), "=f"(d[3]), "=f"(d[4]), "=f"(d[5]), "=f"(d[6]), "=f"(d[7]),
        "=f"(d[8]), "=f"(d[9]), "=f"(d[10]), "=f"(d[11]), "=f"(d[12]), "=f"(d[13]), "=f"(d[14]), "=f"(d[15]),
        "=f"(d[16]), "=f"(d[17]), "=f"(d[18]), "=f"(d[19]), "=f"(d[20]), "=f"(d[21]), "=f"(d[22]), "=f"(d[23]),
        "=f"(d[24]), "=f"(d[25]), "=f"(d[26]), "=f"(d[27]), "=f"(d[28]), "=f"(d[29]), "=f"(d[30]), "=f"(d[31]),
        "=f"(d[32]), "=f"(d[33]), "=f"(d[34]), "=f"(d[35]), "=f"(d[36]), "=f"(d[37]), "=f"(d[38]), "=f"(d[39]),
        "=f"(d[40]), "=f"(d[41]), "=f"(d[42]), "=f"(d[43]), "=f"(d[44]), "=f"(d[45]), "=f"(d[46]), "=f"(d[47]),
        "=f"(d[48]), "=f"(d[49]), "=f"(d[50]), "=f"(d[51]), "=f"(d[52]), "=f"(d[53]), "=f"(d[54]), "=f"(d[55]),
        "=f"(d[56]), "=f"(d[57]), "=f"(d[58]), "=f"(d[59]), "=f"(d[60]), "=f"(d[61]), "=f"(d[62]), "=f"(d[63]),
        "=f"(d[64]), "=f"(d[65]), "=f"(d[66]), "=f"(d[67]), "=f"(d[68]), "=f"(d[69]), "=f"(d[70]), "=f"(d[71]),
        "=f"(d[72]), "=f"(d[73]), "=f"(d[74]), "=f"(d[75]), "=f"(d[76]), "=f"(d[77]), "=f"(d[78]), "=f"(d[79])
      : "r"(a[0]), "r"(a[1]), "r"(a[2]), "r"(a[3]), "l"(descB));
}

__device__ __forceinline__ void feature_map(const uint32_t (&P)[2][10], uint32_t (&fr)[10][4]) {
  constexpr float L2E = 1.4426950408889634f;
#pragma unroll
  for (int p = 0; p < 2; p++) {
#pragma unroll
    for (int r = 0; r < 2; r++) {
      uint32_t mx = P[r][5 * p], mn = mx;
#pragma unroll
      for (int g = 1; g < 5; g++) { mx = max_bf2(mx, P[r][5 * p + g]); mn = min_bf2(mn, P[r][5 * p + g]); }
      mx = max_bf2(mx, __shfl_xor_sync(0xffffffffu, mx, 1));
      mn = min_bf2(mn, __shfl_xor_sync(0xffffffffu, mn, 1));
      mx = max_bf2(mx, __shfl_xor_sync(0xffffffffu, mx, 2));
      mn = min_bf2(mn, __shfl_xor_sync(0xffffffffu, mn, 2));
      float mx0 = -bf_lo(mx) * L2E, mx1 = -bf_hi(mx) * L2E, mn0 = bf_lo(mn) * L2E, mn1 = bf_hi(mn) * L2E;
      float ep0[5], ep1[5], en0[5], en1[5];
      float sp0 = 0.f, sp1 = 0.f, sn0 = 0.f, sn1 = 0.f;
#pragma unroll
      for (int g = 0; g < 5; g++) {
        float x0 = bf_lo(P[r][5 * p + g]), x1 = bf_hi(P[r][5 * p + g]);
        ep0[g] = ex2(fmaf(x0, L2E, mx0)); ep1[g] = ex2(fmaf(x1, L2E, mx1));
        en0[g] = ex2(fmaf(x0, -L2E, mn0)); en1[g] = ex2(fmaf(x1, -L2E, mn1));
        sp0 += ep0[g]; sp1 += ep1[g]; sn0 += en0[g]; sn1 += en1[g];
      }
      sp0 += __shfl_xor_sync(0xffffffffu, sp0, 1); sp1 += __shfl_xor_sync(0xffffffffu, sp1, 1);
      sn0 += __shfl_xor_sync(0xffffffffu, sn0, 1); sn1 += __shfl_xor_sync(0xffffffffu, sn1, 1);
      sp0 += __shfl_xor_sync(0xffffffffu, sp0, 2); sp1 += __shfl_xor_sync(0xffffffffu, sp1, 2);
      sn0 += __shfl_xor_sync(0xffffffffu, sn0, 2); sn1 += __shfl_xor_sync(0xffffffffu, sn1, 2);
      sp0 = rcp(sp0); sp1 = rcp(sp1); sn0 = rcp(sn0); sn1 = rcp(sn1);
#pragma unroll
      for (int g = 0; g < 5; g++) {
        fr[5 * p + g][r] = pack_bf16(ep0[g] * sp0, ep1[g] * sp1);
        fr[5 * p + g][2 + r] = pack_bf16(en0[g] * sn0, en1[g] * sn1);
      }
    }
  }
}

template <bool V> struct BoolC { static constexpr bool value = V; };
struct Ring {
  uint32_t idx, phase;
  template <int N> __device__ __forceinline__ void next() { if (++idx == N) { idx = 0; phase ^= 1; } }
};

}

__global__ void __cluster_dims__(2, 1, 1) __launch_bounds__(384, 1)
fused_kernel(const __grid_constant__ Maps maps, const __nv_bfloat16* __restrict__ x, const __nv_bfloat16* __restrict__ wqkv,
             const __nv_bfloat16* __restrict__ wphi, const __nv_bfloat16* __restrict__ w1, const __nv_bfloat16* __restrict__ w2,
             const __nv_bfloat16* __restrict__ w3, const __nv_bfloat16* __restrict__ w4, const __nv_bfloat16* __restrict__ wo,
             const __nv_bfloat16* __restrict__ gate_w) {
  extern __shared__ __align__(1024) uint8_t sgen[];
  const uint32_t sb = smem_u32(sgen);
  const uint32_t sb16 = (sb & 0x3FFFFu) >> 4;
  const uint32_t bars = sb + OFF_BAR;
  const uint32_t fullA = bars + 8 * B_FULLA, emptyA = bars + 8 * B_EMPTYA, fullB = bars + 8 * B_FULLB, emptyB = bars + 8 * B_EMPTYB;

  const int tid = threadIdx.x;
  const int rank = blockIdx.x & 1;
  const int pairIdx = blockIdx.x >> 1;
  const int i = pairIdx >> 2, j = 2 * (pairIdx & 3) + rank;

  TSTAMP(0);
  auto load_p1_b = [&](int k, uint32_t slot, uint32_t bar) {
    mbar_expect_tx(bar, 40960);
    tma4d(slot + 8192, &maps.qm, bar, 0, 64 * k, 0, j);
    tma3d(slot, &maps.w1m, bar, 0, 64 * k, j);
    tma4d(slot + 32768 + 2048, &maps.qr, bar, 64, 64 * k, 0, j);
    tma3d(slot + 32768, &maps.w1r, bar, 64, 64 * k, j);
  };
  if (tid >= 256) {
    asm volatile("setmaxnreg.dec.sync.aligned.u32 40;");
    if (tid == 256) {
#pragma unroll
      for (int s = 0; s < NA; s++) mbar_init(fullA + 8 * s, 1);
      asm volatile("fence.mbarrier_init.release.cluster;" ::: "memory");
#pragma unroll 1
      for (int u = 0; u < 4; u++) {
        if ((u & 1) == 0) mbar_expect_tx(fullA + 4 * u, SLOT_A);
        tma2d(sb + OFF_A + u * 8192, &maps.x, fullA + 8 * (u >> 1), 64 * (u >> 1), 128 * i + 64 * (u & 1));
      }
    } else if (tid == 288) {
#pragma unroll
      for (int s = 0; s < NB; s++) mbar_init(fullB + 8 * s, 1);
      asm volatile("fence.mbarrier_init.release.cluster;" ::: "memory");
#pragma unroll 1
      for (int k = 0; k < 2; k++) load_p1_b(k, sb + OFF_B + k * SLOT_B, fullB + 8 * k);
    } else if (tid == 320) {
#pragma unroll
      for (int b = B_CS; b < NBAR; b++) mbar_init(bars + 8 * b, b < B_EMPTYB ? 1 : b < B_EMPTYA ? 8 : 16);
#pragma unroll
      for (int b = B_DSR; b < B_EMPTYB; b++) mbar_expect_tx(bars + 8 * b, 10240);
      asm volatile("fence.mbarrier_init.release.cluster;" ::: "memory");
    }
    __syncwarp();
    asm volatile("barrier.cluster.arrive.relaxed.aligned;" ::: "memory");
    auto get_epoch = [&]() { return *reinterpret_cast<volatile unsigned*>(g_flags + FL_DONE * 32) / NCTA; };
    if (tid >= 320) {
      const int lane = tid & 31, ch = lane % 10, rg = lane / 10;
      const __nv_bfloat16* p = w1 + (size_t)(40 * i + (tid >= 352 ? 20 : 0) + rg) * D_ + 80 * j + 8 * ch;
      const unsigned par = get_epoch() & 1;
      float a[8];
#pragma unroll
      for (int e = 0; e < 8; e++) a[e] = 0.f;
#pragma unroll
      for (int it = 0; it < 7; it++) {
        uint4 v = make_uint4(0, 0, 0, 0);
        if (lane < 30 && 3 * it + rg < 20) v = __ldg(reinterpret_cast<const uint4*>(p + (size_t)it * 3 * D_));
        a[0] += bf_lo(v.x); a[1] += bf_hi(v.x); a[2] += bf_lo(v.y); a[3] += bf_hi(v.y);
        a[4] += bf_lo(v.z); a[5] += bf_hi(v.z); a[6] += bf_lo(v.w); a[7] += bf_hi(v.w);
      }
#pragma unroll
      for (int e = 0; e < 8; e++) a[e] += __shfl_down_sync(0xffffffffu, a[e], 10) + __shfl_down_sync(0xffffffffu, a[e], 20);
      if (lane < 10) {
        float* cd = g_acc[par] + 8 * KV_J + 80 * j + 8 * ch;
        red_add4(cd, a[0], a[1], a[2], a[3]); red_add4(cd + 4, a[4], a[5], a[6], a[7]);
      }
      __syncwarp();
      if (lane == 0) flag_add(FL_CS + j);
      __syncwarp();
    }
    asm volatile("barrier.cluster.wait.aligned;" ::: "memory");
    const int lane = tid & 31, pw = (tid >> 5) & 3;
    if (pw == 0) {
      if (tid == 256) {
        Ring r{2, 1};
        unsigned ep1 = 0;
#pragma unroll 1
        for (int k = 2; k < 30; k++) {
          if (k == 4) ep1 = get_epoch() + 1;
          if (k == 10 || k == 20) {
            const unsigned tgt = ep1 * 8u;
            const unsigned* f0 = g_flags + (k == 10 ? FL_H + ((i - 1) & 15) : FL_X1 + i) * 32;
            const unsigned* f1 = g_flags + (k == 10 ? FL_H + i : FL_X1 + i) * 32;
            const unsigned* f2 = g_flags + (k == 10 ? FL_H + ((i + 1) & 15) : FL_X1 + i) * 32;
            uint32_t n = 0;
            while (++n < (WAIT_LIMIT >> 4)) {
              unsigned v0, v1, v2;
              asm volatile("ld.relaxed.gpu.global.u32 %0, [%3];\nld.relaxed.gpu.global.u32 %1, [%4];\nld.acquire.gpu.global.u32 %2, [%5];"
                           : "=r"(v0), "=r"(v1), "=r"(v2) : "l"(f0), "l"(f1), "l"(f2) : "memory");
              if ((int)((v0 - tgt) | (v1 - tgt) | (v2 - tgt)) >= 0) break;
            }
            TSTAMPX(k == 10 ? 29 : 30);
          }
          mbar_wait(emptyA + 8 * r.idx, r.phase);
          const uint32_t bar = fullA + 8 * r.idx, slot = sb + OFF_A + r.idx * SLOT_A;
          TRACE(k);
          mbar_expect_tx(bar, SLOT_A);
          tma2d_mc(slot + rank * 8192, k < 10 ? &maps.x : k < 20 ? &maps.hs : &maps.x1, bar, 64 * (k % 10), 128 * i + 64 * rank);
          r.next<NA>();
        }
      }
    } else if (pw == 1) {
      if (tid == 288) {
        Ring r{2, 1};
#pragma unroll 1
        for (int k = 2; k < 18; k++) {
          mbar_wait(emptyB + 8 * r.idx, r.phase);
          const uint32_t bar = fullB + 8 * r.idx, slot = sb + OFF_B + r.idx * SLOT_B;
          if (k < 10) {
            load_p1_b(k, slot, bar);
          } else if (k < 13) {
            if (k == 12) mbar_wait(fullA + 8 * 2, 0);
            mbar_expect_tx(bar, k < 12 ? 40960 : 20480);
#pragma unroll 1
            for (int u = 0; u < (k < 12 ? 4 : 2); u++) tma3d(slot + u * 10240, &maps.w2, bar, 0, 256 * (k - 10) + 64 * u, 5 * j);
          } else {
            mbar_expect_tx(bar, 49152);
            tma3d(slot, &maps.w3, bar, 0, 128 * (k - 13), 3 * j);
            tma3d(slot + 24576, &maps.w3, bar, 0, 128 * (k - 13) + 64, 3 * j);
          }
          r.next<NB>();
        }
        Ring r4{0, 1};
#pragma unroll 1
        for (int n = 0; n < 16; n++) {
          if (n == 0 || n == 1 || n == 3) { mbar_wait(emptyB + 8 * r.idx, r.phase); r.next<NB>(); }
          mbar_wait(bars + 8 * (B_EMPTY4 + r4.idx), r4.phase);
          const uint32_t bar = bars + 8 * (B_FULL4 + r4.idx), slot = sb + OFF_B + r4.idx * UNIT4;
          const int u = n & 3, m = ((j >> 1) + 1 + (n >> 2)) & 3;
          mbar_expect_tx(bar, u == 3 ? 25600 : 20480);
          tma3d(slot, u == 3 ? &maps.wo : &maps.w4, bar, 0, u == 3 ? 80 * j : 192 * j + 64 * u, 5 * m);
          r4.next<NU4>();
        }
      }
    } else {
      const unsigned epoch = get_epoch();
      float* accg = g_acc[epoch & 1];
      if (pw == 2) {
        {
          float* nxt = g_acc[(epoch + 1) & 1];
          constexpr int PER = ACC_FLOATS / NCTA;
#pragma unroll 1
          for (int e = lane; e < PER; e += 32) nxt[blockIdx.x * PER + e] = 0.f;
        }
        if (tid == 320) {
          flag_wait(FL_CS + j, (epoch + 1) * 32u);
          flag_wait(FL_ST + i, (epoch + 1) * 8u);
          fence_async_glb();
          *reinterpret_cast<volatile uint32_t*>(sgen + OFF_BAR + 8 * NBAR) = (epoch + 1) & 1;
          mbar_expect_tx(bars + 8 * B_CS, 320 + 2048);
          bulk_load(sb + OFF_CS, accg + 8 * KV_J + 80 * j, 320, bars + 8 * B_CS);
          bulk_load(sb + OFF_XST, g_xstat + 128 * i, 2048, bars + 8 * B_CS);
          TSTAMPX(21);
          l2_prefetch(w2 + (size_t)blockIdx.x * (D_ * D_ / NCTA), D_ * D_ * 2 / NCTA);
          flag_wait(FL_H + i, (epoch + 1) * 8u);
          l2_prefetch(w3 + (size_t)blockIdx.x * (F_ * D_ / NCTA), F_ * D_ * 2 / NCTA);
          l2_prefetch(w4 + (size_t)blockIdx.x * (F_ * D_ / NCTA), F_ * D_ * 2 / NCTA);
          l2_prefetch(wo + (size_t)blockIdx.x * (D_ * D_ / NCTA), D_ * D_ * 2 / NCTA);
          flag_wait(FL_KV + j, (epoch + 1) * 16u);
          mbar_expect_tx(bars + 8 * B_KV, KV_J * 4);
          bulk_load(sb + OFF_MISC, accg + j * KV_J, KV_J * 4, bars + 8 * B_KV);
          TSTAMPX(22);
        }
        __syncwarp();
#pragma unroll 1
        for (int m = 0; m < 6; m++) {
          const int col = 192 * j + 32 * m + 8 * (lane & 3);
          const __nv_bfloat16* p = w3 + (size_t)(40 * i + (lane >> 2) * 5) * F_ + col;
          float a[8];
#pragma unroll
          for (int e = 0; e < 8; e++) a[e] = 0.f;
#pragma unroll
          for (int it = 0; it < 5; it++) {
            const uint4 v = __ldg(reinterpret_cast<const uint4*>(p + (size_t)it * F_));
            a[0] += bf_lo(v.x); a[1] += bf_hi(v.x); a[2] += bf_lo(v.y); a[3] += bf_hi(v.y);
            a[4] += bf_lo(v.z); a[5] += bf_hi(v.z); a[6] += bf_lo(v.w); a[7] += bf_hi(v.w);
          }
#pragma unroll
          for (int e = 0; e < 4; e++) {
            const float snd = (lane & 4) ? a[e] : a[e + 4], keep = (lane & 4) ? a[e + 4] : a[e];
            a[e] = keep + __shfl_xor_sync(0xffffffffu, snd, 4);
            a[e] += __shfl_xor_sync(0xffffffffu, a[e], 8);
            a[e] += __shfl_xor_sync(0xffffffffu, a[e], 16);
          }
          if (lane < 8) red_add4(accg + 8 * KV_J + D_ + col + (lane >> 2) * 4, a[0], a[1], a[2], a[3]);
        }
        __syncwarp();
        if (tid == 320) {
          flag_add(FL_CS3 + j);
          mbar_wait(bars + 8 * B_MFREE, 0);
          flag_wait(FL_X1 + i, (epoch + 1) * 8u);
          flag_wait(FL_CS3 + j, (epoch + 1) * 16u);
          fence_async_glb();
          mbar_expect_tx(bars + 8 * B_ST1, 8192 + 768);
          bulk_load(sb + OFF_CS + 320, accg + 8 * KV_J + D_ + 192 * j, 768, bars + 8 * B_ST1);
          bulk_load(sb + OFF_MISC, g_st1 + 128 * i * 8, 8192, bars + 8 * B_ST1);
        }
      }
      if (tid == 352) {
        mbar_wait(bars + 8 * B_SIGP, 0);
        flag_add(FL_ST + i);
        TSTAMPX(20);
        mbar_expect_tx(bars + 8 * B_XR, 20480);
#pragma unroll 1
        for (int u = 0; u < 8; u++)
          tma2d(sb + OFF_B + (u / 3) * SLOT_B + SPARE + (u % 3) * 2560, &maps.xr, bars + 8 * B_XR, 80 * j, 128 * i + 16 * u);
        const int shift = (j < 2) ? 1 : (j < 4) ? -1 : (j < 6) ? 2 : -2;
        if ((shift > 0 && i == 0) || (shift < 0 && i == 15)) {
          const int nz = shift > 0 ? shift : -shift, zr = shift > 0 ? 0 : S_ - nz;
#pragma unroll 1
          for (int e = 0; e < nz * 10; e++)
            reinterpret_cast<uint4*>(g_Hs + (size_t)(2 + zr + e / 10) * D_ + 80 * j)[e % 10] = make_uint4(0, 0, 0, 0);
          fence_async_glb();
        }
        prefetch_tmap(&maps.st_h); prefetch_tmap(&maps.st_x1); prefetch_tmap(&maps.hs); prefetch_tmap(&maps.x1); prefetch_tmap(&maps.xr);
        prefetch_tmap(&maps.w2); prefetch_tmap(&maps.w3); prefetch_tmap(&maps.w4); prefetch_tmap(&maps.wo); prefetch_tmap(&maps.st_out);
        mbar_wait(bars + 8 * B_SIGH, 0);
        TSTAMPX(23);
        tma2d_store(&maps.st_h, sb + OFF_STG, 80 * j, 128 * i + 2 + shift);
        tma2d_store(&maps.st_h, sb + OFF_STG + 10240, 80 * j, 128 * i + 66 + shift);
        bulk_commit(); bulk_wait<0>();
        flag_add(FL_H + i);
        TSTAMPX(24);
        mbar_wait(bars + 8 * B_SIGKV, 0);
        TSTAMPX(25);
        asm volatile("cp.reduce.async.bulk.global.shared::cta.bulk_group.add.f32 [%0], [%1], %2;"
                     ::"l"(accg + j * KV_J), "r"(sb + OFF_MISC), "r"(KV_J * 4) : "memory");
        bulk_commit(); bulk_wait<0>();
        flag_add(FL_KV + j);
        TSTAMPX(26);
        mbar_wait(bars + 8 * B_SIGX1, 0);
        TSTAMPX(27);
        tma2d_store(&maps.st_x1, sb + OFF_STG, 80 * j, 128 * i);
        tma2d_store(&maps.st_x1, sb + OFF_STG + 10240, 80 * j, 128 * i + 64);
        bulk_commit(); bulk_wait<0>();
        flag_add(FL_X1 + i);
        TSTAMPX(28);
      }
    }
  } else {
    uint4 pv[5], pw_[5], pre;
    {
      const int row = 128 * i + 16 * j + (tid >> 4), l16 = tid & 15;
#pragma unroll
      for (int c = 0; c < 5; c++) pv[c] = __ldg(reinterpret_cast<const uint4*>(x + (size_t)row * D_ + c * 128 + l16 * 8));
      pre = __ldg(reinterpret_cast<const uint4*>(wphi + (size_t)j * 1600) + (tid < 200 ? tid : 0));
#pragma unroll
      for (int c = 0; c < 5; c++) pw_[c] = __ldg(reinterpret_cast<const uint4*>(gate_w + c * 128 + l16 * 8));
    }
    asm volatile("barrier.cluster.arrive.relaxed.aligned;" ::: "memory");
    asm volatile("setmaxnreg.inc.sync.aligned.u32 232;");
    const int wg = tid >> 7, warp = tid >> 5, lane = tid & 31, t = lane & 3;
    const int rloc = warp * 16 + (lane >> 2);
    const float* s_cs = reinterpret_cast<const float*>(sgen + OFF_CS);
    auto signal = [&](int b) {
      __syncwarp();
      if (lane == 0) mbar_arrive(bars + 8 * b);
    };
    auto releaseB = [&](uint32_t bar) {
      __syncwarp();
      if (lane == 0) mbar_arrive(bar);
    };
    auto release = [&](uint32_t bar) {
      __syncwarp();
      if (lane < 2) mbar_arrive_cta(bar, lane);
    };
    const uint32_t stg_lane = (warp * 16 + ((lane >> 3) & 1) * 8 + (lane & 7)) * 160 + (lane >> 4) * 16;

    {
#pragma unroll 1
      for (int e = tid; e < 800; e += 256) sts128(sb + OFF_MISC + e * 16, make_uint4(0, 0, 0, 0));
      bar_sync(1, 256);
      float f[40];
      float s = 0.f, gs = 0.f;
#pragma unroll
      for (int c = 0; c < 5; c++) {
        const uint32_t vv[4] = {pv[c].x, pv[c].y, pv[c].z, pv[c].w}, ww[4] = {pw_[c].x, pw_[c].y, pw_[c].z, pw_[c].w};
#pragma unroll
        for (int e = 0; e < 4; e++) {
          f[8 * c + 2 * e] = bf_lo(vv[e]); f[8 * c + 2 * e + 1] = bf_hi(vv[e]);
          s += f[8 * c + 2 * e] + f[8 * c + 2 * e + 1];
          gs = fmaf(f[8 * c + 2 * e], bf_lo(ww[e]), gs); gs = fmaf(f[8 * c + 2 * e + 1], bf_hi(ww[e]), gs);
        }
      }
#pragma unroll
      for (int o = 1; o < 16; o <<= 1) { s += __shfl_xor_sync(0xffffffffu, s, o); gs += __shfl_xor_sync(0xffffffffu, gs, o); }
      const float mean = s * (1.f / D_);
      float q = 0.f;
#pragma unroll
      for (int e = 0; e < 40; e++) { const float d = f[e] - mean; q = fmaf(d, d, q); }
#pragma unroll
      for (int o = 1; o < 16; o <<= 1) q += __shfl_xor_sync(0xffffffffu, q, o);
      const float rstd = rsqrtf(q * (1.f / D_) + 1e-5f);
      asm volatile("barrier.cluster.wait.aligned;" ::: "memory");
      if ((tid & 15) == 0) g_xstat[128 * i + 16 * j + (tid >> 4)] = make_float4(rstd, -mean * rstd, rcp(1.f + __expf(-gs)), 0.f);
      signal(B_SIGP);
      if (tid < 200) {
        const uint32_t ww[4] = {pre.x, pre.y, pre.z, pre.w};
        const int h = tid / 50;
#pragma unroll
        for (int e = 0; e < 8; e++) {
          const int idx = tid * 8 + e, k = idx / 20, ff = idx - 20 * k;
          const int n = 40 * (h >> 1) + 8 * (ff >> 2) + 2 * (ff & 3) + (h & 1);
          const int off = (k >> 4) * 2560 + n * 32 + ((((k >> 3) ^ (n >> 2)) & 1) << 4) + (k & 7) * 2;
          *reinterpret_cast<unsigned short*>(sgen + OFF_MISC + off) = (unsigned short)(ww[e >> 1] >> ((e & 1) * 16));
        }
      }
    }
    TSTAMP(1);

    Ring ra{0, 0}, rb{0, 0};
    uint32_t qp[2][10], P[2][10];
    float st_g[2];
    {
      float accM[128], accR[32];
      zero_regs(accM); zero_regs(accR);
      uint32_t pa = 0, pb = 0;
#pragma unroll 1
      for (int k = 0; k < 10; k++) {
        mbar_wait(fullA + 8 * ra.idx, ra.phase);
        if (tid == 0) TRACE(32 + k);
        mbar_wait(fullB + 8 * rb.idx, rb.phase);
        if (tid == 0) TRACE(64 + k);
        if (k == 0) TSTAMP(2);
        const uint32_t a0 = sb16 + ((OFF_A + ra.idx * SLOT_A + wg * 8192) >> 4), b0 = sb16 + ((OFF_B + rb.idx * SLOT_B) >> 4);
        wg_fence();
#pragma unroll
        for (int kk = 0; kk < 4; kk++) {
          const uint64_t da = make_desc(a0, kk * 32, 16, 1024, 1);
          mma_ss256(accM, da, make_desc(b0, kk * 2048, 8192, 1024, 1));
          mma_ss64(accR, da, make_desc(b0, 32768 + kk * 512, 2048, 256, 3));
          if (kk == 0) {
            wg_commit();
            if (k > 0) {
              wg_wait<1>();
              if (k - 1 < 8) release(emptyA + 8 * pa);
              releaseB(emptyB + 8 * pb);
            }
          }
        }
        wg_commit();
        pa = ra.idx; pb = rb.idx;
        ra.next<NA>(); rb.next<NB>();
      }
      TSTAMP(18);
      float st_rstd[2], st_mr[2];
      mbar_wait(bars + 8 * B_CS, 0);
#pragma unroll
      for (int r = 0; r < 2; r++) {
        const uint4 st = lds128(sb + OFF_XST + (rloc + 8 * r) * 16);
        st_rstd[r] = __uint_as_float(st.x); st_mr[r] = __uint_as_float(st.y); st_g[r] = __uint_as_float(st.z);
      }
      TSTAMP(19);
      wg_wait<0>();
      fence_regs(accM); fence_regs(accR);
      TSTAMP(3);
#define ACC(P_, G, I_) ((G) < 8 ? accM[(P_) * 32 + ((G) & 7) * 4 + (I_)] : accR[(P_) * 8 + ((G) & 1) * 4 + (I_)])
      {
        uint32_t hv[10][2];
#pragma unroll
        for (int g = 0; g < 10; g++) {
          const float2 cs = *reinterpret_cast<const float2*>(s_cs + 8 * g + 2 * t);
          const float v0 = gelu_s(fmaf(ACC(0, g, 0), st_rstd[0], st_mr[0] * cs.x), 0.5f), v1 = gelu_s(fmaf(ACC(0, g, 1), st_rstd[0], st_mr[0] * cs.y), 0.5f);
          const float v2 = gelu_s(fmaf(ACC(0, g, 2), st_rstd[1], st_mr[1] * cs.x), 0.5f), v3 = gelu_s(fmaf(ACC(0, g, 3), st_rstd[1], st_mr[1] * cs.y), 0.5f);
          hv[g][0] = pack_bf16(v0, v1); hv[g][1] = pack_bf16(v2, v3);
        }
        fence_async_smem();
        bar_sync(1, 256);
#pragma unroll
        for (int s = 0; s < 5; s++) stsm4(sb + OFF_STG + stg_lane + s * 32, hv[2 * s][0], hv[2 * s][1], hv[2 * s + 1][0], hv[2 * s + 1][1]);
        fence_async_smem();
        signal(B_SIGH);
      }
      TSTAMP(4);
      uint32_t kf[5][4], qf[5][4];
#pragma unroll
      for (int s = 0; s < 5; s++) {
        kf[s][0] = pack_bf16(ACC(2, 2 * s, 0), ACC(2, 2 * s, 1)); kf[s][1] = pack_bf16(ACC(2, 2 * s, 2), ACC(2, 2 * s, 3));
        kf[s][2] = pack_bf16(ACC(2, 2 * s + 1, 0), ACC(2, 2 * s + 1, 1)); kf[s][3] = pack_bf16(ACC(2, 2 * s + 1, 2), ACC(2, 2 * s + 1, 3));
        qf[s][0] = pack_bf16(ACC(1, 2 * s, 0), ACC(1, 2 * s, 1)); qf[s][1] = pack_bf16(ACC(1, 2 * s, 2), ACC(1, 2 * s, 3));
        qf[s][2] = pack_bf16(ACC(1, 2 * s + 1, 0), ACC(1, 2 * s + 1, 1)); qf[s][3] = pack_bf16(ACC(1, 2 * s + 1, 2), ACC(1, 2 * s + 1, 3));
      }
      float pk[40], pq[40];
      wg_fence();
#pragma unroll
      for (int s = 0; s < 5; s++) {
        if (s == 0) mma_rs80_k_z(pk, kf[s], make_desc(sb16, OFF_MISC, 16, 256, 3));
        else mma_rs80_k(pk, kf[s], make_desc(sb16, OFF_MISC + s * 2560, 16, 256, 3));
      }
#pragma unroll
      for (int s = 0; s < 5; s++) {
        if (s == 0) mma_rs80_k_z(pq, qf[s], make_desc(sb16, OFF_MISC, 16, 256, 3));
        else mma_rs80_k(pq, qf[s], make_desc(sb16, OFF_MISC + s * 2560, 16, 256, 3));
      }
      wg_commit();
      {
        const int mat = lane >> 3;
        const int tok = warp * 16 + (mat & 1) * 8 + (lane & 7);
        const uint32_t ones = (t == 0) ? 0x00003f80u : 0u;
        __syncwarp();
#pragma unroll
        for (int p = 0; p < 2; p++) {
          const uint32_t rowa = sb + OFF_A + p * SLOT_A + tok * 128;
#pragma unroll
          for (int gg = 0; gg < 3; gg++) {
            const int g0 = 5 * p + 2 * gg;
            uint32_t r0 = pack_bf16(ACC(3, g0, 0), ACC(3, g0, 1)), r1 = pack_bf16(ACC(3, g0, 2), ACC(3, g0, 3));
            uint32_t r2 = ones, r3 = ones;
            if (gg < 2) { r2 = pack_bf16(ACC(3, g0 + 1, 0), ACC(3, g0 + 1, 1)); r3 = pack_bf16(ACC(3, g0 + 1, 2), ACC(3, g0 + 1, 3)); }
            stsm4(rowa + (((2 * gg + (mat >> 1)) ^ (tok & 7)) << 4), r0, r1, r2, r3);
          }
        }
      }
#undef ACC
      wg_wait<0>();
      fence_regs(pk); fence_regs(pq);
#pragma unroll
      for (int G = 0; G < 10; G++) {
        P[0][G] = pack_bf16(pk[4 * G], pk[4 * G + 1]); P[1][G] = pack_bf16(pk[4 * G + 2], pk[4 * G + 3]);
        qp[0][G] = pack_bf16(pq[4 * G], pq[4 * G + 1]); qp[1][G] = pack_bf16(pq[4 * G + 2], pq[4 * G + 3]);
      }
    }

    uint32_t fr[10][4];
    uint32_t xv[2][10];
#pragma unroll
    for (int g = 0; g < 10; g++) xv[0][g] = xv[1][g] = 0u;
    int pass;
    pass = gridDim.y;
#pragma unroll 1
    do {
    feature_map(P, fr);
    if (pass != 0) {
    {
      const int mat = lane >> 3;
      const int tok = warp * 16 + (mat & 1) * 8 + (lane & 7);
      const uint32_t base = sb + OFF_B + tok * 32 + (((mat >> 1) ^ ((tok >> 2) & 1)) << 4);
#pragma unroll
      for (int G = 0; G < 10; G++) stsm4(base + G * 4096, fr[G][0], fr[G][1], fr[G][2], fr[G][3]);
      fence_async_smem();
      bar_sync(1, 256);
      float kv[40];
      const uint32_t a0 = sb16 + ((OFF_A + wg * SLOT_A) >> 4), b0 = sb16 + ((OFF_B + wg * 20480) >> 4);
      wg_fence();
#pragma unroll
      for (int ks = 0; ks < 8; ks++) {
        if (ks == 0) mma_ss80_tt_z(kv, make_desc(a0, 0, 16, 1024, 1), make_desc(b0, 0, 4096, 256, 3));
        else mma_ss80_tt(kv, make_desc(a0, ks * 2048, 16, 1024, 1), make_desc(b0, ks * 512, 4096, 256, 3));
      }
      wg_commit();
      wg_wait<0>();
      fence_regs(kv);
      TSTAMP(31);
      release(emptyA); release(emptyA + 8); releaseB(emptyB);
      const uint32_t dst = sb + OFF_MISC + wg * (KV_PAIR * 4);
      const int m0 = (warp & 3) * 16 + (lane >> 2);
#pragma unroll
      for (int r = 0; r < 2; r++) {
        const int m = m0 + 8 * r;
        const bool hi = m >= 20;
        uint32_t v[10];
#pragma unroll
        for (int G = 0; G < 10; G++) v[G] = __float_as_uint(hi ? kv[4 * G + 2 * r + 1] : kv[4 * G + 2 * r]);
        const uint32_t p = dst + 4 * (m < 40 ? m * 48 + t * 12 : 1920 + t * 24 + 12);
        if (m <= 40) {
          sts128(p, make_uint4(v[0], v[1], v[2], v[3])); sts128(p + 16, make_uint4(v[4], v[5], v[6], v[7]));
          sts128(p + 32, make_uint4(v[8], v[9], 0u, 0u));
        }
      }
      if (m0 == 32) {
        const uint32_t p = dst + 4 * (1920 + t * 24);
        sts128(p, make_uint4(__float_as_uint(kv[2]), __float_as_uint(kv[6]), __float_as_uint(kv[10]), __float_as_uint(kv[14])));
        sts128(p + 16, make_uint4(__float_as_uint(kv[18]), __float_as_uint(kv[22]), __float_as_uint(kv[26]), __float_as_uint(kv[30])));
        sts128(p + 32, make_uint4(__float_as_uint(kv[34]), __float_as_uint(kv[38]), 0u, 0u));
      }
      fence_async_smem();
      signal(B_SIGKV);
    }
    TSTAMP(5);

    {
      {
        mbar_wait(bars + 8 * B_XR, 0);
        const uint32_t xa = sb + OFF_B + (warp / 3) * SLOT_B + SPARE + (warp % 3) * 2560 + (lane >> 2) * 160 + t * 4;
#pragma unroll
        for (int g = 0; g < 10; g++) { xv[0][g] = lds32(xa + g * 16); xv[1][g] = lds32(xa + 1280 + g * 16); }
      }
      float acc[40];
      zero_regs(acc);
      uint32_t pa = 0, pb = 0;
#pragma unroll 1
      for (int k = 0; k < 10; k++) {
        mbar_wait(fullA + 8 * ra.idx, ra.phase);
        if (tid == 0) TRACE(42 + k);
        if ((k & 3) == 0) mbar_wait(fullB + 8 * rb.idx, rb.phase);
        if (tid == 0) TRACE(74 + k);
        if (k == 0) TSTAMP(6);
        const uint32_t a0 = sb16 + ((OFF_A + ra.idx * SLOT_A + wg * 8192) >> 4);
        const uint32_t b0 = sb16 + ((OFF_B + rb.idx * SLOT_B + (k & 3) * 10240) >> 4);
        wg_fence();
#pragma unroll
        for (int kk = 0; kk < 4; kk++) {
          mma_ss80(acc, make_desc(a0, kk * 32, 16, 1024, 1), make_desc(b0, kk * 512, 2048, 256, 3));
          if (kk == 1) {
            wg_commit();
            if (k > 0) {
              wg_wait<1>();
              release(emptyA + 8 * pa);
              if ((k & 3) == 0) releaseB(emptyB + 8 * pb);
            }
          }
        }
        wg_commit();
        pa = ra.idx; pb = rb.idx;
        ra.next<NA>();
        if ((k & 3) == 3 || k == 9) rb.next<NB>();
      }
      wg_wait<0>();
      fence_regs(acc);
      release(emptyA + 8 * pa); releaseB(emptyB + 8 * pb);
      TSTAMP(7);
#pragma unroll
      for (int r = 0; r < 2; r++) {
#pragma unroll
        for (int g = 0; g < 10; g++)
          xv[r][g] = pack_bf16(bf_lo(xv[r][g]) + acc[4 * g + 2 * r], bf_hi(xv[r][g]) + acc[4 * g + 2 * r + 1]);
      }
      bar_sync(1, 256);
#pragma unroll
      for (int s = 0; s < 5; s++) stsm4(sb + OFF_STG + stg_lane + s * 32, xv[0][2 * s], xv[1][2 * s], xv[0][2 * s + 1], xv[1][2 * s + 1]);
#pragma unroll
      for (int r = 0; r < 2; r++) {
        float s = 0.f;
#pragma unroll
        for (int g = 0; g < 10; g++) {
          acc[4 * g + 2 * r] = bf_lo(xv[r][g]); acc[4 * g + 2 * r + 1] = bf_hi(xv[r][g]);
          s += acc[4 * g + 2 * r] + acc[4 * g + 2 * r + 1];
        }
        s += __shfl_xor_sync(0xffffffffu, s, 1); s += __shfl_xor_sync(0xffffffffu, s, 2);
        const float mu = s * (1.f / 80.f);
        float q = 0.f;
#pragma unroll
        for (int g = 0; g < 10; g++) {
          const float d0 = acc[4 * g + 2 * r] - mu, d1 = acc[4 * g + 2 * r + 1] - mu;
          q = fmaf(d0, d0, q); q = fmaf(d1, d1, q);
        }
        q += __shfl_xor_sync(0xffffffffu, q, 1); q += __shfl_xor_sync(0xffffffffu, q, 2);
        if (t == 0) g_st1[(128 * i + rloc + 8 * r) * 8 + j] = make_float2(mu, q);
      }
      fence_async_smem();
      signal(B_SIGX1);
    }
    TSTAMP(8);
#pragma unroll
    for (int G = 0; G < 10; G++) { P[0][G] = qp[0][G]; P[1][G] = qp[1][G]; }
    }
    asm volatile("" : "+r"(pass));
    } while (pass-- != 0);

    uint32_t of[5][4];
    {
      mbar_wait(bars + 8 * B_KV, 0);
      uint4 kvr[2][3];
#pragma unroll
      for (int u = 0; u < 2; u++) {
        const int it = tid + 256 * u, p = it / 192, rem = it - 192 * p, n = rem >> 2, tq = rem & 3;
        const uint32_t sp = sb + OFF_MISC + 4 * (p * KV_PAIR + (n < 40 ? n * 48 + tq * 12 : 1920 + tq * 24 + (n & 1) * 12));
        if (it < 384) { kvr[u][0] = lds128(sp); kvr[u][1] = lds128(sp + 16); kvr[u][2] = lds128(sp + 32); }
      }
      bar_sync(1, 256);
#pragma unroll
      for (int u = 0; u < 2; u++) {
        const int it = tid + 256 * u, p = it / 192, rem = it - 192 * p, n = rem >> 2, tq = rem & 3;
        const int sh = (n < 40 ? (n >= 20) : (n & 1)) * 16;
        const uint32_t v[10] = {kvr[u][0].x, kvr[u][0].y, kvr[u][0].z, kvr[u][0].w, kvr[u][1].x, kvr[u][1].y, kvr[u][1].z, kvr[u][1].w, kvr[u][2].x, kvr[u][2].y};
        uint8_t* dst = sgen + OFF_MISC + p * 7680 + n * 32 + tq * 4;
        const int sw = ((n >> 2) & 1) << 4;
        if (it < 384) {
#pragma unroll
          for (int G = 0; G < 10; G++)
            *reinterpret_cast<uint32_t*>(dst + (G >> 1) * 1536 + (((G & 1) << 4) ^ sw)) = pack_bf16(__uint_as_float(v[G]), 0.f) << sh;
        }
      }
      fence_async_smem();
      bar_sync(1, 256);
      float o0[24], o1[24];
      wg_fence();
#pragma unroll
      for (int g = 0; g < 5; g++) {
        if (g == 0) mma_rs48_k_z(o0, fr[g], make_desc(sb16, OFF_MISC, 16, 256, 3));
        else mma_rs48_k(o0, fr[g], make_desc(sb16, OFF_MISC + g * 1536, 16, 256, 3));
      }
#pragma unroll
      for (int g = 0; g < 5; g++) {
        if (g == 0) mma_rs48_k_z(o1, fr[5], make_desc(sb16, OFF_MISC + 7680, 16, 256, 3));
        else mma_rs48_k(o1, fr[5 + g], make_desc(sb16, OFF_MISC + 7680 + g * 1536, 16, 256, 3));
      }
      wg_commit();
      wg_wait<0>();
      fence_regs(o0); fence_regs(o1);
      signal(B_MFREE);
#pragma unroll
      for (int r = 0; r < 2; r++) {
        const float a0 = __fdividef(st_g[r], o0[20 + 2 * r] + 1e-6f), a1 = __fdividef(st_g[r], o0[21 + 2 * r] + 1e-6f);
        const float b0 = __fdividef(st_g[r], o1[20 + 2 * r] + 1e-6f), b1 = __fdividef(st_g[r], o1[21 + 2 * r] + 1e-6f);
        const float am = t < 2 ? a0 : a1, bm = t < 2 ? b0 : b1;
#pragma unroll
        for (int g = 0; g < 5; g++) {
          const float sa = g < 2 ? a0 : (g == 2 ? am : a1), sb2 = g < 2 ? b0 : (g == 2 ? bm : b1);
          of[g >> 1][(g & 1) * 2 + r] = pack_bf16(o0[4 * g + 2 * r] * sa, o0[4 * g + 2 * r + 1] * sa);
          of[(5 + g) >> 1][((5 + g) & 1) * 2 + r] = pack_bf16(o1[4 * g + 2 * r] * sb2, o1[4 * g + 2 * r + 1] * sb2);
        }
      }
    }
    TSTAMP(9);

    uint32_t hf[12][4];
    {
      float acc[96];
      zero_regs(acc);
      uint32_t pa = 0, pb = 0;
#pragma unroll 1
      for (int k = 0; k < 10; k++) {
        mbar_wait(fullA + 8 * ra.idx, ra.phase);
        if (tid == 0) TRACE(52 + k);
        if ((k & 1) == 0) mbar_wait(fullB + 8 * rb.idx, rb.phase);
        if (tid == 0) TRACE(84 + k);
        if (k == 0) TSTAMP(10);
        const uint32_t a0 = sb16 + ((OFF_A + ra.idx * SLOT_A + wg * 8192) >> 4);
        const uint32_t b0 = sb16 + ((OFF_B + rb.idx * SLOT_B + (k & 1) * 24576) >> 4);
        wg_fence();
#pragma unroll
        for (int kk = 0; kk < 4; kk++) {
          mma_ss192(acc, make_desc(a0, kk * 32, 16, 1024, 1), make_desc(b0, kk * 2048, 8192, 1024, 1));
          if (kk == 0) {
            wg_commit();
            if (k > 0) {
              wg_wait<1>();
              release(emptyA + 8 * pa);
              if ((k & 1) == 0) releaseB(emptyB + 8 * pb);
            }
          }
        }
        wg_commit();
        pa = ra.idx; pb = rb.idx;
        ra.next<NA>();
        if (k & 1) rb.next<NB>();
      }
      float rs[2], mm[2];
      mbar_wait(bars + 8 * B_ST1, 0);
#pragma unroll
      for (int r = 0; r < 2; r++) {
        const uint4 su = lds128(sb + OFF_MISC + (rloc + 8 * r) * 64 + t * 16);
        const float m0 = __uint_as_float(su.x), m1 = __uint_as_float(su.z);
        float mu = m0 + m1;
        mu += __shfl_xor_sync(0xffffffffu, mu, 1); mu += __shfl_xor_sync(0xffffffffu, mu, 2);
        mu *= 0.125f;
        const float d0 = m0 - mu, d1 = m1 - mu;
        float q = __uint_as_float(su.y) + __uint_as_float(su.w) + 80.f * (d0 * d0 + d1 * d1);
        q += __shfl_xor_sync(0xffffffffu, q, 1); q += __shfl_xor_sync(0xffffffffu, q, 2);
        rs[r] = rsqrtf(q * (1.f / D_) + 1e-5f);
        mm[r] = -mu * rs[r];
      }
      wg_wait<0>();
      fence_regs(acc);
      releaseB(emptyB + 8 * pb);
      release(bars + 8 * B_PEER);
      TSTAMP(11);
      const float hs0 = 0.5f - 0.5f * st_g[0], hs1 = 0.5f - 0.5f * st_g[1];
#pragma unroll
      for (int g = 0; g < 24; g++) {
        const float2 cs = *reinterpret_cast<const float2*>(s_cs + 80 + 8 * g + 2 * t);
        const float v0 = gelu_s(fmaf(acc[4 * g], rs[0], mm[0] * cs.x), hs0), v1 = gelu_s(fmaf(acc[4 * g + 1], rs[0], mm[0] * cs.y), hs0);
        const float v2 = gelu_s(fmaf(acc[4 * g + 2], rs[1], mm[1] * cs.x), hs1), v3 = gelu_s(fmaf(acc[4 * g + 3], rs[1], mm[1] * cs.y), hs1);
        hf[g >> 1][(g & 1) * 2] = pack_bf16(v0, v1);
        hf[g >> 1][(g & 1) * 2 + 1] = pack_bf16(v2, v3);
      }
    }
    TSTAMP(12);

    {
      float acc[80], kp[40];
      uint32_t sn[20], kb[20];
      const uint32_t peer = map_peer(sb, rank ^ 1);
      const uint32_t tag = lds32(sb + OFF_BAR + 8 * NBAR);
      const uint4* gp = g_part + (size_t)(i * 8 + j) * 3840 + tid;
      uint4 pv4[15];
      Ring r4{0, 0};
      auto add8 = [&](int q, const uint4 v) {
        float* d = &kp[8 * q];
        d[0] += bf_lo(v.x); d[1] += bf_hi(v.x); d[2] += bf_lo(v.y); d[3] += bf_hi(v.y);
        d[4] += bf_lo(v.z); d[5] += bf_hi(v.z); d[6] += bf_lo(v.w); d[7] += bf_hi(v.w);
      };
      auto send = [&](int c) {
        const uint32_t dso = peer + OFF_DS + (c & 1) * 20480 + tid * 16, dsb = peer + OFF_BAR + 8 * (B_DSR + 2 * c + wg);
#pragma unroll
        for (int q = 0; q < 5; q++) st_async16(dso + q * 4096, sn[4 * q], sn[4 * q + 1], sn[4 * q + 2], sn[4 * q + 3], dsb);
      };
      auto finish = [&](int c) {
        mbar_wait(bars + 8 * (B_DSR + 2 * c + wg), 0);
        uint4* dst = g_part + (size_t)((i * 8 + ((j + 2 * c + 2) & 7)) * 3 + c) * 1280 + tid;
#pragma unroll
        for (int q = 0; q < 5; q++) {
          const uint4 v = lds128(sb + OFF_DS + (c & 1) * 20480 + tid * 16 + q * 4096);
          st_relaxed16(dst + q * 256, (add_bf2(v.x, kb[4 * q]) & ~1u) | tag, add_bf2(v.y, kb[4 * q + 1]),
                       add_bf2(v.z, kb[4 * q + 2]), add_bf2(v.w, kb[4 * q + 3]));
        }
      };
#pragma unroll
      for (int e = 0; e < 20; e++) sn[e] = kb[e] = 0u;
      auto chunk = [&](const int c, auto last_c) {
        constexpr bool LAST = decltype(last_c)::value;
        const uint32_t e0 = r4.idx;
        auto rel = [&](int u) { const uint32_t e = e0 + u; releaseB(bars + 8 * (B_EMPTY4 + (e >= NU4 ? e - NU4 : e))); };
#pragma unroll
        for (int u = 0; u < 4; u++) {
          mbar_wait(bars + 8 * (B_FULL4 + r4.idx), r4.phase);
          const uint32_t b0 = sb16 + ((OFF_B + r4.idx * UNIT4) >> 4);
          TRS(c * 16 + u * 3);
          wg_fence();
#pragma unroll
          for (int s = 0; s < (u < 3 ? 4 : 5); s++) {
            const uint64_t db = make_desc(b0, s * 1024, u < 3 ? 4096 : 5120, 512, 2);
            if (u == 0 && s == 0) mma_rs160_n_z(acc, hf[0], db);
            else if (u < 3) mma_rs160_n(acc, hf[(4 * u + s) % 12], db);
            else mma_rs160_n(acc, of[s], db);
          }
          wg_commit();
          TRS(c * 16 + u * 3 + 1);
          r4.next<NU4>();
          if (u > 0 && !LAST) { wg_wait<1>(); rel(u - 1); }
          if (u == 0 && c > 0) send(c - 1);
          if (u == 1 && c == 0) { if (wg == 0) bar_arrive(2, 256); mbar_wait(bars + 8 * B_PEER, 0); }
          if (u == (LAST ? 1 : 2) && c > 0) finish(c - 1);
          TRS(c * 16 + u * 3 + 2);
        }
        if (LAST) {
#pragma unroll
          for (int q = 0; q < 10; q++) pv4[q] = ld_relaxed16(gp + q * 256);
        }
        wg_wait<0>();
        fence_regs(acc);
        if (!LAST) rel(3);
        TRS(c * 16 + 12);
        if (rank) {
#pragma unroll
          for (int e = 0; e < 20; e++) { sn[e] = pack_bf16(acc[2 * e], acc[2 * e + 1]); kb[e] = pack_bf16(acc[40 + 2 * e], acc[41 + 2 * e]); }
        } else {
#pragma unroll
          for (int e = 0; e < 20; e++) { kb[e] = pack_bf16(acc[2 * e], acc[2 * e + 1]); sn[e] = pack_bf16(acc[40 + 2 * e], acc[41 + 2 * e]); }
        }
#pragma unroll
        for (int e = 0; e < 20; e++) asm volatile("" : "+r"(sn[e]), "+r"(kb[e]));
        TRS(c * 16 + 13);
      };
      if (wg == 1) bar_sync(2, 256);
#pragma unroll 1
      for (int c = 0; c < 3; c++) chunk(c, BoolC<false>{});
      chunk(3, BoolC<true>{});
#pragma unroll
      for (int q = 10; q < 15; q++) pv4[q] = ld_relaxed16(gp + q * 256);
      send(3);
      TSTAMP(13);
      {
        const float w0 = 1.f - st_g[0], w1s = 1.f - st_g[1];
#pragma unroll
        for (int g = 0; g < 10; g++) {
          kp[4 * g] = fmaf(w0, bf_lo(xv[0][g]), rank ? acc[40 + 4 * g] : acc[4 * g]);
          kp[4 * g + 1] = fmaf(w0, bf_hi(xv[0][g]), rank ? acc[41 + 4 * g] : acc[4 * g + 1]);
          kp[4 * g + 2] = fmaf(w1s, bf_lo(xv[1][g]), rank ? acc[42 + 4 * g] : acc[4 * g + 2]);
          kp[4 * g + 3] = fmaf(w1s, bf_hi(xv[1][g]), rank ? acc[43 + 4 * g] : acc[4 * g + 3]);
        }
      }
      mbar_wait(bars + 8 * (B_DSR + 6 + wg), 0);
#pragma unroll
      for (int q = 0; q < 5; q++) add8(q, lds128(sb + OFF_DS + 20480 + tid * 16 + q * 4096));
#pragma unroll 1
      for (uint32_t n = 0; n < (WAIT_LIMIT >> 4); n++) {
        uint32_t m = 0u;
#pragma unroll
        for (int q = 0; q < 15; q++) {
          const uint32_t bad = (pv4[q].x ^ tag) & 1u;
          m |= bad;
          if (bad) pv4[q] = ld_relaxed16(gp + q * 256);
        }
        if (m == 0u) break;
      }
      TSTAMP(14);
#pragma unroll
      for (int q = 0; q < 15; q++) add8(q % 5, pv4[q]);
      __syncwarp();
#pragma unroll
      for (int s = 0; s < 5; s++)
        stsm4(sb + OFF_OUT + stg_lane + s * 32, pack_bf16(kp[8 * s], kp[8 * s + 1]), pack_bf16(kp[8 * s + 2], kp[8 * s + 3]),
              pack_bf16(kp[8 * s + 4], kp[8 * s + 5]), pack_bf16(kp[8 * s + 6], kp[8 * s + 7]));
      fence_async_smem();
      __syncwarp();
      if (lane == 0) {
        tma2d_store(&maps.st_out, sb + OFF_OUT + warp * 2560, 80 * j, 128 * i + 16 * warp);
        bulk_commit();
      }
      if (lane == 0) bulk_wait_read();
    }
    TSTAMP(15);
    if (tid == 0) asm volatile("red.relaxed.gpu.global.add.u32 [%0], 1;" ::"l"(g_flags + FL_DONE * 32) : "memory");
  }
}

namespace {
typedef CUresult (*EncodeFn)(CUtensorMap*, CUtensorMapDataType, cuuint32_t, void*, const cuuint64_t*, const cuuint64_t*,
                             const cuuint32_t*, const cuuint32_t*, CUtensorMapInterleave, CUtensorMapSwizzle,
                             CUtensorMapL2promotion, CUtensorMapFloatOOBfill);

void encode(EncodeFn fn, CUtensorMap* m, const void* ptr, int rank, const cuuint64_t* dims, const cuuint64_t* strides,
            const cuuint32_t* box, CUtensorMapSwizzle swz) {
  cuuint32_t es[5] = {1, 1, 1, 1, 1};
  fn(m, CU_TENSOR_MAP_DATA_TYPE_BFLOAT16, rank, const_cast<void*>(ptr), dims, strides, box, es, CU_TENSOR_MAP_INTERLEAVE_NONE,
     swz, CU_TENSOR_MAP_L2_PROMOTION_L2_128B, CU_TENSOR_MAP_FLOAT_OOB_FILL_NONE);
}
}

extern "C" void kernel_launch(void* const* d_in, const int* in_sizes, int n_in, void* d_out, int out_size) {
  (void)in_sizes; (void)n_in; (void)out_size;
  const __nv_bfloat16* x = (const __nv_bfloat16*)d_in[0];
  const __nv_bfloat16* wqkv = (const __nv_bfloat16*)d_in[1];
  const __nv_bfloat16* wphi = (const __nv_bfloat16*)d_in[2];
  const __nv_bfloat16* wo = (const __nv_bfloat16*)d_in[3];
  const __nv_bfloat16* w1 = (const __nv_bfloat16*)d_in[5];
  const __nv_bfloat16* w2 = (const __nv_bfloat16*)d_in[6];
  const __nv_bfloat16* w3 = (const __nv_bfloat16*)d_in[7];
  const __nv_bfloat16* w4 = (const __nv_bfloat16*)d_in[8];
  const __nv_bfloat16* gate_w = (const __nv_bfloat16*)d_in[9];

  static EncodeFn enc = nullptr;
  static void *pHs = nullptr, *pX1 = nullptr;
  if (!enc) {
    cudaDriverEntryPointQueryResult qr;
    cudaGetDriverEntryPoint("cuTensorMapEncodeTiled", (void**)&enc, cudaEnableDefault, &qr);
    cudaGetSymbolAddress(&pHs, g_Hs);
    cudaGetSymbolAddress(&pX1, g_X1);
    cudaFuncSetAttribute(fused_kernel, cudaFuncAttributeMaxDynamicSharedMemorySize, SMEM_BYTES);
  }
  Maps m;
  {
    cuuint64_t dims[2] = {D_, S_}, str[1] = {D_ * 2};
    cuuint32_t boxh[2] = {64, 64};
    encode(enc, &m.x, x, 2, dims, str, boxh, CU_TENSOR_MAP_SWIZZLE_128B);
    encode(enc, &m.hs, (const char*)pHs + 2 * D_ * 2, 2, dims, str, boxh, CU_TENSOR_MAP_SWIZZLE_128B);
    encode(enc, &m.x1, pX1, 2, dims, str, boxh, CU_TENSOR_MAP_SWIZZLE_128B);
    cuuint32_t boxs[2] = {80, 64};
    cuuint64_t dimsp[2] = {D_, S_ + 4};
    encode(enc, &m.st_h, pHs, 2, dimsp, str, boxs, CU_TENSOR_MAP_SWIZZLE_NONE);
    encode(enc, &m.st_x1, pX1, 2, dims, str, boxs, CU_TENSOR_MAP_SWIZZLE_NONE);
    cuuint32_t boxr[2] = {80, 16};
    encode(enc, &m.st_out, d_out, 2, dims, str, boxr, CU_TENSOR_MAP_SWIZZLE_NONE);
    encode(enc, &m.xr, x, 2, dims, str, boxr, CU_TENSOR_MAP_SWIZZLE_NONE);
  }
  {
    cuuint64_t dims[3] = {80, D_, 8}, str[2] = {D_ * 2, 160};
    cuuint32_t boxm[3] = {64, 64, 1}, boxr[3] = {16, 64, 1};
    encode(enc, &m.w1m, w1, 3, dims, str, boxm, CU_TENSOR_MAP_SWIZZLE_128B);
    encode(enc, &m.w1r, w1, 3, dims, str, boxr, CU_TENSOR_MAP_SWIZZLE_32B);
  }
  {
    cuuint64_t dims[4] = {80, D_, 3, 8}, str[3] = {3 * D_ * 2, D_ * 2, 160};
    cuuint32_t boxm[4] = {64, 64, 3, 1}, boxr[4] = {16, 64, 3, 1};
    encode(enc, &m.qm, wqkv, 4, dims, str, boxm, CU_TENSOR_MAP_SWIZZLE_128B);
    encode(enc, &m.qr, wqkv, 4, dims, str, boxr, CU_TENSOR_MAP_SWIZZLE_32B);
  }
  {
    cuuint64_t dims[3] = {16, D_, 40}, str[2] = {D_ * 2, 32};
    cuuint32_t box2[3] = {16, 64, 5};
    encode(enc, &m.w2, w2, 3, dims, str, box2, CU_TENSOR_MAP_SWIZZLE_32B);
  }
  {
    cuuint64_t dims[3] = {32, D_, 20}, dims4[3] = {32, F_, 20}, str[2] = {D_ * 2, 64};
    cuuint32_t box4[3] = {32, 64, 5}, boxo[3] = {32, 80, 5};
    encode(enc, &m.w4, w4, 3, dims4, str, box4, CU_TENSOR_MAP_SWIZZLE_64B);
    encode(enc, &m.wo, wo, 3, dims, str, boxo, CU_TENSOR_MAP_SWIZZLE_64B);
  }
  {
    cuuint64_t dims[3] = {64, D_, 24}, str[2] = {F_ * 2, 128};
    cuuint32_t box[3] = {64, 64, 3};
    encode(enc, &m.w3, w3, 3, dims, str, box, CU_TENSOR_MAP_SWIZZLE_128B);
  }
  fused_kernel<<<NCTA, 384, SMEM_BYTES, cudaStreamPerThread>>>(m, x, wqkv, wphi, w1, w2, w3, w4, wo, gate_w);
}
```

```cpp
#include <cuda_runtime.h>
#include <cuda_bf16.h>
#include <cuda.h>
#include <stdint.h>

namespace {

constexpr int S_ = 2048, D_ = 640, F_ = 1536;
constexpr int NCTA = 128;
constexpr int KV_PAIR = 40 * 48 + 96;
constexpr int KV_J = 2 * KV_PAIR;

constexpr int SLOT_B = 49152, NB = 3;
constexpr int SLOT_A = 16384, NA = 4;
constexpr int OFF_B = 0;
constexpr int OFF_A = OFF_B + NB * SLOT_B;
constexpr int OFF_STG = OFF_A + 2 * SLOT_A;
constexpr int OFF_MISC = OFF_A + NA * SLOT_A;
constexpr int OFF_XST = OFF_MISC + 13312;
constexpr int OFF_CS = OFF_MISC + 16384;
constexpr int OFF_BAR = OFF_CS + 1088;
constexpr int SMEM_BYTES = OFF_BAR + 512 + 512;
constexpr int B_FULLA = 0, B_FULLB = 4, B_CS = 7, B_XR = 8, B_KV = 9, B_ST1 = 10, B_FULL4 = 11  , B_DSR = 16  ,
              B_EMPTYB = 26  , B_SIGP = 29, B_SIGH = 30, B_SIGKV = 31, B_SIGX1 = 32, B_MFREE = 33, B_EMPTY4 = 34  ,
              B_EMPTYA = 39  , B_PEER = 43, B_PEER2 = 44, NBAR = 45;
constexpr int SPARE = 40960;
constexpr int UNIT4 = 25600, NU4 = 5;
constexpr int OFF_DS = OFF_A, OFF_OUT = OFF_A + 40960;

constexpr int FL_DONE = 0, FL_H = 1  , FL_X1 = FL_H + 32, FL_KV = FL_X1 + 16, FL_CS = FL_KV + 8, FL_CS3 = FL_CS + 8, FL_ST = FL_CS3 + 8;
constexpr int FL_COUNT = FL_ST + 16;
constexpr int ACC_FLOATS = 8 * KV_J + D_ + F_;

struct Maps {
  CUtensorMap x, w1m, w1r, qm, qr, hs, w2, x1, w3, w4, wo, xr;
};

}

__device__ __align__(1024) __nv_bfloat16 g_Hs[(S_ + 4) * D_];
__device__ __align__(1024) __nv_bfloat16 g_X1[S_ * D_];
__device__ __align__(128) float g_acc[2][ACC_FLOATS];
__device__ __align__(128) float4 g_xstat[S_];
__device__ __align__(128) float2 g_st1[S_ * 8];
__device__ __align__(128) uint4 g_part[16 * 8 * 3 * 1280];
__device__ __align__(128) unsigned g_flags[FL_COUNT * 32];
#define TSTAMP(n) do {} while (0)
#define TSTAMPX(n) do {} while (0)
#define TRACE(n) do {} while (0)
#define TRS(n) do {} while (0)

namespace {

__device__ __forceinline__ long long gtime() { long long t; asm volatile("mov.u64 %0, %%globaltimer;" : "=l"(t)); return t; }
__device__ __forceinline__ uint32_t smem_u32(const void* p) { return (uint32_t)__cvta_generic_to_shared(p); }
__device__ __forceinline__ void mbar_init(uint32_t bar, int cnt) {
  asm volatile("mbarrier.init.shared::cta.b64 [%0], %1;" ::"r"(bar), "r"(cnt) : "memory");
}
__device__ __forceinline__ void mbar_expect_tx(uint32_t bar, int bytes) {
  asm volatile("mbarrier.arrive.expect_tx.shared::cta.b64 _, [%0], %1;" ::"r"(bar), "r"(bytes) : "memory");
}
__device__ __forceinline__ void mbar_arrive_cta(uint32_t bar, uint32_t cta) {
  asm volatile("{\n.reg .b32 ra;\nmapa.shared::cluster.u32 ra, %0, %1;\nmbarrier.arrive.shared::cluster.b64 _, [ra];\n}"
               ::"r"(bar), "r"(cta) : "memory");
}
__device__ __forceinline__ uint32_t mbar_try(uint32_t bar, uint32_t parity) {
  uint32_t ok;
  asm volatile("{\n.reg .pred p;\nmbarrier.try_wait.parity.shared::cta.b64 p, [%1], %2;\nselp.u32 %0, 1, 0, p;\n}"
               : "=r"(ok) : "r"(bar), "r"(parity) : "memory");
  return ok;
}
constexpr uint32_t WAIT_LIMIT = 1u << 22;
__device__ __forceinline__ void mbar_wait(uint32_t bar, uint32_t parity) {
  uint32_t n = 0;
  while (!mbar_try(bar, parity) && ++n < WAIT_LIMIT) {}
}
__device__ __forceinline__ unsigned ld_acquire(const unsigned* p) {
  unsigned v;
  asm volatile("ld.acquire.gpu.global.u32 %0, [%1];" : "=r"(v) : "l"(p) : "memory");
  return v;
}
__device__ __forceinline__ void flag_wait(int idx, unsigned target) {
  const unsigned* p = g_flags + idx * 32;
  uint32_t n = 0;
  while ((int)(ld_acquire(p) - target) < 0 && ++n < (WAIT_LIMIT >> 4)) {}
}
__device__ __forceinline__ void flag_add(int idx) {
  asm volatile("red.release.gpu.global.add.u32 [%0], 1;" ::"l"(g_flags + idx * 32) : "memory");
}
__device__ __forceinline__ void flag_add_relaxed(int idx) {
  asm volatile("red.relaxed.gpu.global.add.u32 [%0], 1;" ::"l"(g_flags + idx * 32) : "memory");
}
__device__ __forceinline__ uint32_t mbar_test(uint32_t bar, uint32_t parity) {
  uint32_t ok;
  asm volatile("{\n.reg .pred p;\nmbarrier.test_wait.parity.shared::cta.b64 p, [%1], %2;\nselp.u32 %0, 1, 0, p;\n}"
               : "=r"(ok) : "r"(bar), "r"(parity) : "memory");
  return ok;
}
__device__ __forceinline__ uint32_t lds32(uint32_t a) {
  uint32_t v;
  asm volatile("ld.shared.u32 %0, [%1];" : "=r"(v) : "r"(a) : "memory");
  return v;
}
__device__ __forceinline__ void mbar_arrive(uint32_t bar) {
  asm volatile("mbarrier.arrive.shared::cta.b64 _, [%0];" ::"r"(bar) : "memory");
}
__device__ __forceinline__ void fence_async_glb() { asm volatile("fence.proxy.async.global;" ::: "memory"); }
__device__ __forceinline__ void fence_async_smem() { asm volatile("fence.proxy.async.shared::cta;" ::: "memory"); }
__device__ __forceinline__ void bar_sync(int id, int n) { asm volatile("bar.sync %0, %1;" ::"r"(id), "r"(n) : "memory"); }

__device__ __forceinline__ void tma2d(uint32_t dst, const CUtensorMap* m, uint32_t bar, int c0, int c1) {
  asm volatile("cp.async.bulk.tensor.2d.shared::cluster.global.mbarrier::complete_tx::bytes [%0], [%1, {%3, %4}], [%2];"
               ::"r"(dst), "l"(m), "r"(bar), "r"(c0), "r"(c1) : "memory");
}
__device__ __forceinline__ void tma2d_mc(uint32_t dst, const CUtensorMap* m, uint32_t bar, int c0, int c1) {
  asm volatile("cp.async.bulk.tensor.2d.shared::cluster.global.mbarrier::complete_tx::bytes.multicast::cluster"
               " [%0], [%1, {%3, %4}], [%2], %5;"
               ::"r"(dst), "l"(m), "r"(bar), "r"(c0), "r"(c1), "h"((uint16_t)3) : "memory");
}
__device__ __forceinline__ void tma3d(uint32_t dst, const CUtensorMap* m, uint32_t bar, int c0, int c1, int c2) {
  asm volatile("cp.async.bulk.tensor.3d.shared::cluster.global.mbarrier::complete_tx::bytes [%0], [%1, {%3, %4, %5}], [%2];"
               ::"r"(dst), "l"(m), "r"(bar), "r"(c0), "r"(c1), "r"(c2) : "memory");
}
__device__ __forceinline__ void tma4d(uint32_t dst, const CUtensorMap* m, uint32_t bar, int c0, int c1, int c2, int c3) {
  asm volatile("cp.async.bulk.tensor.4d.shared::cluster.global.mbarrier::complete_tx::bytes [%0], [%1, {%3, %4, %5, %6}], [%2];"
               ::"r"(dst), "l"(m), "r"(bar), "r"(c0), "r"(c1), "r"(c2), "r"(c3) : "memory");
}
__device__ __forceinline__ void tma2d_store(const CUtensorMap* m, uint32_t src, int c0, int c1) {
  asm volatile("cp.async.bulk.tensor.2d.global.shared::cta.bulk_group [%0, {%2, %3}], [%1];"
               ::"l"(m), "r"(src), "r"(c0), "r"(c1) : "memory");
}
__device__ __forceinline__ void bulk_store(void* dst, uint32_t src, uint32_t bytes) {
  asm volatile("cp.async.bulk.global.shared::cta.bulk_group [%0], [%1], %2;" ::"l"(dst), "r"(src), "r"(bytes) : "memory");
}
__device__ __forceinline__ void bulk_load(uint32_t dst, const void* src, uint32_t bytes, uint32_t bar) {
  asm volatile("cp.async.bulk.shared::cluster.global.mbarrier::complete_tx::bytes [%0], [%1], %2, [%3];"
               ::"r"(dst), "l"(src), "r"(bytes), "r"(bar) : "memory");
}
__device__ __forceinline__ void bulk_commit() { asm volatile("cp.async.bulk.commit_group;" ::: "memory"); }
template <int N> __device__ __forceinline__ void bulk_wait() { asm volatile("cp.async.bulk.wait_group %0;" ::"n"(N) : "memory"); }
__device__ __forceinline__ void bulk_wait_read() { asm volatile("cp.async.bulk.wait_group.read 0;" ::: "memory"); }
__device__ __forceinline__ void bar_arrive(int id, int n) { asm volatile("bar.arrive %0, %1;" ::"r"(id), "r"(n) : "memory"); }
__device__ __forceinline__ uint4 lds128(uint32_t a) {
  uint4 v;
  asm volatile("ld.shared.v4.u32 {%0, %1, %2, %3}, [%4];" : "=r"(v.x), "=r"(v.y), "=r"(v.z), "=r"(v.w) : "r"(a) : "memory");
  return v;
}
__device__ __forceinline__ void sts128(uint32_t a, uint4 v) {
  asm volatile("st.shared.v4.u32 [%0], {%1, %2, %3, %4};" ::"r"(a), "r"(v.x), "r"(v.y), "r"(v.z), "r"(v.w) : "memory");
}
__device__ __forceinline__ uint4 ld_relaxed16(const uint4* p) {
  uint4 v;
  asm volatile("ld.relaxed.gpu.global.v4.u32 {%0, %1, %2, %3}, [%4];" : "=r"(v.x), "=r"(v.y), "=r"(v.z), "=r"(v.w) : "l"(p) : "memory");
  return v;
}
__device__ __forceinline__ void st_relaxed16(uint4* p, uint32_t a, uint32_t b, uint32_t c, uint32_t d) {
  asm volatile("st.relaxed.gpu.global.v4.u32 [%0], {%1, %2, %3, %4};" ::"l"(p), "r"(a), "r"(b), "r"(c), "r"(d) : "memory");
}
__device__ __forceinline__ uint32_t map_peer(uint32_t addr, uint32_t cta) {
  uint32_t r;
  asm("mapa.shared::cluster.u32 %0, %1, %2;" : "=r"(r) : "r"(addr), "r"(cta));
  return r;
}
__device__ __forceinline__ void st_async16(uint32_t addr, uint32_t a, uint32_t b, uint32_t c, uint32_t d, uint32_t bar) {
  asm volatile("st.async.weak.shared::cluster.mbarrier::complete_tx::bytes.v4.b32 [%0], {%1, %2, %3, %4}, [%5];"
               ::"r"(addr), "r"(a), "r"(b), "r"(c), "r"(d), "r"(bar) : "memory");
}
__device__ __forceinline__ void l2_prefetch(const void* p, uint32_t bytes) {
  asm volatile("cp.async.bulk.prefetch.L2.global [%0], %1;" ::"l"(p), "r"(bytes) : "memory");
}
__device__ __forceinline__ void prefetch_tmap(const CUtensorMap* m) {
  asm volatile("prefetch.tensormap [%0];" ::"l"(m) : "memory");
}
__device__ __forceinline__ uint64_t make_desc(uint32_t a16, uint32_t off, uint32_t lbo, uint32_t sbo, uint32_t swz) {
  const uint32_t lo = a16 + ((off >> 4) + ((lbo >> 4) << 16)), hi = (sbo >> 4) | (swz << 30);
  uint64_t d;
  asm("mov.b64 %0, {%1, %2};" : "=l"(d) : "r"(lo), "r"(hi));
  return d;
}
__device__ __forceinline__ void wg_fence() { asm volatile("wgmma.fence.sync.aligned;" ::: "memory"); }
__device__ __forceinline__ void wg_commit() { asm volatile("wgmma.commit_group.sync.aligned;" ::: "memory"); }
template <int N> __device__ __forceinline__ void wg_wait() { asm volatile("wgmma.wait_group.sync.aligned %0;" ::"n"(N) : "memory"); }
template <int N> __device__ __forceinline__ void fence_regs(float (&d)[N]) {
#pragma unroll
  for (int i = 0; i < N; i++) asm volatile("" : "+f"(d[i])::"memory");
}
template <int N> __device__ __forceinline__ void zero_regs(float (&d)[N]) {
#pragma unroll
  for (int i = 0; i < N; i++) d[i] = 0.f;
}
__device__ __forceinline__ uint32_t pack_bf16(float lo, float hi) {
  uint32_t r;
  asm("cvt.rn.bf16x2.f32 %0, %1, %2;" : "=r"(r) : "f"(hi), "f"(lo));
  return r;
}
__device__ __forceinline__ float bf_lo(uint32_t v) { return __uint_as_float(v << 16); }
__device__ __forceinline__ float bf_hi(uint32_t v) { return __uint_as_float(v & 0xffff0000u); }
__device__ __forceinline__ uint32_t max_bf2(uint32_t a, uint32_t b) {
  uint32_t r; asm("max.bf16x2 %0, %1, %2;" : "=r"(r) : "r"(a), "r"(b)); return r;
}
__device__ __forceinline__ uint32_t min_bf2(uint32_t a, uint32_t b) {
  uint32_t r; asm("min.bf16x2 %0, %1, %2;" : "=r"(r) : "r"(a), "r"(b)); return r;
}
__device__ __forceinline__ uint32_t add_bf2(uint32_t a, uint32_t b) {
  uint32_t r; asm("add.rn.bf16x2 %0, %1, %2;" : "=r"(r) : "r"(a), "r"(b)); return r;
}
__device__ __forceinline__ float ex2(float x) { float r; asm("ex2.approx.ftz.f32 %0, %1;" : "=f"(r) : "f"(x)); return r; }
__device__ __forceinline__ float rcp(float x) { float r; asm("rcp.approx.ftz.f32 %0, %1;" : "=f"(r) : "f"(x)); return r; }
__device__ __forceinline__ float tanh_ap(float x) { float r; asm("tanh.approx.f32 %0, %1;" : "=f"(r) : "f"(x)); return r; }
__device__ __forceinline__ float gelu_s(float x, float hs) {
  float u = x * fmaf(x * x, 0.0356774081f, 0.7978845608f);
  float hx = x * hs;
  return fmaf(hx, tanh_ap(u), hx);
}
__device__ __forceinline__ void stsm4(uint32_t addr, uint32_t r0, uint32_t r1, uint32_t r2, uint32_t r3) {
  asm volatile("stmatrix.sync.aligned.m8n8.x4.shared.b16 [%0], {%1, %2, %3, %4};"
               ::"r"(addr), "r"(r0), "r"(r1), "r"(r2), "r"(r3) : "memory");
}
__device__ __forceinline__ void red_add4(float* p, float a, float b, float c, float d) {
  asm volatile("red.global.add.v4.f32 [%0], {%1, %2, %3, %4};" ::"l"(p), "f"(a), "f"(b), "f"(c), "f"(d) : "memory");
}

__device__ __forceinline__ void mma_ss256(float (&d)[128], uint64_t descA, uint64_t descB) {
  asm volatile("wgmma.mma_async.sync.aligned.m64n256k16.f32.bf16.bf16 {"
      "%0, %1, %2, %3, %4, %5, %6, %7, %8, %9, %10, %11, %12, %13, %14, %15, "
      "%16, %17, %18, %19, %20, %21, %22, %23, %24, %25, %26, %27, %28, %29, %30, %31, "
      "%32, %33, %34, %35, %36, %37, %38, %39, %40, %41, %42, %43, %44, %45, %46, %47, "
      "%48, %49, %50, %51, %52, %53, %54, %55, %56, %57, %58, %59, %60, %61, %62, %63, "
      "%64, %65, %66, %67, %68, %69, %70, %71, %72, %73, %74, %75, %76, %77, %78, %79, "
      "%80, %81, %82, %83, %84, %85, %86, %87, %88, %89, %90, %91, %92, %93, %94, %95, "
      "%96, %97, %98, %99, %100, %101, %102, %103, %104, %105, %106, %107, %108, %109, %110, %111, "
      "%112, %113, %114, %115, %116, %117, %118, %119, %120, %121, %122, %123, %124, %125, %126, %127"
      "}, %128, %129, 1, 1, 1, 0, 1;\n"
      : "+f"(d[0]), "+f"(d[1]), "+f"(d[2]), "+f"(d[3]), "+f"(d[4]), "+f"(d[5]), "+f"(d[6]), "+f"(d[7]),
        "+f"(d[8]), "+f"(d[9]), "+f"(d[10]), "+f"(d[11]), "+f"(d[12]), "+f"(d[13]), "+f"(d[14]), "+f"(d[15]),
        "+f"(d[16]), "+f"(d[17]), "+f"(d[18]), "+f"(d[19]), "+f"(d[20]), "+f"(d[21]), "+f"(d[22]), "+f"(d[23]),
        "+f"(d[24]), "+f"(d[25]), "+f"(d[26]), "+f"(d[27]), "+f"(d[28]), "+f"(d[29]), "+f"(d[30]), "+f"(d[31]),
        "+f"(d[32]), "+f"(d[33]), "+f"(d[34]), "+f"(d[35]), "+f"(d[36]), "+f"(d[37]), "+f"(d[38]), "+f"(d[39]),
        "+f"(d[40]), "+f"(d[41]), "+f"(d[42]), "+f"(d[43]), "+f"(d[44]), "+f"(d[45]), "+f"(d[46]), "+f"(d[47]),
        "+f"(d[48]), "+f"(d[49]), "+f"(d[50]), "+f"(d[51]), "+f"(d[52]), "+f"(d[53]), "+f"(d[54]), "+f"(d[55]),
        "+f"(d[56]), "+f"(d[57]), "+f"(d[58]), "+f"(d[59]), "+f"(d[60]), "+f"(d[61]), "+f"(d[62]), "+f"(d[63]),
        "+f"(d[64]), "+f"(d[65]), "+f"(d[66]), "+f"(d[67]), "+f"(d[68]), "+f"(d[69]), "+f"(d[70]), "+f"(d[71]),
        "+f"(d[72]), "+f"(d[73]), "+f"(d[74]), "+f"(d[75]), "+f"(d[76]), "+f"(d[77]), "+f"(d[78]), "+f"(d[79]),
        "+f"(d[80]), "+f"(d[81]), "+f"(d[82]), "+f"(d[83]), "+f"(d[84]), "+f"(d[85]), "+f"(d[86]), "+f"(d[87]),
        "+f"(d[88]), "+f"(d[89]), "+f"(d[90]), "+f"(d[91]), "+f"(d[92]), "+f"(d[93]), "+f"(d[94]), "+f"(d[95]),
        "+f"(d[96]), "+f"(d[97]), "+f"(d[98]), "+f"(d[99]), "+f"(d[100]), "+f"(d[101]), "+f"(d[102]), "+f"(d[103]),
        "+f"(d[104]), "+f"(d[105]), "+f"(d[106]), "+f"(d[107]), "+f"(d[108]), "+f"(d[109]), "+f"(d[110]), "+f"(d[111]),
        "+f"(d[112]), "+f"(d[113]), "+f"(d[114]), "+f"(d[115]), "+f"(d[116]), "+f"(d[117]), "+f"(d[118]), "+f"(d[119]),
        "+f"(d[120]), "+f"(d[121]), "+f"(d[122]), "+f"(d[123]), "+f"(d[124]), "+f"(d[125]), "+f"(d[126]), "+f"(d[127])
      : "l"(descA), "l"(descB));
}
__device__ __forceinline__ void mma_ss256_p(float (&d)[128], uint64_t descA, uint64_t descB, int acc) {
  asm volatile("{\n.reg .pred p;\nsetp.ne.b32 p, %130, 0;\n"
      "wgmma.mma_async.sync.aligned.m64n256k16.f32.bf16.bf16 {"
      "%0, %1, %2, %3, %4, %5, %6, %7, %8, %9, %10, %11, %12, %13, %14, %15, "
      "%16, %17, %18, %19, %20, %21, %22, %23, %24, %25, %26, %27, %28, %29, %30, %31, "
      "%32, %33, %34, %35, %36, %37, %38, %39, %40, %41, %42, %43, %44, %45, %46, %47, "
      "%48, %49, %50, %51, %52, %53, %54, %55, %56, %57, %58, %59, %60, %61, %62, %63, "
      "%64, %65, %66, %67, %68, %69, %70, %71, %72, %73, %74, %75, %76, %77, %78, %79, "
      "%80, %81, %82, %83, %84, %85, %86, %87, %88, %89, %90, %91, %92, %93, %94, %95, "
      "%96, %97, %98, %99, %100, %101, %102, %103, %104, %105, %106, %107, %108, %109, %110, %111, "
      "%112, %113, %114, %115, %116, %117, %118, %119, %120, %121, %122, %123, %124, %125, %126, %127"
      "}, %128, %129, p, 1, 1, 0, 1;\n}\n"
      : "+f"(d[0]), "+f"(d[1]), "+f"(d[2]), "+f"(d[3]), "+f"(d[4]), "+f"(d[5]), "+f"(d[6]), "+f"(d[7]),
        "+f"(d[8]), "+f"(d[9]), "+f"(d[10]), "+f"(d[11]), "+f"(d[12]), "+f"(d[13]), "+f"(d[14]), "+f"(d[15]),
        "+f"(d[16]), "+f"(d[17]), "+f"(d[18]), "+f"(d[19]), "+f"(d[20]), "+f"(d[21]), "+f"(d[22]), "+f"(d[23]),
        "+f"(d[24]), "+f"(d[25]), "+f"(d[26]), "+f"(d[27]), "+f"(d[28]), "+f"(d[29]), "+f"(d[30]), "+f"(d[31]),
        "+f"(d[32]), "+f"(d[33]), "+f"(d[34]), "+f"(d[35]), "+f"(d[36]), "+f"(d[37]), "+f"(d[38]), "+f"(d[39]),
        "+f"(d[40]), "+f"(d[41]), "+f"(d[42]), "+f"(d[43]), "+f"(d[44]), "+f"(d[45]), "+f"(d[46]), "+f"(d[47]),
        "+f"(d[48]), "+f"(d[49]), "+f"(d[50]), "+f"(d[51]), "+f"(d[52]), "+f"(d[53]), "+f"(d[54]), "+f"(d[55]),
        "+f"(d[56]), "+f"(d[57]), "+f"(d[58]), "+f"(d[59]), "+f"(d[60]), "+f"(d[61]), "+f"(d[62]), "+f"(d[63]),
        "+f"(d[64]), "+f"(d[65]), "+f"(d[66]), "+f"(d[67]), "+f"(d[68]), "+f"(d[69]), "+f"(d[70]), "+f"(d[71]),
        "+f"(d[72]), "+f"(d[73]), "+f"(d[74]), "+f"(d[75]), "+f"(d[76]), "+f"(d[77]), "+f"(d[78]), "+f"(d[79]),
        "+f"(d[80]), "+f"(d[81]), "+f"(d[82]), "+f"(d[83]), "+f"(d[84]), "+f"(d[85]), "+f"(d[86]), "+f"(d[87]),
        "+f"(d[88]), "+f"(d[89]), "+f"(d[90]), "+f"(d[91]), "+f"(d[92]), "+f"(d[93]), "+f"(d[94]), "+f"(d[95]),
        "+f"(d[96]), "+f"(d[97]), "+f"(d[98]), "+f"(d[99]), "+f"(d[100]), "+f"(d[101]), "+f"(d[102]), "+f"(d[103]),
        "+f"(d[104]), "+f"(d[105]), "+f"(d[106]), "+f"(d[107]), "+f"(d[108]), "+f"(d[109]), "+f"(d[110]), "+f"(d[111]),
        "+f"(d[112]), "+f"(d[113]), "+f"(d[114]), "+f"(d[115]), "+f"(d[116]), "+f"(d[117]), "+f"(d[118]), "+f"(d[119]),
        "+f"(d[120]), "+f"(d[121]), "+f"(d[122]), "+f"(d[123]), "+f"(d[124]), "+f"(d[125]), "+f"(d[126]), "+f"(d[127])
      : "l"(descA), "l"(descB), "r"(acc));
}

__device__ __forceinline__ void mma_ss64(float (&d)[32], uint64_t descA, uint64_t descB) {
  asm volatile("wgmma.mma_async.sync.aligned.m64n64k16.f32.bf16.bf16 {"
      "%0, %1, %2, %3, %4, %5, %6, %7, %8, %9, %10, %11, %12, %13, %14, %15, "
      "%16, %17, %18, %19, %20, %21, %22, %23, %24, %25, %26, %27, %28, %29, %30, %31"
      "}, %32, %33, 1, 1, 1, 0, 1;\n"
      : "+f"(d[0]), "+f"(d[1]), "+f"(d[2]), "+f"(d[3]), "+f"(d[4]), "+f"(d[5]), "+f"(d[6]), "+f"(d[7]),
        "+f"(d[8]), "+f"(d[9]), "+f"(d[10]), "+f"(d[11]), "+f"(d[12]), "+f"(d[13]), "+f"(d[14]), "+f"(d[15]),
        "+f"(d[16]), "+f"(d[17]), "+f"(d[18]), "+f"(d[19]), "+f"(d[20]), "+f"(d[21]), "+f"(d[22]), "+f"(d[23]),
        "+f"(d[24]), "+f"(d[25]), "+f"(d[26]), "+f"(d[27]), "+f"(d[28]), "+f"(d[29]), "+f"(d[30]), "+f"(d[31])
      : "l"(descA), "l"(descB));
}
__device__ __forceinline__ void mma_ss64_p(float (&d)[32], uint64_t descA, uint64_t descB, int acc) {
  asm volatile("{\n.reg .pred p;\nsetp.ne.b32 p, %34, 0;\n"
      "wgmma.mma_async.sync.aligned.m64n64k16.f32.bf16.bf16 {"
      "%0, %1, %2, %3, %4, %5, %6, %7, %8, %9, %10, %11, %12, %13, %14, %15, "
      "%16, %17, %18, %19, %20, %21, %22, %23, %24, %25, %26, %27, %28, %29, %30, %31"
      "}, %32, %33, p, 1, 1, 0, 1;\n}\n"
      : "+f"(d[0]), "+f"(d[1]), "+f"(d[2]), "+f"(d[3]), "+f"(d[4]), "+f"(d[5]), "+f"(d[6]), "+f"(d[7]),
        "+f"(d[8]), "+f"(d[9]), "+f"(d[10]), "+f"(d[11]), "+f"(d[12]), "+f"(d[13]), "+f"(d[14]), "+f"(d[15]),
        "+f"(d[16]), "+f"(d[17]), "+f"(d[18]), "+f"(d[19]), "+f"(d[20]), "+f"(d[21]), "+f"(d[22]), "+f"(d[23]),
        "+f"(d[24]), "+f"(d[25]), "+f"(d[26]), "+f"(d[27]), "+f"(d[28]), "+f"(d[29]), "+f"(d[30]), "+f"(d[31])
      : "l"(descA), "l"(descB), "r"(acc));
}

__device__ __forceinline__ void mma_ss160(float (&d)[80], uint64_t descA, uint64_t descB) {
  asm volatile("wgmma.mma_async.sync.aligned.m64n160k16.f32.bf16.bf16 {"
      "%0, %1, %2, %3, %4, %5, %6, %7, %8, %9, %10, %11, %12, %13, %14, %15, "
      "%16, %17, %18, %19, %20, %21, %22, %23, %24, %25, %26, %27, %28, %29, %30, %31, "
      "%32, %33, %34, %35, %36, %37, %38, %39, %40, %41, %42, %43, %44, %45, %46, %47, "
      "%48, %49, %50, %51, %52, %53, %54, %55, %56, %57, %58, %59, %60, %61, %62, %63, "
      "%64, %65, %66, %67, %68, %69, %70, %71, %72, %73, %74, %75, %76, %77, %78, %79"
      "}, %80, %81, 1, 1, 1, 0, 1;\n"
      : "+f"(d[0]), "+f"(d[1]), "+f"(d[2]), "+f"(d[3]), "+f"(d[4]), "+f"(d[5]), "+f"(d[6]), "+f"(d[7]),
        "+f"(d[8]), "+f"(d[9]), "+f"(d[10]), "+f"(d[11]), "+f"(d[12]), "+f"(d[13]), "+f"(d[14]), "+f"(d[15]),
        "+f"(d[16]), "+f"(d[17]), "+f"(d[18]), "+f"(d[19]), "+f"(d[20]), "+f"(d[21]), "+f"(d[22]), "+f"(d[23]),
        "+f"(d[24]), "+f"(d[25]), "+f"(d[26]), "+f"(d[27]), "+f"(d[28]), "+f"(d[29]), "+f"(d[30]), "+f"(d[31]),
        "+f"(d[32]), "+f"(d[33]), "+f"(d[34]), "+f"(d[35]), "+f"(d[36]), "+f"(d[37]), "+f"(d[38]), "+f"(d[39]),
        "+f"(d[40]), "+f"(d[41]), "+f"(d[42]), "+f"(d[43]), "+f"(d[44]), "+f"(d[45]), "+f"(d[46]), "+f"(d[47]),
        "+f"(d[48]), "+f"(d[49]), "+f"(d[50]), "+f"(d[51]), "+f"(d[52]), "+f"(d[53]), "+f"(d[54]), "+f"(d[55]),
        "+f"(d[56]), "+f"(d[57]), "+f"(d[58]), "+f"(d[59]), "+f"(d[60]), "+f"(d[61]), "+f"(d[62]), "+f"(d[63]),
        "+f"(d[64]), "+f"(d[65]), "+f"(d[66]), "+f"(d[67]), "+f"(d[68]), "+f"(d[69]), "+f"(d[70]), "+f"(d[71]),
        "+f"(d[72]), "+f"(d[73]), "+f"(d[74]), "+f"(d[75]), "+f"(d[76]), "+f"(d[77]), "+f"(d[78]), "+f"(d[79])
      : "l"(descA), "l"(descB));
}

__device__ __forceinline__ void mma_ss192(float (&d)[96], uint64_t descA, uint64_t descB) {
  asm volatile("wgmma.mma_async.sync.aligned.m64n192k16.f32.bf16.bf16 {"
      "%0, %1, %2, %3, %4, %5, %6, %7, %8, %9, %10, %11, %12, %13, %14, %15, "
      "%16, %17, %18, %19, %20, %21, %22, %23, %24, %25, %26, %27, %28, %29, %30, %31, "
      "%32, %33, %34, %35, %36, %37, %38, %39, %40, %41, %42, %43, %44, %45, %46, %47, "
      "%48, %49, %50, %51, %52, %53, %54, %55, %56, %57, %58, %59, %60, %61, %62, %63, "
      "%64, %65, %66, %67, %68, %69, %70, %71, %72, %73, %74, %75, %76, %77, %78, %79, "
      "%80, %81, %82, %83, %84, %85, %86, %87, %88, %89, %90, %91, %92, %93, %94, %95"
      "}, %96, %97, 1, 1, 1, 0, 1;\n"
      : "+f"(d[0]), "+f"(d[1]), "+f"(d[2]), "+f"(d[3]), "+f"(d[4]), "+f"(d[5]), "+f"(d[6]), "+f"(d[7]),
        "+f"(d[8]), "+f"(d[9]), "+f"(d[10]), "+f"(d[11]), "+f"(d[12]), "+f"(d[13]), "+f"(d[14]), "+f"(d[15]),
        "+f"(d[16]), "+f"(d[17]), "+f"(d[18]), "+f"(d[19]), "+f"(d[20]), "+f"(d[21]), "+f"(d[22]), "+f"(d[23]),
        "+f"(d[24]), "+f"(d[25]), "+f"(d[26]), "+f"(d[27]), "+f"(d[28]), "+f"(d[29]), "+f"(d[30]), "+f"(d[31]),
        "+f"(d[32]), "+f"(d[33]), "+f"(d[34]), "+f"(d[35]), "+f"(d[36]), "+f"(d[37]), "+f"(d[38]), "+f"(d[39]),
        "+f"(d[40]), "+f"(d[41]), "+f"(d[42]), "+f"(d[43]), "+f"(d[44]), "+f"(d[45]), "+f"(d[46]), "+f"(d[47]),
        "+f"(d[48]), "+f"(d[49]), "+f"(d[50]), "+f"(d[51]), "+f"(d[52]), "+f"(d[53]), "+f"(d[54]), "+f"(d[55]),
        "+f"(d[56]), "+f"(d[57]), "+f"(d[58]), "+f"(d[59]), "+f"(d[60]), "+f"(d[61]), "+f"(d[62]), "+f"(d[63]),
        "+f"(d[64]), "+f"(d[65]), "+f"(d[66]), "+f"(d[67]), "+f"(d[68]), "+f"(d[69]), "+f"(d[70]), "+f"(d[71]),
        "+f"(d[72]), "+f"(d[73]), "+f"(d[74]), "+f"(d[75]), "+f"(d[76]), "+f"(d[77]), "+f"(d[78]), "+f"(d[79]),
        "+f"(d[80]), "+f"(d[81]), "+f"(d[82]), "+f"(d[83]), "+f"(d[84]), "+f"(d[85]), "+f"(d[86]), "+f"(d[87]),
        "+f"(d[88]), "+f"(d[89]), "+f"(d[90]), "+f"(d[91]), "+f"(d[92]), "+f"(d[93]), "+f"(d[94]), "+f"(d[95])
      : "l"(descA), "l"(descB));
}
__device__ __forceinline__ void mma_ss192_p(float (&d)[96], uint64_t descA, uint64_t descB, int acc) {
  asm volatile("{\n.reg .pred p;\nsetp.ne.b32 p, %98, 0;\n"
      "wgmma.mma_async.sync.aligned.m64n192k16.f32.bf16.bf16 {"
      "%0, %1, %2, %3, %4, %5, %6, %7, %8, %9, %10, %11, %12, %13, %14, %15, "
      "%16, %17, %18, %19, %20, %21, %22, %23, %24, %25, %26, %27, %28, %29, %30, %31, "
      "%32, %33, %34, %35, %36, %37, %38, %39, %40, %41, %42, %43, %44, %45, %46, %47, "
      "%48, %49, %50, %51, %52, %53, %54, %55, %56, %57, %58, %59, %60, %61, %62, %63, "
      "%64, %65, %66, %67, %68, %69, %70, %71, %72, %73, %74, %75, %76, %77, %78, %79, "
      "%80, %81, %82, %83, %84, %85, %86, %87, %88, %89, %90, %91, %92, %93, %94, %95"
      "}, %96, %97, p, 1, 1, 0, 1;\n}\n"
      : "+f"(d[0]), "+f"(d[1]), "+f"(d[2]), "+f"(d[3]), "+f"(d[4]), "+f"(d[5]), "+f"(d[6]), "+f"(d[7]),
        "+f"(d[8]), "+f"(d[9]), "+f"(d[10]), "+f"(d[11]), "+f"(d[12]), "+f"(d[13]), "+f"(d[14]), "+f"(d[15]),
        "+f"(d[16]), "+f"(d[17]), "+f"(d[18]), "+f"(d[19]), "+f"(d[20]), "+f"(d[21]), "+f"(d[22]), "+f"(d[23]),
        "+f"(d[24]), "+f"(d[25]), "+f"(d[26]), "+f"(d[27]), "+f"(d[28]), "+f"(d[29]), "+f"(d[30]), "+f"(d[31]),
        "+f"(d[32]), "+f"(d[33]), "+f"(d[34]), "+f"(d[35]), "+f"(d[36]), "+f"(d[37]), "+f"(d[38]), "+f"(d[39]),
        "+f"(d[40]), "+f"(d[41]), "+f"(d[42]), "+f"(d[43]), "+f"(d[44]), "+f"(d[45]), "+f"(d[46]), "+f"(d[47]),
        "+f"(d[48]), "+f"(d[49]), "+f"(d[50]), "+f"(d[51]), "+f"(d[52]), "+f"(d[53]), "+f"(d[54]), "+f"(d[55]),
        "+f"(d[56]), "+f"(d[57]), "+f"(d[58]), "+f"(d[59]), "+f"(d[60]), "+f"(d[61]), "+f"(d[62]), "+f"(d[63]),
        "+f"(d[64]), "+f"(d[65]), "+f"(d[66]), "+f"(d[67]), "+f"(d[68]), "+f"(d[69]), "+f"(d[70]), "+f"(d[71]),
        "+f"(d[72]), "+f"(d[73]), "+f"(d[74]), "+f"(d[75]), "+f"(d[76]), "+f"(d[77]), "+f"(d[78]), "+f"(d[79]),
        "+f"(d[80]), "+f"(d[81]), "+f"(d[82]), "+f"(d[83]), "+f"(d[84]), "+f"(d[85]), "+f"(d[86]), "+f"(d[87]),
        "+f"(d[88]), "+f"(d[89]), "+f"(d[90]), "+f"(d[91]), "+f"(d[92]), "+f"(d[93]), "+f"(d[94]), "+f"(d[95])
      : "l"(descA), "l"(descB), "r"(acc));
}

__device__ __forceinline__ void mma_ss80_tt(float (&d)[40], uint64_t descA, uint64_t descB) {
  asm volatile("wgmma.mma_async.sync.aligned.m64n80k16.f32.bf16.bf16 {"
      "%0, %1, %2, %3, %4, %5, %6, %7, %8, %9, %10, %11, %12, %13, %14, %15, "
      "%16, %17, %18, %19, %20, %21, %22, %23, %24, %25, %26, %27, %28, %29, %30, %31, "
      "%32, %33, %34, %35, %36, %37, %38, %39"
      "}, %40, %41, 1, 1, 1, 1, 1;\n"
      : "+f"(d[0]), "+f"(d[1]), "+f"(d[2]), "+f"(d[3]), "+f"(d[4]), "+f"(d[5]), "+f"(d[6]), "+f"(d[7]),
        "+f"(d[8]), "+f"(d[9]), "+f"(d[10]), "+f"(d[11]), "+f"(d[12]), "+f"(d[13]), "+f"(d[14]), "+f"(d[15]),
        "+f"(d[16]), "+f"(d[17]), "+f"(d[18]), "+f"(d[19]), "+f"(d[20]), "+f"(d[21]), "+f"(d[22]), "+f"(d[23]),
        "+f"(d[24]), "+f"(d[25]), "+f"(d[26]), "+f"(d[27]), "+f"(d[28]), "+f"(d[29]), "+f"(d[30]), "+f"(d[31]),
        "+f"(d[32]), "+f"(d[33]), "+f"(d[34]), "+f"(d[35]), "+f"(d[36]), "+f"(d[37]), "+f"(d[38]), "+f"(d[39])
      : "l"(descA), "l"(descB));
}
__device__ __forceinline__ void mma_ss80_tt_z(float (&d)[40], uint64_t descA, uint64_t descB) {
  asm volatile("wgmma.mma_async.sync.aligned.m64n80k16.f32.bf16.bf16 {"
      "%0, %1, %2, %3, %4, %5, %6, %7, %8, %9, %10, %11, %12, %13, %14, %15, "
      "%16, %17, %18, %19, %20, %21, %22, %23, %24, %25, %26, %27, %28, %29, %30, %31, "
      "%32, %33, %34, %35, %36, %37, %38, %39"
      "}, %40, %41, 0, 1, 1, 1, 1;\n"
      : "=f"(d[0]), "=f"(d[1]), "=f"(d[2]), "=f"(d[3]), "=f"(d[4]), "=f"(d[5]), "=f"(d[6]), "=f"(d[7]),
        "=f"(d[8]), "=f"(d[9]), "=f"(d[10]), "=f"(d[11]), "=f"(d[12]), "=f"(d[13]), "=f"(d[14]), "=f"(d[15]),
        "=f"(d[16]), "=f"(d[17]), "=f"(d[18]), "=f"(d[19]), "=f"(d[20]), "=f"(d[21]), "=f"(d[22]), "=f"(d[23]),
        "=f"(d[24]), "=f"(d[25]), "=f"(d[26]), "=f"(d[27]), "=f"(d[28]), "=f"(d[29]), "=f"(d[30]), "=f"(d[31]),
        "=f"(d[32]), "=f"(d[33]), "=f"(d[34]), "=f"(d[35]), "=f"(d[36]), "=f"(d[37]), "=f"(d[38]), "=f"(d[39])
      : "l"(descA), "l"(descB));
}

__device__ __forceinline__ void mma_rs80_k(float (&d)[40], const uint32_t (&a)[4], uint64_t descB) {
  asm volatile("wgmma.mma_async.sync.aligned.m64n80k16.f32.bf16.bf16 {"
      "%0, %1, %2, %3, %4, %5, %6, %7, %8, %9, %10, %11, %12, %13, %14, %15, "
      "%16, %17, %18, %19, %20, %21, %22, %23, %24, %25, %26, %27, %28, %29, %30, %31, "
      "%32, %33, %34, %35, %36, %37, %38, %39"
      "}, {%40, %41, %42, %43}, %44, 1, 1, 1, 0;\n"
      : "+f"(d[0]), "+f"(d[1]), "+f"(d[2]), "+f"(d[3]), "+f"(d[4]), "+f"(d[5]), "+f"(d[6]), "+f"(d[7]),
        "+f"(d[8]), "+f"(d[9]), "+f"(d[10]), "+f"(d[11]), "+f"(d[12]), "+f"(d[13]), "+f"(d[14]), "+f"(d[15]),
        "+f"(d[16]), "+f"(d[17]), "+f"(d[18]), "+f"(d[19]), "+f"(d[20]), "+f"(d[21]), "+f"(d[22]), "+f"(d[23]),
        "+f"(d[24]), "+f"(d[25]), "+f"(d[26]), "+f"(d[27]), "+f"(d[28]), "+f"(d[29]), "+f"(d[30]), "+f"(d[31]),
        "+f"(d[32]), "+f"(d[33]), "+f"(d[34]), "+f"(d[35]), "+f"(d[36]), "+f"(d[37]), "+f"(d[38]), "+f"(d[39])
      : "r"(a[0]), "r"(a[1]), "r"(a[2]), "r"(a[3]), "l"(descB));
}
__device__ __forceinline__ void mma_rs80_k_z(float (&d)[40], const uint32_t (&a)[4], uint64_t descB) {
  asm volatile("wgmma.mma_async.sync.aligned.m64n80k16.f32.bf16.bf16 {"
      "%0, %1, %2, %3, %4, %5, %6, %7, %8, %9, %10, %11, %12, %13, %14, %15, "
      "%16, %17, %18, %19, %20, %21, %22, %23, %24, %25, %26, %27, %28, %29, %30, %31, "
      "%32, %33, %34, %35, %36, %37, %38, %39"
      "}, {%40, %41, %42, %43}, %44, 0, 1, 1, 0;\n"
      : "=f"(d[0]), "=f"(d[1]), "=f"(d[2]), "=f"(d[3]), "=f"(d[4]), "=f"(d[5]), "=f"(d[6]), "=f"(d[7]),
        "=f"(d[8]), "=f"(d[9]), "=f"(d[10]), "=f"(d[11]), "=f"(d[12]), "=f"(d[13]), "=f"(d[14]), "=f"(d[15]),
        "=f"(d[16]), "=f"(d[17]), "=f"(d[18]), "=f"(d[19]), "=f"(d[20]), "=f"(d[21]), "=f"(d[22]), "=f"(d[23]),
        "=f"(d[24]), "=f"(d[25]), "=f"(d[26]), "=f"(d[27]), "=f"(d[28]), "=f"(d[29]), "=f"(d[30]), "=f"(d[31]),
        "=f"(d[32]), "=f"(d[33]), "=f"(d[34]), "=f"(d[35]), "=f"(d[36]), "=f"(d[37]), "=f"(d[38]), "=f"(d[39])
      : "r"(a[0]), "r"(a[1]), "r"(a[2]), "r"(a[3]), "l"(descB));
}

__device__ __forceinline__ void mma_rs48_k(float (&d)[24], const uint32_t (&a)[4], uint64_t descB) {
  asm volatile("wgmma.mma_async.sync.aligned.m64n48k16.f32.bf16.bf16 {"
      "%0, %1, %2, %3, %4, %5, %6, %7, %8, %9, %10, %11, %12, %13, %14, %15, "
      "%16, %17, %18, %19, %20, %21, %22, %23"
      "}, {%24, %25, %26, %27}, %28, 1, 1, 1, 0;\n"
      : "+f"(d[0]), "+f"(d[1]), "+f"(d[2]), "+f"(d[3]), "+f"(d[4]), "+f"(d[5]), "+f"(d[6]), "+f"(d[7]),
        "+f"(d[8]), "+f"(d[9]), "+f"(d[10]), "+f"(d[11]), "+f"(d[12]), "+f"(d[13]), "+f"(d[14]), "+f"(d[15]),
        "+f"(d[16]), "+f"(d[17]), "+f"(d[18]), "+f"(d[19]), "+f"(d[20]), "+f"(d[21]), "+f"(d[22]), "+f"(d[23])
      : "r"(a[0]), "r"(a[1]), "r"(a[2]), "r"(a[3]), "l"(descB));
}
__device__ __forceinline__ void mma_rs48_k_z(float (&d)[24], const uint32_t (&a)[4], uint64_t descB) {
  asm volatile("wgmma.mma_async.sync.aligned.m64n48k16.f32.bf16.bf16 {"
      "%0, %1, %2, %3, %4, %5, %6, %7, %8, %9, %10, %11, %12, %13, %14, %15, "
      "%16, %17, %18, %19, %20, %21, %22, %23"
      "}, {%24, %25, %26, %27}, %28, 0, 1, 1, 0;\n"
      : "=f"(d[0]), "=f"(d[1]), "=f"(d[2]), "=f"(d[3]), "=f"(d[4]), "=f"(d[5]), "=f"(d[6]), "=f"(d[7]),
        "=f"(d[8]), "=f"(d[9]), "=f"(d[10]), "=f"(d[11]), "=f"(d[12]), "=f"(d[13]), "=f"(d[14]), "=f"(d[15]),
        "=f"(d[16]), "=f"(d[17]), "=f"(d[18]), "=f"(d[19]), "=f"(d[20]), "=f"(d[21]), "=f"(d[22]), "=f"(d[23])
      : "r"(a[0]), "r"(a[1]), "r"(a[2]), "r"(a[3]), "l"(descB));
}

__device__ __forceinline__ void mma_rs160_n(float (&d)[80], const uint32_t (&a)[4], uint64_t descB) {
  asm volatile("wgmma.mma_async.sync.aligned.m64n160k16.f32.bf16.bf16 {"
      "%0, %1, %2, %3, %4, %5, %6, %7, %8, %9, %10, %11, %12, %13, %14, %15, "
      "%16, %17, %18, %19, %20, %21, %22, %23, %24, %25, %26, %27, %28, %29, %30, %31, "
      "%32, %33, %34, %35, %36, %37, %38, %39, %40, %41, %42, %43, %44, %45, %46, %47, "
      "%48, %49, %50, %51, %52, %53, %54, %55, %56, %57, %58, %59, %60, %61, %62, %63, "
      "%64, %65, %66, %67, %68, %69, %70, %71, %72, %73, %74, %75, %76, %77, %78, %79"
      "}, {%80, %81, %82, %83}, %84, 1, 1, 1, 1;\n"
      : "+f"(d[0]), "+f"(d[1]), "+f"(d[2]), "+f"(d[3]), "+f"(d[4]), "+f"(d[5]), "+f"(d[6]), "+f"(d[7]),
        "+f"(d[8]), "+f"(d[9]), "+f"(d[10]), "+f"(d[11]), "+f"(d[12]), "+f"(d[13]), "+f"(d[14]), "+f"(d[15]),
        "+f"(d[16]), "+f"(d[17]), "+f"(d[18]), "+f"(d[19]), "+f"(d[20]), "+f"(d[21]), "+f"(d[22]), "+f"(d[23]),
        "+f"(d[24]), "+f"(d[25]), "+f"(d[26]), "+f"(d[27]), "+f"(d[28]), "+f"(d[29]), "+f"(d[30]), "+f"(d[31]),
        "+f"(d[32]), "+f"(d[33]), "+f"(d[34]), "+f"(d[35]), "+f"(d[36]), "+f"(d[37]), "+f"(d[38]), "+f"(d[39]),
        "+f"(d[40]), "+f"(d[41]), "+f"(d[42]), "+f"(d[43]), "+f"(d[44]), "+f"(d[45]), "+f"(d[46]), "+f"(d[47]),
        "+f"(d[48]), "+f"(d[49]), "+f"(d[50]), "+f"(d[51]), "+f"(d[52]), "+f"(d[53]), "+f"(d[54]), "+f"(d[55]),
        "+f"(d[56]), "+f"(d[57]), "+f"(d[58]), "+f"(d[59]), "+f"(d[60]), "+f"(d[61]), "+f"(d[62]), "+f"(d[63]),
        "+f"(d[64]), "+f"(d[65]), "+f"(d[66]), "+f"(d[67]), "+f"(d[68]), "+f"(d[69]), "+f"(d[70]), "+f"(d[71]),
        "+f"(d[72]), "+f"(d[73]), "+f"(d[74]), "+f"(d[75]), "+f"(d[76]), "+f"(d[77]), "+f"(d[78]), "+f"(d[79])
      : "r"(a[0]), "r"(a[1]), "r"(a[2]), "r"(a[3]), "l"(descB));
}
__device__ __forceinline__ void mma_rs160_n_z(float (&d)[80], const uint32_t (&a)[4], uint64_t descB) {
  asm volatile("wgmma.mma_async.sync.aligned.m64n160k16.f32.bf16.bf16 {"
      "%0, %1, %2, %3, %4, %5, %6, %7, %8, %9, %10, %11, %12, %13, %14, %15, "
      "%16, %17, %18, %19, %20, %21, %22, %23, %24, %25, %26, %27, %28, %29, %30, %31, "
      "%32, %33, %34, %35, %36, %37, %38, %39, %40, %41, %42, %43, %44, %45, %46, %47, "
      "%48, %49, %50, %51, %52, %53, %54, %55, %56, %57, %58, %59, %60, %61, %62, %63, "
      "%64, %65, %66, %67, %68, %69, %70, %71, %72, %73, %74, %75, %76, %77, %78, %79"
      "}, {%80, %81, %82, %83}, %84, 0, 1, 1, 1;\n"
      : "=f"(d[0]), "=f"(d[1]), "=f"(d[2]), "=f"(d[3]), "=f"(d[4]), "=f"(d[5]), "=f"(d[6]), "=f"(d[7]),
        "=f"(d[8]), "=f"(d[9]), "=f"(d[10]), "=f"(d[11]), "=f"(d[12]), "=f"(d[13]), "=f"(d[14]), "=f"(d[15]),
        "=f"(d[16]), "=f"(d[17]), "=f"(d[18]), "=f"(d[19]), "=f"(d[20]), "=f"(d[21]), "=f"(d[22]), "=f"(d[23]),
        "=f"(d[24]), "=f"(d[25]), "=f"(d[26]), "=f"(d[27]), "=f"(d[28]), "=f"(d[29]), "=f"(d[30]), "=f"(d[31]),
        "=f"(d[32]), "=f"(d[33]), "=f"(d[34]), "=f"(d[35]), "=f"(d[36]), "=f"(d[37]), "=f"(d[38]), "=f"(d[39]),
        "=f"(d[40]), "=f"(d[41]), "=f"(d[42]), "=f"(d[43]), "=f"(d[44]), "=f"(d[45]), "=f"(d[46]), "=f"(d[47]),
        "=f"(d[48]), "=f"(d[49]), "=f"(d[50]), "=f"(d[51]), "=f"(d[52]), "=f"(d[53]), "=f"(d[54]), "=f"(d[55]),
        "=f"(d[56]), "=f"(d[57]), "=f"(d[58]), "=f"(d[59]), "=f"(d[60]), "=f"(d[61]), "=f"(d[62]), "=f"(d[63]),
        "=f"(d[64]), "=f"(d[65]), "=f"(d[66]), "=f"(d[67]), "=f"(d[68]), "=f"(d[69]), "=f"(d[70]), "=f"(d[71]),
        "=f"(d[72]), "=f"(d[73]), "=f"(d[74]), "=f"(d[75]), "=f"(d[76]), "=f"(d[77]), "=f"(d[78]), "=f"(d[79])
      : "r"(a[0]), "r"(a[1]), "r"(a[2]), "r"(a[3]), "l"(descB));
}

__device__ __forceinline__ void feature_map(const uint32_t (&P)[2][10], uint32_t (&fr)[10][4]) {
  constexpr float L2E = 1.4426950408889634f;
#pragma unroll
  for (int p = 0; p < 2; p++) {
#pragma unroll
    for (int r = 0; r < 2; r++) {
      uint32_t mx = P[r][5 * p], mn = mx;
#pragma unroll
      for (int g = 1; g < 5; g++) { mx = max_bf2(mx, P[r][5 * p + g]); mn = min_bf2(mn, P[r][5 * p + g]); }
      mx = max_bf2(mx, __shfl_xor_sync(0xffffffffu, mx, 1));
      mn = min_bf2(mn, __shfl_xor_sync(0xffffffffu, mn, 1));
      mx = max_bf2(mx, __shfl_xor_sync(0xffffffffu, mx, 2));
      mn = min_bf2(mn, __shfl_xor_sync(0xffffffffu, mn, 2));
      float mx0 = -bf_lo(mx) * L2E, mx1 = -bf_hi(mx) * L2E, mn0 = bf_lo(mn) * L2E, mn1 = bf_hi(mn) * L2E;
      float ep0[5], ep1[5], en0[5], en1[5];
      float sp0 = 0.f, sp1 = 0.f, sn0 = 0.f, sn1 = 0.f;
#pragma unroll
      for (int g = 0; g < 5; g++) {
        float x0 = bf_lo(P[r][5 * p + g]), x1 = bf_hi(P[r][5 * p + g]);
        ep0[g] = ex2(fmaf(x0, L2E, mx0)); ep1[g] = ex2(fmaf(x1, L2E, mx1));
        en0[g] = ex2(fmaf(x0, -L2E, mn0)); en1[g] = ex2(fmaf(x1, -L2E, mn1));
        sp0 += ep0[g]; sp1 += ep1[g]; sn0 += en0[g]; sn1 += en1[g];
      }
      sp0 += __shfl_xor_sync(0xffffffffu, sp0, 1); sp1 += __shfl_xor_sync(0xffffffffu, sp1, 1);
      sn0 += __shfl_xor_sync(0xffffffffu, sn0, 1); sn1 += __shfl_xor_sync(0xffffffffu, sn1, 1);
      sp0 += __shfl_xor_sync(0xffffffffu, sp0, 2); sp1 += __shfl_xor_sync(0xffffffffu, sp1, 2);
      sn0 += __shfl_xor_sync(0xffffffffu, sn0, 2); sn1 += __shfl_xor_sync(0xffffffffu, sn1, 2);
      sp0 = rcp(sp0); sp1 = rcp(sp1); sn0 = rcp(sn0); sn1 = rcp(sn1);
#pragma unroll
      for (int g = 0; g < 5; g++) {
        fr[5 * p + g][r] = pack_bf16(ep0[g] * sp0, ep1[g] * sp1);
        fr[5 * p + g][2 + r] = pack_bf16(en0[g] * sn0, en1[g] * sn1);
      }
    }
  }
}

template <bool V> struct BoolC { static constexpr bool value = V; };
struct Ring {
  uint32_t idx, phase;
  template <int N> __device__ __forceinline__ void next() { if (++idx == N) { idx = 0; phase ^= 1; } }
};

}

__global__ void __cluster_dims__(2, 1, 1) __launch_bounds__(384, 1)
fused_kernel(const __grid_constant__ Maps maps, const __nv_bfloat16* __restrict__ x, const __nv_bfloat16* __restrict__ wqkv,
             const __nv_bfloat16* __restrict__ wphi, const __nv_bfloat16* __restrict__ w1, const __nv_bfloat16* __restrict__ w2,
             const __nv_bfloat16* __restrict__ w3, const __nv_bfloat16* __restrict__ w4, const __nv_bfloat16* __restrict__ wo,
             const __nv_bfloat16* __restrict__ gate_w, __nv_bfloat16* __restrict__ out) {
  extern __shared__ __align__(1024) uint8_t sgen[];
  const uint32_t sb = smem_u32(sgen);
  const uint32_t sb16 = (sb & 0x3FFFFu) >> 4;
  const uint32_t bars = sb + OFF_BAR;
  const uint32_t fullA = bars + 8 * B_FULLA, emptyA = bars + 8 * B_EMPTYA, fullB = bars + 8 * B_FULLB, emptyB = bars + 8 * B_EMPTYB;

  const int tid = threadIdx.x;
  const int rank = blockIdx.x & 1;
  const int pairIdx = blockIdx.x >> 1;
  const int i = pairIdx >> 2, j = 2 * (pairIdx & 3) + rank;

  TSTAMP(0);
  auto load_p1_b = [&](int k, uint32_t slot, uint32_t bar) {
    mbar_expect_tx(bar, 40960);
    tma4d(slot + 8192, &maps.qm, bar, 0, 64 * k, 0, j);
    tma3d(slot, &maps.w1m, bar, 0, 64 * k, j);
    tma4d(slot + 32768 + 2048, &maps.qr, bar, 64, 64 * k, 0, j);
    tma3d(slot + 32768, &maps.w1r, bar, 64, 64 * k, j);
  };
  if (tid >= 256) {
    asm volatile("setmaxnreg.dec.sync.aligned.u32 40;");
    if (tid == 256) {
#pragma unroll
      for (int s = 0; s < NA; s++) mbar_init(fullA + 8 * s, 1);
      asm volatile("fence.mbarrier_init.release.cluster;" ::: "memory");
#pragma unroll 1
      for (int u = 0; u < 4; u++) {
        if ((u & 1) == 0) mbar_expect_tx(fullA + 4 * u, SLOT_A);
        tma2d(sb + OFF_A + u * 8192, &maps.x, fullA + 8 * (u >> 1), 64 * (u >> 1), 128 * i + 64 * (u & 1));
      }
    } else if (tid == 288) {
#pragma unroll
      for (int s = 0; s < NB; s++) mbar_init(fullB + 8 * s, 1);
      asm volatile("fence.mbarrier_init.release.cluster;" ::: "memory");
#pragma unroll 1
      for (int k = 0; k < 2; k++) load_p1_b(k, sb + OFF_B + k * SLOT_B, fullB + 8 * k);
    } else if (tid == 320) {
#pragma unroll
      for (int b = B_CS; b < NBAR; b++) mbar_init(bars + 8 * b, b < B_EMPTYB ? 1 : b < B_EMPTYA ? 8 : 16);
#pragma unroll
      for (int b = B_DSR; b < B_EMPTYB; b++) mbar_expect_tx(bars + 8 * b, 10240);
      asm volatile("fence.mbarrier_init.release.cluster;" ::: "memory");
    }
    __syncwarp();
    asm volatile("barrier.cluster.arrive.relaxed.aligned;" ::: "memory");
    auto get_epoch = [&]() { return *reinterpret_cast<volatile unsigned*>(g_flags + FL_DONE * 32) / NCTA; };
    if (tid >= 320) {
      const int lane = tid & 31, ch = lane % 10, rg = lane / 10;
      const __nv_bfloat16* p = w1 + (size_t)(40 * i + (tid >= 352 ? 20 : 0) + rg) * D_ + 80 * j + 8 * ch;
      const unsigned par = get_epoch() & 1;
      float a[8];
#pragma unroll
      for (int e = 0; e < 8; e++) a[e] = 0.f;
#pragma unroll
      for (int it = 0; it < 7; it++) {
        uint4 v = make_uint4(0, 0, 0, 0);
        if (lane < 30 && 3 * it + rg < 20) v = __ldg(reinterpret_cast<const uint4*>(p + (size_t)it * 3 * D_));
        a[0] += bf_lo(v.x); a[1] += bf_hi(v.x); a[2] += bf_lo(v.y); a[3] += bf_hi(v.y);
        a[4] += bf_lo(v.z); a[5] += bf_hi(v.z); a[6] += bf_lo(v.w); a[7] += bf_hi(v.w);
      }
#pragma unroll
      for (int e = 0; e < 8; e++) a[e] += __shfl_down_sync(0xffffffffu, a[e], 10) + __shfl_down_sync(0xffffffffu, a[e], 20);
      if (lane < 10) {
        float* cd = g_acc[par] + 8 * KV_J + 80 * j + 8 * ch;
        red_add4(cd, a[0], a[1], a[2], a[3]); red_add4(cd + 4, a[4], a[5], a[6], a[7]);
      }
      __syncwarp();
      if (lane == 0) flag_add(FL_CS + j);
      __syncwarp();
    }
    asm volatile("barrier.cluster.wait.aligned;" ::: "memory");
    const int lane = tid & 31, pw = (tid >> 5) & 3;
    if (pw == 0) {
      if (tid == 256) {
        Ring r{2, 1};
        unsigned ep1 = 0;
#pragma unroll 1
        for (int k = 2; k < 25; k++) {
          if (k == 4) ep1 = get_epoch() + 1;
          if (k == 10 || k == 15) {
            if (k == 10) mbar_wait(bars + 8 * B_SIGH, 0);
            flag_wait(k == 10 ? FL_H + 2 * i + rank : FL_X1 + i, ep1 * 8u);
            TSTAMPX(k == 10 ? 29 : 30);
          }
          mbar_wait(emptyA + 8 * r.idx, r.phase);
          const uint32_t bar = fullA + 8 * r.idx, slot = sb + OFF_A + r.idx * SLOT_A;
          mbar_expect_tx(bar, SLOT_A);
          if (k >= 10 && k < 15) tma2d(slot, &maps.hs, bar, 64 * (k - 10) + 320 * rank, 128 * i);
          else tma2d_mc(slot + rank * 8192, k < 10 ? &maps.x : &maps.x1, bar, 64 * (k < 10 ? k : k - 15), 128 * i + 64 * rank);
          r.next<NA>();
        }
      }
    } else if (pw == 1) {
      if (tid == 288) {
        Ring r{2, 1};
#pragma unroll 1
        for (int k = 2; k < 18; k++) {
          mbar_wait(emptyB + 8 * r.idx, r.phase);
          const uint32_t bar = fullB + 8 * r.idx, slot = sb + OFF_B + r.idx * SLOT_B;
          if (k < 10) {
            load_p1_b(k, slot, bar);
          } else if (k < 13) {
            mbar_expect_tx(bar, k < 12 ? 40960 : 20480);
            tma3d(slot, &maps.w2, bar, 0, 320 * rank + 128 * (k - 10), 5 * (j >> 1));
            if (k < 12) tma3d(slot + 20480, &maps.w2, bar, 0, 320 * rank + 128 * (k - 10) + 64, 5 * (j >> 1));
          } else {
            mbar_expect_tx(bar, 49152);
            tma3d(slot, &maps.w3, bar, 0, 128 * (k - 13), 3 * j);
            tma3d(slot + 24576, &maps.w3, bar, 0, 128 * (k - 13) + 64, 3 * j);
          }
          r.next<NB>();
        }
        Ring r4{0, 1};
#pragma unroll 1
        for (int n = 0; n < 16; n++) {
          if (n == 0 || n == 1 || n == 3) { mbar_wait(emptyB + 8 * r.idx, r.phase); r.next<NB>(); }
          mbar_wait(bars + 8 * (B_EMPTY4 + r4.idx), r4.phase);
          const uint32_t bar = bars + 8 * (B_FULL4 + r4.idx), slot = sb + OFF_B + r4.idx * UNIT4;
          const int u = n & 3, m = ((j >> 1) + 1 + (n >> 2)) & 3;
          mbar_expect_tx(bar, u == 3 ? 25600 : 20480);
          tma3d(slot, u == 3 ? &maps.wo : &maps.w4, bar, 0, u == 3 ? 80 * j : 192 * j + 64 * u, 5 * m);
          r4.next<NU4>();
        }
      }
    } else {
      const unsigned epoch = get_epoch();
      float* accg = g_acc[epoch & 1];
      if (pw == 2) {
        {
          float* nxt = g_acc[(epoch + 1) & 1];
          constexpr int PER = ACC_FLOATS / NCTA;
#pragma unroll 1
          for (int e = lane; e < PER; e += 32) nxt[blockIdx.x * PER + e] = 0.f;
        }
        if (tid == 320) {
          flag_wait(FL_CS + j, (epoch + 1) * 32u);
          flag_wait(FL_ST + i, (epoch + 1) * 8u);
          fence_async_glb();
          *reinterpret_cast<volatile uint32_t*>(sgen + OFF_BAR + 8 * NBAR) = (epoch + 1) & 1;
          mbar_expect_tx(bars + 8 * B_CS, 320 + 2048);
          bulk_load(sb + OFF_CS, accg + 8 * KV_J + 80 * j, 320, bars + 8 * B_CS);
          bulk_load(sb + OFF_XST, g_xstat + 128 * i, 2048, bars + 8 * B_CS);
          TSTAMPX(21);
          l2_prefetch(w2 + (size_t)blockIdx.x * (D_ * D_ / NCTA), D_ * D_ * 2 / NCTA);
          flag_wait(FL_H + 2 * i + rank, (epoch + 1) * 8u);
          l2_prefetch(w3 + (size_t)blockIdx.x * (F_ * D_ / NCTA), F_ * D_ * 2 / NCTA);
          l2_prefetch(w4 + (size_t)blockIdx.x * (F_ * D_ / NCTA), F_ * D_ * 2 / NCTA);
          l2_prefetch(wo + (size_t)blockIdx.x * (D_ * D_ / NCTA), D_ * D_ * 2 / NCTA);
          flag_wait(FL_KV + j, (epoch + 1) * 16u);
          mbar_expect_tx(bars + 8 * B_KV, KV_J * 4);
          bulk_load(sb + OFF_MISC, accg + j * KV_J, KV_J * 4, bars + 8 * B_KV);
          TSTAMPX(22);
        }
        __syncwarp();
#pragma unroll 1
        for (int m = 0; m < 6; m++) {
          const int col = 192 * j + 32 * m + 8 * (lane & 3);
          const __nv_bfloat16* p = w3 + (size_t)(40 * i + (lane >> 2) * 5) * F_ + col;
          float a[8];
#pragma unroll
          for (int e = 0; e < 8; e++) a[e] = 0.f;
#pragma unroll
          for (int it = 0; it < 5; it++) {
            const uint4 v = __ldg(reinterpret_cast<const uint4*>(p + (size_t)it * F_));
            a[0] += bf_lo(v.x); a[1] += bf_hi(v.x); a[2] += bf_lo(v.y); a[3] += bf_hi(v.y);
            a[4] += bf_lo(v.z); a[5] += bf_hi(v.z); a[6] += bf_lo(v.w); a[7] += bf_hi(v.w);
          }
#pragma unroll
          for (int e = 0; e < 4; e++) {
            const float snd = (lane & 4) ? a[e] : a[e + 4], keep = (lane & 4) ? a[e + 4] : a[e];
            a[e] = keep + __shfl_xor_sync(0xffffffffu, snd, 4);
            a[e] += __shfl_xor_sync(0xffffffffu, a[e], 8);
            a[e] += __shfl_xor_sync(0xffffffffu, a[e], 16);
          }
          if (lane < 8) red_add4(accg + 8 * KV_J + D_ + col + (lane >> 2) * 4, a[0], a[1], a[2], a[3]);
        }
        __syncwarp();
        if (tid == 320) {
          flag_add(FL_CS3 + j);
          mbar_wait(bars + 8 * B_MFREE, 0);
          flag_wait(FL_X1 + i, (epoch + 1) * 8u);
          flag_wait(FL_CS3 + j, (epoch + 1) * 16u);
          fence_async_glb();
          mbar_expect_tx(bars + 8 * B_ST1, 8192 + 768);
          bulk_load(sb + OFF_CS + 320, accg + 8 * KV_J + D_ + 192 * j, 768, bars + 8 * B_ST1);
          bulk_load(sb + OFF_MISC, g_st1 + 128 * i * 8, 8192, bars + 8 * B_ST1);
        }
      }
      if (tid == 352) {
        mbar_wait(bars + 8 * B_SIGP, 0);
        flag_add(FL_ST + i);
        TSTAMPX(20);
        mbar_expect_tx(bars + 8 * B_XR, 20480);
#pragma unroll 1
        for (int u = 0; u < 8; u++)
          tma2d(sb + OFF_B + (u / 3) * SLOT_B + SPARE + (u % 3) * 2560, &maps.xr, bars + 8 * B_XR, 80 * j, 128 * i + 16 * u);
        const int shift = (j < 2) ? 1 : (j < 4) ? -1 : (j < 6) ? 2 : -2;
        if ((shift > 0 && i == 0) || (shift < 0 && i == 15)) {
          const int nz = shift > 0 ? shift : -shift, zr = shift > 0 ? 0 : S_ - nz;
#pragma unroll 1
          for (int e = 0; e < nz * 10; e++)
            reinterpret_cast<uint4*>(g_Hs + (size_t)(2 + zr + e / 10) * D_ + 80 * j)[e % 10] = make_uint4(0, 0, 0, 0);
        }
        prefetch_tmap(&maps.hs); prefetch_tmap(&maps.x1);
        prefetch_tmap(&maps.w2); prefetch_tmap(&maps.w3); prefetch_tmap(&maps.w4); prefetch_tmap(&maps.wo);
        mbar_wait(bars + 8 * B_SIGH, 0);
        TSTAMPX(23);
        fence_async_glb();
        flag_add(FL_H + 2 * i + (j >> 2));
        flag_add_relaxed(FL_H + 2 * ((i + (shift > 0 ? 1 : -1)) & 15) + (j >> 2));
        TSTAMPX(24);
        mbar_wait(bars + 8 * B_SIGKV, 0);
        TSTAMPX(25);
        fence_async_smem();
        asm volatile("cp.reduce.async.bulk.global.shared::cta.bulk_group.add.f32 [%0], [%1], %2;"
                     ::"l"(accg + j * KV_J), "r"(sb + OFF_MISC), "r"(KV_J * 4) : "memory");
        bulk_commit(); bulk_wait<0>();
        flag_add(FL_KV + j);
        TSTAMPX(26);
        mbar_wait(bars + 8 * B_SIGX1, 0);
        TSTAMPX(27);
        fence_async_glb();
        flag_add(FL_X1 + i);
        TSTAMPX(28);
      }
    }
  } else {
    uint4 pv[5], pw_[5], pre;
    {
      const int row = 128 * i + 16 * j + (tid >> 4), l16 = tid & 15;
#pragma unroll
      for (int c = 0; c < 5; c++) pv[c] = __ldg(reinterpret_cast<const uint4*>(x + (size_t)row * D_ + c * 128 + l16 * 8));
      pre = __ldg(reinterpret_cast<const uint4*>(wphi + (size_t)j * 1600) + (tid < 200 ? tid : 0));
#pragma unroll
      for (int c = 0; c < 5; c++) pw_[c] = __ldg(reinterpret_cast<const uint4*>(gate_w + c * 128 + l16 * 8));
    }
    asm volatile("barrier.cluster.arrive.relaxed.aligned;" ::: "memory");
    asm volatile("setmaxnreg.inc.sync.aligned.u32 232;");
    const int wg = tid >> 7, warp = tid >> 5, lane = tid & 31, t = lane & 3;
    const int rloc = warp * 16 + (lane >> 2);
    const float* s_cs = reinterpret_cast<const float*>(sgen + OFF_CS);
    auto signal = [&](int b) {
      __syncwarp();
      if (lane == 0) mbar_arrive(bars + 8 * b);
    };
    auto releaseB = [&](uint32_t bar) {
      __syncwarp();
      if (lane == 0) mbar_arrive(bar);
    };
    auto release = [&](uint32_t bar) {
      __syncwarp();
      if (lane < 2) mbar_arrive_cta(bar, lane);
    };
    const uint32_t stg_lane = (warp * 16 + ((lane >> 3) & 1) * 8 + (lane & 7)) * 160 + (lane >> 4) * 16;

    auto store_tile = [&](uint32_t stg, const uint32_t (&v)[2][10], __nv_bfloat16* dst  ) {
#pragma unroll
      for (int s = 0; s < 5; s++) stsm4(stg + stg_lane + s * 32, v[0][2 * s], v[1][2 * s], v[0][2 * s + 1], v[1][2 * s + 1]);
      __syncwarp();
      const uint32_t src = stg + warp * 2560 + (lane >> 1) * 160 + (lane & 1) * 16;
      uint4* d4 = reinterpret_cast<uint4*>(dst + (lane >> 1) * D_ + (lane & 1) * 8);
#pragma unroll
      for (int q = 0; q < 5; q++) d4[2 * q] = lds128(src + q * 32);
    };

    {
#pragma unroll 1
      for (int e = tid; e < 800; e += 256) sts128(sb + OFF_MISC + e * 16, make_uint4(0, 0, 0, 0));
      bar_sync(1, 256);
      float f[40];
      float s = 0.f, gs = 0.f;
#pragma unroll
      for (int c = 0; c < 5; c++) {
        const uint32_t vv[4] = {pv[c].x, pv[c].y, pv[c].z, pv[c].w}, ww[4] = {pw_[c].x, pw_[c].y, pw_[c].z, pw_[c].w};
#pragma unroll
        for (int e = 0; e < 4; e++) {
          f[8 * c + 2 * e] = bf_lo(vv[e]); f[8 * c + 2 * e + 1] = bf_hi(vv[e]);
          s += f[8 * c + 2 * e] + f[8 * c + 2 * e + 1];
          gs = fmaf(f[8 * c + 2 * e], bf_lo(ww[e]), gs); gs = fmaf(f[8 * c + 2 * e + 1], bf_hi(ww[e]), gs);
        }
      }
#pragma unroll
      for (int o = 1; o < 16; o <<= 1) { s += __shfl_xor_sync(0xffffffffu, s, o); gs += __shfl_xor_sync(0xffffffffu, gs, o); }
      const float mean = s * (1.f / D_);
      float q = 0.f;
#pragma unroll
      for (int e = 0; e < 40; e++) { const float d = f[e] - mean; q = fmaf(d, d, q); }
#pragma unroll
      for (int o = 1; o < 16; o <<= 1) q += __shfl_xor_sync(0xffffffffu, q, o);
      const float rstd = rsqrtf(q * (1.f / D_) + 1e-5f);
      asm volatile("barrier.cluster.wait.aligned;" ::: "memory");
      if ((tid & 15) == 0) g_xstat[128 * i + 16 * j + (tid >> 4)] = make_float4(rstd, -mean * rstd, rcp(1.f + __expf(-gs)), 0.f);
      signal(B_SIGP);
      if (tid < 200) {
        const uint32_t ww[4] = {pre.x, pre.y, pre.z, pre.w};
        const int h = tid / 50;
#pragma unroll
        for (int e = 0; e < 8; e++) {
          const int idx = tid * 8 + e, k = idx / 20, ff = idx - 20 * k;
          const int n = 40 * (h >> 1) + 8 * (ff >> 2) + 2 * (ff & 3) + (h & 1);
          const int off = (k >> 4) * 2560 + n * 32 + ((((k >> 3) ^ (n >> 2)) & 1) << 4) + (k & 7) * 2;
          *reinterpret_cast<unsigned short*>(sgen + OFF_MISC + off) = (unsigned short)(ww[e >> 1] >> ((e & 1) * 16));
        }
      }
    }
    TSTAMP(1);

    Ring ra{0, 0}, rb{0, 0};
    uint32_t qp[2][10], P[2][10];
    float st_g[2];
    {
      float accM[128], accR[32];
      uint32_t pa = 0, pb = 0;
#pragma unroll 1
      for (int k = 0; k < 10; k++) {
        mbar_wait(fullA + 8 * ra.idx, ra.phase);
        if (tid == 0) TRACE(32 + k);
        mbar_wait(fullB + 8 * rb.idx, rb.phase);
        if (tid == 0) TRACE(64 + k);
        if (k == 0) TSTAMP(2);
        const uint32_t a0 = sb16 + ((OFF_A + ra.idx * SLOT_A + wg * 8192) >> 4), b0 = sb16 + ((OFF_B + rb.idx * SLOT_B) >> 4);
        wg_fence();
#pragma unroll
        for (int kk = 0; kk < 4; kk++) {
          const uint64_t da = make_desc(a0, kk * 32, 16, 1024, 1);
          if (kk == 0) {
            mma_ss256_p(accM, da, make_desc(b0, 0, 8192, 1024, 1), k);
            mma_ss64_p(accR, da, make_desc(b0, 32768, 2048, 256, 3), k);
          } else {
            mma_ss256(accM, da, make_desc(b0, kk * 2048, 8192, 1024, 1));
            mma_ss64(accR, da, make_desc(b0, 32768 + kk * 512, 2048, 256, 3));
          }
          if (kk == 0) {
            wg_commit();
            if (k > 0) {
              wg_wait<1>();
              if (k - 1 < 8) release(emptyA + 8 * pa);
              releaseB(emptyB + 8 * pb);
            }
          }
        }
        wg_commit();
        pa = ra.idx; pb = rb.idx;
        ra.next<NA>(); rb.next<NB>();
      }
      TSTAMP(18);
      float st_rstd[2], st_mr[2];
      mbar_wait(bars + 8 * B_CS, 0);
#pragma unroll
      for (int r = 0; r < 2; r++) {
        const uint4 st = lds128(sb + OFF_XST + (rloc + 8 * r) * 16);
        st_rstd[r] = __uint_as_float(st.x); st_mr[r] = __uint_as_float(st.y); st_g[r] = __uint_as_float(st.z);
      }
      TSTAMP(19);
      wg_wait<0>();
      fence_regs(accM); fence_regs(accR);
      TSTAMP(3);
#define ACC(P_, G, I_) ((G) < 8 ? accM[(P_) * 32 + ((G) & 7) * 4 + (I_)] : accR[(P_) * 8 + ((G) & 1) * 4 + (I_)])
      {
        uint32_t hv[2][10];
#pragma unroll
        for (int g = 0; g < 10; g++) {
          const float2 cs = *reinterpret_cast<const float2*>(s_cs + 8 * g + 2 * t);
          const float v0 = gelu_s(fmaf(ACC(0, g, 0), st_rstd[0], st_mr[0] * cs.x), 0.5f), v1 = gelu_s(fmaf(ACC(0, g, 1), st_rstd[0], st_mr[0] * cs.y), 0.5f);
          const float v2 = gelu_s(fmaf(ACC(0, g, 2), st_rstd[1], st_mr[1] * cs.x), 0.5f), v3 = gelu_s(fmaf(ACC(0, g, 3), st_rstd[1], st_mr[1] * cs.y), 0.5f);
          hv[0][g] = pack_bf16(v0, v1); hv[1][g] = pack_bf16(v2, v3);
        }
        fence_async_smem();
        bar_sync(1, 256);
        const int shift = (j < 2) ? 1 : (j < 4) ? -1 : (j < 6) ? 2 : -2;
        store_tile(sb + OFF_STG, hv, g_Hs + (size_t)(128 * i + 16 * warp + 2 + shift) * D_ + 80 * j);
        signal(B_SIGH);
      }
      TSTAMP(4);
      uint32_t kf[5][4], qf[5][4];
#pragma unroll
      for (int s = 0; s < 5; s++) {
        kf[s][0] = pack_bf16(ACC(2, 2 * s, 0), ACC(2, 2 * s, 1)); kf[s][1] = pack_bf16(ACC(2, 2 * s, 2), ACC(2, 2 * s, 3));
        kf[s][2] = pack_bf16(ACC(2, 2 * s + 1, 0), ACC(2, 2 * s + 1, 1)); kf[s][3] = pack_bf16(ACC(2, 2 * s + 1, 2), ACC(2, 2 * s + 1, 3));
        qf[s][0] = pack_bf16(ACC(1, 2 * s, 0), ACC(1, 2 * s, 1)); qf[s][1] = pack_bf16(ACC(1, 2 * s, 2), ACC(1, 2 * s, 3));
        qf[s][2] = pack_bf16(ACC(1, 2 * s + 1, 0), ACC(1, 2 * s + 1, 1)); qf[s][3] = pack_bf16(ACC(1, 2 * s + 1, 2), ACC(1, 2 * s + 1, 3));
      }
      float pk[40], pq[40];
      wg_fence();
#pragma unroll
      for (int s = 0; s < 5; s++) {
        if (s == 0) mma_rs80_k_z(pk, kf[s], make_desc(sb16, OFF_MISC, 16, 256, 3));
        else mma_rs80_k(pk, kf[s], make_desc(sb16, OFF_MISC + s * 2560, 16, 256, 3));
      }
      wg_commit();
#pragma unroll
      for (int s = 0; s < 5; s++) {
        if (s == 0) mma_rs80_k_z(pq, qf[s], make_desc(sb16, OFF_MISC, 16, 256, 3));
        else mma_rs80_k(pq, qf[s], make_desc(sb16, OFF_MISC + s * 2560, 16, 256, 3));
      }
      wg_commit();
      {
        const int mat = lane >> 3;
        const int tok = warp * 16 + (mat & 1) * 8 + (lane & 7);
        const uint32_t ones = (t == 0) ? 0x00003f80u : 0u;
        __syncwarp();
#pragma unroll
        for (int p = 0; p < 2; p++) {
          const uint32_t rowa = sb + OFF_A + p * SLOT_A + tok * 128;
#pragma unroll
          for (int gg = 0; gg < 3; gg++) {
            const int g0 = 5 * p + 2 * gg;
            uint32_t r0 = pack_bf16(ACC(3, g0, 0), ACC(3, g0, 1)), r1 = pack_bf16(ACC(3, g0, 2), ACC(3, g0, 3));
            uint32_t r2 = ones, r3 = ones;
            if (gg < 2) { r2 = pack_bf16(ACC(3, g0 + 1, 0), ACC(3, g0 + 1, 1)); r3 = pack_bf16(ACC(3, g0 + 1, 2), ACC(3, g0 + 1, 3)); }
            stsm4(rowa + (((2 * gg + (mat >> 1)) ^ (tok & 7)) << 4), r0, r1, r2, r3);
          }
        }
      }
#undef ACC
      wg_wait<1>();
      fence_regs(pk);
#pragma unroll
      for (int G = 0; G < 10; G++) {
        P[0][G] = pack_bf16(pk[4 * G], pk[4 * G + 1]); P[1][G] = pack_bf16(pk[4 * G + 2], pk[4 * G + 3]);
      }
      wg_wait<0>();
      fence_regs(pq);
#pragma unroll
      for (int G = 0; G < 10; G++) {
        qp[0][G] = pack_bf16(pq[4 * G], pq[4 * G + 1]); qp[1][G] = pack_bf16(pq[4 * G + 2], pq[4 * G + 3]);
      }
    }

    uint32_t fr[10][4];
    uint32_t xv[2][10];
#pragma unroll
    for (int g = 0; g < 10; g++) xv[0][g] = xv[1][g] = 0u;
    int pass;
    pass = gridDim.y;
#pragma unroll 1
    do {
    feature_map(P, fr);
    if (pass != 0) {
    {
      const int mat = lane >> 3;
      const int tok = warp * 16 + (mat & 1) * 8 + (lane & 7);
      const uint32_t base = sb + OFF_B + tok * 32 + (((mat >> 1) ^ ((tok >> 2) & 1)) << 4);
#pragma unroll
      for (int G = 0; G < 10; G++) stsm4(base + G * 4096, fr[G][0], fr[G][1], fr[G][2], fr[G][3]);
      fence_async_smem();
      bar_sync(1, 256);
      float kv[40];
      const uint32_t a0 = sb16 + ((OFF_A + wg * SLOT_A) >> 4), b0 = sb16 + ((OFF_B + wg * 20480) >> 4);
      wg_fence();
#pragma unroll
      for (int ks = 0; ks < 8; ks++) {
        if (ks == 0) mma_ss80_tt_z(kv, make_desc(a0, 0, 16, 1024, 1), make_desc(b0, 0, 4096, 256, 3));
        else mma_ss80_tt(kv, make_desc(a0, ks * 2048, 16, 1024, 1), make_desc(b0, ks * 512, 4096, 256, 3));
      }
      wg_commit();
      wg_wait<0>();
      fence_regs(kv);
      TSTAMP(31);
      release(emptyA); release(emptyA + 8); releaseB(emptyB); release(bars + 8 * B_PEER2);
      const uint32_t dst = sb + OFF_MISC + wg * (KV_PAIR * 4);
      const int m0 = (warp & 3) * 16 + (lane >> 2);
#pragma unroll
      for (int r = 0; r < 2; r++) {
        const int m = m0 + 8 * r;
        const bool hi = m >= 20;
        uint32_t v[10];
#pragma unroll
        for (int G = 0; G < 10; G++) v[G] = __float_as_uint(hi ? kv[4 * G + 2 * r + 1] : kv[4 * G + 2 * r]);
        const uint32_t p = dst + 4 * (m < 40 ? m * 48 + t * 12 : 1920 + t * 24 + 12);
        if (m <= 40) {
          sts128(p, make_uint4(v[0], v[1], v[2], v[3])); sts128(p + 16, make_uint4(v[4], v[5], v[6], v[7]));
          sts128(p + 32, make_uint4(v[8], v[9], 0u, 0u));
        }
      }
      if (m0 == 32) {
        const uint32_t p = dst + 4 * (1920 + t * 24);
        sts128(p, make_uint4(__float_as_uint(kv[2]), __float_as_uint(kv[6]), __float_as_uint(kv[10]), __float_as_uint(kv[14])));
        sts128(p + 16, make_uint4(__float_as_uint(kv[18]), __float_as_uint(kv[22]), __float_as_uint(kv[26]), __float_as_uint(kv[30])));
        sts128(p + 32, make_uint4(__float_as_uint(kv[34]), __float_as_uint(kv[38]), 0u, 0u));
      }
      signal(B_SIGKV);
    }
    TSTAMP(5);

    {
      {
        mbar_wait(bars + 8 * B_XR, 0);
        const uint32_t xa = sb + OFF_B + (warp / 3) * SLOT_B + SPARE + (warp % 3) * 2560 + (lane >> 2) * 160 + t * 4;
#pragma unroll
        for (int g = 0; g < 10; g++) { xv[0][g] = lds32(xa + g * 16); xv[1][g] = lds32(xa + 1280 + g * 16); }
      }
      float acc[80];
      zero_regs(acc);
      uint32_t pa = 0, pb = 0;
#pragma unroll 1
      for (int k = 0; k < 5; k++) {
        mbar_wait(fullA + 8 * ra.idx, ra.phase);
        if ((k & 1) == 0) mbar_wait(fullB + 8 * rb.idx, rb.phase);
        if (k == 0) TSTAMP(6);
        const uint32_t a0 = sb16 + ((OFF_A + ra.idx * SLOT_A + wg * 8192) >> 4);
        const uint32_t b0 = sb16 + ((OFF_B + rb.idx * SLOT_B + (k & 1) * 20480) >> 4);
        wg_fence();
#pragma unroll
        for (int kk = 0; kk < 4; kk++) {
          mma_ss160(acc, make_desc(a0, kk * 32, 16, 1024, 1), make_desc(b0, kk * 1024, 4096, 512, 2));
          if (kk == 0) {
            wg_commit();
            if (k > 0) {
              wg_wait<1>();
              release(emptyA + 8 * pa);
              if ((k & 1) == 0) releaseB(emptyB + 8 * pb);
            }
          }
        }
        wg_commit();
        pa = ra.idx; pb = rb.idx;
        ra.next<NA>();
        if ((k & 1) || k == 4) rb.next<NB>();
      }
      mbar_wait(bars + 8 * B_PEER2, 0);
      wg_wait<0>();
      fence_regs(acc);
      release(emptyA + 8 * pa);
      TSTAMP(7);
      {
        uint32_t sn[20];
        if (rank) {
#pragma unroll
          for (int e = 0; e < 20; e++) sn[e] = pack_bf16(acc[2 * e], acc[2 * e + 1]);
#pragma unroll
          for (int e = 0; e < 40; e++) acc[e] = acc[40 + e];
        } else {
#pragma unroll
          for (int e = 0; e < 20; e++) sn[e] = pack_bf16(acc[40 + 2 * e], acc[41 + 2 * e]);
        }
        const uint32_t peer = map_peer(sb, rank ^ 1);
#pragma unroll
        for (int q = 0; q < 5; q++)
          st_async16(peer + OFF_B + 20480 + tid * 16 + q * 4096, sn[4 * q], sn[4 * q + 1], sn[4 * q + 2], sn[4 * q + 3],
                     peer + OFF_BAR + 8 * (B_DSR + 8 + wg));
#pragma unroll
        for (int g = 0; g < 10; g++) {
          acc[4 * g] += bf_lo(xv[0][g]); acc[4 * g + 1] += bf_hi(xv[0][g]);
          acc[4 * g + 2] += bf_lo(xv[1][g]); acc[4 * g + 3] += bf_hi(xv[1][g]);
        }
        bar_sync(1, 256);
        mbar_wait(bars + 8 * (B_DSR + 8 + wg), 0);
#pragma unroll
        for (int q = 0; q < 5; q++) {
          const uint4 v = lds128(sb + OFF_B + 20480 + tid * 16 + q * 4096);
          xv[0][2 * q] = pack_bf16(acc[8 * q] + bf_lo(v.x), acc[8 * q + 1] + bf_hi(v.x));
          xv[1][2 * q] = pack_bf16(acc[8 * q + 2] + bf_lo(v.y), acc[8 * q + 3] + bf_hi(v.y));
          xv[0][2 * q + 1] = pack_bf16(acc[8 * q + 4] + bf_lo(v.z), acc[8 * q + 5] + bf_hi(v.z));
          xv[1][2 * q + 1] = pack_bf16(acc[8 * q + 6] + bf_lo(v.w), acc[8 * q + 7] + bf_hi(v.w));
        }
        releaseB(emptyB + 8 * pb);
      }
      store_tile(sb + OFF_STG, xv, g_X1 + (size_t)(128 * i + 16 * warp) * D_ + 80 * j);
#pragma unroll
      for (int r = 0; r < 2; r++) {
        float s = 0.f;
#pragma unroll
        for (int g = 0; g < 10; g++) {
          acc[4 * g + 2 * r] = bf_lo(xv[r][g]); acc[4 * g + 2 * r + 1] = bf_hi(xv[r][g]);
          s += acc[4 * g + 2 * r] + acc[4 * g + 2 * r + 1];
        }
        s += __shfl_xor_sync(0xffffffffu, s, 1); s += __shfl_xor_sync(0xffffffffu, s, 2);
        const float mu = s * (1.f / 80.f);
        float q = 0.f;
#pragma unroll
        for (int g = 0; g < 10; g++) {
          const float d0 = acc[4 * g + 2 * r] - mu, d1 = acc[4 * g + 2 * r + 1] - mu;
          q = fmaf(d0, d0, q); q = fmaf(d1, d1, q);
        }
        q += __shfl_xor_sync(0xffffffffu, q, 1); q += __shfl_xor_sync(0xffffffffu, q, 2);
        if (t == 0) g_st1[(128 * i + rloc + 8 * r) * 8 + j] = make_float2(mu, q);
      }
      signal(B_SIGX1);
    }
    TSTAMP(8);
#pragma unroll
    for (int G = 0; G < 10; G++) { P[0][G] = qp[0][G]; P[1][G] = qp[1][G]; }
    }
    asm volatile("" : "+r"(pass));
    } while (pass-- != 0);

    uint32_t of[5][4];
    {
      mbar_wait(bars + 8 * B_KV, 0);
      uint4 kvr[2][3];
#pragma unroll
      for (int u = 0; u < 2; u++) {
        const int it = tid + 256 * u, p = it / 192, rem = it - 192 * p, n = rem >> 2, tq = rem & 3;
        const uint32_t sp = sb + OFF_MISC + 4 * (p * KV_PAIR + (n < 40 ? n * 48 + tq * 12 : 1920 + tq * 24 + (n & 1) * 12));
        if (it < 384) { kvr[u][0] = lds128(sp); kvr[u][1] = lds128(sp + 16); kvr[u][2] = lds128(sp + 32); }
      }
      bar_sync(1, 256);
#pragma unroll
      for (int u = 0; u < 2; u++) {
        const int it = tid + 256 * u, p = it / 192, rem = it - 192 * p, n = rem >> 2, tq = rem & 3;
        const int sh = (n < 40 ? (n >= 20) : (n & 1)) * 16;
        const uint32_t v[10] = {kvr[u][0].x, kvr[u][0].y, kvr[u][0].z, kvr[u][0].w, kvr[u][1].x, kvr[u][1].y, kvr[u][1].z, kvr[u][1].w, kvr[u][2].x, kvr[u][2].y};
        uint8_t* dst = sgen + OFF_MISC + p * 7680 + n * 32 + tq * 4;
        const int sw = ((n >> 2) & 1) << 4;
        if (it < 384) {
#pragma unroll
          for (int G = 0; G < 10; G++)
            *reinterpret_cast<uint32_t*>(dst + (G >> 1) * 1536 + (((G & 1) << 4) ^ sw)) = pack_bf16(__uint_as_float(v[G]), 0.f) << sh;
        }
      }
      fence_async_smem();
      bar_sync(1, 256);
      float o0[24], o1[24];
      wg_fence();
#pragma unroll
      for (int g = 0; g < 5; g++) {
        if (g == 0) mma_rs48_k_z(o0, fr[g], make_desc(sb16, OFF_MISC, 16, 256, 3));
        else mma_rs48_k(o0, fr[g], make_desc(sb16, OFF_MISC + g * 1536, 16, 256, 3));
      }
#pragma unroll
      for (int g = 0; g < 5; g++) {
        if (g == 0) mma_rs48_k_z(o1, fr[5], make_desc(sb16, OFF_MISC + 7680, 16, 256, 3));
        else mma_rs48_k(o1, fr[5 + g], make_desc(sb16, OFF_MISC + 7680 + g * 1536, 16, 256, 3));
      }
      wg_commit();
      wg_wait<0>();
      fence_regs(o0); fence_regs(o1);
      signal(B_MFREE);
#pragma unroll
      for (int r = 0; r < 2; r++) {
        const float a0 = __fdividef(st_g[r], o0[20 + 2 * r] + 1e-6f), a1 = __fdividef(st_g[r], o0[21 + 2 * r] + 1e-6f);
        const float b0 = __fdividef(st_g[r], o1[20 + 2 * r] + 1e-6f), b1 = __fdividef(st_g[r], o1[21 + 2 * r] + 1e-6f);
        const float am = t < 2 ? a0 : a1, bm = t < 2 ? b0 : b1;
#pragma unroll
        for (int g = 0; g < 5; g++) {
          const float sa = g < 2 ? a0 : (g == 2 ? am : a1), sb2 = g < 2 ? b0 : (g == 2 ? bm : b1);
          of[g >> 1][(g & 1) * 2 + r] = pack_bf16(o0[4 * g + 2 * r] * sa, o0[4 * g + 2 * r + 1] * sa);
          of[(5 + g) >> 1][((5 + g) & 1) * 2 + r] = pack_bf16(o1[4 * g + 2 * r] * sb2, o1[4 * g + 2 * r + 1] * sb2);
        }
      }
    }
    TSTAMP(9);

    uint32_t hf[12][4];
    {
      float acc[96];
      uint32_t pa = 0, pb = 0;
#pragma unroll 1
      for (int k = 0; k < 10; k++) {
        mbar_wait(fullA + 8 * ra.idx, ra.phase);
        if (tid == 0) TRACE(52 + k);
        if ((k & 1) == 0) mbar_wait(fullB + 8 * rb.idx, rb.phase);
        if (tid == 0) TRACE(84 + k);
        if (k == 0) TSTAMP(10);
        const uint32_t a0 = sb16 + ((OFF_A + ra.idx * SLOT_A + wg * 8192) >> 4);
        const uint32_t b0 = sb16 + ((OFF_B + rb.idx * SLOT_B + (k & 1) * 24576) >> 4);
        wg_fence();
#pragma unroll
        for (int kk = 0; kk < 4; kk++) {
          if (kk == 0) mma_ss192_p(acc, make_desc(a0, 0, 16, 1024, 1), make_desc(b0, 0, 8192, 1024, 1), k);
          else mma_ss192(acc, make_desc(a0, kk * 32, 16, 1024, 1), make_desc(b0, kk * 2048, 8192, 1024, 1));
          if (kk == 0) {
            wg_commit();
            if (k > 0) {
              wg_wait<1>();
              release(emptyA + 8 * pa);
              if ((k & 1) == 0) releaseB(emptyB + 8 * pb);
            }
          }
        }
        wg_commit();
        pa = ra.idx; pb = rb.idx;
        ra.next<NA>();
        if (k & 1) rb.next<NB>();
      }
      float rs[2], mm[2];
      mbar_wait(bars + 8 * B_ST1, 0);
#pragma unroll
      for (int r = 0; r < 2; r++) {
        const uint4 su = lds128(sb + OFF_MISC + (rloc + 8 * r) * 64 + t * 16);
        const float m0 = __uint_as_float(su.x), m1 = __uint_as_float(su.z);
        float mu = m0 + m1;
        mu += __shfl_xor_sync(0xffffffffu, mu, 1); mu += __shfl_xor_sync(0xffffffffu, mu, 2);
        mu *= 0.125f;
        const float d0 = m0 - mu, d1 = m1 - mu;
        float q = __uint_as_float(su.y) + __uint_as_float(su.w) + 80.f * (d0 * d0 + d1 * d1);
        q += __shfl_xor_sync(0xffffffffu, q, 1); q += __shfl_xor_sync(0xffffffffu, q, 2);
        rs[r] = rsqrtf(q * (1.f / D_) + 1e-5f);
        mm[r] = -mu * rs[r];
      }
      wg_wait<0>();
      fence_regs(acc);
      releaseB(emptyB + 8 * pb);
      release(bars + 8 * B_PEER);
      TSTAMP(11);
      const float hs0 = 0.5f - 0.5f * st_g[0], hs1 = 0.5f - 0.5f * st_g[1];
#pragma unroll
      for (int g = 0; g < 24; g++) {
        const float2 cs = *reinterpret_cast<const float2*>(s_cs + 80 + 8 * g + 2 * t);
        const float v0 = gelu_s(fmaf(acc[4 * g], rs[0], mm[0] * cs.x), hs0), v1 = gelu_s(fmaf(acc[4 * g + 1], rs[0], mm[0] * cs.y), hs0);
        const float v2 = gelu_s(fmaf(acc[4 * g + 2], rs[1], mm[1] * cs.x), hs1), v3 = gelu_s(fmaf(acc[4 * g + 3], rs[1], mm[1] * cs.y), hs1);
        hf[g >> 1][(g & 1) * 2] = pack_bf16(v0, v1);
        hf[g >> 1][(g & 1) * 2 + 1] = pack_bf16(v2, v3);
      }
    }
    TSTAMP(12);

    {
      float acc[80], kp[40];
      uint32_t sn[20], kb[20];
      const uint32_t peer = map_peer(sb, rank ^ 1);
      const uint32_t tag = lds32(sb + OFF_BAR + 8 * NBAR);
      const uint4* gp = g_part + (size_t)(i * 8 + j) * 3840 + tid;
      uint4 pv4[15];
      Ring r4{0, 0};
      auto add8 = [&](int q, const uint4 v) {
        float* d = &kp[8 * q];
        d[0] += bf_lo(v.x); d[1] += bf_hi(v.x); d[2] += bf_lo(v.y); d[3] += bf_hi(v.y);
        d[4] += bf_lo(v.z); d[5] += bf_hi(v.z); d[6] += bf_lo(v.w); d[7] += bf_hi(v.w);
      };
      auto send = [&](int c) {
        const uint32_t dso = peer + OFF_DS + (c & 1) * 20480 + tid * 16, dsb = peer + OFF_BAR + 8 * (B_DSR + 2 * c + wg);
#pragma unroll
        for (int q = 0; q < 5; q++) st_async16(dso + q * 4096, sn[4 * q], sn[4 * q + 1], sn[4 * q + 2], sn[4 * q + 3], dsb);
      };
      auto finish = [&](int c) {
        mbar_wait(bars + 8 * (B_DSR + 2 * c + wg), 0);
        uint4* dst = g_part + (size_t)((i * 8 + ((j + 2 * c + 2) & 7)) * 3 + c) * 1280 + tid;
#pragma unroll
        for (int q = 0; q < 5; q++) {
          const uint4 v = lds128(sb + OFF_DS + (c & 1) * 20480 + tid * 16 + q * 4096);
          st_relaxed16(dst + q * 256, (add_bf2(v.x, kb[4 * q]) & ~1u) | tag, add_bf2(v.y, kb[4 * q + 1]),
                       add_bf2(v.z, kb[4 * q + 2]), add_bf2(v.w, kb[4 * q + 3]));
        }
      };
#pragma unroll
      for (int e = 0; e < 20; e++) sn[e] = kb[e] = 0u;
      auto chunk = [&](const int c, auto last_c) {
        constexpr bool LAST = decltype(last_c)::value;
        const uint32_t e0 = r4.idx;
        auto rel = [&](int u) { const uint32_t e = e0 + u; releaseB(bars + 8 * (B_EMPTY4 + (e >= NU4 ? e - NU4 : e))); };
#pragma unroll
        for (int u = 0; u < 4; u++) {
          mbar_wait(bars + 8 * (B_FULL4 + r4.idx), r4.phase);
          const uint32_t b0 = sb16 + ((OFF_B + r4.idx * UNIT4) >> 4);
          TRS(c * 16 + u * 3);
          wg_fence();
#pragma unroll
          for (int s = 0; s < (u < 3 ? 4 : 5); s++) {
            const uint64_t db = make_desc(b0, s * 1024, u < 3 ? 4096 : 5120, 512, 2);
            if (u == 0 && s == 0) mma_rs160_n_z(acc, hf[0], db);
            else if (u < 3) mma_rs160_n(acc, hf[(4 * u + s) % 12], db);
            else mma_rs160_n(acc, of[s], db);
          }
          wg_commit();
          TRS(c * 16 + u * 3 + 1);
          r4.next<NU4>();
          if (u > 0 && !LAST) { wg_wait<1>(); rel(u - 1); }
          if (u == 0 && c > 0) send(c - 1);
          if (u == 1 && c == 0) { if (wg == 0) bar_arrive(2, 256); mbar_wait(bars + 8 * B_PEER, 0); }
          if (u == (LAST ? 1 : 2) && c > 0) finish(c - 1);
          TRS(c * 16 + u * 3 + 2);
        }
        if (LAST) {
#pragma unroll
          for (int q = 0; q < 10; q++) pv4[q] = ld_relaxed16(gp + q * 256);
        }
        wg_wait<0>();
        fence_regs(acc);
        if (!LAST) rel(3);
        TRS(c * 16 + 12);
        if (rank) {
#pragma unroll
          for (int e = 0; e < 20; e++) { sn[e] = pack_bf16(acc[2 * e], acc[2 * e + 1]); kb[e] = pack_bf16(acc[40 + 2 * e], acc[41 + 2 * e]); }
        } else {
#pragma unroll
          for (int e = 0; e < 20; e++) { kb[e] = pack_bf16(acc[2 * e], acc[2 * e + 1]); sn[e] = pack_bf16(acc[40 + 2 * e], acc[41 + 2 * e]); }
        }
#pragma unroll
        for (int e = 0; e < 20; e++) asm volatile("" : "+r"(sn[e]), "+r"(kb[e]));
        TRS(c * 16 + 13);
      };
      if (wg == 1) bar_sync(2, 256);
#pragma unroll 1
      for (int c = 0; c < 3; c++) chunk(c, BoolC<false>{});
      chunk(3, BoolC<true>{});
#pragma unroll
      for (int q = 10; q < 15; q++) pv4[q] = ld_relaxed16(gp + q * 256);
      send(3);
      TSTAMP(13);
      {
        const float w0 = 1.f - st_g[0], w1s = 1.f - st_g[1];
#pragma unroll
        for (int g = 0; g < 10; g++) {
          kp[4 * g] = fmaf(w0, bf_lo(xv[0][g]), rank ? acc[40 + 4 * g] : acc[4 * g]);
          kp[4 * g + 1] = fmaf(w0, bf_hi(xv[0][g]), rank ? acc[41 + 4 * g] : acc[4 * g + 1]);
          kp[4 * g + 2] = fmaf(w1s, bf_lo(xv[1][g]), rank ? acc[42 + 4 * g] : acc[4 * g + 2]);
          kp[4 * g + 3] = fmaf(w1s, bf_hi(xv[1][g]), rank ? acc[43 + 4 * g] : acc[4 * g + 3]);
        }
      }
      mbar_wait(bars + 8 * (B_DSR + 6 + wg), 0);
#pragma unroll
      for (int q = 0; q < 5; q++) add8(q, lds128(sb + OFF_DS + 20480 + tid * 16 + q * 4096));
#pragma unroll 1
      for (uint32_t n = 0; n < (WAIT_LIMIT >> 4); n++) {
        uint32_t m = 0u;
#pragma unroll
        for (int q = 0; q < 15; q++) {
          const uint32_t bad = (pv4[q].x ^ tag) & 1u;
          m |= bad;
          if (bad) pv4[q] = ld_relaxed16(gp + q * 256);
        }
        if (m == 0u) break;
      }
      TSTAMP(14);
#pragma unroll
      for (int q = 0; q < 15; q++) add8(q % 5, pv4[q]);
      __syncwarp();
      uint32_t ov[2][10];
#pragma unroll
      for (int g = 0; g < 10; g++) { ov[0][g] = pack_bf16(kp[4 * g], kp[4 * g + 1]); ov[1][g] = pack_bf16(kp[4 * g + 2], kp[4 * g + 3]); }
      store_tile(sb + OFF_OUT, ov, out + (size_t)(128 * i + 16 * warp) * D_ + 80 * j);
    }
    TSTAMP(15);
    if (tid == 0) asm volatile("red.relaxed.gpu.global.add.u32 [%0], 1;" ::"l"(g_flags + FL_DONE * 32) : "memory");
  }
}

namespace {
typedef CUresult (*EncodeFn)(CUtensorMap*, CUtensorMapDataType, cuuint32_t, void*, const cuuint64_t*, const cuuint64_t*,
                             const cuuint32_t*, const cuuint32_t*, CUtensorMapInterleave, CUtensorMapSwizzle,
                             CUtensorMapL2promotion, CUtensorMapFloatOOBfill);

void encode(EncodeFn fn, CUtensorMap* m, const void* ptr, int rank, const cuuint64_t* dims, const cuuint64_t* strides,
            const cuuint32_t* box, CUtensorMapSwizzle swz) {
  cuuint32_t es[5] = {1, 1, 1, 1, 1};
  fn(m, CU_TENSOR_MAP_DATA_TYPE_BFLOAT16, rank, const_cast<void*>(ptr), dims, strides, box, es, CU_TENSOR_MAP_INTERLEAVE_NONE,
     swz, CU_TENSOR_MAP_L2_PROMOTION_L2_128B, CU_TENSOR_MAP_FLOAT_OOB_FILL_NONE);
}
}

extern "C" void kernel_launch(void* const* d_in, const int* in_sizes, int n_in, void* d_out, int out_size) {
  (void)in_sizes; (void)n_in; (void)out_size;
  const __nv_bfloat16* x = (const __nv_bfloat16*)d_in[0];
  const __nv_bfloat16* wqkv = (const __nv_bfloat16*)d_in[1];
  const __nv_bfloat16* wphi = (const __nv_bfloat16*)d_in[2];
  const __nv_bfloat16* wo = (const __nv_bfloat16*)d_in[3];
  const __nv_bfloat16* w1 = (const __nv_bfloat16*)d_in[5];
  const __nv_bfloat16* w2 = (const __nv_bfloat16*)d_in[6];
  const __nv_bfloat16* w3 = (const __nv_bfloat16*)d_in[7];
  const __nv_bfloat16* w4 = (const __nv_bfloat16*)d_in[8];
  const __nv_bfloat16* gate_w = (const __nv_bfloat16*)d_in[9];

  static EncodeFn enc = nullptr;
  static void *pHs = nullptr, *pX1 = nullptr;
  if (!enc) {
    cudaDriverEntryPointQueryResult qr;
    cudaGetDriverEntryPoint("cuTensorMapEncodeTiled", (void**)&enc, cudaEnableDefault, &qr);
    cudaGetSymbolAddress(&pHs, g_Hs);
    cudaGetSymbolAddress(&pX1, g_X1);
    cudaFuncSetAttribute(fused_kernel, cudaFuncAttributeMaxDynamicSharedMemorySize, SMEM_BYTES);
  }
  Maps m;
  {
    cuuint64_t dims[2] = {D_, S_}, str[1] = {D_ * 2};
    cuuint32_t box[2] = {64, 128}, boxh[2] = {64, 64};
    encode(enc, &m.x, x, 2, dims, str, boxh, CU_TENSOR_MAP_SWIZZLE_128B);
    encode(enc, &m.hs, (const char*)pHs + 2 * D_ * 2, 2, dims, str, box, CU_TENSOR_MAP_SWIZZLE_128B);
    encode(enc, &m.x1, pX1, 2, dims, str, boxh, CU_TENSOR_MAP_SWIZZLE_128B);
    cuuint32_t boxr[2] = {80, 16};
    encode(enc, &m.xr, x, 2, dims, str, boxr, CU_TENSOR_MAP_SWIZZLE_NONE);
  }
  {
    cuuint64_t dims[3] = {80, D_, 8}, str[2] = {D_ * 2, 160};
    cuuint32_t boxm[3] = {64, 64, 1}, boxr[3] = {16, 64, 1};
    encode(enc, &m.w1m, w1, 3, dims, str, boxm, CU_TENSOR_MAP_SWIZZLE_128B);
    encode(enc, &m.w1r, w1, 3, dims, str, boxr, CU_TENSOR_MAP_SWIZZLE_32B);
  }
  {
    cuuint64_t dims[4] = {80, D_, 3, 8}, str[3] = {3 * D_ * 2, D_ * 2, 160};
    cuuint32_t boxm[4] = {64, 64, 3, 1}, boxr[4] = {16, 64, 3, 1};
    encode(enc, &m.qm, wqkv, 4, dims, str, boxm, CU_TENSOR_MAP_SWIZZLE_128B);
    encode(enc, &m.qr, wqkv, 4, dims, str, boxr, CU_TENSOR_MAP_SWIZZLE_32B);
  }
  {
    cuuint64_t dims[3] = {32, D_, 20}, dims4[3] = {32, F_, 20}, str[2] = {D_ * 2, 64};
    cuuint32_t box4[3] = {32, 64, 5}, boxo[3] = {32, 80, 5};
    encode(enc, &m.w4, w4, 3, dims4, str, box4, CU_TENSOR_MAP_SWIZZLE_64B);
    encode(enc, &m.wo, wo, 3, dims, str, boxo, CU_TENSOR_MAP_SWIZZLE_64B);
    encode(enc, &m.w2, w2, 3, dims, str, box4, CU_TENSOR_MAP_SWIZZLE_64B);
  }
  {
    cuuint64_t dims[3] = {64, D_, 24}, str[2] = {F_ * 2, 128};
    cuuint32_t box[3] = {64, 64, 3};
    encode(enc, &m.w3, w3, 3, dims, str, box, CU_TENSOR_MAP_SWIZZLE_128B);
  }
  fused_kernel<<<NCTA, 384, SMEM_BYTES, cudaStreamPerThread>>>(m, x, wqkv, wphi, w1, w2, w3, w4, wo, gate_w, (__nv_bfloat16*)d_out);
}
```

```cpp
#include <cuda_runtime.h>
#include <cuda_bf16.h>
#include <cuda.h>
#include <stdint.h>

namespace {

constexpr int S_ = 2048, D_ = 640, F_ = 1536;
constexpr int NCTA = 128;
constexpr int KV_PAIR = 40 * 48 + 96;
constexpr int KV_J = 2 * KV_PAIR;

constexpr int SLOT_B = 49152, NB = 3;
constexpr int SLOT_A = 16384, NA = 4;
constexpr int OFF_B = 0;
constexpr int OFF_A = OFF_B + NB * SLOT_B;
constexpr int OFF_STG = OFF_A + 2 * SLOT_A;
constexpr int OFF_MISC = OFF_A + NA * SLOT_A;
constexpr int OFF_XST = OFF_MISC + 13312;
constexpr int OFF_CS = OFF_MISC + 16384;
constexpr int OFF_BAR = OFF_CS + 1088;
constexpr int SMEM_BYTES = OFF_BAR + 512 + 512;
constexpr int B_FULLA = 0, B_FULLB = 4, B_CS = 7, B_XR = 8, B_KV = 9, B_ST1 = 10, B_FULL4 = 11  , B_DSR = 16  ,
              B_EMPTYB = 26  , B_SIGP = 29, B_SIGH = 30, B_SIGKV = 31, B_SIGX1 = 32, B_MFREE = 33, B_EMPTY4 = 34  ,
              B_EMPTYA = 39  , B_PEER = 43, B_PEER2 = 44, NBAR = 45;
constexpr int SPARE = 40960;
constexpr int UNIT4 = 25600, NU4 = 5;
constexpr int OFF_DS = OFF_A, OFF_OUT = OFF_A + 40960;

constexpr int FL_DONE = 0, FL_H = 1  , FL_X1 = FL_H + 32, FL_KV = FL_X1 + 16, FL_CS = FL_KV + 8, FL_CS3 = FL_CS + 8, FL_ST = FL_CS3 + 8;
constexpr int FL_S1 = FL_ST + 16, FL_COUNT = FL_S1 + 16;
constexpr int ACC_FLOATS = 8 * KV_J + D_ + F_;

struct Maps {
  CUtensorMap x, w1m, w1r, qm, qr, hs, w2, x1, w3, w4, wo, xr;
};

}

__device__ __align__(1024) __nv_bfloat16 g_Hs[(S_ + 4) * D_];
__device__ __align__(1024) __nv_bfloat16 g_X1[S_ * D_];
__device__ __align__(128) float g_acc[2][ACC_FLOATS];
__device__ __align__(128) float4 g_xstat[S_];
__device__ __align__(128) float2 g_st1[S_ * 8];
__device__ __align__(128) uint4 g_part[16 * 8 * 3 * 1280];
__device__ __align__(128) unsigned g_flags[FL_COUNT * 32];
#define TSTAMP(n) do {} while (0)
#define TSTAMPX(n) do {} while (0)
#define TRACE(n) do {} while (0)
#define TRS(n) do {} while (0)

namespace {

__device__ __forceinline__ long long gtime() { long long t; asm volatile("mov.u64 %0, %%globaltimer;" : "=l"(t)); return t; }
__device__ __forceinline__ uint32_t smem_u32(const void* p) { return (uint32_t)__cvta_generic_to_shared(p); }
__device__ __forceinline__ void mbar_init(uint32_t bar, int cnt) {
  asm volatile("mbarrier.init.shared::cta.b64 [%0], %1;" ::"r"(bar), "r"(cnt) : "memory");
}
__device__ __forceinline__ void mbar_expect_tx(uint32_t bar, int bytes) {
  asm volatile("mbarrier.arrive.expect_tx.shared::cta.b64 _, [%0], %1;" ::"r"(bar), "r"(bytes) : "memory");
}
__device__ __forceinline__ void mbar_arrive_cta(uint32_t bar, uint32_t cta) {
  asm volatile("{\n.reg .b32 ra;\nmapa.shared::cluster.u32 ra, %0, %1;\nmbarrier.arrive.shared::cluster.b64 _, [ra];\n}"
               ::"r"(bar), "r"(cta) : "memory");
}
__device__ __forceinline__ uint32_t mbar_try(uint32_t bar, uint32_t parity) {
  uint32_t ok;
  asm volatile("{\n.reg .pred p;\nmbarrier.try_wait.parity.shared::cta.b64 p, [%1], %2;\nselp.u32 %0, 1, 0, p;\n}"
               : "=r"(ok) : "r"(bar), "r"(parity) : "memory");
  return ok;
}
constexpr uint32_t WAIT_LIMIT = 1u << 22;
__device__ __forceinline__ void mbar_wait(uint32_t bar, uint32_t parity) {
  uint32_t n = 0;
  while (!mbar_try(bar, parity) && ++n < WAIT_LIMIT) {}
}
__device__ __forceinline__ unsigned ld_acquire(const unsigned* p) {
  unsigned v;
  asm volatile("ld.acquire.gpu.global.u32 %0, [%1];" : "=r"(v) : "l"(p) : "memory");
  return v;
}
__device__ __forceinline__ void flag_wait(int idx, unsigned target) {
  const unsigned* p = g_flags + idx * 32;
  uint32_t n = 0;
  while ((int)(ld_acquire(p) - target) < 0 && ++n < (WAIT_LIMIT >> 4)) {}
}
__device__ __forceinline__ void flag_add(int idx) {
  asm volatile("red.release.gpu.global.add.u32 [%0], 1;" ::"l"(g_flags + idx * 32) : "memory");
}
__device__ __forceinline__ void flag_add_relaxed(int idx) {
  asm volatile("red.relaxed.gpu.global.add.u32 [%0], 1;" ::"l"(g_flags + idx * 32) : "memory");
}
__device__ __forceinline__ uint32_t mbar_test(uint32_t bar, uint32_t parity) {
  uint32_t ok;
  asm volatile("{\n.reg .pred p;\nmbarrier.test_wait.parity.shared::cta.b64 p, [%1], %2;\nselp.u32 %0, 1, 0, p;\n}"
               : "=r"(ok) : "r"(bar), "r"(parity) : "memory");
  return ok;
}
__device__ __forceinline__ uint32_t lds32(uint32_t a) {
  uint32_t v;
  asm volatile("ld.shared.u32 %0, [%1];" : "=r"(v) : "r"(a) : "memory");
  return v;
}
__device__ __forceinline__ void mbar_arrive(uint32_t bar) {
  asm volatile("mbarrier.arrive.shared::cta.b64 _, [%0];" ::"r"(bar) : "memory");
}
__device__ __forceinline__ void fence_async_glb() { asm volatile("fence.proxy.async.global;" ::: "memory"); }
__device__ __forceinline__ void fence_async_smem() { asm volatile("fence.proxy.async.shared::cta;" ::: "memory"); }
__device__ __forceinline__ void bar_sync(int id, int n) { asm volatile("bar.sync %0, %1;" ::"r"(id), "r"(n) : "memory"); }

__device__ __forceinline__ void tma2d(uint32_t dst, const CUtensorMap* m, uint32_t bar, int c0, int c1) {
  asm volatile("cp.async.bulk.tensor.2d.shared::cluster.global.mbarrier::complete_tx::bytes [%0], [%1, {%3, %4}], [%2];"
               ::"r"(dst), "l"(m), "r"(bar), "r"(c0), "r"(c1) : "memory");
}
__device__ __forceinline__ void tma2d_mc(uint32_t dst, const CUtensorMap* m, uint32_t bar, int c0, int c1) {
  asm volatile("cp.async.bulk.tensor.2d.shared::cluster.global.mbarrier::complete_tx::bytes.multicast::cluster"
               " [%0], [%1, {%3, %4}], [%2], %5;"
               ::"r"(dst), "l"(m), "r"(bar), "r"(c0), "r"(c1), "h"((uint16_t)3) : "memory");
}
__device__ __forceinline__ void tma3d(uint32_t dst, const CUtensorMap* m, uint32_t bar, int c0, int c1, int c2) {
  asm volatile("cp.async.bulk.tensor.3d.shared::cluster.global.mbarrier::complete_tx::bytes [%0], [%1, {%3, %4, %5}], [%2];"
               ::"r"(dst), "l"(m), "r"(bar), "r"(c0), "r"(c1), "r"(c2) : "memory");
}
__device__ __forceinline__ void tma4d(uint32_t dst, const CUtensorMap* m, uint32_t bar, int c0, int c1, int c2, int c3) {
  asm volatile("cp.async.bulk.tensor.4d.shared::cluster.global.mbarrier::complete_tx::bytes [%0], [%1, {%3, %4, %5, %6}], [%2];"
               ::"r"(dst), "l"(m), "r"(bar), "r"(c0), "r"(c1), "r"(c2), "r"(c3) : "memory");
}
__device__ __forceinline__ void tma2d_store(const CUtensorMap* m, uint32_t src, int c0, int c1) {
  asm volatile("cp.async.bulk.tensor.2d.global.shared::cta.bulk_group [%0, {%2, %3}], [%1];"
               ::"l"(m), "r"(src), "r"(c0), "r"(c1) : "memory");
}
__device__ __forceinline__ void bulk_store(void* dst, uint32_t src, uint32_t bytes) {
  asm volatile("cp.async.bulk.global.shared::cta.bulk_group [%0], [%1], %2;" ::"l"(dst), "r"(src), "r"(bytes) : "memory");
}
__device__ __forceinline__ void bulk_load(uint32_t dst, const void* src, uint32_t bytes, uint32_t bar) {
  asm volatile("cp.async.bulk.shared::cluster.global.mbarrier::complete_tx::bytes [%0], [%1], %2, [%3];"
               ::"r"(dst), "l"(src), "r"(bytes), "r"(bar) : "memory");
}
__device__ __forceinline__ void bulk_commit() { asm volatile("cp.async.bulk.commit_group;" ::: "memory"); }
template <int N> __device__ __forceinline__ void bulk_wait() { asm volatile("cp.async.bulk.wait_group %0;" ::"n"(N) : "memory"); }
__device__ __forceinline__ void bulk_wait_read() { asm volatile("cp.async.bulk.wait_group.read 0;" ::: "memory"); }
__device__ __forceinline__ void bar_arrive(int id, int n) { asm volatile("bar.arrive %0, %1;" ::"r"(id), "r"(n) : "memory"); }
__device__ __forceinline__ uint4 lds128(uint32_t a) {
  uint4 v;
  asm volatile("ld.shared.v4.u32 {%0, %1, %2, %3}, [%4];" : "=r"(v.x), "=r"(v.y), "=r"(v.z), "=r"(v.w) : "r"(a) : "memory");
  return v;
}
__device__ __forceinline__ void sts128(uint32_t a, uint4 v) {
  asm volatile("st.shared.v4.u32 [%0], {%1, %2, %3, %4};" ::"r"(a), "r"(v.x), "r"(v.y), "r"(v.z), "r"(v.w) : "memory");
}
__device__ __forceinline__ uint4 ld_relaxed16(const uint4* p) {
  uint4 v;
  asm volatile("ld.relaxed.gpu.global.v4.u32 {%0, %1, %2, %3}, [%4];" : "=r"(v.x), "=r"(v.y), "=r"(v.z), "=r"(v.w) : "l"(p) : "memory");
  return v;
}
__device__ __forceinline__ void st_relaxed16(uint4* p, uint32_t a, uint32_t b, uint32_t c, uint32_t d) {
  asm volatile("st.relaxed.gpu.global.v4.u32 [%0], {%1, %2, %3, %4};" ::"l"(p), "r"(a), "r"(b), "r"(c), "r"(d) : "memory");
}
__device__ __forceinline__ uint32_t map_peer(uint32_t addr, uint32_t cta) {
  uint32_t r;
  asm("mapa.shared::cluster.u32 %0, %1, %2;" : "=r"(r) : "r"(addr), "r"(cta));
  return r;
}
__device__ __forceinline__ void st_async16(uint32_t addr, uint32_t a, uint32_t b, uint32_t c, uint32_t d, uint32_t bar) {
  asm volatile("st.async.weak.shared::cluster.mbarrier::complete_tx::bytes.v4.b32 [%0], {%1, %2, %3, %4}, [%5];"
               ::"r"(addr), "r"(a), "r"(b), "r"(c), "r"(d), "r"(bar) : "memory");
}
__device__ __forceinline__ void l2_prefetch(const void* p, uint32_t bytes) {
  asm volatile("cp.async.bulk.prefetch.L2.global [%0], %1;" ::"l"(p), "r"(bytes) : "memory");
}
__device__ __forceinline__ void prefetch_tmap(const CUtensorMap* m) {
  asm volatile("prefetch.tensormap [%0];" ::"l"(m) : "memory");
}
__device__ __forceinline__ uint64_t make_desc(uint32_t a16, uint32_t off, uint32_t lbo, uint32_t sbo, uint32_t swz) {
  const uint32_t lo = a16 + ((off >> 4) + ((lbo >> 4) << 16)), hi = (sbo >> 4) | (swz << 30);
  uint64_t d;
  asm("mov.b64 %0, {%1, %2};" : "=l"(d) : "r"(lo), "r"(hi));
  return d;
}
__device__ __forceinline__ void wg_fence() { asm volatile("wgmma.fence.sync.aligned;" ::: "memory"); }
__device__ __forceinline__ void wg_commit() { asm volatile("wgmma.commit_group.sync.aligned;" ::: "memory"); }
template <int N> __device__ __forceinline__ void wg_wait() { asm volatile("wgmma.wait_group.sync.aligned %0;" ::"n"(N) : "memory"); }
template <int N> __device__ __forceinline__ void fence_regs(float (&d)[N]) {
#pragma unroll
  for (int i = 0; i < N; i++) asm volatile("" : "+f"(d[i])::"memory");
}
template <int N> __device__ __forceinline__ void zero_regs(float (&d)[N]) {
#pragma unroll
  for (int i = 0; i < N; i++) d[i] = 0.f;
}
__device__ __forceinline__ uint32_t pack_bf16(float lo, float hi) {
  uint32_t r;
  asm("cvt.rn.bf16x2.f32 %0, %1, %2;" : "=r"(r) : "f"(hi), "f"(lo));
  return r;
}
__device__ __forceinline__ float bf_lo(uint32_t v) { return __uint_as_float(v << 16); }
__device__ __forceinline__ float bf_hi(uint32_t v) { return __uint_as_float(v & 0xffff0000u); }
__device__ __forceinline__ uint32_t max_bf2(uint32_t a, uint32_t b) {
  uint32_t r; asm("max.bf16x2 %0, %1, %2;" : "=r"(r) : "r"(a), "r"(b)); return r;
}
__device__ __forceinline__ uint32_t min_bf2(uint32_t a, uint32_t b) {
  uint32_t r; asm("min.bf16x2 %0, %1, %2;" : "=r"(r) : "r"(a), "r"(b)); return r;
}
__device__ __forceinline__ uint32_t add_bf2(uint32_t a, uint32_t b) {
  uint32_t r; asm("add.rn.bf16x2 %0, %1, %2;" : "=r"(r) : "r"(a), "r"(b)); return r;
}
__device__ __forceinline__ float ex2(float x) { float r; asm("ex2.approx.ftz.f32 %0, %1;" : "=f"(r) : "f"(x)); return r; }
__device__ __forceinline__ float rcp(float x) { float r; asm("rcp.approx.ftz.f32 %0, %1;" : "=f"(r) : "f"(x)); return r; }
__device__ __forceinline__ float tanh_ap(float x) { float r; asm("tanh.approx.f32 %0, %1;" : "=f"(r) : "f"(x)); return r; }
struct GeluC { float c0, c1, ch; };
__device__ __forceinline__ GeluC gelu_consts(float rstd, float scale) {
  return GeluC{0.7978845608f * rstd, 0.0356774081f * rstd * rstd * rstd, 0.5f * scale * rstd};
}
__device__ __forceinline__ float gelu_s(float y, const GeluC& c) {
  const float u = y * fmaf(y * y, c.c1, c.c0);
  const float hx = y * c.ch;
  return fmaf(hx, tanh_ap(u), hx);
}
__device__ __forceinline__ void stsm4(uint32_t addr, uint32_t r0, uint32_t r1, uint32_t r2, uint32_t r3) {
  asm volatile("stmatrix.sync.aligned.m8n8.x4.shared.b16 [%0], {%1, %2, %3, %4};"
               ::"r"(addr), "r"(r0), "r"(r1), "r"(r2), "r"(r3) : "memory");
}
__device__ __forceinline__ void red_add4(float* p, float a, float b, float c, float d) {
  asm volatile("red.global.add.v4.f32 [%0], {%1, %2, %3, %4};" ::"l"(p), "f"(a), "f"(b), "f"(c), "f"(d) : "memory");
}

__device__ __forceinline__ void mma_ss256(float (&d)[128], uint64_t descA, uint64_t descB) {
  asm volatile("wgmma.mma_async.sync.aligned.m64n256k16.f32.bf16.bf16 {"
      "%0, %1, %2, %3, %4, %5, %6, %7, %8, %9, %10, %11, %12, %13, %14, %15, "
      "%16, %17, %18, %19, %20, %21, %22, %23, %24, %25, %26, %27, %28, %29, %30, %31, "
      "%32, %33, %34, %35, %36, %37, %38, %39, %40, %41, %42, %43, %44, %45, %46, %47, "
      "%48, %49, %50, %51, %52, %53, %54, %55, %56, %57, %58, %59, %60, %61, %62, %63, "
      "%64, %65, %66, %67, %68, %69, %70, %71, %72, %73, %74, %75, %76, %77, %78, %79, "
      "%80, %81, %82, %83, %84, %85, %86, %87, %88, %89, %90, %91, %92, %93, %94, %95, "
      "%96, %97, %98, %99, %100, %101, %102, %103, %104, %105, %106, %107, %108, %109, %110, %111, "
      "%112, %113, %114, %115, %116, %117, %118, %119, %120, %121, %122, %123, %124, %125, %126, %127"
      "}, %128, %129, 1, 1, 1, 0, 1;\n"
      : "+f"(d[0]), "+f"(d[1]), "+f"(d[2]), "+f"(d[3]), "+f"(d[4]), "+f"(d[5]), "+f"(d[6]), "+f"(d[7]),
        "+f"(d[8]), "+f"(d[9]), "+f"(d[10]), "+f"(d[11]), "+f"(d[12]), "+f"(d[13]), "+f"(d[14]), "+f"(d[15]),
        "+f"(d[16]), "+f"(d[17]), "+f"(d[18]), "+f"(d[19]), "+f"(d[20]), "+f"(d[21]), "+f"(d[22]), "+f"(d[23]),
        "+f"(d[24]), "+f"(d[25]), "+f"(d[26]), "+f"(d[27]), "+f"(d[28]), "+f"(d[29]), "+f"(d[30]), "+f"(d[31]),
        "+f"(d[32]), "+f"(d[33]), "+f"(d[34]), "+f"(d[35]), "+f"(d[36]), "+f"(d[37]), "+f"(d[38]), "+f"(d[39]),
        "+f"(d[40]), "+f"(d[41]), "+f"(d[42]), "+f"(d[43]), "+f"(d[44]), "+f"(d[45]), "+f"(d[46]), "+f"(d[47]),
        "+f"(d[48]), "+f"(d[49]), "+f"(d[50]), "+f"(d[51]), "+f"(d[52]), "+f"(d[53]), "+f"(d[54]), "+f"(d[55]),
        "+f"(d[56]), "+f"(d[57]), "+f"(d[58]), "+f"(d[59]), "+f"(d[60]), "+f"(d[61]), "+f"(d[62]), "+f"(d[63]),
        "+f"(d[64]), "+f"(d[65]), "+f"(d[66]), "+f"(d[67]), "+f"(d[68]), "+f"(d[69]), "+f"(d[70]), "+f"(d[71]),
        "+f"(d[72]), "+f"(d[73]), "+f"(d[74]), "+f"(d[75]), "+f"(d[76]), "+f"(d[77]), "+f"(d[78]), "+f"(d[79]),
        "+f"(d[80]), "+f"(d[81]), "+f"(d[82]), "+f"(d[83]), "+f"(d[84]), "+f"(d[85]), "+f"(d[86]), "+f"(d[87]),
        "+f"(d[88]), "+f"(d[89]), "+f"(d[90]), "+f"(d[91]), "+f"(d[92]), "+f"(d[93]), "+f"(d[94]), "+f"(d[95]),
        "+f"(d[96]), "+f"(d[97]), "+f"(d[98]), "+f"(d[99]), "+f"(d[100]), "+f"(d[101]), "+f"(d[102]), "+f"(d[103]),
        "+f"(d[104]), "+f"(d[105]), "+f"(d[106]), "+f"(d[107]), "+f"(d[108]), "+f"(d[109]), "+f"(d[110]), "+f"(d[111]),
        "+f"(d[112]), "+f"(d[113]), "+f"(d[114]), "+f"(d[115]), "+f"(d[116]), "+f"(d[117]), "+f"(d[118]), "+f"(d[119]),
        "+f"(d[120]), "+f"(d[121]), "+f"(d[122]), "+f"(d[123]), "+f"(d[124]), "+f"(d[125]), "+f"(d[126]), "+f"(d[127])
      : "l"(descA), "l"(descB));
}
__device__ __forceinline__ void mma_ss256_p(float (&d)[128], uint64_t descA, uint64_t descB, int acc) {
  asm volatile("{\n.reg .pred p;\nsetp.ne.b32 p, %130, 0;\n"
      "wgmma.mma_async.sync.aligned.m64n256k16.f32.bf16.bf16 {"
      "%0, %1, %2, %3, %4, %5, %6, %7, %8, %9, %10, %11, %12, %13, %14, %15, "
      "%16, %17, %18, %19, %20, %21, %22, %23, %24, %25, %26, %27, %28, %29, %30, %31, "
      "%32, %33, %34, %35, %36, %37, %38, %39, %40, %41, %42, %43, %44, %45, %46, %47, "
      "%48, %49, %50, %51, %52, %53, %54, %55, %56, %57, %58, %59, %60, %61, %62, %63, "
      "%64, %65, %66, %67, %68, %69, %70, %71, %72, %73, %74, %75, %76, %77, %78, %79, "
      "%80, %81, %82, %83, %84, %85, %86, %87, %88, %89, %90, %91, %92, %93, %94, %95, "
      "%96, %97, %98, %99, %100, %101, %102, %103, %104, %105, %106, %107, %108, %109, %110, %111, "
      "%112, %113, %114, %115, %116, %117, %118, %119, %120, %121, %122, %123, %124, %125, %126, %127"
      "}, %128, %129, p, 1, 1, 0, 1;\n}\n"
      : "+f"(d[0]), "+f"(d[1]), "+f"(d[2]), "+f"(d[3]), "+f"(d[4]), "+f"(d[5]), "+f"(d[6]), "+f"(d[7]),
        "+f"(d[8]), "+f"(d[9]), "+f"(d[10]), "+f"(d[11]), "+f"(d[12]), "+f"(d[13]), "+f"(d[14]), "+f"(d[15]),
        "+f"(d[16]), "+f"(d[17]), "+f"(d[18]), "+f"(d[19]), "+f"(d[20]), "+f"(d[21]), "+f"(d[22]), "+f"(d[23]),
        "+f"(d[24]), "+f"(d[25]), "+f"(d[26]), "+f"(d[27]), "+f"(d[28]), "+f"(d[29]), "+f"(d[30]), "+f"(d[31]),
        "+f"(d[32]), "+f"(d[33]), "+f"(d[34]), "+f"(d[35]), "+f"(d[36]), "+f"(d[37]), "+f"(d[38]), "+f"(d[39]),
        "+f"(d[40]), "+f"(d[41]), "+f"(d[42]), "+f"(d[43]), "+f"(d[44]), "+f"(d[45]), "+f"(d[46]), "+f"(d[47]),
        "+f"(d[48]), "+f"(d[49]), "+f"(d[50]), "+f"(d[51]), "+f"(d[52]), "+f"(d[53]), "+f"(d[54]), "+f"(d[55]),
        "+f"(d[56]), "+f"(d[57]), "+f"(d[58]), "+f"(d[59]), "+f"(d[60]), "+f"(d[61]), "+f"(d[62]), "+f"(d[63]),
        "+f"(d[64]), "+f"(d[65]), "+f"(d[66]), "+f"(d[67]), "+f"(d[68]), "+f"(d[69]), "+f"(d[70]), "+f"(d[71]),
        "+f"(d[72]), "+f"(d[73]), "+f"(d[74]), "+f"(d[75]), "+f"(d[76]), "+f"(d[77]), "+f"(d[78]), "+f"(d[79]),
        "+f"(d[80]), "+f"(d[81]), "+f"(d[82]), "+f"(d[83]), "+f"(d[84]), "+f"(d[85]), "+f"(d[86]), "+f"(d[87]),
        "+f"(d[88]), "+f"(d[89]), "+f"(d[90]), "+f"(d[91]), "+f"(d[92]), "+f"(d[93]), "+f"(d[94]), "+f"(d[95]),
        "+f"(d[96]), "+f"(d[97]), "+f"(d[98]), "+f"(d[99]), "+f"(d[100]), "+f"(d[101]), "+f"(d[102]), "+f"(d[103]),
        "+f"(d[104]), "+f"(d[105]), "+f"(d[106]), "+f"(d[107]), "+f"(d[108]), "+f"(d[109]), "+f"(d[110]), "+f"(d[111]),
        "+f"(d[112]), "+f"(d[113]), "+f"(d[114]), "+f"(d[115]), "+f"(d[116]), "+f"(d[117]), "+f"(d[118]), "+f"(d[119]),
        "+f"(d[120]), "+f"(d[121]), "+f"(d[122]), "+f"(d[123]), "+f"(d[124]), "+f"(d[125]), "+f"(d[126]), "+f"(d[127])
      : "l"(descA), "l"(descB), "r"(acc));
}

__device__ __forceinline__ void mma_ss64(float (&d)[32], uint64_t descA, uint64_t descB) {
  asm volatile("wgmma.mma_async.sync.aligned.m64n64k16.f32.bf16.bf16 {"
      "%0, %1, %2, %3, %4, %5, %6, %7, %8, %9, %10, %11, %12, %13, %14, %15, "
      "%16, %17, %18, %19, %20, %21, %22, %23, %24, %25, %26, %27, %28, %29, %30, %31"
      "}, %32, %33, 1, 1, 1, 0, 1;\n"
      : "+f"(d[0]), "+f"(d[1]), "+f"(d[2]), "+f"(d[3]), "+f"(d[4]), "+f"(d[5]), "+f"(d[6]), "+f"(d[7]),
        "+f"(d[8]), "+f"(d[9]), "+f"(d[10]), "+f"(d[11]), "+f"(d[12]), "+f"(d[13]), "+f"(d[14]), "+f"(d[15]),
        "+f"(d[16]), "+f"(d[17]), "+f"(d[18]), "+f"(d[19]), "+f"(d[20]), "+f"(d[21]), "+f"(d[22]), "+f"(d[23]),
        "+f"(d[24]), "+f"(d[25]), "+f"(d[26]), "+f"(d[27]), "+f"(d[28]), "+f"(d[29]), "+f"(d[30]), "+f"(d[31])
      : "l"(descA), "l"(descB));
}
__device__ __forceinline__ void mma_ss64_p(float (&d)[32], uint64_t descA, uint64_t descB, int acc) {
  asm volatile("{\n.reg .pred p;\nsetp.ne.b32 p, %34, 0;\n"
      "wgmma.mma_async.sync.aligned.m64n64k16.f32.bf16.bf16 {"
      "%0, %1, %2, %3, %4, %5, %6, %7, %8, %9, %10, %11, %12, %13, %14, %15, "
      "%16, %17, %18, %19, %20, %21, %22, %23, %24, %25, %26, %27, %28, %29, %30, %31"
      "}, %32, %33, p, 1, 1, 0, 1;\n}\n"
      : "+f"(d[0]), "+f"(d[1]), "+f"(d[2]), "+f"(d[3]), "+f"(d[4]), "+f"(d[5]), "+f"(d[6]), "+f"(d[7]),
        "+f"(d[8]), "+f"(d[9]), "+f"(d[10]), "+f"(d[11]), "+f"(d[12]), "+f"(d[13]), "+f"(d[14]), "+f"(d[15]),
        "+f"(d[16]), "+f"(d[17]), "+f"(d[18]), "+f"(d[19]), "+f"(d[20]), "+f"(d[21]), "+f"(d[22]), "+f"(d[23]),
        "+f"(d[24]), "+f"(d[25]), "+f"(d[26]), "+f"(d[27]), "+f"(d[28]), "+f"(d[29]), "+f"(d[30]), "+f"(d[31])
      : "l"(descA), "l"(descB), "r"(acc));
}

__device__ __forceinline__ void mma_ss160(float (&d)[80], uint64_t descA, uint64_t descB) {
  asm volatile("wgmma.mma_async.sync.aligned.m64n160k16.f32.bf16.bf16 {"
      "%0, %1, %2, %3, %4, %5, %6, %7, %8, %9, %10, %11, %12, %13, %14, %15, "
      "%16, %17, %18, %19, %20, %21, %22, %23, %24, %25, %26, %27, %28, %29, %30, %31, "
      "%32, %33, %34, %35, %36, %37, %38, %39, %40, %41, %42, %43, %44, %45, %46, %47, "
      "%48, %49, %50, %51, %52, %53, %54, %55, %56, %57, %58, %59, %60, %61, %62, %63, "
      "%64, %65, %66, %67, %68, %69, %70, %71, %72, %73, %74, %75, %76, %77, %78, %79"
      "}, %80, %81, 1, 1, 1, 0, 1;\n"
      : "+f"(d[0]), "+f"(d[1]), "+f"(d[2]), "+f"(d[3]), "+f"(d[4]), "+f"(d[5]), "+f"(d[6]), "+f"(d[7]),
        "+f"(d[8]), "+f"(d[9]), "+f"(d[10]), "+f"(d[11]), "+f"(d[12]), "+f"(d[13]), "+f"(d[14]), "+f"(d[15]),
        "+f"(d[16]), "+f"(d[17]), "+f"(d[18]), "+f"(d[19]), "+f"(d[20]), "+f"(d[21]), "+f"(d[22]), "+f"(d[23]),
        "+f"(d[24]), "+f"(d[25]), "+f"(d[26]), "+f"(d[27]), "+f"(d[28]), "+f"(d[29]), "+f"(d[30]), "+f"(d[31]),
        "+f"(d[32]), "+f"(d[33]), "+f"(d[34]), "+f"(d[35]), "+f"(d[36]), "+f"(d[37]), "+f"(d[38]), "+f"(d[39]),
        "+f"(d[40]), "+f"(d[41]), "+f"(d[42]), "+f"(d[43]), "+f"(d[44]), "+f"(d[45]), "+f"(d[46]), "+f"(d[47]),
        "+f"(d[48]), "+f"(d[49]), "+f"(d[50]), "+f"(d[51]), "+f"(d[52]), "+f"(d[53]), "+f"(d[54]), "+f"(d[55]),
        "+f"(d[56]), "+f"(d[57]), "+f"(d[58]), "+f"(d[59]), "+f"(d[60]), "+f"(d[61]), "+f"(d[62]), "+f"(d[63]),
        "+f"(d[64]), "+f"(d[65]), "+f"(d[66]), "+f"(d[67]), "+f"(d[68]), "+f"(d[69]), "+f"(d[70]), "+f"(d[71]),
        "+f"(d[72]), "+f"(d[73]), "+f"(d[74]), "+f"(d[75]), "+f"(d[76]), "+f"(d[77]), "+f"(d[78]), "+f"(d[79])
      : "l"(descA), "l"(descB));
}

__device__ __forceinline__ void mma_ss192(float (&d)[96], uint64_t descA, uint64_t descB) {
  asm volatile("wgmma.mma_async.sync.aligned.m64n192k16.f32.bf16.bf16 {"
      "%0, %1, %2, %3, %4, %5, %6, %7, %8, %9, %10, %11, %12, %13, %14, %15, "
      "%16, %17, %18, %19, %20, %21, %22, %23, %24, %25, %26, %27, %28, %29, %30, %31, "
      "%32, %33, %34, %35, %36, %37, %38, %39, %40, %41, %42, %43, %44, %45, %46, %47, "
      "%48, %49, %50, %51, %52, %53, %54, %55, %56, %57, %58, %59, %60, %61, %62, %63, "
      "%64, %65, %66, %67, %68, %69, %70, %71, %72, %73, %74, %75, %76, %77, %78, %79, "
      "%80, %81, %82, %83, %84, %85, %86, %87, %88, %89, %90, %91, %92, %93, %94, %95"
      "}, %96, %97, 1, 1, 1, 0, 1;\n"
      : "+f"(d[0]), "+f"(d[1]), "+f"(d[2]), "+f"(d[3]), "+f"(d[4]), "+f"(d[5]), "+f"(d[6]), "+f"(d[7]),
        "+f"(d[8]), "+f"(d[9]), "+f"(d[10]), "+f"(d[11]), "+f"(d[12]), "+f"(d[13]), "+f"(d[14]), "+f"(d[15]),
        "+f"(d[16]), "+f"(d[17]), "+f"(d[18]), "+f"(d[19]), "+f"(d[20]), "+f"(d[21]), "+f"(d[22]), "+f"(d[23]),
        "+f"(d[24]), "+f"(d[25]), "+f"(d[26]), "+f"(d[27]), "+f"(d[28]), "+f"(d[29]), "+f"(d[30]), "+f"(d[31]),
        "+f"(d[32]), "+f"(d[33]), "+f"(d[34]), "+f"(d[35]), "+f"(d[36]), "+f"(d[37]), "+f"(d[38]), "+f"(d[39]),
        "+f"(d[40]), "+f"(d[41]), "+f"(d[42]), "+f"(d[43]), "+f"(d[44]), "+f"(d[45]), "+f"(d[46]), "+f"(d[47]),
        "+f"(d[48]), "+f"(d[49]), "+f"(d[50]), "+f"(d[51]), "+f"(d[52]), "+f"(d[53]), "+f"(d[54]), "+f"(d[55]),
        "+f"(d[56]), "+f"(d[57]), "+f"(d[58]), "+f"(d[59]), "+f"(d[60]), "+f"(d[61]), "+f"(d[62]), "+f"(d[63]),
        "+f"(d[64]), "+f"(d[65]), "+f"(d[66]), "+f"(d[67]), "+f"(d[68]), "+f"(d[69]), "+f"(d[70]), "+f"(d[71]),
        "+f"(d[72]), "+f"(d[73]), "+f"(d[74]), "+f"(d[75]), "+f"(d[76]), "+f"(d[77]), "+f"(d[78]), "+f"(d[79]),
        "+f"(d[80]), "+f"(d[81]), "+f"(d[82]), "+f"(d[83]), "+f"(d[84]), "+f"(d[85]), "+f"(d[86]), "+f"(d[87]),
        "+f"(d[88]), "+f"(d[89]), "+f"(d[90]), "+f"(d[91]), "+f"(d[92]), "+f"(d[93]), "+f"(d[94]), "+f"(d[95])
      : "l"(descA), "l"(descB));
}
__device__ __forceinline__ void mma_ss192_p(float (&d)[96], uint64_t descA, uint64_t descB, int acc) {
  asm volatile("{\n.reg .pred p;\nsetp.ne.b32 p, %98, 0;\n"
      "wgmma.mma_async.sync.aligned.m64n192k16.f32.bf16.bf16 {"
      "%0, %1, %2, %3, %4, %5, %6, %7, %8, %9, %10, %11, %12, %13, %14, %15, "
      "%16, %17, %18, %19, %20, %21, %22, %23, %24, %25, %26, %27, %28, %29, %30, %31, "
      "%32, %33, %34, %35, %36, %37, %38, %39, %40, %41, %42, %43, %44, %45, %46, %47, "
      "%48, %49, %50, %51, %52, %53, %54, %55, %56, %57, %58, %59, %60, %61, %62, %63, "
      "%64, %65, %66, %67, %68, %69, %70, %71, %72, %73, %74, %75, %76, %77, %78, %79, "
      "%80, %81, %82, %83, %84, %85, %86, %87, %88, %89, %90, %91, %92, %93, %94, %95"
      "}, %96, %97, p, 1, 1, 0, 1;\n}\n"
      : "+f"(d[0]), "+f"(d[1]), "+f"(d[2]), "+f"(d[3]), "+f"(d[4]), "+f"(d[5]), "+f"(d[6]), "+f"(d[7]),
        "+f"(d[8]), "+f"(d[9]), "+f"(d[10]), "+f"(d[11]), "+f"(d[12]), "+f"(d[13]), "+f"(d[14]), "+f"(d[15]),
        "+f"(d[16]), "+f"(d[17]), "+f"(d[18]), "+f"(d[19]), "+f"(d[20]), "+f"(d[21]), "+f"(d[22]), "+f"(d[23]),
        "+f"(d[24]), "+f"(d[25]), "+f"(d[26]), "+f"(d[27]), "+f"(d[28]), "+f"(d[29]), "+f"(d[30]), "+f"(d[31]),
        "+f"(d[32]), "+f"(d[33]), "+f"(d[34]), "+f"(d[35]), "+f"(d[36]), "+f"(d[37]), "+f"(d[38]), "+f"(d[39]),
        "+f"(d[40]), "+f"(d[41]), "+f"(d[42]), "+f"(d[43]), "+f"(d[44]), "+f"(d[45]), "+f"(d[46]), "+f"(d[47]),
        "+f"(d[48]), "+f"(d[49]), "+f"(d[50]), "+f"(d[51]), "+f"(d[52]), "+f"(d[53]), "+f"(d[54]), "+f"(d[55]),
        "+f"(d[56]), "+f"(d[57]), "+f"(d[58]), "+f"(d[59]), "+f"(d[60]), "+f"(d[61]), "+f"(d[62]), "+f"(d[63]),
        "+f"(d[64]), "+f"(d[65]), "+f"(d[66]), "+f"(d[67]), "+f"(d[68]), "+f"(d[69]), "+f"(d[70]), "+f"(d[71]),
        "+f"(d[72]), "+f"(d[73]), "+f"(d[74]), "+f"(d[75]), "+f"(d[76]), "+f"(d[77]), "+f"(d[78]), "+f"(d[79]),
        "+f"(d[80]), "+f"(d[81]), "+f"(d[82]), "+f"(d[83]), "+f"(d[84]), "+f"(d[85]), "+f"(d[86]), "+f"(d[87]),
        "+f"(d[88]), "+f"(d[89]), "+f"(d[90]), "+f"(d[91]), "+f"(d[92]), "+f"(d[93]), "+f"(d[94]), "+f"(d[95])
      : "l"(descA), "l"(descB), "r"(acc));
}

__device__ __forceinline__ void mma_ss80_tt(float (&d)[40], uint64_t descA, uint64_t descB) {
  asm volatile("wgmma.mma_async.sync.aligned.m64n80k16.f32.bf16.bf16 {"
      "%0, %1, %2, %3, %4, %5, %6, %7, %8, %9, %10, %11, %12, %13, %14, %15, "
      "%16, %17, %18, %19, %20, %21, %22, %23, %24, %25, %26, %27, %28, %29, %30, %31, "
      "%32, %33, %34, %35, %36, %37, %38, %39"
      "}, %40, %41, 1, 1, 1, 1, 1;\n"
      : "+f"(d[0]), "+f"(d[1]), "+f"(d[2]), "+f"(d[3]), "+f"(d[4]), "+f"(d[5]), "+f"(d[6]), "+f"(d[7]),
        "+f"(d[8]), "+f"(d[9]), "+f"(d[10]), "+f"(d[11]), "+f"(d[12]), "+f"(d[13]), "+f"(d[14]), "+f"(d[15]),
        "+f"(d[16]), "+f"(d[17]), "+f"(d[18]), "+f"(d[19]), "+f"(d[20]), "+f"(d[21]), "+f"(d[22]), "+f"(d[23]),
        "+f"(d[24]), "+f"(d[25]), "+f"(d[26]), "+f"(d[27]), "+f"(d[28]), "+f"(d[29]), "+f"(d[30]), "+f"(d[31]),
        "+f"(d[32]), "+f"(d[33]), "+f"(d[34]), "+f"(d[35]), "+f"(d[36]), "+f"(d[37]), "+f"(d[38]), "+f"(d[39])
      : "l"(descA), "l"(descB));
}
__device__ __forceinline__ void mma_ss80_tt_z(float (&d)[40], uint64_t descA, uint64_t descB) {
  asm volatile("wgmma.mma_async.sync.aligned.m64n80k16.f32.bf16.bf16 {"
      "%0, %1, %2, %3, %4, %5, %6, %7, %8, %9, %10, %11, %12, %13, %14, %15, "
      "%16, %17, %18, %19, %20, %21, %22, %23, %24, %25, %26, %27, %28, %29, %30, %31, "
      "%32, %33, %34, %35, %36, %37, %38, %39"
      "}, %40, %41, 0, 1, 1, 1, 1;\n"
      : "=f"(d[0]), "=f"(d[1]), "=f"(d[2]), "=f"(d[3]), "=f"(d[4]), "=f"(d[5]), "=f"(d[6]), "=f"(d[7]),
        "=f"(d[8]), "=f"(d[9]), "=f"(d[10]), "=f"(d[11]), "=f"(d[12]), "=f"(d[13]), "=f"(d[14]), "=f"(d[15]),
        "=f"(d[16]), "=f"(d[17]), "=f"(d[18]), "=f"(d[19]), "=f"(d[20]), "=f"(d[21]), "=f"(d[22]), "=f"(d[23]),
        "=f"(d[24]), "=f"(d[25]), "=f"(d[26]), "=f"(d[27]), "=f"(d[28]), "=f"(d[29]), "=f"(d[30]), "=f"(d[31]),
        "=f"(d[32]), "=f"(d[33]), "=f"(d[34]), "=f"(d[35]), "=f"(d[36]), "=f"(d[37]), "=f"(d[38]), "=f"(d[39])
      : "l"(descA), "l"(descB));
}

__device__ __forceinline__ void mma_rs80_k(float (&d)[40], const uint32_t (&a)[4], uint64_t descB) {
  asm volatile("wgmma.mma_async.sync.aligned.m64n80k16.f32.bf16.bf16 {"
      "%0, %1, %2, %3, %4, %5, %6, %7, %8, %9, %10, %11, %12, %13, %14, %15, "
      "%16, %17, %18, %19, %20, %21, %22, %23, %24, %25, %26, %27, %28, %29, %30, %31, "
      "%32, %33, %34, %35, %36, %37, %38, %39"
      "}, {%40, %41, %42, %43}, %44, 1, 1, 1, 0;\n"
      : "+f"(d[0]), "+f"(d[1]), "+f"(d[2]), "+f"(d[3]), "+f"(d[4]), "+f"(d[5]), "+f"(d[6]), "+f"(d[7]),
        "+f"(d[8]), "+f"(d[9]), "+f"(d[10]), "+f"(d[11]), "+f"(d[12]), "+f"(d[13]), "+f"(d[14]), "+f"(d[15]),
        "+f"(d[16]), "+f"(d[17]), "+f"(d[18]), "+f"(d[19]), "+f"(d[20]), "+f"(d[21]), "+f"(d[22]), "+f"(d[23]),
        "+f"(d[24]), "+f"(d[25]), "+f"(d[26]), "+f"(d[27]), "+f"(d[28]), "+f"(d[29]), "+f"(d[30]), "+f"(d[31]),
        "+f"(d[32]), "+f"(d[33]), "+f"(d[34]), "+f"(d[35]), "+f"(d[36]), "+f"(d[37]), "+f"(d[38]), "+f"(d[39])
      : "r"(a[0]), "r"(a[1]), "r"(a[2]), "r"(a[3]), "l"(descB));
}
__device__ __forceinline__ void mma_rs80_k_z(float (&d)[40], const uint32_t (&a)[4], uint64_t descB) {
  asm volatile("wgmma.mma_async.sync.aligned.m64n80k16.f32.bf16.bf16 {"
      "%0, %1, %2, %3, %4, %5, %6, %7, %8, %9, %10, %11, %12, %13, %14, %15, "
      "%16, %17, %18, %19, %20, %21, %22, %23, %24, %25, %26, %27, %28, %29, %30, %31, "
      "%32, %33, %34, %35, %36, %37, %38, %39"
      "}, {%40, %41, %42, %43}, %44, 0, 1, 1, 0;\n"
      : "=f"(d[0]), "=f"(d[1]), "=f"(d[2]), "=f"(d[3]), "=f"(d[4]), "=f"(d[5]), "=f"(d[6]), "=f"(d[7]),
        "=f"(d[8]), "=f"(d[9]), "=f"(d[10]), "=f"(d[11]), "=f"(d[12]), "=f"(d[13]), "=f"(d[14]), "=f"(d[15]),
        "=f"(d[16]), "=f"(d[17]), "=f"(d[18]), "=f"(d[19]), "=f"(d[20]), "=f"(d[21]), "=f"(d[22]), "=f"(d[23]),
        "=f"(d[24]), "=f"(d[25]), "=f"(d[26]), "=f"(d[27]), "=f"(d[28]), "=f"(d[29]), "=f"(d[30]), "=f"(d[31]),
        "=f"(d[32]), "=f"(d[33]), "=f"(d[34]), "=f"(d[35]), "=f"(d[36]), "=f"(d[37]), "=f"(d[38]), "=f"(d[39])
      : "r"(a[0]), "r"(a[1]), "r"(a[2]), "r"(a[3]), "l"(descB));
}

__device__ __forceinline__ void mma_rs48_k(float (&d)[24], const uint32_t (&a)[4], uint64_t descB) {
  asm volatile("wgmma.mma_async.sync.aligned.m64n48k16.f32.bf16.bf16 {"
      "%0, %1, %2, %3, %4, %5, %6, %7, %8, %9, %10, %11, %12, %13, %14, %15, "
      "%16, %17, %18, %19, %20, %21, %22, %23"
      "}, {%24, %25, %26, %27}, %28, 1, 1, 1, 0;\n"
      : "+f"(d[0]), "+f"(d[1]), "+f"(d[2]), "+f"(d[3]), "+f"(d[4]), "+f"(d[5]), "+f"(d[6]), "+f"(d[7]),
        "+f"(d[8]), "+f"(d[9]), "+f"(d[10]), "+f"(d[11]), "+f"(d[12]), "+f"(d[13]), "+f"(d[14]), "+f"(d[15]),
        "+f"(d[16]), "+f"(d[17]), "+f"(d[18]), "+f"(d[19]), "+f"(d[20]), "+f"(d[21]), "+f"(d[22]), "+f"(d[23])
      : "r"(a[0]), "r"(a[1]), "r"(a[2]), "r"(a[3]), "l"(descB));
}
__device__ __forceinline__ void mma_rs48_k_z(float (&d)[24], const uint32_t (&a)[4], uint64_t descB) {
  asm volatile("wgmma.mma_async.sync.aligned.m64n48k16.f32.bf16.bf16 {"
      "%0, %1, %2, %3, %4, %5, %6, %7, %8, %9, %10, %11, %12, %13, %14, %15, "
      "%16, %17, %18, %19, %20, %21, %22, %23"
      "}, {%24, %25, %26, %27}, %28, 0, 1, 1, 0;\n"
      : "=f"(d[0]), "=f"(d[1]), "=f"(d[2]), "=f"(d[3]), "=f"(d[4]), "=f"(d[5]), "=f"(d[6]), "=f"(d[7]),
        "=f"(d[8]), "=f"(d[9]), "=f"(d[10]), "=f"(d[11]), "=f"(d[12]), "=f"(d[13]), "=f"(d[14]), "=f"(d[15]),
        "=f"(d[16]), "=f"(d[17]), "=f"(d[18]), "=f"(d[19]), "=f"(d[20]), "=f"(d[21]), "=f"(d[22]), "=f"(d[23])
      : "r"(a[0]), "r"(a[1]), "r"(a[2]), "r"(a[3]), "l"(descB));
}

__device__ __forceinline__ void mma_rs160_n(float (&d)[80], const uint32_t (&a)[4], uint64_t descB) {
  asm volatile("wgmma.mma_async.sync.aligned.m64n160k16.f32.bf16.bf16 {"
      "%0, %1, %2, %3, %4, %5, %6, %7, %8, %9, %10, %11, %12, %13, %14, %15, "
      "%16, %17, %18, %19, %20, %21, %22, %23, %24, %25, %26, %27, %28, %29, %30, %31, "
      "%32, %33, %34, %35, %36, %37, %38, %39, %40, %41, %42, %43, %44, %45, %46, %47, "
      "%48, %49, %50, %51, %52, %53, %54, %55, %56, %57, %58, %59, %60, %61, %62, %63, "
      "%64, %65, %66, %67, %68, %69, %70, %71, %72, %73, %74, %75, %76, %77, %78, %79"
      "}, {%80, %81, %82, %83}, %84, 1, 1, 1, 1;\n"
      : "+f"(d[0]), "+f"(d[1]), "+f"(d[2]), "+f"(d[3]), "+f"(d[4]), "+f"(d[5]), "+f"(d[6]), "+f"(d[7]),
        "+f"(d[8]), "+f"(d[9]), "+f"(d[10]), "+f"(d[11]), "+f"(d[12]), "+f"(d[13]), "+f"(d[14]), "+f"(d[15]),
        "+f"(d[16]), "+f"(d[17]), "+f"(d[18]), "+f"(d[19]), "+f"(d[20]), "+f"(d[21]), "+f"(d[22]), "+f"(d[23]),
        "+f"(d[24]), "+f"(d[25]), "+f"(d[26]), "+f"(d[27]), "+f"(d[28]), "+f"(d[29]), "+f"(d[30]), "+f"(d[31]),
        "+f"(d[32]), "+f"(d[33]), "+f"(d[34]), "+f"(d[35]), "+f"(d[36]), "+f"(d[37]), "+f"(d[38]), "+f"(d[39]),
        "+f"(d[40]), "+f"(d[41]), "+f"(d[42]), "+f"(d[43]), "+f"(d[44]), "+f"(d[45]), "+f"(d[46]), "+f"(d[47]),
        "+f"(d[48]), "+f"(d[49]), "+f"(d[50]), "+f"(d[51]), "+f"(d[52]), "+f"(d[53]), "+f"(d[54]), "+f"(d[55]),
        "+f"(d[56]), "+f"(d[57]), "+f"(d[58]), "+f"(d[59]), "+f"(d[60]), "+f"(d[61]), "+f"(d[62]), "+f"(d[63]),
        "+f"(d[64]), "+f"(d[65]), "+f"(d[66]), "+f"(d[67]), "+f"(d[68]), "+f"(d[69]), "+f"(d[70]), "+f"(d[71]),
        "+f"(d[72]), "+f"(d[73]), "+f"(d[74]), "+f"(d[75]), "+f"(d[76]), "+f"(d[77]), "+f"(d[78]), "+f"(d[79])
      : "r"(a[0]), "r"(a[1]), "r"(a[2]), "r"(a[3]), "l"(descB));
}
__device__ __forceinline__ void mma_rs160_n_z(float (&d)[80], const uint32_t (&a)[4], uint64_t descB) {
  asm volatile("wgmma.mma_async.sync.aligned.m64n160k16.f32.bf16.bf16 {"
      "%0, %1, %2, %3, %4, %5, %6, %7, %8, %9, %10, %11, %12, %13, %14, %15, "
      "%16, %17, %18, %19, %20, %21, %22, %23, %24, %25, %26, %27, %28, %29, %30, %31, "
      "%32, %33, %34, %35, %36, %37, %38, %39, %40, %41, %42, %43, %44, %45, %46, %47, "
      "%48, %49, %50, %51, %52, %53, %54, %55, %56, %57, %58, %59, %60, %61, %62, %63, "
      "%64, %65, %66, %67, %68, %69, %70, %71, %72, %73, %74, %75, %76, %77, %78, %79"
      "}, {%80, %81, %82, %83}, %84, 0, 1, 1, 1;\n"
      : "=f"(d[0]), "=f"(d[1]), "=f"(d[2]), "=f"(d[3]), "=f"(d[4]), "=f"(d[5]), "=f"(d[6]), "=f"(d[7]),
        "=f"(d[8]), "=f"(d[9]), "=f"(d[10]), "=f"(d[11]), "=f"(d[12]), "=f"(d[13]), "=f"(d[14]), "=f"(d[15]),
        "=f"(d[16]), "=f"(d[17]), "=f"(d[18]), "=f"(d[19]), "=f"(d[20]), "=f"(d[21]), "=f"(d[22]), "=f"(d[23]),
        "=f"(d[24]), "=f"(d[25]), "=f"(d[26]), "=f"(d[27]), "=f"(d[28]), "=f"(d[29]), "=f"(d[30]), "=f"(d[31]),
        "=f"(d[32]), "=f"(d[33]), "=f"(d[34]), "=f"(d[35]), "=f"(d[36]), "=f"(d[37]), "=f"(d[38]), "=f"(d[39]),
        "=f"(d[40]), "=f"(d[41]), "=f"(d[42]), "=f"(d[43]), "=f"(d[44]), "=f"(d[45]), "=f"(d[46]), "=f"(d[47]),
        "=f"(d[48]), "=f"(d[49]), "=f"(d[50]), "=f"(d[51]), "=f"(d[52]), "=f"(d[53]), "=f"(d[54]), "=f"(d[55]),
        "=f"(d[56]), "=f"(d[57]), "=f"(d[58]), "=f"(d[59]), "=f"(d[60]), "=f"(d[61]), "=f"(d[62]), "=f"(d[63]),
        "=f"(d[64]), "=f"(d[65]), "=f"(d[66]), "=f"(d[67]), "=f"(d[68]), "=f"(d[69]), "=f"(d[70]), "=f"(d[71]),
        "=f"(d[72]), "=f"(d[73]), "=f"(d[74]), "=f"(d[75]), "=f"(d[76]), "=f"(d[77]), "=f"(d[78]), "=f"(d[79])
      : "r"(a[0]), "r"(a[1]), "r"(a[2]), "r"(a[3]), "l"(descB));
}

__device__ __forceinline__ void feature_map(const uint32_t (&P)[2][10], uint32_t (&fr)[10][4]) {
  constexpr float L2E = 1.4426950408889634f;
#pragma unroll
  for (int p = 0; p < 2; p++) {
#pragma unroll
    for (int r = 0; r < 2; r++) {
      uint32_t mx = P[r][5 * p], mn = mx;
#pragma unroll
      for (int g = 1; g < 5; g++) { mx = max_bf2(mx, P[r][5 * p + g]); mn = min_bf2(mn, P[r][5 * p + g]); }
      mx = max_bf2(mx, __shfl_xor_sync(0xffffffffu, mx, 1));
      mn = min_bf2(mn, __shfl_xor_sync(0xffffffffu, mn, 1));
      mx = max_bf2(mx, __shfl_xor_sync(0xffffffffu, mx, 2));
      mn = min_bf2(mn, __shfl_xor_sync(0xffffffffu, mn, 2));
      float mx0 = -bf_lo(mx) * L2E, mx1 = -bf_hi(mx) * L2E, mn0 = bf_lo(mn) * L2E, mn1 = bf_hi(mn) * L2E;
      float ep0[5], ep1[5], en0[5], en1[5];
      float sp0 = 0.f, sp1 = 0.f, sn0 = 0.f, sn1 = 0.f;
#pragma unroll
      for (int g = 0; g < 5; g++) {
        float x0 = bf_lo(P[r][5 * p + g]), x1 = bf_hi(P[r][5 * p + g]);
        ep0[g] = ex2(fmaf(x0, L2E, mx0)); ep1[g] = ex2(fmaf(x1, L2E, mx1));
        en0[g] = ex2(fmaf(x0, -L2E, mn0)); en1[g] = ex2(fmaf(x1, -L2E, mn1));
        sp0 += ep0[g]; sp1 += ep1[g]; sn0 += en0[g]; sn1 += en1[g];
      }
      sp0 += __shfl_xor_sync(0xffffffffu, sp0, 1); sp1 += __shfl_xor_sync(0xffffffffu, sp1, 1);
      sn0 += __shfl_xor_sync(0xffffffffu, sn0, 1); sn1 += __shfl_xor_sync(0xffffffffu, sn1, 1);
      sp0 += __shfl_xor_sync(0xffffffffu, sp0, 2); sp1 += __shfl_xor_sync(0xffffffffu, sp1, 2);
      sn0 += __shfl_xor_sync(0xffffffffu, sn0, 2); sn1 += __shfl_xor_sync(0xffffffffu, sn1, 2);
      sp0 = rcp(sp0); sp1 = rcp(sp1); sn0 = rcp(sn0); sn1 = rcp(sn1);
#pragma unroll
      for (int g = 0; g < 5; g++) {
        fr[5 * p + g][r] = pack_bf16(ep0[g] * sp0, ep1[g] * sp1);
        fr[5 * p + g][2 + r] = pack_bf16(en0[g] * sn0, en1[g] * sn1);
      }
    }
  }
}

template <bool V> struct BoolC { static constexpr bool value = V; };
struct Ring {
  uint32_t idx, phase;
  template <int N> __device__ __forceinline__ void next() { if (++idx == N) { idx = 0; phase ^= 1; } }
};

}

__global__ void __cluster_dims__(2, 1, 1) __launch_bounds__(384, 1)
fused_kernel(const __grid_constant__ Maps maps, const __nv_bfloat16* __restrict__ x, const __nv_bfloat16* __restrict__ wqkv,
             const __nv_bfloat16* __restrict__ wphi, const __nv_bfloat16* __restrict__ w1, const __nv_bfloat16* __restrict__ w2,
             const __nv_bfloat16* __restrict__ w3, const __nv_bfloat16* __restrict__ w4, const __nv_bfloat16* __restrict__ wo,
             const __nv_bfloat16* __restrict__ gate_w, __nv_bfloat16* __restrict__ out) {
  extern __shared__ __align__(1024) uint8_t sgen[];
  const uint32_t sb = smem_u32(sgen);
  const uint32_t sb16 = (sb & 0x3FFFFu) >> 4;
  const uint32_t bars = sb + OFF_BAR;
  const uint32_t fullA = bars + 8 * B_FULLA, emptyA = bars + 8 * B_EMPTYA, fullB = bars + 8 * B_FULLB, emptyB = bars + 8 * B_EMPTYB;

  const int tid = threadIdx.x;
  const int rank = blockIdx.x & 1;
  const int pairIdx = blockIdx.x >> 1;
  const int i = pairIdx >> 2, j = 2 * (pairIdx & 3) + rank;

  TSTAMP(0);
  auto load_p1_b = [&](int k, uint32_t slot, uint32_t bar) {
    mbar_expect_tx(bar, 40960);
    tma4d(slot + 8192, &maps.qm, bar, 0, 64 * k, 0, j);
    tma3d(slot, &maps.w1m, bar, 0, 64 * k, j);
    tma4d(slot + 32768 + 2048, &maps.qr, bar, 64, 64 * k, 0, j);
    tma3d(slot + 32768, &maps.w1r, bar, 64, 64 * k, j);
  };
  if (tid >= 256) {
    asm volatile("setmaxnreg.dec.sync.aligned.u32 40;");
    if (tid == 256) {
#pragma unroll
      for (int s = 0; s < NA; s++) mbar_init(fullA + 8 * s, 1);
      asm volatile("fence.mbarrier_init.release.cluster;" ::: "memory");
#pragma unroll 1
      for (int u = 0; u < 4; u++) {
        if ((u & 1) == 0) mbar_expect_tx(fullA + 4 * u, SLOT_A);
        tma2d(sb + OFF_A + u * 8192, &maps.x, fullA + 8 * (u >> 1), 64 * (u >> 1), 128 * i + 64 * (u & 1));
      }
    } else if (tid == 288) {
#pragma unroll
      for (int s = 0; s < NB; s++) mbar_init(fullB + 8 * s, 1);
      asm volatile("fence.mbarrier_init.release.cluster;" ::: "memory");
#pragma unroll 1
      for (int k = 0; k < 2; k++) load_p1_b(k, sb + OFF_B + k * SLOT_B, fullB + 8 * k);
    } else if (tid == 320) {
#pragma unroll
      for (int b = B_CS; b < NBAR; b++) mbar_init(bars + 8 * b, b < B_EMPTYB ? 1 : b < B_EMPTYA ? 8 : 16);
#pragma unroll
      for (int b = B_DSR; b < B_EMPTYB; b++) mbar_expect_tx(bars + 8 * b, 10240);
      asm volatile("fence.mbarrier_init.release.cluster;" ::: "memory");
    }
    __syncwarp();
    asm volatile("barrier.cluster.arrive.relaxed.aligned;" ::: "memory");
    auto get_epoch = [&]() { return *reinterpret_cast<volatile unsigned*>(g_flags + FL_DONE * 32) / NCTA; };
    if (tid >= 320) {
      const int lane = tid & 31, ch = lane % 10, rg = lane / 10;
      const __nv_bfloat16* p = w1 + (size_t)(40 * i + (tid >= 352 ? 20 : 0) + rg) * D_ + 80 * j + 8 * ch;
      const unsigned par = get_epoch() & 1;
      float a[8];
#pragma unroll
      for (int e = 0; e < 8; e++) a[e] = 0.f;
#pragma unroll
      for (int it = 0; it < 7; it++) {
        uint4 v = make_uint4(0, 0, 0, 0);
        if (lane < 30 && 3 * it + rg < 20) v = __ldg(reinterpret_cast<const uint4*>(p + (size_t)it * 3 * D_));
        a[0] += bf_lo(v.x); a[1] += bf_hi(v.x); a[2] += bf_lo(v.y); a[3] += bf_hi(v.y);
        a[4] += bf_lo(v.z); a[5] += bf_hi(v.z); a[6] += bf_lo(v.w); a[7] += bf_hi(v.w);
      }
#pragma unroll
      for (int e = 0; e < 8; e++) a[e] += __shfl_down_sync(0xffffffffu, a[e], 10) + __shfl_down_sync(0xffffffffu, a[e], 20);
      if (lane < 10) {
        float* cd = g_acc[par] + 8 * KV_J + 80 * j + 8 * ch;
        red_add4(cd, a[0], a[1], a[2], a[3]); red_add4(cd + 4, a[4], a[5], a[6], a[7]);
      }
      __syncwarp();
      if (lane == 0) flag_add(FL_CS + j);
      __syncwarp();
    }
    asm volatile("barrier.cluster.wait.aligned;" ::: "memory");
    const int lane = tid & 31, pw = (tid >> 5) & 3;
    if (pw == 0) {
      if (tid == 256) {
        Ring r{2, 1};
        unsigned ep1 = 0;
#pragma unroll 1
        for (int k = 2; k < 25; k++) {
          if (k == 4) ep1 = get_epoch() + 1;
          if (k == 10 || k == 15) {
            if (k == 10) mbar_wait(bars + 8 * B_SIGH, 0);
            flag_wait(k == 10 ? FL_H + 2 * i + rank : FL_X1 + i, ep1 * 8u);
            TSTAMPX(k == 10 ? 29 : 30);
          }
          mbar_wait(emptyA + 8 * r.idx, r.phase);
          const uint32_t bar = fullA + 8 * r.idx, slot = sb + OFF_A + r.idx * SLOT_A;
          mbar_expect_tx(bar, SLOT_A);
          if (k >= 10 && k < 15) tma2d(slot, &maps.hs, bar, 64 * (k - 10) + 320 * rank, 128 * i);
          else tma2d_mc(slot + rank * 8192, k < 10 ? &maps.x : &maps.x1, bar, 64 * (k < 10 ? k : k - 15), 128 * i + 64 * rank);
          r.next<NA>();
        }
      }
    } else if (pw == 1) {
      if (tid == 288) {
        Ring r{2, 1};
#pragma unroll 1
        for (int k = 2; k < 18; k++) {
          mbar_wait(emptyB + 8 * r.idx, r.phase);
          const uint32_t bar = fullB + 8 * r.idx, slot = sb + OFF_B + r.idx * SLOT_B;
          if (k < 10) {
            load_p1_b(k, slot, bar);
          } else if (k < 13) {
            mbar_expect_tx(bar, k < 12 ? 40960 : 20480);
            tma3d(slot, &maps.w2, bar, 0, 320 * rank + 128 * (k - 10), 5 * (j >> 1));
            if (k < 12) tma3d(slot + 20480, &maps.w2, bar, 0, 320 * rank + 128 * (k - 10) + 64, 5 * (j >> 1));
          } else {
            mbar_expect_tx(bar, 49152);
            tma3d(slot, &maps.w3, bar, 0, 128 * (k - 13), 3 * j);
            tma3d(slot + 24576, &maps.w3, bar, 0, 128 * (k - 13) + 64, 3 * j);
          }
          r.next<NB>();
        }
        Ring r4{0, 1};
#pragma unroll 1
        for (int n = 0; n < 16; n++) {
          if (n == 0 || n == 1 || n == 3) { mbar_wait(emptyB + 8 * r.idx, r.phase); r.next<NB>(); }
          mbar_wait(bars + 8 * (B_EMPTY4 + r4.idx), r4.phase);
          const uint32_t bar = bars + 8 * (B_FULL4 + r4.idx), slot = sb + OFF_B + r4.idx * UNIT4;
          const int u = n & 3, m = ((j >> 1) + 1 + (n >> 2)) & 3;
          mbar_expect_tx(bar, u == 3 ? 25600 : 20480);
          tma3d(slot, u == 3 ? &maps.wo : &maps.w4, bar, 0, u == 3 ? 80 * j : 192 * j + 64 * u, 5 * m);
          r4.next<NU4>();
        }
      }
    } else {
      const unsigned epoch = get_epoch();
      float* accg = g_acc[epoch & 1];
      if (pw == 2) {
        {
          float* nxt = g_acc[(epoch + 1) & 1];
          constexpr int PER = ACC_FLOATS / NCTA;
#pragma unroll 1
          for (int e = lane; e < PER; e += 32) nxt[blockIdx.x * PER + e] = 0.f;
        }
        if (tid == 320) {
          flag_wait(FL_CS + j, (epoch + 1) * 32u);
          flag_wait(FL_ST + i, (epoch + 1) * 8u);
          fence_async_glb();
          *reinterpret_cast<volatile uint32_t*>(sgen + OFF_BAR + 8 * NBAR) = (epoch + 1) & 1;
          mbar_expect_tx(bars + 8 * B_CS, 320 + 2048);
          bulk_load(sb + OFF_CS, accg + 8 * KV_J + 80 * j, 320, bars + 8 * B_CS);
          bulk_load(sb + OFF_XST, g_xstat + 128 * i, 2048, bars + 8 * B_CS);
          TSTAMPX(21);
          l2_prefetch(w2 + (size_t)blockIdx.x * (D_ * D_ / NCTA), D_ * D_ * 2 / NCTA);
          flag_wait(FL_H + 2 * i + rank, (epoch + 1) * 8u);
          l2_prefetch(w3 + (size_t)blockIdx.x * (F_ * D_ / NCTA), F_ * D_ * 2 / NCTA);
          l2_prefetch(w4 + (size_t)blockIdx.x * (F_ * D_ / NCTA), F_ * D_ * 2 / NCTA);
          l2_prefetch(wo + (size_t)blockIdx.x * (D_ * D_ / NCTA), D_ * D_ * 2 / NCTA);
          flag_wait(FL_KV + j, (epoch + 1) * 16u);
          mbar_expect_tx(bars + 8 * B_KV, KV_J * 4);
          bulk_load(sb + OFF_MISC, accg + j * KV_J, KV_J * 4, bars + 8 * B_KV);
          TSTAMPX(22);
        }
        __syncwarp();
#pragma unroll 1
        for (int m = 0; m < 6; m++) {
          const int col = 192 * j + 32 * m + 8 * (lane & 3);
          const __nv_bfloat16* p = w3 + (size_t)(40 * i + (lane >> 2) * 5) * F_ + col;
          float a[8];
#pragma unroll
          for (int e = 0; e < 8; e++) a[e] = 0.f;
#pragma unroll
          for (int it = 0; it < 5; it++) {
            const uint4 v = __ldg(reinterpret_cast<const uint4*>(p + (size_t)it * F_));
            a[0] += bf_lo(v.x); a[1] += bf_hi(v.x); a[2] += bf_lo(v.y); a[3] += bf_hi(v.y);
            a[4] += bf_lo(v.z); a[5] += bf_hi(v.z); a[6] += bf_lo(v.w); a[7] += bf_hi(v.w);
          }
#pragma unroll
          for (int e = 0; e < 4; e++) {
            const float snd = (lane & 4) ? a[e] : a[e + 4], keep = (lane & 4) ? a[e + 4] : a[e];
            a[e] = keep + __shfl_xor_sync(0xffffffffu, snd, 4);
            a[e] += __shfl_xor_sync(0xffffffffu, a[e], 8);
            a[e] += __shfl_xor_sync(0xffffffffu, a[e], 16);
          }
          if (lane < 8) red_add4(accg + 8 * KV_J + D_ + col + (lane >> 2) * 4, a[0], a[1], a[2], a[3]);
        }
        __syncwarp();
        if (tid == 320) {
          flag_add(FL_CS3 + j);
          flag_wait(FL_S1 + i, (epoch + 1) * 8u);
          flag_wait(FL_CS3 + j, (epoch + 1) * 16u);
          fence_async_glb();
          mbar_expect_tx(bars + 8 * B_ST1, 8192 + 768);
          bulk_load(sb + OFF_CS + 320, accg + 8 * KV_J + D_ + 192 * j, 768, bars + 8 * B_ST1);
          bulk_load(sb + OFF_MISC, g_st1 + 128 * i * 8, 8192, bars + 8 * B_ST1);
        }
      }
      if (tid == 352) {
        mbar_wait(bars + 8 * B_SIGP, 0);
        flag_add(FL_ST + i);
        TSTAMPX(20);
        mbar_expect_tx(bars + 8 * B_XR, 20480);
#pragma unroll 1
        for (int u = 0; u < 8; u++)
          tma2d(sb + OFF_B + (u / 3) * SLOT_B + SPARE + (u % 3) * 2560, &maps.xr, bars + 8 * B_XR, 80 * j, 128 * i + 16 * u);
        const int shift = (j < 2) ? 1 : (j < 4) ? -1 : (j < 6) ? 2 : -2;
        if ((shift > 0 && i == 0) || (shift < 0 && i == 15)) {
          const int nz = shift > 0 ? shift : -shift, zr = shift > 0 ? 0 : S_ - nz;
#pragma unroll 1
          for (int e = 0; e < nz * 10; e++)
            reinterpret_cast<uint4*>(g_Hs + (size_t)(2 + zr + e / 10) * D_ + 80 * j)[e % 10] = make_uint4(0, 0, 0, 0);
        }
        prefetch_tmap(&maps.hs); prefetch_tmap(&maps.x1);
        prefetch_tmap(&maps.w2); prefetch_tmap(&maps.w3); prefetch_tmap(&maps.w4); prefetch_tmap(&maps.wo);
        mbar_wait(bars + 8 * B_SIGH, 0);
        TSTAMPX(23);
        fence_async_glb();
        flag_add(FL_H + 2 * i + (j >> 2));
        flag_add_relaxed(FL_H + 2 * ((i + (shift > 0 ? 1 : -1)) & 15) + (j >> 2));
        TSTAMPX(24);
        mbar_wait(bars + 8 * B_SIGKV, 0);
        TSTAMPX(25);
        fence_async_smem();
        asm volatile("cp.reduce.async.bulk.global.shared::cta.bulk_group.add.f32 [%0], [%1], %2;"
                     ::"l"(accg + j * KV_J), "r"(sb + OFF_MISC), "r"(KV_J * 4) : "memory");
        bulk_commit(); bulk_wait<0>();
        flag_add(FL_KV + j);
        TSTAMPX(26);
        mbar_wait(bars + 8 * B_SIGX1, 0);
        TSTAMPX(27);
        fence_async_glb();
        flag_add(FL_X1 + i);
        TSTAMPX(28);
        mbar_wait(bars + 8 * B_MFREE, 0);
        flag_add(FL_S1 + i);
      }
    }
  } else {
    uint4 pv[5], pw_[5], pre;
    {
      const int row = 128 * i + 16 * j + (tid >> 4), l16 = tid & 15;
#pragma unroll
      for (int c = 0; c < 5; c++) pv[c] = __ldg(reinterpret_cast<const uint4*>(x + (size_t)row * D_ + c * 128 + l16 * 8));
      pre = __ldg(reinterpret_cast<const uint4*>(wphi + (size_t)j * 1600) + (tid < 200 ? tid : 0));
#pragma unroll
      for (int c = 0; c < 5; c++) pw_[c] = __ldg(reinterpret_cast<const uint4*>(gate_w + c * 128 + l16 * 8));
    }
    asm volatile("barrier.cluster.arrive.relaxed.aligned;" ::: "memory");
    asm volatile("setmaxnreg.inc.sync.aligned.u32 232;");
    const int wg = tid >> 7, warp = tid >> 5, lane = tid & 31, t = lane & 3;
    const int rloc = warp * 16 + (lane >> 2);
    const float* s_cs = reinterpret_cast<const float*>(sgen + OFF_CS);
    auto signal = [&](int b) {
      __syncwarp();
      if (lane == 0) mbar_arrive(bars + 8 * b);
    };
    auto releaseB = [&](uint32_t bar) {
      __syncwarp();
      if (lane == 0) mbar_arrive(bar);
    };
    auto release = [&](uint32_t bar) {
      __syncwarp();
      if (lane < 2) mbar_arrive_cta(bar, lane);
    };
    const uint32_t stg_lane = (warp * 16 + ((lane >> 3) & 1) * 8 + (lane & 7)) * 160 + (lane >> 4) * 16;

    auto store_tile = [&](uint32_t stg, const uint32_t (&v)[2][10], __nv_bfloat16* dst  ) {
#pragma unroll
      for (int s = 0; s < 5; s++) stsm4(stg + stg_lane + s * 32, v[0][2 * s], v[1][2 * s], v[0][2 * s + 1], v[1][2 * s + 1]);
      __syncwarp();
      const uint32_t src = stg + warp * 2560 + (lane >> 1) * 160 + (lane & 1) * 16;
      uint4* d4 = reinterpret_cast<uint4*>(dst + (lane >> 1) * D_ + (lane & 1) * 8);
#pragma unroll
      for (int q = 0; q < 5; q++) d4[2 * q] = lds128(src + q * 32);
    };

    {
#pragma unroll 1
      for (int e = tid; e < 800; e += 256) sts128(sb + OFF_MISC + e * 16, make_uint4(0, 0, 0, 0));
      bar_sync(1, 256);
      float f[40];
      float s = 0.f, gs = 0.f;
#pragma unroll
      for (int c = 0; c < 5; c++) {
        const uint32_t vv[4] = {pv[c].x, pv[c].y, pv[c].z, pv[c].w}, ww[4] = {pw_[c].x, pw_[c].y, pw_[c].z, pw_[c].w};
#pragma unroll
        for (int e = 0; e < 4; e++) {
          f[8 * c + 2 * e] = bf_lo(vv[e]); f[8 * c + 2 * e + 1] = bf_hi(vv[e]);
          s += f[8 * c + 2 * e] + f[8 * c + 2 * e + 1];
          gs = fmaf(f[8 * c + 2 * e], bf_lo(ww[e]), gs); gs = fmaf(f[8 * c + 2 * e + 1], bf_hi(ww[e]), gs);
        }
      }
#pragma unroll
      for (int o = 1; o < 16; o <<= 1) { s += __shfl_xor_sync(0xffffffffu, s, o); gs += __shfl_xor_sync(0xffffffffu, gs, o); }
      const float mean = s * (1.f / D_);
      float q = 0.f;
#pragma unroll
      for (int e = 0; e < 40; e++) { const float d = f[e] - mean; q = fmaf(d, d, q); }
#pragma unroll
      for (int o = 1; o < 16; o <<= 1) q += __shfl_xor_sync(0xffffffffu, q, o);
      const float rstd = rsqrtf(q * (1.f / D_) + 1e-5f);
      asm volatile("barrier.cluster.wait.aligned;" ::: "memory");
      if ((tid & 15) == 0) g_xstat[128 * i + 16 * j + (tid >> 4)] = make_float4(rstd, -mean, rcp(1.f + __expf(-gs)), 0.f);
      signal(B_SIGP);
      if (tid < 200) {
        const uint32_t ww[4] = {pre.x, pre.y, pre.z, pre.w};
        const int h = tid / 50;
#pragma unroll
        for (int e = 0; e < 8; e++) {
          const int idx = tid * 8 + e, k = idx / 20, ff = idx - 20 * k;
          const int n = 40 * (h >> 1) + 8 * (ff >> 2) + 2 * (ff & 3) + (h & 1);
          const int off = (k >> 4) * 2560 + n * 32 + ((((k >> 3) ^ (n >> 2)) & 1) << 4) + (k & 7) * 2;
          *reinterpret_cast<unsigned short*>(sgen + OFF_MISC + off) = (unsigned short)(ww[e >> 1] >> ((e & 1) * 16));
        }
      }
    }
    TSTAMP(1);

    Ring ra{0, 0}, rb{0, 0};
    uint32_t qp[2][10], P[2][10];
    float st_g[2];
    {
      float accM[128], accR[32];
      uint32_t pa = 0, pb = 0;
#pragma unroll 1
      for (int k = 0; k < 10; k++) {
        mbar_wait(fullA + 8 * ra.idx, ra.phase);
        if (tid == 0) TRACE(32 + k);
        mbar_wait(fullB + 8 * rb.idx, rb.phase);
        if (tid == 0) TRACE(64 + k);
        if (k == 0) TSTAMP(2);
        const uint32_t a0 = sb16 + ((OFF_A + ra.idx * SLOT_A + wg * 8192) >> 4), b0 = sb16 + ((OFF_B + rb.idx * SLOT_B) >> 4);
        wg_fence();
#pragma unroll
        for (int kk = 0; kk < 4; kk++) {
          const uint64_t da = make_desc(a0, kk * 32, 16, 1024, 1);
          if (kk == 0) {
            mma_ss256_p(accM, da, make_desc(b0, 0, 8192, 1024, 1), k);
            mma_ss64_p(accR, da, make_desc(b0, 32768, 2048, 256, 3), k);
          } else {
            mma_ss256(accM, da, make_desc(b0, kk * 2048, 8192, 1024, 1));
            mma_ss64(accR, da, make_desc(b0, 32768 + kk * 512, 2048, 256, 3));
          }
          if (kk == 0) {
            wg_commit();
            if (k > 0) {
              wg_wait<1>();
              if (k - 1 < 8) release(emptyA + 8 * pa);
              releaseB(emptyB + 8 * pb);
            }
          }
        }
        wg_commit();
        pa = ra.idx; pb = rb.idx;
        ra.next<NA>(); rb.next<NB>();
      }
      TSTAMP(18);
      float st_rstd[2], st_mr[2];
      mbar_wait(bars + 8 * B_CS, 0);
#pragma unroll
      for (int r = 0; r < 2; r++) {
        const uint4 st = lds128(sb + OFF_XST + (rloc + 8 * r) * 16);
        st_rstd[r] = __uint_as_float(st.x); st_mr[r] = __uint_as_float(st.y); st_g[r] = __uint_as_float(st.z);
      }
      TSTAMP(19);
      wg_wait<0>();
      fence_regs(accM); fence_regs(accR);
      TSTAMP(3);
#define ACC(P_, G, I_) ((G) < 8 ? accM[(P_) * 32 + ((G) & 7) * 4 + (I_)] : accR[(P_) * 8 + ((G) & 1) * 4 + (I_)])
      {
        uint32_t hv[2][10];
        const GeluC g0 = gelu_consts(st_rstd[0], 1.f), g1 = gelu_consts(st_rstd[1], 1.f);
#pragma unroll
        for (int g = 0; g < 10; g++) {
          const float2 cs = *reinterpret_cast<const float2*>(s_cs + 8 * g + 2 * t);
          const float v0 = gelu_s(fmaf(st_mr[0], cs.x, ACC(0, g, 0)), g0), v1 = gelu_s(fmaf(st_mr[0], cs.y, ACC(0, g, 1)), g0);
          const float v2 = gelu_s(fmaf(st_mr[1], cs.x, ACC(0, g, 2)), g1), v3 = gelu_s(fmaf(st_mr[1], cs.y, ACC(0, g, 3)), g1);
          hv[0][g] = pack_bf16(v0, v1); hv[1][g] = pack_bf16(v2, v3);
        }
        fence_async_smem();
        bar_sync(1, 256);
        const int shift = (j < 2) ? 1 : (j < 4) ? -1 : (j < 6) ? 2 : -2;
        store_tile(sb + OFF_STG, hv, g_Hs + (size_t)(128 * i + 16 * warp + 2 + shift) * D_ + 80 * j);
        signal(B_SIGH);
      }
      TSTAMP(4);
      uint32_t kf[5][4], qf[5][4];
#pragma unroll
      for (int s = 0; s < 5; s++) {
        kf[s][0] = pack_bf16(ACC(2, 2 * s, 0), ACC(2, 2 * s, 1)); kf[s][1] = pack_bf16(ACC(2, 2 * s, 2), ACC(2, 2 * s, 3));
        kf[s][2] = pack_bf16(ACC(2, 2 * s + 1, 0), ACC(2, 2 * s + 1, 1)); kf[s][3] = pack_bf16(ACC(2, 2 * s + 1, 2), ACC(2, 2 * s + 1, 3));
        qf[s][0] = pack_bf16(ACC(1, 2 * s, 0), ACC(1, 2 * s, 1)); qf[s][1] = pack_bf16(ACC(1, 2 * s, 2), ACC(1, 2 * s, 3));
        qf[s][2] = pack_bf16(ACC(1, 2 * s + 1, 0), ACC(1, 2 * s + 1, 1)); qf[s][3] = pack_bf16(ACC(1, 2 * s + 1, 2), ACC(1, 2 * s + 1, 3));
      }
      float pk[40], pq[40];
      wg_fence();
#pragma unroll
      for (int s = 0; s < 5; s++) {
        if (s == 0) mma_rs80_k_z(pk, kf[s], make_desc(sb16, OFF_MISC, 16, 256, 3));
        else mma_rs80_k(pk, kf[s], make_desc(sb16, OFF_MISC + s * 2560, 16, 256, 3));
      }
      wg_commit();
#pragma unroll
      for (int s = 0; s < 5; s++) {
        if (s == 0) mma_rs80_k_z(pq, qf[s], make_desc(sb16, OFF_MISC, 16, 256, 3));
        else mma_rs80_k(pq, qf[s], make_desc(sb16, OFF_MISC + s * 2560, 16, 256, 3));
      }
      wg_commit();
      {
        const int mat = lane >> 3;
        const int tok = warp * 16 + (mat & 1) * 8 + (lane & 7);
        const uint32_t ones = (t == 0) ? 0x00003f80u : 0u;
        __syncwarp();
#pragma unroll
        for (int p = 0; p < 2; p++) {
          const uint32_t rowa = sb + OFF_A + p * SLOT_A + tok * 128;
#pragma unroll
          for (int gg = 0; gg < 3; gg++) {
            const int g0 = 5 * p + 2 * gg;
            uint32_t r0 = pack_bf16(ACC(3, g0, 0), ACC(3, g0, 1)), r1 = pack_bf16(ACC(3, g0, 2), ACC(3, g0, 3));
            uint32_t r2 = ones, r3 = ones;
            if (gg < 2) { r2 = pack_bf16(ACC(3, g0 + 1, 0), ACC(3, g0 + 1, 1)); r3 = pack_bf16(ACC(3, g0 + 1, 2), ACC(3, g0 + 1, 3)); }
            stsm4(rowa + (((2 * gg + (mat >> 1)) ^ (tok & 7)) << 4), r0, r1, r2, r3);
          }
        }
      }
#undef ACC
      wg_wait<1>();
      fence_regs(pk);
#pragma unroll
      for (int G = 0; G < 10; G++) {
        P[0][G] = pack_bf16(pk[4 * G], pk[4 * G + 1]); P[1][G] = pack_bf16(pk[4 * G + 2], pk[4 * G + 3]);
      }
      wg_wait<0>();
      fence_regs(pq);
#pragma unroll
      for (int G = 0; G < 10; G++) {
        qp[0][G] = pack_bf16(pq[4 * G], pq[4 * G + 1]); qp[1][G] = pack_bf16(pq[4 * G + 2], pq[4 * G + 3]);
      }
    }

    uint32_t fr[10][4];
    uint32_t xv[2][10];
#pragma unroll
    for (int g = 0; g < 10; g++) xv[0][g] = xv[1][g] = 0u;
    int pass;
    pass = gridDim.y;
#pragma unroll 1
    do {
    feature_map(P, fr);
    if (pass != 0) {
    {
      const int mat = lane >> 3;
      const int tok = warp * 16 + (mat & 1) * 8 + (lane & 7);
      const uint32_t base = sb + OFF_B + tok * 32 + (((mat >> 1) ^ ((tok >> 2) & 1)) << 4);
#pragma unroll
      for (int G = 0; G < 10; G++) stsm4(base + G * 4096, fr[G][0], fr[G][1], fr[G][2], fr[G][3]);
      fence_async_smem();
      bar_sync(1, 256);
      float kv[40];
      const uint32_t a0 = sb16 + ((OFF_A + wg * SLOT_A) >> 4), b0 = sb16 + ((OFF_B + wg * 20480) >> 4);
      wg_fence();
#pragma unroll
      for (int ks = 0; ks < 8; ks++) {
        if (ks == 0) mma_ss80_tt_z(kv, make_desc(a0, 0, 16, 1024, 1), make_desc(b0, 0, 4096, 256, 3));
        else mma_ss80_tt(kv, make_desc(a0, ks * 2048, 16, 1024, 1), make_desc(b0, ks * 512, 4096, 256, 3));
      }
      wg_commit();
      wg_wait<0>();
      fence_regs(kv);
      TSTAMP(31);
      release(emptyA); release(emptyA + 8); releaseB(emptyB); release(bars + 8 * B_PEER2);
      const uint32_t dst = sb + OFF_MISC + wg * (KV_PAIR * 4);
      const int m0 = (warp & 3) * 16 + (lane >> 2);
#pragma unroll
      for (int r = 0; r < 2; r++) {
        const int m = m0 + 8 * r;
        const bool hi = m >= 20;
        uint32_t v[10];
#pragma unroll
        for (int G = 0; G < 10; G++) v[G] = __float_as_uint(hi ? kv[4 * G + 2 * r + 1] : kv[4 * G + 2 * r]);
        const uint32_t p = dst + 4 * (m < 40 ? m * 48 + t * 12 : 1920 + t * 24 + 12);
        if (m <= 40) {
          sts128(p, make_uint4(v[0], v[1], v[2], v[3])); sts128(p + 16, make_uint4(v[4], v[5], v[6], v[7]));
          sts128(p + 32, make_uint4(v[8], v[9], 0u, 0u));
        }
      }
      if (m0 == 32) {
        const uint32_t p = dst + 4 * (1920 + t * 24);
        sts128(p, make_uint4(__float_as_uint(kv[2]), __float_as_uint(kv[6]), __float_as_uint(kv[10]), __float_as_uint(kv[14])));
        sts128(p + 16, make_uint4(__float_as_uint(kv[18]), __float_as_uint(kv[22]), __float_as_uint(kv[26]), __float_as_uint(kv[30])));
        sts128(p + 32, make_uint4(__float_as_uint(kv[34]), __float_as_uint(kv[38]), 0u, 0u));
      }
      signal(B_SIGKV);
    }
    TSTAMP(5);

    {
      {
        mbar_wait(bars + 8 * B_XR, 0);
        const uint32_t xa = sb + OFF_B + (warp / 3) * SLOT_B + SPARE + (warp % 3) * 2560 + (lane >> 2) * 160 + t * 4;
#pragma unroll
        for (int g = 0; g < 10; g++) { xv[0][g] = lds32(xa + g * 16); xv[1][g] = lds32(xa + 1280 + g * 16); }
      }
      float acc[80];
      zero_regs(acc);
      uint32_t pa = 0, pb = 0;
#pragma unroll 1
      for (int k = 0; k < 5; k++) {
        mbar_wait(fullA + 8 * ra.idx, ra.phase);
        if ((k & 1) == 0) mbar_wait(fullB + 8 * rb.idx, rb.phase);
        if (k == 0) TSTAMP(6);
        const uint32_t a0 = sb16 + ((OFF_A + ra.idx * SLOT_A + wg * 8192) >> 4);
        const uint32_t b0 = sb16 + ((OFF_B + rb.idx * SLOT_B + (k & 1) * 20480) >> 4);
        wg_fence();
#pragma unroll
        for (int kk = 0; kk < 4; kk++) {
          mma_ss160(acc, make_desc(a0, kk * 32, 16, 1024, 1), make_desc(b0, kk * 1024, 4096, 512, 2));
          if (kk == 0) {
            wg_commit();
            if (k > 0) {
              wg_wait<1>();
              release(emptyA + 8 * pa);
              if ((k & 1) == 0) releaseB(emptyB + 8 * pb);
            }
          }
        }
        wg_commit();
        pa = ra.idx; pb = rb.idx;
        ra.next<NA>();
        if ((k & 1) || k == 4) rb.next<NB>();
      }
      mbar_wait(bars + 8 * B_PEER2, 0);
      wg_wait<0>();
      fence_regs(acc);
      release(emptyA + 8 * pa);
      TSTAMP(7);
      {
        uint32_t sn[20];
        if (rank) {
#pragma unroll
          for (int e = 0; e < 20; e++) sn[e] = pack_bf16(acc[2 * e], acc[2 * e + 1]);
#pragma unroll
          for (int e = 0; e < 40; e++) acc[e] = acc[40 + e];
        } else {
#pragma unroll
          for (int e = 0; e < 20; e++) sn[e] = pack_bf16(acc[40 + 2 * e], acc[41 + 2 * e]);
        }
        const uint32_t peer = map_peer(sb, rank ^ 1);
#pragma unroll
        for (int q = 0; q < 5; q++)
          st_async16(peer + OFF_B + 20480 + tid * 16 + q * 4096, sn[4 * q], sn[4 * q + 1], sn[4 * q + 2], sn[4 * q + 3],
                     peer + OFF_BAR + 8 * (B_DSR + 8 + wg));
#pragma unroll
        for (int g = 0; g < 10; g++) {
          acc[4 * g] += bf_lo(xv[0][g]); acc[4 * g + 1] += bf_hi(xv[0][g]);
          acc[4 * g + 2] += bf_lo(xv[1][g]); acc[4 * g + 3] += bf_hi(xv[1][g]);
        }
        bar_sync(1, 256);
        mbar_wait(bars + 8 * (B_DSR + 8 + wg), 0);
#pragma unroll
        for (int q = 0; q < 5; q++) {
          const uint4 v = lds128(sb + OFF_B + 20480 + tid * 16 + q * 4096);
          xv[0][2 * q] = pack_bf16(acc[8 * q] + bf_lo(v.x), acc[8 * q + 1] + bf_hi(v.x));
          xv[1][2 * q] = pack_bf16(acc[8 * q + 2] + bf_lo(v.y), acc[8 * q + 3] + bf_hi(v.y));
          xv[0][2 * q + 1] = pack_bf16(acc[8 * q + 4] + bf_lo(v.z), acc[8 * q + 5] + bf_hi(v.z));
          xv[1][2 * q + 1] = pack_bf16(acc[8 * q + 6] + bf_lo(v.w), acc[8 * q + 7] + bf_hi(v.w));
        }
        releaseB(emptyB + 8 * pb);
      }
      TSTAMP(16);
      store_tile(sb + OFF_STG, xv, g_X1 + (size_t)(128 * i + 16 * warp) * D_ + 80 * j);
      signal(B_SIGX1);
      TSTAMP(17);
#pragma unroll
      for (int r = 0; r < 2; r++) {
        float s = 0.f;
#pragma unroll
        for (int g = 0; g < 10; g++) {
          acc[4 * g + 2 * r] = bf_lo(xv[r][g]); acc[4 * g + 2 * r + 1] = bf_hi(xv[r][g]);
          s += acc[4 * g + 2 * r] + acc[4 * g + 2 * r + 1];
        }
        s += __shfl_xor_sync(0xffffffffu, s, 1); s += __shfl_xor_sync(0xffffffffu, s, 2);
        const float mu = s * (1.f / 80.f);
        float q = 0.f;
#pragma unroll
        for (int g = 0; g < 10; g++) {
          const float d0 = acc[4 * g + 2 * r] - mu, d1 = acc[4 * g + 2 * r + 1] - mu;
          q = fmaf(d0, d0, q); q = fmaf(d1, d1, q);
        }
        q += __shfl_xor_sync(0xffffffffu, q, 1); q += __shfl_xor_sync(0xffffffffu, q, 2);
        if (t == 0) g_st1[(128 * i + rloc + 8 * r) * 8 + j] = make_float2(mu, q);
      }
    }
    TSTAMP(8);
#pragma unroll
    for (int G = 0; G < 10; G++) { P[0][G] = qp[0][G]; P[1][G] = qp[1][G]; }
    }
    asm volatile("" : "+r"(pass));
    } while (pass-- != 0);

    uint32_t of[5][4];
    {
      mbar_wait(bars + 8 * B_KV, 0);
      uint4 kvr[2][3];
#pragma unroll
      for (int u = 0; u < 2; u++) {
        const int it = tid + 256 * u, p = it / 192, rem = it - 192 * p, n = rem >> 2, tq = rem & 3;
        const uint32_t sp = sb + OFF_MISC + 4 * (p * KV_PAIR + (n < 40 ? n * 48 + tq * 12 : 1920 + tq * 24 + (n & 1) * 12));
        if (it < 384) { kvr[u][0] = lds128(sp); kvr[u][1] = lds128(sp + 16); kvr[u][2] = lds128(sp + 32); }
      }
      bar_sync(1, 256);
#pragma unroll
      for (int u = 0; u < 2; u++) {
        const int it = tid + 256 * u, p = it / 192, rem = it - 192 * p, n = rem >> 2, tq = rem & 3;
        const int sh = (n < 40 ? (n >= 20) : (n & 1)) * 16;
        const uint32_t v[10] = {kvr[u][0].x, kvr[u][0].y, kvr[u][0].z, kvr[u][0].w, kvr[u][1].x, kvr[u][1].y, kvr[u][1].z, kvr[u][1].w, kvr[u][2].x, kvr[u][2].y};
        uint8_t* dst = sgen + OFF_MISC + p * 7680 + n * 32 + tq * 4;
        const int sw = ((n >> 2) & 1) << 4;
        if (it < 384) {
#pragma unroll
          for (int G = 0; G < 10; G++)
            *reinterpret_cast<uint32_t*>(dst + (G >> 1) * 1536 + (((G & 1) << 4) ^ sw)) = pack_bf16(__uint_as_float(v[G]), 0.f) << sh;
        }
      }
      fence_async_smem();
      bar_sync(1, 256);
      float o0[24], o1[24];
      wg_fence();
#pragma unroll
      for (int g = 0; g < 5; g++) {
        if (g == 0) mma_rs48_k_z(o0, fr[g], make_desc(sb16, OFF_MISC, 16, 256, 3));
        else mma_rs48_k(o0, fr[g], make_desc(sb16, OFF_MISC + g * 1536, 16, 256, 3));
      }
#pragma unroll
      for (int g = 0; g < 5; g++) {
        if (g == 0) mma_rs48_k_z(o1, fr[5], make_desc(sb16, OFF_MISC + 7680, 16, 256, 3));
        else mma_rs48_k(o1, fr[5 + g], make_desc(sb16, OFF_MISC + 7680 + g * 1536, 16, 256, 3));
      }
      wg_commit();
      wg_wait<0>();
      fence_regs(o0); fence_regs(o1);
      signal(B_MFREE);
#pragma unroll
      for (int r = 0; r < 2; r++) {
        const float a0 = __fdividef(st_g[r], o0[20 + 2 * r] + 1e-6f), a1 = __fdividef(st_g[r], o0[21 + 2 * r] + 1e-6f);
        const float b0 = __fdividef(st_g[r], o1[20 + 2 * r] + 1e-6f), b1 = __fdividef(st_g[r], o1[21 + 2 * r] + 1e-6f);
        const float am = t < 2 ? a0 : a1, bm = t < 2 ? b0 : b1;
#pragma unroll
        for (int g = 0; g < 5; g++) {
          const float sa = g < 2 ? a0 : (g == 2 ? am : a1), sb2 = g < 2 ? b0 : (g == 2 ? bm : b1);
          of[g >> 1][(g & 1) * 2 + r] = pack_bf16(o0[4 * g + 2 * r] * sa, o0[4 * g + 2 * r + 1] * sa);
          of[(5 + g) >> 1][((5 + g) & 1) * 2 + r] = pack_bf16(o1[4 * g + 2 * r] * sb2, o1[4 * g + 2 * r + 1] * sb2);
        }
      }
    }
    TSTAMP(9);

    uint32_t hf[12][4];
    {
      float acc[96];
      uint32_t pa = 0, pb = 0;
#pragma unroll 1
      for (int k = 0; k < 10; k++) {
        mbar_wait(fullA + 8 * ra.idx, ra.phase);
        if (tid == 0) TRACE(52 + k);
        if ((k & 1) == 0) mbar_wait(fullB + 8 * rb.idx, rb.phase);
        if (tid == 0) TRACE(84 + k);
        if (k == 0) TSTAMP(10);
        const uint32_t a0 = sb16 + ((OFF_A + ra.idx * SLOT_A + wg * 8192) >> 4);
        const uint32_t b0 = sb16 + ((OFF_B + rb.idx * SLOT_B + (k & 1) * 24576) >> 4);
        wg_fence();
#pragma unroll
        for (int kk = 0; kk < 4; kk++) {
          if (kk == 0) mma_ss192_p(acc, make_desc(a0, 0, 16, 1024, 1), make_desc(b0, 0, 8192, 1024, 1), k);
          else mma_ss192(acc, make_desc(a0, kk * 32, 16, 1024, 1), make_desc(b0, kk * 2048, 8192, 1024, 1));
          if (kk == 0) {
            wg_commit();
            if (k > 0) {
              wg_wait<1>();
              release(emptyA + 8 * pa);
              if ((k & 1) == 0) releaseB(emptyB + 8 * pb);
            }
          }
        }
        wg_commit();
        pa = ra.idx; pb = rb.idx;
        ra.next<NA>();
        if (k & 1) rb.next<NB>();
      }
      float rs[2], mm[2];
      mbar_wait(bars + 8 * B_ST1, 0);
#pragma unroll
      for (int r = 0; r < 2; r++) {
        const uint4 su = lds128(sb + OFF_MISC + (rloc + 8 * r) * 64 + t * 16);
        const float m0 = __uint_as_float(su.x), m1 = __uint_as_float(su.z);
        float mu = m0 + m1;
        mu += __shfl_xor_sync(0xffffffffu, mu, 1); mu += __shfl_xor_sync(0xffffffffu, mu, 2);
        mu *= 0.125f;
        const float d0 = m0 - mu, d1 = m1 - mu;
        float q = __uint_as_float(su.y) + __uint_as_float(su.w) + 80.f * (d0 * d0 + d1 * d1);
        q += __shfl_xor_sync(0xffffffffu, q, 1); q += __shfl_xor_sync(0xffffffffu, q, 2);
        rs[r] = rsqrtf(q * (1.f / D_) + 1e-5f);
        mm[r] = -mu;
      }
      wg_wait<0>();
      fence_regs(acc);
      releaseB(emptyB + 8 * pb);
      release(bars + 8 * B_PEER);
      TSTAMP(11);
      const GeluC g0 = gelu_consts(rs[0], 1.f - st_g[0]), g1 = gelu_consts(rs[1], 1.f - st_g[1]);
#pragma unroll
      for (int g = 0; g < 24; g++) {
        const float2 cs = *reinterpret_cast<const float2*>(s_cs + 80 + 8 * g + 2 * t);
        const float v0 = gelu_s(fmaf(mm[0], cs.x, acc[4 * g]), g0), v1 = gelu_s(fmaf(mm[0], cs.y, acc[4 * g + 1]), g0);
        const float v2 = gelu_s(fmaf(mm[1], cs.x, acc[4 * g + 2]), g1), v3 = gelu_s(fmaf(mm[1], cs.y, acc[4 * g + 3]), g1);
        hf[g >> 1][(g & 1) * 2] = pack_bf16(v0, v1);
        hf[g >> 1][(g & 1) * 2 + 1] = pack_bf16(v2, v3);
      }
    }
    TSTAMP(12);

    {
      float acc[80], kp[40];
      uint32_t sn[20], kb[20];
      const uint32_t peer = map_peer(sb, rank ^ 1);
      const uint32_t tag = lds32(sb + OFF_BAR + 8 * NBAR);
      const uint4* gp = g_part + (size_t)(i * 8 + j) * 3840 + tid;
      uint4 pv4[15];
      Ring r4{0, 0};
      auto add8 = [&](int q, const uint4 v) {
        float* d = &kp[8 * q];
        d[0] += bf_lo(v.x); d[1] += bf_hi(v.x); d[2] += bf_lo(v.y); d[3] += bf_hi(v.y);
        d[4] += bf_lo(v.z); d[5] += bf_hi(v.z); d[6] += bf_lo(v.w); d[7] += bf_hi(v.w);
      };
      auto send = [&](int c) {
        const uint32_t dso = peer + OFF_DS + (c & 1) * 20480 + tid * 16, dsb = peer + OFF_BAR + 8 * (B_DSR + 2 * c + wg);
#pragma unroll
        for (int q = 0; q < 5; q++) st_async16(dso + q * 4096, sn[4 * q], sn[4 * q + 1], sn[4 * q + 2], sn[4 * q + 3], dsb);
      };
      auto finish = [&](int c) {
        mbar_wait(bars + 8 * (B_DSR + 2 * c + wg), 0);
        uint4* dst = g_part + (size_t)((i * 8 + ((j + 2 * c + 2) & 7)) * 3 + c) * 1280 + tid;
#pragma unroll
        for (int q = 0; q < 5; q++) {
          const uint4 v = lds128(sb + OFF_DS + (c & 1) * 20480 + tid * 16 + q * 4096);
          st_relaxed16(dst + q * 256, (add_bf2(v.x, kb[4 * q]) & ~1u) | tag, add_bf2(v.y, kb[4 * q + 1]),
                       add_bf2(v.z, kb[4 * q + 2]), add_bf2(v.w, kb[4 * q + 3]));
        }
      };
#pragma unroll
      for (int e = 0; e < 20; e++) sn[e] = kb[e] = 0u;
      auto chunk = [&](const int c, auto last_c) {
        constexpr bool LAST = decltype(last_c)::value;
        const uint32_t e0 = r4.idx;
        auto rel = [&](int u) { const uint32_t e = e0 + u; releaseB(bars + 8 * (B_EMPTY4 + (e >= NU4 ? e - NU4 : e))); };
#pragma unroll
        for (int u = 0; u < 4; u++) {
          mbar_wait(bars + 8 * (B_FULL4 + r4.idx), r4.phase);
          const uint32_t b0 = sb16 + ((OFF_B + r4.idx * UNIT4) >> 4);
          TRS(c * 16 + u * 3);
          wg_fence();
#pragma unroll
          for (int s = 0; s < (u < 3 ? 4 : 5); s++) {
            const uint64_t db = make_desc(b0, s * 1024, u < 3 ? 4096 : 5120, 512, 2);
            if (u == 0 && s == 0) mma_rs160_n_z(acc, hf[0], db);
            else if (u < 3) mma_rs160_n(acc, hf[(4 * u + s) % 12], db);
            else mma_rs160_n(acc, of[s], db);
          }
          wg_commit();
          TRS(c * 16 + u * 3 + 1);
          r4.next<NU4>();
          if (u > 0 && !LAST) { wg_wait<1>(); rel(u - 1); }
          if (u == 0 && c > 0) send(c - 1);
          if (u == 1 && c == 0) { if (wg == 0) bar_arrive(2, 256); mbar_wait(bars + 8 * B_PEER, 0); }
          if (u == (LAST ? 1 : 2) && c > 0) finish(c - 1);
          TRS(c * 16 + u * 3 + 2);
        }
        if (LAST) {
#pragma unroll
          for (int q = 0; q < 10; q++) pv4[q] = ld_relaxed16(gp + q * 256);
        }
        wg_wait<0>();
        fence_regs(acc);
        if (!LAST) rel(3);
        TRS(c * 16 + 12);
        if (rank) {
#pragma unroll
          for (int e = 0; e < 20; e++) { sn[e] = pack_bf16(acc[2 * e], acc[2 * e + 1]); kb[e] = pack_bf16(acc[40 + 2 * e], acc[41 + 2 * e]); }
        } else {
#pragma unroll
          for (int e = 0; e < 20; e++) { kb[e] = pack_bf16(acc[2 * e], acc[2 * e + 1]); sn[e] = pack_bf16(acc[40 + 2 * e], acc[41 + 2 * e]); }
        }
#pragma unroll
        for (int e = 0; e < 20; e++) asm volatile("" : "+r"(sn[e]), "+r"(kb[e]));
        TRS(c * 16 + 13);
      };
      if (wg == 1) bar_sync(2, 256);
#pragma unroll 1
      for (int c = 0; c < 3; c++) chunk(c, BoolC<false>{});
      chunk(3, BoolC<true>{});
#pragma unroll
      for (int q = 10; q < 15; q++) pv4[q] = ld_relaxed16(gp + q * 256);
      send(3);
      TSTAMP(13);
      {
        const float w0 = 1.f - st_g[0], w1s = 1.f - st_g[1];
#pragma unroll
        for (int g = 0; g < 10; g++) {
          kp[4 * g] = fmaf(w0, bf_lo(xv[0][g]), rank ? acc[40 + 4 * g] : acc[4 * g]);
          kp[4 * g + 1] = fmaf(w0, bf_hi(xv[0][g]), rank ? acc[41 + 4 * g] : acc[4 * g + 1]);
          kp[4 * g + 2] = fmaf(w1s, bf_lo(xv[1][g]), rank ? acc[42 + 4 * g] : acc[4 * g + 2]);
          kp[4 * g + 3] = fmaf(w1s, bf_hi(xv[1][g]), rank ? acc[43 + 4 * g] : acc[4 * g + 3]);
        }
      }
      mbar_wait(bars + 8 * (B_DSR + 6 + wg), 0);
      uint4 pr[5];
#pragma unroll
      for (int q = 0; q < 5; q++) pr[q] = lds128(sb + OFF_DS + 20480 + tid * 16 + q * 4096);
#pragma unroll 1
      for (uint32_t n = 0; n < (WAIT_LIMIT >> 4); n++) {
        uint32_t m = 0u;
#pragma unroll
        for (int q = 0; q < 15; q++) {
          const uint32_t bad = (pv4[q].x ^ tag) & 1u;
          m |= bad;
          if (bad) pv4[q] = ld_relaxed16(gp + q * 256);
        }
        if (m == 0u) break;
      }
      TSTAMP(14);
#pragma unroll
      for (int q = 0; q < 5; q++) {
        const uint4 a = pv4[q], b = pv4[5 + q], c = pv4[10 + q], d = pr[q];
        add8(q, make_uint4(add_bf2(a.x, b.x), add_bf2(a.y, b.y), add_bf2(a.z, b.z), add_bf2(a.w, b.w)));
        add8(q, make_uint4(add_bf2(c.x, d.x), add_bf2(c.y, d.y), add_bf2(c.z, d.z), add_bf2(c.w, d.w)));
      }
      __syncwarp();
      uint32_t ov[2][10];
#pragma unroll
      for (int g = 0; g < 10; g++) { ov[0][g] = pack_bf16(kp[4 * g], kp[4 * g + 1]); ov[1][g] = pack_bf16(kp[4 * g + 2], kp[4 * g + 3]); }
      store_tile(sb + OFF_OUT, ov, out + (size_t)(128 * i + 16 * warp) * D_ + 80 * j);
    }
    TSTAMP(15);
    if (tid == 0) asm volatile("red.relaxed.gpu.global.add.u32 [%0], 1;" ::"l"(g_flags + FL_DONE * 32) : "memory");
  }
}

namespace {
typedef CUresult (*EncodeFn)(CUtensorMap*, CUtensorMapDataType, cuuint32_t, void*, const cuuint64_t*, const cuuint64_t*,
                             const cuuint32_t*, const cuuint32_t*, CUtensorMapInterleave, CUtensorMapSwizzle,
                             CUtensorMapL2promotion, CUtensorMapFloatOOBfill);

void encode(EncodeFn fn, CUtensorMap* m, const void* ptr, int rank, const cuuint64_t* dims, const cuuint64_t* strides,
            const cuuint32_t* box, CUtensorMapSwizzle swz) {
  cuuint32_t es[5] = {1, 1, 1, 1, 1};
  fn(m, CU_TENSOR_MAP_DATA_TYPE_BFLOAT16, rank, const_cast<void*>(ptr), dims, strides, box, es, CU_TENSOR_MAP_INTERLEAVE_NONE,
     swz, CU_TENSOR_MAP_L2_PROMOTION_L2_128B, CU_TENSOR_MAP_FLOAT_OOB_FILL_NONE);
}
}

extern "C" void kernel_launch(void* const* d_in, const int* in_sizes, int n_in, void* d_out, int out_size) {
  (void)in_sizes; (void)n_in; (void)out_size;
  const __nv_bfloat16* x = (const __nv_bfloat16*)d_in[0];
  const __nv_bfloat16* wqkv = (const __nv_bfloat16*)d_in[1];
  const __nv_bfloat16* wphi = (const __nv_bfloat16*)d_in[2];
  const __nv_bfloat16* wo = (const __nv_bfloat16*)d_in[3];
  const __nv_bfloat16* w1 = (const __nv_bfloat16*)d_in[5];
  const __nv_bfloat16* w2 = (const __nv_bfloat16*)d_in[6];
  const __nv_bfloat16* w3 = (const __nv_bfloat16*)d_in[7];
  const __nv_bfloat16* w4 = (const __nv_bfloat16*)d_in[8];
  const __nv_bfloat16* gate_w = (const __nv_bfloat16*)d_in[9];

  static EncodeFn enc = nullptr;
  static void *pHs = nullptr, *pX1 = nullptr;
  if (!enc) {
    cudaDriverEntryPointQueryResult qr;
    cudaGetDriverEntryPoint("cuTensorMapEncodeTiled", (void**)&enc, cudaEnableDefault, &qr);
    cudaGetSymbolAddress(&pHs, g_Hs);
    cudaGetSymbolAddress(&pX1, g_X1);
    cudaFuncSetAttribute(fused_kernel, cudaFuncAttributeMaxDynamicSharedMemorySize, SMEM_BYTES);
  }
  Maps m;
  {
    cuuint64_t dims[2] = {D_, S_}, str[1] = {D_ * 2};
    cuuint32_t box[2] = {64, 128}, boxh[2] = {64, 64};
    encode(enc, &m.x, x, 2, dims, str, boxh, CU_TENSOR_MAP_SWIZZLE_128B);
    encode(enc, &m.hs, (const char*)pHs + 2 * D_ * 2, 2, dims, str, box, CU_TENSOR_MAP_SWIZZLE_128B);
    encode(enc, &m.x1, pX1, 2, dims, str, boxh, CU_TENSOR_MAP_SWIZZLE_128B);
    cuuint32_t boxr[2] = {80, 16};
    encode(enc, &m.xr, x, 2, dims, str, boxr, CU_TENSOR_MAP_SWIZZLE_NONE);
  }
  {
    cuuint64_t dims[3] = {80, D_, 8}, str[2] = {D_ * 2, 160};
    cuuint32_t boxm[3] = {64, 64, 1}, boxr[3] = {16, 64, 1};
    encode(enc, &m.w1m, w1, 3, dims, str, boxm, CU_TENSOR_MAP_SWIZZLE_128B);
    encode(enc, &m.w1r, w1, 3, dims, str, boxr, CU_TENSOR_MAP_SWIZZLE_32B);
  }
  {
    cuuint64_t dims[4] = {80, D_, 3, 8}, str[3] = {3 * D_ * 2, D_ * 2, 160};
    cuuint32_t boxm[4] = {64, 64, 3, 1}, boxr[4] = {16, 64, 3, 1};
    encode(enc, &m.qm, wqkv, 4, dims, str, boxm, CU_TENSOR_MAP_SWIZZLE_128B);
    encode(enc, &m.qr, wqkv, 4, dims, str, boxr, CU_TENSOR_MAP_SWIZZLE_32B);
  }
  {
    cuuint64_t dims[3] = {32, D_, 20}, dims4[3] = {32, F_, 20}, str[2] = {D_ * 2, 64};
    cuuint32_t box4[3] = {32, 64, 5}, boxo[3] = {32, 80, 5};
    encode(enc, &m.w4, w4, 3, dims4, str, box4, CU_TENSOR_MAP_SWIZZLE_64B);
    encode(enc, &m.wo, wo, 3, dims, str, boxo, CU_TENSOR_MAP_SWIZZLE_64B);
    encode(enc, &m.w2, w2, 3, dims, str, box4, CU_TENSOR_MAP_SWIZZLE_64B);
  }
  {
    cuuint64_t dims[3] = {64, D_, 24}, str[2] = {F_ * 2, 128};
    cuuint32_t box[3] = {64, 64, 3};
    encode(enc, &m.w3, w3, 3, dims, str, box, CU_TENSOR_MAP_SWIZZLE_128B);
  }
  fused_kernel<<<NCTA, 384, SMEM_BYTES, cudaStreamPerThread>>>(m, x, wqkv, wphi, w1, w2, w3, w4, wo, gate_w, (__nv_bfloat16*)d_out);
}
```

```cpp
#include <cuda_runtime.h>
#include <cuda_bf16.h>
#include <cuda.h>
#include <stdint.h>

namespace {

constexpr int S_ = 2048, D_ = 640, F_ = 1536;
constexpr int NCTA = 128;
constexpr int KV_PAIR = 40 * 48 + 96;
constexpr int KV_J = 2 * KV_PAIR;

constexpr int SLOT_B = 49152, NB = 3;
constexpr int SLOT_A = 16384, NA = 4;
constexpr int OFF_B = 0;
constexpr int OFF_A = OFF_B + NB * SLOT_B;
constexpr int OFF_STG = OFF_A + 2 * SLOT_A;
constexpr int OFF_MISC = OFF_A + NA * SLOT_A;
constexpr int OFF_XST = OFF_MISC + 13312;
constexpr int OFF_CS = OFF_MISC + 16384;
constexpr int OFF_BAR = OFF_CS + 1088;
constexpr int SMEM_BYTES = OFF_BAR + 512 + 512;
constexpr int B_FULLA = 0, B_FULLB = 4, B_CS = 7, B_XR = 8, B_KV = 9, B_ST1 = 10, B_HST = 11, B_FULL4 = 12  ,
              B_DSR = 17  , B_EMPTYB = 27  , B_SIGP = 30, B_SIGH = 31, B_SIGKV = 32, B_SIGX1 = 33, B_MFREE = 34,
              B_EMPTY4 = 35  , B_EMPTYA = 40  , B_PEER = 44, B_PEER2 = 45, NBAR = 46;
constexpr int SPARE = 40960;
constexpr int UNIT4 = 25600, NU4 = 5;
constexpr int OFF_DS = OFF_A, OFF_OUT = OFF_A + 40960;

constexpr int FL_DONE = 0, FL_H = 1  , FL_X1 = FL_H + 32, FL_KV = FL_X1 + 16, FL_CS = FL_KV + 8, FL_CS3 = FL_CS + 8, FL_ST = FL_CS3 + 8;
constexpr int FL_S1 = FL_ST + 16, FL_COUNT = FL_S1 + 16;
constexpr int ACC_FLOATS = 8 * KV_J + D_ + F_;

struct Maps {
  CUtensorMap x, w1m, w1r, qm, qr, hs, w2, x1, w3, w4, wo, xr, st_h, st_x1;
};

}

__device__ __align__(1024) __nv_bfloat16 g_Hs[(S_ + 4) * D_];
__device__ __align__(1024) __nv_bfloat16 g_X1[S_ * D_];
__device__ __align__(128) float g_acc[2][ACC_FLOATS];
__device__ __align__(128) float4 g_xstat[S_];
__device__ __align__(128) float2 g_st1[S_ * 8];
__device__ __align__(128) uint4 g_part[16 * 8 * 3 * 1280];
__device__ __align__(128) unsigned g_flags[FL_COUNT * 32];
#define TSTAMP(n) do {} while (0)
#define TSTAMPX(n) do {} while (0)
#define TRACE(n) do {} while (0)
#define TRS(n) do {} while (0)

namespace {

__device__ __forceinline__ long long gtime() { long long t; asm volatile("mov.u64 %0, %%globaltimer;" : "=l"(t)); return t; }
__device__ __forceinline__ uint32_t smem_u32(const void* p) { return (uint32_t)__cvta_generic_to_shared(p); }
__device__ __forceinline__ void mbar_init(uint32_t bar, int cnt) {
  asm volatile("mbarrier.init.shared::cta.b64 [%0], %1;" ::"r"(bar), "r"(cnt) : "memory");
}
__device__ __forceinline__ void mbar_expect_tx(uint32_t bar, int bytes) {
  asm volatile("mbarrier.arrive.expect_tx.shared::cta.b64 _, [%0], %1;" ::"r"(bar), "r"(bytes) : "memory");
}
__device__ __forceinline__ void mbar_arrive_cta(uint32_t bar, uint32_t cta) {
  asm volatile("{\n.reg .b32 ra;\nmapa.shared::cluster.u32 ra, %0, %1;\nmbarrier.arrive.shared::cluster.b64 _, [ra];\n}"
               ::"r"(bar), "r"(cta) : "memory");
}
__device__ __forceinline__ uint32_t mbar_try(uint32_t bar, uint32_t parity) {
  uint32_t ok;
  asm volatile("{\n.reg .pred p;\nmbarrier.try_wait.parity.shared::cta.b64 p, [%1], %2;\nselp.u32 %0, 1, 0, p;\n}"
               : "=r"(ok) : "r"(bar), "r"(parity) : "memory");
  return ok;
}
constexpr uint32_t WAIT_LIMIT = 1u << 22;
__device__ __forceinline__ void mbar_wait(uint32_t bar, uint32_t parity) {
  uint32_t n = 0;
  while (!mbar_try(bar, parity) && ++n < WAIT_LIMIT) {}
}
__device__ __forceinline__ unsigned ld_acquire(const unsigned* p) {
  unsigned v;
  asm volatile("ld.acquire.gpu.global.u32 %0, [%1];" : "=r"(v) : "l"(p) : "memory");
  return v;
}
__device__ __forceinline__ void flag_wait(int idx, unsigned target) {
  const unsigned* p = g_flags + idx * 32;
  uint32_t n = 0;
  while ((int)(ld_acquire(p) - target) < 0 && ++n < (WAIT_LIMIT >> 4)) {}
}
__device__ __forceinline__ void flag_add(int idx) {
  asm volatile("red.release.gpu.global.add.u32 [%0], 1;" ::"l"(g_flags + idx * 32) : "memory");
}
__device__ __forceinline__ void flag_add_relaxed(int idx) {
  asm volatile("red.relaxed.gpu.global.add.u32 [%0], 1;" ::"l"(g_flags + idx * 32) : "memory");
}
__device__ __forceinline__ uint32_t mbar_test(uint32_t bar, uint32_t parity) {
  uint32_t ok;
  asm volatile("{\n.reg .pred p;\nmbarrier.test_wait.parity.shared::cta.b64 p, [%1], %2;\nselp.u32 %0, 1, 0, p;\n}"
               : "=r"(ok) : "r"(bar), "r"(parity) : "memory");
  return ok;
}
__device__ __forceinline__ uint32_t lds32(uint32_t a) {
  uint32_t v;
  asm volatile("ld.shared.u32 %0, [%1];" : "=r"(v) : "r"(a) : "memory");
  return v;
}
__device__ __forceinline__ void mbar_arrive(uint32_t bar) {
  asm volatile("mbarrier.arrive.shared::cta.b64 _, [%0];" ::"r"(bar) : "memory");
}
__device__ __forceinline__ void fence_async_glb() { asm volatile("fence.proxy.async.global;" ::: "memory"); }
__device__ __forceinline__ void fence_async_smem() { asm volatile("fence.proxy.async.shared::cta;" ::: "memory"); }
__device__ __forceinline__ void bar_sync(int id, int n) { asm volatile("bar.sync %0, %1;" ::"r"(id), "r"(n) : "memory"); }

__device__ __forceinline__ void tma2d(uint32_t dst, const CUtensorMap* m, uint32_t bar, int c0, int c1) {
  asm volatile("cp.async.bulk.tensor.2d.shared::cluster.global.mbarrier::complete_tx::bytes [%0], [%1, {%3, %4}], [%2];"
               ::"r"(dst), "l"(m), "r"(bar), "r"(c0), "r"(c1) : "memory");
}
__device__ __forceinline__ void tma2d_mc(uint32_t dst, const CUtensorMap* m, uint32_t bar, int c0, int c1) {
  asm volatile("cp.async.bulk.tensor.2d.shared::cluster.global.mbarrier::complete_tx::bytes.multicast::cluster"
               " [%0], [%1, {%3, %4}], [%2], %5;"
               ::"r"(dst), "l"(m), "r"(bar), "r"(c0), "r"(c1), "h"((uint16_t)3) : "memory");
}
__device__ __forceinline__ void tma3d(uint32_t dst, const CUtensorMap* m, uint32_t bar, int c0, int c1, int c2) {
  asm volatile("cp.async.bulk.tensor.3d.shared::cluster.global.mbarrier::complete_tx::bytes [%0], [%1, {%3, %4, %5}], [%2];"
               ::"r"(dst), "l"(m), "r"(bar), "r"(c0), "r"(c1), "r"(c2) : "memory");
}
__device__ __forceinline__ void tma4d(uint32_t dst, const CUtensorMap* m, uint32_t bar, int c0, int c1, int c2, int c3) {
  asm volatile("cp.async.bulk.tensor.4d.shared::cluster.global.mbarrier::complete_tx::bytes [%0], [%1, {%3, %4, %5, %6}], [%2];"
               ::"r"(dst), "l"(m), "r"(bar), "r"(c0), "r"(c1), "r"(c2), "r"(c3) : "memory");
}
__device__ __forceinline__ void tma2d_store(const CUtensorMap* m, uint32_t src, int c0, int c1) {
  asm volatile("cp.async.bulk.tensor.2d.global.shared::cta.bulk_group [%0, {%2, %3}], [%1];"
               ::"l"(m), "r"(src), "r"(c0), "r"(c1) : "memory");
}
__device__ __forceinline__ void bulk_store(void* dst, uint32_t src, uint32_t bytes) {
  asm volatile("cp.async.bulk.global.shared::cta.bulk_group [%0], [%1], %2;" ::"l"(dst), "r"(src), "r"(bytes) : "memory");
}
__device__ __forceinline__ void bulk_load(uint32_t dst, const void* src, uint32_t bytes, uint32_t bar) {
  asm volatile("cp.async.bulk.shared::cluster.global.mbarrier::complete_tx::bytes [%0], [%1], %2, [%3];"
               ::"r"(dst), "l"(src), "r"(bytes), "r"(bar) : "memory");
}
__device__ __forceinline__ void bulk_commit() { asm volatile("cp.async.bulk.commit_group;" ::: "memory"); }
template <int N> __device__ __forceinline__ void bulk_wait() { asm volatile("cp.async.bulk.wait_group %0;" ::"n"(N) : "memory"); }
__device__ __forceinline__ void bulk_wait_read() { asm volatile("cp.async.bulk.wait_group.read 0;" ::: "memory"); }
__device__ __forceinline__ void bar_arrive(int id, int n) { asm volatile("bar.arrive %0, %1;" ::"r"(id), "r"(n) : "memory"); }
__device__ __forceinline__ uint4 lds128(uint32_t a) {
  uint4 v;
  asm volatile("ld.shared.v4.u32 {%0, %1, %2, %3}, [%4];" : "=r"(v.x), "=r"(v.y), "=r"(v.z), "=r"(v.w) : "r"(a) : "memory");
  return v;
}
__device__ __forceinline__ void sts128(uint32_t a, uint4 v) {
  asm volatile("st.shared.v4.u32 [%0], {%1, %2, %3, %4};" ::"r"(a), "r"(v.x), "r"(v.y), "r"(v.z), "r"(v.w) : "memory");
}
__device__ __forceinline__ uint4 ld_relaxed16(const uint4* p) {
  uint4 v;
  asm volatile("ld.relaxed.gpu.global.v4.u32 {%0, %1, %2, %3}, [%4];" : "=r"(v.x), "=r"(v.y), "=r"(v.z), "=r"(v.w) : "l"(p) : "memory");
  return v;
}
__device__ __forceinline__ void st_relaxed16(uint4* p, uint32_t a, uint32_t b, uint32_t c, uint32_t d) {
  asm volatile("st.relaxed.gpu.global.v4.u32 [%0], {%1, %2, %3, %4};" ::"l"(p), "r"(a), "r"(b), "r"(c), "r"(d) : "memory");
}
__device__ __forceinline__ uint32_t map_peer(uint32_t addr, uint32_t cta) {
  uint32_t r;
  asm("mapa.shared::cluster.u32 %0, %1, %2;" : "=r"(r) : "r"(addr), "r"(cta));
  return r;
}
__device__ __forceinline__ void st_async16(uint32_t addr, uint32_t a, uint32_t b, uint32_t c, uint32_t d, uint32_t bar) {
  asm volatile("st.async.weak.shared::cluster.mbarrier::complete_tx::bytes.v4.b32 [%0], {%1, %2, %3, %4}, [%5];"
               ::"r"(addr), "r"(a), "r"(b), "r"(c), "r"(d), "r"(bar) : "memory");
}
__device__ __forceinline__ void l2_prefetch(const void* p, uint32_t bytes) {
  asm volatile("cp.async.bulk.prefetch.L2.global [%0], %1;" ::"l"(p), "r"(bytes) : "memory");
}
__device__ __forceinline__ void prefetch_tmap(const CUtensorMap* m) {
  asm volatile("prefetch.tensormap [%0];" ::"l"(m) : "memory");
}
__device__ __forceinline__ uint64_t make_desc(uint32_t a16, uint32_t off, uint32_t lbo, uint32_t sbo, uint32_t swz) {
  const uint32_t lo = a16 + ((off >> 4) + ((lbo >> 4) << 16)), hi = (sbo >> 4) | (swz << 30);
  uint64_t d;
  asm("mov.b64 %0, {%1, %2};" : "=l"(d) : "r"(lo), "r"(hi));
  return d;
}
__device__ __forceinline__ void wg_fence() { asm volatile("wgmma.fence.sync.aligned;" ::: "memory"); }
__device__ __forceinline__ void wg_commit() { asm volatile("wgmma.commit_group.sync.aligned;" ::: "memory"); }
template <int N> __device__ __forceinline__ void wg_wait() { asm volatile("wgmma.wait_group.sync.aligned %0;" ::"n"(N) : "memory"); }
template <int N> __device__ __forceinline__ void fence_regs(float (&d)[N]) {
#pragma unroll
  for (int i = 0; i < N; i++) asm volatile("" : "+f"(d[i])::"memory");
}
template <int N> __device__ __forceinline__ void zero_regs(float (&d)[N]) {
#pragma unroll
  for (int i = 0; i < N; i++) d[i] = 0.f;
}
__device__ __forceinline__ uint32_t pack_bf16(float lo, float hi) {
  uint32_t r;
  asm("cvt.rn.bf16x2.f32 %0, %1, %2;" : "=r"(r) : "f"(hi), "f"(lo));
  return r;
}
__device__ __forceinline__ float bf_lo(uint32_t v) { return __uint_as_float(v << 16); }
__device__ __forceinline__ float bf_hi(uint32_t v) { return __uint_as_float(v & 0xffff0000u); }
__device__ __forceinline__ uint32_t max_bf2(uint32_t a, uint32_t b) {
  uint32_t r; asm("max.bf16x2 %0, %1, %2;" : "=r"(r) : "r"(a), "r"(b)); return r;
}
__device__ __forceinline__ uint32_t min_bf2(uint32_t a, uint32_t b) {
  uint32_t r; asm("min.bf16x2 %0, %1, %2;" : "=r"(r) : "r"(a), "r"(b)); return r;
}
__device__ __forceinline__ uint32_t add_bf2(uint32_t a, uint32_t b) {
  uint32_t r; asm("add.rn.bf16x2 %0, %1, %2;" : "=r"(r) : "r"(a), "r"(b)); return r;
}
__device__ __forceinline__ float ex2(float x) { float r; asm("ex2.approx.ftz.f32 %0, %1;" : "=f"(r) : "f"(x)); return r; }
__device__ __forceinline__ float rcp(float x) { float r; asm("rcp.approx.ftz.f32 %0, %1;" : "=f"(r) : "f"(x)); return r; }
__device__ __forceinline__ float tanh_ap(float x) { float r; asm("tanh.approx.f32 %0, %1;" : "=f"(r) : "f"(x)); return r; }
struct GeluC { float c0, c1, ch; };
__device__ __forceinline__ GeluC gelu_consts(float rstd, float scale) {
  return GeluC{0.7978845608f * rstd, 0.0356774081f * rstd * rstd * rstd, 0.5f * scale * rstd};
}
__device__ __forceinline__ float gelu_s(float y, const GeluC& c) {
  const float u = y * fmaf(y * y, c.c1, c.c0);
  const float hx = y * c.ch;
  return fmaf(hx, tanh_ap(u), hx);
}
__device__ __forceinline__ void stsm4(uint32_t addr, uint32_t r0, uint32_t r1, uint32_t r2, uint32_t r3) {
  asm volatile("stmatrix.sync.aligned.m8n8.x4.shared.b16 [%0], {%1, %2, %3, %4};"
               ::"r"(addr), "r"(r0), "r"(r1), "r"(r2), "r"(r3) : "memory");
}
__device__ __forceinline__ void red_add4(float* p, float a, float b, float c, float d) {
  asm volatile("red.global.add.v4.f32 [%0], {%1, %2, %3, %4};" ::"l"(p), "f"(a), "f"(b), "f"(c), "f"(d) : "memory");
}

__device__ __forceinline__ void mma_ss256(float (&d)[128], uint64_t descA, uint64_t descB) {
  asm volatile("wgmma.mma_async.sync.aligned.m64n256k16.f32.bf16.bf16 {"
      "%0, %1, %2, %3, %4, %5, %6, %7, %8, %9, %10, %11, %12, %13, %14, %15, "
      "%16, %17, %18, %19, %20, %21, %22, %23, %24, %25, %26, %27, %28, %29, %30, %31, "
      "%32, %33, %34, %35, %36, %37, %38, %39, %40, %41, %42, %43, %44, %45, %46, %47, "
      "%48, %49, %50, %51, %52, %53, %54, %55, %56, %57, %58, %59, %60, %61, %62, %63, "
      "%64, %65, %66, %67, %68, %69, %70, %71, %72, %73, %74, %75, %76, %77, %78, %79, "
      "%80, %81, %82, %83, %84, %85, %86, %87, %88, %89, %90, %91, %92, %93, %94, %95, "
      "%96, %97, %98, %99, %100, %101, %102, %103, %104, %105, %106, %107, %108, %109, %110, %111, "
      "%112, %113, %114, %115, %116, %117, %118, %119, %120, %121, %122, %123, %124, %125, %126, %127"
      "}, %128, %129, 1, 1, 1, 0, 1;\n"
      : "+f"(d[0]), "+f"(d[1]), "+f"(d[2]), "+f"(d[3]), "+f"(d[4]), "+f"(d[5]), "+f"(d[6]), "+f"(d[7]),
        "+f"(d[8]), "+f"(d[9]), "+f"(d[10]), "+f"(d[11]), "+f"(d[12]), "+f"(d[13]), "+f"(d[14]), "+f"(d[15]),
        "+f"(d[16]), "+f"(d[17]), "+f"(d[18]), "+f"(d[19]), "+f"(d[20]), "+f"(d[21]), "+f"(d[22]), "+f"(d[23]),
        "+f"(d[24]), "+f"(d[25]), "+f"(d[26]), "+f"(d[27]), "+f"(d[28]), "+f"(d[29]), "+f"(d[30]), "+f"(d[31]),
        "+f"(d[32]), "+f"(d[33]), "+f"(d[34]), "+f"(d[35]), "+f"(d[36]), "+f"(d[37]), "+f"(d[38]), "+f"(d[39]),
        "+f"(d[40]), "+f"(d[41]), "+f"(d[42]), "+f"(d[43]), "+f"(d[44]), "+f"(d[45]), "+f"(d[46]), "+f"(d[47]),
        "+f"(d[48]), "+f"(d[49]), "+f"(d[50]), "+f"(d[51]), "+f"(d[52]), "+f"(d[53]), "+f"(d[54]), "+f"(d[55]),
        "+f"(d[56]), "+f"(d[57]), "+f"(d[58]), "+f"(d[59]), "+f"(d[60]), "+f"(d[61]), "+f"(d[62]), "+f"(d[63]),
        "+f"(d[64]), "+f"(d[65]), "+f"(d[66]), "+f"(d[67]), "+f"(d[68]), "+f"(d[69]), "+f"(d[70]), "+f"(d[71]),
        "+f"(d[72]), "+f"(d[73]), "+f"(d[74]), "+f"(d[75]), "+f"(d[76]), "+f"(d[77]), "+f"(d[78]), "+f"(d[79]),
        "+f"(d[80]), "+f"(d[81]), "+f"(d[82]), "+f"(d[83]), "+f"(d[84]), "+f"(d[85]), "+f"(d[86]), "+f"(d[87]),
        "+f"(d[88]), "+f"(d[89]), "+f"(d[90]), "+f"(d[91]), "+f"(d[92]), "+f"(d[93]), "+f"(d[94]), "+f"(d[95]),
        "+f"(d[96]), "+f"(d[97]), "+f"(d[98]), "+f"(d[99]), "+f"(d[100]), "+f"(d[101]), "+f"(d[102]), "+f"(d[103]),
        "+f"(d[104]), "+f"(d[105]), "+f"(d[106]), "+f"(d[107]), "+f"(d[108]), "+f"(d[109]), "+f"(d[110]), "+f"(d[111]),
        "+f"(d[112]), "+f"(d[113]), "+f"(d[114]), "+f"(d[115]), "+f"(d[116]), "+f"(d[117]), "+f"(d[118]), "+f"(d[119]),
        "+f"(d[120]), "+f"(d[121]), "+f"(d[122]), "+f"(d[123]), "+f"(d[124]), "+f"(d[125]), "+f"(d[126]), "+f"(d[127])
      : "l"(descA), "l"(descB));
}
__device__ __forceinline__ void mma_ss256_p(float (&d)[128], uint64_t descA, uint64_t descB, int acc) {
  asm volatile("{\n.reg .pred p;\nsetp.ne.b32 p, %130, 0;\n"
      "wgmma.mma_async.sync.aligned.m64n256k16.f32.bf16.bf16 {"
      "%0, %1, %2, %3, %4, %5, %6, %7, %8, %9, %10, %11, %12, %13, %14, %15, "
      "%16, %17, %18, %19, %20, %21, %22, %23, %24, %25, %26, %27, %28, %29, %30, %31, "
      "%32, %33, %34, %35, %36, %37, %38, %39, %40, %41, %42, %43, %44, %45, %46, %47, "
      "%48, %49, %50, %51, %52, %53, %54, %55, %56, %57, %58, %59, %60, %61, %62, %63, "
      "%64, %65, %66, %67, %68, %69, %70, %71, %72, %73, %74, %75, %76, %77, %78, %79, "
      "%80, %81, %82, %83, %84, %85, %86, %87, %88, %89, %90, %91, %92, %93, %94, %95, "
      "%96, %97, %98, %99, %100, %101, %102, %103, %104, %105, %106, %107, %108, %109, %110, %111, "
      "%112, %113, %114, %115, %116, %117, %118, %119, %120, %121, %122, %123, %124, %125, %126, %127"
      "}, %128, %129, p, 1, 1, 0, 1;\n}\n"
      : "+f"(d[0]), "+f"(d[1]), "+f"(d[2]), "+f"(d[3]), "+f"(d[4]), "+f"(d[5]), "+f"(d[6]), "+f"(d[7]),
        "+f"(d[8]), "+f"(d[9]), "+f"(d[10]), "+f"(d[11]), "+f"(d[12]), "+f"(d[13]), "+f"(d[14]), "+f"(d[15]),
        "+f"(d[16]), "+f"(d[17]), "+f"(d[18]), "+f"(d[19]), "+f"(d[20]), "+f"(d[21]), "+f"(d[22]), "+f"(d[23]),
        "+f"(d[24]), "+f"(d[25]), "+f"(d[26]), "+f"(d[27]), "+f"(d[28]), "+f"(d[29]), "+f"(d[30]), "+f"(d[31]),
        "+f"(d[32]), "+f"(d[33]), "+f"(d[34]), "+f"(d[35]), "+f"(d[36]), "+f"(d[37]), "+f"(d[38]), "+f"(d[39]),
        "+f"(d[40]), "+f"(d[41]), "+f"(d[42]), "+f"(d[43]), "+f"(d[44]), "+f"(d[45]), "+f"(d[46]), "+f"(d[47]),
        "+f"(d[48]), "+f"(d[49]), "+f"(d[50]), "+f"(d[51]), "+f"(d[52]), "+f"(d[53]), "+f"(d[54]), "+f"(d[55]),
        "+f"(d[56]), "+f"(d[57]), "+f"(d[58]), "+f"(d[59]), "+f"(d[60]), "+f"(d[61]), "+f"(d[62]), "+f"(d[63]),
        "+f"(d[64]), "+f"(d[65]), "+f"(d[66]), "+f"(d[67]), "+f"(d[68]), "+f"(d[69]), "+f"(d[70]), "+f"(d[71]),
        "+f"(d[72]), "+f"(d[73]), "+f"(d[74]), "+f"(d[75]), "+f"(d[76]), "+f"(d[77]), "+f"(d[78]), "+f"(d[79]),
        "+f"(d[80]), "+f"(d[81]), "+f"(d[82]), "+f"(d[83]), "+f"(d[84]), "+f"(d[85]), "+f"(d[86]), "+f"(d[87]),
        "+f"(d[88]), "+f"(d[89]), "+f"(d[90]), "+f"(d[91]), "+f"(d[92]), "+f"(d[93]), "+f"(d[94]), "+f"(d[95]),
        "+f"(d[96]), "+f"(d[97]), "+f"(d[98]), "+f"(d[99]), "+f"(d[100]), "+f"(d[101]), "+f"(d[102]), "+f"(d[103]),
        "+f"(d[104]), "+f"(d[105]), "+f"(d[106]), "+f"(d[107]), "+f"(d[108]), "+f"(d[109]), "+f"(d[110]), "+f"(d[111]),
        "+f"(d[112]), "+f"(d[113]), "+f"(d[114]), "+f"(d[115]), "+f"(d[116]), "+f"(d[117]), "+f"(d[118]), "+f"(d[119]),
        "+f"(d[120]), "+f"(d[121]), "+f"(d[122]), "+f"(d[123]), "+f"(d[124]), "+f"(d[125]), "+f"(d[126]), "+f"(d[127])
      : "l"(descA), "l"(descB), "r"(acc));
}

__device__ __forceinline__ void mma_ss64(float (&d)[32], uint64_t descA, uint64_t descB) {
  asm volatile("wgmma.mma_async.sync.aligned.m64n64k16.f32.bf16.bf16 {"
      "%0, %1, %2, %3, %4, %5, %6, %7, %8, %9, %10, %11, %12, %13, %14, %15, "
      "%16, %17, %18, %19, %20, %21, %22, %23, %24, %25, %26, %27, %28, %29, %30, %31"
      "}, %32, %33, 1, 1, 1, 0, 1;\n"
      : "+f"(d[0]), "+f"(d[1]), "+f"(d[2]), "+f"(d[3]), "+f"(d[4]), "+f"(d[5]), "+f"(d[6]), "+f"(d[7]),
        "+f"(d[8]), "+f"(d[9]), "+f"(d[10]), "+f"(d[11]), "+f"(d[12]), "+f"(d[13]), "+f"(d[14]), "+f"(d[15]),
        "+f"(d[16]), "+f"(d[17]), "+f"(d[18]), "+f"(d[19]), "+f"(d[20]), "+f"(d[21]), "+f"(d[22]), "+f"(d[23]),
        "+f"(d[24]), "+f"(d[25]), "+f"(d[26]), "+f"(d[27]), "+f"(d[28]), "+f"(d[29]), "+f"(d[30]), "+f"(d[31])
      : "l"(descA), "l"(descB));
}
__device__ __forceinline__ void mma_ss64_p(float (&d)[32], uint64_t descA, uint64_t descB, int acc) {
  asm volatile("{\n.reg .pred p;\nsetp.ne.b32 p, %34, 0;\n"
      "wgmma.mma_async.sync.aligned.m64n64k16.f32.bf16.bf16 {"
      "%0, %1, %2, %3, %4, %5, %6, %7, %8, %9, %10, %11, %12, %13, %14, %15, "
      "%16, %17, %18, %19, %20, %21, %22, %23, %24, %25, %26, %27, %28, %29, %30, %31"
      "}, %32, %33, p, 1, 1, 0, 1;\n}\n"
      : "+f"(d[0]), "+f"(d[1]), "+f"(d[2]), "+f"(d[3]), "+f"(d[4]), "+f"(d[5]), "+f"(d[6]), "+f"(d[7]),
        "+f"(d[8]), "+f"(d[9]), "+f"(d[10]), "+f"(d[11]), "+f"(d[12]), "+f"(d[13]), "+f"(d[14]), "+f"(d[15]),
        "+f"(d[16]), "+f"(d[17]), "+f"(d[18]), "+f"(d[19]), "+f"(d[20]), "+f"(d[21]), "+f"(d[22]), "+f"(d[23]),
        "+f"(d[24]), "+f"(d[25]), "+f"(d[26]), "+f"(d[27]), "+f"(d[28]), "+f"(d[29]), "+f"(d[30]), "+f"(d[31])
      : "l"(descA), "l"(descB), "r"(acc));
}

__device__ __forceinline__ void mma_ss160(float (&d)[80], uint64_t descA, uint64_t descB) {
  asm volatile("wgmma.mma_async.sync.aligned.m64n160k16.f32.bf16.bf16 {"
      "%0, %1, %2, %3, %4, %5, %6, %7, %8, %9, %10, %11, %12, %13, %14, %15, "
      "%16, %17, %18, %19, %20, %21, %22, %23, %24, %25, %26, %27, %28, %29, %30, %31, "
      "%32, %33, %34, %35, %36, %37, %38, %39, %40, %41, %42, %43, %44, %45, %46, %47, "
      "%48, %49, %50, %51, %52, %53, %54, %55, %56, %57, %58, %59, %60, %61, %62, %63, "
      "%64, %65, %66, %67, %68, %69, %70, %71, %72, %73, %74, %75, %76, %77, %78, %79"
      "}, %80, %81, 1, 1, 1, 0, 1;\n"
      : "+f"(d[0]), "+f"(d[1]), "+f"(d[2]), "+f"(d[3]), "+f"(d[4]), "+f"(d[5]), "+f"(d[6]), "+f"(d[7]),
        "+f"(d[8]), "+f"(d[9]), "+f"(d[10]), "+f"(d[11]), "+f"(d[12]), "+f"(d[13]), "+f"(d[14]), "+f"(d[15]),
        "+f"(d[16]), "+f"(d[17]), "+f"(d[18]), "+f"(d[19]), "+f"(d[20]), "+f"(d[21]), "+f"(d[22]), "+f"(d[23]),
        "+f"(d[24]), "+f"(d[25]), "+f"(d[26]), "+f"(d[27]), "+f"(d[28]), "+f"(d[29]), "+f"(d[30]), "+f"(d[31]),
        "+f"(d[32]), "+f"(d[33]), "+f"(d[34]), "+f"(d[35]), "+f"(d[36]), "+f"(d[37]), "+f"(d[38]), "+f"(d[39]),
        "+f"(d[40]), "+f"(d[41]), "+f"(d[42]), "+f"(d[43]), "+f"(d[44]), "+f"(d[45]), "+f"(d[46]), "+f"(d[47]),
        "+f"(d[48]), "+f"(d[49]), "+f"(d[50]), "+f"(d[51]), "+f"(d[52]), "+f"(d[53]), "+f"(d[54]), "+f"(d[55]),
        "+f"(d[56]), "+f"(d[57]), "+f"(d[58]), "+f"(d[59]), "+f"(d[60]), "+f"(d[61]), "+f"(d[62]), "+f"(d[63]),
        "+f"(d[64]), "+f"(d[65]), "+f"(d[66]), "+f"(d[67]), "+f"(d[68]), "+f"(d[69]), "+f"(d[70]), "+f"(d[71]),
        "+f"(d[72]), "+f"(d[73]), "+f"(d[74]), "+f"(d[75]), "+f"(d[76]), "+f"(d[77]), "+f"(d[78]), "+f"(d[79])
      : "l"(descA), "l"(descB));
}

__device__ __forceinline__ void mma_ss192(float (&d)[96], uint64_t descA, uint64_t descB) {
  asm volatile("wgmma.mma_async.sync.aligned.m64n192k16.f32.bf16.bf16 {"
      "%0, %1, %2, %3, %4, %5, %6, %7, %8, %9, %10, %11, %12, %13, %14, %15, "
      "%16, %17, %18, %19, %20, %21, %22, %23, %24, %25, %26, %27, %28, %29, %30, %31, "
      "%32, %33, %34, %35, %36, %37, %38, %39, %40, %41, %42, %43, %44, %45, %46, %47, "
      "%48, %49, %50, %51, %52, %53, %54, %55, %56, %57, %58, %59, %60, %61, %62, %63, "
      "%64, %65, %66, %67, %68, %69, %70, %71, %72, %73, %74, %75, %76, %77, %78, %79, "
      "%80, %81, %82, %83, %84, %85, %86, %87, %88, %89, %90, %91, %92, %93, %94, %95"
      "}, %96, %97, 1, 1, 1, 0, 1;\n"
      : "+f"(d[0]), "+f"(d[1]), "+f"(d[2]), "+f"(d[3]), "+f"(d[4]), "+f"(d[5]), "+f"(d[6]), "+f"(d[7]),
        "+f"(d[8]), "+f"(d[9]), "+f"(d[10]), "+f"(d[11]), "+f"(d[12]), "+f"(d[13]), "+f"(d[14]), "+f"(d[15]),
        "+f"(d[16]), "+f"(d[17]), "+f"(d[18]), "+f"(d[19]), "+f"(d[20]), "+f"(d[21]), "+f"(d[22]), "+f"(d[23]),
        "+f"(d[24]), "+f"(d[25]), "+f"(d[26]), "+f"(d[27]), "+f"(d[28]), "+f"(d[29]), "+f"(d[30]), "+f"(d[31]),
        "+f"(d[32]), "+f"(d[33]), "+f"(d[34]), "+f"(d[35]), "+f"(d[36]), "+f"(d[37]), "+f"(d[38]), "+f"(d[39]),
        "+f"(d[40]), "+f"(d[41]), "+f"(d[42]), "+f"(d[43]), "+f"(d[44]), "+f"(d[45]), "+f"(d[46]), "+f"(d[47]),
        "+f"(d[48]), "+f"(d[49]), "+f"(d[50]), "+f"(d[51]), "+f"(d[52]), "+f"(d[53]), "+f"(d[54]), "+f"(d[55]),
        "+f"(d[56]), "+f"(d[57]), "+f"(d[58]), "+f"(d[59]), "+f"(d[60]), "+f"(d[61]), "+f"(d[62]), "+f"(d[63]),
        "+f"(d[64]), "+f"(d[65]), "+f"(d[66]), "+f"(d[67]), "+f"(d[68]), "+f"(d[69]), "+f"(d[70]), "+f"(d[71]),
        "+f"(d[72]), "+f"(d[73]), "+f"(d[74]), "+f"(d[75]), "+f"(d[76]), "+f"(d[77]), "+f"(d[78]), "+f"(d[79]),
        "+f"(d[80]), "+f"(d[81]), "+f"(d[82]), "+f"(d[83]), "+f"(d[84]), "+f"(d[85]), "+f"(d[86]), "+f"(d[87]),
        "+f"(d[88]), "+f"(d[89]), "+f"(d[90]), "+f"(d[91]), "+f"(d[92]), "+f"(d[93]), "+f"(d[94]), "+f"(d[95])
      : "l"(descA), "l"(descB));
}
__device__ __forceinline__ void mma_ss192_p(float (&d)[96], uint64_t descA, uint64_t descB, int acc) {
  asm volatile("{\n.reg .pred p;\nsetp.ne.b32 p, %98, 0;\n"
      "wgmma.mma_async.sync.aligned.m64n192k16.f32.bf16.bf16 {"
      "%0, %1, %2, %3, %4, %5, %6, %7, %8, %9, %10, %11, %12, %13, %14, %15, "
      "%16, %17, %18, %19, %20, %21, %22, %23, %24, %25, %26, %27, %28, %29, %30, %31, "
      "%32, %33, %34, %35, %36, %37, %38, %39, %40, %41, %42, %43, %44, %45, %46, %47, "
      "%48, %49, %50, %51, %52, %53, %54, %55, %56, %57, %58, %59, %60, %61, %62, %63, "
      "%64, %65, %66, %67, %68, %69, %70, %71, %72, %73, %74, %75, %76, %77, %78, %79, "
      "%80, %81, %82, %83, %84, %85, %86, %87, %88, %89, %90, %91, %92, %93, %94, %95"
      "}, %96, %97, p, 1, 1, 0, 1;\n}\n"
      : "+f"(d[0]), "+f"(d[1]), "+f"(d[2]), "+f"(d[3]), "+f"(d[4]), "+f"(d[5]), "+f"(d[6]), "+f"(d[7]),
        "+f"(d[8]), "+f"(d[9]), "+f"(d[10]), "+f"(d[11]), "+f"(d[12]), "+f"(d[13]), "+f"(d[14]), "+f"(d[15]),
        "+f"(d[16]), "+f"(d[17]), "+f"(d[18]), "+f"(d[19]), "+f"(d[20]), "+f"(d[21]), "+f"(d[22]), "+f"(d[23]),
        "+f"(d[24]), "+f"(d[25]), "+f"(d[26]), "+f"(d[27]), "+f"(d[28]), "+f"(d[29]), "+f"(d[30]), "+f"(d[31]),
        "+f"(d[32]), "+f"(d[33]), "+f"(d[34]), "+f"(d[35]), "+f"(d[36]), "+f"(d[37]), "+f"(d[38]), "+f"(d[39]),
        "+f"(d[40]), "+f"(d[41]), "+f"(d[42]), "+f"(d[43]), "+f"(d[44]), "+f"(d[45]), "+f"(d[46]), "+f"(d[47]),
        "+f"(d[48]), "+f"(d[49]), "+f"(d[50]), "+f"(d[51]), "+f"(d[52]), "+f"(d[53]), "+f"(d[54]), "+f"(d[55]),
        "+f"(d[56]), "+f"(d[57]), "+f"(d[58]), "+f"(d[59]), "+f"(d[60]), "+f"(d[61]), "+f"(d[62]), "+f"(d[63]),
        "+f"(d[64]), "+f"(d[65]), "+f"(d[66]), "+f"(d[67]), "+f"(d[68]), "+f"(d[69]), "+f"(d[70]), "+f"(d[71]),
        "+f"(d[72]), "+f"(d[73]), "+f"(d[74]), "+f"(d[75]), "+f"(d[76]), "+f"(d[77]), "+f"(d[78]), "+f"(d[79]),
        "+f"(d[80]), "+f"(d[81]), "+f"(d[82]), "+f"(d[83]), "+f"(d[84]), "+f"(d[85]), "+f"(d[86]), "+f"(d[87]),
        "+f"(d[88]), "+f"(d[89]), "+f"(d[90]), "+f"(d[91]), "+f"(d[92]), "+f"(d[93]), "+f"(d[94]), "+f"(d[95])
      : "l"(descA), "l"(descB), "r"(acc));
}

__device__ __forceinline__ void mma_ss80_tt(float (&d)[40], uint64_t descA, uint64_t descB) {
  asm volatile("wgmma.mma_async.sync.aligned.m64n80k16.f32.bf16.bf16 {"
      "%0, %1, %2, %3, %4, %5, %6, %7, %8, %9, %10, %11, %12, %13, %14, %15, "
      "%16, %17, %18, %19, %20, %21, %22, %23, %24, %25, %26, %27, %28, %29, %30, %31, "
      "%32, %33, %34, %35, %36, %37, %38, %39"
      "}, %40, %41, 1, 1, 1, 1, 1;\n"
      : "+f"(d[0]), "+f"(d[1]), "+f"(d[2]), "+f"(d[3]), "+f"(d[4]), "+f"(d[5]), "+f"(d[6]), "+f"(d[7]),
        "+f"(d[8]), "+f"(d[9]), "+f"(d[10]), "+f"(d[11]), "+f"(d[12]), "+f"(d[13]), "+f"(d[14]), "+f"(d[15]),
        "+f"(d[16]), "+f"(d[17]), "+f"(d[18]), "+f"(d[19]), "+f"(d[20]), "+f"(d[21]), "+f"(d[22]), "+f"(d[23]),
        "+f"(d[24]), "+f"(d[25]), "+f"(d[26]), "+f"(d[27]), "+f"(d[28]), "+f"(d[29]), "+f"(d[30]), "+f"(d[31]),
        "+f"(d[32]), "+f"(d[33]), "+f"(d[34]), "+f"(d[35]), "+f"(d[36]), "+f"(d[37]), "+f"(d[38]), "+f"(d[39])
      : "l"(descA), "l"(descB));
}
__device__ __forceinline__ void mma_ss80_tt_z(float (&d)[40], uint64_t descA, uint64_t descB) {
  asm volatile("wgmma.mma_async.sync.aligned.m64n80k16.f32.bf16.bf16 {"
      "%0, %1, %2, %3, %4, %5, %6, %7, %8, %9, %10, %11, %12, %13, %14, %15, "
      "%16, %17, %18, %19, %20, %21, %22, %23, %24, %25, %26, %27, %28, %29, %30, %31, "
      "%32, %33, %34, %35, %36, %37, %38, %39"
      "}, %40, %41, 0, 1, 1, 1, 1;\n"
      : "=f"(d[0]), "=f"(d[1]), "=f"(d[2]), "=f"(d[3]), "=f"(d[4]), "=f"(d[5]), "=f"(d[6]), "=f"(d[7]),
        "=f"(d[8]), "=f"(d[9]), "=f"(d[10]), "=f"(d[11]), "=f"(d[12]), "=f"(d[13]), "=f"(d[14]), "=f"(d[15]),
        "=f"(d[16]), "=f"(d[17]), "=f"(d[18]), "=f"(d[19]), "=f"(d[20]), "=f"(d[21]), "=f"(d[22]), "=f"(d[23]),
        "=f"(d[24]), "=f"(d[25]), "=f"(d[26]), "=f"(d[27]), "=f"(d[28]), "=f"(d[29]), "=f"(d[30]), "=f"(d[31]),
        "=f"(d[32]), "=f"(d[33]), "=f"(d[34]), "=f"(d[35]), "=f"(d[36]), "=f"(d[37]), "=f"(d[38]), "=f"(d[39])
      : "l"(descA), "l"(descB));
}

__device__ __forceinline__ void mma_rs80_k(float (&d)[40], const uint32_t (&a)[4], uint64_t descB) {
  asm volatile("wgmma.mma_async.sync.aligned.m64n80k16.f32.bf16.bf16 {"
      "%0, %1, %2, %3, %4, %5, %6, %7, %8, %9, %10, %11, %12, %13, %14, %15, "
      "%16, %17, %18, %19, %20, %21, %22, %23, %24, %25, %26, %27, %28, %29, %30, %31, "
      "%32, %33, %34, %35, %36, %37, %38, %39"
      "}, {%40, %41, %42, %43}, %44, 1, 1, 1, 0;\n"
      : "+f"(d[0]), "+f"(d[1]), "+f"(d[2]), "+f"(d[3]), "+f"(d[4]), "+f"(d[5]), "+f"(d[6]), "+f"(d[7]),
        "+f"(d[8]), "+f"(d[9]), "+f"(d[10]), "+f"(d[11]), "+f"(d[12]), "+f"(d[13]), "+f"(d[14]), "+f"(d[15]),
        "+f"(d[16]), "+f"(d[17]), "+f"(d[18]), "+f"(d[19]), "+f"(d[20]), "+f"(d[21]), "+f"(d[22]), "+f"(d[23]),
        "+f"(d[24]), "+f"(d[25]), "+f"(d[26]), "+f"(d[27]), "+f"(d[28]), "+f"(d[29]), "+f"(d[30]), "+f"(d[31]),
        "+f"(d[32]), "+f"(d[33]), "+f"(d[34]), "+f"(d[35]), "+f"(d[36]), "+f"(d[37]), "+f"(d[38]), "+f"(d[39])
      : "r"(a[0]), "r"(a[1]), "r"(a[2]), "r"(a[3]), "l"(descB));
}
__device__ __forceinline__ void mma_rs80_k_z(float (&d)[40], const uint32_t (&a)[4], uint64_t descB) {
  asm volatile("wgmma.mma_async.sync.aligned.m64n80k16.f32.bf16.bf16 {"
      "%0, %1, %2, %3, %4, %5, %6, %7, %8, %9, %10, %11, %12, %13, %14, %15, "
      "%16, %17, %18, %19, %20, %21, %22, %23, %24, %25, %26, %27, %28, %29, %30, %31, "
      "%32, %33, %34, %35, %36, %37, %38, %39"
      "}, {%40, %41, %42, %43}, %44, 0, 1, 1, 0;\n"
      : "=f"(d[0]), "=f"(d[1]), "=f"(d[2]), "=f"(d[3]), "=f"(d[4]), "=f"(d[5]), "=f"(d[6]), "=f"(d[7]),
        "=f"(d[8]), "=f"(d[9]), "=f"(d[10]), "=f"(d[11]), "=f"(d[12]), "=f"(d[13]), "=f"(d[14]), "=f"(d[15]),
        "=f"(d[16]), "=f"(d[17]), "=f"(d[18]), "=f"(d[19]), "=f"(d[20]), "=f"(d[21]), "=f"(d[22]), "=f"(d[23]),
        "=f"(d[24]), "=f"(d[25]), "=f"(d[26]), "=f"(d[27]), "=f"(d[28]), "=f"(d[29]), "=f"(d[30]), "=f"(d[31]),
        "=f"(d[32]), "=f"(d[33]), "=f"(d[34]), "=f"(d[35]), "=f"(d[36]), "=f"(d[37]), "=f"(d[38]), "=f"(d[39])
      : "r"(a[0]), "r"(a[1]), "r"(a[2]), "r"(a[3]), "l"(descB));
}

__device__ __forceinline__ void mma_rs48_k(float (&d)[24], const uint32_t (&a)[4], uint64_t descB) {
  asm volatile("wgmma.mma_async.sync.aligned.m64n48k16.f32.bf16.bf16 {"
      "%0, %1, %2, %3, %4, %5, %6, %7, %8, %9, %10, %11, %12, %13, %14, %15, "
      "%16, %17, %18, %19, %20, %21, %22, %23"
      "}, {%24, %25, %26, %27}, %28, 1, 1, 1, 0;\n"
      : "+f"(d[0]), "+f"(d[1]), "+f"(d[2]), "+f"(d[3]), "+f"(d[4]), "+f"(d[5]), "+f"(d[6]), "+f"(d[7]),
        "+f"(d[8]), "+f"(d[9]), "+f"(d[10]), "+f"(d[11]), "+f"(d[12]), "+f"(d[13]), "+f"(d[14]), "+f"(d[15]),
        "+f"(d[16]), "+f"(d[17]), "+f"(d[18]), "+f"(d[19]), "+f"(d[20]), "+f"(d[21]), "+f"(d[22]), "+f"(d[23])
      : "r"(a[0]), "r"(a[1]), "r"(a[2]), "r"(a[3]), "l"(descB));
}
__device__ __forceinline__ void mma_rs48_k_z(float (&d)[24], const uint32_t (&a)[4], uint64_t descB) {
  asm volatile("wgmma.mma_async.sync.aligned.m64n48k16.f32.bf16.bf16 {"
      "%0, %1, %2, %3, %4, %5, %6, %7, %8, %9, %10, %11, %12, %13, %14, %15, "
      "%16, %17, %18, %19, %20, %21, %22, %23"
      "}, {%24, %25, %26, %27}, %28, 0, 1, 1, 0;\n"
      : "=f"(d[0]), "=f"(d[1]), "=f"(d[2]), "=f"(d[3]), "=f"(d[4]), "=f"(d[5]), "=f"(d[6]), "=f"(d[7]),
        "=f"(d[8]), "=f"(d[9]), "=f"(d[10]), "=f"(d[11]), "=f"(d[12]), "=f"(d[13]), "=f"(d[14]), "=f"(d[15]),
        "=f"(d[16]), "=f"(d[17]), "=f"(d[18]), "=f"(d[19]), "=f"(d[20]), "=f"(d[21]), "=f"(d[22]), "=f"(d[23])
      : "r"(a[0]), "r"(a[1]), "r"(a[2]), "r"(a[3]), "l"(descB));
}

__device__ __forceinline__ void mma_rs160_n(float (&d)[80], const uint32_t (&a)[4], uint64_t descB) {
  asm volatile("wgmma.mma_async.sync.aligned.m64n160k16.f32.bf16.bf16 {"
      "%0, %1, %2, %3, %4, %5, %6, %7, %8, %9, %10, %11, %12, %13, %14, %15, "
      "%16, %17, %18, %19, %20, %21, %22, %23, %24, %25, %26, %27, %28, %29, %30, %31, "
      "%32, %33, %34, %35, %36, %37, %38, %39, %40, %41, %42, %43, %44, %45, %46, %47, "
      "%48, %49, %50, %51, %52, %53, %54, %55, %56, %57, %58, %59, %60, %61, %62, %63, "
      "%64, %65, %66, %67, %68, %69, %70, %71, %72, %73, %74, %75, %76, %77, %78, %79"
      "}, {%80, %81, %82, %83}, %84, 1, 1, 1, 1;\n"
      : "+f"(d[0]), "+f"(d[1]), "+f"(d[2]), "+f"(d[3]), "+f"(d[4]), "+f"(d[5]), "+f"(d[6]), "+f"(d[7]),
        "+f"(d[8]), "+f"(d[9]), "+f"(d[10]), "+f"(d[11]), "+f"(d[12]), "+f"(d[13]), "+f"(d[14]), "+f"(d[15]),
        "+f"(d[16]), "+f"(d[17]), "+f"(d[18]), "+f"(d[19]), "+f"(d[20]), "+f"(d[21]), "+f"(d[22]), "+f"(d[23]),
        "+f"(d[24]), "+f"(d[25]), "+f"(d[26]), "+f"(d[27]), "+f"(d[28]), "+f"(d[29]), "+f"(d[30]), "+f"(d[31]),
        "+f"(d[32]), "+f"(d[33]), "+f"(d[34]), "+f"(d[35]), "+f"(d[36]), "+f"(d[37]), "+f"(d[38]), "+f"(d[39]),
        "+f"(d[40]), "+f"(d[41]), "+f"(d[42]), "+f"(d[43]), "+f"(d[44]), "+f"(d[45]), "+f"(d[46]), "+f"(d[47]),
        "+f"(d[48]), "+f"(d[49]), "+f"(d[50]), "+f"(d[51]), "+f"(d[52]), "+f"(d[53]), "+f"(d[54]), "+f"(d[55]),
        "+f"(d[56]), "+f"(d[57]), "+f"(d[58]), "+f"(d[59]), "+f"(d[60]), "+f"(d[61]), "+f"(d[62]), "+f"(d[63]),
        "+f"(d[64]), "+f"(d[65]), "+f"(d[66]), "+f"(d[67]), "+f"(d[68]), "+f"(d[69]), "+f"(d[70]), "+f"(d[71]),
        "+f"(d[72]), "+f"(d[73]), "+f"(d[74]), "+f"(d[75]), "+f"(d[76]), "+f"(d[77]), "+f"(d[78]), "+f"(d[79])
      : "r"(a[0]), "r"(a[1]), "r"(a[2]), "r"(a[3]), "l"(descB));
}
__device__ __forceinline__ void mma_rs160_n_z(float (&d)[80], const uint32_t (&a)[4], uint64_t descB) {
  asm volatile("wgmma.mma_async.sync.aligned.m64n160k16.f32.bf16.bf16 {"
      "%0, %1, %2, %3, %4, %5, %6, %7, %8, %9, %10, %11, %12, %13, %14, %15, "
      "%16, %17, %18, %19, %20, %21, %22, %23, %24, %25, %26, %27, %28, %29, %30, %31, "
      "%32, %33, %34, %35, %36, %37, %38, %39, %40, %41, %42, %43, %44, %45, %46, %47, "
      "%48, %49, %50, %51, %52, %53, %54, %55, %56, %57, %58, %59, %60, %61, %62, %63, "
      "%64, %65, %66, %67, %68, %69, %70, %71, %72, %73, %74, %75, %76, %77, %78, %79"
      "}, {%80, %81, %82, %83}, %84, 0, 1, 1, 1;\n"
      : "=f"(d[0]), "=f"(d[1]), "=f"(d[2]), "=f"(d[3]), "=f"(d[4]), "=f"(d[5]), "=f"(d[6]), "=f"(d[7]),
        "=f"(d[8]), "=f"(d[9]), "=f"(d[10]), "=f"(d[11]), "=f"(d[12]), "=f"(d[13]), "=f"(d[14]), "=f"(d[15]),
        "=f"(d[16]), "=f"(d[17]), "=f"(d[18]), "=f"(d[19]), "=f"(d[20]), "=f"(d[21]), "=f"(d[22]), "=f"(d[23]),
        "=f"(d[24]), "=f"(d[25]), "=f"(d[26]), "=f"(d[27]), "=f"(d[28]), "=f"(d[29]), "=f"(d[30]), "=f"(d[31]),
        "=f"(d[32]), "=f"(d[33]), "=f"(d[34]), "=f"(d[35]), "=f"(d[36]), "=f"(d[37]), "=f"(d[38]), "=f"(d[39]),
        "=f"(d[40]), "=f"(d[41]), "=f"(d[42]), "=f"(d[43]), "=f"(d[44]), "=f"(d[45]), "=f"(d[46]), "=f"(d[47]),
        "=f"(d[48]), "=f"(d[49]), "=f"(d[50]), "=f"(d[51]), "=f"(d[52]), "=f"(d[53]), "=f"(d[54]), "=f"(d[55]),
        "=f"(d[56]), "=f"(d[57]), "=f"(d[58]), "=f"(d[59]), "=f"(d[60]), "=f"(d[61]), "=f"(d[62]), "=f"(d[63]),
        "=f"(d[64]), "=f"(d[65]), "=f"(d[66]), "=f"(d[67]), "=f"(d[68]), "=f"(d[69]), "=f"(d[70]), "=f"(d[71]),
        "=f"(d[72]), "=f"(d[73]), "=f"(d[74]), "=f"(d[75]), "=f"(d[76]), "=f"(d[77]), "=f"(d[78]), "=f"(d[79])
      : "r"(a[0]), "r"(a[1]), "r"(a[2]), "r"(a[3]), "l"(descB));
}

__device__ __forceinline__ void feature_map(const uint32_t (&P)[2][10], uint32_t (&fr)[10][4]) {
  constexpr float L2E = 1.4426950408889634f;
#pragma unroll
  for (int p = 0; p < 2; p++) {
#pragma unroll
    for (int r = 0; r < 2; r++) {
      uint32_t mx = P[r][5 * p], mn = mx;
#pragma unroll
      for (int g = 1; g < 5; g++) { mx = max_bf2(mx, P[r][5 * p + g]); mn = min_bf2(mn, P[r][5 * p + g]); }
      mx = max_bf2(mx, __shfl_xor_sync(0xffffffffu, mx, 1));
      mn = min_bf2(mn, __shfl_xor_sync(0xffffffffu, mn, 1));
      mx = max_bf2(mx, __shfl_xor_sync(0xffffffffu, mx, 2));
      mn = min_bf2(mn, __shfl_xor_sync(0xffffffffu, mn, 2));
      float mx0 = -bf_lo(mx) * L2E, mx1 = -bf_hi(mx) * L2E, mn0 = bf_lo(mn) * L2E, mn1 = bf_hi(mn) * L2E;
      float ep0[5], ep1[5], en0[5], en1[5];
      float sp0 = 0.f, sp1 = 0.f, sn0 = 0.f, sn1 = 0.f;
#pragma unroll
      for (int g = 0; g < 5; g++) {
        float x0 = bf_lo(P[r][5 * p + g]), x1 = bf_hi(P[r][5 * p + g]);
        ep0[g] = ex2(fmaf(x0, L2E, mx0)); ep1[g] = ex2(fmaf(x1, L2E, mx1));
        en0[g] = ex2(fmaf(x0, -L2E, mn0)); en1[g] = ex2(fmaf(x1, -L2E, mn1));
        sp0 += ep0[g]; sp1 += ep1[g]; sn0 += en0[g]; sn1 += en1[g];
      }
      sp0 += __shfl_xor_sync(0xffffffffu, sp0, 1); sp1 += __shfl_xor_sync(0xffffffffu, sp1, 1);
      sn0 += __shfl_xor_sync(0xffffffffu, sn0, 1); sn1 += __shfl_xor_sync(0xffffffffu, sn1, 1);
      sp0 += __shfl_xor_sync(0xffffffffu, sp0, 2); sp1 += __shfl_xor_sync(0xffffffffu, sp1, 2);
      sn0 += __shfl_xor_sync(0xffffffffu, sn0, 2); sn1 += __shfl_xor_sync(0xffffffffu, sn1, 2);
      sp0 = rcp(sp0); sp1 = rcp(sp1); sn0 = rcp(sn0); sn1 = rcp(sn1);
#pragma unroll
      for (int g = 0; g < 5; g++) {
        fr[5 * p + g][r] = pack_bf16(ep0[g] * sp0, ep1[g] * sp1);
        fr[5 * p + g][2 + r] = pack_bf16(en0[g] * sn0, en1[g] * sn1);
      }
    }
  }
}

template <bool V> struct BoolC { static constexpr bool value = V; };
struct Ring {
  uint32_t idx, phase;
  template <int N> __device__ __forceinline__ void next() { if (++idx == N) { idx = 0; phase ^= 1; } }
};

}

__global__ void __cluster_dims__(2, 1, 1) __launch_bounds__(384, 1)
fused_kernel(const __grid_constant__ Maps maps, const __nv_bfloat16* __restrict__ x, const __nv_bfloat16* __restrict__ wqkv,
             const __nv_bfloat16* __restrict__ wphi, const __nv_bfloat16* __restrict__ w1, const __nv_bfloat16* __restrict__ w2,
             const __nv_bfloat16* __restrict__ w3, const __nv_bfloat16* __restrict__ w4, const __nv_bfloat16* __restrict__ wo,
             const __nv_bfloat16* __restrict__ gate_w, __nv_bfloat16* __restrict__ out) {
  extern __shared__ __align__(1024) uint8_t sgen[];
  const uint32_t sb = smem_u32(sgen);
  const uint32_t sb16 = (sb & 0x3FFFFu) >> 4;
  const uint32_t bars = sb + OFF_BAR;
  const uint32_t fullA = bars + 8 * B_FULLA, emptyA = bars + 8 * B_EMPTYA, fullB = bars + 8 * B_FULLB, emptyB = bars + 8 * B_EMPTYB;

  const int tid = threadIdx.x;
  const int rank = blockIdx.x & 1;
  const int pairIdx = blockIdx.x >> 1;
  const int i = pairIdx >> 2, j = 2 * (pairIdx & 3) + rank;

  TSTAMP(0);
  auto load_p1_b = [&](int k, uint32_t slot, uint32_t bar) {
    mbar_expect_tx(bar, 40960);
    tma4d(slot + 8192, &maps.qm, bar, 0, 64 * k, 0, j);
    tma3d(slot, &maps.w1m, bar, 0, 64 * k, j);
    tma4d(slot + 32768 + 2048, &maps.qr, bar, 64, 64 * k, 0, j);
    tma3d(slot + 32768, &maps.w1r, bar, 64, 64 * k, j);
  };
  if (tid >= 256) {
    asm volatile("setmaxnreg.dec.sync.aligned.u32 40;");
    if (tid == 256) {
#pragma unroll
      for (int s = 0; s < NA; s++) mbar_init(fullA + 8 * s, 1);
      asm volatile("fence.mbarrier_init.release.cluster;" ::: "memory");
#pragma unroll 1
      for (int u = 0; u < 4; u++) {
        if ((u & 1) == 0) mbar_expect_tx(fullA + 4 * u, SLOT_A);
        tma2d(sb + OFF_A + u * 8192, &maps.x, fullA + 8 * (u >> 1), 64 * (u >> 1), 128 * i + 64 * (u & 1));
      }
    } else if (tid == 288) {
#pragma unroll
      for (int s = 0; s < NB; s++) mbar_init(fullB + 8 * s, 1);
      asm volatile("fence.mbarrier_init.release.cluster;" ::: "memory");
#pragma unroll 1
      for (int k = 0; k < 2; k++) load_p1_b(k, sb + OFF_B + k * SLOT_B, fullB + 8 * k);
    } else if (tid == 320) {
#pragma unroll
      for (int b = B_CS; b < NBAR; b++) mbar_init(bars + 8 * b, b < B_EMPTYB ? 1 : b < B_EMPTYA ? 8 : 16);
#pragma unroll
      for (int b = B_DSR; b < B_EMPTYB; b++) mbar_expect_tx(bars + 8 * b, 10240);
      asm volatile("fence.mbarrier_init.release.cluster;" ::: "memory");
    }
    __syncwarp();
    asm volatile("barrier.cluster.arrive.relaxed.aligned;" ::: "memory");
    auto get_epoch = [&]() { return *reinterpret_cast<volatile unsigned*>(g_flags + FL_DONE * 32) / NCTA; };
    if (tid >= 320) {
      const int lane = tid & 31, ch = lane % 10, rg = lane / 10;
      const __nv_bfloat16* p = w1 + (size_t)(40 * i + (tid >= 352 ? 20 : 0) + rg) * D_ + 80 * j + 8 * ch;
      const unsigned par = get_epoch() & 1;
      float a[8];
#pragma unroll
      for (int e = 0; e < 8; e++) a[e] = 0.f;
#pragma unroll
      for (int it = 0; it < 7; it++) {
        uint4 v = make_uint4(0, 0, 0, 0);
        if (lane < 30 && 3 * it + rg < 20) v = __ldg(reinterpret_cast<const uint4*>(p + (size_t)it * 3 * D_));
        a[0] += bf_lo(v.x); a[1] += bf_hi(v.x); a[2] += bf_lo(v.y); a[3] += bf_hi(v.y);
        a[4] += bf_lo(v.z); a[5] += bf_hi(v.z); a[6] += bf_lo(v.w); a[7] += bf_hi(v.w);
      }
#pragma unroll
      for (int e = 0; e < 8; e++) a[e] += __shfl_down_sync(0xffffffffu, a[e], 10) + __shfl_down_sync(0xffffffffu, a[e], 20);
      if (lane < 10) {
        float* cd = g_acc[par] + 8 * KV_J + 80 * j + 8 * ch;
        red_add4(cd, a[0], a[1], a[2], a[3]); red_add4(cd + 4, a[4], a[5], a[6], a[7]);
      }
      __syncwarp();
      if (lane == 0) flag_add(FL_CS + j);
      __syncwarp();
    }
    asm volatile("barrier.cluster.wait.aligned;" ::: "memory");
    const int lane = tid & 31, pw = (tid >> 5) & 3;
    if (pw == 0) {
      if (tid == 256) {
        Ring r{2, 1};
        unsigned ep1 = 0;
#pragma unroll 1
        for (int k = 2; k < 25; k++) {
          if (k == 4) ep1 = get_epoch() + 1;
          if (k == 10 || k == 15) {
            if (k == 10) mbar_wait(bars + 8 * B_HST, 0);
            flag_wait(k == 10 ? FL_H + 2 * i + rank : FL_X1 + i, ep1 * 8u);
            TSTAMPX(k == 10 ? 29 : 30);
          }
          mbar_wait(emptyA + 8 * r.idx, r.phase);
          const uint32_t bar = fullA + 8 * r.idx, slot = sb + OFF_A + r.idx * SLOT_A;
          mbar_expect_tx(bar, SLOT_A);
          if (k >= 10 && k < 15) tma2d(slot, &maps.hs, bar, 64 * (k - 10) + 320 * rank, 128 * i);
          else tma2d_mc(slot + rank * 8192, k < 10 ? &maps.x : &maps.x1, bar, 64 * (k < 10 ? k : k - 15), 128 * i + 64 * rank);
          r.next<NA>();
        }
      }
    } else if (pw == 1) {
      if (tid == 288) {
        Ring r{2, 1};
#pragma unroll 1
        for (int k = 2; k < 18; k++) {
          mbar_wait(emptyB + 8 * r.idx, r.phase);
          const uint32_t bar = fullB + 8 * r.idx, slot = sb + OFF_B + r.idx * SLOT_B;
          if (k < 10) {
            load_p1_b(k, slot, bar);
          } else if (k < 13) {
            mbar_expect_tx(bar, k < 12 ? 40960 : 20480);
            tma3d(slot, &maps.w2, bar, 0, 320 * rank + 128 * (k - 10), 5 * (j >> 1));
            if (k < 12) tma3d(slot + 20480, &maps.w2, bar, 0, 320 * rank + 128 * (k - 10) + 64, 5 * (j >> 1));
          } else {
            mbar_expect_tx(bar, 49152);
            tma3d(slot, &maps.w3, bar, 0, 128 * (k - 13), 3 * j);
            tma3d(slot + 24576, &maps.w3, bar, 0, 128 * (k - 13) + 64, 3 * j);
          }
          r.next<NB>();
        }
        Ring r4{0, 1};
#pragma unroll 1
        for (int n = 0; n < 16; n++) {
          if (n == 0 || n == 1 || n == 3) { mbar_wait(emptyB + 8 * r.idx, r.phase); r.next<NB>(); }
          mbar_wait(bars + 8 * (B_EMPTY4 + r4.idx), r4.phase);
          const uint32_t bar = bars + 8 * (B_FULL4 + r4.idx), slot = sb + OFF_B + r4.idx * UNIT4;
          const int u = n & 3, m = ((j >> 1) + 1 + (n >> 2)) & 3;
          mbar_expect_tx(bar, u == 3 ? 25600 : 20480);
          tma3d(slot, u == 3 ? &maps.wo : &maps.w4, bar, 0, u == 3 ? 80 * j : 192 * j + 64 * u, 5 * m);
          r4.next<NU4>();
        }
      }
    } else {
      const unsigned epoch = get_epoch();
      float* accg = g_acc[epoch & 1];
      if (pw == 2) {
        {
          float* nxt = g_acc[(epoch + 1) & 1];
          constexpr int PER = ACC_FLOATS / NCTA;
#pragma unroll 1
          for (int e = lane; e < PER; e += 32) nxt[blockIdx.x * PER + e] = 0.f;
        }
        if (tid == 320) {
          flag_wait(FL_CS + j, (epoch + 1) * 32u);
          flag_wait(FL_ST + i, (epoch + 1) * 8u);
          fence_async_glb();
          *reinterpret_cast<volatile uint32_t*>(sgen + OFF_BAR + 8 * NBAR) = (epoch + 1) & 1;
          mbar_expect_tx(bars + 8 * B_CS, 320 + 2048);
          bulk_load(sb + OFF_CS, accg + 8 * KV_J + 80 * j, 320, bars + 8 * B_CS);
          bulk_load(sb + OFF_XST, g_xstat + 128 * i, 2048, bars + 8 * B_CS);
          TSTAMPX(21);
          l2_prefetch(w2 + (size_t)blockIdx.x * (D_ * D_ / NCTA), D_ * D_ * 2 / NCTA);
          flag_wait(FL_H + 2 * i + rank, (epoch + 1) * 8u);
          l2_prefetch(w3 + (size_t)blockIdx.x * (F_ * D_ / NCTA), F_ * D_ * 2 / NCTA);
          l2_prefetch(w4 + (size_t)blockIdx.x * (F_ * D_ / NCTA), F_ * D_ * 2 / NCTA);
          l2_prefetch(wo + (size_t)blockIdx.x * (D_ * D_ / NCTA), D_ * D_ * 2 / NCTA);
          flag_wait(FL_KV + j, (epoch + 1) * 16u);
          mbar_expect_tx(bars + 8 * B_KV, KV_J * 4);
          bulk_load(sb + OFF_MISC, accg + j * KV_J, KV_J * 4, bars + 8 * B_KV);
          TSTAMPX(22);
        }
        __syncwarp();
#pragma unroll 1
        for (int m = 0; m < 6; m++) {
          const int col = 192 * j + 32 * m + 8 * (lane & 3);
          const __nv_bfloat16* p = w3 + (size_t)(40 * i + (lane >> 2) * 5) * F_ + col;
          float a[8];
#pragma unroll
          for (int e = 0; e < 8; e++) a[e] = 0.f;
#pragma unroll
          for (int it = 0; it < 5; it++) {
            const uint4 v = __ldg(reinterpret_cast<const uint4*>(p + (size_t)it * F_));
            a[0] += bf_lo(v.x); a[1] += bf_hi(v.x); a[2] += bf_lo(v.y); a[3] += bf_hi(v.y);
            a[4] += bf_lo(v.z); a[5] += bf_hi(v.z); a[6] += bf_lo(v.w); a[7] += bf_hi(v.w);
          }
#pragma unroll
          for (int e = 0; e < 4; e++) {
            const float snd = (lane & 4) ? a[e] : a[e + 4], keep = (lane & 4) ? a[e + 4] : a[e];
            a[e] = keep + __shfl_xor_sync(0xffffffffu, snd, 4);
            a[e] += __shfl_xor_sync(0xffffffffu, a[e], 8);
            a[e] += __shfl_xor_sync(0xffffffffu, a[e], 16);
          }
          if (lane < 8) red_add4(accg + 8 * KV_J + D_ + col + (lane >> 2) * 4, a[0], a[1], a[2], a[3]);
        }
        __syncwarp();
        if (tid == 320) {
          flag_add(FL_CS3 + j);
          flag_wait(FL_S1 + i, (epoch + 1) * 8u);
          flag_wait(FL_CS3 + j, (epoch + 1) * 16u);
          fence_async_glb();
          mbar_expect_tx(bars + 8 * B_ST1, 8192 + 768);
          bulk_load(sb + OFF_CS + 320, accg + 8 * KV_J + D_ + 192 * j, 768, bars + 8 * B_ST1);
          bulk_load(sb + OFF_MISC, g_st1 + 128 * i * 8, 8192, bars + 8 * B_ST1);
        }
      }
      if (tid == 352) {
        mbar_wait(bars + 8 * B_SIGP, 0);
        flag_add(FL_ST + i);
        TSTAMPX(20);
        mbar_expect_tx(bars + 8 * B_XR, 20480);
#pragma unroll 1
        for (int u = 0; u < 8; u++)
          tma2d(sb + OFF_B + (u / 3) * SLOT_B + SPARE + (u % 3) * 2560, &maps.xr, bars + 8 * B_XR, 80 * j, 128 * i + 16 * u);
        const int shift = (j < 2) ? 1 : (j < 4) ? -1 : (j < 6) ? 2 : -2;
        if ((shift > 0 && i == 0) || (shift < 0 && i == 15)) {
          const int nz = shift > 0 ? shift : -shift, zr = shift > 0 ? 0 : S_ - nz;
#pragma unroll 1
          for (int e = 0; e < nz * 10; e++)
            reinterpret_cast<uint4*>(g_Hs + (size_t)(2 + zr + e / 10) * D_ + 80 * j)[e % 10] = make_uint4(0, 0, 0, 0);
          fence_async_glb();
        }
        prefetch_tmap(&maps.st_h); prefetch_tmap(&maps.st_x1); prefetch_tmap(&maps.hs); prefetch_tmap(&maps.x1);
        prefetch_tmap(&maps.w2); prefetch_tmap(&maps.w3); prefetch_tmap(&maps.w4); prefetch_tmap(&maps.wo);
        mbar_wait(bars + 8 * B_SIGH, 0);
        TSTAMPX(23);
        tma2d_store(&maps.st_h, sb + OFF_STG, 80 * j, 128 * i + 2 + shift);
        bulk_commit(); bulk_wait<0>();
        mbar_arrive(bars + 8 * B_HST);
        flag_add(FL_H + 2 * i + (j >> 2));
        flag_add_relaxed(FL_H + 2 * ((i + (shift > 0 ? 1 : -1)) & 15) + (j >> 2));
        TSTAMPX(24);
        mbar_wait(bars + 8 * B_SIGKV, 0);
        TSTAMPX(25);
        fence_async_smem();
        asm volatile("cp.reduce.async.bulk.global.shared::cta.bulk_group.add.f32 [%0], [%1], %2;"
                     ::"l"(accg + j * KV_J), "r"(sb + OFF_MISC), "r"(KV_J * 4) : "memory");
        bulk_commit(); bulk_wait<0>();
        flag_add(FL_KV + j);
        TSTAMPX(26);
        mbar_wait(bars + 8 * B_SIGX1, 0);
        TSTAMPX(27);
        tma2d_store(&maps.st_x1, sb + OFF_STG, 80 * j, 128 * i);
        bulk_commit(); bulk_wait<0>();
        flag_add(FL_X1 + i);
        TSTAMPX(28);
        mbar_wait(bars + 8 * B_MFREE, 0);
        flag_add(FL_S1 + i);
      }
    }
  } else {
    uint4 pv[5], pw_[5], pre;
    {
      const int row = 128 * i + 16 * j + (tid >> 4), l16 = tid & 15;
#pragma unroll
      for (int c = 0; c < 5; c++) pv[c] = __ldg(reinterpret_cast<const uint4*>(x + (size_t)row * D_ + c * 128 + l16 * 8));
      pre = __ldg(reinterpret_cast<const uint4*>(wphi + (size_t)j * 1600) + (tid < 200 ? tid : 0));
#pragma unroll
      for (int c = 0; c < 5; c++) pw_[c] = __ldg(reinterpret_cast<const uint4*>(gate_w + c * 128 + l16 * 8));
    }
    asm volatile("barrier.cluster.arrive.relaxed.aligned;" ::: "memory");
    asm volatile("setmaxnreg.inc.sync.aligned.u32 232;");
    const int wg = tid >> 7, warp = tid >> 5, lane = tid & 31, t = lane & 3;
    const int rloc = warp * 16 + (lane >> 2);
    const float* s_cs = reinterpret_cast<const float*>(sgen + OFF_CS);
    auto signal = [&](int b) {
      __syncwarp();
      if (lane == 0) mbar_arrive(bars + 8 * b);
    };
    auto releaseB = [&](uint32_t bar) {
      __syncwarp();
      if (lane == 0) mbar_arrive(bar);
    };
    auto release = [&](uint32_t bar) {
      __syncwarp();
      if (lane < 2) mbar_arrive_cta(bar, lane);
    };
    const uint32_t stg_lane = (warp * 16 + ((lane >> 3) & 1) * 8 + (lane & 7)) * 160 + (lane >> 4) * 16;

    auto stage_tile = [&](uint32_t stg, const uint32_t (&v)[2][10]) {
#pragma unroll
      for (int s = 0; s < 5; s++) stsm4(stg + stg_lane + s * 32, v[0][2 * s], v[1][2 * s], v[0][2 * s + 1], v[1][2 * s + 1]);
    };

    {
#pragma unroll 1
      for (int e = tid; e < 800; e += 256) sts128(sb + OFF_MISC + e * 16, make_uint4(0, 0, 0, 0));
      bar_sync(1, 256);
      float f[40];
      float s = 0.f, gs = 0.f;
#pragma unroll
      for (int c = 0; c < 5; c++) {
        const uint32_t vv[4] = {pv[c].x, pv[c].y, pv[c].z, pv[c].w}, ww[4] = {pw_[c].x, pw_[c].y, pw_[c].z, pw_[c].w};
#pragma unroll
        for (int e = 0; e < 4; e++) {
          f[8 * c + 2 * e] = bf_lo(vv[e]); f[8 * c + 2 * e + 1] = bf_hi(vv[e]);
          s += f[8 * c + 2 * e] + f[8 * c + 2 * e + 1];
          gs = fmaf(f[8 * c + 2 * e], bf_lo(ww[e]), gs); gs = fmaf(f[8 * c + 2 * e + 1], bf_hi(ww[e]), gs);
        }
      }
#pragma unroll
      for (int o = 1; o < 16; o <<= 1) { s += __shfl_xor_sync(0xffffffffu, s, o); gs += __shfl_xor_sync(0xffffffffu, gs, o); }
      const float mean = s * (1.f / D_);
      float q = 0.f;
#pragma unroll
      for (int e = 0; e < 40; e++) { const float d = f[e] - mean; q = fmaf(d, d, q); }
#pragma unroll
      for (int o = 1; o < 16; o <<= 1) q += __shfl_xor_sync(0xffffffffu, q, o);
      const float rstd = rsqrtf(q * (1.f / D_) + 1e-5f);
      asm volatile("barrier.cluster.wait.aligned;" ::: "memory");
      if ((tid & 15) == 0) g_xstat[128 * i + 16 * j + (tid >> 4)] = make_float4(rstd, -mean, rcp(1.f + __expf(-gs)), 0.f);
      signal(B_SIGP);
      if (tid < 200) {
        const uint32_t ww[4] = {pre.x, pre.y, pre.z, pre.w};
        const int h = tid / 50;
#pragma unroll
        for (int e = 0; e < 8; e++) {
          const int idx = tid * 8 + e, k = idx / 20, ff = idx - 20 * k;
          const int n = 40 * (h >> 1) + 8 * (ff >> 2) + 2 * (ff & 3) + (h & 1);
          const int off = (k >> 4) * 2560 + n * 32 + ((((k >> 3) ^ (n >> 2)) & 1) << 4) + (k & 7) * 2;
          *reinterpret_cast<unsigned short*>(sgen + OFF_MISC + off) = (unsigned short)(ww[e >> 1] >> ((e & 1) * 16));
        }
      }
    }
    TSTAMP(1);

    Ring ra{0, 0}, rb{0, 0};
    uint32_t qp[2][10], P[2][10];
    float st_g[2];
    {
      float accM[128], accR[32];
      uint32_t pa = 0, pb = 0;
#pragma unroll 1
      for (int k = 0; k < 10; k++) {
        mbar_wait(fullA + 8 * ra.idx, ra.phase);
        if (tid == 0) TRACE(32 + k);
        mbar_wait(fullB + 8 * rb.idx, rb.phase);
        if (tid == 0) TRACE(64 + k);
        if (k == 0) TSTAMP(2);
        const uint32_t a0 = sb16 + ((OFF_A + ra.idx * SLOT_A + wg * 8192) >> 4), b0 = sb16 + ((OFF_B + rb.idx * SLOT_B) >> 4);
        wg_fence();
#pragma unroll
        for (int kk = 0; kk < 4; kk++) {
          const uint64_t da = make_desc(a0, kk * 32, 16, 1024, 1);
          if (kk == 0) {
            mma_ss256_p(accM, da, make_desc(b0, 0, 8192, 1024, 1), k);
            mma_ss64_p(accR, da, make_desc(b0, 32768, 2048, 256, 3), k);
          } else {
            mma_ss256(accM, da, make_desc(b0, kk * 2048, 8192, 1024, 1));
            mma_ss64(accR, da, make_desc(b0, 32768 + kk * 512, 2048, 256, 3));
          }
          if (kk == 0) {
            wg_commit();
            if (k > 0) {
              wg_wait<1>();
              if (k - 1 < 8) release(emptyA + 8 * pa);
              releaseB(emptyB + 8 * pb);
            }
          }
        }
        wg_commit();
        pa = ra.idx; pb = rb.idx;
        ra.next<NA>(); rb.next<NB>();
      }
      TSTAMP(18);
      float st_rstd[2], st_mr[2];
      mbar_wait(bars + 8 * B_CS, 0);
#pragma unroll
      for (int r = 0; r < 2; r++) {
        const uint4 st = lds128(sb + OFF_XST + (rloc + 8 * r) * 16);
        st_rstd[r] = __uint_as_float(st.x); st_mr[r] = __uint_as_float(st.y); st_g[r] = __uint_as_float(st.z);
      }
      TSTAMP(19);
      wg_wait<0>();
      fence_regs(accM); fence_regs(accR);
      TSTAMP(3);
#define ACC(P_, G, I_) ((G) < 8 ? accM[(P_) * 32 + ((G) & 7) * 4 + (I_)] : accR[(P_) * 8 + ((G) & 1) * 4 + (I_)])
      {
        uint32_t hv[2][10];
        const GeluC g0 = gelu_consts(st_rstd[0], 1.f), g1 = gelu_consts(st_rstd[1], 1.f);
#pragma unroll
        for (int g = 0; g < 10; g++) {
          const float2 cs = *reinterpret_cast<const float2*>(s_cs + 8 * g + 2 * t);
          const float v0 = gelu_s(fmaf(st_mr[0], cs.x, ACC(0, g, 0)), g0), v1 = gelu_s(fmaf(st_mr[0], cs.y, ACC(0, g, 1)), g0);
          const float v2 = gelu_s(fmaf(st_mr[1], cs.x, ACC(0, g, 2)), g1), v3 = gelu_s(fmaf(st_mr[1], cs.y, ACC(0, g, 3)), g1);
          hv[0][g] = pack_bf16(v0, v1); hv[1][g] = pack_bf16(v2, v3);
        }
        fence_async_smem();
        bar_sync(1, 256);
        stage_tile(sb + OFF_STG, hv);
        fence_async_smem();
        signal(B_SIGH);
      }
      TSTAMP(4);
      uint32_t kf[5][4], qf[5][4];
#pragma unroll
      for (int s = 0; s < 5; s++) {
        kf[s][0] = pack_bf16(ACC(2, 2 * s, 0), ACC(2, 2 * s, 1)); kf[s][1] = pack_bf16(ACC(2, 2 * s, 2), ACC(2, 2 * s, 3));
        kf[s][2] = pack_bf16(ACC(2, 2 * s + 1, 0), ACC(2, 2 * s + 1, 1)); kf[s][3] = pack_bf16(ACC(2, 2 * s + 1, 2), ACC(2, 2 * s + 1, 3));
        qf[s][0] = pack_bf16(ACC(1, 2 * s, 0), ACC(1, 2 * s, 1)); qf[s][1] = pack_bf16(ACC(1, 2 * s, 2), ACC(1, 2 * s, 3));
        qf[s][2] = pack_bf16(ACC(1, 2 * s + 1, 0), ACC(1, 2 * s + 1, 1)); qf[s][3] = pack_bf16(ACC(1, 2 * s + 1, 2), ACC(1, 2 * s + 1, 3));
      }
      float pk[40], pq[40];
      wg_fence();
#pragma unroll
      for (int s = 0; s < 5; s++) {
        if (s == 0) mma_rs80_k_z(pk, kf[s], make_desc(sb16, OFF_MISC, 16, 256, 3));
        else mma_rs80_k(pk, kf[s], make_desc(sb16, OFF_MISC + s * 2560, 16, 256, 3));
      }
      wg_commit();
#pragma unroll
      for (int s = 0; s < 5; s++) {
        if (s == 0) mma_rs80_k_z(pq, qf[s], make_desc(sb16, OFF_MISC, 16, 256, 3));
        else mma_rs80_k(pq, qf[s], make_desc(sb16, OFF_MISC + s * 2560, 16, 256, 3));
      }
      wg_commit();
      {
        const int mat = lane >> 3;
        const int tok = warp * 16 + (mat & 1) * 8 + (lane & 7);
        const uint32_t ones = (t == 0) ? 0x00003f80u : 0u;
        __syncwarp();
#pragma unroll
        for (int p = 0; p < 2; p++) {
          const uint32_t rowa = sb + OFF_A + p * SLOT_A + tok * 128;
#pragma unroll
          for (int gg = 0; gg < 3; gg++) {
            const int g0 = 5 * p + 2 * gg;
            uint32_t r0 = pack_bf16(ACC(3, g0, 0), ACC(3, g0, 1)), r1 = pack_bf16(ACC(3, g0, 2), ACC(3, g0, 3));
            uint32_t r2 = ones, r3 = ones;
            if (gg < 2) { r2 = pack_bf16(ACC(3, g0 + 1, 0), ACC(3, g0 + 1, 1)); r3 = pack_bf16(ACC(3, g0 + 1, 2), ACC(3, g0 + 1, 3)); }
            stsm4(rowa + (((2 * gg + (mat >> 1)) ^ (tok & 7)) << 4), r0, r1, r2, r3);
          }
        }
      }
#undef ACC
      wg_wait<1>();
      fence_regs(pk);
#pragma unroll
      for (int G = 0; G < 10; G++) {
        P[0][G] = pack_bf16(pk[4 * G], pk[4 * G + 1]); P[1][G] = pack_bf16(pk[4 * G + 2], pk[4 * G + 3]);
      }
      wg_wait<0>();
      fence_regs(pq);
#pragma unroll
      for (int G = 0; G < 10; G++) {
        qp[0][G] = pack_bf16(pq[4 * G], pq[4 * G + 1]); qp[1][G] = pack_bf16(pq[4 * G + 2], pq[4 * G + 3]);
      }
    }

    uint32_t fr[10][4];
    uint32_t xv[2][10];
#pragma unroll
    for (int g = 0; g < 10; g++) xv[0][g] = xv[1][g] = 0u;
    int pass;
    pass = gridDim.y;
#pragma unroll 1
    do {
    feature_map(P, fr);
    if (pass != 0) {
    {
      const int mat = lane >> 3;
      const int tok = warp * 16 + (mat & 1) * 8 + (lane & 7);
      const uint32_t base = sb + OFF_B + tok * 32 + (((mat >> 1) ^ ((tok >> 2) & 1)) << 4);
#pragma unroll
      for (int G = 0; G < 10; G++) stsm4(base + G * 4096, fr[G][0], fr[G][1], fr[G][2], fr[G][3]);
      fence_async_smem();
      bar_sync(1, 256);
      float kv[40];
      const uint32_t a0 = sb16 + ((OFF_A + wg * SLOT_A) >> 4), b0 = sb16 + ((OFF_B + wg * 20480) >> 4);
      wg_fence();
#pragma unroll
      for (int ks = 0; ks < 8; ks++) {
        if (ks == 0) mma_ss80_tt_z(kv, make_desc(a0, 0, 16, 1024, 1), make_desc(b0, 0, 4096, 256, 3));
        else mma_ss80_tt(kv, make_desc(a0, ks * 2048, 16, 1024, 1), make_desc(b0, ks * 512, 4096, 256, 3));
      }
      wg_commit();
      wg_wait<0>();
      fence_regs(kv);
      TSTAMP(31);
      release(emptyA); release(emptyA + 8); releaseB(emptyB); release(bars + 8 * B_PEER2);
      const uint32_t dst = sb + OFF_MISC + wg * (KV_PAIR * 4);
      const int m0 = (warp & 3) * 16 + (lane >> 2);
#pragma unroll
      for (int r = 0; r < 2; r++) {
        const int m = m0 + 8 * r;
        const bool hi = m >= 20;
        uint32_t v[10];
#pragma unroll
        for (int G = 0; G < 10; G++) v[G] = __float_as_uint(hi ? kv[4 * G + 2 * r + 1] : kv[4 * G + 2 * r]);
        const uint32_t p = dst + 4 * (m < 40 ? m * 48 + t * 12 : 1920 + t * 24 + 12);
        if (m <= 40) {
          sts128(p, make_uint4(v[0], v[1], v[2], v[3])); sts128(p + 16, make_uint4(v[4], v[5], v[6], v[7]));
          sts128(p + 32, make_uint4(v[8], v[9], 0u, 0u));
        }
      }
      if (m0 == 32) {
        const uint32_t p = dst + 4 * (1920 + t * 24);
        sts128(p, make_uint4(__float_as_uint(kv[2]), __float_as_uint(kv[6]), __float_as_uint(kv[10]), __float_as_uint(kv[14])));
        sts128(p + 16, make_uint4(__float_as_uint(kv[18]), __float_as_uint(kv[22]), __float_as_uint(kv[26]), __float_as_uint(kv[30])));
        sts128(p + 32, make_uint4(__float_as_uint(kv[34]), __float_as_uint(kv[38]), 0u, 0u));
      }
      signal(B_SIGKV);
    }
    TSTAMP(5);

    {
      {
        mbar_wait(bars + 8 * B_XR, 0);
        const uint32_t xa = sb + OFF_B + (warp / 3) * SLOT_B + SPARE + (warp % 3) * 2560 + (lane >> 2) * 160 + t * 4;
#pragma unroll
        for (int g = 0; g < 10; g++) { xv[0][g] = lds32(xa + g * 16); xv[1][g] = lds32(xa + 1280 + g * 16); }
      }
      float acc[80];
      zero_regs(acc);
      uint32_t pa = 0, pb = 0;
#pragma unroll 1
      for (int k = 0; k < 5; k++) {
        mbar_wait(fullA + 8 * ra.idx, ra.phase);
        if ((k & 1) == 0) mbar_wait(fullB + 8 * rb.idx, rb.phase);
        if (k == 0) TSTAMP(6);
        const uint32_t a0 = sb16 + ((OFF_A + ra.idx * SLOT_A + wg * 8192) >> 4);
        const uint32_t b0 = sb16 + ((OFF_B + rb.idx * SLOT_B + (k & 1) * 20480) >> 4);
        wg_fence();
#pragma unroll
        for (int kk = 0; kk < 4; kk++) {
          mma_ss160(acc, make_desc(a0, kk * 32, 16, 1024, 1), make_desc(b0, kk * 1024, 4096, 512, 2));
          if (kk == 0) {
            wg_commit();
            if (k > 0) {
              wg_wait<1>();
              release(emptyA + 8 * pa);
              if ((k & 1) == 0) releaseB(emptyB + 8 * pb);
            }
          }
        }
        wg_commit();
        pa = ra.idx; pb = rb.idx;
        ra.next<NA>();
        if ((k & 1) || k == 4) rb.next<NB>();
      }
      mbar_wait(bars + 8 * B_PEER2, 0);
      wg_wait<0>();
      fence_regs(acc);
      release(emptyA + 8 * pa);
      TSTAMP(7);
      {
        uint32_t sn[20];
        if (rank) {
#pragma unroll
          for (int e = 0; e < 20; e++) sn[e] = pack_bf16(acc[2 * e], acc[2 * e + 1]);
#pragma unroll
          for (int e = 0; e < 40; e++) acc[e] = acc[40 + e];
        } else {
#pragma unroll
          for (int e = 0; e < 20; e++) sn[e] = pack_bf16(acc[40 + 2 * e], acc[41 + 2 * e]);
        }
        const uint32_t peer = map_peer(sb, rank ^ 1);
#pragma unroll
        for (int q = 0; q < 5; q++)
          st_async16(peer + OFF_B + 20480 + tid * 16 + q * 4096, sn[4 * q], sn[4 * q + 1], sn[4 * q + 2], sn[4 * q + 3],
                     peer + OFF_BAR + 8 * (B_DSR + 8 + wg));
#pragma unroll
        for (int g = 0; g < 10; g++) {
          acc[4 * g] += bf_lo(xv[0][g]); acc[4 * g + 1] += bf_hi(xv[0][g]);
          acc[4 * g + 2] += bf_lo(xv[1][g]); acc[4 * g + 3] += bf_hi(xv[1][g]);
        }
        bar_sync(1, 256);
        mbar_wait(bars + 8 * (B_DSR + 8 + wg), 0);
#pragma unroll
        for (int q = 0; q < 5; q++) {
          const uint4 v = lds128(sb + OFF_B + 20480 + tid * 16 + q * 4096);
          xv[0][2 * q] = pack_bf16(acc[8 * q] + bf_lo(v.x), acc[8 * q + 1] + bf_hi(v.x));
          xv[1][2 * q] = pack_bf16(acc[8 * q + 2] + bf_lo(v.y), acc[8 * q + 3] + bf_hi(v.y));
          xv[0][2 * q + 1] = pack_bf16(acc[8 * q + 4] + bf_lo(v.z), acc[8 * q + 5] + bf_hi(v.z));
          xv[1][2 * q + 1] = pack_bf16(acc[8 * q + 6] + bf_lo(v.w), acc[8 * q + 7] + bf_hi(v.w));
        }
        releaseB(emptyB + 8 * pb);
      }
      TSTAMP(16);
      stage_tile(sb + OFF_STG, xv);
      fence_async_smem();
      signal(B_SIGX1);
      TSTAMP(17);
#pragma unroll
      for (int r = 0; r < 2; r++) {
        float s = 0.f;
#pragma unroll
        for (int g = 0; g < 10; g++) {
          acc[4 * g + 2 * r] = bf_lo(xv[r][g]); acc[4 * g + 2 * r + 1] = bf_hi(xv[r][g]);
          s += acc[4 * g + 2 * r] + acc[4 * g + 2 * r + 1];
        }
        s += __shfl_xor_sync(0xffffffffu, s, 1); s += __shfl_xor_sync(0xffffffffu, s, 2);
        const float mu = s * (1.f / 80.f);
        float q = 0.f;
#pragma unroll
        for (int g = 0; g < 10; g++) {
          const float d0 = acc[4 * g + 2 * r] - mu, d1 = acc[4 * g + 2 * r + 1] - mu;
          q = fmaf(d0, d0, q); q = fmaf(d1, d1, q);
        }
        q += __shfl_xor_sync(0xffffffffu, q, 1); q += __shfl_xor_sync(0xffffffffu, q, 2);
        if (t == 0) g_st1[(128 * i + rloc + 8 * r) * 8 + j] = make_float2(mu, q);
      }
    }
    TSTAMP(8);
#pragma unroll
    for (int G = 0; G < 10; G++) { P[0][G] = qp[0][G]; P[1][G] = qp[1][G]; }
    }
    asm volatile("" : "+r"(pass));
    } while (pass-- != 0);

    uint32_t of[5][4];
    {
      mbar_wait(bars + 8 * B_KV, 0);
      uint4 kvr[2][3];
#pragma unroll
      for (int u = 0; u < 2; u++) {
        const int it = tid + 256 * u, p = it / 192, rem = it - 192 * p, n = rem >> 2, tq = rem & 3;
        const uint32_t sp = sb + OFF_MISC + 4 * (p * KV_PAIR + (n < 40 ? n * 48 + tq * 12 : 1920 + tq * 24 + (n & 1) * 12));
        if (it < 384) { kvr[u][0] = lds128(sp); kvr[u][1] = lds128(sp + 16); kvr[u][2] = lds128(sp + 32); }
      }
      bar_sync(1, 256);
#pragma unroll
      for (int u = 0; u < 2; u++) {
        const int it = tid + 256 * u, p = it / 192, rem = it - 192 * p, n = rem >> 2, tq = rem & 3;
        const int sh = (n < 40 ? (n >= 20) : (n & 1)) * 16;
        const uint32_t v[10] = {kvr[u][0].x, kvr[u][0].y, kvr[u][0].z, kvr[u][0].w, kvr[u][1].x, kvr[u][1].y, kvr[u][1].z, kvr[u][1].w, kvr[u][2].x, kvr[u][2].y};
        uint8_t* dst = sgen + OFF_MISC + p * 7680 + n * 32 + tq * 4;
        const int sw = ((n >> 2) & 1) << 4;
        if (it < 384) {
#pragma unroll
          for (int G = 0; G < 10; G++)
            *reinterpret_cast<uint32_t*>(dst + (G >> 1) * 1536 + (((G & 1) << 4) ^ sw)) = pack_bf16(__uint_as_float(v[G]), 0.f) << sh;
        }
      }
      fence_async_smem();
      bar_sync(1, 256);
      float o0[24], o1[24];
      wg_fence();
#pragma unroll
      for (int g = 0; g < 5; g++) {
        if (g == 0) mma_rs48_k_z(o0, fr[g], make_desc(sb16, OFF_MISC, 16, 256, 3));
        else mma_rs48_k(o0, fr[g], make_desc(sb16, OFF_MISC + g * 1536, 16, 256, 3));
      }
#pragma unroll
      for (int g = 0; g < 5; g++) {
        if (g == 0) mma_rs48_k_z(o1, fr[5], make_desc(sb16, OFF_MISC + 7680, 16, 256, 3));
        else mma_rs48_k(o1, fr[5 + g], make_desc(sb16, OFF_MISC + 7680 + g * 1536, 16, 256, 3));
      }
      wg_commit();
      wg_wait<0>();
      fence_regs(o0); fence_regs(o1);
      signal(B_MFREE);
#pragma unroll
      for (int r = 0; r < 2; r++) {
        const float a0 = __fdividef(st_g[r], o0[20 + 2 * r] + 1e-6f), a1 = __fdividef(st_g[r], o0[21 + 2 * r] + 1e-6f);
        const float b0 = __fdividef(st_g[r], o1[20 + 2 * r] + 1e-6f), b1 = __fdividef(st_g[r], o1[21 + 2 * r] + 1e-6f);
        const float am = t < 2 ? a0 : a1, bm = t < 2 ? b0 : b1;
#pragma unroll
        for (int g = 0; g < 5; g++) {
          const float sa = g < 2 ? a0 : (g == 2 ? am : a1), sb2 = g < 2 ? b0 : (g == 2 ? bm : b1);
          of[g >> 1][(g & 1) * 2 + r] = pack_bf16(o0[4 * g + 2 * r] * sa, o0[4 * g + 2 * r + 1] * sa);
          of[(5 + g) >> 1][((5 + g) & 1) * 2 + r] = pack_bf16(o1[4 * g + 2 * r] * sb2, o1[4 * g + 2 * r + 1] * sb2);
        }
      }
    }
    TSTAMP(9);

    uint32_t hf[12][4];
    {
      float acc[96];
      uint32_t pa = 0, pb = 0;
#pragma unroll 1
      for (int k = 0; k < 10; k++) {
        mbar_wait(fullA + 8 * ra.idx, ra.phase);
        if (tid == 0) TRACE(52 + k);
        if ((k & 1) == 0) mbar_wait(fullB + 8 * rb.idx, rb.phase);
        if (tid == 0) TRACE(84 + k);
        if (k == 0) TSTAMP(10);
        const uint32_t a0 = sb16 + ((OFF_A + ra.idx * SLOT_A + wg * 8192) >> 4);
        const uint32_t b0 = sb16 + ((OFF_B + rb.idx * SLOT_B + (k & 1) * 24576) >> 4);
        wg_fence();
#pragma unroll
        for (int kk = 0; kk < 4; kk++) {
          if (kk == 0) mma_ss192_p(acc, make_desc(a0, 0, 16, 1024, 1), make_desc(b0, 0, 8192, 1024, 1), k);
          else mma_ss192(acc, make_desc(a0, kk * 32, 16, 1024, 1), make_desc(b0, kk * 2048, 8192, 1024, 1));
          if (kk == 0) {
            wg_commit();
            if (k > 0) {
              wg_wait<1>();
              release(emptyA + 8 * pa);
              if ((k & 1) == 0) releaseB(emptyB + 8 * pb);
            }
          }
        }
        wg_commit();
        pa = ra.idx; pb = rb.idx;
        ra.next<NA>();
        if (k & 1) rb.next<NB>();
      }
      float rs[2], mm[2];
      mbar_wait(bars + 8 * B_ST1, 0);
#pragma unroll
      for (int r = 0; r < 2; r++) {
        const uint4 su = lds128(sb + OFF_MISC + (rloc + 8 * r) * 64 + t * 16);
        const float m0 = __uint_as_float(su.x), m1 = __uint_as_float(su.z);
        float mu = m0 + m1;
        mu += __shfl_xor_sync(0xffffffffu, mu, 1); mu += __shfl_xor_sync(0xffffffffu, mu, 2);
        mu *= 0.125f;
        const float d0 = m0 - mu, d1 = m1 - mu;
        float q = __uint_as_float(su.y) + __uint_as_float(su.w) + 80.f * (d0 * d0 + d1 * d1);
        q += __shfl_xor_sync(0xffffffffu, q, 1); q += __shfl_xor_sync(0xffffffffu, q, 2);
        rs[r] = rsqrtf(q * (1.f / D_) + 1e-5f);
        mm[r] = -mu;
      }
      wg_wait<0>();
      fence_regs(acc);
      releaseB(emptyB + 8 * pb);
      release(bars + 8 * B_PEER);
      TSTAMP(11);
      const GeluC g0 = gelu_consts(rs[0], 1.f - st_g[0]), g1 = gelu_consts(rs[1], 1.f - st_g[1]);
#pragma unroll
      for (int g = 0; g < 24; g++) {
        const float2 cs = *reinterpret_cast<const float2*>(s_cs + 80 + 8 * g + 2 * t);
        const float v0 = gelu_s(fmaf(mm[0], cs.x, acc[4 * g]), g0), v1 = gelu_s(fmaf(mm[0], cs.y, acc[4 * g + 1]), g0);
        const float v2 = gelu_s(fmaf(mm[1], cs.x, acc[4 * g + 2]), g1), v3 = gelu_s(fmaf(mm[1], cs.y, acc[4 * g + 3]), g1);
        hf[g >> 1][(g & 1) * 2] = pack_bf16(v0, v1);
        hf[g >> 1][(g & 1) * 2 + 1] = pack_bf16(v2, v3);
      }
    }
    TSTAMP(12);

    {
      float acc[80], kp[40];
      uint32_t sn[20], kb[20];
      const uint32_t peer = map_peer(sb, rank ^ 1);
      const uint32_t tag = lds32(sb + OFF_BAR + 8 * NBAR);
      const uint4* gp = g_part + (size_t)(i * 8 + j) * 3840 + tid;
      uint4 pv4[15];
      Ring r4{0, 0};
      auto add8 = [&](int q, const uint4 v) {
        float* d = &kp[8 * q];
        d[0] += bf_lo(v.x); d[1] += bf_hi(v.x); d[2] += bf_lo(v.y); d[3] += bf_hi(v.y);
        d[4] += bf_lo(v.z); d[5] += bf_hi(v.z); d[6] += bf_lo(v.w); d[7] += bf_hi(v.w);
      };
      auto send = [&](int c) {
        const uint32_t dso = peer + OFF_DS + (c & 1) * 20480 + tid * 16, dsb = peer + OFF_BAR + 8 * (B_DSR + 2 * c + wg);
#pragma unroll
        for (int q = 0; q < 5; q++) st_async16(dso + q * 4096, sn[4 * q], sn[4 * q + 1], sn[4 * q + 2], sn[4 * q + 3], dsb);
      };
      auto finish = [&](int c) {
        mbar_wait(bars + 8 * (B_DSR + 2 * c + wg), 0);
        uint4* dst = g_part + (size_t)((i * 8 + ((j + 2 * c + 2) & 7)) * 3 + c) * 1280 + tid;
#pragma unroll
        for (int q = 0; q < 5; q++) {
          const uint4 v = lds128(sb + OFF_DS + (c & 1) * 20480 + tid * 16 + q * 4096);
          st_relaxed16(dst + q * 256, (add_bf2(v.x, kb[4 * q]) & ~1u) | tag, add_bf2(v.y, kb[4 * q + 1]),
                       add_bf2(v.z, kb[4 * q + 2]), add_bf2(v.w, kb[4 * q + 3]));
        }
      };
#pragma unroll
      for (int e = 0; e < 20; e++) sn[e] = kb[e] = 0u;
      auto chunk = [&](const int c, auto last_c) {
        constexpr bool LAST = decltype(last_c)::value;
        const uint32_t e0 = r4.idx;
        auto rel = [&](int u) { const uint32_t e = e0 + u; releaseB(bars + 8 * (B_EMPTY4 + (e >= NU4 ? e - NU4 : e))); };
#pragma unroll
        for (int u = 0; u < 4; u++) {
          mbar_wait(bars + 8 * (B_FULL4 + r4.idx), r4.phase);
          const uint32_t b0 = sb16 + ((OFF_B + r4.idx * UNIT4) >> 4);
          TRS(c * 16 + u * 3);
          wg_fence();
#pragma unroll
          for (int s = 0; s < (u < 3 ? 4 : 5); s++) {
            const uint64_t db = make_desc(b0, s * 1024, u < 3 ? 4096 : 5120, 512, 2);
            if (u == 0 && s == 0) mma_rs160_n_z(acc, hf[0], db);
            else if (u < 3) mma_rs160_n(acc, hf[(4 * u + s) % 12], db);
            else mma_rs160_n(acc, of[s], db);
          }
          wg_commit();
          TRS(c * 16 + u * 3 + 1);
          r4.next<NU4>();
          if (u > 0 && !LAST) { wg_wait<1>(); rel(u - 1); }
          if (u == 0 && c > 0) send(c - 1);
          if (u == 1 && c == 0) { if (wg == 0) bar_arrive(2, 256); mbar_wait(bars + 8 * B_PEER, 0); }
          if (u == (LAST ? 1 : 2) && c > 0) finish(c - 1);
          TRS(c * 16 + u * 3 + 2);
        }
        if (LAST) {
#pragma unroll
          for (int q = 0; q < 10; q++) pv4[q] = ld_relaxed16(gp + q * 256);
        }
        wg_wait<0>();
        fence_regs(acc);
        if (!LAST) rel(3);
        TRS(c * 16 + 12);
        if (rank) {
#pragma unroll
          for (int e = 0; e < 20; e++) { sn[e] = pack_bf16(acc[2 * e], acc[2 * e + 1]); kb[e] = pack_bf16(acc[40 + 2 * e], acc[41 + 2 * e]); }
        } else {
#pragma unroll
          for (int e = 0; e < 20; e++) { kb[e] = pack_bf16(acc[2 * e], acc[2 * e + 1]); sn[e] = pack_bf16(acc[40 + 2 * e], acc[41 + 2 * e]); }
        }
#pragma unroll
        for (int e = 0; e < 20; e++) asm volatile("" : "+r"(sn[e]), "+r"(kb[e]));
        TRS(c * 16 + 13);
      };
      if (wg == 1) bar_sync(2, 256);
#pragma unroll 1
      for (int c = 0; c < 3; c++) chunk(c, BoolC<false>{});
      chunk(3, BoolC<true>{});
#pragma unroll
      for (int q = 10; q < 15; q++) pv4[q] = ld_relaxed16(gp + q * 256);
      send(3);
      TSTAMP(13);
      {
        const float w0 = 1.f - st_g[0], w1s = 1.f - st_g[1];
#pragma unroll
        for (int g = 0; g < 10; g++) {
          kp[4 * g] = fmaf(w0, bf_lo(xv[0][g]), rank ? acc[40 + 4 * g] : acc[4 * g]);
          kp[4 * g + 1] = fmaf(w0, bf_hi(xv[0][g]), rank ? acc[41 + 4 * g] : acc[4 * g + 1]);
          kp[4 * g + 2] = fmaf(w1s, bf_lo(xv[1][g]), rank ? acc[42 + 4 * g] : acc[4 * g + 2]);
          kp[4 * g + 3] = fmaf(w1s, bf_hi(xv[1][g]), rank ? acc[43 + 4 * g] : acc[4 * g + 3]);
        }
      }
      mbar_wait(bars + 8 * (B_DSR + 6 + wg), 0);
      uint4 pr[5];
#pragma unroll
      for (int q = 0; q < 5; q++) pr[q] = lds128(sb + OFF_DS + 20480 + tid * 16 + q * 4096);
#pragma unroll 1
      for (uint32_t n = 0; n < (WAIT_LIMIT >> 4); n++) {
        uint32_t m = 0u;
#pragma unroll
        for (int q = 0; q < 15; q++) {
          const uint32_t bad = (pv4[q].x ^ tag) & 1u;
          m |= bad;
          if (bad) pv4[q] = ld_relaxed16(gp + q * 256);
        }
        if (m == 0u) break;
      }
      TSTAMP(14);
#pragma unroll
      for (int q = 0; q < 5; q++) {
        const uint4 a = pv4[q], b = pv4[5 + q], c = pv4[10 + q], d = pr[q];
        add8(q, make_uint4(add_bf2(a.x, b.x), add_bf2(a.y, b.y), add_bf2(a.z, b.z), add_bf2(a.w, b.w)));
        add8(q, make_uint4(add_bf2(c.x, d.x), add_bf2(c.y, d.y), add_bf2(c.z, d.z), add_bf2(c.w, d.w)));
      }
      __syncwarp();
      uint32_t ov[2][10];
#pragma unroll
      for (int g = 0; g < 10; g++) { ov[0][g] = pack_bf16(kp[4 * g], kp[4 * g + 1]); ov[1][g] = pack_bf16(kp[4 * g + 2], kp[4 * g + 3]); }
      stage_tile(sb + OFF_OUT, ov);
      __syncwarp();
      __nv_bfloat16* dst = out + (size_t)(128 * i + 16 * warp) * D_ + 80 * j;
#pragma unroll
      for (int q = 0; q < 5; q++) {
        const int id = q * 32 + lane, r = id / 10;
        *reinterpret_cast<uint4*>(dst + r * (D_ - 80) + id * 8) = lds128(sb + OFF_OUT + warp * 2560 + id * 16);
      }
    }
    TSTAMP(15);
    if (tid == 0) asm volatile("red.relaxed.gpu.global.add.u32 [%0], 1;" ::"l"(g_flags + FL_DONE * 32) : "memory");
  }
}

namespace {
typedef CUresult (*EncodeFn)(CUtensorMap*, CUtensorMapDataType, cuuint32_t, void*, const cuuint64_t*, const cuuint64_t*,
                             const cuuint32_t*, const cuuint32_t*, CUtensorMapInterleave, CUtensorMapSwizzle,
                             CUtensorMapL2promotion, CUtensorMapFloatOOBfill);

void encode(EncodeFn fn, CUtensorMap* m, const void* ptr, int rank, const cuuint64_t* dims, const cuuint64_t* strides,
            const cuuint32_t* box, CUtensorMapSwizzle swz) {
  cuuint32_t es[5] = {1, 1, 1, 1, 1};
  fn(m, CU_TENSOR_MAP_DATA_TYPE_BFLOAT16, rank, const_cast<void*>(ptr), dims, strides, box, es, CU_TENSOR_MAP_INTERLEAVE_NONE,
     swz, CU_TENSOR_MAP_L2_PROMOTION_L2_128B, CU_TENSOR_MAP_FLOAT_OOB_FILL_NONE);
}
}

extern "C" void kernel_launch(void* const* d_in, const int* in_sizes, int n_in, void* d_out, int out_size) {
  (void)in_sizes; (void)n_in; (void)out_size;
  const __nv_bfloat16* x = (const __nv_bfloat16*)d_in[0];
  const __nv_bfloat16* wqkv = (const __nv_bfloat16*)d_in[1];
  const __nv_bfloat16* wphi = (const __nv_bfloat16*)d_in[2];
  const __nv_bfloat16* wo = (const __nv_bfloat16*)d_in[3];
  const __nv_bfloat16* w1 = (const __nv_bfloat16*)d_in[5];
  const __nv_bfloat16* w2 = (const __nv_bfloat16*)d_in[6];
  const __nv_bfloat16* w3 = (const __nv_bfloat16*)d_in[7];
  const __nv_bfloat16* w4 = (const __nv_bfloat16*)d_in[8];
  const __nv_bfloat16* gate_w = (const __nv_bfloat16*)d_in[9];

  static EncodeFn enc = nullptr;
  static void *pHs = nullptr, *pX1 = nullptr;
  if (!enc) {
    cudaDriverEntryPointQueryResult qr;
    cudaGetDriverEntryPoint("cuTensorMapEncodeTiled", (void**)&enc, cudaEnableDefault, &qr);
    cudaGetSymbolAddress(&pHs, g_Hs);
    cudaGetSymbolAddress(&pX1, g_X1);
    cudaFuncSetAttribute(fused_kernel, cudaFuncAttributeMaxDynamicSharedMemorySize, SMEM_BYTES);
  }
  Maps m;
  {
    cuuint64_t dims[2] = {D_, S_}, str[1] = {D_ * 2};
    cuuint32_t box[2] = {64, 128}, boxh[2] = {64, 64};
    encode(enc, &m.x, x, 2, dims, str, boxh, CU_TENSOR_MAP_SWIZZLE_128B);
    encode(enc, &m.hs, (const char*)pHs + 2 * D_ * 2, 2, dims, str, box, CU_TENSOR_MAP_SWIZZLE_128B);
    encode(enc, &m.x1, pX1, 2, dims, str, boxh, CU_TENSOR_MAP_SWIZZLE_128B);
    cuuint32_t boxr[2] = {80, 16}, boxs[2] = {80, 128};
    cuuint64_t dimsp[2] = {D_, S_ + 4};
    encode(enc, &m.st_h, pHs, 2, dimsp, str, boxs, CU_TENSOR_MAP_SWIZZLE_NONE);
    encode(enc, &m.st_x1, pX1, 2, dims, str, boxs, CU_TENSOR_MAP_SWIZZLE_NONE);
    encode(enc, &m.xr, x, 2, dims, str, boxr, CU_TENSOR_MAP_SWIZZLE_NONE);
  }
  {
    cuuint64_t dims[3] = {80, D_, 8}, str[2] = {D_ * 2, 160};
    cuuint32_t boxm[3] = {64, 64, 1}, boxr[3] = {16, 64, 1};
    encode(enc, &m.w1m, w1, 3, dims, str, boxm, CU_TENSOR_MAP_SWIZZLE_128B);
    encode(enc, &m.w1r, w1, 3, dims, str, boxr, CU_TENSOR_MAP_SWIZZLE_32B);
  }
  {
    cuuint64_t dims[4] = {80, D_, 3, 8}, str[3] = {3 * D_ * 2, D_ * 2, 160};
    cuuint32_t boxm[4] = {64, 64, 3, 1}, boxr[4] = {16, 64, 3, 1};
    encode(enc, &m.qm, wqkv, 4, dims, str, boxm, CU_TENSOR_MAP_SWIZZLE_128B);
    encode(enc, &m.qr, wqkv, 4, dims, str, boxr, CU_TENSOR_MAP_SWIZZLE_32B);
  }
  {
    cuuint64_t dims[3] = {32, D_, 20}, dims4[3] = {32, F_, 20}, str[2] = {D_ * 2, 64};
    cuuint32_t box4[3] = {32, 64, 5}, boxo[3] = {32, 80, 5};
    encode(enc, &m.w4, w4, 3, dims4, str, box4, CU_TENSOR_MAP_SWIZZLE_64B);
    encode(enc, &m.wo, wo, 3, dims, str, boxo, CU_TENSOR_MAP_SWIZZLE_64B);
    encode(enc, &m.w2, w2, 3, dims, str, box4, CU_TENSOR_MAP_SWIZZLE_64B);
  }
  {
    cuuint64_t dims[3] = {64, D_, 24}, str[2] = {F_ * 2, 128};
    cuuint32_t box[3] = {64, 64, 3};
    encode(enc, &m.w3, w3, 3, dims, str, box, CU_TENSOR_MAP_SWIZZLE_128B);
  }
  fused_kernel<<<NCTA, 384, SMEM_BYTES, cudaStreamPerThread>>>(m, x, wqkv, wphi, w1, w2, w3, w4, wo, gate_w, (__nv_bfloat16*)d_out);
}
```

```cpp
#include <cuda_runtime.h>
#include <cuda_bf16.h>
#include <cuda.h>
#include <stdint.h>

namespace {

constexpr int S_ = 2048, D_ = 640, F_ = 1536;
constexpr int NCTA = 128;
constexpr int KV_PAIR = 40 * 48 + 96;
constexpr int KV_J = 2 * KV_PAIR;

constexpr int SLOT_B = 49152, NB = 3;
constexpr int SLOT_A = 16384, NA = 4;
constexpr int OFF_B = 0;
constexpr int OFF_A = OFF_B + NB * SLOT_B;
constexpr int OFF_STG = OFF_A + 2 * SLOT_A;
constexpr int OFF_MISC = OFF_A + NA * SLOT_A;
constexpr int OFF_XST = OFF_MISC + 13312;
constexpr int OFF_CS = OFF_MISC + 16384;
constexpr int OFF_BAR = OFF_CS + 1088;
constexpr int SMEM_BYTES = OFF_BAR + 512 + 512;
constexpr int B_FULLA = 0, B_FULLB = 4, B_CS = 7, B_XR = 8, B_KV = 9, B_ST1 = 10, B_HST = 11, B_FULL4 = 12  ,
              B_DSR = 17  , B_EMPTYB = 27  , B_SIGP = 30, B_SIGH = 31, B_SIGKV = 32, B_SIGX1 = 33, B_MFREE = 34,
              B_EMPTY4 = 35  , B_EMPTYA = 40  , B_PEER = 44, B_PEER2 = 45, B_X1P = 46  , NBAR = 47;
constexpr int SPARE = 40960;
constexpr int UNIT4 = 25600, NU4 = 5;
constexpr int OFF_DS = OFF_A, OFF_OUT = OFF_A + 40960;

constexpr int FL_DONE = 0, FL_H = 1  , FL_X1 = FL_H + 32, FL_KV = FL_X1 + 16, FL_CS = FL_KV + 8, FL_CS3 = FL_CS + 8, FL_ST = FL_CS3 + 8;
constexpr int FL_S1 = FL_ST + 16, FL_COUNT = FL_S1 + 16;
constexpr int ACC_FLOATS = 8 * KV_J + D_ + F_;

struct Maps {
  CUtensorMap x, w1m, w1r, qm, qr, hs, w2, x1, w3, w4, wo, xr, st_h, st_x1;
};

}

__device__ __align__(1024) __nv_bfloat16 g_Hs[(S_ + 4) * D_];
__device__ __align__(1024) __nv_bfloat16 g_X1[S_ * D_];
__device__ __align__(128) float g_acc[2][ACC_FLOATS];
__device__ __align__(128) float4 g_xstat[S_];
__device__ __align__(128) float2 g_st1[S_ * 8];
__device__ __align__(128) uint4 g_part[16 * 8 * 3 * 1280];
__device__ __align__(128) unsigned g_flags[FL_COUNT * 32];
#define TSTAMP(n) do {} while (0)
#define TSTAMPX(n) do {} while (0)
#define TRACE(n) do {} while (0)
#define TRS(n) do {} while (0)

namespace {

__device__ __forceinline__ long long gtime() { long long t; asm volatile("mov.u64 %0, %%globaltimer;" : "=l"(t)); return t; }
__device__ __forceinline__ uint32_t smem_u32(const void* p) { return (uint32_t)__cvta_generic_to_shared(p); }
__device__ __forceinline__ void mbar_init(uint32_t bar, int cnt) {
  asm volatile("mbarrier.init.shared::cta.b64 [%0], %1;" ::"r"(bar), "r"(cnt) : "memory");
}
__device__ __forceinline__ void mbar_expect_tx(uint32_t bar, int bytes) {
  asm volatile("mbarrier.arrive.expect_tx.shared::cta.b64 _, [%0], %1;" ::"r"(bar), "r"(bytes) : "memory");
}
__device__ __forceinline__ void mbar_arrive_cta(uint32_t bar, uint32_t cta) {
  asm volatile("{\n.reg .b32 ra;\nmapa.shared::cluster.u32 ra, %0, %1;\nmbarrier.arrive.shared::cluster.b64 _, [ra];\n}"
               ::"r"(bar), "r"(cta) : "memory");
}
__device__ __forceinline__ uint32_t mbar_try(uint32_t bar, uint32_t parity) {
  uint32_t ok;
  asm volatile("{\n.reg .pred p;\nmbarrier.try_wait.parity.shared::cta.b64 p, [%1], %2;\nselp.u32 %0, 1, 0, p;\n}"
               : "=r"(ok) : "r"(bar), "r"(parity) : "memory");
  return ok;
}
constexpr uint32_t WAIT_LIMIT = 1u << 18;
__device__ __forceinline__ void mbar_wait(uint32_t bar, uint32_t parity) {
  uint32_t n = 0;
  while (!mbar_try(bar, parity) && ++n < WAIT_LIMIT) {}
}
__device__ __forceinline__ unsigned ld_acquire(const unsigned* p) {
  unsigned v;
  asm volatile("ld.acquire.gpu.global.u32 %0, [%1];" : "=r"(v) : "l"(p) : "memory");
  return v;
}
__device__ __forceinline__ void flag_wait(int idx, unsigned target) {
  const unsigned* p = g_flags + idx * 32;
  uint32_t n = 0;
  while ((int)(ld_acquire(p) - target) < 0 && ++n < (WAIT_LIMIT >> 2)) {}
}
__device__ __forceinline__ void flag_add(int idx) {
  asm volatile("red.release.gpu.global.add.u32 [%0], 1;" ::"l"(g_flags + idx * 32) : "memory");
}
__device__ __forceinline__ void flag_add_relaxed(int idx) {
  asm volatile("red.relaxed.gpu.global.add.u32 [%0], 1;" ::"l"(g_flags + idx * 32) : "memory");
}
__device__ __forceinline__ uint32_t mbar_test(uint32_t bar, uint32_t parity) {
  uint32_t ok;
  asm volatile("{\n.reg .pred p;\nmbarrier.test_wait.parity.shared::cta.b64 p, [%1], %2;\nselp.u32 %0, 1, 0, p;\n}"
               : "=r"(ok) : "r"(bar), "r"(parity) : "memory");
  return ok;
}
__device__ __forceinline__ uint32_t lds32(uint32_t a) {
  uint32_t v;
  asm volatile("ld.shared.u32 %0, [%1];" : "=r"(v) : "r"(a) : "memory");
  return v;
}
__device__ __forceinline__ void mbar_arrive(uint32_t bar) {
  asm volatile("mbarrier.arrive.shared::cta.b64 _, [%0];" ::"r"(bar) : "memory");
}
__device__ __forceinline__ void fence_async_glb() { asm volatile("fence.proxy.async.global;" ::: "memory"); }
__device__ __forceinline__ void fence_async_smem() { asm volatile("fence.proxy.async.shared::cta;" ::: "memory"); }
__device__ __forceinline__ void bar_sync(int id, int n) { asm volatile("bar.sync %0, %1;" ::"r"(id), "r"(n) : "memory"); }

__device__ __forceinline__ void tma2d(uint32_t dst, const CUtensorMap* m, uint32_t bar, int c0, int c1) {
  asm volatile("cp.async.bulk.tensor.2d.shared::cluster.global.mbarrier::complete_tx::bytes [%0], [%1, {%3, %4}], [%2];"
               ::"r"(dst), "l"(m), "r"(bar), "r"(c0), "r"(c1) : "memory");
}
__device__ __forceinline__ void tma2d_mc(uint32_t dst, const CUtensorMap* m, uint32_t bar, int c0, int c1) {
  asm volatile("cp.async.bulk.tensor.2d.shared::cluster.global.mbarrier::complete_tx::bytes.multicast::cluster"
               " [%0], [%1, {%3, %4}], [%2], %5;"
               ::"r"(dst), "l"(m), "r"(bar), "r"(c0), "r"(c1), "h"((uint16_t)3) : "memory");
}
__device__ __forceinline__ void tma3d(uint32_t dst, const CUtensorMap* m, uint32_t bar, int c0, int c1, int c2) {
  asm volatile("cp.async.bulk.tensor.3d.shared::cluster.global.mbarrier::complete_tx::bytes [%0], [%1, {%3, %4, %5}], [%2];"
               ::"r"(dst), "l"(m), "r"(bar), "r"(c0), "r"(c1), "r"(c2) : "memory");
}
__device__ __forceinline__ void tma4d(uint32_t dst, const CUtensorMap* m, uint32_t bar, int c0, int c1, int c2, int c3) {
  asm volatile("cp.async.bulk.tensor.4d.shared::cluster.global.mbarrier::complete_tx::bytes [%0], [%1, {%3, %4, %5, %6}], [%2];"
               ::"r"(dst), "l"(m), "r"(bar), "r"(c0), "r"(c1), "r"(c2), "r"(c3) : "memory");
}
__device__ __forceinline__ void tma2d_store(const CUtensorMap* m, uint32_t src, int c0, int c1) {
  asm volatile("cp.async.bulk.tensor.2d.global.shared::cta.bulk_group [%0, {%2, %3}], [%1];"
               ::"l"(m), "r"(src), "r"(c0), "r"(c1) : "memory");
}
__device__ __forceinline__ void bulk_store(void* dst, uint32_t src, uint32_t bytes) {
  asm volatile("cp.async.bulk.global.shared::cta.bulk_group [%0], [%1], %2;" ::"l"(dst), "r"(src), "r"(bytes) : "memory");
}
__device__ __forceinline__ void bulk_load(uint32_t dst, const void* src, uint32_t bytes, uint32_t bar) {
  asm volatile("cp.async.bulk.shared::cluster.global.mbarrier::complete_tx::bytes [%0], [%1], %2, [%3];"
               ::"r"(dst), "l"(src), "r"(bytes), "r"(bar) : "memory");
}
__device__ __forceinline__ void bulk_commit() { asm volatile("cp.async.bulk.commit_group;" ::: "memory"); }
template <int N> __device__ __forceinline__ void bulk_wait() { asm volatile("cp.async.bulk.wait_group %0;" ::"n"(N) : "memory"); }
__device__ __forceinline__ void bulk_wait_read() { asm volatile("cp.async.bulk.wait_group.read 0;" ::: "memory"); }
__device__ __forceinline__ void bar_arrive(int id, int n) { asm volatile("bar.arrive %0, %1;" ::"r"(id), "r"(n) : "memory"); }
__device__ __forceinline__ uint4 lds128(uint32_t a) {
  uint4 v;
  asm volatile("ld.shared.v4.u32 {%0, %1, %2, %3}, [%4];" : "=r"(v.x), "=r"(v.y), "=r"(v.z), "=r"(v.w) : "r"(a) : "memory");
  return v;
}
__device__ __forceinline__ void sts128(uint32_t a, uint4 v) {
  asm volatile("st.shared.v4.u32 [%0], {%1, %2, %3, %4};" ::"r"(a), "r"(v.x), "r"(v.y), "r"(v.z), "r"(v.w) : "memory");
}
__device__ __forceinline__ uint4 ld_relaxed16(const uint4* p) {
  uint4 v;
  asm volatile("ld.relaxed.gpu.global.v4.u32 {%0, %1, %2, %3}, [%4];" : "=r"(v.x), "=r"(v.y), "=r"(v.z), "=r"(v.w) : "l"(p) : "memory");
  return v;
}
__device__ __forceinline__ void st_relaxed16(uint4* p, uint32_t a, uint32_t b, uint32_t c, uint32_t d) {
  asm volatile("st.relaxed.gpu.global.v4.u32 [%0], {%1, %2, %3, %4};" ::"l"(p), "r"(a), "r"(b), "r"(c), "r"(d) : "memory");
}
__device__ __forceinline__ uint32_t map_peer(uint32_t addr, uint32_t cta) {
  uint32_t r;
  asm("mapa.shared::cluster.u32 %0, %1, %2;" : "=r"(r) : "r"(addr), "r"(cta));
  return r;
}
__device__ __forceinline__ void st_async16(uint32_t addr, uint32_t a, uint32_t b, uint32_t c, uint32_t d, uint32_t bar) {
  asm volatile("st.async.weak.shared::cluster.mbarrier::complete_tx::bytes.v4.b32 [%0], {%1, %2, %3, %4}, [%5];"
               ::"r"(addr), "r"(a), "r"(b), "r"(c), "r"(d), "r"(bar) : "memory");
}
__device__ __forceinline__ void l2_prefetch(const void* p, uint32_t bytes) {
  asm volatile("cp.async.bulk.prefetch.L2.global [%0], %1;" ::"l"(p), "r"(bytes) : "memory");
}
__device__ __forceinline__ void prefetch_tmap(const CUtensorMap* m) {
  asm volatile("prefetch.tensormap [%0];" ::"l"(m) : "memory");
}
__device__ __forceinline__ uint64_t make_desc(uint32_t a16, uint32_t off, uint32_t lbo, uint32_t sbo, uint32_t swz) {
  const uint32_t lo = a16 + ((off >> 4) + ((lbo >> 4) << 16)), hi = (sbo >> 4) | (swz << 30);
  uint64_t d;
  asm("mov.b64 %0, {%1, %2};" : "=l"(d) : "r"(lo), "r"(hi));
  return d;
}
__device__ __forceinline__ void wg_fence() { asm volatile("wgmma.fence.sync.aligned;" ::: "memory"); }
__device__ __forceinline__ void wg_commit() { asm volatile("wgmma.commit_group.sync.aligned;" ::: "memory"); }
template <int N> __device__ __forceinline__ void wg_wait() { asm volatile("wgmma.wait_group.sync.aligned %0;" ::"n"(N) : "memory"); }
template <int N> __device__ __forceinline__ void fence_regs(float (&d)[N]) {
#pragma unroll
  for (int i = 0; i < N; i++) asm volatile("" : "+f"(d[i])::"memory");
}
template <int N> __device__ __forceinline__ void zero_regs(float (&d)[N]) {
#pragma unroll
  for (int i = 0; i < N; i++) d[i] = 0.f;
}
__device__ __forceinline__ uint32_t pack_bf16(float lo, float hi) {
  uint32_t r;
  asm("cvt.rn.bf16x2.f32 %0, %1, %2;" : "=r"(r) : "f"(hi), "f"(lo));
  return r;
}
__device__ __forceinline__ float bf_lo(uint32_t v) { return __uint_as_float(v << 16); }
__device__ __forceinline__ float bf_hi(uint32_t v) { return __uint_as_float(v & 0xffff0000u); }
__device__ __forceinline__ uint32_t max_bf2(uint32_t a, uint32_t b) {
  uint32_t r; asm("max.bf16x2 %0, %1, %2;" : "=r"(r) : "r"(a), "r"(b)); return r;
}
__device__ __forceinline__ uint32_t min_bf2(uint32_t a, uint32_t b) {
  uint32_t r; asm("min.bf16x2 %0, %1, %2;" : "=r"(r) : "r"(a), "r"(b)); return r;
}
__device__ __forceinline__ uint32_t add_bf2(uint32_t a, uint32_t b) {
  uint32_t r; asm("add.rn.bf16x2 %0, %1, %2;" : "=r"(r) : "r"(a), "r"(b)); return r;
}
__device__ __forceinline__ float ex2(float x) { float r; asm("ex2.approx.ftz.f32 %0, %1;" : "=f"(r) : "f"(x)); return r; }
__device__ __forceinline__ float rcp(float x) { float r; asm("rcp.approx.ftz.f32 %0, %1;" : "=f"(r) : "f"(x)); return r; }
__device__ __forceinline__ float tanh_ap(float x) { float r; asm("tanh.approx.f32 %0, %1;" : "=f"(r) : "f"(x)); return r; }
struct GeluC { float c0, c1, ch; };
__device__ __forceinline__ GeluC gelu_consts(float rstd, float scale) {
  return GeluC{0.7978845608f * rstd, 0.0356774081f * rstd * rstd * rstd, 0.5f * scale * rstd};
}
__device__ __forceinline__ float gelu_s(float y, const GeluC& c) {
  const float u = y * fmaf(y * y, c.c1, c.c0);
  const float hx = y * c.ch;
  return fmaf(hx, tanh_ap(u), hx);
}
__device__ __forceinline__ void stsm4(uint32_t addr, uint32_t r0, uint32_t r1, uint32_t r2, uint32_t r3) {
  asm volatile("stmatrix.sync.aligned.m8n8.x4.shared.b16 [%0], {%1, %2, %3, %4};"
               ::"r"(addr), "r"(r0), "r"(r1), "r"(r2), "r"(r3) : "memory");
}
__device__ __forceinline__ void red_add4(float* p, float a, float b, float c, float d) {
  asm volatile("red.global.add.v4.f32 [%0], {%1, %2, %3, %4};" ::"l"(p), "f"(a), "f"(b), "f"(c), "f"(d) : "memory");
}

__device__ __forceinline__ void mma_ss256(float (&d)[128], uint64_t descA, uint64_t descB) {
  asm volatile("wgmma.mma_async.sync.aligned.m64n256k16.f32.bf16.bf16 {"
      "%0, %1, %2, %3, %4, %5, %6, %7, %8, %9, %10, %11, %12, %13, %14, %15, "
      "%16, %17, %18, %19, %20, %21, %22, %23, %24, %25, %26, %27, %28, %29, %30, %31, "
      "%32, %33, %34, %35, %36, %37, %38, %39, %40, %41, %42, %43, %44, %45, %46, %47, "
      "%48, %49, %50, %51, %52, %53, %54, %55, %56, %57, %58, %59, %60, %61, %62, %63, "
      "%64, %65, %66, %67, %68, %69, %70, %71, %72, %73, %74, %75, %76, %77, %78, %79, "
      "%80, %81, %82, %83, %84, %85, %86, %87, %88, %89, %90, %91, %92, %93, %94, %95, "
      "%96, %97, %98, %99, %100, %101, %102, %103, %104, %105, %106, %107, %108, %109, %110, %111, "
      "%112, %113, %114, %115, %116, %117, %118, %119, %120, %121, %122, %123, %124, %125, %126, %127"
      "}, %128, %129, 1, 1, 1, 0, 1;\n"
      : "+f"(d[0]), "+f"(d[1]), "+f"(d[2]), "+f"(d[3]), "+f"(d[4]), "+f"(d[5]), "+f"(d[6]), "+f"(d[7]),
        "+f"(d[8]), "+f"(d[9]), "+f"(d[10]), "+f"(d[11]), "+f"(d[12]), "+f"(d[13]), "+f"(d[14]), "+f"(d[15]),
        "+f"(d[16]), "+f"(d[17]), "+f"(d[18]), "+f"(d[19]), "+f"(d[20]), "+f"(d[21]), "+f"(d[22]), "+f"(d[23]),
        "+f"(d[24]), "+f"(d[25]), "+f"(d[26]), "+f"(d[27]), "+f"(d[28]), "+f"(d[29]), "+f"(d[30]), "+f"(d[31]),
        "+f"(d[32]), "+f"(d[33]), "+f"(d[34]), "+f"(d[35]), "+f"(d[36]), "+f"(d[37]), "+f"(d[38]), "+f"(d[39]),
        "+f"(d[40]), "+f"(d[41]), "+f"(d[42]), "+f"(d[43]), "+f"(d[44]), "+f"(d[45]), "+f"(d[46]), "+f"(d[47]),
        "+f"(d[48]), "+f"(d[49]), "+f"(d[50]), "+f"(d[51]), "+f"(d[52]), "+f"(d[53]), "+f"(d[54]), "+f"(d[55]),
        "+f"(d[56]), "+f"(d[57]), "+f"(d[58]), "+f"(d[59]), "+f"(d[60]), "+f"(d[61]), "+f"(d[62]), "+f"(d[63]),
        "+f"(d[64]), "+f"(d[65]), "+f"(d[66]), "+f"(d[67]), "+f"(d[68]), "+f"(d[69]), "+f"(d[70]), "+f"(d[71]),
        "+f"(d[72]), "+f"(d[73]), "+f"(d[74]), "+f"(d[75]), "+f"(d[76]), "+f"(d[77]), "+f"(d[78]), "+f"(d[79]),
        "+f"(d[80]), "+f"(d[81]), "+f"(d[82]), "+f"(d[83]), "+f"(d[84]), "+f"(d[85]), "+f"(d[86]), "+f"(d[87]),
        "+f"(d[88]), "+f"(d[89]), "+f"(d[90]), "+f"(d[91]), "+f"(d[92]), "+f"(d[93]), "+f"(d[94]), "+f"(d[95]),
        "+f"(d[96]), "+f"(d[97]), "+f"(d[98]), "+f"(d[99]), "+f"(d[100]), "+f"(d[101]), "+f"(d[102]), "+f"(d[103]),
        "+f"(d[104]), "+f"(d[105]), "+f"(d[106]), "+f"(d[107]), "+f"(d[108]), "+f"(d[109]), "+f"(d[110]), "+f"(d[111]),
        "+f"(d[112]), "+f"(d[113]), "+f"(d[114]), "+f"(d[115]), "+f"(d[116]), "+f"(d[117]), "+f"(d[118]), "+f"(d[119]),
        "+f"(d[120]), "+f"(d[121]), "+f"(d[122]), "+f"(d[123]), "+f"(d[124]), "+f"(d[125]), "+f"(d[126]), "+f"(d[127])
      : "l"(descA), "l"(descB));
}
__device__ __forceinline__ void mma_ss256_p(float (&d)[128], uint64_t descA, uint64_t descB, int acc) {
  asm volatile("{\n.reg .pred p;\nsetp.ne.b32 p, %130, 0;\n"
      "wgmma.mma_async.sync.aligned.m64n256k16.f32.bf16.bf16 {"
      "%0, %1, %2, %3, %4, %5, %6, %7, %8, %9, %10, %11, %12, %13, %14, %15, "
      "%16, %17, %18, %19, %20, %21, %22, %23, %24, %25, %26, %27, %28, %29, %30, %31, "
      "%32, %33, %34, %35, %36, %37, %38, %39, %40, %41, %42, %43, %44, %45, %46, %47, "
      "%48, %49, %50, %51, %52, %53, %54, %55, %56, %57, %58, %59, %60, %61, %62, %63, "
      "%64, %65, %66, %67, %68, %69, %70, %71, %72, %73, %74, %75, %76, %77, %78, %79, "
      "%80, %81, %82, %83, %84, %85, %86, %87, %88, %89, %90, %91, %92, %93, %94, %95, "
      "%96, %97, %98, %99, %100, %101, %102, %103, %104, %105, %106, %107, %108, %109, %110, %111, "
      "%112, %113, %114, %115, %116, %117, %118, %119, %120, %121, %122, %123, %124, %125, %126, %127"
      "}, %128, %129, p, 1, 1, 0, 1;\n}\n"
      : "+f"(d[0]), "+f"(d[1]), "+f"(d[2]), "+f"(d[3]), "+f"(d[4]), "+f"(d[5]), "+f"(d[6]), "+f"(d[7]),
        "+f"(d[8]), "+f"(d[9]), "+f"(d[10]), "+f"(d[11]), "+f"(d[12]), "+f"(d[13]), "+f"(d[14]), "+f"(d[15]),
        "+f"(d[16]), "+f"(d[17]), "+f"(d[18]), "+f"(d[19]), "+f"(d[20]), "+f"(d[21]), "+f"(d[22]), "+f"(d[23]),
        "+f"(d[24]), "+f"(d[25]), "+f"(d[26]), "+f"(d[27]), "+f"(d[28]), "+f"(d[29]), "+f"(d[30]), "+f"(d[31]),
        "+f"(d[32]), "+f"(d[33]), "+f"(d[34]), "+f"(d[35]), "+f"(d[36]), "+f"(d[37]), "+f"(d[38]), "+f"(d[39]),
        "+f"(d[40]), "+f"(d[41]), "+f"(d[42]), "+f"(d[43]), "+f"(d[44]), "+f"(d[45]), "+f"(d[46]), "+f"(d[47]),
        "+f"(d[48]), "+f"(d[49]), "+f"(d[50]), "+f"(d[51]), "+f"(d[52]), "+f"(d[53]), "+f"(d[54]), "+f"(d[55]),
        "+f"(d[56]), "+f"(d[57]), "+f"(d[58]), "+f"(d[59]), "+f"(d[60]), "+f"(d[61]), "+f"(d[62]), "+f"(d[63]),
        "+f"(d[64]), "+f"(d[65]), "+f"(d[66]), "+f"(d[67]), "+f"(d[68]), "+f"(d[69]), "+f"(d[70]), "+f"(d[71]),
        "+f"(d[72]), "+f"(d[73]), "+f"(d[74]), "+f"(d[75]), "+f"(d[76]), "+f"(d[77]), "+f"(d[78]), "+f"(d[79]),
        "+f"(d[80]), "+f"(d[81]), "+f"(d[82]), "+f"(d[83]), "+f"(d[84]), "+f"(d[85]), "+f"(d[86]), "+f"(d[87]),
        "+f"(d[88]), "+f"(d[89]), "+f"(d[90]), "+f"(d[91]), "+f"(d[92]), "+f"(d[93]), "+f"(d[94]), "+f"(d[95]),
        "+f"(d[96]), "+f"(d[97]), "+f"(d[98]), "+f"(d[99]), "+f"(d[100]), "+f"(d[101]), "+f"(d[102]), "+f"(d[103]),
        "+f"(d[104]), "+f"(d[105]), "+f"(d[106]), "+f"(d[107]), "+f"(d[108]), "+f"(d[109]), "+f"(d[110]), "+f"(d[111]),
        "+f"(d[112]), "+f"(d[113]), "+f"(d[114]), "+f"(d[115]), "+f"(d[116]), "+f"(d[117]), "+f"(d[118]), "+f"(d[119]),
        "+f"(d[120]), "+f"(d[121]), "+f"(d[122]), "+f"(d[123]), "+f"(d[124]), "+f"(d[125]), "+f"(d[126]), "+f"(d[127])
      : "l"(descA), "l"(descB), "r"(acc));
}

__device__ __forceinline__ void mma_ss64(float (&d)[32], uint64_t descA, uint64_t descB) {
  asm volatile("wgmma.mma_async.sync.aligned.m64n64k16.f32.bf16.bf16 {"
      "%0, %1, %2, %3, %4, %5, %6, %7, %8, %9, %10, %11, %12, %13, %14, %15, "
      "%16, %17, %18, %19, %20, %21, %22, %23, %24, %25, %26, %27, %28, %29, %30, %31"
      "}, %32, %33, 1, 1, 1, 0, 1;\n"
      : "+f"(d[0]), "+f"(d[1]), "+f"(d[2]), "+f"(d[3]), "+f"(d[4]), "+f"(d[5]), "+f"(d[6]), "+f"(d[7]),
        "+f"(d[8]), "+f"(d[9]), "+f"(d[10]), "+f"(d[11]), "+f"(d[12]), "+f"(d[13]), "+f"(d[14]), "+f"(d[15]),
        "+f"(d[16]), "+f"(d[17]), "+f"(d[18]), "+f"(d[19]), "+f"(d[20]), "+f"(d[21]), "+f"(d[22]), "+f"(d[23]),
        "+f"(d[24]), "+f"(d[25]), "+f"(d[26]), "+f"(d[27]), "+f"(d[28]), "+f"(d[29]), "+f"(d[30]), "+f"(d[31])
      : "l"(descA), "l"(descB));
}
__device__ __forceinline__ void mma_ss64_p(float (&d)[32], uint64_t descA, uint64_t descB, int acc) {
  asm volatile("{\n.reg .pred p;\nsetp.ne.b32 p, %34, 0;\n"
      "wgmma.mma_async.sync.aligned.m64n64k16.f32.bf16.bf16 {"
      "%0, %1, %2, %3, %4, %5, %6, %7, %8, %9, %10, %11, %12, %13, %14, %15, "
      "%16, %17, %18, %19, %20, %21, %22, %23, %24, %25, %26, %27, %28, %29, %30, %31"
      "}, %32, %33, p, 1, 1, 0, 1;\n}\n"
      : "+f"(d[0]), "+f"(d[1]), "+f"(d[2]), "+f"(d[3]), "+f"(d[4]), "+f"(d[5]), "+f"(d[6]), "+f"(d[7]),
        "+f"(d[8]), "+f"(d[9]), "+f"(d[10]), "+f"(d[11]), "+f"(d[12]), "+f"(d[13]), "+f"(d[14]), "+f"(d[15]),
        "+f"(d[16]), "+f"(d[17]), "+f"(d[18]), "+f"(d[19]), "+f"(d[20]), "+f"(d[21]), "+f"(d[22]), "+f"(d[23]),
        "+f"(d[24]), "+f"(d[25]), "+f"(d[26]), "+f"(d[27]), "+f"(d[28]), "+f"(d[29]), "+f"(d[30]), "+f"(d[31])
      : "l"(descA), "l"(descB), "r"(acc));
}

__device__ __forceinline__ void mma_ss160(float (&d)[80], uint64_t descA, uint64_t descB) {
  asm volatile("wgmma.mma_async.sync.aligned.m64n160k16.f32.bf16.bf16 {"
      "%0, %1, %2, %3, %4, %5, %6, %7, %8, %9, %10, %11, %12, %13, %14, %15, "
      "%16, %17, %18, %19, %20, %21, %22, %23, %24, %25, %26, %27, %28, %29, %30, %31, "
      "%32, %33, %34, %35, %36, %37, %38, %39, %40, %41, %42, %43, %44, %45, %46, %47, "
      "%48, %49, %50, %51, %52, %53, %54, %55, %56, %57, %58, %59, %60, %61, %62, %63, "
      "%64, %65, %66, %67, %68, %69, %70, %71, %72, %73, %74, %75, %76, %77, %78, %79"
      "}, %80, %81, 1, 1, 1, 0, 1;\n"
      : "+f"(d[0]), "+f"(d[1]), "+f"(d[2]), "+f"(d[3]), "+f"(d[4]), "+f"(d[5]), "+f"(d[6]), "+f"(d[7]),
        "+f"(d[8]), "+f"(d[9]), "+f"(d[10]), "+f"(d[11]), "+f"(d[12]), "+f"(d[13]), "+f"(d[14]), "+f"(d[15]),
        "+f"(d[16]), "+f"(d[17]), "+f"(d[18]), "+f"(d[19]), "+f"(d[20]), "+f"(d[21]), "+f"(d[22]), "+f"(d[23]),
        "+f"(d[24]), "+f"(d[25]), "+f"(d[26]), "+f"(d[27]), "+f"(d[28]), "+f"(d[29]), "+f"(d[30]), "+f"(d[31]),
        "+f"(d[32]), "+f"(d[33]), "+f"(d[34]), "+f"(d[35]), "+f"(d[36]), "+f"(d[37]), "+f"(d[38]), "+f"(d[39]),
        "+f"(d[40]), "+f"(d[41]), "+f"(d[42]), "+f"(d[43]), "+f"(d[44]), "+f"(d[45]), "+f"(d[46]), "+f"(d[47]),
        "+f"(d[48]), "+f"(d[49]), "+f"(d[50]), "+f"(d[51]), "+f"(d[52]), "+f"(d[53]), "+f"(d[54]), "+f"(d[55]),
        "+f"(d[56]), "+f"(d[57]), "+f"(d[58]), "+f"(d[59]), "+f"(d[60]), "+f"(d[61]), "+f"(d[62]), "+f"(d[63]),
        "+f"(d[64]), "+f"(d[65]), "+f"(d[66]), "+f"(d[67]), "+f"(d[68]), "+f"(d[69]), "+f"(d[70]), "+f"(d[71]),
        "+f"(d[72]), "+f"(d[73]), "+f"(d[74]), "+f"(d[75]), "+f"(d[76]), "+f"(d[77]), "+f"(d[78]), "+f"(d[79])
      : "l"(descA), "l"(descB));
}
__device__ __forceinline__ void mma_ss160_z(float (&d)[80], uint64_t descA, uint64_t descB) {
  asm volatile("wgmma.mma_async.sync.aligned.m64n160k16.f32.bf16.bf16 {"
      "%0, %1, %2, %3, %4, %5, %6, %7, %8, %9, %10, %11, %12, %13, %14, %15, "
      "%16, %17, %18, %19, %20, %21, %22, %23, %24, %25, %26, %27, %28, %29, %30, %31, "
      "%32, %33, %34, %35, %36, %37, %38, %39, %40, %41, %42, %43, %44, %45, %46, %47, "
      "%48, %49, %50, %51, %52, %53, %54, %55, %56, %57, %58, %59, %60, %61, %62, %63, "
      "%64, %65, %66, %67, %68, %69, %70, %71, %72, %73, %74, %75, %76, %77, %78, %79"
      "}, %80, %81, 0, 1, 1, 0, 1;\n"
      : "=f"(d[0]), "=f"(d[1]), "=f"(d[2]), "=f"(d[3]), "=f"(d[4]), "=f"(d[5]), "=f"(d[6]), "=f"(d[7]),
        "=f"(d[8]), "=f"(d[9]), "=f"(d[10]), "=f"(d[11]), "=f"(d[12]), "=f"(d[13]), "=f"(d[14]), "=f"(d[15]),
        "=f"(d[16]), "=f"(d[17]), "=f"(d[18]), "=f"(d[19]), "=f"(d[20]), "=f"(d[21]), "=f"(d[22]), "=f"(d[23]),
        "=f"(d[24]), "=f"(d[25]), "=f"(d[26]), "=f"(d[27]), "=f"(d[28]), "=f"(d[29]), "=f"(d[30]), "=f"(d[31]),
        "=f"(d[32]), "=f"(d[33]), "=f"(d[34]), "=f"(d[35]), "=f"(d[36]), "=f"(d[37]), "=f"(d[38]), "=f"(d[39]),
        "=f"(d[40]), "=f"(d[41]), "=f"(d[42]), "=f"(d[43]), "=f"(d[44]), "=f"(d[45]), "=f"(d[46]), "=f"(d[47]),
        "=f"(d[48]), "=f"(d[49]), "=f"(d[50]), "=f"(d[51]), "=f"(d[52]), "=f"(d[53]), "=f"(d[54]), "=f"(d[55]),
        "=f"(d[56]), "=f"(d[57]), "=f"(d[58]), "=f"(d[59]), "=f"(d[60]), "=f"(d[61]), "=f"(d[62]), "=f"(d[63]),
        "=f"(d[64]), "=f"(d[65]), "=f"(d[66]), "=f"(d[67]), "=f"(d[68]), "=f"(d[69]), "=f"(d[70]), "=f"(d[71]),
        "=f"(d[72]), "=f"(d[73]), "=f"(d[74]), "=f"(d[75]), "=f"(d[76]), "=f"(d[77]), "=f"(d[78]), "=f"(d[79])
      : "l"(descA), "l"(descB));
}

__device__ __forceinline__ void mma_ss192(float (&d)[96], uint64_t descA, uint64_t descB) {
  asm volatile("wgmma.mma_async.sync.aligned.m64n192k16.f32.bf16.bf16 {"
      "%0, %1, %2, %3, %4, %5, %6, %7, %8, %9, %10, %11, %12, %13, %14, %15, "
      "%16, %17, %18, %19, %20, %21, %22, %23, %24, %25, %26, %27, %28, %29, %30, %31, "
      "%32, %33, %34, %35, %36, %37, %38, %39, %40, %41, %42, %43, %44, %45, %46, %47, "
      "%48, %49, %50, %51, %52, %53, %54, %55, %56, %57, %58, %59, %60, %61, %62, %63, "
      "%64, %65, %66, %67, %68, %69, %70, %71, %72, %73, %74, %75, %76, %77, %78, %79, "
      "%80, %81, %82, %83, %84, %85, %86, %87, %88, %89, %90, %91, %92, %93, %94, %95"
      "}, %96, %97, 1, 1, 1, 0, 1;\n"
      : "+f"(d[0]), "+f"(d[1]), "+f"(d[2]), "+f"(d[3]), "+f"(d[4]), "+f"(d[5]), "+f"(d[6]), "+f"(d[7]),
        "+f"(d[8]), "+f"(d[9]), "+f"(d[10]), "+f"(d[11]), "+f"(d[12]), "+f"(d[13]), "+f"(d[14]), "+f"(d[15]),
        "+f"(d[16]), "+f"(d[17]), "+f"(d[18]), "+f"(d[19]), "+f"(d[20]), "+f"(d[21]), "+f"(d[22]), "+f"(d[23]),
        "+f"(d[24]), "+f"(d[25]), "+f"(d[26]), "+f"(d[27]), "+f"(d[28]), "+f"(d[29]), "+f"(d[30]), "+f"(d[31]),
        "+f"(d[32]), "+f"(d[33]), "+f"(d[34]), "+f"(d[35]), "+f"(d[36]), "+f"(d[37]), "+f"(d[38]), "+f"(d[39]),
        "+f"(d[40]), "+f"(d[41]), "+f"(d[42]), "+f"(d[43]), "+f"(d[44]), "+f"(d[45]), "+f"(d[46]), "+f"(d[47]),
        "+f"(d[48]), "+f"(d[49]), "+f"(d[50]), "+f"(d[51]), "+f"(d[52]), "+f"(d[53]), "+f"(d[54]), "+f"(d[55]),
        "+f"(d[56]), "+f"(d[57]), "+f"(d[58]), "+f"(d[59]), "+f"(d[60]), "+f"(d[61]), "+f"(d[62]), "+f"(d[63]),
        "+f"(d[64]), "+f"(d[65]), "+f"(d[66]), "+f"(d[67]), "+f"(d[68]), "+f"(d[69]), "+f"(d[70]), "+f"(d[71]),
        "+f"(d[72]), "+f"(d[73]), "+f"(d[74]), "+f"(d[75]), "+f"(d[76]), "+f"(d[77]), "+f"(d[78]), "+f"(d[79]),
        "+f"(d[80]), "+f"(d[81]), "+f"(d[82]), "+f"(d[83]), "+f"(d[84]), "+f"(d[85]), "+f"(d[86]), "+f"(d[87]),
        "+f"(d[88]), "+f"(d[89]), "+f"(d[90]), "+f"(d[91]), "+f"(d[92]), "+f"(d[93]), "+f"(d[94]), "+f"(d[95])
      : "l"(descA), "l"(descB));
}
__device__ __forceinline__ void mma_ss192_p(float (&d)[96], uint64_t descA, uint64_t descB, int acc) {
  asm volatile("{\n.reg .pred p;\nsetp.ne.b32 p, %98, 0;\n"
      "wgmma.mma_async.sync.aligned.m64n192k16.f32.bf16.bf16 {"
      "%0, %1, %2, %3, %4, %5, %6, %7, %8, %9, %10, %11, %12, %13, %14, %15, "
      "%16, %17, %18, %19, %20, %21, %22, %23, %24, %25, %26, %27, %28, %29, %30, %31, "
      "%32, %33, %34, %35, %36, %37, %38, %39, %40, %41, %42, %43, %44, %45, %46, %47, "
      "%48, %49, %50, %51, %52, %53, %54, %55, %56, %57, %58, %59, %60, %61, %62, %63, "
      "%64, %65, %66, %67, %68, %69, %70, %71, %72, %73, %74, %75, %76, %77, %78, %79, "
      "%80, %81, %82, %83, %84, %85, %86, %87, %88, %89, %90, %91, %92, %93, %94, %95"
      "}, %96, %97, p, 1, 1, 0, 1;\n}\n"
      : "+f"(d[0]), "+f"(d[1]), "+f"(d[2]), "+f"(d[3]), "+f"(d[4]), "+f"(d[5]), "+f"(d[6]), "+f"(d[7]),
        "+f"(d[8]), "+f"(d[9]), "+f"(d[10]), "+f"(d[11]), "+f"(d[12]), "+f"(d[13]), "+f"(d[14]), "+f"(d[15]),
        "+f"(d[16]), "+f"(d[17]), "+f"(d[18]), "+f"(d[19]), "+f"(d[20]), "+f"(d[21]), "+f"(d[22]), "+f"(d[23]),
        "+f"(d[24]), "+f"(d[25]), "+f"(d[26]), "+f"(d[27]), "+f"(d[28]), "+f"(d[29]), "+f"(d[30]), "+f"(d[31]),
        "+f"(d[32]), "+f"(d[33]), "+f"(d[34]), "+f"(d[35]), "+f"(d[36]), "+f"(d[37]), "+f"(d[38]), "+f"(d[39]),
        "+f"(d[40]), "+f"(d[41]), "+f"(d[42]), "+f"(d[43]), "+f"(d[44]), "+f"(d[45]), "+f"(d[46]), "+f"(d[47]),
        "+f"(d[48]), "+f"(d[49]), "+f"(d[50]), "+f"(d[51]), "+f"(d[52]), "+f"(d[53]), "+f"(d[54]), "+f"(d[55]),
        "+f"(d[56]), "+f"(d[57]), "+f"(d[58]), "+f"(d[59]), "+f"(d[60]), "+f"(d[61]), "+f"(d[62]), "+f"(d[63]),
        "+f"(d[64]), "+f"(d[65]), "+f"(d[66]), "+f"(d[67]), "+f"(d[68]), "+f"(d[69]), "+f"(d[70]), "+f"(d[71]),
        "+f"(d[72]), "+f"(d[73]), "+f"(d[74]), "+f"(d[75]), "+f"(d[76]), "+f"(d[77]), "+f"(d[78]), "+f"(d[79]),
        "+f"(d[80]), "+f"(d[81]), "+f"(d[82]), "+f"(d[83]), "+f"(d[84]), "+f"(d[85]), "+f"(d[86]), "+f"(d[87]),
        "+f"(d[88]), "+f"(d[89]), "+f"(d[90]), "+f"(d[91]), "+f"(d[92]), "+f"(d[93]), "+f"(d[94]), "+f"(d[95])
      : "l"(descA), "l"(descB), "r"(acc));
}

__device__ __forceinline__ void mma_ss80_tt(float (&d)[40], uint64_t descA, uint64_t descB) {
  asm volatile("wgmma.mma_async.sync.aligned.m64n80k16.f32.bf16.bf16 {"
      "%0, %1, %2, %3, %4, %5, %6, %7, %8, %9, %10, %11, %12, %13, %14, %15, "
      "%16, %17, %18, %19, %20, %21, %22, %23, %24, %25, %26, %27, %28, %29, %30, %31, "
      "%32, %33, %34, %35, %36, %37, %38, %39"
      "}, %40, %41, 1, 1, 1, 1, 1;\n"
      : "+f"(d[0]), "+f"(d[1]), "+f"(d[2]), "+f"(d[3]), "+f"(d[4]), "+f"(d[5]), "+f"(d[6]), "+f"(d[7]),
        "+f"(d[8]), "+f"(d[9]), "+f"(d[10]), "+f"(d[11]), "+f"(d[12]), "+f"(d[13]), "+f"(d[14]), "+f"(d[15]),
        "+f"(d[16]), "+f"(d[17]), "+f"(d[18]), "+f"(d[19]), "+f"(d[20]), "+f"(d[21]), "+f"(d[22]), "+f"(d[23]),
        "+f"(d[24]), "+f"(d[25]), "+f"(d[26]), "+f"(d[27]), "+f"(d[28]), "+f"(d[29]), "+f"(d[30]), "+f"(d[31]),
        "+f"(d[32]), "+f"(d[33]), "+f"(d[34]), "+f"(d[35]), "+f"(d[36]), "+f"(d[37]), "+f"(d[38]), "+f"(d[39])
      : "l"(descA), "l"(descB));
}
__device__ __forceinline__ void mma_ss80_tt_z(float (&d)[40], uint64_t descA, uint64_t descB) {
  asm volatile("wgmma.mma_async.sync.aligned.m64n80k16.f32.bf16.bf16 {"
      "%0, %1, %2, %3, %4, %5, %6, %7, %8, %9, %10, %11, %12, %13, %14, %15, "
      "%16, %17, %18, %19, %20, %21, %22, %23, %24, %25, %26, %27, %28, %29, %30, %31, "
      "%32, %33, %34, %35, %36, %37, %38, %39"
      "}, %40, %41, 0, 1, 1, 1, 1;\n"
      : "=f"(d[0]), "=f"(d[1]), "=f"(d[2]), "=f"(d[3]), "=f"(d[4]), "=f"(d[5]), "=f"(d[6]), "=f"(d[7]),
        "=f"(d[8]), "=f"(d[9]), "=f"(d[10]), "=f"(d[11]), "=f"(d[12]), "=f"(d[13]), "=f"(d[14]), "=f"(d[15]),
        "=f"(d[16]), "=f"(d[17]), "=f"(d[18]), "=f"(d[19]), "=f"(d[20]), "=f"(d[21]), "=f"(d[22]), "=f"(d[23]),
        "=f"(d[24]), "=f"(d[25]), "=f"(d[26]), "=f"(d[27]), "=f"(d[28]), "=f"(d[29]), "=f"(d[30]), "=f"(d[31]),
        "=f"(d[32]), "=f"(d[33]), "=f"(d[34]), "=f"(d[35]), "=f"(d[36]), "=f"(d[37]), "=f"(d[38]), "=f"(d[39])
      : "l"(descA), "l"(descB));
}

__device__ __forceinline__ void mma_rs80_k(float (&d)[40], const uint32_t (&a)[4], uint64_t descB) {
  asm volatile("wgmma.mma_async.sync.aligned.m64n80k16.f32.bf16.bf16 {"
      "%0, %1, %2, %3, %4, %5, %6, %7, %8, %9, %10, %11, %12, %13, %14, %15, "
      "%16, %17, %18, %19, %20, %21, %22, %23, %24, %25, %26, %27, %28, %29, %30, %31, "
      "%32, %33, %34, %35, %36, %37, %38, %39"
      "}, {%40, %41, %42, %43}, %44, 1, 1, 1, 0;\n"
      : "+f"(d[0]), "+f"(d[1]), "+f"(d[2]), "+f"(d[3]), "+f"(d[4]), "+f"(d[5]), "+f"(d[6]), "+f"(d[7]),
        "+f"(d[8]), "+f"(d[9]), "+f"(d[10]), "+f"(d[11]), "+f"(d[12]), "+f"(d[13]), "+f"(d[14]), "+f"(d[15]),
        "+f"(d[16]), "+f"(d[17]), "+f"(d[18]), "+f"(d[19]), "+f"(d[20]), "+f"(d[21]), "+f"(d[22]), "+f"(d[23]),
        "+f"(d[24]), "+f"(d[25]), "+f"(d[26]), "+f"(d[27]), "+f"(d[28]), "+f"(d[29]), "+f"(d[30]), "+f"(d[31]),
        "+f"(d[32]), "+f"(d[33]), "+f"(d[34]), "+f"(d[35]), "+f"(d[36]), "+f"(d[37]), "+f"(d[38]), "+f"(d[39])
      : "r"(a[0]), "r"(a[1]), "r"(a[2]), "r"(a[3]), "l"(descB));
}
__device__ __forceinline__ void mma_rs80_k_z(float (&d)[40], const uint32_t (&a)[4], uint64_t descB) {
  asm volatile("wgmma.mma_async.sync.aligned.m64n80k16.f32.bf16.bf16 {"
      "%0, %1, %2, %3, %4, %5, %6, %7, %8, %9, %10, %11, %12, %13, %14, %15, "
      "%16, %17, %18, %19, %20, %21, %22, %23, %24, %25, %26, %27, %28, %29, %30, %31, "
      "%32, %33, %34, %35, %36, %37, %38, %39"
      "}, {%40, %41, %42, %43}, %44, 0, 1, 1, 0;\n"
      : "=f"(d[0]), "=f"(d[1]), "=f"(d[2]), "=f"(d[3]), "=f"(d[4]), "=f"(d[5]), "=f"(d[6]), "=f"(d[7]),
        "=f"(d[8]), "=f"(d[9]), "=f"(d[10]), "=f"(d[11]), "=f"(d[12]), "=f"(d[13]), "=f"(d[14]), "=f"(d[15]),
        "=f"(d[16]), "=f"(d[17]), "=f"(d[18]), "=f"(d[19]), "=f"(d[20]), "=f"(d[21]), "=f"(d[22]), "=f"(d[23]),
        "=f"(d[24]), "=f"(d[25]), "=f"(d[26]), "=f"(d[27]), "=f"(d[28]), "=f"(d[29]), "=f"(d[30]), "=f"(d[31]),
        "=f"(d[32]), "=f"(d[33]), "=f"(d[34]), "=f"(d[35]), "=f"(d[36]), "=f"(d[37]), "=f"(d[38]), "=f"(d[39])
      : "r"(a[0]), "r"(a[1]), "r"(a[2]), "r"(a[3]), "l"(descB));
}

__device__ __forceinline__ void mma_rs48_k(float (&d)[24], const uint32_t (&a)[4], uint64_t descB) {
  asm volatile("wgmma.mma_async.sync.aligned.m64n48k16.f32.bf16.bf16 {"
      "%0, %1, %2, %3, %4, %5, %6, %7, %8, %9, %10, %11, %12, %13, %14, %15, "
      "%16, %17, %18, %19, %20, %21, %22, %23"
      "}, {%24, %25, %26, %27}, %28, 1, 1, 1, 0;\n"
      : "+f"(d[0]), "+f"(d[1]), "+f"(d[2]), "+f"(d[3]), "+f"(d[4]), "+f"(d[5]), "+f"(d[6]), "+f"(d[7]),
        "+f"(d[8]), "+f"(d[9]), "+f"(d[10]), "+f"(d[11]), "+f"(d[12]), "+f"(d[13]), "+f"(d[14]), "+f"(d[15]),
        "+f"(d[16]), "+f"(d[17]), "+f"(d[18]), "+f"(d[19]), "+f"(d[20]), "+f"(d[21]), "+f"(d[22]), "+f"(d[23])
      : "r"(a[0]), "r"(a[1]), "r"(a[2]), "r"(a[3]), "l"(descB));
}
__device__ __forceinline__ void mma_rs48_k_z(float (&d)[24], const uint32_t (&a)[4], uint64_t descB) {
  asm volatile("wgmma.mma_async.sync.aligned.m64n48k16.f32.bf16.bf16 {"
      "%0, %1, %2, %3, %4, %5, %6, %7, %8, %9, %10, %11, %12, %13, %14, %15, "
      "%16, %17, %18, %19, %20, %21, %22, %23"
      "}, {%24, %25, %26, %27}, %28, 0, 1, 1, 0;\n"
      : "=f"(d[0]), "=f"(d[1]), "=f"(d[2]), "=f"(d[3]), "=f"(d[4]), "=f"(d[5]), "=f"(d[6]), "=f"(d[7]),
        "=f"(d[8]), "=f"(d[9]), "=f"(d[10]), "=f"(d[11]), "=f"(d[12]), "=f"(d[13]), "=f"(d[14]), "=f"(d[15]),
        "=f"(d[16]), "=f"(d[17]), "=f"(d[18]), "=f"(d[19]), "=f"(d[20]), "=f"(d[21]), "=f"(d[22]), "=f"(d[23])
      : "r"(a[0]), "r"(a[1]), "r"(a[2]), "r"(a[3]), "l"(descB));
}

__device__ __forceinline__ void mma_rs160_n(float (&d)[80], const uint32_t (&a)[4], uint64_t descB) {
  asm volatile("wgmma.mma_async.sync.aligned.m64n160k16.f32.bf16.bf16 {"
      "%0, %1, %2, %3, %4, %5, %6, %7, %8, %9, %10, %11, %12, %13, %14, %15, "
      "%16, %17, %18, %19, %20, %21, %22, %23, %24, %25, %26, %27, %28, %29, %30, %31, "
      "%32, %33, %34, %35, %36, %37, %38, %39, %40, %41, %42, %43, %44, %45, %46, %47, "
      "%48, %49, %50, %51, %52, %53, %54, %55, %56, %57, %58, %59, %60, %61, %62, %63, "
      "%64, %65, %66, %67, %68, %69, %70, %71, %72, %73, %74, %75, %76, %77, %78, %79"
      "}, {%80, %81, %82, %83}, %84, 1, 1, 1, 1;\n"
      : "+f"(d[0]), "+f"(d[1]), "+f"(d[2]), "+f"(d[3]), "+f"(d[4]), "+f"(d[5]), "+f"(d[6]), "+f"(d[7]),
        "+f"(d[8]), "+f"(d[9]), "+f"(d[10]), "+f"(d[11]), "+f"(d[12]), "+f"(d[13]), "+f"(d[14]), "+f"(d[15]),
        "+f"(d[16]), "+f"(d[17]), "+f"(d[18]), "+f"(d[19]), "+f"(d[20]), "+f"(d[21]), "+f"(d[22]), "+f"(d[23]),
        "+f"(d[24]), "+f"(d[25]), "+f"(d[26]), "+f"(d[27]), "+f"(d[28]), "+f"(d[29]), "+f"(d[30]), "+f"(d[31]),
        "+f"(d[32]), "+f"(d[33]), "+f"(d[34]), "+f"(d[35]), "+f"(d[36]), "+f"(d[37]), "+f"(d[38]), "+f"(d[39]),
        "+f"(d[40]), "+f"(d[41]), "+f"(d[42]), "+f"(d[43]), "+f"(d[44]), "+f"(d[45]), "+f"(d[46]), "+f"(d[47]),
        "+f"(d[48]), "+f"(d[49]), "+f"(d[50]), "+f"(d[51]), "+f"(d[52]), "+f"(d[53]), "+f"(d[54]), "+f"(d[55]),
        "+f"(d[56]), "+f"(d[57]), "+f"(d[58]), "+f"(d[59]), "+f"(d[60]), "+f"(d[61]), "+f"(d[62]), "+f"(d[63]),
        "+f"(d[64]), "+f"(d[65]), "+f"(d[66]), "+f"(d[67]), "+f"(d[68]), "+f"(d[69]), "+f"(d[70]), "+f"(d[71]),
        "+f"(d[72]), "+f"(d[73]), "+f"(d[74]), "+f"(d[75]), "+f"(d[76]), "+f"(d[77]), "+f"(d[78]), "+f"(d[79])
      : "r"(a[0]), "r"(a[1]), "r"(a[2]), "r"(a[3]), "l"(descB));
}
__device__ __forceinline__ void mma_rs160_n_z(float (&d)[80], const uint32_t (&a)[4], uint64_t descB) {
  asm volatile("wgmma.mma_async.sync.aligned.m64n160k16.f32.bf16.bf16 {"
      "%0, %1, %2, %3, %4, %5, %6, %7, %8, %9, %10, %11, %12, %13, %14, %15, "
      "%16, %17, %18, %19, %20, %21, %22, %23, %24, %25, %26, %27, %28, %29, %30, %31, "
      "%32, %33, %34, %35, %36, %37, %38, %39, %40, %41, %42, %43, %44, %45, %46, %47, "
      "%48, %49, %50, %51, %52, %53, %54, %55, %56, %57, %58, %59, %60, %61, %62, %63, "
      "%64, %65, %66, %67, %68, %69, %70, %71, %72, %73, %74, %75, %76, %77, %78, %79"
      "}, {%80, %81, %82, %83}, %84, 0, 1, 1, 1;\n"
      : "=f"(d[0]), "=f"(d[1]), "=f"(d[2]), "=f"(d[3]), "=f"(d[4]), "=f"(d[5]), "=f"(d[6]), "=f"(d[7]),
        "=f"(d[8]), "=f"(d[9]), "=f"(d[10]), "=f"(d[11]), "=f"(d[12]), "=f"(d[13]), "=f"(d[14]), "=f"(d[15]),
        "=f"(d[16]), "=f"(d[17]), "=f"(d[18]), "=f"(d[19]), "=f"(d[20]), "=f"(d[21]), "=f"(d[22]), "=f"(d[23]),
        "=f"(d[24]), "=f"(d[25]), "=f"(d[26]), "=f"(d[27]), "=f"(d[28]), "=f"(d[29]), "=f"(d[30]), "=f"(d[31]),
        "=f"(d[32]), "=f"(d[33]), "=f"(d[34]), "=f"(d[35]), "=f"(d[36]), "=f"(d[37]), "=f"(d[38]), "=f"(d[39]),
        "=f"(d[40]), "=f"(d[41]), "=f"(d[42]), "=f"(d[43]), "=f"(d[44]), "=f"(d[45]), "=f"(d[46]), "=f"(d[47]),
        "=f"(d[48]), "=f"(d[49]), "=f"(d[50]), "=f"(d[51]), "=f"(d[52]), "=f"(d[53]), "=f"(d[54]), "=f"(d[55]),
        "=f"(d[56]), "=f"(d[57]), "=f"(d[58]), "=f"(d[59]), "=f"(d[60]), "=f"(d[61]), "=f"(d[62]), "=f"(d[63]),
        "=f"(d[64]), "=f"(d[65]), "=f"(d[66]), "=f"(d[67]), "=f"(d[68]), "=f"(d[69]), "=f"(d[70]), "=f"(d[71]),
        "=f"(d[72]), "=f"(d[73]), "=f"(d[74]), "=f"(d[75]), "=f"(d[76]), "=f"(d[77]), "=f"(d[78]), "=f"(d[79])
      : "r"(a[0]), "r"(a[1]), "r"(a[2]), "r"(a[3]), "l"(descB));
}

__device__ __forceinline__ void feature_map(const uint32_t (&P)[2][10], uint32_t (&fr)[10][4]) {
  constexpr float L2E = 1.4426950408889634f;
#pragma unroll
  for (int p = 0; p < 2; p++) {
#pragma unroll
    for (int r = 0; r < 2; r++) {
      uint32_t mx = P[r][5 * p], mn = mx;
#pragma unroll
      for (int g = 1; g < 5; g++) { mx = max_bf2(mx, P[r][5 * p + g]); mn = min_bf2(mn, P[r][5 * p + g]); }
      mx = max_bf2(mx, __shfl_xor_sync(0xffffffffu, mx, 1));
      mn = min_bf2(mn, __shfl_xor_sync(0xffffffffu, mn, 1));
      mx = max_bf2(mx, __shfl_xor_sync(0xffffffffu, mx, 2));
      mn = min_bf2(mn, __shfl_xor_sync(0xffffffffu, mn, 2));
      float mx0 = -bf_lo(mx) * L2E, mx1 = -bf_hi(mx) * L2E, mn0 = bf_lo(mn) * L2E, mn1 = bf_hi(mn) * L2E;
      float ep0[5], ep1[5], en0[5], en1[5];
      float sp0 = 0.f, sp1 = 0.f, sn0 = 0.f, sn1 = 0.f;
#pragma unroll
      for (int g = 0; g < 5; g++) {
        float x0 = bf_lo(P[r][5 * p + g]), x1 = bf_hi(P[r][5 * p + g]);
        ep0[g] = ex2(fmaf(x0, L2E, mx0)); ep1[g] = ex2(fmaf(x1, L2E, mx1));
        en0[g] = ex2(fmaf(x0, -L2E, mn0)); en1[g] = ex2(fmaf(x1, -L2E, mn1));
        sp0 += ep0[g]; sp1 += ep1[g]; sn0 += en0[g]; sn1 += en1[g];
      }
      sp0 += __shfl_xor_sync(0xffffffffu, sp0, 1); sp1 += __shfl_xor_sync(0xffffffffu, sp1, 1);
      sn0 += __shfl_xor_sync(0xffffffffu, sn0, 1); sn1 += __shfl_xor_sync(0xffffffffu, sn1, 1);
      sp0 += __shfl_xor_sync(0xffffffffu, sp0, 2); sp1 += __shfl_xor_sync(0xffffffffu, sp1, 2);
      sn0 += __shfl_xor_sync(0xffffffffu, sn0, 2); sn1 += __shfl_xor_sync(0xffffffffu, sn1, 2);
      sp0 = rcp(sp0); sp1 = rcp(sp1); sn0 = rcp(sn0); sn1 = rcp(sn1);
#pragma unroll
      for (int g = 0; g < 5; g++) {
        fr[5 * p + g][r] = pack_bf16(ep0[g] * sp0, ep1[g] * sp1);
        fr[5 * p + g][2 + r] = pack_bf16(en0[g] * sn0, en1[g] * sn1);
      }
    }
  }
}

template <bool V> struct BoolC { static constexpr bool value = V; };
struct Ring {
  uint32_t idx, phase;
  template <int N> __device__ __forceinline__ void next() { if (++idx == N) { idx = 0; phase ^= 1; } }
};

}

__global__ void __cluster_dims__(2, 1, 1) __launch_bounds__(384, 1)
fused_kernel(const __grid_constant__ Maps maps, const __nv_bfloat16* __restrict__ x, const __nv_bfloat16* __restrict__ wqkv,
             const __nv_bfloat16* __restrict__ wphi, const __nv_bfloat16* __restrict__ w1, const __nv_bfloat16* __restrict__ w2,
             const __nv_bfloat16* __restrict__ w3, const __nv_bfloat16* __restrict__ w4, const __nv_bfloat16* __restrict__ wo,
             const __nv_bfloat16* __restrict__ gate_w, __nv_bfloat16* __restrict__ out) {
  extern __shared__ __align__(1024) uint8_t sgen[];
  const uint32_t sb = smem_u32(sgen);
  const uint32_t sb16 = (sb & 0x3FFFFu) >> 4;
  const uint32_t bars = sb + OFF_BAR;
  const uint32_t fullA = bars + 8 * B_FULLA, emptyA = bars + 8 * B_EMPTYA, fullB = bars + 8 * B_FULLB, emptyB = bars + 8 * B_EMPTYB;

  const int tid = threadIdx.x;
  const int rank = blockIdx.x & 1;
  const int pairIdx = blockIdx.x >> 1;
  const int i = pairIdx >> 2, j = 2 * (pairIdx & 3) + rank;
  const int k3 = (5 * (pairIdx & 3) + 1) >> 1;

  TSTAMP(0);
  auto load_p1_b = [&](int k, uint32_t slot, uint32_t bar) {
    mbar_expect_tx(bar, 40960);
    tma4d(slot + 8192, &maps.qm, bar, 0, 64 * k, 0, j);
    tma3d(slot, &maps.w1m, bar, 0, 64 * k, j);
    tma4d(slot + 32768 + 2048, &maps.qr, bar, 64, 64 * k, 0, j);
    tma3d(slot + 32768, &maps.w1r, bar, 64, 64 * k, j);
  };
  if (tid >= 256) {
    asm volatile("setmaxnreg.dec.sync.aligned.u32 40;");
    if (tid == 256) {
#pragma unroll
      for (int s = 0; s < NA; s++) mbar_init(fullA + 8 * s, 1);
      asm volatile("fence.mbarrier_init.release.cluster;" ::: "memory");
#pragma unroll 1
      for (int u = 0; u < 4; u++) {
        if ((u & 1) == 0) mbar_expect_tx(fullA + 4 * u, SLOT_A);
        tma2d(sb + OFF_A + u * 8192, &maps.x, fullA + 8 * (u >> 1), 64 * (u >> 1), 128 * i + 64 * (u & 1));
      }
    } else if (tid == 288) {
#pragma unroll
      for (int s = 0; s < NB; s++) mbar_init(fullB + 8 * s, 1);
      asm volatile("fence.mbarrier_init.release.cluster;" ::: "memory");
#pragma unroll 1
      for (int k = 0; k < 2; k++) load_p1_b(k, sb + OFF_B + k * SLOT_B, fullB + 8 * k);
    } else if (tid == 320) {
#pragma unroll
      for (int b = B_CS; b < NBAR; b++) mbar_init(bars + 8 * b, b < B_EMPTYB ? 1 : b < B_EMPTYA ? 8 : b < B_X1P ? 16 : 2);
#pragma unroll
      for (int b = B_DSR; b < B_EMPTYB; b++) mbar_expect_tx(bars + 8 * b, 10240);
      asm volatile("fence.mbarrier_init.release.cluster;" ::: "memory");
    }
    __syncwarp();
    asm volatile("barrier.cluster.arrive.relaxed.aligned;" ::: "memory");
    auto get_epoch = [&]() { return *reinterpret_cast<volatile unsigned*>(g_flags + FL_DONE * 32) / NCTA; };
    if (tid >= 320) {
      const int lane = tid & 31, ch = lane % 10, rg = lane / 10;
      const __nv_bfloat16* p = w1 + (size_t)(40 * i + (tid >= 352 ? 20 : 0) + rg) * D_ + 80 * j + 8 * ch;
      const unsigned par = get_epoch() & 1;
      float a[8];
#pragma unroll
      for (int e = 0; e < 8; e++) a[e] = 0.f;
#pragma unroll
      for (int it = 0; it < 7; it++) {
        uint4 v = make_uint4(0, 0, 0, 0);
        if (lane < 30 && 3 * it + rg < 20) v = __ldg(reinterpret_cast<const uint4*>(p + (size_t)it * 3 * D_));
        a[0] += bf_lo(v.x); a[1] += bf_hi(v.x); a[2] += bf_lo(v.y); a[3] += bf_hi(v.y);
        a[4] += bf_lo(v.z); a[5] += bf_hi(v.z); a[6] += bf_lo(v.w); a[7] += bf_hi(v.w);
      }
#pragma unroll
      for (int e = 0; e < 8; e++) a[e] += __shfl_down_sync(0xffffffffu, a[e], 10) + __shfl_down_sync(0xffffffffu, a[e], 20);
      if (lane < 10) {
        float* cd = g_acc[par] + 8 * KV_J + 80 * j + 8 * ch;
        red_add4(cd, a[0], a[1], a[2], a[3]); red_add4(cd + 4, a[4], a[5], a[6], a[7]);
      }
      __syncwarp();
      if (lane == 0) flag_add(FL_CS + j);
      __syncwarp();
    }
    asm volatile("barrier.cluster.wait.aligned;" ::: "memory");
    const int lane = tid & 31, pw = (tid >> 5) & 3;
    if (pw == 0) {
      if (tid == 256) {
        Ring r{2, 1};
        unsigned ep1 = 0;
#pragma unroll 1
        for (int k = 2; k < 25; k++) {
          if (k == 4) ep1 = get_epoch() + 1;
          if (k == 10 || k == 17) {
            if (k == 10) mbar_wait(bars + 8 * B_HST, 0);
            flag_wait(k == 10 ? FL_H + 2 * i + rank : FL_X1 + i, ep1 * 8u);
            TSTAMPX(k == 10 ? 29 : 30);
          }
          if (k == 15) mbar_wait(bars + 8 * B_X1P, 0);
          mbar_wait(emptyA + 8 * r.idx, r.phase);
          const uint32_t bar = fullA + 8 * r.idx, slot = sb + OFF_A + r.idx * SLOT_A;
          mbar_expect_tx(bar, SLOT_A);
          if (k >= 10 && k < 15) tma2d(slot, &maps.hs, bar, 64 * (k - 10) + 320 * rank, 128 * i);
          else tma2d_mc(slot + rank * 8192, k < 10 ? &maps.x : &maps.x1, bar, 64 * (k < 10 ? k : (k - 15 + k3) % 10), 128 * i + 64 * rank);
          r.next<NA>();
        }
      }
    } else if (pw == 1) {
      if (tid == 288) {
        Ring r{2, 1};
#pragma unroll 1
        for (int k = 2; k < 18; k++) {
          mbar_wait(emptyB + 8 * r.idx, r.phase);
          const uint32_t bar = fullB + 8 * r.idx, slot = sb + OFF_B + r.idx * SLOT_B;
          if (k < 10) {
            load_p1_b(k, slot, bar);
          } else if (k < 13) {
            mbar_expect_tx(bar, k < 12 ? 40960 : 20480);
            tma3d(slot, &maps.w2, bar, 0, 320 * rank + 128 * (k - 10), 5 * (j >> 1));
            if (k < 12) tma3d(slot + 20480, &maps.w2, bar, 0, 320 * rank + 128 * (k - 10) + 64, 5 * (j >> 1));
          } else {
            mbar_expect_tx(bar, 49152);
            tma3d(slot, &maps.w3, bar, 0, 64 * ((2 * (k - 13) + k3) % 10), 3 * j);
            tma3d(slot + 24576, &maps.w3, bar, 0, 64 * ((2 * (k - 13) + 1 + k3) % 10), 3 * j);
          }
          r.next<NB>();
        }
        Ring r4{0, 1};
#pragma unroll 1
        for (int n = 0; n < 16; n++) {
          if (n == 0 || n == 1 || n == 3) { mbar_wait(emptyB + 8 * r.idx, r.phase); r.next<NB>(); }
          mbar_wait(bars + 8 * (B_EMPTY4 + r4.idx), r4.phase);
          const uint32_t bar = bars + 8 * (B_FULL4 + r4.idx), slot = sb + OFF_B + r4.idx * UNIT4;
          const int u = n & 3, m = ((j >> 1) + 1 + (n >> 2)) & 3;
          mbar_expect_tx(bar, u == 3 ? 25600 : 20480);
          tma3d(slot, u == 3 ? &maps.wo : &maps.w4, bar, 0, u == 3 ? 80 * j : 192 * j + 64 * u, 5 * m);
          r4.next<NU4>();
        }
      }
    } else {
      const unsigned epoch = get_epoch();
      float* accg = g_acc[epoch & 1];
      if (pw == 2) {
        {
          float* nxt = g_acc[(epoch + 1) & 1];
          constexpr int PER = ACC_FLOATS / NCTA;
#pragma unroll 1
          for (int e = lane; e < PER; e += 32) nxt[blockIdx.x * PER + e] = 0.f;
        }
        if (tid == 320) {
          flag_wait(FL_CS + j, (epoch + 1) * 32u);
          flag_wait(FL_ST + i, (epoch + 1) * 8u);
          fence_async_glb();
          *reinterpret_cast<volatile uint32_t*>(sgen + OFF_BAR + 8 * NBAR) = (epoch + 1) & 1;
          mbar_expect_tx(bars + 8 * B_CS, 320 + 2048);
          bulk_load(sb + OFF_CS, accg + 8 * KV_J + 80 * j, 320, bars + 8 * B_CS);
          bulk_load(sb + OFF_XST, g_xstat + 128 * i, 2048, bars + 8 * B_CS);
          TSTAMPX(21);
          l2_prefetch(w2 + (size_t)blockIdx.x * (D_ * D_ / NCTA), D_ * D_ * 2 / NCTA);
          flag_wait(FL_H + 2 * i + rank, (epoch + 1) * 8u);
          l2_prefetch(w3 + (size_t)blockIdx.x * (F_ * D_ / NCTA), F_ * D_ * 2 / NCTA);
          l2_prefetch(w4 + (size_t)blockIdx.x * (F_ * D_ / NCTA), F_ * D_ * 2 / NCTA);
          l2_prefetch(wo + (size_t)blockIdx.x * (D_ * D_ / NCTA), D_ * D_ * 2 / NCTA);
          flag_wait(FL_KV + j, (epoch + 1) * 16u);
          mbar_expect_tx(bars + 8 * B_KV, KV_J * 4);
          bulk_load(sb + OFF_MISC, accg + j * KV_J, KV_J * 4, bars + 8 * B_KV);
          TSTAMPX(22);
        }
        __syncwarp();
#pragma unroll 1
        for (int m = 0; m < 6; m++) {
          const int col = 192 * j + 32 * m + 8 * (lane & 3);
          const __nv_bfloat16* p = w3 + (size_t)(40 * i + (lane >> 2) * 5) * F_ + col;
          float a[8];
#pragma unroll
          for (int e = 0; e < 8; e++) a[e] = 0.f;
#pragma unroll
          for (int it = 0; it < 5; it++) {
            const uint4 v = __ldg(reinterpret_cast<const uint4*>(p + (size_t)it * F_));
            a[0] += bf_lo(v.x); a[1] += bf_hi(v.x); a[2] += bf_lo(v.y); a[3] += bf_hi(v.y);
            a[4] += bf_lo(v.z); a[5] += bf_hi(v.z); a[6] += bf_lo(v.w); a[7] += bf_hi(v.w);
          }
#pragma unroll
          for (int e = 0; e < 4; e++) {
            const float snd = (lane & 4) ? a[e] : a[e + 4], keep = (lane & 4) ? a[e + 4] : a[e];
            a[e] = keep + __shfl_xor_sync(0xffffffffu, snd, 4);
            a[e] += __shfl_xor_sync(0xffffffffu, a[e], 8);
            a[e] += __shfl_xor_sync(0xffffffffu, a[e], 16);
          }
          if (lane < 8) red_add4(accg + 8 * KV_J + D_ + col + (lane >> 2) * 4, a[0], a[1], a[2], a[3]);
        }
        __syncwarp();
        if (tid == 320) {
          flag_add(FL_CS3 + j);
          flag_wait(FL_S1 + i, (epoch + 1) * 8u);
          flag_wait(FL_CS3 + j, (epoch + 1) * 16u);
          fence_async_glb();
          mbar_expect_tx(bars + 8 * B_ST1, 8192 + 768);
          bulk_load(sb + OFF_CS + 320, accg + 8 * KV_J + D_ + 192 * j, 768, bars + 8 * B_ST1);
          bulk_load(sb + OFF_MISC, g_st1 + 128 * i * 8, 8192, bars + 8 * B_ST1);
        }
      }
      if (tid == 352) {
        mbar_wait(bars + 8 * B_SIGP, 0);
        flag_add(FL_ST + i);
        TSTAMPX(20);
        mbar_expect_tx(bars + 8 * B_XR, 20480);
#pragma unroll 1
        for (int u = 0; u < 8; u++)
          tma2d(sb + OFF_B + (u / 3) * SLOT_B + SPARE + (u % 3) * 2560, &maps.xr, bars + 8 * B_XR, 80 * j, 128 * i + 16 * u);
        const int shift = (j < 2) ? 1 : (j < 4) ? -1 : (j < 6) ? 2 : -2;
        if ((shift > 0 && i == 0) || (shift < 0 && i == 15)) {
          const int nz = shift > 0 ? shift : -shift, zr = shift > 0 ? 0 : S_ - nz;
#pragma unroll 1
          for (int e = 0; e < nz * 10; e++)
            reinterpret_cast<uint4*>(g_Hs + (size_t)(2 + zr + e / 10) * D_ + 80 * j)[e % 10] = make_uint4(0, 0, 0, 0);
          fence_async_glb();
        }
        prefetch_tmap(&maps.st_h); prefetch_tmap(&maps.st_x1); prefetch_tmap(&maps.hs); prefetch_tmap(&maps.x1);
        prefetch_tmap(&maps.w2); prefetch_tmap(&maps.w3); prefetch_tmap(&maps.w4); prefetch_tmap(&maps.wo);
        mbar_wait(bars + 8 * B_SIGH, 0);
        TSTAMPX(23);
        tma2d_store(&maps.st_h, sb + OFF_STG, 80 * j, 128 * i + 2 + shift);
        bulk_commit(); bulk_wait<0>();
        mbar_arrive(bars + 8 * B_HST);
        flag_add(FL_H + 2 * i + (j >> 2));
        flag_add_relaxed(FL_H + 2 * ((i + (shift > 0 ? 1 : -1)) & 15) + (j >> 2));
        TSTAMPX(24);
        mbar_wait(bars + 8 * B_SIGKV, 0);
        TSTAMPX(25);
        fence_async_smem();
        asm volatile("cp.reduce.async.bulk.global.shared::cta.bulk_group.add.f32 [%0], [%1], %2;"
                     ::"l"(accg + j * KV_J), "r"(sb + OFF_MISC), "r"(KV_J * 4) : "memory");
        bulk_commit(); bulk_wait<0>();
        flag_add(FL_KV + j);
        TSTAMPX(26);
        mbar_wait(bars + 8 * B_SIGX1, 0);
        TSTAMPX(27);
        tma2d_store(&maps.st_x1, sb + OFF_STG, 80 * j, 128 * i);
        bulk_commit(); bulk_wait<0>();
        flag_add(FL_X1 + i);
        mbar_arrive_cta(bars + 8 * B_X1P, 0); mbar_arrive_cta(bars + 8 * B_X1P, 1);
        TSTAMPX(28);
        mbar_wait(bars + 8 * B_MFREE, 0);
        flag_add(FL_S1 + i);
      }
    }
  } else {
    uint4 pv[5], pw_[5], pre;
    {
      const int row = 128 * i + 16 * j + (tid >> 4), l16 = tid & 15;
#pragma unroll
      for (int c = 0; c < 5; c++) pv[c] = __ldg(reinterpret_cast<const uint4*>(x + (size_t)row * D_ + c * 128 + l16 * 8));
      pre = __ldg(reinterpret_cast<const uint4*>(wphi + (size_t)j * 1600) + (tid < 200 ? tid : 0));
#pragma unroll
      for (int c = 0; c < 5; c++) pw_[c] = __ldg(reinterpret_cast<const uint4*>(gate_w + c * 128 + l16 * 8));
    }
    asm volatile("barrier.cluster.arrive.relaxed.aligned;" ::: "memory");
    asm volatile("setmaxnreg.inc.sync.aligned.u32 232;");
    const int wg = tid >> 7, warp = tid >> 5, lane = tid & 31, t = lane & 3;
    const int rloc = warp * 16 + (lane >> 2);
    const float* s_cs = reinterpret_cast<const float*>(sgen + OFF_CS);
    auto signal = [&](int b) {
      __syncwarp();
      if (lane == 0) mbar_arrive(bars + 8 * b);
    };
    auto releaseB = [&](uint32_t bar) {
      __syncwarp();
      if (lane == 0) mbar_arrive(bar);
    };
    auto release = [&](uint32_t bar) {
      __syncwarp();
      if (lane < 2) mbar_arrive_cta(bar, lane);
    };
    const uint32_t stg_lane = (warp * 16 + ((lane >> 3) & 1) * 8 + (lane & 7)) * 160 + (lane >> 4) * 16;

    auto stage_tile = [&](uint32_t stg, const uint32_t (&v)[2][10]) {
#pragma unroll
      for (int s = 0; s < 5; s++) stsm4(stg + stg_lane + s * 32, v[0][2 * s], v[1][2 * s], v[0][2 * s + 1], v[1][2 * s + 1]);
    };

    {
#pragma unroll 1
      for (int e = tid; e < 800; e += 256) sts128(sb + OFF_MISC + e * 16, make_uint4(0, 0, 0, 0));
      bar_sync(1, 256);
      float f[40];
      float s = 0.f, gs = 0.f;
#pragma unroll
      for (int c = 0; c < 5; c++) {
        const uint32_t vv[4] = {pv[c].x, pv[c].y, pv[c].z, pv[c].w}, ww[4] = {pw_[c].x, pw_[c].y, pw_[c].z, pw_[c].w};
#pragma unroll
        for (int e = 0; e < 4; e++) {
          f[8 * c + 2 * e] = bf_lo(vv[e]); f[8 * c + 2 * e + 1] = bf_hi(vv[e]);
          s += f[8 * c + 2 * e] + f[8 * c + 2 * e + 1];
          gs = fmaf(f[8 * c + 2 * e], bf_lo(ww[e]), gs); gs = fmaf(f[8 * c + 2 * e + 1], bf_hi(ww[e]), gs);
        }
      }
#pragma unroll
      for (int o = 1; o < 16; o <<= 1) { s += __shfl_xor_sync(0xffffffffu, s, o); gs += __shfl_xor_sync(0xffffffffu, gs, o); }
      const float mean = s * (1.f / D_);
      float q = 0.f;
#pragma unroll
      for (int e = 0; e < 40; e++) { const float d = f[e] - mean; q = fmaf(d, d, q); }
#pragma unroll
      for (int o = 1; o < 16; o <<= 1) q += __shfl_xor_sync(0xffffffffu, q, o);
      const float rstd = rsqrtf(q * (1.f / D_) + 1e-5f);
      asm volatile("barrier.cluster.wait.aligned;" ::: "memory");
      if ((tid & 15) == 0) g_xstat[128 * i + 16 * j + (tid >> 4)] = make_float4(rstd, -mean, rcp(1.f + __expf(-gs)), 0.f);
      signal(B_SIGP);
      if (tid < 200) {
        const uint32_t ww[4] = {pre.x, pre.y, pre.z, pre.w};
        const int h = tid / 50;
#pragma unroll
        for (int e = 0; e < 8; e++) {
          const int idx = tid * 8 + e, k = idx / 20, ff = idx - 20 * k;
          const int n = 40 * (h >> 1) + 8 * (ff >> 2) + 2 * (ff & 3) + (h & 1);
          const int off = (k >> 4) * 2560 + n * 32 + ((((k >> 3) ^ (n >> 2)) & 1) << 4) + (k & 7) * 2;
          *reinterpret_cast<unsigned short*>(sgen + OFF_MISC + off) = (unsigned short)(ww[e >> 1] >> ((e & 1) * 16));
        }
      }
    }
    TSTAMP(1);

    Ring ra{0, 0}, rb{0, 0};
    uint32_t qp[2][10], P[2][10];
    float st_g[2];
    {
      float accM[128], accR[32];
      uint32_t pa = 0, pb = 0;
#pragma unroll 1
      for (int k = 0; k < 10; k++) {
        mbar_wait(fullA + 8 * ra.idx, ra.phase);
        if (tid == 0) TRACE(32 + k);
        mbar_wait(fullB + 8 * rb.idx, rb.phase);
        if (tid == 0) TRACE(64 + k);
        if (k == 0) TSTAMP(2);
        const uint32_t a0 = sb16 + ((OFF_A + ra.idx * SLOT_A + wg * 8192) >> 4), b0 = sb16 + ((OFF_B + rb.idx * SLOT_B) >> 4);
        wg_fence();
#pragma unroll
        for (int kk = 0; kk < 4; kk++) {
          const uint64_t da = make_desc(a0, kk * 32, 16, 1024, 1);
          if (kk == 0) {
            mma_ss256_p(accM, da, make_desc(b0, 0, 8192, 1024, 1), k);
            mma_ss64_p(accR, da, make_desc(b0, 32768, 2048, 256, 3), k);
          } else {
            mma_ss256(accM, da, make_desc(b0, kk * 2048, 8192, 1024, 1));
            mma_ss64(accR, da, make_desc(b0, 32768 + kk * 512, 2048, 256, 3));
          }
          if (kk == 0) {
            wg_commit();
            if (k > 0) {
              wg_wait<1>();
              if (k - 1 < 8) release(emptyA + 8 * pa);
              releaseB(emptyB + 8 * pb);
            }
          }
        }
        wg_commit();
        pa = ra.idx; pb = rb.idx;
        ra.next<NA>(); rb.next<NB>();
      }
      TSTAMP(18);
      float st_rstd[2], st_mr[2];
      mbar_wait(bars + 8 * B_CS, 0);
#pragma unroll
      for (int r = 0; r < 2; r++) {
        const uint4 st = lds128(sb + OFF_XST + (rloc + 8 * r) * 16);
        st_rstd[r] = __uint_as_float(st.x); st_mr[r] = __uint_as_float(st.y); st_g[r] = __uint_as_float(st.z);
      }
      TSTAMP(19);
      wg_wait<0>();
      fence_regs(accM); fence_regs(accR);
      TSTAMP(3);
#define ACC(P_, G, I_) ((G) < 8 ? accM[(P_) * 32 + ((G) & 7) * 4 + (I_)] : accR[(P_) * 8 + ((G) & 1) * 4 + (I_)])
      {
        uint32_t hv[2][10];
        const GeluC g0 = gelu_consts(st_rstd[0], 1.f), g1 = gelu_consts(st_rstd[1], 1.f);
#pragma unroll
        for (int g = 0; g < 10; g++) {
          const float2 cs = *reinterpret_cast<const float2*>(s_cs + 8 * g + 2 * t);
          const float v0 = gelu_s(fmaf(st_mr[0], cs.x, ACC(0, g, 0)), g0), v1 = gelu_s(fmaf(st_mr[0], cs.y, ACC(0, g, 1)), g0);
          const float v2 = gelu_s(fmaf(st_mr[1], cs.x, ACC(0, g, 2)), g1), v3 = gelu_s(fmaf(st_mr[1], cs.y, ACC(0, g, 3)), g1);
          hv[0][g] = pack_bf16(v0, v1); hv[1][g] = pack_bf16(v2, v3);
        }
        fence_async_smem();
        bar_sync(1, 256);
        stage_tile(sb + OFF_STG, hv);
        fence_async_smem();
        signal(B_SIGH);
      }
      TSTAMP(4);
      uint32_t kf[5][4], qf[5][4];
#pragma unroll
      for (int s = 0; s < 5; s++) {
        kf[s][0] = pack_bf16(ACC(2, 2 * s, 0), ACC(2, 2 * s, 1)); kf[s][1] = pack_bf16(ACC(2, 2 * s, 2), ACC(2, 2 * s, 3));
        kf[s][2] = pack_bf16(ACC(2, 2 * s + 1, 0), ACC(2, 2 * s + 1, 1)); kf[s][3] = pack_bf16(ACC(2, 2 * s + 1, 2), ACC(2, 2 * s + 1, 3));
        qf[s][0] = pack_bf16(ACC(1, 2 * s, 0), ACC(1, 2 * s, 1)); qf[s][1] = pack_bf16(ACC(1, 2 * s, 2), ACC(1, 2 * s, 3));
        qf[s][2] = pack_bf16(ACC(1, 2 * s + 1, 0), ACC(1, 2 * s + 1, 1)); qf[s][3] = pack_bf16(ACC(1, 2 * s + 1, 2), ACC(1, 2 * s + 1, 3));
      }
      float pk[40], pq[40];
      wg_fence();
#pragma unroll
      for (int s = 0; s < 5; s++) {
        if (s == 0) mma_rs80_k_z(pk, kf[s], make_desc(sb16, OFF_MISC, 16, 256, 3));
        else mma_rs80_k(pk, kf[s], make_desc(sb16, OFF_MISC + s * 2560, 16, 256, 3));
      }
      wg_commit();
#pragma unroll
      for (int s = 0; s < 5; s++) {
        if (s == 0) mma_rs80_k_z(pq, qf[s], make_desc(sb16, OFF_MISC, 16, 256, 3));
        else mma_rs80_k(pq, qf[s], make_desc(sb16, OFF_MISC + s * 2560, 16, 256, 3));
      }
      wg_commit();
      {
        const int mat = lane >> 3;
        const int tok = warp * 16 + (mat & 1) * 8 + (lane & 7);
        const uint32_t ones = (t == 0) ? 0x00003f80u : 0u;
        __syncwarp();
#pragma unroll
        for (int p = 0; p < 2; p++) {
          const uint32_t rowa = sb + OFF_A + p * SLOT_A + tok * 128;
#pragma unroll
          for (int gg = 0; gg < 3; gg++) {
            const int g0 = 5 * p + 2 * gg;
            uint32_t r0 = pack_bf16(ACC(3, g0, 0), ACC(3, g0, 1)), r1 = pack_bf16(ACC(3, g0, 2), ACC(3, g0, 3));
            uint32_t r2 = ones, r3 = ones;
            if (gg < 2) { r2 = pack_bf16(ACC(3, g0 + 1, 0), ACC(3, g0 + 1, 1)); r3 = pack_bf16(ACC(3, g0 + 1, 2), ACC(3, g0 + 1, 3)); }
            stsm4(rowa + (((2 * gg + (mat >> 1)) ^ (tok & 7)) << 4), r0, r1, r2, r3);
          }
        }
      }
#undef ACC
      wg_wait<1>();
      fence_regs(pk);
#pragma unroll
      for (int G = 0; G < 10; G++) {
        P[0][G] = pack_bf16(pk[4 * G], pk[4 * G + 1]); P[1][G] = pack_bf16(pk[4 * G + 2], pk[4 * G + 3]);
      }
      wg_wait<0>();
      fence_regs(pq);
#pragma unroll
      for (int G = 0; G < 10; G++) {
        qp[0][G] = pack_bf16(pq[4 * G], pq[4 * G + 1]); qp[1][G] = pack_bf16(pq[4 * G + 2], pq[4 * G + 3]);
      }
    }

    uint32_t fr[10][4];
    uint32_t xv[2][10];
#pragma unroll
    for (int g = 0; g < 10; g++) xv[0][g] = xv[1][g] = 0u;
    int pass;
    pass = gridDim.y;
#pragma unroll 1
    do {
    feature_map(P, fr);
    if (pass != 0) {
    {
      const int mat = lane >> 3;
      const int tok = warp * 16 + (mat & 1) * 8 + (lane & 7);
      const uint32_t base = sb + OFF_B + tok * 32 + (((mat >> 1) ^ ((tok >> 2) & 1)) << 4);
#pragma unroll
      for (int G = 0; G < 10; G++) stsm4(base + G * 4096, fr[G][0], fr[G][1], fr[G][2], fr[G][3]);
      fence_async_smem();
      bar_sync(1, 256);
      float kv[40];
      const uint32_t va = sb16 + ((OFF_A + wg * SLOT_A) >> 4), vb = sb16 + ((OFF_B + wg * 20480) >> 4);
      wg_fence();
#pragma unroll
      for (int ks = 0; ks < 8; ks++) {
        if (ks == 0) mma_ss80_tt_z(kv, make_desc(va, 0, 16, 1024, 1), make_desc(vb, 0, 4096, 256, 3));
        else mma_ss80_tt(kv, make_desc(va, ks * 2048, 16, 1024, 1), make_desc(vb, ks * 512, 4096, 256, 3));
      }
      wg_commit();
      {
        mbar_wait(bars + 8 * B_XR, 0);
        const uint32_t xa = sb + OFF_B + (warp / 3) * SLOT_B + SPARE + (warp % 3) * 2560 + (lane >> 2) * 160 + t * 4;
#pragma unroll
        for (int g = 0; g < 10; g++) { xv[0][g] = lds32(xa + g * 16); xv[1][g] = lds32(xa + 1280 + g * 16); }
      }
      float acc[80];
      TSTAMP(5);
      mbar_wait(fullA + 8 * 2, 0);
      mbar_wait(fullB + 8 * 1, 1);
      TSTAMP(6);
      wg_fence();
#pragma unroll
      for (int kk = 0; kk < 4; kk++) {
        const uint64_t da = make_desc(sb16 + wg * 512, OFF_A + 2 * SLOT_A + kk * 32, 16, 1024, 1);
        const uint64_t db = make_desc(sb16, OFF_B + SLOT_B + kk * 1024, 4096, 512, 2);
        if (kk == 0) mma_ss160_z(acc, da, db); else mma_ss160(acc, da, db);
      }
      wg_commit();
      ra.next<NA>();
      wg_wait<1>();
      fence_regs(kv);
      TSTAMP(31);
      release(emptyA); release(emptyA + 8); releaseB(emptyB); release(bars + 8 * B_PEER2);
      const uint32_t dst = sb + OFF_MISC + wg * (KV_PAIR * 4);
      const int m0 = (warp & 3) * 16 + (lane >> 2);
#pragma unroll
      for (int r = 0; r < 2; r++) {
        const int m = m0 + 8 * r;
        const bool hi = m >= 20;
        uint32_t v[10];
#pragma unroll
        for (int G = 0; G < 10; G++) v[G] = __float_as_uint(hi ? kv[4 * G + 2 * r + 1] : kv[4 * G + 2 * r]);
        const uint32_t p = dst + 4 * (m < 40 ? m * 48 + t * 12 : 1920 + t * 24 + 12);
        if (m <= 40) {
          sts128(p, make_uint4(v[0], v[1], v[2], v[3])); sts128(p + 16, make_uint4(v[4], v[5], v[6], v[7]));
          sts128(p + 32, make_uint4(v[8], v[9], 0u, 0u));
        }
      }
      if (m0 == 32) {
        const uint32_t p = dst + 4 * (1920 + t * 24);
        sts128(p, make_uint4(__float_as_uint(kv[2]), __float_as_uint(kv[6]), __float_as_uint(kv[10]), __float_as_uint(kv[14])));
        sts128(p + 16, make_uint4(__float_as_uint(kv[18]), __float_as_uint(kv[22]), __float_as_uint(kv[26]), __float_as_uint(kv[30])));
        sts128(p + 32, make_uint4(__float_as_uint(kv[34]), __float_as_uint(kv[38]), 0u, 0u));
      }
      signal(B_SIGKV);
      uint32_t pa = 2, pb = 1;
#pragma unroll 1
      for (int k = 1; k < 5; k++) {
        mbar_wait(fullA + 8 * ra.idx, ra.phase);
        if ((k & 1) == 0) mbar_wait(fullB + 8 * rb.idx, rb.phase);
        const uint32_t a0 = sb16 + ((OFF_A + ra.idx * SLOT_A + wg * 8192) >> 4);
        const uint32_t b0 = sb16 + ((OFF_B + rb.idx * SLOT_B + (k & 1) * 20480) >> 4);
        wg_fence();
#pragma unroll
        for (int kk = 0; kk < 4; kk++) {
          mma_ss160(acc, make_desc(a0, kk * 32, 16, 1024, 1), make_desc(b0, kk * 1024, 4096, 512, 2));
          if (kk == 0) {
            wg_commit();
            wg_wait<1>();
            release(emptyA + 8 * pa);
            if ((k & 1) == 0) releaseB(emptyB + 8 * pb);
          }
        }
        wg_commit();
        pa = ra.idx; pb = rb.idx;
        ra.next<NA>();
        if ((k & 1) || k == 4) rb.next<NB>();
      }
      mbar_wait(bars + 8 * B_PEER2, 0);
      wg_wait<0>();
      fence_regs(acc);
      release(emptyA + 8 * pa);
      TSTAMP(7);
      {
        uint32_t sn[20];
        if (rank) {
#pragma unroll
          for (int e = 0; e < 20; e++) sn[e] = pack_bf16(acc[2 * e], acc[2 * e + 1]);
#pragma unroll
          for (int e = 0; e < 40; e++) acc[e] = acc[40 + e];
        } else {
#pragma unroll
          for (int e = 0; e < 20; e++) sn[e] = pack_bf16(acc[40 + 2 * e], acc[41 + 2 * e]);
        }
        const uint32_t peer = map_peer(sb, rank ^ 1);
#pragma unroll
        for (int q = 0; q < 5; q++)
          st_async16(peer + OFF_B + 20480 + tid * 16 + q * 4096, sn[4 * q], sn[4 * q + 1], sn[4 * q + 2], sn[4 * q + 3],
                     peer + OFF_BAR + 8 * (B_DSR + 8 + wg));
#pragma unroll
        for (int g = 0; g < 10; g++) {
          acc[4 * g] += bf_lo(xv[0][g]); acc[4 * g + 1] += bf_hi(xv[0][g]);
          acc[4 * g + 2] += bf_lo(xv[1][g]); acc[4 * g + 3] += bf_hi(xv[1][g]);
        }
        bar_sync(1, 256);
        mbar_wait(bars + 8 * (B_DSR + 8 + wg), 0);
#pragma unroll
        for (int q = 0; q < 5; q++) {
          const uint4 v = lds128(sb + OFF_B + 20480 + tid * 16 + q * 4096);
          xv[0][2 * q] = pack_bf16(acc[8 * q] + bf_lo(v.x), acc[8 * q + 1] + bf_hi(v.x));
          xv[1][2 * q] = pack_bf16(acc[8 * q + 2] + bf_lo(v.y), acc[8 * q + 3] + bf_hi(v.y));
          xv[0][2 * q + 1] = pack_bf16(acc[8 * q + 4] + bf_lo(v.z), acc[8 * q + 5] + bf_hi(v.z));
          xv[1][2 * q + 1] = pack_bf16(acc[8 * q + 6] + bf_lo(v.w), acc[8 * q + 7] + bf_hi(v.w));
        }
        releaseB(emptyB + 8 * pb);
      }
      TSTAMP(16);
      stage_tile(sb + OFF_STG, xv);
      fence_async_smem();
      signal(B_SIGX1);
      TSTAMP(17);
#pragma unroll
      for (int r = 0; r < 2; r++) {
        float s = 0.f;
#pragma unroll
        for (int g = 0; g < 10; g++) {
          acc[4 * g + 2 * r] = bf_lo(xv[r][g]); acc[4 * g + 2 * r + 1] = bf_hi(xv[r][g]);
          s += acc[4 * g + 2 * r] + acc[4 * g + 2 * r + 1];
        }
        s += __shfl_xor_sync(0xffffffffu, s, 1); s += __shfl_xor_sync(0xffffffffu, s, 2);
        const float mu = s * (1.f / 80.f);
        float q = 0.f;
#pragma unroll
        for (int g = 0; g < 10; g++) {
          const float d0 = acc[4 * g + 2 * r] - mu, d1 = acc[4 * g + 2 * r + 1] - mu;
          q = fmaf(d0, d0, q); q = fmaf(d1, d1, q);
        }
        q += __shfl_xor_sync(0xffffffffu, q, 1); q += __shfl_xor_sync(0xffffffffu, q, 2);
        if (t == 0) g_st1[(128 * i + rloc + 8 * r) * 8 + j] = make_float2(mu, q);
      }
    }
    TSTAMP(8);
#pragma unroll
    for (int G = 0; G < 10; G++) { P[0][G] = qp[0][G]; P[1][G] = qp[1][G]; }
    }
    asm volatile("" : "+r"(pass));
    } while (pass-- != 0);

    uint32_t of[5][4];
    {
      mbar_wait(bars + 8 * B_KV, 0);
      uint4 kvr[2][3];
#pragma unroll
      for (int u = 0; u < 2; u++) {
        const int it = tid + 256 * u, p = it / 192, rem = it - 192 * p, n = rem >> 2, tq = rem & 3;
        const uint32_t sp = sb + OFF_MISC + 4 * (p * KV_PAIR + (n < 40 ? n * 48 + tq * 12 : 1920 + tq * 24 + (n & 1) * 12));
        if (it < 384) { kvr[u][0] = lds128(sp); kvr[u][1] = lds128(sp + 16); kvr[u][2] = lds128(sp + 32); }
      }
      bar_sync(1, 256);
#pragma unroll
      for (int u = 0; u < 2; u++) {
        const int it = tid + 256 * u, p = it / 192, rem = it - 192 * p, n = rem >> 2, tq = rem & 3;
        const int sh = (n < 40 ? (n >= 20) : (n & 1)) * 16;
        const uint32_t v[10] = {kvr[u][0].x, kvr[u][0].y, kvr[u][0].z, kvr[u][0].w, kvr[u][1].x, kvr[u][1].y, kvr[u][1].z, kvr[u][1].w, kvr[u][2].x, kvr[u][2].y};
        uint8_t* dst = sgen + OFF_MISC + p * 7680 + n * 32 + tq * 4;
        const int sw = ((n >> 2) & 1) << 4;
        if (it < 384) {
#pragma unroll
          for (int G = 0; G < 10; G++)
            *reinterpret_cast<uint32_t*>(dst + (G >> 1) * 1536 + (((G & 1) << 4) ^ sw)) = pack_bf16(__uint_as_float(v[G]), 0.f) << sh;
        }
      }
      fence_async_smem();
      bar_sync(1, 256);
      float o0[24], o1[24];
      wg_fence();
#pragma unroll
      for (int g = 0; g < 5; g++) {
        if (g == 0) mma_rs48_k_z(o0, fr[g], make_desc(sb16, OFF_MISC, 16, 256, 3));
        else mma_rs48_k(o0, fr[g], make_desc(sb16, OFF_MISC + g * 1536, 16, 256, 3));
      }
#pragma unroll
      for (int g = 0; g < 5; g++) {
        if (g == 0) mma_rs48_k_z(o1, fr[5], make_desc(sb16, OFF_MISC + 7680, 16, 256, 3));
        else mma_rs48_k(o1, fr[5 + g], make_desc(sb16, OFF_MISC + 7680 + g * 1536, 16, 256, 3));
      }
      wg_commit();
      wg_wait<0>();
      fence_regs(o0); fence_regs(o1);
      signal(B_MFREE);
#pragma unroll
      for (int r = 0; r < 2; r++) {
        const float a0 = __fdividef(st_g[r], o0[20 + 2 * r] + 1e-6f), a1 = __fdividef(st_g[r], o0[21 + 2 * r] + 1e-6f);
        const float b0 = __fdividef(st_g[r], o1[20 + 2 * r] + 1e-6f), b1 = __fdividef(st_g[r], o1[21 + 2 * r] + 1e-6f);
        const float am = t < 2 ? a0 : a1, bm = t < 2 ? b0 : b1;
#pragma unroll
        for (int g = 0; g < 5; g++) {
          const float sa = g < 2 ? a0 : (g == 2 ? am : a1), sb2 = g < 2 ? b0 : (g == 2 ? bm : b1);
          of[g >> 1][(g & 1) * 2 + r] = pack_bf16(o0[4 * g + 2 * r] * sa, o0[4 * g + 2 * r + 1] * sa);
          of[(5 + g) >> 1][((5 + g) & 1) * 2 + r] = pack_bf16(o1[4 * g + 2 * r] * sb2, o1[4 * g + 2 * r + 1] * sb2);
        }
      }
    }
    TSTAMP(9);

    uint32_t hf[12][4];
    {
      float acc[96];
      uint32_t pa = 0, pb = 0;
#pragma unroll 1
      for (int k = 0; k < 10; k++) {
        mbar_wait(fullA + 8 * ra.idx, ra.phase);
        if (tid == 0) TRACE(52 + k);
        if ((k & 1) == 0) mbar_wait(fullB + 8 * rb.idx, rb.phase);
        if (tid == 0) TRACE(84 + k);
        if (k == 0) TSTAMP(10);
        const uint32_t a0 = sb16 + ((OFF_A + ra.idx * SLOT_A + wg * 8192) >> 4);
        const uint32_t b0 = sb16 + ((OFF_B + rb.idx * SLOT_B + (k & 1) * 24576) >> 4);
        wg_fence();
#pragma unroll
        for (int kk = 0; kk < 4; kk++) {
          if (kk == 0) mma_ss192_p(acc, make_desc(a0, 0, 16, 1024, 1), make_desc(b0, 0, 8192, 1024, 1), k);
          else mma_ss192(acc, make_desc(a0, kk * 32, 16, 1024, 1), make_desc(b0, kk * 2048, 8192, 1024, 1));
          if (kk == 0) {
            wg_commit();
            if (k > 0) {
              wg_wait<1>();
              release(emptyA + 8 * pa);
              if ((k & 1) == 0) releaseB(emptyB + 8 * pb);
            }
          }
        }
        wg_commit();
        pa = ra.idx; pb = rb.idx;
        ra.next<NA>();
        if (k & 1) rb.next<NB>();
      }
      float rs[2], mm[2];
      mbar_wait(bars + 8 * B_ST1, 0);
#pragma unroll
      for (int r = 0; r < 2; r++) {
        const uint4 su = lds128(sb + OFF_MISC + (rloc + 8 * r) * 64 + t * 16);
        const float m0 = __uint_as_float(su.x), m1 = __uint_as_float(su.z);
        float mu = m0 + m1;
        mu += __shfl_xor_sync(0xffffffffu, mu, 1); mu += __shfl_xor_sync(0xffffffffu, mu, 2);
        mu *= 0.125f;
        const float d0 = m0 - mu, d1 = m1 - mu;
        float q = __uint_as_float(su.y) + __uint_as_float(su.w) + 80.f * (d0 * d0 + d1 * d1);
        q += __shfl_xor_sync(0xffffffffu, q, 1); q += __shfl_xor_sync(0xffffffffu, q, 2);
        rs[r] = rsqrtf(q * (1.f / D_) + 1e-5f);
        mm[r] = -mu;
      }
      wg_wait<0>();
      fence_regs(acc);
      releaseB(emptyB + 8 * pb);
      release(bars + 8 * B_PEER);
      TSTAMP(11);
      if (wg == 1) bar_sync(2, 256);
      const GeluC g0 = gelu_consts(rs[0], 1.f - st_g[0]), g1 = gelu_consts(rs[1], 1.f - st_g[1]);
#pragma unroll
      for (int g = 0; g < 24; g++) {
        const float2 cs = *reinterpret_cast<const float2*>(s_cs + 80 + 8 * g + 2 * t);
        const float v0 = gelu_s(fmaf(mm[0], cs.x, acc[4 * g]), g0), v1 = gelu_s(fmaf(mm[0], cs.y, acc[4 * g + 1]), g0);
        const float v2 = gelu_s(fmaf(mm[1], cs.x, acc[4 * g + 2]), g1), v3 = gelu_s(fmaf(mm[1], cs.y, acc[4 * g + 3]), g1);
        hf[g >> 1][(g & 1) * 2] = pack_bf16(v0, v1);
        hf[g >> 1][(g & 1) * 2 + 1] = pack_bf16(v2, v3);
      }
    }
    TSTAMP(12);

    {
      float acc[80], kp[40];
      uint32_t sn[20], kb[20];
      const uint32_t peer = map_peer(sb, rank ^ 1);
      const uint32_t tag = lds32(sb + OFF_BAR + 8 * NBAR);
      const uint4* gp = g_part + (size_t)(i * 8 + j) * 3840 + tid;
      uint4 pv4[15];
      Ring r4{0, 0};
      auto add8 = [&](int q, const uint4 v) {
        float* d = &kp[8 * q];
        d[0] += bf_lo(v.x); d[1] += bf_hi(v.x); d[2] += bf_lo(v.y); d[3] += bf_hi(v.y);
        d[4] += bf_lo(v.z); d[5] += bf_hi(v.z); d[6] += bf_lo(v.w); d[7] += bf_hi(v.w);
      };
      auto send = [&](int c) {
        const uint32_t dso = peer + OFF_DS + (c & 1) * 20480 + tid * 16, dsb = peer + OFF_BAR + 8 * (B_DSR + 2 * c + wg);
#pragma unroll
        for (int q = 0; q < 5; q++) st_async16(dso + q * 4096, sn[4 * q], sn[4 * q + 1], sn[4 * q + 2], sn[4 * q + 3], dsb);
      };
      auto finish = [&](int c) {
        mbar_wait(bars + 8 * (B_DSR + 2 * c + wg), 0);
        uint4* dst = g_part + (size_t)((i * 8 + ((j + 2 * c + 2) & 7)) * 3 + c) * 1280 + tid;
#pragma unroll
        for (int q = 0; q < 5; q++) {
          const uint4 v = lds128(sb + OFF_DS + (c & 1) * 20480 + tid * 16 + q * 4096);
          st_relaxed16(dst + q * 256, (add_bf2(v.x, kb[4 * q]) & ~1u) | tag, add_bf2(v.y, kb[4 * q + 1]),
                       add_bf2(v.z, kb[4 * q + 2]), add_bf2(v.w, kb[4 * q + 3]));
        }
      };
#pragma unroll
      for (int e = 0; e < 20; e++) sn[e] = kb[e] = 0u;
      auto chunk = [&](const int c, auto last_c) {
        constexpr bool LAST = decltype(last_c)::value;
        const uint32_t e0 = r4.idx;
        auto rel = [&](int u) { const uint32_t e = e0 + u; releaseB(bars + 8 * (B_EMPTY4 + (e >= NU4 ? e - NU4 : e))); };
#pragma unroll
        for (int u = 0; u < 4; u++) {
          mbar_wait(bars + 8 * (B_FULL4 + r4.idx), r4.phase);
          const uint32_t b0 = sb16 + ((OFF_B + r4.idx * UNIT4) >> 4);
          TRS(c * 16 + u * 3);
          wg_fence();
#pragma unroll
          for (int s = 0; s < (u < 3 ? 4 : 5); s++) {
            const uint64_t db = make_desc(b0, s * 1024, u < 3 ? 4096 : 5120, 512, 2);
            if (u == 0 && s == 0) mma_rs160_n_z(acc, hf[0], db);
            else if (u < 3) mma_rs160_n(acc, hf[(4 * u + s) % 12], db);
            else mma_rs160_n(acc, of[s], db);
          }
          wg_commit();
          TRS(c * 16 + u * 3 + 1);
          r4.next<NU4>();
          if (u > 0 && !LAST) { wg_wait<1>(); rel(u - 1); }
          if (u == 0 && c > 0) send(c - 1);
          if (u == 1 && c == 0) mbar_wait(bars + 8 * B_PEER, 0);
          if (u == (LAST ? 1 : 2) && c > 0) finish(c - 1);
          TRS(c * 16 + u * 3 + 2);
        }
        if (LAST) {
#pragma unroll
          for (int q = 0; q < 10; q++) pv4[q] = ld_relaxed16(gp + q * 256);
        }
        wg_wait<0>();
        fence_regs(acc);
        if (!LAST) rel(3);
        TRS(c * 16 + 12);
        if (rank) {
#pragma unroll
          for (int e = 0; e < 20; e++) { sn[e] = pack_bf16(acc[2 * e], acc[2 * e + 1]); kb[e] = pack_bf16(acc[40 + 2 * e], acc[41 + 2 * e]); }
        } else {
#pragma unroll
          for (int e = 0; e < 20; e++) { kb[e] = pack_bf16(acc[2 * e], acc[2 * e + 1]); sn[e] = pack_bf16(acc[40 + 2 * e], acc[41 + 2 * e]); }
        }
#pragma unroll
        for (int e = 0; e < 20; e++) asm volatile("" : "+r"(sn[e]), "+r"(kb[e]));
        TRS(c * 16 + 13);
      };
      if (wg == 0) bar_arrive(2, 256);
#pragma unroll 1
      for (int c = 0; c < 3; c++) chunk(c, BoolC<false>{});
      chunk(3, BoolC<true>{});
#pragma unroll
      for (int q = 10; q < 15; q++) pv4[q] = ld_relaxed16(gp + q * 256);
      send(3);
      TSTAMP(13);
      {
        const float w0 = 1.f - st_g[0], w1s = 1.f - st_g[1];
#pragma unroll
        for (int g = 0; g < 10; g++) {
          kp[4 * g] = fmaf(w0, bf_lo(xv[0][g]), rank ? acc[40 + 4 * g] : acc[4 * g]);
          kp[4 * g + 1] = fmaf(w0, bf_hi(xv[0][g]), rank ? acc[41 + 4 * g] : acc[4 * g + 1]);
          kp[4 * g + 2] = fmaf(w1s, bf_lo(xv[1][g]), rank ? acc[42 + 4 * g] : acc[4 * g + 2]);
          kp[4 * g + 3] = fmaf(w1s, bf_hi(xv[1][g]), rank ? acc[43 + 4 * g] : acc[4 * g + 3]);
        }
      }
      mbar_wait(bars + 8 * (B_DSR + 6 + wg), 0);
      uint4 pr[5];
#pragma unroll
      for (int q = 0; q < 5; q++) pr[q] = lds128(sb + OFF_DS + 20480 + tid * 16 + q * 4096);
#pragma unroll 1
      for (uint32_t n = 0; n < (WAIT_LIMIT >> 2); n++) {
        uint32_t m = 0u;
#pragma unroll
        for (int q = 0; q < 15; q++) {
          const uint32_t bad = (pv4[q].x ^ tag) & 1u;
          m |= bad;
          if (bad) pv4[q] = ld_relaxed16(gp + q * 256);
        }
        if (m == 0u) break;
      }
      TSTAMP(14);
#pragma unroll
      for (int q = 0; q < 5; q++) {
        const uint4 a = pv4[q], b = pv4[5 + q], c = pv4[10 + q], d = pr[q];
        add8(q, make_uint4(add_bf2(a.x, b.x), add_bf2(a.y, b.y), add_bf2(a.z, b.z), add_bf2(a.w, b.w)));
        add8(q, make_uint4(add_bf2(c.x, d.x), add_bf2(c.y, d.y), add_bf2(c.z, d.z), add_bf2(c.w, d.w)));
      }
      __syncwarp();
      uint32_t ov[2][10];
#pragma unroll
      for (int g = 0; g < 10; g++) { ov[0][g] = pack_bf16(kp[4 * g], kp[4 * g + 1]); ov[1][g] = pack_bf16(kp[4 * g + 2], kp[4 * g + 3]); }
      stage_tile(sb + OFF_OUT, ov);
      __syncwarp();
      __nv_bfloat16* dst = out + (size_t)(128 * i + 16 * warp) * D_ + 80 * j;
#pragma unroll
      for (int q = 0; q < 5; q++) {
        const int id = q * 32 + lane, r = id / 10;
        *reinterpret_cast<uint4*>(dst + r * (D_ - 80) + id * 8) = lds128(sb + OFF_OUT + warp * 2560 + id * 16);
      }
    }
    TSTAMP(15);
    if (tid == 0) asm volatile("red.relaxed.gpu.global.add.u32 [%0], 1;" ::"l"(g_flags + FL_DONE * 32) : "memory");
  }
}

namespace {
typedef CUresult (*EncodeFn)(CUtensorMap*, CUtensorMapDataType, cuuint32_t, void*, const cuuint64_t*, const cuuint64_t*,
                             const cuuint32_t*, const cuuint32_t*, CUtensorMapInterleave, CUtensorMapSwizzle,
                             CUtensorMapL2promotion, CUtensorMapFloatOOBfill);

void encode(EncodeFn fn, CUtensorMap* m, const void* ptr, int rank, const cuuint64_t* dims, const cuuint64_t* strides,
            const cuuint32_t* box, CUtensorMapSwizzle swz) {
  cuuint32_t es[5] = {1, 1, 1, 1, 1};
  fn(m, CU_TENSOR_MAP_DATA_TYPE_BFLOAT16, rank, const_cast<void*>(ptr), dims, strides, box, es, CU_TENSOR_MAP_INTERLEAVE_NONE,
     swz, CU_TENSOR_MAP_L2_PROMOTION_L2_128B, CU_TENSOR_MAP_FLOAT_OOB_FILL_NONE);
}
}

extern "C" void kernel_launch(void* const* d_in, const int* in_sizes, int n_in, void* d_out, int out_size) {
  (void)in_sizes; (void)n_in; (void)out_size;
  const __nv_bfloat16* x = (const __nv_bfloat16*)d_in[0];
  const __nv_bfloat16* wqkv = (const __nv_bfloat16*)d_in[1];
  const __nv_bfloat16* wphi = (const __nv_bfloat16*)d_in[2];
  const __nv_bfloat16* wo = (const __nv_bfloat16*)d_in[3];
  const __nv_bfloat16* w1 = (const __nv_bfloat16*)d_in[5];
  const __nv_bfloat16* w2 = (const __nv_bfloat16*)d_in[6];
  const __nv_bfloat16* w3 = (const __nv_bfloat16*)d_in[7];
  const __nv_bfloat16* w4 = (const __nv_bfloat16*)d_in[8];
  const __nv_bfloat16* gate_w = (const __nv_bfloat16*)d_in[9];

  static EncodeFn enc = nullptr;
  static void *pHs = nullptr, *pX1 = nullptr;
  if (!enc) {
    cudaDriverEntryPointQueryResult qr;
    cudaGetDriverEntryPoint("cuTensorMapEncodeTiled", (void**)&enc, cudaEnableDefault, &qr);
    cudaGetSymbolAddress(&pHs, g_Hs);
    cudaGetSymbolAddress(&pX1, g_X1);
    cudaFuncSetAttribute(fused_kernel, cudaFuncAttributeMaxDynamicSharedMemorySize, SMEM_BYTES);
  }
  Maps m;
  {
    cuuint64_t dims[2] = {D_, S_}, str[1] = {D_ * 2};
    cuuint32_t box[2] = {64, 128}, boxh[2] = {64, 64};
    encode(enc, &m.x, x, 2, dims, str, boxh, CU_TENSOR_MAP_SWIZZLE_128B);
    encode(enc, &m.hs, (const char*)pHs + 2 * D_ * 2, 2, dims, str, box, CU_TENSOR_MAP_SWIZZLE_128B);
    encode(enc, &m.x1, pX1, 2, dims, str, boxh, CU_TENSOR_MAP_SWIZZLE_128B);
    cuuint32_t boxr[2] = {80, 16}, boxs[2] = {80, 128};
    cuuint64_t dimsp[2] = {D_, S_ + 4};
    encode(enc, &m.st_h, pHs, 2, dimsp, str, boxs, CU_TENSOR_MAP_SWIZZLE_NONE);
    encode(enc, &m.st_x1, pX1, 2, dims, str, boxs, CU_TENSOR_MAP_SWIZZLE_NONE);
    encode(enc, &m.xr, x, 2, dims, str, boxr, CU_TENSOR_MAP_SWIZZLE_NONE);
  }
  {
    cuuint64_t dims[3] = {80, D_, 8}, str[2] = {D_ * 2, 160};
    cuuint32_t boxm[3] = {64, 64, 1}, boxr[3] = {16, 64, 1};
    encode(enc, &m.w1m, w1, 3, dims, str, boxm, CU_TENSOR_MAP_SWIZZLE_128B);
    encode(enc, &m.w1r, w1, 3, dims, str, boxr, CU_TENSOR_MAP_SWIZZLE_32B);
  }
  {
    cuuint64_t dims[4] = {80, D_, 3, 8}, str[3] = {3 * D_ * 2, D_ * 2, 160};
    cuuint32_t boxm[4] = {64, 64, 3, 1}, boxr[4] = {16, 64, 3, 1};
    encode(enc, &m.qm, wqkv, 4, dims, str, boxm, CU_TENSOR_MAP_SWIZZLE_128B);
    encode(enc, &m.qr, wqkv, 4, dims, str, boxr, CU_TENSOR_MAP_SWIZZLE_32B);
  }
  {
    cuuint64_t dims[3] = {32, D_, 20}, dims4[3] = {32, F_, 20}, str[2] = {D_ * 2, 64};
    cuuint32_t box4[3] = {32, 64, 5}, boxo[3] = {32, 80, 5};
    encode(enc, &m.w4, w4, 3, dims4, str, box4, CU_TENSOR_MAP_SWIZZLE_64B);
    encode(enc, &m.wo, wo, 3, dims, str, boxo, CU_TENSOR_MAP_SWIZZLE_64B);
    encode(enc, &m.w2, w2, 3, dims, str, box4, CU_TENSOR_MAP_SWIZZLE_64B);
  }
  {
    cuuint64_t dims[3] = {64, D_, 24}, str[2] = {F_ * 2, 128};
    cuuint32_t box[3] = {64, 64, 3};
    encode(enc, &m.w3, w3, 3, dims, str, box, CU_TENSOR_MAP_SWIZZLE_128B);
  }
  fused_kernel<<<NCTA, 384, SMEM_BYTES, cudaStreamPerThread>>>(m, x, wqkv, wphi, w1, w2, w3, w4, wo, gate_w, (__nv_bfloat16*)d_out);
}
```

```cpp
#include <cuda_runtime.h>
#include <cuda_bf16.h>
#include <cuda.h>
#include <stdint.h>

namespace {

constexpr int S_ = 2048, D_ = 640, F_ = 1536;
constexpr int NCTA = 128;
constexpr int KV_PAIR = 40 * 48 + 96;
constexpr int KV_J = 2 * KV_PAIR;

constexpr int SLOT_B = 49152, NB = 3;
constexpr int SLOT_A = 16384, NA = 4;
constexpr int OFF_B = 0;
constexpr int OFF_A = OFF_B + NB * SLOT_B;
constexpr int OFF_STG = OFF_A + 2 * SLOT_A;
constexpr int OFF_MISC = OFF_A + NA * SLOT_A;
constexpr int OFF_XST = OFF_MISC + 13312;
constexpr int OFF_CS = OFF_MISC + 16384;
constexpr int OFF_BAR = OFF_CS + 1088;
constexpr int SMEM_BYTES = OFF_BAR + 512 + 512 + 128;
constexpr int B_FULLA = 0, B_FULLB = 4, B_CS = 7, B_XR = 8, B_KV = 9, B_ST1 = 10, B_HST = 11, B_FULL4 = 12  ,
              B_DSR = 17  , B_EMPTYB = 27  , B_SIGP = 30, B_SIGH = 31, B_SIGKV = 32, B_SIGX1 = 33, B_MFREE = 34,
              B_EMPTY4 = 35  , B_EMPTYA = 40  , B_PEER = 44, B_PEER2 = 45, B_X1P = 46  , NBAR = 47;
constexpr int SPARE = 40960;
constexpr int UNIT4 = 25600, NU4 = 5;
constexpr int OFF_DS = OFF_A, OFF_OUT = OFF_A + 40960;

constexpr int FL_DONE = 0, FL_H = 1  , FL_X1 = FL_H + 32, FL_KV = FL_X1 + 16, FL_CS = FL_KV + 8, FL_CS3 = FL_CS + 8, FL_ST = FL_CS3 + 8;
constexpr int FL_S1 = FL_ST + 16, FL_COUNT = FL_S1 + 16;
constexpr int ACC_FLOATS = 8 * KV_J + D_ + F_;

struct Maps {
  CUtensorMap x, w1m, w1r, qm, qr, hs, w2, x1, w3, w4, wo, xr, st_h, st_x1;
};

}

__device__ __align__(1024) __nv_bfloat16 g_Hs[(S_ + 4) * D_];
__device__ __align__(1024) __nv_bfloat16 g_X1[S_ * D_];
__device__ __align__(128) float g_acc[2][ACC_FLOATS];
__device__ __align__(128) float4 g_xstat[S_];
__device__ __align__(128) float2 g_st1[S_ * 8];
__device__ __align__(128) uint4 g_part[16 * 8 * 3 * 1280];
__device__ __align__(128) unsigned g_flags[FL_COUNT * 32];
#define TSTAMP(n) do {} while (0)
#define TSTAMPX(n) do {} while (0)
#define TRACE(n) do {} while (0)
#define TRS(n) do {} while (0)

namespace {

__device__ __forceinline__ long long gtime() { long long t; asm volatile("mov.u64 %0, %%globaltimer;" : "=l"(t)); return t; }
__device__ __forceinline__ uint32_t smem_u32(const void* p) { return (uint32_t)__cvta_generic_to_shared(p); }
__device__ __forceinline__ void mbar_init(uint32_t bar, int cnt) {
  asm volatile("mbarrier.init.shared::cta.b64 [%0], %1;" ::"r"(bar), "r"(cnt) : "memory");
}
__device__ __forceinline__ void mbar_expect_tx(uint32_t bar, int bytes) {
  asm volatile("mbarrier.arrive.expect_tx.shared::cta.b64 _, [%0], %1;" ::"r"(bar), "r"(bytes) : "memory");
}
__device__ __forceinline__ void mbar_arrive_cta(uint32_t bar, uint32_t cta) {
  asm volatile("{\n.reg .b32 ra;\nmapa.shared::cluster.u32 ra, %0, %1;\nmbarrier.arrive.shared::cluster.b64 _, [ra];\n}"
               ::"r"(bar), "r"(cta) : "memory");
}
__device__ __forceinline__ uint32_t mbar_try(uint32_t bar, uint32_t parity) {
  uint32_t ok;
  asm volatile("{\n.reg .pred p;\nmbarrier.try_wait.parity.shared::cta.b64 p, [%1], %2;\nselp.u32 %0, 1, 0, p;\n}"
               : "=r"(ok) : "r"(bar), "r"(parity) : "memory");
  return ok;
}
constexpr uint32_t WAIT_LIMIT = 1u << 18;
__device__ __forceinline__ void mbar_wait(uint32_t bar, uint32_t parity) {
  uint32_t n = 0;
  while (!mbar_try(bar, parity) && ++n < WAIT_LIMIT) {}
}
__device__ __forceinline__ unsigned ld_acquire(const unsigned* p) {
  unsigned v;
  asm volatile("ld.acquire.gpu.global.u32 %0, [%1];" : "=r"(v) : "l"(p) : "memory");
  return v;
}
__device__ __forceinline__ void flag_wait(int idx, unsigned target) {
  const unsigned* p = g_flags + idx * 32;
  uint32_t n = 0;
  while ((int)(ld_acquire(p) - target) < 0 && ++n < (WAIT_LIMIT >> 2)) {}
}
__device__ __forceinline__ void flag_add(int idx) {
  asm volatile("red.release.gpu.global.add.u32 [%0], 1;" ::"l"(g_flags + idx * 32) : "memory");
}
__device__ __forceinline__ void flag_add_relaxed(int idx) {
  asm volatile("red.relaxed.gpu.global.add.u32 [%0], 1;" ::"l"(g_flags + idx * 32) : "memory");
}
__device__ __forceinline__ uint32_t mbar_test(uint32_t bar, uint32_t parity) {
  uint32_t ok;
  asm volatile("{\n.reg .pred p;\nmbarrier.test_wait.parity.shared::cta.b64 p, [%1], %2;\nselp.u32 %0, 1, 0, p;\n}"
               : "=r"(ok) : "r"(bar), "r"(parity) : "memory");
  return ok;
}
__device__ __forceinline__ uint32_t lds32(uint32_t a) {
  uint32_t v;
  asm volatile("ld.shared.u32 %0, [%1];" : "=r"(v) : "r"(a) : "memory");
  return v;
}
__device__ __forceinline__ void mbar_arrive(uint32_t bar) {
  asm volatile("mbarrier.arrive.shared::cta.b64 _, [%0];" ::"r"(bar) : "memory");
}
__device__ __forceinline__ void fence_async_glb() { asm volatile("fence.proxy.async.global;" ::: "memory"); }
__device__ __forceinline__ void fence_async_smem() { asm volatile("fence.proxy.async.shared::cta;" ::: "memory"); }
__device__ __forceinline__ void bar_sync(int id, int n) { asm volatile("bar.sync %0, %1;" ::"r"(id), "r"(n) : "memory"); }

__device__ __forceinline__ void tma2d(uint32_t dst, const CUtensorMap* m, uint32_t bar, int c0, int c1) {
  asm volatile("cp.async.bulk.tensor.2d.shared::cluster.global.mbarrier::complete_tx::bytes [%0], [%1, {%3, %4}], [%2];"
               ::"r"(dst), "l"(m), "r"(bar), "r"(c0), "r"(c1) : "memory");
}
__device__ __forceinline__ void tma2d_mc(uint32_t dst, const CUtensorMap* m, uint32_t bar, int c0, int c1) {
  asm volatile("cp.async.bulk.tensor.2d.shared::cluster.global.mbarrier::complete_tx::bytes.multicast::cluster"
               " [%0], [%1, {%3, %4}], [%2], %5;"
               ::"r"(dst), "l"(m), "r"(bar), "r"(c0), "r"(c1), "h"((uint16_t)3) : "memory");
}
__device__ __forceinline__ void tma3d(uint32_t dst, const CUtensorMap* m, uint32_t bar, int c0, int c1, int c2) {
  asm volatile("cp.async.bulk.tensor.3d.shared::cluster.global.mbarrier::complete_tx::bytes [%0], [%1, {%3, %4, %5}], [%2];"
               ::"r"(dst), "l"(m), "r"(bar), "r"(c0), "r"(c1), "r"(c2) : "memory");
}
__device__ __forceinline__ void tma4d(uint32_t dst, const CUtensorMap* m, uint32_t bar, int c0, int c1, int c2, int c3) {
  asm volatile("cp.async.bulk.tensor.4d.shared::cluster.global.mbarrier::complete_tx::bytes [%0], [%1, {%3, %4, %5, %6}], [%2];"
               ::"r"(dst), "l"(m), "r"(bar), "r"(c0), "r"(c1), "r"(c2), "r"(c3) : "memory");
}
__device__ __forceinline__ void tma2d_store(const CUtensorMap* m, uint32_t src, int c0, int c1) {
  asm volatile("cp.async.bulk.tensor.2d.global.shared::cta.bulk_group [%0, {%2, %3}], [%1];"
               ::"l"(m), "r"(src), "r"(c0), "r"(c1) : "memory");
}
__device__ __forceinline__ void bulk_store(void* dst, uint32_t src, uint32_t bytes) {
  asm volatile("cp.async.bulk.global.shared::cta.bulk_group [%0], [%1], %2;" ::"l"(dst), "r"(src), "r"(bytes) : "memory");
}
__device__ __forceinline__ void bulk_load(uint32_t dst, const void* src, uint32_t bytes, uint32_t bar) {
  asm volatile("cp.async.bulk.shared::cluster.global.mbarrier::complete_tx::bytes [%0], [%1], %2, [%3];"
               ::"r"(dst), "l"(src), "r"(bytes), "r"(bar) : "memory");
}
__device__ __forceinline__ void bulk_commit() { asm volatile("cp.async.bulk.commit_group;" ::: "memory"); }
template <int N> __device__ __forceinline__ void bulk_wait() { asm volatile("cp.async.bulk.wait_group %0;" ::"n"(N) : "memory"); }
__device__ __forceinline__ void bulk_wait_read() { asm volatile("cp.async.bulk.wait_group.read 0;" ::: "memory"); }
__device__ __forceinline__ void bar_arrive(int id, int n) { asm volatile("bar.arrive %0, %1;" ::"r"(id), "r"(n) : "memory"); }
__device__ __forceinline__ uint4 lds128(uint32_t a) {
  uint4 v;
  asm volatile("ld.shared.v4.u32 {%0, %1, %2, %3}, [%4];" : "=r"(v.x), "=r"(v.y), "=r"(v.z), "=r"(v.w) : "r"(a) : "memory");
  return v;
}
__device__ __forceinline__ void sts128(uint32_t a, uint4 v) {
  asm volatile("st.shared.v4.u32 [%0], {%1, %2, %3, %4};" ::"r"(a), "r"(v.x), "r"(v.y), "r"(v.z), "r"(v.w) : "memory");
}
__device__ __forceinline__ uint4 ld_relaxed16(const uint4* p) {
  uint4 v;
  asm volatile("ld.relaxed.gpu.global.v4.u32 {%0, %1, %2, %3}, [%4];" : "=r"(v.x), "=r"(v.y), "=r"(v.z), "=r"(v.w) : "l"(p) : "memory");
  return v;
}
__device__ __forceinline__ void st_relaxed16(uint4* p, uint32_t a, uint32_t b, uint32_t c, uint32_t d) {
  asm volatile("st.relaxed.gpu.global.v4.u32 [%0], {%1, %2, %3, %4};" ::"l"(p), "r"(a), "r"(b), "r"(c), "r"(d) : "memory");
}
__device__ __forceinline__ uint32_t map_peer(uint32_t addr, uint32_t cta) {
  uint32_t r;
  asm("mapa.shared::cluster.u32 %0, %1, %2;" : "=r"(r) : "r"(addr), "r"(cta));
  return r;
}
__device__ __forceinline__ void st_async16(uint32_t addr, uint32_t a, uint32_t b, uint32_t c, uint32_t d, uint32_t bar) {
  asm volatile("st.async.weak.shared::cluster.mbarrier::complete_tx::bytes.v4.b32 [%0], {%1, %2, %3, %4}, [%5];"
               ::"r"(addr), "r"(a), "r"(b), "r"(c), "r"(d), "r"(bar) : "memory");
}
__device__ __forceinline__ void l2_prefetch(const void* p, uint32_t bytes) {
  asm volatile("cp.async.bulk.prefetch.L2.global [%0], %1;" ::"l"(p), "r"(bytes) : "memory");
}
__device__ __forceinline__ void prefetch_tmap(const CUtensorMap* m) {
  asm volatile("prefetch.tensormap [%0];" ::"l"(m) : "memory");
}
__device__ __forceinline__ uint64_t make_desc(uint32_t a16, uint32_t off, uint32_t lbo, uint32_t sbo, uint32_t swz) {
  const uint32_t lo = a16 + ((off >> 4) + ((lbo >> 4) << 16)), hi = (sbo >> 4) | (swz << 30);
  uint64_t d;
  asm("mov.b64 %0, {%1, %2};" : "=l"(d) : "r"(lo), "r"(hi));
  return d;
}
__device__ __forceinline__ void wg_fence() { asm volatile("wgmma.fence.sync.aligned;" ::: "memory"); }
__device__ __forceinline__ void wg_commit() { asm volatile("wgmma.commit_group.sync.aligned;" ::: "memory"); }
template <int N> __device__ __forceinline__ void wg_wait() { asm volatile("wgmma.wait_group.sync.aligned %0;" ::"n"(N) : "memory"); }
template <int N> __device__ __forceinline__ void fence_regs(float (&d)[N]) {
#pragma unroll
  for (int i = 0; i < N; i++) asm volatile("" : "+f"(d[i])::"memory");
}
template <int N> __device__ __forceinline__ void zero_regs(float (&d)[N]) {
#pragma unroll
  for (int i = 0; i < N; i++) d[i] = 0.f;
}
__device__ __forceinline__ uint32_t pack_bf16(float lo, float hi) {
  uint32_t r;
  asm("cvt.rn.bf16x2.f32 %0, %1, %2;" : "=r"(r) : "f"(hi), "f"(lo));
  return r;
}
__device__ __forceinline__ float bf_lo(uint32_t v) { return __uint_as_float(v << 16); }
__device__ __forceinline__ float bf_hi(uint32_t v) { return __uint_as_float(v & 0xffff0000u); }
__device__ __forceinline__ uint32_t max_bf2(uint32_t a, uint32_t b) {
  uint32_t r; asm("max.bf16x2 %0, %1, %2;" : "=r"(r) : "r"(a), "r"(b)); return r;
}
__device__ __forceinline__ uint32_t min_bf2(uint32_t a, uint32_t b) {
  uint32_t r; asm("min.bf16x2 %0, %1, %2;" : "=r"(r) : "r"(a), "r"(b)); return r;
}
__device__ __forceinline__ uint32_t add_bf2(uint32_t a, uint32_t b) {
  uint32_t r; asm("add.rn.bf16x2 %0, %1, %2;" : "=r"(r) : "r"(a), "r"(b)); return r;
}
__device__ __forceinline__ float ex2(float x) { float r; asm("ex2.approx.ftz.f32 %0, %1;" : "=f"(r) : "f"(x)); return r; }
__device__ __forceinline__ float rcp(float x) { float r; asm("rcp.approx.ftz.f32 %0, %1;" : "=f"(r) : "f"(x)); return r; }
__device__ __forceinline__ float tanh_ap(float x) { float r; asm("tanh.approx.f32 %0, %1;" : "=f"(r) : "f"(x)); return r; }
struct GeluC { float c0, c1, ch; };
__device__ __forceinline__ GeluC gelu_consts(float rstd, float scale) {
  return GeluC{0.7978845608f * rstd, 0.0356774081f * rstd * rstd * rstd, 0.5f * scale * rstd};
}
__device__ __forceinline__ float gelu_s(float y, const GeluC& c) {
  const float u = y * fmaf(y * y, c.c1, c.c0);
  const float hx = y * c.ch;
  return fmaf(hx, tanh_ap(u), hx);
}
__device__ __forceinline__ void stsm4(uint32_t addr, uint32_t r0, uint32_t r1, uint32_t r2, uint32_t r3) {
  asm volatile("stmatrix.sync.aligned.m8n8.x4.shared.b16 [%0], {%1, %2, %3, %4};"
               ::"r"(addr), "r"(r0), "r"(r1), "r"(r2), "r"(r3) : "memory");
}
__device__ __forceinline__ void red_add4(float* p, float a, float b, float c, float d) {
  asm volatile("red.global.add.v4.f32 [%0], {%1, %2, %3, %4};" ::"l"(p), "f"(a), "f"(b), "f"(c), "f"(d) : "memory");
}

__device__ __forceinline__ void mma_ss256(float (&d)[128], uint64_t descA, uint64_t descB) {
  asm volatile("wgmma.mma_async.sync.aligned.m64n256k16.f32.bf16.bf16 {"
      "%0, %1, %2, %3, %4, %5, %6, %7, %8, %9, %10, %11, %12, %13, %14, %15, "
      "%16, %17, %18, %19, %20, %21, %22, %23, %24, %25, %26, %27, %28, %29, %30, %31, "
      "%32, %33, %34, %35, %36, %37, %38, %39, %40, %41, %42, %43, %44, %45, %46, %47, "
      "%48, %49, %50, %51, %52, %53, %54, %55, %56, %57, %58, %59, %60, %61, %62, %63, "
      "%64, %65, %66, %67, %68, %69, %70, %71, %72, %73, %74, %75, %76, %77, %78, %79, "
      "%80, %81, %82, %83, %84, %85, %86, %87, %88, %89, %90, %91, %92, %93, %94, %95, "
      "%96, %97, %98, %99, %100, %101, %102, %103, %104, %105, %106, %107, %108, %109, %110, %111, "
      "%112, %113, %114, %115, %116, %117, %118, %119, %120, %121, %122, %123, %124, %125, %126, %127"
      "}, %128, %129, 1, 1, 1, 0, 1;\n"
      : "+f"(d[0]), "+f"(d[1]), "+f"(d[2]), "+f"(d[3]), "+f"(d[4]), "+f"(d[5]), "+f"(d[6]), "+f"(d[7]),
        "+f"(d[8]), "+f"(d[9]), "+f"(d[10]), "+f"(d[11]), "+f"(d[12]), "+f"(d[13]), "+f"(d[14]), "+f"(d[15]),
        "+f"(d[16]), "+f"(d[17]), "+f"(d[18]), "+f"(d[19]), "+f"(d[20]), "+f"(d[21]), "+f"(d[22]), "+f"(d[23]),
        "+f"(d[24]), "+f"(d[25]), "+f"(d[26]), "+f"(d[27]), "+f"(d[28]), "+f"(d[29]), "+f"(d[30]), "+f"(d[31]),
        "+f"(d[32]), "+f"(d[33]), "+f"(d[34]), "+f"(d[35]), "+f"(d[36]), "+f"(d[37]), "+f"(d[38]), "+f"(d[39]),
        "+f"(d[40]), "+f"(d[41]), "+f"(d[42]), "+f"(d[43]), "+f"(d[44]), "+f"(d[45]), "+f"(d[46]), "+f"(d[47]),
        "+f"(d[48]), "+f"(d[49]), "+f"(d[50]), "+f"(d[51]), "+f"(d[52]), "+f"(d[53]), "+f"(d[54]), "+f"(d[55]),
        "+f"(d[56]), "+f"(d[57]), "+f"(d[58]), "+f"(d[59]), "+f"(d[60]), "+f"(d[61]), "+f"(d[62]), "+f"(d[63]),
        "+f"(d[64]), "+f"(d[65]), "+f"(d[66]), "+f"(d[67]), "+f"(d[68]), "+f"(d[69]), "+f"(d[70]), "+f"(d[71]),
        "+f"(d[72]), "+f"(d[73]), "+f"(d[74]), "+f"(d[75]), "+f"(d[76]), "+f"(d[77]), "+f"(d[78]), "+f"(d[79]),
        "+f"(d[80]), "+f"(d[81]), "+f"(d[82]), "+f"(d[83]), "+f"(d[84]), "+f"(d[85]), "+f"(d[86]), "+f"(d[87]),
        "+f"(d[88]), "+f"(d[89]), "+f"(d[90]), "+f"(d[91]), "+f"(d[92]), "+f"(d[93]), "+f"(d[94]), "+f"(d[95]),
        "+f"(d[96]), "+f"(d[97]), "+f"(d[98]), "+f"(d[99]), "+f"(d[100]), "+f"(d[101]), "+f"(d[102]), "+f"(d[103]),
        "+f"(d[104]), "+f"(d[105]), "+f"(d[106]), "+f"(d[107]), "+f"(d[108]), "+f"(d[109]), "+f"(d[110]), "+f"(d[111]),
        "+f"(d[112]), "+f"(d[113]), "+f"(d[114]), "+f"(d[115]), "+f"(d[116]), "+f"(d[117]), "+f"(d[118]), "+f"(d[119]),
        "+f"(d[120]), "+f"(d[121]), "+f"(d[122]), "+f"(d[123]), "+f"(d[124]), "+f"(d[125]), "+f"(d[126]), "+f"(d[127])
      : "l"(descA), "l"(descB));
}
__device__ __forceinline__ void mma_ss256_p(float (&d)[128], uint64_t descA, uint64_t descB, int acc) {
  asm volatile("{\n.reg .pred p;\nsetp.ne.b32 p, %130, 0;\n"
      "wgmma.mma_async.sync.aligned.m64n256k16.f32.bf16.bf16 {"
      "%0, %1, %2, %3, %4, %5, %6, %7, %8, %9, %10, %11, %12, %13, %14, %15, "
      "%16, %17, %18, %19, %20, %21, %22, %23, %24, %25, %26, %27, %28, %29, %30, %31, "
      "%32, %33, %34, %35, %36, %37, %38, %39, %40, %41, %42, %43, %44, %45, %46, %47, "
      "%48, %49, %50, %51, %52, %53, %54, %55, %56, %57, %58, %59, %60, %61, %62, %63, "
      "%64, %65, %66, %67, %68, %69, %70, %71, %72, %73, %74, %75, %76, %77, %78, %79, "
      "%80, %81, %82, %83, %84, %85, %86, %87, %88, %89, %90, %91, %92, %93, %94, %95, "
      "%96, %97, %98, %99, %100, %101, %102, %103, %104, %105, %106, %107, %108, %109, %110, %111, "
      "%112, %113, %114, %115, %116, %117, %118, %119, %120, %121, %122, %123, %124, %125, %126, %127"
      "}, %128, %129, p, 1, 1, 0, 1;\n}\n"
      : "+f"(d[0]), "+f"(d[1]), "+f"(d[2]), "+f"(d[3]), "+f"(d[4]), "+f"(d[5]), "+f"(d[6]), "+f"(d[7]),
        "+f"(d[8]), "+f"(d[9]), "+f"(d[10]), "+f"(d[11]), "+f"(d[12]), "+f"(d[13]), "+f"(d[14]), "+f"(d[15]),
        "+f"(d[16]), "+f"(d[17]), "+f"(d[18]), "+f"(d[19]), "+f"(d[20]), "+f"(d[21]), "+f"(d[22]), "+f"(d[23]),
        "+f"(d[24]), "+f"(d[25]), "+f"(d[26]), "+f"(d[27]), "+f"(d[28]), "+f"(d[29]), "+f"(d[30]), "+f"(d[31]),
        "+f"(d[32]), "+f"(d[33]), "+f"(d[34]), "+f"(d[35]), "+f"(d[36]), "+f"(d[37]), "+f"(d[38]), "+f"(d[39]),
        "+f"(d[40]), "+f"(d[41]), "+f"(d[42]), "+f"(d[43]), "+f"(d[44]), "+f"(d[45]), "+f"(d[46]), "+f"(d[47]),
        "+f"(d[48]), "+f"(d[49]), "+f"(d[50]), "+f"(d[51]), "+f"(d[52]), "+f"(d[53]), "+f"(d[54]), "+f"(d[55]),
        "+f"(d[56]), "+f"(d[57]), "+f"(d[58]), "+f"(d[59]), "+f"(d[60]), "+f"(d[61]), "+f"(d[62]), "+f"(d[63]),
        "+f"(d[64]), "+f"(d[65]), "+f"(d[66]), "+f"(d[67]), "+f"(d[68]), "+f"(d[69]), "+f"(d[70]), "+f"(d[71]),
        "+f"(d[72]), "+f"(d[73]), "+f"(d[74]), "+f"(d[75]), "+f"(d[76]), "+f"(d[77]), "+f"(d[78]), "+f"(d[79]),
        "+f"(d[80]), "+f"(d[81]), "+f"(d[82]), "+f"(d[83]), "+f"(d[84]), "+f"(d[85]), "+f"(d[86]), "+f"(d[87]),
        "+f"(d[88]), "+f"(d[89]), "+f"(d[90]), "+f"(d[91]), "+f"(d[92]), "+f"(d[93]), "+f"(d[94]), "+f"(d[95]),
        "+f"(d[96]), "+f"(d[97]), "+f"(d[98]), "+f"(d[99]), "+f"(d[100]), "+f"(d[101]), "+f"(d[102]), "+f"(d[103]),
        "+f"(d[104]), "+f"(d[105]), "+f"(d[106]), "+f"(d[107]), "+f"(d[108]), "+f"(d[109]), "+f"(d[110]), "+f"(d[111]),
        "+f"(d[112]), "+f"(d[113]), "+f"(d[114]), "+f"(d[115]), "+f"(d[116]), "+f"(d[117]), "+f"(d[118]), "+f"(d[119]),
        "+f"(d[120]), "+f"(d[121]), "+f"(d[122]), "+f"(d[123]), "+f"(d[124]), "+f"(d[125]), "+f"(d[126]), "+f"(d[127])
      : "l"(descA), "l"(descB), "r"(acc));
}

__device__ __forceinline__ void mma_ss64(float (&d)[32], uint64_t descA, uint64_t descB) {
  asm volatile("wgmma.mma_async.sync.aligned.m64n64k16.f32.bf16.bf16 {"
      "%0, %1, %2, %3, %4, %5, %6, %7, %8, %9, %10, %11, %12, %13, %14, %15, "
      "%16, %17, %18, %19, %20, %21, %22, %23, %24, %25, %26, %27, %28, %29, %30, %31"
      "}, %32, %33, 1, 1, 1, 0, 1;\n"
      : "+f"(d[0]), "+f"(d[1]), "+f"(d[2]), "+f"(d[3]), "+f"(d[4]), "+f"(d[5]), "+f"(d[6]), "+f"(d[7]),
        "+f"(d[8]), "+f"(d[9]), "+f"(d[10]), "+f"(d[11]), "+f"(d[12]), "+f"(d[13]), "+f"(d[14]), "+f"(d[15]),
        "+f"(d[16]), "+f"(d[17]), "+f"(d[18]), "+f"(d[19]), "+f"(d[20]), "+f"(d[21]), "+f"(d[22]), "+f"(d[23]),
        "+f"(d[24]), "+f"(d[25]), "+f"(d[26]), "+f"(d[27]), "+f"(d[28]), "+f"(d[29]), "+f"(d[30]), "+f"(d[31])
      : "l"(descA), "l"(descB));
}
__device__ __forceinline__ void mma_ss64_p(float (&d)[32], uint64_t descA, uint64_t descB, int acc) {
  asm volatile("{\n.reg .pred p;\nsetp.ne.b32 p, %34, 0;\n"
      "wgmma.mma_async.sync.aligned.m64n64k16.f32.bf16.bf16 {"
      "%0, %1, %2, %3, %4, %5, %6, %7, %8, %9, %10, %11, %12, %13, %14, %15, "
      "%16, %17, %18, %19, %20, %21, %22, %23, %24, %25, %26, %27, %28, %29, %30, %31"
      "}, %32, %33, p, 1, 1, 0, 1;\n}\n"
      : "+f"(d[0]), "+f"(d[1]), "+f"(d[2]), "+f"(d[3]), "+f"(d[4]), "+f"(d[5]), "+f"(d[6]), "+f"(d[7]),
        "+f"(d[8]), "+f"(d[9]), "+f"(d[10]), "+f"(d[11]), "+f"(d[12]), "+f"(d[13]), "+f"(d[14]), "+f"(d[15]),
        "+f"(d[16]), "+f"(d[17]), "+f"(d[18]), "+f"(d[19]), "+f"(d[20]), "+f"(d[21]), "+f"(d[22]), "+f"(d[23]),
        "+f"(d[24]), "+f"(d[25]), "+f"(d[26]), "+f"(d[27]), "+f"(d[28]), "+f"(d[29]), "+f"(d[30]), "+f"(d[31])
      : "l"(descA), "l"(descB), "r"(acc));
}

__device__ __forceinline__ void mma_ss160(float (&d)[80], uint64_t descA, uint64_t descB) {
  asm volatile("wgmma.mma_async.sync.aligned.m64n160k16.f32.bf16.bf16 {"
      "%0, %1, %2, %3, %4, %5, %6, %7, %8, %9, %10, %11, %12, %13, %14, %15, "
      "%16, %17, %18, %19, %20, %21, %22, %23, %24, %25, %26, %27, %28, %29, %30, %31, "
      "%32, %33, %34, %35, %36, %37, %38, %39, %40, %41, %42, %43, %44, %45, %46, %47, "
      "%48, %49, %50, %51, %52, %53, %54, %55, %56, %57, %58, %59, %60, %61, %62, %63, "
      "%64, %65, %66, %67, %68, %69, %70, %71, %72, %73, %74, %75, %76, %77, %78, %79"
      "}, %80, %81, 1, 1, 1, 0, 1;\n"
      : "+f"(d[0]), "+f"(d[1]), "+f"(d[2]), "+f"(d[3]), "+f"(d[4]), "+f"(d[5]), "+f"(d[6]), "+f"(d[7]),
        "+f"(d[8]), "+f"(d[9]), "+f"(d[10]), "+f"(d[11]), "+f"(d[12]), "+f"(d[13]), "+f"(d[14]), "+f"(d[15]),
        "+f"(d[16]), "+f"(d[17]), "+f"(d[18]), "+f"(d[19]), "+f"(d[20]), "+f"(d[21]), "+f"(d[22]), "+f"(d[23]),
        "+f"(d[24]), "+f"(d[25]), "+f"(d[26]), "+f"(d[27]), "+f"(d[28]), "+f"(d[29]), "+f"(d[30]), "+f"(d[31]),
        "+f"(d[32]), "+f"(d[33]), "+f"(d[34]), "+f"(d[35]), "+f"(d[36]), "+f"(d[37]), "+f"(d[38]), "+f"(d[39]),
        "+f"(d[40]), "+f"(d[41]), "+f"(d[42]), "+f"(d[43]), "+f"(d[44]), "+f"(d[45]), "+f"(d[46]), "+f"(d[47]),
        "+f"(d[48]), "+f"(d[49]), "+f"(d[50]), "+f"(d[51]), "+f"(d[52]), "+f"(d[53]), "+f"(d[54]), "+f"(d[55]),
        "+f"(d[56]), "+f"(d[57]), "+f"(d[58]), "+f"(d[59]), "+f"(d[60]), "+f"(d[61]), "+f"(d[62]), "+f"(d[63]),
        "+f"(d[64]), "+f"(d[65]), "+f"(d[66]), "+f"(d[67]), "+f"(d[68]), "+f"(d[69]), "+f"(d[70]), "+f"(d[71]),
        "+f"(d[72]), "+f"(d[73]), "+f"(d[74]), "+f"(d[75]), "+f"(d[76]), "+f"(d[77]), "+f"(d[78]), "+f"(d[79])
      : "l"(descA), "l"(descB));
}
__device__ __forceinline__ void mma_ss160_z(float (&d)[80], uint64_t descA, uint64_t descB) {
  asm volatile("wgmma.mma_async.sync.aligned.m64n160k16.f32.bf16.bf16 {"
      "%0, %1, %2, %3, %4, %5, %6, %7, %8, %9, %10, %11, %12, %13, %14, %15, "
      "%16, %17, %18, %19, %20, %21, %22, %23, %24, %25, %26, %27, %28, %29, %30, %31, "
      "%32, %33, %34, %35, %36, %37, %38, %39, %40, %41, %42, %43, %44, %45, %46, %47, "
      "%48, %49, %50, %51, %52, %53, %54, %55, %56, %57, %58, %59, %60, %61, %62, %63, "
      "%64, %65, %66, %67, %68, %69, %70, %71, %72, %73, %74, %75, %76, %77, %78, %79"
      "}, %80, %81, 0, 1, 1, 0, 1;\n"
      : "=f"(d[0]), "=f"(d[1]), "=f"(d[2]), "=f"(d[3]), "=f"(d[4]), "=f"(d[5]), "=f"(d[6]), "=f"(d[7]),
        "=f"(d[8]), "=f"(d[9]), "=f"(d[10]), "=f"(d[11]), "=f"(d[12]), "=f"(d[13]), "=f"(d[14]), "=f"(d[15]),
        "=f"(d[16]), "=f"(d[17]), "=f"(d[18]), "=f"(d[19]), "=f"(d[20]), "=f"(d[21]), "=f"(d[22]), "=f"(d[23]),
        "=f"(d[24]), "=f"(d[25]), "=f"(d[26]), "=f"(d[27]), "=f"(d[28]), "=f"(d[29]), "=f"(d[30]), "=f"(d[31]),
        "=f"(d[32]), "=f"(d[33]), "=f"(d[34]), "=f"(d[35]), "=f"(d[36]), "=f"(d[37]), "=f"(d[38]), "=f"(d[39]),
        "=f"(d[40]), "=f"(d[41]), "=f"(d[42]), "=f"(d[43]), "=f"(d[44]), "=f"(d[45]), "=f"(d[46]), "=f"(d[47]),
        "=f"(d[48]), "=f"(d[49]), "=f"(d[50]), "=f"(d[51]), "=f"(d[52]), "=f"(d[53]), "=f"(d[54]), "=f"(d[55]),
        "=f"(d[56]), "=f"(d[57]), "=f"(d[58]), "=f"(d[59]), "=f"(d[60]), "=f"(d[61]), "=f"(d[62]), "=f"(d[63]),
        "=f"(d[64]), "=f"(d[65]), "=f"(d[66]), "=f"(d[67]), "=f"(d[68]), "=f"(d[69]), "=f"(d[70]), "=f"(d[71]),
        "=f"(d[72]), "=f"(d[73]), "=f"(d[74]), "=f"(d[75]), "=f"(d[76]), "=f"(d[77]), "=f"(d[78]), "=f"(d[79])
      : "l"(descA), "l"(descB));
}

__device__ __forceinline__ void mma_ss192(float (&d)[96], uint64_t descA, uint64_t descB) {
  asm volatile("wgmma.mma_async.sync.aligned.m64n192k16.f32.bf16.bf16 {"
      "%0, %1, %2, %3, %4, %5, %6, %7, %8, %9, %10, %11, %12, %13, %14, %15, "
      "%16, %17, %18, %19, %20, %21, %22, %23, %24, %25, %26, %27, %28, %29, %30, %31, "
      "%32, %33, %34, %35, %36, %37, %38, %39, %40, %41, %42, %43, %44, %45, %46, %47, "
      "%48, %49, %50, %51, %52, %53, %54, %55, %56, %57, %58, %59, %60, %61, %62, %63, "
      "%64, %65, %66, %67, %68, %69, %70, %71, %72, %73, %74, %75, %76, %77, %78, %79, "
      "%80, %81, %82, %83, %84, %85, %86, %87, %88, %89, %90, %91, %92, %93, %94, %95"
      "}, %96, %97, 1, 1, 1, 0, 1;\n"
      : "+f"(d[0]), "+f"(d[1]), "+f"(d[2]), "+f"(d[3]), "+f"(d[4]), "+f"(d[5]), "+f"(d[6]), "+f"(d[7]),
        "+f"(d[8]), "+f"(d[9]), "+f"(d[10]), "+f"(d[11]), "+f"(d[12]), "+f"(d[13]), "+f"(d[14]), "+f"(d[15]),
        "+f"(d[16]), "+f"(d[17]), "+f"(d[18]), "+f"(d[19]), "+f"(d[20]), "+f"(d[21]), "+f"(d[22]), "+f"(d[23]),
        "+f"(d[24]), "+f"(d[25]), "+f"(d[26]), "+f"(d[27]), "+f"(d[28]), "+f"(d[29]), "+f"(d[30]), "+f"(d[31]),
        "+f"(d[32]), "+f"(d[33]), "+f"(d[34]), "+f"(d[35]), "+f"(d[36]), "+f"(d[37]), "+f"(d[38]), "+f"(d[39]),
        "+f"(d[40]), "+f"(d[41]), "+f"(d[42]), "+f"(d[43]), "+f"(d[44]), "+f"(d[45]), "+f"(d[46]), "+f"(d[47]),
        "+f"(d[48]), "+f"(d[49]), "+f"(d[50]), "+f"(d[51]), "+f"(d[52]), "+f"(d[53]), "+f"(d[54]), "+f"(d[55]),
        "+f"(d[56]), "+f"(d[57]), "+f"(d[58]), "+f"(d[59]), "+f"(d[60]), "+f"(d[61]), "+f"(d[62]), "+f"(d[63]),
        "+f"(d[64]), "+f"(d[65]), "+f"(d[66]), "+f"(d[67]), "+f"(d[68]), "+f"(d[69]), "+f"(d[70]), "+f"(d[71]),
        "+f"(d[72]), "+f"(d[73]), "+f"(d[74]), "+f"(d[75]), "+f"(d[76]), "+f"(d[77]), "+f"(d[78]), "+f"(d[79]),
        "+f"(d[80]), "+f"(d[81]), "+f"(d[82]), "+f"(d[83]), "+f"(d[84]), "+f"(d[85]), "+f"(d[86]), "+f"(d[87]),
        "+f"(d[88]), "+f"(d[89]), "+f"(d[90]), "+f"(d[91]), "+f"(d[92]), "+f"(d[93]), "+f"(d[94]), "+f"(d[95])
      : "l"(descA), "l"(descB));
}
__device__ __forceinline__ void mma_ss192_p(float (&d)[96], uint64_t descA, uint64_t descB, int acc) {
  asm volatile("{\n.reg .pred p;\nsetp.ne.b32 p, %98, 0;\n"
      "wgmma.mma_async.sync.aligned.m64n192k16.f32.bf16.bf16 {"
      "%0, %1, %2, %3, %4, %5, %6, %7, %8, %9, %10, %11, %12, %13, %14, %15, "
      "%16, %17, %18, %19, %20, %21, %22, %23, %24, %25, %26, %27, %28, %29, %30, %31, "
      "%32, %33, %34, %35, %36, %37, %38, %39, %40, %41, %42, %43, %44, %45, %46, %47, "
      "%48, %49, %50, %51, %52, %53, %54, %55, %56, %57, %58, %59, %60, %61, %62, %63, "
      "%64, %65, %66, %67, %68, %69, %70, %71, %72, %73, %74, %75, %76, %77, %78, %79, "
      "%80, %81, %82, %83, %84, %85, %86, %87, %88, %89, %90, %91, %92, %93, %94, %95"
      "}, %96, %97, p, 1, 1, 0, 1;\n}\n"
      : "+f"(d[0]), "+f"(d[1]), "+f"(d[2]), "+f"(d[3]), "+f"(d[4]), "+f"(d[5]), "+f"(d[6]), "+f"(d[7]),
        "+f"(d[8]), "+f"(d[9]), "+f"(d[10]), "+f"(d[11]), "+f"(d[12]), "+f"(d[13]), "+f"(d[14]), "+f"(d[15]),
        "+f"(d[16]), "+f"(d[17]), "+f"(d[18]), "+f"(d[19]), "+f"(d[20]), "+f"(d[21]), "+f"(d[22]), "+f"(d[23]),
        "+f"(d[24]), "+f"(d[25]), "+f"(d[26]), "+f"(d[27]), "+f"(d[28]), "+f"(d[29]), "+f"(d[30]), "+f"(d[31]),
        "+f"(d[32]), "+f"(d[33]), "+f"(d[34]), "+f"(d[35]), "+f"(d[36]), "+f"(d[37]), "+f"(d[38]), "+f"(d[39]),
        "+f"(d[40]), "+f"(d[41]), "+f"(d[42]), "+f"(d[43]), "+f"(d[44]), "+f"(d[45]), "+f"(d[46]), "+f"(d[47]),
        "+f"(d[48]), "+f"(d[49]), "+f"(d[50]), "+f"(d[51]), "+f"(d[52]), "+f"(d[53]), "+f"(d[54]), "+f"(d[55]),
        "+f"(d[56]), "+f"(d[57]), "+f"(d[58]), "+f"(d[59]), "+f"(d[60]), "+f"(d[61]), "+f"(d[62]), "+f"(d[63]),
        "+f"(d[64]), "+f"(d[65]), "+f"(d[66]), "+f"(d[67]), "+f"(d[68]), "+f"(d[69]), "+f"(d[70]), "+f"(d[71]),
        "+f"(d[72]), "+f"(d[73]), "+f"(d[74]), "+f"(d[75]), "+f"(d[76]), "+f"(d[77]), "+f"(d[78]), "+f"(d[79]),
        "+f"(d[80]), "+f"(d[81]), "+f"(d[82]), "+f"(d[83]), "+f"(d[84]), "+f"(d[85]), "+f"(d[86]), "+f"(d[87]),
        "+f"(d[88]), "+f"(d[89]), "+f"(d[90]), "+f"(d[91]), "+f"(d[92]), "+f"(d[93]), "+f"(d[94]), "+f"(d[95])
      : "l"(descA), "l"(descB), "r"(acc));
}

__device__ __forceinline__ void mma_ss80_tt(float (&d)[40], uint64_t descA, uint64_t descB) {
  asm volatile("wgmma.mma_async.sync.aligned.m64n80k16.f32.bf16.bf16 {"
      "%0, %1, %2, %3, %4, %5, %6, %7, %8, %9, %10, %11, %12, %13, %14, %15, "
      "%16, %17, %18, %19, %20, %21, %22, %23, %24, %25, %26, %27, %28, %29, %30, %31, "
      "%32, %33, %34, %35, %36, %37, %38, %39"
      "}, %40, %41, 1, 1, 1, 1, 1;\n"
      : "+f"(d[0]), "+f"(d[1]), "+f"(d[2]), "+f"(d[3]), "+f"(d[4]), "+f"(d[5]), "+f"(d[6]), "+f"(d[7]),
        "+f"(d[8]), "+f"(d[9]), "+f"(d[10]), "+f"(d[11]), "+f"(d[12]), "+f"(d[13]), "+f"(d[14]), "+f"(d[15]),
        "+f"(d[16]), "+f"(d[17]), "+f"(d[18]), "+f"(d[19]), "+f"(d[20]), "+f"(d[21]), "+f"(d[22]), "+f"(d[23]),
        "+f"(d[24]), "+f"(d[25]), "+f"(d[26]), "+f"(d[27]), "+f"(d[28]), "+f"(d[29]), "+f"(d[30]), "+f"(d[31]),
        "+f"(d[32]), "+f"(d[33]), "+f"(d[34]), "+f"(d[35]), "+f"(d[36]), "+f"(d[37]), "+f"(d[38]), "+f"(d[39])
      : "l"(descA), "l"(descB));
}
__device__ __forceinline__ void mma_ss80_tt_z(float (&d)[40], uint64_t descA, uint64_t descB) {
  asm volatile("wgmma.mma_async.sync.aligned.m64n80k16.f32.bf16.bf16 {"
      "%0, %1, %2, %3, %4, %5, %6, %7, %8, %9, %10, %11, %12, %13, %14, %15, "
      "%16, %17, %18, %19, %20, %21, %22, %23, %24, %25, %26, %27, %28, %29, %30, %31, "
      "%32, %33, %34, %35, %36, %37, %38, %39"
      "}, %40, %41, 0, 1, 1, 1, 1;\n"
      : "=f"(d[0]), "=f"(d[1]), "=f"(d[2]), "=f"(d[3]), "=f"(d[4]), "=f"(d[5]), "=f"(d[6]), "=f"(d[7]),
        "=f"(d[8]), "=f"(d[9]), "=f"(d[10]), "=f"(d[11]), "=f"(d[12]), "=f"(d[13]), "=f"(d[14]), "=f"(d[15]),
        "=f"(d[16]), "=f"(d[17]), "=f"(d[18]), "=f"(d[19]), "=f"(d[20]), "=f"(d[21]), "=f"(d[22]), "=f"(d[23]),
        "=f"(d[24]), "=f"(d[25]), "=f"(d[26]), "=f"(d[27]), "=f"(d[28]), "=f"(d[29]), "=f"(d[30]), "=f"(d[31]),
        "=f"(d[32]), "=f"(d[33]), "=f"(d[34]), "=f"(d[35]), "=f"(d[36]), "=f"(d[37]), "=f"(d[38]), "=f"(d[39])
      : "l"(descA), "l"(descB));
}

__device__ __forceinline__ void mma_rs80_k(float (&d)[40], const uint32_t (&a)[4], uint64_t descB) {
  asm volatile("wgmma.mma_async.sync.aligned.m64n80k16.f32.bf16.bf16 {"
      "%0, %1, %2, %3, %4, %5, %6, %7, %8, %9, %10, %11, %12, %13, %14, %15, "
      "%16, %17, %18, %19, %20, %21, %22, %23, %24, %25, %26, %27, %28, %29, %30, %31, "
      "%32, %33, %34, %35, %36, %37, %38, %39"
      "}, {%40, %41, %42, %43}, %44, 1, 1, 1, 0;\n"
      : "+f"(d[0]), "+f"(d[1]), "+f"(d[2]), "+f"(d[3]), "+f"(d[4]), "+f"(d[5]), "+f"(d[6]), "+f"(d[7]),
        "+f"(d[8]), "+f"(d[9]), "+f"(d[10]), "+f"(d[11]), "+f"(d[12]), "+f"(d[13]), "+f"(d[14]), "+f"(d[15]),
        "+f"(d[16]), "+f"(d[17]), "+f"(d[18]), "+f"(d[19]), "+f"(d[20]), "+f"(d[21]), "+f"(d[22]), "+f"(d[23]),
        "+f"(d[24]), "+f"(d[25]), "+f"(d[26]), "+f"(d[27]), "+f"(d[28]), "+f"(d[29]), "+f"(d[30]), "+f"(d[31]),
        "+f"(d[32]), "+f"(d[33]), "+f"(d[34]), "+f"(d[35]), "+f"(d[36]), "+f"(d[37]), "+f"(d[38]), "+f"(d[39])
      : "r"(a[0]), "r"(a[1]), "r"(a[2]), "r"(a[3]), "l"(descB));
}
__device__ __forceinline__ void mma_rs80_k_z(float (&d)[40], const uint32_t (&a)[4], uint64_t descB) {
  asm volatile("wgmma.mma_async.sync.aligned.m64n80k16.f32.bf16.bf16 {"
      "%0, %1, %2, %3, %4, %5, %6, %7, %8, %9, %10, %11, %12, %13, %14, %15, "
      "%16, %17, %18, %19, %20, %21, %22, %23, %24, %25, %26, %27, %28, %29, %30, %31, "
      "%32, %33, %34, %35, %36, %37, %38, %39"
      "}, {%40, %41, %42, %43}, %44, 0, 1, 1, 0;\n"
      : "=f"(d[0]), "=f"(d[1]), "=f"(d[2]), "=f"(d[3]), "=f"(d[4]), "=f"(d[5]), "=f"(d[6]), "=f"(d[7]),
        "=f"(d[8]), "=f"(d[9]), "=f"(d[10]), "=f"(d[11]), "=f"(d[12]), "=f"(d[13]), "=f"(d[14]), "=f"(d[15]),
        "=f"(d[16]), "=f"(d[17]), "=f"(d[18]), "=f"(d[19]), "=f"(d[20]), "=f"(d[21]), "=f"(d[22]), "=f"(d[23]),
        "=f"(d[24]), "=f"(d[25]), "=f"(d[26]), "=f"(d[27]), "=f"(d[28]), "=f"(d[29]), "=f"(d[30]), "=f"(d[31]),
        "=f"(d[32]), "=f"(d[33]), "=f"(d[34]), "=f"(d[35]), "=f"(d[36]), "=f"(d[37]), "=f"(d[38]), "=f"(d[39])
      : "r"(a[0]), "r"(a[1]), "r"(a[2]), "r"(a[3]), "l"(descB));
}

__device__ __forceinline__ void mma_rs48_k(float (&d)[24], const uint32_t (&a)[4], uint64_t descB) {
  asm volatile("wgmma.mma_async.sync.aligned.m64n48k16.f32.bf16.bf16 {"
      "%0, %1, %2, %3, %4, %5, %6, %7, %8, %9, %10, %11, %12, %13, %14, %15, "
      "%16, %17, %18, %19, %20, %21, %22, %23"
      "}, {%24, %25, %26, %27}, %28, 1, 1, 1, 0;\n"
      : "+f"(d[0]), "+f"(d[1]), "+f"(d[2]), "+f"(d[3]), "+f"(d[4]), "+f"(d[5]), "+f"(d[6]), "+f"(d[7]),
        "+f"(d[8]), "+f"(d[9]), "+f"(d[10]), "+f"(d[11]), "+f"(d[12]), "+f"(d[13]), "+f"(d[14]), "+f"(d[15]),
        "+f"(d[16]), "+f"(d[17]), "+f"(d[18]), "+f"(d[19]), "+f"(d[20]), "+f"(d[21]), "+f"(d[22]), "+f"(d[23])
      : "r"(a[0]), "r"(a[1]), "r"(a[2]), "r"(a[3]), "l"(descB));
}
__device__ __forceinline__ void mma_rs48_k_z(float (&d)[24], const uint32_t (&a)[4], uint64_t descB) {
  asm volatile("wgmma.mma_async.sync.aligned.m64n48k16.f32.bf16.bf16 {"
      "%0, %1, %2, %3, %4, %5, %6, %7, %8, %9, %10, %11, %12, %13, %14, %15, "
      "%16, %17, %18, %19, %20, %21, %22, %23"
      "}, {%24, %25, %26, %27}, %28, 0, 1, 1, 0;\n"
      : "=f"(d[0]), "=f"(d[1]), "=f"(d[2]), "=f"(d[3]), "=f"(d[4]), "=f"(d[5]), "=f"(d[6]), "=f"(d[7]),
        "=f"(d[8]), "=f"(d[9]), "=f"(d[10]), "=f"(d[11]), "=f"(d[12]), "=f"(d[13]), "=f"(d[14]), "=f"(d[15]),
        "=f"(d[16]), "=f"(d[17]), "=f"(d[18]), "=f"(d[19]), "=f"(d[20]), "=f"(d[21]), "=f"(d[22]), "=f"(d[23])
      : "r"(a[0]), "r"(a[1]), "r"(a[2]), "r"(a[3]), "l"(descB));
}

__device__ __forceinline__ void mma_rs160_n(float (&d)[80], const uint32_t (&a)[4], uint64_t descB) {
  asm volatile("wgmma.mma_async.sync.aligned.m64n160k16.f32.bf16.bf16 {"
      "%0, %1, %2, %3, %4, %5, %6, %7, %8, %9, %10, %11, %12, %13, %14, %15, "
      "%16, %17, %18, %19, %20, %21, %22, %23, %24, %25, %26, %27, %28, %29, %30, %31, "
      "%32, %33, %34, %35, %36, %37, %38, %39, %40, %41, %42, %43, %44, %45, %46, %47, "
      "%48, %49, %50, %51, %52, %53, %54, %55, %56, %57, %58, %59, %60, %61, %62, %63, "
      "%64, %65, %66, %67, %68, %69, %70, %71, %72, %73, %74, %75, %76, %77, %78, %79"
      "}, {%80, %81, %82, %83}, %84, 1, 1, 1, 1;\n"
      : "+f"(d[0]), "+f"(d[1]), "+f"(d[2]), "+f"(d[3]), "+f"(d[4]), "+f"(d[5]), "+f"(d[6]), "+f"(d[7]),
        "+f"(d[8]), "+f"(d[9]), "+f"(d[10]), "+f"(d[11]), "+f"(d[12]), "+f"(d[13]), "+f"(d[14]), "+f"(d[15]),
        "+f"(d[16]), "+f"(d[17]), "+f"(d[18]), "+f"(d[19]), "+f"(d[20]), "+f"(d[21]), "+f"(d[22]), "+f"(d[23]),
        "+f"(d[24]), "+f"(d[25]), "+f"(d[26]), "+f"(d[27]), "+f"(d[28]), "+f"(d[29]), "+f"(d[30]), "+f"(d[31]),
        "+f"(d[32]), "+f"(d[33]), "+f"(d[34]), "+f"(d[35]), "+f"(d[36]), "+f"(d[37]), "+f"(d[38]), "+f"(d[39]),
        "+f"(d[40]), "+f"(d[41]), "+f"(d[42]), "+f"(d[43]), "+f"(d[44]), "+f"(d[45]), "+f"(d[46]), "+f"(d[47]),
        "+f"(d[48]), "+f"(d[49]), "+f"(d[50]), "+f"(d[51]), "+f"(d[52]), "+f"(d[53]), "+f"(d[54]), "+f"(d[55]),
        "+f"(d[56]), "+f"(d[57]), "+f"(d[58]), "+f"(d[59]), "+f"(d[60]), "+f"(d[61]), "+f"(d[62]), "+f"(d[63]),
        "+f"(d[64]), "+f"(d[65]), "+f"(d[66]), "+f"(d[67]), "+f"(d[68]), "+f"(d[69]), "+f"(d[70]), "+f"(d[71]),
        "+f"(d[72]), "+f"(d[73]), "+f"(d[74]), "+f"(d[75]), "+f"(d[76]), "+f"(d[77]), "+f"(d[78]), "+f"(d[79])
      : "r"(a[0]), "r"(a[1]), "r"(a[2]), "r"(a[3]), "l"(descB));
}
__device__ __forceinline__ void mma_rs160_n_z(float (&d)[80], const uint32_t (&a)[4], uint64_t descB) {
  asm volatile("wgmma.mma_async.sync.aligned.m64n160k16.f32.bf16.bf16 {"
      "%0, %1, %2, %3, %4, %5, %6, %7, %8, %9, %10, %11, %12, %13, %14, %15, "
      "%16, %17, %18, %19, %20, %21, %22, %23, %24, %25, %26, %27, %28, %29, %30, %31, "
      "%32, %33, %34, %35, %36, %37, %38, %39, %40, %41, %42, %43, %44, %45, %46, %47, "
      "%48, %49, %50, %51, %52, %53, %54, %55, %56, %57, %58, %59, %60, %61, %62, %63, "
      "%64, %65, %66, %67, %68, %69, %70, %71, %72, %73, %74, %75, %76, %77, %78, %79"
      "}, {%80, %81, %82, %83}, %84, 0, 1, 1, 1;\n"
      : "=f"(d[0]), "=f"(d[1]), "=f"(d[2]), "=f"(d[3]), "=f"(d[4]), "=f"(d[5]), "=f"(d[6]), "=f"(d[7]),
        "=f"(d[8]), "=f"(d[9]), "=f"(d[10]), "=f"(d[11]), "=f"(d[12]), "=f"(d[13]), "=f"(d[14]), "=f"(d[15]),
        "=f"(d[16]), "=f"(d[17]), "=f"(d[18]), "=f"(d[19]), "=f"(d[20]), "=f"(d[21]), "=f"(d[22]), "=f"(d[23]),
        "=f"(d[24]), "=f"(d[25]), "=f"(d[26]), "=f"(d[27]), "=f"(d[28]), "=f"(d[29]), "=f"(d[30]), "=f"(d[31]),
        "=f"(d[32]), "=f"(d[33]), "=f"(d[34]), "=f"(d[35]), "=f"(d[36]), "=f"(d[37]), "=f"(d[38]), "=f"(d[39]),
        "=f"(d[40]), "=f"(d[41]), "=f"(d[42]), "=f"(d[43]), "=f"(d[44]), "=f"(d[45]), "=f"(d[46]), "=f"(d[47]),
        "=f"(d[48]), "=f"(d[49]), "=f"(d[50]), "=f"(d[51]), "=f"(d[52]), "=f"(d[53]), "=f"(d[54]), "=f"(d[55]),
        "=f"(d[56]), "=f"(d[57]), "=f"(d[58]), "=f"(d[59]), "=f"(d[60]), "=f"(d[61]), "=f"(d[62]), "=f"(d[63]),
        "=f"(d[64]), "=f"(d[65]), "=f"(d[66]), "=f"(d[67]), "=f"(d[68]), "=f"(d[69]), "=f"(d[70]), "=f"(d[71]),
        "=f"(d[72]), "=f"(d[73]), "=f"(d[74]), "=f"(d[75]), "=f"(d[76]), "=f"(d[77]), "=f"(d[78]), "=f"(d[79])
      : "r"(a[0]), "r"(a[1]), "r"(a[2]), "r"(a[3]), "l"(descB));
}

__device__ __forceinline__ void feature_map(const uint32_t (&P)[2][10], uint32_t (&fr)[10][4]) {
  constexpr float L2E = 1.4426950408889634f;
#pragma unroll
  for (int p = 0; p < 2; p++) {
#pragma unroll
    for (int r = 0; r < 2; r++) {
      uint32_t mx = P[r][5 * p], mn = mx;
#pragma unroll
      for (int g = 1; g < 5; g++) { mx = max_bf2(mx, P[r][5 * p + g]); mn = min_bf2(mn, P[r][5 * p + g]); }
      mx = max_bf2(mx, __shfl_xor_sync(0xffffffffu, mx, 1));
      mn = min_bf2(mn, __shfl_xor_sync(0xffffffffu, mn, 1));
      mx = max_bf2(mx, __shfl_xor_sync(0xffffffffu, mx, 2));
      mn = min_bf2(mn, __shfl_xor_sync(0xffffffffu, mn, 2));
      float mx0 = -bf_lo(mx) * L2E, mx1 = -bf_hi(mx) * L2E, mn0 = bf_lo(mn) * L2E, mn1 = bf_hi(mn) * L2E;
      float ep0[5], ep1[5], en0[5], en1[5];
      float sp0 = 0.f, sp1 = 0.f, sn0 = 0.f, sn1 = 0.f;
#pragma unroll
      for (int g = 0; g < 5; g++) {
        float x0 = bf_lo(P[r][5 * p + g]), x1 = bf_hi(P[r][5 * p + g]);
        ep0[g] = ex2(fmaf(x0, L2E, mx0)); ep1[g] = ex2(fmaf(x1, L2E, mx1));
        en0[g] = ex2(fmaf(x0, -L2E, mn0)); en1[g] = ex2(fmaf(x1, -L2E, mn1));
        sp0 += ep0[g]; sp1 += ep1[g]; sn0 += en0[g]; sn1 += en1[g];
      }
      sp0 += __shfl_xor_sync(0xffffffffu, sp0, 1); sp1 += __shfl_xor_sync(0xffffffffu, sp1, 1);
      sn0 += __shfl_xor_sync(0xffffffffu, sn0, 1); sn1 += __shfl_xor_sync(0xffffffffu, sn1, 1);
      sp0 += __shfl_xor_sync(0xffffffffu, sp0, 2); sp1 += __shfl_xor_sync(0xffffffffu, sp1, 2);
      sn0 += __shfl_xor_sync(0xffffffffu, sn0, 2); sn1 += __shfl_xor_sync(0xffffffffu, sn1, 2);
      sp0 = rcp(sp0); sp1 = rcp(sp1); sn0 = rcp(sn0); sn1 = rcp(sn1);
#pragma unroll
      for (int g = 0; g < 5; g++) {
        fr[5 * p + g][r] = pack_bf16(ep0[g] * sp0, ep1[g] * sp1);
        fr[5 * p + g][2 + r] = pack_bf16(en0[g] * sn0, en1[g] * sn1);
      }
    }
  }
}

template <int V> struct IntC { static constexpr int value = V; };
struct Ring {
  uint32_t idx, phase;
  template <int N> __device__ __forceinline__ void next() { if (++idx == N) { idx = 0; phase ^= 1; } }
};

}

__global__ void __cluster_dims__(2, 1, 1) __launch_bounds__(384, 1)
fused_kernel(const __grid_constant__ Maps maps, const __nv_bfloat16* __restrict__ x, const __nv_bfloat16* __restrict__ wqkv,
             const __nv_bfloat16* __restrict__ wphi, const __nv_bfloat16* __restrict__ w1, const __nv_bfloat16* __restrict__ w2,
             const __nv_bfloat16* __restrict__ w3, const __nv_bfloat16* __restrict__ w4, const __nv_bfloat16* __restrict__ wo,
             const __nv_bfloat16* __restrict__ gate_w, __nv_bfloat16* __restrict__ out) {
  extern __shared__ __align__(1024) uint8_t sgen[];
  const uint32_t sb = smem_u32(sgen);
  const uint32_t sb16 = (sb & 0x3FFFFu) >> 4;
  const uint32_t bars = sb + OFF_BAR;
  const uint32_t fullA = bars + 8 * B_FULLA, emptyA = bars + 8 * B_EMPTYA, fullB = bars + 8 * B_FULLB, emptyB = bars + 8 * B_EMPTYB;

  const int tid = threadIdx.x;
  const int rank = blockIdx.x & 1;
  const int pairIdx = blockIdx.x >> 1;
  const int i = pairIdx >> 2, j = 2 * (pairIdx & 3) + rank;
  const int k3 = (5 * (pairIdx & 3) + 1) >> 1;

  TSTAMP(0);
  auto load_p1_b = [&](int k, uint32_t slot, uint32_t bar) {
    mbar_expect_tx(bar, 40960);
    tma4d(slot + 8192, &maps.qm, bar, 0, 64 * k, 0, j);
    tma3d(slot, &maps.w1m, bar, 0, 64 * k, j);
    tma4d(slot + 32768 + 2048, &maps.qr, bar, 64, 64 * k, 0, j);
    tma3d(slot + 32768, &maps.w1r, bar, 64, 64 * k, j);
  };
  if (tid >= 256) {
    asm volatile("setmaxnreg.dec.sync.aligned.u32 40;");
    if (tid == 256) {
#pragma unroll
      for (int s = 0; s < NA; s++) mbar_init(fullA + 8 * s, 1);
      asm volatile("fence.mbarrier_init.release.cluster;" ::: "memory");
#pragma unroll 1
      for (int u = 0; u < 4; u++) {
        if ((u & 1) == 0) mbar_expect_tx(fullA + 4 * u, SLOT_A);
        tma2d(sb + OFF_A + u * 8192, &maps.x, fullA + 8 * (u >> 1), 64 * (u >> 1), 128 * i + 64 * (u & 1));
      }
    } else if (tid == 288) {
#pragma unroll
      for (int s = 0; s < NB; s++) mbar_init(fullB + 8 * s, 1);
      asm volatile("fence.mbarrier_init.release.cluster;" ::: "memory");
#pragma unroll 1
      for (int k = 0; k < 2; k++) load_p1_b(k, sb + OFF_B + k * SLOT_B, fullB + 8 * k);
      l2_prefetch(wqkv + (size_t)(128 + 4 * blockIdx.x) * (3 * D_), 4 * 3 * D_ * 2);
    } else if (tid == 320) {
#pragma unroll
      for (int b = B_CS; b < NBAR; b++) mbar_init(bars + 8 * b, b < B_EMPTYB ? 1 : b < B_EMPTYA ? 8 : b < B_X1P ? 16 : 2);
#pragma unroll
      for (int b = B_DSR; b < B_EMPTYB; b++) mbar_expect_tx(bars + 8 * b, 10240);
      asm volatile("fence.mbarrier_init.release.cluster;" ::: "memory");
    }
    __syncwarp();
    asm volatile("barrier.cluster.arrive.relaxed.aligned;" ::: "memory");
    auto get_epoch = [&]() { return *reinterpret_cast<volatile unsigned*>(g_flags + FL_DONE * 32) / NCTA; };
    if (tid >= 320) {
      const int lane = tid & 31, ch = lane % 10, rg = lane / 10;
      const __nv_bfloat16* p = w1 + (size_t)(40 * i + (tid >= 352 ? 20 : 0) + rg) * D_ + 80 * j + 8 * ch;
      const unsigned par = get_epoch() & 1;
      float a[8];
#pragma unroll
      for (int e = 0; e < 8; e++) a[e] = 0.f;
#pragma unroll
      for (int it = 0; it < 7; it++) {
        uint4 v = make_uint4(0, 0, 0, 0);
        if (lane < 30 && 3 * it + rg < 20) v = __ldg(reinterpret_cast<const uint4*>(p + (size_t)it * 3 * D_));
        a[0] += bf_lo(v.x); a[1] += bf_hi(v.x); a[2] += bf_lo(v.y); a[3] += bf_hi(v.y);
        a[4] += bf_lo(v.z); a[5] += bf_hi(v.z); a[6] += bf_lo(v.w); a[7] += bf_hi(v.w);
      }
#pragma unroll
      for (int e = 0; e < 8; e++) a[e] += __shfl_down_sync(0xffffffffu, a[e], 10) + __shfl_down_sync(0xffffffffu, a[e], 20);
      if (lane < 10) {
        float* cd = g_acc[par] + 8 * KV_J + 80 * j + 8 * ch;
        red_add4(cd, a[0], a[1], a[2], a[3]); red_add4(cd + 4, a[4], a[5], a[6], a[7]);
      }
      __syncwarp();
      if (lane == 0) flag_add(FL_CS + j);
      __syncwarp();
    }
    asm volatile("barrier.cluster.wait.aligned;" ::: "memory");
    const int lane = tid & 31, pw = (tid >> 5) & 3;
    if (pw == 0) {
      if (tid == 256) {
        Ring r{2, 1};
        unsigned ep1 = 0;
#pragma unroll 1
        for (int k = 2; k < 25; k++) {
          if (k == 4) ep1 = get_epoch() + 1;
          if (k == 10 || k == 17) {
            if (k == 10) mbar_wait(bars + 8 * B_HST, 0);
            flag_wait(k == 10 ? FL_H + 2 * i + rank : FL_X1 + i, ep1 * 8u);
            TSTAMPX(k == 10 ? 29 : 30);
          }
          if (k == 15) mbar_wait(bars + 8 * B_X1P, 0);
          mbar_wait(emptyA + 8 * r.idx, r.phase);
          const uint32_t bar = fullA + 8 * r.idx, slot = sb + OFF_A + r.idx * SLOT_A;
          mbar_expect_tx(bar, SLOT_A);
          if (k >= 10 && k < 15) tma2d(slot, &maps.hs, bar, 64 * (k - 10) + 320 * rank, 128 * i);
          else tma2d_mc(slot + rank * 8192, k < 10 ? &maps.x : &maps.x1, bar, 64 * (k < 10 ? k : (k - 15 + k3) % 10), 128 * i + 64 * rank);
          r.next<NA>();
        }
      }
    } else if (pw == 1) {
      if (tid == 288) {
        Ring r{2, 1};
#pragma unroll 1
        for (int k = 2; k < 18; k++) {
          mbar_wait(emptyB + 8 * r.idx, r.phase);
          const uint32_t bar = fullB + 8 * r.idx, slot = sb + OFF_B + r.idx * SLOT_B;
          if (k < 10) {
            load_p1_b(k, slot, bar);
          } else if (k < 13) {
            mbar_expect_tx(bar, k < 12 ? 40960 : 20480);
            tma3d(slot, &maps.w2, bar, 0, 320 * rank + 128 * (k - 10), 5 * (j >> 1));
            if (k < 12) tma3d(slot + 20480, &maps.w2, bar, 0, 320 * rank + 128 * (k - 10) + 64, 5 * (j >> 1));
          } else {
            mbar_expect_tx(bar, 49152);
            tma3d(slot, &maps.w3, bar, 0, 64 * ((2 * (k - 13) + k3) % 10), 3 * j);
            tma3d(slot + 24576, &maps.w3, bar, 0, 64 * ((2 * (k - 13) + 1 + k3) % 10), 3 * j);
          }
          r.next<NB>();
        }
        Ring r4{0, 1};
#pragma unroll 1
        for (int n = 0; n < 16; n++) {
          if (n == 0 || n == 1 || n == 3) { mbar_wait(emptyB + 8 * r.idx, r.phase); r.next<NB>(); }
          mbar_wait(bars + 8 * (B_EMPTY4 + r4.idx), r4.phase);
          const uint32_t bar = bars + 8 * (B_FULL4 + r4.idx), slot = sb + OFF_B + r4.idx * UNIT4;
          const int u = n & 3, m = ((j >> 1) + 1 + (n >> 2)) & 3;
          mbar_expect_tx(bar, u == 0 ? 25600 : 20480);
          tma3d(slot, u == 0 ? &maps.wo : &maps.w4, bar, 0, u == 0 ? 80 * j : 192 * j + 64 * u - 64, 5 * m);
          r4.next<NU4>();
        }
      }
    } else {
      const unsigned epoch = get_epoch();
      float* accg = g_acc[epoch & 1];
      if (pw == 2) {
        {
          float* nxt = g_acc[(epoch + 1) & 1];
          constexpr int PER = ACC_FLOATS / NCTA;
#pragma unroll 1
          for (int e = lane; e < PER; e += 32) nxt[blockIdx.x * PER + e] = 0.f;
        }
        if (tid == 320) {
          flag_wait(FL_CS + j, (epoch + 1) * 32u);
          flag_wait(FL_ST + i, (epoch + 1) * 8u);
          fence_async_glb();
          *reinterpret_cast<volatile uint32_t*>(sgen + OFF_BAR + 8 * NBAR) = (epoch + 1) & 1;
          mbar_expect_tx(bars + 8 * B_CS, 320 + 2048);
          bulk_load(sb + OFF_CS, accg + 8 * KV_J + 80 * j, 320, bars + 8 * B_CS);
          bulk_load(sb + OFF_XST, g_xstat + 128 * i, 2048, bars + 8 * B_CS);
          TSTAMPX(21);
          l2_prefetch(w2 + (size_t)blockIdx.x * (D_ * D_ / NCTA), D_ * D_ * 2 / NCTA);
          flag_wait(FL_H + 2 * i + rank, (epoch + 1) * 8u);
          l2_prefetch(w3 + (size_t)blockIdx.x * (F_ * D_ / NCTA), F_ * D_ * 2 / NCTA);
          l2_prefetch(w4 + (size_t)blockIdx.x * (F_ * D_ / NCTA), F_ * D_ * 2 / NCTA);
          l2_prefetch(wo + (size_t)blockIdx.x * (D_ * D_ / NCTA), D_ * D_ * 2 / NCTA);
          flag_wait(FL_KV + j, (epoch + 1) * 16u);
          mbar_expect_tx(bars + 8 * B_KV, KV_J * 4);
          bulk_load(sb + OFF_MISC, accg + j * KV_J, KV_J * 4, bars + 8 * B_KV);
          TSTAMPX(22);
        }
        __syncwarp();
#pragma unroll 1
        for (int m = 0; m < 6; m++) {
          const int col = 192 * j + 32 * m + 8 * (lane & 3);
          const __nv_bfloat16* p = w3 + (size_t)(40 * i + (lane >> 2) * 5) * F_ + col;
          float a[8];
#pragma unroll
          for (int e = 0; e < 8; e++) a[e] = 0.f;
#pragma unroll
          for (int it = 0; it < 5; it++) {
            const uint4 v = __ldg(reinterpret_cast<const uint4*>(p + (size_t)it * F_));
            a[0] += bf_lo(v.x); a[1] += bf_hi(v.x); a[2] += bf_lo(v.y); a[3] += bf_hi(v.y);
            a[4] += bf_lo(v.z); a[5] += bf_hi(v.z); a[6] += bf_lo(v.w); a[7] += bf_hi(v.w);
          }
#pragma unroll
          for (int e = 0; e < 4; e++) {
            const float snd = (lane & 4) ? a[e] : a[e + 4], keep = (lane & 4) ? a[e + 4] : a[e];
            a[e] = keep + __shfl_xor_sync(0xffffffffu, snd, 4);
            a[e] += __shfl_xor_sync(0xffffffffu, a[e], 8);
            a[e] += __shfl_xor_sync(0xffffffffu, a[e], 16);
          }
          if (lane < 8) red_add4(accg + 8 * KV_J + D_ + col + (lane >> 2) * 4, a[0], a[1], a[2], a[3]);
        }
        __syncwarp();
        if (tid == 320) {
          flag_add(FL_CS3 + j);
          flag_wait(FL_S1 + i, (epoch + 1) * 8u);
          flag_wait(FL_CS3 + j, (epoch + 1) * 16u);
          fence_async_glb();
          mbar_expect_tx(bars + 8 * B_ST1, 8192 + 768);
          bulk_load(sb + OFF_CS + 320, accg + 8 * KV_J + D_ + 192 * j, 768, bars + 8 * B_ST1);
          bulk_load(sb + OFF_MISC, g_st1 + 128 * i * 8, 8192, bars + 8 * B_ST1);
        }
      }
      if (tid == 352) {
        mbar_wait(bars + 8 * B_SIGP, 0);
        flag_add(FL_ST + i);
        TSTAMPX(20);
        mbar_expect_tx(bars + 8 * B_XR, 20480);
#pragma unroll 1
        for (int u = 0; u < 8; u++)
          tma2d(sb + OFF_B + (u / 3) * SLOT_B + SPARE + (u % 3) * 2560, &maps.xr, bars + 8 * B_XR, 80 * j, 128 * i + 16 * u);
        const int shift = (j < 2) ? 1 : (j < 4) ? -1 : (j < 6) ? 2 : -2;
        if ((shift > 0 && i == 0) || (shift < 0 && i == 15)) {
          const int nz = shift > 0 ? shift : -shift, zr = shift > 0 ? 0 : S_ - nz;
#pragma unroll 1
          for (int e = 0; e < nz * 10; e++)
            reinterpret_cast<uint4*>(g_Hs + (size_t)(2 + zr + e / 10) * D_ + 80 * j)[e % 10] = make_uint4(0, 0, 0, 0);
          fence_async_glb();
        }
        prefetch_tmap(&maps.st_h); prefetch_tmap(&maps.st_x1); prefetch_tmap(&maps.hs); prefetch_tmap(&maps.x1);
        prefetch_tmap(&maps.w2); prefetch_tmap(&maps.w3); prefetch_tmap(&maps.w4); prefetch_tmap(&maps.wo);
        mbar_wait(bars + 8 * B_SIGH, 0);
        TSTAMPX(23);
        tma2d_store(&maps.st_h, sb + OFF_STG, 80 * j, 128 * i + 2 + shift);
        bulk_commit(); bulk_wait<0>();
        mbar_arrive(bars + 8 * B_HST);
        flag_add(FL_H + 2 * i + (j >> 2));
        flag_add_relaxed(FL_H + 2 * ((i + (shift > 0 ? 1 : -1)) & 15) + (j >> 2));
        TSTAMPX(24);
        mbar_wait(bars + 8 * B_SIGKV, 0);
        TSTAMPX(25);
        fence_async_smem();
        asm volatile("cp.reduce.async.bulk.global.shared::cta.bulk_group.add.f32 [%0], [%1], %2;"
                     ::"l"(accg + j * KV_J), "r"(sb + OFF_MISC), "r"(KV_J * 4) : "memory");
        bulk_commit(); bulk_wait<0>();
        flag_add(FL_KV + j);
        TSTAMPX(26);
        mbar_wait(bars + 8 * B_SIGX1, 0);
        TSTAMPX(27);
        tma2d_store(&maps.st_x1, sb + OFF_STG, 80 * j, 128 * i);
        bulk_commit(); bulk_wait<0>();
        flag_add(FL_X1 + i);
        mbar_arrive_cta(bars + 8 * B_X1P, 0); mbar_arrive_cta(bars + 8 * B_X1P, 1);
        TSTAMPX(28);
        mbar_wait(bars + 8 * B_MFREE, 0);
        flag_add(FL_S1 + i);
        mbar_wait(bars + 8 * B_PEER, 0);
        mbar_expect_tx(bars + 8 * B_XR, 20480);
        tma2d(sb + OFF_OUT, &maps.st_x1, bars + 8 * B_XR, 80 * j, 128 * i);
      }
    }
  } else {
    uint4 pv[5], pw_[5], pre;
    {
      const int row = 128 * i + 16 * j + (tid >> 4), l16 = tid & 15;
#pragma unroll
      for (int c = 0; c < 5; c++) pv[c] = __ldg(reinterpret_cast<const uint4*>(x + (size_t)row * D_ + c * 128 + l16 * 8));
      pre = __ldg(reinterpret_cast<const uint4*>(wphi + (size_t)j * 1600) + (tid < 200 ? tid : 0));
#pragma unroll
      for (int c = 0; c < 5; c++) pw_[c] = __ldg(reinterpret_cast<const uint4*>(gate_w + c * 128 + l16 * 8));
    }
    asm volatile("barrier.cluster.arrive.relaxed.aligned;" ::: "memory");
    asm volatile("setmaxnreg.inc.sync.aligned.u32 232;");
    const int wg = tid >> 7, warp = tid >> 5, lane = tid & 31, t = lane & 3;
    const int rloc = warp * 16 + (lane >> 2);
    const float* s_cs = reinterpret_cast<const float*>(sgen + OFF_CS);
    auto signal = [&](int b) {
      __syncwarp();
      if (lane == 0) mbar_arrive(bars + 8 * b);
    };
    auto releaseB = [&](uint32_t bar) {
      __syncwarp();
      if (lane == 0) mbar_arrive(bar);
    };
    auto release = [&](uint32_t bar) {
      __syncwarp();
      if (lane < 2) mbar_arrive_cta(bar, lane);
    };
    const uint32_t stg_lane = (warp * 16 + ((lane >> 3) & 1) * 8 + (lane & 7)) * 160 + (lane >> 4) * 16;

    auto stage_tile = [&](uint32_t stg, const uint32_t (&v)[2][10]) {
#pragma unroll
      for (int s = 0; s < 5; s++) stsm4(stg + stg_lane + s * 32, v[0][2 * s], v[1][2 * s], v[0][2 * s + 1], v[1][2 * s + 1]);
    };

    {
#pragma unroll 1
      for (int e = tid; e < 800; e += 256) sts128(sb + OFF_MISC + e * 16, make_uint4(0, 0, 0, 0));
      bar_sync(1, 256);
      float f[40];
      float s = 0.f, gs = 0.f;
#pragma unroll
      for (int c = 0; c < 5; c++) {
        const uint32_t vv[4] = {pv[c].x, pv[c].y, pv[c].z, pv[c].w}, ww[4] = {pw_[c].x, pw_[c].y, pw_[c].z, pw_[c].w};
#pragma unroll
        for (int e = 0; e < 4; e++) {
          f[8 * c + 2 * e] = bf_lo(vv[e]); f[8 * c + 2 * e + 1] = bf_hi(vv[e]);
          s += f[8 * c + 2 * e] + f[8 * c + 2 * e + 1];
          gs = fmaf(f[8 * c + 2 * e], bf_lo(ww[e]), gs); gs = fmaf(f[8 * c + 2 * e + 1], bf_hi(ww[e]), gs);
        }
      }
#pragma unroll
      for (int o = 1; o < 16; o <<= 1) { s += __shfl_xor_sync(0xffffffffu, s, o); gs += __shfl_xor_sync(0xffffffffu, gs, o); }
      const float mean = s * (1.f / D_);
      float q = 0.f;
#pragma unroll
      for (int e = 0; e < 40; e++) { const float d = f[e] - mean; q = fmaf(d, d, q); }
#pragma unroll
      for (int o = 1; o < 16; o <<= 1) q += __shfl_xor_sync(0xffffffffu, q, o);
      const float rstd = rsqrtf(q * (1.f / D_) + 1e-5f);
      asm volatile("barrier.cluster.wait.aligned;" ::: "memory");
      if ((tid & 15) == 0) g_xstat[128 * i + 16 * j + (tid >> 4)] = make_float4(rstd, -mean, rcp(1.f + __expf(-gs)), 0.f);
      signal(B_SIGP);
      if (tid < 200) {
        const uint32_t ww[4] = {pre.x, pre.y, pre.z, pre.w};
        const int h = tid / 50;
#pragma unroll
        for (int e = 0; e < 8; e++) {
          const int idx = tid * 8 + e, k = idx / 20, ff = idx - 20 * k;
          const int n = 40 * (h >> 1) + 8 * (ff >> 2) + 2 * (ff & 3) + (h & 1);
          const int off = (k >> 4) * 2560 + n * 32 + ((((k >> 3) ^ (n >> 2)) & 1) << 4) + (k & 7) * 2;
          *reinterpret_cast<unsigned short*>(sgen + OFF_MISC + off) = (unsigned short)(ww[e >> 1] >> ((e & 1) * 16));
        }
      }
    }
    TSTAMP(1);

    Ring ra{0, 0}, rb{0, 0};
    uint32_t qp[2][10], P[2][10];
    float st_g[2];
    {
      float accM[128], accR[32];
      uint32_t pa = 0, pb = 0;
#pragma unroll 1
      for (int k = 0; k < 10; k++) {
        mbar_wait(fullA + 8 * ra.idx, ra.phase);
        if (tid == 0) TRACE(32 + k);
        mbar_wait(fullB + 8 * rb.idx, rb.phase);
        if (tid == 0) TRACE(64 + k);
        if (k == 0) TSTAMP(2);
        const uint32_t a0 = sb16 + ((OFF_A + ra.idx * SLOT_A + wg * 8192) >> 4), b0 = sb16 + ((OFF_B + rb.idx * SLOT_B) >> 4);
        wg_fence();
#pragma unroll
        for (int kk = 0; kk < 4; kk++) {
          const uint64_t da = make_desc(a0, kk * 32, 16, 1024, 1);
          if (kk == 0) {
            mma_ss256_p(accM, da, make_desc(b0, 0, 8192, 1024, 1), k);
            mma_ss64_p(accR, da, make_desc(b0, 32768, 2048, 256, 3), k);
          } else {
            mma_ss256(accM, da, make_desc(b0, kk * 2048, 8192, 1024, 1));
            mma_ss64(accR, da, make_desc(b0, 32768 + kk * 512, 2048, 256, 3));
          }
          if (kk == 0) {
            wg_commit();
            if (k > 0) {
              wg_wait<1>();
              if (k - 1 < 8) release(emptyA + 8 * pa);
              releaseB(emptyB + 8 * pb);
            }
          }
        }
        wg_commit();
        pa = ra.idx; pb = rb.idx;
        ra.next<NA>(); rb.next<NB>();
      }
      TSTAMP(18);
      float st_rstd[2], st_mr[2];
      mbar_wait(bars + 8 * B_CS, 0);
#pragma unroll
      for (int r = 0; r < 2; r++) {
        const uint4 st = lds128(sb + OFF_XST + (rloc + 8 * r) * 16);
        st_rstd[r] = __uint_as_float(st.x); st_mr[r] = __uint_as_float(st.y); st_g[r] = __uint_as_float(st.z);
      }
      TSTAMP(19);
      wg_wait<0>();
      fence_regs(accM); fence_regs(accR);
      TSTAMP(3);
#define ACC(P_, G, I_) ((G) < 8 ? accM[(P_) * 32 + ((G) & 7) * 4 + (I_)] : accR[(P_) * 8 + ((G) & 1) * 4 + (I_)])
      {
        uint32_t hv[2][10];
        const GeluC g0 = gelu_consts(st_rstd[0], 1.f), g1 = gelu_consts(st_rstd[1], 1.f);
#pragma unroll
        for (int g = 0; g < 10; g++) {
          const float2 cs = *reinterpret_cast<const float2*>(s_cs + 8 * g + 2 * t);
          const float v0 = gelu_s(fmaf(st_mr[0], cs.x, ACC(0, g, 0)), g0), v1 = gelu_s(fmaf(st_mr[0], cs.y, ACC(0, g, 1)), g0);
          const float v2 = gelu_s(fmaf(st_mr[1], cs.x, ACC(0, g, 2)), g1), v3 = gelu_s(fmaf(st_mr[1], cs.y, ACC(0, g, 3)), g1);
          hv[0][g] = pack_bf16(v0, v1); hv[1][g] = pack_bf16(v2, v3);
        }
        fence_async_smem();
        bar_sync(1, 256);
        stage_tile(sb + OFF_STG, hv);
        fence_async_smem();
        signal(B_SIGH);
      }
      TSTAMP(4);
      uint32_t kf[5][4], qf[5][4];
#pragma unroll
      for (int s = 0; s < 5; s++) {
        kf[s][0] = pack_bf16(ACC(2, 2 * s, 0), ACC(2, 2 * s, 1)); kf[s][1] = pack_bf16(ACC(2, 2 * s, 2), ACC(2, 2 * s, 3));
        kf[s][2] = pack_bf16(ACC(2, 2 * s + 1, 0), ACC(2, 2 * s + 1, 1)); kf[s][3] = pack_bf16(ACC(2, 2 * s + 1, 2), ACC(2, 2 * s + 1, 3));
        qf[s][0] = pack_bf16(ACC(1, 2 * s, 0), ACC(1, 2 * s, 1)); qf[s][1] = pack_bf16(ACC(1, 2 * s, 2), ACC(1, 2 * s, 3));
        qf[s][2] = pack_bf16(ACC(1, 2 * s + 1, 0), ACC(1, 2 * s + 1, 1)); qf[s][3] = pack_bf16(ACC(1, 2 * s + 1, 2), ACC(1, 2 * s + 1, 3));
      }
      float pk[40], pq[40];
      wg_fence();
#pragma unroll
      for (int s = 0; s < 5; s++) {
        if (s == 0) mma_rs80_k_z(pk, kf[s], make_desc(sb16, OFF_MISC, 16, 256, 3));
        else mma_rs80_k(pk, kf[s], make_desc(sb16, OFF_MISC + s * 2560, 16, 256, 3));
      }
      wg_commit();
#pragma unroll
      for (int s = 0; s < 5; s++) {
        if (s == 0) mma_rs80_k_z(pq, qf[s], make_desc(sb16, OFF_MISC, 16, 256, 3));
        else mma_rs80_k(pq, qf[s], make_desc(sb16, OFF_MISC + s * 2560, 16, 256, 3));
      }
      wg_commit();
      {
        const int mat = lane >> 3;
        const int tok = warp * 16 + (mat & 1) * 8 + (lane & 7);
        const uint32_t ones = (t == 0) ? 0x00003f80u : 0u;
        __syncwarp();
#pragma unroll
        for (int p = 0; p < 2; p++) {
          const uint32_t rowa = sb + OFF_A + p * SLOT_A + tok * 128;
#pragma unroll
          for (int gg = 0; gg < 3; gg++) {
            const int g0 = 5 * p + 2 * gg;
            uint32_t r0 = pack_bf16(ACC(3, g0, 0), ACC(3, g0, 1)), r1 = pack_bf16(ACC(3, g0, 2), ACC(3, g0, 3));
            uint32_t r2 = ones, r3 = ones;
            if (gg < 2) { r2 = pack_bf16(ACC(3, g0 + 1, 0), ACC(3, g0 + 1, 1)); r3 = pack_bf16(ACC(3, g0 + 1, 2), ACC(3, g0 + 1, 3)); }
            stsm4(rowa + (((2 * gg + (mat >> 1)) ^ (tok & 7)) << 4), r0, r1, r2, r3);
          }
        }
      }
#undef ACC
      wg_wait<1>();
      fence_regs(pk);
#pragma unroll
      for (int G = 0; G < 10; G++) {
        P[0][G] = pack_bf16(pk[4 * G], pk[4 * G + 1]); P[1][G] = pack_bf16(pk[4 * G + 2], pk[4 * G + 3]);
      }
      wg_wait<0>();
      fence_regs(pq);
#pragma unroll
      for (int G = 0; G < 10; G++) {
        qp[0][G] = pack_bf16(pq[4 * G], pq[4 * G + 1]); qp[1][G] = pack_bf16(pq[4 * G + 2], pq[4 * G + 3]);
      }
    }

    uint32_t fr[10][4];
    int pass;
    pass = gridDim.y;
#pragma unroll 1
    do {
    feature_map(P, fr);
    if (pass != 0) {
    {
      const int mat = lane >> 3;
      const int tok = warp * 16 + (mat & 1) * 8 + (lane & 7);
      const uint32_t base = sb + OFF_B + tok * 32 + (((mat >> 1) ^ ((tok >> 2) & 1)) << 4);
#pragma unroll
      for (int G = 0; G < 10; G++) stsm4(base + G * 4096, fr[G][0], fr[G][1], fr[G][2], fr[G][3]);
      fence_async_smem();
      bar_sync(1, 256);
      float kv[40];
      const uint32_t va = sb16 + ((OFF_A + wg * SLOT_A) >> 4), vb = sb16 + ((OFF_B + wg * 20480) >> 4);
      wg_fence();
#pragma unroll
      for (int ks = 0; ks < 8; ks++) {
        if (ks == 0) mma_ss80_tt_z(kv, make_desc(va, 0, 16, 1024, 1), make_desc(vb, 0, 4096, 256, 3));
        else mma_ss80_tt(kv, make_desc(va, ks * 2048, 16, 1024, 1), make_desc(vb, ks * 512, 4096, 256, 3));
      }
      wg_commit();
      uint32_t xv[2][10];
      {
        mbar_wait(bars + 8 * B_XR, 0);
        const uint32_t xa = sb + OFF_B + (warp / 3) * SLOT_B + SPARE + (warp % 3) * 2560 + (lane >> 2) * 160 + t * 4;
#pragma unroll
        for (int g = 0; g < 10; g++) { xv[0][g] = lds32(xa + g * 16); xv[1][g] = lds32(xa + 1280 + g * 16); }
      }
      float acc[80];
      wg_wait<0>();
      release(emptyA); release(emptyA + 8); releaseB(emptyB); release(bars + 8 * B_PEER2);
      TSTAMP(5);
      mbar_wait(fullA + 8 * 2, 0);
      mbar_wait(fullB + 8 * 1, 1);
      TSTAMP(6);
      wg_fence();
#pragma unroll
      for (int kk = 0; kk < 4; kk++) {
        const uint64_t da = make_desc(sb16 + wg * 512, OFF_A + 2 * SLOT_A + kk * 32, 16, 1024, 1);
        const uint64_t db = make_desc(sb16, OFF_B + SLOT_B + kk * 1024, 4096, 512, 2);
        if (kk == 0) mma_ss160_z(acc, da, db); else mma_ss160(acc, da, db);
      }
      wg_commit();
      ra.next<NA>();
      wg_wait<1>();
      fence_regs(kv);
      TSTAMP(31);
      const uint32_t dst = sb + OFF_MISC + wg * (KV_PAIR * 4);
      const int m0 = (warp & 3) * 16 + (lane >> 2);
#pragma unroll
      for (int r = 0; r < 2; r++) {
        const int m = m0 + 8 * r;
        const bool hi = m >= 20;
        uint32_t v[10];
#pragma unroll
        for (int G = 0; G < 10; G++) v[G] = __float_as_uint(hi ? kv[4 * G + 2 * r + 1] : kv[4 * G + 2 * r]);
        const uint32_t p = dst + 4 * (m < 40 ? m * 48 + t * 12 : 1920 + t * 24 + 12);
        if (m <= 40) {
          sts128(p, make_uint4(v[0], v[1], v[2], v[3])); sts128(p + 16, make_uint4(v[4], v[5], v[6], v[7]));
          sts128(p + 32, make_uint4(v[8], v[9], 0u, 0u));
        }
      }
      if (m0 == 32) {
        const uint32_t p = dst + 4 * (1920 + t * 24);
        sts128(p, make_uint4(__float_as_uint(kv[2]), __float_as_uint(kv[6]), __float_as_uint(kv[10]), __float_as_uint(kv[14])));
        sts128(p + 16, make_uint4(__float_as_uint(kv[18]), __float_as_uint(kv[22]), __float_as_uint(kv[26]), __float_as_uint(kv[30])));
        sts128(p + 32, make_uint4(__float_as_uint(kv[34]), __float_as_uint(kv[38]), 0u, 0u));
      }
      signal(B_SIGKV);
      uint32_t pa = 2, pb = 1;
#pragma unroll 1
      for (int k = 1; k < 5; k++) {
        mbar_wait(fullA + 8 * ra.idx, ra.phase);
        if ((k & 1) == 0) mbar_wait(fullB + 8 * rb.idx, rb.phase);
        const uint32_t a0 = sb16 + ((OFF_A + ra.idx * SLOT_A + wg * 8192) >> 4);
        const uint32_t b0 = sb16 + ((OFF_B + rb.idx * SLOT_B + (k & 1) * 20480) >> 4);
        wg_fence();
#pragma unroll
        for (int kk = 0; kk < 4; kk++) {
          mma_ss160(acc, make_desc(a0, kk * 32, 16, 1024, 1), make_desc(b0, kk * 1024, 4096, 512, 2));
          if (kk == 0) {
            wg_commit();
            wg_wait<1>();
            release(emptyA + 8 * pa);
            if ((k & 1) == 0) releaseB(emptyB + 8 * pb);
          }
        }
        wg_commit();
        pa = ra.idx; pb = rb.idx;
        ra.next<NA>();
        if ((k & 1) || k == 4) rb.next<NB>();
      }
      mbar_wait(bars + 8 * B_PEER2, 0);
      wg_wait<0>();
      fence_regs(acc);
      release(emptyA + 8 * pa);
      TSTAMP(7);
      {
        uint32_t sn[20];
        if (rank) {
#pragma unroll
          for (int e = 0; e < 20; e++) sn[e] = pack_bf16(acc[2 * e], acc[2 * e + 1]);
#pragma unroll
          for (int e = 0; e < 40; e++) acc[e] = acc[40 + e];
        } else {
#pragma unroll
          for (int e = 0; e < 20; e++) sn[e] = pack_bf16(acc[40 + 2 * e], acc[41 + 2 * e]);
        }
        const uint32_t peer = map_peer(sb, rank ^ 1);
#pragma unroll
        for (int q = 0; q < 5; q++)
          st_async16(peer + OFF_B + 20480 + tid * 16 + q * 4096, sn[4 * q], sn[4 * q + 1], sn[4 * q + 2], sn[4 * q + 3],
                     peer + OFF_BAR + 8 * (B_DSR + 8 + wg));
#pragma unroll
        for (int g = 0; g < 10; g++) {
          acc[4 * g] += bf_lo(xv[0][g]); acc[4 * g + 1] += bf_hi(xv[0][g]);
          acc[4 * g + 2] += bf_lo(xv[1][g]); acc[4 * g + 3] += bf_hi(xv[1][g]);
        }
        bar_sync(1, 256);
        mbar_wait(bars + 8 * (B_DSR + 8 + wg), 0);
#pragma unroll
        for (int q = 0; q < 5; q++) {
          const uint4 v = lds128(sb + OFF_B + 20480 + tid * 16 + q * 4096);
          xv[0][2 * q] = pack_bf16(acc[8 * q] + bf_lo(v.x), acc[8 * q + 1] + bf_hi(v.x));
          xv[1][2 * q] = pack_bf16(acc[8 * q + 2] + bf_lo(v.y), acc[8 * q + 3] + bf_hi(v.y));
          xv[0][2 * q + 1] = pack_bf16(acc[8 * q + 4] + bf_lo(v.z), acc[8 * q + 5] + bf_hi(v.z));
          xv[1][2 * q + 1] = pack_bf16(acc[8 * q + 6] + bf_lo(v.w), acc[8 * q + 7] + bf_hi(v.w));
        }
        releaseB(emptyB + 8 * pb);
      }
      TSTAMP(16);
      stage_tile(sb + OFF_STG, xv);
      fence_async_smem();
      signal(B_SIGX1);
      TSTAMP(17);
#pragma unroll
      for (int r = 0; r < 2; r++) {
        float s = 0.f;
#pragma unroll
        for (int g = 0; g < 10; g++) {
          acc[4 * g + 2 * r] = bf_lo(xv[r][g]); acc[4 * g + 2 * r + 1] = bf_hi(xv[r][g]);
          s += acc[4 * g + 2 * r] + acc[4 * g + 2 * r + 1];
        }
        s += __shfl_xor_sync(0xffffffffu, s, 1); s += __shfl_xor_sync(0xffffffffu, s, 2);
        const float mu = s * (1.f / 80.f);
        float q = 0.f;
#pragma unroll
        for (int g = 0; g < 10; g++) {
          const float d0 = acc[4 * g + 2 * r] - mu, d1 = acc[4 * g + 2 * r + 1] - mu;
          q = fmaf(d0, d0, q); q = fmaf(d1, d1, q);
        }
        q += __shfl_xor_sync(0xffffffffu, q, 1); q += __shfl_xor_sync(0xffffffffu, q, 2);
        if (t == 0) g_st1[(128 * i + rloc + 8 * r) * 8 + j] = make_float2(mu, q);
      }
    }
    TSTAMP(8);
#pragma unroll
    for (int G = 0; G < 10; G++) { P[0][G] = qp[0][G]; P[1][G] = qp[1][G]; }
    }
    asm volatile("" : "+r"(pass));
    } while (pass-- != 0);

    uint32_t of[5][4];
    {
      mbar_wait(bars + 8 * B_KV, 0);
      uint4 kvr[2][3];
#pragma unroll
      for (int u = 0; u < 2; u++) {
        const int it = tid + 256 * u, p = it / 192, rem = it - 192 * p, n = rem >> 2, tq = rem & 3;
        const uint32_t sp = sb + OFF_MISC + 4 * (p * KV_PAIR + (n < 40 ? n * 48 + tq * 12 : 1920 + tq * 24 + (n & 1) * 12));
        if (it < 384) { kvr[u][0] = lds128(sp); kvr[u][1] = lds128(sp + 16); kvr[u][2] = lds128(sp + 32); }
      }
      bar_sync(1, 256);
#pragma unroll
      for (int u = 0; u < 2; u++) {
        const int it = tid + 256 * u, p = it / 192, rem = it - 192 * p, n = rem >> 2, tq = rem & 3;
        const int sh = (n < 40 ? (n >= 20) : (n & 1)) * 16;
        const uint32_t v[10] = {kvr[u][0].x, kvr[u][0].y, kvr[u][0].z, kvr[u][0].w, kvr[u][1].x, kvr[u][1].y, kvr[u][1].z, kvr[u][1].w, kvr[u][2].x, kvr[u][2].y};
        uint8_t* dst = sgen + OFF_MISC + p * 7680 + n * 32 + tq * 4;
        const int sw = ((n >> 2) & 1) << 4;
        if (it < 384) {
#pragma unroll
          for (int G = 0; G < 10; G++)
            *reinterpret_cast<uint32_t*>(dst + (G >> 1) * 1536 + (((G & 1) << 4) ^ sw)) = pack_bf16(__uint_as_float(v[G]), 0.f) << sh;
        }
      }
      fence_async_smem();
      bar_sync(1, 256);
      float o0[24], o1[24];
      wg_fence();
#pragma unroll
      for (int g = 0; g < 5; g++) {
        if (g == 0) mma_rs48_k_z(o0, fr[g], make_desc(sb16, OFF_MISC, 16, 256, 3));
        else mma_rs48_k(o0, fr[g], make_desc(sb16, OFF_MISC + g * 1536, 16, 256, 3));
      }
#pragma unroll
      for (int g = 0; g < 5; g++) {
        if (g == 0) mma_rs48_k_z(o1, fr[5], make_desc(sb16, OFF_MISC + 7680, 16, 256, 3));
        else mma_rs48_k(o1, fr[5 + g], make_desc(sb16, OFF_MISC + 7680 + g * 1536, 16, 256, 3));
      }
      wg_commit();
      wg_wait<0>();
      fence_regs(o0); fence_regs(o1);
      signal(B_MFREE);
#pragma unroll
      for (int r = 0; r < 2; r++) {
        const float a0 = __fdividef(st_g[r], o0[20 + 2 * r] + 1e-6f), a1 = __fdividef(st_g[r], o0[21 + 2 * r] + 1e-6f);
        const float b0 = __fdividef(st_g[r], o1[20 + 2 * r] + 1e-6f), b1 = __fdividef(st_g[r], o1[21 + 2 * r] + 1e-6f);
        const float am = t < 2 ? a0 : a1, bm = t < 2 ? b0 : b1;
#pragma unroll
        for (int g = 0; g < 5; g++) {
          const float sa = g < 2 ? a0 : (g == 2 ? am : a1), sb2 = g < 2 ? b0 : (g == 2 ? bm : b1);
          of[g >> 1][(g & 1) * 2 + r] = pack_bf16(o0[4 * g + 2 * r] * sa, o0[4 * g + 2 * r + 1] * sa);
          of[(5 + g) >> 1][((5 + g) & 1) * 2 + r] = pack_bf16(o1[4 * g + 2 * r] * sb2, o1[4 * g + 2 * r + 1] * sb2);
        }
      }
    }
    TSTAMP(9);

    uint32_t hf[12][4];
    float ac4[80];
    Ring r4{0, 0};
    auto unit = [&](auto uc) {
      constexpr int u = decltype(uc)::value;
      mbar_wait(bars + 8 * (B_FULL4 + r4.idx), r4.phase);
      const uint32_t b0 = sb16 + ((OFF_B + r4.idx * UNIT4) >> 4);
      wg_fence();
#pragma unroll
      for (int s = 0; s < (u ? 4 : 5); s++) {
        const uint64_t db = make_desc(b0, s * 1024, u ? 4096 : 5120, 512, 2);
        if (u == 0 && s == 0) mma_rs160_n_z(ac4, of[0], db);
        else if (u == 0) mma_rs160_n(ac4, of[s], db);
        else mma_rs160_n(ac4, hf[(4 * u + 8 + s) % 12], db);
      }
      wg_commit();
      r4.next<NU4>();
    };
    auto rel4 = [&](int back) {
      const int e = (int)r4.idx - back;
      releaseB(bars + 8 * (B_EMPTY4 + (e < 0 ? e + NU4 : e)));
    };
    {
      float acc[96];
      uint32_t pa = 0, pb = 0;
#pragma unroll 1
      for (int k = 0; k < 10; k++) {
        mbar_wait(fullA + 8 * ra.idx, ra.phase);
        if (tid == 0) TRACE(52 + k);
        if ((k & 1) == 0) mbar_wait(fullB + 8 * rb.idx, rb.phase);
        if (tid == 0) TRACE(84 + k);
        if (k == 0) TSTAMP(10);
        const uint32_t a0 = sb16 + ((OFF_A + ra.idx * SLOT_A + wg * 8192) >> 4);
        const uint32_t b0 = sb16 + ((OFF_B + rb.idx * SLOT_B + (k & 1) * 24576) >> 4);
        wg_fence();
#pragma unroll
        for (int kk = 0; kk < 4; kk++) {
          if (kk == 0) mma_ss192_p(acc, make_desc(a0, 0, 16, 1024, 1), make_desc(b0, 0, 8192, 1024, 1), k);
          else mma_ss192(acc, make_desc(a0, kk * 32, 16, 1024, 1), make_desc(b0, kk * 2048, 8192, 1024, 1));
          if (kk == 0) {
            wg_commit();
            if (k > 0) {
              wg_wait<1>();
              release(emptyA + 8 * pa);
              if ((k & 1) == 0) releaseB(emptyB + 8 * pb);
            }
          }
        }
        wg_commit();
        pa = ra.idx; pb = rb.idx;
        ra.next<NA>();
        if (k & 1) rb.next<NB>();
      }
      float rs[2], mm[2];
      mbar_wait(bars + 8 * B_ST1, 0);
#pragma unroll
      for (int r = 0; r < 2; r++) {
        const uint4 su = lds128(sb + OFF_MISC + (rloc + 8 * r) * 64 + t * 16);
        const float m0 = __uint_as_float(su.x), m1 = __uint_as_float(su.z);
        float mu = m0 + m1;
        mu += __shfl_xor_sync(0xffffffffu, mu, 1); mu += __shfl_xor_sync(0xffffffffu, mu, 2);
        mu *= 0.125f;
        const float d0 = m0 - mu, d1 = m1 - mu;
        float q = __uint_as_float(su.y) + __uint_as_float(su.w) + 80.f * (d0 * d0 + d1 * d1);
        q += __shfl_xor_sync(0xffffffffu, q, 1); q += __shfl_xor_sync(0xffffffffu, q, 2);
        rs[r] = rsqrtf(q * (1.f / D_) + 1e-5f);
        mm[r] = -mu;
      }
      unit(IntC<0>{});
      wg_wait<1>();
      fence_regs(acc);
      releaseB(emptyB + 8 * pb);
      release(bars + 8 * B_PEER);
      TSTAMP(11);
      const GeluC g0 = gelu_consts(rs[0], 1.f - st_g[0]), g1 = gelu_consts(rs[1], 1.f - st_g[1]);
#pragma unroll
      for (int g = 0; g < 24; g++) {
        const float2 cs = *reinterpret_cast<const float2*>(s_cs + 80 + 8 * g + 2 * t);
        const float v0 = gelu_s(fmaf(mm[0], cs.x, acc[4 * g]), g0), v1 = gelu_s(fmaf(mm[0], cs.y, acc[4 * g + 1]), g0);
        const float v2 = gelu_s(fmaf(mm[1], cs.x, acc[4 * g + 2]), g1), v3 = gelu_s(fmaf(mm[1], cs.y, acc[4 * g + 3]), g1);
        hf[g >> 1][(g & 1) * 2] = pack_bf16(v0, v1);
        hf[g >> 1][(g & 1) * 2 + 1] = pack_bf16(v2, v3);
        if (g == 7) unit(IntC<1>{});
        if (g == 15) unit(IntC<2>{});
        if (g == 23) unit(IntC<3>{});
        if ((g & 7) == 7) { wg_wait<1>(); rel4(2); }
      }
    }
    TSTAMP(12);

    {
      float kp[40];
      uint32_t sn[20], kb[20];
      const uint32_t peer = map_peer(sb, rank ^ 1);
      const uint32_t tag = lds32(sb + OFF_BAR + 8 * NBAR);
      auto add8 = [&](int q, const uint4 v) {
        float* d = &kp[8 * q];
        d[0] += bf_lo(v.x); d[1] += bf_hi(v.x); d[2] += bf_lo(v.y); d[3] += bf_hi(v.y);
        d[4] += bf_lo(v.z); d[5] += bf_hi(v.z); d[6] += bf_lo(v.w); d[7] += bf_hi(v.w);
      };
      auto send = [&](int c) {
        const uint32_t dso = peer + OFF_DS + (c & 1) * 20480 + tid * 16, dsb = peer + OFF_BAR + 8 * (B_DSR + 2 * c + wg);
#pragma unroll
        for (int q = 0; q < 5; q++) st_async16(dso + q * 4096, sn[4 * q], sn[4 * q + 1], sn[4 * q + 2], sn[4 * q + 3], dsb);
      };
      mbar_wait(bars + 8 * B_PEER, 0);
#pragma unroll 1
      for (int c = 0; c < 3; c++) {
        wg_wait<0>();
        fence_regs(ac4);
        rel4(1);
        if (rank) {
#pragma unroll
          for (int e = 0; e < 20; e++) { sn[e] = pack_bf16(ac4[2 * e], ac4[2 * e + 1]); kb[e] = pack_bf16(ac4[40 + 2 * e], ac4[41 + 2 * e]); }
        } else {
#pragma unroll
          for (int e = 0; e < 20; e++) { kb[e] = pack_bf16(ac4[2 * e], ac4[2 * e + 1]); sn[e] = pack_bf16(ac4[40 + 2 * e], ac4[41 + 2 * e]); }
        }
#pragma unroll
        for (int e = 0; e < 20; e++) asm volatile("" : "+r"(sn[e]), "+r"(kb[e]));
        unit(IntC<0>{});
        send(c);
        unit(IntC<1>{});
        wg_wait<1>(); rel4(2);
        {
          mbar_wait(bars + 8 * (B_DSR + 2 * c + wg), 0);
          uint4* dst = g_part + (size_t)((i * 8 + ((j + 2 * c + 2) & 7)) * 3 + c) * 1280 + tid;
#pragma unroll
          for (int q = 0; q < 5; q++) {
            const uint4 v = lds128(sb + OFF_DS + (c & 1) * 20480 + tid * 16 + q * 4096);
            st_relaxed16(dst + q * 256, (add_bf2(v.x, kb[4 * q]) & ~1u) | tag, add_bf2(v.y, kb[4 * q + 1]),
                         add_bf2(v.z, kb[4 * q + 2]), add_bf2(v.w, kb[4 * q + 3]));
          }
        }
        unit(IntC<2>{});
        wg_wait<1>(); rel4(2);
        unit(IntC<3>{});
        wg_wait<1>(); rel4(2);
      }
      const uint4* gp = g_part + (size_t)(i * 8 + j) * 3840 + tid;
      uint4 pv4[15];
#pragma unroll
      for (int q = 0; q < 15; q++) pv4[q] = ld_relaxed16(gp + q * 256);
      wg_wait<0>();
      fence_regs(ac4);
      if (rank) {
#pragma unroll
        for (int e = 0; e < 20; e++) sn[e] = pack_bf16(ac4[2 * e], ac4[2 * e + 1]);
#pragma unroll
        for (int e = 0; e < 40; e++) kp[e] = ac4[40 + e];
      } else {
#pragma unroll
        for (int e = 0; e < 20; e++) sn[e] = pack_bf16(ac4[40 + 2 * e], ac4[41 + 2 * e]);
#pragma unroll
        for (int e = 0; e < 40; e++) kp[e] = ac4[e];
      }
      send(3);
      TSTAMP(13);
      {
        mbar_wait(bars + 8 * B_XR, 1);
        const float w0 = 1.f - st_g[0], w1s = 1.f - st_g[1];
        const uint32_t xa = sb + OFF_OUT + rloc * 160 + t * 4;
#pragma unroll
        for (int g = 0; g < 10; g++) {
          const uint32_t x0 = lds32(xa + g * 16), x1 = lds32(xa + 1280 + g * 16);
          kp[4 * g] = fmaf(w0, bf_lo(x0), kp[4 * g]); kp[4 * g + 1] = fmaf(w0, bf_hi(x0), kp[4 * g + 1]);
          kp[4 * g + 2] = fmaf(w1s, bf_lo(x1), kp[4 * g + 2]); kp[4 * g + 3] = fmaf(w1s, bf_hi(x1), kp[4 * g + 3]);
        }
      }
#pragma unroll 1
      for (uint32_t n = 0; n < (WAIT_LIMIT >> 2); n++) {
        uint32_t m = 0u;
#pragma unroll
        for (int q = 0; q < 15; q++) {
          const uint32_t bad = (pv4[q].x ^ tag) & 1u;
          m |= bad;
          if (bad) pv4[q] = ld_relaxed16(gp + q * 256);
        }
        if (m == 0u) break;
      }
#pragma unroll
      for (int q = 0; q < 5; q++) {
        const uint4 a = pv4[q], b = pv4[5 + q];
        add8(q, make_uint4(add_bf2(a.x, b.x), add_bf2(a.y, b.y), add_bf2(a.z, b.z), add_bf2(a.w, b.w)));
      }
      mbar_wait(bars + 8 * (B_DSR + 6 + wg), 0);
      TSTAMP(14);
#pragma unroll
      for (int q = 0; q < 5; q++) {
        const uint4 c = pv4[10 + q], d = lds128(sb + OFF_DS + 20480 + tid * 16 + q * 4096);
        add8(q, make_uint4(add_bf2(c.x, d.x), add_bf2(c.y, d.y), add_bf2(c.z, d.z), add_bf2(c.w, d.w)));
      }
      __syncwarp();
      uint32_t ov[2][10];
#pragma unroll
      for (int g = 0; g < 10; g++) { ov[0][g] = pack_bf16(kp[4 * g], kp[4 * g + 1]); ov[1][g] = pack_bf16(kp[4 * g + 2], kp[4 * g + 3]); }
      stage_tile(sb + OFF_OUT, ov);
      __syncwarp();
      __nv_bfloat16* dst = out + (size_t)(128 * i + 16 * warp) * D_ + 80 * j;
#pragma unroll
      for (int q = 0; q < 5; q++) {
        const int id = q * 32 + lane, r = id / 10;
        *reinterpret_cast<uint4*>(dst + r * (D_ - 80) + id * 8) = lds128(sb + OFF_OUT + warp * 2560 + id * 16);
      }
    }
    TSTAMP(15);
    if (tid == 0) asm volatile("red.relaxed.gpu.global.add.u32 [%0], 1;" ::"l"(g_flags + FL_DONE * 32) : "memory");
  }
}

namespace {
typedef CUresult (*EncodeFn)(CUtensorMap*, CUtensorMapDataType, cuuint32_t, void*, const cuuint64_t*, const cuuint64_t*,
                             const cuuint32_t*, const cuuint32_t*, CUtensorMapInterleave, CUtensorMapSwizzle,
                             CUtensorMapL2promotion, CUtensorMapFloatOOBfill);

void encode(EncodeFn fn, CUtensorMap* m, const void* ptr, int rank, const cuuint64_t* dims, const cuuint64_t* strides,
            const cuuint32_t* box, CUtensorMapSwizzle swz) {
  cuuint32_t es[5] = {1, 1, 1, 1, 1};
  fn(m, CU_TENSOR_MAP_DATA_TYPE_BFLOAT16, rank, const_cast<void*>(ptr), dims, strides, box, es, CU_TENSOR_MAP_INTERLEAVE_NONE,
     swz, CU_TENSOR_MAP_L2_PROMOTION_L2_128B, CU_TENSOR_MAP_FLOAT_OOB_FILL_NONE);
}
}

extern "C" void kernel_launch(void* const* d_in, const int* in_sizes, int n_in, void* d_out, int out_size) {
  (void)in_sizes; (void)n_in; (void)out_size;
  const __nv_bfloat16* x = (const __nv_bfloat16*)d_in[0];
  const __nv_bfloat16* wqkv = (const __nv_bfloat16*)d_in[1];
  const __nv_bfloat16* wphi = (const __nv_bfloat16*)d_in[2];
  const __nv_bfloat16* wo = (const __nv_bfloat16*)d_in[3];
  const __nv_bfloat16* w1 = (const __nv_bfloat16*)d_in[5];
  const __nv_bfloat16* w2 = (const __nv_bfloat16*)d_in[6];
  const __nv_bfloat16* w3 = (const __nv_bfloat16*)d_in[7];
  const __nv_bfloat16* w4 = (const __nv_bfloat16*)d_in[8];
  const __nv_bfloat16* gate_w = (const __nv_bfloat16*)d_in[9];

  static EncodeFn enc = nullptr;
  static void *pHs = nullptr, *pX1 = nullptr;
  if (!enc) {
    cudaDriverEntryPointQueryResult qr;
    cudaGetDriverEntryPoint("cuTensorMapEncodeTiled", (void**)&enc, cudaEnableDefault, &qr);
    cudaGetSymbolAddress(&pHs, g_Hs);
    cudaGetSymbolAddress(&pX1, g_X1);
    cudaFuncSetAttribute(fused_kernel, cudaFuncAttributeMaxDynamicSharedMemorySize, SMEM_BYTES);
  }
  Maps m;
  {
    cuuint64_t dims[2] = {D_, S_}, str[1] = {D_ * 2};
    cuuint32_t box[2] = {64, 128}, boxh[2] = {64, 64};
    encode(enc, &m.x, x, 2, dims, str, boxh, CU_TENSOR_MAP_SWIZZLE_128B);
    encode(enc, &m.hs, (const char*)pHs + 2 * D_ * 2, 2, dims, str, box, CU_TENSOR_MAP_SWIZZLE_128B);
    encode(enc, &m.x1, pX1, 2, dims, str, boxh, CU_TENSOR_MAP_SWIZZLE_128B);
    cuuint32_t boxr[2] = {80, 16}, boxs[2] = {80, 128};
    cuuint64_t dimsp[2] = {D_, S_ + 4};
    encode(enc, &m.st_h, pHs, 2, dimsp, str, boxs, CU_TENSOR_MAP_SWIZZLE_NONE);
    encode(enc, &m.st_x1, pX1, 2, dims, str, boxs, CU_TENSOR_MAP_SWIZZLE_NONE);
    encode(enc, &m.xr, x, 2, dims, str, boxr, CU_TENSOR_MAP_SWIZZLE_NONE);
  }
  {
    cuuint64_t dims[3] = {80, D_, 8}, str[2] = {D_ * 2, 160};
    cuuint32_t boxm[3] = {64, 64, 1}, boxr[3] = {16, 64, 1};
    encode(enc, &m.w1m, w1, 3, dims, str, boxm, CU_TENSOR_MAP_SWIZZLE_128B);
    encode(enc, &m.w1r, w1, 3, dims, str, boxr, CU_TENSOR_MAP_SWIZZLE_32B);
  }
  {
    cuuint64_t dims[4] = {80, D_, 3, 8}, str[3] = {3 * D_ * 2, D_ * 2, 160};
    cuuint32_t boxm[4] = {64, 64, 3, 1}, boxr[4] = {16, 64, 3, 1};
    encode(enc, &m.qm, wqkv, 4, dims, str, boxm, CU_TENSOR_MAP_SWIZZLE_128B);
    encode(enc, &m.qr, wqkv, 4, dims, str, boxr, CU_TENSOR_MAP_SWIZZLE_32B);
  }
  {
    cuuint64_t dims[3] = {32, D_, 20}, dims4[3] = {32, F_, 20}, str[2] = {D_ * 2, 64};
    cuuint32_t box4[3] = {32, 64, 5}, boxo[3] = {32, 80, 5};
    encode(enc, &m.w4, w4, 3, dims4, str, box4, CU_TENSOR_MAP_SWIZZLE_64B);
    encode(enc, &m.wo, wo, 3, dims, str, boxo, CU_TENSOR_MAP_SWIZZLE_64B);
    encode(enc, &m.w2, w2, 3, dims, str, box4, CU_TENSOR_MAP_SWIZZLE_64B);
  }
  {
    cuuint64_t dims[3] = {64, D_, 24}, str[2] = {F_ * 2, 128};
    cuuint32_t box[3] = {64, 64, 3};
    encode(enc, &m.w3, w3, 3, dims, str, box, CU_TENSOR_MAP_SWIZZLE_128B);
  }
  fused_kernel<<<NCTA, 384, SMEM_BYTES, cudaStreamPerThread>>>(m, x, wqkv, wphi, w1, w2, w3, w4, wo, gate_w, (__nv_bfloat16*)d_out);
}
```

```cpp
#include <cuda_runtime.h>
#include <cuda_bf16.h>
#include <cuda.h>
#include <stdint.h>

namespace {

constexpr int S_ = 2048, D_ = 640, F_ = 1536;
constexpr int NCTA = 128;
constexpr int KV_PAIR = 40 * 48 + 96;
constexpr int KV_J = 2 * KV_PAIR;

constexpr int SLOT_B = 49152, NB = 3;
constexpr int SLOT_A = 16384, NA = 4;
constexpr int OFF_B = 0;
constexpr int OFF_A = OFF_B + NB * SLOT_B;
constexpr int OFF_STG = OFF_A + 2 * SLOT_A;
constexpr int OFF_MISC = OFF_A + NA * SLOT_A;
constexpr int OFF_XST = OFF_MISC + 13312;
constexpr int OFF_CS = OFF_MISC + 16384;
constexpr int OFF_BAR = OFF_CS + 1088;
constexpr int SMEM_BYTES = OFF_BAR + 512 + 512 + 128;
constexpr int B_FULLA = 0, B_FULLB = 4, B_CS = 7, B_XR = 8, B_KV = 9, B_ST1 = 10, B_HST = 11, B_FULL4 = 12  ,
              B_DSR = 20  , B_EMPTYB = 30  , B_SIGP = 33, B_SIGH = 34, B_SIGKV = 35, B_SIGX1 = 36, B_MFREE = 37,
              B_EMPTY4 = 38  , B_EMPTYA = 46  , B_PEER = 50, B_PEER2 = 51, B_X1P = 52  , NBAR = 53;
constexpr int SPARE = 40960;
constexpr int SET4 = 87040, OFF_DS = 2 * SET4, OFF_G0 = 0, OFF_OUT = 40960;

constexpr int FL_DONE = 0, FL_H = 1  , FL_X1 = FL_H + 32, FL_KV = FL_X1 + 16, FL_CS = FL_KV + 8, FL_CS3 = FL_CS + 8, FL_ST = FL_CS3 + 8;
constexpr int FL_S1 = FL_ST + 16, FL_COUNT = FL_S1 + 16;
constexpr int ACC_FLOATS = 8 * KV_J + D_ + F_;

struct Maps {
  CUtensorMap x, w1m, w1r, qm, qr, hs, w2, x1, w3, w4, wo, xr, st_h, st_x1;
};

}

__device__ __align__(1024) __nv_bfloat16 g_Hs[(S_ + 4) * D_];
__device__ __align__(1024) __nv_bfloat16 g_X1[S_ * D_];
__device__ __align__(128) float g_acc[2][ACC_FLOATS];
__device__ __align__(128) float4 g_xstat[S_];
__device__ __align__(128) float2 g_st1[S_ * 8];
__device__ __align__(128) uint4 g_part[16 * 8 * 3 * 1280];
__device__ __align__(128) unsigned g_flags[FL_COUNT * 32];
#define TSTAMP(n) do {} while (0)
#define TSTAMPX(n) do {} while (0)
#define TRACE(n) do {} while (0)
#define TRS(n) do {} while (0)

namespace {

__device__ __forceinline__ long long gtime() { long long t; asm volatile("mov.u64 %0, %%globaltimer;" : "=l"(t)); return t; }
__device__ __forceinline__ uint32_t smem_u32(const void* p) { return (uint32_t)__cvta_generic_to_shared(p); }
__device__ __forceinline__ void mbar_init(uint32_t bar, int cnt) {
  asm volatile("mbarrier.init.shared::cta.b64 [%0], %1;" ::"r"(bar), "r"(cnt) : "memory");
}
__device__ __forceinline__ void mbar_expect_tx(uint32_t bar, int bytes) {
  asm volatile("mbarrier.arrive.expect_tx.shared::cta.b64 _, [%0], %1;" ::"r"(bar), "r"(bytes) : "memory");
}
__device__ __forceinline__ void mbar_arrive_cta(uint32_t bar, uint32_t cta) {
  asm volatile("{\n.reg .b32 ra;\nmapa.shared::cluster.u32 ra, %0, %1;\nmbarrier.arrive.shared::cluster.b64 _, [ra];\n}"
               ::"r"(bar), "r"(cta) : "memory");
}
__device__ __forceinline__ uint32_t mbar_try(uint32_t bar, uint32_t parity) {
  uint32_t ok;
  asm volatile("{\n.reg .pred p;\nmbarrier.try_wait.parity.shared::cta.b64 p, [%1], %2;\nselp.u32 %0, 1, 0, p;\n}"
               : "=r"(ok) : "r"(bar), "r"(parity) : "memory");
  return ok;
}
constexpr uint32_t WAIT_LIMIT = 1u << 18;
__device__ __forceinline__ void mbar_wait(uint32_t bar, uint32_t parity) {
  uint32_t n = 0;
  while (!mbar_try(bar, parity) && ++n < WAIT_LIMIT) {}
}
__device__ __forceinline__ unsigned ld_acquire(const unsigned* p) {
  unsigned v;
  asm volatile("ld.acquire.gpu.global.u32 %0, [%1];" : "=r"(v) : "l"(p) : "memory");
  return v;
}
__device__ __forceinline__ void flag_wait(int idx, unsigned target) {
  const unsigned* p = g_flags + idx * 32;
  uint32_t n = 0;
  while ((int)(ld_acquire(p) - target) < 0 && ++n < (WAIT_LIMIT >> 2)) {}
}
__device__ __forceinline__ void flag_add(int idx) {
  asm volatile("red.release.gpu.global.add.u32 [%0], 1;" ::"l"(g_flags + idx * 32) : "memory");
}
__device__ __forceinline__ void flag_add_relaxed(int idx) {
  asm volatile("red.relaxed.gpu.global.add.u32 [%0], 1;" ::"l"(g_flags + idx * 32) : "memory");
}
__device__ __forceinline__ uint32_t mbar_test(uint32_t bar, uint32_t parity) {
  uint32_t ok;
  asm volatile("{\n.reg .pred p;\nmbarrier.test_wait.parity.shared::cta.b64 p, [%1], %2;\nselp.u32 %0, 1, 0, p;\n}"
               : "=r"(ok) : "r"(bar), "r"(parity) : "memory");
  return ok;
}
__device__ __forceinline__ uint32_t lds32(uint32_t a) {
  uint32_t v;
  asm volatile("ld.shared.u32 %0, [%1];" : "=r"(v) : "r"(a) : "memory");
  return v;
}
__device__ __forceinline__ void mbar_arrive(uint32_t bar) {
  asm volatile("mbarrier.arrive.shared::cta.b64 _, [%0];" ::"r"(bar) : "memory");
}
__device__ __forceinline__ void fence_async_glb() { asm volatile("fence.proxy.async.global;" ::: "memory"); }
__device__ __forceinline__ void fence_async_smem() { asm volatile("fence.proxy.async.shared::cta;" ::: "memory"); }
__device__ __forceinline__ void bar_sync(int id, int n) { asm volatile("bar.sync %0, %1;" ::"r"(id), "r"(n) : "memory"); }

__device__ __forceinline__ void tma2d(uint32_t dst, const CUtensorMap* m, uint32_t bar, int c0, int c1) {
  asm volatile("cp.async.bulk.tensor.2d.shared::cluster.global.mbarrier::complete_tx::bytes [%0], [%1, {%3, %4}], [%2];"
               ::"r"(dst), "l"(m), "r"(bar), "r"(c0), "r"(c1) : "memory");
}
__device__ __forceinline__ void tma2d_mc(uint32_t dst, const CUtensorMap* m, uint32_t bar, int c0, int c1) {
  asm volatile("cp.async.bulk.tensor.2d.shared::cluster.global.mbarrier::complete_tx::bytes.multicast::cluster"
               " [%0], [%1, {%3, %4}], [%2], %5;"
               ::"r"(dst), "l"(m), "r"(bar), "r"(c0), "r"(c1), "h"((uint16_t)3) : "memory");
}
__device__ __forceinline__ void tma3d(uint32_t dst, const CUtensorMap* m, uint32_t bar, int c0, int c1, int c2) {
  asm volatile("cp.async.bulk.tensor.3d.shared::cluster.global.mbarrier::complete_tx::bytes [%0], [%1, {%3, %4, %5}], [%2];"
               ::"r"(dst), "l"(m), "r"(bar), "r"(c0), "r"(c1), "r"(c2) : "memory");
}
__device__ __forceinline__ void tma4d(uint32_t dst, const CUtensorMap* m, uint32_t bar, int c0, int c1, int c2, int c3) {
  asm volatile("cp.async.bulk.tensor.4d.shared::cluster.global.mbarrier::complete_tx::bytes [%0], [%1, {%3, %4, %5, %6}], [%2];"
               ::"r"(dst), "l"(m), "r"(bar), "r"(c0), "r"(c1), "r"(c2), "r"(c3) : "memory");
}
__device__ __forceinline__ void tma2d_store(const CUtensorMap* m, uint32_t src, int c0, int c1) {
  asm volatile("cp.async.bulk.tensor.2d.global.shared::cta.bulk_group [%0, {%2, %3}], [%1];"
               ::"l"(m), "r"(src), "r"(c0), "r"(c1) : "memory");
}
__device__ __forceinline__ void bulk_store(void* dst, uint32_t src, uint32_t bytes) {
  asm volatile("cp.async.bulk.global.shared::cta.bulk_group [%0], [%1], %2;" ::"l"(dst), "r"(src), "r"(bytes) : "memory");
}
__device__ __forceinline__ void bulk_load(uint32_t dst, const void* src, uint32_t bytes, uint32_t bar) {
  asm volatile("cp.async.bulk.shared::cluster.global.mbarrier::complete_tx::bytes [%0], [%1], %2, [%3];"
               ::"r"(dst), "l"(src), "r"(bytes), "r"(bar) : "memory");
}
__device__ __forceinline__ void bulk_commit() { asm volatile("cp.async.bulk.commit_group;" ::: "memory"); }
template <int N> __device__ __forceinline__ void bulk_wait() { asm volatile("cp.async.bulk.wait_group %0;" ::"n"(N) : "memory"); }
__device__ __forceinline__ void bulk_wait_read() { asm volatile("cp.async.bulk.wait_group.read 0;" ::: "memory"); }
__device__ __forceinline__ void bar_arrive(int id, int n) { asm volatile("bar.arrive %0, %1;" ::"r"(id), "r"(n) : "memory"); }
__device__ __forceinline__ uint4 lds128(uint32_t a) {
  uint4 v;
  asm volatile("ld.shared.v4.u32 {%0, %1, %2, %3}, [%4];" : "=r"(v.x), "=r"(v.y), "=r"(v.z), "=r"(v.w) : "r"(a) : "memory");
  return v;
}
__device__ __forceinline__ void sts128(uint32_t a, uint4 v) {
  asm volatile("st.shared.v4.u32 [%0], {%1, %2, %3, %4};" ::"r"(a), "r"(v.x), "r"(v.y), "r"(v.z), "r"(v.w) : "memory");
}
__device__ __forceinline__ uint4 ld_relaxed16(const uint4* p) {
  uint4 v;
  asm volatile("ld.relaxed.gpu.global.v4.u32 {%0, %1, %2, %3}, [%4];" : "=r"(v.x), "=r"(v.y), "=r"(v.z), "=r"(v.w) : "l"(p) : "memory");
  return v;
}
__device__ __forceinline__ void st_relaxed16(uint4* p, uint32_t a, uint32_t b, uint32_t c, uint32_t d) {
  asm volatile("st.relaxed.gpu.global.v4.u32 [%0], {%1, %2, %3, %4};" ::"l"(p), "r"(a), "r"(b), "r"(c), "r"(d) : "memory");
}
__device__ __forceinline__ uint32_t map_peer(uint32_t addr, uint32_t cta) {
  uint32_t r;
  asm("mapa.shared::cluster.u32 %0, %1, %2;" : "=r"(r) : "r"(addr), "r"(cta));
  return r;
}
__device__ __forceinline__ void st_async16(uint32_t addr, uint32_t a, uint32_t b, uint32_t c, uint32_t d, uint32_t bar) {
  asm volatile("st.async.weak.shared::cluster.mbarrier::complete_tx::bytes.v4.b32 [%0], {%1, %2, %3, %4}, [%5];"
               ::"r"(addr), "r"(a), "r"(b), "r"(c), "r"(d), "r"(bar) : "memory");
}
__device__ __forceinline__ void l2_prefetch(const void* p, uint32_t bytes) {
  asm volatile("cp.async.bulk.prefetch.L2.global [%0], %1;" ::"l"(p), "r"(bytes) : "memory");
}
__device__ __forceinline__ void prefetch_tmap(const CUtensorMap* m) {
  asm volatile("prefetch.tensormap [%0];" ::"l"(m) : "memory");
}
__device__ __forceinline__ uint64_t make_desc(uint32_t a16, uint32_t off, uint32_t lbo, uint32_t sbo, uint32_t swz) {
  const uint32_t lo = a16 + ((off >> 4) + ((lbo >> 4) << 16)), hi = (sbo >> 4) | (swz << 30);
  uint64_t d;
  asm("mov.b64 %0, {%1, %2};" : "=l"(d) : "r"(lo), "r"(hi));
  return d;
}
__device__ __forceinline__ void wg_fence() { asm volatile("wgmma.fence.sync.aligned;" ::: "memory"); }
__device__ __forceinline__ void wg_commit() { asm volatile("wgmma.commit_group.sync.aligned;" ::: "memory"); }
template <int N> __device__ __forceinline__ void wg_wait() { asm volatile("wgmma.wait_group.sync.aligned %0;" ::"n"(N) : "memory"); }
template <int N> __device__ __forceinline__ void fence_regs(float (&d)[N]) {
#pragma unroll
  for (int i = 0; i < N; i++) asm volatile("" : "+f"(d[i])::"memory");
}
template <int N> __device__ __forceinline__ void zero_regs(float (&d)[N]) {
#pragma unroll
  for (int i = 0; i < N; i++) d[i] = 0.f;
}
__device__ __forceinline__ uint32_t pack_bf16(float lo, float hi) {
  uint32_t r;
  asm("cvt.rn.bf16x2.f32 %0, %1, %2;" : "=r"(r) : "f"(hi), "f"(lo));
  return r;
}
__device__ __forceinline__ float bf_lo(uint32_t v) { return __uint_as_float(v << 16); }
__device__ __forceinline__ float bf_hi(uint32_t v) { return __uint_as_float(v & 0xffff0000u); }
__device__ __forceinline__ uint32_t max_bf2(uint32_t a, uint32_t b) {
  uint32_t r; asm("max.bf16x2 %0, %1, %2;" : "=r"(r) : "r"(a), "r"(b)); return r;
}
__device__ __forceinline__ uint32_t min_bf2(uint32_t a, uint32_t b) {
  uint32_t r; asm("min.bf16x2 %0, %1, %2;" : "=r"(r) : "r"(a), "r"(b)); return r;
}
__device__ __forceinline__ uint32_t add_bf2(uint32_t a, uint32_t b) {
  uint32_t r; asm("add.rn.bf16x2 %0, %1, %2;" : "=r"(r) : "r"(a), "r"(b)); return r;
}
__device__ __forceinline__ float ex2(float x) { float r; asm("ex2.approx.ftz.f32 %0, %1;" : "=f"(r) : "f"(x)); return r; }
__device__ __forceinline__ float rcp(float x) { float r; asm("rcp.approx.ftz.f32 %0, %1;" : "=f"(r) : "f"(x)); return r; }
__device__ __forceinline__ float tanh_ap(float x) { float r; asm("tanh.approx.f32 %0, %1;" : "=f"(r) : "f"(x)); return r; }
struct GeluC { float c0, c1, ch; };
__device__ __forceinline__ GeluC gelu_consts(float rstd, float scale) {
  return GeluC{0.7978845608f * rstd, 0.0356774081f * rstd * rstd * rstd, 0.5f * scale * rstd};
}
__device__ __forceinline__ float gelu_s(float y, const GeluC& c) {
  const float u = y * fmaf(y * y, c.c1, c.c0);
  const float hx = y * c.ch;
  return fmaf(hx, tanh_ap(u), hx);
}
__device__ __forceinline__ void stsm4(uint32_t addr, uint32_t r0, uint32_t r1, uint32_t r2, uint32_t r3) {
  asm volatile("stmatrix.sync.aligned.m8n8.x4.shared.b16 [%0], {%1, %2, %3, %4};"
               ::"r"(addr), "r"(r0), "r"(r1), "r"(r2), "r"(r3) : "memory");
}
__device__ __forceinline__ void red_add4(float* p, float a, float b, float c, float d) {
  asm volatile("red.global.add.v4.f32 [%0], {%1, %2, %3, %4};" ::"l"(p), "f"(a), "f"(b), "f"(c), "f"(d) : "memory");
}

__device__ __forceinline__ void mma_ss256(float (&d)[128], uint64_t descA, uint64_t descB) {
  asm volatile("wgmma.mma_async.sync.aligned.m64n256k16.f32.bf16.bf16 {"
      "%0, %1, %2, %3, %4, %5, %6, %7, %8, %9, %10, %11, %12, %13, %14, %15, "
      "%16, %17, %18, %19, %20, %21, %22, %23, %24, %25, %26, %27, %28, %29, %30, %31, "
      "%32, %33, %34, %35, %36, %37, %38, %39, %40, %41, %42, %43, %44, %45, %46, %47, "
      "%48, %49, %50, %51, %52, %53, %54, %55, %56, %57, %58, %59, %60, %61, %62, %63, "
      "%64, %65, %66, %67, %68, %69, %70, %71, %72, %73, %74, %75, %76, %77, %78, %79, "
      "%80, %81, %82, %83, %84, %85, %86, %87, %88, %89, %90, %91, %92, %93, %94, %95, "
      "%96, %97, %98, %99, %100, %101, %102, %103, %104, %105, %106, %107, %108, %109, %110, %111, "
      "%112, %113, %114, %115, %116, %117, %118, %119, %120, %121, %122, %123, %124, %125, %126, %127"
      "}, %128, %129, 1, 1, 1, 0, 1;\n"
      : "+f"(d[0]), "+f"(d[1]), "+f"(d[2]), "+f"(d[3]), "+f"(d[4]), "+f"(d[5]), "+f"(d[6]), "+f"(d[7]),
        "+f"(d[8]), "+f"(d[9]), "+f"(d[10]), "+f"(d[11]), "+f"(d[12]), "+f"(d[13]), "+f"(d[14]), "+f"(d[15]),
        "+f"(d[16]), "+f"(d[17]), "+f"(d[18]), "+f"(d[19]), "+f"(d[20]), "+f"(d[21]), "+f"(d[22]), "+f"(d[23]),
        "+f"(d[24]), "+f"(d[25]), "+f"(d[26]), "+f"(d[27]), "+f"(d[28]), "+f"(d[29]), "+f"(d[30]), "+f"(d[31]),
        "+f"(d[32]), "+f"(d[33]), "+f"(d[34]), "+f"(d[35]), "+f"(d[36]), "+f"(d[37]), "+f"(d[38]), "+f"(d[39]),
        "+f"(d[40]), "+f"(d[41]), "+f"(d[42]), "+f"(d[43]), "+f"(d[44]), "+f"(d[45]), "+f"(d[46]), "+f"(d[47]),
        "+f"(d[48]), "+f"(d[49]), "+f"(d[50]), "+f"(d[51]), "+f"(d[52]), "+f"(d[53]), "+f"(d[54]), "+f"(d[55]),
        "+f"(d[56]), "+f"(d[57]), "+f"(d[58]), "+f"(d[59]), "+f"(d[60]), "+f"(d[61]), "+f"(d[62]), "+f"(d[63]),
        "+f"(d[64]), "+f"(d[65]), "+f"(d[66]), "+f"(d[67]), "+f"(d[68]), "+f"(d[69]), "+f"(d[70]), "+f"(d[71]),
        "+f"(d[72]), "+f"(d[73]), "+f"(d[74]), "+f"(d[75]), "+f"(d[76]), "+f"(d[77]), "+f"(d[78]), "+f"(d[79]),
        "+f"(d[80]), "+f"(d[81]), "+f"(d[82]), "+f"(d[83]), "+f"(d[84]), "+f"(d[85]), "+f"(d[86]), "+f"(d[87]),
        "+f"(d[88]), "+f"(d[89]), "+f"(d[90]), "+f"(d[91]), "+f"(d[92]), "+f"(d[93]), "+f"(d[94]), "+f"(d[95]),
        "+f"(d[96]), "+f"(d[97]), "+f"(d[98]), "+f"(d[99]), "+f"(d[100]), "+f"(d[101]), "+f"(d[102]), "+f"(d[103]),
        "+f"(d[104]), "+f"(d[105]), "+f"(d[106]), "+f"(d[107]), "+f"(d[108]), "+f"(d[109]), "+f"(d[110]), "+f"(d[111]),
        "+f"(d[112]), "+f"(d[113]), "+f"(d[114]), "+f"(d[115]), "+f"(d[116]), "+f"(d[117]), "+f"(d[118]), "+f"(d[119]),
        "+f"(d[120]), "+f"(d[121]), "+f"(d[122]), "+f"(d[123]), "+f"(d[124]), "+f"(d[125]), "+f"(d[126]), "+f"(d[127])
      : "l"(descA), "l"(descB));
}
__device__ __forceinline__ void mma_ss256_p(float (&d)[128], uint64_t descA, uint64_t descB, int acc) {
  asm volatile("{\n.reg .pred p;\nsetp.ne.b32 p, %130, 0;\n"
      "wgmma.mma_async.sync.aligned.m64n256k16.f32.bf16.bf16 {"
      "%0, %1, %2, %3, %4, %5, %6, %7, %8, %9, %10, %11, %12, %13, %14, %15, "
      "%16, %17, %18, %19, %20, %21, %22, %23, %24, %25, %26, %27, %28, %29, %30, %31, "
      "%32, %33, %34, %35, %36, %37, %38, %39, %40, %41, %42, %43, %44, %45, %46, %47, "
      "%48, %49, %50, %51, %52, %53, %54, %55, %56, %57, %58, %59, %60, %61, %62, %63, "
      "%64, %65, %66, %67, %68, %69, %70, %71, %72, %73, %74, %75, %76, %77, %78, %79, "
      "%80, %81, %82, %83, %84, %85, %86, %87, %88, %89, %90, %91, %92, %93, %94, %95, "
      "%96, %97, %98, %99, %100, %101, %102, %103, %104, %105, %106, %107, %108, %109, %110, %111, "
      "%112, %113, %114, %115, %116, %117, %118, %119, %120, %121, %122, %123, %124, %125, %126, %127"
      "}, %128, %129, p, 1, 1, 0, 1;\n}\n"
      : "+f"(d[0]), "+f"(d[1]), "+f"(d[2]), "+f"(d[3]), "+f"(d[4]), "+f"(d[5]), "+f"(d[6]), "+f"(d[7]),
        "+f"(d[8]), "+f"(d[9]), "+f"(d[10]), "+f"(d[11]), "+f"(d[12]), "+f"(d[13]), "+f"(d[14]), "+f"(d[15]),
        "+f"(d[16]), "+f"(d[17]), "+f"(d[18]), "+f"(d[19]), "+f"(d[20]), "+f"(d[21]), "+f"(d[22]), "+f"(d[23]),
        "+f"(d[24]), "+f"(d[25]), "+f"(d[26]), "+f"(d[27]), "+f"(d[28]), "+f"(d[29]), "+f"(d[30]), "+f"(d[31]),
        "+f"(d[32]), "+f"(d[33]), "+f"(d[34]), "+f"(d[35]), "+f"(d[36]), "+f"(d[37]), "+f"(d[38]), "+f"(d[39]),
        "+f"(d[40]), "+f"(d[41]), "+f"(d[42]), "+f"(d[43]), "+f"(d[44]), "+f"(d[45]), "+f"(d[46]), "+f"(d[47]),
        "+f"(d[48]), "+f"(d[49]), "+f"(d[50]), "+f"(d[51]), "+f"(d[52]), "+f"(d[53]), "+f"(d[54]), "+f"(d[55]),
        "+f"(d[56]), "+f"(d[57]), "+f"(d[58]), "+f"(d[59]), "+f"(d[60]), "+f"(d[61]), "+f"(d[62]), "+f"(d[63]),
        "+f"(d[64]), "+f"(d[65]), "+f"(d[66]), "+f"(d[67]), "+f"(d[68]), "+f"(d[69]), "+f"(d[70]), "+f"(d[71]),
        "+f"(d[72]), "+f"(d[73]), "+f"(d[74]), "+f"(d[75]), "+f"(d[76]), "+f"(d[77]), "+f"(d[78]), "+f"(d[79]),
        "+f"(d[80]), "+f"(d[81]), "+f"(d[82]), "+f"(d[83]), "+f"(d[84]), "+f"(d[85]), "+f"(d[86]), "+f"(d[87]),
        "+f"(d[88]), "+f"(d[89]), "+f"(d[90]), "+f"(d[91]), "+f"(d[92]), "+f"(d[93]), "+f"(d[94]), "+f"(d[95]),
        "+f"(d[96]), "+f"(d[97]), "+f"(d[98]), "+f"(d[99]), "+f"(d[100]), "+f"(d[101]), "+f"(d[102]), "+f"(d[103]),
        "+f"(d[104]), "+f"(d[105]), "+f"(d[106]), "+f"(d[107]), "+f"(d[108]), "+f"(d[109]), "+f"(d[110]), "+f"(d[111]),
        "+f"(d[112]), "+f"(d[113]), "+f"(d[114]), "+f"(d[115]), "+f"(d[116]), "+f"(d[117]), "+f"(d[118]), "+f"(d[119]),
        "+f"(d[120]), "+f"(d[121]), "+f"(d[122]), "+f"(d[123]), "+f"(d[124]), "+f"(d[125]), "+f"(d[126]), "+f"(d[127])
      : "l"(descA), "l"(descB), "r"(acc));
}

__device__ __forceinline__ void mma_ss64(float (&d)[32], uint64_t descA, uint64_t descB) {
  asm volatile("wgmma.mma_async.sync.aligned.m64n64k16.f32.bf16.bf16 {"
      "%0, %1, %2, %3, %4, %5, %6, %7, %8, %9, %10, %11, %12, %13, %14, %15, "
      "%16, %17, %18, %19, %20, %21, %22, %23, %24, %25, %26, %27, %28, %29, %30, %31"
      "}, %32, %33, 1, 1, 1, 0, 1;\n"
      : "+f"(d[0]), "+f"(d[1]), "+f"(d[2]), "+f"(d[3]), "+f"(d[4]), "+f"(d[5]), "+f"(d[6]), "+f"(d[7]),
        "+f"(d[8]), "+f"(d[9]), "+f"(d[10]), "+f"(d[11]), "+f"(d[12]), "+f"(d[13]), "+f"(d[14]), "+f"(d[15]),
        "+f"(d[16]), "+f"(d[17]), "+f"(d[18]), "+f"(d[19]), "+f"(d[20]), "+f"(d[21]), "+f"(d[22]), "+f"(d[23]),
        "+f"(d[24]), "+f"(d[25]), "+f"(d[26]), "+f"(d[27]), "+f"(d[28]), "+f"(d[29]), "+f"(d[30]), "+f"(d[31])
      : "l"(descA), "l"(descB));
}
__device__ __forceinline__ void mma_ss64_p(float (&d)[32], uint64_t descA, uint64_t descB, int acc) {
  asm volatile("{\n.reg .pred p;\nsetp.ne.b32 p, %34, 0;\n"
      "wgmma.mma_async.sync.aligned.m64n64k16.f32.bf16.bf16 {"
      "%0, %1, %2, %3, %4, %5, %6, %7, %8, %9, %10, %11, %12, %13, %14, %15, "
      "%16, %17, %18, %19, %20, %21, %22, %23, %24, %25, %26, %27, %28, %29, %30, %31"
      "}, %32, %33, p, 1, 1, 0, 1;\n}\n"
      : "+f"(d[0]), "+f"(d[1]), "+f"(d[2]), "+f"(d[3]), "+f"(d[4]), "+f"(d[5]), "+f"(d[6]), "+f"(d[7]),
        "+f"(d[8]), "+f"(d[9]), "+f"(d[10]), "+f"(d[11]), "+f"(d[12]), "+f"(d[13]), "+f"(d[14]), "+f"(d[15]),
        "+f"(d[16]), "+f"(d[17]), "+f"(d[18]), "+f"(d[19]), "+f"(d[20]), "+f"(d[21]), "+f"(d[22]), "+f"(d[23]),
        "+f"(d[24]), "+f"(d[25]), "+f"(d[26]), "+f"(d[27]), "+f"(d[28]), "+f"(d[29]), "+f"(d[30]), "+f"(d[31])
      : "l"(descA), "l"(descB), "r"(acc));
}

__device__ __forceinline__ void mma_ss160(float (&d)[80], uint64_t descA, uint64_t descB) {
  asm volatile("wgmma.mma_async.sync.aligned.m64n160k16.f32.bf16.bf16 {"
      "%0, %1, %2, %3, %4, %5, %6, %7, %8, %9, %10, %11, %12, %13, %14, %15, "
      "%16, %17, %18, %19, %20, %21, %22, %23, %24, %25, %26, %27, %28, %29, %30, %31, "
      "%32, %33, %34, %35, %36, %37, %38, %39, %40, %41, %42, %43, %44, %45, %46, %47, "
      "%48, %49, %50, %51, %52, %53, %54, %55, %56, %57, %58, %59, %60, %61, %62, %63, "
      "%64, %65, %66, %67, %68, %69, %70, %71, %72, %73, %74, %75, %76, %77, %78, %79"
      "}, %80, %81, 1, 1, 1, 0, 1;\n"
      : "+f"(d[0]), "+f"(d[1]), "+f"(d[2]), "+f"(d[3]), "+f"(d[4]), "+f"(d[5]), "+f"(d[6]), "+f"(d[7]),
        "+f"(d[8]), "+f"(d[9]), "+f"(d[10]), "+f"(d[11]), "+f"(d[12]), "+f"(d[13]), "+f"(d[14]), "+f"(d[15]),
        "+f"(d[16]), "+f"(d[17]), "+f"(d[18]), "+f"(d[19]), "+f"(d[20]), "+f"(d[21]), "+f"(d[22]), "+f"(d[23]),
        "+f"(d[24]), "+f"(d[25]), "+f"(d[26]), "+f"(d[27]), "+f"(d[28]), "+f"(d[29]), "+f"(d[30]), "+f"(d[31]),
        "+f"(d[32]), "+f"(d[33]), "+f"(d[34]), "+f"(d[35]), "+f"(d[36]), "+f"(d[37]), "+f"(d[38]), "+f"(d[39]),
        "+f"(d[40]), "+f"(d[41]), "+f"(d[42]), "+f"(d[43]), "+f"(d[44]), "+f"(d[45]), "+f"(d[46]), "+f"(d[47]),
        "+f"(d[48]), "+f"(d[49]), "+f"(d[50]), "+f"(d[51]), "+f"(d[52]), "+f"(d[53]), "+f"(d[54]), "+f"(d[55]),
        "+f"(d[56]), "+f"(d[57]), "+f"(d[58]), "+f"(d[59]), "+f"(d[60]), "+f"(d[61]), "+f"(d[62]), "+f"(d[63]),
        "+f"(d[64]), "+f"(d[65]), "+f"(d[66]), "+f"(d[67]), "+f"(d[68]), "+f"(d[69]), "+f"(d[70]), "+f"(d[71]),
        "+f"(d[72]), "+f"(d[73]), "+f"(d[74]), "+f"(d[75]), "+f"(d[76]), "+f"(d[77]), "+f"(d[78]), "+f"(d[79])
      : "l"(descA), "l"(descB));
}
__device__ __forceinline__ void mma_ss160_z(float (&d)[80], uint64_t descA, uint64_t descB) {
  asm volatile("wgmma.mma_async.sync.aligned.m64n160k16.f32.bf16.bf16 {"
      "%0, %1, %2, %3, %4, %5, %6, %7, %8, %9, %10, %11, %12, %13, %14, %15, "
      "%16, %17, %18, %19, %20, %21, %22, %23, %24, %25, %26, %27, %28, %29, %30, %31, "
      "%32, %33, %34, %35, %36, %37, %38, %39, %40, %41, %42, %43, %44, %45, %46, %47, "
      "%48, %49, %50, %51, %52, %53, %54, %55, %56, %57, %58, %59, %60, %61, %62, %63, "
      "%64, %65, %66, %67, %68, %69, %70, %71, %72, %73, %74, %75, %76, %77, %78, %79"
      "}, %80, %81, 0, 1, 1, 0, 1;\n"
      : "=f"(d[0]), "=f"(d[1]), "=f"(d[2]), "=f"(d[3]), "=f"(d[4]), "=f"(d[5]), "=f"(d[6]), "=f"(d[7]),
        "=f"(d[8]), "=f"(d[9]), "=f"(d[10]), "=f"(d[11]), "=f"(d[12]), "=f"(d[13]), "=f"(d[14]), "=f"(d[15]),
        "=f"(d[16]), "=f"(d[17]), "=f"(d[18]), "=f"(d[19]), "=f"(d[20]), "=f"(d[21]), "=f"(d[22]), "=f"(d[23]),
        "=f"(d[24]), "=f"(d[25]), "=f"(d[26]), "=f"(d[27]), "=f"(d[28]), "=f"(d[29]), "=f"(d[30]), "=f"(d[31]),
        "=f"(d[32]), "=f"(d[33]), "=f"(d[34]), "=f"(d[35]), "=f"(d[36]), "=f"(d[37]), "=f"(d[38]), "=f"(d[39]),
        "=f"(d[40]), "=f"(d[41]), "=f"(d[42]), "=f"(d[43]), "=f"(d[44]), "=f"(d[45]), "=f"(d[46]), "=f"(d[47]),
        "=f"(d[48]), "=f"(d[49]), "=f"(d[50]), "=f"(d[51]), "=f"(d[52]), "=f"(d[53]), "=f"(d[54]), "=f"(d[55]),
        "=f"(d[56]), "=f"(d[57]), "=f"(d[58]), "=f"(d[59]), "=f"(d[60]), "=f"(d[61]), "=f"(d[62]), "=f"(d[63]),
        "=f"(d[64]), "=f"(d[65]), "=f"(d[66]), "=f"(d[67]), "=f"(d[68]), "=f"(d[69]), "=f"(d[70]), "=f"(d[71]),
        "=f"(d[72]), "=f"(d[73]), "=f"(d[74]), "=f"(d[75]), "=f"(d[76]), "=f"(d[77]), "=f"(d[78]), "=f"(d[79])
      : "l"(descA), "l"(descB));
}

__device__ __forceinline__ void mma_ss192(float (&d)[96], uint64_t descA, uint64_t descB) {
  asm volatile("wgmma.mma_async.sync.aligned.m64n192k16.f32.bf16.bf16 {"
      "%0, %1, %2, %3, %4, %5, %6, %7, %8, %9, %10, %11, %12, %13, %14, %15, "
      "%16, %17, %18, %19, %20, %21, %22, %23, %24, %25, %26, %27, %28, %29, %30, %31, "
      "%32, %33, %34, %35, %36, %37, %38, %39, %40, %41, %42, %43, %44, %45, %46, %47, "
      "%48, %49, %50, %51, %52, %53, %54, %55, %56, %57, %58, %59, %60, %61, %62, %63, "
      "%64, %65, %66, %67, %68, %69, %70, %71, %72, %73, %74, %75, %76, %77, %78, %79, "
      "%80, %81, %82, %83, %84, %85, %86, %87, %88, %89, %90, %91, %92, %93, %94, %95"
      "}, %96, %97, 1, 1, 1, 0, 1;\n"
      : "+f"(d[0]), "+f"(d[1]), "+f"(d[2]), "+f"(d[3]), "+f"(d[4]), "+f"(d[5]), "+f"(d[6]), "+f"(d[7]),
        "+f"(d[8]), "+f"(d[9]), "+f"(d[10]), "+f"(d[11]), "+f"(d[12]), "+f"(d[13]), "+f"(d[14]), "+f"(d[15]),
        "+f"(d[16]), "+f"(d[17]), "+f"(d[18]), "+f"(d[19]), "+f"(d[20]), "+f"(d[21]), "+f"(d[22]), "+f"(d[23]),
        "+f"(d[24]), "+f"(d[25]), "+f"(d[26]), "+f"(d[27]), "+f"(d[28]), "+f"(d[29]), "+f"(d[30]), "+f"(d[31]),
        "+f"(d[32]), "+f"(d[33]), "+f"(d[34]), "+f"(d[35]), "+f"(d[36]), "+f"(d[37]), "+f"(d[38]), "+f"(d[39]),
        "+f"(d[40]), "+f"(d[41]), "+f"(d[42]), "+f"(d[43]), "+f"(d[44]), "+f"(d[45]), "+f"(d[46]), "+f"(d[47]),
        "+f"(d[48]), "+f"(d[49]), "+f"(d[50]), "+f"(d[51]), "+f"(d[52]), "+f"(d[53]), "+f"(d[54]), "+f"(d[55]),
        "+f"(d[56]), "+f"(d[57]), "+f"(d[58]), "+f"(d[59]), "+f"(d[60]), "+f"(d[61]), "+f"(d[62]), "+f"(d[63]),
        "+f"(d[64]), "+f"(d[65]), "+f"(d[66]), "+f"(d[67]), "+f"(d[68]), "+f"(d[69]), "+f"(d[70]), "+f"(d[71]),
        "+f"(d[72]), "+f"(d[73]), "+f"(d[74]), "+f"(d[75]), "+f"(d[76]), "+f"(d[77]), "+f"(d[78]), "+f"(d[79]),
        "+f"(d[80]), "+f"(d[81]), "+f"(d[82]), "+f"(d[83]), "+f"(d[84]), "+f"(d[85]), "+f"(d[86]), "+f"(d[87]),
        "+f"(d[88]), "+f"(d[89]), "+f"(d[90]), "+f"(d[91]), "+f"(d[92]), "+f"(d[93]), "+f"(d[94]), "+f"(d[95])
      : "l"(descA), "l"(descB));
}
__device__ __forceinline__ void mma_ss192_p(float (&d)[96], uint64_t descA, uint64_t descB, int acc) {
  asm volatile("{\n.reg .pred p;\nsetp.ne.b32 p, %98, 0;\n"
      "wgmma.mma_async.sync.aligned.m64n192k16.f32.bf16.bf16 {"
      "%0, %1, %2, %3, %4, %5, %6, %7, %8, %9, %10, %11, %12, %13, %14, %15, "
      "%16, %17, %18, %19, %20, %21, %22, %23, %24, %25, %26, %27, %28, %29, %30, %31, "
      "%32, %33, %34, %35, %36, %37, %38, %39, %40, %41, %42, %43, %44, %45, %46, %47, "
      "%48, %49, %50, %51, %52, %53, %54, %55, %56, %57, %58, %59, %60, %61, %62, %63, "
      "%64, %65, %66, %67, %68, %69, %70, %71, %72, %73, %74, %75, %76, %77, %78, %79, "
      "%80, %81, %82, %83, %84, %85, %86, %87, %88, %89, %90, %91, %92, %93, %94, %95"
      "}, %96, %97, p, 1, 1, 0, 1;\n}\n"
      : "+f"(d[0]), "+f"(d[1]), "+f"(d[2]), "+f"(d[3]), "+f"(d[4]), "+f"(d[5]), "+f"(d[6]), "+f"(d[7]),
        "+f"(d[8]), "+f"(d[9]), "+f"(d[10]), "+f"(d[11]), "+f"(d[12]), "+f"(d[13]), "+f"(d[14]), "+f"(d[15]),
        "+f"(d[16]), "+f"(d[17]), "+f"(d[18]), "+f"(d[19]), "+f"(d[20]), "+f"(d[21]), "+f"(d[22]), "+f"(d[23]),
        "+f"(d[24]), "+f"(d[25]), "+f"(d[26]), "+f"(d[27]), "+f"(d[28]), "+f"(d[29]), "+f"(d[30]), "+f"(d[31]),
        "+f"(d[32]), "+f"(d[33]), "+f"(d[34]), "+f"(d[35]), "+f"(d[36]), "+f"(d[37]), "+f"(d[38]), "+f"(d[39]),
        "+f"(d[40]), "+f"(d[41]), "+f"(d[42]), "+f"(d[43]), "+f"(d[44]), "+f"(d[45]), "+f"(d[46]), "+f"(d[47]),
        "+f"(d[48]), "+f"(d[49]), "+f"(d[50]), "+f"(d[51]), "+f"(d[52]), "+f"(d[53]), "+f"(d[54]), "+f"(d[55]),
        "+f"(d[56]), "+f"(d[57]), "+f"(d[58]), "+f"(d[59]), "+f"(d[60]), "+f"(d[61]), "+f"(d[62]), "+f"(d[63]),
        "+f"(d[64]), "+f"(d[65]), "+f"(d[66]), "+f"(d[67]), "+f"(d[68]), "+f"(d[69]), "+f"(d[70]), "+f"(d[71]),
        "+f"(d[72]), "+f"(d[73]), "+f"(d[74]), "+f"(d[75]), "+f"(d[76]), "+f"(d[77]), "+f"(d[78]), "+f"(d[79]),
        "+f"(d[80]), "+f"(d[81]), "+f"(d[82]), "+f"(d[83]), "+f"(d[84]), "+f"(d[85]), "+f"(d[86]), "+f"(d[87]),
        "+f"(d[88]), "+f"(d[89]), "+f"(d[90]), "+f"(d[91]), "+f"(d[92]), "+f"(d[93]), "+f"(d[94]), "+f"(d[95])
      : "l"(descA), "l"(descB), "r"(acc));
}

__device__ __forceinline__ void mma_ss80_tt(float (&d)[40], uint64_t descA, uint64_t descB) {
  asm volatile("wgmma.mma_async.sync.aligned.m64n80k16.f32.bf16.bf16 {"
      "%0, %1, %2, %3, %4, %5, %6, %7, %8, %9, %10, %11, %12, %13, %14, %15, "
      "%16, %17, %18, %19, %20, %21, %22, %23, %24, %25, %26, %27, %28, %29, %30, %31, "
      "%32, %33, %34, %35, %36, %37, %38, %39"
      "}, %40, %41, 1, 1, 1, 1, 1;\n"
      : "+f"(d[0]), "+f"(d[1]), "+f"(d[2]), "+f"(d[3]), "+f"(d[4]), "+f"(d[5]), "+f"(d[6]), "+f"(d[7]),
        "+f"(d[8]), "+f"(d[9]), "+f"(d[10]), "+f"(d[11]), "+f"(d[12]), "+f"(d[13]), "+f"(d[14]), "+f"(d[15]),
        "+f"(d[16]), "+f"(d[17]), "+f"(d[18]), "+f"(d[19]), "+f"(d[20]), "+f"(d[21]), "+f"(d[22]), "+f"(d[23]),
        "+f"(d[24]), "+f"(d[25]), "+f"(d[26]), "+f"(d[27]), "+f"(d[28]), "+f"(d[29]), "+f"(d[30]), "+f"(d[31]),
        "+f"(d[32]), "+f"(d[33]), "+f"(d[34]), "+f"(d[35]), "+f"(d[36]), "+f"(d[37]), "+f"(d[38]), "+f"(d[39])
      : "l"(descA), "l"(descB));
}
__device__ __forceinline__ void mma_ss80_tt_z(float (&d)[40], uint64_t descA, uint64_t descB) {
  asm volatile("wgmma.mma_async.sync.aligned.m64n80k16.f32.bf16.bf16 {"
      "%0, %1, %2, %3, %4, %5, %6, %7, %8, %9, %10, %11, %12, %13, %14, %15, "
      "%16, %17, %18, %19, %20, %21, %22, %23, %24, %25, %26, %27, %28, %29, %30, %31, "
      "%32, %33, %34, %35, %36, %37, %38, %39"
      "}, %40, %41, 0, 1, 1, 1, 1;\n"
      : "=f"(d[0]), "=f"(d[1]), "=f"(d[2]), "=f"(d[3]), "=f"(d[4]), "=f"(d[5]), "=f"(d[6]), "=f"(d[7]),
        "=f"(d[8]), "=f"(d[9]), "=f"(d[10]), "=f"(d[11]), "=f"(d[12]), "=f"(d[13]), "=f"(d[14]), "=f"(d[15]),
        "=f"(d[16]), "=f"(d[17]), "=f"(d[18]), "=f"(d[19]), "=f"(d[20]), "=f"(d[21]), "=f"(d[22]), "=f"(d[23]),
        "=f"(d[24]), "=f"(d[25]), "=f"(d[26]), "=f"(d[27]), "=f"(d[28]), "=f"(d[29]), "=f"(d[30]), "=f"(d[31]),
        "=f"(d[32]), "=f"(d[33]), "=f"(d[34]), "=f"(d[35]), "=f"(d[36]), "=f"(d[37]), "=f"(d[38]), "=f"(d[39])
      : "l"(descA), "l"(descB));
}

__device__ __forceinline__ void mma_rs80_k(float (&d)[40], const uint32_t (&a)[4], uint64_t descB) {
  asm volatile("wgmma.mma_async.sync.aligned.m64n80k16.f32.bf16.bf16 {"
      "%0, %1, %2, %3, %4, %5, %6, %7, %8, %9, %10, %11, %12, %13, %14, %15, "
      "%16, %17, %18, %19, %20, %21, %22, %23, %24, %25, %26, %27, %28, %29, %30, %31, "
      "%32, %33, %34, %35, %36, %37, %38, %39"
      "}, {%40, %41, %42, %43}, %44, 1, 1, 1, 0;\n"
      : "+f"(d[0]), "+f"(d[1]), "+f"(d[2]), "+f"(d[3]), "+f"(d[4]), "+f"(d[5]), "+f"(d[6]), "+f"(d[7]),
        "+f"(d[8]), "+f"(d[9]), "+f"(d[10]), "+f"(d[11]), "+f"(d[12]), "+f"(d[13]), "+f"(d[14]), "+f"(d[15]),
        "+f"(d[16]), "+f"(d[17]), "+f"(d[18]), "+f"(d[19]), "+f"(d[20]), "+f"(d[21]), "+f"(d[22]), "+f"(d[23]),
        "+f"(d[24]), "+f"(d[25]), "+f"(d[26]), "+f"(d[27]), "+f"(d[28]), "+f"(d[29]), "+f"(d[30]), "+f"(d[31]),
        "+f"(d[32]), "+f"(d[33]), "+f"(d[34]), "+f"(d[35]), "+f"(d[36]), "+f"(d[37]), "+f"(d[38]), "+f"(d[39])
      : "r"(a[0]), "r"(a[1]), "r"(a[2]), "r"(a[3]), "l"(descB));
}
__device__ __forceinline__ void mma_rs80_k_z(float (&d)[40], const uint32_t (&a)[4], uint64_t descB) {
  asm volatile("wgmma.mma_async.sync.aligned.m64n80k16.f32.bf16.bf16 {"
      "%0, %1, %2, %3, %4, %5, %6, %7, %8, %9, %10, %11, %12, %13, %14, %15, "
      "%16, %17, %18, %19, %20, %21, %22, %23, %24, %25, %26, %27, %28, %29, %30, %31, "
      "%32, %33, %34, %35, %36, %37, %38, %39"
      "}, {%40, %41, %42, %43}, %44, 0, 1, 1, 0;\n"
      : "=f"(d[0]), "=f"(d[1]), "=f"(d[2]), "=f"(d[3]), "=f"(d[4]), "=f"(d[5]), "=f"(d[6]), "=f"(d[7]),
        "=f"(d[8]), "=f"(d[9]), "=f"(d[10]), "=f"(d[11]), "=f"(d[12]), "=f"(d[13]), "=f"(d[14]), "=f"(d[15]),
        "=f"(d[16]), "=f"(d[17]), "=f"(d[18]), "=f"(d[19]), "=f"(d[20]), "=f"(d[21]), "=f"(d[22]), "=f"(d[23]),
        "=f"(d[24]), "=f"(d[25]), "=f"(d[26]), "=f"(d[27]), "=f"(d[28]), "=f"(d[29]), "=f"(d[30]), "=f"(d[31]),
        "=f"(d[32]), "=f"(d[33]), "=f"(d[34]), "=f"(d[35]), "=f"(d[36]), "=f"(d[37]), "=f"(d[38]), "=f"(d[39])
      : "r"(a[0]), "r"(a[1]), "r"(a[2]), "r"(a[3]), "l"(descB));
}

__device__ __forceinline__ void mma_rs48_k(float (&d)[24], const uint32_t (&a)[4], uint64_t descB) {
  asm volatile("wgmma.mma_async.sync.aligned.m64n48k16.f32.bf16.bf16 {"
      "%0, %1, %2, %3, %4, %5, %6, %7, %8, %9, %10, %11, %12, %13, %14, %15, "
      "%16, %17, %18, %19, %20, %21, %22, %23"
      "}, {%24, %25, %26, %27}, %28, 1, 1, 1, 0;\n"
      : "+f"(d[0]), "+f"(d[1]), "+f"(d[2]), "+f"(d[3]), "+f"(d[4]), "+f"(d[5]), "+f"(d[6]), "+f"(d[7]),
        "+f"(d[8]), "+f"(d[9]), "+f"(d[10]), "+f"(d[11]), "+f"(d[12]), "+f"(d[13]), "+f"(d[14]), "+f"(d[15]),
        "+f"(d[16]), "+f"(d[17]), "+f"(d[18]), "+f"(d[19]), "+f"(d[20]), "+f"(d[21]), "+f"(d[22]), "+f"(d[23])
      : "r"(a[0]), "r"(a[1]), "r"(a[2]), "r"(a[3]), "l"(descB));
}
__device__ __forceinline__ void mma_rs48_k_z(float (&d)[24], const uint32_t (&a)[4], uint64_t descB) {
  asm volatile("wgmma.mma_async.sync.aligned.m64n48k16.f32.bf16.bf16 {"
      "%0, %1, %2, %3, %4, %5, %6, %7, %8, %9, %10, %11, %12, %13, %14, %15, "
      "%16, %17, %18, %19, %20, %21, %22, %23"
      "}, {%24, %25, %26, %27}, %28, 0, 1, 1, 0;\n"
      : "=f"(d[0]), "=f"(d[1]), "=f"(d[2]), "=f"(d[3]), "=f"(d[4]), "=f"(d[5]), "=f"(d[6]), "=f"(d[7]),
        "=f"(d[8]), "=f"(d[9]), "=f"(d[10]), "=f"(d[11]), "=f"(d[12]), "=f"(d[13]), "=f"(d[14]), "=f"(d[15]),
        "=f"(d[16]), "=f"(d[17]), "=f"(d[18]), "=f"(d[19]), "=f"(d[20]), "=f"(d[21]), "=f"(d[22]), "=f"(d[23])
      : "r"(a[0]), "r"(a[1]), "r"(a[2]), "r"(a[3]), "l"(descB));
}

__device__ __forceinline__ void mma_rs160_n(float (&d)[80], const uint32_t (&a)[4], uint64_t descB) {
  asm volatile("wgmma.mma_async.sync.aligned.m64n160k16.f32.bf16.bf16 {"
      "%0, %1, %2, %3, %4, %5, %6, %7, %8, %9, %10, %11, %12, %13, %14, %15, "
      "%16, %17, %18, %19, %20, %21, %22, %23, %24, %25, %26, %27, %28, %29, %30, %31, "
      "%32, %33, %34, %35, %36, %37, %38, %39, %40, %41, %42, %43, %44, %45, %46, %47, "
      "%48, %49, %50, %51, %52, %53, %54, %55, %56, %57, %58, %59, %60, %61, %62, %63, "
      "%64, %65, %66, %67, %68, %69, %70, %71, %72, %73, %74, %75, %76, %77, %78, %79"
      "}, {%80, %81, %82, %83}, %84, 1, 1, 1, 1;\n"
      : "+f"(d[0]), "+f"(d[1]), "+f"(d[2]), "+f"(d[3]), "+f"(d[4]), "+f"(d[5]), "+f"(d[6]), "+f"(d[7]),
        "+f"(d[8]), "+f"(d[9]), "+f"(d[10]), "+f"(d[11]), "+f"(d[12]), "+f"(d[13]), "+f"(d[14]), "+f"(d[15]),
        "+f"(d[16]), "+f"(d[17]), "+f"(d[18]), "+f"(d[19]), "+f"(d[20]), "+f"(d[21]), "+f"(d[22]), "+f"(d[23]),
        "+f"(d[24]), "+f"(d[25]), "+f"(d[26]), "+f"(d[27]), "+f"(d[28]), "+f"(d[29]), "+f"(d[30]), "+f"(d[31]),
        "+f"(d[32]), "+f"(d[33]), "+f"(d[34]), "+f"(d[35]), "+f"(d[36]), "+f"(d[37]), "+f"(d[38]), "+f"(d[39]),
        "+f"(d[40]), "+f"(d[41]), "+f"(d[42]), "+f"(d[43]), "+f"(d[44]), "+f"(d[45]), "+f"(d[46]), "+f"(d[47]),
        "+f"(d[48]), "+f"(d[49]), "+f"(d[50]), "+f"(d[51]), "+f"(d[52]), "+f"(d[53]), "+f"(d[54]), "+f"(d[55]),
        "+f"(d[56]), "+f"(d[57]), "+f"(d[58]), "+f"(d[59]), "+f"(d[60]), "+f"(d[61]), "+f"(d[62]), "+f"(d[63]),
        "+f"(d[64]), "+f"(d[65]), "+f"(d[66]), "+f"(d[67]), "+f"(d[68]), "+f"(d[69]), "+f"(d[70]), "+f"(d[71]),
        "+f"(d[72]), "+f"(d[73]), "+f"(d[74]), "+f"(d[75]), "+f"(d[76]), "+f"(d[77]), "+f"(d[78]), "+f"(d[79])
      : "r"(a[0]), "r"(a[1]), "r"(a[2]), "r"(a[3]), "l"(descB));
}
__device__ __forceinline__ void mma_rs160_n_z(float (&d)[80], const uint32_t (&a)[4], uint64_t descB) {
  asm volatile("wgmma.mma_async.sync.aligned.m64n160k16.f32.bf16.bf16 {"
      "%0, %1, %2, %3, %4, %5, %6, %7, %8, %9, %10, %11, %12, %13, %14, %15, "
      "%16, %17, %18, %19, %20, %21, %22, %23, %24, %25, %26, %27, %28, %29, %30, %31, "
      "%32, %33, %34, %35, %36, %37, %38, %39, %40, %41, %42, %43, %44, %45, %46, %47, "
      "%48, %49, %50, %51, %52, %53, %54, %55, %56, %57, %58, %59, %60, %61, %62, %63, "
      "%64, %65, %66, %67, %68, %69, %70, %71, %72, %73, %74, %75, %76, %77, %78, %79"
      "}, {%80, %81, %82, %83}, %84, 0, 1, 1, 1;\n"
      : "=f"(d[0]), "=f"(d[1]), "=f"(d[2]), "=f"(d[3]), "=f"(d[4]), "=f"(d[5]), "=f"(d[6]), "=f"(d[7]),
        "=f"(d[8]), "=f"(d[9]), "=f"(d[10]), "=f"(d[11]), "=f"(d[12]), "=f"(d[13]), "=f"(d[14]), "=f"(d[15]),
        "=f"(d[16]), "=f"(d[17]), "=f"(d[18]), "=f"(d[19]), "=f"(d[20]), "=f"(d[21]), "=f"(d[22]), "=f"(d[23]),
        "=f"(d[24]), "=f"(d[25]), "=f"(d[26]), "=f"(d[27]), "=f"(d[28]), "=f"(d[29]), "=f"(d[30]), "=f"(d[31]),
        "=f"(d[32]), "=f"(d[33]), "=f"(d[34]), "=f"(d[35]), "=f"(d[36]), "=f"(d[37]), "=f"(d[38]), "=f"(d[39]),
        "=f"(d[40]), "=f"(d[41]), "=f"(d[42]), "=f"(d[43]), "=f"(d[44]), "=f"(d[45]), "=f"(d[46]), "=f"(d[47]),
        "=f"(d[48]), "=f"(d[49]), "=f"(d[50]), "=f"(d[51]), "=f"(d[52]), "=f"(d[53]), "=f"(d[54]), "=f"(d[55]),
        "=f"(d[56]), "=f"(d[57]), "=f"(d[58]), "=f"(d[59]), "=f"(d[60]), "=f"(d[61]), "=f"(d[62]), "=f"(d[63]),
        "=f"(d[64]), "=f"(d[65]), "=f"(d[66]), "=f"(d[67]), "=f"(d[68]), "=f"(d[69]), "=f"(d[70]), "=f"(d[71]),
        "=f"(d[72]), "=f"(d[73]), "=f"(d[74]), "=f"(d[75]), "=f"(d[76]), "=f"(d[77]), "=f"(d[78]), "=f"(d[79])
      : "r"(a[0]), "r"(a[1]), "r"(a[2]), "r"(a[3]), "l"(descB));
}

__device__ __forceinline__ void feature_map(const uint32_t (&P)[2][10], uint32_t (&fr)[10][4]) {
  constexpr float L2E = 1.4426950408889634f;
#pragma unroll
  for (int p = 0; p < 2; p++) {
#pragma unroll
    for (int r = 0; r < 2; r++) {
      uint32_t mx = P[r][5 * p], mn = mx;
#pragma unroll
      for (int g = 1; g < 5; g++) { mx = max_bf2(mx, P[r][5 * p + g]); mn = min_bf2(mn, P[r][5 * p + g]); }
      mx = max_bf2(mx, __shfl_xor_sync(0xffffffffu, mx, 1));
      mn = min_bf2(mn, __shfl_xor_sync(0xffffffffu, mn, 1));
      mx = max_bf2(mx, __shfl_xor_sync(0xffffffffu, mx, 2));
      mn = min_bf2(mn, __shfl_xor_sync(0xffffffffu, mn, 2));
      float mx0 = -bf_lo(mx) * L2E, mx1 = -bf_hi(mx) * L2E, mn0 = bf_lo(mn) * L2E, mn1 = bf_hi(mn) * L2E;
      float ep0[5], ep1[5], en0[5], en1[5];
      float sp0 = 0.f, sp1 = 0.f, sn0 = 0.f, sn1 = 0.f;
#pragma unroll
      for (int g = 0; g < 5; g++) {
        float x0 = bf_lo(P[r][5 * p + g]), x1 = bf_hi(P[r][5 * p + g]);
        ep0[g] = ex2(fmaf(x0, L2E, mx0)); ep1[g] = ex2(fmaf(x1, L2E, mx1));
        en0[g] = ex2(fmaf(x0, -L2E, mn0)); en1[g] = ex2(fmaf(x1, -L2E, mn1));
        sp0 += ep0[g]; sp1 += ep1[g]; sn0 += en0[g]; sn1 += en1[g];
      }
      sp0 += __shfl_xor_sync(0xffffffffu, sp0, 1); sp1 += __shfl_xor_sync(0xffffffffu, sp1, 1);
      sn0 += __shfl_xor_sync(0xffffffffu, sn0, 1); sn1 += __shfl_xor_sync(0xffffffffu, sn1, 1);
      sp0 += __shfl_xor_sync(0xffffffffu, sp0, 2); sp1 += __shfl_xor_sync(0xffffffffu, sp1, 2);
      sn0 += __shfl_xor_sync(0xffffffffu, sn0, 2); sn1 += __shfl_xor_sync(0xffffffffu, sn1, 2);
      sp0 = rcp(sp0); sp1 = rcp(sp1); sn0 = rcp(sn0); sn1 = rcp(sn1);
#pragma unroll
      for (int g = 0; g < 5; g++) {
        fr[5 * p + g][r] = pack_bf16(ep0[g] * sp0, ep1[g] * sp1);
        fr[5 * p + g][2 + r] = pack_bf16(en0[g] * sn0, en1[g] * sn1);
      }
    }
  }
}

template <int V> struct IntC { static constexpr int value = V; };
struct Ring {
  uint32_t idx, phase;
  template <int N> __device__ __forceinline__ void next() { if (++idx == N) { idx = 0; phase ^= 1; } }
};

}

__global__ void __cluster_dims__(2, 1, 1) __launch_bounds__(384, 1)
fused_kernel(const __grid_constant__ Maps maps, const __nv_bfloat16* __restrict__ x, const __nv_bfloat16* __restrict__ wqkv,
             const __nv_bfloat16* __restrict__ wphi, const __nv_bfloat16* __restrict__ w1, const __nv_bfloat16* __restrict__ w2,
             const __nv_bfloat16* __restrict__ w3, const __nv_bfloat16* __restrict__ w4, const __nv_bfloat16* __restrict__ wo,
             const __nv_bfloat16* __restrict__ gate_w, __nv_bfloat16* __restrict__ out) {
  extern __shared__ __align__(1024) uint8_t sgen[];
  const uint32_t sb = smem_u32(sgen);
  const uint32_t sb16 = (sb & 0x3FFFFu) >> 4;
  const uint32_t bars = sb + OFF_BAR;
  const uint32_t fullA = bars + 8 * B_FULLA, emptyA = bars + 8 * B_EMPTYA, fullB = bars + 8 * B_FULLB, emptyB = bars + 8 * B_EMPTYB;

  const int tid = threadIdx.x;
  const int rank = blockIdx.x & 1;
  const int pairIdx = blockIdx.x >> 1;
  const int i = pairIdx >> 2, j = 2 * (pairIdx & 3) + rank;
  const int k3 = (5 * (pairIdx & 3) + 1) >> 1;

  TSTAMP(0);
  auto load_p1_b = [&](int k, uint32_t slot, uint32_t bar) {
    mbar_expect_tx(bar, 40960);
    tma4d(slot + 8192, &maps.qm, bar, 0, 64 * k, 0, j);
    tma3d(slot, &maps.w1m, bar, 0, 64 * k, j);
    tma4d(slot + 32768 + 2048, &maps.qr, bar, 64, 64 * k, 0, j);
    tma3d(slot + 32768, &maps.w1r, bar, 64, 64 * k, j);
  };
  if (tid >= 256) {
    asm volatile("setmaxnreg.dec.sync.aligned.u32 40;");
    if (tid == 256) {
#pragma unroll
      for (int s = 0; s < NA; s++) mbar_init(fullA + 8 * s, 1);
      asm volatile("fence.mbarrier_init.release.cluster;" ::: "memory");
#pragma unroll 1
      for (int u = 0; u < 4; u++) {
        if ((u & 1) == 0) mbar_expect_tx(fullA + 4 * u, SLOT_A);
        tma2d(sb + OFF_A + u * 8192, &maps.x, fullA + 8 * (u >> 1), 64 * (u >> 1), 128 * i + 64 * (u & 1));
      }
    } else if (tid == 288) {
#pragma unroll
      for (int s = 0; s < NB; s++) mbar_init(fullB + 8 * s, 1);
      asm volatile("fence.mbarrier_init.release.cluster;" ::: "memory");
#pragma unroll 1
      for (int k = 0; k < 2; k++) load_p1_b(k, sb + OFF_B + k * SLOT_B, fullB + 8 * k);
      l2_prefetch(wqkv + (size_t)(128 + 4 * blockIdx.x) * (3 * D_), 4 * 3 * D_ * 2);
    } else if (tid == 320) {
#pragma unroll
      for (int b = B_CS; b < NBAR; b++) mbar_init(bars + 8 * b, b < B_EMPTYB ? 1 : b < B_EMPTYA ? 8 : b < B_X1P ? 16 : 2);
#pragma unroll
      for (int b = B_DSR; b < B_EMPTYB; b++) mbar_expect_tx(bars + 8 * b, 10240);
      asm volatile("fence.mbarrier_init.release.cluster;" ::: "memory");
    }
    __syncwarp();
    asm volatile("barrier.cluster.arrive.relaxed.aligned;" ::: "memory");
    auto get_epoch = [&]() { return *reinterpret_cast<volatile unsigned*>(g_flags + FL_DONE * 32) / NCTA; };
    if (tid >= 320) {
      const int lane = tid & 31, ch = lane % 10, rg = lane / 10;
      const __nv_bfloat16* p = w1 + (size_t)(40 * i + (tid >= 352 ? 20 : 0) + rg) * D_ + 80 * j + 8 * ch;
      const unsigned par = get_epoch() & 1;
      float a[8];
#pragma unroll
      for (int e = 0; e < 8; e++) a[e] = 0.f;
#pragma unroll
      for (int it = 0; it < 7; it++) {
        uint4 v = make_uint4(0, 0, 0, 0);
        if (lane < 30 && 3 * it + rg < 20) v = __ldg(reinterpret_cast<const uint4*>(p + (size_t)it * 3 * D_));
        a[0] += bf_lo(v.x); a[1] += bf_hi(v.x); a[2] += bf_lo(v.y); a[3] += bf_hi(v.y);
        a[4] += bf_lo(v.z); a[5] += bf_hi(v.z); a[6] += bf_lo(v.w); a[7] += bf_hi(v.w);
      }
#pragma unroll
      for (int e = 0; e < 8; e++) a[e] += __shfl_down_sync(0xffffffffu, a[e], 10) + __shfl_down_sync(0xffffffffu, a[e], 20);
      if (lane < 10) {
        float* cd = g_acc[par] + 8 * KV_J + 80 * j + 8 * ch;
        red_add4(cd, a[0], a[1], a[2], a[3]); red_add4(cd + 4, a[4], a[5], a[6], a[7]);
      }
      __syncwarp();
      if (lane == 0) flag_add(FL_CS + j);
      __syncwarp();
    }
    asm volatile("barrier.cluster.wait.aligned;" ::: "memory");
    const int lane = tid & 31, pw = (tid >> 5) & 3;
    if (pw == 0) {
      if (tid == 256) {
        Ring r{2, 1};
        unsigned ep1 = 0;
#pragma unroll 1
        for (int k = 2; k < 25; k++) {
          if (k == 4) ep1 = get_epoch() + 1;
          if (k == 10 || k == 17) {
            if (k == 10) mbar_wait(bars + 8 * B_HST, 0);
            flag_wait(k == 10 ? FL_H + 2 * i + rank : FL_X1 + i, ep1 * 8u);
            TSTAMPX(k == 10 ? 29 : 30);
          }
          if (k == 15) mbar_wait(bars + 8 * B_X1P, 0);
          mbar_wait(emptyA + 8 * r.idx, r.phase);
          const uint32_t bar = fullA + 8 * r.idx, slot = sb + OFF_A + r.idx * SLOT_A;
          mbar_expect_tx(bar, SLOT_A);
          if (k >= 10 && k < 15) tma2d(slot, &maps.hs, bar, 64 * (k - 10) + 320 * rank, 128 * i);
          else tma2d_mc(slot + rank * 8192, k < 10 ? &maps.x : &maps.x1, bar, 64 * (k < 10 ? k : (k - 15 + k3) % 10), 128 * i + 64 * rank);
          r.next<NA>();
        }
      }
    } else if (pw == 1) {
      if (tid == 288) {
        Ring r{2, 1};
#pragma unroll 1
        for (int k = 2; k < 18; k++) {
          mbar_wait(emptyB + 8 * r.idx, r.phase);
          const uint32_t bar = fullB + 8 * r.idx, slot = sb + OFF_B + r.idx * SLOT_B;
          if (k < 10) {
            load_p1_b(k, slot, bar);
          } else if (k < 13) {
            mbar_expect_tx(bar, k < 12 ? 40960 : 20480);
            tma3d(slot, &maps.w2, bar, 0, 320 * rank + 128 * (k - 10), 5 * (j >> 1));
            if (k < 12) tma3d(slot + 20480, &maps.w2, bar, 0, 320 * rank + 128 * (k - 10) + 64, 5 * (j >> 1));
          } else {
            mbar_expect_tx(bar, 49152);
            tma3d(slot, &maps.w3, bar, 0, 64 * ((2 * (k - 13) + k3) % 10), 3 * j);
            tma3d(slot + 24576, &maps.w3, bar, 0, 64 * ((2 * (k - 13) + 1 + k3) % 10), 3 * j);
          }
          r.next<NB>();
        }
#pragma unroll 1
        for (int n = 0; n < 8; n++) {
          if (n < 3) { mbar_wait(emptyB + 8 * r.idx, r.phase); r.next<NB>(); }
          if (n >= 4) mbar_wait(bars + 8 * (B_EMPTY4 + n - 4), 0);
          const uint32_t bar = bars + 8 * (B_FULL4 + n), set = sb + ((n >> 1) & 1) * SET4;
          const int h = n & 1, m = ((j >> 1) + 1 + (n >> 1)) & 3;
          mbar_expect_tx(bar, h ? 40960 : 46080);
          tma3d(set + (h ? 46080 : 0), h ? &maps.w4 : &maps.wo, bar, 0, h ? 192 * j + 64 : 80 * j, 5 * m);
          tma3d(set + (h ? 66560 : 25600), &maps.w4, bar, 0, 192 * j + 128 * h, 5 * m);
        }
        mbar_wait(bars + 8 * (B_EMPTY4 + 4), 0);
        mbar_wait(bars + 8 * (B_EMPTY4 + 5), 0);
        fence_async_glb();
        mbar_expect_tx(bars + 8 * B_XR, 61440);
        tma2d(sb + OFF_OUT, &maps.st_x1, bars + 8 * B_XR, 80 * j, 128 * i);
        bulk_load(sb + OFF_G0, g_part + (size_t)(i * 8 + j) * 3840, 40960, bars + 8 * B_XR);
      }
    } else {
      const unsigned epoch = get_epoch();
      float* accg = g_acc[epoch & 1];
      if (pw == 2) {
        {
          float* nxt = g_acc[(epoch + 1) & 1];
          constexpr int PER = ACC_FLOATS / NCTA;
#pragma unroll 1
          for (int e = lane; e < PER; e += 32) nxt[blockIdx.x * PER + e] = 0.f;
        }
        if (tid == 320) {
          flag_wait(FL_CS + j, (epoch + 1) * 32u);
          flag_wait(FL_ST + i, (epoch + 1) * 8u);
          fence_async_glb();
          *reinterpret_cast<volatile uint32_t*>(sgen + OFF_BAR + 8 * NBAR) = (epoch + 1) & 1;
          mbar_expect_tx(bars + 8 * B_CS, 320 + 2048);
          bulk_load(sb + OFF_CS, accg + 8 * KV_J + 80 * j, 320, bars + 8 * B_CS);
          bulk_load(sb + OFF_XST, g_xstat + 128 * i, 2048, bars + 8 * B_CS);
          TSTAMPX(21);
          l2_prefetch(w2 + (size_t)blockIdx.x * (D_ * D_ / NCTA), D_ * D_ * 2 / NCTA);
          flag_wait(FL_H + 2 * i + rank, (epoch + 1) * 8u);
          l2_prefetch(w3 + (size_t)blockIdx.x * (F_ * D_ / NCTA), F_ * D_ * 2 / NCTA);
          l2_prefetch(w4 + (size_t)blockIdx.x * (F_ * D_ / NCTA), F_ * D_ * 2 / NCTA);
          l2_prefetch(wo + (size_t)blockIdx.x * (D_ * D_ / NCTA), D_ * D_ * 2 / NCTA);
          flag_wait(FL_KV + j, (epoch + 1) * 16u);
          mbar_expect_tx(bars + 8 * B_KV, KV_J * 4);
          bulk_load(sb + OFF_MISC, accg + j * KV_J, KV_J * 4, bars + 8 * B_KV);
          TSTAMPX(22);
        }
        __syncwarp();
#pragma unroll 1
        for (int m = 0; m < 6; m++) {
          const int col = 192 * j + 32 * m + 8 * (lane & 3);
          const __nv_bfloat16* p = w3 + (size_t)(40 * i + (lane >> 2) * 5) * F_ + col;
          float a[8];
#pragma unroll
          for (int e = 0; e < 8; e++) a[e] = 0.f;
#pragma unroll
          for (int it = 0; it < 5; it++) {
            const uint4 v = __ldg(reinterpret_cast<const uint4*>(p + (size_t)it * F_));
            a[0] += bf_lo(v.x); a[1] += bf_hi(v.x); a[2] += bf_lo(v.y); a[3] += bf_hi(v.y);
            a[4] += bf_lo(v.z); a[5] += bf_hi(v.z); a[6] += bf_lo(v.w); a[7] += bf_hi(v.w);
          }
#pragma unroll
          for (int e = 0; e < 4; e++) {
            const float snd = (lane & 4) ? a[e] : a[e + 4], keep = (lane & 4) ? a[e + 4] : a[e];
            a[e] = keep + __shfl_xor_sync(0xffffffffu, snd, 4);
            a[e] += __shfl_xor_sync(0xffffffffu, a[e], 8);
            a[e] += __shfl_xor_sync(0xffffffffu, a[e], 16);
          }
          if (lane < 8) red_add4(accg + 8 * KV_J + D_ + col + (lane >> 2) * 4, a[0], a[1], a[2], a[3]);
        }
        __syncwarp();
        if (tid == 320) {
          flag_add(FL_CS3 + j);
          flag_wait(FL_S1 + i, (epoch + 1) * 8u);
          flag_wait(FL_CS3 + j, (epoch + 1) * 16u);
          fence_async_glb();
          mbar_expect_tx(bars + 8 * B_ST1, 8192 + 768);
          bulk_load(sb + OFF_CS + 320, accg + 8 * KV_J + D_ + 192 * j, 768, bars + 8 * B_ST1);
          bulk_load(sb + OFF_MISC, g_st1 + 128 * i * 8, 8192, bars + 8 * B_ST1);
        }
      }
      if (tid == 352) {
        mbar_wait(bars + 8 * B_SIGP, 0);
        flag_add(FL_ST + i);
        TSTAMPX(20);
        mbar_expect_tx(bars + 8 * B_XR, 20480);
#pragma unroll 1
        for (int u = 0; u < 8; u++)
          tma2d(sb + OFF_B + (u / 3) * SLOT_B + SPARE + (u % 3) * 2560, &maps.xr, bars + 8 * B_XR, 80 * j, 128 * i + 16 * u);
        const int shift = (j < 2) ? 1 : (j < 4) ? -1 : (j < 6) ? 2 : -2;
        if ((shift > 0 && i == 0) || (shift < 0 && i == 15)) {
          const int nz = shift > 0 ? shift : -shift, zr = shift > 0 ? 0 : S_ - nz;
#pragma unroll 1
          for (int e = 0; e < nz * 10; e++)
            reinterpret_cast<uint4*>(g_Hs + (size_t)(2 + zr + e / 10) * D_ + 80 * j)[e % 10] = make_uint4(0, 0, 0, 0);
          fence_async_glb();
        }
        prefetch_tmap(&maps.st_h); prefetch_tmap(&maps.st_x1); prefetch_tmap(&maps.hs); prefetch_tmap(&maps.x1);
        prefetch_tmap(&maps.w2); prefetch_tmap(&maps.w3); prefetch_tmap(&maps.w4); prefetch_tmap(&maps.wo);
        mbar_wait(bars + 8 * B_SIGH, 0);
        TSTAMPX(23);
        tma2d_store(&maps.st_h, sb + OFF_STG, 80 * j, 128 * i + 2 + shift);
        bulk_commit(); bulk_wait<0>();
        mbar_arrive(bars + 8 * B_HST);
        flag_add(FL_H + 2 * i + (j >> 2));
        flag_add_relaxed(FL_H + 2 * ((i + (shift > 0 ? 1 : -1)) & 15) + (j >> 2));
        TSTAMPX(24);
        mbar_wait(bars + 8 * B_SIGKV, 0);
        TSTAMPX(25);
        fence_async_smem();
        asm volatile("cp.reduce.async.bulk.global.shared::cta.bulk_group.add.f32 [%0], [%1], %2;"
                     ::"l"(accg + j * KV_J), "r"(sb + OFF_MISC), "r"(KV_J * 4) : "memory");
        bulk_commit(); bulk_wait<0>();
        flag_add(FL_KV + j);
        TSTAMPX(26);
        mbar_wait(bars + 8 * B_SIGX1, 0);
        TSTAMPX(27);
        tma2d_store(&maps.st_x1, sb + OFF_STG, 80 * j, 128 * i);
        bulk_commit(); bulk_wait<0>();
        flag_add(FL_X1 + i);
        mbar_arrive_cta(bars + 8 * B_X1P, 0); mbar_arrive_cta(bars + 8 * B_X1P, 1);
        TSTAMPX(28);
        mbar_wait(bars + 8 * B_MFREE, 0);
        flag_add(FL_S1 + i);
      }
    }
  } else {
    uint4 pv[5], pw_[5], pre;
    {
      const int row = 128 * i + 16 * j + (tid >> 4), l16 = tid & 15;
#pragma unroll
      for (int c = 0; c < 5; c++) pv[c] = __ldg(reinterpret_cast<const uint4*>(x + (size_t)row * D_ + c * 128 + l16 * 8));
      pre = __ldg(reinterpret_cast<const uint4*>(wphi + (size_t)j * 1600) + (tid < 200 ? tid : 0));
#pragma unroll
      for (int c = 0; c < 5; c++) pw_[c] = __ldg(reinterpret_cast<const uint4*>(gate_w + c * 128 + l16 * 8));
    }
    asm volatile("barrier.cluster.arrive.relaxed.aligned;" ::: "memory");
    asm volatile("setmaxnreg.inc.sync.aligned.u32 232;");
    const int wg = tid >> 7, warp = tid >> 5, lane = tid & 31, t = lane & 3;
    const int rloc = warp * 16 + (lane >> 2);
    const float* s_cs = reinterpret_cast<const float*>(sgen + OFF_CS);
    auto signal = [&](int b) {
      __syncwarp();
      if (lane == 0) mbar_arrive(bars + 8 * b);
    };
    auto releaseB = [&](uint32_t bar) {
      __syncwarp();
      if (lane == 0) mbar_arrive(bar);
    };
    auto release = [&](uint32_t bar) {
      __syncwarp();
      if (lane < 2) mbar_arrive_cta(bar, lane);
    };
    const uint32_t stg_lane = (warp * 16 + ((lane >> 3) & 1) * 8 + (lane & 7)) * 160 + (lane >> 4) * 16;

    auto stage_tile = [&](uint32_t stg, const uint32_t (&v)[2][10]) {
#pragma unroll
      for (int s = 0; s < 5; s++) stsm4(stg + stg_lane + s * 32, v[0][2 * s], v[1][2 * s], v[0][2 * s + 1], v[1][2 * s + 1]);
    };

    {
#pragma unroll 1
      for (int e = tid; e < 800; e += 256) sts128(sb + OFF_MISC + e * 16, make_uint4(0, 0, 0, 0));
      bar_sync(1, 256);
      float f[40];
      float s = 0.f, gs = 0.f;
#pragma unroll
      for (int c = 0; c < 5; c++) {
        const uint32_t vv[4] = {pv[c].x, pv[c].y, pv[c].z, pv[c].w}, ww[4] = {pw_[c].x, pw_[c].y, pw_[c].z, pw_[c].w};
#pragma unroll
        for (int e = 0; e < 4; e++) {
          f[8 * c + 2 * e] = bf_lo(vv[e]); f[8 * c + 2 * e + 1] = bf_hi(vv[e]);
          s += f[8 * c + 2 * e] + f[8 * c + 2 * e + 1];
          gs = fmaf(f[8 * c + 2 * e], bf_lo(ww[e]), gs); gs = fmaf(f[8 * c + 2 * e + 1], bf_hi(ww[e]), gs);
        }
      }
#pragma unroll
      for (int o = 1; o < 16; o <<= 1) { s += __shfl_xor_sync(0xffffffffu, s, o); gs += __shfl_xor_sync(0xffffffffu, gs, o); }
      const float mean = s * (1.f / D_);
      float q = 0.f;
#pragma unroll
      for (int e = 0; e < 40; e++) { const float d = f[e] - mean; q = fmaf(d, d, q); }
#pragma unroll
      for (int o = 1; o < 16; o <<= 1) q += __shfl_xor_sync(0xffffffffu, q, o);
      const float rstd = rsqrtf(q * (1.f / D_) + 1e-5f);
      asm volatile("barrier.cluster.wait.aligned;" ::: "memory");
      if ((tid & 15) == 0) g_xstat[128 * i + 16 * j + (tid >> 4)] = make_float4(rstd, -mean, rcp(1.f + __expf(-gs)), 0.f);
      signal(B_SIGP);
      if (tid < 200) {
        const uint32_t ww[4] = {pre.x, pre.y, pre.z, pre.w};
        const int h = tid / 50;
#pragma unroll
        for (int e = 0; e < 8; e++) {
          const int idx = tid * 8 + e, k = idx / 20, ff = idx - 20 * k;
          const int n = 40 * (h >> 1) + 8 * (ff >> 2) + 2 * (ff & 3) + (h & 1);
          const int off = (k >> 4) * 2560 + n * 32 + ((((k >> 3) ^ (n >> 2)) & 1) << 4) + (k & 7) * 2;
          *reinterpret_cast<unsigned short*>(sgen + OFF_MISC + off) = (unsigned short)(ww[e >> 1] >> ((e & 1) * 16));
        }
      }
    }
    TSTAMP(1);

    Ring ra{0, 0}, rb{0, 0};
    uint32_t qp[2][10], P[2][10];
    float st_g[2];
    {
      float accM[128], accR[32];
      uint32_t pa = 0, pb = 0;
#pragma unroll 1
      for (int k = 0; k < 10; k++) {
        mbar_wait(fullA + 8 * ra.idx, ra.phase);
        if (tid == 0) TRACE(32 + k);
        mbar_wait(fullB + 8 * rb.idx, rb.phase);
        if (tid == 0) TRACE(64 + k);
        if (k == 0) TSTAMP(2);
        const uint32_t a0 = sb16 + ((OFF_A + ra.idx * SLOT_A + wg * 8192) >> 4), b0 = sb16 + ((OFF_B + rb.idx * SLOT_B) >> 4);
        wg_fence();
#pragma unroll
        for (int kk = 0; kk < 4; kk++) {
          const uint64_t da = make_desc(a0, kk * 32, 16, 1024, 1);
          if (kk == 0) {
            mma_ss256_p(accM, da, make_desc(b0, 0, 8192, 1024, 1), k);
            mma_ss64_p(accR, da, make_desc(b0, 32768, 2048, 256, 3), k);
          } else {
            mma_ss256(accM, da, make_desc(b0, kk * 2048, 8192, 1024, 1));
            mma_ss64(accR, da, make_desc(b0, 32768 + kk * 512, 2048, 256, 3));
          }
          if (kk == 0) {
            wg_commit();
            if (k > 0) {
              wg_wait<1>();
              if (k - 1 < 8) release(emptyA + 8 * pa);
              releaseB(emptyB + 8 * pb);
            }
          }
        }
        wg_commit();
        pa = ra.idx; pb = rb.idx;
        ra.next<NA>(); rb.next<NB>();
      }
      TSTAMP(18);
      float st_rstd[2], st_mr[2];
      mbar_wait(bars + 8 * B_CS, 0);
#pragma unroll
      for (int r = 0; r < 2; r++) {
        const uint4 st = lds128(sb + OFF_XST + (rloc + 8 * r) * 16);
        st_rstd[r] = __uint_as_float(st.x); st_mr[r] = __uint_as_float(st.y); st_g[r] = __uint_as_float(st.z);
      }
      TSTAMP(19);
      wg_wait<0>();
      fence_regs(accM); fence_regs(accR);
      TSTAMP(3);
#define ACC(P_, G, I_) ((G) < 8 ? accM[(P_) * 32 + ((G) & 7) * 4 + (I_)] : accR[(P_) * 8 + ((G) & 1) * 4 + (I_)])
      {
        uint32_t hv[2][10];
        const GeluC g0 = gelu_consts(st_rstd[0], 1.f), g1 = gelu_consts(st_rstd[1], 1.f);
#pragma unroll
        for (int g = 0; g < 10; g++) {
          const float2 cs = *reinterpret_cast<const float2*>(s_cs + 8 * g + 2 * t);
          const float v0 = gelu_s(fmaf(st_mr[0], cs.x, ACC(0, g, 0)), g0), v1 = gelu_s(fmaf(st_mr[0], cs.y, ACC(0, g, 1)), g0);
          const float v2 = gelu_s(fmaf(st_mr[1], cs.x, ACC(0, g, 2)), g1), v3 = gelu_s(fmaf(st_mr[1], cs.y, ACC(0, g, 3)), g1);
          hv[0][g] = pack_bf16(v0, v1); hv[1][g] = pack_bf16(v2, v3);
        }
        fence_async_smem();
        bar_sync(1, 256);
        stage_tile(sb + OFF_STG, hv);
        fence_async_smem();
        signal(B_SIGH);
      }
      TSTAMP(4);
      uint32_t kf[5][4], qf[5][4];
#pragma unroll
      for (int s = 0; s < 5; s++) {
        kf[s][0] = pack_bf16(ACC(2, 2 * s, 0), ACC(2, 2 * s, 1)); kf[s][1] = pack_bf16(ACC(2, 2 * s, 2), ACC(2, 2 * s, 3));
        kf[s][2] = pack_bf16(ACC(2, 2 * s + 1, 0), ACC(2, 2 * s + 1, 1)); kf[s][3] = pack_bf16(ACC(2, 2 * s + 1, 2), ACC(2, 2 * s + 1, 3));
        qf[s][0] = pack_bf16(ACC(1, 2 * s, 0), ACC(1, 2 * s, 1)); qf[s][1] = pack_bf16(ACC(1, 2 * s, 2), ACC(1, 2 * s, 3));
        qf[s][2] = pack_bf16(ACC(1, 2 * s + 1, 0), ACC(1, 2 * s + 1, 1)); qf[s][3] = pack_bf16(ACC(1, 2 * s + 1, 2), ACC(1, 2 * s + 1, 3));
      }
      float pk[40], pq[40];
      wg_fence();
#pragma unroll
      for (int s = 0; s < 5; s++) {
        if (s == 0) mma_rs80_k_z(pk, kf[s], make_desc(sb16, OFF_MISC, 16, 256, 3));
        else mma_rs80_k(pk, kf[s], make_desc(sb16, OFF_MISC + s * 2560, 16, 256, 3));
      }
      wg_commit();
#pragma unroll
      for (int s = 0; s < 5; s++) {
        if (s == 0) mma_rs80_k_z(pq, qf[s], make_desc(sb16, OFF_MISC, 16, 256, 3));
        else mma_rs80_k(pq, qf[s], make_desc(sb16, OFF_MISC + s * 2560, 16, 256, 3));
      }
      wg_commit();
      {
        const int mat = lane >> 3;
        const int tok = warp * 16 + (mat & 1) * 8 + (lane & 7);
        const uint32_t ones = (t == 0) ? 0x00003f80u : 0u;
        __syncwarp();
#pragma unroll
        for (int p = 0; p < 2; p++) {
          const uint32_t rowa = sb + OFF_A + p * SLOT_A + tok * 128;
#pragma unroll
          for (int gg = 0; gg < 3; gg++) {
            const int g0 = 5 * p + 2 * gg;
            uint32_t r0 = pack_bf16(ACC(3, g0, 0), ACC(3, g0, 1)), r1 = pack_bf16(ACC(3, g0, 2), ACC(3, g0, 3));
            uint32_t r2 = ones, r3 = ones;
            if (gg < 2) { r2 = pack_bf16(ACC(3, g0 + 1, 0), ACC(3, g0 + 1, 1)); r3 = pack_bf16(ACC(3, g0 + 1, 2), ACC(3, g0 + 1, 3)); }
            stsm4(rowa + (((2 * gg + (mat >> 1)) ^ (tok & 7)) << 4), r0, r1, r2, r3);
          }
        }
      }
#undef ACC
      wg_wait<1>();
      fence_regs(pk);
#pragma unroll
      for (int G = 0; G < 10; G++) {
        P[0][G] = pack_bf16(pk[4 * G], pk[4 * G + 1]); P[1][G] = pack_bf16(pk[4 * G + 2], pk[4 * G + 3]);
      }
      wg_wait<0>();
      fence_regs(pq);
#pragma unroll
      for (int G = 0; G < 10; G++) {
        qp[0][G] = pack_bf16(pq[4 * G], pq[4 * G + 1]); qp[1][G] = pack_bf16(pq[4 * G + 2], pq[4 * G + 3]);
      }
    }

    uint32_t fr[10][4];
    int pass;
    pass = gridDim.y;
#pragma unroll 1
    do {
    feature_map(P, fr);
    if (pass != 0) {
    {
      const int mat = lane >> 3;
      const int tok = warp * 16 + (mat & 1) * 8 + (lane & 7);
      const uint32_t base = sb + OFF_B + tok * 32 + (((mat >> 1) ^ ((tok >> 2) & 1)) << 4);
#pragma unroll
      for (int G = 0; G < 10; G++) stsm4(base + G * 4096, fr[G][0], fr[G][1], fr[G][2], fr[G][3]);
      fence_async_smem();
      bar_sync(1, 256);
      float kv[40];
      const uint32_t va = sb16 + ((OFF_A + wg * SLOT_A) >> 4), vb = sb16 + ((OFF_B + wg * 20480) >> 4);
      wg_fence();
#pragma unroll
      for (int ks = 0; ks < 8; ks++) {
        if (ks == 0) mma_ss80_tt_z(kv, make_desc(va, 0, 16, 1024, 1), make_desc(vb, 0, 4096, 256, 3));
        else mma_ss80_tt(kv, make_desc(va, ks * 2048, 16, 1024, 1), make_desc(vb, ks * 512, 4096, 256, 3));
      }
      wg_commit();
      uint32_t xv[2][10];
      {
        mbar_wait(bars + 8 * B_XR, 0);
        const uint32_t xa = sb + OFF_B + (warp / 3) * SLOT_B + SPARE + (warp % 3) * 2560 + (lane >> 2) * 160 + t * 4;
#pragma unroll
        for (int g = 0; g < 10; g++) { xv[0][g] = lds32(xa + g * 16); xv[1][g] = lds32(xa + 1280 + g * 16); }
      }
      float acc[80];
      wg_wait<0>();
      release(emptyA); release(emptyA + 8); releaseB(emptyB); release(bars + 8 * B_PEER2);
      TSTAMP(5);
      mbar_wait(fullA + 8 * 2, 0);
      mbar_wait(fullB + 8 * 1, 1);
      TSTAMP(6);
      wg_fence();
#pragma unroll
      for (int kk = 0; kk < 4; kk++) {
        const uint64_t da = make_desc(sb16 + wg * 512, OFF_A + 2 * SLOT_A + kk * 32, 16, 1024, 1);
        const uint64_t db = make_desc(sb16, OFF_B + SLOT_B + kk * 1024, 4096, 512, 2);
        if (kk == 0) mma_ss160_z(acc, da, db); else mma_ss160(acc, da, db);
      }
      wg_commit();
      ra.next<NA>();
      wg_wait<1>();
      fence_regs(kv);
      TSTAMP(31);
      const uint32_t dst = sb + OFF_MISC + wg * (KV_PAIR * 4);
      const int m0 = (warp & 3) * 16 + (lane >> 2);
#pragma unroll
      for (int r = 0; r < 2; r++) {
        const int m = m0 + 8 * r;
        const bool hi = m >= 20;
        uint32_t v[10];
#pragma unroll
        for (int G = 0; G < 10; G++) v[G] = __float_as_uint(hi ? kv[4 * G + 2 * r + 1] : kv[4 * G + 2 * r]);
        const uint32_t p = dst + 4 * (m < 40 ? m * 48 + t * 12 : 1920 + t * 24 + 12);
        if (m <= 40) {
          sts128(p, make_uint4(v[0], v[1], v[2], v[3])); sts128(p + 16, make_uint4(v[4], v[5], v[6], v[7]));
          sts128(p + 32, make_uint4(v[8], v[9], 0u, 0u));
        }
      }
      if (m0 == 32) {
        const uint32_t p = dst + 4 * (1920 + t * 24);
        sts128(p, make_uint4(__float_as_uint(kv[2]), __float_as_uint(kv[6]), __float_as_uint(kv[10]), __float_as_uint(kv[14])));
        sts128(p + 16, make_uint4(__float_as_uint(kv[18]), __float_as_uint(kv[22]), __float_as_uint(kv[26]), __float_as_uint(kv[30])));
        sts128(p + 32, make_uint4(__float_as_uint(kv[34]), __float_as_uint(kv[38]), 0u, 0u));
      }
      signal(B_SIGKV);
      uint32_t pa = 2, pb = 1;
#pragma unroll 1
      for (int k = 1; k < 5; k++) {
        mbar_wait(fullA + 8 * ra.idx, ra.phase);
        if ((k & 1) == 0) mbar_wait(fullB + 8 * rb.idx, rb.phase);
        const uint32_t a0 = sb16 + ((OFF_A + ra.idx * SLOT_A + wg * 8192) >> 4);
        const uint32_t b0 = sb16 + ((OFF_B + rb.idx * SLOT_B + (k & 1) * 20480) >> 4);
        wg_fence();
#pragma unroll
        for (int kk = 0; kk < 4; kk++) {
          mma_ss160(acc, make_desc(a0, kk * 32, 16, 1024, 1), make_desc(b0, kk * 1024, 4096, 512, 2));
          if (kk == 0) {
            wg_commit();
            wg_wait<1>();
            release(emptyA + 8 * pa);
            if ((k & 1) == 0) releaseB(emptyB + 8 * pb);
          }
        }
        wg_commit();
        pa = ra.idx; pb = rb.idx;
        ra.next<NA>();
        if ((k & 1) || k == 4) rb.next<NB>();
      }
      mbar_wait(bars + 8 * B_PEER2, 0);
      wg_wait<0>();
      fence_regs(acc);
      release(emptyA + 8 * pa);
      TSTAMP(7);
      {
        uint32_t sn[20];
        if (rank) {
#pragma unroll
          for (int e = 0; e < 20; e++) sn[e] = pack_bf16(acc[2 * e], acc[2 * e + 1]);
#pragma unroll
          for (int e = 0; e < 40; e++) acc[e] = acc[40 + e];
        } else {
#pragma unroll
          for (int e = 0; e < 20; e++) sn[e] = pack_bf16(acc[40 + 2 * e], acc[41 + 2 * e]);
        }
        const uint32_t peer = map_peer(sb, rank ^ 1);
#pragma unroll
        for (int q = 0; q < 5; q++)
          st_async16(peer + OFF_B + 20480 + tid * 16 + q * 4096, sn[4 * q], sn[4 * q + 1], sn[4 * q + 2], sn[4 * q + 3],
                     peer + OFF_BAR + 8 * (B_DSR + 8 + wg));
#pragma unroll
        for (int g = 0; g < 10; g++) {
          acc[4 * g] += bf_lo(xv[0][g]); acc[4 * g + 1] += bf_hi(xv[0][g]);
          acc[4 * g + 2] += bf_lo(xv[1][g]); acc[4 * g + 3] += bf_hi(xv[1][g]);
        }
        bar_sync(1, 256);
        mbar_wait(bars + 8 * (B_DSR + 8 + wg), 0);
#pragma unroll
        for (int q = 0; q < 5; q++) {
          const uint4 v = lds128(sb + OFF_B + 20480 + tid * 16 + q * 4096);
          xv[0][2 * q] = pack_bf16(acc[8 * q] + bf_lo(v.x), acc[8 * q + 1] + bf_hi(v.x));
          xv[1][2 * q] = pack_bf16(acc[8 * q + 2] + bf_lo(v.y), acc[8 * q + 3] + bf_hi(v.y));
          xv[0][2 * q + 1] = pack_bf16(acc[8 * q + 4] + bf_lo(v.z), acc[8 * q + 5] + bf_hi(v.z));
          xv[1][2 * q + 1] = pack_bf16(acc[8 * q + 6] + bf_lo(v.w), acc[8 * q + 7] + bf_hi(v.w));
        }
        releaseB(emptyB + 8 * pb);
      }
      TSTAMP(16);
      stage_tile(sb + OFF_STG, xv);
      fence_async_smem();
      signal(B_SIGX1);
      TSTAMP(17);
#pragma unroll
      for (int r = 0; r < 2; r++) {
        float s = 0.f;
#pragma unroll
        for (int g = 0; g < 10; g++) {
          acc[4 * g + 2 * r] = bf_lo(xv[r][g]); acc[4 * g + 2 * r + 1] = bf_hi(xv[r][g]);
          s += acc[4 * g + 2 * r] + acc[4 * g + 2 * r + 1];
        }
        s += __shfl_xor_sync(0xffffffffu, s, 1); s += __shfl_xor_sync(0xffffffffu, s, 2);
        const float mu = s * (1.f / 80.f);
        float q = 0.f;
#pragma unroll
        for (int g = 0; g < 10; g++) {
          const float d0 = acc[4 * g + 2 * r] - mu, d1 = acc[4 * g + 2 * r + 1] - mu;
          q = fmaf(d0, d0, q); q = fmaf(d1, d1, q);
        }
        q += __shfl_xor_sync(0xffffffffu, q, 1); q += __shfl_xor_sync(0xffffffffu, q, 2);
        if (t == 0) g_st1[(128 * i + rloc + 8 * r) * 8 + j] = make_float2(mu, q);
      }
    }
    TSTAMP(8);
#pragma unroll
    for (int G = 0; G < 10; G++) { P[0][G] = qp[0][G]; P[1][G] = qp[1][G]; }
    }
    asm volatile("" : "+r"(pass));
    } while (pass-- != 0);

    uint32_t of[5][4];
    {
      mbar_wait(bars + 8 * B_KV, 0);
      uint4 kvr[2][3];
#pragma unroll
      for (int u = 0; u < 2; u++) {
        const int it = tid + 256 * u, p = it / 192, rem = it - 192 * p, n = rem >> 2, tq = rem & 3;
        const uint32_t sp = sb + OFF_MISC + 4 * (p * KV_PAIR + (n < 40 ? n * 48 + tq * 12 : 1920 + tq * 24 + (n & 1) * 12));
        if (it < 384) { kvr[u][0] = lds128(sp); kvr[u][1] = lds128(sp + 16); kvr[u][2] = lds128(sp + 32); }
      }
      bar_sync(1, 256);
#pragma unroll
      for (int u = 0; u < 2; u++) {
        const int it = tid + 256 * u, p = it / 192, rem = it - 192 * p, n = rem >> 2, tq = rem & 3;
        const int sh = (n < 40 ? (n >= 20) : (n & 1)) * 16;
        const uint32_t v[10] = {kvr[u][0].x, kvr[u][0].y, kvr[u][0].z, kvr[u][0].w, kvr[u][1].x, kvr[u][1].y, kvr[u][1].z, kvr[u][1].w, kvr[u][2].x, kvr[u][2].y};
        uint8_t* dst = sgen + OFF_MISC + p * 7680 + n * 32 + tq * 4;
        const int sw = ((n >> 2) & 1) << 4;
        if (it < 384) {
#pragma unroll
          for (int G = 0; G < 10; G++)
            *reinterpret_cast<uint32_t*>(dst + (G >> 1) * 1536 + (((G & 1) << 4) ^ sw)) = pack_bf16(__uint_as_float(v[G]), 0.f) << sh;
        }
      }
      fence_async_smem();
      bar_sync(1, 256);
      float o0[24], o1[24];
      wg_fence();
#pragma unroll
      for (int g = 0; g < 5; g++) {
        if (g == 0) mma_rs48_k_z(o0, fr[g], make_desc(sb16, OFF_MISC, 16, 256, 3));
        else mma_rs48_k(o0, fr[g], make_desc(sb16, OFF_MISC + g * 1536, 16, 256, 3));
      }
#pragma unroll
      for (int g = 0; g < 5; g++) {
        if (g == 0) mma_rs48_k_z(o1, fr[5], make_desc(sb16, OFF_MISC + 7680, 16, 256, 3));
        else mma_rs48_k(o1, fr[5 + g], make_desc(sb16, OFF_MISC + 7680 + g * 1536, 16, 256, 3));
      }
      wg_commit();
      wg_wait<0>();
      fence_regs(o0); fence_regs(o1);
      signal(B_MFREE);
#pragma unroll
      for (int r = 0; r < 2; r++) {
        const float a0 = __fdividef(st_g[r], o0[20 + 2 * r] + 1e-6f), a1 = __fdividef(st_g[r], o0[21 + 2 * r] + 1e-6f);
        const float b0 = __fdividef(st_g[r], o1[20 + 2 * r] + 1e-6f), b1 = __fdividef(st_g[r], o1[21 + 2 * r] + 1e-6f);
        const float am = t < 2 ? a0 : a1, bm = t < 2 ? b0 : b1;
#pragma unroll
        for (int g = 0; g < 5; g++) {
          const float sa = g < 2 ? a0 : (g == 2 ? am : a1), sb2 = g < 2 ? b0 : (g == 2 ? bm : b1);
          of[g >> 1][(g & 1) * 2 + r] = pack_bf16(o0[4 * g + 2 * r] * sa, o0[4 * g + 2 * r + 1] * sa);
          of[(5 + g) >> 1][((5 + g) & 1) * 2 + r] = pack_bf16(o1[4 * g + 2 * r] * sb2, o1[4 * g + 2 * r + 1] * sb2);
        }
      }
    }
    TSTAMP(9);

    uint32_t hf[12][4];
    float ac4[80];
    auto unit = [&](auto uc, uint32_t b0) {
      constexpr int u = decltype(uc)::value;
#pragma unroll
      for (int s = 0; s < (u ? 4 : 5); s++) {
        const uint64_t db = make_desc(b0, (u ? 5120 + 20480 * u : 0) + s * 1024, u ? 4096 : 5120, 512, 2);
        if (u == 0 && s == 0) mma_rs160_n_z(ac4, of[0], db);
        else if (u == 0) mma_rs160_n(ac4, of[s], db);
        else mma_rs160_n(ac4, hf[(4 * u + 8 + s) % 12], db);
      }
      wg_commit();
    };
    {
      float acc[96];
      uint32_t pa = 0, pb = 0;
#pragma unroll 1
      for (int k = 0; k < 10; k++) {
        mbar_wait(fullA + 8 * ra.idx, ra.phase);
        if (tid == 0) TRACE(52 + k);
        if ((k & 1) == 0) mbar_wait(fullB + 8 * rb.idx, rb.phase);
        if (tid == 0) TRACE(84 + k);
        if (k == 0) TSTAMP(10);
        const uint32_t a0 = sb16 + ((OFF_A + ra.idx * SLOT_A + wg * 8192) >> 4);
        const uint32_t b0 = sb16 + ((OFF_B + rb.idx * SLOT_B + (k & 1) * 24576) >> 4);
        wg_fence();
#pragma unroll
        for (int kk = 0; kk < 4; kk++) {
          if (kk == 0) mma_ss192_p(acc, make_desc(a0, 0, 16, 1024, 1), make_desc(b0, 0, 8192, 1024, 1), k);
          else mma_ss192(acc, make_desc(a0, kk * 32, 16, 1024, 1), make_desc(b0, kk * 2048, 8192, 1024, 1));
          if (kk == 0) {
            wg_commit();
            if (k > 0) {
              wg_wait<1>();
              release(emptyA + 8 * pa);
              if ((k & 1) == 0) releaseB(emptyB + 8 * pb);
            }
          }
        }
        wg_commit();
        pa = ra.idx; pb = rb.idx;
        ra.next<NA>();
        if (k & 1) rb.next<NB>();
      }
      float rs[2], mm[2];
      mbar_wait(bars + 8 * B_ST1, 0);
#pragma unroll
      for (int r = 0; r < 2; r++) {
        const uint4 su = lds128(sb + OFF_MISC + (rloc + 8 * r) * 64 + t * 16);
        const float m0 = __uint_as_float(su.x), m1 = __uint_as_float(su.z);
        float mu = m0 + m1;
        mu += __shfl_xor_sync(0xffffffffu, mu, 1); mu += __shfl_xor_sync(0xffffffffu, mu, 2);
        mu *= 0.125f;
        const float d0 = m0 - mu, d1 = m1 - mu;
        float q = __uint_as_float(su.y) + __uint_as_float(su.w) + 80.f * (d0 * d0 + d1 * d1);
        q += __shfl_xor_sync(0xffffffffu, q, 1); q += __shfl_xor_sync(0xffffffffu, q, 2);
        rs[r] = rsqrtf(q * (1.f / D_) + 1e-5f);
        mm[r] = -mu;
      }
      mbar_wait(bars + 8 * B_FULL4, 0);
      wg_fence();
      unit(IntC<0>{}, sb16);
      wg_wait<1>();
      fence_regs(acc);
      releaseB(emptyB + 8 * pb);
      release(bars + 8 * B_PEER);
      TSTAMP(11);
      const GeluC g0 = gelu_consts(rs[0], 1.f - st_g[0]), g1 = gelu_consts(rs[1], 1.f - st_g[1]);
#pragma unroll
      for (int g = 0; g < 24; g++) {
        const float2 cs = *reinterpret_cast<const float2*>(s_cs + 80 + 8 * g + 2 * t);
        const float v0 = gelu_s(fmaf(mm[0], cs.x, acc[4 * g]), g0), v1 = gelu_s(fmaf(mm[0], cs.y, acc[4 * g + 1]), g0);
        const float v2 = gelu_s(fmaf(mm[1], cs.x, acc[4 * g + 2]), g1), v3 = gelu_s(fmaf(mm[1], cs.y, acc[4 * g + 3]), g1);
        hf[g >> 1][(g & 1) * 2] = pack_bf16(v0, v1);
        hf[g >> 1][(g & 1) * 2 + 1] = pack_bf16(v2, v3);
        if (g == 7) { wg_fence(); unit(IntC<1>{}, sb16); }
        if (g == 15) { mbar_wait(bars + 8 * (B_FULL4 + 1), 0); wg_fence(); unit(IntC<2>{}, sb16); }
        if (g == 23) { wg_wait<1>(); signal(B_EMPTY4); wg_fence(); unit(IntC<3>{}, sb16); }
      }
    }
    TSTAMP(12);

    {
      float kp[40];
      uint32_t sn[20], kb[20];
      const uint32_t peer = map_peer(sb, rank ^ 1);
      const uint32_t tag = lds32(sb + OFF_BAR + 8 * NBAR);
      auto add8 = [&](int q, const uint4 v) {
        float* d = &kp[8 * q];
        d[0] += bf_lo(v.x); d[1] += bf_hi(v.x); d[2] += bf_lo(v.y); d[3] += bf_hi(v.y);
        d[4] += bf_lo(v.z); d[5] += bf_hi(v.z); d[6] += bf_lo(v.w); d[7] += bf_hi(v.w);
      };
      auto send = [&](int c) {
        const uint32_t dso = peer + OFF_DS + (c & 1) * 20480 + tid * 16, dsb = peer + OFF_BAR + 8 * (B_DSR + 2 * c + wg);
#pragma unroll
        for (int q = 0; q < 5; q++) st_async16(dso + q * 4096, sn[4 * q], sn[4 * q + 1], sn[4 * q + 2], sn[4 * q + 3], dsb);
      };
      mbar_wait(bars + 8 * B_PEER, 0);
      uint4* gdst = g_part + (size_t)i * 8 * 3840 + tid;
#pragma unroll 1
      for (int c = 0; c < 3; c++) {
        const uint32_t b0 = sb16 + ((c & 1) ? 0 : SET4 >> 4), bc = bars + 16 * c;
        mbar_wait(bc + 8 * (B_FULL4 + 2), 0);
        wg_wait<0>();
        fence_regs(ac4);
        if (rank) {
#pragma unroll
          for (int e = 0; e < 20; e++) { sn[e] = pack_bf16(ac4[2 * e], ac4[2 * e + 1]); kb[e] = pack_bf16(ac4[40 + 2 * e], ac4[41 + 2 * e]); }
        } else {
#pragma unroll
          for (int e = 0; e < 20; e++) { kb[e] = pack_bf16(ac4[2 * e], ac4[2 * e + 1]); sn[e] = pack_bf16(ac4[40 + 2 * e], ac4[41 + 2 * e]); }
        }
#pragma unroll
        for (int e = 0; e < 20; e++) asm volatile("" : "+r"(sn[e]), "+r"(kb[e]));
        if (c == 0 && wg == 1) bar_sync(2, 256);
        wg_fence();
        unit(IntC<0>{}, b0);
        if (lane == 0) mbar_arrive(bc + 8 * (B_EMPTY4 + 1));
        send(c);
        unit(IntC<1>{}, b0);
        if (c == 0 && wg == 0) bar_arrive(2, 256);
        {
          mbar_wait(bc + 8 * (B_DSR + wg), 0);
          uint4* dst = gdst + (((j + 2 * c + 2) & 7) * 3 + c) * 1280;
#pragma unroll
          for (int q = 0; q < 5; q++) {
            const uint4 v = lds128(sb + OFF_DS + (c & 1) * 20480 + tid * 16 + q * 4096);
            st_relaxed16(dst + q * 256, (add_bf2(v.x, kb[4 * q]) & ~1u) | tag, add_bf2(v.y, kb[4 * q + 1]),
                         add_bf2(v.z, kb[4 * q + 2]), add_bf2(v.w, kb[4 * q + 3]));
          }
        }
        mbar_wait(bc + 8 * (B_FULL4 + 3), 0);
        wg_fence();
        unit(IntC<2>{}, b0);
        wg_wait<1>();
        if (lane == 0) mbar_arrive(bc + 8 * (B_EMPTY4 + 2));
        unit(IntC<3>{}, b0);
      }
      const uint4* gp = gdst + j * 3840;
      uint4 pv4[15];
#pragma unroll
      for (int q = 10; q < 15; q++) pv4[q] = ld_relaxed16(gp + q * 256);
      mbar_wait(bars + 8 * B_XR, 1);
#pragma unroll
      for (int q = 0; q < 10; q++) pv4[q] = lds128(sb + OFF_G0 + tid * 16 + q * 4096);
      wg_wait<0>();
      fence_regs(ac4);
      if (rank) {
#pragma unroll
        for (int e = 0; e < 20; e++) sn[e] = pack_bf16(ac4[2 * e], ac4[2 * e + 1]);
#pragma unroll
        for (int e = 0; e < 40; e++) kp[e] = ac4[40 + e];
      } else {
#pragma unroll
        for (int e = 0; e < 20; e++) sn[e] = pack_bf16(ac4[40 + 2 * e], ac4[41 + 2 * e]);
#pragma unroll
        for (int e = 0; e < 40; e++) kp[e] = ac4[e];
      }
      send(3);
      TSTAMP(13);
      {
        const float w0 = 1.f - st_g[0], w1s = 1.f - st_g[1];
        const uint32_t xa = sb + OFF_OUT + rloc * 160 + t * 4;
#pragma unroll
        for (int g = 0; g < 10; g++) {
          const uint32_t x0 = lds32(xa + g * 16), x1 = lds32(xa + 1280 + g * 16);
          kp[4 * g] = fmaf(w0, bf_lo(x0), kp[4 * g]); kp[4 * g + 1] = fmaf(w0, bf_hi(x0), kp[4 * g + 1]);
          kp[4 * g + 2] = fmaf(w1s, bf_lo(x1), kp[4 * g + 2]); kp[4 * g + 3] = fmaf(w1s, bf_hi(x1), kp[4 * g + 3]);
        }
      }
#pragma unroll 1
      for (uint32_t n = 0; n < (WAIT_LIMIT >> 2); n++) {
        uint32_t m = 0u;
#pragma unroll
        for (int q = 0; q < 15; q++) {
          const uint32_t bad = (pv4[q].x ^ tag) & 1u;
          m |= bad;
          if (bad) pv4[q] = ld_relaxed16(gp + q * 256);
        }
        if (m == 0u) break;
      }
#pragma unroll
      for (int q = 0; q < 5; q++) {
        const uint4 a = pv4[q], b = pv4[5 + q];
        add8(q, make_uint4(add_bf2(a.x, b.x), add_bf2(a.y, b.y), add_bf2(a.z, b.z), add_bf2(a.w, b.w)));
      }
      mbar_wait(bars + 8 * (B_DSR + 6 + wg), 0);
      TSTAMP(14);
#pragma unroll
      for (int q = 0; q < 5; q++) {
        const uint4 c = pv4[10 + q], d = lds128(sb + OFF_DS + 20480 + tid * 16 + q * 4096);
        add8(q, make_uint4(add_bf2(c.x, d.x), add_bf2(c.y, d.y), add_bf2(c.z, d.z), add_bf2(c.w, d.w)));
      }
      __syncwarp();
      uint32_t ov[2][10];
#pragma unroll
      for (int g = 0; g < 10; g++) { ov[0][g] = pack_bf16(kp[4 * g], kp[4 * g + 1]); ov[1][g] = pack_bf16(kp[4 * g + 2], kp[4 * g + 3]); }
      stage_tile(sb + OFF_OUT, ov);
      __syncwarp();
      __nv_bfloat16* dst = out + (size_t)(128 * i + 16 * warp) * D_ + 80 * j;
#pragma unroll
      for (int q = 0; q < 5; q++) {
        const int id = q * 32 + lane, r = id / 10;
        *reinterpret_cast<uint4*>(dst + r * (D_ - 80) + id * 8) = lds128(sb + OFF_OUT + warp * 2560 + id * 16);
      }
    }
    TSTAMP(15);
    if (tid == 0) asm volatile("red.relaxed.gpu.global.add.u32 [%0], 1;" ::"l"(g_flags + FL_DONE * 32) : "memory");
  }
}

namespace {
typedef CUresult (*EncodeFn)(CUtensorMap*, CUtensorMapDataType, cuuint32_t, void*, const cuuint64_t*, const cuuint64_t*,
                             const cuuint32_t*, const cuuint32_t*, CUtensorMapInterleave, CUtensorMapSwizzle,
                             CUtensorMapL2promotion, CUtensorMapFloatOOBfill);

void encode(EncodeFn fn, CUtensorMap* m, const void* ptr, int rank, const cuuint64_t* dims, const cuuint64_t* strides,
            const cuuint32_t* box, CUtensorMapSwizzle swz) {
  cuuint32_t es[5] = {1, 1, 1, 1, 1};
  fn(m, CU_TENSOR_MAP_DATA_TYPE_BFLOAT16, rank, const_cast<void*>(ptr), dims, strides, box, es, CU_TENSOR_MAP_INTERLEAVE_NONE,
     swz, CU_TENSOR_MAP_L2_PROMOTION_L2_128B, CU_TENSOR_MAP_FLOAT_OOB_FILL_NONE);
}
}

extern "C" void kernel_launch(void* const* d_in, const int* in_sizes, int n_in, void* d_out, int out_size) {
  (void)in_sizes; (void)n_in; (void)out_size;
  const __nv_bfloat16* x = (const __nv_bfloat16*)d_in[0];
  const __nv_bfloat16* wqkv = (const __nv_bfloat16*)d_in[1];
  const __nv_bfloat16* wphi = (const __nv_bfloat16*)d_in[2];
  const __nv_bfloat16* wo = (const __nv_bfloat16*)d_in[3];
  const __nv_bfloat16* w1 = (const __nv_bfloat16*)d_in[5];
  const __nv_bfloat16* w2 = (const __nv_bfloat16*)d_in[6];
  const __nv_bfloat16* w3 = (const __nv_bfloat16*)d_in[7];
  const __nv_bfloat16* w4 = (const __nv_bfloat16*)d_in[8];
  const __nv_bfloat16* gate_w = (const __nv_bfloat16*)d_in[9];

  static EncodeFn enc = nullptr;
  static void *pHs = nullptr, *pX1 = nullptr;
  if (!enc) {
    cudaDriverEntryPointQueryResult qr;
    cudaGetDriverEntryPoint("cuTensorMapEncodeTiled", (void**)&enc, cudaEnableDefault, &qr);
    cudaGetSymbolAddress(&pHs, g_Hs);
    cudaGetSymbolAddress(&pX1, g_X1);
    cudaFuncSetAttribute(fused_kernel, cudaFuncAttributeMaxDynamicSharedMemorySize, SMEM_BYTES);
  }
  Maps m;
  {
    cuuint64_t dims[2] = {D_, S_}, str[1] = {D_ * 2};
    cuuint32_t box[2] = {64, 128}, boxh[2] = {64, 64};
    encode(enc, &m.x, x, 2, dims, str, boxh, CU_TENSOR_MAP_SWIZZLE_128B);
    encode(enc, &m.hs, (const char*)pHs + 2 * D_ * 2, 2, dims, str, box, CU_TENSOR_MAP_SWIZZLE_128B);
    encode(enc, &m.x1, pX1, 2, dims, str, boxh, CU_TENSOR_MAP_SWIZZLE_128B);
    cuuint32_t boxr[2] = {80, 16}, boxs[2] = {80, 128};
    cuuint64_t dimsp[2] = {D_, S_ + 4};
    encode(enc, &m.st_h, pHs, 2, dimsp, str, boxs, CU_TENSOR_MAP_SWIZZLE_NONE);
    encode(enc, &m.st_x1, pX1, 2, dims, str, boxs, CU_TENSOR_MAP_SWIZZLE_NONE);
    encode(enc, &m.xr, x, 2, dims, str, boxr, CU_TENSOR_MAP_SWIZZLE_NONE);
  }
  {
    cuuint64_t dims[3] = {80, D_, 8}, str[2] = {D_ * 2, 160};
    cuuint32_t boxm[3] = {64, 64, 1}, boxr[3] = {16, 64, 1};
    encode(enc, &m.w1m, w1, 3, dims, str, boxm, CU_TENSOR_MAP_SWIZZLE_128B);
    encode(enc, &m.w1r, w1, 3, dims, str, boxr, CU_TENSOR_MAP_SWIZZLE_32B);
  }
  {
    cuuint64_t dims[4] = {80, D_, 3, 8}, str[3] = {3 * D_ * 2, D_ * 2, 160};
    cuuint32_t boxm[4] = {64, 64, 3, 1}, boxr[4] = {16, 64, 3, 1};
    encode(enc, &m.qm, wqkv, 4, dims, str, boxm, CU_TENSOR_MAP_SWIZZLE_128B);
    encode(enc, &m.qr, wqkv, 4, dims, str, boxr, CU_TENSOR_MAP_SWIZZLE_32B);
  }
  {
    cuuint64_t dims[3] = {32, D_, 20}, dims4[3] = {32, F_, 20}, str[2] = {D_ * 2, 64};
    cuuint32_t box4[3] = {32, 64, 5}, boxo[3] = {32, 80, 5};
    encode(enc, &m.w4, w4, 3, dims4, str, box4, CU_TENSOR_MAP_SWIZZLE_64B);
    encode(enc, &m.wo, wo, 3, dims, str, boxo, CU_TENSOR_MAP_SWIZZLE_64B);
    encode(enc, &m.w2, w2, 3, dims, str, box4, CU_TENSOR_MAP_SWIZZLE_64B);
  }
  {
    cuuint64_t dims[3] = {64, D_, 24}, str[2] = {F_ * 2, 128};
    cuuint32_t box[3] = {64, 64, 3};
    encode(enc, &m.w3, w3, 3, dims, str, box, CU_TENSOR_MAP_SWIZZLE_128B);
  }
  fused_kernel<<<NCTA, 384, SMEM_BYTES, cudaStreamPerThread>>>(m, x, wqkv, wphi, w1, w2, w3, w4, wo, gate_w, (__nv_bfloat16*)d_out);
}
```

```cpp
#include <cuda_runtime.h>
#include <cuda_bf16.h>
#include <cuda.h>
#include <stdint.h>

namespace {

constexpr int S_ = 2048, D_ = 640, F_ = 1536;
constexpr int NCTA = 128;
constexpr int KV_PAIR = 40 * 48 + 96;
constexpr int KV_J = 2 * KV_PAIR;

constexpr int SLOT_B = 49152, NB = 3;
constexpr int SLOT_A = 16384, NA = 4;
constexpr int OFF_B = 0;
constexpr int OFF_A = OFF_B + NB * SLOT_B;
constexpr int OFF_STG = OFF_A + 2 * SLOT_A;
constexpr int OFF_MISC = OFF_A + NA * SLOT_A;
constexpr int OFF_XST = OFF_MISC + 13312;
constexpr int OFF_CS = OFF_MISC + 16384;
constexpr int OFF_BAR = OFF_CS + 1088;
constexpr int SMEM_BYTES = OFF_BAR + 512 + 512 + 128;
constexpr int B_FULLA = 0, B_FULLB = 4, B_CS = 7, B_XR = 8, B_KV = 9, B_ST1 = 10, B_HST = 11, B_FULL4 = 12  , B_RDY = 20  ,
              B_DSR = 23  , B_EMPTYB = 33  , B_SIGP = 36, B_SIGH = 37, B_SIGKV = 38, B_SIGX1 = 39, B_MFREE = 40,
              B_EMPTY4 = 41  , B_EMPTYA = 49  , B_PEER = 53, B_PEER2 = 54, B_X1P = 55  , NBAR = 56;
constexpr int SPARE = 40960;
constexpr int SET4 = 87040, OFF_DS = 2 * SET4, OFF_OUT = 20480;

constexpr int FL_DONE = 0, FL_H = 1  , FL_X1 = FL_H + 32, FL_KV = FL_X1 + 16, FL_CS = FL_KV + 8, FL_CS3 = FL_CS + 8, FL_ST = FL_CS3 + 8;
constexpr int FL_S1 = FL_ST + 16, FL_COUNT = FL_S1 + 16;
constexpr int ACC_FLOATS = 8 * KV_J + D_ + F_;

struct Maps {
  CUtensorMap x, w1m, w1r, qm, qr, hs, w2, x1, w3, w4, wo, xr, st_h, st_x1;
};

}

__device__ __align__(1024) __nv_bfloat16 g_Hs[(S_ + 4) * D_];
__device__ __align__(1024) __nv_bfloat16 g_X1[S_ * D_];
__device__ __align__(128) float g_acc[2][ACC_FLOATS];
__device__ __align__(128) float4 g_xstat[S_];
__device__ __align__(128) float2 g_st1[S_ * 8];
__device__ __align__(128) uint4 g_part[16 * 8 * 3 * 1280];
__device__ __align__(128) unsigned g_flags[FL_COUNT * 32];
#define TSTAMP(n) do {} while (0)
#define TSTAMPX(n) do {} while (0)
#define TRACE(n) do {} while (0)
#define TRS(n) do {} while (0)

namespace {

__device__ __forceinline__ long long gtime() { long long t; asm volatile("mov.u64 %0, %%globaltimer;" : "=l"(t)); return t; }
__device__ __forceinline__ uint32_t smem_u32(const void* p) { return (uint32_t)__cvta_generic_to_shared(p); }
__device__ __forceinline__ void mbar_init(uint32_t bar, int cnt) {
  asm volatile("mbarrier.init.shared::cta.b64 [%0], %1;" ::"r"(bar), "r"(cnt) : "memory");
}
__device__ __forceinline__ void mbar_expect_tx(uint32_t bar, int bytes) {
  asm volatile("mbarrier.arrive.expect_tx.shared::cta.b64 _, [%0], %1;" ::"r"(bar), "r"(bytes) : "memory");
}
__device__ __forceinline__ void mbar_arrive_cta(uint32_t bar, uint32_t cta) {
  asm volatile("{\n.reg .b32 ra;\nmapa.shared::cluster.u32 ra, %0, %1;\nmbarrier.arrive.shared::cluster.b64 _, [ra];\n}"
               ::"r"(bar), "r"(cta) : "memory");
}
__device__ __forceinline__ uint32_t mbar_try(uint32_t bar, uint32_t parity) {
  uint32_t ok;
  asm volatile("{\n.reg .pred p;\nmbarrier.try_wait.parity.shared::cta.b64 p, [%1], %2;\nselp.u32 %0, 1, 0, p;\n}"
               : "=r"(ok) : "r"(bar), "r"(parity) : "memory");
  return ok;
}
constexpr uint32_t WAIT_LIMIT = 1u << 18;
__device__ __forceinline__ void mbar_wait(uint32_t bar, uint32_t parity) {
  uint32_t n = 0;
  while (!mbar_try(bar, parity) && ++n < WAIT_LIMIT) {}
}
__device__ __forceinline__ unsigned ld_acquire(const unsigned* p) {
  unsigned v;
  asm volatile("ld.acquire.gpu.global.u32 %0, [%1];" : "=r"(v) : "l"(p) : "memory");
  return v;
}
__device__ __forceinline__ void flag_wait(int idx, unsigned target) {
  const unsigned* p = g_flags + idx * 32;
  uint32_t n = 0;
  while ((int)(ld_acquire(p) - target) < 0 && ++n < (WAIT_LIMIT >> 2)) {}
}
__device__ __forceinline__ void flag_add(int idx) {
  asm volatile("red.release.gpu.global.add.u32 [%0], 1;" ::"l"(g_flags + idx * 32) : "memory");
}
__device__ __forceinline__ void flag_add_relaxed(int idx) {
  asm volatile("red.relaxed.gpu.global.add.u32 [%0], 1;" ::"l"(g_flags + idx * 32) : "memory");
}
__device__ __forceinline__ uint32_t mbar_test(uint32_t bar, uint32_t parity) {
  uint32_t ok;
  asm volatile("{\n.reg .pred p;\nmbarrier.test_wait.parity.shared::cta.b64 p, [%1], %2;\nselp.u32 %0, 1, 0, p;\n}"
               : "=r"(ok) : "r"(bar), "r"(parity) : "memory");
  return ok;
}
__device__ __forceinline__ uint32_t lds32(uint32_t a) {
  uint32_t v;
  asm volatile("ld.shared.u32 %0, [%1];" : "=r"(v) : "r"(a) : "memory");
  return v;
}
__device__ __forceinline__ void mbar_arrive(uint32_t bar) {
  asm volatile("mbarrier.arrive.shared::cta.b64 _, [%0];" ::"r"(bar) : "memory");
}
__device__ __forceinline__ void fence_async_glb() { asm volatile("fence.proxy.async.global;" ::: "memory"); }
__device__ __forceinline__ void fence_async_smem() { asm volatile("fence.proxy.async.shared::cta;" ::: "memory"); }
__device__ __forceinline__ void bar_sync(int id, int n) { asm volatile("bar.sync %0, %1;" ::"r"(id), "r"(n) : "memory"); }

__device__ __forceinline__ void tma2d(uint32_t dst, const CUtensorMap* m, uint32_t bar, int c0, int c1) {
  asm volatile("cp.async.bulk.tensor.2d.shared::cluster.global.mbarrier::complete_tx::bytes [%0], [%1, {%3, %4}], [%2];"
               ::"r"(dst), "l"(m), "r"(bar), "r"(c0), "r"(c1) : "memory");
}
__device__ __forceinline__ void tma2d_mc(uint32_t dst, const CUtensorMap* m, uint32_t bar, int c0, int c1) {
  asm volatile("cp.async.bulk.tensor.2d.shared::cluster.global.mbarrier::complete_tx::bytes.multicast::cluster"
               " [%0], [%1, {%3, %4}], [%2], %5;"
               ::"r"(dst), "l"(m), "r"(bar), "r"(c0), "r"(c1), "h"((uint16_t)3) : "memory");
}
__device__ __forceinline__ void tma3d(uint32_t dst, const CUtensorMap* m, uint32_t bar, int c0, int c1, int c2) {
  asm volatile("cp.async.bulk.tensor.3d.shared::cluster.global.mbarrier::complete_tx::bytes [%0], [%1, {%3, %4, %5}], [%2];"
               ::"r"(dst), "l"(m), "r"(bar), "r"(c0), "r"(c1), "r"(c2) : "memory");
}
__device__ __forceinline__ void tma4d(uint32_t dst, const CUtensorMap* m, uint32_t bar, int c0, int c1, int c2, int c3) {
  asm volatile("cp.async.bulk.tensor.4d.shared::cluster.global.mbarrier::complete_tx::bytes [%0], [%1, {%3, %4, %5, %6}], [%2];"
               ::"r"(dst), "l"(m), "r"(bar), "r"(c0), "r"(c1), "r"(c2), "r"(c3) : "memory");
}
__device__ __forceinline__ void tma2d_store(const CUtensorMap* m, uint32_t src, int c0, int c1) {
  asm volatile("cp.async.bulk.tensor.2d.global.shared::cta.bulk_group [%0, {%2, %3}], [%1];"
               ::"l"(m), "r"(src), "r"(c0), "r"(c1) : "memory");
}
__device__ __forceinline__ void bulk_store(void* dst, uint32_t src, uint32_t bytes) {
  asm volatile("cp.async.bulk.global.shared::cta.bulk_group [%0], [%1], %2;" ::"l"(dst), "r"(src), "r"(bytes) : "memory");
}
__device__ __forceinline__ void bulk_load(uint32_t dst, const void* src, uint32_t bytes, uint32_t bar) {
  asm volatile("cp.async.bulk.shared::cluster.global.mbarrier::complete_tx::bytes [%0], [%1], %2, [%3];"
               ::"r"(dst), "l"(src), "r"(bytes), "r"(bar) : "memory");
}
__device__ __forceinline__ void bulk_commit() { asm volatile("cp.async.bulk.commit_group;" ::: "memory"); }
template <int N> __device__ __forceinline__ void bulk_wait() { asm volatile("cp.async.bulk.wait_group %0;" ::"n"(N) : "memory"); }
__device__ __forceinline__ void bulk_wait_read() { asm volatile("cp.async.bulk.wait_group.read 0;" ::: "memory"); }
__device__ __forceinline__ void bar_arrive(int id, int n) { asm volatile("bar.arrive %0, %1;" ::"r"(id), "r"(n) : "memory"); }
__device__ __forceinline__ uint4 lds128(uint32_t a) {
  uint4 v;
  asm volatile("ld.shared.v4.u32 {%0, %1, %2, %3}, [%4];" : "=r"(v.x), "=r"(v.y), "=r"(v.z), "=r"(v.w) : "r"(a) : "memory");
  return v;
}
__device__ __forceinline__ void sts128(uint32_t a, uint4 v) {
  asm volatile("st.shared.v4.u32 [%0], {%1, %2, %3, %4};" ::"r"(a), "r"(v.x), "r"(v.y), "r"(v.z), "r"(v.w) : "memory");
}
__device__ __forceinline__ uint4 ld_relaxed16(const uint4* p) {
  uint4 v;
  asm volatile("ld.relaxed.gpu.global.v4.u32 {%0, %1, %2, %3}, [%4];" : "=r"(v.x), "=r"(v.y), "=r"(v.z), "=r"(v.w) : "l"(p) : "memory");
  return v;
}
__device__ __forceinline__ void st_relaxed16(uint4* p, uint32_t a, uint32_t b, uint32_t c, uint32_t d) {
  asm volatile("st.relaxed.gpu.global.v4.u32 [%0], {%1, %2, %3, %4};" ::"l"(p), "r"(a), "r"(b), "r"(c), "r"(d) : "memory");
}
__device__ __forceinline__ uint32_t map_peer(uint32_t addr, uint32_t cta) {
  uint32_t r;
  asm("mapa.shared::cluster.u32 %0, %1, %2;" : "=r"(r) : "r"(addr), "r"(cta));
  return r;
}
__device__ __forceinline__ void st_async16(uint32_t addr, uint32_t a, uint32_t b, uint32_t c, uint32_t d, uint32_t bar) {
  asm volatile("st.async.weak.shared::cluster.mbarrier::complete_tx::bytes.v4.b32 [%0], {%1, %2, %3, %4}, [%5];"
               ::"r"(addr), "r"(a), "r"(b), "r"(c), "r"(d), "r"(bar) : "memory");
}
__device__ __forceinline__ void l2_prefetch(const void* p, uint32_t bytes) {
  asm volatile("cp.async.bulk.prefetch.L2.global [%0], %1;" ::"l"(p), "r"(bytes) : "memory");
}
__device__ __forceinline__ void prefetch_tmap(const CUtensorMap* m) {
  asm volatile("prefetch.tensormap [%0];" ::"l"(m) : "memory");
}
__device__ __forceinline__ uint64_t make_desc(uint32_t a16, uint32_t off, uint32_t lbo, uint32_t sbo, uint32_t swz) {
  const uint32_t lo = a16 + ((off >> 4) + ((lbo >> 4) << 16)), hi = (sbo >> 4) | (swz << 30);
  uint64_t d;
  asm("mov.b64 %0, {%1, %2};" : "=l"(d) : "r"(lo), "r"(hi));
  return d;
}
__device__ __forceinline__ void wg_fence() { asm volatile("wgmma.fence.sync.aligned;" ::: "memory"); }
__device__ __forceinline__ void wg_commit() { asm volatile("wgmma.commit_group.sync.aligned;" ::: "memory"); }
template <int N> __device__ __forceinline__ void wg_wait() { asm volatile("wgmma.wait_group.sync.aligned %0;" ::"n"(N) : "memory"); }
template <int N> __device__ __forceinline__ void fence_regs(float (&d)[N]) {
#pragma unroll
  for (int i = 0; i < N; i++) asm volatile("" : "+f"(d[i])::"memory");
}
template <int N> __device__ __forceinline__ void zero_regs(float (&d)[N]) {
#pragma unroll
  for (int i = 0; i < N; i++) d[i] = 0.f;
}
__device__ __forceinline__ uint32_t pack_bf16(float lo, float hi) {
  uint32_t r;
  asm("cvt.rn.bf16x2.f32 %0, %1, %2;" : "=r"(r) : "f"(hi), "f"(lo));
  return r;
}
__device__ __forceinline__ float bf_lo(uint32_t v) { return __uint_as_float(v << 16); }
__device__ __forceinline__ float bf_hi(uint32_t v) { return __uint_as_float(v & 0xffff0000u); }
__device__ __forceinline__ uint32_t max_bf2(uint32_t a, uint32_t b) {
  uint32_t r; asm("max.bf16x2 %0, %1, %2;" : "=r"(r) : "r"(a), "r"(b)); return r;
}
__device__ __forceinline__ uint32_t min_bf2(uint32_t a, uint32_t b) {
  uint32_t r; asm("min.bf16x2 %0, %1, %2;" : "=r"(r) : "r"(a), "r"(b)); return r;
}
__device__ __forceinline__ uint32_t add_bf2(uint32_t a, uint32_t b) {
  uint32_t r; asm("add.rn.bf16x2 %0, %1, %2;" : "=r"(r) : "r"(a), "r"(b)); return r;
}
__device__ __forceinline__ float ex2(float x) { float r; asm("ex2.approx.ftz.f32 %0, %1;" : "=f"(r) : "f"(x)); return r; }
__device__ __forceinline__ float rcp(float x) { float r; asm("rcp.approx.ftz.f32 %0, %1;" : "=f"(r) : "f"(x)); return r; }
__device__ __forceinline__ float tanh_ap(float x) { float r; asm("tanh.approx.f32 %0, %1;" : "=f"(r) : "f"(x)); return r; }
struct GeluC { float c0, c1, ch; };
__device__ __forceinline__ GeluC gelu_consts(float rstd, float scale) {
  return GeluC{0.7978845608f * rstd, 0.0356774081f * rstd * rstd * rstd, 0.5f * scale * rstd};
}
__device__ __forceinline__ float gelu_s(float y, const GeluC& c) {
  const float u = y * fmaf(y * y, c.c1, c.c0);
  const float hx = y * c.ch;
  return fmaf(hx, tanh_ap(u), hx);
}
__device__ __forceinline__ void stsm4(uint32_t addr, uint32_t r0, uint32_t r1, uint32_t r2, uint32_t r3) {
  asm volatile("stmatrix.sync.aligned.m8n8.x4.shared.b16 [%0], {%1, %2, %3, %4};"
               ::"r"(addr), "r"(r0), "r"(r1), "r"(r2), "r"(r3) : "memory");
}
__device__ __forceinline__ void red_add4(float* p, float a, float b, float c, float d) {
  asm volatile("red.global.add.v4.f32 [%0], {%1, %2, %3, %4};" ::"l"(p), "f"(a), "f"(b), "f"(c), "f"(d) : "memory");
}

__device__ __forceinline__ void mma_ss256(float (&d)[128], uint64_t descA, uint64_t descB) {
  asm volatile("wgmma.mma_async.sync.aligned.m64n256k16.f32.bf16.bf16 {"
      "%0, %1, %2, %3, %4, %5, %6, %7, %8, %9, %10, %11, %12, %13, %14, %15, "
      "%16, %17, %18, %19, %20, %21, %22, %23, %24, %25, %26, %27, %28, %29, %30, %31, "
      "%32, %33, %34, %35, %36, %37, %38, %39, %40, %41, %42, %43, %44, %45, %46, %47, "
      "%48, %49, %50, %51, %52, %53, %54, %55, %56, %57, %58, %59, %60, %61, %62, %63, "
      "%64, %65, %66, %67, %68, %69, %70, %71, %72, %73, %74, %75, %76, %77, %78, %79, "
      "%80, %81, %82, %83, %84, %85, %86, %87, %88, %89, %90, %91, %92, %93, %94, %95, "
      "%96, %97, %98, %99, %100, %101, %102, %103, %104, %105, %106, %107, %108, %109, %110, %111, "
      "%112, %113, %114, %115, %116, %117, %118, %119, %120, %121, %122, %123, %124, %125, %126, %127"
      "}, %128, %129, 1, 1, 1, 0, 1;\n"
      : "+f"(d[0]), "+f"(d[1]), "+f"(d[2]), "+f"(d[3]), "+f"(d[4]), "+f"(d[5]), "+f"(d[6]), "+f"(d[7]),
        "+f"(d[8]), "+f"(d[9]), "+f"(d[10]), "+f"(d[11]), "+f"(d[12]), "+f"(d[13]), "+f"(d[14]), "+f"(d[15]),
        "+f"(d[16]), "+f"(d[17]), "+f"(d[18]), "+f"(d[19]), "+f"(d[20]), "+f"(d[21]), "+f"(d[22]), "+f"(d[23]),
        "+f"(d[24]), "+f"(d[25]), "+f"(d[26]), "+f"(d[27]), "+f"(d[28]), "+f"(d[29]), "+f"(d[30]), "+f"(d[31]),
        "+f"(d[32]), "+f"(d[33]), "+f"(d[34]), "+f"(d[35]), "+f"(d[36]), "+f"(d[37]), "+f"(d[38]), "+f"(d[39]),
        "+f"(d[40]), "+f"(d[41]), "+f"(d[42]), "+f"(d[43]), "+f"(d[44]), "+f"(d[45]), "+f"(d[46]), "+f"(d[47]),
        "+f"(d[48]), "+f"(d[49]), "+f"(d[50]), "+f"(d[51]), "+f"(d[52]), "+f"(d[53]), "+f"(d[54]), "+f"(d[55]),
        "+f"(d[56]), "+f"(d[57]), "+f"(d[58]), "+f"(d[59]), "+f"(d[60]), "+f"(d[61]), "+f"(d[62]), "+f"(d[63]),
        "+f"(d[64]), "+f"(d[65]), "+f"(d[66]), "+f"(d[67]), "+f"(d[68]), "+f"(d[69]), "+f"(d[70]), "+f"(d[71]),
        "+f"(d[72]), "+f"(d[73]), "+f"(d[74]), "+f"(d[75]), "+f"(d[76]), "+f"(d[77]), "+f"(d[78]), "+f"(d[79]),
        "+f"(d[80]), "+f"(d[81]), "+f"(d[82]), "+f"(d[83]), "+f"(d[84]), "+f"(d[85]), "+f"(d[86]), "+f"(d[87]),
        "+f"(d[88]), "+f"(d[89]), "+f"(d[90]), "+f"(d[91]), "+f"(d[92]), "+f"(d[93]), "+f"(d[94]), "+f"(d[95]),
        "+f"(d[96]), "+f"(d[97]), "+f"(d[98]), "+f"(d[99]), "+f"(d[100]), "+f"(d[101]), "+f"(d[102]), "+f"(d[103]),
        "+f"(d[104]), "+f"(d[105]), "+f"(d[106]), "+f"(d[107]), "+f"(d[108]), "+f"(d[109]), "+f"(d[110]), "+f"(d[111]),
        "+f"(d[112]), "+f"(d[113]), "+f"(d[114]), "+f"(d[115]), "+f"(d[116]), "+f"(d[117]), "+f"(d[118]), "+f"(d[119]),
        "+f"(d[120]), "+f"(d[121]), "+f"(d[122]), "+f"(d[123]), "+f"(d[124]), "+f"(d[125]), "+f"(d[126]), "+f"(d[127])
      : "l"(descA), "l"(descB));
}
__device__ __forceinline__ void mma_ss256_p(float (&d)[128], uint64_t descA, uint64_t descB, int acc) {
  asm volatile("{\n.reg .pred p;\nsetp.ne.b32 p, %130, 0;\n"
      "wgmma.mma_async.sync.aligned.m64n256k16.f32.bf16.bf16 {"
      "%0, %1, %2, %3, %4, %5, %6, %7, %8, %9, %10, %11, %12, %13, %14, %15, "
      "%16, %17, %18, %19, %20, %21, %22, %23, %24, %25, %26, %27, %28, %29, %30, %31, "
      "%32, %33, %34, %35, %36, %37, %38, %39, %40, %41, %42, %43, %44, %45, %46, %47, "
      "%48, %49, %50, %51, %52, %53, %54, %55, %56, %57, %58, %59, %60, %61, %62, %63, "
      "%64, %65, %66, %67, %68, %69, %70, %71, %72, %73, %74, %75, %76, %77, %78, %79, "
      "%80, %81, %82, %83, %84, %85, %86, %87, %88, %89, %90, %91, %92, %93, %94, %95, "
      "%96, %97, %98, %99, %100, %101, %102, %103, %104, %105, %106, %107, %108, %109, %110, %111, "
      "%112, %113, %114, %115, %116, %117, %118, %119, %120, %121, %122, %123, %124, %125, %126, %127"
      "}, %128, %129, p, 1, 1, 0, 1;\n}\n"
      : "+f"(d[0]), "+f"(d[1]), "+f"(d[2]), "+f"(d[3]), "+f"(d[4]), "+f"(d[5]), "+f"(d[6]), "+f"(d[7]),
        "+f"(d[8]), "+f"(d[9]), "+f"(d[10]), "+f"(d[11]), "+f"(d[12]), "+f"(d[13]), "+f"(d[14]), "+f"(d[15]),
        "+f"(d[16]), "+f"(d[17]), "+f"(d[18]), "+f"(d[19]), "+f"(d[20]), "+f"(d[21]), "+f"(d[22]), "+f"(d[23]),
        "+f"(d[24]), "+f"(d[25]), "+f"(d[26]), "+f"(d[27]), "+f"(d[28]), "+f"(d[29]), "+f"(d[30]), "+f"(d[31]),
        "+f"(d[32]), "+f"(d[33]), "+f"(d[34]), "+f"(d[35]), "+f"(d[36]), "+f"(d[37]), "+f"(d[38]), "+f"(d[39]),
        "+f"(d[40]), "+f"(d[41]), "+f"(d[42]), "+f"(d[43]), "+f"(d[44]), "+f"(d[45]), "+f"(d[46]), "+f"(d[47]),
        "+f"(d[48]), "+f"(d[49]), "+f"(d[50]), "+f"(d[51]), "+f"(d[52]), "+f"(d[53]), "+f"(d[54]), "+f"(d[55]),
        "+f"(d[56]), "+f"(d[57]), "+f"(d[58]), "+f"(d[59]), "+f"(d[60]), "+f"(d[61]), "+f"(d[62]), "+f"(d[63]),
        "+f"(d[64]), "+f"(d[65]), "+f"(d[66]), "+f"(d[67]), "+f"(d[68]), "+f"(d[69]), "+f"(d[70]), "+f"(d[71]),
        "+f"(d[72]), "+f"(d[73]), "+f"(d[74]), "+f"(d[75]), "+f"(d[76]), "+f"(d[77]), "+f"(d[78]), "+f"(d[79]),
        "+f"(d[80]), "+f"(d[81]), "+f"(d[82]), "+f"(d[83]), "+f"(d[84]), "+f"(d[85]), "+f"(d[86]), "+f"(d[87]),
        "+f"(d[88]), "+f"(d[89]), "+f"(d[90]), "+f"(d[91]), "+f"(d[92]), "+f"(d[93]), "+f"(d[94]), "+f"(d[95]),
        "+f"(d[96]), "+f"(d[97]), "+f"(d[98]), "+f"(d[99]), "+f"(d[100]), "+f"(d[101]), "+f"(d[102]), "+f"(d[103]),
        "+f"(d[104]), "+f"(d[105]), "+f"(d[106]), "+f"(d[107]), "+f"(d[108]), "+f"(d[109]), "+f"(d[110]), "+f"(d[111]),
        "+f"(d[112]), "+f"(d[113]), "+f"(d[114]), "+f"(d[115]), "+f"(d[116]), "+f"(d[117]), "+f"(d[118]), "+f"(d[119]),
        "+f"(d[120]), "+f"(d[121]), "+f"(d[122]), "+f"(d[123]), "+f"(d[124]), "+f"(d[125]), "+f"(d[126]), "+f"(d[127])
      : "l"(descA), "l"(descB), "r"(acc));
}

__device__ __forceinline__ void mma_ss64(float (&d)[32], uint64_t descA, uint64_t descB) {
  asm volatile("wgmma.mma_async.sync.aligned.m64n64k16.f32.bf16.bf16 {"
      "%0, %1, %2, %3, %4, %5, %6, %7, %8, %9, %10, %11, %12, %13, %14, %15, "
      "%16, %17, %18, %19, %20, %21, %22, %23, %24, %25, %26, %27, %28, %29, %30, %31"
      "}, %32, %33, 1, 1, 1, 0, 1;\n"
      : "+f"(d[0]), "+f"(d[1]), "+f"(d[2]), "+f"(d[3]), "+f"(d[4]), "+f"(d[5]), "+f"(d[6]), "+f"(d[7]),
        "+f"(d[8]), "+f"(d[9]), "+f"(d[10]), "+f"(d[11]), "+f"(d[12]), "+f"(d[13]), "+f"(d[14]), "+f"(d[15]),
        "+f"(d[16]), "+f"(d[17]), "+f"(d[18]), "+f"(d[19]), "+f"(d[20]), "+f"(d[21]), "+f"(d[22]), "+f"(d[23]),
        "+f"(d[24]), "+f"(d[25]), "+f"(d[26]), "+f"(d[27]), "+f"(d[28]), "+f"(d[29]), "+f"(d[30]), "+f"(d[31])
      : "l"(descA), "l"(descB));
}
__device__ __forceinline__ void mma_ss64_p(float (&d)[32], uint64_t descA, uint64_t descB, int acc) {
  asm volatile("{\n.reg .pred p;\nsetp.ne.b32 p, %34, 0;\n"
      "wgmma.mma_async.sync.aligned.m64n64k16.f32.bf16.bf16 {"
      "%0, %1, %2, %3, %4, %5, %6, %7, %8, %9, %10, %11, %12, %13, %14, %15, "
      "%16, %17, %18, %19, %20, %21, %22, %23, %24, %25, %26, %27, %28, %29, %30, %31"
      "}, %32, %33, p, 1, 1, 0, 1;\n}\n"
      : "+f"(d[0]), "+f"(d[1]), "+f"(d[2]), "+f"(d[3]), "+f"(d[4]), "+f"(d[5]), "+f"(d[6]), "+f"(d[7]),
        "+f"(d[8]), "+f"(d[9]), "+f"(d[10]), "+f"(d[11]), "+f"(d[12]), "+f"(d[13]), "+f"(d[14]), "+f"(d[15]),
        "+f"(d[16]), "+f"(d[17]), "+f"(d[18]), "+f"(d[19]), "+f"(d[20]), "+f"(d[21]), "+f"(d[22]), "+f"(d[23]),
        "+f"(d[24]), "+f"(d[25]), "+f"(d[26]), "+f"(d[27]), "+f"(d[28]), "+f"(d[29]), "+f"(d[30]), "+f"(d[31])
      : "l"(descA), "l"(descB), "r"(acc));
}

__device__ __forceinline__ void mma_ss160(float (&d)[80], uint64_t descA, uint64_t descB) {
  asm volatile("wgmma.mma_async.sync.aligned.m64n160k16.f32.bf16.bf16 {"
      "%0, %1, %2, %3, %4, %5, %6, %7, %8, %9, %10, %11, %12, %13, %14, %15, "
      "%16, %17, %18, %19, %20, %21, %22, %23, %24, %25, %26, %27, %28, %29, %30, %31, "
      "%32, %33, %34, %35, %36, %37, %38, %39, %40, %41, %42, %43, %44, %45, %46, %47, "
      "%48, %49, %50, %51, %52, %53, %54, %55, %56, %57, %58, %59, %60, %61, %62, %63, "
      "%64, %65, %66, %67, %68, %69, %70, %71, %72, %73, %74, %75, %76, %77, %78, %79"
      "}, %80, %81, 1, 1, 1, 0, 1;\n"
      : "+f"(d[0]), "+f"(d[1]), "+f"(d[2]), "+f"(d[3]), "+f"(d[4]), "+f"(d[5]), "+f"(d[6]), "+f"(d[7]),
        "+f"(d[8]), "+f"(d[9]), "+f"(d[10]), "+f"(d[11]), "+f"(d[12]), "+f"(d[13]), "+f"(d[14]), "+f"(d[15]),
        "+f"(d[16]), "+f"(d[17]), "+f"(d[18]), "+f"(d[19]), "+f"(d[20]), "+f"(d[21]), "+f"(d[22]), "+f"(d[23]),
        "+f"(d[24]), "+f"(d[25]), "+f"(d[26]), "+f"(d[27]), "+f"(d[28]), "+f"(d[29]), "+f"(d[30]), "+f"(d[31]),
        "+f"(d[32]), "+f"(d[33]), "+f"(d[34]), "+f"(d[35]), "+f"(d[36]), "+f"(d[37]), "+f"(d[38]), "+f"(d[39]),
        "+f"(d[40]), "+f"(d[41]), "+f"(d[42]), "+f"(d[43]), "+f"(d[44]), "+f"(d[45]), "+f"(d[46]), "+f"(d[47]),
        "+f"(d[48]), "+f"(d[49]), "+f"(d[50]), "+f"(d[51]), "+f"(d[52]), "+f"(d[53]), "+f"(d[54]), "+f"(d[55]),
        "+f"(d[56]), "+f"(d[57]), "+f"(d[58]), "+f"(d[59]), "+f"(d[60]), "+f"(d[61]), "+f"(d[62]), "+f"(d[63]),
        "+f"(d[64]), "+f"(d[65]), "+f"(d[66]), "+f"(d[67]), "+f"(d[68]), "+f"(d[69]), "+f"(d[70]), "+f"(d[71]),
        "+f"(d[72]), "+f"(d[73]), "+f"(d[74]), "+f"(d[75]), "+f"(d[76]), "+f"(d[77]), "+f"(d[78]), "+f"(d[79])
      : "l"(descA), "l"(descB));
}
__device__ __forceinline__ void mma_ss160_z(float (&d)[80], uint64_t descA, uint64_t descB) {
  asm volatile("wgmma.mma_async.sync.aligned.m64n160k16.f32.bf16.bf16 {"
      "%0, %1, %2, %3, %4, %5, %6, %7, %8, %9, %10, %11, %12, %13, %14, %15, "
      "%16, %17, %18, %19, %20, %21, %22, %23, %24, %25, %26, %27, %28, %29, %30, %31, "
      "%32, %33, %34, %35, %36, %37, %38, %39, %40, %41, %42, %43, %44, %45, %46, %47, "
      "%48, %49, %50, %51, %52, %53, %54, %55, %56, %57, %58, %59, %60, %61, %62, %63, "
      "%64, %65, %66, %67, %68, %69, %70, %71, %72, %73, %74, %75, %76, %77, %78, %79"
      "}, %80, %81, 0, 1, 1, 0, 1;\n"
      : "=f"(d[0]), "=f"(d[1]), "=f"(d[2]), "=f"(d[3]), "=f"(d[4]), "=f"(d[5]), "=f"(d[6]), "=f"(d[7]),
        "=f"(d[8]), "=f"(d[9]), "=f"(d[10]), "=f"(d[11]), "=f"(d[12]), "=f"(d[13]), "=f"(d[14]), "=f"(d[15]),
        "=f"(d[16]), "=f"(d[17]), "=f"(d[18]), "=f"(d[19]), "=f"(d[20]), "=f"(d[21]), "=f"(d[22]), "=f"(d[23]),
        "=f"(d[24]), "=f"(d[25]), "=f"(d[26]), "=f"(d[27]), "=f"(d[28]), "=f"(d[29]), "=f"(d[30]), "=f"(d[31]),
        "=f"(d[32]), "=f"(d[33]), "=f"(d[34]), "=f"(d[35]), "=f"(d[36]), "=f"(d[37]), "=f"(d[38]), "=f"(d[39]),
        "=f"(d[40]), "=f"(d[41]), "=f"(d[42]), "=f"(d[43]), "=f"(d[44]), "=f"(d[45]), "=f"(d[46]), "=f"(d[47]),
        "=f"(d[48]), "=f"(d[49]), "=f"(d[50]), "=f"(d[51]), "=f"(d[52]), "=f"(d[53]), "=f"(d[54]), "=f"(d[55]),
        "=f"(d[56]), "=f"(d[57]), "=f"(d[58]), "=f"(d[59]), "=f"(d[60]), "=f"(d[61]), "=f"(d[62]), "=f"(d[63]),
        "=f"(d[64]), "=f"(d[65]), "=f"(d[66]), "=f"(d[67]), "=f"(d[68]), "=f"(d[69]), "=f"(d[70]), "=f"(d[71]),
        "=f"(d[72]), "=f"(d[73]), "=f"(d[74]), "=f"(d[75]), "=f"(d[76]), "=f"(d[77]), "=f"(d[78]), "=f"(d[79])
      : "l"(descA), "l"(descB));
}

__device__ __forceinline__ void mma_ss192(float (&d)[96], uint64_t descA, uint64_t descB) {
  asm volatile("wgmma.mma_async.sync.aligned.m64n192k16.f32.bf16.bf16 {"
      "%0, %1, %2, %3, %4, %5, %6, %7, %8, %9, %10, %11, %12, %13, %14, %15, "
      "%16, %17, %18, %19, %20, %21, %22, %23, %24, %25, %26, %27, %28, %29, %30, %31, "
      "%32, %33, %34, %35, %36, %37, %38, %39, %40, %41, %42, %43, %44, %45, %46, %47, "
      "%48, %49, %50, %51, %52, %53, %54, %55, %56, %57, %58, %59, %60, %61, %62, %63, "
      "%64, %65, %66, %67, %68, %69, %70, %71, %72, %73, %74, %75, %76, %77, %78, %79, "
      "%80, %81, %82, %83, %84, %85, %86, %87, %88, %89, %90, %91, %92, %93, %94, %95"
      "}, %96, %97, 1, 1, 1, 0, 1;\n"
      : "+f"(d[0]), "+f"(d[1]), "+f"(d[2]), "+f"(d[3]), "+f"(d[4]), "+f"(d[5]), "+f"(d[6]), "+f"(d[7]),
        "+f"(d[8]), "+f"(d[9]), "+f"(d[10]), "+f"(d[11]), "+f"(d[12]), "+f"(d[13]), "+f"(d[14]), "+f"(d[15]),
        "+f"(d[16]), "+f"(d[17]), "+f"(d[18]), "+f"(d[19]), "+f"(d[20]), "+f"(d[21]), "+f"(d[22]), "+f"(d[23]),
        "+f"(d[24]), "+f"(d[25]), "+f"(d[26]), "+f"(d[27]), "+f"(d[28]), "+f"(d[29]), "+f"(d[30]), "+f"(d[31]),
        "+f"(d[32]), "+f"(d[33]), "+f"(d[34]), "+f"(d[35]), "+f"(d[36]), "+f"(d[37]), "+f"(d[38]), "+f"(d[39]),
        "+f"(d[40]), "+f"(d[41]), "+f"(d[42]), "+f"(d[43]), "+f"(d[44]), "+f"(d[45]), "+f"(d[46]), "+f"(d[47]),
        "+f"(d[48]), "+f"(d[49]), "+f"(d[50]), "+f"(d[51]), "+f"(d[52]), "+f"(d[53]), "+f"(d[54]), "+f"(d[55]),
        "+f"(d[56]), "+f"(d[57]), "+f"(d[58]), "+f"(d[59]), "+f"(d[60]), "+f"(d[61]), "+f"(d[62]), "+f"(d[63]),
        "+f"(d[64]), "+f"(d[65]), "+f"(d[66]), "+f"(d[67]), "+f"(d[68]), "+f"(d[69]), "+f"(d[70]), "+f"(d[71]),
        "+f"(d[72]), "+f"(d[73]), "+f"(d[74]), "+f"(d[75]), "+f"(d[76]), "+f"(d[77]), "+f"(d[78]), "+f"(d[79]),
        "+f"(d[80]), "+f"(d[81]), "+f"(d[82]), "+f"(d[83]), "+f"(d[84]), "+f"(d[85]), "+f"(d[86]), "+f"(d[87]),
        "+f"(d[88]), "+f"(d[89]), "+f"(d[90]), "+f"(d[91]), "+f"(d[92]), "+f"(d[93]), "+f"(d[94]), "+f"(d[95])
      : "l"(descA), "l"(descB));
}
__device__ __forceinline__ void mma_ss192_p(float (&d)[96], uint64_t descA, uint64_t descB, int acc) {
  asm volatile("{\n.reg .pred p;\nsetp.ne.b32 p, %98, 0;\n"
      "wgmma.mma_async.sync.aligned.m64n192k16.f32.bf16.bf16 {"
      "%0, %1, %2, %3, %4, %5, %6, %7, %8, %9, %10, %11, %12, %13, %14, %15, "
      "%16, %17, %18, %19, %20, %21, %22, %23, %24, %25, %26, %27, %28, %29, %30, %31, "
      "%32, %33, %34, %35, %36, %37, %38, %39, %40, %41, %42, %43, %44, %45, %46, %47, "
      "%48, %49, %50, %51, %52, %53, %54, %55, %56, %57, %58, %59, %60, %61, %62, %63, "
      "%64, %65, %66, %67, %68, %69, %70, %71, %72, %73, %74, %75, %76, %77, %78, %79, "
      "%80, %81, %82, %83, %84, %85, %86, %87, %88, %89, %90, %91, %92, %93, %94, %95"
      "}, %96, %97, p, 1, 1, 0, 1;\n}\n"
      : "+f"(d[0]), "+f"(d[1]), "+f"(d[2]), "+f"(d[3]), "+f"(d[4]), "+f"(d[5]), "+f"(d[6]), "+f"(d[7]),
        "+f"(d[8]), "+f"(d[9]), "+f"(d[10]), "+f"(d[11]), "+f"(d[12]), "+f"(d[13]), "+f"(d[14]), "+f"(d[15]),
        "+f"(d[16]), "+f"(d[17]), "+f"(d[18]), "+f"(d[19]), "+f"(d[20]), "+f"(d[21]), "+f"(d[22]), "+f"(d[23]),
        "+f"(d[24]), "+f"(d[25]), "+f"(d[26]), "+f"(d[27]), "+f"(d[28]), "+f"(d[29]), "+f"(d[30]), "+f"(d[31]),
        "+f"(d[32]), "+f"(d[33]), "+f"(d[34]), "+f"(d[35]), "+f"(d[36]), "+f"(d[37]), "+f"(d[38]), "+f"(d[39]),
        "+f"(d[40]), "+f"(d[41]), "+f"(d[42]), "+f"(d[43]), "+f"(d[44]), "+f"(d[45]), "+f"(d[46]), "+f"(d[47]),
        "+f"(d[48]), "+f"(d[49]), "+f"(d[50]), "+f"(d[51]), "+f"(d[52]), "+f"(d[53]), "+f"(d[54]), "+f"(d[55]),
        "+f"(d[56]), "+f"(d[57]), "+f"(d[58]), "+f"(d[59]), "+f"(d[60]), "+f"(d[61]), "+f"(d[62]), "+f"(d[63]),
        "+f"(d[64]), "+f"(d[65]), "+f"(d[66]), "+f"(d[67]), "+f"(d[68]), "+f"(d[69]), "+f"(d[70]), "+f"(d[71]),
        "+f"(d[72]), "+f"(d[73]), "+f"(d[74]), "+f"(d[75]), "+f"(d[76]), "+f"(d[77]), "+f"(d[78]), "+f"(d[79]),
        "+f"(d[80]), "+f"(d[81]), "+f"(d[82]), "+f"(d[83]), "+f"(d[84]), "+f"(d[85]), "+f"(d[86]), "+f"(d[87]),
        "+f"(d[88]), "+f"(d[89]), "+f"(d[90]), "+f"(d[91]), "+f"(d[92]), "+f"(d[93]), "+f"(d[94]), "+f"(d[95])
      : "l"(descA), "l"(descB), "r"(acc));
}

__device__ __forceinline__ void mma_ss80_tt(float (&d)[40], uint64_t descA, uint64_t descB) {
  asm volatile("wgmma.mma_async.sync.aligned.m64n80k16.f32.bf16.bf16 {"
      "%0, %1, %2, %3, %4, %5, %6, %7, %8, %9, %10, %11, %12, %13, %14, %15, "
      "%16, %17, %18, %19, %20, %21, %22, %23, %24, %25, %26, %27, %28, %29, %30, %31, "
      "%32, %33, %34, %35, %36, %37, %38, %39"
      "}, %40, %41, 1, 1, 1, 1, 1;\n"
      : "+f"(d[0]), "+f"(d[1]), "+f"(d[2]), "+f"(d[3]), "+f"(d[4]), "+f"(d[5]), "+f"(d[6]), "+f"(d[7]),
        "+f"(d[8]), "+f"(d[9]), "+f"(d[10]), "+f"(d[11]), "+f"(d[12]), "+f"(d[13]), "+f"(d[14]), "+f"(d[15]),
        "+f"(d[16]), "+f"(d[17]), "+f"(d[18]), "+f"(d[19]), "+f"(d[20]), "+f"(d[21]), "+f"(d[22]), "+f"(d[23]),
        "+f"(d[24]), "+f"(d[25]), "+f"(d[26]), "+f"(d[27]), "+f"(d[28]), "+f"(d[29]), "+f"(d[30]), "+f"(d[31]),
        "+f"(d[32]), "+f"(d[33]), "+f"(d[34]), "+f"(d[35]), "+f"(d[36]), "+f"(d[37]), "+f"(d[38]), "+f"(d[39])
      : "l"(descA), "l"(descB));
}
__device__ __forceinline__ void mma_ss80_tt_z(float (&d)[40], uint64_t descA, uint64_t descB) {
  asm volatile("wgmma.mma_async.sync.aligned.m64n80k16.f32.bf16.bf16 {"
      "%0, %1, %2, %3, %4, %5, %6, %7, %8, %9, %10, %11, %12, %13, %14, %15, "
      "%16, %17, %18, %19, %20, %21, %22, %23, %24, %25, %26, %27, %28, %29, %30, %31, "
      "%32, %33, %34, %35, %36, %37, %38, %39"
      "}, %40, %41, 0, 1, 1, 1, 1;\n"
      : "=f"(d[0]), "=f"(d[1]), "=f"(d[2]), "=f"(d[3]), "=f"(d[4]), "=f"(d[5]), "=f"(d[6]), "=f"(d[7]),
        "=f"(d[8]), "=f"(d[9]), "=f"(d[10]), "=f"(d[11]), "=f"(d[12]), "=f"(d[13]), "=f"(d[14]), "=f"(d[15]),
        "=f"(d[16]), "=f"(d[17]), "=f"(d[18]), "=f"(d[19]), "=f"(d[20]), "=f"(d[21]), "=f"(d[22]), "=f"(d[23]),
        "=f"(d[24]), "=f"(d[25]), "=f"(d[26]), "=f"(d[27]), "=f"(d[28]), "=f"(d[29]), "=f"(d[30]), "=f"(d[31]),
        "=f"(d[32]), "=f"(d[33]), "=f"(d[34]), "=f"(d[35]), "=f"(d[36]), "=f"(d[37]), "=f"(d[38]), "=f"(d[39])
      : "l"(descA), "l"(descB));
}

__device__ __forceinline__ void mma_rs80_k(float (&d)[40], const uint32_t (&a)[4], uint64_t descB) {
  asm volatile("wgmma.mma_async.sync.aligned.m64n80k16.f32.bf16.bf16 {"
      "%0, %1, %2, %3, %4, %5, %6, %7, %8, %9, %10, %11, %12, %13, %14, %15, "
      "%16, %17, %18, %19, %20, %21, %22, %23, %24, %25, %26, %27, %28, %29, %30, %31, "
      "%32, %33, %34, %35, %36, %37, %38, %39"
      "}, {%40, %41, %42, %43}, %44, 1, 1, 1, 0;\n"
      : "+f"(d[0]), "+f"(d[1]), "+f"(d[2]), "+f"(d[3]), "+f"(d[4]), "+f"(d[5]), "+f"(d[6]), "+f"(d[7]),
        "+f"(d[8]), "+f"(d[9]), "+f"(d[10]), "+f"(d[11]), "+f"(d[12]), "+f"(d[13]), "+f"(d[14]), "+f"(d[15]),
        "+f"(d[16]), "+f"(d[17]), "+f"(d[18]), "+f"(d[19]), "+f"(d[20]), "+f"(d[21]), "+f"(d[22]), "+f"(d[23]),
        "+f"(d[24]), "+f"(d[25]), "+f"(d[26]), "+f"(d[27]), "+f"(d[28]), "+f"(d[29]), "+f"(d[30]), "+f"(d[31]),
        "+f"(d[32]), "+f"(d[33]), "+f"(d[34]), "+f"(d[35]), "+f"(d[36]), "+f"(d[37]), "+f"(d[38]), "+f"(d[39])
      : "r"(a[0]), "r"(a[1]), "r"(a[2]), "r"(a[3]), "l"(descB));
}
__device__ __forceinline__ void mma_rs80_k_z(float (&d)[40], const uint32_t (&a)[4], uint64_t descB) {
  asm volatile("wgmma.mma_async.sync.aligned.m64n80k16.f32.bf16.bf16 {"
      "%0, %1, %2, %3, %4, %5, %6, %7, %8, %9, %10, %11, %12, %13, %14, %15, "
      "%16, %17, %18, %19, %20, %21, %22, %23, %24, %25, %26, %27, %28, %29, %30, %31, "
      "%32, %33, %34, %35, %36, %37, %38, %39"
      "}, {%40, %41, %42, %43}, %44, 0, 1, 1, 0;\n"
      : "=f"(d[0]), "=f"(d[1]), "=f"(d[2]), "=f"(d[3]), "=f"(d[4]), "=f"(d[5]), "=f"(d[6]), "=f"(d[7]),
        "=f"(d[8]), "=f"(d[9]), "=f"(d[10]), "=f"(d[11]), "=f"(d[12]), "=f"(d[13]), "=f"(d[14]), "=f"(d[15]),
        "=f"(d[16]), "=f"(d[17]), "=f"(d[18]), "=f"(d[19]), "=f"(d[20]), "=f"(d[21]), "=f"(d[22]), "=f"(d[23]),
        "=f"(d[24]), "=f"(d[25]), "=f"(d[26]), "=f"(d[27]), "=f"(d[28]), "=f"(d[29]), "=f"(d[30]), "=f"(d[31]),
        "=f"(d[32]), "=f"(d[33]), "=f"(d[34]), "=f"(d[35]), "=f"(d[36]), "=f"(d[37]), "=f"(d[38]), "=f"(d[39])
      : "r"(a[0]), "r"(a[1]), "r"(a[2]), "r"(a[3]), "l"(descB));
}

__device__ __forceinline__ void mma_rs48_k(float (&d)[24], const uint32_t (&a)[4], uint64_t descB) {
  asm volatile("wgmma.mma_async.sync.aligned.m64n48k16.f32.bf16.bf16 {"
      "%0, %1, %2, %3, %4, %5, %6, %7, %8, %9, %10, %11, %12, %13, %14, %15, "
      "%16, %17, %18, %19, %20, %21, %22, %23"
      "}, {%24, %25, %26, %27}, %28, 1, 1, 1, 0;\n"
      : "+f"(d[0]), "+f"(d[1]), "+f"(d[2]), "+f"(d[3]), "+f"(d[4]), "+f"(d[5]), "+f"(d[6]), "+f"(d[7]),
        "+f"(d[8]), "+f"(d[9]), "+f"(d[10]), "+f"(d[11]), "+f"(d[12]), "+f"(d[13]), "+f"(d[14]), "+f"(d[15]),
        "+f"(d[16]), "+f"(d[17]), "+f"(d[18]), "+f"(d[19]), "+f"(d[20]), "+f"(d[21]), "+f"(d[22]), "+f"(d[23])
      : "r"(a[0]), "r"(a[1]), "r"(a[2]), "r"(a[3]), "l"(descB));
}
__device__ __forceinline__ void mma_rs48_k_z(float (&d)[24], const uint32_t (&a)[4], uint64_t descB) {
  asm volatile("wgmma.mma_async.sync.aligned.m64n48k16.f32.bf16.bf16 {"
      "%0, %1, %2, %3, %4, %5, %6, %7, %8, %9, %10, %11, %12, %13, %14, %15, "
      "%16, %17, %18, %19, %20, %21, %22, %23"
      "}, {%24, %25, %26, %27}, %28, 0, 1, 1, 0;\n"
      : "=f"(d[0]), "=f"(d[1]), "=f"(d[2]), "=f"(d[3]), "=f"(d[4]), "=f"(d[5]), "=f"(d[6]), "=f"(d[7]),
        "=f"(d[8]), "=f"(d[9]), "=f"(d[10]), "=f"(d[11]), "=f"(d[12]), "=f"(d[13]), "=f"(d[14]), "=f"(d[15]),
        "=f"(d[16]), "=f"(d[17]), "=f"(d[18]), "=f"(d[19]), "=f"(d[20]), "=f"(d[21]), "=f"(d[22]), "=f"(d[23])
      : "r"(a[0]), "r"(a[1]), "r"(a[2]), "r"(a[3]), "l"(descB));
}

__device__ __forceinline__ void mma_rs160_n(float (&d)[80], const uint32_t (&a)[4], uint64_t descB) {
  asm volatile("wgmma.mma_async.sync.aligned.m64n160k16.f32.bf16.bf16 {"
      "%0, %1, %2, %3, %4, %5, %6, %7, %8, %9, %10, %11, %12, %13, %14, %15, "
      "%16, %17, %18, %19, %20, %21, %22, %23, %24, %25, %26, %27, %28, %29, %30, %31, "
      "%32, %33, %34, %35, %36, %37, %38, %39, %40, %41, %42, %43, %44, %45, %46, %47, "
      "%48, %49, %50, %51, %52, %53, %54, %55, %56, %57, %58, %59, %60, %61, %62, %63, "
      "%64, %65, %66, %67, %68, %69, %70, %71, %72, %73, %74, %75, %76, %77, %78, %79"
      "}, {%80, %81, %82, %83}, %84, 1, 1, 1, 1;\n"
      : "+f"(d[0]), "+f"(d[1]), "+f"(d[2]), "+f"(d[3]), "+f"(d[4]), "+f"(d[5]), "+f"(d[6]), "+f"(d[7]),
        "+f"(d[8]), "+f"(d[9]), "+f"(d[10]), "+f"(d[11]), "+f"(d[12]), "+f"(d[13]), "+f"(d[14]), "+f"(d[15]),
        "+f"(d[16]), "+f"(d[17]), "+f"(d[18]), "+f"(d[19]), "+f"(d[20]), "+f"(d[21]), "+f"(d[22]), "+f"(d[23]),
        "+f"(d[24]), "+f"(d[25]), "+f"(d[26]), "+f"(d[27]), "+f"(d[28]), "+f"(d[29]), "+f"(d[30]), "+f"(d[31]),
        "+f"(d[32]), "+f"(d[33]), "+f"(d[34]), "+f"(d[35]), "+f"(d[36]), "+f"(d[37]), "+f"(d[38]), "+f"(d[39]),
        "+f"(d[40]), "+f"(d[41]), "+f"(d[42]), "+f"(d[43]), "+f"(d[44]), "+f"(d[45]), "+f"(d[46]), "+f"(d[47]),
        "+f"(d[48]), "+f"(d[49]), "+f"(d[50]), "+f"(d[51]), "+f"(d[52]), "+f"(d[53]), "+f"(d[54]), "+f"(d[55]),
        "+f"(d[56]), "+f"(d[57]), "+f"(d[58]), "+f"(d[59]), "+f"(d[60]), "+f"(d[61]), "+f"(d[62]), "+f"(d[63]),
        "+f"(d[64]), "+f"(d[65]), "+f"(d[66]), "+f"(d[67]), "+f"(d[68]), "+f"(d[69]), "+f"(d[70]), "+f"(d[71]),
        "+f"(d[72]), "+f"(d[73]), "+f"(d[74]), "+f"(d[75]), "+f"(d[76]), "+f"(d[77]), "+f"(d[78]), "+f"(d[79])
      : "r"(a[0]), "r"(a[1]), "r"(a[2]), "r"(a[3]), "l"(descB));
}
__device__ __forceinline__ void mma_rs160_n_z(float (&d)[80], const uint32_t (&a)[4], uint64_t descB) {
  asm volatile("wgmma.mma_async.sync.aligned.m64n160k16.f32.bf16.bf16 {"
      "%0, %1, %2, %3, %4, %5, %6, %7, %8, %9, %10, %11, %12, %13, %14, %15, "
      "%16, %17, %18, %19, %20, %21, %22, %23, %24, %25, %26, %27, %28, %29, %30, %31, "
      "%32, %33, %34, %35, %36, %37, %38, %39, %40, %41, %42, %43, %44, %45, %46, %47, "
      "%48, %49, %50, %51, %52, %53, %54, %55, %56, %57, %58, %59, %60, %61, %62, %63, "
      "%64, %65, %66, %67, %68, %69, %70, %71, %72, %73, %74, %75, %76, %77, %78, %79"
      "}, {%80, %81, %82, %83}, %84, 0, 1, 1, 1;\n"
      : "=f"(d[0]), "=f"(d[1]), "=f"(d[2]), "=f"(d[3]), "=f"(d[4]), "=f"(d[5]), "=f"(d[6]), "=f"(d[7]),
        "=f"(d[8]), "=f"(d[9]), "=f"(d[10]), "=f"(d[11]), "=f"(d[12]), "=f"(d[13]), "=f"(d[14]), "=f"(d[15]),
        "=f"(d[16]), "=f"(d[17]), "=f"(d[18]), "=f"(d[19]), "=f"(d[20]), "=f"(d[21]), "=f"(d[22]), "=f"(d[23]),
        "=f"(d[24]), "=f"(d[25]), "=f"(d[26]), "=f"(d[27]), "=f"(d[28]), "=f"(d[29]), "=f"(d[30]), "=f"(d[31]),
        "=f"(d[32]), "=f"(d[33]), "=f"(d[34]), "=f"(d[35]), "=f"(d[36]), "=f"(d[37]), "=f"(d[38]), "=f"(d[39]),
        "=f"(d[40]), "=f"(d[41]), "=f"(d[42]), "=f"(d[43]), "=f"(d[44]), "=f"(d[45]), "=f"(d[46]), "=f"(d[47]),
        "=f"(d[48]), "=f"(d[49]), "=f"(d[50]), "=f"(d[51]), "=f"(d[52]), "=f"(d[53]), "=f"(d[54]), "=f"(d[55]),
        "=f"(d[56]), "=f"(d[57]), "=f"(d[58]), "=f"(d[59]), "=f"(d[60]), "=f"(d[61]), "=f"(d[62]), "=f"(d[63]),
        "=f"(d[64]), "=f"(d[65]), "=f"(d[66]), "=f"(d[67]), "=f"(d[68]), "=f"(d[69]), "=f"(d[70]), "=f"(d[71]),
        "=f"(d[72]), "=f"(d[73]), "=f"(d[74]), "=f"(d[75]), "=f"(d[76]), "=f"(d[77]), "=f"(d[78]), "=f"(d[79])
      : "r"(a[0]), "r"(a[1]), "r"(a[2]), "r"(a[3]), "l"(descB));
}

__device__ __forceinline__ void feature_map(const uint32_t (&P)[2][10], uint32_t (&fr)[10][4]) {
  constexpr float L2E = 1.4426950408889634f;
#pragma unroll
  for (int p = 0; p < 2; p++) {
#pragma unroll
    for (int r = 0; r < 2; r++) {
      uint32_t mx = P[r][5 * p], mn = mx;
#pragma unroll
      for (int g = 1; g < 5; g++) { mx = max_bf2(mx, P[r][5 * p + g]); mn = min_bf2(mn, P[r][5 * p + g]); }
      mx = max_bf2(mx, __shfl_xor_sync(0xffffffffu, mx, 1));
      mn = min_bf2(mn, __shfl_xor_sync(0xffffffffu, mn, 1));
      mx = max_bf2(mx, __shfl_xor_sync(0xffffffffu, mx, 2));
      mn = min_bf2(mn, __shfl_xor_sync(0xffffffffu, mn, 2));
      float mx0 = -bf_lo(mx) * L2E, mx1 = -bf_hi(mx) * L2E, mn0 = bf_lo(mn) * L2E, mn1 = bf_hi(mn) * L2E;
      float ep0[5], ep1[5], en0[5], en1[5];
      float sp0 = 0.f, sp1 = 0.f, sn0 = 0.f, sn1 = 0.f;
#pragma unroll
      for (int g = 0; g < 5; g++) {
        float x0 = bf_lo(P[r][5 * p + g]), x1 = bf_hi(P[r][5 * p + g]);
        ep0[g] = ex2(fmaf(x0, L2E, mx0)); ep1[g] = ex2(fmaf(x1, L2E, mx1));
        en0[g] = ex2(fmaf(x0, -L2E, mn0)); en1[g] = ex2(fmaf(x1, -L2E, mn1));
        sp0 += ep0[g]; sp1 += ep1[g]; sn0 += en0[g]; sn1 += en1[g];
      }
      sp0 += __shfl_xor_sync(0xffffffffu, sp0, 1); sp1 += __shfl_xor_sync(0xffffffffu, sp1, 1);
      sn0 += __shfl_xor_sync(0xffffffffu, sn0, 1); sn1 += __shfl_xor_sync(0xffffffffu, sn1, 1);
      sp0 += __shfl_xor_sync(0xffffffffu, sp0, 2); sp1 += __shfl_xor_sync(0xffffffffu, sp1, 2);
      sn0 += __shfl_xor_sync(0xffffffffu, sn0, 2); sn1 += __shfl_xor_sync(0xffffffffu, sn1, 2);
      sp0 = rcp(sp0); sp1 = rcp(sp1); sn0 = rcp(sn0); sn1 = rcp(sn1);
#pragma unroll
      for (int g = 0; g < 5; g++) {
        fr[5 * p + g][r] = pack_bf16(ep0[g] * sp0, ep1[g] * sp1);
        fr[5 * p + g][2 + r] = pack_bf16(en0[g] * sn0, en1[g] * sn1);
      }
    }
  }
}

template <int V> struct IntC { static constexpr int value = V; };
struct Ring {
  uint32_t idx, phase;
  template <int N> __device__ __forceinline__ void next() { if (++idx == N) { idx = 0; phase ^= 1; } }
};

}

__global__ void __cluster_dims__(2, 1, 1) __launch_bounds__(384, 1)
fused_kernel(const __grid_constant__ Maps maps, const __nv_bfloat16* __restrict__ x, const __nv_bfloat16* __restrict__ wqkv,
             const __nv_bfloat16* __restrict__ wphi, const __nv_bfloat16* __restrict__ w1, const __nv_bfloat16* __restrict__ w2,
             const __nv_bfloat16* __restrict__ w3, const __nv_bfloat16* __restrict__ w4, const __nv_bfloat16* __restrict__ wo,
             const __nv_bfloat16* __restrict__ gate_w, __nv_bfloat16* __restrict__ out) {
  extern __shared__ __align__(1024) uint8_t sgen[];
  const uint32_t sb = smem_u32(sgen);
  const uint32_t sb16 = (sb & 0x3FFFFu) >> 4;
  const uint32_t bars = sb + OFF_BAR;
  const uint32_t fullA = bars + 8 * B_FULLA, emptyA = bars + 8 * B_EMPTYA, fullB = bars + 8 * B_FULLB, emptyB = bars + 8 * B_EMPTYB;

  const int tid = threadIdx.x;
  const int rank = blockIdx.x & 1;
  const int pairIdx = blockIdx.x >> 1;
  const int i = pairIdx >> 2, j = 2 * (pairIdx & 3) + rank;
  const int k3 = (5 * (pairIdx & 3) + 1) >> 1;

  TSTAMP(0);
  auto load_p1_b = [&](int k, uint32_t slot, uint32_t bar) {
    mbar_expect_tx(bar, 40960);
    tma4d(slot + 8192, &maps.qm, bar, 0, 64 * k, 0, j);
    tma3d(slot, &maps.w1m, bar, 0, 64 * k, j);
    tma4d(slot + 32768 + 2048, &maps.qr, bar, 64, 64 * k, 0, j);
    tma3d(slot + 32768, &maps.w1r, bar, 64, 64 * k, j);
  };
  if (tid >= 256) {
    asm volatile("setmaxnreg.dec.sync.aligned.u32 40;");
    if (tid == 256) {
#pragma unroll
      for (int s = 0; s < NA; s++) mbar_init(fullA + 8 * s, 1);
      asm volatile("fence.mbarrier_init.release.cluster;" ::: "memory");
#pragma unroll 1
      for (int u = 0; u < 4; u++) {
        if ((u & 1) == 0) mbar_expect_tx(fullA + 4 * u, SLOT_A);
        tma2d(sb + OFF_A + u * 8192, &maps.x, fullA + 8 * (u >> 1), 64 * (u >> 1), 128 * i + 64 * (u & 1));
      }
    } else if (tid == 288) {
#pragma unroll
      for (int s = 0; s < NB; s++) mbar_init(fullB + 8 * s, 1);
      asm volatile("fence.mbarrier_init.release.cluster;" ::: "memory");
#pragma unroll 1
      for (int k = 0; k < 2; k++) load_p1_b(k, sb + OFF_B + k * SLOT_B, fullB + 8 * k);
      l2_prefetch(wqkv + (size_t)(128 + 4 * blockIdx.x) * (3 * D_), 4 * 3 * D_ * 2);
    } else if (tid == 320) {
#pragma unroll
      for (int b = B_CS; b < NBAR; b++) mbar_init(bars + 8 * b, b < B_EMPTYB ? 1 : b < B_EMPTYA ? 8 : b < B_X1P ? 16 : 2);
#pragma unroll
      for (int b = B_DSR; b < B_EMPTYB; b++) mbar_expect_tx(bars + 8 * b, 10240);
      asm volatile("fence.mbarrier_init.release.cluster;" ::: "memory");
    }
    __syncwarp();
    asm volatile("barrier.cluster.arrive.relaxed.aligned;" ::: "memory");
    auto get_epoch = [&]() { return *reinterpret_cast<volatile unsigned*>(g_flags + FL_DONE * 32) / NCTA; };
    if (tid >= 320) {
      const int lane = tid & 31, ch = lane % 10, rg = lane / 10;
      const __nv_bfloat16* p = w1 + (size_t)(40 * i + (tid >= 352 ? 20 : 0) + rg) * D_ + 80 * j + 8 * ch;
      const unsigned par = get_epoch() & 1;
      float a[8];
#pragma unroll
      for (int e = 0; e < 8; e++) a[e] = 0.f;
#pragma unroll
      for (int it = 0; it < 7; it++) {
        uint4 v = make_uint4(0, 0, 0, 0);
        if (lane < 30 && 3 * it + rg < 20) v = __ldg(reinterpret_cast<const uint4*>(p + (size_t)it * 3 * D_));
        a[0] += bf_lo(v.x); a[1] += bf_hi(v.x); a[2] += bf_lo(v.y); a[3] += bf_hi(v.y);
        a[4] += bf_lo(v.z); a[5] += bf_hi(v.z); a[6] += bf_lo(v.w); a[7] += bf_hi(v.w);
      }
#pragma unroll
      for (int e = 0; e < 8; e++) a[e] += __shfl_down_sync(0xffffffffu, a[e], 10) + __shfl_down_sync(0xffffffffu, a[e], 20);
      if (lane < 10) {
        float* cd = g_acc[par] + 8 * KV_J + 80 * j + 8 * ch;
        red_add4(cd, a[0], a[1], a[2], a[3]); red_add4(cd + 4, a[4], a[5], a[6], a[7]);
      }
      __syncwarp();
      if (lane == 0) flag_add(FL_CS + j);
      __syncwarp();
    }
    asm volatile("barrier.cluster.wait.aligned;" ::: "memory");
    const int lane = tid & 31, pw = (tid >> 5) & 3;
    if (pw == 0) {
      if (tid == 256) {
        Ring r{2, 1};
        unsigned ep1 = 0;
#pragma unroll 1
        for (int k = 2; k < 25; k++) {
          if (k == 4) ep1 = get_epoch() + 1;
          if (k == 10 || k == 17) {
            if (k == 10) mbar_wait(bars + 8 * B_HST, 0);
            flag_wait(k == 10 ? FL_H + 2 * i + rank : FL_X1 + i, ep1 * 8u);
            TSTAMPX(k == 10 ? 29 : 30);
          }
          if (k == 15) mbar_wait(bars + 8 * B_X1P, 0);
          mbar_wait(emptyA + 8 * r.idx, r.phase);
          const uint32_t bar = fullA + 8 * r.idx, slot = sb + OFF_A + r.idx * SLOT_A;
          mbar_expect_tx(bar, SLOT_A);
          if (k >= 10 && k < 15) tma2d(slot, &maps.hs, bar, 64 * (k - 10) + 320 * rank, 128 * i);
          else tma2d_mc(slot + rank * 8192, k < 10 ? &maps.x : &maps.x1, bar, 64 * (k < 10 ? k : (k - 15 + k3) % 10), 128 * i + 64 * rank);
          r.next<NA>();
        }
      }
    } else if (pw == 1) {
      if (tid == 288) {
        Ring r{2, 1};
#pragma unroll 1
        for (int k = 2; k < 18; k++) {
          mbar_wait(emptyB + 8 * r.idx, r.phase);
          const uint32_t bar = fullB + 8 * r.idx, slot = sb + OFF_B + r.idx * SLOT_B;
          if (k < 10) {
            load_p1_b(k, slot, bar);
          } else if (k < 13) {
            mbar_expect_tx(bar, k < 12 ? 40960 : 20480);
            tma3d(slot, &maps.w2, bar, 0, 320 * rank + 128 * (k - 10), 5 * (j >> 1));
            if (k < 12) tma3d(slot + 20480, &maps.w2, bar, 0, 320 * rank + 128 * (k - 10) + 64, 5 * (j >> 1));
          } else {
            mbar_expect_tx(bar, 49152);
            tma3d(slot, &maps.w3, bar, 0, 64 * ((2 * (k - 13) + k3) % 10), 3 * j);
            tma3d(slot + 24576, &maps.w3, bar, 0, 64 * ((2 * (k - 13) + 1 + k3) % 10), 3 * j);
          }
          r.next<NB>();
        }
#pragma unroll 1
        for (int n = 0; n < 8; n++) {
          if (n < 3) { mbar_wait(emptyB + 8 * r.idx, r.phase); r.next<NB>(); }
          if (n >= 4) mbar_wait(bars + 8 * (B_EMPTY4 + n - 4), 0);
          const uint32_t bar = bars + 8 * (B_FULL4 + n), set = sb + ((n >> 1) & 1) * SET4;
          const int h = n & 1, m = ((j >> 1) + 1 + (n >> 1)) & 3;
          mbar_expect_tx(bar, h ? 40960 : 46080);
          tma3d(set + (h ? 46080 : 0), h ? &maps.w4 : &maps.wo, bar, 0, h ? 192 * j + 64 : 80 * j, 5 * m);
          tma3d(set + (h ? 66560 : 25600), &maps.w4, bar, 0, 192 * j + 128 * h, 5 * m);
        }
        mbar_wait(bars + 8 * (B_EMPTY4 + 4), 0);
        mbar_expect_tx(bars + 8 * B_XR, 20480);
        tma2d(sb + OFF_OUT, &maps.st_x1, bars + 8 * B_XR, 80 * j, 128 * i);
      }
    } else {
      const unsigned epoch = get_epoch();
      float* accg = g_acc[epoch & 1];
      if (pw == 2) {
        {
          float* nxt = g_acc[(epoch + 1) & 1];
          constexpr int PER = ACC_FLOATS / NCTA;
#pragma unroll 1
          for (int e = lane; e < PER; e += 32) nxt[blockIdx.x * PER + e] = 0.f;
        }
        if (tid == 320) {
          flag_wait(FL_CS + j, (epoch + 1) * 32u);
          flag_wait(FL_ST + i, (epoch + 1) * 8u);
          fence_async_glb();
          *reinterpret_cast<volatile uint32_t*>(sgen + OFF_BAR + 8 * NBAR) = (epoch + 1) & 1;
          mbar_expect_tx(bars + 8 * B_CS, 320 + 2048);
          bulk_load(sb + OFF_CS, accg + 8 * KV_J + 80 * j, 320, bars + 8 * B_CS);
          bulk_load(sb + OFF_XST, g_xstat + 128 * i, 2048, bars + 8 * B_CS);
          TSTAMPX(21);
          l2_prefetch(w2 + (size_t)blockIdx.x * (D_ * D_ / NCTA), D_ * D_ * 2 / NCTA);
          flag_wait(FL_H + 2 * i + rank, (epoch + 1) * 8u);
          l2_prefetch(w3 + (size_t)blockIdx.x * (F_ * D_ / NCTA), F_ * D_ * 2 / NCTA);
          l2_prefetch(w4 + (size_t)blockIdx.x * (F_ * D_ / NCTA), F_ * D_ * 2 / NCTA);
          l2_prefetch(wo + (size_t)blockIdx.x * (D_ * D_ / NCTA), D_ * D_ * 2 / NCTA);
          flag_wait(FL_KV + j, (epoch + 1) * 16u);
          mbar_expect_tx(bars + 8 * B_KV, KV_J * 4);
          bulk_load(sb + OFF_MISC, accg + j * KV_J, KV_J * 4, bars + 8 * B_KV);
          TSTAMPX(22);
        }
        __syncwarp();
#pragma unroll 1
        for (int m = 0; m < 6; m++) {
          const int col = 192 * j + 32 * m + 8 * (lane & 3);
          const __nv_bfloat16* p = w3 + (size_t)(40 * i + (lane >> 2) * 5) * F_ + col;
          float a[8];
#pragma unroll
          for (int e = 0; e < 8; e++) a[e] = 0.f;
#pragma unroll
          for (int it = 0; it < 5; it++) {
            const uint4 v = __ldg(reinterpret_cast<const uint4*>(p + (size_t)it * F_));
            a[0] += bf_lo(v.x); a[1] += bf_hi(v.x); a[2] += bf_lo(v.y); a[3] += bf_hi(v.y);
            a[4] += bf_lo(v.z); a[5] += bf_hi(v.z); a[6] += bf_lo(v.w); a[7] += bf_hi(v.w);
          }
#pragma unroll
          for (int e = 0; e < 4; e++) {
            const float snd = (lane & 4) ? a[e] : a[e + 4], keep = (lane & 4) ? a[e + 4] : a[e];
            a[e] = keep + __shfl_xor_sync(0xffffffffu, snd, 4);
            a[e] += __shfl_xor_sync(0xffffffffu, a[e], 8);
            a[e] += __shfl_xor_sync(0xffffffffu, a[e], 16);
          }
          if (lane < 8) red_add4(accg + 8 * KV_J + D_ + col + (lane >> 2) * 4, a[0], a[1], a[2], a[3]);
        }
        __syncwarp();
        if (tid == 320) {
          flag_add(FL_CS3 + j);
          flag_wait(FL_S1 + i, (epoch + 1) * 8u);
          flag_wait(FL_CS3 + j, (epoch + 1) * 16u);
          fence_async_glb();
          mbar_expect_tx(bars + 8 * B_ST1, 8192 + 768);
          bulk_load(sb + OFF_CS + 320, accg + 8 * KV_J + D_ + 192 * j, 768, bars + 8 * B_ST1);
          bulk_load(sb + OFF_MISC, g_st1 + 128 * i * 8, 8192, bars + 8 * B_ST1);
        }
        __syncwarp();
#pragma unroll 1
        for (int c = 0; c < 3; c++) {
          mbar_wait(bars + 8 * (B_EMPTY4 + (c ? 5 : 4)), 0);
          const uint4* src = g_part + (size_t)((i * 8 + j) * 3 + c) * 1280;
          const unsigned* tp = reinterpret_cast<const unsigned*>(src + 1024 + (lane & 7) * 32 + 31);
          uint32_t n = 0;
          while (!__all_sync(0xffffffffu, (ld_acquire(tp) ^ epoch) & 1u) && ++n < (WAIT_LIMIT >> 2)) {}
          if (tid == 320) {
            mbar_expect_tx(bars + 8 * (B_RDY + c), 20480);
            bulk_load(sb + (c ? 25600 + 20480 * c : 0), src, 20480, bars + 8 * (B_RDY + c));
          }
        }
      }
      if (tid == 352) {
        mbar_wait(bars + 8 * B_SIGP, 0);
        flag_add(FL_ST + i);
        TSTAMPX(20);
        mbar_expect_tx(bars + 8 * B_XR, 20480);
#pragma unroll 1
        for (int u = 0; u < 8; u++)
          tma2d(sb + OFF_B + (u / 3) * SLOT_B + SPARE + (u % 3) * 2560, &maps.xr, bars + 8 * B_XR, 80 * j, 128 * i + 16 * u);
        const int shift = (j < 2) ? 1 : (j < 4) ? -1 : (j < 6) ? 2 : -2;
        if ((shift > 0 && i == 0) || (shift < 0 && i == 15)) {
          const int nz = shift > 0 ? shift : -shift, zr = shift > 0 ? 0 : S_ - nz;
#pragma unroll 1
          for (int e = 0; e < nz * 10; e++)
            reinterpret_cast<uint4*>(g_Hs + (size_t)(2 + zr + e / 10) * D_ + 80 * j)[e % 10] = make_uint4(0, 0, 0, 0);
          fence_async_glb();
        }
        prefetch_tmap(&maps.st_h); prefetch_tmap(&maps.st_x1); prefetch_tmap(&maps.hs); prefetch_tmap(&maps.x1);
        prefetch_tmap(&maps.w2); prefetch_tmap(&maps.w3); prefetch_tmap(&maps.w4); prefetch_tmap(&maps.wo);
        mbar_wait(bars + 8 * B_SIGH, 0);
        TSTAMPX(23);
        tma2d_store(&maps.st_h, sb + OFF_STG, 80 * j, 128 * i + 2 + shift);
        bulk_commit(); bulk_wait<0>();
        mbar_arrive(bars + 8 * B_HST);
        flag_add(FL_H + 2 * i + (j >> 2));
        flag_add_relaxed(FL_H + 2 * ((i + (shift > 0 ? 1 : -1)) & 15) + (j >> 2));
        TSTAMPX(24);
        mbar_wait(bars + 8 * B_SIGKV, 0);
        TSTAMPX(25);
        fence_async_smem();
        asm volatile("cp.reduce.async.bulk.global.shared::cta.bulk_group.add.f32 [%0], [%1], %2;"
                     ::"l"(accg + j * KV_J), "r"(sb + OFF_MISC), "r"(KV_J * 4) : "memory");
        bulk_commit(); bulk_wait<0>();
        flag_add(FL_KV + j);
        TSTAMPX(26);
        mbar_wait(bars + 8 * B_SIGX1, 0);
        TSTAMPX(27);
        tma2d_store(&maps.st_x1, sb + OFF_STG, 80 * j, 128 * i);
        bulk_commit(); bulk_wait<0>();
        flag_add(FL_X1 + i);
        mbar_arrive_cta(bars + 8 * B_X1P, 0); mbar_arrive_cta(bars + 8 * B_X1P, 1);
        TSTAMPX(28);
        mbar_wait(bars + 8 * B_MFREE, 0);
        flag_add(FL_S1 + i);
      }
    }
  } else {
    uint4 pv[5], pw_[5], pre;
    {
      const int row = 128 * i + 16 * j + (tid >> 4), l16 = tid & 15;
#pragma unroll
      for (int c = 0; c < 5; c++) pv[c] = __ldg(reinterpret_cast<const uint4*>(x + (size_t)row * D_ + c * 128 + l16 * 8));
      pre = __ldg(reinterpret_cast<const uint4*>(wphi + (size_t)j * 1600) + (tid < 200 ? tid : 0));
#pragma unroll
      for (int c = 0; c < 5; c++) pw_[c] = __ldg(reinterpret_cast<const uint4*>(gate_w + c * 128 + l16 * 8));
    }
    asm volatile("barrier.cluster.arrive.relaxed.aligned;" ::: "memory");
    asm volatile("setmaxnreg.inc.sync.aligned.u32 232;");
    const int wg = tid >> 7, warp = tid >> 5, lane = tid & 31, t = lane & 3;
    const int rloc = warp * 16 + (lane >> 2);
    const float* s_cs = reinterpret_cast<const float*>(sgen + OFF_CS);
    auto signal = [&](int b) {
      __syncwarp();
      if (lane == 0) mbar_arrive(bars + 8 * b);
    };
    auto releaseB = [&](uint32_t bar) {
      __syncwarp();
      if (lane == 0) mbar_arrive(bar);
    };
    auto release = [&](uint32_t bar) {
      __syncwarp();
      if (lane < 2) mbar_arrive_cta(bar, lane);
    };
    const uint32_t stg_lane = (warp * 16 + ((lane >> 3) & 1) * 8 + (lane & 7)) * 160 + (lane >> 4) * 16;

    auto stage_tile = [&](uint32_t stg, const uint32_t (&v)[2][10]) {
#pragma unroll
      for (int s = 0; s < 5; s++) stsm4(stg + stg_lane + s * 32, v[0][2 * s], v[1][2 * s], v[0][2 * s + 1], v[1][2 * s + 1]);
    };

    {
#pragma unroll 1
      for (int e = tid; e < 800; e += 256) sts128(sb + OFF_MISC + e * 16, make_uint4(0, 0, 0, 0));
      bar_sync(1, 256);
      float f[40];
      float s = 0.f, gs = 0.f;
#pragma unroll
      for (int c = 0; c < 5; c++) {
        const uint32_t vv[4] = {pv[c].x, pv[c].y, pv[c].z, pv[c].w}, ww[4] = {pw_[c].x, pw_[c].y, pw_[c].z, pw_[c].w};
#pragma unroll
        for (int e = 0; e < 4; e++) {
          f[8 * c + 2 * e] = bf_lo(vv[e]); f[8 * c + 2 * e + 1] = bf_hi(vv[e]);
          s += f[8 * c + 2 * e] + f[8 * c + 2 * e + 1];
          gs = fmaf(f[8 * c + 2 * e], bf_lo(ww[e]), gs); gs = fmaf(f[8 * c + 2 * e + 1], bf_hi(ww[e]), gs);
        }
      }
#pragma unroll
      for (int o = 1; o < 16; o <<= 1) { s += __shfl_xor_sync(0xffffffffu, s, o); gs += __shfl_xor_sync(0xffffffffu, gs, o); }
      const float mean = s * (1.f / D_);
      float q = 0.f;
#pragma unroll
      for (int e = 0; e < 40; e++) { const float d = f[e] - mean; q = fmaf(d, d, q); }
#pragma unroll
      for (int o = 1; o < 16; o <<= 1) q += __shfl_xor_sync(0xffffffffu, q, o);
      const float rstd = rsqrtf(q * (1.f / D_) + 1e-5f);
      asm volatile("barrier.cluster.wait.aligned;" ::: "memory");
      if ((tid & 15) == 0) g_xstat[128 * i + 16 * j + (tid >> 4)] = make_float4(rstd, -mean, rcp(1.f + __expf(-gs)), 0.f);
      signal(B_SIGP);
      if (tid < 200) {
        const uint32_t ww[4] = {pre.x, pre.y, pre.z, pre.w};
        const int h = tid / 50;
#pragma unroll
        for (int e = 0; e < 8; e++) {
          const int idx = tid * 8 + e, k = idx / 20, ff = idx - 20 * k;
          const int n = 40 * (h >> 1) + 8 * (ff >> 2) + 2 * (ff & 3) + (h & 1);
          const int off = (k >> 4) * 2560 + n * 32 + ((((k >> 3) ^ (n >> 2)) & 1) << 4) + (k & 7) * 2;
          *reinterpret_cast<unsigned short*>(sgen + OFF_MISC + off) = (unsigned short)(ww[e >> 1] >> ((e & 1) * 16));
        }
      }
    }
    TSTAMP(1);

    Ring ra{0, 0}, rb{0, 0};
    uint32_t qp[2][10], P[2][10];
    float st_g[2];
    {
      float accM[128], accR[32];
      uint32_t pa = 0, pb = 0;
#pragma unroll 1
      for (int k = 0; k < 10; k++) {
        mbar_wait(fullA + 8 * ra.idx, ra.phase);
        if (tid == 0) TRACE(32 + k);
        mbar_wait(fullB + 8 * rb.idx, rb.phase);
        if (tid == 0) TRACE(64 + k);
        if (k == 0) TSTAMP(2);
        const uint32_t a0 = sb16 + ((OFF_A + ra.idx * SLOT_A + wg * 8192) >> 4), b0 = sb16 + ((OFF_B + rb.idx * SLOT_B) >> 4);
        wg_fence();
#pragma unroll
        for (int kk = 0; kk < 4; kk++) {
          const uint64_t da = make_desc(a0, kk * 32, 16, 1024, 1);
          if (kk == 0) {
            mma_ss256_p(accM, da, make_desc(b0, 0, 8192, 1024, 1), k);
            mma_ss64_p(accR, da, make_desc(b0, 32768, 2048, 256, 3), k);
          } else {
            mma_ss256(accM, da, make_desc(b0, kk * 2048, 8192, 1024, 1));
            mma_ss64(accR, da, make_desc(b0, 32768 + kk * 512, 2048, 256, 3));
          }
          if (kk == 0) {
            wg_commit();
            if (k > 0) {
              wg_wait<1>();
              if (k - 1 < 8) release(emptyA + 8 * pa);
              releaseB(emptyB + 8 * pb);
            }
          }
        }
        wg_commit();
        pa = ra.idx; pb = rb.idx;
        ra.next<NA>(); rb.next<NB>();
      }
      TSTAMP(18);
      float st_rstd[2], st_mr[2];
      mbar_wait(bars + 8 * B_CS, 0);
#pragma unroll
      for (int r = 0; r < 2; r++) {
        const uint4 st = lds128(sb + OFF_XST + (rloc + 8 * r) * 16);
        st_rstd[r] = __uint_as_float(st.x); st_mr[r] = __uint_as_float(st.y); st_g[r] = __uint_as_float(st.z);
      }
      TSTAMP(19);
      wg_wait<0>();
      fence_regs(accM); fence_regs(accR);
      TSTAMP(3);
#define ACC(P_, G, I_) ((G) < 8 ? accM[(P_) * 32 + ((G) & 7) * 4 + (I_)] : accR[(P_) * 8 + ((G) & 1) * 4 + (I_)])
      {
        uint32_t hv[2][10];
        const GeluC g0 = gelu_consts(st_rstd[0], 1.f), g1 = gelu_consts(st_rstd[1], 1.f);
#pragma unroll
        for (int g = 0; g < 10; g++) {
          const float2 cs = *reinterpret_cast<const float2*>(s_cs + 8 * g + 2 * t);
          const float v0 = gelu_s(fmaf(st_mr[0], cs.x, ACC(0, g, 0)), g0), v1 = gelu_s(fmaf(st_mr[0], cs.y, ACC(0, g, 1)), g0);
          const float v2 = gelu_s(fmaf(st_mr[1], cs.x, ACC(0, g, 2)), g1), v3 = gelu_s(fmaf(st_mr[1], cs.y, ACC(0, g, 3)), g1);
          hv[0][g] = pack_bf16(v0, v1); hv[1][g] = pack_bf16(v2, v3);
        }
        fence_async_smem();
        bar_sync(1, 256);
        stage_tile(sb + OFF_STG, hv);
        fence_async_smem();
        signal(B_SIGH);
      }
      TSTAMP(4);
      uint32_t kf[5][4], qf[5][4];
#pragma unroll
      for (int s = 0; s < 5; s++) {
        kf[s][0] = pack_bf16(ACC(2, 2 * s, 0), ACC(2, 2 * s, 1)); kf[s][1] = pack_bf16(ACC(2, 2 * s, 2), ACC(2, 2 * s, 3));
        kf[s][2] = pack_bf16(ACC(2, 2 * s + 1, 0), ACC(2, 2 * s + 1, 1)); kf[s][3] = pack_bf16(ACC(2, 2 * s + 1, 2), ACC(2, 2 * s + 1, 3));
        qf[s][0] = pack_bf16(ACC(1, 2 * s, 0), ACC(1, 2 * s, 1)); qf[s][1] = pack_bf16(ACC(1, 2 * s, 2), ACC(1, 2 * s, 3));
        qf[s][2] = pack_bf16(ACC(1, 2 * s + 1, 0), ACC(1, 2 * s + 1, 1)); qf[s][3] = pack_bf16(ACC(1, 2 * s + 1, 2), ACC(1, 2 * s + 1, 3));
      }
      float pk[40], pq[40];
      wg_fence();
#pragma unroll
      for (int s = 0; s < 5; s++) {
        if (s == 0) mma_rs80_k_z(pk, kf[s], make_desc(sb16, OFF_MISC, 16, 256, 3));
        else mma_rs80_k(pk, kf[s], make_desc(sb16, OFF_MISC + s * 2560, 16, 256, 3));
      }
      wg_commit();
#pragma unroll
      for (int s = 0; s < 5; s++) {
        if (s == 0) mma_rs80_k_z(pq, qf[s], make_desc(sb16, OFF_MISC, 16, 256, 3));
        else mma_rs80_k(pq, qf[s], make_desc(sb16, OFF_MISC + s * 2560, 16, 256, 3));
      }
      wg_commit();
      {
        const int mat = lane >> 3;
        const int tok = warp * 16 + (mat & 1) * 8 + (lane & 7);
        const uint32_t ones = (t == 0) ? 0x00003f80u : 0u;
        __syncwarp();
#pragma unroll
        for (int p = 0; p < 2; p++) {
          const uint32_t rowa = sb + OFF_A + p * SLOT_A + tok * 128;
#pragma unroll
          for (int gg = 0; gg < 3; gg++) {
            const int g0 = 5 * p + 2 * gg;
            uint32_t r0 = pack_bf16(ACC(3, g0, 0), ACC(3, g0, 1)), r1 = pack_bf16(ACC(3, g0, 2), ACC(3, g0, 3));
            uint32_t r2 = ones, r3 = ones;
            if (gg < 2) { r2 = pack_bf16(ACC(3, g0 + 1, 0), ACC(3, g0 + 1, 1)); r3 = pack_bf16(ACC(3, g0 + 1, 2), ACC(3, g0 + 1, 3)); }
            stsm4(rowa + (((2 * gg + (mat >> 1)) ^ (tok & 7)) << 4), r0, r1, r2, r3);
          }
        }
      }
#undef ACC
      wg_wait<1>();
      fence_regs(pk);
#pragma unroll
      for (int G = 0; G < 10; G++) {
        P[0][G] = pack_bf16(pk[4 * G], pk[4 * G + 1]); P[1][G] = pack_bf16(pk[4 * G + 2], pk[4 * G + 3]);
      }
      wg_wait<0>();
      fence_regs(pq);
#pragma unroll
      for (int G = 0; G < 10; G++) {
        qp[0][G] = pack_bf16(pq[4 * G], pq[4 * G + 1]); qp[1][G] = pack_bf16(pq[4 * G + 2], pq[4 * G + 3]);
      }
    }

    uint32_t fr[10][4];
    int pass;
    pass = gridDim.y;
#pragma unroll 1
    do {
    feature_map(P, fr);
    if (pass != 0) {
    {
      const int mat = lane >> 3;
      const int tok = warp * 16 + (mat & 1) * 8 + (lane & 7);
      const uint32_t base = sb + OFF_B + tok * 32 + (((mat >> 1) ^ ((tok >> 2) & 1)) << 4);
#pragma unroll
      for (int G = 0; G < 10; G++) stsm4(base + G * 4096, fr[G][0], fr[G][1], fr[G][2], fr[G][3]);
      fence_async_smem();
      bar_sync(1, 256);
      float kv[40];
      const uint32_t va = sb16 + ((OFF_A + wg * SLOT_A) >> 4), vb = sb16 + ((OFF_B + wg * 20480) >> 4);
      wg_fence();
#pragma unroll
      for (int ks = 0; ks < 8; ks++) {
        if (ks == 0) mma_ss80_tt_z(kv, make_desc(va, 0, 16, 1024, 1), make_desc(vb, 0, 4096, 256, 3));
        else mma_ss80_tt(kv, make_desc(va, ks * 2048, 16, 1024, 1), make_desc(vb, ks * 512, 4096, 256, 3));
      }
      wg_commit();
      uint32_t xv[2][10];
      {
        mbar_wait(bars + 8 * B_XR, 0);
        const uint32_t xa = sb + OFF_B + (warp / 3) * SLOT_B + SPARE + (warp % 3) * 2560 + (lane >> 2) * 160 + t * 4;
#pragma unroll
        for (int g = 0; g < 10; g++) { xv[0][g] = lds32(xa + g * 16); xv[1][g] = lds32(xa + 1280 + g * 16); }
      }
      float acc[80];
      wg_wait<0>();
      release(emptyA); release(emptyA + 8); releaseB(emptyB); release(bars + 8 * B_PEER2);
      TSTAMP(5);
      mbar_wait(fullA + 8 * 2, 0);
      mbar_wait(fullB + 8 * 1, 1);
      TSTAMP(6);
      wg_fence();
#pragma unroll
      for (int kk = 0; kk < 4; kk++) {
        const uint64_t da = make_desc(sb16 + wg * 512, OFF_A + 2 * SLOT_A + kk * 32, 16, 1024, 1);
        const uint64_t db = make_desc(sb16, OFF_B + SLOT_B + kk * 1024, 4096, 512, 2);
        if (kk == 0) mma_ss160_z(acc, da, db); else mma_ss160(acc, da, db);
      }
      wg_commit();
      ra.next<NA>();
      wg_wait<1>();
      fence_regs(kv);
      TSTAMP(31);
      const uint32_t dst = sb + OFF_MISC + wg * (KV_PAIR * 4);
      const int m0 = (warp & 3) * 16 + (lane >> 2);
#pragma unroll
      for (int r = 0; r < 2; r++) {
        const int m = m0 + 8 * r;
        const bool hi = m >= 20;
        uint32_t v[10];
#pragma unroll
        for (int G = 0; G < 10; G++) v[G] = __float_as_uint(hi ? kv[4 * G + 2 * r + 1] : kv[4 * G + 2 * r]);
        const uint32_t p = dst + 4 * (m < 40 ? m * 48 + t * 12 : 1920 + t * 24 + 12);
        if (m <= 40) {
          sts128(p, make_uint4(v[0], v[1], v[2], v[3])); sts128(p + 16, make_uint4(v[4], v[5], v[6], v[7]));
          sts128(p + 32, make_uint4(v[8], v[9], 0u, 0u));
        }
      }
      if (m0 == 32) {
        const uint32_t p = dst + 4 * (1920 + t * 24);
        sts128(p, make_uint4(__float_as_uint(kv[2]), __float_as_uint(kv[6]), __float_as_uint(kv[10]), __float_as_uint(kv[14])));
        sts128(p + 16, make_uint4(__float_as_uint(kv[18]), __float_as_uint(kv[22]), __float_as_uint(kv[26]), __float_as_uint(kv[30])));
        sts128(p + 32, make_uint4(__float_as_uint(kv[34]), __float_as_uint(kv[38]), 0u, 0u));
      }
      signal(B_SIGKV);
      uint32_t pa = 2, pb = 1;
#pragma unroll 1
      for (int k = 1; k < 5; k++) {
        mbar_wait(fullA + 8 * ra.idx, ra.phase);
        if ((k & 1) == 0) mbar_wait(fullB + 8 * rb.idx, rb.phase);
        const uint32_t a0 = sb16 + ((OFF_A + ra.idx * SLOT_A + wg * 8192) >> 4);
        const uint32_t b0 = sb16 + ((OFF_B + rb.idx * SLOT_B + (k & 1) * 20480) >> 4);
        wg_fence();
#pragma unroll
        for (int kk = 0; kk < 4; kk++) {
          mma_ss160(acc, make_desc(a0, kk * 32, 16, 1024, 1), make_desc(b0, kk * 1024, 4096, 512, 2));
          if (kk == 0) {
            wg_commit();
            wg_wait<1>();
            release(emptyA + 8 * pa);
            if ((k & 1) == 0) releaseB(emptyB + 8 * pb);
          }
        }
        wg_commit();
        pa = ra.idx; pb = rb.idx;
        ra.next<NA>();
        if ((k & 1) || k == 4) rb.next<NB>();
      }
      mbar_wait(bars + 8 * B_PEER2, 0);
      wg_wait<0>();
      fence_regs(acc);
      release(emptyA + 8 * pa);
      TSTAMP(7);
      {
        uint32_t sn[20];
        if (rank) {
#pragma unroll
          for (int e = 0; e < 20; e++) sn[e] = pack_bf16(acc[2 * e], acc[2 * e + 1]);
#pragma unroll
          for (int e = 0; e < 40; e++) acc[e] = acc[40 + e];
        } else {
#pragma unroll
          for (int e = 0; e < 20; e++) sn[e] = pack_bf16(acc[40 + 2 * e], acc[41 + 2 * e]);
        }
        const uint32_t peer = map_peer(sb, rank ^ 1);
#pragma unroll
        for (int q = 0; q < 5; q++)
          st_async16(peer + OFF_B + 20480 + tid * 16 + q * 4096, sn[4 * q], sn[4 * q + 1], sn[4 * q + 2], sn[4 * q + 3],
                     peer + OFF_BAR + 8 * (B_DSR + 8 + wg));
#pragma unroll
        for (int g = 0; g < 10; g++) {
          acc[4 * g] += bf_lo(xv[0][g]); acc[4 * g + 1] += bf_hi(xv[0][g]);
          acc[4 * g + 2] += bf_lo(xv[1][g]); acc[4 * g + 3] += bf_hi(xv[1][g]);
        }
        bar_sync(1, 256);
        mbar_wait(bars + 8 * (B_DSR + 8 + wg), 0);
#pragma unroll
        for (int q = 0; q < 5; q++) {
          const uint4 v = lds128(sb + OFF_B + 20480 + tid * 16 + q * 4096);
          xv[0][2 * q] = pack_bf16(acc[8 * q] + bf_lo(v.x), acc[8 * q + 1] + bf_hi(v.x));
          xv[1][2 * q] = pack_bf16(acc[8 * q + 2] + bf_lo(v.y), acc[8 * q + 3] + bf_hi(v.y));
          xv[0][2 * q + 1] = pack_bf16(acc[8 * q + 4] + bf_lo(v.z), acc[8 * q + 5] + bf_hi(v.z));
          xv[1][2 * q + 1] = pack_bf16(acc[8 * q + 6] + bf_lo(v.w), acc[8 * q + 7] + bf_hi(v.w));
        }
        releaseB(emptyB + 8 * pb);
      }
      TSTAMP(16);
      stage_tile(sb + OFF_STG, xv);
      fence_async_smem();
      signal(B_SIGX1);
      TSTAMP(17);
#pragma unroll
      for (int r = 0; r < 2; r++) {
        float s = 0.f;
#pragma unroll
        for (int g = 0; g < 10; g++) {
          acc[4 * g + 2 * r] = bf_lo(xv[r][g]); acc[4 * g + 2 * r + 1] = bf_hi(xv[r][g]);
          s += acc[4 * g + 2 * r] + acc[4 * g + 2 * r + 1];
        }
        s += __shfl_xor_sync(0xffffffffu, s, 1); s += __shfl_xor_sync(0xffffffffu, s, 2);
        const float mu = s * (1.f / 80.f);
        float q = 0.f;
#pragma unroll
        for (int g = 0; g < 10; g++) {
          const float d0 = acc[4 * g + 2 * r] - mu, d1 = acc[4 * g + 2 * r + 1] - mu;
          q = fmaf(d0, d0, q); q = fmaf(d1, d1, q);
        }
        q += __shfl_xor_sync(0xffffffffu, q, 1); q += __shfl_xor_sync(0xffffffffu, q, 2);
        if (t == 0) g_st1[(128 * i + rloc + 8 * r) * 8 + j] = make_float2(mu, q);
      }
    }
    TSTAMP(8);
#pragma unroll
    for (int G = 0; G < 10; G++) { P[0][G] = qp[0][G]; P[1][G] = qp[1][G]; }
    }
    asm volatile("" : "+r"(pass));
    } while (pass-- != 0);

    uint32_t of[5][4];
    {
      mbar_wait(bars + 8 * B_KV, 0);
      uint4 kvr[2][3];
#pragma unroll
      for (int u = 0; u < 2; u++) {
        const int it = tid + 256 * u, p = it / 192, rem = it - 192 * p, n = rem >> 2, tq = rem & 3;
        const uint32_t sp = sb + OFF_MISC + 4 * (p * KV_PAIR + (n < 40 ? n * 48 + tq * 12 : 1920 + tq * 24 + (n & 1) * 12));
        if (it < 384) { kvr[u][0] = lds128(sp); kvr[u][1] = lds128(sp + 16); kvr[u][2] = lds128(sp + 32); }
      }
      bar_sync(1, 256);
#pragma unroll
      for (int u = 0; u < 2; u++) {
        const int it = tid + 256 * u, p = it / 192, rem = it - 192 * p, n = rem >> 2, tq = rem & 3;
        const int sh = (n < 40 ? (n >= 20) : (n & 1)) * 16;
        const uint32_t v[10] = {kvr[u][0].x, kvr[u][0].y, kvr[u][0].z, kvr[u][0].w, kvr[u][1].x, kvr[u][1].y, kvr[u][1].z, kvr[u][1].w, kvr[u][2].x, kvr[u][2].y};
        uint8_t* dst = sgen + OFF_MISC + p * 7680 + n * 32 + tq * 4;
        const int sw = ((n >> 2) & 1) << 4;
        if (it < 384) {
#pragma unroll
          for (int G = 0; G < 10; G++)
            *reinterpret_cast<uint32_t*>(dst + (G >> 1) * 1536 + (((G & 1) << 4) ^ sw)) = pack_bf16(__uint_as_float(v[G]), 0.f) << sh;
        }
      }
      fence_async_smem();
      bar_sync(1, 256);
      float o0[24], o1[24];
      wg_fence();
#pragma unroll
      for (int g = 0; g < 5; g++) {
        if (g == 0) mma_rs48_k_z(o0, fr[g], make_desc(sb16, OFF_MISC, 16, 256, 3));
        else mma_rs48_k(o0, fr[g], make_desc(sb16, OFF_MISC + g * 1536, 16, 256, 3));
      }
#pragma unroll
      for (int g = 0; g < 5; g++) {
        if (g == 0) mma_rs48_k_z(o1, fr[5], make_desc(sb16, OFF_MISC + 7680, 16, 256, 3));
        else mma_rs48_k(o1, fr[5 + g], make_desc(sb16, OFF_MISC + 7680 + g * 1536, 16, 256, 3));
      }
      wg_commit();
      wg_wait<0>();
      fence_regs(o0); fence_regs(o1);
      signal(B_MFREE);
#pragma unroll
      for (int r = 0; r < 2; r++) {
        const float a0 = __fdividef(st_g[r], o0[20 + 2 * r] + 1e-6f), a1 = __fdividef(st_g[r], o0[21 + 2 * r] + 1e-6f);
        const float b0 = __fdividef(st_g[r], o1[20 + 2 * r] + 1e-6f), b1 = __fdividef(st_g[r], o1[21 + 2 * r] + 1e-6f);
        const float am = t < 2 ? a0 : a1, bm = t < 2 ? b0 : b1;
#pragma unroll
        for (int g = 0; g < 5; g++) {
          const float sa = g < 2 ? a0 : (g == 2 ? am : a1), sb2 = g < 2 ? b0 : (g == 2 ? bm : b1);
          of[g >> 1][(g & 1) * 2 + r] = pack_bf16(o0[4 * g + 2 * r] * sa, o0[4 * g + 2 * r + 1] * sa);
          of[(5 + g) >> 1][((5 + g) & 1) * 2 + r] = pack_bf16(o1[4 * g + 2 * r] * sb2, o1[4 * g + 2 * r + 1] * sb2);
        }
      }
    }
    TSTAMP(9);

    uint32_t hf[12][4];
    float ac4[80];
    auto unit = [&](auto uc, uint32_t b0) {
      constexpr int u = decltype(uc)::value;
#pragma unroll
      for (int s = 0; s < (u ? 4 : 5); s++) {
        const uint64_t db = make_desc(b0, (u ? 5120 + 20480 * u : 0) + s * 1024, u ? 4096 : 5120, 512, 2);
        if (u == 0 && s == 0) mma_rs160_n_z(ac4, of[0], db);
        else if (u == 0) mma_rs160_n(ac4, of[s], db);
        else mma_rs160_n(ac4, hf[(4 * u + 8 + s) % 12], db);
      }
      wg_commit();
    };
    {
      float acc[96];
      uint32_t pa = 0, pb = 0;
#pragma unroll 1
      for (int k = 0; k < 10; k++) {
        mbar_wait(fullA + 8 * ra.idx, ra.phase);
        if (tid == 0) TRACE(52 + k);
        if ((k & 1) == 0) mbar_wait(fullB + 8 * rb.idx, rb.phase);
        if (tid == 0) TRACE(84 + k);
        if (k == 0) TSTAMP(10);
        const uint32_t a0 = sb16 + ((OFF_A + ra.idx * SLOT_A + wg * 8192) >> 4);
        const uint32_t b0 = sb16 + ((OFF_B + rb.idx * SLOT_B + (k & 1) * 24576) >> 4);
        wg_fence();
#pragma unroll
        for (int kk = 0; kk < 4; kk++) {
          if (kk == 0) mma_ss192_p(acc, make_desc(a0, 0, 16, 1024, 1), make_desc(b0, 0, 8192, 1024, 1), k);
          else mma_ss192(acc, make_desc(a0, kk * 32, 16, 1024, 1), make_desc(b0, kk * 2048, 8192, 1024, 1));
          if (kk == 0) {
            wg_commit();
            if (k > 0) {
              wg_wait<1>();
              release(emptyA + 8 * pa);
              if ((k & 1) == 0) releaseB(emptyB + 8 * pb);
            }
          }
        }
        wg_commit();
        pa = ra.idx; pb = rb.idx;
        ra.next<NA>();
        if (k & 1) rb.next<NB>();
      }
      float rs[2], mm[2];
      mbar_wait(bars + 8 * B_ST1, 0);
#pragma unroll
      for (int r = 0; r < 2; r++) {
        const uint4 su = lds128(sb + OFF_MISC + (rloc + 8 * r) * 64 + t * 16);
        const float m0 = __uint_as_float(su.x), m1 = __uint_as_float(su.z);
        float mu = m0 + m1;
        mu += __shfl_xor_sync(0xffffffffu, mu, 1); mu += __shfl_xor_sync(0xffffffffu, mu, 2);
        mu *= 0.125f;
        const float d0 = m0 - mu, d1 = m1 - mu;
        float q = __uint_as_float(su.y) + __uint_as_float(su.w) + 80.f * (d0 * d0 + d1 * d1);
        q += __shfl_xor_sync(0xffffffffu, q, 1); q += __shfl_xor_sync(0xffffffffu, q, 2);
        rs[r] = rsqrtf(q * (1.f / D_) + 1e-5f);
        mm[r] = -mu;
      }
      mbar_wait(bars + 8 * B_FULL4, 0);
      wg_fence();
      unit(IntC<0>{}, sb16);
      wg_wait<1>();
      fence_regs(acc);
      releaseB(emptyB + 8 * pb);
      release(bars + 8 * B_PEER);
      TSTAMP(11);
      const GeluC g0 = gelu_consts(rs[0], 1.f - st_g[0]), g1 = gelu_consts(rs[1], 1.f - st_g[1]);
#pragma unroll
      for (int g = 0; g < 24; g++) {
        const float2 cs = *reinterpret_cast<const float2*>(s_cs + 80 + 8 * g + 2 * t);
        const float v0 = gelu_s(fmaf(mm[0], cs.x, acc[4 * g]), g0), v1 = gelu_s(fmaf(mm[0], cs.y, acc[4 * g + 1]), g0);
        const float v2 = gelu_s(fmaf(mm[1], cs.x, acc[4 * g + 2]), g1), v3 = gelu_s(fmaf(mm[1], cs.y, acc[4 * g + 3]), g1);
        hf[g >> 1][(g & 1) * 2] = pack_bf16(v0, v1);
        hf[g >> 1][(g & 1) * 2 + 1] = pack_bf16(v2, v3);
        if (g == 7) { wg_fence(); unit(IntC<1>{}, sb16); }
        if (g == 15) { mbar_wait(bars + 8 * (B_FULL4 + 1), 0); wg_fence(); unit(IntC<2>{}, sb16); }
        if (g == 23) { wg_wait<1>(); signal(B_EMPTY4); wg_fence(); unit(IntC<3>{}, sb16); }
      }
    }
    TSTAMP(12);

    {
      float kp[40];
      uint32_t sn[20], kb[20];
      const uint32_t peer = map_peer(sb, rank ^ 1);
      const uint32_t tag = lds32(sb + OFF_BAR + 8 * NBAR);
      auto add8 = [&](int q, const uint4 v) {
        float* d = &kp[8 * q];
        d[0] += bf_lo(v.x); d[1] += bf_hi(v.x); d[2] += bf_lo(v.y); d[3] += bf_hi(v.y);
        d[4] += bf_lo(v.z); d[5] += bf_hi(v.z); d[6] += bf_lo(v.w); d[7] += bf_hi(v.w);
      };
      auto send = [&](int c) {
        const uint32_t dso = peer + OFF_DS + (c & 1) * 20480 + tid * 16, dsb = peer + OFF_BAR + 8 * (B_DSR + 2 * c + wg);
#pragma unroll
        for (int q = 0; q < 5; q++) st_async16(dso + q * 4096, sn[4 * q], sn[4 * q + 1], sn[4 * q + 2], sn[4 * q + 3], dsb);
      };
      mbar_wait(bars + 8 * B_PEER, 0);
      uint4* gdst = g_part + (size_t)i * 8 * 3840 + tid;
#pragma unroll 1
      for (int c = 0; c < 3; c++) {
        const uint32_t b0 = sb16 + ((c & 1) ? 0 : SET4 >> 4), bc = bars + 16 * c;
        mbar_wait(bc + 8 * (B_FULL4 + 2), 0);
        wg_wait<0>();
        fence_regs(ac4);
        if (rank) {
#pragma unroll
          for (int e = 0; e < 20; e++) { sn[e] = pack_bf16(ac4[2 * e], ac4[2 * e + 1]); kb[e] = pack_bf16(ac4[40 + 2 * e], ac4[41 + 2 * e]); }
        } else {
#pragma unroll
          for (int e = 0; e < 20; e++) { kb[e] = pack_bf16(ac4[2 * e], ac4[2 * e + 1]); sn[e] = pack_bf16(ac4[40 + 2 * e], ac4[41 + 2 * e]); }
        }
#pragma unroll
        for (int e = 0; e < 20; e++) asm volatile("" : "+r"(sn[e]), "+r"(kb[e]));
        if (c == 0 && wg == 1) bar_sync(2, 256);
        wg_fence();
        unit(IntC<0>{}, b0);
        if (lane == 0) mbar_arrive(bc + 8 * (B_EMPTY4 + 1));
        send(c);
        unit(IntC<1>{}, b0);
        if (c == 0 && wg == 0) bar_arrive(2, 256);
        {
          mbar_wait(bc + 8 * (B_DSR + wg), 0);
          uint4* dst = gdst + (((j + 2 * c + 2) & 7) * 3 + c) * 1280;
#pragma unroll
          for (int q = 0; q < 5; q++) {
            const uint4 v = lds128(sb + OFF_DS + (c & 1) * 20480 + tid * 16 + q * 4096);
            st_relaxed16(dst + q * 256, (add_bf2(v.x, kb[4 * q]) & ~1u) | tag, add_bf2(v.y, kb[4 * q + 1]),
                         add_bf2(v.z, kb[4 * q + 2]), add_bf2(v.w, kb[4 * q + 3]));
          }
        }
        mbar_wait(bc + 8 * (B_FULL4 + 3), 0);
        wg_fence();
        unit(IntC<2>{}, b0);
        wg_wait<1>();
        if (lane == 0) mbar_arrive(bc + 8 * (B_EMPTY4 + 2));
        unit(IntC<3>{}, b0);
      }
      auto partial = [&](int c, uint4 (&v)[5]) {
        mbar_wait(bars + 8 * (B_RDY + c), 0);
        uint32_t bad = 0;
#pragma unroll
        for (int q = 0; q < 5; q++) { v[q] = lds128(sb + (c ? 25600 + 20480 * c : 0) + tid * 16 + q * 4096); bad |= v[q].x ^ tag; }
#pragma unroll 1
        for (uint32_t n = 0; (bad & 1u) && n < (WAIT_LIMIT >> 2); n++) {
          bad = 0;
#pragma unroll
          for (int q = 0; q < 5; q++) { v[q] = ld_relaxed16(gdst + (j * 3 + c) * 1280 + q * 256); bad |= v[q].x ^ tag; }
        }
      };
      uint4 pa4[5], pb4[5];
      partial(0, pa4);
      partial(1, pb4);
#pragma unroll
      for (int q = 0; q < 5; q++)
        pa4[q] = make_uint4(add_bf2(pa4[q].x, pb4[q].x), add_bf2(pa4[q].y, pb4[q].y), add_bf2(pa4[q].z, pb4[q].z), add_bf2(pa4[q].w, pb4[q].w));
      wg_wait<0>();
      fence_regs(ac4);
      if (rank) {
#pragma unroll
        for (int e = 0; e < 20; e++) sn[e] = pack_bf16(ac4[2 * e], ac4[2 * e + 1]);
#pragma unroll
        for (int e = 0; e < 40; e++) kp[e] = ac4[40 + e];
      } else {
#pragma unroll
        for (int e = 0; e < 20; e++) sn[e] = pack_bf16(ac4[40 + 2 * e], ac4[41 + 2 * e]);
#pragma unroll
        for (int e = 0; e < 40; e++) kp[e] = ac4[e];
      }
      send(3);
      TSTAMP(13);
      {
        mbar_wait(bars + 8 * B_XR, 1);
        const float w0 = 1.f - st_g[0], w1s = 1.f - st_g[1];
        const uint32_t xa = sb + OFF_OUT + rloc * 160 + t * 4;
#pragma unroll
        for (int g = 0; g < 10; g++) {
          const uint32_t x0 = lds32(xa + g * 16), x1 = lds32(xa + 1280 + g * 16);
          kp[4 * g] = fmaf(w0, bf_lo(x0), kp[4 * g]); kp[4 * g + 1] = fmaf(w0, bf_hi(x0), kp[4 * g + 1]);
          kp[4 * g + 2] = fmaf(w1s, bf_lo(x1), kp[4 * g + 2]); kp[4 * g + 3] = fmaf(w1s, bf_hi(x1), kp[4 * g + 3]);
        }
      }
#pragma unroll
      for (int q = 0; q < 5; q++) add8(q, pa4[q]);
      partial(2, pb4);
      mbar_wait(bars + 8 * (B_DSR + 6 + wg), 0);
      TSTAMP(14);
#pragma unroll
      for (int q = 0; q < 5; q++) {
        const uint4 c = pb4[q], d = lds128(sb + OFF_DS + 20480 + tid * 16 + q * 4096);
        add8(q, make_uint4(add_bf2(c.x, d.x), add_bf2(c.y, d.y), add_bf2(c.z, d.z), add_bf2(c.w, d.w)));
      }
      __syncwarp();
      uint32_t ov[2][10];
#pragma unroll
      for (int g = 0; g < 10; g++) { ov[0][g] = pack_bf16(kp[4 * g], kp[4 * g + 1]); ov[1][g] = pack_bf16(kp[4 * g + 2], kp[4 * g + 3]); }
      stage_tile(sb + OFF_OUT, ov);
      __syncwarp();
      __nv_bfloat16* dst = out + (size_t)(128 * i + 16 * warp) * D_ + 80 * j;
#pragma unroll
      for (int q = 0; q < 5; q++) {
        const int id = q * 32 + lane, r = id / 10;
        *reinterpret_cast<uint4*>(dst + r * (D_ - 80) + id * 8) = lds128(sb + OFF_OUT + warp * 2560 + id * 16);
      }
    }
    TSTAMP(15);
    if (tid == 0) asm volatile("red.relaxed.gpu.global.add.u32 [%0], 1;" ::"l"(g_flags + FL_DONE * 32) : "memory");
  }
}

namespace {
typedef CUresult (*EncodeFn)(CUtensorMap*, CUtensorMapDataType, cuuint32_t, void*, const cuuint64_t*, const cuuint64_t*,
                             const cuuint32_t*, const cuuint32_t*, CUtensorMapInterleave, CUtensorMapSwizzle,
                             CUtensorMapL2promotion, CUtensorMapFloatOOBfill);

void encode(EncodeFn fn, CUtensorMap* m, const void* ptr, int rank, const cuuint64_t* dims, const cuuint64_t* strides,
            const cuuint32_t* box, CUtensorMapSwizzle swz) {
  cuuint32_t es[5] = {1, 1, 1, 1, 1};
  fn(m, CU_TENSOR_MAP_DATA_TYPE_BFLOAT16, rank, const_cast<void*>(ptr), dims, strides, box, es, CU_TENSOR_MAP_INTERLEAVE_NONE,
     swz, CU_TENSOR_MAP_L2_PROMOTION_L2_128B, CU_TENSOR_MAP_FLOAT_OOB_FILL_NONE);
}
}

extern "C" void kernel_launch(void* const* d_in, const int* in_sizes, int n_in, void* d_out, int out_size) {
  (void)in_sizes; (void)n_in; (void)out_size;
  const __nv_bfloat16* x = (const __nv_bfloat16*)d_in[0];
  const __nv_bfloat16* wqkv = (const __nv_bfloat16*)d_in[1];
  const __nv_bfloat16* wphi = (const __nv_bfloat16*)d_in[2];
  const __nv_bfloat16* wo = (const __nv_bfloat16*)d_in[3];
  const __nv_bfloat16* w1 = (const __nv_bfloat16*)d_in[5];
  const __nv_bfloat16* w2 = (const __nv_bfloat16*)d_in[6];
  const __nv_bfloat16* w3 = (const __nv_bfloat16*)d_in[7];
  const __nv_bfloat16* w4 = (const __nv_bfloat16*)d_in[8];
  const __nv_bfloat16* gate_w = (const __nv_bfloat16*)d_in[9];

  static EncodeFn enc = nullptr;
  static void *pHs = nullptr, *pX1 = nullptr;
  if (!enc) {
    cudaDriverEntryPointQueryResult qr;
    cudaGetDriverEntryPoint("cuTensorMapEncodeTiled", (void**)&enc, cudaEnableDefault, &qr);
    cudaGetSymbolAddress(&pHs, g_Hs);
    cudaGetSymbolAddress(&pX1, g_X1);
    cudaFuncSetAttribute(fused_kernel, cudaFuncAttributeMaxDynamicSharedMemorySize, SMEM_BYTES);
  }
  Maps m;
  {
    cuuint64_t dims[2] = {D_, S_}, str[1] = {D_ * 2};
    cuuint32_t box[2] = {64, 128}, boxh[2] = {64, 64};
    encode(enc, &m.x, x, 2, dims, str, boxh, CU_TENSOR_MAP_SWIZZLE_128B);
    encode(enc, &m.hs, (const char*)pHs + 2 * D_ * 2, 2, dims, str, box, CU_TENSOR_MAP_SWIZZLE_128B);
    encode(enc, &m.x1, pX1, 2, dims, str, boxh, CU_TENSOR_MAP_SWIZZLE_128B);
    cuuint32_t boxr[2] = {80, 16}, boxs[2] = {80, 128};
    cuuint64_t dimsp[2] = {D_, S_ + 4};
    encode(enc, &m.st_h, pHs, 2, dimsp, str, boxs, CU_TENSOR_MAP_SWIZZLE_NONE);
    encode(enc, &m.st_x1, pX1, 2, dims, str, boxs, CU_TENSOR_MAP_SWIZZLE_NONE);
    encode(enc, &m.xr, x, 2, dims, str, boxr, CU_TENSOR_MAP_SWIZZLE_NONE);
  }
  {
    cuuint64_t dims[3] = {80, D_, 8}, str[2] = {D_ * 2, 160};
    cuuint32_t boxm[3] = {64, 64, 1}, boxr[3] = {16, 64, 1};
    encode(enc, &m.w1m, w1, 3, dims, str, boxm, CU_TENSOR_MAP_SWIZZLE_128B);
    encode(enc, &m.w1r, w1, 3, dims, str, boxr, CU_TENSOR_MAP_SWIZZLE_32B);
  }
  {
    cuuint64_t dims[4] = {80, D_, 3, 8}, str[3] = {3 * D_ * 2, D_ * 2, 160};
    cuuint32_t boxm[4] = {64, 64, 3, 1}, boxr[4] = {16, 64, 3, 1};
    encode(enc, &m.qm, wqkv, 4, dims, str, boxm, CU_TENSOR_MAP_SWIZZLE_128B);
    encode(enc, &m.qr, wqkv, 4, dims, str, boxr, CU_TENSOR_MAP_SWIZZLE_32B);
  }
  {
    cuuint64_t dims[3] = {32, D_, 20}, dims4[3] = {32, F_, 20}, str[2] = {D_ * 2, 64};
    cuuint32_t box4[3] = {32, 64, 5}, boxo[3] = {32, 80, 5};
    encode(enc, &m.w4, w4, 3, dims4, str, box4, CU_TENSOR_MAP_SWIZZLE_64B);
    encode(enc, &m.wo, wo, 3, dims, str, boxo, CU_TENSOR_MAP_SWIZZLE_64B);
    encode(enc, &m.w2, w2, 3, dims, str, box4, CU_TENSOR_MAP_SWIZZLE_64B);
  }
  {
    cuuint64_t dims[3] = {64, D_, 24}, str[2] = {F_ * 2, 128};
    cuuint32_t box[3] = {64, 64, 3};
    encode(enc, &m.w3, w3, 3, dims, str, box, CU_TENSOR_MAP_SWIZZLE_128B);
  }
  fused_kernel<<<NCTA, 384, SMEM_BYTES, cudaStreamPerThread>>>(m, x, wqkv, wphi, w1, w2, w3, w4, wo, gate_w, (__nv_bfloat16*)d_out);
}
```

```cpp
#include <cuda_runtime.h>
#include <cuda_bf16.h>
#include <cuda.h>
#include <stdint.h>

namespace {

constexpr int S_ = 2048, D_ = 640, F_ = 1536;
constexpr int NCTA = 128, NSVC = 4;
constexpr int KV_PAIR = 40 * 48 + 96;
constexpr int KV_J = 2 * KV_PAIR;

constexpr int SLOT_B = 49152, NB = 3;
constexpr int SLOT_A = 16384, NA = 4;
constexpr int OFF_B = 0;
constexpr int OFF_A = OFF_B + NB * SLOT_B;
constexpr int OFF_STG = OFF_A + 2 * SLOT_A;
constexpr int OFF_MISC = OFF_A + NA * SLOT_A;
constexpr int OFF_XST = OFF_MISC + 13312;
constexpr int OFF_CS = OFF_MISC + 16384;
constexpr int OFF_BAR = OFF_CS + 1088;
constexpr int SMEM_BYTES = OFF_BAR + 512 + 512 + 128;
constexpr int B_FULLA = 0, B_FULLB = 4, B_CS = 7, B_XR = 8, B_KV = 9, B_ST1 = 10, B_HST = 11, B_FULL4 = 12  , B_RDY = 20  ,
              B_DSR = 23  , B_EMPTYB = 33  , B_SIGP = 36, B_SIGH = 37, B_SIGKV = 38, B_SIGX1 = 39, B_MFREE = 40,
              B_EMPTY4 = 41  , B_EMPTYA = 49  , B_PEER = 53, B_PEER2 = 54, B_X1P = 55  , NBAR = 56;
constexpr int SPARE = 40960;
constexpr int SET4 = 87040, OFF_DS = 2 * SET4, OFF_OUT = 20480;

constexpr int FL_DONE = 0, FL_H = 1  , FL_X1 = FL_H + 32, FL_KV = FL_X1 + 16, FL_CS = FL_KV + 8, FL_CS3 = FL_CS + 1, FL_ST = FL_CS3 + 1;
constexpr int FL_S1 = FL_ST + 16, FL_COUNT = FL_S1 + 16;

struct Maps {
  CUtensorMap x, w1m, w1r, qm, qr, hs, w2, x1, w3, w4, wo, xr, st_h, st_x1;
};

}

__device__ __align__(1024) __nv_bfloat16 g_Hs[(S_ + 4) * D_];
__device__ __align__(1024) __nv_bfloat16 g_X1[S_ * D_];
__device__ __align__(128) float g_acc[2][8 * KV_J];
__device__ __align__(128) float g_cs[D_ + F_];
__device__ __align__(128) uint4 g_wphi[8 * 800];
__device__ __align__(128) float4 g_xstat[S_];
__device__ __align__(128) float2 g_st1[S_ * 8];
__device__ __align__(128) uint4 g_part[16 * 8 * 3 * 1280];
__device__ __align__(128) unsigned g_flags[FL_COUNT * 32];
#define TSTAMP(n) do {} while (0)
#define TSTAMPX(n) do {} while (0)
#define TRACE(n) do {} while (0)
#define TRS(n) do {} while (0)

namespace {

__device__ __forceinline__ long long gtime() { long long t; asm volatile("mov.u64 %0, %%globaltimer;" : "=l"(t)); return t; }
__device__ __forceinline__ uint32_t smem_u32(const void* p) { return (uint32_t)__cvta_generic_to_shared(p); }
__device__ __forceinline__ void mbar_init(uint32_t bar, int cnt) {
  asm volatile("mbarrier.init.shared::cta.b64 [%0], %1;" ::"r"(bar), "r"(cnt) : "memory");
}
__device__ __forceinline__ void mbar_expect_tx(uint32_t bar, int bytes) {
  asm volatile("mbarrier.arrive.expect_tx.shared::cta.b64 _, [%0], %1;" ::"r"(bar), "r"(bytes) : "memory");
}
__device__ __forceinline__ void mbar_arrive_cta(uint32_t bar, uint32_t cta) {
  asm volatile("{\n.reg .b32 ra;\nmapa.shared::cluster.u32 ra, %0, %1;\nmbarrier.arrive.shared::cluster.b64 _, [ra];\n}"
               ::"r"(bar), "r"(cta) : "memory");
}
__device__ __forceinline__ uint32_t mbar_try(uint32_t bar, uint32_t parity) {
  uint32_t ok;
  asm volatile("{\n.reg .pred p;\nmbarrier.try_wait.parity.shared::cta.b64 p, [%1], %2;\nselp.u32 %0, 1, 0, p;\n}"
               : "=r"(ok) : "r"(bar), "r"(parity) : "memory");
  return ok;
}
constexpr uint32_t WAIT_LIMIT = 1u << 18;
__device__ __forceinline__ void mbar_wait(uint32_t bar, uint32_t parity) {
  uint32_t n = 0;
  while (!mbar_try(bar, parity) && ++n < WAIT_LIMIT) {}
}
__device__ __forceinline__ unsigned ld_acquire(const unsigned* p) {
  unsigned v;
  asm volatile("ld.acquire.gpu.global.u32 %0, [%1];" : "=r"(v) : "l"(p) : "memory");
  return v;
}
__device__ __forceinline__ void flag_wait(int idx, unsigned target) {
  const unsigned* p = g_flags + idx * 32;
  uint32_t n = 0;
  while ((int)(ld_acquire(p) - target) < 0 && ++n < (WAIT_LIMIT >> 2)) {}
}
__device__ __forceinline__ void flag_add(int idx) {
  asm volatile("red.release.gpu.global.add.u32 [%0], 1;" ::"l"(g_flags + idx * 32) : "memory");
}
__device__ __forceinline__ void flag_add_relaxed(int idx) {
  asm volatile("red.relaxed.gpu.global.add.u32 [%0], 1;" ::"l"(g_flags + idx * 32) : "memory");
}
__device__ __forceinline__ uint32_t mbar_test(uint32_t bar, uint32_t parity) {
  uint32_t ok;
  asm volatile("{\n.reg .pred p;\nmbarrier.test_wait.parity.shared::cta.b64 p, [%1], %2;\nselp.u32 %0, 1, 0, p;\n}"
               : "=r"(ok) : "r"(bar), "r"(parity) : "memory");
  return ok;
}
__device__ __forceinline__ uint32_t lds32(uint32_t a) {
  uint32_t v;
  asm volatile("ld.shared.u32 %0, [%1];" : "=r"(v) : "r"(a) : "memory");
  return v;
}
__device__ __forceinline__ void mbar_arrive(uint32_t bar) {
  asm volatile("mbarrier.arrive.shared::cta.b64 _, [%0];" ::"r"(bar) : "memory");
}
__device__ __forceinline__ void fence_async_glb() { asm volatile("fence.proxy.async.global;" ::: "memory"); }
__device__ __forceinline__ void fence_async_smem() { asm volatile("fence.proxy.async.shared::cta;" ::: "memory"); }
__device__ __forceinline__ void bar_sync(int id, int n) { asm volatile("bar.sync %0, %1;" ::"r"(id), "r"(n) : "memory"); }

__device__ __forceinline__ void tma2d(uint32_t dst, const CUtensorMap* m, uint32_t bar, int c0, int c1) {
  asm volatile("cp.async.bulk.tensor.2d.shared::cluster.global.mbarrier::complete_tx::bytes [%0], [%1, {%3, %4}], [%2];"
               ::"r"(dst), "l"(m), "r"(bar), "r"(c0), "r"(c1) : "memory");
}
__device__ __forceinline__ void tma2d_mc(uint32_t dst, const CUtensorMap* m, uint32_t bar, int c0, int c1) {
  asm volatile("cp.async.bulk.tensor.2d.shared::cluster.global.mbarrier::complete_tx::bytes.multicast::cluster"
               " [%0], [%1, {%3, %4}], [%2], %5;"
               ::"r"(dst), "l"(m), "r"(bar), "r"(c0), "r"(c1), "h"((uint16_t)3) : "memory");
}
__device__ __forceinline__ void tma3d(uint32_t dst, const CUtensorMap* m, uint32_t bar, int c0, int c1, int c2) {
  asm volatile("cp.async.bulk.tensor.3d.shared::cluster.global.mbarrier::complete_tx::bytes [%0], [%1, {%3, %4, %5}], [%2];"
               ::"r"(dst), "l"(m), "r"(bar), "r"(c0), "r"(c1), "r"(c2) : "memory");
}
__device__ __forceinline__ void tma4d(uint32_t dst, const CUtensorMap* m, uint32_t bar, int c0, int c1, int c2, int c3) {
  asm volatile("cp.async.bulk.tensor.4d.shared::cluster.global.mbarrier::complete_tx::bytes [%0], [%1, {%3, %4, %5, %6}], [%2];"
               ::"r"(dst), "l"(m), "r"(bar), "r"(c0), "r"(c1), "r"(c2), "r"(c3) : "memory");
}
__device__ __forceinline__ void tma2d_store(const CUtensorMap* m, uint32_t src, int c0, int c1) {
  asm volatile("cp.async.bulk.tensor.2d.global.shared::cta.bulk_group [%0, {%2, %3}], [%1];"
               ::"l"(m), "r"(src), "r"(c0), "r"(c1) : "memory");
}
__device__ __forceinline__ void bulk_store(void* dst, uint32_t src, uint32_t bytes) {
  asm volatile("cp.async.bulk.global.shared::cta.bulk_group [%0], [%1], %2;" ::"l"(dst), "r"(src), "r"(bytes) : "memory");
}
__device__ __forceinline__ void bulk_load(uint32_t dst, const void* src, uint32_t bytes, uint32_t bar) {
  asm volatile("cp.async.bulk.shared::cluster.global.mbarrier::complete_tx::bytes [%0], [%1], %2, [%3];"
               ::"r"(dst), "l"(src), "r"(bytes), "r"(bar) : "memory");
}
__device__ __forceinline__ void bulk_commit() { asm volatile("cp.async.bulk.commit_group;" ::: "memory"); }
template <int N> __device__ __forceinline__ void bulk_wait() { asm volatile("cp.async.bulk.wait_group %0;" ::"n"(N) : "memory"); }
__device__ __forceinline__ void bulk_wait_read() { asm volatile("cp.async.bulk.wait_group.read 0;" ::: "memory"); }
__device__ __forceinline__ void bar_arrive(int id, int n) { asm volatile("bar.arrive %0, %1;" ::"r"(id), "r"(n) : "memory"); }
__device__ __forceinline__ uint4 lds128(uint32_t a) {
  uint4 v;
  asm volatile("ld.shared.v4.u32 {%0, %1, %2, %3}, [%4];" : "=r"(v.x), "=r"(v.y), "=r"(v.z), "=r"(v.w) : "r"(a) : "memory");
  return v;
}
__device__ __forceinline__ void sts128(uint32_t a, uint4 v) {
  asm volatile("st.shared.v4.u32 [%0], {%1, %2, %3, %4};" ::"r"(a), "r"(v.x), "r"(v.y), "r"(v.z), "r"(v.w) : "memory");
}
__device__ __forceinline__ uint4 ld_relaxed16(const uint4* p) {
  uint4 v;
  asm volatile("ld.relaxed.gpu.global.v4.u32 {%0, %1, %2, %3}, [%4];" : "=r"(v.x), "=r"(v.y), "=r"(v.z), "=r"(v.w) : "l"(p) : "memory");
  return v;
}
__device__ __forceinline__ void st_relaxed16(uint4* p, uint32_t a, uint32_t b, uint32_t c, uint32_t d) {
  asm volatile("st.relaxed.gpu.global.v4.u32 [%0], {%1, %2, %3, %4};" ::"l"(p), "r"(a), "r"(b), "r"(c), "r"(d) : "memory");
}
__device__ __forceinline__ uint32_t map_peer(uint32_t addr, uint32_t cta) {
  uint32_t r;
  asm("mapa.shared::cluster.u32 %0, %1, %2;" : "=r"(r) : "r"(addr), "r"(cta));
  return r;
}
__device__ __forceinline__ void st_async16(uint32_t addr, uint32_t a, uint32_t b, uint32_t c, uint32_t d, uint32_t bar) {
  asm volatile("st.async.weak.shared::cluster.mbarrier::complete_tx::bytes.v4.b32 [%0], {%1, %2, %3, %4}, [%5];"
               ::"r"(addr), "r"(a), "r"(b), "r"(c), "r"(d), "r"(bar) : "memory");
}
__device__ __forceinline__ void l2_prefetch(const void* p, uint32_t bytes) {
  asm volatile("cp.async.bulk.prefetch.L2.global [%0], %1;" ::"l"(p), "r"(bytes) : "memory");
}
__device__ __forceinline__ void prefetch_tmap(const CUtensorMap* m) {
  asm volatile("prefetch.tensormap [%0];" ::"l"(m) : "memory");
}
__device__ __forceinline__ uint64_t make_desc(uint32_t a16, uint32_t off, uint32_t lbo, uint32_t sbo, uint32_t swz) {
  const uint32_t lo = a16 + ((off >> 4) + ((lbo >> 4) << 16)), hi = (sbo >> 4) | (swz << 30);
  uint64_t d;
  asm("mov.b64 %0, {%1, %2};" : "=l"(d) : "r"(lo), "r"(hi));
  return d;
}
__device__ __forceinline__ void wg_fence() { asm volatile("wgmma.fence.sync.aligned;" ::: "memory"); }
__device__ __forceinline__ void wg_commit() { asm volatile("wgmma.commit_group.sync.aligned;" ::: "memory"); }
template <int N> __device__ __forceinline__ void wg_wait() { asm volatile("wgmma.wait_group.sync.aligned %0;" ::"n"(N) : "memory"); }
template <int N> __device__ __forceinline__ void fence_regs(float (&d)[N]) {
#pragma unroll
  for (int i = 0; i < N; i++) asm volatile("" : "+f"(d[i])::"memory");
}
template <int N> __device__ __forceinline__ void zero_regs(float (&d)[N]) {
#pragma unroll
  for (int i = 0; i < N; i++) d[i] = 0.f;
}
__device__ __forceinline__ uint32_t pack_bf16(float lo, float hi) {
  uint32_t r;
  asm("cvt.rn.bf16x2.f32 %0, %1, %2;" : "=r"(r) : "f"(hi), "f"(lo));
  return r;
}
__device__ __forceinline__ float bf_lo(uint32_t v) { return __uint_as_float(v << 16); }
__device__ __forceinline__ float bf_hi(uint32_t v) { return __uint_as_float(v & 0xffff0000u); }
__device__ __forceinline__ uint32_t max_bf2(uint32_t a, uint32_t b) {
  uint32_t r; asm("max.bf16x2 %0, %1, %2;" : "=r"(r) : "r"(a), "r"(b)); return r;
}
__device__ __forceinline__ uint32_t min_bf2(uint32_t a, uint32_t b) {
  uint32_t r; asm("min.bf16x2 %0, %1, %2;" : "=r"(r) : "r"(a), "r"(b)); return r;
}
__device__ __forceinline__ uint32_t add_bf2(uint32_t a, uint32_t b) {
  uint32_t r; asm("add.rn.bf16x2 %0, %1, %2;" : "=r"(r) : "r"(a), "r"(b)); return r;
}
__device__ __forceinline__ float ex2(float x) { float r; asm("ex2.approx.ftz.f32 %0, %1;" : "=f"(r) : "f"(x)); return r; }
__device__ __forceinline__ float rcp(float x) { float r; asm("rcp.approx.ftz.f32 %0, %1;" : "=f"(r) : "f"(x)); return r; }
__device__ __forceinline__ float tanh_ap(float x) { float r; asm("tanh.approx.f32 %0, %1;" : "=f"(r) : "f"(x)); return r; }
struct GeluC { float c0, c1, ch; };
__device__ __forceinline__ GeluC gelu_consts(float rstd, float scale) {
  return GeluC{0.7978845608f * rstd, 0.0356774081f * rstd * rstd * rstd, 0.5f * scale * rstd};
}
__device__ __forceinline__ float gelu_s(float y, const GeluC& c) {
  const float u = y * fmaf(y * y, c.c1, c.c0);
  const float hx = y * c.ch;
  return fmaf(hx, tanh_ap(u), hx);
}
__device__ __forceinline__ void stsm4(uint32_t addr, uint32_t r0, uint32_t r1, uint32_t r2, uint32_t r3) {
  asm volatile("stmatrix.sync.aligned.m8n8.x4.shared.b16 [%0], {%1, %2, %3, %4};"
               ::"r"(addr), "r"(r0), "r"(r1), "r"(r2), "r"(r3) : "memory");
}

__device__ __forceinline__ void mma_ss256(float (&d)[128], uint64_t descA, uint64_t descB) {
  asm volatile("wgmma.mma_async.sync.aligned.m64n256k16.f32.bf16.bf16 {"
      "%0, %1, %2, %3, %4, %5, %6, %7, %8, %9, %10, %11, %12, %13, %14, %15, "
      "%16, %17, %18, %19, %20, %21, %22, %23, %24, %25, %26, %27, %28, %29, %30, %31, "
      "%32, %33, %34, %35, %36, %37, %38, %39, %40, %41, %42, %43, %44, %45, %46, %47, "
      "%48, %49, %50, %51, %52, %53, %54, %55, %56, %57, %58, %59, %60, %61, %62, %63, "
      "%64, %65, %66, %67, %68, %69, %70, %71, %72, %73, %74, %75, %76, %77, %78, %79, "
      "%80, %81, %82, %83, %84, %85, %86, %87, %88, %89, %90, %91, %92, %93, %94, %95, "
      "%96, %97, %98, %99, %100, %101, %102, %103, %104, %105, %106, %107, %108, %109, %110, %111, "
      "%112, %113, %114, %115, %116, %117, %118, %119, %120, %121, %122, %123, %124, %125, %126, %127"
      "}, %128, %129, 1, 1, 1, 0, 1;\n"
      : "+f"(d[0]), "+f"(d[1]), "+f"(d[2]), "+f"(d[3]), "+f"(d[4]), "+f"(d[5]), "+f"(d[6]), "+f"(d[7]),
        "+f"(d[8]), "+f"(d[9]), "+f"(d[10]), "+f"(d[11]), "+f"(d[12]), "+f"(d[13]), "+f"(d[14]), "+f"(d[15]),
        "+f"(d[16]), "+f"(d[17]), "+f"(d[18]), "+f"(d[19]), "+f"(d[20]), "+f"(d[21]), "+f"(d[22]), "+f"(d[23]),
        "+f"(d[24]), "+f"(d[25]), "+f"(d[26]), "+f"(d[27]), "+f"(d[28]), "+f"(d[29]), "+f"(d[30]), "+f"(d[31]),
        "+f"(d[32]), "+f"(d[33]), "+f"(d[34]), "+f"(d[35]), "+f"(d[36]), "+f"(d[37]), "+f"(d[38]), "+f"(d[39]),
        "+f"(d[40]), "+f"(d[41]), "+f"(d[42]), "+f"(d[43]), "+f"(d[44]), "+f"(d[45]), "+f"(d[46]), "+f"(d[47]),
        "+f"(d[48]), "+f"(d[49]), "+f"(d[50]), "+f"(d[51]), "+f"(d[52]), "+f"(d[53]), "+f"(d[54]), "+f"(d[55]),
        "+f"(d[56]), "+f"(d[57]), "+f"(d[58]), "+f"(d[59]), "+f"(d[60]), "+f"(d[61]), "+f"(d[62]), "+f"(d[63]),
        "+f"(d[64]), "+f"(d[65]), "+f"(d[66]), "+f"(d[67]), "+f"(d[68]), "+f"(d[69]), "+f"(d[70]), "+f"(d[71]),
        "+f"(d[72]), "+f"(d[73]), "+f"(d[74]), "+f"(d[75]), "+f"(d[76]), "+f"(d[77]), "+f"(d[78]), "+f"(d[79]),
        "+f"(d[80]), "+f"(d[81]), "+f"(d[82]), "+f"(d[83]), "+f"(d[84]), "+f"(d[85]), "+f"(d[86]), "+f"(d[87]),
        "+f"(d[88]), "+f"(d[89]), "+f"(d[90]), "+f"(d[91]), "+f"(d[92]), "+f"(d[93]), "+f"(d[94]), "+f"(d[95]),
        "+f"(d[96]), "+f"(d[97]), "+f"(d[98]), "+f"(d[99]), "+f"(d[100]), "+f"(d[101]), "+f"(d[102]), "+f"(d[103]),
        "+f"(d[104]), "+f"(d[105]), "+f"(d[106]), "+f"(d[107]), "+f"(d[108]), "+f"(d[109]), "+f"(d[110]), "+f"(d[111]),
        "+f"(d[112]), "+f"(d[113]), "+f"(d[114]), "+f"(d[115]), "+f"(d[116]), "+f"(d[117]), "+f"(d[118]), "+f"(d[119]),
        "+f"(d[120]), "+f"(d[121]), "+f"(d[122]), "+f"(d[123]), "+f"(d[124]), "+f"(d[125]), "+f"(d[126]), "+f"(d[127])
      : "l"(descA), "l"(descB));
}
__device__ __forceinline__ void mma_ss256_p(float (&d)[128], uint64_t descA, uint64_t descB, int acc) {
  asm volatile("{\n.reg .pred p;\nsetp.ne.b32 p, %130, 0;\n"
      "wgmma.mma_async.sync.aligned.m64n256k16.f32.bf16.bf16 {"
      "%0, %1, %2, %3, %4, %5, %6, %7, %8, %9, %10, %11, %12, %13, %14, %15, "
      "%16, %17, %18, %19, %20, %21, %22, %23, %24, %25, %26, %27, %28, %29, %30, %31, "
      "%32, %33, %34, %35, %36, %37, %38, %39, %40, %41, %42, %43, %44, %45, %46, %47, "
      "%48, %49, %50, %51, %52, %53, %54, %55, %56, %57, %58, %59, %60, %61, %62, %63, "
      "%64, %65, %66, %67, %68, %69, %70, %71, %72, %73, %74, %75, %76, %77, %78, %79, "
      "%80, %81, %82, %83, %84, %85, %86, %87, %88, %89, %90, %91, %92, %93, %94, %95, "
      "%96, %97, %98, %99, %100, %101, %102, %103, %104, %105, %106, %107, %108, %109, %110, %111, "
      "%112, %113, %114, %115, %116, %117, %118, %119, %120, %121, %122, %123, %124, %125, %126, %127"
      "}, %128, %129, p, 1, 1, 0, 1;\n}\n"
      : "+f"(d[0]), "+f"(d[1]), "+f"(d[2]), "+f"(d[3]), "+f"(d[4]), "+f"(d[5]), "+f"(d[6]), "+f"(d[7]),
        "+f"(d[8]), "+f"(d[9]), "+f"(d[10]), "+f"(d[11]), "+f"(d[12]), "+f"(d[13]), "+f"(d[14]), "+f"(d[15]),
        "+f"(d[16]), "+f"(d[17]), "+f"(d[18]), "+f"(d[19]), "+f"(d[20]), "+f"(d[21]), "+f"(d[22]), "+f"(d[23]),
        "+f"(d[24]), "+f"(d[25]), "+f"(d[26]), "+f"(d[27]), "+f"(d[28]), "+f"(d[29]), "+f"(d[30]), "+f"(d[31]),
        "+f"(d[32]), "+f"(d[33]), "+f"(d[34]), "+f"(d[35]), "+f"(d[36]), "+f"(d[37]), "+f"(d[38]), "+f"(d[39]),
        "+f"(d[40]), "+f"(d[41]), "+f"(d[42]), "+f"(d[43]), "+f"(d[44]), "+f"(d[45]), "+f"(d[46]), "+f"(d[47]),
        "+f"(d[48]), "+f"(d[49]), "+f"(d[50]), "+f"(d[51]), "+f"(d[52]), "+f"(d[53]), "+f"(d[54]), "+f"(d[55]),
        "+f"(d[56]), "+f"(d[57]), "+f"(d[58]), "+f"(d[59]), "+f"(d[60]), "+f"(d[61]), "+f"(d[62]), "+f"(d[63]),
        "+f"(d[64]), "+f"(d[65]), "+f"(d[66]), "+f"(d[67]), "+f"(d[68]), "+f"(d[69]), "+f"(d[70]), "+f"(d[71]),
        "+f"(d[72]), "+f"(d[73]), "+f"(d[74]), "+f"(d[75]), "+f"(d[76]), "+f"(d[77]), "+f"(d[78]), "+f"(d[79]),
        "+f"(d[80]), "+f"(d[81]), "+f"(d[82]), "+f"(d[83]), "+f"(d[84]), "+f"(d[85]), "+f"(d[86]), "+f"(d[87]),
        "+f"(d[88]), "+f"(d[89]), "+f"(d[90]), "+f"(d[91]), "+f"(d[92]), "+f"(d[93]), "+f"(d[94]), "+f"(d[95]),
        "+f"(d[96]), "+f"(d[97]), "+f"(d[98]), "+f"(d[99]), "+f"(d[100]), "+f"(d[101]), "+f"(d[102]), "+f"(d[103]),
        "+f"(d[104]), "+f"(d[105]), "+f"(d[106]), "+f"(d[107]), "+f"(d[108]), "+f"(d[109]), "+f"(d[110]), "+f"(d[111]),
        "+f"(d[112]), "+f"(d[113]), "+f"(d[114]), "+f"(d[115]), "+f"(d[116]), "+f"(d[117]), "+f"(d[118]), "+f"(d[119]),
        "+f"(d[120]), "+f"(d[121]), "+f"(d[122]), "+f"(d[123]), "+f"(d[124]), "+f"(d[125]), "+f"(d[126]), "+f"(d[127])
      : "l"(descA), "l"(descB), "r"(acc));
}

__device__ __forceinline__ void mma_ss64(float (&d)[32], uint64_t descA, uint64_t descB) {
  asm volatile("wgmma.mma_async.sync.aligned.m64n64k16.f32.bf16.bf16 {"
      "%0, %1, %2, %3, %4, %5, %6, %7, %8, %9, %10, %11, %12, %13, %14, %15, "
      "%16, %17, %18, %19, %20, %21, %22, %23, %24, %25, %26, %27, %28, %29, %30, %31"
      "}, %32, %33, 1, 1, 1, 0, 1;\n"
      : "+f"(d[0]), "+f"(d[1]), "+f"(d[2]), "+f"(d[3]), "+f"(d[4]), "+f"(d[5]), "+f"(d[6]), "+f"(d[7]),
        "+f"(d[8]), "+f"(d[9]), "+f"(d[10]), "+f"(d[11]), "+f"(d[12]), "+f"(d[13]), "+f"(d[14]), "+f"(d[15]),
        "+f"(d[16]), "+f"(d[17]), "+f"(d[18]), "+f"(d[19]), "+f"(d[20]), "+f"(d[21]), "+f"(d[22]), "+f"(d[23]),
        "+f"(d[24]), "+f"(d[25]), "+f"(d[26]), "+f"(d[27]), "+f"(d[28]), "+f"(d[29]), "+f"(d[30]), "+f"(d[31])
      : "l"(descA), "l"(descB));
}
__device__ __forceinline__ void mma_ss64_p(float (&d)[32], uint64_t descA, uint64_t descB, int acc) {
  asm volatile("{\n.reg .pred p;\nsetp.ne.b32 p, %34, 0;\n"
      "wgmma.mma_async.sync.aligned.m64n64k16.f32.bf16.bf16 {"
      "%0, %1, %2, %3, %4, %5, %6, %7, %8, %9, %10, %11, %12, %13, %14, %15, "
      "%16, %17, %18, %19, %20, %21, %22, %23, %24, %25, %26, %27, %28, %29, %30, %31"
      "}, %32, %33, p, 1, 1, 0, 1;\n}\n"
      : "+f"(d[0]), "+f"(d[1]), "+f"(d[2]), "+f"(d[3]), "+f"(d[4]), "+f"(d[5]), "+f"(d[6]), "+f"(d[7]),
        "+f"(d[8]), "+f"(d[9]), "+f"(d[10]), "+f"(d[11]), "+f"(d[12]), "+f"(d[13]), "+f"(d[14]), "+f"(d[15]),
        "+f"(d[16]), "+f"(d[17]), "+f"(d[18]), "+f"(d[19]), "+f"(d[20]), "+f"(d[21]), "+f"(d[22]), "+f"(d[23]),
        "+f"(d[24]), "+f"(d[25]), "+f"(d[26]), "+f"(d[27]), "+f"(d[28]), "+f"(d[29]), "+f"(d[30]), "+f"(d[31])
      : "l"(descA), "l"(descB), "r"(acc));
}

__device__ __forceinline__ void mma_ss160(float (&d)[80], uint64_t descA, uint64_t descB) {
  asm volatile("wgmma.mma_async.sync.aligned.m64n160k16.f32.bf16.bf16 {"
      "%0, %1, %2, %3, %4, %5, %6, %7, %8, %9, %10, %11, %12, %13, %14, %15, "
      "%16, %17, %18, %19, %20, %21, %22, %23, %24, %25, %26, %27, %28, %29, %30, %31, "
      "%32, %33, %34, %35, %36, %37, %38, %39, %40, %41, %42, %43, %44, %45, %46, %47, "
      "%48, %49, %50, %51, %52, %53, %54, %55, %56, %57, %58, %59, %60, %61, %62, %63, "
      "%64, %65, %66, %67, %68, %69, %70, %71, %72, %73, %74, %75, %76, %77, %78, %79"
      "}, %80, %81, 1, 1, 1, 0, 1;\n"
      : "+f"(d[0]), "+f"(d[1]), "+f"(d[2]), "+f"(d[3]), "+f"(d[4]), "+f"(d[5]), "+f"(d[6]), "+f"(d[7]),
        "+f"(d[8]), "+f"(d[9]), "+f"(d[10]), "+f"(d[11]), "+f"(d[12]), "+f"(d[13]), "+f"(d[14]), "+f"(d[15]),
        "+f"(d[16]), "+f"(d[17]), "+f"(d[18]), "+f"(d[19]), "+f"(d[20]), "+f"(d[21]), "+f"(d[22]), "+f"(d[23]),
        "+f"(d[24]), "+f"(d[25]), "+f"(d[26]), "+f"(d[27]), "+f"(d[28]), "+f"(d[29]), "+f"(d[30]), "+f"(d[31]),
        "+f"(d[32]), "+f"(d[33]), "+f"(d[34]), "+f"(d[35]), "+f"(d[36]), "+f"(d[37]), "+f"(d[38]), "+f"(d[39]),
        "+f"(d[40]), "+f"(d[41]), "+f"(d[42]), "+f"(d[43]), "+f"(d[44]), "+f"(d[45]), "+f"(d[46]), "+f"(d[47]),
        "+f"(d[48]), "+f"(d[49]), "+f"(d[50]), "+f"(d[51]), "+f"(d[52]), "+f"(d[53]), "+f"(d[54]), "+f"(d[55]),
        "+f"(d[56]), "+f"(d[57]), "+f"(d[58]), "+f"(d[59]), "+f"(d[60]), "+f"(d[61]), "+f"(d[62]), "+f"(d[63]),
        "+f"(d[64]), "+f"(d[65]), "+f"(d[66]), "+f"(d[67]), "+f"(d[68]), "+f"(d[69]), "+f"(d[70]), "+f"(d[71]),
        "+f"(d[72]), "+f"(d[73]), "+f"(d[74]), "+f"(d[75]), "+f"(d[76]), "+f"(d[77]), "+f"(d[78]), "+f"(d[79])
      : "l"(descA), "l"(descB));
}
__device__ __forceinline__ void mma_ss160_z(float (&d)[80], uint64_t descA, uint64_t descB) {
  asm volatile("wgmma.mma_async.sync.aligned.m64n160k16.f32.bf16.bf16 {"
      "%0, %1, %2, %3, %4, %5, %6, %7, %8, %9, %10, %11, %12, %13, %14, %15, "
      "%16, %17, %18, %19, %20, %21, %22, %23, %24, %25, %26, %27, %28, %29, %30, %31, "
      "%32, %33, %34, %35, %36, %37, %38, %39, %40, %41, %42, %43, %44, %45, %46, %47, "
      "%48, %49, %50, %51, %52, %53, %54, %55, %56, %57, %58, %59, %60, %61, %62, %63, "
      "%64, %65, %66, %67, %68, %69, %70, %71, %72, %73, %74, %75, %76, %77, %78, %79"
      "}, %80, %81, 0, 1, 1, 0, 1;\n"
      : "=f"(d[0]), "=f"(d[1]), "=f"(d[2]), "=f"(d[3]), "=f"(d[4]), "=f"(d[5]), "=f"(d[6]), "=f"(d[7]),
        "=f"(d[8]), "=f"(d[9]), "=f"(d[10]), "=f"(d[11]), "=f"(d[12]), "=f"(d[13]), "=f"(d[14]), "=f"(d[15]),
        "=f"(d[16]), "=f"(d[17]), "=f"(d[18]), "=f"(d[19]), "=f"(d[20]), "=f"(d[21]), "=f"(d[22]), "=f"(d[23]),
        "=f"(d[24]), "=f"(d[25]), "=f"(d[26]), "=f"(d[27]), "=f"(d[28]), "=f"(d[29]), "=f"(d[30]), "=f"(d[31]),
        "=f"(d[32]), "=f"(d[33]), "=f"(d[34]), "=f"(d[35]), "=f"(d[36]), "=f"(d[37]), "=f"(d[38]), "=f"(d[39]),
        "=f"(d[40]), "=f"(d[41]), "=f"(d[42]), "=f"(d[43]), "=f"(d[44]), "=f"(d[45]), "=f"(d[46]), "=f"(d[47]),
        "=f"(d[48]), "=f"(d[49]), "=f"(d[50]), "=f"(d[51]), "=f"(d[52]), "=f"(d[53]), "=f"(d[54]), "=f"(d[55]),
        "=f"(d[56]), "=f"(d[57]), "=f"(d[58]), "=f"(d[59]), "=f"(d[60]), "=f"(d[61]), "=f"(d[62]), "=f"(d[63]),
        "=f"(d[64]), "=f"(d[65]), "=f"(d[66]), "=f"(d[67]), "=f"(d[68]), "=f"(d[69]), "=f"(d[70]), "=f"(d[71]),
        "=f"(d[72]), "=f"(d[73]), "=f"(d[74]), "=f"(d[75]), "=f"(d[76]), "=f"(d[77]), "=f"(d[78]), "=f"(d[79])
      : "l"(descA), "l"(descB));
}

__device__ __forceinline__ void mma_ss192(float (&d)[96], uint64_t descA, uint64_t descB) {
  asm volatile("wgmma.mma_async.sync.aligned.m64n192k16.f32.bf16.bf16 {"
      "%0, %1, %2, %3, %4, %5, %6, %7, %8, %9, %10, %11, %12, %13, %14, %15, "
      "%16, %17, %18, %19, %20, %21, %22, %23, %24, %25, %26, %27, %28, %29, %30, %31, "
      "%32, %33, %34, %35, %36, %37, %38, %39, %40, %41, %42, %43, %44, %45, %46, %47, "
      "%48, %49, %50, %51, %52, %53, %54, %55, %56, %57, %58, %59, %60, %61, %62, %63, "
      "%64, %65, %66, %67, %68, %69, %70, %71, %72, %73, %74, %75, %76, %77, %78, %79, "
      "%80, %81, %82, %83, %84, %85, %86, %87, %88, %89, %90, %91, %92, %93, %94, %95"
      "}, %96, %97, 1, 1, 1, 0, 1;\n"
      : "+f"(d[0]), "+f"(d[1]), "+f"(d[2]), "+f"(d[3]), "+f"(d[4]), "+f"(d[5]), "+f"(d[6]), "+f"(d[7]),
        "+f"(d[8]), "+f"(d[9]), "+f"(d[10]), "+f"(d[11]), "+f"(d[12]), "+f"(d[13]), "+f"(d[14]), "+f"(d[15]),
        "+f"(d[16]), "+f"(d[17]), "+f"(d[18]), "+f"(d[19]), "+f"(d[20]), "+f"(d[21]), "+f"(d[22]), "+f"(d[23]),
        "+f"(d[24]), "+f"(d[25]), "+f"(d[26]), "+f"(d[27]), "+f"(d[28]), "+f"(d[29]), "+f"(d[30]), "+f"(d[31]),
        "+f"(d[32]), "+f"(d[33]), "+f"(d[34]), "+f"(d[35]), "+f"(d[36]), "+f"(d[37]), "+f"(d[38]), "+f"(d[39]),
        "+f"(d[40]), "+f"(d[41]), "+f"(d[42]), "+f"(d[43]), "+f"(d[44]), "+f"(d[45]), "+f"(d[46]), "+f"(d[47]),
        "+f"(d[48]), "+f"(d[49]), "+f"(d[50]), "+f"(d[51]), "+f"(d[52]), "+f"(d[53]), "+f"(d[54]), "+f"(d[55]),
        "+f"(d[56]), "+f"(d[57]), "+f"(d[58]), "+f"(d[59]), "+f"(d[60]), "+f"(d[61]), "+f"(d[62]), "+f"(d[63]),
        "+f"(d[64]), "+f"(d[65]), "+f"(d[66]), "+f"(d[67]), "+f"(d[68]), "+f"(d[69]), "+f"(d[70]), "+f"(d[71]),
        "+f"(d[72]), "+f"(d[73]), "+f"(d[74]), "+f"(d[75]), "+f"(d[76]), "+f"(d[77]), "+f"(d[78]), "+f"(d[79]),
        "+f"(d[80]), "+f"(d[81]), "+f"(d[82]), "+f"(d[83]), "+f"(d[84]), "+f"(d[85]), "+f"(d[86]), "+f"(d[87]),
        "+f"(d[88]), "+f"(d[89]), "+f"(d[90]), "+f"(d[91]), "+f"(d[92]), "+f"(d[93]), "+f"(d[94]), "+f"(d[95])
      : "l"(descA), "l"(descB));
}
__device__ __forceinline__ void mma_ss192_p(float (&d)[96], uint64_t descA, uint64_t descB, int acc) {
  asm volatile("{\n.reg .pred p;\nsetp.ne.b32 p, %98, 0;\n"
      "wgmma.mma_async.sync.aligned.m64n192k16.f32.bf16.bf16 {"
      "%0, %1, %2, %3, %4, %5, %6, %7, %8, %9, %10, %11, %12, %13, %14, %15, "
      "%16, %17, %18, %19, %20, %21, %22, %23, %24, %25, %26, %27, %28, %29, %30, %31, "
      "%32, %33, %34, %35, %36, %37, %38, %39, %40, %41, %42, %43, %44, %45, %46, %47, "
      "%48, %49, %50, %51, %52, %53, %54, %55, %56, %57, %58, %59, %60, %61, %62, %63, "
      "%64, %65, %66, %67, %68, %69, %70, %71, %72, %73, %74, %75, %76, %77, %78, %79, "
      "%80, %81, %82, %83, %84, %85, %86, %87, %88, %89, %90, %91, %92, %93, %94, %95"
      "}, %96, %97, p, 1, 1, 0, 1;\n}\n"
      : "+f"(d[0]), "+f"(d[1]), "+f"(d[2]), "+f"(d[3]), "+f"(d[4]), "+f"(d[5]), "+f"(d[6]), "+f"(d[7]),
        "+f"(d[8]), "+f"(d[9]), "+f"(d[10]), "+f"(d[11]), "+f"(d[12]), "+f"(d[13]), "+f"(d[14]), "+f"(d[15]),
        "+f"(d[16]), "+f"(d[17]), "+f"(d[18]), "+f"(d[19]), "+f"(d[20]), "+f"(d[21]), "+f"(d[22]), "+f"(d[23]),
        "+f"(d[24]), "+f"(d[25]), "+f"(d[26]), "+f"(d[27]), "+f"(d[28]), "+f"(d[29]), "+f"(d[30]), "+f"(d[31]),
        "+f"(d[32]), "+f"(d[33]), "+f"(d[34]), "+f"(d[35]), "+f"(d[36]), "+f"(d[37]), "+f"(d[38]), "+f"(d[39]),
        "+f"(d[40]), "+f"(d[41]), "+f"(d[42]), "+f"(d[43]), "+f"(d[44]), "+f"(d[45]), "+f"(d[46]), "+f"(d[47]),
        "+f"(d[48]), "+f"(d[49]), "+f"(d[50]), "+f"(d[51]), "+f"(d[52]), "+f"(d[53]), "+f"(d[54]), "+f"(d[55]),
        "+f"(d[56]), "+f"(d[57]), "+f"(d[58]), "+f"(d[59]), "+f"(d[60]), "+f"(d[61]), "+f"(d[62]), "+f"(d[63]),
        "+f"(d[64]), "+f"(d[65]), "+f"(d[66]), "+f"(d[67]), "+f"(d[68]), "+f"(d[69]), "+f"(d[70]), "+f"(d[71]),
        "+f"(d[72]), "+f"(d[73]), "+f"(d[74]), "+f"(d[75]), "+f"(d[76]), "+f"(d[77]), "+f"(d[78]), "+f"(d[79]),
        "+f"(d[80]), "+f"(d[81]), "+f"(d[82]), "+f"(d[83]), "+f"(d[84]), "+f"(d[85]), "+f"(d[86]), "+f"(d[87]),
        "+f"(d[88]), "+f"(d[89]), "+f"(d[90]), "+f"(d[91]), "+f"(d[92]), "+f"(d[93]), "+f"(d[94]), "+f"(d[95])
      : "l"(descA), "l"(descB), "r"(acc));
}

__device__ __forceinline__ void mma_ss80_tt(float (&d)[40], uint64_t descA, uint64_t descB) {
  asm volatile("wgmma.mma_async.sync.aligned.m64n80k16.f32.bf16.bf16 {"
      "%0, %1, %2, %3, %4, %5, %6, %7, %8, %9, %10, %11, %12, %13, %14, %15, "
      "%16, %17, %18, %19, %20, %21, %22, %23, %24, %25, %26, %27, %28, %29, %30, %31, "
      "%32, %33, %34, %35, %36, %37, %38, %39"
      "}, %40, %41, 1, 1, 1, 1, 1;\n"
      : "+f"(d[0]), "+f"(d[1]), "+f"(d[2]), "+f"(d[3]), "+f"(d[4]), "+f"(d[5]), "+f"(d[6]), "+f"(d[7]),
        "+f"(d[8]), "+f"(d[9]), "+f"(d[10]), "+f"(d[11]), "+f"(d[12]), "+f"(d[13]), "+f"(d[14]), "+f"(d[15]),
        "+f"(d[16]), "+f"(d[17]), "+f"(d[18]), "+f"(d[19]), "+f"(d[20]), "+f"(d[21]), "+f"(d[22]), "+f"(d[23]),
        "+f"(d[24]), "+f"(d[25]), "+f"(d[26]), "+f"(d[27]), "+f"(d[28]), "+f"(d[29]), "+f"(d[30]), "+f"(d[31]),
        "+f"(d[32]), "+f"(d[33]), "+f"(d[34]), "+f"(d[35]), "+f"(d[36]), "+f"(d[37]), "+f"(d[38]), "+f"(d[39])
      : "l"(descA), "l"(descB));
}
__device__ __forceinline__ void mma_ss80_tt_z(float (&d)[40], uint64_t descA, uint64_t descB) {
  asm volatile("wgmma.mma_async.sync.aligned.m64n80k16.f32.bf16.bf16 {"
      "%0, %1, %2, %3, %4, %5, %6, %7, %8, %9, %10, %11, %12, %13, %14, %15, "
      "%16, %17, %18, %19, %20, %21, %22, %23, %24, %25, %26, %27, %28, %29, %30, %31, "
      "%32, %33, %34, %35, %36, %37, %38, %39"
      "}, %40, %41, 0, 1, 1, 1, 1;\n"
      : "=f"(d[0]), "=f"(d[1]), "=f"(d[2]), "=f"(d[3]), "=f"(d[4]), "=f"(d[5]), "=f"(d[6]), "=f"(d[7]),
        "=f"(d[8]), "=f"(d[9]), "=f"(d[10]), "=f"(d[11]), "=f"(d[12]), "=f"(d[13]), "=f"(d[14]), "=f"(d[15]),
        "=f"(d[16]), "=f"(d[17]), "=f"(d[18]), "=f"(d[19]), "=f"(d[20]), "=f"(d[21]), "=f"(d[22]), "=f"(d[23]),
        "=f"(d[24]), "=f"(d[25]), "=f"(d[26]), "=f"(d[27]), "=f"(d[28]), "=f"(d[29]), "=f"(d[30]), "=f"(d[31]),
        "=f"(d[32]), "=f"(d[33]), "=f"(d[34]), "=f"(d[35]), "=f"(d[36]), "=f"(d[37]), "=f"(d[38]), "=f"(d[39])
      : "l"(descA), "l"(descB));
}

__device__ __forceinline__ void mma_rs80_k(float (&d)[40], const uint32_t (&a)[4], uint64_t descB) {
  asm volatile("wgmma.mma_async.sync.aligned.m64n80k16.f32.bf16.bf16 {"
      "%0, %1, %2, %3, %4, %5, %6, %7, %8, %9, %10, %11, %12, %13, %14, %15, "
      "%16, %17, %18, %19, %20, %21, %22, %23, %24, %25, %26, %27, %28, %29, %30, %31, "
      "%32, %33, %34, %35, %36, %37, %38, %39"
      "}, {%40, %41, %42, %43}, %44, 1, 1, 1, 0;\n"
      : "+f"(d[0]), "+f"(d[1]), "+f"(d[2]), "+f"(d[3]), "+f"(d[4]), "+f"(d[5]), "+f"(d[6]), "+f"(d[7]),
        "+f"(d[8]), "+f"(d[9]), "+f"(d[10]), "+f"(d[11]), "+f"(d[12]), "+f"(d[13]), "+f"(d[14]), "+f"(d[15]),
        "+f"(d[16]), "+f"(d[17]), "+f"(d[18]), "+f"(d[19]), "+f"(d[20]), "+f"(d[21]), "+f"(d[22]), "+f"(d[23]),
        "+f"(d[24]), "+f"(d[25]), "+f"(d[26]), "+f"(d[27]), "+f"(d[28]), "+f"(d[29]), "+f"(d[30]), "+f"(d[31]),
        "+f"(d[32]), "+f"(d[33]), "+f"(d[34]), "+f"(d[35]), "+f"(d[36]), "+f"(d[37]), "+f"(d[38]), "+f"(d[39])
      : "r"(a[0]), "r"(a[1]), "r"(a[2]), "r"(a[3]), "l"(descB));
}
__device__ __forceinline__ void mma_rs80_k_z(float (&d)[40], const uint32_t (&a)[4], uint64_t descB) {
  asm volatile("wgmma.mma_async.sync.aligned.m64n80k16.f32.bf16.bf16 {"
      "%0, %1, %2, %3, %4, %5, %6, %7, %8, %9, %10, %11, %12, %13, %14, %15, "
      "%16, %17, %18, %19, %20, %21, %22, %23, %24, %25, %26, %27, %28, %29, %30, %31, "
      "%32, %33, %34, %35, %36, %37, %38, %39"
      "}, {%40, %41, %42, %43}, %44, 0, 1, 1, 0;\n"
      : "=f"(d[0]), "=f"(d[1]), "=f"(d[2]), "=f"(d[3]), "=f"(d[4]), "=f"(d[5]), "=f"(d[6]), "=f"(d[7]),
        "=f"(d[8]), "=f"(d[9]), "=f"(d[10]), "=f"(d[11]), "=f"(d[12]), "=f"(d[13]), "=f"(d[14]), "=f"(d[15]),
        "=f"(d[16]), "=f"(d[17]), "=f"(d[18]), "=f"(d[19]), "=f"(d[20]), "=f"(d[21]), "=f"(d[22]), "=f"(d[23]),
        "=f"(d[24]), "=f"(d[25]), "=f"(d[26]), "=f"(d[27]), "=f"(d[28]), "=f"(d[29]), "=f"(d[30]), "=f"(d[31]),
        "=f"(d[32]), "=f"(d[33]), "=f"(d[34]), "=f"(d[35]), "=f"(d[36]), "=f"(d[37]), "=f"(d[38]), "=f"(d[39])
      : "r"(a[0]), "r"(a[1]), "r"(a[2]), "r"(a[3]), "l"(descB));
}

__device__ __forceinline__ void mma_rs48_k(float (&d)[24], const uint32_t (&a)[4], uint64_t descB) {
  asm volatile("wgmma.mma_async.sync.aligned.m64n48k16.f32.bf16.bf16 {"
      "%0, %1, %2, %3, %4, %5, %6, %7, %8, %9, %10, %11, %12, %13, %14, %15, "
      "%16, %17, %18, %19, %20, %21, %22, %23"
      "}, {%24, %25, %26, %27}, %28, 1, 1, 1, 0;\n"
      : "+f"(d[0]), "+f"(d[1]), "+f"(d[2]), "+f"(d[3]), "+f"(d[4]), "+f"(d[5]), "+f"(d[6]), "+f"(d[7]),
        "+f"(d[8]), "+f"(d[9]), "+f"(d[10]), "+f"(d[11]), "+f"(d[12]), "+f"(d[13]), "+f"(d[14]), "+f"(d[15]),
        "+f"(d[16]), "+f"(d[17]), "+f"(d[18]), "+f"(d[19]), "+f"(d[20]), "+f"(d[21]), "+f"(d[22]), "+f"(d[23])
      : "r"(a[0]), "r"(a[1]), "r"(a[2]), "r"(a[3]), "l"(descB));
}
__device__ __forceinline__ void mma_rs48_k_z(float (&d)[24], const uint32_t (&a)[4], uint64_t descB) {
  asm volatile("wgmma.mma_async.sync.aligned.m64n48k16.f32.bf16.bf16 {"
      "%0, %1, %2, %3, %4, %5, %6, %7, %8, %9, %10, %11, %12, %13, %14, %15, "
      "%16, %17, %18, %19, %20, %21, %22, %23"
      "}, {%24, %25, %26, %27}, %28, 0, 1, 1, 0;\n"
      : "=f"(d[0]), "=f"(d[1]), "=f"(d[2]), "=f"(d[3]), "=f"(d[4]), "=f"(d[5]), "=f"(d[6]), "=f"(d[7]),
        "=f"(d[8]), "=f"(d[9]), "=f"(d[10]), "=f"(d[11]), "=f"(d[12]), "=f"(d[13]), "=f"(d[14]), "=f"(d[15]),
        "=f"(d[16]), "=f"(d[17]), "=f"(d[18]), "=f"(d[19]), "=f"(d[20]), "=f"(d[21]), "=f"(d[22]), "=f"(d[23])
      : "r"(a[0]), "r"(a[1]), "r"(a[2]), "r"(a[3]), "l"(descB));
}

__device__ __forceinline__ void mma_rs160_n(float (&d)[80], const uint32_t (&a)[4], uint64_t descB) {
  asm volatile("wgmma.mma_async.sync.aligned.m64n160k16.f32.bf16.bf16 {"
      "%0, %1, %2, %3, %4, %5, %6, %7, %8, %9, %10, %11, %12, %13, %14, %15, "
      "%16, %17, %18, %19, %20, %21, %22, %23, %24, %25, %26, %27, %28, %29, %30, %31, "
      "%32, %33, %34, %35, %36, %37, %38, %39, %40, %41, %42, %43, %44, %45, %46, %47, "
      "%48, %49, %50, %51, %52, %53, %54, %55, %56, %57, %58, %59, %60, %61, %62, %63, "
      "%64, %65, %66, %67, %68, %69, %70, %71, %72, %73, %74, %75, %76, %77, %78, %79"
      "}, {%80, %81, %82, %83}, %84, 1, 1, 1, 1;\n"
      : "+f"(d[0]), "+f"(d[1]), "+f"(d[2]), "+f"(d[3]), "+f"(d[4]), "+f"(d[5]), "+f"(d[6]), "+f"(d[7]),
        "+f"(d[8]), "+f"(d[9]), "+f"(d[10]), "+f"(d[11]), "+f"(d[12]), "+f"(d[13]), "+f"(d[14]), "+f"(d[15]),
        "+f"(d[16]), "+f"(d[17]), "+f"(d[18]), "+f"(d[19]), "+f"(d[20]), "+f"(d[21]), "+f"(d[22]), "+f"(d[23]),
        "+f"(d[24]), "+f"(d[25]), "+f"(d[26]), "+f"(d[27]), "+f"(d[28]), "+f"(d[29]), "+f"(d[30]), "+f"(d[31]),
        "+f"(d[32]), "+f"(d[33]), "+f"(d[34]), "+f"(d[35]), "+f"(d[36]), "+f"(d[37]), "+f"(d[38]), "+f"(d[39]),
        "+f"(d[40]), "+f"(d[41]), "+f"(d[42]), "+f"(d[43]), "+f"(d[44]), "+f"(d[45]), "+f"(d[46]), "+f"(d[47]),
        "+f"(d[48]), "+f"(d[49]), "+f"(d[50]), "+f"(d[51]), "+f"(d[52]), "+f"(d[53]), "+f"(d[54]), "+f"(d[55]),
        "+f"(d[56]), "+f"(d[57]), "+f"(d[58]), "+f"(d[59]), "+f"(d[60]), "+f"(d[61]), "+f"(d[62]), "+f"(d[63]),
        "+f"(d[64]), "+f"(d[65]), "+f"(d[66]), "+f"(d[67]), "+f"(d[68]), "+f"(d[69]), "+f"(d[70]), "+f"(d[71]),
        "+f"(d[72]), "+f"(d[73]), "+f"(d[74]), "+f"(d[75]), "+f"(d[76]), "+f"(d[77]), "+f"(d[78]), "+f"(d[79])
      : "r"(a[0]), "r"(a[1]), "r"(a[2]), "r"(a[3]), "l"(descB));
}
__device__ __forceinline__ void mma_rs160_n_z(float (&d)[80], const uint32_t (&a)[4], uint64_t descB) {
  asm volatile("wgmma.mma_async.sync.aligned.m64n160k16.f32.bf16.bf16 {"
      "%0, %1, %2, %3, %4, %5, %6, %7, %8, %9, %10, %11, %12, %13, %14, %15, "
      "%16, %17, %18, %19, %20, %21, %22, %23, %24, %25, %26, %27, %28, %29, %30, %31, "
      "%32, %33, %34, %35, %36, %37, %38, %39, %40, %41, %42, %43, %44, %45, %46, %47, "
      "%48, %49, %50, %51, %52, %53, %54, %55, %56, %57, %58, %59, %60, %61, %62, %63, "
      "%64, %65, %66, %67, %68, %69, %70, %71, %72, %73, %74, %75, %76, %77, %78, %79"
      "}, {%80, %81, %82, %83}, %84, 0, 1, 1, 1;\n"
      : "=f"(d[0]), "=f"(d[1]), "=f"(d[2]), "=f"(d[3]), "=f"(d[4]), "=f"(d[5]), "=f"(d[6]), "=f"(d[7]),
        "=f"(d[8]), "=f"(d[9]), "=f"(d[10]), "=f"(d[11]), "=f"(d[12]), "=f"(d[13]), "=f"(d[14]), "=f"(d[15]),
        "=f"(d[16]), "=f"(d[17]), "=f"(d[18]), "=f"(d[19]), "=f"(d[20]), "=f"(d[21]), "=f"(d[22]), "=f"(d[23]),
        "=f"(d[24]), "=f"(d[25]), "=f"(d[26]), "=f"(d[27]), "=f"(d[28]), "=f"(d[29]), "=f"(d[30]), "=f"(d[31]),
        "=f"(d[32]), "=f"(d[33]), "=f"(d[34]), "=f"(d[35]), "=f"(d[36]), "=f"(d[37]), "=f"(d[38]), "=f"(d[39]),
        "=f"(d[40]), "=f"(d[41]), "=f"(d[42]), "=f"(d[43]), "=f"(d[44]), "=f"(d[45]), "=f"(d[46]), "=f"(d[47]),
        "=f"(d[48]), "=f"(d[49]), "=f"(d[50]), "=f"(d[51]), "=f"(d[52]), "=f"(d[53]), "=f"(d[54]), "=f"(d[55]),
        "=f"(d[56]), "=f"(d[57]), "=f"(d[58]), "=f"(d[59]), "=f"(d[60]), "=f"(d[61]), "=f"(d[62]), "=f"(d[63]),
        "=f"(d[64]), "=f"(d[65]), "=f"(d[66]), "=f"(d[67]), "=f"(d[68]), "=f"(d[69]), "=f"(d[70]), "=f"(d[71]),
        "=f"(d[72]), "=f"(d[73]), "=f"(d[74]), "=f"(d[75]), "=f"(d[76]), "=f"(d[77]), "=f"(d[78]), "=f"(d[79])
      : "r"(a[0]), "r"(a[1]), "r"(a[2]), "r"(a[3]), "l"(descB));
}

__device__ __forceinline__ void feature_map(const uint32_t (&P)[2][10], uint32_t (&fr)[10][4]) {
  constexpr float L2E = 1.4426950408889634f;
#pragma unroll
  for (int p = 0; p < 2; p++) {
#pragma unroll
    for (int r = 0; r < 2; r++) {
      uint32_t mx = P[r][5 * p], mn = mx;
#pragma unroll
      for (int g = 1; g < 5; g++) { mx = max_bf2(mx, P[r][5 * p + g]); mn = min_bf2(mn, P[r][5 * p + g]); }
      mx = max_bf2(mx, __shfl_xor_sync(0xffffffffu, mx, 1));
      mn = min_bf2(mn, __shfl_xor_sync(0xffffffffu, mn, 1));
      mx = max_bf2(mx, __shfl_xor_sync(0xffffffffu, mx, 2));
      mn = min_bf2(mn, __shfl_xor_sync(0xffffffffu, mn, 2));
      float mx0 = -bf_lo(mx) * L2E, mx1 = -bf_hi(mx) * L2E, mn0 = bf_lo(mn) * L2E, mn1 = bf_hi(mn) * L2E;
      float ep0[5], ep1[5], en0[5], en1[5];
      float sp0 = 0.f, sp1 = 0.f, sn0 = 0.f, sn1 = 0.f;
#pragma unroll
      for (int g = 0; g < 5; g++) {
        float x0 = bf_lo(P[r][5 * p + g]), x1 = bf_hi(P[r][5 * p + g]);
        ep0[g] = ex2(fmaf(x0, L2E, mx0)); ep1[g] = ex2(fmaf(x1, L2E, mx1));
        en0[g] = ex2(fmaf(x0, -L2E, mn0)); en1[g] = ex2(fmaf(x1, -L2E, mn1));
        sp0 += ep0[g]; sp1 += ep1[g]; sn0 += en0[g]; sn1 += en1[g];
      }
      sp0 += __shfl_xor_sync(0xffffffffu, sp0, 1); sp1 += __shfl_xor_sync(0xffffffffu, sp1, 1);
      sn0 += __shfl_xor_sync(0xffffffffu, sn0, 1); sn1 += __shfl_xor_sync(0xffffffffu, sn1, 1);
      sp0 += __shfl_xor_sync(0xffffffffu, sp0, 2); sp1 += __shfl_xor_sync(0xffffffffu, sp1, 2);
      sn0 += __shfl_xor_sync(0xffffffffu, sn0, 2); sn1 += __shfl_xor_sync(0xffffffffu, sn1, 2);
      sp0 = rcp(sp0); sp1 = rcp(sp1); sn0 = rcp(sn0); sn1 = rcp(sn1);
#pragma unroll
      for (int g = 0; g < 5; g++) {
        fr[5 * p + g][r] = pack_bf16(ep0[g] * sp0, ep1[g] * sp1);
        fr[5 * p + g][2 + r] = pack_bf16(en0[g] * sn0, en1[g] * sn1);
      }
    }
  }
}

template <int V> struct IntC { static constexpr int value = V; };
struct Ring {
  uint32_t idx, phase;
  template <int N> __device__ __forceinline__ void next() { if (++idx == N) { idx = 0; phase ^= 1; } }
};

}

__global__ void __cluster_dims__(2, 1, 1) __launch_bounds__(384, 1)
fused_kernel(const __grid_constant__ Maps maps, const __nv_bfloat16* __restrict__ x, const __nv_bfloat16* __restrict__ wqkv,
             const __nv_bfloat16* __restrict__ wphi, const __nv_bfloat16* __restrict__ w1, const __nv_bfloat16* __restrict__ w2,
             const __nv_bfloat16* __restrict__ w3, const __nv_bfloat16* __restrict__ w4, const __nv_bfloat16* __restrict__ wo,
             const __nv_bfloat16* __restrict__ gate_w, __nv_bfloat16* __restrict__ out) {
  extern __shared__ __align__(1024) uint8_t sgen[];
  const uint32_t sb = smem_u32(sgen);
  const uint32_t sb16 = (sb & 0x3FFFFu) >> 4;
  const uint32_t bars = sb + OFF_BAR;
  const uint32_t fullA = bars + 8 * B_FULLA, emptyA = bars + 8 * B_EMPTYA, fullB = bars + 8 * B_FULLB, emptyB = bars + 8 * B_EMPTYB;

  const int tid = threadIdx.x;
  const int rank = blockIdx.x & 1;
  const int bid = blockIdx.x - NSVC, pairIdx = bid >> 1;
  const int i = pairIdx >> 2, j = 2 * (pairIdx & 3) + rank;
  const int k3 = (5 * (pairIdx & 3) + 1) >> 1;

  if (bid < 0) {
    const int sv = blockIdx.x;
    const unsigned epoch = *reinterpret_cast<volatile unsigned*>(g_flags + FL_DONE * 32) / NCTA;
    float* red = reinterpret_cast<float*>(sgen);
    for (int e = tid; e < 1600; e += 384) sts128(sb + 32768 + e * 16, make_uint4(0, 0, 0, 0));
    __syncthreads();
    for (int e = tid; e < 3200; e += 384) {
      const int jj = e / 1600, idx = e - 1600 * jj, h = idx / 400, k = idx / 20, ff = idx - 20 * k;
      const int n = 40 * (h >> 1) + 8 * (ff >> 2) + 2 * (ff & 3) + (h & 1);
      const int off = jj * 12800 + (k >> 4) * 2560 + n * 32 + ((((k >> 3) ^ (n >> 2)) & 1) << 4) + (k & 7) * 2;
      *reinterpret_cast<__nv_bfloat16*>(sgen + 32768 + off) = wphi[sv * 3200 + e];
    }
    if (tid < 40 && (tid < 20 || sv >= 2))
      reinterpret_cast<uint4*>(g_Hs + (size_t)(2 + ((sv & 1) ? S_ - 1 - tid / 20 : tid / 20)) * D_ + 160 * sv)[tid % 20] = make_uint4(0, 0, 0, 0);
#pragma unroll 1
    for (int ph = 0; ph < 2; ph++) {
      const int nch = ph ? 48 : 20, nrg = ph ? 8 : 16, ld = ph ? F_ : D_;
      const int ch = tid % nch, rg = tid / nch;
      float a[8];
#pragma unroll
      for (int e = 0; e < 8; e++) a[e] = 0.f;
      if (rg < nrg) {
        const __nv_bfloat16* p = (ph ? w3 : w1) + (size_t)rg * ld + 8 * (nch * sv + ch);
#pragma unroll 20
        for (int r = 0; r < D_; r += nrg) {
          const uint4 v = __ldg(reinterpret_cast<const uint4*>(p + (size_t)r * ld));
          a[0] += bf_lo(v.x); a[1] += bf_hi(v.x); a[2] += bf_lo(v.y); a[3] += bf_hi(v.y);
          a[4] += bf_lo(v.z); a[5] += bf_hi(v.z); a[6] += bf_lo(v.w); a[7] += bf_hi(v.w);
        }
#pragma unroll
        for (int e = 0; e < 8; e++) red[tid * 8 + e] = a[e];
      }
      __syncthreads();
      if (tid < 8 * nch) {
        float t = 0.f;
        for (int r = 0; r < nrg; r++) t += red[r * nch * 8 + tid];
        g_cs[(ph ? D_ : 0) + 8 * nch * sv + tid] = t;
      }
      if (ph == 0)
        for (int e = tid; e < 1600; e += 384) g_wphi[sv * 1600 + e] = lds128(sb + 32768 + e * 16);
      __syncthreads();
      if (tid == 0) {
        flag_add(ph ? FL_CS3 : FL_CS);
        if (ph == 0) l2_prefetch(w2 + (size_t)sv * (D_ * D_ / NSVC), D_ * D_ * 2 / NSVC);
      }
    }
    for (int e = tid; e < 2 * KV_J; e += 384) g_acc[(epoch + 1) & 1][sv * 2 * KV_J + e] = 0.f;
    if (tid < 32) {
      l2_prefetch(w4 + (size_t)(sv * 32 + tid) * (F_ * D_ / 128), F_ * D_ * 2 / 128);
      l2_prefetch(wo + (size_t)(sv * 32 + tid) * (D_ * D_ / 128), D_ * D_ * 2 / 128);
    }
    return;
  }
  TSTAMP(0);
  auto load_p1_b = [&](int k, uint32_t slot, uint32_t bar) {
    mbar_expect_tx(bar, 40960);
    tma4d(slot + 8192, &maps.qm, bar, 0, 64 * k, 0, j);
    tma3d(slot, &maps.w1m, bar, 0, 64 * k, j);
    tma4d(slot + 32768 + 2048, &maps.qr, bar, 64, 64 * k, 0, j);
    tma3d(slot + 32768, &maps.w1r, bar, 64, 64 * k, j);
  };
  if (tid >= 256) {
    asm volatile("setmaxnreg.dec.sync.aligned.u32 40;");
    if (tid == 256) {
#pragma unroll
      for (int s = 0; s < NA; s++) mbar_init(fullA + 8 * s, 1);
      asm volatile("fence.mbarrier_init.release.cluster;" ::: "memory");
#pragma unroll 1
      for (int u = 0; u < 4; u++) {
        if ((u & 1) == 0) mbar_expect_tx(fullA + 4 * u, SLOT_A);
        tma2d(sb + OFF_A + u * 8192, &maps.x, fullA + 8 * (u >> 1), 64 * (u >> 1), 128 * i + 64 * (u & 1));
      }
    } else if (tid == 288) {
#pragma unroll
      for (int s = 0; s < NB; s++) mbar_init(fullB + 8 * s, 1);
      asm volatile("fence.mbarrier_init.release.cluster;" ::: "memory");
#pragma unroll 1
      for (int k = 0; k < 2; k++) load_p1_b(k, sb + OFF_B + k * SLOT_B, fullB + 8 * k);
      l2_prefetch(wqkv + (size_t)(128 + 4 * bid) * (3 * D_), 4 * 3 * D_ * 2);
    } else if (tid == 320) {
#pragma unroll
      for (int b = B_CS; b < NBAR; b++) mbar_init(bars + 8 * b, b < B_EMPTYB ? 1 : b < B_EMPTYA ? 8 : b < B_X1P ? 16 : 2);
#pragma unroll
      for (int b = B_DSR; b < B_EMPTYB; b++) mbar_expect_tx(bars + 8 * b, 10240);
      asm volatile("fence.mbarrier_init.release.cluster;" ::: "memory");
    }
    __syncwarp();
    asm volatile("barrier.cluster.arrive.relaxed.aligned;" ::: "memory");
    auto get_epoch = [&]() { return *reinterpret_cast<volatile unsigned*>(g_flags + FL_DONE * 32) / NCTA; };
    asm volatile("barrier.cluster.wait.aligned;" ::: "memory");
    const int lane = tid & 31, pw = (tid >> 5) & 3;
    if (pw == 0) {
      if (tid == 256) {
        Ring r{2, 1};
        unsigned ep1 = 0;
#pragma unroll 1
        for (int k = 2; k < 25; k++) {
          if (k == 4) ep1 = get_epoch() + 1;
          if (k == 10 || k == 17) {
            if (k == 10) mbar_wait(bars + 8 * B_HST, 0);
            flag_wait(k == 10 ? FL_H + 2 * i + rank : FL_X1 + i, ep1 * 8u);
            TSTAMPX(k == 10 ? 29 : 30);
          }
          if (k == 15) mbar_wait(bars + 8 * B_X1P, 0);
          mbar_wait(emptyA + 8 * r.idx, r.phase);
          const uint32_t bar = fullA + 8 * r.idx, slot = sb + OFF_A + r.idx * SLOT_A;
          mbar_expect_tx(bar, SLOT_A);
          if (k >= 10 && k < 15) tma2d(slot, &maps.hs, bar, 64 * (k - 10) + 320 * rank, 128 * i);
          else tma2d_mc(slot + rank * 8192, k < 10 ? &maps.x : &maps.x1, bar, 64 * (k < 10 ? k : (k - 15 + k3) % 10), 128 * i + 64 * rank);
          r.next<NA>();
        }
      }
    } else if (pw == 1) {
      if (tid == 288) {
        Ring r{2, 1};
#pragma unroll 1
        for (int k = 2; k < 18; k++) {
          mbar_wait(emptyB + 8 * r.idx, r.phase);
          const uint32_t bar = fullB + 8 * r.idx, slot = sb + OFF_B + r.idx * SLOT_B;
          if (k < 10) {
            load_p1_b(k, slot, bar);
          } else if (k < 13) {
            mbar_expect_tx(bar, k < 12 ? 40960 : 20480);
            tma3d(slot, &maps.w2, bar, 0, 320 * rank + 128 * (k - 10), 5 * (j >> 1));
            if (k < 12) tma3d(slot + 20480, &maps.w2, bar, 0, 320 * rank + 128 * (k - 10) + 64, 5 * (j >> 1));
          } else {
            mbar_expect_tx(bar, 49152);
            tma3d(slot, &maps.w3, bar, 0, 64 * ((2 * (k - 13) + k3) % 10), 3 * j);
            tma3d(slot + 24576, &maps.w3, bar, 0, 64 * ((2 * (k - 13) + 1 + k3) % 10), 3 * j);
          }
          r.next<NB>();
        }
#pragma unroll 1
        for (int n = 0; n < 8; n++) {
          if (n < 3) { mbar_wait(emptyB + 8 * r.idx, r.phase); r.next<NB>(); }
          if (n >= 4) mbar_wait(bars + 8 * (B_EMPTY4 + n - 4), 0);
          const uint32_t bar = bars + 8 * (B_FULL4 + n), set = sb + ((n >> 1) & 1) * SET4;
          const int h = n & 1, m = ((j >> 1) + 1 + (n >> 1)) & 3;
          mbar_expect_tx(bar, h ? 40960 : 46080);
          tma3d(set + (h ? 46080 : 0), h ? &maps.w4 : &maps.wo, bar, 0, h ? 192 * j + 64 : 80 * j, 5 * m);
          tma3d(set + (h ? 66560 : 25600), &maps.w4, bar, 0, 192 * j + 128 * h, 5 * m);
        }
        mbar_wait(bars + 8 * (B_EMPTY4 + 4), 0);
        mbar_expect_tx(bars + 8 * B_XR, 20480);
        tma2d(sb + OFF_OUT, &maps.st_x1, bars + 8 * B_XR, 80 * j, 128 * i);
      }
    } else {
      const unsigned epoch = get_epoch();
      float* accg = g_acc[epoch & 1];
      if (pw == 2) {
        if (tid == 320) {
          flag_wait(FL_CS, (epoch + 1) * NSVC);
          flag_wait(FL_ST + i, (epoch + 1) * 8u);
          fence_async_glb();
          *reinterpret_cast<volatile uint32_t*>(sgen + OFF_BAR + 8 * NBAR) = (epoch + 1) & 1;
          mbar_expect_tx(bars + 8 * B_CS, 320 + 2048 + 12800);
          bulk_load(sb + OFF_CS, g_cs + 80 * j, 320, bars + 8 * B_CS);
          bulk_load(sb + OFF_XST, g_xstat + 128 * i, 2048, bars + 8 * B_CS);
          bulk_load(sb + OFF_MISC, g_wphi + j * 800, 12800, bars + 8 * B_CS);
          TSTAMPX(21);
          flag_wait(FL_KV + j, (epoch + 1) * 16u);
          mbar_expect_tx(bars + 8 * B_KV, KV_J * 4);
          bulk_load(sb + OFF_MISC, accg + j * KV_J, KV_J * 4, bars + 8 * B_KV);
          TSTAMPX(22);
          flag_wait(FL_CS3, (epoch + 1) * NSVC);
          flag_wait(FL_S1 + i, (epoch + 1) * 8u);
          fence_async_glb();
          mbar_expect_tx(bars + 8 * B_ST1, 8192 + 768);
          bulk_load(sb + OFF_CS + 320, g_cs + D_ + 192 * j, 768, bars + 8 * B_ST1);
          bulk_load(sb + OFF_MISC, g_st1 + 128 * i * 8, 8192, bars + 8 * B_ST1);
        }
        __syncwarp();
#pragma unroll 1
        for (int c = 0; c < 3; c++) {
          mbar_wait(bars + 8 * (B_EMPTY4 + (c ? 5 : 4)), 0);
          const uint4* src = g_part + (size_t)((i * 8 + j) * 3 + c) * 1280;
          const unsigned* tp = reinterpret_cast<const unsigned*>(src + 1024 + (lane & 7) * 32 + 31);
          uint32_t n = 0;
          while (!__all_sync(0xffffffffu, (ld_acquire(tp) ^ epoch) & 1u) && ++n < (WAIT_LIMIT >> 2)) {}
          if (tid == 320) {
            mbar_expect_tx(bars + 8 * (B_RDY + c), 20480);
            bulk_load(sb + (c ? 25600 + 20480 * c : 0), src, 20480, bars + 8 * (B_RDY + c));
          }
        }
      }
      if (tid == 352) {
        mbar_wait(bars + 8 * B_SIGP, 0);
        flag_add(FL_ST + i);
        TSTAMPX(20);
        mbar_expect_tx(bars + 8 * B_XR, 20480);
#pragma unroll 1
        for (int u = 0; u < 8; u++)
          tma2d(sb + OFF_B + (u / 3) * SLOT_B + SPARE + (u % 3) * 2560, &maps.xr, bars + 8 * B_XR, 80 * j, 128 * i + 16 * u);
        const int shift = (j < 2) ? 1 : (j < 4) ? -1 : (j < 6) ? 2 : -2;
        prefetch_tmap(&maps.st_h); prefetch_tmap(&maps.st_x1); prefetch_tmap(&maps.hs); prefetch_tmap(&maps.x1);
        prefetch_tmap(&maps.w2); prefetch_tmap(&maps.w3); prefetch_tmap(&maps.w4); prefetch_tmap(&maps.wo);
        mbar_wait(bars + 8 * B_SIGH, 0);
        TSTAMPX(23);
        tma2d_store(&maps.st_h, sb + OFF_STG, 80 * j, 128 * i + 2 + shift);
        bulk_commit(); bulk_wait<0>();
        mbar_arrive(bars + 8 * B_HST);
        flag_add(FL_H + 2 * i + (j >> 2));
        flag_add_relaxed(FL_H + 2 * ((i + (shift > 0 ? 1 : -1)) & 15) + (j >> 2));
        TSTAMPX(24);
        mbar_wait(bars + 8 * B_SIGKV, 0);
        TSTAMPX(25);
        fence_async_smem();
        asm volatile("cp.reduce.async.bulk.global.shared::cta.bulk_group.add.f32 [%0], [%1], %2;"
                     ::"l"(accg + j * KV_J), "r"(sb + OFF_MISC), "r"(KV_J * 4) : "memory");
        bulk_commit(); bulk_wait<0>();
        flag_add(FL_KV + j);
        TSTAMPX(26);
        mbar_wait(bars + 8 * B_SIGX1, 0);
        TSTAMPX(27);
        tma2d_store(&maps.st_x1, sb + OFF_STG, 80 * j, 128 * i);
        bulk_commit(); bulk_wait<0>();
        flag_add(FL_X1 + i);
        mbar_arrive_cta(bars + 8 * B_X1P, 0); mbar_arrive_cta(bars + 8 * B_X1P, 1);
        TSTAMPX(28);
        mbar_wait(bars + 8 * B_MFREE, 0);
        flag_add(FL_S1 + i);
      }
    }
  } else {
    uint4 pv[5], pw_[5];
    {
      const int row = 128 * i + 16 * j + (tid >> 4), l16 = tid & 15;
#pragma unroll
      for (int c = 0; c < 5; c++) pv[c] = __ldg(reinterpret_cast<const uint4*>(x + (size_t)row * D_ + c * 128 + l16 * 8));
#pragma unroll
      for (int c = 0; c < 5; c++) pw_[c] = __ldg(reinterpret_cast<const uint4*>(gate_w + c * 128 + l16 * 8));
    }
    asm volatile("barrier.cluster.arrive.relaxed.aligned;" ::: "memory");
    asm volatile("setmaxnreg.inc.sync.aligned.u32 232;");
    const int wg = tid >> 7, warp = tid >> 5, lane = tid & 31, t = lane & 3;
    const int rloc = warp * 16 + (lane >> 2);
    const float* s_cs = reinterpret_cast<const float*>(sgen + OFF_CS);
    auto signal = [&](int b) {
      __syncwarp();
      if (lane == 0) mbar_arrive(bars + 8 * b);
    };
    auto releaseB = [&](uint32_t bar) {
      __syncwarp();
      if (lane == 0) mbar_arrive(bar);
    };
    auto release = [&](uint32_t bar) {
      __syncwarp();
      if (lane < 2) mbar_arrive_cta(bar, lane);
    };
    const uint32_t stg_lane = (warp * 16 + ((lane >> 3) & 1) * 8 + (lane & 7)) * 160 + (lane >> 4) * 16;

    auto stage_tile = [&](uint32_t stg, const uint32_t (&v)[2][10]) {
#pragma unroll
      for (int s = 0; s < 5; s++) stsm4(stg + stg_lane + s * 32, v[0][2 * s], v[1][2 * s], v[0][2 * s + 1], v[1][2 * s + 1]);
    };

    {
      float f[40];
      float s = 0.f, gs = 0.f;
#pragma unroll
      for (int c = 0; c < 5; c++) {
        const uint32_t vv[4] = {pv[c].x, pv[c].y, pv[c].z, pv[c].w}, ww[4] = {pw_[c].x, pw_[c].y, pw_[c].z, pw_[c].w};
#pragma unroll
        for (int e = 0; e < 4; e++) {
          f[8 * c + 2 * e] = bf_lo(vv[e]); f[8 * c + 2 * e + 1] = bf_hi(vv[e]);
          s += f[8 * c + 2 * e] + f[8 * c + 2 * e + 1];
          gs = fmaf(f[8 * c + 2 * e], bf_lo(ww[e]), gs); gs = fmaf(f[8 * c + 2 * e + 1], bf_hi(ww[e]), gs);
        }
      }
#pragma unroll
      for (int o = 1; o < 16; o <<= 1) { s += __shfl_xor_sync(0xffffffffu, s, o); gs += __shfl_xor_sync(0xffffffffu, gs, o); }
      const float mean = s * (1.f / D_);
      float q = 0.f;
#pragma unroll
      for (int e = 0; e < 40; e++) { const float d = f[e] - mean; q = fmaf(d, d, q); }
#pragma unroll
      for (int o = 1; o < 16; o <<= 1) q += __shfl_xor_sync(0xffffffffu, q, o);
      const float rstd = rsqrtf(q * (1.f / D_) + 1e-5f);
      asm volatile("barrier.cluster.wait.aligned;" ::: "memory");
      if ((tid & 15) == 0) g_xstat[128 * i + 16 * j + (tid >> 4)] = make_float4(rstd, -mean, rcp(1.f + __expf(-gs)), 0.f);
      signal(B_SIGP);
    }
    TSTAMP(1);

    Ring ra{0, 0}, rb{0, 0};
    uint32_t qp[2][10], P[2][10];
    float st_g[2];
    {
      float accM[128], accR[32];
      uint32_t pa = 0, pb = 0;
#pragma unroll 1
      for (int k = 0; k < 10; k++) {
        mbar_wait(fullA + 8 * ra.idx, ra.phase);
        if (tid == 0) TRACE(32 + k);
        mbar_wait(fullB + 8 * rb.idx, rb.phase);
        if (tid == 0) TRACE(64 + k);
        if (k == 0) TSTAMP(2);
        const uint32_t a0 = sb16 + ((OFF_A + ra.idx * SLOT_A + wg * 8192) >> 4), b0 = sb16 + ((OFF_B + rb.idx * SLOT_B) >> 4);
        wg_fence();
#pragma unroll
        for (int kk = 0; kk < 4; kk++) {
          const uint64_t da = make_desc(a0, kk * 32, 16, 1024, 1);
          if (kk == 0) {
            mma_ss256_p(accM, da, make_desc(b0, 0, 8192, 1024, 1), k);
            mma_ss64_p(accR, da, make_desc(b0, 32768, 2048, 256, 3), k);
          } else {
            mma_ss256(accM, da, make_desc(b0, kk * 2048, 8192, 1024, 1));
            mma_ss64(accR, da, make_desc(b0, 32768 + kk * 512, 2048, 256, 3));
          }
          if (kk == 0) {
            wg_commit();
            if (k > 0) {
              wg_wait<1>();
              if (k - 1 < 8) release(emptyA + 8 * pa);
              releaseB(emptyB + 8 * pb);
            }
          }
        }
        wg_commit();
        pa = ra.idx; pb = rb.idx;
        ra.next<NA>(); rb.next<NB>();
      }
      TSTAMP(18);
      float st_rstd[2], st_mr[2];
      mbar_wait(bars + 8 * B_CS, 0);
#pragma unroll
      for (int r = 0; r < 2; r++) {
        const uint4 st = lds128(sb + OFF_XST + (rloc + 8 * r) * 16);
        st_rstd[r] = __uint_as_float(st.x); st_mr[r] = __uint_as_float(st.y); st_g[r] = __uint_as_float(st.z);
      }
      TSTAMP(19);
      wg_wait<0>();
      fence_regs(accM); fence_regs(accR);
      TSTAMP(3);
#define ACC(P_, G, I_) ((G) < 8 ? accM[(P_) * 32 + ((G) & 7) * 4 + (I_)] : accR[(P_) * 8 + ((G) & 1) * 4 + (I_)])
      {
        uint32_t hv[2][10];
        const GeluC g0 = gelu_consts(st_rstd[0], 1.f), g1 = gelu_consts(st_rstd[1], 1.f);
#pragma unroll
        for (int g = 0; g < 10; g++) {
          const float2 cs = *reinterpret_cast<const float2*>(s_cs + 8 * g + 2 * t);
          const float v0 = gelu_s(fmaf(st_mr[0], cs.x, ACC(0, g, 0)), g0), v1 = gelu_s(fmaf(st_mr[0], cs.y, ACC(0, g, 1)), g0);
          const float v2 = gelu_s(fmaf(st_mr[1], cs.x, ACC(0, g, 2)), g1), v3 = gelu_s(fmaf(st_mr[1], cs.y, ACC(0, g, 3)), g1);
          hv[0][g] = pack_bf16(v0, v1); hv[1][g] = pack_bf16(v2, v3);
        }
        bar_sync(1, 256);
        stage_tile(sb + OFF_STG, hv);
        fence_async_smem();
        signal(B_SIGH);
      }
      TSTAMP(4);
      uint32_t kf[5][4], qf[5][4];
#pragma unroll
      for (int s = 0; s < 5; s++) {
        kf[s][0] = pack_bf16(ACC(2, 2 * s, 0), ACC(2, 2 * s, 1)); kf[s][1] = pack_bf16(ACC(2, 2 * s, 2), ACC(2, 2 * s, 3));
        kf[s][2] = pack_bf16(ACC(2, 2 * s + 1, 0), ACC(2, 2 * s + 1, 1)); kf[s][3] = pack_bf16(ACC(2, 2 * s + 1, 2), ACC(2, 2 * s + 1, 3));
        qf[s][0] = pack_bf16(ACC(1, 2 * s, 0), ACC(1, 2 * s, 1)); qf[s][1] = pack_bf16(ACC(1, 2 * s, 2), ACC(1, 2 * s, 3));
        qf[s][2] = pack_bf16(ACC(1, 2 * s + 1, 0), ACC(1, 2 * s + 1, 1)); qf[s][3] = pack_bf16(ACC(1, 2 * s + 1, 2), ACC(1, 2 * s + 1, 3));
      }
      float pk[40], pq[40];
      wg_fence();
#pragma unroll
      for (int s = 0; s < 5; s++) {
        if (s == 0) mma_rs80_k_z(pk, kf[s], make_desc(sb16, OFF_MISC, 16, 256, 3));
        else mma_rs80_k(pk, kf[s], make_desc(sb16, OFF_MISC + s * 2560, 16, 256, 3));
      }
      wg_commit();
#pragma unroll
      for (int s = 0; s < 5; s++) {
        if (s == 0) mma_rs80_k_z(pq, qf[s], make_desc(sb16, OFF_MISC, 16, 256, 3));
        else mma_rs80_k(pq, qf[s], make_desc(sb16, OFF_MISC + s * 2560, 16, 256, 3));
      }
      wg_commit();
      {
        const int mat = lane >> 3;
        const int tok = warp * 16 + (mat & 1) * 8 + (lane & 7);
        const uint32_t ones = (t == 0) ? 0x00003f80u : 0u;
        __syncwarp();
#pragma unroll
        for (int p = 0; p < 2; p++) {
          const uint32_t rowa = sb + OFF_A + p * SLOT_A + tok * 128;
#pragma unroll
          for (int gg = 0; gg < 3; gg++) {
            const int g0 = 5 * p + 2 * gg;
            uint32_t r0 = pack_bf16(ACC(3, g0, 0), ACC(3, g0, 1)), r1 = pack_bf16(ACC(3, g0, 2), ACC(3, g0, 3));
            uint32_t r2 = ones, r3 = ones;
            if (gg < 2) { r2 = pack_bf16(ACC(3, g0 + 1, 0), ACC(3, g0 + 1, 1)); r3 = pack_bf16(ACC(3, g0 + 1, 2), ACC(3, g0 + 1, 3)); }
            stsm4(rowa + (((2 * gg + (mat >> 1)) ^ (tok & 7)) << 4), r0, r1, r2, r3);
          }
        }
      }
#undef ACC
      wg_wait<1>();
      fence_regs(pk);
#pragma unroll
      for (int G = 0; G < 10; G++) {
        P[0][G] = pack_bf16(pk[4 * G], pk[4 * G + 1]); P[1][G] = pack_bf16(pk[4 * G + 2], pk[4 * G + 3]);
      }
      wg_wait<0>();
      fence_regs(pq);
#pragma unroll
      for (int G = 0; G < 10; G++) {
        qp[0][G] = pack_bf16(pq[4 * G], pq[4 * G + 1]); qp[1][G] = pack_bf16(pq[4 * G + 2], pq[4 * G + 3]);
      }
    }

    uint32_t fr[10][4];
    int pass;
    pass = gridDim.y;
#pragma unroll 1
    do {
    feature_map(P, fr);
    if (pass != 0) {
    {
      const int mat = lane >> 3;
      const int tok = warp * 16 + (mat & 1) * 8 + (lane & 7);
      const uint32_t base = sb + OFF_B + tok * 32 + (((mat >> 1) ^ ((tok >> 2) & 1)) << 4);
#pragma unroll
      for (int G = 0; G < 10; G++) stsm4(base + G * 4096, fr[G][0], fr[G][1], fr[G][2], fr[G][3]);
      fence_async_smem();
      bar_sync(1, 256);
      float kv[40];
      const uint32_t va = sb16 + ((OFF_A + wg * SLOT_A) >> 4), vb = sb16 + ((OFF_B + wg * 20480) >> 4);
      wg_fence();
#pragma unroll
      for (int ks = 0; ks < 8; ks++) {
        if (ks == 0) mma_ss80_tt_z(kv, make_desc(va, 0, 16, 1024, 1), make_desc(vb, 0, 4096, 256, 3));
        else mma_ss80_tt(kv, make_desc(va, ks * 2048, 16, 1024, 1), make_desc(vb, ks * 512, 4096, 256, 3));
      }
      wg_commit();
      uint32_t xv[2][10];
      {
        mbar_wait(bars + 8 * B_XR, 0);
        const uint32_t xa = sb + OFF_B + (warp / 3) * SLOT_B + SPARE + (warp % 3) * 2560 + (lane >> 2) * 160 + t * 4;
#pragma unroll
        for (int g = 0; g < 10; g++) { xv[0][g] = lds32(xa + g * 16); xv[1][g] = lds32(xa + 1280 + g * 16); }
      }
      float acc[80];
      wg_wait<0>();
      release(emptyA); release(emptyA + 8); releaseB(emptyB); release(bars + 8 * B_PEER2);
      TSTAMP(5);
      mbar_wait(fullA + 8 * 2, 0);
      mbar_wait(fullB + 8 * 1, 1);
      TSTAMP(6);
      wg_fence();
#pragma unroll
      for (int kk = 0; kk < 4; kk++) {
        const uint64_t da = make_desc(sb16 + wg * 512, OFF_A + 2 * SLOT_A + kk * 32, 16, 1024, 1);
        const uint64_t db = make_desc(sb16, OFF_B + SLOT_B + kk * 1024, 4096, 512, 2);
        if (kk == 0) mma_ss160_z(acc, da, db); else mma_ss160(acc, da, db);
      }
      wg_commit();
      ra.next<NA>();
      wg_wait<1>();
      fence_regs(kv);
      TSTAMP(31);
      const uint32_t dst = sb + OFF_MISC + wg * (KV_PAIR * 4);
      const int m0 = (warp & 3) * 16 + (lane >> 2);
#pragma unroll
      for (int r = 0; r < 2; r++) {
        const int m = m0 + 8 * r;
        const bool hi = m >= 20;
        uint32_t v[10];
#pragma unroll
        for (int G = 0; G < 10; G++) v[G] = __float_as_uint(hi ? kv[4 * G + 2 * r + 1] : kv[4 * G + 2 * r]);
        const uint32_t p = dst + 4 * (m < 40 ? m * 48 + t * 12 : 1920 + t * 24 + 12);
        if (m <= 40) {
          sts128(p, make_uint4(v[0], v[1], v[2], v[3])); sts128(p + 16, make_uint4(v[4], v[5], v[6], v[7]));
          sts128(p + 32, make_uint4(v[8], v[9], 0u, 0u));
        }
      }
      if (m0 == 32) {
        const uint32_t p = dst + 4 * (1920 + t * 24);
        sts128(p, make_uint4(__float_as_uint(kv[2]), __float_as_uint(kv[6]), __float_as_uint(kv[10]), __float_as_uint(kv[14])));
        sts128(p + 16, make_uint4(__float_as_uint(kv[18]), __float_as_uint(kv[22]), __float_as_uint(kv[26]), __float_as_uint(kv[30])));
        sts128(p + 32, make_uint4(__float_as_uint(kv[34]), __float_as_uint(kv[38]), 0u, 0u));
      }
      signal(B_SIGKV);
      uint32_t pa = 2, pb = 1;
#pragma unroll 1
      for (int k = 1; k < 5; k++) {
        mbar_wait(fullA + 8 * ra.idx, ra.phase);
        if ((k & 1) == 0) mbar_wait(fullB + 8 * rb.idx, rb.phase);
        const uint32_t a0 = sb16 + ((OFF_A + ra.idx * SLOT_A + wg * 8192) >> 4);
        const uint32_t b0 = sb16 + ((OFF_B + rb.idx * SLOT_B + (k & 1) * 20480) >> 4);
        wg_fence();
#pragma unroll
        for (int kk = 0; kk < 4; kk++) {
          mma_ss160(acc, make_desc(a0, kk * 32, 16, 1024, 1), make_desc(b0, kk * 1024, 4096, 512, 2));
          if (kk == 0) {
            wg_commit();
            wg_wait<1>();
            release(emptyA + 8 * pa);
            if ((k & 1) == 0) releaseB(emptyB + 8 * pb);
          }
        }
        wg_commit();
        pa = ra.idx; pb = rb.idx;
        ra.next<NA>();
        if ((k & 1) || k == 4) rb.next<NB>();
      }
      mbar_wait(bars + 8 * B_PEER2, 0);
      wg_wait<0>();
      fence_regs(acc);
      release(emptyA + 8 * pa);
      TSTAMP(7);
      {
        uint32_t sn[20];
        if (rank) {
#pragma unroll
          for (int e = 0; e < 20; e++) sn[e] = pack_bf16(acc[2 * e], acc[2 * e + 1]);
#pragma unroll
          for (int e = 0; e < 40; e++) acc[e] = acc[40 + e];
        } else {
#pragma unroll
          for (int e = 0; e < 20; e++) sn[e] = pack_bf16(acc[40 + 2 * e], acc[41 + 2 * e]);
        }
        const uint32_t peer = map_peer(sb, rank ^ 1);
#pragma unroll
        for (int q = 0; q < 5; q++)
          st_async16(peer + OFF_B + 20480 + tid * 16 + q * 4096, sn[4 * q], sn[4 * q + 1], sn[4 * q + 2], sn[4 * q + 3],
                     peer + OFF_BAR + 8 * (B_DSR + 8 + wg));
#pragma unroll
        for (int g = 0; g < 10; g++) {
          acc[4 * g] += bf_lo(xv[0][g]); acc[4 * g + 1] += bf_hi(xv[0][g]);
          acc[4 * g + 2] += bf_lo(xv[1][g]); acc[4 * g + 3] += bf_hi(xv[1][g]);
        }
        bar_sync(1, 256);
        mbar_wait(bars + 8 * (B_DSR + 8 + wg), 0);
#pragma unroll
        for (int q = 0; q < 5; q++) {
          const uint4 v = lds128(sb + OFF_B + 20480 + tid * 16 + q * 4096);
          xv[0][2 * q] = pack_bf16(acc[8 * q] + bf_lo(v.x), acc[8 * q + 1] + bf_hi(v.x));
          xv[1][2 * q] = pack_bf16(acc[8 * q + 2] + bf_lo(v.y), acc[8 * q + 3] + bf_hi(v.y));
          xv[0][2 * q + 1] = pack_bf16(acc[8 * q + 4] + bf_lo(v.z), acc[8 * q + 5] + bf_hi(v.z));
          xv[1][2 * q + 1] = pack_bf16(acc[8 * q + 6] + bf_lo(v.w), acc[8 * q + 7] + bf_hi(v.w));
        }
        releaseB(emptyB + 8 * pb);
      }
      TSTAMP(16);
      stage_tile(sb + OFF_STG, xv);
      fence_async_smem();
      signal(B_SIGX1);
      TSTAMP(17);
#pragma unroll
      for (int r = 0; r < 2; r++) {
        float s = 0.f;
#pragma unroll
        for (int g = 0; g < 10; g++) {
          acc[4 * g + 2 * r] = bf_lo(xv[r][g]); acc[4 * g + 2 * r + 1] = bf_hi(xv[r][g]);
          s += acc[4 * g + 2 * r] + acc[4 * g + 2 * r + 1];
        }
        s += __shfl_xor_sync(0xffffffffu, s, 1); s += __shfl_xor_sync(0xffffffffu, s, 2);
        const float mu = s * (1.f / 80.f);
        float q = 0.f;
#pragma unroll
        for (int g = 0; g < 10; g++) {
          const float d0 = acc[4 * g + 2 * r] - mu, d1 = acc[4 * g + 2 * r + 1] - mu;
          q = fmaf(d0, d0, q); q = fmaf(d1, d1, q);
        }
        q += __shfl_xor_sync(0xffffffffu, q, 1); q += __shfl_xor_sync(0xffffffffu, q, 2);
        if (t == 0) g_st1[(128 * i + rloc + 8 * r) * 8 + j] = make_float2(mu, q);
      }
    }
    TSTAMP(8);
#pragma unroll
    for (int G = 0; G < 10; G++) { P[0][G] = qp[0][G]; P[1][G] = qp[1][G]; }
    }
    asm volatile("" : "+r"(pass));
    } while (pass-- != 0);

    uint32_t of[5][4];
    {
      mbar_wait(bars + 8 * B_KV, 0);
      uint4 kvr[2][3];
#pragma unroll
      for (int u = 0; u < 2; u++) {
        const int it = tid + 256 * u, p = it / 192, rem = it - 192 * p, n = rem >> 2, tq = rem & 3;
        const uint32_t sp = sb + OFF_MISC + 4 * (p * KV_PAIR + (n < 40 ? n * 48 + tq * 12 : 1920 + tq * 24 + (n & 1) * 12));
        if (it < 384) { kvr[u][0] = lds128(sp); kvr[u][1] = lds128(sp + 16); kvr[u][2] = lds128(sp + 32); }
      }
      bar_sync(1, 256);
#pragma unroll
      for (int u = 0; u < 2; u++) {
        const int it = tid + 256 * u, p = it / 192, rem = it - 192 * p, n = rem >> 2, tq = rem & 3;
        const int sh = (n < 40 ? (n >= 20) : (n & 1)) * 16;
        const uint32_t v[10] = {kvr[u][0].x, kvr[u][0].y, kvr[u][0].z, kvr[u][0].w, kvr[u][1].x, kvr[u][1].y, kvr[u][1].z, kvr[u][1].w, kvr[u][2].x, kvr[u][2].y};
        uint8_t* dst = sgen + OFF_MISC + p * 7680 + n * 32 + tq * 4;
        const int sw = ((n >> 2) & 1) << 4;
        if (it < 384) {
#pragma unroll
          for (int G = 0; G < 10; G++)
            *reinterpret_cast<uint32_t*>(dst + (G >> 1) * 1536 + (((G & 1) << 4) ^ sw)) = pack_bf16(__uint_as_float(v[G]), 0.f) << sh;
        }
      }
      fence_async_smem();
      bar_sync(1, 256);
      float o0[24], o1[24];
      wg_fence();
#pragma unroll
      for (int g = 0; g < 5; g++) {
        if (g == 0) mma_rs48_k_z(o0, fr[g], make_desc(sb16, OFF_MISC, 16, 256, 3));
        else mma_rs48_k(o0, fr[g], make_desc(sb16, OFF_MISC + g * 1536, 16, 256, 3));
      }
#pragma unroll
      for (int g = 0; g < 5; g++) {
        if (g == 0) mma_rs48_k_z(o1, fr[5], make_desc(sb16, OFF_MISC + 7680, 16, 256, 3));
        else mma_rs48_k(o1, fr[5 + g], make_desc(sb16, OFF_MISC + 7680 + g * 1536, 16, 256, 3));
      }
      wg_commit();
      wg_wait<0>();
      fence_regs(o0); fence_regs(o1);
      signal(B_MFREE);
#pragma unroll
      for (int r = 0; r < 2; r++) {
        const float a0 = __fdividef(st_g[r], o0[20 + 2 * r] + 1e-6f), a1 = __fdividef(st_g[r], o0[21 + 2 * r] + 1e-6f);
        const float b0 = __fdividef(st_g[r], o1[20 + 2 * r] + 1e-6f), b1 = __fdividef(st_g[r], o1[21 + 2 * r] + 1e-6f);
        const float am = t < 2 ? a0 : a1, bm = t < 2 ? b0 : b1;
#pragma unroll
        for (int g = 0; g < 5; g++) {
          const float sa = g < 2 ? a0 : (g == 2 ? am : a1), sb2 = g < 2 ? b0 : (g == 2 ? bm : b1);
          of[g >> 1][(g & 1) * 2 + r] = pack_bf16(o0[4 * g + 2 * r] * sa, o0[4 * g + 2 * r + 1] * sa);
          of[(5 + g) >> 1][((5 + g) & 1) * 2 + r] = pack_bf16(o1[4 * g + 2 * r] * sb2, o1[4 * g + 2 * r + 1] * sb2);
        }
      }
    }
    TSTAMP(9);

    uint32_t hf[12][4];
    float ac4[80];
    auto unit = [&](auto uc, uint32_t b0) {
      constexpr int u = decltype(uc)::value;
#pragma unroll
      for (int s = 0; s < (u ? 4 : 5); s++) {
        const uint64_t db = make_desc(b0, (u ? 5120 + 20480 * u : 0) + s * 1024, u ? 4096 : 5120, 512, 2);
        if (u == 0 && s == 0) mma_rs160_n_z(ac4, of[0], db);
        else if (u == 0) mma_rs160_n(ac4, of[s], db);
        else mma_rs160_n(ac4, hf[(4 * u + 8 + s) % 12], db);
      }
      wg_commit();
    };
    {
      float acc[96];
      uint32_t pa = 0, pb = 0;
#pragma unroll 1
      for (int k = 0; k < 10; k++) {
        mbar_wait(fullA + 8 * ra.idx, ra.phase);
        if (tid == 0) TRACE(52 + k);
        if ((k & 1) == 0) mbar_wait(fullB + 8 * rb.idx, rb.phase);
        if (tid == 0) TRACE(84 + k);
        if (k == 0) TSTAMP(10);
        const uint32_t a0 = sb16 + ((OFF_A + ra.idx * SLOT_A + wg * 8192) >> 4);
        const uint32_t b0 = sb16 + ((OFF_B + rb.idx * SLOT_B + (k & 1) * 24576) >> 4);
        wg_fence();
#pragma unroll
        for (int kk = 0; kk < 4; kk++) {
          if (kk == 0) mma_ss192_p(acc, make_desc(a0, 0, 16, 1024, 1), make_desc(b0, 0, 8192, 1024, 1), k);
          else mma_ss192(acc, make_desc(a0, kk * 32, 16, 1024, 1), make_desc(b0, kk * 2048, 8192, 1024, 1));
          if (kk == 0) {
            wg_commit();
            if (k > 0) {
              wg_wait<1>();
              release(emptyA + 8 * pa);
              if ((k & 1) == 0) releaseB(emptyB + 8 * pb);
            }
          }
        }
        wg_commit();
        pa = ra.idx; pb = rb.idx;
        ra.next<NA>();
        if (k & 1) rb.next<NB>();
      }
      float rs[2], mm[2];
      mbar_wait(bars + 8 * B_ST1, 0);
#pragma unroll
      for (int r = 0; r < 2; r++) {
        const uint4 su = lds128(sb + OFF_MISC + (rloc + 8 * r) * 64 + t * 16);
        const float m0 = __uint_as_float(su.x), m1 = __uint_as_float(su.z);
        float mu = m0 + m1;
        mu += __shfl_xor_sync(0xffffffffu, mu, 1); mu += __shfl_xor_sync(0xffffffffu, mu, 2);
        mu *= 0.125f;
        const float d0 = m0 - mu, d1 = m1 - mu;
        float q = __uint_as_float(su.y) + __uint_as_float(su.w) + 80.f * (d0 * d0 + d1 * d1);
        q += __shfl_xor_sync(0xffffffffu, q, 1); q += __shfl_xor_sync(0xffffffffu, q, 2);
        rs[r] = rsqrtf(q * (1.f / D_) + 1e-5f);
        mm[r] = -mu;
      }
      mbar_wait(bars + 8 * B_FULL4, 0);
      wg_fence();
      unit(IntC<0>{}, sb16);
      wg_wait<1>();
      fence_regs(acc);
      releaseB(emptyB + 8 * pb);
      release(bars + 8 * B_PEER);
      TSTAMP(11);
      const GeluC g0 = gelu_consts(rs[0], 1.f - st_g[0]), g1 = gelu_consts(rs[1], 1.f - st_g[1]);
#pragma unroll
      for (int g = 0; g < 24; g++) {
        const float2 cs = *reinterpret_cast<const float2*>(s_cs + 80 + 8 * g + 2 * t);
        const float v0 = gelu_s(fmaf(mm[0], cs.x, acc[4 * g]), g0), v1 = gelu_s(fmaf(mm[0], cs.y, acc[4 * g + 1]), g0);
        const float v2 = gelu_s(fmaf(mm[1], cs.x, acc[4 * g + 2]), g1), v3 = gelu_s(fmaf(mm[1], cs.y, acc[4 * g + 3]), g1);
        hf[g >> 1][(g & 1) * 2] = pack_bf16(v0, v1);
        hf[g >> 1][(g & 1) * 2 + 1] = pack_bf16(v2, v3);
        if (g == 7) { wg_fence(); unit(IntC<1>{}, sb16); }
        if (g == 15) { mbar_wait(bars + 8 * (B_FULL4 + 1), 0); wg_fence(); unit(IntC<2>{}, sb16); }
        if (g == 23) { wg_wait<1>(); signal(B_EMPTY4); wg_fence(); unit(IntC<3>{}, sb16); }
      }
    }
    TSTAMP(12);

    {
      float kp[40];
      uint32_t sn[20], kb[20];
      const uint32_t peer = map_peer(sb, rank ^ 1);
      const uint32_t tag = lds32(sb + OFF_BAR + 8 * NBAR);
      auto add8 = [&](int q, const uint4 v) {
        float* d = &kp[8 * q];
        d[0] += bf_lo(v.x); d[1] += bf_hi(v.x); d[2] += bf_lo(v.y); d[3] += bf_hi(v.y);
        d[4] += bf_lo(v.z); d[5] += bf_hi(v.z); d[6] += bf_lo(v.w); d[7] += bf_hi(v.w);
      };
      auto send = [&](int c) {
        const uint32_t dso = peer + OFF_DS + (c & 1) * 20480 + tid * 16, dsb = peer + OFF_BAR + 8 * (B_DSR + 2 * c + wg);
#pragma unroll
        for (int q = 0; q < 5; q++) st_async16(dso + q * 4096, sn[4 * q], sn[4 * q + 1], sn[4 * q + 2], sn[4 * q + 3], dsb);
      };
      mbar_wait(bars + 8 * B_PEER, 0);
      uint4* gdst = g_part + (size_t)i * 8 * 3840 + tid;
#pragma unroll 1
      for (int c = 0; c < 3; c++) {
        const uint32_t b0 = sb16 + ((c & 1) ? 0 : SET4 >> 4), bc = bars + 16 * c;
        mbar_wait(bc + 8 * (B_FULL4 + 2), 0);
        wg_wait<0>();
        fence_regs(ac4);
        if (rank) {
#pragma unroll
          for (int e = 0; e < 20; e++) { sn[e] = pack_bf16(ac4[2 * e], ac4[2 * e + 1]); kb[e] = pack_bf16(ac4[40 + 2 * e], ac4[41 + 2 * e]); }
        } else {
#pragma unroll
          for (int e = 0; e < 20; e++) { kb[e] = pack_bf16(ac4[2 * e], ac4[2 * e + 1]); sn[e] = pack_bf16(ac4[40 + 2 * e], ac4[41 + 2 * e]); }
        }
#pragma unroll
        for (int e = 0; e < 20; e++) asm volatile("" : "+r"(sn[e]), "+r"(kb[e]));
        if (c == 0 && wg == 1) bar_sync(2, 256);
        wg_fence();
        unit(IntC<0>{}, b0);
        if (lane == 0) mbar_arrive(bc + 8 * (B_EMPTY4 + 1));
        send(c);
        unit(IntC<1>{}, b0);
        if (c == 0 && wg == 0) bar_arrive(2, 256);
        {
          mbar_wait(bc + 8 * (B_DSR + wg), 0);
          uint4* dst = gdst + (((j + 2 * c + 2) & 7) * 3 + c) * 1280;
#pragma unroll
          for (int q = 0; q < 5; q++) {
            const uint4 v = lds128(sb + OFF_DS + (c & 1) * 20480 + tid * 16 + q * 4096);
            st_relaxed16(dst + q * 256, (add_bf2(v.x, kb[4 * q]) & ~1u) | tag, add_bf2(v.y, kb[4 * q + 1]),
                         add_bf2(v.z, kb[4 * q + 2]), add_bf2(v.w, kb[4 * q + 3]));
          }
        }
        mbar_wait(bc + 8 * (B_FULL4 + 3), 0);
        wg_fence();
        unit(IntC<2>{}, b0);
        wg_wait<1>();
        if (lane == 0) mbar_arrive(bc + 8 * (B_EMPTY4 + 2));
        unit(IntC<3>{}, b0);
      }
      auto partial = [&](int c, uint4 (&v)[5]) {
        mbar_wait(bars + 8 * (B_RDY + c), 0);
        uint32_t bad = 0;
#pragma unroll
        for (int q = 0; q < 5; q++) { v[q] = lds128(sb + (c ? 25600 + 20480 * c : 0) + tid * 16 + q * 4096); bad |= v[q].x ^ tag; }
#pragma unroll 1
        for (uint32_t n = 0; (bad & 1u) && n < (WAIT_LIMIT >> 2); n++) {
          bad = 0;
#pragma unroll
          for (int q = 0; q < 5; q++) { v[q] = ld_relaxed16(gdst + (j * 3 + c) * 1280 + q * 256); bad |= v[q].x ^ tag; }
        }
      };
      uint4 pa4[5], pb4[5];
      partial(0, pa4);
      wg_wait<0>();
      fence_regs(ac4);
      if (rank) {
#pragma unroll
        for (int e = 0; e < 20; e++) sn[e] = pack_bf16(ac4[2 * e], ac4[2 * e + 1]);
#pragma unroll
        for (int e = 0; e < 40; e++) kp[e] = ac4[40 + e];
      } else {
#pragma unroll
        for (int e = 0; e < 20; e++) sn[e] = pack_bf16(ac4[40 + 2 * e], ac4[41 + 2 * e]);
#pragma unroll
        for (int e = 0; e < 40; e++) kp[e] = ac4[e];
      }
      send(3);
      TSTAMP(13);
      {
        mbar_wait(bars + 8 * B_XR, 1);
        const float w0 = 1.f - st_g[0], w1s = 1.f - st_g[1];
        const uint32_t xa = sb + OFF_OUT + rloc * 160 + t * 4;
#pragma unroll
        for (int g = 0; g < 10; g++) {
          const uint32_t x0 = lds32(xa + g * 16), x1 = lds32(xa + 1280 + g * 16);
          kp[4 * g] = fmaf(w0, bf_lo(x0), kp[4 * g]); kp[4 * g + 1] = fmaf(w0, bf_hi(x0), kp[4 * g + 1]);
          kp[4 * g + 2] = fmaf(w1s, bf_lo(x1), kp[4 * g + 2]); kp[4 * g + 3] = fmaf(w1s, bf_hi(x1), kp[4 * g + 3]);
        }
      }
      partial(1, pb4);
#pragma unroll
      for (int q = 0; q < 5; q++)
        pa4[q] = make_uint4(add_bf2(pa4[q].x, pb4[q].x), add_bf2(pa4[q].y, pb4[q].y), add_bf2(pa4[q].z, pb4[q].z), add_bf2(pa4[q].w, pb4[q].w));
#pragma unroll
      for (int q = 0; q < 5; q++) add8(q, pa4[q]);
      partial(2, pb4);
      mbar_wait(bars + 8 * (B_DSR + 6 + wg), 0);
      TSTAMP(14);
#pragma unroll
      for (int q = 0; q < 5; q++) {
        const uint4 c = pb4[q], d = lds128(sb + OFF_DS + 20480 + tid * 16 + q * 4096);
        add8(q, make_uint4(add_bf2(c.x, d.x), add_bf2(c.y, d.y), add_bf2(c.z, d.z), add_bf2(c.w, d.w)));
      }
      __syncwarp();
      uint32_t ov[2][10];
#pragma unroll
      for (int g = 0; g < 10; g++) { ov[0][g] = pack_bf16(kp[4 * g], kp[4 * g + 1]); ov[1][g] = pack_bf16(kp[4 * g + 2], kp[4 * g + 3]); }
      stage_tile(sb + OFF_OUT, ov);
      __syncwarp();
      __nv_bfloat16* dst = out + (size_t)(128 * i + 16 * warp) * D_ + 80 * j;
#pragma unroll
      for (int q = 0; q < 5; q++) {
        const int id = q * 32 + lane, r = id / 10;
        *reinterpret_cast<uint4*>(dst + r * (D_ - 80) + id * 8) = lds128(sb + OFF_OUT + warp * 2560 + id * 16);
      }
    }
    TSTAMP(15);
    if (tid == 0) asm volatile("red.relaxed.gpu.global.add.u32 [%0], 1;" ::"l"(g_flags + FL_DONE * 32) : "memory");
  }
}

namespace {
typedef CUresult (*EncodeFn)(CUtensorMap*, CUtensorMapDataType, cuuint32_t, void*, const cuuint64_t*, const cuuint64_t*,
                             const cuuint32_t*, const cuuint32_t*, CUtensorMapInterleave, CUtensorMapSwizzle,
                             CUtensorMapL2promotion, CUtensorMapFloatOOBfill);

void encode(EncodeFn fn, CUtensorMap* m, const void* ptr, int rank, const cuuint64_t* dims, const cuuint64_t* strides,
            const cuuint32_t* box, CUtensorMapSwizzle swz) {
  cuuint32_t es[5] = {1, 1, 1, 1, 1};
  fn(m, CU_TENSOR_MAP_DATA_TYPE_BFLOAT16, rank, const_cast<void*>(ptr), dims, strides, box, es, CU_TENSOR_MAP_INTERLEAVE_NONE,
     swz, CU_TENSOR_MAP_L2_PROMOTION_L2_128B, CU_TENSOR_MAP_FLOAT_OOB_FILL_NONE);
}
}

extern "C" void kernel_launch(void* const* d_in, const int* in_sizes, int n_in, void* d_out, int out_size) {
  (void)in_sizes; (void)n_in; (void)out_size;
  const __nv_bfloat16* x = (const __nv_bfloat16*)d_in[0];
  const __nv_bfloat16* wqkv = (const __nv_bfloat16*)d_in[1];
  const __nv_bfloat16* wphi = (const __nv_bfloat16*)d_in[2];
  const __nv_bfloat16* wo = (const __nv_bfloat16*)d_in[3];
  const __nv_bfloat16* w1 = (const __nv_bfloat16*)d_in[5];
  const __nv_bfloat16* w2 = (const __nv_bfloat16*)d_in[6];
  const __nv_bfloat16* w3 = (const __nv_bfloat16*)d_in[7];
  const __nv_bfloat16* w4 = (const __nv_bfloat16*)d_in[8];
  const __nv_bfloat16* gate_w = (const __nv_bfloat16*)d_in[9];

  static EncodeFn enc = nullptr;
  static void *pHs = nullptr, *pX1 = nullptr;
  if (!enc) {
    cudaDriverEntryPointQueryResult qr;
    cudaGetDriverEntryPoint("cuTensorMapEncodeTiled", (void**)&enc, cudaEnableDefault, &qr);
    cudaGetSymbolAddress(&pHs, g_Hs);
    cudaGetSymbolAddress(&pX1, g_X1);
    cudaFuncSetAttribute(fused_kernel, cudaFuncAttributeMaxDynamicSharedMemorySize, SMEM_BYTES);
  }
  Maps m;
  {
    cuuint64_t dims[2] = {D_, S_}, str[1] = {D_ * 2};
    cuuint32_t box[2] = {64, 128}, boxh[2] = {64, 64};
    encode(enc, &m.x, x, 2, dims, str, boxh, CU_TENSOR_MAP_SWIZZLE_128B);
    encode(enc, &m.hs, (const char*)pHs + 2 * D_ * 2, 2, dims, str, box, CU_TENSOR_MAP_SWIZZLE_128B);
    encode(enc, &m.x1, pX1, 2, dims, str, boxh, CU_TENSOR_MAP_SWIZZLE_128B);
    cuuint32_t boxr[2] = {80, 16}, boxs[2] = {80, 128};
    cuuint64_t dimsp[2] = {D_, S_ + 4};
    encode(enc, &m.st_h, pHs, 2, dimsp, str, boxs, CU_TENSOR_MAP_SWIZZLE_NONE);
    encode(enc, &m.st_x1, pX1, 2, dims, str, boxs, CU_TENSOR_MAP_SWIZZLE_NONE);
    encode(enc, &m.xr, x, 2, dims, str, boxr, CU_TENSOR_MAP_SWIZZLE_NONE);
  }
  {
    cuuint64_t dims[3] = {80, D_, 8}, str[2] = {D_ * 2, 160};
    cuuint32_t boxm[3] = {64, 64, 1}, boxr[3] = {16, 64, 1};
    encode(enc, &m.w1m, w1, 3, dims, str, boxm, CU_TENSOR_MAP_SWIZZLE_128B);
    encode(enc, &m.w1r, w1, 3, dims, str, boxr, CU_TENSOR_MAP_SWIZZLE_32B);
  }
  {
    cuuint64_t dims[4] = {80, D_, 3, 8}, str[3] = {3 * D_ * 2, D_ * 2, 160};
    cuuint32_t boxm[4] = {64, 64, 3, 1}, boxr[4] = {16, 64, 3, 1};
    encode(enc, &m.qm, wqkv, 4, dims, str, boxm, CU_TENSOR_MAP_SWIZZLE_128B);
    encode(enc, &m.qr, wqkv, 4, dims, str, boxr, CU_TENSOR_MAP_SWIZZLE_32B);
  }
  {
    cuuint64_t dims[3] = {32, D_, 20}, dims4[3] = {32, F_, 20}, str[2] = {D_ * 2, 64};
    cuuint32_t box4[3] = {32, 64, 5}, boxo[3] = {32, 80, 5};
    encode(enc, &m.w4, w4, 3, dims4, str, box4, CU_TENSOR_MAP_SWIZZLE_64B);
    encode(enc, &m.wo, wo, 3, dims, str, boxo, CU_TENSOR_MAP_SWIZZLE_64B);
    encode(enc, &m.w2, w2, 3, dims, str, box4, CU_TENSOR_MAP_SWIZZLE_64B);
  }
  {
    cuuint64_t dims[3] = {64, D_, 24}, str[2] = {F_ * 2, 128};
    cuuint32_t box[3] = {64, 64, 3};
    encode(enc, &m.w3, w3, 3, dims, str, box, CU_TENSOR_MAP_SWIZZLE_128B);
  }
  fused_kernel<<<NCTA + NSVC, 384, SMEM_BYTES, cudaStreamPerThread>>>(m, x, wqkv, wphi, w1, w2, w3, w4, wo, gate_w, (__nv_bfloat16*)d_out);
}
```

```cpp
#include <cuda_runtime.h>
#include <cuda_bf16.h>
#include <cuda.h>
#include <stdint.h>

namespace {

constexpr int S_ = 2048, D_ = 640, F_ = 1536;
constexpr int NCTA = 128, NSVC = 4;
constexpr int KV_PAIR = 40 * 48 + 96;
constexpr int KV_J = 2 * KV_PAIR;

constexpr int SLOT_B = 49152, NB = 3;
constexpr int SLOT_A = 16384, NA = 4;
constexpr int OFF_B = 0;
constexpr int OFF_A = OFF_B + NB * SLOT_B;
constexpr int OFF_STG = OFF_A + 2 * SLOT_A;
constexpr int OFF_MISC = OFF_A + NA * SLOT_A;
constexpr int OFF_XST = OFF_MISC + 13312;
constexpr int OFF_CS = OFF_MISC + 16384;
constexpr int OFF_BAR = OFF_CS + 1088;
constexpr int SMEM_BYTES = OFF_BAR + 512 + 512 + 128;
constexpr int B_FULLA = 0, B_FULLB = 4, B_CS = 7, B_XR = 8, B_KV = 9, B_ST1 = 10, B_HST = 11, B_FULL4 = 12  , B_RDY = 20  ,
              B_DSR = 23  , B_EMPTYB = 33  , B_SIGP = 36, B_SIGH = 37, B_SIGKV = 38, B_SIGX1 = 39, B_MFREE = 40,
              B_EMPTY4 = 41  , B_EMPTYA = 49  , B_PEER = 53, B_PEER2 = 54, B_X1P = 55  , NBAR = 56;
constexpr int SPARE = 40960;
constexpr int SET4 = 87040, OFF_DS = 2 * SET4, OFF_OUT = 20480;

constexpr int FL_DONE = 0, FL_H = 1  , FL_X1 = FL_H + 32, FL_KV = FL_X1 + 16, FL_CS = FL_KV + 8, FL_CS3 = FL_CS + 1, FL_ST = FL_CS3 + 1;
constexpr int FL_S1 = FL_ST + 16, FL_COUNT = FL_S1 + 16;

struct Maps {
  CUtensorMap x, w1m, w1r, qm, qr, hs, w2, x1, w3, w4, wo, xr, st_h, st_x1;
};

}

__device__ __align__(1024) __nv_bfloat16 g_Hs[(S_ + 4) * D_];
__device__ __align__(1024) __nv_bfloat16 g_X1[S_ * D_];
__device__ __align__(128) float g_acc[2][8 * KV_J];
__device__ __align__(128) float g_cs[D_ + F_];
__device__ __align__(128) uint4 g_wphi[8 * 800];
__device__ __align__(128) float4 g_xstat[S_];
__device__ __align__(128) float2 g_st1[S_ * 8];
__device__ __align__(128) uint4 g_part[16 * 8 * 3 * 1280];
__device__ __align__(128) unsigned g_flags[FL_COUNT * 32];
#define TSTAMP(n) do {} while (0)
#define TSTAMPX(n) do {} while (0)
#define TRACE(n) do {} while (0)
#define TRS(n) do {} while (0)

namespace {

__device__ __forceinline__ long long gtime() { long long t; asm volatile("mov.u64 %0, %%globaltimer;" : "=l"(t)); return t; }
__device__ __forceinline__ uint32_t smem_u32(const void* p) { return (uint32_t)__cvta_generic_to_shared(p); }
__device__ __forceinline__ void mbar_init(uint32_t bar, int cnt) {
  asm volatile("mbarrier.init.shared::cta.b64 [%0], %1;" ::"r"(bar), "r"(cnt) : "memory");
}
__device__ __forceinline__ void mbar_expect_tx(uint32_t bar, int bytes) {
  asm volatile("mbarrier.arrive.expect_tx.shared::cta.b64 _, [%0], %1;" ::"r"(bar), "r"(bytes) : "memory");
}
__device__ __forceinline__ void mbar_arrive_cta(uint32_t bar, uint32_t cta) {
  asm volatile("{\n.reg .b32 ra;\nmapa.shared::cluster.u32 ra, %0, %1;\nmbarrier.arrive.shared::cluster.b64 _, [ra];\n}"
               ::"r"(bar), "r"(cta) : "memory");
}
__device__ __forceinline__ uint32_t mbar_try(uint32_t bar, uint32_t parity) {
  uint32_t ok;
  asm volatile("{\n.reg .pred p;\nmbarrier.try_wait.parity.shared::cta.b64 p, [%1], %2;\nselp.u32 %0, 1, 0, p;\n}"
               : "=r"(ok) : "r"(bar), "r"(parity) : "memory");
  return ok;
}
constexpr uint32_t WAIT_LIMIT = 1u << 18;
__device__ __forceinline__ void mbar_wait(uint32_t bar, uint32_t parity) {
  uint32_t n = 0;
  while (!mbar_try(bar, parity) && ++n < WAIT_LIMIT) {}
}
__device__ __forceinline__ unsigned ld_acquire(const unsigned* p) {
  unsigned v;
  asm volatile("ld.acquire.gpu.global.u32 %0, [%1];" : "=r"(v) : "l"(p) : "memory");
  return v;
}
__device__ __forceinline__ void flag_wait(int idx, unsigned target) {
  const unsigned* p = g_flags + idx * 32;
  uint32_t n = 0;
  while ((int)(ld_acquire(p) - target) < 0 && ++n < (WAIT_LIMIT >> 2)) {}
}
__device__ __forceinline__ void flag_add(int idx) {
  asm volatile("red.release.gpu.global.add.u32 [%0], 1;" ::"l"(g_flags + idx * 32) : "memory");
}
__device__ __forceinline__ void flag_add_relaxed(int idx) {
  asm volatile("red.relaxed.gpu.global.add.u32 [%0], 1;" ::"l"(g_flags + idx * 32) : "memory");
}
__device__ __forceinline__ uint32_t mbar_test(uint32_t bar, uint32_t parity) {
  uint32_t ok;
  asm volatile("{\n.reg .pred p;\nmbarrier.test_wait.parity.shared::cta.b64 p, [%1], %2;\nselp.u32 %0, 1, 0, p;\n}"
               : "=r"(ok) : "r"(bar), "r"(parity) : "memory");
  return ok;
}
__device__ __forceinline__ uint32_t lds32(uint32_t a) {
  uint32_t v;
  asm volatile("ld.shared.u32 %0, [%1];" : "=r"(v) : "r"(a) : "memory");
  return v;
}
__device__ __forceinline__ void mbar_arrive(uint32_t bar) {
  asm volatile("mbarrier.arrive.shared::cta.b64 _, [%0];" ::"r"(bar) : "memory");
}
__device__ __forceinline__ void fence_async_glb() { asm volatile("fence.proxy.async.global;" ::: "memory"); }
__device__ __forceinline__ void fence_async_smem() { asm volatile("fence.proxy.async.shared::cta;" ::: "memory"); }
__device__ __forceinline__ void bar_sync(int id, int n) { asm volatile("bar.sync %0, %1;" ::"r"(id), "r"(n) : "memory"); }

__device__ __forceinline__ void tma2d(uint32_t dst, const CUtensorMap* m, uint32_t bar, int c0, int c1) {
  asm volatile("cp.async.bulk.tensor.2d.shared::cluster.global.mbarrier::complete_tx::bytes [%0], [%1, {%3, %4}], [%2];"
               ::"r"(dst), "l"(m), "r"(bar), "r"(c0), "r"(c1) : "memory");
}
__device__ __forceinline__ void tma2d_mc(uint32_t dst, const CUtensorMap* m, uint32_t bar, int c0, int c1) {
  asm volatile("cp.async.bulk.tensor.2d.shared::cluster.global.mbarrier::complete_tx::bytes.multicast::cluster"
               " [%0], [%1, {%3, %4}], [%2], %5;"
               ::"r"(dst), "l"(m), "r"(bar), "r"(c0), "r"(c1), "h"((uint16_t)3) : "memory");
}
__device__ __forceinline__ void tma3d(uint32_t dst, const CUtensorMap* m, uint32_t bar, int c0, int c1, int c2) {
  asm volatile("cp.async.bulk.tensor.3d.shared::cluster.global.mbarrier::complete_tx::bytes [%0], [%1, {%3, %4, %5}], [%2];"
               ::"r"(dst), "l"(m), "r"(bar), "r"(c0), "r"(c1), "r"(c2) : "memory");
}
__device__ __forceinline__ void tma4d(uint32_t dst, const CUtensorMap* m, uint32_t bar, int c0, int c1, int c2, int c3) {
  asm volatile("cp.async.bulk.tensor.4d.shared::cluster.global.mbarrier::complete_tx::bytes [%0], [%1, {%3, %4, %5, %6}], [%2];"
               ::"r"(dst), "l"(m), "r"(bar), "r"(c0), "r"(c1), "r"(c2), "r"(c3) : "memory");
}
__device__ __forceinline__ void tma2d_store(const CUtensorMap* m, uint32_t src, int c0, int c1) {
  asm volatile("cp.async.bulk.tensor.2d.global.shared::cta.bulk_group [%0, {%2, %3}], [%1];"
               ::"l"(m), "r"(src), "r"(c0), "r"(c1) : "memory");
}
__device__ __forceinline__ void bulk_store(void* dst, uint32_t src, uint32_t bytes) {
  asm volatile("cp.async.bulk.global.shared::cta.bulk_group [%0], [%1], %2;" ::"l"(dst), "r"(src), "r"(bytes) : "memory");
}
__device__ __forceinline__ void bulk_load(uint32_t dst, const void* src, uint32_t bytes, uint32_t bar) {
  asm volatile("cp.async.bulk.shared::cluster.global.mbarrier::complete_tx::bytes [%0], [%1], %2, [%3];"
               ::"r"(dst), "l"(src), "r"(bytes), "r"(bar) : "memory");
}
__device__ __forceinline__ void bulk_commit() { asm volatile("cp.async.bulk.commit_group;" ::: "memory"); }
template <int N> __device__ __forceinline__ void bulk_wait() { asm volatile("cp.async.bulk.wait_group %0;" ::"n"(N) : "memory"); }
__device__ __forceinline__ void bulk_wait_read() { asm volatile("cp.async.bulk.wait_group.read 0;" ::: "memory"); }
__device__ __forceinline__ void bar_arrive(int id, int n) { asm volatile("bar.arrive %0, %1;" ::"r"(id), "r"(n) : "memory"); }
__device__ __forceinline__ uint4 lds128(uint32_t a) {
  uint4 v;
  asm volatile("ld.shared.v4.u32 {%0, %1, %2, %3}, [%4];" : "=r"(v.x), "=r"(v.y), "=r"(v.z), "=r"(v.w) : "r"(a) : "memory");
  return v;
}
__device__ __forceinline__ void sts128(uint32_t a, uint4 v) {
  asm volatile("st.shared.v4.u32 [%0], {%1, %2, %3, %4};" ::"r"(a), "r"(v.x), "r"(v.y), "r"(v.z), "r"(v.w) : "memory");
}
__device__ __forceinline__ uint4 ld_relaxed16(const uint4* p) {
  uint4 v;
  asm volatile("ld.relaxed.gpu.global.v4.u32 {%0, %1, %2, %3}, [%4];" : "=r"(v.x), "=r"(v.y), "=r"(v.z), "=r"(v.w) : "l"(p) : "memory");
  return v;
}
__device__ __forceinline__ void st_relaxed16(uint4* p, uint32_t a, uint32_t b, uint32_t c, uint32_t d) {
  asm volatile("st.relaxed.gpu.global.v4.u32 [%0], {%1, %2, %3, %4};" ::"l"(p), "r"(a), "r"(b), "r"(c), "r"(d) : "memory");
}
__device__ __forceinline__ uint32_t map_peer(uint32_t addr, uint32_t cta) {
  uint32_t r;
  asm("mapa.shared::cluster.u32 %0, %1, %2;" : "=r"(r) : "r"(addr), "r"(cta));
  return r;
}
__device__ __forceinline__ void st_async16(uint32_t addr, uint32_t a, uint32_t b, uint32_t c, uint32_t d, uint32_t bar) {
  asm volatile("st.async.weak.shared::cluster.mbarrier::complete_tx::bytes.v4.b32 [%0], {%1, %2, %3, %4}, [%5];"
               ::"r"(addr), "r"(a), "r"(b), "r"(c), "r"(d), "r"(bar) : "memory");
}
__device__ __forceinline__ void l2_prefetch(const void* p, uint32_t bytes) {
  asm volatile("cp.async.bulk.prefetch.L2.global [%0], %1;" ::"l"(p), "r"(bytes) : "memory");
}
__device__ __forceinline__ void prefetch_tmap(const CUtensorMap* m) {
  asm volatile("prefetch.tensormap [%0];" ::"l"(m) : "memory");
}
__device__ __forceinline__ uint64_t make_desc(uint32_t a16, uint32_t off, uint32_t lbo, uint32_t sbo, uint32_t swz) {
  const uint32_t lo = a16 + ((off >> 4) + ((lbo >> 4) << 16)), hi = (sbo >> 4) | (swz << 30);
  uint64_t d;
  asm("mov.b64 %0, {%1, %2};" : "=l"(d) : "r"(lo), "r"(hi));
  return d;
}
__device__ __forceinline__ void wg_fence() { asm volatile("wgmma.fence.sync.aligned;" ::: "memory"); }
__device__ __forceinline__ void wg_commit() { asm volatile("wgmma.commit_group.sync.aligned;" ::: "memory"); }
template <int N> __device__ __forceinline__ void wg_wait() { asm volatile("wgmma.wait_group.sync.aligned %0;" ::"n"(N) : "memory"); }
template <int N> __device__ __forceinline__ void fence_regs(float (&d)[N]) {
#pragma unroll
  for (int i = 0; i < N; i++) asm volatile("" : "+f"(d[i])::"memory");
}
template <int N> __device__ __forceinline__ void zero_regs(float (&d)[N]) {
#pragma unroll
  for (int i = 0; i < N; i++) d[i] = 0.f;
}
__device__ __forceinline__ uint32_t pack_bf16(float lo, float hi) {
  uint32_t r;
  asm("cvt.rn.bf16x2.f32 %0, %1, %2;" : "=r"(r) : "f"(hi), "f"(lo));
  return r;
}
__device__ __forceinline__ float bf_lo(uint32_t v) { return __uint_as_float(v << 16); }
__device__ __forceinline__ float bf_hi(uint32_t v) { return __uint_as_float(v & 0xffff0000u); }
__device__ __forceinline__ uint32_t max_bf2(uint32_t a, uint32_t b) {
  uint32_t r; asm("max.bf16x2 %0, %1, %2;" : "=r"(r) : "r"(a), "r"(b)); return r;
}
__device__ __forceinline__ uint32_t min_bf2(uint32_t a, uint32_t b) {
  uint32_t r; asm("min.bf16x2 %0, %1, %2;" : "=r"(r) : "r"(a), "r"(b)); return r;
}
__device__ __forceinline__ uint32_t add_bf2(uint32_t a, uint32_t b) {
  uint32_t r; asm("add.rn.bf16x2 %0, %1, %2;" : "=r"(r) : "r"(a), "r"(b)); return r;
}
__device__ __forceinline__ float ex2(float x) { float r; asm("ex2.approx.ftz.f32 %0, %1;" : "=f"(r) : "f"(x)); return r; }
__device__ __forceinline__ float rcp(float x) { float r; asm("rcp.approx.ftz.f32 %0, %1;" : "=f"(r) : "f"(x)); return r; }
__device__ __forceinline__ float tanh_ap(float x) { float r; asm("tanh.approx.f32 %0, %1;" : "=f"(r) : "f"(x)); return r; }
struct GeluC { float c0, c1, ch; };
__device__ __forceinline__ GeluC gelu_consts(float rstd, float scale) {
  return GeluC{0.7978845608f * rstd, 0.0356774081f * rstd * rstd * rstd, 0.5f * scale * rstd};
}
__device__ __forceinline__ float gelu_s(float y, const GeluC& c) {
  const float u = y * fmaf(y * y, c.c1, c.c0);
  const float hx = y * c.ch;
  return fmaf(hx, tanh_ap(u), hx);
}
__device__ __forceinline__ void stsm4(uint32_t addr, uint32_t r0, uint32_t r1, uint32_t r2, uint32_t r3) {
  asm volatile("stmatrix.sync.aligned.m8n8.x4.shared.b16 [%0], {%1, %2, %3, %4};"
               ::"r"(addr), "r"(r0), "r"(r1), "r"(r2), "r"(r3) : "memory");
}

__device__ __forceinline__ void mma_ss256(float (&d)[128], uint64_t descA, uint64_t descB) {
  asm volatile("wgmma.mma_async.sync.aligned.m64n256k16.f32.bf16.bf16 {"
      "%0, %1, %2, %3, %4, %5, %6, %7, %8, %9, %10, %11, %12, %13, %14, %15, "
      "%16, %17, %18, %19, %20, %21, %22, %23, %24, %25, %26, %27, %28, %29, %30, %31, "
      "%32, %33, %34, %35, %36, %37, %38, %39, %40, %41, %42, %43, %44, %45, %46, %47, "
      "%48, %49, %50, %51, %52, %53, %54, %55, %56, %57, %58, %59, %60, %61, %62, %63, "
      "%64, %65, %66, %67, %68, %69, %70, %71, %72, %73, %74, %75, %76, %77, %78, %79, "
      "%80, %81, %82, %83, %84, %85, %86, %87, %88, %89, %90, %91, %92, %93, %94, %95, "
      "%96, %97, %98, %99, %100, %101, %102, %103, %104, %105, %106, %107, %108, %109, %110, %111, "
      "%112, %113, %114, %115, %116, %117, %118, %119, %120, %121, %122, %123, %124, %125, %126, %127"
      "}, %128, %129, 1, 1, 1, 0, 1;\n"
      : "+f"(d[0]), "+f"(d[1]), "+f"(d[2]), "+f"(d[3]), "+f"(d[4]), "+f"(d[5]), "+f"(d[6]), "+f"(d[7]),
        "+f"(d[8]), "+f"(d[9]), "+f"(d[10]), "+f"(d[11]), "+f"(d[12]), "+f"(d[13]), "+f"(d[14]), "+f"(d[15]),
        "+f"(d[16]), "+f"(d[17]), "+f"(d[18]), "+f"(d[19]), "+f"(d[20]), "+f"(d[21]), "+f"(d[22]), "+f"(d[23]),
        "+f"(d[24]), "+f"(d[25]), "+f"(d[26]), "+f"(d[27]), "+f"(d[28]), "+f"(d[29]), "+f"(d[30]), "+f"(d[31]),
        "+f"(d[32]), "+f"(d[33]), "+f"(d[34]), "+f"(d[35]), "+f"(d[36]), "+f"(d[37]), "+f"(d[38]), "+f"(d[39]),
        "+f"(d[40]), "+f"(d[41]), "+f"(d[42]), "+f"(d[43]), "+f"(d[44]), "+f"(d[45]), "+f"(d[46]), "+f"(d[47]),
        "+f"(d[48]), "+f"(d[49]), "+f"(d[50]), "+f"(d[51]), "+f"(d[52]), "+f"(d[53]), "+f"(d[54]), "+f"(d[55]),
        "+f"(d[56]), "+f"(d[57]), "+f"(d[58]), "+f"(d[59]), "+f"(d[60]), "+f"(d[61]), "+f"(d[62]), "+f"(d[63]),
        "+f"(d[64]), "+f"(d[65]), "+f"(d[66]), "+f"(d[67]), "+f"(d[68]), "+f"(d[69]), "+f"(d[70]), "+f"(d[71]),
        "+f"(d[72]), "+f"(d[73]), "+f"(d[74]), "+f"(d[75]), "+f"(d[76]), "+f"(d[77]), "+f"(d[78]), "+f"(d[79]),
        "+f"(d[80]), "+f"(d[81]), "+f"(d[82]), "+f"(d[83]), "+f"(d[84]), "+f"(d[85]), "+f"(d[86]), "+f"(d[87]),
        "+f"(d[88]), "+f"(d[89]), "+f"(d[90]), "+f"(d[91]), "+f"(d[92]), "+f"(d[93]), "+f"(d[94]), "+f"(d[95]),
        "+f"(d[96]), "+f"(d[97]), "+f"(d[98]), "+f"(d[99]), "+f"(d[100]), "+f"(d[101]), "+f"(d[102]), "+f"(d[103]),
        "+f"(d[104]), "+f"(d[105]), "+f"(d[106]), "+f"(d[107]), "+f"(d[108]), "+f"(d[109]), "+f"(d[110]), "+f"(d[111]),
        "+f"(d[112]), "+f"(d[113]), "+f"(d[114]), "+f"(d[115]), "+f"(d[116]), "+f"(d[117]), "+f"(d[118]), "+f"(d[119]),
        "+f"(d[120]), "+f"(d[121]), "+f"(d[122]), "+f"(d[123]), "+f"(d[124]), "+f"(d[125]), "+f"(d[126]), "+f"(d[127])
      : "l"(descA), "l"(descB));
}
__device__ __forceinline__ void mma_ss256_p(float (&d)[128], uint64_t descA, uint64_t descB, int acc) {
  asm volatile("{\n.reg .pred p;\nsetp.ne.b32 p, %130, 0;\n"
      "wgmma.mma_async.sync.aligned.m64n256k16.f32.bf16.bf16 {"
      "%0, %1, %2, %3, %4, %5, %6, %7, %8, %9, %10, %11, %12, %13, %14, %15, "
      "%16, %17, %18, %19, %20, %21, %22, %23, %24, %25, %26, %27, %28, %29, %30, %31, "
      "%32, %33, %34, %35, %36, %37, %38, %39, %40, %41, %42, %43, %44, %45, %46, %47, "
      "%48, %49, %50, %51, %52, %53, %54, %55, %56, %57, %58, %59, %60, %61, %62, %63, "
      "%64, %65, %66, %67, %68, %69, %70, %71, %72, %73, %74, %75, %76, %77, %78, %79, "
      "%80, %81, %82, %83, %84, %85, %86, %87, %88, %89, %90, %91, %92, %93, %94, %95, "
      "%96, %97, %98, %99, %100, %101, %102, %103, %104, %105, %106, %107, %108, %109, %110, %111, "
      "%112, %113, %114, %115, %116, %117, %118, %119, %120, %121, %122, %123, %124, %125, %126, %127"
      "}, %128, %129, p, 1, 1, 0, 1;\n}\n"
      : "+f"(d[0]), "+f"(d[1]), "+f"(d[2]), "+f"(d[3]), "+f"(d[4]), "+f"(d[5]), "+f"(d[6]), "+f"(d[7]),
        "+f"(d[8]), "+f"(d[9]), "+f"(d[10]), "+f"(d[11]), "+f"(d[12]), "+f"(d[13]), "+f"(d[14]), "+f"(d[15]),
        "+f"(d[16]), "+f"(d[17]), "+f"(d[18]), "+f"(d[19]), "+f"(d[20]), "+f"(d[21]), "+f"(d[22]), "+f"(d[23]),
        "+f"(d[24]), "+f"(d[25]), "+f"(d[26]), "+f"(d[27]), "+f"(d[28]), "+f"(d[29]), "+f"(d[30]), "+f"(d[31]),
        "+f"(d[32]), "+f"(d[33]), "+f"(d[34]), "+f"(d[35]), "+f"(d[36]), "+f"(d[37]), "+f"(d[38]), "+f"(d[39]),
        "+f"(d[40]), "+f"(d[41]), "+f"(d[42]), "+f"(d[43]), "+f"(d[44]), "+f"(d[45]), "+f"(d[46]), "+f"(d[47]),
        "+f"(d[48]), "+f"(d[49]), "+f"(d[50]), "+f"(d[51]), "+f"(d[52]), "+f"(d[53]), "+f"(d[54]), "+f"(d[55]),
        "+f"(d[56]), "+f"(d[57]), "+f"(d[58]), "+f"(d[59]), "+f"(d[60]), "+f"(d[61]), "+f"(d[62]), "+f"(d[63]),
        "+f"(d[64]), "+f"(d[65]), "+f"(d[66]), "+f"(d[67]), "+f"(d[68]), "+f"(d[69]), "+f"(d[70]), "+f"(d[71]),
        "+f"(d[72]), "+f"(d[73]), "+f"(d[74]), "+f"(d[75]), "+f"(d[76]), "+f"(d[77]), "+f"(d[78]), "+f"(d[79]),
        "+f"(d[80]), "+f"(d[81]), "+f"(d[82]), "+f"(d[83]), "+f"(d[84]), "+f"(d[85]), "+f"(d[86]), "+f"(d[87]),
        "+f"(d[88]), "+f"(d[89]), "+f"(d[90]), "+f"(d[91]), "+f"(d[92]), "+f"(d[93]), "+f"(d[94]), "+f"(d[95]),
        "+f"(d[96]), "+f"(d[97]), "+f"(d[98]), "+f"(d[99]), "+f"(d[100]), "+f"(d[101]), "+f"(d[102]), "+f"(d[103]),
        "+f"(d[104]), "+f"(d[105]), "+f"(d[106]), "+f"(d[107]), "+f"(d[108]), "+f"(d[109]), "+f"(d[110]), "+f"(d[111]),
        "+f"(d[112]), "+f"(d[113]), "+f"(d[114]), "+f"(d[115]), "+f"(d[116]), "+f"(d[117]), "+f"(d[118]), "+f"(d[119]),
        "+f"(d[120]), "+f"(d[121]), "+f"(d[122]), "+f"(d[123]), "+f"(d[124]), "+f"(d[125]), "+f"(d[126]), "+f"(d[127])
      : "l"(descA), "l"(descB), "r"(acc));
}

__device__ __forceinline__ void mma_ss64(float (&d)[32], uint64_t descA, uint64_t descB) {
  asm volatile("wgmma.mma_async.sync.aligned.m64n64k16.f32.bf16.bf16 {"
      "%0, %1, %2, %3, %4, %5, %6, %7, %8, %9, %10, %11, %12, %13, %14, %15, "
      "%16, %17, %18, %19, %20, %21, %22, %23, %24, %25, %26, %27, %28, %29, %30, %31"
      "}, %32, %33, 1, 1, 1, 0, 1;\n"
      : "+f"(d[0]), "+f"(d[1]), "+f"(d[2]), "+f"(d[3]), "+f"(d[4]), "+f"(d[5]), "+f"(d[6]), "+f"(d[7]),
        "+f"(d[8]), "+f"(d[9]), "+f"(d[10]), "+f"(d[11]), "+f"(d[12]), "+f"(d[13]), "+f"(d[14]), "+f"(d[15]),
        "+f"(d[16]), "+f"(d[17]), "+f"(d[18]), "+f"(d[19]), "+f"(d[20]), "+f"(d[21]), "+f"(d[22]), "+f"(d[23]),
        "+f"(d[24]), "+f"(d[25]), "+f"(d[26]), "+f"(d[27]), "+f"(d[28]), "+f"(d[29]), "+f"(d[30]), "+f"(d[31])
      : "l"(descA), "l"(descB));
}
__device__ __forceinline__ void mma_ss64_p(float (&d)[32], uint64_t descA, uint64_t descB, int acc) {
  asm volatile("{\n.reg .pred p;\nsetp.ne.b32 p, %34, 0;\n"
      "wgmma.mma_async.sync.aligned.m64n64k16.f32.bf16.bf16 {"
      "%0, %1, %2, %3, %4, %5, %6, %7, %8, %9, %10, %11, %12, %13, %14, %15, "
      "%16, %17, %18, %19, %20, %21, %22, %23, %24, %25, %26, %27, %28, %29, %30, %31"
      "}, %32, %33, p, 1, 1, 0, 1;\n}\n"
      : "+f"(d[0]), "+f"(d[1]), "+f"(d[2]), "+f"(d[3]), "+f"(d[4]), "+f"(d[5]), "+f"(d[6]), "+f"(d[7]),
        "+f"(d[8]), "+f"(d[9]), "+f"(d[10]), "+f"(d[11]), "+f"(d[12]), "+f"(d[13]), "+f"(d[14]), "+f"(d[15]),
        "+f"(d[16]), "+f"(d[17]), "+f"(d[18]), "+f"(d[19]), "+f"(d[20]), "+f"(d[21]), "+f"(d[22]), "+f"(d[23]),
        "+f"(d[24]), "+f"(d[25]), "+f"(d[26]), "+f"(d[27]), "+f"(d[28]), "+f"(d[29]), "+f"(d[30]), "+f"(d[31])
      : "l"(descA), "l"(descB), "r"(acc));
}

__device__ __forceinline__ void mma_ss160(float (&d)[80], uint64_t descA, uint64_t descB) {
  asm volatile("wgmma.mma_async.sync.aligned.m64n160k16.f32.bf16.bf16 {"
      "%0, %1, %2, %3, %4, %5, %6, %7, %8, %9, %10, %11, %12, %13, %14, %15, "
      "%16, %17, %18, %19, %20, %21, %22, %23, %24, %25, %26, %27, %28, %29, %30, %31, "
      "%32, %33, %34, %35, %36, %37, %38, %39, %40, %41, %42, %43, %44, %45, %46, %47, "
      "%48, %49, %50, %51, %52, %53, %54, %55, %56, %57, %58, %59, %60, %61, %62, %63, "
      "%64, %65, %66, %67, %68, %69, %70, %71, %72, %73, %74, %75, %76, %77, %78, %79"
      "}, %80, %81, 1, 1, 1, 0, 1;\n"
      : "+f"(d[0]), "+f"(d[1]), "+f"(d[2]), "+f"(d[3]), "+f"(d[4]), "+f"(d[5]), "+f"(d[6]), "+f"(d[7]),
        "+f"(d[8]), "+f"(d[9]), "+f"(d[10]), "+f"(d[11]), "+f"(d[12]), "+f"(d[13]), "+f"(d[14]), "+f"(d[15]),
        "+f"(d[16]), "+f"(d[17]), "+f"(d[18]), "+f"(d[19]), "+f"(d[20]), "+f"(d[21]), "+f"(d[22]), "+f"(d[23]),
        "+f"(d[24]), "+f"(d[25]), "+f"(d[26]), "+f"(d[27]), "+f"(d[28]), "+f"(d[29]), "+f"(d[30]), "+f"(d[31]),
        "+f"(d[32]), "+f"(d[33]), "+f"(d[34]), "+f"(d[35]), "+f"(d[36]), "+f"(d[37]), "+f"(d[38]), "+f"(d[39]),
        "+f"(d[40]), "+f"(d[41]), "+f"(d[42]), "+f"(d[43]), "+f"(d[44]), "+f"(d[45]), "+f"(d[46]), "+f"(d[47]),
        "+f"(d[48]), "+f"(d[49]), "+f"(d[50]), "+f"(d[51]), "+f"(d[52]), "+f"(d[53]), "+f"(d[54]), "+f"(d[55]),
        "+f"(d[56]), "+f"(d[57]), "+f"(d[58]), "+f"(d[59]), "+f"(d[60]), "+f"(d[61]), "+f"(d[62]), "+f"(d[63]),
        "+f"(d[64]), "+f"(d[65]), "+f"(d[66]), "+f"(d[67]), "+f"(d[68]), "+f"(d[69]), "+f"(d[70]), "+f"(d[71]),
        "+f"(d[72]), "+f"(d[73]), "+f"(d[74]), "+f"(d[75]), "+f"(d[76]), "+f"(d[77]), "+f"(d[78]), "+f"(d[79])
      : "l"(descA), "l"(descB));
}
__device__ __forceinline__ void mma_ss160_z(float (&d)[80], uint64_t descA, uint64_t descB) {
  asm volatile("wgmma.mma_async.sync.aligned.m64n160k16.f32.bf16.bf16 {"
      "%0, %1, %2, %3, %4, %5, %6, %7, %8, %9, %10, %11, %12, %13, %14, %15, "
      "%16, %17, %18, %19, %20, %21, %22, %23, %24, %25, %26, %27, %28, %29, %30, %31, "
      "%32, %33, %34, %35, %36, %37, %38, %39, %40, %41, %42, %43, %44, %45, %46, %47, "
      "%48, %49, %50, %51, %52, %53, %54, %55, %56, %57, %58, %59, %60, %61, %62, %63, "
      "%64, %65, %66, %67, %68, %69, %70, %71, %72, %73, %74, %75, %76, %77, %78, %79"
      "}, %80, %81, 0, 1, 1, 0, 1;\n"
      : "=f"(d[0]), "=f"(d[1]), "=f"(d[2]), "=f"(d[3]), "=f"(d[4]), "=f"(d[5]), "=f"(d[6]), "=f"(d[7]),
        "=f"(d[8]), "=f"(d[9]), "=f"(d[10]), "=f"(d[11]), "=f"(d[12]), "=f"(d[13]), "=f"(d[14]), "=f"(d[15]),
        "=f"(d[16]), "=f"(d[17]), "=f"(d[18]), "=f"(d[19]), "=f"(d[20]), "=f"(d[21]), "=f"(d[22]), "=f"(d[23]),
        "=f"(d[24]), "=f"(d[25]), "=f"(d[26]), "=f"(d[27]), "=f"(d[28]), "=f"(d[29]), "=f"(d[30]), "=f"(d[31]),
        "=f"(d[32]), "=f"(d[33]), "=f"(d[34]), "=f"(d[35]), "=f"(d[36]), "=f"(d[37]), "=f"(d[38]), "=f"(d[39]),
        "=f"(d[40]), "=f"(d[41]), "=f"(d[42]), "=f"(d[43]), "=f"(d[44]), "=f"(d[45]), "=f"(d[46]), "=f"(d[47]),
        "=f"(d[48]), "=f"(d[49]), "=f"(d[50]), "=f"(d[51]), "=f"(d[52]), "=f"(d[53]), "=f"(d[54]), "=f"(d[55]),
        "=f"(d[56]), "=f"(d[57]), "=f"(d[58]), "=f"(d[59]), "=f"(d[60]), "=f"(d[61]), "=f"(d[62]), "=f"(d[63]),
        "=f"(d[64]), "=f"(d[65]), "=f"(d[66]), "=f"(d[67]), "=f"(d[68]), "=f"(d[69]), "=f"(d[70]), "=f"(d[71]),
        "=f"(d[72]), "=f"(d[73]), "=f"(d[74]), "=f"(d[75]), "=f"(d[76]), "=f"(d[77]), "=f"(d[78]), "=f"(d[79])
      : "l"(descA), "l"(descB));
}

__device__ __forceinline__ void mma_ss192(float (&d)[96], uint64_t descA, uint64_t descB) {
  asm volatile("wgmma.mma_async.sync.aligned.m64n192k16.f32.bf16.bf16 {"
      "%0, %1, %2, %3, %4, %5, %6, %7, %8, %9, %10, %11, %12, %13, %14, %15, "
      "%16, %17, %18, %19, %20, %21, %22, %23, %24, %25, %26, %27, %28, %29, %30, %31, "
      "%32, %33, %34, %35, %36, %37, %38, %39, %40, %41, %42, %43, %44, %45, %46, %47, "
      "%48, %49, %50, %51, %52, %53, %54, %55, %56, %57, %58, %59, %60, %61, %62, %63, "
      "%64, %65, %66, %67, %68, %69, %70, %71, %72, %73, %74, %75, %76, %77, %78, %79, "
      "%80, %81, %82, %83, %84, %85, %86, %87, %88, %89, %90, %91, %92, %93, %94, %95"
      "}, %96, %97, 1, 1, 1, 0, 1;\n"
      : "+f"(d[0]), "+f"(d[1]), "+f"(d[2]), "+f"(d[3]), "+f"(d[4]), "+f"(d[5]), "+f"(d[6]), "+f"(d[7]),
        "+f"(d[8]), "+f"(d[9]), "+f"(d[10]), "+f"(d[11]), "+f"(d[12]), "+f"(d[13]), "+f"(d[14]), "+f"(d[15]),
        "+f"(d[16]), "+f"(d[17]), "+f"(d[18]), "+f"(d[19]), "+f"(d[20]), "+f"(d[21]), "+f"(d[22]), "+f"(d[23]),
        "+f"(d[24]), "+f"(d[25]), "+f"(d[26]), "+f"(d[27]), "+f"(d[28]), "+f"(d[29]), "+f"(d[30]), "+f"(d[31]),
        "+f"(d[32]), "+f"(d[33]), "+f"(d[34]), "+f"(d[35]), "+f"(d[36]), "+f"(d[37]), "+f"(d[38]), "+f"(d[39]),
        "+f"(d[40]), "+f"(d[41]), "+f"(d[42]), "+f"(d[43]), "+f"(d[44]), "+f"(d[45]), "+f"(d[46]), "+f"(d[47]),
        "+f"(d[48]), "+f"(d[49]), "+f"(d[50]), "+f"(d[51]), "+f"(d[52]), "+f"(d[53]), "+f"(d[54]), "+f"(d[55]),
        "+f"(d[56]), "+f"(d[57]), "+f"(d[58]), "+f"(d[59]), "+f"(d[60]), "+f"(d[61]), "+f"(d[62]), "+f"(d[63]),
        "+f"(d[64]), "+f"(d[65]), "+f"(d[66]), "+f"(d[67]), "+f"(d[68]), "+f"(d[69]), "+f"(d[70]), "+f"(d[71]),
        "+f"(d[72]), "+f"(d[73]), "+f"(d[74]), "+f"(d[75]), "+f"(d[76]), "+f"(d[77]), "+f"(d[78]), "+f"(d[79]),
        "+f"(d[80]), "+f"(d[81]), "+f"(d[82]), "+f"(d[83]), "+f"(d[84]), "+f"(d[85]), "+f"(d[86]), "+f"(d[87]),
        "+f"(d[88]), "+f"(d[89]), "+f"(d[90]), "+f"(d[91]), "+f"(d[92]), "+f"(d[93]), "+f"(d[94]), "+f"(d[95])
      : "l"(descA), "l"(descB));
}
__device__ __forceinline__ void mma_ss192_p(float (&d)[96], uint64_t descA, uint64_t descB, int acc) {
  asm volatile("{\n.reg .pred p;\nsetp.ne.b32 p, %98, 0;\n"
      "wgmma.mma_async.sync.aligned.m64n192k16.f32.bf16.bf16 {"
      "%0, %1, %2, %3, %4, %5, %6, %7, %8, %9, %10, %11, %12, %13, %14, %15, "
      "%16, %17, %18, %19, %20, %21, %22, %23, %24, %25, %26, %27, %28, %29, %30, %31, "
      "%32, %33, %34, %35, %36, %37, %38, %39, %40, %41, %42, %43, %44, %45, %46, %47, "
      "%48, %49, %50, %51, %52, %53, %54, %55, %56, %57, %58, %59, %60, %61, %62, %63, "
      "%64, %65, %66, %67, %68, %69, %70, %71, %72, %73, %74, %75, %76, %77, %78, %79, "
      "%80, %81, %82, %83, %84, %85, %86, %87, %88, %89, %90, %91, %92, %93, %94, %95"
      "}, %96, %97, p, 1, 1, 0, 1;\n}\n"
      : "+f"(d[0]), "+f"(d[1]), "+f"(d[2]), "+f"(d[3]), "+f"(d[4]), "+f"(d[5]), "+f"(d[6]), "+f"(d[7]),
        "+f"(d[8]), "+f"(d[9]), "+f"(d[10]), "+f"(d[11]), "+f"(d[12]), "+f"(d[13]), "+f"(d[14]), "+f"(d[15]),
        "+f"(d[16]), "+f"(d[17]), "+f"(d[18]), "+f"(d[19]), "+f"(d[20]), "+f"(d[21]), "+f"(d[22]), "+f"(d[23]),
        "+f"(d[24]), "+f"(d[25]), "+f"(d[26]), "+f"(d[27]), "+f"(d[28]), "+f"(d[29]), "+f"(d[30]), "+f"(d[31]),
        "+f"(d[32]), "+f"(d[33]), "+f"(d[34]), "+f"(d[35]), "+f"(d[36]), "+f"(d[37]), "+f"(d[38]), "+f"(d[39]),
        "+f"(d[40]), "+f"(d[41]), "+f"(d[42]), "+f"(d[43]), "+f"(d[44]), "+f"(d[45]), "+f"(d[46]), "+f"(d[47]),
        "+f"(d[48]), "+f"(d[49]), "+f"(d[50]), "+f"(d[51]), "+f"(d[52]), "+f"(d[53]), "+f"(d[54]), "+f"(d[55]),
        "+f"(d[56]), "+f"(d[57]), "+f"(d[58]), "+f"(d[59]), "+f"(d[60]), "+f"(d[61]), "+f"(d[62]), "+f"(d[63]),
        "+f"(d[64]), "+f"(d[65]), "+f"(d[66]), "+f"(d[67]), "+f"(d[68]), "+f"(d[69]), "+f"(d[70]), "+f"(d[71]),
        "+f"(d[72]), "+f"(d[73]), "+f"(d[74]), "+f"(d[75]), "+f"(d[76]), "+f"(d[77]), "+f"(d[78]), "+f"(d[79]),
        "+f"(d[80]), "+f"(d[81]), "+f"(d[82]), "+f"(d[83]), "+f"(d[84]), "+f"(d[85]), "+f"(d[86]), "+f"(d[87]),
        "+f"(d[88]), "+f"(d[89]), "+f"(d[90]), "+f"(d[91]), "+f"(d[92]), "+f"(d[93]), "+f"(d[94]), "+f"(d[95])
      : "l"(descA), "l"(descB), "r"(acc));
}

__device__ __forceinline__ void mma_ss80_tt(float (&d)[40], uint64_t descA, uint64_t descB) {
  asm volatile("wgmma.mma_async.sync.aligned.m64n80k16.f32.bf16.bf16 {"
      "%0, %1, %2, %3, %4, %5, %6, %7, %8, %9, %10, %11, %12, %13, %14, %15, "
      "%16, %17, %18, %19, %20, %21, %22, %23, %24, %25, %26, %27, %28, %29, %30, %31, "
      "%32, %33, %34, %35, %36, %37, %38, %39"
      "}, %40, %41, 1, 1, 1, 1, 1;\n"
      : "+f"(d[0]), "+f"(d[1]), "+f"(d[2]), "+f"(d[3]), "+f"(d[4]), "+f"(d[5]), "+f"(d[6]), "+f"(d[7]),
        "+f"(d[8]), "+f"(d[9]), "+f"(d[10]), "+f"(d[11]), "+f"(d[12]), "+f"(d[13]), "+f"(d[14]), "+f"(d[15]),
        "+f"(d[16]), "+f"(d[17]), "+f"(d[18]), "+f"(d[19]), "+f"(d[20]), "+f"(d[21]), "+f"(d[22]), "+f"(d[23]),
        "+f"(d[24]), "+f"(d[25]), "+f"(d[26]), "+f"(d[27]), "+f"(d[28]), "+f"(d[29]), "+f"(d[30]), "+f"(d[31]),
        "+f"(d[32]), "+f"(d[33]), "+f"(d[34]), "+f"(d[35]), "+f"(d[36]), "+f"(d[37]), "+f"(d[38]), "+f"(d[39])
      : "l"(descA), "l"(descB));
}
__device__ __forceinline__ void mma_ss80_tt_z(float (&d)[40], uint64_t descA, uint64_t descB) {
  asm volatile("wgmma.mma_async.sync.aligned.m64n80k16.f32.bf16.bf16 {"
      "%0, %1, %2, %3, %4, %5, %6, %7, %8, %9, %10, %11, %12, %13, %14, %15, "
      "%16, %17, %18, %19, %20, %21, %22, %23, %24, %25, %26, %27, %28, %29, %30, %31, "
      "%32, %33, %34, %35, %36, %37, %38, %39"
      "}, %40, %41, 0, 1, 1, 1, 1;\n"
      : "=f"(d[0]), "=f"(d[1]), "=f"(d[2]), "=f"(d[3]), "=f"(d[4]), "=f"(d[5]), "=f"(d[6]), "=f"(d[7]),
        "=f"(d[8]), "=f"(d[9]), "=f"(d[10]), "=f"(d[11]), "=f"(d[12]), "=f"(d[13]), "=f"(d[14]), "=f"(d[15]),
        "=f"(d[16]), "=f"(d[17]), "=f"(d[18]), "=f"(d[19]), "=f"(d[20]), "=f"(d[21]), "=f"(d[22]), "=f"(d[23]),
        "=f"(d[24]), "=f"(d[25]), "=f"(d[26]), "=f"(d[27]), "=f"(d[28]), "=f"(d[29]), "=f"(d[30]), "=f"(d[31]),
        "=f"(d[32]), "=f"(d[33]), "=f"(d[34]), "=f"(d[35]), "=f"(d[36]), "=f"(d[37]), "=f"(d[38]), "=f"(d[39])
      : "l"(descA), "l"(descB));
}

__device__ __forceinline__ void mma_rs80_k(float (&d)[40], const uint32_t (&a)[4], uint64_t descB) {
  asm volatile("wgmma.mma_async.sync.aligned.m64n80k16.f32.bf16.bf16 {"
      "%0, %1, %2, %3, %4, %5, %6, %7, %8, %9, %10, %11, %12, %13, %14, %15, "
      "%16, %17, %18, %19, %20, %21, %22, %23, %24, %25, %26, %27, %28, %29, %30, %31, "
      "%32, %33, %34, %35, %36, %37, %38, %39"
      "}, {%40, %41, %42, %43}, %44, 1, 1, 1, 0;\n"
      : "+f"(d[0]), "+f"(d[1]), "+f"(d[2]), "+f"(d[3]), "+f"(d[4]), "+f"(d[5]), "+f"(d[6]), "+f"(d[7]),
        "+f"(d[8]), "+f"(d[9]), "+f"(d[10]), "+f"(d[11]), "+f"(d[12]), "+f"(d[13]), "+f"(d[14]), "+f"(d[15]),
        "+f"(d[16]), "+f"(d[17]), "+f"(d[18]), "+f"(d[19]), "+f"(d[20]), "+f"(d[21]), "+f"(d[22]), "+f"(d[23]),
        "+f"(d[24]), "+f"(d[25]), "+f"(d[26]), "+f"(d[27]), "+f"(d[28]), "+f"(d[29]), "+f"(d[30]), "+f"(d[31]),
        "+f"(d[32]), "+f"(d[33]), "+f"(d[34]), "+f"(d[35]), "+f"(d[36]), "+f"(d[37]), "+f"(d[38]), "+f"(d[39])
      : "r"(a[0]), "r"(a[1]), "r"(a[2]), "r"(a[3]), "l"(descB));
}
__device__ __forceinline__ void mma_rs80_k_z(float (&d)[40], const uint32_t (&a)[4], uint64_t descB) {
  asm volatile("wgmma.mma_async.sync.aligned.m64n80k16.f32.bf16.bf16 {"
      "%0, %1, %2, %3, %4, %5, %6, %7, %8, %9, %10, %11, %12, %13, %14, %15, "
      "%16, %17, %18, %19, %20, %21, %22, %23, %24, %25, %26, %27, %28, %29, %30, %31, "
      "%32, %33, %34, %35, %36, %37, %38, %39"
      "}, {%40, %41, %42, %43}, %44, 0, 1, 1, 0;\n"
      : "=f"(d[0]), "=f"(d[1]), "=f"(d[2]), "=f"(d[3]), "=f"(d[4]), "=f"(d[5]), "=f"(d[6]), "=f"(d[7]),
        "=f"(d[8]), "=f"(d[9]), "=f"(d[10]), "=f"(d[11]), "=f"(d[12]), "=f"(d[13]), "=f"(d[14]), "=f"(d[15]),
        "=f"(d[16]), "=f"(d[17]), "=f"(d[18]), "=f"(d[19]), "=f"(d[20]), "=f"(d[21]), "=f"(d[22]), "=f"(d[23]),
        "=f"(d[24]), "=f"(d[25]), "=f"(d[26]), "=f"(d[27]), "=f"(d[28]), "=f"(d[29]), "=f"(d[30]), "=f"(d[31]),
        "=f"(d[32]), "=f"(d[33]), "=f"(d[34]), "=f"(d[35]), "=f"(d[36]), "=f"(d[37]), "=f"(d[38]), "=f"(d[39])
      : "r"(a[0]), "r"(a[1]), "r"(a[2]), "r"(a[3]), "l"(descB));
}

__device__ __forceinline__ void mma_rs48_k(float (&d)[24], const uint32_t (&a)[4], uint64_t descB) {
  asm volatile("wgmma.mma_async.sync.aligned.m64n48k16.f32.bf16.bf16 {"
      "%0, %1, %2, %3, %4, %5, %6, %7, %8, %9, %10, %11, %12, %13, %14, %15, "
      "%16, %17, %18, %19, %20, %21, %22, %23"
      "}, {%24, %25, %26, %27}, %28, 1, 1, 1, 0;\n"
      : "+f"(d[0]), "+f"(d[1]), "+f"(d[2]), "+f"(d[3]), "+f"(d[4]), "+f"(d[5]), "+f"(d[6]), "+f"(d[7]),
        "+f"(d[8]), "+f"(d[9]), "+f"(d[10]), "+f"(d[11]), "+f"(d[12]), "+f"(d[13]), "+f"(d[14]), "+f"(d[15]),
        "+f"(d[16]), "+f"(d[17]), "+f"(d[18]), "+f"(d[19]), "+f"(d[20]), "+f"(d[21]), "+f"(d[22]), "+f"(d[23])
      : "r"(a[0]), "r"(a[1]), "r"(a[2]), "r"(a[3]), "l"(descB));
}
__device__ __forceinline__ void mma_rs48_k_z(float (&d)[24], const uint32_t (&a)[4], uint64_t descB) {
  asm volatile("wgmma.mma_async.sync.aligned.m64n48k16.f32.bf16.bf16 {"
      "%0, %1, %2, %3, %4, %5, %6, %7, %8, %9, %10, %11, %12, %13, %14, %15, "
      "%16, %17, %18, %19, %20, %21, %22, %23"
      "}, {%24, %25, %26, %27}, %28, 0, 1, 1, 0;\n"
      : "=f"(d[0]), "=f"(d[1]), "=f"(d[2]), "=f"(d[3]), "=f"(d[4]), "=f"(d[5]), "=f"(d[6]), "=f"(d[7]),
        "=f"(d[8]), "=f"(d[9]), "=f"(d[10]), "=f"(d[11]), "=f"(d[12]), "=f"(d[13]), "=f"(d[14]), "=f"(d[15]),
        "=f"(d[16]), "=f"(d[17]), "=f"(d[18]), "=f"(d[19]), "=f"(d[20]), "=f"(d[21]), "=f"(d[22]), "=f"(d[23])
      : "r"(a[0]), "r"(a[1]), "r"(a[2]), "r"(a[3]), "l"(descB));
}

__device__ __forceinline__ void mma_rs160_n(float (&d)[80], const uint32_t (&a)[4], uint64_t descB) {
  asm volatile("wgmma.mma_async.sync.aligned.m64n160k16.f32.bf16.bf16 {"
      "%0, %1, %2, %3, %4, %5, %6, %7, %8, %9, %10, %11, %12, %13, %14, %15, "
      "%16, %17, %18, %19, %20, %21, %22, %23, %24, %25, %26, %27, %28, %29, %30, %31, "
      "%32, %33, %34, %35, %36, %37, %38, %39, %40, %41, %42, %43, %44, %45, %46, %47, "
      "%48, %49, %50, %51, %52, %53, %54, %55, %56, %57, %58, %59, %60, %61, %62, %63, "
      "%64, %65, %66, %67, %68, %69, %70, %71, %72, %73, %74, %75, %76, %77, %78, %79"
      "}, {%80, %81, %82, %83}, %84, 1, 1, 1, 1;\n"
      : "+f"(d[0]), "+f"(d[1]), "+f"(d[2]), "+f"(d[3]), "+f"(d[4]), "+f"(d[5]), "+f"(d[6]), "+f"(d[7]),
        "+f"(d[8]), "+f"(d[9]), "+f"(d[10]), "+f"(d[11]), "+f"(d[12]), "+f"(d[13]), "+f"(d[14]), "+f"(d[15]),
        "+f"(d[16]), "+f"(d[17]), "+f"(d[18]), "+f"(d[19]), "+f"(d[20]), "+f"(d[21]), "+f"(d[22]), "+f"(d[23]),
        "+f"(d[24]), "+f"(d[25]), "+f"(d[26]), "+f"(d[27]), "+f"(d[28]), "+f"(d[29]), "+f"(d[30]), "+f"(d[31]),
        "+f"(d[32]), "+f"(d[33]), "+f"(d[34]), "+f"(d[35]), "+f"(d[36]), "+f"(d[37]), "+f"(d[38]), "+f"(d[39]),
        "+f"(d[40]), "+f"(d[41]), "+f"(d[42]), "+f"(d[43]), "+f"(d[44]), "+f"(d[45]), "+f"(d[46]), "+f"(d[47]),
        "+f"(d[48]), "+f"(d[49]), "+f"(d[50]), "+f"(d[51]), "+f"(d[52]), "+f"(d[53]), "+f"(d[54]), "+f"(d[55]),
        "+f"(d[56]), "+f"(d[57]), "+f"(d[58]), "+f"(d[59]), "+f"(d[60]), "+f"(d[61]), "+f"(d[62]), "+f"(d[63]),
        "+f"(d[64]), "+f"(d[65]), "+f"(d[66]), "+f"(d[67]), "+f"(d[68]), "+f"(d[69]), "+f"(d[70]), "+f"(d[71]),
        "+f"(d[72]), "+f"(d[73]), "+f"(d[74]), "+f"(d[75]), "+f"(d[76]), "+f"(d[77]), "+f"(d[78]), "+f"(d[79])
      : "r"(a[0]), "r"(a[1]), "r"(a[2]), "r"(a[3]), "l"(descB));
}
__device__ __forceinline__ void mma_rs160_n_z(float (&d)[80], const uint32_t (&a)[4], uint64_t descB) {
  asm volatile("wgmma.mma_async.sync.aligned.m64n160k16.f32.bf16.bf16 {"
      "%0, %1, %2, %3, %4, %5, %6, %7, %8, %9, %10, %11, %12, %13, %14, %15, "
      "%16, %17, %18, %19, %20, %21, %22, %23, %24, %25, %26, %27, %28, %29, %30, %31, "
      "%32, %33, %34, %35, %36, %37, %38, %39, %40, %41, %42, %43, %44, %45, %46, %47, "
      "%48, %49, %50, %51, %52, %53, %54, %55, %56, %57, %58, %59, %60, %61, %62, %63, "
      "%64, %65, %66, %67, %68, %69, %70, %71, %72, %73, %74, %75, %76, %77, %78, %79"
      "}, {%80, %81, %82, %83}, %84, 0, 1, 1, 1;\n"
      : "=f"(d[0]), "=f"(d[1]), "=f"(d[2]), "=f"(d[3]), "=f"(d[4]), "=f"(d[5]), "=f"(d[6]), "=f"(d[7]),
        "=f"(d[8]), "=f"(d[9]), "=f"(d[10]), "=f"(d[11]), "=f"(d[12]), "=f"(d[13]), "=f"(d[14]), "=f"(d[15]),
        "=f"(d[16]), "=f"(d[17]), "=f"(d[18]), "=f"(d[19]), "=f"(d[20]), "=f"(d[21]), "=f"(d[22]), "=f"(d[23]),
        "=f"(d[24]), "=f"(d[25]), "=f"(d[26]), "=f"(d[27]), "=f"(d[28]), "=f"(d[29]), "=f"(d[30]), "=f"(d[31]),
        "=f"(d[32]), "=f"(d[33]), "=f"(d[34]), "=f"(d[35]), "=f"(d[36]), "=f"(d[37]), "=f"(d[38]), "=f"(d[39]),
        "=f"(d[40]), "=f"(d[41]), "=f"(d[42]), "=f"(d[43]), "=f"(d[44]), "=f"(d[45]), "=f"(d[46]), "=f"(d[47]),
        "=f"(d[48]), "=f"(d[49]), "=f"(d[50]), "=f"(d[51]), "=f"(d[52]), "=f"(d[53]), "=f"(d[54]), "=f"(d[55]),
        "=f"(d[56]), "=f"(d[57]), "=f"(d[58]), "=f"(d[59]), "=f"(d[60]), "=f"(d[61]), "=f"(d[62]), "=f"(d[63]),
        "=f"(d[64]), "=f"(d[65]), "=f"(d[66]), "=f"(d[67]), "=f"(d[68]), "=f"(d[69]), "=f"(d[70]), "=f"(d[71]),
        "=f"(d[72]), "=f"(d[73]), "=f"(d[74]), "=f"(d[75]), "=f"(d[76]), "=f"(d[77]), "=f"(d[78]), "=f"(d[79])
      : "r"(a[0]), "r"(a[1]), "r"(a[2]), "r"(a[3]), "l"(descB));
}

__device__ __forceinline__ void feature_map(const uint32_t (&P)[2][10], uint32_t (&fr)[10][4]) {
  constexpr float L2E = 1.4426950408889634f;
#pragma unroll
  for (int p = 0; p < 2; p++) {
#pragma unroll
    for (int r = 0; r < 2; r++) {
      uint32_t mx = P[r][5 * p], mn = mx;
#pragma unroll
      for (int g = 1; g < 5; g++) { mx = max_bf2(mx, P[r][5 * p + g]); mn = min_bf2(mn, P[r][5 * p + g]); }
      mx = max_bf2(mx, __shfl_xor_sync(0xffffffffu, mx, 1));
      mn = min_bf2(mn, __shfl_xor_sync(0xffffffffu, mn, 1));
      mx = max_bf2(mx, __shfl_xor_sync(0xffffffffu, mx, 2));
      mn = min_bf2(mn, __shfl_xor_sync(0xffffffffu, mn, 2));
      float mx0 = -bf_lo(mx) * L2E, mx1 = -bf_hi(mx) * L2E, mn0 = bf_lo(mn) * L2E, mn1 = bf_hi(mn) * L2E;
      float ep0[5], ep1[5], en0[5], en1[5];
      float sp0 = 0.f, sp1 = 0.f, sn0 = 0.f, sn1 = 0.f;
#pragma unroll
      for (int g = 0; g < 5; g++) {
        float x0 = bf_lo(P[r][5 * p + g]), x1 = bf_hi(P[r][5 * p + g]);
        ep0[g] = ex2(fmaf(x0, L2E, mx0)); ep1[g] = ex2(fmaf(x1, L2E, mx1));
        en0[g] = ex2(fmaf(x0, -L2E, mn0)); en1[g] = ex2(fmaf(x1, -L2E, mn1));
        sp0 += ep0[g]; sp1 += ep1[g]; sn0 += en0[g]; sn1 += en1[g];
      }
      sp0 += __shfl_xor_sync(0xffffffffu, sp0, 1); sp1 += __shfl_xor_sync(0xffffffffu, sp1, 1);
      sn0 += __shfl_xor_sync(0xffffffffu, sn0, 1); sn1 += __shfl_xor_sync(0xffffffffu, sn1, 1);
      sp0 += __shfl_xor_sync(0xffffffffu, sp0, 2); sp1 += __shfl_xor_sync(0xffffffffu, sp1, 2);
      sn0 += __shfl_xor_sync(0xffffffffu, sn0, 2); sn1 += __shfl_xor_sync(0xffffffffu, sn1, 2);
      sp0 = rcp(sp0); sp1 = rcp(sp1); sn0 = rcp(sn0); sn1 = rcp(sn1);
#pragma unroll
      for (int g = 0; g < 5; g++) {
        fr[5 * p + g][r] = pack_bf16(ep0[g] * sp0, ep1[g] * sp1);
        fr[5 * p + g][2 + r] = pack_bf16(en0[g] * sn0, en1[g] * sn1);
      }
    }
  }
}

template <int V> struct IntC { static constexpr int value = V; };
struct Ring {
  uint32_t idx, phase;
  template <int N> __device__ __forceinline__ void next() { if (++idx == N) { idx = 0; phase ^= 1; } }
};

}

__global__ void __cluster_dims__(2, 1, 1) __launch_bounds__(384, 1)
fused_kernel(const __grid_constant__ Maps maps, const __nv_bfloat16* __restrict__ x, const __nv_bfloat16* __restrict__ wqkv,
             const __nv_bfloat16* __restrict__ wphi, const __nv_bfloat16* __restrict__ w1, const __nv_bfloat16* __restrict__ w2,
             const __nv_bfloat16* __restrict__ w3, const __nv_bfloat16* __restrict__ w4, const __nv_bfloat16* __restrict__ wo,
             const __nv_bfloat16* __restrict__ gate_w, __nv_bfloat16* __restrict__ out) {
  extern __shared__ __align__(1024) uint8_t sgen[];
  const uint32_t sb = smem_u32(sgen);
  const uint32_t sb16 = (sb & 0x3FFFFu) >> 4;
  const uint32_t bars = sb + OFF_BAR;
  const uint32_t fullA = bars + 8 * B_FULLA, emptyA = bars + 8 * B_EMPTYA, fullB = bars + 8 * B_FULLB, emptyB = bars + 8 * B_EMPTYB;

  const int tid = threadIdx.x;
  const int rank = blockIdx.x & 1;
  const int bid = blockIdx.x - NSVC, pairIdx = bid >> 1;
  const int i = pairIdx >> 2, j = 2 * (pairIdx & 3) + rank;
  const int k3 = (5 * (pairIdx & 3) + 1) >> 1;

  if (bid < 0) {
    const int sv = blockIdx.x;
    const unsigned epoch = *reinterpret_cast<volatile unsigned*>(g_flags + FL_DONE * 32) / NCTA;
    float* red = reinterpret_cast<float*>(sgen + 204800);
    if (tid == 0) mbar_init(bars, 1);
    __syncthreads();
    float a[8];
#pragma unroll 1
    for (int rd = 0; rd < 5; rd++) {
      const int nch = rd ? 48 : 20, nrg = rd ? 8 : 16, rows = rd ? 160 : 640;
      if (tid == 0) mbar_expect_tx(bars, rows * nch * 16);
      for (int r = tid; r < rows; r += 384)
        bulk_load(sb + r * nch * 16, rd ? w3 + (size_t)(160 * (rd - 1) + r) * F_ + 384 * sv : w1 + (size_t)r * D_ + 160 * sv, nch * 16, bars);
      if (rd == 0) {
        for (int e = tid; e < 1600; e += 384) {
          const int jj = e / 800, it = e - 800 * jj, st = it / 160, n = (it - 160 * st) >> 1, k0 = 16 * st + 8 * ((it ^ (n >> 2)) & 1);
          const int nn = n % 40, h = 2 * (n / 40) + (nn & 1), ff = 4 * (nn >> 3) + ((nn >> 1) & 3);
          uint32_t w[8];
#pragma unroll
          for (int q = 0; q < 8; q++) {
            const int k = k0 + q;
            w[q] = k / 20 == h ? __ldg(reinterpret_cast<const unsigned short*>(wphi) + (2 * sv + jj) * 1600 + k * 20 + ff) : 0u;
          }
          g_wphi[sv * 1600 + e] = make_uint4(w[0] | (w[1] << 16), w[2] | (w[3] << 16), w[4] | (w[5] << 16), w[6] | (w[7] << 16));
        }
        if (tid < 40 && (tid < 20 || sv >= 2))
          reinterpret_cast<uint4*>(g_Hs + (size_t)(2 + ((sv & 1) ? S_ - 1 - tid / 20 : tid / 20)) * D_ + 160 * sv)[tid % 20] = make_uint4(0, 0, 0, 0);
      }
      if (rd < 2) {
#pragma unroll
        for (int e = 0; e < 8; e++) a[e] = 0.f;
      }
      mbar_wait(bars, rd & 1);
      if (tid < nch * nrg) {
#pragma unroll 4
        for (int r = 0; r < rows; r += nrg) {
          const uint4 v = lds128(sb + (r * nch + tid) * 16);
          a[0] += bf_lo(v.x); a[1] += bf_hi(v.x); a[2] += bf_lo(v.y); a[3] += bf_hi(v.y);
          a[4] += bf_lo(v.z); a[5] += bf_hi(v.z); a[6] += bf_lo(v.w); a[7] += bf_hi(v.w);
        }
#pragma unroll
        for (int e = 0; e < 8; e++) red[tid * 8 + e] = a[e];
      }
      __syncthreads();
      if (rd == 0 || rd == 4) {
        if (tid < 8 * nch) {
          float t = 0.f;
          for (int r = 0; r < nrg; r++) t += red[r * nch * 8 + tid];
          g_cs[(rd ? D_ : 0) + 8 * nch * sv + tid] = t;
        }
        __syncthreads();
        if (tid == 0) {
          flag_add(rd ? FL_CS3 : FL_CS);
          if (rd == 0) l2_prefetch(w2 + (size_t)sv * (D_ * D_ / NSVC), D_ * D_ * 2 / NSVC);
        }
      }
    }
    for (int e = tid; e < 2 * KV_J; e += 384) g_acc[(epoch + 1) & 1][sv * 2 * KV_J + e] = 0.f;
    if (tid < 32) {
      l2_prefetch(w4 + (size_t)(sv * 32 + tid) * (F_ * D_ / 128), F_ * D_ * 2 / 128);
      l2_prefetch(wo + (size_t)(sv * 32 + tid) * (D_ * D_ / 128), D_ * D_ * 2 / 128);
    }
    return;
  }
  TSTAMP(0);
  auto load_p1_b = [&](int k, uint32_t slot, uint32_t bar) {
    mbar_expect_tx(bar, 40960);
    tma4d(slot + 8192, &maps.qm, bar, 0, 64 * k, 0, j);
    tma3d(slot, &maps.w1m, bar, 0, 64 * k, j);
    tma4d(slot + 32768 + 2048, &maps.qr, bar, 64, 64 * k, 0, j);
    tma3d(slot + 32768, &maps.w1r, bar, 64, 64 * k, j);
  };
  if (tid >= 256) {
    asm volatile("setmaxnreg.dec.sync.aligned.u32 40;");
    if (tid == 256) {
#pragma unroll
      for (int s = 0; s < NA; s++) mbar_init(fullA + 8 * s, 1);
      asm volatile("fence.mbarrier_init.release.cluster;" ::: "memory");
#pragma unroll 1
      for (int u = 0; u < 4; u++) {
        if ((u & 1) == 0) mbar_expect_tx(fullA + 4 * u, SLOT_A);
        tma2d(sb + OFF_A + u * 8192, &maps.x, fullA + 8 * (u >> 1), 64 * (u >> 1), 128 * i + 64 * (u & 1));
      }
    } else if (tid == 288) {
#pragma unroll
      for (int s = 0; s < NB; s++) mbar_init(fullB + 8 * s, 1);
      asm volatile("fence.mbarrier_init.release.cluster;" ::: "memory");
#pragma unroll 1
      for (int k = 0; k < 2; k++) load_p1_b(k, sb + OFF_B + k * SLOT_B, fullB + 8 * k);
      l2_prefetch(wqkv + (size_t)(128 + 4 * bid) * (3 * D_), 4 * 3 * D_ * 2);
    } else if (tid == 320) {
#pragma unroll
      for (int b = B_CS; b < NBAR; b++) mbar_init(bars + 8 * b, b < B_EMPTYB ? 1 : b < B_EMPTYA ? 8 : b < B_X1P ? 16 : 2);
#pragma unroll
      for (int b = B_DSR; b < B_EMPTYB; b++) mbar_expect_tx(bars + 8 * b, 10240);
      asm volatile("fence.mbarrier_init.release.cluster;" ::: "memory");
    }
    __syncwarp();
    asm volatile("barrier.cluster.arrive.relaxed.aligned;" ::: "memory");
    auto get_epoch = [&]() { return *reinterpret_cast<volatile unsigned*>(g_flags + FL_DONE * 32) / NCTA; };
    asm volatile("barrier.cluster.wait.aligned;" ::: "memory");
    const int lane = tid & 31, pw = (tid >> 5) & 3;
    if (pw == 0) {
      if (tid == 256) {
        Ring r{2, 1};
        unsigned ep1 = 0;
#pragma unroll 1
        for (int k = 2; k < 25; k++) {
          if (k == 4) ep1 = get_epoch() + 1;
          if (k == 10 || k == 17) {
            if (k == 10) mbar_wait(bars + 8 * B_HST, 0);
            flag_wait(k == 10 ? FL_H + 2 * i + rank : FL_X1 + i, ep1 * 8u);
            TSTAMPX(k == 10 ? 29 : 30);
          }
          if (k == 15) mbar_wait(bars + 8 * B_X1P, 0);
          mbar_wait(emptyA + 8 * r.idx, r.phase);
          const uint32_t bar = fullA + 8 * r.idx, slot = sb + OFF_A + r.idx * SLOT_A;
          mbar_expect_tx(bar, SLOT_A);
          if (k >= 10 && k < 15) tma2d(slot, &maps.hs, bar, 64 * (k - 10) + 320 * rank, 128 * i);
          else tma2d_mc(slot + rank * 8192, k < 10 ? &maps.x : &maps.x1, bar, 64 * (k < 10 ? k : (k - 15 + k3) % 10), 128 * i + 64 * rank);
          r.next<NA>();
        }
      }
    } else if (pw == 1) {
      if (tid == 288) {
        Ring r{2, 1};
#pragma unroll 1
        for (int k = 2; k < 18; k++) {
          mbar_wait(emptyB + 8 * r.idx, r.phase);
          const uint32_t bar = fullB + 8 * r.idx, slot = sb + OFF_B + r.idx * SLOT_B;
          if (k < 10) {
            load_p1_b(k, slot, bar);
          } else if (k < 13) {
            mbar_expect_tx(bar, k < 12 ? 40960 : 20480);
            tma3d(slot, &maps.w2, bar, 0, 320 * rank + 128 * (k - 10), 5 * (j >> 1));
            if (k < 12) tma3d(slot + 20480, &maps.w2, bar, 0, 320 * rank + 128 * (k - 10) + 64, 5 * (j >> 1));
          } else {
            mbar_expect_tx(bar, 49152);
            tma3d(slot, &maps.w3, bar, 0, 64 * ((2 * (k - 13) + k3) % 10), 3 * j);
            tma3d(slot + 24576, &maps.w3, bar, 0, 64 * ((2 * (k - 13) + 1 + k3) % 10), 3 * j);
          }
          r.next<NB>();
        }
#pragma unroll 1
        for (int n = 0; n < 8; n++) {
          if (n < 3) { mbar_wait(emptyB + 8 * r.idx, r.phase); r.next<NB>(); }
          if (n >= 4) mbar_wait(bars + 8 * (B_EMPTY4 + n - 4), 0);
          const uint32_t bar = bars + 8 * (B_FULL4 + n), set = sb + ((n >> 1) & 1) * SET4;
          const int h = n & 1, m = ((j >> 1) + 1 + (n >> 1)) & 3;
          mbar_expect_tx(bar, h ? 40960 : 46080);
          tma3d(set + (h ? 46080 : 0), h ? &maps.w4 : &maps.wo, bar, 0, h ? 192 * j + 64 : 80 * j, 5 * m);
          tma3d(set + (h ? 66560 : 25600), &maps.w4, bar, 0, 192 * j + 128 * h, 5 * m);
        }
        mbar_wait(bars + 8 * (B_EMPTY4 + 4), 0);
        mbar_expect_tx(bars + 8 * B_XR, 20480);
        tma2d(sb + OFF_OUT, &maps.st_x1, bars + 8 * B_XR, 80 * j, 128 * i);
      }
    } else {
      const unsigned epoch = get_epoch();
      float* accg = g_acc[epoch & 1];
      if (pw == 2) {
        if (tid == 320) {
          flag_wait(FL_CS, (epoch + 1) * NSVC);
          flag_wait(FL_ST + i, (epoch + 1) * 8u);
          fence_async_glb();
          *reinterpret_cast<volatile uint32_t*>(sgen + OFF_BAR + 8 * NBAR) = (epoch + 1) & 1;
          mbar_expect_tx(bars + 8 * B_CS, 320 + 2048 + 12800);
          bulk_load(sb + OFF_CS, g_cs + 80 * j, 320, bars + 8 * B_CS);
          bulk_load(sb + OFF_XST, g_xstat + 128 * i, 2048, bars + 8 * B_CS);
          bulk_load(sb + OFF_MISC, g_wphi + j * 800, 12800, bars + 8 * B_CS);
          TSTAMPX(21);
          flag_wait(FL_KV + j, (epoch + 1) * 16u);
          mbar_expect_tx(bars + 8 * B_KV, KV_J * 4);
          bulk_load(sb + OFF_MISC, accg + j * KV_J, KV_J * 4, bars + 8 * B_KV);
          TSTAMPX(22);
          flag_wait(FL_CS3, (epoch + 1) * NSVC);
          flag_wait(FL_S1 + i, (epoch + 1) * 8u);
          fence_async_glb();
          mbar_expect_tx(bars + 8 * B_ST1, 8192 + 768);
          bulk_load(sb + OFF_CS + 320, g_cs + D_ + 192 * j, 768, bars + 8 * B_ST1);
          bulk_load(sb + OFF_MISC, g_st1 + 128 * i * 8, 8192, bars + 8 * B_ST1);
        }
        __syncwarp();
#pragma unroll 1
        for (int c = 0; c < 3; c++) {
          mbar_wait(bars + 8 * (B_EMPTY4 + (c ? 5 : 4)), 0);
          const uint4* src = g_part + (size_t)((i * 8 + j) * 3 + c) * 1280;
          const unsigned* tp = reinterpret_cast<const unsigned*>(src + 1024 + (lane & 7) * 32 + 31);
          uint32_t n = 0;
          while (!__all_sync(0xffffffffu, (ld_acquire(tp) ^ epoch) & 1u) && ++n < (WAIT_LIMIT >> 2)) {}
          if (tid == 320) {
            mbar_expect_tx(bars + 8 * (B_RDY + c), 20480);
            bulk_load(sb + (c ? 25600 + 20480 * c : 0), src, 20480, bars + 8 * (B_RDY + c));
          }
        }
      }
      if (tid == 352) {
        mbar_wait(bars + 8 * B_SIGP, 0);
        flag_add(FL_ST + i);
        TSTAMPX(20);
        mbar_expect_tx(bars + 8 * B_XR, 20480);
#pragma unroll 1
        for (int u = 0; u < 8; u++)
          tma2d(sb + OFF_B + (u / 3) * SLOT_B + SPARE + (u % 3) * 2560, &maps.xr, bars + 8 * B_XR, 80 * j, 128 * i + 16 * u);
        const int shift = (j < 2) ? 1 : (j < 4) ? -1 : (j < 6) ? 2 : -2;
        prefetch_tmap(&maps.st_h); prefetch_tmap(&maps.st_x1); prefetch_tmap(&maps.hs); prefetch_tmap(&maps.x1);
        prefetch_tmap(&maps.w2); prefetch_tmap(&maps.w3); prefetch_tmap(&maps.w4); prefetch_tmap(&maps.wo);
        mbar_wait(bars + 8 * B_SIGH, 0);
        TSTAMPX(23);
        tma2d_store(&maps.st_h, sb + OFF_STG, 80 * j, 128 * i + 2 + shift);
        bulk_commit(); bulk_wait<0>();
        mbar_arrive(bars + 8 * B_HST);
        flag_add(FL_H + 2 * i + (j >> 2));
        flag_add_relaxed(FL_H + 2 * ((i + (shift > 0 ? 1 : -1)) & 15) + (j >> 2));
        TSTAMPX(24);
        mbar_wait(bars + 8 * B_SIGKV, 0);
        TSTAMPX(25);
        fence_async_smem();
        asm volatile("cp.reduce.async.bulk.global.shared::cta.bulk_group.add.f32 [%0], [%1], %2;"
                     ::"l"(accg + j * KV_J), "r"(sb + OFF_MISC), "r"(KV_J * 4) : "memory");
        bulk_commit(); bulk_wait<0>();
        flag_add(FL_KV + j);
        TSTAMPX(26);
        mbar_wait(bars + 8 * B_SIGX1, 0);
        TSTAMPX(27);
        tma2d_store(&maps.st_x1, sb + OFF_STG, 80 * j, 128 * i);
        bulk_commit(); bulk_wait<0>();
        flag_add(FL_X1 + i);
        mbar_arrive_cta(bars + 8 * B_X1P, 0); mbar_arrive_cta(bars + 8 * B_X1P, 1);
        TSTAMPX(28);
        mbar_wait(bars + 8 * B_MFREE, 0);
        flag_add(FL_S1 + i);
      }
    }
  } else {
    uint4 pv[5], pw_[5];
    {
      const int row = 128 * i + 16 * j + (tid >> 4), l16 = tid & 15;
#pragma unroll
      for (int c = 0; c < 5; c++) pv[c] = __ldg(reinterpret_cast<const uint4*>(x + (size_t)row * D_ + c * 128 + l16 * 8));
#pragma unroll
      for (int c = 0; c < 5; c++) pw_[c] = __ldg(reinterpret_cast<const uint4*>(gate_w + c * 128 + l16 * 8));
    }
    asm volatile("barrier.cluster.arrive.relaxed.aligned;" ::: "memory");
    asm volatile("setmaxnreg.inc.sync.aligned.u32 232;");
    const int wg = tid >> 7, warp = tid >> 5, lane = tid & 31, t = lane & 3;
    const int rloc = warp * 16 + (lane >> 2);
    const float* s_cs = reinterpret_cast<const float*>(sgen + OFF_CS);
    auto signal = [&](int b) {
      __syncwarp();
      if (lane == 0) mbar_arrive(bars + 8 * b);
    };
    auto releaseB = [&](uint32_t bar) {
      __syncwarp();
      if (lane == 0) mbar_arrive(bar);
    };
    auto release = [&](uint32_t bar) {
      __syncwarp();
      if (lane < 2) mbar_arrive_cta(bar, lane);
    };
    const uint32_t stg_lane = (warp * 16 + ((lane >> 3) & 1) * 8 + (lane & 7)) * 160 + (lane >> 4) * 16;

    auto stage_tile = [&](uint32_t stg, const uint32_t (&v)[2][10]) {
#pragma unroll
      for (int s = 0; s < 5; s++) stsm4(stg + stg_lane + s * 32, v[0][2 * s], v[1][2 * s], v[0][2 * s + 1], v[1][2 * s + 1]);
    };

    {
      float f[40];
      float s = 0.f, gs = 0.f;
#pragma unroll
      for (int c = 0; c < 5; c++) {
        const uint32_t vv[4] = {pv[c].x, pv[c].y, pv[c].z, pv[c].w}, ww[4] = {pw_[c].x, pw_[c].y, pw_[c].z, pw_[c].w};
#pragma unroll
        for (int e = 0; e < 4; e++) {
          f[8 * c + 2 * e] = bf_lo(vv[e]); f[8 * c + 2 * e + 1] = bf_hi(vv[e]);
          s += f[8 * c + 2 * e] + f[8 * c + 2 * e + 1];
          gs = fmaf(f[8 * c + 2 * e], bf_lo(ww[e]), gs); gs = fmaf(f[8 * c + 2 * e + 1], bf_hi(ww[e]), gs);
        }
      }
#pragma unroll
      for (int o = 1; o < 16; o <<= 1) { s += __shfl_xor_sync(0xffffffffu, s, o); gs += __shfl_xor_sync(0xffffffffu, gs, o); }
      const float mean = s * (1.f / D_);
      float q = 0.f;
#pragma unroll
      for (int e = 0; e < 40; e++) { const float d = f[e] - mean; q = fmaf(d, d, q); }
#pragma unroll
      for (int o = 1; o < 16; o <<= 1) q += __shfl_xor_sync(0xffffffffu, q, o);
      const float rstd = rsqrtf(q * (1.f / D_) + 1e-5f);
      asm volatile("barrier.cluster.wait.aligned;" ::: "memory");
      if ((tid & 15) == 0) g_xstat[128 * i + 16 * j + (tid >> 4)] = make_float4(rstd, -mean, rcp(1.f + __expf(-gs)), 0.f);
      signal(B_SIGP);
    }
    TSTAMP(1);

    Ring ra{0, 0}, rb{0, 0};
    uint32_t qp[2][10], P[2][10];
    float st_g[2];
    {
      float accM[128], accR[32];
      uint32_t pa = 0, pb = 0;
#pragma unroll 1
      for (int k = 0; k < 10; k++) {
        mbar_wait(fullA + 8 * ra.idx, ra.phase);
        if (tid == 0) TRACE(32 + k);
        mbar_wait(fullB + 8 * rb.idx, rb.phase);
        if (tid == 0) TRACE(64 + k);
        if (k == 0) TSTAMP(2);
        const uint32_t a0 = sb16 + ((OFF_A + ra.idx * SLOT_A + wg * 8192) >> 4), b0 = sb16 + ((OFF_B + rb.idx * SLOT_B) >> 4);
        wg_fence();
#pragma unroll
        for (int kk = 0; kk < 4; kk++) {
          const uint64_t da = make_desc(a0, kk * 32, 16, 1024, 1);
          if (kk == 0) {
            mma_ss256_p(accM, da, make_desc(b0, 0, 8192, 1024, 1), k);
            mma_ss64_p(accR, da, make_desc(b0, 32768, 2048, 256, 3), k);
          } else {
            mma_ss256(accM, da, make_desc(b0, kk * 2048, 8192, 1024, 1));
            mma_ss64(accR, da, make_desc(b0, 32768 + kk * 512, 2048, 256, 3));
          }
          if (kk == 0) {
            wg_commit();
            if (k > 0) {
              wg_wait<1>();
              if (k - 1 < 8) release(emptyA + 8 * pa);
              releaseB(emptyB + 8 * pb);
            }
          }
        }
        wg_commit();
        pa = ra.idx; pb = rb.idx;
        ra.next<NA>(); rb.next<NB>();
      }
      TSTAMP(18);
      float st_rstd[2], st_mr[2];
      mbar_wait(bars + 8 * B_CS, 0);
#pragma unroll
      for (int r = 0; r < 2; r++) {
        const uint4 st = lds128(sb + OFF_XST + (rloc + 8 * r) * 16);
        st_rstd[r] = __uint_as_float(st.x); st_mr[r] = __uint_as_float(st.y); st_g[r] = __uint_as_float(st.z);
      }
      TSTAMP(19);
      wg_wait<0>();
      fence_regs(accM); fence_regs(accR);
      TSTAMP(3);
#define ACC(P_, G, I_) ((G) < 8 ? accM[(P_) * 32 + ((G) & 7) * 4 + (I_)] : accR[(P_) * 8 + ((G) & 1) * 4 + (I_)])
      {
        uint32_t hv[2][10];
        const GeluC g0 = gelu_consts(st_rstd[0], 1.f), g1 = gelu_consts(st_rstd[1], 1.f);
#pragma unroll
        for (int g = 0; g < 10; g++) {
          const float2 cs = *reinterpret_cast<const float2*>(s_cs + 8 * g + 2 * t);
          const float v0 = gelu_s(fmaf(st_mr[0], cs.x, ACC(0, g, 0)), g0), v1 = gelu_s(fmaf(st_mr[0], cs.y, ACC(0, g, 1)), g0);
          const float v2 = gelu_s(fmaf(st_mr[1], cs.x, ACC(0, g, 2)), g1), v3 = gelu_s(fmaf(st_mr[1], cs.y, ACC(0, g, 3)), g1);
          hv[0][g] = pack_bf16(v0, v1); hv[1][g] = pack_bf16(v2, v3);
        }
        bar_sync(1, 256);
        stage_tile(sb + OFF_STG, hv);
        fence_async_smem();
        signal(B_SIGH);
      }
      TSTAMP(4);
      uint32_t kf[5][4], qf[5][4];
#pragma unroll
      for (int s = 0; s < 5; s++) {
        kf[s][0] = pack_bf16(ACC(2, 2 * s, 0), ACC(2, 2 * s, 1)); kf[s][1] = pack_bf16(ACC(2, 2 * s, 2), ACC(2, 2 * s, 3));
        kf[s][2] = pack_bf16(ACC(2, 2 * s + 1, 0), ACC(2, 2 * s + 1, 1)); kf[s][3] = pack_bf16(ACC(2, 2 * s + 1, 2), ACC(2, 2 * s + 1, 3));
        qf[s][0] = pack_bf16(ACC(1, 2 * s, 0), ACC(1, 2 * s, 1)); qf[s][1] = pack_bf16(ACC(1, 2 * s, 2), ACC(1, 2 * s, 3));
        qf[s][2] = pack_bf16(ACC(1, 2 * s + 1, 0), ACC(1, 2 * s + 1, 1)); qf[s][3] = pack_bf16(ACC(1, 2 * s + 1, 2), ACC(1, 2 * s + 1, 3));
      }
      float pk[40], pq[40];
      wg_fence();
#pragma unroll
      for (int s = 0; s < 5; s++) {
        if (s == 0) mma_rs80_k_z(pk, kf[s], make_desc(sb16, OFF_MISC, 16, 256, 3));
        else mma_rs80_k(pk, kf[s], make_desc(sb16, OFF_MISC + s * 2560, 16, 256, 3));
      }
      wg_commit();
#pragma unroll
      for (int s = 0; s < 5; s++) {
        if (s == 0) mma_rs80_k_z(pq, qf[s], make_desc(sb16, OFF_MISC, 16, 256, 3));
        else mma_rs80_k(pq, qf[s], make_desc(sb16, OFF_MISC + s * 2560, 16, 256, 3));
      }
      wg_commit();
      {
        const int mat = lane >> 3;
        const int tok = warp * 16 + (mat & 1) * 8 + (lane & 7);
        const uint32_t ones = (t == 0) ? 0x00003f80u : 0u;
        __syncwarp();
#pragma unroll
        for (int p = 0; p < 2; p++) {
          const uint32_t rowa = sb + OFF_A + p * SLOT_A + tok * 128;
#pragma unroll
          for (int gg = 0; gg < 3; gg++) {
            const int g0 = 5 * p + 2 * gg;
            uint32_t r0 = pack_bf16(ACC(3, g0, 0), ACC(3, g0, 1)), r1 = pack_bf16(ACC(3, g0, 2), ACC(3, g0, 3));
            uint32_t r2 = ones, r3 = ones;
            if (gg < 2) { r2 = pack_bf16(ACC(3, g0 + 1, 0), ACC(3, g0 + 1, 1)); r3 = pack_bf16(ACC(3, g0 + 1, 2), ACC(3, g0 + 1, 3)); }
            stsm4(rowa + (((2 * gg + (mat >> 1)) ^ (tok & 7)) << 4), r0, r1, r2, r3);
          }
        }
      }
#undef ACC
      wg_wait<1>();
      fence_regs(pk);
#pragma unroll
      for (int G = 0; G < 10; G++) {
        P[0][G] = pack_bf16(pk[4 * G], pk[4 * G + 1]); P[1][G] = pack_bf16(pk[4 * G + 2], pk[4 * G + 3]);
      }
      wg_wait<0>();
      fence_regs(pq);
#pragma unroll
      for (int G = 0; G < 10; G++) {
        qp[0][G] = pack_bf16(pq[4 * G], pq[4 * G + 1]); qp[1][G] = pack_bf16(pq[4 * G + 2], pq[4 * G + 3]);
      }
    }

    uint32_t fr[10][4];
    int pass;
    pass = gridDim.y;
#pragma unroll 1
    do {
    feature_map(P, fr);
    if (pass != 0) {
    {
      const int mat = lane >> 3;
      const int tok = warp * 16 + (mat & 1) * 8 + (lane & 7);
      const uint32_t base = sb + OFF_B + tok * 32 + (((mat >> 1) ^ ((tok >> 2) & 1)) << 4);
#pragma unroll
      for (int G = 0; G < 10; G++) stsm4(base + G * 4096, fr[G][0], fr[G][1], fr[G][2], fr[G][3]);
      fence_async_smem();
      bar_sync(1, 256);
      float kv[40];
      const uint32_t va = sb16 + ((OFF_A + wg * SLOT_A) >> 4), vb = sb16 + ((OFF_B + wg * 20480) >> 4);
      wg_fence();
#pragma unroll
      for (int ks = 0; ks < 8; ks++) {
        if (ks == 0) mma_ss80_tt_z(kv, make_desc(va, 0, 16, 1024, 1), make_desc(vb, 0, 4096, 256, 3));
        else mma_ss80_tt(kv, make_desc(va, ks * 2048, 16, 1024, 1), make_desc(vb, ks * 512, 4096, 256, 3));
      }
      wg_commit();
      uint32_t xv[2][10];
      {
        mbar_wait(bars + 8 * B_XR, 0);
        const uint32_t xa = sb + OFF_B + (warp / 3) * SLOT_B + SPARE + (warp % 3) * 2560 + (lane >> 2) * 160 + t * 4;
#pragma unroll
        for (int g = 0; g < 10; g++) { xv[0][g] = lds32(xa + g * 16); xv[1][g] = lds32(xa + 1280 + g * 16); }
      }
      float acc[80];
      wg_wait<0>();
      release(emptyA); release(emptyA + 8); releaseB(emptyB); release(bars + 8 * B_PEER2);
      TSTAMP(5);
      mbar_wait(fullA + 8 * 2, 0);
      mbar_wait(fullB + 8 * 1, 1);
      TSTAMP(6);
      wg_fence();
#pragma unroll
      for (int kk = 0; kk < 4; kk++) {
        const uint64_t da = make_desc(sb16 + wg * 512, OFF_A + 2 * SLOT_A + kk * 32, 16, 1024, 1);
        const uint64_t db = make_desc(sb16, OFF_B + SLOT_B + kk * 1024, 4096, 512, 2);
        if (kk == 0) mma_ss160_z(acc, da, db); else mma_ss160(acc, da, db);
      }
      wg_commit();
      ra.next<NA>();
      wg_wait<1>();
      fence_regs(kv);
      TSTAMP(31);
      const uint32_t dst = sb + OFF_MISC + wg * (KV_PAIR * 4);
      const int m0 = (warp & 3) * 16 + (lane >> 2);
#pragma unroll
      for (int r = 0; r < 2; r++) {
        const int m = m0 + 8 * r;
        const bool hi = m >= 20;
        uint32_t v[10];
#pragma unroll
        for (int G = 0; G < 10; G++) v[G] = __float_as_uint(hi ? kv[4 * G + 2 * r + 1] : kv[4 * G + 2 * r]);
        const uint32_t p = dst + 4 * (m < 40 ? m * 48 + t * 12 : 1920 + t * 24 + 12);
        if (m <= 40) {
          sts128(p, make_uint4(v[0], v[1], v[2], v[3])); sts128(p + 16, make_uint4(v[4], v[5], v[6], v[7]));
          sts128(p + 32, make_uint4(v[8], v[9], 0u, 0u));
        }
      }
      if (m0 == 32) {
        const uint32_t p = dst + 4 * (1920 + t * 24);
        sts128(p, make_uint4(__float_as_uint(kv[2]), __float_as_uint(kv[6]), __float_as_uint(kv[10]), __float_as_uint(kv[14])));
        sts128(p + 16, make_uint4(__float_as_uint(kv[18]), __float_as_uint(kv[22]), __float_as_uint(kv[26]), __float_as_uint(kv[30])));
        sts128(p + 32, make_uint4(__float_as_uint(kv[34]), __float_as_uint(kv[38]), 0u, 0u));
      }
      signal(B_SIGKV);
      uint32_t pa = 2, pb = 1;
#pragma unroll 1
      for (int k = 1; k < 5; k++) {
        mbar_wait(fullA + 8 * ra.idx, ra.phase);
        if ((k & 1) == 0) mbar_wait(fullB + 8 * rb.idx, rb.phase);
        const uint32_t a0 = sb16 + ((OFF_A + ra.idx * SLOT_A + wg * 8192) >> 4);
        const uint32_t b0 = sb16 + ((OFF_B + rb.idx * SLOT_B + (k & 1) * 20480) >> 4);
        wg_fence();
#pragma unroll
        for (int kk = 0; kk < 4; kk++) {
          mma_ss160(acc, make_desc(a0, kk * 32, 16, 1024, 1), make_desc(b0, kk * 1024, 4096, 512, 2));
          if (kk == 0) {
            wg_commit();
            wg_wait<1>();
            release(emptyA + 8 * pa);
            if ((k & 1) == 0) releaseB(emptyB + 8 * pb);
          }
        }
        wg_commit();
        pa = ra.idx; pb = rb.idx;
        ra.next<NA>();
        if ((k & 1) || k == 4) rb.next<NB>();
      }
      mbar_wait(bars + 8 * B_PEER2, 0);
      wg_wait<0>();
      fence_regs(acc);
      release(emptyA + 8 * pa);
      TSTAMP(7);
      {
        uint32_t sn[20];
        if (rank) {
#pragma unroll
          for (int e = 0; e < 20; e++) sn[e] = pack_bf16(acc[2 * e], acc[2 * e + 1]);
#pragma unroll
          for (int e = 0; e < 40; e++) acc[e] = acc[40 + e];
        } else {
#pragma unroll
          for (int e = 0; e < 20; e++) sn[e] = pack_bf16(acc[40 + 2 * e], acc[41 + 2 * e]);
        }
        const uint32_t peer = map_peer(sb, rank ^ 1);
#pragma unroll
        for (int q = 0; q < 5; q++)
          st_async16(peer + OFF_B + 20480 + tid * 16 + q * 4096, sn[4 * q], sn[4 * q + 1], sn[4 * q + 2], sn[4 * q + 3],
                     peer + OFF_BAR + 8 * (B_DSR + 8 + wg));
#pragma unroll
        for (int g = 0; g < 10; g++) {
          acc[4 * g] += bf_lo(xv[0][g]); acc[4 * g + 1] += bf_hi(xv[0][g]);
          acc[4 * g + 2] += bf_lo(xv[1][g]); acc[4 * g + 3] += bf_hi(xv[1][g]);
        }
        bar_sync(1, 256);
        mbar_wait(bars + 8 * (B_DSR + 8 + wg), 0);
#pragma unroll
        for (int q = 0; q < 5; q++) {
          const uint4 v = lds128(sb + OFF_B + 20480 + tid * 16 + q * 4096);
          xv[0][2 * q] = pack_bf16(acc[8 * q] + bf_lo(v.x), acc[8 * q + 1] + bf_hi(v.x));
          xv[1][2 * q] = pack_bf16(acc[8 * q + 2] + bf_lo(v.y), acc[8 * q + 3] + bf_hi(v.y));
          xv[0][2 * q + 1] = pack_bf16(acc[8 * q + 4] + bf_lo(v.z), acc[8 * q + 5] + bf_hi(v.z));
          xv[1][2 * q + 1] = pack_bf16(acc[8 * q + 6] + bf_lo(v.w), acc[8 * q + 7] + bf_hi(v.w));
        }
        releaseB(emptyB + 8 * pb);
      }
      TSTAMP(16);
      stage_tile(sb + OFF_STG, xv);
      fence_async_smem();
      signal(B_SIGX1);
      TSTAMP(17);
#pragma unroll
      for (int r = 0; r < 2; r++) {
        float s = 0.f;
#pragma unroll
        for (int g = 0; g < 10; g++) {
          acc[4 * g + 2 * r] = bf_lo(xv[r][g]); acc[4 * g + 2 * r + 1] = bf_hi(xv[r][g]);
          s += acc[4 * g + 2 * r] + acc[4 * g + 2 * r + 1];
        }
        s += __shfl_xor_sync(0xffffffffu, s, 1); s += __shfl_xor_sync(0xffffffffu, s, 2);
        const float mu = s * (1.f / 80.f);
        float q = 0.f;
#pragma unroll
        for (int g = 0; g < 10; g++) {
          const float d0 = acc[4 * g + 2 * r] - mu, d1 = acc[4 * g + 2 * r + 1] - mu;
          q = fmaf(d0, d0, q); q = fmaf(d1, d1, q);
        }
        q += __shfl_xor_sync(0xffffffffu, q, 1); q += __shfl_xor_sync(0xffffffffu, q, 2);
        if (t == 0) g_st1[(128 * i + rloc + 8 * r) * 8 + j] = make_float2(mu, q);
      }
    }
    TSTAMP(8);
#pragma unroll
    for (int G = 0; G < 10; G++) { P[0][G] = qp[0][G]; P[1][G] = qp[1][G]; }
    }
    asm volatile("" : "+r"(pass));
    } while (pass-- != 0);

    uint32_t of[5][4];
    {
      mbar_wait(bars + 8 * B_KV, 0);
      uint4 kvr[2][3];
#pragma unroll
      for (int u = 0; u < 2; u++) {
        const int it = tid + 256 * u, p = it / 192, rem = it - 192 * p, n = rem >> 2, tq = rem & 3;
        const uint32_t sp = sb + OFF_MISC + 4 * (p * KV_PAIR + (n < 40 ? n * 48 + tq * 12 : 1920 + tq * 24 + (n & 1) * 12));
        if (it < 384) { kvr[u][0] = lds128(sp); kvr[u][1] = lds128(sp + 16); kvr[u][2] = lds128(sp + 32); }
      }
      bar_sync(1, 256);
#pragma unroll
      for (int u = 0; u < 2; u++) {
        const int it = tid + 256 * u, p = it / 192, rem = it - 192 * p, n = rem >> 2, tq = rem & 3;
        const int sh = (n < 40 ? (n >= 20) : (n & 1)) * 16;
        const uint32_t v[10] = {kvr[u][0].x, kvr[u][0].y, kvr[u][0].z, kvr[u][0].w, kvr[u][1].x, kvr[u][1].y, kvr[u][1].z, kvr[u][1].w, kvr[u][2].x, kvr[u][2].y};
        uint8_t* dst = sgen + OFF_MISC + p * 7680 + n * 32 + tq * 4;
        const int sw = ((n >> 2) & 1) << 4;
        if (it < 384) {
#pragma unroll
          for (int G = 0; G < 10; G++)
            *reinterpret_cast<uint32_t*>(dst + (G >> 1) * 1536 + (((G & 1) << 4) ^ sw)) = pack_bf16(__uint_as_float(v[G]), 0.f) << sh;
        }
      }
      fence_async_smem();
      bar_sync(1, 256);
      float o0[24], o1[24];
      wg_fence();
#pragma unroll
      for (int g = 0; g < 5; g++) {
        if (g == 0) mma_rs48_k_z(o0, fr[g], make_desc(sb16, OFF_MISC, 16, 256, 3));
        else mma_rs48_k(o0, fr[g], make_desc(sb16, OFF_MISC + g * 1536, 16, 256, 3));
      }
#pragma unroll
      for (int g = 0; g < 5; g++) {
        if (g == 0) mma_rs48_k_z(o1, fr[5], make_desc(sb16, OFF_MISC + 7680, 16, 256, 3));
        else mma_rs48_k(o1, fr[5 + g], make_desc(sb16, OFF_MISC + 7680 + g * 1536, 16, 256, 3));
      }
      wg_commit();
      wg_wait<0>();
      fence_regs(o0); fence_regs(o1);
      signal(B_MFREE);
#pragma unroll
      for (int r = 0; r < 2; r++) {
        const float a0 = __fdividef(st_g[r], o0[20 + 2 * r] + 1e-6f), a1 = __fdividef(st_g[r], o0[21 + 2 * r] + 1e-6f);
        const float b0 = __fdividef(st_g[r], o1[20 + 2 * r] + 1e-6f), b1 = __fdividef(st_g[r], o1[21 + 2 * r] + 1e-6f);
        const float am = t < 2 ? a0 : a1, bm = t < 2 ? b0 : b1;
#pragma unroll
        for (int g = 0; g < 5; g++) {
          const float sa = g < 2 ? a0 : (g == 2 ? am : a1), sb2 = g < 2 ? b0 : (g == 2 ? bm : b1);
          of[g >> 1][(g & 1) * 2 + r] = pack_bf16(o0[4 * g + 2 * r] * sa, o0[4 * g + 2 * r + 1] * sa);
          of[(5 + g) >> 1][((5 + g) & 1) * 2 + r] = pack_bf16(o1[4 * g + 2 * r] * sb2, o1[4 * g + 2 * r + 1] * sb2);
        }
      }
    }
    TSTAMP(9);

    uint32_t hf[12][4];
    float ac4[80];
    auto unit = [&](auto uc, uint32_t b0) {
      constexpr int u = decltype(uc)::value;
#pragma unroll
      for (int s = 0; s < (u ? 4 : 5); s++) {
        const uint64_t db = make_desc(b0, (u ? 5120 + 20480 * u : 0) + s * 1024, u ? 4096 : 5120, 512, 2);
        if (u == 0 && s == 0) mma_rs160_n_z(ac4, of[0], db);
        else if (u == 0) mma_rs160_n(ac4, of[s], db);
        else mma_rs160_n(ac4, hf[(4 * u + 8 + s) % 12], db);
      }
      wg_commit();
    };
    {
      float acc[96];
      uint32_t pa = 0, pb = 0;
#pragma unroll 1
      for (int k = 0; k < 10; k++) {
        mbar_wait(fullA + 8 * ra.idx, ra.phase);
        if (tid == 0) TRACE(52 + k);
        if ((k & 1) == 0) mbar_wait(fullB + 8 * rb.idx, rb.phase);
        if (tid == 0) TRACE(84 + k);
        if (k == 0) TSTAMP(10);
        const uint32_t a0 = sb16 + ((OFF_A + ra.idx * SLOT_A + wg * 8192) >> 4);
        const uint32_t b0 = sb16 + ((OFF_B + rb.idx * SLOT_B + (k & 1) * 24576) >> 4);
        wg_fence();
#pragma unroll
        for (int kk = 0; kk < 4; kk++) {
          if (kk == 0) mma_ss192_p(acc, make_desc(a0, 0, 16, 1024, 1), make_desc(b0, 0, 8192, 1024, 1), k);
          else mma_ss192(acc, make_desc(a0, kk * 32, 16, 1024, 1), make_desc(b0, kk * 2048, 8192, 1024, 1));
          if (kk == 0) {
            wg_commit();
            if (k > 0) {
              wg_wait<1>();
              release(emptyA + 8 * pa);
              if ((k & 1) == 0) releaseB(emptyB + 8 * pb);
            }
          }
        }
        wg_commit();
        pa = ra.idx; pb = rb.idx;
        ra.next<NA>();
        if (k & 1) rb.next<NB>();
      }
      float rs[2], mm[2];
      mbar_wait(bars + 8 * B_ST1, 0);
#pragma unroll
      for (int r = 0; r < 2; r++) {
        const uint4 su = lds128(sb + OFF_MISC + (rloc + 8 * r) * 64 + t * 16);
        const float m0 = __uint_as_float(su.x), m1 = __uint_as_float(su.z);
        float mu = m0 + m1;
        mu += __shfl_xor_sync(0xffffffffu, mu, 1); mu += __shfl_xor_sync(0xffffffffu, mu, 2);
        mu *= 0.125f;
        const float d0 = m0 - mu, d1 = m1 - mu;
        float q = __uint_as_float(su.y) + __uint_as_float(su.w) + 80.f * (d0 * d0 + d1 * d1);
        q += __shfl_xor_sync(0xffffffffu, q, 1); q += __shfl_xor_sync(0xffffffffu, q, 2);
        rs[r] = rsqrtf(q * (1.f / D_) + 1e-5f);
        mm[r] = -mu;
      }
      mbar_wait(bars + 8 * B_FULL4, 0);
      wg_fence();
      unit(IntC<0>{}, sb16);
      wg_wait<1>();
      fence_regs(acc);
      releaseB(emptyB + 8 * pb);
      release(bars + 8 * B_PEER);
      TSTAMP(11);
      const GeluC g0 = gelu_consts(rs[0], 1.f - st_g[0]), g1 = gelu_consts(rs[1], 1.f - st_g[1]);
#pragma unroll
      for (int g = 0; g < 24; g++) {
        const float2 cs = *reinterpret_cast<const float2*>(s_cs + 80 + 8 * g + 2 * t);
        const float v0 = gelu_s(fmaf(mm[0], cs.x, acc[4 * g]), g0), v1 = gelu_s(fmaf(mm[0], cs.y, acc[4 * g + 1]), g0);
        const float v2 = gelu_s(fmaf(mm[1], cs.x, acc[4 * g + 2]), g1), v3 = gelu_s(fmaf(mm[1], cs.y, acc[4 * g + 3]), g1);
        hf[g >> 1][(g & 1) * 2] = pack_bf16(v0, v1);
        hf[g >> 1][(g & 1) * 2 + 1] = pack_bf16(v2, v3);
        if (g == 7) { wg_fence(); unit(IntC<1>{}, sb16); }
        if (g == 15) { mbar_wait(bars + 8 * (B_FULL4 + 1), 0); wg_fence(); unit(IntC<2>{}, sb16); }
        if (g == 23) { wg_wait<1>(); signal(B_EMPTY4); wg_fence(); unit(IntC<3>{}, sb16); }
      }
    }
    TSTAMP(12);

    {
      float kp[40];
      uint32_t sn[20], kb[20];
      const uint32_t peer = map_peer(sb, rank ^ 1);
      const uint32_t tag = lds32(sb + OFF_BAR + 8 * NBAR);
      auto add8 = [&](int q, const uint4 v) {
        float* d = &kp[8 * q];
        d[0] += bf_lo(v.x); d[1] += bf_hi(v.x); d[2] += bf_lo(v.y); d[3] += bf_hi(v.y);
        d[4] += bf_lo(v.z); d[5] += bf_hi(v.z); d[6] += bf_lo(v.w); d[7] += bf_hi(v.w);
      };
      auto send = [&](int c) {
        const uint32_t dso = peer + OFF_DS + (c & 1) * 20480 + tid * 16, dsb = peer + OFF_BAR + 8 * (B_DSR + 2 * c + wg);
#pragma unroll
        for (int q = 0; q < 5; q++) st_async16(dso + q * 4096, sn[4 * q], sn[4 * q + 1], sn[4 * q + 2], sn[4 * q + 3], dsb);
      };
      mbar_wait(bars + 8 * B_PEER, 0);
      uint4* gdst = g_part + (size_t)i * 8 * 3840 + tid;
#pragma unroll 1
      for (int c = 0; c < 3; c++) {
        const uint32_t b0 = sb16 + ((c & 1) ? 0 : SET4 >> 4), bc = bars + 16 * c;
        mbar_wait(bc + 8 * (B_FULL4 + 2), 0);
        wg_wait<0>();
        fence_regs(ac4);
        if (rank) {
#pragma unroll
          for (int e = 0; e < 20; e++) { sn[e] = pack_bf16(ac4[2 * e], ac4[2 * e + 1]); kb[e] = pack_bf16(ac4[40 + 2 * e], ac4[41 + 2 * e]); }
        } else {
#pragma unroll
          for (int e = 0; e < 20; e++) { kb[e] = pack_bf16(ac4[2 * e], ac4[2 * e + 1]); sn[e] = pack_bf16(ac4[40 + 2 * e], ac4[41 + 2 * e]); }
        }
#pragma unroll
        for (int e = 0; e < 20; e++) asm volatile("" : "+r"(sn[e]), "+r"(kb[e]));
        if (c == 0 && wg == 1) bar_sync(2, 256);
        wg_fence();
        unit(IntC<0>{}, b0);
        if (lane == 0) mbar_arrive(bc + 8 * (B_EMPTY4 + 1));
        send(c);
        unit(IntC<1>{}, b0);
        if (c == 0 && wg == 0) bar_arrive(2, 256);
        {
          mbar_wait(bc + 8 * (B_DSR + wg), 0);
          uint4* dst = gdst + (((j + 2 * c + 2) & 7) * 3 + c) * 1280;
#pragma unroll
          for (int q = 0; q < 5; q++) {
            const uint4 v = lds128(sb + OFF_DS + (c & 1) * 20480 + tid * 16 + q * 4096);
            st_relaxed16(dst + q * 256, (add_bf2(v.x, kb[4 * q]) & ~1u) | tag, add_bf2(v.y, kb[4 * q + 1]),
                         add_bf2(v.z, kb[4 * q + 2]), add_bf2(v.w, kb[4 * q + 3]));
          }
        }
        mbar_wait(bc + 8 * (B_FULL4 + 3), 0);
        wg_fence();
        unit(IntC<2>{}, b0);
        wg_wait<1>();
        if (lane == 0) mbar_arrive(bc + 8 * (B_EMPTY4 + 2));
        unit(IntC<3>{}, b0);
      }
      auto partial = [&](int c, uint4 (&v)[5]) {
        mbar_wait(bars + 8 * (B_RDY + c), 0);
        uint32_t bad = 0;
#pragma unroll
        for (int q = 0; q < 5; q++) { v[q] = lds128(sb + (c ? 25600 + 20480 * c : 0) + tid * 16 + q * 4096); bad |= v[q].x ^ tag; }
#pragma unroll 1
        for (uint32_t n = 0; (bad & 1u) && n < (WAIT_LIMIT >> 2); n++) {
          bad = 0;
#pragma unroll
          for (int q = 0; q < 5; q++) { v[q] = ld_relaxed16(gdst + (j * 3 + c) * 1280 + q * 256); bad |= v[q].x ^ tag; }
        }
      };
      uint4 pa4[5], pb4[5];
      partial(0, pa4);
      wg_wait<0>();
      fence_regs(ac4);
      if (rank) {
#pragma unroll
        for (int e = 0; e < 20; e++) sn[e] = pack_bf16(ac4[2 * e], ac4[2 * e + 1]);
#pragma unroll
        for (int e = 0; e < 40; e++) kp[e] = ac4[40 + e];
      } else {
#pragma unroll
        for (int e = 0; e < 20; e++) sn[e] = pack_bf16(ac4[40 + 2 * e], ac4[41 + 2 * e]);
#pragma unroll
        for (int e = 0; e < 40; e++) kp[e] = ac4[e];
      }
      send(3);
      TSTAMP(13);
      {
        mbar_wait(bars + 8 * B_XR, 1);
        const float w0 = 1.f - st_g[0], w1s = 1.f - st_g[1];
        const uint32_t xa = sb + OFF_OUT + rloc * 160 + t * 4;
#pragma unroll
        for (int g = 0; g < 10; g++) {
          const uint32_t x0 = lds32(xa + g * 16), x1 = lds32(xa + 1280 + g * 16);
          kp[4 * g] = fmaf(w0, bf_lo(x0), kp[4 * g]); kp[4 * g + 1] = fmaf(w0, bf_hi(x0), kp[4 * g + 1]);
          kp[4 * g + 2] = fmaf(w1s, bf_lo(x1), kp[4 * g + 2]); kp[4 * g + 3] = fmaf(w1s, bf_hi(x1), kp[4 * g + 3]);
        }
      }
      partial(1, pb4);
#pragma unroll
      for (int q = 0; q < 5; q++)
        pa4[q] = make_uint4(add_bf2(pa4[q].x, pb4[q].x), add_bf2(pa4[q].y, pb4[q].y), add_bf2(pa4[q].z, pb4[q].z), add_bf2(pa4[q].w, pb4[q].w));
#pragma unroll
      for (int q = 0; q < 5; q++) add8(q, pa4[q]);
      partial(2, pb4);
      mbar_wait(bars + 8 * (B_DSR + 6 + wg), 0);
      TSTAMP(14);
#pragma unroll
      for (int q = 0; q < 5; q++) {
        const uint4 c = pb4[q], d = lds128(sb + OFF_DS + 20480 + tid * 16 + q * 4096);
        add8(q, make_uint4(add_bf2(c.x, d.x), add_bf2(c.y, d.y), add_bf2(c.z, d.z), add_bf2(c.w, d.w)));
      }
      __syncwarp();
      uint32_t ov[2][10];
#pragma unroll
      for (int g = 0; g < 10; g++) { ov[0][g] = pack_bf16(kp[4 * g], kp[4 * g + 1]); ov[1][g] = pack_bf16(kp[4 * g + 2], kp[4 * g + 3]); }
      stage_tile(sb + OFF_OUT, ov);
      __syncwarp();
      __nv_bfloat16* dst = out + (size_t)(128 * i + 16 * warp) * D_ + 80 * j;
#pragma unroll
      for (int q = 0; q < 5; q++) {
        const int id = q * 32 + lane, r = id / 10;
        *reinterpret_cast<uint4*>(dst + r * (D_ - 80) + id * 8) = lds128(sb + OFF_OUT + warp * 2560 + id * 16);
      }
    }
    TSTAMP(15);
    if (tid == 0) asm volatile("red.relaxed.gpu.global.add.u32 [%0], 1;" ::"l"(g_flags + FL_DONE * 32) : "memory");
  }
}

namespace {
typedef CUresult (*EncodeFn)(CUtensorMap*, CUtensorMapDataType, cuuint32_t, void*, const cuuint64_t*, const cuuint64_t*,
                             const cuuint32_t*, const cuuint32_t*, CUtensorMapInterleave, CUtensorMapSwizzle,
                             CUtensorMapL2promotion, CUtensorMapFloatOOBfill);

void encode(EncodeFn fn, CUtensorMap* m, const void* ptr, int rank, const cuuint64_t* dims, const cuuint64_t* strides,
            const cuuint32_t* box, CUtensorMapSwizzle swz) {
  cuuint32_t es[5] = {1, 1, 1, 1, 1};
  fn(m, CU_TENSOR_MAP_DATA_TYPE_BFLOAT16, rank, const_cast<void*>(ptr), dims, strides, box, es, CU_TENSOR_MAP_INTERLEAVE_NONE,
     swz, CU_TENSOR_MAP_L2_PROMOTION_L2_128B, CU_TENSOR_MAP_FLOAT_OOB_FILL_NONE);
}
}

extern "C" void kernel_launch(void* const* d_in, const int* in_sizes, int n_in, void* d_out, int out_size) {
  (void)in_sizes; (void)n_in; (void)out_size;
  const __nv_bfloat16* x = (const __nv_bfloat16*)d_in[0];
  const __nv_bfloat16* wqkv = (const __nv_bfloat16*)d_in[1];
  const __nv_bfloat16* wphi = (const __nv_bfloat16*)d_in[2];
  const __nv_bfloat16* wo = (const __nv_bfloat16*)d_in[3];
  const __nv_bfloat16* w1 = (const __nv_bfloat16*)d_in[5];
  const __nv_bfloat16* w2 = (const __nv_bfloat16*)d_in[6];
  const __nv_bfloat16* w3 = (const __nv_bfloat16*)d_in[7];
  const __nv_bfloat16* w4 = (const __nv_bfloat16*)d_in[8];
  const __nv_bfloat16* gate_w = (const __nv_bfloat16*)d_in[9];

  static EncodeFn enc = nullptr;
  static void *pHs = nullptr, *pX1 = nullptr;
  if (!enc) {
    cudaDriverEntryPointQueryResult qr;
    cudaGetDriverEntryPoint("cuTensorMapEncodeTiled", (void**)&enc, cudaEnableDefault, &qr);
    cudaGetSymbolAddress(&pHs, g_Hs);
    cudaGetSymbolAddress(&pX1, g_X1);
    cudaFuncSetAttribute(fused_kernel, cudaFuncAttributeMaxDynamicSharedMemorySize, SMEM_BYTES);
  }
  Maps m;
  {
    cuuint64_t dims[2] = {D_, S_}, str[1] = {D_ * 2};
    cuuint32_t box[2] = {64, 128}, boxh[2] = {64, 64};
    encode(enc, &m.x, x, 2, dims, str, boxh, CU_TENSOR_MAP_SWIZZLE_128B);
    encode(enc, &m.hs, (const char*)pHs + 2 * D_ * 2, 2, dims, str, box, CU_TENSOR_MAP_SWIZZLE_128B);
    encode(enc, &m.x1, pX1, 2, dims, str, boxh, CU_TENSOR_MAP_SWIZZLE_128B);
    cuuint32_t boxr[2] = {80, 16}, boxs[2] = {80, 128};
    cuuint64_t dimsp[2] = {D_, S_ + 4};
    encode(enc, &m.st_h, pHs, 2, dimsp, str, boxs, CU_TENSOR_MAP_SWIZZLE_NONE);
    encode(enc, &m.st_x1, pX1, 2, dims, str, boxs, CU_TENSOR_MAP_SWIZZLE_NONE);
    encode(enc, &m.xr, x, 2, dims, str, boxr, CU_TENSOR_MAP_SWIZZLE_NONE);
  }
  {
    cuuint64_t dims[3] = {80, D_, 8}, str[2] = {D_ * 2, 160};
    cuuint32_t boxm[3] = {64, 64, 1}, boxr[3] = {16, 64, 1};
    encode(enc, &m.w1m, w1, 3, dims, str, boxm, CU_TENSOR_MAP_SWIZZLE_128B);
    encode(enc, &m.w1r, w1, 3, dims, str, boxr, CU_TENSOR_MAP_SWIZZLE_32B);
  }
  {
    cuuint64_t dims[4] = {80, D_, 3, 8}, str[3] = {3 * D_ * 2, D_ * 2, 160};
    cuuint32_t boxm[4] = {64, 64, 3, 1}, boxr[4] = {16, 64, 3, 1};
    encode(enc, &m.qm, wqkv, 4, dims, str, boxm, CU_TENSOR_MAP_SWIZZLE_128B);
    encode(enc, &m.qr, wqkv, 4, dims, str, boxr, CU_TENSOR_MAP_SWIZZLE_32B);
  }
  {
    cuuint64_t dims[3] = {32, D_, 20}, dims4[3] = {32, F_, 20}, str[2] = {D_ * 2, 64};
    cuuint32_t box4[3] = {32, 64, 5}, boxo[3] = {32, 80, 5};
    encode(enc, &m.w4, w4, 3, dims4, str, box4, CU_TENSOR_MAP_SWIZZLE_64B);
    encode(enc, &m.wo, wo, 3, dims, str, boxo, CU_TENSOR_MAP_SWIZZLE_64B);
    encode(enc, &m.w2, w2, 3, dims, str, box4, CU_TENSOR_MAP_SWIZZLE_64B);
  }
  {
    cuuint64_t dims[3] = {64, D_, 24}, str[2] = {F_ * 2, 128};
    cuuint32_t box[3] = {64, 64, 3};
    encode(enc, &m.w3, w3, 3, dims, str, box, CU_TENSOR_MAP_SWIZZLE_128B);
  }
  fused_kernel<<<NCTA + NSVC, 384, SMEM_BYTES, cudaStreamPerThread>>>(m, x, wqkv, wphi, w1, w2, w3, w4, wo, gate_w, (__nv_bfloat16*)d_out);
}
```

```cpp
#include <cuda_runtime.h>
#include <cuda_bf16.h>
#include <cuda.h>
#include <stdint.h>

namespace {

constexpr int S_ = 2048, D_ = 640, F_ = 1536;
constexpr int NCTA = 128, NSVC = 4;
constexpr int KV_PAIR = 40 * 48 + 96;
constexpr int KV_J = 2 * KV_PAIR;

constexpr int SLOT_B = 49152, NB = 3;
constexpr int SLOT_A = 16384, NA = 4;
constexpr int OFF_B = 0;
constexpr int OFF_A = OFF_B + NB * SLOT_B;
constexpr int OFF_STG = OFF_A + 2 * SLOT_A;
constexpr int OFF_MISC = OFF_A + NA * SLOT_A;
constexpr int OFF_XST = OFF_MISC + 13312;
constexpr int OFF_CS = OFF_MISC + 16384;
constexpr int OFF_BAR = OFF_CS + 1088;
constexpr int SMEM_BYTES = OFF_BAR + 512 + 512 + 128;
constexpr int B_FULLA = 0, B_FULLB = 4, B_CS = 7, B_XR = 8, B_KV = 9, B_ST1 = 10, B_HST = 11, B_FULL4 = 12  , B_RDY = 20  ,
              B_DSR = 23  , B_EMPTYB = 33  , B_SIGP = 36, B_SIGH = 37, B_SIGKV = 38, B_SIGX1 = 39, B_MFREE = 40,
              B_EMPTY4 = 41  , B_EMPTYA = 49  , B_PEER = 53, B_PEER2 = 54, B_X1P = 55  , NBAR = 56;
constexpr int SPARE = 40960;
constexpr int SET4 = 87040, OFF_DS = 2 * SET4, OFF_OUT = 20480;

constexpr int FL_DONE = 0, FL_H = 1  , FL_X1 = FL_H + 32, FL_KV = FL_X1 + 16, FL_CS = FL_KV + 8, FL_CS3 = FL_CS + 1, FL_ST = FL_CS3 + 1;
constexpr int FL_S1 = FL_ST + 16, FL_COUNT = FL_S1 + 16;

struct Maps {
  CUtensorMap x, w1m, w1r, qm, qr, hs, w2, x1, w3, w4, wo, xr, st_h, st_x1;
};

}

__device__ __align__(1024) __nv_bfloat16 g_Hs[(S_ + 4) * D_];
__device__ __align__(1024) __nv_bfloat16 g_X1[S_ * D_];
__device__ __align__(128) float g_acc[2][8 * KV_J];
__device__ __align__(128) float g_cs[2][D_ + F_];
__device__ __align__(128) uint4 g_wphi[8 * 800];
__device__ __align__(128) float4 g_xstat[S_];
__device__ __align__(128) float2 g_st1[S_ * 8];
__device__ __align__(128) uint4 g_part[16 * 8 * 3 * 1280];
__device__ __align__(128) unsigned g_flags[FL_COUNT * 32];
#define TSTAMP(n) do {} while (0)
#define TSTAMPX(n) do {} while (0)
#define TRACE(n) do {} while (0)
#define TRS(n) do {} while (0)

namespace {

__device__ __forceinline__ long long gtime() { long long t; asm volatile("mov.u64 %0, %%globaltimer;" : "=l"(t)); return t; }
__device__ __forceinline__ uint32_t smem_u32(const void* p) { return (uint32_t)__cvta_generic_to_shared(p); }
__device__ __forceinline__ void mbar_init(uint32_t bar, int cnt) {
  asm volatile("mbarrier.init.shared::cta.b64 [%0], %1;" ::"r"(bar), "r"(cnt) : "memory");
}
__device__ __forceinline__ void mbar_expect_tx(uint32_t bar, int bytes) {
  asm volatile("mbarrier.arrive.expect_tx.shared::cta.b64 _, [%0], %1;" ::"r"(bar), "r"(bytes) : "memory");
}
__device__ __forceinline__ void mbar_arrive_cta(uint32_t bar, uint32_t cta) {
  asm volatile("{\n.reg .b32 ra;\nmapa.shared::cluster.u32 ra, %0, %1;\nmbarrier.arrive.shared::cluster.b64 _, [ra];\n}"
               ::"r"(bar), "r"(cta) : "memory");
}
__device__ __forceinline__ uint32_t mbar_try(uint32_t bar, uint32_t parity) {
  uint32_t ok;
  asm volatile("{\n.reg .pred p;\nmbarrier.try_wait.parity.shared::cta.b64 p, [%1], %2;\nselp.u32 %0, 1, 0, p;\n}"
               : "=r"(ok) : "r"(bar), "r"(parity) : "memory");
  return ok;
}
constexpr uint32_t WAIT_LIMIT = 1u << 18;
__device__ __forceinline__ void mbar_wait(uint32_t bar, uint32_t parity) {
  uint32_t n = 0;
  while (!mbar_try(bar, parity) && ++n < WAIT_LIMIT) {}
}
__device__ __forceinline__ unsigned ld_acquire(const unsigned* p) {
  unsigned v;
  asm volatile("ld.acquire.gpu.global.u32 %0, [%1];" : "=r"(v) : "l"(p) : "memory");
  return v;
}
__device__ __forceinline__ void flag_wait(int idx, unsigned target) {
  const unsigned* p = g_flags + idx * 32;
  uint32_t n = 0;
  while ((int)(ld_acquire(p) - target) < 0 && ++n < (WAIT_LIMIT >> 2)) {}
}
__device__ __forceinline__ void flag_add(int idx) {
  asm volatile("red.release.gpu.global.add.u32 [%0], 1;" ::"l"(g_flags + idx * 32) : "memory");
}
__device__ __forceinline__ void flag_add_relaxed(int idx) {
  asm volatile("red.relaxed.gpu.global.add.u32 [%0], 1;" ::"l"(g_flags + idx * 32) : "memory");
}
__device__ __forceinline__ uint32_t mbar_test(uint32_t bar, uint32_t parity) {
  uint32_t ok;
  asm volatile("{\n.reg .pred p;\nmbarrier.test_wait.parity.shared::cta.b64 p, [%1], %2;\nselp.u32 %0, 1, 0, p;\n}"
               : "=r"(ok) : "r"(bar), "r"(parity) : "memory");
  return ok;
}
__device__ __forceinline__ uint32_t lds32(uint32_t a) {
  uint32_t v;
  asm volatile("ld.shared.u32 %0, [%1];" : "=r"(v) : "r"(a) : "memory");
  return v;
}
__device__ __forceinline__ void mbar_arrive(uint32_t bar) {
  asm volatile("mbarrier.arrive.shared::cta.b64 _, [%0];" ::"r"(bar) : "memory");
}
__device__ __forceinline__ void fence_async_glb() { asm volatile("fence.proxy.async.global;" ::: "memory"); }
__device__ __forceinline__ void fence_async_smem() { asm volatile("fence.proxy.async.shared::cta;" ::: "memory"); }
__device__ __forceinline__ void bar_sync(int id, int n) { asm volatile("bar.sync %0, %1;" ::"r"(id), "r"(n) : "memory"); }

__device__ __forceinline__ void tma2d(uint32_t dst, const CUtensorMap* m, uint32_t bar, int c0, int c1) {
  asm volatile("cp.async.bulk.tensor.2d.shared::cluster.global.mbarrier::complete_tx::bytes [%0], [%1, {%3, %4}], [%2];"
               ::"r"(dst), "l"(m), "r"(bar), "r"(c0), "r"(c1) : "memory");
}
__device__ __forceinline__ void tma2d_mc(uint32_t dst, const CUtensorMap* m, uint32_t bar, int c0, int c1) {
  asm volatile("cp.async.bulk.tensor.2d.shared::cluster.global.mbarrier::complete_tx::bytes.multicast::cluster"
               " [%0], [%1, {%3, %4}], [%2], %5;"
               ::"r"(dst), "l"(m), "r"(bar), "r"(c0), "r"(c1), "h"((uint16_t)3) : "memory");
}
__device__ __forceinline__ void tma3d(uint32_t dst, const CUtensorMap* m, uint32_t bar, int c0, int c1, int c2) {
  asm volatile("cp.async.bulk.tensor.3d.shared::cluster.global.mbarrier::complete_tx::bytes [%0], [%1, {%3, %4, %5}], [%2];"
               ::"r"(dst), "l"(m), "r"(bar), "r"(c0), "r"(c1), "r"(c2) : "memory");
}
__device__ __forceinline__ void tma4d(uint32_t dst, const CUtensorMap* m, uint32_t bar, int c0, int c1, int c2, int c3) {
  asm volatile("cp.async.bulk.tensor.4d.shared::cluster.global.mbarrier::complete_tx::bytes [%0], [%1, {%3, %4, %5, %6}], [%2];"
               ::"r"(dst), "l"(m), "r"(bar), "r"(c0), "r"(c1), "r"(c2), "r"(c3) : "memory");
}
__device__ __forceinline__ void tma2d_store(const CUtensorMap* m, uint32_t src, int c0, int c1) {
  asm volatile("cp.async.bulk.tensor.2d.global.shared::cta.bulk_group [%0, {%2, %3}], [%1];"
               ::"l"(m), "r"(src), "r"(c0), "r"(c1) : "memory");
}
__device__ __forceinline__ void bulk_store(void* dst, uint32_t src, uint32_t bytes) {
  asm volatile("cp.async.bulk.global.shared::cta.bulk_group [%0], [%1], %2;" ::"l"(dst), "r"(src), "r"(bytes) : "memory");
}
__device__ __forceinline__ void bulk_load(uint32_t dst, const void* src, uint32_t bytes, uint32_t bar) {
  asm volatile("cp.async.bulk.shared::cluster.global.mbarrier::complete_tx::bytes [%0], [%1], %2, [%3];"
               ::"r"(dst), "l"(src), "r"(bytes), "r"(bar) : "memory");
}
__device__ __forceinline__ void bulk_commit() { asm volatile("cp.async.bulk.commit_group;" ::: "memory"); }
template <int N> __device__ __forceinline__ void bulk_wait() { asm volatile("cp.async.bulk.wait_group %0;" ::"n"(N) : "memory"); }
__device__ __forceinline__ void bulk_wait_read() { asm volatile("cp.async.bulk.wait_group.read 0;" ::: "memory"); }
__device__ __forceinline__ void bar_arrive(int id, int n) { asm volatile("bar.arrive %0, %1;" ::"r"(id), "r"(n) : "memory"); }
__device__ __forceinline__ uint4 lds128(uint32_t a) {
  uint4 v;
  asm volatile("ld.shared.v4.u32 {%0, %1, %2, %3}, [%4];" : "=r"(v.x), "=r"(v.y), "=r"(v.z), "=r"(v.w) : "r"(a) : "memory");
  return v;
}
__device__ __forceinline__ void sts128(uint32_t a, uint4 v) {
  asm volatile("st.shared.v4.u32 [%0], {%1, %2, %3, %4};" ::"r"(a), "r"(v.x), "r"(v.y), "r"(v.z), "r"(v.w) : "memory");
}
__device__ __forceinline__ uint4 ld_relaxed16(const uint4* p) {
  uint4 v;
  asm volatile("ld.relaxed.gpu.global.v4.u32 {%0, %1, %2, %3}, [%4];" : "=r"(v.x), "=r"(v.y), "=r"(v.z), "=r"(v.w) : "l"(p) : "memory");
  return v;
}
__device__ __forceinline__ void st_relaxed16(uint4* p, uint32_t a, uint32_t b, uint32_t c, uint32_t d) {
  asm volatile("st.relaxed.gpu.global.v4.u32 [%0], {%1, %2, %3, %4};" ::"l"(p), "r"(a), "r"(b), "r"(c), "r"(d) : "memory");
}
__device__ __forceinline__ uint32_t map_peer(uint32_t addr, uint32_t cta) {
  uint32_t r;
  asm("mapa.shared::cluster.u32 %0, %1, %2;" : "=r"(r) : "r"(addr), "r"(cta));
  return r;
}
__device__ __forceinline__ void st_async16(uint32_t addr, uint32_t a, uint32_t b, uint32_t c, uint32_t d, uint32_t bar) {
  asm volatile("st.async.weak.shared::cluster.mbarrier::complete_tx::bytes.v4.b32 [%0], {%1, %2, %3, %4}, [%5];"
               ::"r"(addr), "r"(a), "r"(b), "r"(c), "r"(d), "r"(bar) : "memory");
}
__device__ __forceinline__ void l2_prefetch(const void* p, uint32_t bytes) {
  asm volatile("cp.async.bulk.prefetch.L2.global [%0], %1;" ::"l"(p), "r"(bytes) : "memory");
}
__device__ __forceinline__ void prefetch_tmap(const CUtensorMap* m) {
  asm volatile("prefetch.tensormap [%0];" ::"l"(m) : "memory");
}
__device__ __forceinline__ uint64_t make_desc(uint32_t a16, uint32_t off, uint32_t lbo, uint32_t sbo, uint32_t swz) {
  const uint32_t lo = a16 + ((off >> 4) + ((lbo >> 4) << 16)), hi = (sbo >> 4) | (swz << 30);
  uint64_t d;
  asm("mov.b64 %0, {%1, %2};" : "=l"(d) : "r"(lo), "r"(hi));
  return d;
}
__device__ __forceinline__ void wg_fence() { asm volatile("wgmma.fence.sync.aligned;" ::: "memory"); }
__device__ __forceinline__ void wg_commit() { asm volatile("wgmma.commit_group.sync.aligned;" ::: "memory"); }
template <int N> __device__ __forceinline__ void wg_wait() { asm volatile("wgmma.wait_group.sync.aligned %0;" ::"n"(N) : "memory"); }
template <int N> __device__ __forceinline__ void fence_regs(float (&d)[N]) {
#pragma unroll
  for (int i = 0; i < N; i++) asm volatile("" : "+f"(d[i])::"memory");
}
template <int N> __device__ __forceinline__ void zero_regs(float (&d)[N]) {
#pragma unroll
  for (int i = 0; i < N; i++) d[i] = 0.f;
}
__device__ __forceinline__ uint32_t pack_bf16(float lo, float hi) {
  uint32_t r;
  asm("cvt.rn.bf16x2.f32 %0, %1, %2;" : "=r"(r) : "f"(hi), "f"(lo));
  return r;
}
__device__ __forceinline__ float bf_lo(uint32_t v) { return __uint_as_float(v << 16); }
__device__ __forceinline__ float bf_hi(uint32_t v) { return __uint_as_float(v & 0xffff0000u); }
__device__ __forceinline__ uint32_t max_bf2(uint32_t a, uint32_t b) {
  uint32_t r; asm("max.bf16x2 %0, %1, %2;" : "=r"(r) : "r"(a), "r"(b)); return r;
}
__device__ __forceinline__ uint32_t min_bf2(uint32_t a, uint32_t b) {
  uint32_t r; asm("min.bf16x2 %0, %1, %2;" : "=r"(r) : "r"(a), "r"(b)); return r;
}
__device__ __forceinline__ uint32_t add_bf2(uint32_t a, uint32_t b) {
  uint32_t r; asm("add.rn.bf16x2 %0, %1, %2;" : "=r"(r) : "r"(a), "r"(b)); return r;
}
__device__ __forceinline__ float ex2(float x) { float r; asm("ex2.approx.ftz.f32 %0, %1;" : "=f"(r) : "f"(x)); return r; }
__device__ __forceinline__ float rcp(float x) { float r; asm("rcp.approx.ftz.f32 %0, %1;" : "=f"(r) : "f"(x)); return r; }
__device__ __forceinline__ float tanh_ap(float x) { float r; asm("tanh.approx.f32 %0, %1;" : "=f"(r) : "f"(x)); return r; }
struct GeluC { float c0, c1, ch; };
__device__ __forceinline__ GeluC gelu_consts(float rstd, float scale) {
  return GeluC{0.7978845608f * rstd, 0.0356774081f * rstd * rstd * rstd, 0.5f * scale * rstd};
}
__device__ __forceinline__ float gelu_s(float y, const GeluC& c) {
  const float u = y * fmaf(y * y, c.c1, c.c0);
  const float hx = y * c.ch;
  return fmaf(hx, tanh_ap(u), hx);
}
__device__ __forceinline__ void stsm4(uint32_t addr, uint32_t r0, uint32_t r1, uint32_t r2, uint32_t r3) {
  asm volatile("stmatrix.sync.aligned.m8n8.x4.shared.b16 [%0], {%1, %2, %3, %4};"
               ::"r"(addr), "r"(r0), "r"(r1), "r"(r2), "r"(r3) : "memory");
}

__device__ __forceinline__ void red_add4(float* p, float a, float b, float c, float d) {
  asm volatile("red.global.add.v4.f32 [%0], {%1, %2, %3, %4};" ::"l"(p), "f"(a), "f"(b), "f"(c), "f"(d) : "memory");
}

__device__ __forceinline__ void mma_ss256(float (&d)[128], uint64_t descA, uint64_t descB) {
  asm volatile("wgmma.mma_async.sync.aligned.m64n256k16.f32.bf16.bf16 {"
      "%0, %1, %2, %3, %4, %5, %6, %7, %8, %9, %10, %11, %12, %13, %14, %15, "
      "%16, %17, %18, %19, %20, %21, %22, %23, %24, %25, %26, %27, %28, %29, %30, %31, "
      "%32, %33, %34, %35, %36, %37, %38, %39, %40, %41, %42, %43, %44, %45, %46, %47, "
      "%48, %49, %50, %51, %52, %53, %54, %55, %56, %57, %58, %59, %60, %61, %62, %63, "
      "%64, %65, %66, %67, %68, %69, %70, %71, %72, %73, %74, %75, %76, %77, %78, %79, "
      "%80, %81, %82, %83, %84, %85, %86, %87, %88, %89, %90, %91, %92, %93, %94, %95, "
      "%96, %97, %98, %99, %100, %101, %102, %103, %104, %105, %106, %107, %108, %109, %110, %111, "
      "%112, %113, %114, %115, %116, %117, %118, %119, %120, %121, %122, %123, %124, %125, %126, %127"
      "}, %128, %129, 1, 1, 1, 0, 1;\n"
      : "+f"(d[0]), "+f"(d[1]), "+f"(d[2]), "+f"(d[3]), "+f"(d[4]), "+f"(d[5]), "+f"(d[6]), "+f"(d[7]),
        "+f"(d[8]), "+f"(d[9]), "+f"(d[10]), "+f"(d[11]), "+f"(d[12]), "+f"(d[13]), "+f"(d[14]), "+f"(d[15]),
        "+f"(d[16]), "+f"(d[17]), "+f"(d[18]), "+f"(d[19]), "+f"(d[20]), "+f"(d[21]), "+f"(d[22]), "+f"(d[23]),
        "+f"(d[24]), "+f"(d[25]), "+f"(d[26]), "+f"(d[27]), "+f"(d[28]), "+f"(d[29]), "+f"(d[30]), "+f"(d[31]),
        "+f"(d[32]), "+f"(d[33]), "+f"(d[34]), "+f"(d[35]), "+f"(d[36]), "+f"(d[37]), "+f"(d[38]), "+f"(d[39]),
        "+f"(d[40]), "+f"(d[41]), "+f"(d[42]), "+f"(d[43]), "+f"(d[44]), "+f"(d[45]), "+f"(d[46]), "+f"(d[47]),
        "+f"(d[48]), "+f"(d[49]), "+f"(d[50]), "+f"(d[51]), "+f"(d[52]), "+f"(d[53]), "+f"(d[54]), "+f"(d[55]),
        "+f"(d[56]), "+f"(d[57]), "+f"(d[58]), "+f"(d[59]), "+f"(d[60]), "+f"(d[61]), "+f"(d[62]), "+f"(d[63]),
        "+f"(d[64]), "+f"(d[65]), "+f"(d[66]), "+f"(d[67]), "+f"(d[68]), "+f"(d[69]), "+f"(d[70]), "+f"(d[71]),
        "+f"(d[72]), "+f"(d[73]), "+f"(d[74]), "+f"(d[75]), "+f"(d[76]), "+f"(d[77]), "+f"(d[78]), "+f"(d[79]),
        "+f"(d[80]), "+f"(d[81]), "+f"(d[82]), "+f"(d[83]), "+f"(d[84]), "+f"(d[85]), "+f"(d[86]), "+f"(d[87]),
        "+f"(d[88]), "+f"(d[89]), "+f"(d[90]), "+f"(d[91]), "+f"(d[92]), "+f"(d[93]), "+f"(d[94]), "+f"(d[95]),
        "+f"(d[96]), "+f"(d[97]), "+f"(d[98]), "+f"(d[99]), "+f"(d[100]), "+f"(d[101]), "+f"(d[102]), "+f"(d[103]),
        "+f"(d[104]), "+f"(d[105]), "+f"(d[106]), "+f"(d[107]), "+f"(d[108]), "+f"(d[109]), "+f"(d[110]), "+f"(d[111]),
        "+f"(d[112]), "+f"(d[113]), "+f"(d[114]), "+f"(d[115]), "+f"(d[116]), "+f"(d[117]), "+f"(d[118]), "+f"(d[119]),
        "+f"(d[120]), "+f"(d[121]), "+f"(d[122]), "+f"(d[123]), "+f"(d[124]), "+f"(d[125]), "+f"(d[126]), "+f"(d[127])
      : "l"(descA), "l"(descB));
}
__device__ __forceinline__ void mma_ss256_p(float (&d)[128], uint64_t descA, uint64_t descB, int acc) {
  asm volatile("{\n.reg .pred p;\nsetp.ne.b32 p, %130, 0;\n"
      "wgmma.mma_async.sync.aligned.m64n256k16.f32.bf16.bf16 {"
      "%0, %1, %2, %3, %4, %5, %6, %7, %8, %9, %10, %11, %12, %13, %14, %15, "
      "%16, %17, %18, %19, %20, %21, %22, %23, %24, %25, %26, %27, %28, %29, %30, %31, "
      "%32, %33, %34, %35, %36, %37, %38, %39, %40, %41, %42, %43, %44, %45, %46, %47, "
      "%48, %49, %50, %51, %52, %53, %54, %55, %56, %57, %58, %59, %60, %61, %62, %63, "
      "%64, %65, %66, %67, %68, %69, %70, %71, %72, %73, %74, %75, %76, %77, %78, %79, "
      "%80, %81, %82, %83, %84, %85, %86, %87, %88, %89, %90, %91, %92, %93, %94, %95, "
      "%96, %97, %98, %99, %100, %101, %102, %103, %104, %105, %106, %107, %108, %109, %110, %111, "
      "%112, %113, %114, %115, %116, %117, %118, %119, %120, %121, %122, %123, %124, %125, %126, %127"
      "}, %128, %129, p, 1, 1, 0, 1;\n}\n"
      : "+f"(d[0]), "+f"(d[1]), "+f"(d[2]), "+f"(d[3]), "+f"(d[4]), "+f"(d[5]), "+f"(d[6]), "+f"(d[7]),
        "+f"(d[8]), "+f"(d[9]), "+f"(d[10]), "+f"(d[11]), "+f"(d[12]), "+f"(d[13]), "+f"(d[14]), "+f"(d[15]),
        "+f"(d[16]), "+f"(d[17]), "+f"(d[18]), "+f"(d[19]), "+f"(d[20]), "+f"(d[21]), "+f"(d[22]), "+f"(d[23]),
        "+f"(d[24]), "+f"(d[25]), "+f"(d[26]), "+f"(d[27]), "+f"(d[28]), "+f"(d[29]), "+f"(d[30]), "+f"(d[31]),
        "+f"(d[32]), "+f"(d[33]), "+f"(d[34]), "+f"(d[35]), "+f"(d[36]), "+f"(d[37]), "+f"(d[38]), "+f"(d[39]),
        "+f"(d[40]), "+f"(d[41]), "+f"(d[42]), "+f"(d[43]), "+f"(d[44]), "+f"(d[45]), "+f"(d[46]), "+f"(d[47]),
        "+f"(d[48]), "+f"(d[49]), "+f"(d[50]), "+f"(d[51]), "+f"(d[52]), "+f"(d[53]), "+f"(d[54]), "+f"(d[55]),
        "+f"(d[56]), "+f"(d[57]), "+f"(d[58]), "+f"(d[59]), "+f"(d[60]), "+f"(d[61]), "+f"(d[62]), "+f"(d[63]),
        "+f"(d[64]), "+f"(d[65]), "+f"(d[66]), "+f"(d[67]), "+f"(d[68]), "+f"(d[69]), "+f"(d[70]), "+f"(d[71]),
        "+f"(d[72]), "+f"(d[73]), "+f"(d[74]), "+f"(d[75]), "+f"(d[76]), "+f"(d[77]), "+f"(d[78]), "+f"(d[79]),
        "+f"(d[80]), "+f"(d[81]), "+f"(d[82]), "+f"(d[83]), "+f"(d[84]), "+f"(d[85]), "+f"(d[86]), "+f"(d[87]),
        "+f"(d[88]), "+f"(d[89]), "+f"(d[90]), "+f"(d[91]), "+f"(d[92]), "+f"(d[93]), "+f"(d[94]), "+f"(d[95]),
        "+f"(d[96]), "+f"(d[97]), "+f"(d[98]), "+f"(d[99]), "+f"(d[100]), "+f"(d[101]), "+f"(d[102]), "+f"(d[103]),
        "+f"(d[104]), "+f"(d[105]), "+f"(d[106]), "+f"(d[107]), "+f"(d[108]), "+f"(d[109]), "+f"(d[110]), "+f"(d[111]),
        "+f"(d[112]), "+f"(d[113]), "+f"(d[114]), "+f"(d[115]), "+f"(d[116]), "+f"(d[117]), "+f"(d[118]), "+f"(d[119]),
        "+f"(d[120]), "+f"(d[121]), "+f"(d[122]), "+f"(d[123]), "+f"(d[124]), "+f"(d[125]), "+f"(d[126]), "+f"(d[127])
      : "l"(descA), "l"(descB), "r"(acc));
}

__device__ __forceinline__ void mma_ss64(float (&d)[32], uint64_t descA, uint64_t descB) {
  asm volatile("wgmma.mma_async.sync.aligned.m64n64k16.f32.bf16.bf16 {"
      "%0, %1, %2, %3, %4, %5, %6, %7, %8, %9, %10, %11, %12, %13, %14, %15, "
      "%16, %17, %18, %19, %20, %21, %22, %23, %24, %25, %26, %27, %28, %29, %30, %31"
      "}, %32, %33, 1, 1, 1, 0, 1;\n"
      : "+f"(d[0]), "+f"(d[1]), "+f"(d[2]), "+f"(d[3]), "+f"(d[4]), "+f"(d[5]), "+f"(d[6]), "+f"(d[7]),
        "+f"(d[8]), "+f"(d[9]), "+f"(d[10]), "+f"(d[11]), "+f"(d[12]), "+f"(d[13]), "+f"(d[14]), "+f"(d[15]),
        "+f"(d[16]), "+f"(d[17]), "+f"(d[18]), "+f"(d[19]), "+f"(d[20]), "+f"(d[21]), "+f"(d[22]), "+f"(d[23]),
        "+f"(d[24]), "+f"(d[25]), "+f"(d[26]), "+f"(d[27]), "+f"(d[28]), "+f"(d[29]), "+f"(d[30]), "+f"(d[31])
      : "l"(descA), "l"(descB));
}
__device__ __forceinline__ void mma_ss64_p(float (&d)[32], uint64_t descA, uint64_t descB, int acc) {
  asm volatile("{\n.reg .pred p;\nsetp.ne.b32 p, %34, 0;\n"
      "wgmma.mma_async.sync.aligned.m64n64k16.f32.bf16.bf16 {"
      "%0, %1, %2, %3, %4, %5, %6, %7, %8, %9, %10, %11, %12, %13, %14, %15, "
      "%16, %17, %18, %19, %20, %21, %22, %23, %24, %25, %26, %27, %28, %29, %30, %31"
      "}, %32, %33, p, 1, 1, 0, 1;\n}\n"
      : "+f"(d[0]), "+f"(d[1]), "+f"(d[2]), "+f"(d[3]), "+f"(d[4]), "+f"(d[5]), "+f"(d[6]), "+f"(d[7]),
        "+f"(d[8]), "+f"(d[9]), "+f"(d[10]), "+f"(d[11]), "+f"(d[12]), "+f"(d[13]), "+f"(d[14]), "+f"(d[15]),
        "+f"(d[16]), "+f"(d[17]), "+f"(d[18]), "+f"(d[19]), "+f"(d[20]), "+f"(d[21]), "+f"(d[22]), "+f"(d[23]),
        "+f"(d[24]), "+f"(d[25]), "+f"(d[26]), "+f"(d[27]), "+f"(d[28]), "+f"(d[29]), "+f"(d[30]), "+f"(d[31])
      : "l"(descA), "l"(descB), "r"(acc));
}

__device__ __forceinline__ void mma_ss160(float (&d)[80], uint64_t descA, uint64_t descB) {
  asm volatile("wgmma.mma_async.sync.aligned.m64n160k16.f32.bf16.bf16 {"
      "%0, %1, %2, %3, %4, %5, %6, %7, %8, %9, %10, %11, %12, %13, %14, %15, "
      "%16, %17, %18, %19, %20, %21, %22, %23, %24, %25, %26, %27, %28, %29, %30, %31, "
      "%32, %33, %34, %35, %36, %37, %38, %39, %40, %41, %42, %43, %44, %45, %46, %47, "
      "%48, %49, %50, %51, %52, %53, %54, %55, %56, %57, %58, %59, %60, %61, %62, %63, "
      "%64, %65, %66, %67, %68, %69, %70, %71, %72, %73, %74, %75, %76, %77, %78, %79"
      "}, %80, %81, 1, 1, 1, 0, 1;\n"
      : "+f"(d[0]), "+f"(d[1]), "+f"(d[2]), "+f"(d[3]), "+f"(d[4]), "+f"(d[5]), "+f"(d[6]), "+f"(d[7]),
        "+f"(d[8]), "+f"(d[9]), "+f"(d[10]), "+f"(d[11]), "+f"(d[12]), "+f"(d[13]), "+f"(d[14]), "+f"(d[15]),
        "+f"(d[16]), "+f"(d[17]), "+f"(d[18]), "+f"(d[19]), "+f"(d[20]), "+f"(d[21]), "+f"(d[22]), "+f"(d[23]),
        "+f"(d[24]), "+f"(d[25]), "+f"(d[26]), "+f"(d[27]), "+f"(d[28]), "+f"(d[29]), "+f"(d[30]), "+f"(d[31]),
        "+f"(d[32]), "+f"(d[33]), "+f"(d[34]), "+f"(d[35]), "+f"(d[36]), "+f"(d[37]), "+f"(d[38]), "+f"(d[39]),
        "+f"(d[40]), "+f"(d[41]), "+f"(d[42]), "+f"(d[43]), "+f"(d[44]), "+f"(d[45]), "+f"(d[46]), "+f"(d[47]),
        "+f"(d[48]), "+f"(d[49]), "+f"(d[50]), "+f"(d[51]), "+f"(d[52]), "+f"(d[53]), "+f"(d[54]), "+f"(d[55]),
        "+f"(d[56]), "+f"(d[57]), "+f"(d[58]), "+f"(d[59]), "+f"(d[60]), "+f"(d[61]), "+f"(d[62]), "+f"(d[63]),
        "+f"(d[64]), "+f"(d[65]), "+f"(d[66]), "+f"(d[67]), "+f"(d[68]), "+f"(d[69]), "+f"(d[70]), "+f"(d[71]),
        "+f"(d[72]), "+f"(d[73]), "+f"(d[74]), "+f"(d[75]), "+f"(d[76]), "+f"(d[77]), "+f"(d[78]), "+f"(d[79])
      : "l"(descA), "l"(descB));
}
__device__ __forceinline__ void mma_ss160_z(float (&d)[80], uint64_t descA, uint64_t descB) {
  asm volatile("wgmma.mma_async.sync.aligned.m64n160k16.f32.bf16.bf16 {"
      "%0, %1, %2, %3, %4, %5, %6, %7, %8, %9, %10, %11, %12, %13, %14, %15, "
      "%16, %17, %18, %19, %20, %21, %22, %23, %24, %25, %26, %27, %28, %29, %30, %31, "
      "%32, %33, %34, %35, %36, %37, %38, %39, %40, %41, %42, %43, %44, %45, %46, %47, "
      "%48, %49, %50, %51, %52, %53, %54, %55, %56, %57, %58, %59, %60, %61, %62, %63, "
      "%64, %65, %66, %67, %68, %69, %70, %71, %72, %73, %74, %75, %76, %77, %78, %79"
      "}, %80, %81, 0, 1, 1, 0, 1;\n"
      : "=f"(d[0]), "=f"(d[1]), "=f"(d[2]), "=f"(d[3]), "=f"(d[4]), "=f"(d[5]), "=f"(d[6]), "=f"(d[7]),
        "=f"(d[8]), "=f"(d[9]), "=f"(d[10]), "=f"(d[11]), "=f"(d[12]), "=f"(d[13]), "=f"(d[14]), "=f"(d[15]),
        "=f"(d[16]), "=f"(d[17]), "=f"(d[18]), "=f"(d[19]), "=f"(d[20]), "=f"(d[21]), "=f"(d[22]), "=f"(d[23]),
        "=f"(d[24]), "=f"(d[25]), "=f"(d[26]), "=f"(d[27]), "=f"(d[28]), "=f"(d[29]), "=f"(d[30]), "=f"(d[31]),
        "=f"(d[32]), "=f"(d[33]), "=f"(d[34]), "=f"(d[35]), "=f"(d[36]), "=f"(d[37]), "=f"(d[38]), "=f"(d[39]),
        "=f"(d[40]), "=f"(d[41]), "=f"(d[42]), "=f"(d[43]), "=f"(d[44]), "=f"(d[45]), "=f"(d[46]), "=f"(d[47]),
        "=f"(d[48]), "=f"(d[49]), "=f"(d[50]), "=f"(d[51]), "=f"(d[52]), "=f"(d[53]), "=f"(d[54]), "=f"(d[55]),
        "=f"(d[56]), "=f"(d[57]), "=f"(d[58]), "=f"(d[59]), "=f"(d[60]), "=f"(d[61]), "=f"(d[62]), "=f"(d[63]),
        "=f"(d[64]), "=f"(d[65]), "=f"(d[66]), "=f"(d[67]), "=f"(d[68]), "=f"(d[69]), "=f"(d[70]), "=f"(d[71]),
        "=f"(d[72]), "=f"(d[73]), "=f"(d[74]), "=f"(d[75]), "=f"(d[76]), "=f"(d[77]), "=f"(d[78]), "=f"(d[79])
      : "l"(descA), "l"(descB));
}

__device__ __forceinline__ void mma_ss192(float (&d)[96], uint64_t descA, uint64_t descB) {
  asm volatile("wgmma.mma_async.sync.aligned.m64n192k16.f32.bf16.bf16 {"
      "%0, %1, %2, %3, %4, %5, %6, %7, %8, %9, %10, %11, %12, %13, %14, %15, "
      "%16, %17, %18, %19, %20, %21, %22, %23, %24, %25, %26, %27, %28, %29, %30, %31, "
      "%32, %33, %34, %35, %36, %37, %38, %39, %40, %41, %42, %43, %44, %45, %46, %47, "
      "%48, %49, %50, %51, %52, %53, %54, %55, %56, %57, %58, %59, %60, %61, %62, %63, "
      "%64, %65, %66, %67, %68, %69, %70, %71, %72, %73, %74, %75, %76, %77, %78, %79, "
      "%80, %81, %82, %83, %84, %85, %86, %87, %88, %89, %90, %91, %92, %93, %94, %95"
      "}, %96, %97, 1, 1, 1, 0, 1;\n"
      : "+f"(d[0]), "+f"(d[1]), "+f"(d[2]), "+f"(d[3]), "+f"(d[4]), "+f"(d[5]), "+f"(d[6]), "+f"(d[7]),
        "+f"(d[8]), "+f"(d[9]), "+f"(d[10]), "+f"(d[11]), "+f"(d[12]), "+f"(d[13]), "+f"(d[14]), "+f"(d[15]),
        "+f"(d[16]), "+f"(d[17]), "+f"(d[18]), "+f"(d[19]), "+f"(d[20]), "+f"(d[21]), "+f"(d[22]), "+f"(d[23]),
        "+f"(d[24]), "+f"(d[25]), "+f"(d[26]), "+f"(d[27]), "+f"(d[28]), "+f"(d[29]), "+f"(d[30]), "+f"(d[31]),
        "+f"(d[32]), "+f"(d[33]), "+f"(d[34]), "+f"(d[35]), "+f"(d[36]), "+f"(d[37]), "+f"(d[38]), "+f"(d[39]),
        "+f"(d[40]), "+f"(d[41]), "+f"(d[42]), "+f"(d[43]), "+f"(d[44]), "+f"(d[45]), "+f"(d[46]), "+f"(d[47]),
        "+f"(d[48]), "+f"(d[49]), "+f"(d[50]), "+f"(d[51]), "+f"(d[52]), "+f"(d[53]), "+f"(d[54]), "+f"(d[55]),
        "+f"(d[56]), "+f"(d[57]), "+f"(d[58]), "+f"(d[59]), "+f"(d[60]), "+f"(d[61]), "+f"(d[62]), "+f"(d[63]),
        "+f"(d[64]), "+f"(d[65]), "+f"(d[66]), "+f"(d[67]), "+f"(d[68]), "+f"(d[69]), "+f"(d[70]), "+f"(d[71]),
        "+f"(d[72]), "+f"(d[73]), "+f"(d[74]), "+f"(d[75]), "+f"(d[76]), "+f"(d[77]), "+f"(d[78]), "+f"(d[79]),
        "+f"(d[80]), "+f"(d[81]), "+f"(d[82]), "+f"(d[83]), "+f"(d[84]), "+f"(d[85]), "+f"(d[86]), "+f"(d[87]),
        "+f"(d[88]), "+f"(d[89]), "+f"(d[90]), "+f"(d[91]), "+f"(d[92]), "+f"(d[93]), "+f"(d[94]), "+f"(d[95])
      : "l"(descA), "l"(descB));
}
__device__ __forceinline__ void mma_ss192_p(float (&d)[96], uint64_t descA, uint64_t descB, int acc) {
  asm volatile("{\n.reg .pred p;\nsetp.ne.b32 p, %98, 0;\n"
      "wgmma.mma_async.sync.aligned.m64n192k16.f32.bf16.bf16 {"
      "%0, %1, %2, %3, %4, %5, %6, %7, %8, %9, %10, %11, %12, %13, %14, %15, "
      "%16, %17, %18, %19, %20, %21, %22, %23, %24, %25, %26, %27, %28, %29, %30, %31, "
      "%32, %33, %34, %35, %36, %37, %38, %39, %40, %41, %42, %43, %44, %45, %46, %47, "
      "%48, %49, %50, %51, %52, %53, %54, %55, %56, %57, %58, %59, %60, %61, %62, %63, "
      "%64, %65, %66, %67, %68, %69, %70, %71, %72, %73, %74, %75, %76, %77, %78, %79, "
      "%80, %81, %82, %83, %84, %85, %86, %87, %88, %89, %90, %91, %92, %93, %94, %95"
      "}, %96, %97, p, 1, 1, 0, 1;\n}\n"
      : "+f"(d[0]), "+f"(d[1]), "+f"(d[2]), "+f"(d[3]), "+f"(d[4]), "+f"(d[5]), "+f"(d[6]), "+f"(d[7]),
        "+f"(d[8]), "+f"(d[9]), "+f"(d[10]), "+f"(d[11]), "+f"(d[12]), "+f"(d[13]), "+f"(d[14]), "+f"(d[15]),
        "+f"(d[16]), "+f"(d[17]), "+f"(d[18]), "+f"(d[19]), "+f"(d[20]), "+f"(d[21]), "+f"(d[22]), "+f"(d[23]),
        "+f"(d[24]), "+f"(d[25]), "+f"(d[26]), "+f"(d[27]), "+f"(d[28]), "+f"(d[29]), "+f"(d[30]), "+f"(d[31]),
        "+f"(d[32]), "+f"(d[33]), "+f"(d[34]), "+f"(d[35]), "+f"(d[36]), "+f"(d[37]), "+f"(d[38]), "+f"(d[39]),
        "+f"(d[40]), "+f"(d[41]), "+f"(d[42]), "+f"(d[43]), "+f"(d[44]), "+f"(d[45]), "+f"(d[46]), "+f"(d[47]),
        "+f"(d[48]), "+f"(d[49]), "+f"(d[50]), "+f"(d[51]), "+f"(d[52]), "+f"(d[53]), "+f"(d[54]), "+f"(d[55]),
        "+f"(d[56]), "+f"(d[57]), "+f"(d[58]), "+f"(d[59]), "+f"(d[60]), "+f"(d[61]), "+f"(d[62]), "+f"(d[63]),
        "+f"(d[64]), "+f"(d[65]), "+f"(d[66]), "+f"(d[67]), "+f"(d[68]), "+f"(d[69]), "+f"(d[70]), "+f"(d[71]),
        "+f"(d[72]), "+f"(d[73]), "+f"(d[74]), "+f"(d[75]), "+f"(d[76]), "+f"(d[77]), "+f"(d[78]), "+f"(d[79]),
        "+f"(d[80]), "+f"(d[81]), "+f"(d[82]), "+f"(d[83]), "+f"(d[84]), "+f"(d[85]), "+f"(d[86]), "+f"(d[87]),
        "+f"(d[88]), "+f"(d[89]), "+f"(d[90]), "+f"(d[91]), "+f"(d[92]), "+f"(d[93]), "+f"(d[94]), "+f"(d[95])
      : "l"(descA), "l"(descB), "r"(acc));
}

__device__ __forceinline__ void mma_ss80_tt(float (&d)[40], uint64_t descA, uint64_t descB) {
  asm volatile("wgmma.mma_async.sync.aligned.m64n80k16.f32.bf16.bf16 {"
      "%0, %1, %2, %3, %4, %5, %6, %7, %8, %9, %10, %11, %12, %13, %14, %15, "
      "%16, %17, %18, %19, %20, %21, %22, %23, %24, %25, %26, %27, %28, %29, %30, %31, "
      "%32, %33, %34, %35, %36, %37, %38, %39"
      "}, %40, %41, 1, 1, 1, 1, 1;\n"
      : "+f"(d[0]), "+f"(d[1]), "+f"(d[2]), "+f"(d[3]), "+f"(d[4]), "+f"(d[5]), "+f"(d[6]), "+f"(d[7]),
        "+f"(d[8]), "+f"(d[9]), "+f"(d[10]), "+f"(d[11]), "+f"(d[12]), "+f"(d[13]), "+f"(d[14]), "+f"(d[15]),
        "+f"(d[16]), "+f"(d[17]), "+f"(d[18]), "+f"(d[19]), "+f"(d[20]), "+f"(d[21]), "+f"(d[22]), "+f"(d[23]),
        "+f"(d[24]), "+f"(d[25]), "+f"(d[26]), "+f"(d[27]), "+f"(d[28]), "+f"(d[29]), "+f"(d[30]), "+f"(d[31]),
        "+f"(d[32]), "+f"(d[33]), "+f"(d[34]), "+f"(d[35]), "+f"(d[36]), "+f"(d[37]), "+f"(d[38]), "+f"(d[39])
      : "l"(descA), "l"(descB));
}
__device__ __forceinline__ void mma_ss80_tt_z(float (&d)[40], uint64_t descA, uint64_t descB) {
  asm volatile("wgmma.mma_async.sync.aligned.m64n80k16.f32.bf16.bf16 {"
      "%0, %1, %2, %3, %4, %5, %6, %7, %8, %9, %10, %11, %12, %13, %14, %15, "
      "%16, %17, %18, %19, %20, %21, %22, %23, %24, %25, %26, %27, %28, %29, %30, %31, "
      "%32, %33, %34, %35, %36, %37, %38, %39"
      "}, %40, %41, 0, 1, 1, 1, 1;\n"
      : "=f"(d[0]), "=f"(d[1]), "=f"(d[2]), "=f"(d[3]), "=f"(d[4]), "=f"(d[5]), "=f"(d[6]), "=f"(d[7]),
        "=f"(d[8]), "=f"(d[9]), "=f"(d[10]), "=f"(d[11]), "=f"(d[12]), "=f"(d[13]), "=f"(d[14]), "=f"(d[15]),
        "=f"(d[16]), "=f"(d[17]), "=f"(d[18]), "=f"(d[19]), "=f"(d[20]), "=f"(d[21]), "=f"(d[22]), "=f"(d[23]),
        "=f"(d[24]), "=f"(d[25]), "=f"(d[26]), "=f"(d[27]), "=f"(d[28]), "=f"(d[29]), "=f"(d[30]), "=f"(d[31]),
        "=f"(d[32]), "=f"(d[33]), "=f"(d[34]), "=f"(d[35]), "=f"(d[36]), "=f"(d[37]), "=f"(d[38]), "=f"(d[39])
      : "l"(descA), "l"(descB));
}

__device__ __forceinline__ void mma_rs80_k(float (&d)[40], const uint32_t (&a)[4], uint64_t descB) {
  asm volatile("wgmma.mma_async.sync.aligned.m64n80k16.f32.bf16.bf16 {"
      "%0, %1, %2, %3, %4, %5, %6, %7, %8, %9, %10, %11, %12, %13, %14, %15, "
      "%16, %17, %18, %19, %20, %21, %22, %23, %24, %25, %26, %27, %28, %29, %30, %31, "
      "%32, %33, %34, %35, %36, %37, %38, %39"
      "}, {%40, %41, %42, %43}, %44, 1, 1, 1, 0;\n"
      : "+f"(d[0]), "+f"(d[1]), "+f"(d[2]), "+f"(d[3]), "+f"(d[4]), "+f"(d[5]), "+f"(d[6]), "+f"(d[7]),
        "+f"(d[8]), "+f"(d[9]), "+f"(d[10]), "+f"(d[11]), "+f"(d[12]), "+f"(d[13]), "+f"(d[14]), "+f"(d[15]),
        "+f"(d[16]), "+f"(d[17]), "+f"(d[18]), "+f"(d[19]), "+f"(d[20]), "+f"(d[21]), "+f"(d[22]), "+f"(d[23]),
        "+f"(d[24]), "+f"(d[25]), "+f"(d[26]), "+f"(d[27]), "+f"(d[28]), "+f"(d[29]), "+f"(d[30]), "+f"(d[31]),
        "+f"(d[32]), "+f"(d[33]), "+f"(d[34]), "+f"(d[35]), "+f"(d[36]), "+f"(d[37]), "+f"(d[38]), "+f"(d[39])
      : "r"(a[0]), "r"(a[1]), "r"(a[2]), "r"(a[3]), "l"(descB));
}
__device__ __forceinline__ void mma_rs80_k_z(float (&d)[40], const uint32_t (&a)[4], uint64_t descB) {
  asm volatile("wgmma.mma_async.sync.aligned.m64n80k16.f32.bf16.bf16 {"
      "%0, %1, %2, %3, %4, %5, %6, %7, %8, %9, %10, %11, %12, %13, %14, %15, "
      "%16, %17, %18, %19, %20, %21, %22, %23, %24, %25, %26, %27, %28, %29, %30, %31, "
      "%32, %33, %34, %35, %36, %37, %38, %39"
      "}, {%40, %41, %42, %43}, %44, 0, 1, 1, 0;\n"
      : "=f"(d[0]), "=f"(d[1]), "=f"(d[2]), "=f"(d[3]), "=f"(d[4]), "=f"(d[5]), "=f"(d[6]), "=f"(d[7]),
        "=f"(d[8]), "=f"(d[9]), "=f"(d[10]), "=f"(d[11]), "=f"(d[12]), "=f"(d[13]), "=f"(d[14]), "=f"(d[15]),
        "=f"(d[16]), "=f"(d[17]), "=f"(d[18]), "=f"(d[19]), "=f"(d[20]), "=f"(d[21]), "=f"(d[22]), "=f"(d[23]),
        "=f"(d[24]), "=f"(d[25]), "=f"(d[26]), "=f"(d[27]), "=f"(d[28]), "=f"(d[29]), "=f"(d[30]), "=f"(d[31]),
        "=f"(d[32]), "=f"(d[33]), "=f"(d[34]), "=f"(d[35]), "=f"(d[36]), "=f"(d[37]), "=f"(d[38]), "=f"(d[39])
      : "r"(a[0]), "r"(a[1]), "r"(a[2]), "r"(a[3]), "l"(descB));
}

__device__ __forceinline__ void mma_rs48_k(float (&d)[24], const uint32_t (&a)[4], uint64_t descB) {
  asm volatile("wgmma.mma_async.sync.aligned.m64n48k16.f32.bf16.bf16 {"
      "%0, %1, %2, %3, %4, %5, %6, %7, %8, %9, %10, %11, %12, %13, %14, %15, "
      "%16, %17, %18, %19, %20, %21, %22, %23"
      "}, {%24, %25, %26, %27}, %28, 1, 1, 1, 0;\n"
      : "+f"(d[0]), "+f"(d[1]), "+f"(d[2]), "+f"(d[3]), "+f"(d[4]), "+f"(d[5]), "+f"(d[6]), "+f"(d[7]),
        "+f"(d[8]), "+f"(d[9]), "+f"(d[10]), "+f"(d[11]), "+f"(d[12]), "+f"(d[13]), "+f"(d[14]), "+f"(d[15]),
        "+f"(d[16]), "+f"(d[17]), "+f"(d[18]), "+f"(d[19]), "+f"(d[20]), "+f"(d[21]), "+f"(d[22]), "+f"(d[23])
      : "r"(a[0]), "r"(a[1]), "r"(a[2]), "r"(a[3]), "l"(descB));
}
__device__ __forceinline__ void mma_rs48_k_z(float (&d)[24], const uint32_t (&a)[4], uint64_t descB) {
  asm volatile("wgmma.mma_async.sync.aligned.m64n48k16.f32.bf16.bf16 {"
      "%0, %1, %2, %3, %4, %5, %6, %7, %8, %9, %10, %11, %12, %13, %14, %15, "
      "%16, %17, %18, %19, %20, %21, %22, %23"
      "}, {%24, %25, %26, %27}, %28, 0, 1, 1, 0;\n"
      : "=f"(d[0]), "=f"(d[1]), "=f"(d[2]), "=f"(d[3]), "=f"(d[4]), "=f"(d[5]), "=f"(d[6]), "=f"(d[7]),
        "=f"(d[8]), "=f"(d[9]), "=f"(d[10]), "=f"(d[11]), "=f"(d[12]), "=f"(d[13]), "=f"(d[14]), "=f"(d[15]),
        "=f"(d[16]), "=f"(d[17]), "=f"(d[18]), "=f"(d[19]), "=f"(d[20]), "=f"(d[21]), "=f"(d[22]), "=f"(d[23])
      : "r"(a[0]), "r"(a[1]), "r"(a[2]), "r"(a[3]), "l"(descB));
}

__device__ __forceinline__ void mma_rs160_n(float (&d)[80], const uint32_t (&a)[4], uint64_t descB) {
  asm volatile("wgmma.mma_async.sync.aligned.m64n160k16.f32.bf16.bf16 {"
      "%0, %1, %2, %3, %4, %5, %6, %7, %8, %9, %10, %11, %12, %13, %14, %15, "
      "%16, %17, %18, %19, %20, %21, %22, %23, %24, %25, %26, %27, %28, %29, %30, %31, "
      "%32, %33, %34, %35, %36, %37, %38, %39, %40, %41, %42, %43, %44, %45, %46, %47, "
      "%48, %49, %50, %51, %52, %53, %54, %55, %56, %57, %58, %59, %60, %61, %62, %63, "
      "%64, %65, %66, %67, %68, %69, %70, %71, %72, %73, %74, %75, %76, %77, %78, %79"
      "}, {%80, %81, %82, %83}, %84, 1, 1, 1, 1;\n"
      : "+f"(d[0]), "+f"(d[1]), "+f"(d[2]), "+f"(d[3]), "+f"(d[4]), "+f"(d[5]), "+f"(d[6]), "+f"(d[7]),
        "+f"(d[8]), "+f"(d[9]), "+f"(d[10]), "+f"(d[11]), "+f"(d[12]), "+f"(d[13]), "+f"(d[14]), "+f"(d[15]),
        "+f"(d[16]), "+f"(d[17]), "+f"(d[18]), "+f"(d[19]), "+f"(d[20]), "+f"(d[21]), "+f"(d[22]), "+f"(d[23]),
        "+f"(d[24]), "+f"(d[25]), "+f"(d[26]), "+f"(d[27]), "+f"(d[28]), "+f"(d[29]), "+f"(d[30]), "+f"(d[31]),
        "+f"(d[32]), "+f"(d[33]), "+f"(d[34]), "+f"(d[35]), "+f"(d[36]), "+f"(d[37]), "+f"(d[38]), "+f"(d[39]),
        "+f"(d[40]), "+f"(d[41]), "+f"(d[42]), "+f"(d[43]), "+f"(d[44]), "+f"(d[45]), "+f"(d[46]), "+f"(d[47]),
        "+f"(d[48]), "+f"(d[49]), "+f"(d[50]), "+f"(d[51]), "+f"(d[52]), "+f"(d[53]), "+f"(d[54]), "+f"(d[55]),
        "+f"(d[56]), "+f"(d[57]), "+f"(d[58]), "+f"(d[59]), "+f"(d[60]), "+f"(d[61]), "+f"(d[62]), "+f"(d[63]),
        "+f"(d[64]), "+f"(d[65]), "+f"(d[66]), "+f"(d[67]), "+f"(d[68]), "+f"(d[69]), "+f"(d[70]), "+f"(d[71]),
        "+f"(d[72]), "+f"(d[73]), "+f"(d[74]), "+f"(d[75]), "+f"(d[76]), "+f"(d[77]), "+f"(d[78]), "+f"(d[79])
      : "r"(a[0]), "r"(a[1]), "r"(a[2]), "r"(a[3]), "l"(descB));
}
__device__ __forceinline__ void mma_rs160_n_z(float (&d)[80], const uint32_t (&a)[4], uint64_t descB) {
  asm volatile("wgmma.mma_async.sync.aligned.m64n160k16.f32.bf16.bf16 {"
      "%0, %1, %2, %3, %4, %5, %6, %7, %8, %9, %10, %11, %12, %13, %14, %15, "
      "%16, %17, %18, %19, %20, %21, %22, %23, %24, %25, %26, %27, %28, %29, %30, %31, "
      "%32, %33, %34, %35, %36, %37, %38, %39, %40, %41, %42, %43, %44, %45, %46, %47, "
      "%48, %49, %50, %51, %52, %53, %54, %55, %56, %57, %58, %59, %60, %61, %62, %63, "
      "%64, %65, %66, %67, %68, %69, %70, %71, %72, %73, %74, %75, %76, %77, %78, %79"
      "}, {%80, %81, %82, %83}, %84, 0, 1, 1, 1;\n"
      : "=f"(d[0]), "=f"(d[1]), "=f"(d[2]), "=f"(d[3]), "=f"(d[4]), "=f"(d[5]), "=f"(d[6]), "=f"(d[7]),
        "=f"(d[8]), "=f"(d[9]), "=f"(d[10]), "=f"(d[11]), "=f"(d[12]), "=f"(d[13]), "=f"(d[14]), "=f"(d[15]),
        "=f"(d[16]), "=f"(d[17]), "=f"(d[18]), "=f"(d[19]), "=f"(d[20]), "=f"(d[21]), "=f"(d[22]), "=f"(d[23]),
        "=f"(d[24]), "=f"(d[25]), "=f"(d[26]), "=f"(d[27]), "=f"(d[28]), "=f"(d[29]), "=f"(d[30]), "=f"(d[31]),
        "=f"(d[32]), "=f"(d[33]), "=f"(d[34]), "=f"(d[35]), "=f"(d[36]), "=f"(d[37]), "=f"(d[38]), "=f"(d[39]),
        "=f"(d[40]), "=f"(d[41]), "=f"(d[42]), "=f"(d[43]), "=f"(d[44]), "=f"(d[45]), "=f"(d[46]), "=f"(d[47]),
        "=f"(d[48]), "=f"(d[49]), "=f"(d[50]), "=f"(d[51]), "=f"(d[52]), "=f"(d[53]), "=f"(d[54]), "=f"(d[55]),
        "=f"(d[56]), "=f"(d[57]), "=f"(d[58]), "=f"(d[59]), "=f"(d[60]), "=f"(d[61]), "=f"(d[62]), "=f"(d[63]),
        "=f"(d[64]), "=f"(d[65]), "=f"(d[66]), "=f"(d[67]), "=f"(d[68]), "=f"(d[69]), "=f"(d[70]), "=f"(d[71]),
        "=f"(d[72]), "=f"(d[73]), "=f"(d[74]), "=f"(d[75]), "=f"(d[76]), "=f"(d[77]), "=f"(d[78]), "=f"(d[79])
      : "r"(a[0]), "r"(a[1]), "r"(a[2]), "r"(a[3]), "l"(descB));
}

__device__ __forceinline__ void feature_map(const uint32_t (&P)[2][10], uint32_t (&fr)[10][4]) {
  constexpr float L2E = 1.4426950408889634f;
#pragma unroll
  for (int p = 0; p < 2; p++) {
#pragma unroll
    for (int r = 0; r < 2; r++) {
      uint32_t mx = P[r][5 * p], mn = mx;
#pragma unroll
      for (int g = 1; g < 5; g++) { mx = max_bf2(mx, P[r][5 * p + g]); mn = min_bf2(mn, P[r][5 * p + g]); }
      mx = max_bf2(mx, __shfl_xor_sync(0xffffffffu, mx, 1));
      mn = min_bf2(mn, __shfl_xor_sync(0xffffffffu, mn, 1));
      mx = max_bf2(mx, __shfl_xor_sync(0xffffffffu, mx, 2));
      mn = min_bf2(mn, __shfl_xor_sync(0xffffffffu, mn, 2));
      float mx0 = -bf_lo(mx) * L2E, mx1 = -bf_hi(mx) * L2E, mn0 = bf_lo(mn) * L2E, mn1 = bf_hi(mn) * L2E;
      float ep0[5], ep1[5], en0[5], en1[5];
      float sp0 = 0.f, sp1 = 0.f, sn0 = 0.f, sn1 = 0.f;
#pragma unroll
      for (int g = 0; g < 5; g++) {
        float x0 = bf_lo(P[r][5 * p + g]), x1 = bf_hi(P[r][5 * p + g]);
        ep0[g] = ex2(fmaf(x0, L2E, mx0)); ep1[g] = ex2(fmaf(x1, L2E, mx1));
        en0[g] = ex2(fmaf(x0, -L2E, mn0)); en1[g] = ex2(fmaf(x1, -L2E, mn1));
        sp0 += ep0[g]; sp1 += ep1[g]; sn0 += en0[g]; sn1 += en1[g];
      }
      sp0 += __shfl_xor_sync(0xffffffffu, sp0, 1); sp1 += __shfl_xor_sync(0xffffffffu, sp1, 1);
      sn0 += __shfl_xor_sync(0xffffffffu, sn0, 1); sn1 += __shfl_xor_sync(0xffffffffu, sn1, 1);
      sp0 += __shfl_xor_sync(0xffffffffu, sp0, 2); sp1 += __shfl_xor_sync(0xffffffffu, sp1, 2);
      sn0 += __shfl_xor_sync(0xffffffffu, sn0, 2); sn1 += __shfl_xor_sync(0xffffffffu, sn1, 2);
      sp0 = rcp(sp0); sp1 = rcp(sp1); sn0 = rcp(sn0); sn1 = rcp(sn1);
#pragma unroll
      for (int g = 0; g < 5; g++) {
        fr[5 * p + g][r] = pack_bf16(ep0[g] * sp0, ep1[g] * sp1);
        fr[5 * p + g][2 + r] = pack_bf16(en0[g] * sn0, en1[g] * sn1);
      }
    }
  }
}

template <int V> struct IntC { static constexpr int value = V; };
struct Ring {
  uint32_t idx, phase;
  template <int N> __device__ __forceinline__ void next() { if (++idx == N) { idx = 0; phase ^= 1; } }
};

}

__global__ void __cluster_dims__(2, 1, 1) __launch_bounds__(384, 1)
fused_kernel(const __grid_constant__ Maps maps, const __nv_bfloat16* __restrict__ x, const __nv_bfloat16* __restrict__ wqkv,
             const __nv_bfloat16* __restrict__ wphi, const __nv_bfloat16* __restrict__ w1, const __nv_bfloat16* __restrict__ w2,
             const __nv_bfloat16* __restrict__ w3, const __nv_bfloat16* __restrict__ w4, const __nv_bfloat16* __restrict__ wo,
             const __nv_bfloat16* __restrict__ gate_w, __nv_bfloat16* __restrict__ out) {
  extern __shared__ __align__(1024) uint8_t sgen[];
  const uint32_t sb = smem_u32(sgen);
  const uint32_t sb16 = (sb & 0x3FFFFu) >> 4;
  const uint32_t bars = sb + OFF_BAR;
  const uint32_t fullA = bars + 8 * B_FULLA, emptyA = bars + 8 * B_EMPTYA, fullB = bars + 8 * B_FULLB, emptyB = bars + 8 * B_EMPTYB;

  const int tid = threadIdx.x;
  const int rank = blockIdx.x & 1;
  const int bid = blockIdx.x - NSVC, pairIdx = bid >> 1;
  const int i = pairIdx >> 2, j = 2 * (pairIdx & 3) + rank;
  const int k3 = (5 * (pairIdx & 3) + 1) >> 1;

  if (bid < 0) {
    const int sv = blockIdx.x;
    const unsigned epoch = *reinterpret_cast<volatile unsigned*>(g_flags + FL_DONE * 32) / NCTA;
    if (tid == 0) mbar_init(bars, 1);
    __syncthreads();
    float a[8];
#pragma unroll 1
    for (int rd = 0; rd < 5; rd++) {
      const int nch = rd ? 192 : 80, nth = rd ? 384 : 320, bytes = rd ? 122880 : 204800;
      if (tid == 0) {
        mbar_expect_tx(bars, bytes + (rd ? 0 : 6400));
        const char* src = reinterpret_cast<const char*>(rd ? w3 + (size_t)(160 * sv + 40 * (rd - 1)) * F_ : w1 + (size_t)160 * sv * D_);
        if (rd == 0) bulk_load(sb + 204800, wphi + sv * 3200, 6400, bars);
        for (int o = 0; o < bytes; o += 20480) bulk_load(sb + o, src + o, 20480, bars);
      }
      if (rd == 0) {
        if (tid < 40 && (tid < 20 || sv >= 2))
          reinterpret_cast<uint4*>(g_Hs + (size_t)(2 + ((sv & 1) ? S_ - 1 - tid / 20 : tid / 20)) * D_ + 160 * sv)[tid % 20] = make_uint4(0, 0, 0, 0);
      }
      if (rd < 2) {
#pragma unroll
        for (int e = 0; e < 8; e++) a[e] = 0.f;
      }
      mbar_wait(bars, rd & 1);
      if (tid < nth) {
#pragma unroll 4
        for (int o = tid * 16; o < bytes; o += nth * 16) {
          const uint4 v = lds128(sb + o);
          a[0] += bf_lo(v.x); a[1] += bf_hi(v.x); a[2] += bf_lo(v.y); a[3] += bf_hi(v.y);
          a[4] += bf_lo(v.z); a[5] += bf_hi(v.z); a[6] += bf_lo(v.w); a[7] += bf_hi(v.w);
        }
        if (rd == 0 || rd == 4) {
          float* cd = g_cs[epoch & 1] + (rd ? D_ : 0) + 8 * (tid % nch);
          red_add4(cd, a[0], a[1], a[2], a[3]); red_add4(cd + 4, a[4], a[5], a[6], a[7]);
        }
      }
      if (rd == 0) {
        for (int e = tid; e < 1600; e += 384) {
          const int jj = e / 800, it = e - 800 * jj, st = it / 160, n = (it - 160 * st) >> 1, k0 = 16 * st + 8 * ((it ^ (n >> 2)) & 1);
          const int nn = n % 40, h = 2 * (n / 40) + (nn & 1), ff = 4 * (nn >> 3) + ((nn >> 1) & 3);
          uint32_t w[8];
#pragma unroll
          for (int q = 0; q < 8; q++) {
            const int k = k0 + q;
            w[q] = k / 20 == h ? reinterpret_cast<const unsigned short*>(sgen + 204800)[jj * 1600 + k * 20 + ff] : 0u;
          }
          g_wphi[sv * 1600 + e] = make_uint4(w[0] | (w[1] << 16), w[2] | (w[3] << 16), w[4] | (w[5] << 16), w[6] | (w[7] << 16));
        }
      }
      __syncthreads();
      if (tid == 32 && (rd == 0 || rd == 4)) {
        flag_add(rd ? FL_CS3 : FL_CS);
        if (rd == 0) l2_prefetch(w2 + (size_t)sv * (D_ * D_ / NSVC), D_ * D_ * 2 / NSVC);
      }
    }
    for (int e = tid; e < (D_ + F_) / NSVC; e += 384) g_cs[(epoch + 1) & 1][sv * ((D_ + F_) / NSVC) + e] = 0.f;
    for (int e = tid; e < 2 * KV_J; e += 384) g_acc[(epoch + 1) & 1][sv * 2 * KV_J + e] = 0.f;
    if (tid < 32) {
      l2_prefetch(w4 + (size_t)(sv * 32 + tid) * (F_ * D_ / 128), F_ * D_ * 2 / 128);
      l2_prefetch(wo + (size_t)(sv * 32 + tid) * (D_ * D_ / 128), D_ * D_ * 2 / 128);
    }
    return;
  }
  TSTAMP(0);
  auto load_p1_b = [&](int k, uint32_t slot, uint32_t bar) {
    mbar_expect_tx(bar, 40960);
    tma4d(slot + 8192, &maps.qm, bar, 0, 64 * k, 0, j);
    tma3d(slot, &maps.w1m, bar, 0, 64 * k, j);
    tma4d(slot + 32768 + 2048, &maps.qr, bar, 64, 64 * k, 0, j);
    tma3d(slot + 32768, &maps.w1r, bar, 64, 64 * k, j);
  };
  if (tid >= 256) {
    asm volatile("setmaxnreg.dec.sync.aligned.u32 40;");
    if (tid == 256) {
#pragma unroll
      for (int s = 0; s < NA; s++) mbar_init(fullA + 8 * s, 1);
      asm volatile("fence.mbarrier_init.release.cluster;" ::: "memory");
#pragma unroll 1
      for (int u = 0; u < 4; u++) {
        if ((u & 1) == 0) mbar_expect_tx(fullA + 4 * u, SLOT_A);
        tma2d(sb + OFF_A + u * 8192, &maps.x, fullA + 8 * (u >> 1), 64 * (u >> 1), 128 * i + 64 * (u & 1));
      }
    } else if (tid == 288) {
#pragma unroll
      for (int s = 0; s < NB; s++) mbar_init(fullB + 8 * s, 1);
      asm volatile("fence.mbarrier_init.release.cluster;" ::: "memory");
#pragma unroll 1
      for (int k = 0; k < 2; k++) load_p1_b(k, sb + OFF_B + k * SLOT_B, fullB + 8 * k);
      l2_prefetch(wqkv + (size_t)(128 + 4 * bid) * (3 * D_), 4 * 3 * D_ * 2);
    } else if (tid == 320) {
#pragma unroll
      for (int b = B_CS; b < NBAR; b++) mbar_init(bars + 8 * b, b < B_EMPTYB ? 1 : b < B_EMPTYA ? 8 : b < B_X1P ? 16 : 2);
#pragma unroll
      for (int b = B_DSR; b < B_EMPTYB; b++) mbar_expect_tx(bars + 8 * b, 10240);
      asm volatile("fence.mbarrier_init.release.cluster;" ::: "memory");
    }
    __syncwarp();
    asm volatile("barrier.cluster.arrive.relaxed.aligned;" ::: "memory");
    auto get_epoch = [&]() { return *reinterpret_cast<volatile unsigned*>(g_flags + FL_DONE * 32) / NCTA; };
    asm volatile("barrier.cluster.wait.aligned;" ::: "memory");
    const int lane = tid & 31, pw = (tid >> 5) & 3;
    if (pw == 0) {
      if (tid == 256) {
        Ring r{2, 1};
        unsigned ep1 = 0;
#pragma unroll 1
        for (int k = 2; k < 25; k++) {
          if (k == 4) ep1 = get_epoch() + 1;
          if (k == 10 || k == 17) {
            if (k == 10) mbar_wait(bars + 8 * B_HST, 0);
            flag_wait(k == 10 ? FL_H + 2 * i + rank : FL_X1 + i, ep1 * 8u);
            TSTAMPX(k == 10 ? 29 : 30);
          }
          if (k == 15) mbar_wait(bars + 8 * B_X1P, 0);
          mbar_wait(emptyA + 8 * r.idx, r.phase);
          const uint32_t bar = fullA + 8 * r.idx, slot = sb + OFF_A + r.idx * SLOT_A;
          mbar_expect_tx(bar, SLOT_A);
          if (k >= 10 && k < 15) tma2d(slot, &maps.hs, bar, 64 * (k - 10) + 320 * rank, 128 * i);
          else tma2d_mc(slot + rank * 8192, k < 10 ? &maps.x : &maps.x1, bar, 64 * (k < 10 ? k : (k - 15 + k3) % 10), 128 * i + 64 * rank);
          r.next<NA>();
        }
      }
    } else if (pw == 1) {
      if (tid == 288) {
        Ring r{2, 1};
#pragma unroll 1
        for (int k = 2; k < 18; k++) {
          mbar_wait(emptyB + 8 * r.idx, r.phase);
          const uint32_t bar = fullB + 8 * r.idx, slot = sb + OFF_B + r.idx * SLOT_B;
          if (k < 10) {
            load_p1_b(k, slot, bar);
          } else if (k < 13) {
            mbar_expect_tx(bar, k < 12 ? 40960 : 20480);
            tma3d(slot, &maps.w2, bar, 0, 320 * rank + 128 * (k - 10), 5 * (j >> 1));
            if (k < 12) tma3d(slot + 20480, &maps.w2, bar, 0, 320 * rank + 128 * (k - 10) + 64, 5 * (j >> 1));
          } else {
            mbar_expect_tx(bar, 49152);
            tma3d(slot, &maps.w3, bar, 0, 64 * ((2 * (k - 13) + k3) % 10), 3 * j);
            tma3d(slot + 24576, &maps.w3, bar, 0, 64 * ((2 * (k - 13) + 1 + k3) % 10), 3 * j);
          }
          r.next<NB>();
        }
#pragma unroll 1
        for (int n = 0; n < 8; n++) {
          if (n < 3) { mbar_wait(emptyB + 8 * r.idx, r.phase); r.next<NB>(); }
          if (n >= 4) mbar_wait(bars + 8 * (B_EMPTY4 + n - 4), 0);
          const uint32_t bar = bars + 8 * (B_FULL4 + n), set = sb + ((n >> 1) & 1) * SET4;
          const int h = n & 1, m = ((j >> 1) + 1 + (n >> 1)) & 3;
          mbar_expect_tx(bar, h ? 40960 : 46080);
          tma3d(set + (h ? 46080 : 0), h ? &maps.w4 : &maps.wo, bar, 0, h ? 192 * j + 64 : 80 * j, 5 * m);
          tma3d(set + (h ? 66560 : 25600), &maps.w4, bar, 0, 192 * j + 128 * h, 5 * m);
        }
        mbar_wait(bars + 8 * (B_EMPTY4 + 4), 0);
        mbar_expect_tx(bars + 8 * B_XR, 20480);
        tma2d(sb + OFF_OUT, &maps.st_x1, bars + 8 * B_XR, 80 * j, 128 * i);
      }
    } else {
      const unsigned epoch = get_epoch();
      float* accg = g_acc[epoch & 1];
      if (pw == 2) {
        if (tid == 320) {
          flag_wait(FL_CS, (epoch + 1) * NSVC);
          flag_wait(FL_ST + i, (epoch + 1) * 8u);
          fence_async_glb();
          *reinterpret_cast<volatile uint32_t*>(sgen + OFF_BAR + 8 * NBAR) = (epoch + 1) & 1;
          mbar_expect_tx(bars + 8 * B_CS, 320 + 2048 + 12800);
          bulk_load(sb + OFF_CS, g_cs[epoch & 1] + 80 * j, 320, bars + 8 * B_CS);
          bulk_load(sb + OFF_XST, g_xstat + 128 * i, 2048, bars + 8 * B_CS);
          bulk_load(sb + OFF_MISC, g_wphi + j * 800, 12800, bars + 8 * B_CS);
          TSTAMPX(21);
          flag_wait(FL_KV + j, (epoch + 1) * 16u);
          mbar_expect_tx(bars + 8 * B_KV, KV_J * 4);
          bulk_load(sb + OFF_MISC, accg + j * KV_J, KV_J * 4, bars + 8 * B_KV);
          TSTAMPX(22);
          flag_wait(FL_CS3, (epoch + 1) * NSVC);
          flag_wait(FL_S1 + i, (epoch + 1) * 8u);
          fence_async_glb();
          mbar_expect_tx(bars + 8 * B_ST1, 8192 + 768);
          bulk_load(sb + OFF_CS + 320, g_cs[epoch & 1] + D_ + 192 * j, 768, bars + 8 * B_ST1);
          bulk_load(sb + OFF_MISC, g_st1 + 128 * i * 8, 8192, bars + 8 * B_ST1);
        }
        __syncwarp();
#pragma unroll 1
        for (int c = 0; c < 3; c++) {
          mbar_wait(bars + 8 * (B_EMPTY4 + (c ? 5 : 4)), 0);
          const uint4* src = g_part + (size_t)((i * 8 + j) * 3 + c) * 1280;
          const unsigned* tp = reinterpret_cast<const unsigned*>(src + 1024 + (lane & 7) * 32 + 31);
          uint32_t n = 0;
          while (!__all_sync(0xffffffffu, (ld_acquire(tp) ^ epoch) & 1u) && ++n < (WAIT_LIMIT >> 2)) {}
          if (tid == 320) {
            mbar_expect_tx(bars + 8 * (B_RDY + c), 20480);
            bulk_load(sb + (c ? 25600 + 20480 * c : 0), src, 20480, bars + 8 * (B_RDY + c));
          }
        }
      }
      if (tid == 352) {
        mbar_wait(bars + 8 * B_SIGP, 0);
        flag_add(FL_ST + i);
        TSTAMPX(20);
        mbar_expect_tx(bars + 8 * B_XR, 20480);
#pragma unroll 1
        for (int u = 0; u < 8; u++)
          tma2d(sb + OFF_B + (u / 3) * SLOT_B + SPARE + (u % 3) * 2560, &maps.xr, bars + 8 * B_XR, 80 * j, 128 * i + 16 * u);
        const int shift = (j < 2) ? 1 : (j < 4) ? -1 : (j < 6) ? 2 : -2;
        prefetch_tmap(&maps.st_h); prefetch_tmap(&maps.st_x1); prefetch_tmap(&maps.hs); prefetch_tmap(&maps.x1);
        prefetch_tmap(&maps.w2); prefetch_tmap(&maps.w3); prefetch_tmap(&maps.w4); prefetch_tmap(&maps.wo);
        mbar_wait(bars + 8 * B_SIGH, 0);
        TSTAMPX(23);
        tma2d_store(&maps.st_h, sb + OFF_STG, 80 * j, 128 * i + 2 + shift);
        bulk_commit(); bulk_wait<0>();
        mbar_arrive(bars + 8 * B_HST);
        flag_add(FL_H + 2 * i + (j >> 2));
        flag_add_relaxed(FL_H + 2 * ((i + (shift > 0 ? 1 : -1)) & 15) + (j >> 2));
        TSTAMPX(24);
        mbar_wait(bars + 8 * B_SIGKV, 0);
        TSTAMPX(25);
        fence_async_smem();
        asm volatile("cp.reduce.async.bulk.global.shared::cta.bulk_group.add.f32 [%0], [%1], %2;"
                     ::"l"(accg + j * KV_J), "r"(sb + OFF_MISC), "r"(KV_J * 4) : "memory");
        bulk_commit(); bulk_wait<0>();
        flag_add(FL_KV + j);
        TSTAMPX(26);
        mbar_wait(bars + 8 * B_SIGX1, 0);
        TSTAMPX(27);
        tma2d_store(&maps.st_x1, sb + OFF_STG, 80 * j, 128 * i);
        bulk_commit(); bulk_wait<0>();
        flag_add(FL_X1 + i);
        mbar_arrive_cta(bars + 8 * B_X1P, 0); mbar_arrive_cta(bars + 8 * B_X1P, 1);
        TSTAMPX(28);
        mbar_wait(bars + 8 * B_MFREE, 0);
        flag_add(FL_S1 + i);
      }
    }
  } else {
    uint4 pv[5], pw_[5];
    {
      const int row = 128 * i + 16 * j + (tid >> 4), l16 = tid & 15;
#pragma unroll
      for (int c = 0; c < 5; c++) pv[c] = __ldg(reinterpret_cast<const uint4*>(x + (size_t)row * D_ + c * 128 + l16 * 8));
#pragma unroll
      for (int c = 0; c < 5; c++) pw_[c] = __ldg(reinterpret_cast<const uint4*>(gate_w + c * 128 + l16 * 8));
    }
    asm volatile("barrier.cluster.arrive.relaxed.aligned;" ::: "memory");
    asm volatile("setmaxnreg.inc.sync.aligned.u32 232;");
    const int wg = tid >> 7, warp = tid >> 5, lane = tid & 31, t = lane & 3;
    const int rloc = warp * 16 + (lane >> 2);
    const float* s_cs = reinterpret_cast<const float*>(sgen + OFF_CS);
    auto signal = [&](int b) {
      __syncwarp();
      if (lane == 0) mbar_arrive(bars + 8 * b);
    };
    auto releaseB = [&](uint32_t bar) {
      __syncwarp();
      if (lane == 0) mbar_arrive(bar);
    };
    auto release = [&](uint32_t bar) {
      __syncwarp();
      if (lane < 2) mbar_arrive_cta(bar, lane);
    };
    const uint32_t stg_lane = (warp * 16 + ((lane >> 3) & 1) * 8 + (lane & 7)) * 160 + (lane >> 4) * 16;

    auto stage_tile = [&](uint32_t stg, const uint32_t (&v)[2][10]) {
#pragma unroll
      for (int s = 0; s < 5; s++) stsm4(stg + stg_lane + s * 32, v[0][2 * s], v[1][2 * s], v[0][2 * s + 1], v[1][2 * s + 1]);
    };

    {
      float f[40];
      float s = 0.f, gs = 0.f;
#pragma unroll
      for (int c = 0; c < 5; c++) {
        const uint32_t vv[4] = {pv[c].x, pv[c].y, pv[c].z, pv[c].w}, ww[4] = {pw_[c].x, pw_[c].y, pw_[c].z, pw_[c].w};
#pragma unroll
        for (int e = 0; e < 4; e++) {
          f[8 * c + 2 * e] = bf_lo(vv[e]); f[8 * c + 2 * e + 1] = bf_hi(vv[e]);
          s += f[8 * c + 2 * e] + f[8 * c + 2 * e + 1];
          gs = fmaf(f[8 * c + 2 * e], bf_lo(ww[e]), gs); gs = fmaf(f[8 * c + 2 * e + 1], bf_hi(ww[e]), gs);
        }
      }
#pragma unroll
      for (int o = 1; o < 16; o <<= 1) { s += __shfl_xor_sync(0xffffffffu, s, o); gs += __shfl_xor_sync(0xffffffffu, gs, o); }
      const float mean = s * (1.f / D_);
      float q = 0.f;
#pragma unroll
      for (int e = 0; e < 40; e++) { const float d = f[e] - mean; q = fmaf(d, d, q); }
#pragma unroll
      for (int o = 1; o < 16; o <<= 1) q += __shfl_xor_sync(0xffffffffu, q, o);
      const float rstd = rsqrtf(q * (1.f / D_) + 1e-5f);
      asm volatile("barrier.cluster.wait.aligned;" ::: "memory");
      if ((tid & 15) == 0) g_xstat[128 * i + 16 * j + (tid >> 4)] = make_float4(rstd, -mean, rcp(1.f + __expf(-gs)), 0.f);
      signal(B_SIGP);
    }
    TSTAMP(1);

    Ring ra{0, 0}, rb{0, 0};
    uint32_t qp[2][10], P[2][10];
    float st_g[2];
    {
      float accM[128], accR[32];
      uint32_t pa = 0, pb = 0;
#pragma unroll 1
      for (int k = 0; k < 10; k++) {
        mbar_wait(fullA + 8 * ra.idx, ra.phase);
        if (tid == 0) TRACE(32 + k);
        mbar_wait(fullB + 8 * rb.idx, rb.phase);
        if (tid == 0) TRACE(64 + k);
        if (k == 0) TSTAMP(2);
        const uint32_t a0 = sb16 + ((OFF_A + ra.idx * SLOT_A + wg * 8192) >> 4), b0 = sb16 + ((OFF_B + rb.idx * SLOT_B) >> 4);
        wg_fence();
#pragma unroll
        for (int kk = 0; kk < 4; kk++) {
          const uint64_t da = make_desc(a0, kk * 32, 16, 1024, 1);
          if (kk == 0) {
            mma_ss256_p(accM, da, make_desc(b0, 0, 8192, 1024, 1), k);
            mma_ss64_p(accR, da, make_desc(b0, 32768, 2048, 256, 3), k);
          } else {
            mma_ss256(accM, da, make_desc(b0, kk * 2048, 8192, 1024, 1));
            mma_ss64(accR, da, make_desc(b0, 32768 + kk * 512, 2048, 256, 3));
          }
          if (kk == 0) {
            wg_commit();
            if (k > 0) {
              wg_wait<1>();
              if (k - 1 < 8) release(emptyA + 8 * pa);
              releaseB(emptyB + 8 * pb);
            }
          }
        }
        wg_commit();
        pa = ra.idx; pb = rb.idx;
        ra.next<NA>(); rb.next<NB>();
      }
      TSTAMP(18);
      float st_rstd[2], st_mr[2];
      mbar_wait(bars + 8 * B_CS, 0);
#pragma unroll
      for (int r = 0; r < 2; r++) {
        const uint4 st = lds128(sb + OFF_XST + (rloc + 8 * r) * 16);
        st_rstd[r] = __uint_as_float(st.x); st_mr[r] = __uint_as_float(st.y); st_g[r] = __uint_as_float(st.z);
      }
      TSTAMP(19);
      wg_wait<0>();
      fence_regs(accM); fence_regs(accR);
      TSTAMP(3);
#define ACC(P_, G, I_) ((G) < 8 ? accM[(P_) * 32 + ((G) & 7) * 4 + (I_)] : accR[(P_) * 8 + ((G) & 1) * 4 + (I_)])
      {
        uint32_t hv[2][10];
        const GeluC g0 = gelu_consts(st_rstd[0], 1.f), g1 = gelu_consts(st_rstd[1], 1.f);
#pragma unroll
        for (int g = 0; g < 10; g++) {
          const float2 cs = *reinterpret_cast<const float2*>(s_cs + 8 * g + 2 * t);
          const float v0 = gelu_s(fmaf(st_mr[0], cs.x, ACC(0, g, 0)), g0), v1 = gelu_s(fmaf(st_mr[0], cs.y, ACC(0, g, 1)), g0);
          const float v2 = gelu_s(fmaf(st_mr[1], cs.x, ACC(0, g, 2)), g1), v3 = gelu_s(fmaf(st_mr[1], cs.y, ACC(0, g, 3)), g1);
          hv[0][g] = pack_bf16(v0, v1); hv[1][g] = pack_bf16(v2, v3);
        }
        bar_sync(1, 256);
        stage_tile(sb + OFF_STG, hv);
        fence_async_smem();
        signal(B_SIGH);
      }
      TSTAMP(4);
      uint32_t kf[5][4], qf[5][4];
#pragma unroll
      for (int s = 0; s < 5; s++) {
        kf[s][0] = pack_bf16(ACC(2, 2 * s, 0), ACC(2, 2 * s, 1)); kf[s][1] = pack_bf16(ACC(2, 2 * s, 2), ACC(2, 2 * s, 3));
        kf[s][2] = pack_bf16(ACC(2, 2 * s + 1, 0), ACC(2, 2 * s + 1, 1)); kf[s][3] = pack_bf16(ACC(2, 2 * s + 1, 2), ACC(2, 2 * s + 1, 3));
        qf[s][0] = pack_bf16(ACC(1, 2 * s, 0), ACC(1, 2 * s, 1)); qf[s][1] = pack_bf16(ACC(1, 2 * s, 2), ACC(1, 2 * s, 3));
        qf[s][2] = pack_bf16(ACC(1, 2 * s + 1, 0), ACC(1, 2 * s + 1, 1)); qf[s][3] = pack_bf16(ACC(1, 2 * s + 1, 2), ACC(1, 2 * s + 1, 3));
      }
      float pk[40], pq[40];
      wg_fence();
#pragma unroll
      for (int s = 0; s < 5; s++) {
        if (s == 0) mma_rs80_k_z(pk, kf[s], make_desc(sb16, OFF_MISC, 16, 256, 3));
        else mma_rs80_k(pk, kf[s], make_desc(sb16, OFF_MISC + s * 2560, 16, 256, 3));
      }
      wg_commit();
#pragma unroll
      for (int s = 0; s < 5; s++) {
        if (s == 0) mma_rs80_k_z(pq, qf[s], make_desc(sb16, OFF_MISC, 16, 256, 3));
        else mma_rs80_k(pq, qf[s], make_desc(sb16, OFF_MISC + s * 2560, 16, 256, 3));
      }
      wg_commit();
      {
        const int mat = lane >> 3;
        const int tok = warp * 16 + (mat & 1) * 8 + (lane & 7);
        const uint32_t ones = (t == 0) ? 0x00003f80u : 0u;
        __syncwarp();
#pragma unroll
        for (int p = 0; p < 2; p++) {
          const uint32_t rowa = sb + OFF_A + p * SLOT_A + tok * 128;
#pragma unroll
          for (int gg = 0; gg < 3; gg++) {
            const int g0 = 5 * p + 2 * gg;
            uint32_t r0 = pack_bf16(ACC(3, g0, 0), ACC(3, g0, 1)), r1 = pack_bf16(ACC(3, g0, 2), ACC(3, g0, 3));
            uint32_t r2 = ones, r3 = ones;
            if (gg < 2) { r2 = pack_bf16(ACC(3, g0 + 1, 0), ACC(3, g0 + 1, 1)); r3 = pack_bf16(ACC(3, g0 + 1, 2), ACC(3, g0 + 1, 3)); }
            stsm4(rowa + (((2 * gg + (mat >> 1)) ^ (tok & 7)) << 4), r0, r1, r2, r3);
          }
        }
      }
#undef ACC
      wg_wait<1>();
      fence_regs(pk);
#pragma unroll
      for (int G = 0; G < 10; G++) {
        P[0][G] = pack_bf16(pk[4 * G], pk[4 * G + 1]); P[1][G] = pack_bf16(pk[4 * G + 2], pk[4 * G + 3]);
      }
      wg_wait<0>();
      fence_regs(pq);
#pragma unroll
      for (int G = 0; G < 10; G++) {
        qp[0][G] = pack_bf16(pq[4 * G], pq[4 * G + 1]); qp[1][G] = pack_bf16(pq[4 * G + 2], pq[4 * G + 3]);
      }
    }

    uint32_t fr[10][4];
    int pass;
    pass = gridDim.y;
#pragma unroll 1
    do {
    feature_map(P, fr);
    if (pass != 0) {
    {
      const int mat = lane >> 3;
      const int tok = warp * 16 + (mat & 1) * 8 + (lane & 7);
      const uint32_t base = sb + OFF_B + tok * 32 + (((mat >> 1) ^ ((tok >> 2) & 1)) << 4);
#pragma unroll
      for (int G = 0; G < 10; G++) stsm4(base + G * 4096, fr[G][0], fr[G][1], fr[G][2], fr[G][3]);
      fence_async_smem();
      bar_sync(1, 256);
      float kv[40];
      const uint32_t va = sb16 + ((OFF_A + wg * SLOT_A) >> 4), vb = sb16 + ((OFF_B + wg * 20480) >> 4);
      wg_fence();
#pragma unroll
      for (int ks = 0; ks < 8; ks++) {
        if (ks == 0) mma_ss80_tt_z(kv, make_desc(va, 0, 16, 1024, 1), make_desc(vb, 0, 4096, 256, 3));
        else mma_ss80_tt(kv, make_desc(va, ks * 2048, 16, 1024, 1), make_desc(vb, ks * 512, 4096, 256, 3));
      }
      wg_commit();
      uint32_t xv[2][10];
      {
        mbar_wait(bars + 8 * B_XR, 0);
        const uint32_t xa = sb + OFF_B + (warp / 3) * SLOT_B + SPARE + (warp % 3) * 2560 + (lane >> 2) * 160 + t * 4;
#pragma unroll
        for (int g = 0; g < 10; g++) { xv[0][g] = lds32(xa + g * 16); xv[1][g] = lds32(xa + 1280 + g * 16); }
      }
      float acc[80];
      wg_wait<0>();
      release(emptyA); release(emptyA + 8); releaseB(emptyB); release(bars + 8 * B_PEER2);
      TSTAMP(5);
      mbar_wait(fullA + 8 * 2, 0);
      mbar_wait(fullB + 8 * 1, 1);
      TSTAMP(6);
      wg_fence();
#pragma unroll
      for (int kk = 0; kk < 4; kk++) {
        const uint64_t da = make_desc(sb16 + wg * 512, OFF_A + 2 * SLOT_A + kk * 32, 16, 1024, 1);
        const uint64_t db = make_desc(sb16, OFF_B + SLOT_B + kk * 1024, 4096, 512, 2);
        if (kk == 0) mma_ss160_z(acc, da, db); else mma_ss160(acc, da, db);
      }
      wg_commit();
      ra.next<NA>();
      wg_wait<1>();
      fence_regs(kv);
      TSTAMP(31);
      const uint32_t dst = sb + OFF_MISC + wg * (KV_PAIR * 4);
      const int m0 = (warp & 3) * 16 + (lane >> 2);
#pragma unroll
      for (int r = 0; r < 2; r++) {
        const int m = m0 + 8 * r;
        const bool hi = m >= 20;
        uint32_t v[10];
#pragma unroll
        for (int G = 0; G < 10; G++) v[G] = __float_as_uint(hi ? kv[4 * G + 2 * r + 1] : kv[4 * G + 2 * r]);
        const uint32_t p = dst + 4 * (m < 40 ? m * 48 + t * 12 : 1920 + t * 24 + 12);
        if (m <= 40) {
          sts128(p, make_uint4(v[0], v[1], v[2], v[3])); sts128(p + 16, make_uint4(v[4], v[5], v[6], v[7]));
          sts128(p + 32, make_uint4(v[8], v[9], 0u, 0u));
        }
      }
      if (m0 == 32) {
        const uint32_t p = dst + 4 * (1920 + t * 24);
        sts128(p, make_uint4(__float_as_uint(kv[2]), __float_as_uint(kv[6]), __float_as_uint(kv[10]), __float_as_uint(kv[14])));
        sts128(p + 16, make_uint4(__float_as_uint(kv[18]), __float_as_uint(kv[22]), __float_as_uint(kv[26]), __float_as_uint(kv[30])));
        sts128(p + 32, make_uint4(__float_as_uint(kv[34]), __float_as_uint(kv[38]), 0u, 0u));
      }
      signal(B_SIGKV);
      uint32_t pa = 2, pb = 1;
#pragma unroll 1
      for (int k = 1; k < 5; k++) {
        mbar_wait(fullA + 8 * ra.idx, ra.phase);
        if ((k & 1) == 0) mbar_wait(fullB + 8 * rb.idx, rb.phase);
        const uint32_t a0 = sb16 + ((OFF_A + ra.idx * SLOT_A + wg * 8192) >> 4);
        const uint32_t b0 = sb16 + ((OFF_B + rb.idx * SLOT_B + (k & 1) * 20480) >> 4);
        wg_fence();
#pragma unroll
        for (int kk = 0; kk < 4; kk++) {
          mma_ss160(acc, make_desc(a0, kk * 32, 16, 1024, 1), make_desc(b0, kk * 1024, 4096, 512, 2));
          if (kk == 0) {
            wg_commit();
            wg_wait<1>();
            release(emptyA + 8 * pa);
            if ((k & 1) == 0) releaseB(emptyB + 8 * pb);
          }
        }
        wg_commit();
        pa = ra.idx; pb = rb.idx;
        ra.next<NA>();
        if ((k & 1) || k == 4) rb.next<NB>();
      }
      mbar_wait(bars + 8 * B_PEER2, 0);
      wg_wait<0>();
      fence_regs(acc);
      release(emptyA + 8 * pa);
      TSTAMP(7);
      {
        uint32_t sn[20];
        if (rank) {
#pragma unroll
          for (int e = 0; e < 20; e++) sn[e] = pack_bf16(acc[2 * e], acc[2 * e + 1]);
#pragma unroll
          for (int e = 0; e < 40; e++) acc[e] = acc[40 + e];
        } else {
#pragma unroll
          for (int e = 0; e < 20; e++) sn[e] = pack_bf16(acc[40 + 2 * e], acc[41 + 2 * e]);
        }
        const uint32_t peer = map_peer(sb, rank ^ 1);
#pragma unroll
        for (int q = 0; q < 5; q++)
          st_async16(peer + OFF_B + 20480 + tid * 16 + q * 4096, sn[4 * q], sn[4 * q + 1], sn[4 * q + 2], sn[4 * q + 3],
                     peer + OFF_BAR + 8 * (B_DSR + 8 + wg));
#pragma unroll
        for (int g = 0; g < 10; g++) {
          acc[4 * g] += bf_lo(xv[0][g]); acc[4 * g + 1] += bf_hi(xv[0][g]);
          acc[4 * g + 2] += bf_lo(xv[1][g]); acc[4 * g + 3] += bf_hi(xv[1][g]);
        }
        bar_sync(1, 256);
        mbar_wait(bars + 8 * (B_DSR + 8 + wg), 0);
#pragma unroll
        for (int q = 0; q < 5; q++) {
          const uint4 v = lds128(sb + OFF_B + 20480 + tid * 16 + q * 4096);
          xv[0][2 * q] = pack_bf16(acc[8 * q] + bf_lo(v.x), acc[8 * q + 1] + bf_hi(v.x));
          xv[1][2 * q] = pack_bf16(acc[8 * q + 2] + bf_lo(v.y), acc[8 * q + 3] + bf_hi(v.y));
          xv[0][2 * q + 1] = pack_bf16(acc[8 * q + 4] + bf_lo(v.z), acc[8 * q + 5] + bf_hi(v.z));
          xv[1][2 * q + 1] = pack_bf16(acc[8 * q + 6] + bf_lo(v.w), acc[8 * q + 7] + bf_hi(v.w));
        }
        releaseB(emptyB + 8 * pb);
      }
      TSTAMP(16);
      stage_tile(sb + OFF_STG, xv);
      fence_async_smem();
      signal(B_SIGX1);
      TSTAMP(17);
#pragma unroll
      for (int r = 0; r < 2; r++) {
        float s = 0.f;
#pragma unroll
        for (int g = 0; g < 10; g++) {
          acc[4 * g + 2 * r] = bf_lo(xv[r][g]); acc[4 * g + 2 * r + 1] = bf_hi(xv[r][g]);
          s += acc[4 * g + 2 * r] + acc[4 * g + 2 * r + 1];
        }
        s += __shfl_xor_sync(0xffffffffu, s, 1); s += __shfl_xor_sync(0xffffffffu, s, 2);
        const float mu = s * (1.f / 80.f);
        float q = 0.f;
#pragma unroll
        for (int g = 0; g < 10; g++) {
          const float d0 = acc[4 * g + 2 * r] - mu, d1 = acc[4 * g + 2 * r + 1] - mu;
          q = fmaf(d0, d0, q); q = fmaf(d1, d1, q);
        }
        q += __shfl_xor_sync(0xffffffffu, q, 1); q += __shfl_xor_sync(0xffffffffu, q, 2);
        if (t == 0) g_st1[(128 * i + rloc + 8 * r) * 8 + j] = make_float2(mu, q);
      }
    }
    TSTAMP(8);
#pragma unroll
    for (int G = 0; G < 10; G++) { P[0][G] = qp[0][G]; P[1][G] = qp[1][G]; }
    }
    asm volatile("" : "+r"(pass));
    } while (pass-- != 0);

    uint32_t of[5][4];
    {
      mbar_wait(bars + 8 * B_KV, 0);
      uint4 kvr[2][3];
#pragma unroll
      for (int u = 0; u < 2; u++) {
        const int it = tid + 256 * u, p = it / 192, rem = it - 192 * p, n = rem >> 2, tq = rem & 3;
        const uint32_t sp = sb + OFF_MISC + 4 * (p * KV_PAIR + (n < 40 ? n * 48 + tq * 12 : 1920 + tq * 24 + (n & 1) * 12));
        if (it < 384) { kvr[u][0] = lds128(sp); kvr[u][1] = lds128(sp + 16); kvr[u][2] = lds128(sp + 32); }
      }
      bar_sync(1, 256);
#pragma unroll
      for (int u = 0; u < 2; u++) {
        const int it = tid + 256 * u, p = it / 192, rem = it - 192 * p, n = rem >> 2, tq = rem & 3;
        const int sh = (n < 40 ? (n >= 20) : (n & 1)) * 16;
        const uint32_t v[10] = {kvr[u][0].x, kvr[u][0].y, kvr[u][0].z, kvr[u][0].w, kvr[u][1].x, kvr[u][1].y, kvr[u][1].z, kvr[u][1].w, kvr[u][2].x, kvr[u][2].y};
        uint8_t* dst = sgen + OFF_MISC + p * 7680 + n * 32 + tq * 4;
        const int sw = ((n >> 2) & 1) << 4;
        if (it < 384) {
#pragma unroll
          for (int G = 0; G < 10; G++)
            *reinterpret_cast<uint32_t*>(dst + (G >> 1) * 1536 + (((G & 1) << 4) ^ sw)) = pack_bf16(__uint_as_float(v[G]), 0.f) << sh;
        }
      }
      fence_async_smem();
      bar_sync(1, 256);
      float o0[24], o1[24];
      wg_fence();
#pragma unroll
      for (int g = 0; g < 5; g++) {
        if (g == 0) mma_rs48_k_z(o0, fr[g], make_desc(sb16, OFF_MISC, 16, 256, 3));
        else mma_rs48_k(o0, fr[g], make_desc(sb16, OFF_MISC + g * 1536, 16, 256, 3));
      }
#pragma unroll
      for (int g = 0; g < 5; g++) {
        if (g == 0) mma_rs48_k_z(o1, fr[5], make_desc(sb16, OFF_MISC + 7680, 16, 256, 3));
        else mma_rs48_k(o1, fr[5 + g], make_desc(sb16, OFF_MISC + 7680 + g * 1536, 16, 256, 3));
      }
      wg_commit();
      wg_wait<0>();
      fence_regs(o0); fence_regs(o1);
      signal(B_MFREE);
#pragma unroll
      for (int r = 0; r < 2; r++) {
        const float a0 = __fdividef(st_g[r], o0[20 + 2 * r] + 1e-6f), a1 = __fdividef(st_g[r], o0[21 + 2 * r] + 1e-6f);
        const float b0 = __fdividef(st_g[r], o1[20 + 2 * r] + 1e-6f), b1 = __fdividef(st_g[r], o1[21 + 2 * r] + 1e-6f);
        const float am = t < 2 ? a0 : a1, bm = t < 2 ? b0 : b1;
#pragma unroll
        for (int g = 0; g < 5; g++) {
          const float sa = g < 2 ? a0 : (g == 2 ? am : a1), sb2 = g < 2 ? b0 : (g == 2 ? bm : b1);
          of[g >> 1][(g & 1) * 2 + r] = pack_bf16(o0[4 * g + 2 * r] * sa, o0[4 * g + 2 * r + 1] * sa);
          of[(5 + g) >> 1][((5 + g) & 1) * 2 + r] = pack_bf16(o1[4 * g + 2 * r] * sb2, o1[4 * g + 2 * r + 1] * sb2);
        }
      }
    }
    TSTAMP(9);

    uint32_t hf[12][4];
    float ac4[80];
    auto unit = [&](auto uc, uint32_t b0) {
      constexpr int u = decltype(uc)::value;
#pragma unroll
      for (int s = 0; s < (u ? 4 : 5); s++) {
        const uint64_t db = make_desc(b0, (u ? 5120 + 20480 * u : 0) + s * 1024, u ? 4096 : 5120, 512, 2);
        if (u == 0 && s == 0) mma_rs160_n_z(ac4, of[0], db);
        else if (u == 0) mma_rs160_n(ac4, of[s], db);
        else mma_rs160_n(ac4, hf[(4 * u + 8 + s) % 12], db);
      }
      wg_commit();
    };
    {
      float acc[96];
      uint32_t pa = 0, pb = 0;
#pragma unroll 1
      for (int k = 0; k < 10; k++) {
        mbar_wait(fullA + 8 * ra.idx, ra.phase);
        if (tid == 0) TRACE(52 + k);
        if ((k & 1) == 0) mbar_wait(fullB + 8 * rb.idx, rb.phase);
        if (tid == 0) TRACE(84 + k);
        if (k == 0) TSTAMP(10);
        const uint32_t a0 = sb16 + ((OFF_A + ra.idx * SLOT_A + wg * 8192) >> 4);
        const uint32_t b0 = sb16 + ((OFF_B + rb.idx * SLOT_B + (k & 1) * 24576) >> 4);
        wg_fence();
#pragma unroll
        for (int kk = 0; kk < 4; kk++) {
          if (kk == 0) mma_ss192_p(acc, make_desc(a0, 0, 16, 1024, 1), make_desc(b0, 0, 8192, 1024, 1), k);
          else mma_ss192(acc, make_desc(a0, kk * 32, 16, 1024, 1), make_desc(b0, kk * 2048, 8192, 1024, 1));
          if (kk == 0) {
            wg_commit();
            if (k > 0) {
              wg_wait<1>();
              release(emptyA + 8 * pa);
              if ((k & 1) == 0) releaseB(emptyB + 8 * pb);
            }
          }
        }
        wg_commit();
        pa = ra.idx; pb = rb.idx;
        ra.next<NA>();
        if (k & 1) rb.next<NB>();
      }
      float rs[2], mm[2];
      mbar_wait(bars + 8 * B_ST1, 0);
#pragma unroll
      for (int r = 0; r < 2; r++) {
        const uint4 su = lds128(sb + OFF_MISC + (rloc + 8 * r) * 64 + t * 16);
        const float m0 = __uint_as_float(su.x), m1 = __uint_as_float(su.z);
        float mu = m0 + m1;
        mu += __shfl_xor_sync(0xffffffffu, mu, 1); mu += __shfl_xor_sync(0xffffffffu, mu, 2);
        mu *= 0.125f;
        const float d0 = m0 - mu, d1 = m1 - mu;
        float q = __uint_as_float(su.y) + __uint_as_float(su.w) + 80.f * (d0 * d0 + d1 * d1);
        q += __shfl_xor_sync(0xffffffffu, q, 1); q += __shfl_xor_sync(0xffffffffu, q, 2);
        rs[r] = rsqrtf(q * (1.f / D_) + 1e-5f);
        mm[r] = -mu;
      }
      mbar_wait(bars + 8 * B_FULL4, 0);
      wg_fence();
      unit(IntC<0>{}, sb16);
      wg_wait<1>();
      fence_regs(acc);
      releaseB(emptyB + 8 * pb);
      release(bars + 8 * B_PEER);
      TSTAMP(11);
      const GeluC g0 = gelu_consts(rs[0], 1.f - st_g[0]), g1 = gelu_consts(rs[1], 1.f - st_g[1]);
#pragma unroll
      for (int g = 0; g < 24; g++) {
        const float2 cs = *reinterpret_cast<const float2*>(s_cs + 80 + 8 * g + 2 * t);
        const float v0 = gelu_s(fmaf(mm[0], cs.x, acc[4 * g]), g0), v1 = gelu_s(fmaf(mm[0], cs.y, acc[4 * g + 1]), g0);
        const float v2 = gelu_s(fmaf(mm[1], cs.x, acc[4 * g + 2]), g1), v3 = gelu_s(fmaf(mm[1], cs.y, acc[4 * g + 3]), g1);
        hf[g >> 1][(g & 1) * 2] = pack_bf16(v0, v1);
        hf[g >> 1][(g & 1) * 2 + 1] = pack_bf16(v2, v3);
        if (g == 7) { wg_fence(); unit(IntC<1>{}, sb16); }
        if (g == 15) { mbar_wait(bars + 8 * (B_FULL4 + 1), 0); wg_fence(); unit(IntC<2>{}, sb16); }
        if (g == 23) { wg_wait<1>(); signal(B_EMPTY4); wg_fence(); unit(IntC<3>{}, sb16); }
      }
    }
    TSTAMP(12);

    {
      float kp[40];
      uint32_t sn[20], kb[20];
      const uint32_t peer = map_peer(sb, rank ^ 1);
      const uint32_t tag = lds32(sb + OFF_BAR + 8 * NBAR);
      auto add8 = [&](int q, const uint4 v) {
        float* d = &kp[8 * q];
        d[0] += bf_lo(v.x); d[1] += bf_hi(v.x); d[2] += bf_lo(v.y); d[3] += bf_hi(v.y);
        d[4] += bf_lo(v.z); d[5] += bf_hi(v.z); d[6] += bf_lo(v.w); d[7] += bf_hi(v.w);
      };
      auto send = [&](int c) {
        const uint32_t dso = peer + OFF_DS + (c & 1) * 20480 + tid * 16, dsb = peer + OFF_BAR + 8 * (B_DSR + 2 * c + wg);
#pragma unroll
        for (int q = 0; q < 5; q++) st_async16(dso + q * 4096, sn[4 * q], sn[4 * q + 1], sn[4 * q + 2], sn[4 * q + 3], dsb);
      };
      mbar_wait(bars + 8 * B_PEER, 0);
      uint4* gdst = g_part + (size_t)i * 8 * 3840 + tid;
#pragma unroll 1
      for (int c = 0; c < 3; c++) {
        const uint32_t b0 = sb16 + ((c & 1) ? 0 : SET4 >> 4), bc = bars + 16 * c;
        mbar_wait(bc + 8 * (B_FULL4 + 2), 0);
        wg_wait<0>();
        fence_regs(ac4);
        if (rank) {
#pragma unroll
          for (int e = 0; e < 20; e++) { sn[e] = pack_bf16(ac4[2 * e], ac4[2 * e + 1]); kb[e] = pack_bf16(ac4[40 + 2 * e], ac4[41 + 2 * e]); }
        } else {
#pragma unroll
          for (int e = 0; e < 20; e++) { kb[e] = pack_bf16(ac4[2 * e], ac4[2 * e + 1]); sn[e] = pack_bf16(ac4[40 + 2 * e], ac4[41 + 2 * e]); }
        }
#pragma unroll
        for (int e = 0; e < 20; e++) asm volatile("" : "+r"(sn[e]), "+r"(kb[e]));
        if (c == 0 && wg == 1) bar_sync(2, 256);
        wg_fence();
        unit(IntC<0>{}, b0);
        if (lane == 0) mbar_arrive(bc + 8 * (B_EMPTY4 + 1));
        send(c);
        unit(IntC<1>{}, b0);
        if (c == 0 && wg == 0) bar_arrive(2, 256);
        {
          mbar_wait(bc + 8 * (B_DSR + wg), 0);
          uint4* dst = gdst + (((j + 2 * c + 2) & 7) * 3 + c) * 1280;
#pragma unroll
          for (int q = 0; q < 5; q++) {
            const uint4 v = lds128(sb + OFF_DS + (c & 1) * 20480 + tid * 16 + q * 4096);
            st_relaxed16(dst + q * 256, (add_bf2(v.x, kb[4 * q]) & ~1u) | tag, add_bf2(v.y, kb[4 * q + 1]),
                         add_bf2(v.z, kb[4 * q + 2]), add_bf2(v.w, kb[4 * q + 3]));
          }
        }
        mbar_wait(bc + 8 * (B_FULL4 + 3), 0);
        wg_fence();
        unit(IntC<2>{}, b0);
        wg_wait<1>();
        if (lane == 0) mbar_arrive(bc + 8 * (B_EMPTY4 + 2));
        unit(IntC<3>{}, b0);
      }
      auto partial = [&](int c, uint4 (&v)[5]) {
        mbar_wait(bars + 8 * (B_RDY + c), 0);
        uint32_t bad = 0;
#pragma unroll
        for (int q = 0; q < 5; q++) { v[q] = lds128(sb + (c ? 25600 + 20480 * c : 0) + tid * 16 + q * 4096); bad |= v[q].x ^ tag; }
#pragma unroll 1
        for (uint32_t n = 0; (bad & 1u) && n < (WAIT_LIMIT >> 2); n++) {
          bad = 0;
#pragma unroll
          for (int q = 0; q < 5; q++) { v[q] = ld_relaxed16(gdst + (j * 3 + c) * 1280 + q * 256); bad |= v[q].x ^ tag; }
        }
      };
      uint4 pa4[5], pb4[5];
      partial(0, pa4);
      wg_wait<0>();
      fence_regs(ac4);
      if (rank) {
#pragma unroll
        for (int e = 0; e < 20; e++) sn[e] = pack_bf16(ac4[2 * e], ac4[2 * e + 1]);
#pragma unroll
        for (int e = 0; e < 40; e++) kp[e] = ac4[40 + e];
      } else {
#pragma unroll
        for (int e = 0; e < 20; e++) sn[e] = pack_bf16(ac4[40 + 2 * e], ac4[41 + 2 * e]);
#pragma unroll
        for (int e = 0; e < 40; e++) kp[e] = ac4[e];
      }
      send(3);
      TSTAMP(13);
      {
        mbar_wait(bars + 8 * B_XR, 1);
        const float w0 = 1.f - st_g[0], w1s = 1.f - st_g[1];
        const uint32_t xa = sb + OFF_OUT + rloc * 160 + t * 4;
#pragma unroll
        for (int g = 0; g < 10; g++) {
          const uint32_t x0 = lds32(xa + g * 16), x1 = lds32(xa + 1280 + g * 16);
          kp[4 * g] = fmaf(w0, bf_lo(x0), kp[4 * g]); kp[4 * g + 1] = fmaf(w0, bf_hi(x0), kp[4 * g + 1]);
          kp[4 * g + 2] = fmaf(w1s, bf_lo(x1), kp[4 * g + 2]); kp[4 * g + 3] = fmaf(w1s, bf_hi(x1), kp[4 * g + 3]);
        }
      }
      partial(1, pb4);
#pragma unroll
      for (int q = 0; q < 5; q++)
        pa4[q] = make_uint4(add_bf2(pa4[q].x, pb4[q].x), add_bf2(pa4[q].y, pb4[q].y), add_bf2(pa4[q].z, pb4[q].z), add_bf2(pa4[q].w, pb4[q].w));
#pragma unroll
      for (int q = 0; q < 5; q++) add8(q, pa4[q]);
      partial(2, pb4);
      mbar_wait(bars + 8 * (B_DSR + 6 + wg), 0);
      TSTAMP(14);
#pragma unroll
      for (int q = 0; q < 5; q++) {
        const uint4 c = pb4[q], d = lds128(sb + OFF_DS + 20480 + tid * 16 + q * 4096);
        add8(q, make_uint4(add_bf2(c.x, d.x), add_bf2(c.y, d.y), add_bf2(c.z, d.z), add_bf2(c.w, d.w)));
      }
      __syncwarp();
      uint32_t ov[2][10];
#pragma unroll
      for (int g = 0; g < 10; g++) { ov[0][g] = pack_bf16(kp[4 * g], kp[4 * g + 1]); ov[1][g] = pack_bf16(kp[4 * g + 2], kp[4 * g + 3]); }
      stage_tile(sb + OFF_OUT, ov);
      __syncwarp();
      __nv_bfloat16* dst = out + (size_t)(128 * i + 16 * warp) * D_ + 80 * j;
#pragma unroll
      for (int q = 0; q < 5; q++) {
        const int id = q * 32 + lane, r = id / 10;
        *reinterpret_cast<uint4*>(dst + r * (D_ - 80) + id * 8) = lds128(sb + OFF_OUT + warp * 2560 + id * 16);
      }
    }
    TSTAMP(15);
    if (tid == 0) asm volatile("red.relaxed.gpu.global.add.u32 [%0], 1;" ::"l"(g_flags + FL_DONE * 32) : "memory");
  }
}

namespace {
typedef CUresult (*EncodeFn)(CUtensorMap*, CUtensorMapDataType, cuuint32_t, void*, const cuuint64_t*, const cuuint64_t*,
                             const cuuint32_t*, const cuuint32_t*, CUtensorMapInterleave, CUtensorMapSwizzle,
                             CUtensorMapL2promotion, CUtensorMapFloatOOBfill);

void encode(EncodeFn fn, CUtensorMap* m, const void* ptr, int rank, const cuuint64_t* dims, const cuuint64_t* strides,
            const cuuint32_t* box, CUtensorMapSwizzle swz) {
  cuuint32_t es[5] = {1, 1, 1, 1, 1};
  fn(m, CU_TENSOR_MAP_DATA_TYPE_BFLOAT16, rank, const_cast<void*>(ptr), dims, strides, box, es, CU_TENSOR_MAP_INTERLEAVE_NONE,
     swz, CU_TENSOR_MAP_L2_PROMOTION_L2_128B, CU_TENSOR_MAP_FLOAT_OOB_FILL_NONE);
}
}

extern "C" void kernel_launch(void* const* d_in, const int* in_sizes, int n_in, void* d_out, int out_size) {
  (void)in_sizes; (void)n_in; (void)out_size;
  const __nv_bfloat16* x = (const __nv_bfloat16*)d_in[0];
  const __nv_bfloat16* wqkv = (const __nv_bfloat16*)d_in[1];
  const __nv_bfloat16* wphi = (const __nv_bfloat16*)d_in[2];
  const __nv_bfloat16* wo = (const __nv_bfloat16*)d_in[3];
  const __nv_bfloat16* w1 = (const __nv_bfloat16*)d_in[5];
  const __nv_bfloat16* w2 = (const __nv_bfloat16*)d_in[6];
  const __nv_bfloat16* w3 = (const __nv_bfloat16*)d_in[7];
  const __nv_bfloat16* w4 = (const __nv_bfloat16*)d_in[8];
  const __nv_bfloat16* gate_w = (const __nv_bfloat16*)d_in[9];

  static EncodeFn enc = nullptr;
  static void *pHs = nullptr, *pX1 = nullptr;
  if (!enc) {
    cudaDriverEntryPointQueryResult qr;
    cudaGetDriverEntryPoint("cuTensorMapEncodeTiled", (void**)&enc, cudaEnableDefault, &qr);
    cudaGetSymbolAddress(&pHs, g_Hs);
    cudaGetSymbolAddress(&pX1, g_X1);
    cudaFuncSetAttribute(fused_kernel, cudaFuncAttributeMaxDynamicSharedMemorySize, SMEM_BYTES);
  }
  Maps m;
  {
    cuuint64_t dims[2] = {D_, S_}, str[1] = {D_ * 2};
    cuuint32_t box[2] = {64, 128}, boxh[2] = {64, 64};
    encode(enc, &m.x, x, 2, dims, str, boxh, CU_TENSOR_MAP_SWIZZLE_128B);
    encode(enc, &m.hs, (const char*)pHs + 2 * D_ * 2, 2, dims, str, box, CU_TENSOR_MAP_SWIZZLE_128B);
    encode(enc, &m.x1, pX1, 2, dims, str, boxh, CU_TENSOR_MAP_SWIZZLE_128B);
    cuuint32_t boxr[2] = {80, 16}, boxs[2] = {80, 128};
    cuuint64_t dimsp[2] = {D_, S_ + 4};
    encode(enc, &m.st_h, pHs, 2, dimsp, str, boxs, CU_TENSOR_MAP_SWIZZLE_NONE);
    encode(enc, &m.st_x1, pX1, 2, dims, str, boxs, CU_TENSOR_MAP_SWIZZLE_NONE);
    encode(enc, &m.xr, x, 2, dims, str, boxr, CU_TENSOR_MAP_SWIZZLE_NONE);
  }
  {
    cuuint64_t dims[3] = {80, D_, 8}, str[2] = {D_ * 2, 160};
    cuuint32_t boxm[3] = {64, 64, 1}, boxr[3] = {16, 64, 1};
    encode(enc, &m.w1m, w1, 3, dims, str, boxm, CU_TENSOR_MAP_SWIZZLE_128B);
    encode(enc, &m.w1r, w1, 3, dims, str, boxr, CU_TENSOR_MAP_SWIZZLE_32B);
  }
  {
    cuuint64_t dims[4] = {80, D_, 3, 8}, str[3] = {3 * D_ * 2, D_ * 2, 160};
    cuuint32_t boxm[4] = {64, 64, 3, 1}, boxr[4] = {16, 64, 3, 1};
    encode(enc, &m.qm, wqkv, 4, dims, str, boxm, CU_TENSOR_MAP_SWIZZLE_128B);
    encode(enc, &m.qr, wqkv, 4, dims, str, boxr, CU_TENSOR_MAP_SWIZZLE_32B);
  }
  {
    cuuint64_t dims[3] = {32, D_, 20}, dims4[3] = {32, F_, 20}, str[2] = {D_ * 2, 64};
    cuuint32_t box4[3] = {32, 64, 5}, boxo[3] = {32, 80, 5};
    encode(enc, &m.w4, w4, 3, dims4, str, box4, CU_TENSOR_MAP_SWIZZLE_64B);
    encode(enc, &m.wo, wo, 3, dims, str, boxo, CU_TENSOR_MAP_SWIZZLE_64B);
    encode(enc, &m.w2, w2, 3, dims, str, box4, CU_TENSOR_MAP_SWIZZLE_64B);
  }
  {
    cuuint64_t dims[3] = {64, D_, 24}, str[2] = {F_ * 2, 128};
    cuuint32_t box[3] = {64, 64, 3};
    encode(enc, &m.w3, w3, 3, dims, str, box, CU_TENSOR_MAP_SWIZZLE_128B);
  }
  fused_kernel<<<NCTA + NSVC, 384, SMEM_BYTES, cudaStreamPerThread>>>(m, x, wqkv, wphi, w1, w2, w3, w4, wo, gate_w, (__nv_bfloat16*)d_out);
}
```

```cpp
#include <cuda_runtime.h>
#include <cuda_bf16.h>
#include <cuda.h>
#include <stdint.h>

namespace {

constexpr int S_ = 2048, D_ = 640, F_ = 1536;
constexpr int NCTA = 128, NSVC = 4;
constexpr int KV_PAIR = 40 * 48 + 96;
constexpr int KV_J = 2 * KV_PAIR;

constexpr int SLOT_B = 49152, NB = 3;
constexpr int SLOT_A = 16384, NA = 4;
constexpr int OFF_B = 0;
constexpr int OFF_A = OFF_B + NB * SLOT_B;
constexpr int OFF_STG = OFF_A + 2 * SLOT_A;
constexpr int OFF_MISC = OFF_A + NA * SLOT_A;
constexpr int OFF_XST = OFF_MISC + 13312;
constexpr int OFF_CS = OFF_MISC + 16384;
constexpr int OFF_BAR = OFF_CS + 1088;
constexpr int SMEM_BYTES = OFF_BAR + 512 + 512 + 128;
constexpr int B_FULLA = 0, B_FULLB = 4, B_CS = 7, B_XR = 8, B_KV = 9, B_ST1 = 10, B_HST = 11, B_FULL4 = 12  , B_RDY = 20  ,
              B_DSR = 23  , B_EMPTYB = 33  , B_SIGP = 36, B_SIGH = 37, B_SIGKV = 38, B_SIGX1 = 39, B_MFREE = 40,
              B_EMPTY4 = 41  , B_EMPTYA = 49  , B_PEER = 53, B_PEER2 = 54, B_X1P = 55  , NBAR = 56;
constexpr int SPARE = 40960;
constexpr int SET4 = 87040, OFF_DS = 2 * SET4, OFF_OUT = 20480;

constexpr int FL_DONE = 0, FL_H = 1  , FL_X1 = FL_H + 32, FL_KV = FL_X1 + 16, FL_CS = FL_KV + 8, FL_CS3 = FL_CS + 1, FL_ST = FL_CS3 + 1;
constexpr int FL_S1 = FL_ST + 16, FL_COUNT = FL_S1 + 16;

struct Maps {
  CUtensorMap x, w1m, w1r, qm, qr, hs, w2, x1, w3, w4, wo, xr, st_h, st_x1;
};

}

__device__ __align__(1024) __nv_bfloat16 g_Hs[(S_ + 4) * D_];
__device__ __align__(1024) __nv_bfloat16 g_X1[S_ * D_];
__device__ __align__(128) float g_acc[2][8 * KV_J];
__device__ __align__(128) float g_cs[2][D_ + F_];
__device__ __align__(128) uint4 g_wphi[8 * 800];
__device__ __align__(128) float4 g_xstat[S_];
__device__ __align__(128) float2 g_st1[S_ * 8];
__device__ __align__(128) uint4 g_part[16 * 8 * 3 * 1280];
__device__ __align__(128) unsigned g_flags[FL_COUNT * 32];
#define TSTAMP(n) do {} while (0)
#define TSTAMPX(n) do {} while (0)
#define TRACE(n) do {} while (0)
#define TRS(n) do {} while (0)

namespace {

__device__ __forceinline__ long long gtime() { long long t; asm volatile("mov.u64 %0, %%globaltimer;" : "=l"(t)); return t; }
__device__ __forceinline__ uint32_t smem_u32(const void* p) { return (uint32_t)__cvta_generic_to_shared(p); }
__device__ __forceinline__ void mbar_init(uint32_t bar, int cnt) {
  asm volatile("mbarrier.init.shared::cta.b64 [%0], %1;" ::"r"(bar), "r"(cnt) : "memory");
}
__device__ __forceinline__ void mbar_expect_tx(uint32_t bar, int bytes) {
  asm volatile("mbarrier.arrive.expect_tx.shared::cta.b64 _, [%0], %1;" ::"r"(bar), "r"(bytes) : "memory");
}
__device__ __forceinline__ void mbar_arrive_cta(uint32_t bar, uint32_t cta) {
  asm volatile("{\n.reg .b32 ra;\nmapa.shared::cluster.u32 ra, %0, %1;\nmbarrier.arrive.shared::cluster.b64 _, [ra];\n}"
               ::"r"(bar), "r"(cta) : "memory");
}
__device__ __forceinline__ uint32_t mbar_try(uint32_t bar, uint32_t parity) {
  uint32_t ok;
  asm volatile("{\n.reg .pred p;\nmbarrier.try_wait.parity.shared::cta.b64 p, [%1], %2;\nselp.u32 %0, 1, 0, p;\n}"
               : "=r"(ok) : "r"(bar), "r"(parity) : "memory");
  return ok;
}
constexpr uint32_t WAIT_LIMIT = 1u << 18;
__device__ __forceinline__ void mbar_wait(uint32_t bar, uint32_t parity) {
  uint32_t n = 0;
  while (!mbar_try(bar, parity) && ++n < WAIT_LIMIT) {}
}
__device__ __forceinline__ unsigned ld_acquire(const unsigned* p) {
  unsigned v;
  asm volatile("ld.acquire.gpu.global.u32 %0, [%1];" : "=r"(v) : "l"(p) : "memory");
  return v;
}
__device__ __forceinline__ void flag_wait(int idx, unsigned target) {
  const unsigned* p = g_flags + idx * 32;
  uint32_t n = 0;
  while ((int)(ld_acquire(p) - target) < 0 && ++n < (WAIT_LIMIT >> 2)) {}
}
__device__ __forceinline__ void flag_add(int idx) {
  asm volatile("red.release.gpu.global.add.u32 [%0], 1;" ::"l"(g_flags + idx * 32) : "memory");
}
__device__ __forceinline__ void flag_add_relaxed(int idx) {
  asm volatile("red.relaxed.gpu.global.add.u32 [%0], 1;" ::"l"(g_flags + idx * 32) : "memory");
}
__device__ __forceinline__ uint32_t mbar_test(uint32_t bar, uint32_t parity) {
  uint32_t ok;
  asm volatile("{\n.reg .pred p;\nmbarrier.test_wait.parity.shared::cta.b64 p, [%1], %2;\nselp.u32 %0, 1, 0, p;\n}"
               : "=r"(ok) : "r"(bar), "r"(parity) : "memory");
  return ok;
}
__device__ __forceinline__ uint32_t lds32(uint32_t a) {
  uint32_t v;
  asm volatile("ld.shared.u32 %0, [%1];" : "=r"(v) : "r"(a) : "memory");
  return v;
}
__device__ __forceinline__ void mbar_arrive(uint32_t bar) {
  asm volatile("mbarrier.arrive.shared::cta.b64 _, [%0];" ::"r"(bar) : "memory");
}
__device__ __forceinline__ void fence_async_glb() { asm volatile("fence.proxy.async.global;" ::: "memory"); }
__device__ __forceinline__ void fence_async_smem() { asm volatile("fence.proxy.async.shared::cta;" ::: "memory"); }
__device__ __forceinline__ void bar_sync(int id, int n) { asm volatile("bar.sync %0, %1;" ::"r"(id), "r"(n) : "memory"); }

__device__ __forceinline__ void tma2d(uint32_t dst, const CUtensorMap* m, uint32_t bar, int c0, int c1) {
  asm volatile("cp.async.bulk.tensor.2d.shared::cluster.global.mbarrier::complete_tx::bytes [%0], [%1, {%3, %4}], [%2];"
               ::"r"(dst), "l"(m), "r"(bar), "r"(c0), "r"(c1) : "memory");
}
__device__ __forceinline__ void tma2d_mc(uint32_t dst, const CUtensorMap* m, uint32_t bar, int c0, int c1) {
  asm volatile("cp.async.bulk.tensor.2d.shared::cluster.global.mbarrier::complete_tx::bytes.multicast::cluster"
               " [%0], [%1, {%3, %4}], [%2], %5;"
               ::"r"(dst), "l"(m), "r"(bar), "r"(c0), "r"(c1), "h"((uint16_t)3) : "memory");
}
__device__ __forceinline__ void tma3d(uint32_t dst, const CUtensorMap* m, uint32_t bar, int c0, int c1, int c2) {
  asm volatile("cp.async.bulk.tensor.3d.shared::cluster.global.mbarrier::complete_tx::bytes [%0], [%1, {%3, %4, %5}], [%2];"
               ::"r"(dst), "l"(m), "r"(bar), "r"(c0), "r"(c1), "r"(c2) : "memory");
}
__device__ __forceinline__ void tma4d(uint32_t dst, const CUtensorMap* m, uint32_t bar, int c0, int c1, int c2, int c3) {
  asm volatile("cp.async.bulk.tensor.4d.shared::cluster.global.mbarrier::complete_tx::bytes [%0], [%1, {%3, %4, %5, %6}], [%2];"
               ::"r"(dst), "l"(m), "r"(bar), "r"(c0), "r"(c1), "r"(c2), "r"(c3) : "memory");
}
__device__ __forceinline__ void tma2d_store(const CUtensorMap* m, uint32_t src, int c0, int c1) {
  asm volatile("cp.async.bulk.tensor.2d.global.shared::cta.bulk_group [%0, {%2, %3}], [%1];"
               ::"l"(m), "r"(src), "r"(c0), "r"(c1) : "memory");
}
__device__ __forceinline__ void bulk_store(void* dst, uint32_t src, uint32_t bytes) {
  asm volatile("cp.async.bulk.global.shared::cta.bulk_group [%0], [%1], %2;" ::"l"(dst), "r"(src), "r"(bytes) : "memory");
}
__device__ __forceinline__ void bulk_load(uint32_t dst, const void* src, uint32_t bytes, uint32_t bar) {
  asm volatile("cp.async.bulk.shared::cluster.global.mbarrier::complete_tx::bytes [%0], [%1], %2, [%3];"
               ::"r"(dst), "l"(src), "r"(bytes), "r"(bar) : "memory");
}
__device__ __forceinline__ void bulk_commit() { asm volatile("cp.async.bulk.commit_group;" ::: "memory"); }
template <int N> __device__ __forceinline__ void bulk_wait() { asm volatile("cp.async.bulk.wait_group %0;" ::"n"(N) : "memory"); }
__device__ __forceinline__ void bulk_wait_read() { asm volatile("cp.async.bulk.wait_group.read 0;" ::: "memory"); }
__device__ __forceinline__ void bar_arrive(int id, int n) { asm volatile("bar.arrive %0, %1;" ::"r"(id), "r"(n) : "memory"); }
__device__ __forceinline__ uint4 lds128(uint32_t a) {
  uint4 v;
  asm volatile("ld.shared.v4.u32 {%0, %1, %2, %3}, [%4];" : "=r"(v.x), "=r"(v.y), "=r"(v.z), "=r"(v.w) : "r"(a) : "memory");
  return v;
}
__device__ __forceinline__ void sts128(uint32_t a, uint4 v) {
  asm volatile("st.shared.v4.u32 [%0], {%1, %2, %3, %4};" ::"r"(a), "r"(v.x), "r"(v.y), "r"(v.z), "r"(v.w) : "memory");
}
__device__ __forceinline__ uint4 ld_relaxed16(const uint4* p) {
  uint4 v;
  asm volatile("ld.relaxed.gpu.global.v4.u32 {%0, %1, %2, %3}, [%4];" : "=r"(v.x), "=r"(v.y), "=r"(v.z), "=r"(v.w) : "l"(p) : "memory");
  return v;
}
__device__ __forceinline__ void st_relaxed16(uint4* p, uint32_t a, uint32_t b, uint32_t c, uint32_t d) {
  asm volatile("st.relaxed.gpu.global.v4.u32 [%0], {%1, %2, %3, %4};" ::"l"(p), "r"(a), "r"(b), "r"(c), "r"(d) : "memory");
}
__device__ __forceinline__ uint32_t map_peer(uint32_t addr, uint32_t cta) {
  uint32_t r;
  asm("mapa.shared::cluster.u32 %0, %1, %2;" : "=r"(r) : "r"(addr), "r"(cta));
  return r;
}
__device__ __forceinline__ void st_async16(uint32_t addr, uint32_t a, uint32_t b, uint32_t c, uint32_t d, uint32_t bar) {
  asm volatile("st.async.weak.shared::cluster.mbarrier::complete_tx::bytes.v4.b32 [%0], {%1, %2, %3, %4}, [%5];"
               ::"r"(addr), "r"(a), "r"(b), "r"(c), "r"(d), "r"(bar) : "memory");
}
__device__ __forceinline__ void l2_prefetch(const void* p, uint32_t bytes) {
  asm volatile("cp.async.bulk.prefetch.L2.global [%0], %1;" ::"l"(p), "r"(bytes) : "memory");
}
__device__ __forceinline__ void prefetch_tmap(const CUtensorMap* m) {
  asm volatile("prefetch.tensormap [%0];" ::"l"(m) : "memory");
}
__device__ __forceinline__ uint64_t make_desc(uint32_t a16, uint32_t off, uint32_t lbo, uint32_t sbo, uint32_t swz) {
  const uint32_t lo = a16 + ((off >> 4) + ((lbo >> 4) << 16)), hi = (sbo >> 4) | (swz << 30);
  uint64_t d;
  asm("mov.b64 %0, {%1, %2};" : "=l"(d) : "r"(lo), "r"(hi));
  return d;
}
__device__ __forceinline__ void wg_fence() { asm volatile("wgmma.fence.sync.aligned;" ::: "memory"); }
__device__ __forceinline__ void wg_commit() { asm volatile("wgmma.commit_group.sync.aligned;" ::: "memory"); }
template <int N> __device__ __forceinline__ void wg_wait() { asm volatile("wgmma.wait_group.sync.aligned %0;" ::"n"(N) : "memory"); }
template <int N> __device__ __forceinline__ void fence_regs(float (&d)[N]) {
#pragma unroll
  for (int i = 0; i < N; i++) asm volatile("" : "+f"(d[i])::"memory");
}
template <int N> __device__ __forceinline__ void zero_regs(float (&d)[N]) {
#pragma unroll
  for (int i = 0; i < N; i++) d[i] = 0.f;
}
__device__ __forceinline__ uint32_t pack_bf16(float lo, float hi) {
  uint32_t r;
  asm("cvt.rn.bf16x2.f32 %0, %1, %2;" : "=r"(r) : "f"(hi), "f"(lo));
  return r;
}
__device__ __forceinline__ float bf_lo(uint32_t v) { return __uint_as_float(v << 16); }
__device__ __forceinline__ float bf_hi(uint32_t v) { return __uint_as_float(v & 0xffff0000u); }
__device__ __forceinline__ uint32_t max_bf2(uint32_t a, uint32_t b) {
  uint32_t r; asm("max.bf16x2 %0, %1, %2;" : "=r"(r) : "r"(a), "r"(b)); return r;
}
__device__ __forceinline__ uint32_t min_bf2(uint32_t a, uint32_t b) {
  uint32_t r; asm("min.bf16x2 %0, %1, %2;" : "=r"(r) : "r"(a), "r"(b)); return r;
}
__device__ __forceinline__ uint32_t add_bf2(uint32_t a, uint32_t b) {
  uint32_t r; asm("add.rn.bf16x2 %0, %1, %2;" : "=r"(r) : "r"(a), "r"(b)); return r;
}
__device__ __forceinline__ float ex2(float x) { float r; asm("ex2.approx.ftz.f32 %0, %1;" : "=f"(r) : "f"(x)); return r; }
__device__ __forceinline__ float rcp(float x) { float r; asm("rcp.approx.ftz.f32 %0, %1;" : "=f"(r) : "f"(x)); return r; }
__device__ __forceinline__ float tanh_ap(float x) { float r; asm("tanh.approx.f32 %0, %1;" : "=f"(r) : "f"(x)); return r; }
struct GeluC { float c0, c1, ch; };
__device__ __forceinline__ GeluC gelu_consts(float rstd, float scale) {
  return GeluC{0.7978845608f * rstd, 0.0356774081f * rstd * rstd * rstd, 0.5f * scale * rstd};
}
__device__ __forceinline__ float gelu_s(float y, const GeluC& c) {
  const float u = y * fmaf(y * y, c.c1, c.c0);
  const float hx = y * c.ch;
  return fmaf(hx, tanh_ap(u), hx);
}
__device__ __forceinline__ void stsm4(uint32_t addr, uint32_t r0, uint32_t r1, uint32_t r2, uint32_t r3) {
  asm volatile("stmatrix.sync.aligned.m8n8.x4.shared.b16 [%0], {%1, %2, %3, %4};"
               ::"r"(addr), "r"(r0), "r"(r1), "r"(r2), "r"(r3) : "memory");
}

__device__ __forceinline__ void red_add4(float* p, float a, float b, float c, float d) {
  asm volatile("red.global.add.v4.f32 [%0], {%1, %2, %3, %4};" ::"l"(p), "f"(a), "f"(b), "f"(c), "f"(d) : "memory");
}

__device__ __forceinline__ void mma_ss256(float (&d)[128], uint64_t descA, uint64_t descB) {
  asm volatile("wgmma.mma_async.sync.aligned.m64n256k16.f32.bf16.bf16 {"
      "%0, %1, %2, %3, %4, %5, %6, %7, %8, %9, %10, %11, %12, %13, %14, %15, "
      "%16, %17, %18, %19, %20, %21, %22, %23, %24, %25, %26, %27, %28, %29, %30, %31, "
      "%32, %33, %34, %35, %36, %37, %38, %39, %40, %41, %42, %43, %44, %45, %46, %47, "
      "%48, %49, %50, %51, %52, %53, %54, %55, %56, %57, %58, %59, %60, %61, %62, %63, "
      "%64, %65, %66, %67, %68, %69, %70, %71, %72, %73, %74, %75, %76, %77, %78, %79, "
      "%80, %81, %82, %83, %84, %85, %86, %87, %88, %89, %90, %91, %92, %93, %94, %95, "
      "%96, %97, %98, %99, %100, %101, %102, %103, %104, %105, %106, %107, %108, %109, %110, %111, "
      "%112, %113, %114, %115, %116, %117, %118, %119, %120, %121, %122, %123, %124, %125, %126, %127"
      "}, %128, %129, 1, 1, 1, 0, 1;\n"
      : "+f"(d[0]), "+f"(d[1]), "+f"(d[2]), "+f"(d[3]), "+f"(d[4]), "+f"(d[5]), "+f"(d[6]), "+f"(d[7]),
        "+f"(d[8]), "+f"(d[9]), "+f"(d[10]), "+f"(d[11]), "+f"(d[12]), "+f"(d[13]), "+f"(d[14]), "+f"(d[15]),
        "+f"(d[16]), "+f"(d[17]), "+f"(d[18]), "+f"(d[19]), "+f"(d[20]), "+f"(d[21]), "+f"(d[22]), "+f"(d[23]),
        "+f"(d[24]), "+f"(d[25]), "+f"(d[26]), "+f"(d[27]), "+f"(d[28]), "+f"(d[29]), "+f"(d[30]), "+f"(d[31]),
        "+f"(d[32]), "+f"(d[33]), "+f"(d[34]), "+f"(d[35]), "+f"(d[36]), "+f"(d[37]), "+f"(d[38]), "+f"(d[39]),
        "+f"(d[40]), "+f"(d[41]), "+f"(d[42]), "+f"(d[43]), "+f"(d[44]), "+f"(d[45]), "+f"(d[46]), "+f"(d[47]),
        "+f"(d[48]), "+f"(d[49]), "+f"(d[50]), "+f"(d[51]), "+f"(d[52]), "+f"(d[53]), "+f"(d[54]), "+f"(d[55]),
        "+f"(d[56]), "+f"(d[57]), "+f"(d[58]), "+f"(d[59]), "+f"(d[60]), "+f"(d[61]), "+f"(d[62]), "+f"(d[63]),
        "+f"(d[64]), "+f"(d[65]), "+f"(d[66]), "+f"(d[67]), "+f"(d[68]), "+f"(d[69]), "+f"(d[70]), "+f"(d[71]),
        "+f"(d[72]), "+f"(d[73]), "+f"(d[74]), "+f"(d[75]), "+f"(d[76]), "+f"(d[77]), "+f"(d[78]), "+f"(d[79]),
        "+f"(d[80]), "+f"(d[81]), "+f"(d[82]), "+f"(d[83]), "+f"(d[84]), "+f"(d[85]), "+f"(d[86]), "+f"(d[87]),
        "+f"(d[88]), "+f"(d[89]), "+f"(d[90]), "+f"(d[91]), "+f"(d[92]), "+f"(d[93]), "+f"(d[94]), "+f"(d[95]),
        "+f"(d[96]), "+f"(d[97]), "+f"(d[98]), "+f"(d[99]), "+f"(d[100]), "+f"(d[101]), "+f"(d[102]), "+f"(d[103]),
        "+f"(d[104]), "+f"(d[105]), "+f"(d[106]), "+f"(d[107]), "+f"(d[108]), "+f"(d[109]), "+f"(d[110]), "+f"(d[111]),
        "+f"(d[112]), "+f"(d[113]), "+f"(d[114]), "+f"(d[115]), "+f"(d[116]), "+f"(d[117]), "+f"(d[118]), "+f"(d[119]),
        "+f"(d[120]), "+f"(d[121]), "+f"(d[122]), "+f"(d[123]), "+f"(d[124]), "+f"(d[125]), "+f"(d[126]), "+f"(d[127])
      : "l"(descA), "l"(descB));
}
__device__ __forceinline__ void mma_ss256_p(float (&d)[128], uint64_t descA, uint64_t descB, int acc) {
  asm volatile("{\n.reg .pred p;\nsetp.ne.b32 p, %130, 0;\n"
      "wgmma.mma_async.sync.aligned.m64n256k16.f32.bf16.bf16 {"
      "%0, %1, %2, %3, %4, %5, %6, %7, %8, %9, %10, %11, %12, %13, %14, %15, "
      "%16, %17, %18, %19, %20, %21, %22, %23, %24, %25, %26, %27, %28, %29, %30, %31, "
      "%32, %33, %34, %35, %36, %37, %38, %39, %40, %41, %42, %43, %44, %45, %46, %47, "
      "%48, %49, %50, %51, %52, %53, %54, %55, %56, %57, %58, %59, %60, %61, %62, %63, "
      "%64, %65, %66, %67, %68, %69, %70, %71, %72, %73, %74, %75, %76, %77, %78, %79, "
      "%80, %81, %82, %83, %84, %85, %86, %87, %88, %89, %90, %91, %92, %93, %94, %95, "
      "%96, %97, %98, %99, %100, %101, %102, %103, %104, %105, %106, %107, %108, %109, %110, %111, "
      "%112, %113, %114, %115, %116, %117, %118, %119, %120, %121, %122, %123, %124, %125, %126, %127"
      "}, %128, %129, p, 1, 1, 0, 1;\n}\n"
      : "+f"(d[0]), "+f"(d[1]), "+f"(d[2]), "+f"(d[3]), "+f"(d[4]), "+f"(d[5]), "+f"(d[6]), "+f"(d[7]),
        "+f"(d[8]), "+f"(d[9]), "+f"(d[10]), "+f"(d[11]), "+f"(d[12]), "+f"(d[13]), "+f"(d[14]), "+f"(d[15]),
        "+f"(d[16]), "+f"(d[17]), "+f"(d[18]), "+f"(d[19]), "+f"(d[20]), "+f"(d[21]), "+f"(d[22]), "+f"(d[23]),
        "+f"(d[24]), "+f"(d[25]), "+f"(d[26]), "+f"(d[27]), "+f"(d[28]), "+f"(d[29]), "+f"(d[30]), "+f"(d[31]),
        "+f"(d[32]), "+f"(d[33]), "+f"(d[34]), "+f"(d[35]), "+f"(d[36]), "+f"(d[37]), "+f"(d[38]), "+f"(d[39]),
        "+f"(d[40]), "+f"(d[41]), "+f"(d[42]), "+f"(d[43]), "+f"(d[44]), "+f"(d[45]), "+f"(d[46]), "+f"(d[47]),
        "+f"(d[48]), "+f"(d[49]), "+f"(d[50]), "+f"(d[51]), "+f"(d[52]), "+f"(d[53]), "+f"(d[54]), "+f"(d[55]),
        "+f"(d[56]), "+f"(d[57]), "+f"(d[58]), "+f"(d[59]), "+f"(d[60]), "+f"(d[61]), "+f"(d[62]), "+f"(d[63]),
        "+f"(d[64]), "+f"(d[65]), "+f"(d[66]), "+f"(d[67]), "+f"(d[68]), "+f"(d[69]), "+f"(d[70]), "+f"(d[71]),
        "+f"(d[72]), "+f"(d[73]), "+f"(d[74]), "+f"(d[75]), "+f"(d[76]), "+f"(d[77]), "+f"(d[78]), "+f"(d[79]),
        "+f"(d[80]), "+f"(d[81]), "+f"(d[82]), "+f"(d[83]), "+f"(d[84]), "+f"(d[85]), "+f"(d[86]), "+f"(d[87]),
        "+f"(d[88]), "+f"(d[89]), "+f"(d[90]), "+f"(d[91]), "+f"(d[92]), "+f"(d[93]), "+f"(d[94]), "+f"(d[95]),
        "+f"(d[96]), "+f"(d[97]), "+f"(d[98]), "+f"(d[99]), "+f"(d[100]), "+f"(d[101]), "+f"(d[102]), "+f"(d[103]),
        "+f"(d[104]), "+f"(d[105]), "+f"(d[106]), "+f"(d[107]), "+f"(d[108]), "+f"(d[109]), "+f"(d[110]), "+f"(d[111]),
        "+f"(d[112]), "+f"(d[113]), "+f"(d[114]), "+f"(d[115]), "+f"(d[116]), "+f"(d[117]), "+f"(d[118]), "+f"(d[119]),
        "+f"(d[120]), "+f"(d[121]), "+f"(d[122]), "+f"(d[123]), "+f"(d[124]), "+f"(d[125]), "+f"(d[126]), "+f"(d[127])
      : "l"(descA), "l"(descB), "r"(acc));
}

__device__ __forceinline__ void mma_ss64(float (&d)[32], uint64_t descA, uint64_t descB) {
  asm volatile("wgmma.mma_async.sync.aligned.m64n64k16.f32.bf16.bf16 {"
      "%0, %1, %2, %3, %4, %5, %6, %7, %8, %9, %10, %11, %12, %13, %14, %15, "
      "%16, %17, %18, %19, %20, %21, %22, %23, %24, %25, %26, %27, %28, %29, %30, %31"
      "}, %32, %33, 1, 1, 1, 0, 1;\n"
      : "+f"(d[0]), "+f"(d[1]), "+f"(d[2]), "+f"(d[3]), "+f"(d[4]), "+f"(d[5]), "+f"(d[6]), "+f"(d[7]),
        "+f"(d[8]), "+f"(d[9]), "+f"(d[10]), "+f"(d[11]), "+f"(d[12]), "+f"(d[13]), "+f"(d[14]), "+f"(d[15]),
        "+f"(d[16]), "+f"(d[17]), "+f"(d[18]), "+f"(d[19]), "+f"(d[20]), "+f"(d[21]), "+f"(d[22]), "+f"(d[23]),
        "+f"(d[24]), "+f"(d[25]), "+f"(d[26]), "+f"(d[27]), "+f"(d[28]), "+f"(d[29]), "+f"(d[30]), "+f"(d[31])
      : "l"(descA), "l"(descB));
}
__device__ __forceinline__ void mma_ss64_p(float (&d)[32], uint64_t descA, uint64_t descB, int acc) {
  asm volatile("{\n.reg .pred p;\nsetp.ne.b32 p, %34, 0;\n"
      "wgmma.mma_async.sync.aligned.m64n64k16.f32.bf16.bf16 {"
      "%0, %1, %2, %3, %4, %5, %6, %7, %8, %9, %10, %11, %12, %13, %14, %15, "
      "%16, %17, %18, %19, %20, %21, %22, %23, %24, %25, %26, %27, %28, %29, %30, %31"
      "}, %32, %33, p, 1, 1, 0, 1;\n}\n"
      : "+f"(d[0]), "+f"(d[1]), "+f"(d[2]), "+f"(d[3]), "+f"(d[4]), "+f"(d[5]), "+f"(d[6]), "+f"(d[7]),
        "+f"(d[8]), "+f"(d[9]), "+f"(d[10]), "+f"(d[11]), "+f"(d[12]), "+f"(d[13]), "+f"(d[14]), "+f"(d[15]),
        "+f"(d[16]), "+f"(d[17]), "+f"(d[18]), "+f"(d[19]), "+f"(d[20]), "+f"(d[21]), "+f"(d[22]), "+f"(d[23]),
        "+f"(d[24]), "+f"(d[25]), "+f"(d[26]), "+f"(d[27]), "+f"(d[28]), "+f"(d[29]), "+f"(d[30]), "+f"(d[31])
      : "l"(descA), "l"(descB), "r"(acc));
}

__device__ __forceinline__ void mma_ss160(float (&d)[80], uint64_t descA, uint64_t descB) {
  asm volatile("wgmma.mma_async.sync.aligned.m64n160k16.f32.bf16.bf16 {"
      "%0, %1, %2, %3, %4, %5, %6, %7, %8, %9, %10, %11, %12, %13, %14, %15, "
      "%16, %17, %18, %19, %20, %21, %22, %23, %24, %25, %26, %27, %28, %29, %30, %31, "
      "%32, %33, %34, %35, %36, %37, %38, %39, %40, %41, %42, %43, %44, %45, %46, %47, "
      "%48, %49, %50, %51, %52, %53, %54, %55, %56, %57, %58, %59, %60, %61, %62, %63, "
      "%64, %65, %66, %67, %68, %69, %70, %71, %72, %73, %74, %75, %76, %77, %78, %79"
      "}, %80, %81, 1, 1, 1, 0, 1;\n"
      : "+f"(d[0]), "+f"(d[1]), "+f"(d[2]), "+f"(d[3]), "+f"(d[4]), "+f"(d[5]), "+f"(d[6]), "+f"(d[7]),
        "+f"(d[8]), "+f"(d[9]), "+f"(d[10]), "+f"(d[11]), "+f"(d[12]), "+f"(d[13]), "+f"(d[14]), "+f"(d[15]),
        "+f"(d[16]), "+f"(d[17]), "+f"(d[18]), "+f"(d[19]), "+f"(d[20]), "+f"(d[21]), "+f"(d[22]), "+f"(d[23]),
        "+f"(d[24]), "+f"(d[25]), "+f"(d[26]), "+f"(d[27]), "+f"(d[28]), "+f"(d[29]), "+f"(d[30]), "+f"(d[31]),
        "+f"(d[32]), "+f"(d[33]), "+f"(d[34]), "+f"(d[35]), "+f"(d[36]), "+f"(d[37]), "+f"(d[38]), "+f"(d[39]),
        "+f"(d[40]), "+f"(d[41]), "+f"(d[42]), "+f"(d[43]), "+f"(d[44]), "+f"(d[45]), "+f"(d[46]), "+f"(d[47]),
        "+f"(d[48]), "+f"(d[49]), "+f"(d[50]), "+f"(d[51]), "+f"(d[52]), "+f"(d[53]), "+f"(d[54]), "+f"(d[55]),
        "+f"(d[56]), "+f"(d[57]), "+f"(d[58]), "+f"(d[59]), "+f"(d[60]), "+f"(d[61]), "+f"(d[62]), "+f"(d[63]),
        "+f"(d[64]), "+f"(d[65]), "+f"(d[66]), "+f"(d[67]), "+f"(d[68]), "+f"(d[69]), "+f"(d[70]), "+f"(d[71]),
        "+f"(d[72]), "+f"(d[73]), "+f"(d[74]), "+f"(d[75]), "+f"(d[76]), "+f"(d[77]), "+f"(d[78]), "+f"(d[79])
      : "l"(descA), "l"(descB));
}
__device__ __forceinline__ void mma_ss160_z(float (&d)[80], uint64_t descA, uint64_t descB) {
  asm volatile("wgmma.mma_async.sync.aligned.m64n160k16.f32.bf16.bf16 {"
      "%0, %1, %2, %3, %4, %5, %6, %7, %8, %9, %10, %11, %12, %13, %14, %15, "
      "%16, %17, %18, %19, %20, %21, %22, %23, %24, %25, %26, %27, %28, %29, %30, %31, "
      "%32, %33, %34, %35, %36, %37, %38, %39, %40, %41, %42, %43, %44, %45, %46, %47, "
      "%48, %49, %50, %51, %52, %53, %54, %55, %56, %57, %58, %59, %60, %61, %62, %63, "
      "%64, %65, %66, %67, %68, %69, %70, %71, %72, %73, %74, %75, %76, %77, %78, %79"
      "}, %80, %81, 0, 1, 1, 0, 1;\n"
      : "=f"(d[0]), "=f"(d[1]), "=f"(d[2]), "=f"(d[3]), "=f"(d[4]), "=f"(d[5]), "=f"(d[6]), "=f"(d[7]),
        "=f"(d[8]), "=f"(d[9]), "=f"(d[10]), "=f"(d[11]), "=f"(d[12]), "=f"(d[13]), "=f"(d[14]), "=f"(d[15]),
        "=f"(d[16]), "=f"(d[17]), "=f"(d[18]), "=f"(d[19]), "=f"(d[20]), "=f"(d[21]), "=f"(d[22]), "=f"(d[23]),
        "=f"(d[24]), "=f"(d[25]), "=f"(d[26]), "=f"(d[27]), "=f"(d[28]), "=f"(d[29]), "=f"(d[30]), "=f"(d[31]),
        "=f"(d[32]), "=f"(d[33]), "=f"(d[34]), "=f"(d[35]), "=f"(d[36]), "=f"(d[37]), "=f"(d[38]), "=f"(d[39]),
        "=f"(d[40]), "=f"(d[41]), "=f"(d[42]), "=f"(d[43]), "=f"(d[44]), "=f"(d[45]), "=f"(d[46]), "=f"(d[47]),
        "=f"(d[48]), "=f"(d[49]), "=f"(d[50]), "=f"(d[51]), "=f"(d[52]), "=f"(d[53]), "=f"(d[54]), "=f"(d[55]),
        "=f"(d[56]), "=f"(d[57]), "=f"(d[58]), "=f"(d[59]), "=f"(d[60]), "=f"(d[61]), "=f"(d[62]), "=f"(d[63]),
        "=f"(d[64]), "=f"(d[65]), "=f"(d[66]), "=f"(d[67]), "=f"(d[68]), "=f"(d[69]), "=f"(d[70]), "=f"(d[71]),
        "=f"(d[72]), "=f"(d[73]), "=f"(d[74]), "=f"(d[75]), "=f"(d[76]), "=f"(d[77]), "=f"(d[78]), "=f"(d[79])
      : "l"(descA), "l"(descB));
}

__device__ __forceinline__ void mma_ss192(float (&d)[96], uint64_t descA, uint64_t descB) {
  asm volatile("wgmma.mma_async.sync.aligned.m64n192k16.f32.bf16.bf16 {"
      "%0, %1, %2, %3, %4, %5, %6, %7, %8, %9, %10, %11, %12, %13, %14, %15, "
      "%16, %17, %18, %19, %20, %21, %22, %23, %24, %25, %26, %27, %28, %29, %30, %31, "
      "%32, %33, %34, %35, %36, %37, %38, %39, %40, %41, %42, %43, %44, %45, %46, %47, "
      "%48, %49, %50, %51, %52, %53, %54, %55, %56, %57, %58, %59, %60, %61, %62, %63, "
      "%64, %65, %66, %67, %68, %69, %70, %71, %72, %73, %74, %75, %76, %77, %78, %79, "
      "%80, %81, %82, %83, %84, %85, %86, %87, %88, %89, %90, %91, %92, %93, %94, %95"
      "}, %96, %97, 1, 1, 1, 0, 1;\n"
      : "+f"(d[0]), "+f"(d[1]), "+f"(d[2]), "+f"(d[3]), "+f"(d[4]), "+f"(d[5]), "+f"(d[6]), "+f"(d[7]),
        "+f"(d[8]), "+f"(d[9]), "+f"(d[10]), "+f"(d[11]), "+f"(d[12]), "+f"(d[13]), "+f"(d[14]), "+f"(d[15]),
        "+f"(d[16]), "+f"(d[17]), "+f"(d[18]), "+f"(d[19]), "+f"(d[20]), "+f"(d[21]), "+f"(d[22]), "+f"(d[23]),
        "+f"(d[24]), "+f"(d[25]), "+f"(d[26]), "+f"(d[27]), "+f"(d[28]), "+f"(d[29]), "+f"(d[30]), "+f"(d[31]),
        "+f"(d[32]), "+f"(d[33]), "+f"(d[34]), "+f"(d[35]), "+f"(d[36]), "+f"(d[37]), "+f"(d[38]), "+f"(d[39]),
        "+f"(d[40]), "+f"(d[41]), "+f"(d[42]), "+f"(d[43]), "+f"(d[44]), "+f"(d[45]), "+f"(d[46]), "+f"(d[47]),
        "+f"(d[48]), "+f"(d[49]), "+f"(d[50]), "+f"(d[51]), "+f"(d[52]), "+f"(d[53]), "+f"(d[54]), "+f"(d[55]),
        "+f"(d[56]), "+f"(d[57]), "+f"(d[58]), "+f"(d[59]), "+f"(d[60]), "+f"(d[61]), "+f"(d[62]), "+f"(d[63]),
        "+f"(d[64]), "+f"(d[65]), "+f"(d[66]), "+f"(d[67]), "+f"(d[68]), "+f"(d[69]), "+f"(d[70]), "+f"(d[71]),
        "+f"(d[72]), "+f"(d[73]), "+f"(d[74]), "+f"(d[75]), "+f"(d[76]), "+f"(d[77]), "+f"(d[78]), "+f"(d[79]),
        "+f"(d[80]), "+f"(d[81]), "+f"(d[82]), "+f"(d[83]), "+f"(d[84]), "+f"(d[85]), "+f"(d[86]), "+f"(d[87]),
        "+f"(d[88]), "+f"(d[89]), "+f"(d[90]), "+f"(d[91]), "+f"(d[92]), "+f"(d[93]), "+f"(d[94]), "+f"(d[95])
      : "l"(descA), "l"(descB));
}
__device__ __forceinline__ void mma_ss192_p(float (&d)[96], uint64_t descA, uint64_t descB, int acc) {
  asm volatile("{\n.reg .pred p;\nsetp.ne.b32 p, %98, 0;\n"
      "wgmma.mma_async.sync.aligned.m64n192k16.f32.bf16.bf16 {"
      "%0, %1, %2, %3, %4, %5, %6, %7, %8, %9, %10, %11, %12, %13, %14, %15, "
      "%16, %17, %18, %19, %20, %21, %22, %23, %24, %25, %26, %27, %28, %29, %30, %31, "
      "%32, %33, %34, %35, %36, %37, %38, %39, %40, %41, %42, %43, %44, %45, %46, %47, "
      "%48, %49, %50, %51, %52, %53, %54, %55, %56, %57, %58, %59, %60, %61, %62, %63, "
      "%64, %65, %66, %67, %68, %69, %70, %71, %72, %73, %74, %75, %76, %77, %78, %79, "
      "%80, %81, %82, %83, %84, %85, %86, %87, %88, %89, %90, %91, %92, %93, %94, %95"
      "}, %96, %97, p, 1, 1, 0, 1;\n}\n"
      : "+f"(d[0]), "+f"(d[1]), "+f"(d[2]), "+f"(d[3]), "+f"(d[4]), "+f"(d[5]), "+f"(d[6]), "+f"(d[7]),
        "+f"(d[8]), "+f"(d[9]), "+f"(d[10]), "+f"(d[11]), "+f"(d[12]), "+f"(d[13]), "+f"(d[14]), "+f"(d[15]),
        "+f"(d[16]), "+f"(d[17]), "+f"(d[18]), "+f"(d[19]), "+f"(d[20]), "+f"(d[21]), "+f"(d[22]), "+f"(d[23]),
        "+f"(d[24]), "+f"(d[25]), "+f"(d[26]), "+f"(d[27]), "+f"(d[28]), "+f"(d[29]), "+f"(d[30]), "+f"(d[31]),
        "+f"(d[32]), "+f"(d[33]), "+f"(d[34]), "+f"(d[35]), "+f"(d[36]), "+f"(d[37]), "+f"(d[38]), "+f"(d[39]),
        "+f"(d[40]), "+f"(d[41]), "+f"(d[42]), "+f"(d[43]), "+f"(d[44]), "+f"(d[45]), "+f"(d[46]), "+f"(d[47]),
        "+f"(d[48]), "+f"(d[49]), "+f"(d[50]), "+f"(d[51]), "+f"(d[52]), "+f"(d[53]), "+f"(d[54]), "+f"(d[55]),
        "+f"(d[56]), "+f"(d[57]), "+f"(d[58]), "+f"(d[59]), "+f"(d[60]), "+f"(d[61]), "+f"(d[62]), "+f"(d[63]),
        "+f"(d[64]), "+f"(d[65]), "+f"(d[66]), "+f"(d[67]), "+f"(d[68]), "+f"(d[69]), "+f"(d[70]), "+f"(d[71]),
        "+f"(d[72]), "+f"(d[73]), "+f"(d[74]), "+f"(d[75]), "+f"(d[76]), "+f"(d[77]), "+f"(d[78]), "+f"(d[79]),
        "+f"(d[80]), "+f"(d[81]), "+f"(d[82]), "+f"(d[83]), "+f"(d[84]), "+f"(d[85]), "+f"(d[86]), "+f"(d[87]),
        "+f"(d[88]), "+f"(d[89]), "+f"(d[90]), "+f"(d[91]), "+f"(d[92]), "+f"(d[93]), "+f"(d[94]), "+f"(d[95])
      : "l"(descA), "l"(descB), "r"(acc));
}

__device__ __forceinline__ void mma_ss80_tt(float (&d)[40], uint64_t descA, uint64_t descB) {
  asm volatile("wgmma.mma_async.sync.aligned.m64n80k16.f32.bf16.bf16 {"
      "%0, %1, %2, %3, %4, %5, %6, %7, %8, %9, %10, %11, %12, %13, %14, %15, "
      "%16, %17, %18, %19, %20, %21, %22, %23, %24, %25, %26, %27, %28, %29, %30, %31, "
      "%32, %33, %34, %35, %36, %37, %38, %39"
      "}, %40, %41, 1, 1, 1, 1, 1;\n"
      : "+f"(d[0]), "+f"(d[1]), "+f"(d[2]), "+f"(d[3]), "+f"(d[4]), "+f"(d[5]), "+f"(d[6]), "+f"(d[7]),
        "+f"(d[8]), "+f"(d[9]), "+f"(d[10]), "+f"(d[11]), "+f"(d[12]), "+f"(d[13]), "+f"(d[14]), "+f"(d[15]),
        "+f"(d[16]), "+f"(d[17]), "+f"(d[18]), "+f"(d[19]), "+f"(d[20]), "+f"(d[21]), "+f"(d[22]), "+f"(d[23]),
        "+f"(d[24]), "+f"(d[25]), "+f"(d[26]), "+f"(d[27]), "+f"(d[28]), "+f"(d[29]), "+f"(d[30]), "+f"(d[31]),
        "+f"(d[32]), "+f"(d[33]), "+f"(d[34]), "+f"(d[35]), "+f"(d[36]), "+f"(d[37]), "+f"(d[38]), "+f"(d[39])
      : "l"(descA), "l"(descB));
}
__device__ __forceinline__ void mma_ss80_tt_z(float (&d)[40], uint64_t descA, uint64_t descB) {
  asm volatile("wgmma.mma_async.sync.aligned.m64n80k16.f32.bf16.bf16 {"
      "%0, %1, %2, %3, %4, %5, %6, %7, %8, %9, %10, %11, %12, %13, %14, %15, "
      "%16, %17, %18, %19, %20, %21, %22, %23, %24, %25, %26, %27, %28, %29, %30, %31, "
      "%32, %33, %34, %35, %36, %37, %38, %39"
      "}, %40, %41, 0, 1, 1, 1, 1;\n"
      : "=f"(d[0]), "=f"(d[1]), "=f"(d[2]), "=f"(d[3]), "=f"(d[4]), "=f"(d[5]), "=f"(d[6]), "=f"(d[7]),
        "=f"(d[8]), "=f"(d[9]), "=f"(d[10]), "=f"(d[11]), "=f"(d[12]), "=f"(d[13]), "=f"(d[14]), "=f"(d[15]),
        "=f"(d[16]), "=f"(d[17]), "=f"(d[18]), "=f"(d[19]), "=f"(d[20]), "=f"(d[21]), "=f"(d[22]), "=f"(d[23]),
        "=f"(d[24]), "=f"(d[25]), "=f"(d[26]), "=f"(d[27]), "=f"(d[28]), "=f"(d[29]), "=f"(d[30]), "=f"(d[31]),
        "=f"(d[32]), "=f"(d[33]), "=f"(d[34]), "=f"(d[35]), "=f"(d[36]), "=f"(d[37]), "=f"(d[38]), "=f"(d[39])
      : "l"(descA), "l"(descB));
}

__device__ __forceinline__ void mma_rs80_k(float (&d)[40], const uint32_t (&a)[4], uint64_t descB) {
  asm volatile("wgmma.mma_async.sync.aligned.m64n80k16.f32.bf16.bf16 {"
      "%0, %1, %2, %3, %4, %5, %6, %7, %8, %9, %10, %11, %12, %13, %14, %15, "
      "%16, %17, %18, %19, %20, %21, %22, %23, %24, %25, %26, %27, %28, %29, %30, %31, "
      "%32, %33, %34, %35, %36, %37, %38, %39"
      "}, {%40, %41, %42, %43}, %44, 1, 1, 1, 0;\n"
      : "+f"(d[0]), "+f"(d[1]), "+f"(d[2]), "+f"(d[3]), "+f"(d[4]), "+f"(d[5]), "+f"(d[6]), "+f"(d[7]),
        "+f"(d[8]), "+f"(d[9]), "+f"(d[10]), "+f"(d[11]), "+f"(d[12]), "+f"(d[13]), "+f"(d[14]), "+f"(d[15]),
        "+f"(d[16]), "+f"(d[17]), "+f"(d[18]), "+f"(d[19]), "+f"(d[20]), "+f"(d[21]), "+f"(d[22]), "+f"(d[23]),
        "+f"(d[24]), "+f"(d[25]), "+f"(d[26]), "+f"(d[27]), "+f"(d[28]), "+f"(d[29]), "+f"(d[30]), "+f"(d[31]),
        "+f"(d[32]), "+f"(d[33]), "+f"(d[34]), "+f"(d[35]), "+f"(d[36]), "+f"(d[37]), "+f"(d[38]), "+f"(d[39])
      : "r"(a[0]), "r"(a[1]), "r"(a[2]), "r"(a[3]), "l"(descB));
}
__device__ __forceinline__ void mma_rs80_k_z(float (&d)[40], const uint32_t (&a)[4], uint64_t descB) {
  asm volatile("wgmma.mma_async.sync.aligned.m64n80k16.f32.bf16.bf16 {"
      "%0, %1, %2, %3, %4, %5, %6, %7, %8, %9, %10, %11, %12, %13, %14, %15, "
      "%16, %17, %18, %19, %20, %21, %22, %23, %24, %25, %26, %27, %28, %29, %30, %31, "
      "%32, %33, %34, %35, %36, %37, %38, %39"
      "}, {%40, %41, %42, %43}, %44, 0, 1, 1, 0;\n"
      : "=f"(d[0]), "=f"(d[1]), "=f"(d[2]), "=f"(d[3]), "=f"(d[4]), "=f"(d[5]), "=f"(d[6]), "=f"(d[7]),
        "=f"(d[8]), "=f"(d[9]), "=f"(d[10]), "=f"(d[11]), "=f"(d[12]), "=f"(d[13]), "=f"(d[14]), "=f"(d[15]),
        "=f"(d[16]), "=f"(d[17]), "=f"(d[18]), "=f"(d[19]), "=f"(d[20]), "=f"(d[21]), "=f"(d[22]), "=f"(d[23]),
        "=f"(d[24]), "=f"(d[25]), "=f"(d[26]), "=f"(d[27]), "=f"(d[28]), "=f"(d[29]), "=f"(d[30]), "=f"(d[31]),
        "=f"(d[32]), "=f"(d[33]), "=f"(d[34]), "=f"(d[35]), "=f"(d[36]), "=f"(d[37]), "=f"(d[38]), "=f"(d[39])
      : "r"(a[0]), "r"(a[1]), "r"(a[2]), "r"(a[3]), "l"(descB));
}

__device__ __forceinline__ void mma_rs48_k(float (&d)[24], const uint32_t (&a)[4], uint64_t descB) {
  asm volatile("wgmma.mma_async.sync.aligned.m64n48k16.f32.bf16.bf16 {"
      "%0, %1, %2, %3, %4, %5, %6, %7, %8, %9, %10, %11, %12, %13, %14, %15, "
      "%16, %17, %18, %19, %20, %21, %22, %23"
      "}, {%24, %25, %26, %27}, %28, 1, 1, 1, 0;\n"
      : "+f"(d[0]), "+f"(d[1]), "+f"(d[2]), "+f"(d[3]), "+f"(d[4]), "+f"(d[5]), "+f"(d[6]), "+f"(d[7]),
        "+f"(d[8]), "+f"(d[9]), "+f"(d[10]), "+f"(d[11]), "+f"(d[12]), "+f"(d[13]), "+f"(d[14]), "+f"(d[15]),
        "+f"(d[16]), "+f"(d[17]), "+f"(d[18]), "+f"(d[19]), "+f"(d[20]), "+f"(d[21]), "+f"(d[22]), "+f"(d[23])
      : "r"(a[0]), "r"(a[1]), "r"(a[2]), "r"(a[3]), "l"(descB));
}
__device__ __forceinline__ void mma_rs48_k_z(float (&d)[24], const uint32_t (&a)[4], uint64_t descB) {
  asm volatile("wgmma.mma_async.sync.aligned.m64n48k16.f32.bf16.bf16 {"
      "%0, %1, %2, %3, %4, %5, %6, %7, %8, %9, %10, %11, %12, %13, %14, %15, "
      "%16, %17, %18, %19, %20, %21, %22, %23"
      "}, {%24, %25, %26, %27}, %28, 0, 1, 1, 0;\n"
      : "=f"(d[0]), "=f"(d[1]), "=f"(d[2]), "=f"(d[3]), "=f"(d[4]), "=f"(d[5]), "=f"(d[6]), "=f"(d[7]),
        "=f"(d[8]), "=f"(d[9]), "=f"(d[10]), "=f"(d[11]), "=f"(d[12]), "=f"(d[13]), "=f"(d[14]), "=f"(d[15]),
        "=f"(d[16]), "=f"(d[17]), "=f"(d[18]), "=f"(d[19]), "=f"(d[20]), "=f"(d[21]), "=f"(d[22]), "=f"(d[23])
      : "r"(a[0]), "r"(a[1]), "r"(a[2]), "r"(a[3]), "l"(descB));
}

__device__ __forceinline__ void mma_rs160_n(float (&d)[80], const uint32_t (&a)[4], uint64_t descB) {
  asm volatile("wgmma.mma_async.sync.aligned.m64n160k16.f32.bf16.bf16 {"
      "%0, %1, %2, %3, %4, %5, %6, %7, %8, %9, %10, %11, %12, %13, %14, %15, "
      "%16, %17, %18, %19, %20, %21, %22, %23, %24, %25, %26, %27, %28, %29, %30, %31, "
      "%32, %33, %34, %35, %36, %37, %38, %39, %40, %41, %42, %43, %44, %45, %46, %47, "
      "%48, %49, %50, %51, %52, %53, %54, %55, %56, %57, %58, %59, %60, %61, %62, %63, "
      "%64, %65, %66, %67, %68, %69, %70, %71, %72, %73, %74, %75, %76, %77, %78, %79"
      "}, {%80, %81, %82, %83}, %84, 1, 1, 1, 1;\n"
      : "+f"(d[0]), "+f"(d[1]), "+f"(d[2]), "+f"(d[3]), "+f"(d[4]), "+f"(d[5]), "+f"(d[6]), "+f"(d[7]),
        "+f"(d[8]), "+f"(d[9]), "+f"(d[10]), "+f"(d[11]), "+f"(d[12]), "+f"(d[13]), "+f"(d[14]), "+f"(d[15]),
        "+f"(d[16]), "+f"(d[17]), "+f"(d[18]), "+f"(d[19]), "+f"(d[20]), "+f"(d[21]), "+f"(d[22]), "+f"(d[23]),
        "+f"(d[24]), "+f"(d[25]), "+f"(d[26]), "+f"(d[27]), "+f"(d[28]), "+f"(d[29]), "+f"(d[30]), "+f"(d[31]),
        "+f"(d[32]), "+f"(d[33]), "+f"(d[34]), "+f"(d[35]), "+f"(d[36]), "+f"(d[37]), "+f"(d[38]), "+f"(d[39]),
        "+f"(d[40]), "+f"(d[41]), "+f"(d[42]), "+f"(d[43]), "+f"(d[44]), "+f"(d[45]), "+f"(d[46]), "+f"(d[47]),
        "+f"(d[48]), "+f"(d[49]), "+f"(d[50]), "+f"(d[51]), "+f"(d[52]), "+f"(d[53]), "+f"(d[54]), "+f"(d[55]),
        "+f"(d[56]), "+f"(d[57]), "+f"(d[58]), "+f"(d[59]), "+f"(d[60]), "+f"(d[61]), "+f"(d[62]), "+f"(d[63]),
        "+f"(d[64]), "+f"(d[65]), "+f"(d[66]), "+f"(d[67]), "+f"(d[68]), "+f"(d[69]), "+f"(d[70]), "+f"(d[71]),
        "+f"(d[72]), "+f"(d[73]), "+f"(d[74]), "+f"(d[75]), "+f"(d[76]), "+f"(d[77]), "+f"(d[78]), "+f"(d[79])
      : "r"(a[0]), "r"(a[1]), "r"(a[2]), "r"(a[3]), "l"(descB));
}
__device__ __forceinline__ void mma_rs160_n_z(float (&d)[80], const uint32_t (&a)[4], uint64_t descB) {
  asm volatile("wgmma.mma_async.sync.aligned.m64n160k16.f32.bf16.bf16 {"
      "%0, %1, %2, %3, %4, %5, %6, %7, %8, %9, %10, %11, %12, %13, %14, %15, "
      "%16, %17, %18, %19, %20, %21, %22, %23, %24, %25, %26, %27, %28, %29, %30, %31, "
      "%32, %33, %34, %35, %36, %37, %38, %39, %40, %41, %42, %43, %44, %45, %46, %47, "
      "%48, %49, %50, %51, %52, %53, %54, %55, %56, %57, %58, %59, %60, %61, %62, %63, "
      "%64, %65, %66, %67, %68, %69, %70, %71, %72, %73, %74, %75, %76, %77, %78, %79"
      "}, {%80, %81, %82, %83}, %84, 0, 1, 1, 1;\n"
      : "=f"(d[0]), "=f"(d[1]), "=f"(d[2]), "=f"(d[3]), "=f"(d[4]), "=f"(d[5]), "=f"(d[6]), "=f"(d[7]),
        "=f"(d[8]), "=f"(d[9]), "=f"(d[10]), "=f"(d[11]), "=f"(d[12]), "=f"(d[13]), "=f"(d[14]), "=f"(d[15]),
        "=f"(d[16]), "=f"(d[17]), "=f"(d[18]), "=f"(d[19]), "=f"(d[20]), "=f"(d[21]), "=f"(d[22]), "=f"(d[23]),
        "=f"(d[24]), "=f"(d[25]), "=f"(d[26]), "=f"(d[27]), "=f"(d[28]), "=f"(d[29]), "=f"(d[30]), "=f"(d[31]),
        "=f"(d[32]), "=f"(d[33]), "=f"(d[34]), "=f"(d[35]), "=f"(d[36]), "=f"(d[37]), "=f"(d[38]), "=f"(d[39]),
        "=f"(d[40]), "=f"(d[41]), "=f"(d[42]), "=f"(d[43]), "=f"(d[44]), "=f"(d[45]), "=f"(d[46]), "=f"(d[47]),
        "=f"(d[48]), "=f"(d[49]), "=f"(d[50]), "=f"(d[51]), "=f"(d[52]), "=f"(d[53]), "=f"(d[54]), "=f"(d[55]),
        "=f"(d[56]), "=f"(d[57]), "=f"(d[58]), "=f"(d[59]), "=f"(d[60]), "=f"(d[61]), "=f"(d[62]), "=f"(d[63]),
        "=f"(d[64]), "=f"(d[65]), "=f"(d[66]), "=f"(d[67]), "=f"(d[68]), "=f"(d[69]), "=f"(d[70]), "=f"(d[71]),
        "=f"(d[72]), "=f"(d[73]), "=f"(d[74]), "=f"(d[75]), "=f"(d[76]), "=f"(d[77]), "=f"(d[78]), "=f"(d[79])
      : "r"(a[0]), "r"(a[1]), "r"(a[2]), "r"(a[3]), "l"(descB));
}

__device__ __forceinline__ void feature_map(const uint32_t (&P)[2][10], uint32_t (&fr)[10][4]) {
  constexpr float L2E = 1.4426950408889634f;
#pragma unroll
  for (int p = 0; p < 2; p++) {
#pragma unroll
    for (int r = 0; r < 2; r++) {
      uint32_t mx = P[r][5 * p], mn = mx;
#pragma unroll
      for (int g = 1; g < 5; g++) { mx = max_bf2(mx, P[r][5 * p + g]); mn = min_bf2(mn, P[r][5 * p + g]); }
      mx = max_bf2(mx, __shfl_xor_sync(0xffffffffu, mx, 1));
      mn = min_bf2(mn, __shfl_xor_sync(0xffffffffu, mn, 1));
      mx = max_bf2(mx, __shfl_xor_sync(0xffffffffu, mx, 2));
      mn = min_bf2(mn, __shfl_xor_sync(0xffffffffu, mn, 2));
      float mx0 = -bf_lo(mx) * L2E, mx1 = -bf_hi(mx) * L2E, mn0 = bf_lo(mn) * L2E, mn1 = bf_hi(mn) * L2E;
      float ep0[5], ep1[5], en0[5], en1[5];
      float sp0 = 0.f, sp1 = 0.f, sn0 = 0.f, sn1 = 0.f;
#pragma unroll
      for (int g = 0; g < 5; g++) {
        float x0 = bf_lo(P[r][5 * p + g]), x1 = bf_hi(P[r][5 * p + g]);
        ep0[g] = ex2(fmaf(x0, L2E, mx0)); ep1[g] = ex2(fmaf(x1, L2E, mx1));
        en0[g] = ex2(fmaf(x0, -L2E, mn0)); en1[g] = ex2(fmaf(x1, -L2E, mn1));
        sp0 += ep0[g]; sp1 += ep1[g]; sn0 += en0[g]; sn1 += en1[g];
      }
      sp0 += __shfl_xor_sync(0xffffffffu, sp0, 1); sp1 += __shfl_xor_sync(0xffffffffu, sp1, 1);
      sn0 += __shfl_xor_sync(0xffffffffu, sn0, 1); sn1 += __shfl_xor_sync(0xffffffffu, sn1, 1);
      sp0 += __shfl_xor_sync(0xffffffffu, sp0, 2); sp1 += __shfl_xor_sync(0xffffffffu, sp1, 2);
      sn0 += __shfl_xor_sync(0xffffffffu, sn0, 2); sn1 += __shfl_xor_sync(0xffffffffu, sn1, 2);
      sp0 = rcp(sp0); sp1 = rcp(sp1); sn0 = rcp(sn0); sn1 = rcp(sn1);
#pragma unroll
      for (int g = 0; g < 5; g++) {
        fr[5 * p + g][r] = pack_bf16(ep0[g] * sp0, ep1[g] * sp1);
        fr[5 * p + g][2 + r] = pack_bf16(en0[g] * sn0, en1[g] * sn1);
      }
    }
  }
}

template <int V> struct IntC { static constexpr int value = V; };
struct Ring {
  uint32_t idx, phase;
  template <int N> __device__ __forceinline__ void next() { if (++idx == N) { idx = 0; phase ^= 1; } }
};

}

__global__ void __cluster_dims__(2, 1, 1) __launch_bounds__(384, 1)
fused_kernel(const __grid_constant__ Maps maps, const __nv_bfloat16* __restrict__ x, const __nv_bfloat16* __restrict__ wqkv,
             const __nv_bfloat16* __restrict__ wphi, const __nv_bfloat16* __restrict__ w1, const __nv_bfloat16* __restrict__ w2,
             const __nv_bfloat16* __restrict__ w3, const __nv_bfloat16* __restrict__ w4, const __nv_bfloat16* __restrict__ wo,
             const __nv_bfloat16* __restrict__ gate_w, __nv_bfloat16* __restrict__ out) {
  extern __shared__ __align__(1024) uint8_t sgen[];
  const uint32_t sb = smem_u32(sgen);
  const uint32_t sb16 = (sb & 0x3FFFFu) >> 4;
  const uint32_t bars = sb + OFF_BAR;
  const uint32_t fullA = bars + 8 * B_FULLA, emptyA = bars + 8 * B_EMPTYA, fullB = bars + 8 * B_FULLB, emptyB = bars + 8 * B_EMPTYB;

  const int tid = threadIdx.x;
  const int rank = blockIdx.x & 1;
  const int bid = blockIdx.x - NSVC, pairIdx = bid >> 1;
  const int i = pairIdx >> 2, j = 2 * (pairIdx & 3) + rank;
  const int k3 = (5 * (pairIdx & 3) + 1) >> 1;

  if (bid < 0) {
    const int sv = blockIdx.x;
    const unsigned epoch = *reinterpret_cast<volatile unsigned*>(g_flags + FL_DONE * 32) / NCTA;
    if (tid == 0) {
      for (int b = 0; b < 11; b++) mbar_init(bars + 8 * b, 1);
      mbar_expect_tx(bars + 80, 6400);
      bulk_load(sb + 204800, wphi + sv * 3200, 6400, bars + 80);
    }
    __syncthreads();
    float a[8];
#pragma unroll 1
    for (int rd = 0; rd < 4; rd++) {
      const int nch = rd ? 192 : 80, nth = rd ? 384 : 320, piece = rd ? 18432 : 20480, np = rd == 3 ? 7 : 10;
      if (tid == 0) {
        const char* src = reinterpret_cast<const char*>(rd ? w3 + (size_t)(160 * sv + 60 * (rd - 1)) * F_ : w1 + (size_t)160 * sv * D_);
        for (int p = 0; p < np; p++) {
          const int bytes = (rd == 3 && p == 6) ? 12288 : piece;
          mbar_expect_tx(bars + 8 * p, bytes);
          bulk_load(sb + p * piece, src + p * piece, bytes, bars + 8 * p);
        }
      }
      if (rd == 0) {
        if (tid < 40 && (tid < 20 || sv >= 2))
          reinterpret_cast<uint4*>(g_Hs + (size_t)(2 + ((sv & 1) ? S_ - 1 - tid / 20 : tid / 20)) * D_ + 160 * sv)[tid % 20] = make_uint4(0, 0, 0, 0);
        mbar_wait(bars + 80, 0);
        for (int e = tid; e < 1600; e += 384) {
          const int jj = e / 800, it = e - 800 * jj, st = it / 160, n = (it - 160 * st) >> 1, k0 = 16 * st + 8 * ((it ^ (n >> 2)) & 1);
          const int nn = n % 40, h = 2 * (n / 40) + (nn & 1), ff = 4 * (nn >> 3) + ((nn >> 1) & 3);
          uint32_t w[8];
#pragma unroll
          for (int q = 0; q < 8; q++) {
            const int k = k0 + q;
            w[q] = (unsigned)(k - 20 * h) < 20u ? reinterpret_cast<const unsigned short*>(sgen + 204800)[jj * 1600 + k * 20 + ff] : 0u;
          }
          g_wphi[sv * 1600 + e] = make_uint4(w[0] | (w[1] << 16), w[2] | (w[3] << 16), w[4] | (w[5] << 16), w[6] | (w[7] << 16));
        }
      }
      if (rd < 2) {
#pragma unroll
        for (int e = 0; e < 8; e++) a[e] = 0.f;
      }
#pragma unroll 1
      for (int p = 0; p < np; p++) {
        mbar_wait(bars + 8 * p, rd & 1);
        const int bytes = (rd == 3 && p == 6) ? 12288 : piece;
        if (tid < nth) {
          for (int o = tid * 16; o < bytes; o += nth * 16) {
            const uint4 v = lds128(sb + p * piece + o);
            a[0] += bf_lo(v.x); a[1] += bf_hi(v.x); a[2] += bf_lo(v.y); a[3] += bf_hi(v.y);
            a[4] += bf_lo(v.z); a[5] += bf_hi(v.z); a[6] += bf_lo(v.w); a[7] += bf_hi(v.w);
          }
        }
      }
      if (tid < nth && (rd == 0 || rd == 3)) {
        float* cd = g_cs[epoch & 1] + (rd ? D_ : 0) + 8 * (tid % nch);
        red_add4(cd, a[0], a[1], a[2], a[3]); red_add4(cd + 4, a[4], a[5], a[6], a[7]);
      }
      __syncthreads();
      if (tid == 0 && (rd == 0 || rd == 3)) {
        flag_add(rd ? FL_CS3 : FL_CS);
        if (rd == 0) l2_prefetch(w2 + (size_t)sv * (D_ * D_ / NSVC), D_ * D_ * 2 / NSVC);
      }
    }
    for (int e = tid; e < (D_ + F_) / NSVC; e += 384) g_cs[(epoch + 1) & 1][sv * ((D_ + F_) / NSVC) + e] = 0.f;
    for (int e = tid; e < 2 * KV_J; e += 384) g_acc[(epoch + 1) & 1][sv * 2 * KV_J + e] = 0.f;
    if (tid < 32) {
      l2_prefetch(w4 + (size_t)(sv * 32 + tid) * (F_ * D_ / 128), F_ * D_ * 2 / 128);
      l2_prefetch(wo + (size_t)(sv * 32 + tid) * (D_ * D_ / 128), D_ * D_ * 2 / 128);
    }
    return;
  }
  TSTAMP(0);
  auto load_p1_b = [&](int k, uint32_t slot, uint32_t bar) {
    mbar_expect_tx(bar, 40960);
    tma4d(slot + 8192, &maps.qm, bar, 0, 64 * k, 0, j);
    tma3d(slot, &maps.w1m, bar, 0, 64 * k, j);
    tma4d(slot + 32768 + 2048, &maps.qr, bar, 64, 64 * k, 0, j);
    tma3d(slot + 32768, &maps.w1r, bar, 64, 64 * k, j);
  };
  if (tid >= 256) {
    asm volatile("setmaxnreg.dec.sync.aligned.u32 40;");
    if (tid == 256) {
#pragma unroll
      for (int s = 0; s < NA; s++) mbar_init(fullA + 8 * s, 1);
      asm volatile("fence.mbarrier_init.release.cluster;" ::: "memory");
#pragma unroll 1
      for (int u = 0; u < 4; u++) {
        if ((u & 1) == 0) mbar_expect_tx(fullA + 4 * u, SLOT_A);
        tma2d(sb + OFF_A + u * 8192, &maps.x, fullA + 8 * (u >> 1), 64 * (u >> 1), 128 * i + 64 * (u & 1));
      }
    } else if (tid == 288) {
#pragma unroll
      for (int s = 0; s < NB; s++) mbar_init(fullB + 8 * s, 1);
      asm volatile("fence.mbarrier_init.release.cluster;" ::: "memory");
#pragma unroll 1
      for (int k = 0; k < 2; k++) load_p1_b(k, sb + OFF_B + k * SLOT_B, fullB + 8 * k);
      l2_prefetch(wqkv + (size_t)(128 + 4 * bid) * (3 * D_), 4 * 3 * D_ * 2);
    } else if (tid == 320) {
#pragma unroll
      for (int b = B_CS; b < NBAR; b++) mbar_init(bars + 8 * b, b < B_EMPTYB ? 1 : b < B_EMPTYA ? 8 : b < B_X1P ? 16 : 2);
#pragma unroll
      for (int b = B_DSR; b < B_EMPTYB; b++) mbar_expect_tx(bars + 8 * b, 10240);
      asm volatile("fence.mbarrier_init.release.cluster;" ::: "memory");
    }
    __syncwarp();
    asm volatile("barrier.cluster.arrive.relaxed.aligned;" ::: "memory");
    auto get_epoch = [&]() { return *reinterpret_cast<volatile unsigned*>(g_flags + FL_DONE * 32) / NCTA; };
    asm volatile("barrier.cluster.wait.aligned;" ::: "memory");
    const int lane = tid & 31, pw = (tid >> 5) & 3;
    if (pw == 0) {
      if (tid == 256) {
        Ring r{2, 1};
        unsigned ep1 = 0;
#pragma unroll 1
        for (int k = 2; k < 25; k++) {
          if (k == 4) ep1 = get_epoch() + 1;
          if (k == 10 || k == 17) {
            if (k == 10) mbar_wait(bars + 8 * B_HST, 0);
            flag_wait(k == 10 ? FL_H + 2 * i + rank : FL_X1 + i, ep1 * 8u);
            TSTAMPX(k == 10 ? 29 : 30);
          }
          if (k == 15) mbar_wait(bars + 8 * B_X1P, 0);
          mbar_wait(emptyA + 8 * r.idx, r.phase);
          const uint32_t bar = fullA + 8 * r.idx, slot = sb + OFF_A + r.idx * SLOT_A;
          mbar_expect_tx(bar, SLOT_A);
          if (k >= 10 && k < 15) tma2d(slot, &maps.hs, bar, 64 * (k - 10) + 320 * rank, 128 * i);
          else tma2d_mc(slot + rank * 8192, k < 10 ? &maps.x : &maps.x1, bar, 64 * (k < 10 ? k : (k - 15 + k3) % 10), 128 * i + 64 * rank);
          r.next<NA>();
        }
      }
    } else if (pw == 1) {
      if (tid == 288) {
        Ring r{2, 1};
#pragma unroll 1
        for (int k = 2; k < 18; k++) {
          mbar_wait(emptyB + 8 * r.idx, r.phase);
          const uint32_t bar = fullB + 8 * r.idx, slot = sb + OFF_B + r.idx * SLOT_B;
          if (k < 10) {
            load_p1_b(k, slot, bar);
          } else if (k < 13) {
            mbar_expect_tx(bar, k < 12 ? 40960 : 20480);
            tma3d(slot, &maps.w2, bar, 0, 320 * rank + 128 * (k - 10), 5 * (j >> 1));
            if (k < 12) tma3d(slot + 20480, &maps.w2, bar, 0, 320 * rank + 128 * (k - 10) + 64, 5 * (j >> 1));
          } else {
            mbar_expect_tx(bar, 49152);
            tma3d(slot, &maps.w3, bar, 0, 64 * ((2 * (k - 13) + k3) % 10), 3 * j);
            tma3d(slot + 24576, &maps.w3, bar, 0, 64 * ((2 * (k - 13) + 1 + k3) % 10), 3 * j);
          }
          r.next<NB>();
        }
#pragma unroll 1
        for (int n = 0; n < 8; n++) {
          if (n < 3) { mbar_wait(emptyB + 8 * r.idx, r.phase); r.next<NB>(); }
          if (n >= 4) mbar_wait(bars + 8 * (B_EMPTY4 + n - 4), 0);
          const uint32_t bar = bars + 8 * (B_FULL4 + n), set = sb + ((n >> 1) & 1) * SET4;
          const int h = n & 1, m = ((j >> 1) + 1 + (n >> 1)) & 3;
          mbar_expect_tx(bar, h ? 40960 : 46080);
          tma3d(set + (h ? 46080 : 0), h ? &maps.w4 : &maps.wo, bar, 0, h ? 192 * j + 64 : 80 * j, 5 * m);
          tma3d(set + (h ? 66560 : 25600), &maps.w4, bar, 0, 192 * j + 128 * h, 5 * m);
        }
        mbar_wait(bars + 8 * (B_EMPTY4 + 4), 0);
        mbar_expect_tx(bars + 8 * B_XR, 20480);
        tma2d(sb + OFF_OUT, &maps.st_x1, bars + 8 * B_XR, 80 * j, 128 * i);
      }
    } else {
      const unsigned epoch = get_epoch();
      float* accg = g_acc[epoch & 1];
      if (pw == 2) {
        if (tid == 320) {
          flag_wait(FL_CS, (epoch + 1) * NSVC);
          flag_wait(FL_ST + i, (epoch + 1) * 8u);
          fence_async_glb();
          *reinterpret_cast<volatile uint32_t*>(sgen + OFF_BAR + 8 * NBAR) = (epoch + 1) & 1;
          mbar_expect_tx(bars + 8 * B_CS, 320 + 2048 + 12800);
          bulk_load(sb + OFF_CS, g_cs[epoch & 1] + 80 * j, 320, bars + 8 * B_CS);
          bulk_load(sb + OFF_XST, g_xstat + 128 * i, 2048, bars + 8 * B_CS);
          bulk_load(sb + OFF_MISC, g_wphi + j * 800, 12800, bars + 8 * B_CS);
          TSTAMPX(21);
          flag_wait(FL_KV + j, (epoch + 1) * 16u);
          mbar_expect_tx(bars + 8 * B_KV, KV_J * 4);
          bulk_load(sb + OFF_MISC, accg + j * KV_J, KV_J * 4, bars + 8 * B_KV);
          TSTAMPX(22);
          flag_wait(FL_CS3, (epoch + 1) * NSVC);
          flag_wait(FL_S1 + i, (epoch + 1) * 8u);
          fence_async_glb();
          mbar_expect_tx(bars + 8 * B_ST1, 8192 + 768);
          bulk_load(sb + OFF_CS + 320, g_cs[epoch & 1] + D_ + 192 * j, 768, bars + 8 * B_ST1);
          bulk_load(sb + OFF_MISC, g_st1 + 128 * i * 8, 8192, bars + 8 * B_ST1);
        }
        __syncwarp();
#pragma unroll 1
        for (int c = 0; c < 3; c++) {
          mbar_wait(bars + 8 * (B_EMPTY4 + (c ? 5 : 4)), 0);
          const uint4* src = g_part + (size_t)((i * 8 + j) * 3 + c) * 1280;
          const unsigned* tp = reinterpret_cast<const unsigned*>(src + 1024 + (lane & 7) * 32 + 31);
          uint32_t n = 0;
          while (!__all_sync(0xffffffffu, (ld_acquire(tp) ^ epoch) & 1u) && ++n < (WAIT_LIMIT >> 2)) {}
          if (tid == 320) {
            mbar_expect_tx(bars + 8 * (B_RDY + c), 20480);
            bulk_load(sb + (c ? 25600 + 20480 * c : 0), src, 20480, bars + 8 * (B_RDY + c));
          }
        }
      }
      if (tid == 352) {
        mbar_wait(bars + 8 * B_SIGP, 0);
        flag_add(FL_ST + i);
        TSTAMPX(20);
        mbar_expect_tx(bars + 8 * B_XR, 20480);
#pragma unroll 1
        for (int u = 0; u < 8; u++)
          tma2d(sb + OFF_B + (u / 3) * SLOT_B + SPARE + (u % 3) * 2560, &maps.xr, bars + 8 * B_XR, 80 * j, 128 * i + 16 * u);
        const int shift = (j < 2) ? 1 : (j < 4) ? -1 : (j < 6) ? 2 : -2;
        prefetch_tmap(&maps.st_h); prefetch_tmap(&maps.st_x1); prefetch_tmap(&maps.hs); prefetch_tmap(&maps.x1);
        prefetch_tmap(&maps.w2); prefetch_tmap(&maps.w3); prefetch_tmap(&maps.w4); prefetch_tmap(&maps.wo);
        mbar_wait(bars + 8 * B_SIGH, 0);
        TSTAMPX(23);
        tma2d_store(&maps.st_h, sb + OFF_STG, 80 * j, 128 * i + 2 + shift);
        bulk_commit(); bulk_wait<0>();
        mbar_arrive(bars + 8 * B_HST);
        flag_add(FL_H + 2 * i + (j >> 2));
        flag_add_relaxed(FL_H + 2 * ((i + (shift > 0 ? 1 : -1)) & 15) + (j >> 2));
        TSTAMPX(24);
        mbar_wait(bars + 8 * B_SIGKV, 0);
        TSTAMPX(25);
        fence_async_smem();
        asm volatile("cp.reduce.async.bulk.global.shared::cta.bulk_group.add.f32 [%0], [%1], %2;"
                     ::"l"(accg + j * KV_J), "r"(sb + OFF_MISC), "r"(KV_J * 4) : "memory");
        bulk_commit(); bulk_wait<0>();
        flag_add(FL_KV + j);
        TSTAMPX(26);
        mbar_wait(bars + 8 * B_SIGX1, 0);
        TSTAMPX(27);
        tma2d_store(&maps.st_x1, sb + OFF_STG, 80 * j, 128 * i);
        bulk_commit(); bulk_wait<0>();
        flag_add(FL_X1 + i);
        mbar_arrive_cta(bars + 8 * B_X1P, 0); mbar_arrive_cta(bars + 8 * B_X1P, 1);
        TSTAMPX(28);
        mbar_wait(bars + 8 * B_MFREE, 0);
        flag_add(FL_S1 + i);
      }
    }
  } else {
    uint4 pv[5], pw_[5];
    {
      const int row = 128 * i + 16 * j + (tid >> 4), l16 = tid & 15;
#pragma unroll
      for (int c = 0; c < 5; c++) pv[c] = __ldg(reinterpret_cast<const uint4*>(x + (size_t)row * D_ + c * 128 + l16 * 8));
#pragma unroll
      for (int c = 0; c < 5; c++) pw_[c] = __ldg(reinterpret_cast<const uint4*>(gate_w + c * 128 + l16 * 8));
    }
    asm volatile("barrier.cluster.arrive.relaxed.aligned;" ::: "memory");
    asm volatile("setmaxnreg.inc.sync.aligned.u32 232;");
    const int wg = tid >> 7, warp = tid >> 5, lane = tid & 31, t = lane & 3;
    const int rloc = warp * 16 + (lane >> 2);
    const float* s_cs = reinterpret_cast<const float*>(sgen + OFF_CS);
    auto signal = [&](int b) {
      __syncwarp();
      if (lane == 0) mbar_arrive(bars + 8 * b);
    };
    auto releaseB = [&](uint32_t bar) {
      __syncwarp();
      if (lane == 0) mbar_arrive(bar);
    };
    auto release = [&](uint32_t bar) {
      __syncwarp();
      if (lane < 2) mbar_arrive_cta(bar, lane);
    };
    const uint32_t stg_lane = (warp * 16 + ((lane >> 3) & 1) * 8 + (lane & 7)) * 160 + (lane >> 4) * 16;

    auto stage_tile = [&](uint32_t stg, const uint32_t (&v)[2][10]) {
#pragma unroll
      for (int s = 0; s < 5; s++) stsm4(stg + stg_lane + s * 32, v[0][2 * s], v[1][2 * s], v[0][2 * s + 1], v[1][2 * s + 1]);
    };

    {
      float f[40];
      float s = 0.f, gs = 0.f;
#pragma unroll
      for (int c = 0; c < 5; c++) {
        const uint32_t vv[4] = {pv[c].x, pv[c].y, pv[c].z, pv[c].w}, ww[4] = {pw_[c].x, pw_[c].y, pw_[c].z, pw_[c].w};
#pragma unroll
        for (int e = 0; e < 4; e++) {
          f[8 * c + 2 * e] = bf_lo(vv[e]); f[8 * c + 2 * e + 1] = bf_hi(vv[e]);
          s += f[8 * c + 2 * e] + f[8 * c + 2 * e + 1];
          gs = fmaf(f[8 * c + 2 * e], bf_lo(ww[e]), gs); gs = fmaf(f[8 * c + 2 * e + 1], bf_hi(ww[e]), gs);
        }
      }
#pragma unroll
      for (int o = 1; o < 16; o <<= 1) { s += __shfl_xor_sync(0xffffffffu, s, o); gs += __shfl_xor_sync(0xffffffffu, gs, o); }
      const float mean = s * (1.f / D_);
      float q = 0.f;
#pragma unroll
      for (int e = 0; e < 40; e++) { const float d = f[e] - mean; q = fmaf(d, d, q); }
#pragma unroll
      for (int o = 1; o < 16; o <<= 1) q += __shfl_xor_sync(0xffffffffu, q, o);
      const float rstd = rsqrtf(q * (1.f / D_) + 1e-5f);
      asm volatile("barrier.cluster.wait.aligned;" ::: "memory");
      if ((tid & 15) == 0) g_xstat[128 * i + 16 * j + (tid >> 4)] = make_float4(rstd, -mean, rcp(1.f + __expf(-gs)), 0.f);
      signal(B_SIGP);
    }
    TSTAMP(1);

    Ring ra{0, 0}, rb{0, 0};
    uint32_t qp[2][10], P[2][10];
    float st_g[2];
    {
      float accM[128], accR[32];
      uint32_t pa = 0, pb = 0;
#pragma unroll 1
      for (int k = 0; k < 10; k++) {
        mbar_wait(fullA + 8 * ra.idx, ra.phase);
        if (tid == 0) TRACE(32 + k);
        mbar_wait(fullB + 8 * rb.idx, rb.phase);
        if (tid == 0) TRACE(64 + k);
        if (k == 0) TSTAMP(2);
        const uint32_t a0 = sb16 + ((OFF_A + ra.idx * SLOT_A + wg * 8192) >> 4), b0 = sb16 + ((OFF_B + rb.idx * SLOT_B) >> 4);
        wg_fence();
#pragma unroll
        for (int kk = 0; kk < 4; kk++) {
          const uint64_t da = make_desc(a0, kk * 32, 16, 1024, 1);
          if (kk == 0) {
            mma_ss256_p(accM, da, make_desc(b0, 0, 8192, 1024, 1), k);
            mma_ss64_p(accR, da, make_desc(b0, 32768, 2048, 256, 3), k);
          } else {
            mma_ss256(accM, da, make_desc(b0, kk * 2048, 8192, 1024, 1));
            mma_ss64(accR, da, make_desc(b0, 32768 + kk * 512, 2048, 256, 3));
          }
          if (kk == 0) {
            wg_commit();
            if (k > 0) {
              wg_wait<1>();
              if (k - 1 < 8) release(emptyA + 8 * pa);
              releaseB(emptyB + 8 * pb);
            }
          }
        }
        wg_commit();
        pa = ra.idx; pb = rb.idx;
        ra.next<NA>(); rb.next<NB>();
      }
      TSTAMP(18);
      float st_rstd[2], st_mr[2];
      mbar_wait(bars + 8 * B_CS, 0);
#pragma unroll
      for (int r = 0; r < 2; r++) {
        const uint4 st = lds128(sb + OFF_XST + (rloc + 8 * r) * 16);
        st_rstd[r] = __uint_as_float(st.x); st_mr[r] = __uint_as_float(st.y); st_g[r] = __uint_as_float(st.z);
      }
      TSTAMP(19);
      wg_wait<0>();
      fence_regs(accM); fence_regs(accR);
      TSTAMP(3);
#define ACC(P_, G, I_) ((G) < 8 ? accM[(P_) * 32 + ((G) & 7) * 4 + (I_)] : accR[(P_) * 8 + ((G) & 1) * 4 + (I_)])
      {
        uint32_t hv[2][10];
        const GeluC g0 = gelu_consts(st_rstd[0], 1.f), g1 = gelu_consts(st_rstd[1], 1.f);
#pragma unroll
        for (int g = 0; g < 10; g++) {
          const float2 cs = *reinterpret_cast<const float2*>(s_cs + 8 * g + 2 * t);
          const float v0 = gelu_s(fmaf(st_mr[0], cs.x, ACC(0, g, 0)), g0), v1 = gelu_s(fmaf(st_mr[0], cs.y, ACC(0, g, 1)), g0);
          const float v2 = gelu_s(fmaf(st_mr[1], cs.x, ACC(0, g, 2)), g1), v3 = gelu_s(fmaf(st_mr[1], cs.y, ACC(0, g, 3)), g1);
          hv[0][g] = pack_bf16(v0, v1); hv[1][g] = pack_bf16(v2, v3);
        }
        bar_sync(1, 256);
        stage_tile(sb + OFF_STG, hv);
        fence_async_smem();
        signal(B_SIGH);
      }
      TSTAMP(4);
      uint32_t kf[5][4], qf[5][4];
#pragma unroll
      for (int s = 0; s < 5; s++) {
        kf[s][0] = pack_bf16(ACC(2, 2 * s, 0), ACC(2, 2 * s, 1)); kf[s][1] = pack_bf16(ACC(2, 2 * s, 2), ACC(2, 2 * s, 3));
        kf[s][2] = pack_bf16(ACC(2, 2 * s + 1, 0), ACC(2, 2 * s + 1, 1)); kf[s][3] = pack_bf16(ACC(2, 2 * s + 1, 2), ACC(2, 2 * s + 1, 3));
        qf[s][0] = pack_bf16(ACC(1, 2 * s, 0), ACC(1, 2 * s, 1)); qf[s][1] = pack_bf16(ACC(1, 2 * s, 2), ACC(1, 2 * s, 3));
        qf[s][2] = pack_bf16(ACC(1, 2 * s + 1, 0), ACC(1, 2 * s + 1, 1)); qf[s][3] = pack_bf16(ACC(1, 2 * s + 1, 2), ACC(1, 2 * s + 1, 3));
      }
      float pk[40], pq[40];
      wg_fence();
#pragma unroll
      for (int s = 0; s < 5; s++) {
        if (s == 0) mma_rs80_k_z(pk, kf[s], make_desc(sb16, OFF_MISC, 16, 256, 3));
        else mma_rs80_k(pk, kf[s], make_desc(sb16, OFF_MISC + s * 2560, 16, 256, 3));
      }
      wg_commit();
#pragma unroll
      for (int s = 0; s < 5; s++) {
        if (s == 0) mma_rs80_k_z(pq, qf[s], make_desc(sb16, OFF_MISC, 16, 256, 3));
        else mma_rs80_k(pq, qf[s], make_desc(sb16, OFF_MISC + s * 2560, 16, 256, 3));
      }
      wg_commit();
      {
        const int mat = lane >> 3;
        const int tok = warp * 16 + (mat & 1) * 8 + (lane & 7);
        const uint32_t ones = (t == 0) ? 0x00003f80u : 0u;
        __syncwarp();
#pragma unroll
        for (int p = 0; p < 2; p++) {
          const uint32_t rowa = sb + OFF_A + p * SLOT_A + tok * 128;
#pragma unroll
          for (int gg = 0; gg < 3; gg++) {
            const int g0 = 5 * p + 2 * gg;
            uint32_t r0 = pack_bf16(ACC(3, g0, 0), ACC(3, g0, 1)), r1 = pack_bf16(ACC(3, g0, 2), ACC(3, g0, 3));
            uint32_t r2 = ones, r3 = ones;
            if (gg < 2) { r2 = pack_bf16(ACC(3, g0 + 1, 0), ACC(3, g0 + 1, 1)); r3 = pack_bf16(ACC(3, g0 + 1, 2), ACC(3, g0 + 1, 3)); }
            stsm4(rowa + (((2 * gg + (mat >> 1)) ^ (tok & 7)) << 4), r0, r1, r2, r3);
          }
        }
      }
#undef ACC
      wg_wait<1>();
      fence_regs(pk);
#pragma unroll
      for (int G = 0; G < 10; G++) {
        P[0][G] = pack_bf16(pk[4 * G], pk[4 * G + 1]); P[1][G] = pack_bf16(pk[4 * G + 2], pk[4 * G + 3]);
      }
      wg_wait<0>();
      fence_regs(pq);
#pragma unroll
      for (int G = 0; G < 10; G++) {
        qp[0][G] = pack_bf16(pq[4 * G], pq[4 * G + 1]); qp[1][G] = pack_bf16(pq[4 * G + 2], pq[4 * G + 3]);
      }
    }

    uint32_t fr[10][4];
    int pass;
    pass = gridDim.y;
#pragma unroll 1
    do {
    feature_map(P, fr);
    if (pass != 0) {
    {
      const int mat = lane >> 3;
      const int tok = warp * 16 + (mat & 1) * 8 + (lane & 7);
      const uint32_t base = sb + OFF_B + tok * 32 + (((mat >> 1) ^ ((tok >> 2) & 1)) << 4);
#pragma unroll
      for (int G = 0; G < 10; G++) stsm4(base + G * 4096, fr[G][0], fr[G][1], fr[G][2], fr[G][3]);
      fence_async_smem();
      bar_sync(1, 256);
      float kv[40];
      const uint32_t va = sb16 + ((OFF_A + wg * SLOT_A) >> 4), vb = sb16 + ((OFF_B + wg * 20480) >> 4);
      wg_fence();
#pragma unroll
      for (int ks = 0; ks < 8; ks++) {
        if (ks == 0) mma_ss80_tt_z(kv, make_desc(va, 0, 16, 1024, 1), make_desc(vb, 0, 4096, 256, 3));
        else mma_ss80_tt(kv, make_desc(va, ks * 2048, 16, 1024, 1), make_desc(vb, ks * 512, 4096, 256, 3));
      }
      wg_commit();
      uint32_t xv[2][10];
      {
        mbar_wait(bars + 8 * B_XR, 0);
        const uint32_t xa = sb + OFF_B + (warp / 3) * SLOT_B + SPARE + (warp % 3) * 2560 + (lane >> 2) * 160 + t * 4;
#pragma unroll
        for (int g = 0; g < 10; g++) { xv[0][g] = lds32(xa + g * 16); xv[1][g] = lds32(xa + 1280 + g * 16); }
      }
      float acc[80];
      wg_wait<0>();
      release(emptyA); release(emptyA + 8); releaseB(emptyB); release(bars + 8 * B_PEER2);
      TSTAMP(5);
      mbar_wait(fullA + 8 * 2, 0);
      mbar_wait(fullB + 8 * 1, 1);
      TSTAMP(6);
      wg_fence();
#pragma unroll
      for (int kk = 0; kk < 4; kk++) {
        const uint64_t da = make_desc(sb16 + wg * 512, OFF_A + 2 * SLOT_A + kk * 32, 16, 1024, 1);
        const uint64_t db = make_desc(sb16, OFF_B + SLOT_B + kk * 1024, 4096, 512, 2);
        if (kk == 0) mma_ss160_z(acc, da, db); else mma_ss160(acc, da, db);
      }
      wg_commit();
      ra.next<NA>();
      wg_wait<1>();
      fence_regs(kv);
      TSTAMP(31);
      const uint32_t dst = sb + OFF_MISC + wg * (KV_PAIR * 4);
      const int m0 = (warp & 3) * 16 + (lane >> 2);
#pragma unroll
      for (int r = 0; r < 2; r++) {
        const int m = m0 + 8 * r;
        const bool hi = m >= 20;
        uint32_t v[10];
#pragma unroll
        for (int G = 0; G < 10; G++) v[G] = __float_as_uint(hi ? kv[4 * G + 2 * r + 1] : kv[4 * G + 2 * r]);
        const uint32_t p = dst + 4 * (m < 40 ? m * 48 + t * 12 : 1920 + t * 24 + 12);
        if (m <= 40) {
          sts128(p, make_uint4(v[0], v[1], v[2], v[3])); sts128(p + 16, make_uint4(v[4], v[5], v[6], v[7]));
          sts128(p + 32, make_uint4(v[8], v[9], 0u, 0u));
        }
      }
      if (m0 == 32) {
        const uint32_t p = dst + 4 * (1920 + t * 24);
        sts128(p, make_uint4(__float_as_uint(kv[2]), __float_as_uint(kv[6]), __float_as_uint(kv[10]), __float_as_uint(kv[14])));
        sts128(p + 16, make_uint4(__float_as_uint(kv[18]), __float_as_uint(kv[22]), __float_as_uint(kv[26]), __float_as_uint(kv[30])));
        sts128(p + 32, make_uint4(__float_as_uint(kv[34]), __float_as_uint(kv[38]), 0u, 0u));
      }
      signal(B_SIGKV);
      uint32_t pa = 2, pb = 1;
#pragma unroll 1
      for (int k = 1; k < 5; k++) {
        mbar_wait(fullA + 8 * ra.idx, ra.phase);
        if ((k & 1) == 0) mbar_wait(fullB + 8 * rb.idx, rb.phase);
        const uint32_t a0 = sb16 + ((OFF_A + ra.idx * SLOT_A + wg * 8192) >> 4);
        const uint32_t b0 = sb16 + ((OFF_B + rb.idx * SLOT_B + (k & 1) * 20480) >> 4);
        wg_fence();
#pragma unroll
        for (int kk = 0; kk < 4; kk++) {
          mma_ss160(acc, make_desc(a0, kk * 32, 16, 1024, 1), make_desc(b0, kk * 1024, 4096, 512, 2));
          if (kk == 0) {
            wg_commit();
            wg_wait<1>();
            release(emptyA + 8 * pa);
            if ((k & 1) == 0) releaseB(emptyB + 8 * pb);
          }
        }
        wg_commit();
        pa = ra.idx; pb = rb.idx;
        ra.next<NA>();
        if ((k & 1) || k == 4) rb.next<NB>();
      }
      mbar_wait(bars + 8 * B_PEER2, 0);
      wg_wait<0>();
      fence_regs(acc);
      release(emptyA + 8 * pa);
      TSTAMP(7);
      {
        uint32_t sn[20];
        if (rank) {
#pragma unroll
          for (int e = 0; e < 20; e++) sn[e] = pack_bf16(acc[2 * e], acc[2 * e + 1]);
#pragma unroll
          for (int e = 0; e < 40; e++) acc[e] = acc[40 + e];
        } else {
#pragma unroll
          for (int e = 0; e < 20; e++) sn[e] = pack_bf16(acc[40 + 2 * e], acc[41 + 2 * e]);
        }
        const uint32_t peer = map_peer(sb, rank ^ 1);
#pragma unroll
        for (int q = 0; q < 5; q++)
          st_async16(peer + OFF_B + 20480 + tid * 16 + q * 4096, sn[4 * q], sn[4 * q + 1], sn[4 * q + 2], sn[4 * q + 3],
                     peer + OFF_BAR + 8 * (B_DSR + 8 + wg));
#pragma unroll
        for (int g = 0; g < 10; g++) {
          acc[4 * g] += bf_lo(xv[0][g]); acc[4 * g + 1] += bf_hi(xv[0][g]);
          acc[4 * g + 2] += bf_lo(xv[1][g]); acc[4 * g + 3] += bf_hi(xv[1][g]);
        }
        bar_sync(1, 256);
        mbar_wait(bars + 8 * (B_DSR + 8 + wg), 0);
#pragma unroll
        for (int q = 0; q < 5; q++) {
          const uint4 v = lds128(sb + OFF_B + 20480 + tid * 16 + q * 4096);
          xv[0][2 * q] = pack_bf16(acc[8 * q] + bf_lo(v.x), acc[8 * q + 1] + bf_hi(v.x));
          xv[1][2 * q] = pack_bf16(acc[8 * q + 2] + bf_lo(v.y), acc[8 * q + 3] + bf_hi(v.y));
          xv[0][2 * q + 1] = pack_bf16(acc[8 * q + 4] + bf_lo(v.z), acc[8 * q + 5] + bf_hi(v.z));
          xv[1][2 * q + 1] = pack_bf16(acc[8 * q + 6] + bf_lo(v.w), acc[8 * q + 7] + bf_hi(v.w));
        }
        releaseB(emptyB + 8 * pb);
      }
      TSTAMP(16);
      stage_tile(sb + OFF_STG, xv);
      fence_async_smem();
      signal(B_SIGX1);
      TSTAMP(17);
#pragma unroll
      for (int r = 0; r < 2; r++) {
        float s = 0.f;
#pragma unroll
        for (int g = 0; g < 10; g++) {
          acc[4 * g + 2 * r] = bf_lo(xv[r][g]); acc[4 * g + 2 * r + 1] = bf_hi(xv[r][g]);
          s += acc[4 * g + 2 * r] + acc[4 * g + 2 * r + 1];
        }
        s += __shfl_xor_sync(0xffffffffu, s, 1); s += __shfl_xor_sync(0xffffffffu, s, 2);
        const float mu = s * (1.f / 80.f);
        float q = 0.f;
#pragma unroll
        for (int g = 0; g < 10; g++) {
          const float d0 = acc[4 * g + 2 * r] - mu, d1 = acc[4 * g + 2 * r + 1] - mu;
          q = fmaf(d0, d0, q); q = fmaf(d1, d1, q);
        }
        q += __shfl_xor_sync(0xffffffffu, q, 1); q += __shfl_xor_sync(0xffffffffu, q, 2);
        if (t == 0) g_st1[(128 * i + rloc + 8 * r) * 8 + j] = make_float2(mu, q);
      }
    }
    TSTAMP(8);
#pragma unroll
    for (int G = 0; G < 10; G++) { P[0][G] = qp[0][G]; P[1][G] = qp[1][G]; }
    }
    asm volatile("" : "+r"(pass));
    } while (pass-- != 0);

    uint32_t of[5][4];
    {
      mbar_wait(bars + 8 * B_KV, 0);
      uint4 kvr[2][3];
#pragma unroll
      for (int u = 0; u < 2; u++) {
        const int it = tid + 256 * u, p = it / 192, rem = it - 192 * p, n = rem >> 2, tq = rem & 3;
        const uint32_t sp = sb + OFF_MISC + 4 * (p * KV_PAIR + (n < 40 ? n * 48 + tq * 12 : 1920 + tq * 24 + (n & 1) * 12));
        if (it < 384) { kvr[u][0] = lds128(sp); kvr[u][1] = lds128(sp + 16); kvr[u][2] = lds128(sp + 32); }
      }
      bar_sync(1, 256);
#pragma unroll
      for (int u = 0; u < 2; u++) {
        const int it = tid + 256 * u, p = it / 192, rem = it - 192 * p, n = rem >> 2, tq = rem & 3;
        const int sh = (n < 40 ? (n >= 20) : (n & 1)) * 16;
        const uint32_t v[10] = {kvr[u][0].x, kvr[u][0].y, kvr[u][0].z, kvr[u][0].w, kvr[u][1].x, kvr[u][1].y, kvr[u][1].z, kvr[u][1].w, kvr[u][2].x, kvr[u][2].y};
        uint8_t* dst = sgen + OFF_MISC + p * 7680 + n * 32 + tq * 4;
        const int sw = ((n >> 2) & 1) << 4;
        if (it < 384) {
#pragma unroll
          for (int G = 0; G < 10; G++)
            *reinterpret_cast<uint32_t*>(dst + (G >> 1) * 1536 + (((G & 1) << 4) ^ sw)) = pack_bf16(__uint_as_float(v[G]), 0.f) << sh;
        }
      }
      fence_async_smem();
      bar_sync(1, 256);
      float o0[24], o1[24];
      wg_fence();
#pragma unroll
      for (int g = 0; g < 5; g++) {
        if (g == 0) mma_rs48_k_z(o0, fr[g], make_desc(sb16, OFF_MISC, 16, 256, 3));
        else mma_rs48_k(o0, fr[g], make_desc(sb16, OFF_MISC + g * 1536, 16, 256, 3));
      }
#pragma unroll
      for (int g = 0; g < 5; g++) {
        if (g == 0) mma_rs48_k_z(o1, fr[5], make_desc(sb16, OFF_MISC + 7680, 16, 256, 3));
        else mma_rs48_k(o1, fr[5 + g], make_desc(sb16, OFF_MISC + 7680 + g * 1536, 16, 256, 3));
      }
      wg_commit();
      wg_wait<0>();
      fence_regs(o0); fence_regs(o1);
      signal(B_MFREE);
#pragma unroll
      for (int r = 0; r < 2; r++) {
        const float a0 = __fdividef(st_g[r], o0[20 + 2 * r] + 1e-6f), a1 = __fdividef(st_g[r], o0[21 + 2 * r] + 1e-6f);
        const float b0 = __fdividef(st_g[r], o1[20 + 2 * r] + 1e-6f), b1 = __fdividef(st_g[r], o1[21 + 2 * r] + 1e-6f);
        const float am = t < 2 ? a0 : a1, bm = t < 2 ? b0 : b1;
#pragma unroll
        for (int g = 0; g < 5; g++) {
          const float sa = g < 2 ? a0 : (g == 2 ? am : a1), sb2 = g < 2 ? b0 : (g == 2 ? bm : b1);
          of[g >> 1][(g & 1) * 2 + r] = pack_bf16(o0[4 * g + 2 * r] * sa, o0[4 * g + 2 * r + 1] * sa);
          of[(5 + g) >> 1][((5 + g) & 1) * 2 + r] = pack_bf16(o1[4 * g + 2 * r] * sb2, o1[4 * g + 2 * r + 1] * sb2);
        }
      }
    }
    TSTAMP(9);

    uint32_t hf[12][4];
    float ac4[80];
    auto unit = [&](auto uc, uint32_t b0) {
      constexpr int u = decltype(uc)::value;
#pragma unroll
      for (int s = 0; s < (u ? 4 : 5); s++) {
        const uint64_t db = make_desc(b0, (u ? 5120 + 20480 * u : 0) + s * 1024, u ? 4096 : 5120, 512, 2);
        if (u == 0 && s == 0) mma_rs160_n_z(ac4, of[0], db);
        else if (u == 0) mma_rs160_n(ac4, of[s], db);
        else mma_rs160_n(ac4, hf[(4 * u + 8 + s) % 12], db);
      }
      wg_commit();
    };
    {
      float acc[96];
      uint32_t pa = 0, pb = 0;
#pragma unroll 1
      for (int k = 0; k < 10; k++) {
        mbar_wait(fullA + 8 * ra.idx, ra.phase);
        if (tid == 0) TRACE(52 + k);
        if ((k & 1) == 0) mbar_wait(fullB + 8 * rb.idx, rb.phase);
        if (tid == 0) TRACE(84 + k);
        if (k == 0) TSTAMP(10);
        const uint32_t a0 = sb16 + ((OFF_A + ra.idx * SLOT_A + wg * 8192) >> 4);
        const uint32_t b0 = sb16 + ((OFF_B + rb.idx * SLOT_B + (k & 1) * 24576) >> 4);
        wg_fence();
#pragma unroll
        for (int kk = 0; kk < 4; kk++) {
          if (kk == 0) mma_ss192_p(acc, make_desc(a0, 0, 16, 1024, 1), make_desc(b0, 0, 8192, 1024, 1), k);
          else mma_ss192(acc, make_desc(a0, kk * 32, 16, 1024, 1), make_desc(b0, kk * 2048, 8192, 1024, 1));
          if (kk == 0) {
            wg_commit();
            if (k > 0) {
              wg_wait<1>();
              release(emptyA + 8 * pa);
              if ((k & 1) == 0) releaseB(emptyB + 8 * pb);
            }
          }
        }
        wg_commit();
        pa = ra.idx; pb = rb.idx;
        ra.next<NA>();
        if (k & 1) rb.next<NB>();
      }
      float rs[2], mm[2];
      mbar_wait(bars + 8 * B_ST1, 0);
#pragma unroll
      for (int r = 0; r < 2; r++) {
        const uint4 su = lds128(sb + OFF_MISC + (rloc + 8 * r) * 64 + t * 16);
        const float m0 = __uint_as_float(su.x), m1 = __uint_as_float(su.z);
        float mu = m0 + m1;
        mu += __shfl_xor_sync(0xffffffffu, mu, 1); mu += __shfl_xor_sync(0xffffffffu, mu, 2);
        mu *= 0.125f;
        const float d0 = m0 - mu, d1 = m1 - mu;
        float q = __uint_as_float(su.y) + __uint_as_float(su.w) + 80.f * (d0 * d0 + d1 * d1);
        q += __shfl_xor_sync(0xffffffffu, q, 1); q += __shfl_xor_sync(0xffffffffu, q, 2);
        rs[r] = rsqrtf(q * (1.f / D_) + 1e-5f);
        mm[r] = -mu;
      }
      mbar_wait(bars + 8 * B_FULL4, 0);
      wg_fence();
      unit(IntC<0>{}, sb16);
      wg_wait<1>();
      fence_regs(acc);
      releaseB(emptyB + 8 * pb);
      release(bars + 8 * B_PEER);
      TSTAMP(11);
      const GeluC g0 = gelu_consts(rs[0], 1.f - st_g[0]), g1 = gelu_consts(rs[1], 1.f - st_g[1]);
#pragma unroll
      for (int g = 0; g < 24; g++) {
        const float2 cs = *reinterpret_cast<const float2*>(s_cs + 80 + 8 * g + 2 * t);
        const float v0 = gelu_s(fmaf(mm[0], cs.x, acc[4 * g]), g0), v1 = gelu_s(fmaf(mm[0], cs.y, acc[4 * g + 1]), g0);
        const float v2 = gelu_s(fmaf(mm[1], cs.x, acc[4 * g + 2]), g1), v3 = gelu_s(fmaf(mm[1], cs.y, acc[4 * g + 3]), g1);
        hf[g >> 1][(g & 1) * 2] = pack_bf16(v0, v1);
        hf[g >> 1][(g & 1) * 2 + 1] = pack_bf16(v2, v3);
        if (g == 7) { wg_fence(); unit(IntC<1>{}, sb16); }
        if (g == 15) { mbar_wait(bars + 8 * (B_FULL4 + 1), 0); wg_fence(); unit(IntC<2>{}, sb16); }
        if (g == 23) { wg_wait<1>(); signal(B_EMPTY4); wg_fence(); unit(IntC<3>{}, sb16); }
      }
    }
    TSTAMP(12);

    {
      float kp[40];
      uint32_t sn[20], kb[20];
      const uint32_t peer = map_peer(sb, rank ^ 1);
      const uint32_t tag = lds32(sb + OFF_BAR + 8 * NBAR);
      auto add8 = [&](int q, const uint4 v) {
        float* d = &kp[8 * q];
        d[0] += bf_lo(v.x); d[1] += bf_hi(v.x); d[2] += bf_lo(v.y); d[3] += bf_hi(v.y);
        d[4] += bf_lo(v.z); d[5] += bf_hi(v.z); d[6] += bf_lo(v.w); d[7] += bf_hi(v.w);
      };
      auto send = [&](int c) {
        const uint32_t dso = peer + OFF_DS + (c & 1) * 20480 + tid * 16, dsb = peer + OFF_BAR + 8 * (B_DSR + 2 * c + wg);
#pragma unroll
        for (int q = 0; q < 5; q++) st_async16(dso + q * 4096, sn[4 * q], sn[4 * q + 1], sn[4 * q + 2], sn[4 * q + 3], dsb);
      };
      mbar_wait(bars + 8 * B_PEER, 0);
      uint4* gdst = g_part + (size_t)i * 8 * 3840 + tid;
#pragma unroll 1
      for (int c = 0; c < 3; c++) {
        const uint32_t b0 = sb16 + ((c & 1) ? 0 : SET4 >> 4), bc = bars + 16 * c;
        mbar_wait(bc + 8 * (B_FULL4 + 2), 0);
        wg_wait<0>();
        fence_regs(ac4);
        if (rank) {
#pragma unroll
          for (int e = 0; e < 20; e++) { sn[e] = pack_bf16(ac4[2 * e], ac4[2 * e + 1]); kb[e] = pack_bf16(ac4[40 + 2 * e], ac4[41 + 2 * e]); }
        } else {
#pragma unroll
          for (int e = 0; e < 20; e++) { kb[e] = pack_bf16(ac4[2 * e], ac4[2 * e + 1]); sn[e] = pack_bf16(ac4[40 + 2 * e], ac4[41 + 2 * e]); }
        }
#pragma unroll
        for (int e = 0; e < 20; e++) asm volatile("" : "+r"(sn[e]), "+r"(kb[e]));
        if (c == 0 && wg == 1) bar_sync(2, 256);
        wg_fence();
        unit(IntC<0>{}, b0);
        if (lane == 0) mbar_arrive(bc + 8 * (B_EMPTY4 + 1));
        send(c);
        unit(IntC<1>{}, b0);
        if (c == 0 && wg == 0) bar_arrive(2, 256);
        {
          mbar_wait(bc + 8 * (B_DSR + wg), 0);
          uint4* dst = gdst + (((j + 2 * c + 2) & 7) * 3 + c) * 1280;
#pragma unroll
          for (int q = 0; q < 5; q++) {
            const uint4 v = lds128(sb + OFF_DS + (c & 1) * 20480 + tid * 16 + q * 4096);
            st_relaxed16(dst + q * 256, (add_bf2(v.x, kb[4 * q]) & ~1u) | tag, add_bf2(v.y, kb[4 * q + 1]),
                         add_bf2(v.z, kb[4 * q + 2]), add_bf2(v.w, kb[4 * q + 3]));
          }
        }
        mbar_wait(bc + 8 * (B_FULL4 + 3), 0);
        wg_fence();
        unit(IntC<2>{}, b0);
        wg_wait<1>();
        if (lane == 0) mbar_arrive(bc + 8 * (B_EMPTY4 + 2));
        unit(IntC<3>{}, b0);
      }
      auto partial = [&](int c, uint4 (&v)[5]) {
        mbar_wait(bars + 8 * (B_RDY + c), 0);
        uint32_t bad = 0;
#pragma unroll
        for (int q = 0; q < 5; q++) { v[q] = lds128(sb + (c ? 25600 + 20480 * c : 0) + tid * 16 + q * 4096); bad |= v[q].x ^ tag; }
#pragma unroll 1
        for (uint32_t n = 0; (bad & 1u) && n < (WAIT_LIMIT >> 2); n++) {
          bad = 0;
#pragma unroll
          for (int q = 0; q < 5; q++) { v[q] = ld_relaxed16(gdst + (j * 3 + c) * 1280 + q * 256); bad |= v[q].x ^ tag; }
        }
      };
      uint4 pa4[5], pb4[5];
      partial(0, pa4);
      wg_wait<0>();
      fence_regs(ac4);
      if (rank) {
#pragma unroll
        for (int e = 0; e < 20; e++) sn[e] = pack_bf16(ac4[2 * e], ac4[2 * e + 1]);
#pragma unroll
        for (int e = 0; e < 40; e++) kp[e] = ac4[40 + e];
      } else {
#pragma unroll
        for (int e = 0; e < 20; e++) sn[e] = pack_bf16(ac4[40 + 2 * e], ac4[41 + 2 * e]);
#pragma unroll
        for (int e = 0; e < 40; e++) kp[e] = ac4[e];
      }
      send(3);
      TSTAMP(13);
      {
        mbar_wait(bars + 8 * B_XR, 1);
        const float w0 = 1.f - st_g[0], w1s = 1.f - st_g[1];
        const uint32_t xa = sb + OFF_OUT + rloc * 160 + t * 4;
#pragma unroll
        for (int g = 0; g < 10; g++) {
          const uint32_t x0 = lds32(xa + g * 16), x1 = lds32(xa + 1280 + g * 16);
          kp[4 * g] = fmaf(w0, bf_lo(x0), kp[4 * g]); kp[4 * g + 1] = fmaf(w0, bf_hi(x0), kp[4 * g + 1]);
          kp[4 * g + 2] = fmaf(w1s, bf_lo(x1), kp[4 * g + 2]); kp[4 * g + 3] = fmaf(w1s, bf_hi(x1), kp[4 * g + 3]);
        }
      }
      partial(1, pb4);
#pragma unroll
      for (int q = 0; q < 5; q++)
        pa4[q] = make_uint4(add_bf2(pa4[q].x, pb4[q].x), add_bf2(pa4[q].y, pb4[q].y), add_bf2(pa4[q].z, pb4[q].z), add_bf2(pa4[q].w, pb4[q].w));
#pragma unroll
      for (int q = 0; q < 5; q++) add8(q, pa4[q]);
      partial(2, pb4);
      mbar_wait(bars + 8 * (B_DSR + 6 + wg), 0);
      TSTAMP(14);
#pragma unroll
      for (int q = 0; q < 5; q++) {
        const uint4 c = pb4[q], d = lds128(sb + OFF_DS + 20480 + tid * 16 + q * 4096);
        add8(q, make_uint4(add_bf2(c.x, d.x), add_bf2(c.y, d.y), add_bf2(c.z, d.z), add_bf2(c.w, d.w)));
      }
      __syncwarp();
      uint32_t ov[2][10];
#pragma unroll
      for (int g = 0; g < 10; g++) { ov[0][g] = pack_bf16(kp[4 * g], kp[4 * g + 1]); ov[1][g] = pack_bf16(kp[4 * g + 2], kp[4 * g + 3]); }
      stage_tile(sb + OFF_OUT, ov);
      __syncwarp();
      __nv_bfloat16* dst = out + (size_t)(128 * i + 16 * warp) * D_ + 80 * j;
#pragma unroll
      for (int q = 0; q < 5; q++) {
        const int id = q * 32 + lane, r = id / 10;
        *reinterpret_cast<uint4*>(dst + r * (D_ - 80) + id * 8) = lds128(sb + OFF_OUT + warp * 2560 + id * 16);
      }
    }
    TSTAMP(15);
    if (tid == 0) asm volatile("red.relaxed.gpu.global.add.u32 [%0], 1;" ::"l"(g_flags + FL_DONE * 32) : "memory");
  }
}

namespace {
typedef CUresult (*EncodeFn)(CUtensorMap*, CUtensorMapDataType, cuuint32_t, void*, const cuuint64_t*, const cuuint64_t*,
                             const cuuint32_t*, const cuuint32_t*, CUtensorMapInterleave, CUtensorMapSwizzle,
                             CUtensorMapL2promotion, CUtensorMapFloatOOBfill);

void encode(EncodeFn fn, CUtensorMap* m, const void* ptr, int rank, const cuuint64_t* dims, const cuuint64_t* strides,
            const cuuint32_t* box, CUtensorMapSwizzle swz) {
  cuuint32_t es[5] = {1, 1, 1, 1, 1};
  fn(m, CU_TENSOR_MAP_DATA_TYPE_BFLOAT16, rank, const_cast<void*>(ptr), dims, strides, box, es, CU_TENSOR_MAP_INTERLEAVE_NONE,
     swz, CU_TENSOR_MAP_L2_PROMOTION_L2_128B, CU_TENSOR_MAP_FLOAT_OOB_FILL_NONE);
}
}

extern "C" void kernel_launch(void* const* d_in, const int* in_sizes, int n_in, void* d_out, int out_size) {
  (void)in_sizes; (void)n_in; (void)out_size;
  const __nv_bfloat16* x = (const __nv_bfloat16*)d_in[0];
  const __nv_bfloat16* wqkv = (const __nv_bfloat16*)d_in[1];
  const __nv_bfloat16* wphi = (const __nv_bfloat16*)d_in[2];
  const __nv_bfloat16* wo = (const __nv_bfloat16*)d_in[3];
  const __nv_bfloat16* w1 = (const __nv_bfloat16*)d_in[5];
  const __nv_bfloat16* w2 = (const __nv_bfloat16*)d_in[6];
  const __nv_bfloat16* w3 = (const __nv_bfloat16*)d_in[7];
  const __nv_bfloat16* w4 = (const __nv_bfloat16*)d_in[8];
  const __nv_bfloat16* gate_w = (const __nv_bfloat16*)d_in[9];

  static EncodeFn enc = nullptr;
  static void *pHs = nullptr, *pX1 = nullptr;
  if (!enc) {
    cudaDriverEntryPointQueryResult qr;
    cudaGetDriverEntryPoint("cuTensorMapEncodeTiled", (void**)&enc, cudaEnableDefault, &qr);
    cudaGetSymbolAddress(&pHs, g_Hs);
    cudaGetSymbolAddress(&pX1, g_X1);
    cudaFuncSetAttribute(fused_kernel, cudaFuncAttributeMaxDynamicSharedMemorySize, SMEM_BYTES);
  }
  Maps m;
  {
    cuuint64_t dims[2] = {D_, S_}, str[1] = {D_ * 2};
    cuuint32_t box[2] = {64, 128}, boxh[2] = {64, 64};
    encode(enc, &m.x, x, 2, dims, str, boxh, CU_TENSOR_MAP_SWIZZLE_128B);
    encode(enc, &m.hs, (const char*)pHs + 2 * D_ * 2, 2, dims, str, box, CU_TENSOR_MAP_SWIZZLE_128B);
    encode(enc, &m.x1, pX1, 2, dims, str, boxh, CU_TENSOR_MAP_SWIZZLE_128B);
    cuuint32_t boxr[2] = {80, 16}, boxs[2] = {80, 128};
    cuuint64_t dimsp[2] = {D_, S_ + 4};
    encode(enc, &m.st_h, pHs, 2, dimsp, str, boxs, CU_TENSOR_MAP_SWIZZLE_NONE);
    encode(enc, &m.st_x1, pX1, 2, dims, str, boxs, CU_TENSOR_MAP_SWIZZLE_NONE);
    encode(enc, &m.xr, x, 2, dims, str, boxr, CU_TENSOR_MAP_SWIZZLE_NONE);
  }
  {
    cuuint64_t dims[3] = {80, D_, 8}, str[2] = {D_ * 2, 160};
    cuuint32_t boxm[3] = {64, 64, 1}, boxr[3] = {16, 64, 1};
    encode(enc, &m.w1m, w1, 3, dims, str, boxm, CU_TENSOR_MAP_SWIZZLE_128B);
    encode(enc, &m.w1r, w1, 3, dims, str, boxr, CU_TENSOR_MAP_SWIZZLE_32B);
  }
  {
    cuuint64_t dims[4] = {80, D_, 3, 8}, str[3] = {3 * D_ * 2, D_ * 2, 160};
    cuuint32_t boxm[4] = {64, 64, 3, 1}, boxr[4] = {16, 64, 3, 1};
    encode(enc, &m.qm, wqkv, 4, dims, str, boxm, CU_TENSOR_MAP_SWIZZLE_128B);
    encode(enc, &m.qr, wqkv, 4, dims, str, boxr, CU_TENSOR_MAP_SWIZZLE_32B);
  }
  {
    cuuint64_t dims[3] = {32, D_, 20}, dims4[3] = {32, F_, 20}, str[2] = {D_ * 2, 64};
    cuuint32_t box4[3] = {32, 64, 5}, boxo[3] = {32, 80, 5};
    encode(enc, &m.w4, w4, 3, dims4, str, box4, CU_TENSOR_MAP_SWIZZLE_64B);
    encode(enc, &m.wo, wo, 3, dims, str, boxo, CU_TENSOR_MAP_SWIZZLE_64B);
    encode(enc, &m.w2, w2, 3, dims, str, box4, CU_TENSOR_MAP_SWIZZLE_64B);
  }
  {
    cuuint64_t dims[3] = {64, D_, 24}, str[2] = {F_ * 2, 128};
    cuuint32_t box[3] = {64, 64, 3};
    encode(enc, &m.w3, w3, 3, dims, str, box, CU_TENSOR_MAP_SWIZZLE_128B);
  }
  fused_kernel<<<NCTA + NSVC, 384, SMEM_BYTES, cudaStreamPerThread>>>(m, x, wqkv, wphi, w1, w2, w3, w4, wo, gate_w, (__nv_bfloat16*)d_out);
}
```

```cpp
#include <cuda_runtime.h>
#include <cuda_bf16.h>
#include <cuda.h>
#include <stdint.h>

namespace {

constexpr int S_ = 2048, D_ = 640, F_ = 1536;
constexpr int NCTA = 128, NSVC = 4;
constexpr int KV_PAIR = 40 * 48 + 96;
constexpr int KV_J = 2 * KV_PAIR;

constexpr int SLOT_B = 49152, NB = 3;
constexpr int SLOT_A = 16384, NA = 4;
constexpr int OFF_B = 0;
constexpr int OFF_A = OFF_B + NB * SLOT_B;
constexpr int OFF_STG = OFF_A + 2 * SLOT_A;
constexpr int OFF_MISC = OFF_A + NA * SLOT_A;
constexpr int OFF_XST = OFF_MISC + 13312;
constexpr int OFF_CS = OFF_MISC + 16384;
constexpr int OFF_BAR = OFF_CS + 1088;
constexpr int SMEM_BYTES = OFF_BAR + 512 + 512 + 128;
constexpr int B_FULLA = 0, B_FULLB = 4, B_CS = 7, B_XR = 8, B_KV = 9, B_ST1 = 10, B_HST = 11, B_FULL4 = 12  , B_RDY = 20  ,
              B_DSR = 23  , B_EMPTYB = 33  , B_SIGP = 36, B_SIGH = 37, B_SIGKV = 38, B_SIGX1 = 39, B_MFREE = 40,
              B_EMPTY4 = 41  , B_EMPTYA = 49  , B_PEER = 53, B_PEER2 = 54, B_X1P = 55  , NBAR = 56;
constexpr int SPARE = 40960;
constexpr int SET4 = 87040, OFF_DS = 2 * SET4, OFF_OUT = 20480;

constexpr int FL_DONE = 0, FL_H = 1  , FL_X1 = FL_H + 32, FL_KV = FL_X1 + 16, FL_CS = FL_KV + 8, FL_CS3 = FL_CS + 1, FL_ST = FL_CS3 + 1;
constexpr int FL_S1 = FL_ST + 16, FL_COUNT = FL_S1 + 16;

struct Maps {
  CUtensorMap x, w1m, w1r, qm, qr, hs, w2, x1, w3, w4, wo, xr, st_h, st_x1;
};

}

__device__ __align__(1024) __nv_bfloat16 g_Hs[(S_ + 4) * D_];
__device__ __align__(1024) __nv_bfloat16 g_X1[S_ * D_];
__device__ __align__(128) float g_acc[2][8 * KV_J];
__device__ __align__(128) float g_cs[2][D_ + F_];
__device__ __align__(128) uint4 g_wphi[8 * 800];
__device__ __align__(128) float4 g_xstat[S_];
__device__ __align__(128) float2 g_st1[S_ * 8];
__device__ __align__(128) uint4 g_part[16 * 8 * 3 * 1280];
__device__ __align__(128) unsigned g_flags[FL_COUNT * 32];
#define TSTAMP(n) do {} while (0)
#define TSTAMPX(n) do {} while (0)
#define TRACE(n) do {} while (0)
#define TRS(n) do {} while (0)

namespace {

__device__ __forceinline__ long long gtime() { long long t; asm volatile("mov.u64 %0, %%globaltimer;" : "=l"(t)); return t; }
__device__ __forceinline__ uint32_t smem_u32(const void* p) { return (uint32_t)__cvta_generic_to_shared(p); }
__device__ __forceinline__ void mbar_init(uint32_t bar, int cnt) {
  asm volatile("mbarrier.init.shared::cta.b64 [%0], %1;" ::"r"(bar), "r"(cnt) : "memory");
}
__device__ __forceinline__ void mbar_expect_tx(uint32_t bar, int bytes) {
  asm volatile("mbarrier.arrive.expect_tx.shared::cta.b64 _, [%0], %1;" ::"r"(bar), "r"(bytes) : "memory");
}
__device__ __forceinline__ void mbar_arrive_cta(uint32_t bar, uint32_t cta) {
  asm volatile("{\n.reg .b32 ra;\nmapa.shared::cluster.u32 ra, %0, %1;\nmbarrier.arrive.shared::cluster.b64 _, [ra];\n}"
               ::"r"(bar), "r"(cta) : "memory");
}
__device__ __forceinline__ uint32_t mbar_try(uint32_t bar, uint32_t parity) {
  uint32_t ok;
  asm volatile("{\n.reg .pred p;\nmbarrier.try_wait.parity.shared::cta.b64 p, [%1], %2;\nselp.u32 %0, 1, 0, p;\n}"
               : "=r"(ok) : "r"(bar), "r"(parity) : "memory");
  return ok;
}
constexpr uint32_t WAIT_LIMIT = 1u << 18;
__device__ __forceinline__ void mbar_wait(uint32_t bar, uint32_t parity) {
  uint32_t n = 0;
  while (!mbar_try(bar, parity) && ++n < WAIT_LIMIT) {}
}
__device__ __forceinline__ unsigned ld_acquire(const unsigned* p) {
  unsigned v;
  asm volatile("ld.acquire.gpu.global.u32 %0, [%1];" : "=r"(v) : "l"(p) : "memory");
  return v;
}
__device__ __forceinline__ void flag_wait(int idx, unsigned target) {
  const unsigned* p = g_flags + idx * 32;
  uint32_t n = 0;
  while ((int)(ld_acquire(p) - target) < 0 && ++n < (WAIT_LIMIT >> 2)) {}
}
__device__ __forceinline__ void flag_add(int idx) {
  asm volatile("red.release.gpu.global.add.u32 [%0], 1;" ::"l"(g_flags + idx * 32) : "memory");
}
__device__ __forceinline__ void flag_add_relaxed(int idx) {
  asm volatile("red.relaxed.gpu.global.add.u32 [%0], 1;" ::"l"(g_flags + idx * 32) : "memory");
}
__device__ __forceinline__ uint32_t mbar_test(uint32_t bar, uint32_t parity) {
  uint32_t ok;
  asm volatile("{\n.reg .pred p;\nmbarrier.test_wait.parity.shared::cta.b64 p, [%1], %2;\nselp.u32 %0, 1, 0, p;\n}"
               : "=r"(ok) : "r"(bar), "r"(parity) : "memory");
  return ok;
}
__device__ __forceinline__ uint32_t lds32(uint32_t a) {
  uint32_t v;
  asm volatile("ld.shared.u32 %0, [%1];" : "=r"(v) : "r"(a) : "memory");
  return v;
}
__device__ __forceinline__ void mbar_arrive(uint32_t bar) {
  asm volatile("mbarrier.arrive.shared::cta.b64 _, [%0];" ::"r"(bar) : "memory");
}
__device__ __forceinline__ void fence_async_glb() { asm volatile("fence.proxy.async.global;" ::: "memory"); }
__device__ __forceinline__ void fence_async_smem() { asm volatile("fence.proxy.async.shared::cta;" ::: "memory"); }
__device__ __forceinline__ void bar_sync(int id, int n) { asm volatile("bar.sync %0, %1;" ::"r"(id), "r"(n) : "memory"); }

__device__ __forceinline__ void tma2d(uint32_t dst, const CUtensorMap* m, uint32_t bar, int c0, int c1) {
  asm volatile("cp.async.bulk.tensor.2d.shared::cluster.global.mbarrier::complete_tx::bytes [%0], [%1, {%3, %4}], [%2];"
               ::"r"(dst), "l"(m), "r"(bar), "r"(c0), "r"(c1) : "memory");
}
__device__ __forceinline__ void tma2d_mc(uint32_t dst, const CUtensorMap* m, uint32_t bar, int c0, int c1) {
  asm volatile("cp.async.bulk.tensor.2d.shared::cluster.global.mbarrier::complete_tx::bytes.multicast::cluster"
               " [%0], [%1, {%3, %4}], [%2], %5;"
               ::"r"(dst), "l"(m), "r"(bar), "r"(c0), "r"(c1), "h"((uint16_t)3) : "memory");
}
__device__ __forceinline__ void tma3d(uint32_t dst, const CUtensorMap* m, uint32_t bar, int c0, int c1, int c2) {
  asm volatile("cp.async.bulk.tensor.3d.shared::cluster.global.mbarrier::complete_tx::bytes [%0], [%1, {%3, %4, %5}], [%2];"
               ::"r"(dst), "l"(m), "r"(bar), "r"(c0), "r"(c1), "r"(c2) : "memory");
}
__device__ __forceinline__ void tma4d(uint32_t dst, const CUtensorMap* m, uint32_t bar, int c0, int c1, int c2, int c3) {
  asm volatile("cp.async.bulk.tensor.4d.shared::cluster.global.mbarrier::complete_tx::bytes [%0], [%1, {%3, %4, %5, %6}], [%2];"
               ::"r"(dst), "l"(m), "r"(bar), "r"(c0), "r"(c1), "r"(c2), "r"(c3) : "memory");
}
__device__ __forceinline__ void tma2d_store(const CUtensorMap* m, uint32_t src, int c0, int c1) {
  asm volatile("cp.async.bulk.tensor.2d.global.shared::cta.bulk_group [%0, {%2, %3}], [%1];"
               ::"l"(m), "r"(src), "r"(c0), "r"(c1) : "memory");
}
__device__ __forceinline__ void bulk_store(void* dst, uint32_t src, uint32_t bytes) {
  asm volatile("cp.async.bulk.global.shared::cta.bulk_group [%0], [%1], %2;" ::"l"(dst), "r"(src), "r"(bytes) : "memory");
}
__device__ __forceinline__ void bulk_load(uint32_t dst, const void* src, uint32_t bytes, uint32_t bar) {
  asm volatile("cp.async.bulk.shared::cluster.global.mbarrier::complete_tx::bytes [%0], [%1], %2, [%3];"
               ::"r"(dst), "l"(src), "r"(bytes), "r"(bar) : "memory");
}
__device__ __forceinline__ void bulk_commit() { asm volatile("cp.async.bulk.commit_group;" ::: "memory"); }
template <int N> __device__ __forceinline__ void bulk_wait() { asm volatile("cp.async.bulk.wait_group %0;" ::"n"(N) : "memory"); }
__device__ __forceinline__ void bulk_wait_read() { asm volatile("cp.async.bulk.wait_group.read 0;" ::: "memory"); }
__device__ __forceinline__ void bar_arrive(int id, int n) { asm volatile("bar.arrive %0, %1;" ::"r"(id), "r"(n) : "memory"); }
__device__ __forceinline__ uint4 lds128(uint32_t a) {
  uint4 v;
  asm volatile("ld.shared.v4.u32 {%0, %1, %2, %3}, [%4];" : "=r"(v.x), "=r"(v.y), "=r"(v.z), "=r"(v.w) : "r"(a) : "memory");
  return v;
}
__device__ __forceinline__ void sts128(uint32_t a, uint4 v) {
  asm volatile("st.shared.v4.u32 [%0], {%1, %2, %3, %4};" ::"r"(a), "r"(v.x), "r"(v.y), "r"(v.z), "r"(v.w) : "memory");
}
__device__ __forceinline__ uint4 ld_relaxed16(const uint4* p) {
  uint4 v;
  asm volatile("ld.relaxed.gpu.global.v4.u32 {%0, %1, %2, %3}, [%4];" : "=r"(v.x), "=r"(v.y), "=r"(v.z), "=r"(v.w) : "l"(p) : "memory");
  return v;
}
__device__ __forceinline__ void st_relaxed16(uint4* p, uint32_t a, uint32_t b, uint32_t c, uint32_t d) {
  asm volatile("st.relaxed.gpu.global.v4.u32 [%0], {%1, %2, %3, %4};" ::"l"(p), "r"(a), "r"(b), "r"(c), "r"(d) : "memory");
}
__device__ __forceinline__ uint32_t map_peer(uint32_t addr, uint32_t cta) {
  uint32_t r;
  asm("mapa.shared::cluster.u32 %0, %1, %2;" : "=r"(r) : "r"(addr), "r"(cta));
  return r;
}
__device__ __forceinline__ void st_async16(uint32_t addr, uint32_t a, uint32_t b, uint32_t c, uint32_t d, uint32_t bar) {
  asm volatile("st.async.weak.shared::cluster.mbarrier::complete_tx::bytes.v4.b32 [%0], {%1, %2, %3, %4}, [%5];"
               ::"r"(addr), "r"(a), "r"(b), "r"(c), "r"(d), "r"(bar) : "memory");
}
__device__ __forceinline__ void l2_prefetch(const void* p, uint32_t bytes) {
  asm volatile("cp.async.bulk.prefetch.L2.global [%0], %1;" ::"l"(p), "r"(bytes) : "memory");
}
__device__ __forceinline__ void prefetch_tmap(const CUtensorMap* m) {
  asm volatile("prefetch.tensormap [%0];" ::"l"(m) : "memory");
}
__device__ __forceinline__ uint64_t make_desc(uint32_t a16, uint32_t off, uint32_t lbo, uint32_t sbo, uint32_t swz) {
  const uint32_t lo = a16 + ((off >> 4) + ((lbo >> 4) << 16)), hi = (sbo >> 4) | (swz << 30);
  uint64_t d;
  asm("mov.b64 %0, {%1, %2};" : "=l"(d) : "r"(lo), "r"(hi));
  return d;
}
__device__ __forceinline__ void wg_fence() { asm volatile("wgmma.fence.sync.aligned;" ::: "memory"); }
__device__ __forceinline__ void wg_commit() { asm volatile("wgmma.commit_group.sync.aligned;" ::: "memory"); }
template <int N> __device__ __forceinline__ void wg_wait() { asm volatile("wgmma.wait_group.sync.aligned %0;" ::"n"(N) : "memory"); }
template <int N> __device__ __forceinline__ void fence_regs(float (&d)[N]) {
#pragma unroll
  for (int i = 0; i < N; i++) asm volatile("" : "+f"(d[i])::"memory");
}
template <int N> __device__ __forceinline__ void zero_regs(float (&d)[N]) {
#pragma unroll
  for (int i = 0; i < N; i++) d[i] = 0.f;
}
__device__ __forceinline__ uint32_t pack_bf16(float lo, float hi) {
  uint32_t r;
  asm("cvt.rn.bf16x2.f32 %0, %1, %2;" : "=r"(r) : "f"(hi), "f"(lo));
  return r;
}
__device__ __forceinline__ float bf_lo(uint32_t v) { return __uint_as_float(v << 16); }
__device__ __forceinline__ float bf_hi(uint32_t v) { return __uint_as_float(v & 0xffff0000u); }
__device__ __forceinline__ uint32_t max_bf2(uint32_t a, uint32_t b) {
  uint32_t r; asm("max.bf16x2 %0, %1, %2;" : "=r"(r) : "r"(a), "r"(b)); return r;
}
__device__ __forceinline__ uint32_t min_bf2(uint32_t a, uint32_t b) {
  uint32_t r; asm("min.bf16x2 %0, %1, %2;" : "=r"(r) : "r"(a), "r"(b)); return r;
}
__device__ __forceinline__ uint32_t add_bf2(uint32_t a, uint32_t b) {
  uint32_t r; asm("add.rn.bf16x2 %0, %1, %2;" : "=r"(r) : "r"(a), "r"(b)); return r;
}
__device__ __forceinline__ float ex2(float x) { float r; asm("ex2.approx.ftz.f32 %0, %1;" : "=f"(r) : "f"(x)); return r; }
__device__ __forceinline__ float rcp(float x) { float r; asm("rcp.approx.ftz.f32 %0, %1;" : "=f"(r) : "f"(x)); return r; }
__device__ __forceinline__ float tanh_ap(float x) { float r; asm("tanh.approx.f32 %0, %1;" : "=f"(r) : "f"(x)); return r; }
struct GeluC { float c0, c1, ch; };
__device__ __forceinline__ GeluC gelu_consts(float rstd, float scale) {
  return GeluC{0.7978845608f * rstd, 0.0356774081f * rstd * rstd * rstd, 0.5f * scale * rstd};
}
__device__ __forceinline__ float gelu_s(float y, const GeluC& c) {
  const float u = y * fmaf(y * y, c.c1, c.c0);
  const float hx = y * c.ch;
  return fmaf(hx, tanh_ap(u), hx);
}
__device__ __forceinline__ void stsm4(uint32_t addr, uint32_t r0, uint32_t r1, uint32_t r2, uint32_t r3) {
  asm volatile("stmatrix.sync.aligned.m8n8.x4.shared.b16 [%0], {%1, %2, %3, %4};"
               ::"r"(addr), "r"(r0), "r"(r1), "r"(r2), "r"(r3) : "memory");
}

__device__ __forceinline__ void red_add4(float* p, float a, float b, float c, float d) {
  asm volatile("red.global.add.v4.f32 [%0], {%1, %2, %3, %4};" ::"l"(p), "f"(a), "f"(b), "f"(c), "f"(d) : "memory");
}

__device__ __forceinline__ void mma_ss256(float (&d)[128], uint64_t descA, uint64_t descB) {
  asm volatile("wgmma.mma_async.sync.aligned.m64n256k16.f32.bf16.bf16 {"
      "%0, %1, %2, %3, %4, %5, %6, %7, %8, %9, %10, %11, %12, %13, %14, %15, "
      "%16, %17, %18, %19, %20, %21, %22, %23, %24, %25, %26, %27, %28, %29, %30, %31, "
      "%32, %33, %34, %35, %36, %37, %38, %39, %40, %41, %42, %43, %44, %45, %46, %47, "
      "%48, %49, %50, %51, %52, %53, %54, %55, %56, %57, %58, %59, %60, %61, %62, %63, "
      "%64, %65, %66, %67, %68, %69, %70, %71, %72, %73, %74, %75, %76, %77, %78, %79, "
      "%80, %81, %82, %83, %84, %85, %86, %87, %88, %89, %90, %91, %92, %93, %94, %95, "
      "%96, %97, %98, %99, %100, %101, %102, %103, %104, %105, %106, %107, %108, %109, %110, %111, "
      "%112, %113, %114, %115, %116, %117, %118, %119, %120, %121, %122, %123, %124, %125, %126, %127"
      "}, %128, %129, 1, 1, 1, 0, 1;\n"
      : "+f"(d[0]), "+f"(d[1]), "+f"(d[2]), "+f"(d[3]), "+f"(d[4]), "+f"(d[5]), "+f"(d[6]), "+f"(d[7]),
        "+f"(d[8]), "+f"(d[9]), "+f"(d[10]), "+f"(d[11]), "+f"(d[12]), "+f"(d[13]), "+f"(d[14]), "+f"(d[15]),
        "+f"(d[16]), "+f"(d[17]), "+f"(d[18]), "+f"(d[19]), "+f"(d[20]), "+f"(d[21]), "+f"(d[22]), "+f"(d[23]),
        "+f"(d[24]), "+f"(d[25]), "+f"(d[26]), "+f"(d[27]), "+f"(d[28]), "+f"(d[29]), "+f"(d[30]), "+f"(d[31]),
        "+f"(d[32]), "+f"(d[33]), "+f"(d[34]), "+f"(d[35]), "+f"(d[36]), "+f"(d[37]), "+f"(d[38]), "+f"(d[39]),
        "+f"(d[40]), "+f"(d[41]), "+f"(d[42]), "+f"(d[43]), "+f"(d[44]), "+f"(d[45]), "+f"(d[46]), "+f"(d[47]),
        "+f"(d[48]), "+f"(d[49]), "+f"(d[50]), "+f"(d[51]), "+f"(d[52]), "+f"(d[53]), "+f"(d[54]), "+f"(d[55]),
        "+f"(d[56]), "+f"(d[57]), "+f"(d[58]), "+f"(d[59]), "+f"(d[60]), "+f"(d[61]), "+f"(d[62]), "+f"(d[63]),
        "+f"(d[64]), "+f"(d[65]), "+f"(d[66]), "+f"(d[67]), "+f"(d[68]), "+f"(d[69]), "+f"(d[70]), "+f"(d[71]),
        "+f"(d[72]), "+f"(d[73]), "+f"(d[74]), "+f"(d[75]), "+f"(d[76]), "+f"(d[77]), "+f"(d[78]), "+f"(d[79]),
        "+f"(d[80]), "+f"(d[81]), "+f"(d[82]), "+f"(d[83]), "+f"(d[84]), "+f"(d[85]), "+f"(d[86]), "+f"(d[87]),
        "+f"(d[88]), "+f"(d[89]), "+f"(d[90]), "+f"(d[91]), "+f"(d[92]), "+f"(d[93]), "+f"(d[94]), "+f"(d[95]),
        "+f"(d[96]), "+f"(d[97]), "+f"(d[98]), "+f"(d[99]), "+f"(d[100]), "+f"(d[101]), "+f"(d[102]), "+f"(d[103]),
        "+f"(d[104]), "+f"(d[105]), "+f"(d[106]), "+f"(d[107]), "+f"(d[108]), "+f"(d[109]), "+f"(d[110]), "+f"(d[111]),
        "+f"(d[112]), "+f"(d[113]), "+f"(d[114]), "+f"(d[115]), "+f"(d[116]), "+f"(d[117]), "+f"(d[118]), "+f"(d[119]),
        "+f"(d[120]), "+f"(d[121]), "+f"(d[122]), "+f"(d[123]), "+f"(d[124]), "+f"(d[125]), "+f"(d[126]), "+f"(d[127])
      : "l"(descA), "l"(descB));
}
__device__ __forceinline__ void mma_ss256_p(float (&d)[128], uint64_t descA, uint64_t descB, int acc) {
  asm volatile("{\n.reg .pred p;\nsetp.ne.b32 p, %130, 0;\n"
      "wgmma.mma_async.sync.aligned.m64n256k16.f32.bf16.bf16 {"
      "%0, %1, %2, %3, %4, %5, %6, %7, %8, %9, %10, %11, %12, %13, %14, %15, "
      "%16, %17, %18, %19, %20, %21, %22, %23, %24, %25, %26, %27, %28, %29, %30, %31, "
      "%32, %33, %34, %35, %36, %37, %38, %39, %40, %41, %42, %43, %44, %45, %46, %47, "
      "%48, %49, %50, %51, %52, %53, %54, %55, %56, %57, %58, %59, %60, %61, %62, %63, "
      "%64, %65, %66, %67, %68, %69, %70, %71, %72, %73, %74, %75, %76, %77, %78, %79, "
      "%80, %81, %82, %83, %84, %85, %86, %87, %88, %89, %90, %91, %92, %93, %94, %95, "
      "%96, %97, %98, %99, %100, %101, %102, %103, %104, %105, %106, %107, %108, %109, %110, %111, "
      "%112, %113, %114, %115, %116, %117, %118, %119, %120, %121, %122, %123, %124, %125, %126, %127"
      "}, %128, %129, p, 1, 1, 0, 1;\n}\n"
      : "+f"(d[0]), "+f"(d[1]), "+f"(d[2]), "+f"(d[3]), "+f"(d[4]), "+f"(d[5]), "+f"(d[6]), "+f"(d[7]),
        "+f"(d[8]), "+f"(d[9]), "+f"(d[10]), "+f"(d[11]), "+f"(d[12]), "+f"(d[13]), "+f"(d[14]), "+f"(d[15]),
        "+f"(d[16]), "+f"(d[17]), "+f"(d[18]), "+f"(d[19]), "+f"(d[20]), "+f"(d[21]), "+f"(d[22]), "+f"(d[23]),
        "+f"(d[24]), "+f"(d[25]), "+f"(d[26]), "+f"(d[27]), "+f"(d[28]), "+f"(d[29]), "+f"(d[30]), "+f"(d[31]),
        "+f"(d[32]), "+f"(d[33]), "+f"(d[34]), "+f"(d[35]), "+f"(d[36]), "+f"(d[37]), "+f"(d[38]), "+f"(d[39]),
        "+f"(d[40]), "+f"(d[41]), "+f"(d[42]), "+f"(d[43]), "+f"(d[44]), "+f"(d[45]), "+f"(d[46]), "+f"(d[47]),
        "+f"(d[48]), "+f"(d[49]), "+f"(d[50]), "+f"(d[51]), "+f"(d[52]), "+f"(d[53]), "+f"(d[54]), "+f"(d[55]),
        "+f"(d[56]), "+f"(d[57]), "+f"(d[58]), "+f"(d[59]), "+f"(d[60]), "+f"(d[61]), "+f"(d[62]), "+f"(d[63]),
        "+f"(d[64]), "+f"(d[65]), "+f"(d[66]), "+f"(d[67]), "+f"(d[68]), "+f"(d[69]), "+f"(d[70]), "+f"(d[71]),
        "+f"(d[72]), "+f"(d[73]), "+f"(d[74]), "+f"(d[75]), "+f"(d[76]), "+f"(d[77]), "+f"(d[78]), "+f"(d[79]),
        "+f"(d[80]), "+f"(d[81]), "+f"(d[82]), "+f"(d[83]), "+f"(d[84]), "+f"(d[85]), "+f"(d[86]), "+f"(d[87]),
        "+f"(d[88]), "+f"(d[89]), "+f"(d[90]), "+f"(d[91]), "+f"(d[92]), "+f"(d[93]), "+f"(d[94]), "+f"(d[95]),
        "+f"(d[96]), "+f"(d[97]), "+f"(d[98]), "+f"(d[99]), "+f"(d[100]), "+f"(d[101]), "+f"(d[102]), "+f"(d[103]),
        "+f"(d[104]), "+f"(d[105]), "+f"(d[106]), "+f"(d[107]), "+f"(d[108]), "+f"(d[109]), "+f"(d[110]), "+f"(d[111]),
        "+f"(d[112]), "+f"(d[113]), "+f"(d[114]), "+f"(d[115]), "+f"(d[116]), "+f"(d[117]), "+f"(d[118]), "+f"(d[119]),
        "+f"(d[120]), "+f"(d[121]), "+f"(d[122]), "+f"(d[123]), "+f"(d[124]), "+f"(d[125]), "+f"(d[126]), "+f"(d[127])
      : "l"(descA), "l"(descB), "r"(acc));
}

__device__ __forceinline__ void mma_ss64(float (&d)[32], uint64_t descA, uint64_t descB) {
  asm volatile("wgmma.mma_async.sync.aligned.m64n64k16.f32.bf16.bf16 {"
      "%0, %1, %2, %3, %4, %5, %6, %7, %8, %9, %10, %11, %12, %13, %14, %15, "
      "%16, %17, %18, %19, %20, %21, %22, %23, %24, %25, %26, %27, %28, %29, %30, %31"
      "}, %32, %33, 1, 1, 1, 0, 1;\n"
      : "+f"(d[0]), "+f"(d[1]), "+f"(d[2]), "+f"(d[3]), "+f"(d[4]), "+f"(d[5]), "+f"(d[6]), "+f"(d[7]),
        "+f"(d[8]), "+f"(d[9]), "+f"(d[10]), "+f"(d[11]), "+f"(d[12]), "+f"(d[13]), "+f"(d[14]), "+f"(d[15]),
        "+f"(d[16]), "+f"(d[17]), "+f"(d[18]), "+f"(d[19]), "+f"(d[20]), "+f"(d[21]), "+f"(d[22]), "+f"(d[23]),
        "+f"(d[24]), "+f"(d[25]), "+f"(d[26]), "+f"(d[27]), "+f"(d[28]), "+f"(d[29]), "+f"(d[30]), "+f"(d[31])
      : "l"(descA), "l"(descB));
}
__device__ __forceinline__ void mma_ss64_p(float (&d)[32], uint64_t descA, uint64_t descB, int acc) {
  asm volatile("{\n.reg .pred p;\nsetp.ne.b32 p, %34, 0;\n"
      "wgmma.mma_async.sync.aligned.m64n64k16.f32.bf16.bf16 {"
      "%0, %1, %2, %3, %4, %5, %6, %7, %8, %9, %10, %11, %12, %13, %14, %15, "
      "%16, %17, %18, %19, %20, %21, %22, %23, %24, %25, %26, %27, %28, %29, %30, %31"
      "}, %32, %33, p, 1, 1, 0, 1;\n}\n"
      : "+f"(d[0]), "+f"(d[1]), "+f"(d[2]), "+f"(d[3]), "+f"(d[4]), "+f"(d[5]), "+f"(d[6]), "+f"(d[7]),
        "+f"(d[8]), "+f"(d[9]), "+f"(d[10]), "+f"(d[11]), "+f"(d[12]), "+f"(d[13]), "+f"(d[14]), "+f"(d[15]),
        "+f"(d[16]), "+f"(d[17]), "+f"(d[18]), "+f"(d[19]), "+f"(d[20]), "+f"(d[21]), "+f"(d[22]), "+f"(d[23]),
        "+f"(d[24]), "+f"(d[25]), "+f"(d[26]), "+f"(d[27]), "+f"(d[28]), "+f"(d[29]), "+f"(d[30]), "+f"(d[31])
      : "l"(descA), "l"(descB), "r"(acc));
}

__device__ __forceinline__ void mma_ss160(float (&d)[80], uint64_t descA, uint64_t descB) {
  asm volatile("wgmma.mma_async.sync.aligned.m64n160k16.f32.bf16.bf16 {"
      "%0, %1, %2, %3, %4, %5, %6, %7, %8, %9, %10, %11, %12, %13, %14, %15, "
      "%16, %17, %18, %19, %20, %21, %22, %23, %24, %25, %26, %27, %28, %29, %30, %31, "
      "%32, %33, %34, %35, %36, %37, %38, %39, %40, %41, %42, %43, %44, %45, %46, %47, "
      "%48, %49, %50, %51, %52, %53, %54, %55, %56, %57, %58, %59, %60, %61, %62, %63, "
      "%64, %65, %66, %67, %68, %69, %70, %71, %72, %73, %74, %75, %76, %77, %78, %79"
      "}, %80, %81, 1, 1, 1, 0, 1;\n"
      : "+f"(d[0]), "+f"(d[1]), "+f"(d[2]), "+f"(d[3]), "+f"(d[4]), "+f"(d[5]), "+f"(d[6]), "+f"(d[7]),
        "+f"(d[8]), "+f"(d[9]), "+f"(d[10]), "+f"(d[11]), "+f"(d[12]), "+f"(d[13]), "+f"(d[14]), "+f"(d[15]),
        "+f"(d[16]), "+f"(d[17]), "+f"(d[18]), "+f"(d[19]), "+f"(d[20]), "+f"(d[21]), "+f"(d[22]), "+f"(d[23]),
        "+f"(d[24]), "+f"(d[25]), "+f"(d[26]), "+f"(d[27]), "+f"(d[28]), "+f"(d[29]), "+f"(d[30]), "+f"(d[31]),
        "+f"(d[32]), "+f"(d[33]), "+f"(d[34]), "+f"(d[35]), "+f"(d[36]), "+f"(d[37]), "+f"(d[38]), "+f"(d[39]),
        "+f"(d[40]), "+f"(d[41]), "+f"(d[42]), "+f"(d[43]), "+f"(d[44]), "+f"(d[45]), "+f"(d[46]), "+f"(d[47]),
        "+f"(d[48]), "+f"(d[49]), "+f"(d[50]), "+f"(d[51]), "+f"(d[52]), "+f"(d[53]), "+f"(d[54]), "+f"(d[55]),
        "+f"(d[56]), "+f"(d[57]), "+f"(d[58]), "+f"(d[59]), "+f"(d[60]), "+f"(d[61]), "+f"(d[62]), "+f"(d[63]),
        "+f"(d[64]), "+f"(d[65]), "+f"(d[66]), "+f"(d[67]), "+f"(d[68]), "+f"(d[69]), "+f"(d[70]), "+f"(d[71]),
        "+f"(d[72]), "+f"(d[73]), "+f"(d[74]), "+f"(d[75]), "+f"(d[76]), "+f"(d[77]), "+f"(d[78]), "+f"(d[79])
      : "l"(descA), "l"(descB));
}
__device__ __forceinline__ void mma_ss160_z(float (&d)[80], uint64_t descA, uint64_t descB) {
  asm volatile("wgmma.mma_async.sync.aligned.m64n160k16.f32.bf16.bf16 {"
      "%0, %1, %2, %3, %4, %5, %6, %7, %8, %9, %10, %11, %12, %13, %14, %15, "
      "%16, %17, %18, %19, %20, %21, %22, %23, %24, %25, %26, %27, %28, %29, %30, %31, "
      "%32, %33, %34, %35, %36, %37, %38, %39, %40, %41, %42, %43, %44, %45, %46, %47, "
      "%48, %49, %50, %51, %52, %53, %54, %55, %56, %57, %58, %59, %60, %61, %62, %63, "
      "%64, %65, %66, %67, %68, %69, %70, %71, %72, %73, %74, %75, %76, %77, %78, %79"
      "}, %80, %81, 0, 1, 1, 0, 1;\n"
      : "=f"(d[0]), "=f"(d[1]), "=f"(d[2]), "=f"(d[3]), "=f"(d[4]), "=f"(d[5]), "=f"(d[6]), "=f"(d[7]),
        "=f"(d[8]), "=f"(d[9]), "=f"(d[10]), "=f"(d[11]), "=f"(d[12]), "=f"(d[13]), "=f"(d[14]), "=f"(d[15]),
        "=f"(d[16]), "=f"(d[17]), "=f"(d[18]), "=f"(d[19]), "=f"(d[20]), "=f"(d[21]), "=f"(d[22]), "=f"(d[23]),
        "=f"(d[24]), "=f"(d[25]), "=f"(d[26]), "=f"(d[27]), "=f"(d[28]), "=f"(d[29]), "=f"(d[30]), "=f"(d[31]),
        "=f"(d[32]), "=f"(d[33]), "=f"(d[34]), "=f"(d[35]), "=f"(d[36]), "=f"(d[37]), "=f"(d[38]), "=f"(d[39]),
        "=f"(d[40]), "=f"(d[41]), "=f"(d[42]), "=f"(d[43]), "=f"(d[44]), "=f"(d[45]), "=f"(d[46]), "=f"(d[47]),
        "=f"(d[48]), "=f"(d[49]), "=f"(d[50]), "=f"(d[51]), "=f"(d[52]), "=f"(d[53]), "=f"(d[54]), "=f"(d[55]),
        "=f"(d[56]), "=f"(d[57]), "=f"(d[58]), "=f"(d[59]), "=f"(d[60]), "=f"(d[61]), "=f"(d[62]), "=f"(d[63]),
        "=f"(d[64]), "=f"(d[65]), "=f"(d[66]), "=f"(d[67]), "=f"(d[68]), "=f"(d[69]), "=f"(d[70]), "=f"(d[71]),
        "=f"(d[72]), "=f"(d[73]), "=f"(d[74]), "=f"(d[75]), "=f"(d[76]), "=f"(d[77]), "=f"(d[78]), "=f"(d[79])
      : "l"(descA), "l"(descB));
}

__device__ __forceinline__ void mma_ss192(float (&d)[96], uint64_t descA, uint64_t descB) {
  asm volatile("wgmma.mma_async.sync.aligned.m64n192k16.f32.bf16.bf16 {"
      "%0, %1, %2, %3, %4, %5, %6, %7, %8, %9, %10, %11, %12, %13, %14, %15, "
      "%16, %17, %18, %19, %20, %21, %22, %23, %24, %25, %26, %27, %28, %29, %30, %31, "
      "%32, %33, %34, %35, %36, %37, %38, %39, %40, %41, %42, %43, %44, %45, %46, %47, "
      "%48, %49, %50, %51, %52, %53, %54, %55, %56, %57, %58, %59, %60, %61, %62, %63, "
      "%64, %65, %66, %67, %68, %69, %70, %71, %72, %73, %74, %75, %76, %77, %78, %79, "
      "%80, %81, %82, %83, %84, %85, %86, %87, %88, %89, %90, %91, %92, %93, %94, %95"
      "}, %96, %97, 1, 1, 1, 0, 1;\n"
      : "+f"(d[0]), "+f"(d[1]), "+f"(d[2]), "+f"(d[3]), "+f"(d[4]), "+f"(d[5]), "+f"(d[6]), "+f"(d[7]),
        "+f"(d[8]), "+f"(d[9]), "+f"(d[10]), "+f"(d[11]), "+f"(d[12]), "+f"(d[13]), "+f"(d[14]), "+f"(d[15]),
        "+f"(d[16]), "+f"(d[17]), "+f"(d[18]), "+f"(d[19]), "+f"(d[20]), "+f"(d[21]), "+f"(d[22]), "+f"(d[23]),
        "+f"(d[24]), "+f"(d[25]), "+f"(d[26]), "+f"(d[27]), "+f"(d[28]), "+f"(d[29]), "+f"(d[30]), "+f"(d[31]),
        "+f"(d[32]), "+f"(d[33]), "+f"(d[34]), "+f"(d[35]), "+f"(d[36]), "+f"(d[37]), "+f"(d[38]), "+f"(d[39]),
        "+f"(d[40]), "+f"(d[41]), "+f"(d[42]), "+f"(d[43]), "+f"(d[44]), "+f"(d[45]), "+f"(d[46]), "+f"(d[47]),
        "+f"(d[48]), "+f"(d[49]), "+f"(d[50]), "+f"(d[51]), "+f"(d[52]), "+f"(d[53]), "+f"(d[54]), "+f"(d[55]),
        "+f"(d[56]), "+f"(d[57]), "+f"(d[58]), "+f"(d[59]), "+f"(d[60]), "+f"(d[61]), "+f"(d[62]), "+f"(d[63]),
        "+f"(d[64]), "+f"(d[65]), "+f"(d[66]), "+f"(d[67]), "+f"(d[68]), "+f"(d[69]), "+f"(d[70]), "+f"(d[71]),
        "+f"(d[72]), "+f"(d[73]), "+f"(d[74]), "+f"(d[75]), "+f"(d[76]), "+f"(d[77]), "+f"(d[78]), "+f"(d[79]),
        "+f"(d[80]), "+f"(d[81]), "+f"(d[82]), "+f"(d[83]), "+f"(d[84]), "+f"(d[85]), "+f"(d[86]), "+f"(d[87]),
        "+f"(d[88]), "+f"(d[89]), "+f"(d[90]), "+f"(d[91]), "+f"(d[92]), "+f"(d[93]), "+f"(d[94]), "+f"(d[95])
      : "l"(descA), "l"(descB));
}
__device__ __forceinline__ void mma_ss192_p(float (&d)[96], uint64_t descA, uint64_t descB, int acc) {
  asm volatile("{\n.reg .pred p;\nsetp.ne.b32 p, %98, 0;\n"
      "wgmma.mma_async.sync.aligned.m64n192k16.f32.bf16.bf16 {"
      "%0, %1, %2, %3, %4, %5, %6, %7, %8, %9, %10, %11, %12, %13, %14, %15, "
      "%16, %17, %18, %19, %20, %21, %22, %23, %24, %25, %26, %27, %28, %29, %30, %31, "
      "%32, %33, %34, %35, %36, %37, %38, %39, %40, %41, %42, %43, %44, %45, %46, %47, "
      "%48, %49, %50, %51, %52, %53, %54, %55, %56, %57, %58, %59, %60, %61, %62, %63, "
      "%64, %65, %66, %67, %68, %69, %70, %71, %72, %73, %74, %75, %76, %77, %78, %79, "
      "%80, %81, %82, %83, %84, %85, %86, %87, %88, %89, %90, %91, %92, %93, %94, %95"
      "}, %96, %97, p, 1, 1, 0, 1;\n}\n"
      : "+f"(d[0]), "+f"(d[1]), "+f"(d[2]), "+f"(d[3]), "+f"(d[4]), "+f"(d[5]), "+f"(d[6]), "+f"(d[7]),
        "+f"(d[8]), "+f"(d[9]), "+f"(d[10]), "+f"(d[11]), "+f"(d[12]), "+f"(d[13]), "+f"(d[14]), "+f"(d[15]),
        "+f"(d[16]), "+f"(d[17]), "+f"(d[18]), "+f"(d[19]), "+f"(d[20]), "+f"(d[21]), "+f"(d[22]), "+f"(d[23]),
        "+f"(d[24]), "+f"(d[25]), "+f"(d[26]), "+f"(d[27]), "+f"(d[28]), "+f"(d[29]), "+f"(d[30]), "+f"(d[31]),
        "+f"(d[32]), "+f"(d[33]), "+f"(d[34]), "+f"(d[35]), "+f"(d[36]), "+f"(d[37]), "+f"(d[38]), "+f"(d[39]),
        "+f"(d[40]), "+f"(d[41]), "+f"(d[42]), "+f"(d[43]), "+f"(d[44]), "+f"(d[45]), "+f"(d[46]), "+f"(d[47]),
        "+f"(d[48]), "+f"(d[49]), "+f"(d[50]), "+f"(d[51]), "+f"(d[52]), "+f"(d[53]), "+f"(d[54]), "+f"(d[55]),
        "+f"(d[56]), "+f"(d[57]), "+f"(d[58]), "+f"(d[59]), "+f"(d[60]), "+f"(d[61]), "+f"(d[62]), "+f"(d[63]),
        "+f"(d[64]), "+f"(d[65]), "+f"(d[66]), "+f"(d[67]), "+f"(d[68]), "+f"(d[69]), "+f"(d[70]), "+f"(d[71]),
        "+f"(d[72]), "+f"(d[73]), "+f"(d[74]), "+f"(d[75]), "+f"(d[76]), "+f"(d[77]), "+f"(d[78]), "+f"(d[79]),
        "+f"(d[80]), "+f"(d[81]), "+f"(d[82]), "+f"(d[83]), "+f"(d[84]), "+f"(d[85]), "+f"(d[86]), "+f"(d[87]),
        "+f"(d[88]), "+f"(d[89]), "+f"(d[90]), "+f"(d[91]), "+f"(d[92]), "+f"(d[93]), "+f"(d[94]), "+f"(d[95])
      : "l"(descA), "l"(descB), "r"(acc));
}

__device__ __forceinline__ void mma_ss80_tt(float (&d)[40], uint64_t descA, uint64_t descB) {
  asm volatile("wgmma.mma_async.sync.aligned.m64n80k16.f32.bf16.bf16 {"
      "%0, %1, %2, %3, %4, %5, %6, %7, %8, %9, %10, %11, %12, %13, %14, %15, "
      "%16, %17, %18, %19, %20, %21, %22, %23, %24, %25, %26, %27, %28, %29, %30, %31, "
      "%32, %33, %34, %35, %36, %37, %38, %39"
      "}, %40, %41, 1, 1, 1, 1, 1;\n"
      : "+f"(d[0]), "+f"(d[1]), "+f"(d[2]), "+f"(d[3]), "+f"(d[4]), "+f"(d[5]), "+f"(d[6]), "+f"(d[7]),
        "+f"(d[8]), "+f"(d[9]), "+f"(d[10]), "+f"(d[11]), "+f"(d[12]), "+f"(d[13]), "+f"(d[14]), "+f"(d[15]),
        "+f"(d[16]), "+f"(d[17]), "+f"(d[18]), "+f"(d[19]), "+f"(d[20]), "+f"(d[21]), "+f"(d[22]), "+f"(d[23]),
        "+f"(d[24]), "+f"(d[25]), "+f"(d[26]), "+f"(d[27]), "+f"(d[28]), "+f"(d[29]), "+f"(d[30]), "+f"(d[31]),
        "+f"(d[32]), "+f"(d[33]), "+f"(d[34]), "+f"(d[35]), "+f"(d[36]), "+f"(d[37]), "+f"(d[38]), "+f"(d[39])
      : "l"(descA), "l"(descB));
}
__device__ __forceinline__ void mma_ss80_tt_z(float (&d)[40], uint64_t descA, uint64_t descB) {
  asm volatile("wgmma.mma_async.sync.aligned.m64n80k16.f32.bf16.bf16 {"
      "%0, %1, %2, %3, %4, %5, %6, %7, %8, %9, %10, %11, %12, %13, %14, %15, "
      "%16, %17, %18, %19, %20, %21, %22, %23, %24, %25, %26, %27, %28, %29, %30, %31, "
      "%32, %33, %34, %35, %36, %37, %38, %39"
      "}, %40, %41, 0, 1, 1, 1, 1;\n"
      : "=f"(d[0]), "=f"(d[1]), "=f"(d[2]), "=f"(d[3]), "=f"(d[4]), "=f"(d[5]), "=f"(d[6]), "=f"(d[7]),
        "=f"(d[8]), "=f"(d[9]), "=f"(d[10]), "=f"(d[11]), "=f"(d[12]), "=f"(d[13]), "=f"(d[14]), "=f"(d[15]),
        "=f"(d[16]), "=f"(d[17]), "=f"(d[18]), "=f"(d[19]), "=f"(d[20]), "=f"(d[21]), "=f"(d[22]), "=f"(d[23]),
        "=f"(d[24]), "=f"(d[25]), "=f"(d[26]), "=f"(d[27]), "=f"(d[28]), "=f"(d[29]), "=f"(d[30]), "=f"(d[31]),
        "=f"(d[32]), "=f"(d[33]), "=f"(d[34]), "=f"(d[35]), "=f"(d[36]), "=f"(d[37]), "=f"(d[38]), "=f"(d[39])
      : "l"(descA), "l"(descB));
}

__device__ __forceinline__ void mma_rs80_k(float (&d)[40], const uint32_t (&a)[4], uint64_t descB) {
  asm volatile("wgmma.mma_async.sync.aligned.m64n80k16.f32.bf16.bf16 {"
      "%0, %1, %2, %3, %4, %5, %6, %7, %8, %9, %10, %11, %12, %13, %14, %15, "
      "%16, %17, %18, %19, %20, %21, %22, %23, %24, %25, %26, %27, %28, %29, %30, %31, "
      "%32, %33, %34, %35, %36, %37, %38, %39"
      "}, {%40, %41, %42, %43}, %44, 1, 1, 1, 0;\n"
      : "+f"(d[0]), "+f"(d[1]), "+f"(d[2]), "+f"(d[3]), "+f"(d[4]), "+f"(d[5]), "+f"(d[6]), "+f"(d[7]),
        "+f"(d[8]), "+f"(d[9]), "+f"(d[10]), "+f"(d[11]), "+f"(d[12]), "+f"(d[13]), "+f"(d[14]), "+f"(d[15]),
        "+f"(d[16]), "+f"(d[17]), "+f"(d[18]), "+f"(d[19]), "+f"(d[20]), "+f"(d[21]), "+f"(d[22]), "+f"(d[23]),
        "+f"(d[24]), "+f"(d[25]), "+f"(d[26]), "+f"(d[27]), "+f"(d[28]), "+f"(d[29]), "+f"(d[30]), "+f"(d[31]),
        "+f"(d[32]), "+f"(d[33]), "+f"(d[34]), "+f"(d[35]), "+f"(d[36]), "+f"(d[37]), "+f"(d[38]), "+f"(d[39])
      : "r"(a[0]), "r"(a[1]), "r"(a[2]), "r"(a[3]), "l"(descB));
}
__device__ __forceinline__ void mma_rs80_k_z(float (&d)[40], const uint32_t (&a)[4], uint64_t descB) {
  asm volatile("wgmma.mma_async.sync.aligned.m64n80k16.f32.bf16.bf16 {"
      "%0, %1, %2, %3, %4, %5, %6, %7, %8, %9, %10, %11, %12, %13, %14, %15, "
      "%16, %17, %18, %19, %20, %21, %22, %23, %24, %25, %26, %27, %28, %29, %30, %31, "
      "%32, %33, %34, %35, %36, %37, %38, %39"
      "}, {%40, %41, %42, %43}, %44, 0, 1, 1, 0;\n"
      : "=f"(d[0]), "=f"(d[1]), "=f"(d[2]), "=f"(d[3]), "=f"(d[4]), "=f"(d[5]), "=f"(d[6]), "=f"(d[7]),
        "=f"(d[8]), "=f"(d[9]), "=f"(d[10]), "=f"(d[11]), "=f"(d[12]), "=f"(d[13]), "=f"(d[14]), "=f"(d[15]),
        "=f"(d[16]), "=f"(d[17]), "=f"(d[18]), "=f"(d[19]), "=f"(d[20]), "=f"(d[21]), "=f"(d[22]), "=f"(d[23]),
        "=f"(d[24]), "=f"(d[25]), "=f"(d[26]), "=f"(d[27]), "=f"(d[28]), "=f"(d[29]), "=f"(d[30]), "=f"(d[31]),
        "=f"(d[32]), "=f"(d[33]), "=f"(d[34]), "=f"(d[35]), "=f"(d[36]), "=f"(d[37]), "=f"(d[38]), "=f"(d[39])
      : "r"(a[0]), "r"(a[1]), "r"(a[2]), "r"(a[3]), "l"(descB));
}

__device__ __forceinline__ void mma_rs48_k(float (&d)[24], const uint32_t (&a)[4], uint64_t descB) {
  asm volatile("wgmma.mma_async.sync.aligned.m64n48k16.f32.bf16.bf16 {"
      "%0, %1, %2, %3, %4, %5, %6, %7, %8, %9, %10, %11, %12, %13, %14, %15, "
      "%16, %17, %18, %19, %20, %21, %22, %23"
      "}, {%24, %25, %26, %27}, %28, 1, 1, 1, 0;\n"
      : "+f"(d[0]), "+f"(d[1]), "+f"(d[2]), "+f"(d[3]), "+f"(d[4]), "+f"(d[5]), "+f"(d[6]), "+f"(d[7]),
        "+f"(d[8]), "+f"(d[9]), "+f"(d[10]), "+f"(d[11]), "+f"(d[12]), "+f"(d[13]), "+f"(d[14]), "+f"(d[15]),
        "+f"(d[16]), "+f"(d[17]), "+f"(d[18]), "+f"(d[19]), "+f"(d[20]), "+f"(d[21]), "+f"(d[22]), "+f"(d[23])
      : "r"(a[0]), "r"(a[1]), "r"(a[2]), "r"(a[3]), "l"(descB));
}
__device__ __forceinline__ void mma_rs48_k_z(float (&d)[24], const uint32_t (&a)[4], uint64_t descB) {
  asm volatile("wgmma.mma_async.sync.aligned.m64n48k16.f32.bf16.bf16 {"
      "%0, %1, %2, %3, %4, %5, %6, %7, %8, %9, %10, %11, %12, %13, %14, %15, "
      "%16, %17, %18, %19, %20, %21, %22, %23"
      "}, {%24, %25, %26, %27}, %28, 0, 1, 1, 0;\n"
      : "=f"(d[0]), "=f"(d[1]), "=f"(d[2]), "=f"(d[3]), "=f"(d[4]), "=f"(d[5]), "=f"(d[6]), "=f"(d[7]),
        "=f"(d[8]), "=f"(d[9]), "=f"(d[10]), "=f"(d[11]), "=f"(d[12]), "=f"(d[13]), "=f"(d[14]), "=f"(d[15]),
        "=f"(d[16]), "=f"(d[17]), "=f"(d[18]), "=f"(d[19]), "=f"(d[20]), "=f"(d[21]), "=f"(d[22]), "=f"(d[23])
      : "r"(a[0]), "r"(a[1]), "r"(a[2]), "r"(a[3]), "l"(descB));
}

__device__ __forceinline__ void mma_rs160_n(float (&d)[80], const uint32_t (&a)[4], uint64_t descB) {
  asm volatile("wgmma.mma_async.sync.aligned.m64n160k16.f32.bf16.bf16 {"
      "%0, %1, %2, %3, %4, %5, %6, %7, %8, %9, %10, %11, %12, %13, %14, %15, "
      "%16, %17, %18, %19, %20, %21, %22, %23, %24, %25, %26, %27, %28, %29, %30, %31, "
      "%32, %33, %34, %35, %36, %37, %38, %39, %40, %41, %42, %43, %44, %45, %46, %47, "
      "%48, %49, %50, %51, %52, %53, %54, %55, %56, %57, %58, %59, %60, %61, %62, %63, "
      "%64, %65, %66, %67, %68, %69, %70, %71, %72, %73, %74, %75, %76, %77, %78, %79"
      "}, {%80, %81, %82, %83}, %84, 1, 1, 1, 1;\n"
      : "+f"(d[0]), "+f"(d[1]), "+f"(d[2]), "+f"(d[3]), "+f"(d[4]), "+f"(d[5]), "+f"(d[6]), "+f"(d[7]),
        "+f"(d[8]), "+f"(d[9]), "+f"(d[10]), "+f"(d[11]), "+f"(d[12]), "+f"(d[13]), "+f"(d[14]), "+f"(d[15]),
        "+f"(d[16]), "+f"(d[17]), "+f"(d[18]), "+f"(d[19]), "+f"(d[20]), "+f"(d[21]), "+f"(d[22]), "+f"(d[23]),
        "+f"(d[24]), "+f"(d[25]), "+f"(d[26]), "+f"(d[27]), "+f"(d[28]), "+f"(d[29]), "+f"(d[30]), "+f"(d[31]),
        "+f"(d[32]), "+f"(d[33]), "+f"(d[34]), "+f"(d[35]), "+f"(d[36]), "+f"(d[37]), "+f"(d[38]), "+f"(d[39]),
        "+f"(d[40]), "+f"(d[41]), "+f"(d[42]), "+f"(d[43]), "+f"(d[44]), "+f"(d[45]), "+f"(d[46]), "+f"(d[47]),
        "+f"(d[48]), "+f"(d[49]), "+f"(d[50]), "+f"(d[51]), "+f"(d[52]), "+f"(d[53]), "+f"(d[54]), "+f"(d[55]),
        "+f"(d[56]), "+f"(d[57]), "+f"(d[58]), "+f"(d[59]), "+f"(d[60]), "+f"(d[61]), "+f"(d[62]), "+f"(d[63]),
        "+f"(d[64]), "+f"(d[65]), "+f"(d[66]), "+f"(d[67]), "+f"(d[68]), "+f"(d[69]), "+f"(d[70]), "+f"(d[71]),
        "+f"(d[72]), "+f"(d[73]), "+f"(d[74]), "+f"(d[75]), "+f"(d[76]), "+f"(d[77]), "+f"(d[78]), "+f"(d[79])
      : "r"(a[0]), "r"(a[1]), "r"(a[2]), "r"(a[3]), "l"(descB));
}
__device__ __forceinline__ void mma_rs160_n_z(float (&d)[80], const uint32_t (&a)[4], uint64_t descB) {
  asm volatile("wgmma.mma_async.sync.aligned.m64n160k16.f32.bf16.bf16 {"
      "%0, %1, %2, %3, %4, %5, %6, %7, %8, %9, %10, %11, %12, %13, %14, %15, "
      "%16, %17, %18, %19, %20, %21, %22, %23, %24, %25, %26, %27, %28, %29, %30, %31, "
      "%32, %33, %34, %35, %36, %37, %38, %39, %40, %41, %42, %43, %44, %45, %46, %47, "
      "%48, %49, %50, %51, %52, %53, %54, %55, %56, %57, %58, %59, %60, %61, %62, %63, "
      "%64, %65, %66, %67, %68, %69, %70, %71, %72, %73, %74, %75, %76, %77, %78, %79"
      "}, {%80, %81, %82, %83}, %84, 0, 1, 1, 1;\n"
      : "=f"(d[0]), "=f"(d[1]), "=f"(d[2]), "=f"(d[3]), "=f"(d[4]), "=f"(d[5]), "=f"(d[6]), "=f"(d[7]),
        "=f"(d[8]), "=f"(d[9]), "=f"(d[10]), "=f"(d[11]), "=f"(d[12]), "=f"(d[13]), "=f"(d[14]), "=f"(d[15]),
        "=f"(d[16]), "=f"(d[17]), "=f"(d[18]), "=f"(d[19]), "=f"(d[20]), "=f"(d[21]), "=f"(d[22]), "=f"(d[23]),
        "=f"(d[24]), "=f"(d[25]), "=f"(d[26]), "=f"(d[27]), "=f"(d[28]), "=f"(d[29]), "=f"(d[30]), "=f"(d[31]),
        "=f"(d[32]), "=f"(d[33]), "=f"(d[34]), "=f"(d[35]), "=f"(d[36]), "=f"(d[37]), "=f"(d[38]), "=f"(d[39]),
        "=f"(d[40]), "=f"(d[41]), "=f"(d[42]), "=f"(d[43]), "=f"(d[44]), "=f"(d[45]), "=f"(d[46]), "=f"(d[47]),
        "=f"(d[48]), "=f"(d[49]), "=f"(d[50]), "=f"(d[51]), "=f"(d[52]), "=f"(d[53]), "=f"(d[54]), "=f"(d[55]),
        "=f"(d[56]), "=f"(d[57]), "=f"(d[58]), "=f"(d[59]), "=f"(d[60]), "=f"(d[61]), "=f"(d[62]), "=f"(d[63]),
        "=f"(d[64]), "=f"(d[65]), "=f"(d[66]), "=f"(d[67]), "=f"(d[68]), "=f"(d[69]), "=f"(d[70]), "=f"(d[71]),
        "=f"(d[72]), "=f"(d[73]), "=f"(d[74]), "=f"(d[75]), "=f"(d[76]), "=f"(d[77]), "=f"(d[78]), "=f"(d[79])
      : "r"(a[0]), "r"(a[1]), "r"(a[2]), "r"(a[3]), "l"(descB));
}

__device__ __forceinline__ void feature_map(const uint32_t (&P)[2][10], uint32_t (&fr)[10][4]) {
  constexpr float L2E = 1.4426950408889634f;
#pragma unroll
  for (int p = 0; p < 2; p++) {
#pragma unroll
    for (int r = 0; r < 2; r++) {
      uint32_t mx = P[r][5 * p], mn = mx;
#pragma unroll
      for (int g = 1; g < 5; g++) { mx = max_bf2(mx, P[r][5 * p + g]); mn = min_bf2(mn, P[r][5 * p + g]); }
      mx = max_bf2(mx, __shfl_xor_sync(0xffffffffu, mx, 1));
      mn = min_bf2(mn, __shfl_xor_sync(0xffffffffu, mn, 1));
      mx = max_bf2(mx, __shfl_xor_sync(0xffffffffu, mx, 2));
      mn = min_bf2(mn, __shfl_xor_sync(0xffffffffu, mn, 2));
      float mx0 = -bf_lo(mx) * L2E, mx1 = -bf_hi(mx) * L2E, mn0 = bf_lo(mn) * L2E, mn1 = bf_hi(mn) * L2E;
      float ep0[5], ep1[5], en0[5], en1[5];
      float sp0 = 0.f, sp1 = 0.f, sn0 = 0.f, sn1 = 0.f;
#pragma unroll
      for (int g = 0; g < 5; g++) {
        float x0 = bf_lo(P[r][5 * p + g]), x1 = bf_hi(P[r][5 * p + g]);
        ep0[g] = ex2(fmaf(x0, L2E, mx0)); ep1[g] = ex2(fmaf(x1, L2E, mx1));
        en0[g] = ex2(fmaf(x0, -L2E, mn0)); en1[g] = ex2(fmaf(x1, -L2E, mn1));
        sp0 += ep0[g]; sp1 += ep1[g]; sn0 += en0[g]; sn1 += en1[g];
      }
      sp0 += __shfl_xor_sync(0xffffffffu, sp0, 1); sp1 += __shfl_xor_sync(0xffffffffu, sp1, 1);
      sn0 += __shfl_xor_sync(0xffffffffu, sn0, 1); sn1 += __shfl_xor_sync(0xffffffffu, sn1, 1);
      sp0 += __shfl_xor_sync(0xffffffffu, sp0, 2); sp1 += __shfl_xor_sync(0xffffffffu, sp1, 2);
      sn0 += __shfl_xor_sync(0xffffffffu, sn0, 2); sn1 += __shfl_xor_sync(0xffffffffu, sn1, 2);
      sp0 = rcp(sp0); sp1 = rcp(sp1); sn0 = rcp(sn0); sn1 = rcp(sn1);
#pragma unroll
      for (int g = 0; g < 5; g++) {
        fr[5 * p + g][r] = pack_bf16(ep0[g] * sp0, ep1[g] * sp1);
        fr[5 * p + g][2 + r] = pack_bf16(en0[g] * sn0, en1[g] * sn1);
      }
    }
  }
}

template <int V> struct IntC { static constexpr int value = V; };
struct Ring {
  uint32_t idx, phase;
  template <int N> __device__ __forceinline__ void next() { if (++idx == N) { idx = 0; phase ^= 1; } }
};

}

__global__ void __cluster_dims__(2, 1, 1) __launch_bounds__(384, 1)
fused_kernel(const __grid_constant__ Maps maps, const __nv_bfloat16* __restrict__ x, const __nv_bfloat16* __restrict__ wqkv,
             const __nv_bfloat16* __restrict__ wphi, const __nv_bfloat16* __restrict__ w1, const __nv_bfloat16* __restrict__ w2,
             const __nv_bfloat16* __restrict__ w3, const __nv_bfloat16* __restrict__ w4, const __nv_bfloat16* __restrict__ wo,
             const __nv_bfloat16* __restrict__ gate_w, __nv_bfloat16* __restrict__ out) {
  extern __shared__ __align__(1024) uint8_t sgen[];
  const uint32_t sb = smem_u32(sgen);
  const uint32_t sb16 = (sb & 0x3FFFFu) >> 4;
  const uint32_t bars = sb + OFF_BAR;
  const uint32_t fullA = bars + 8 * B_FULLA, emptyA = bars + 8 * B_EMPTYA, fullB = bars + 8 * B_FULLB, emptyB = bars + 8 * B_EMPTYB;

  const int tid = threadIdx.x;
  const int rank = blockIdx.x & 1;
  const int bid = blockIdx.x - NSVC, pairIdx = bid >> 1;
  const int i = pairIdx >> 2, j = 2 * (pairIdx & 3) + rank;
  const int k3 = (5 * (pairIdx & 3) + 1) >> 1;

  if (bid < 0) {
    const int sv = blockIdx.x;
    const unsigned epoch = *reinterpret_cast<volatile unsigned*>(g_flags + FL_DONE * 32) / NCTA;
    if (tid == 0) {
#pragma unroll
      for (int b = 0; b < 11; b++) mbar_init(bars + 8 * b, 1);
      mbar_expect_tx(bars + 80, 6400);
      bulk_load(sb + 204800, wphi + sv * 3200, 6400, bars + 80);
    }
    __syncthreads();
    float a[8];
#pragma unroll 1
    for (int rd = 0; rd < 4; rd++) {
      const int nch = rd ? 192 : 80, nth = rd ? 384 : 320, piece = rd ? 18432 : 20480, np = rd == 3 ? 7 : 10;
      if (tid == 0) {
        const char* src = reinterpret_cast<const char*>(rd ? w3 + (size_t)(160 * sv + 60 * (rd - 1)) * F_ : w1 + (size_t)160 * sv * D_);
#pragma unroll 1
        for (int p = 0; p < np; p++) {
          const int bytes = (rd == 3 && p == 6) ? 12288 : piece;
          mbar_expect_tx(bars + 8 * p, bytes);
          bulk_load(sb + p * piece, src + p * piece, bytes, bars + 8 * p);
        }
      }
      if (rd == 0) {
        if (tid < 40 && (tid < 20 || sv >= 2))
          reinterpret_cast<uint4*>(g_Hs + (size_t)(2 + ((sv & 1) ? S_ - 1 - tid / 20 : tid / 20)) * D_ + 160 * sv)[tid % 20] = make_uint4(0, 0, 0, 0);
        mbar_wait(bars + 80, 0);
#pragma unroll 1
        for (int e = tid; e < 1600; e += 384) {
          const int jj = e / 800, it = e - 800 * jj, st = it / 160, n = (it - 160 * st) >> 1, k0 = 16 * st + 8 * ((it ^ (n >> 2)) & 1);
          const int nn = n % 40, h = 2 * (n / 40) + (nn & 1), ff = 4 * (nn >> 3) + ((nn >> 1) & 3);
          uint32_t w[8];
#pragma unroll
          for (int q = 0; q < 8; q++) {
            const int k = k0 + q;
            w[q] = (unsigned)(k - 20 * h) < 20u ? reinterpret_cast<const unsigned short*>(sgen + 204800)[jj * 1600 + k * 20 + ff] : 0u;
          }
          g_wphi[sv * 1600 + e] = make_uint4(w[0] | (w[1] << 16), w[2] | (w[3] << 16), w[4] | (w[5] << 16), w[6] | (w[7] << 16));
        }
      }
      if (rd < 2) {
#pragma unroll
        for (int e = 0; e < 8; e++) a[e] = 0.f;
      }
#pragma unroll 1
      for (int p = 0; p < np; p++) {
        mbar_wait(bars + 8 * p, rd & 1);
        const int bytes = (rd == 3 && p == 6) ? 12288 : piece;
        if (tid < nth) {
#pragma unroll 1
          for (int o = tid * 16; o < bytes; o += nth * 16) {
            const uint4 v = lds128(sb + p * piece + o);
            a[0] += bf_lo(v.x); a[1] += bf_hi(v.x); a[2] += bf_lo(v.y); a[3] += bf_hi(v.y);
            a[4] += bf_lo(v.z); a[5] += bf_hi(v.z); a[6] += bf_lo(v.w); a[7] += bf_hi(v.w);
          }
        }
      }
      if (tid < nth && (rd == 0 || rd == 3)) {
        float* cd = g_cs[epoch & 1] + (rd ? D_ : 0) + 8 * (tid % nch);
        red_add4(cd, a[0], a[1], a[2], a[3]); red_add4(cd + 4, a[4], a[5], a[6], a[7]);
      }
      __syncthreads();
      if (tid == 0 && (rd == 0 || rd == 3)) {
        flag_add(rd ? FL_CS3 : FL_CS);
        if (rd == 0) l2_prefetch(w2 + (size_t)sv * (D_ * D_ / NSVC), D_ * D_ * 2 / NSVC);
      }
    }
#pragma unroll 1
    for (int e = tid; e < (D_ + F_) / NSVC; e += 384) g_cs[(epoch + 1) & 1][sv * ((D_ + F_) / NSVC) + e] = 0.f;
#pragma unroll 1
    for (int e = tid; e < 2 * KV_J; e += 384) g_acc[(epoch + 1) & 1][sv * 2 * KV_J + e] = 0.f;
    if (tid < 32) {
      l2_prefetch(w4 + (size_t)(sv * 32 + tid) * (F_ * D_ / 128), F_ * D_ * 2 / 128);
      l2_prefetch(wo + (size_t)(sv * 32 + tid) * (D_ * D_ / 128), D_ * D_ * 2 / 128);
    }
    return;
  }
  TSTAMP(0);
  if (tid >= 256) {
    asm volatile("setmaxnreg.dec.sync.aligned.u32 40;");
    if (tid == 256) {
#pragma unroll
      for (int s = 0; s < NA; s++) mbar_init(fullA + 8 * s, 1);
      asm volatile("fence.mbarrier_init.release.cluster;" ::: "memory");
#pragma unroll 1
      for (int u = 0; u < 4; u++) {
        if ((u & 1) == 0) mbar_expect_tx(fullA + 4 * u, SLOT_A);
        tma2d(sb + OFF_A + u * 8192, &maps.x, fullA + 8 * (u >> 1), 64 * (u >> 1), 128 * i + 64 * (u & 1));
      }
    } else if (tid == 288) {
#pragma unroll
      for (int s = 0; s < NB; s++) { mbar_init(fullB + 8 * s, 1); mbar_init(emptyB + 8 * s, 8); }
      asm volatile("fence.mbarrier_init.release.cluster;" ::: "memory");
    } else if (tid == 320) {
#pragma unroll
      for (int b = B_CS; b < NBAR; b++) if (b < B_EMPTYB || b >= B_EMPTYB + NB) mbar_init(bars + 8 * b, b < B_EMPTYB ? 1 : b < B_EMPTYA ? 8 : b < B_X1P ? 16 : 2);
#pragma unroll
      for (int b = B_DSR; b < B_EMPTYB; b++) mbar_expect_tx(bars + 8 * b, 10240);
      asm volatile("fence.mbarrier_init.release.cluster;" ::: "memory");
    }
    __syncwarp();
    asm volatile("barrier.cluster.arrive.relaxed.aligned;" ::: "memory");
    auto get_epoch = [&]() { return *reinterpret_cast<volatile unsigned*>(g_flags + FL_DONE * 32) / NCTA; };
    if ((tid >> 5) != 9) asm volatile("barrier.cluster.wait.aligned;" ::: "memory");
    const int lane = tid & 31, pw = (tid >> 5) & 3;
    if (pw == 0) {
      if (tid == 256) {
        Ring r{2, 1};
        unsigned ep1 = 0;
#pragma unroll 1
        for (int k = 2; k < 25; k++) {
          if (k == 4) ep1 = get_epoch() + 1;
          if (k == 10 || k == 17) {
            if (k == 10) mbar_wait(bars + 8 * B_HST, 0);
            flag_wait(k == 10 ? FL_H + 2 * i + rank : FL_X1 + i, ep1 * 8u);
            TSTAMPX(k == 10 ? 29 : 30);
          }
          if (k == 15) mbar_wait(bars + 8 * B_X1P, 0);
          mbar_wait(emptyA + 8 * r.idx, r.phase);
          const uint32_t bar = fullA + 8 * r.idx, slot = sb + OFF_A + r.idx * SLOT_A;
          mbar_expect_tx(bar, SLOT_A);
          if (k >= 10 && k < 15) tma2d(slot, &maps.hs, bar, 64 * (k - 10) + 320 * rank, 128 * i);
          else tma2d_mc(slot + rank * 8192, k < 10 ? &maps.x : &maps.x1, bar, 64 * (k < 10 ? k : (k - 15 + k3) % 10), 128 * i + 64 * rank);
          r.next<NA>();
        }
      }
    } else if (pw == 1) {
      if (tid == 288) {
        Ring r{0, 1};
#pragma unroll 1
        for (int k = 0; k < 18; k++) {
          mbar_wait(emptyB + 8 * r.idx, r.phase);
          const uint32_t bar = fullB + 8 * r.idx, slot = sb + OFF_B + r.idx * SLOT_B;
          if (k < 10) {
            mbar_expect_tx(bar, 40960);
            tma4d(slot + 8192, &maps.qm, bar, 0, 64 * k, 0, j);
            tma3d(slot, &maps.w1m, bar, 0, 64 * k, j);
            tma4d(slot + 32768 + 2048, &maps.qr, bar, 64, 64 * k, 0, j);
            tma3d(slot + 32768, &maps.w1r, bar, 64, 64 * k, j);
          } else if (k < 13) {
            mbar_expect_tx(bar, k < 12 ? 40960 : 20480);
            tma3d(slot, &maps.w2, bar, 0, 320 * rank + 128 * (k - 10), 5 * (j >> 1));
            if (k < 12) tma3d(slot + 20480, &maps.w2, bar, 0, 320 * rank + 128 * (k - 10) + 64, 5 * (j >> 1));
          } else {
            mbar_expect_tx(bar, 49152);
            tma3d(slot, &maps.w3, bar, 0, 64 * ((2 * (k - 13) + k3) % 10), 3 * j);
            tma3d(slot + 24576, &maps.w3, bar, 0, 64 * ((2 * (k - 13) + 1 + k3) % 10), 3 * j);
          }
          r.next<NB>();
        }
#pragma unroll 1
        for (int n = 0; n < 8; n++) {
          if (n < 3) { mbar_wait(emptyB + 8 * r.idx, r.phase); r.next<NB>(); }
          if (n >= 4) mbar_wait(bars + 8 * (B_EMPTY4 + n - 4), 0);
          const uint32_t bar = bars + 8 * (B_FULL4 + n), set = sb + ((n >> 1) & 1) * SET4;
          const int h = n & 1, m = ((j >> 1) + 1 + (n >> 1)) & 3;
          mbar_expect_tx(bar, h ? 40960 : 46080);
          tma3d(set + (h ? 46080 : 0), h ? &maps.w4 : &maps.wo, bar, 0, h ? 192 * j + 64 : 80 * j, 5 * m);
          tma3d(set + (h ? 66560 : 25600), &maps.w4, bar, 0, 192 * j + 128 * h, 5 * m);
        }
        mbar_wait(bars + 8 * (B_EMPTY4 + 4), 0);
        mbar_expect_tx(bars + 8 * B_XR, 20480);
        tma2d(sb + OFF_OUT, &maps.st_x1, bars + 8 * B_XR, 80 * j, 128 * i);
      }
    } else {
      const unsigned epoch = get_epoch();
      float* accg = g_acc[epoch & 1];
      if (pw == 2) {
        if (tid == 320) {
          flag_wait(FL_CS, (epoch + 1) * NSVC);
          flag_wait(FL_ST + i, (epoch + 1) * 8u);
          fence_async_glb();
          *reinterpret_cast<volatile uint32_t*>(sgen + OFF_BAR + 8 * NBAR) = (epoch + 1) & 1;
          mbar_expect_tx(bars + 8 * B_CS, 320 + 2048 + 12800);
          bulk_load(sb + OFF_CS, g_cs[epoch & 1] + 80 * j, 320, bars + 8 * B_CS);
          bulk_load(sb + OFF_XST, g_xstat + 128 * i, 2048, bars + 8 * B_CS);
          bulk_load(sb + OFF_MISC, g_wphi + j * 800, 12800, bars + 8 * B_CS);
          TSTAMPX(21);
          flag_wait(FL_KV + j, (epoch + 1) * 16u);
          mbar_wait(bars + 8 * B_SIGX1, 0);
          mbar_expect_tx(bars + 8 * B_KV, KV_J * 4);
          bulk_load(sb + OFF_A + SLOT_A, accg + j * KV_J, KV_J * 4, bars + 8 * B_KV);
          TSTAMPX(22);
          flag_wait(FL_CS3, (epoch + 1) * NSVC);
          flag_wait(FL_S1 + i, (epoch + 1) * 8u);
          fence_async_glb();
          mbar_expect_tx(bars + 8 * B_ST1, 8192 + 768);
          bulk_load(sb + OFF_CS + 320, g_cs[epoch & 1] + D_ + 192 * j, 768, bars + 8 * B_ST1);
          bulk_load(sb + OFF_MISC, g_st1 + 128 * i * 8, 8192, bars + 8 * B_ST1);
        }
        __syncwarp();
#pragma unroll 1
        for (int c = 0; c < 3; c++) {
          mbar_wait(bars + 8 * (B_EMPTY4 + (c ? 5 : 4)), 0);
          const uint4* src = g_part + (size_t)((i * 8 + j) * 3 + c) * 1280;
          const unsigned* tp = reinterpret_cast<const unsigned*>(src + 1024 + (lane & 7) * 32 + 31);
          uint32_t n = 0;
          while (!__all_sync(0xffffffffu, (ld_acquire(tp) ^ epoch) & 1u) && ++n < (WAIT_LIMIT >> 2)) {}
          if (tid == 320) {
            mbar_expect_tx(bars + 8 * (B_RDY + c), 20480);
            bulk_load(sb + (c ? 25600 + 20480 * c : 0), src, 20480, bars + 8 * (B_RDY + c));
          }
        }
      }
      if (tid == 352) {
        mbar_wait(bars + 8 * B_SIGP, 0);
        flag_add(FL_ST + i);
        TSTAMPX(20);
        const int shift = (j < 2) ? 1 : (j < 4) ? -1 : (j < 6) ? 2 : -2;
        prefetch_tmap(&maps.st_h); prefetch_tmap(&maps.st_x1); prefetch_tmap(&maps.hs); prefetch_tmap(&maps.x1); prefetch_tmap(&maps.xr);
        prefetch_tmap(&maps.w2); prefetch_tmap(&maps.w3); prefetch_tmap(&maps.w4); prefetch_tmap(&maps.wo);
        mbar_wait(bars + 8 * B_SIGH, 0);
        TSTAMPX(23);
        fence_async_smem();
        tma2d_store(&maps.st_h, sb + OFF_STG, 80 * j, 128 * i + 2 + shift);
        bulk_commit(); bulk_wait<0>();
        flag_add(FL_H + 2 * i + (j >> 2));
        flag_add_relaxed(FL_H + 2 * ((i + (shift > 0 ? 1 : -1)) & 15) + (j >> 2));
        mbar_arrive(bars + 8 * B_HST);
        TSTAMPX(24);
        mbar_expect_tx(bars + 8 * B_XR, 20480);
#pragma unroll 1
        for (int u = 0; u < 8; u++)
          tma2d(sb + OFF_B + (u / 3) * SLOT_B + SPARE + (u % 3) * 2560, &maps.xr, bars + 8 * B_XR, 80 * j, 128 * i + 16 * u);
        mbar_wait(bars + 8 * B_SIGKV, 0);
        TSTAMPX(25);
        fence_async_smem();
        asm volatile("cp.reduce.async.bulk.global.shared::cta.bulk_group.add.f32 [%0], [%1], %2;"
                     ::"l"(accg + j * KV_J), "r"(sb + OFF_MISC), "r"(KV_J * 4) : "memory");
        bulk_commit(); bulk_wait<0>();
        flag_add(FL_KV + j);
        TSTAMPX(26);
        mbar_wait(bars + 8 * B_SIGX1, 0);
        TSTAMPX(27);
        fence_async_smem();
        tma2d_store(&maps.st_x1, sb + OFF_STG, 80 * j, 128 * i);
        bulk_commit(); bulk_wait<0>();
        flag_add(FL_X1 + i);
        mbar_arrive_cta(bars + 8 * B_X1P, 0); mbar_arrive_cta(bars + 8 * B_X1P, 1);
        TSTAMPX(28);
        mbar_wait(bars + 8 * B_MFREE, 0);
        flag_add(FL_S1 + i);
      }
    }
  } else {
    uint4 pv[5], pw_[5];
    {
      const int row = 128 * i + 16 * j + (tid >> 4), l16 = tid & 15;
#pragma unroll
      for (int c = 0; c < 5; c++) pv[c] = __ldg(reinterpret_cast<const uint4*>(x + (size_t)row * D_ + c * 128 + l16 * 8));
#pragma unroll
      for (int c = 0; c < 5; c++) pw_[c] = __ldg(reinterpret_cast<const uint4*>(gate_w + c * 128 + l16 * 8));
    }
    asm volatile("barrier.cluster.arrive.relaxed.aligned;" ::: "memory");
    asm volatile("setmaxnreg.inc.sync.aligned.u32 232;");
    const int wg = tid >> 7, warp = tid >> 5, lane = tid & 31, t = lane & 3;
    const int rloc = warp * 16 + (lane >> 2);
    const float* s_cs = reinterpret_cast<const float*>(sgen + OFF_CS);
    auto signal = [&](int b) {
      __syncwarp();
      if (lane == 0) mbar_arrive(bars + 8 * b);
    };
    auto releaseB = [&](uint32_t bar) {
      __syncwarp();
      if (lane == 0) mbar_arrive(bar);
    };
    auto release = [&](uint32_t bar) {
      __syncwarp();
      if (lane < 2) mbar_arrive_cta(bar, lane);
    };
    const uint32_t stg_lane = (warp * 16 + ((lane >> 3) & 1) * 8 + (lane & 7)) * 160 + (lane >> 4) * 16;

    auto stage_tile = [&](uint32_t stg, const uint32_t (&v)[2][10]) {
#pragma unroll
      for (int s = 0; s < 5; s++) stsm4(stg + stg_lane + s * 32, v[0][2 * s], v[1][2 * s], v[0][2 * s + 1], v[1][2 * s + 1]);
    };

    {
      float f[40];
      float s = 0.f, gs = 0.f;
#pragma unroll
      for (int c = 0; c < 5; c++) {
        const uint32_t vv[4] = {pv[c].x, pv[c].y, pv[c].z, pv[c].w}, ww[4] = {pw_[c].x, pw_[c].y, pw_[c].z, pw_[c].w};
#pragma unroll
        for (int e = 0; e < 4; e++) {
          f[8 * c + 2 * e] = bf_lo(vv[e]); f[8 * c + 2 * e + 1] = bf_hi(vv[e]);
          s += f[8 * c + 2 * e] + f[8 * c + 2 * e + 1];
          gs = fmaf(f[8 * c + 2 * e], bf_lo(ww[e]), gs); gs = fmaf(f[8 * c + 2 * e + 1], bf_hi(ww[e]), gs);
        }
      }
#pragma unroll
      for (int o = 1; o < 16; o <<= 1) { s += __shfl_xor_sync(0xffffffffu, s, o); gs += __shfl_xor_sync(0xffffffffu, gs, o); }
      const float mean = s * (1.f / D_);
      float q = 0.f;
#pragma unroll
      for (int e = 0; e < 40; e++) { const float d = f[e] - mean; q = fmaf(d, d, q); }
#pragma unroll
      for (int o = 1; o < 16; o <<= 1) q += __shfl_xor_sync(0xffffffffu, q, o);
      const float rstd = rsqrtf(q * (1.f / D_) + 1e-5f);
      asm volatile("barrier.cluster.wait.aligned;" ::: "memory");
      if ((tid & 15) == 0) g_xstat[128 * i + 16 * j + (tid >> 4)] = make_float4(rstd, -mean, rcp(1.f + __expf(-gs)), 0.f);
      signal(B_SIGP);
    }
    TSTAMP(1);

    Ring ra{0, 0}, rb{0, 0};
    uint32_t qp[2][10], P[2][10];
    float st_g[2];
    {
      float accM[128], accR[32];
      uint32_t pa = 0, pb = 0;
#pragma unroll 1
      for (int k = 0; k < 10; k++) {
        mbar_wait(fullA + 8 * ra.idx, ra.phase);
        if (tid == 0) TRACE(32 + k);
        mbar_wait(fullB + 8 * rb.idx, rb.phase);
        if (tid == 0) TRACE(64 + k);
        if (k == 0) TSTAMP(2);
        const uint32_t a0 = sb16 + ((OFF_A + ra.idx * SLOT_A + wg * 8192) >> 4), b0 = sb16 + ((OFF_B + rb.idx * SLOT_B) >> 4);
        wg_fence();
#pragma unroll
        for (int kk = 0; kk < 4; kk++) {
          const uint64_t da = make_desc(a0, kk * 32, 16, 1024, 1);
          if (kk == 0) {
            mma_ss256_p(accM, da, make_desc(b0, 0, 8192, 1024, 1), k);
            mma_ss64_p(accR, da, make_desc(b0, 32768, 2048, 256, 3), k);
          } else {
            mma_ss256(accM, da, make_desc(b0, kk * 2048, 8192, 1024, 1));
            mma_ss64(accR, da, make_desc(b0, 32768 + kk * 512, 2048, 256, 3));
          }
          if (kk == 0) {
            wg_commit();
            if (k > 0) {
              wg_wait<1>();
              if (k - 1 < 8) release(emptyA + 8 * pa);
              releaseB(emptyB + 8 * pb);
            }
          }
        }
        wg_commit();
        pa = ra.idx; pb = rb.idx;
        ra.next<NA>(); rb.next<NB>();
      }
      TSTAMP(18);
      float st_rstd[2], st_mr[2];
      mbar_wait(bars + 8 * B_CS, 0);
#pragma unroll
      for (int r = 0; r < 2; r++) {
        const uint4 st = lds128(sb + OFF_XST + (rloc + 8 * r) * 16);
        st_rstd[r] = __uint_as_float(st.x); st_mr[r] = __uint_as_float(st.y); st_g[r] = __uint_as_float(st.z);
      }
      TSTAMP(19);
      wg_wait<0>();
      fence_regs(accM); fence_regs(accR);
      TSTAMP(3);
#define ACC(P_, G, I_) ((G) < 8 ? accM[(P_) * 32 + ((G) & 7) * 4 + (I_)] : accR[(P_) * 8 + ((G) & 1) * 4 + (I_)])
      {
        uint32_t hv[2][10];
        const GeluC g0 = gelu_consts(st_rstd[0], 1.f), g1 = gelu_consts(st_rstd[1], 1.f);
#pragma unroll
        for (int g = 0; g < 10; g++) {
          const float2 cs = *reinterpret_cast<const float2*>(s_cs + 8 * g + 2 * t);
          const float v0 = gelu_s(fmaf(st_mr[0], cs.x, ACC(0, g, 0)), g0), v1 = gelu_s(fmaf(st_mr[0], cs.y, ACC(0, g, 1)), g0);
          const float v2 = gelu_s(fmaf(st_mr[1], cs.x, ACC(0, g, 2)), g1), v3 = gelu_s(fmaf(st_mr[1], cs.y, ACC(0, g, 3)), g1);
          hv[0][g] = pack_bf16(v0, v1); hv[1][g] = pack_bf16(v2, v3);
        }
        bar_sync(1, 256);
        stage_tile(sb + OFF_STG, hv);
        signal(B_SIGH);
      }
      TSTAMP(4);
      uint32_t kf[5][4], qf[5][4];
#pragma unroll
      for (int s = 0; s < 5; s++) {
        kf[s][0] = pack_bf16(ACC(2, 2 * s, 0), ACC(2, 2 * s, 1)); kf[s][1] = pack_bf16(ACC(2, 2 * s, 2), ACC(2, 2 * s, 3));
        kf[s][2] = pack_bf16(ACC(2, 2 * s + 1, 0), ACC(2, 2 * s + 1, 1)); kf[s][3] = pack_bf16(ACC(2, 2 * s + 1, 2), ACC(2, 2 * s + 1, 3));
        qf[s][0] = pack_bf16(ACC(1, 2 * s, 0), ACC(1, 2 * s, 1)); qf[s][1] = pack_bf16(ACC(1, 2 * s, 2), ACC(1, 2 * s, 3));
        qf[s][2] = pack_bf16(ACC(1, 2 * s + 1, 0), ACC(1, 2 * s + 1, 1)); qf[s][3] = pack_bf16(ACC(1, 2 * s + 1, 2), ACC(1, 2 * s + 1, 3));
      }
      float pk[40], pq[40];
      wg_fence();
#pragma unroll
      for (int s = 0; s < 5; s++) {
        if (s == 0) mma_rs80_k_z(pk, kf[s], make_desc(sb16, OFF_MISC, 16, 256, 3));
        else mma_rs80_k(pk, kf[s], make_desc(sb16, OFF_MISC + s * 2560, 16, 256, 3));
      }
      wg_commit();
#pragma unroll
      for (int s = 0; s < 5; s++) {
        if (s == 0) mma_rs80_k_z(pq, qf[s], make_desc(sb16, OFF_MISC, 16, 256, 3));
        else mma_rs80_k(pq, qf[s], make_desc(sb16, OFF_MISC + s * 2560, 16, 256, 3));
      }
      wg_commit();
      {
        const int mat = lane >> 3;
        const int tok = warp * 16 + (mat & 1) * 8 + (lane & 7);
        const uint32_t ones = (t == 0) ? 0x00003f80u : 0u;
        __syncwarp();
#pragma unroll
        for (int p = 0; p < 2; p++) {
          const uint32_t rowa = sb + OFF_A + p * SLOT_A + tok * 128;
#pragma unroll
          for (int gg = 0; gg < 3; gg++) {
            const int g0 = 5 * p + 2 * gg;
            uint32_t r0 = pack_bf16(ACC(3, g0, 0), ACC(3, g0, 1)), r1 = pack_bf16(ACC(3, g0, 2), ACC(3, g0, 3));
            uint32_t r2 = ones, r3 = ones;
            if (gg < 2) { r2 = pack_bf16(ACC(3, g0 + 1, 0), ACC(3, g0 + 1, 1)); r3 = pack_bf16(ACC(3, g0 + 1, 2), ACC(3, g0 + 1, 3)); }
            stsm4(rowa + (((2 * gg + (mat >> 1)) ^ (tok & 7)) << 4), r0, r1, r2, r3);
          }
        }
      }
#undef ACC
      wg_wait<1>();
      fence_regs(pk);
#pragma unroll
      for (int G = 0; G < 10; G++) {
        P[0][G] = pack_bf16(pk[4 * G], pk[4 * G + 1]); P[1][G] = pack_bf16(pk[4 * G + 2], pk[4 * G + 3]);
      }
      wg_wait<0>();
      fence_regs(pq);
#pragma unroll
      for (int G = 0; G < 10; G++) {
        qp[0][G] = pack_bf16(pq[4 * G], pq[4 * G + 1]); qp[1][G] = pack_bf16(pq[4 * G + 2], pq[4 * G + 3]);
      }
    }

    uint32_t fr[10][4];
    int pass;
    pass = gridDim.y;
#pragma unroll 1
    do {
    feature_map(P, fr);
    if (pass != 0) {
    {
      const int mat = lane >> 3;
      const int tok = warp * 16 + (mat & 1) * 8 + (lane & 7);
      const uint32_t base = sb + OFF_B + tok * 32 + (((mat >> 1) ^ ((tok >> 2) & 1)) << 4);
#pragma unroll
      for (int G = 0; G < 10; G++) stsm4(base + G * 4096, fr[G][0], fr[G][1], fr[G][2], fr[G][3]);
      fence_async_smem();
      bar_sync(1, 256);
      float kv[40];
      const uint32_t va = sb16 + ((OFF_A + wg * SLOT_A) >> 4), vb = sb16 + ((OFF_B + wg * 20480) >> 4);
      wg_fence();
#pragma unroll
      for (int ks = 0; ks < 8; ks++) {
        if (ks == 0) mma_ss80_tt_z(kv, make_desc(va, 0, 16, 1024, 1), make_desc(vb, 0, 4096, 256, 3));
        else mma_ss80_tt(kv, make_desc(va, ks * 2048, 16, 1024, 1), make_desc(vb, ks * 512, 4096, 256, 3));
      }
      wg_commit();
      uint32_t xv[2][10];
      float acc[80];
      wg_wait<0>();
      release(emptyA); release(emptyA + 8); releaseB(emptyB); release(bars + 8 * B_PEER2);
      TSTAMP(5);
      mbar_wait(fullA + 8 * 2, 0);
      mbar_wait(fullB + 8 * 1, 1);
      TSTAMP(6);
      wg_fence();
#pragma unroll
      for (int kk = 0; kk < 4; kk++) {
        const uint64_t da = make_desc(sb16 + wg * 512, OFF_A + 2 * SLOT_A + kk * 32, 16, 1024, 1);
        const uint64_t db = make_desc(sb16, OFF_B + SLOT_B + kk * 1024, 4096, 512, 2);
        if (kk == 0) mma_ss160_z(acc, da, db); else mma_ss160(acc, da, db);
      }
      wg_commit();
      ra.next<NA>();
      wg_wait<1>();
      fence_regs(kv);
      TSTAMP(31);
      const uint32_t dst = sb + OFF_MISC + wg * (KV_PAIR * 4);
      const int m0 = (warp & 3) * 16 + (lane >> 2);
#pragma unroll
      for (int r = 0; r < 2; r++) {
        const int m = m0 + 8 * r;
        const bool hi = m >= 20;
        uint32_t v[10];
#pragma unroll
        for (int G = 0; G < 10; G++) v[G] = __float_as_uint(hi ? kv[4 * G + 2 * r + 1] : kv[4 * G + 2 * r]);
        const uint32_t p = dst + 4 * (m < 40 ? m * 48 + t * 12 : 1920 + t * 24 + 12);
        if (m <= 40) {
          sts128(p, make_uint4(v[0], v[1], v[2], v[3])); sts128(p + 16, make_uint4(v[4], v[5], v[6], v[7]));
          sts128(p + 32, make_uint4(v[8], v[9], 0u, 0u));
        }
      }
      if (m0 == 32) {
        const uint32_t p = dst + 4 * (1920 + t * 24);
        sts128(p, make_uint4(__float_as_uint(kv[2]), __float_as_uint(kv[6]), __float_as_uint(kv[10]), __float_as_uint(kv[14])));
        sts128(p + 16, make_uint4(__float_as_uint(kv[18]), __float_as_uint(kv[22]), __float_as_uint(kv[26]), __float_as_uint(kv[30])));
        sts128(p + 32, make_uint4(__float_as_uint(kv[34]), __float_as_uint(kv[38]), 0u, 0u));
      }
      signal(B_SIGKV);
      {
        mbar_wait(bars + 8 * B_XR, 0);
        const uint32_t xa = sb + OFF_B + (warp / 3) * SLOT_B + SPARE + (warp % 3) * 2560 + (lane >> 2) * 160 + t * 4;
#pragma unroll
        for (int g = 0; g < 10; g++) { xv[0][g] = lds32(xa + g * 16); xv[1][g] = lds32(xa + 1280 + g * 16); }
      }
      uint32_t pa = 2, pb = 1;
#pragma unroll 1
      for (int k = 1; k < 5; k++) {
        mbar_wait(fullA + 8 * ra.idx, ra.phase);
        if ((k & 1) == 0) mbar_wait(fullB + 8 * rb.idx, rb.phase);
        const uint32_t a0 = sb16 + ((OFF_A + ra.idx * SLOT_A + wg * 8192) >> 4);
        const uint32_t b0 = sb16 + ((OFF_B + rb.idx * SLOT_B + (k & 1) * 20480) >> 4);
        wg_fence();
#pragma unroll
        for (int kk = 0; kk < 4; kk++) {
          mma_ss160(acc, make_desc(a0, kk * 32, 16, 1024, 1), make_desc(b0, kk * 1024, 4096, 512, 2));
          if (kk == 0) {
            wg_commit();
            wg_wait<1>();
            if (k != 4) release(emptyA + 8 * pa);
            if ((k & 1) == 0) releaseB(emptyB + 8 * pb);
          }
        }
        wg_commit();
        pa = ra.idx; pb = rb.idx;
        ra.next<NA>();
        if ((k & 1) || k == 4) rb.next<NB>();
      }
      mbar_wait(bars + 8 * B_PEER2, 0);
      wg_wait<0>();
      fence_regs(acc);
      release(emptyA + 8 * pa);
      TSTAMP(7);
      {
        uint32_t sn[20];
        if (rank) {
#pragma unroll
          for (int e = 0; e < 20; e++) sn[e] = pack_bf16(acc[2 * e], acc[2 * e + 1]);
#pragma unroll
          for (int e = 0; e < 40; e++) acc[e] = acc[40 + e];
        } else {
#pragma unroll
          for (int e = 0; e < 20; e++) sn[e] = pack_bf16(acc[40 + 2 * e], acc[41 + 2 * e]);
        }
        const uint32_t peer = map_peer(sb, rank ^ 1);
#pragma unroll
        for (int q = 0; q < 5; q++)
          st_async16(peer + OFF_B + 20480 + tid * 16 + q * 4096, sn[4 * q], sn[4 * q + 1], sn[4 * q + 2], sn[4 * q + 3],
                     peer + OFF_BAR + 8 * (B_DSR + 8 + wg));
#pragma unroll
        for (int g = 0; g < 10; g++) {
          acc[4 * g] += bf_lo(xv[0][g]); acc[4 * g + 1] += bf_hi(xv[0][g]);
          acc[4 * g + 2] += bf_lo(xv[1][g]); acc[4 * g + 3] += bf_hi(xv[1][g]);
        }
        bar_sync(1, 256);
        mbar_wait(bars + 8 * (B_DSR + 8 + wg), 0);
#pragma unroll
        for (int q = 0; q < 5; q++) {
          const uint4 v = lds128(sb + OFF_B + 20480 + tid * 16 + q * 4096);
          float* d = &acc[8 * q];
          d[0] += bf_lo(v.x); d[1] += bf_hi(v.x); d[2] += bf_lo(v.y); d[3] += bf_hi(v.y);
          d[4] += bf_lo(v.z); d[5] += bf_hi(v.z); d[6] += bf_lo(v.w); d[7] += bf_hi(v.w);
          xv[0][2 * q] = pack_bf16(d[0], d[1]); xv[1][2 * q] = pack_bf16(d[2], d[3]);
          xv[0][2 * q + 1] = pack_bf16(d[4], d[5]); xv[1][2 * q + 1] = pack_bf16(d[6], d[7]);
        }
        releaseB(emptyB + 8 * pb);
      }
      TSTAMP(16);
      stage_tile(sb + OFF_STG, xv);
      signal(B_SIGX1);
      TSTAMP(17);
#pragma unroll
      for (int r = 0; r < 2; r++) {
        float s = 0.f;
#pragma unroll
        for (int g = 0; g < 10; g++) s += acc[4 * g + 2 * r] + acc[4 * g + 2 * r + 1];
        s += __shfl_xor_sync(0xffffffffu, s, 1); s += __shfl_xor_sync(0xffffffffu, s, 2);
        const float mu = s * (1.f / 80.f);
        float q = 0.f;
#pragma unroll
        for (int g = 0; g < 10; g++) {
          const float d0 = acc[4 * g + 2 * r] - mu, d1 = acc[4 * g + 2 * r + 1] - mu;
          q = fmaf(d0, d0, q); q = fmaf(d1, d1, q);
        }
        q += __shfl_xor_sync(0xffffffffu, q, 1); q += __shfl_xor_sync(0xffffffffu, q, 2);
        if (t == 0) g_st1[(128 * i + rloc + 8 * r) * 8 + j] = make_float2(mu, q);
      }
    }
    TSTAMP(8);
#pragma unroll
    for (int G = 0; G < 10; G++) { P[0][G] = qp[0][G]; P[1][G] = qp[1][G]; }
    }
    asm volatile("" : "+r"(pass));
    } while (pass-- != 0);

    uint32_t of[5][4];
    {
      mbar_wait(bars + 8 * B_KV, 0);
#pragma unroll 1
      for (int it = tid; it < 384; it += 256) {
        const int p = it >= 192, rem = it - 192 * p, n = rem >> 2, tq = rem & 3;
        const uint32_t sp = sb + OFF_A + SLOT_A + 4 * (p * KV_PAIR + (n < 40 ? n * 48 + tq * 12 : 1920 + tq * 24 + (n & 1) * 12));
        const uint4 ka = lds128(sp), kb = lds128(sp + 16), kc = lds128(sp + 32);
        const uint32_t v[10] = {ka.x, ka.y, ka.z, ka.w, kb.x, kb.y, kb.z, kb.w, kc.x, kc.y};
        const int sh = (n < 40 ? (n >= 20) : (n & 1)) * 16;
        uint8_t* dst = sgen + OFF_MISC + p * 7680 + n * 32 + tq * 4;
        const int sw = ((n >> 2) & 1) << 4;
#pragma unroll
        for (int G = 0; G < 10; G++)
          *reinterpret_cast<uint32_t*>(dst + (G >> 1) * 1536 + (((G & 1) << 4) ^ sw)) = pack_bf16(__uint_as_float(v[G]), 0.f) << sh;
      }
      release(emptyA + 8);
      fence_async_smem();
      bar_sync(1, 256);
      float o0[24], o1[24];
      wg_fence();
#pragma unroll
      for (int g = 0; g < 5; g++) {
        if (g == 0) mma_rs48_k_z(o0, fr[g], make_desc(sb16, OFF_MISC, 16, 256, 3));
        else mma_rs48_k(o0, fr[g], make_desc(sb16, OFF_MISC + g * 1536, 16, 256, 3));
      }
#pragma unroll
      for (int g = 0; g < 5; g++) {
        if (g == 0) mma_rs48_k_z(o1, fr[5], make_desc(sb16, OFF_MISC + 7680, 16, 256, 3));
        else mma_rs48_k(o1, fr[5 + g], make_desc(sb16, OFF_MISC + 7680 + g * 1536, 16, 256, 3));
      }
      wg_commit();
      wg_wait<0>();
      fence_regs(o0); fence_regs(o1);
      signal(B_MFREE);
#pragma unroll
      for (int r = 0; r < 2; r++) {
        const float a0 = __fdividef(st_g[r], o0[20 + 2 * r] + 1e-6f), a1 = __fdividef(st_g[r], o0[21 + 2 * r] + 1e-6f);
        const float b0 = __fdividef(st_g[r], o1[20 + 2 * r] + 1e-6f), b1 = __fdividef(st_g[r], o1[21 + 2 * r] + 1e-6f);
        const float am = t < 2 ? a0 : a1, bm = t < 2 ? b0 : b1;
#pragma unroll
        for (int g = 0; g < 5; g++) {
          const float sa = g < 2 ? a0 : (g == 2 ? am : a1), sb2 = g < 2 ? b0 : (g == 2 ? bm : b1);
          of[g >> 1][(g & 1) * 2 + r] = pack_bf16(o0[4 * g + 2 * r] * sa, o0[4 * g + 2 * r + 1] * sa);
          of[(5 + g) >> 1][((5 + g) & 1) * 2 + r] = pack_bf16(o1[4 * g + 2 * r] * sb2, o1[4 * g + 2 * r + 1] * sb2);
        }
      }
    }
    TSTAMP(9);

    uint32_t hf[12][4];
    float ac4[80];
    auto unit = [&](auto uc, uint32_t b0) {
      constexpr int u = decltype(uc)::value;
#pragma unroll
      for (int s = 0; s < (u ? 4 : 5); s++) {
        const uint64_t db = make_desc(b0, (u ? 5120 + 20480 * u : 0) + s * 1024, u ? 4096 : 5120, 512, 2);
        if (u == 0 && s == 0) mma_rs160_n_z(ac4, of[0], db);
        else if (u == 0) mma_rs160_n(ac4, of[s], db);
        else mma_rs160_n(ac4, hf[(4 * u + 8 + s) % 12], db);
      }
      wg_commit();
    };
    {
      float acc[96];
      uint32_t pa = 0, pb = 0;
#pragma unroll 1
      for (int k = 0; k < 10; k++) {
        mbar_wait(fullA + 8 * ra.idx, ra.phase);
        if (tid == 0) TRACE(52 + k);
        if ((k & 1) == 0) mbar_wait(fullB + 8 * rb.idx, rb.phase);
        if (tid == 0) TRACE(84 + k);
        if (k == 0) TSTAMP(10);
        const uint32_t a0 = sb16 + ((OFF_A + ra.idx * SLOT_A + wg * 8192) >> 4);
        const uint32_t b0 = sb16 + ((OFF_B + rb.idx * SLOT_B + (k & 1) * 24576) >> 4);
        wg_fence();
#pragma unroll
        for (int kk = 0; kk < 4; kk++) {
          if (kk == 0) mma_ss192_p(acc, make_desc(a0, 0, 16, 1024, 1), make_desc(b0, 0, 8192, 1024, 1), k);
          else mma_ss192(acc, make_desc(a0, kk * 32, 16, 1024, 1), make_desc(b0, kk * 2048, 8192, 1024, 1));
          if (kk == 0) {
            wg_commit();
            if (k > 0) {
              wg_wait<1>();
              release(emptyA + 8 * pa);
              if ((k & 1) == 0) releaseB(emptyB + 8 * pb);
            }
          }
        }
        wg_commit();
        pa = ra.idx; pb = rb.idx;
        ra.next<NA>();
        if (k & 1) rb.next<NB>();
      }
      float rs[2], mm[2];
      mbar_wait(bars + 8 * B_ST1, 0);
#pragma unroll
      for (int r = 0; r < 2; r++) {
        const uint4 su = lds128(sb + OFF_MISC + (rloc + 8 * r) * 64 + t * 16);
        const float m0 = __uint_as_float(su.x), m1 = __uint_as_float(su.z);
        float mu = m0 + m1;
        mu += __shfl_xor_sync(0xffffffffu, mu, 1); mu += __shfl_xor_sync(0xffffffffu, mu, 2);
        mu *= 0.125f;
        const float d0 = m0 - mu, d1 = m1 - mu;
        float q = __uint_as_float(su.y) + __uint_as_float(su.w) + 80.f * (d0 * d0 + d1 * d1);
        q += __shfl_xor_sync(0xffffffffu, q, 1); q += __shfl_xor_sync(0xffffffffu, q, 2);
        rs[r] = rsqrtf(q * (1.f / D_) + 1e-5f);
        mm[r] = -mu;
      }
      mbar_wait(bars + 8 * B_FULL4, 0);
      wg_fence();
      unit(IntC<0>{}, sb16);
      wg_wait<1>();
      fence_regs(acc);
      releaseB(emptyB + 8 * pb);
      release(bars + 8 * B_PEER);
      TSTAMP(11);
      const GeluC g0 = gelu_consts(rs[0], 1.f - st_g[0]), g1 = gelu_consts(rs[1], 1.f - st_g[1]);
#pragma unroll
      for (int g = 0; g < 24; g++) {
        const float2 cs = *reinterpret_cast<const float2*>(s_cs + 80 + 8 * g + 2 * t);
        const float v0 = gelu_s(fmaf(mm[0], cs.x, acc[4 * g]), g0), v1 = gelu_s(fmaf(mm[0], cs.y, acc[4 * g + 1]), g0);
        const float v2 = gelu_s(fmaf(mm[1], cs.x, acc[4 * g + 2]), g1), v3 = gelu_s(fmaf(mm[1], cs.y, acc[4 * g + 3]), g1);
        hf[g >> 1][(g & 1) * 2] = pack_bf16(v0, v1);
        hf[g >> 1][(g & 1) * 2 + 1] = pack_bf16(v2, v3);
        if (g == 7) { wg_fence(); unit(IntC<1>{}, sb16); }
        if (g == 15) { mbar_wait(bars + 8 * (B_FULL4 + 1), 0); wg_fence(); unit(IntC<2>{}, sb16); }
        if (g == 23) { wg_wait<1>(); signal(B_EMPTY4); wg_fence(); unit(IntC<3>{}, sb16); }
      }
    }
    TSTAMP(12);

    {
      float kp[40];
      uint32_t sn[20], kb[20];
      const uint32_t peer = map_peer(sb, rank ^ 1);
      const uint32_t tag = lds32(sb + OFF_BAR + 8 * NBAR);
      auto add8 = [&](int q, const uint4 v) {
        float* d = &kp[8 * q];
        d[0] += bf_lo(v.x); d[1] += bf_hi(v.x); d[2] += bf_lo(v.y); d[3] += bf_hi(v.y);
        d[4] += bf_lo(v.z); d[5] += bf_hi(v.z); d[6] += bf_lo(v.w); d[7] += bf_hi(v.w);
      };
      auto send = [&](int c) {
        const uint32_t dso = peer + OFF_DS + (c & 1) * 20480 + tid * 16, dsb = peer + OFF_BAR + 8 * (B_DSR + 2 * c + wg);
#pragma unroll
        for (int q = 0; q < 5; q++) st_async16(dso + q * 4096, sn[4 * q], sn[4 * q + 1], sn[4 * q + 2], sn[4 * q + 3], dsb);
      };
      mbar_wait(bars + 8 * B_PEER, 0);
      uint4* gdst = g_part + (size_t)i * 8 * 3840 + tid;
#pragma unroll 1
      for (int c = 0; c < 3; c++) {
        const uint32_t b0 = sb16 + ((c & 1) ? 0 : SET4 >> 4), bc = bars + 16 * c;
        mbar_wait(bc + 8 * (B_FULL4 + 2), 0);
        wg_wait<0>();
        fence_regs(ac4);
        if (rank) {
#pragma unroll
          for (int e = 0; e < 20; e++) { sn[e] = pack_bf16(ac4[2 * e], ac4[2 * e + 1]); kb[e] = pack_bf16(ac4[40 + 2 * e], ac4[41 + 2 * e]); }
        } else {
#pragma unroll
          for (int e = 0; e < 20; e++) { kb[e] = pack_bf16(ac4[2 * e], ac4[2 * e + 1]); sn[e] = pack_bf16(ac4[40 + 2 * e], ac4[41 + 2 * e]); }
        }
#pragma unroll
        for (int e = 0; e < 20; e++) asm volatile("" : "+r"(sn[e]), "+r"(kb[e]));
        send(c);
        if (c == 0 && wg == 1) bar_sync(2, 256);
        wg_fence();
        unit(IntC<0>{}, b0);
        if (lane == 0) mbar_arrive(bc + 8 * (B_EMPTY4 + 1));
        unit(IntC<1>{}, b0);
        if (c == 0 && wg == 0) bar_arrive(2, 256);
        {
          mbar_wait(bc + 8 * (B_DSR + wg), 0);
          uint4* dst = gdst + (((j + 2 * c + 2) & 7) * 3 + c) * 1280;
#pragma unroll
          for (int q = 0; q < 5; q++) {
            const uint4 v = lds128(sb + OFF_DS + (c & 1) * 20480 + tid * 16 + q * 4096);
            st_relaxed16(dst + q * 256, (add_bf2(v.x, kb[4 * q]) & ~1u) | tag, add_bf2(v.y, kb[4 * q + 1]),
                         add_bf2(v.z, kb[4 * q + 2]), add_bf2(v.w, kb[4 * q + 3]));
          }
        }
        mbar_wait(bc + 8 * (B_FULL4 + 3), 0);
        wg_fence();
        unit(IntC<2>{}, b0);
        wg_wait<1>();
        if (lane == 0) mbar_arrive(bc + 8 * (B_EMPTY4 + 2));
        unit(IntC<3>{}, b0);
      }
      auto partial = [&](int c, uint4 (&v)[5]) {
        mbar_wait(bars + 8 * (B_RDY + c), 0);
        uint32_t bad = 0;
#pragma unroll
        for (int q = 0; q < 5; q++) { v[q] = lds128(sb + (c ? 25600 + 20480 * c : 0) + tid * 16 + q * 4096); bad |= v[q].x ^ tag; }
#pragma unroll 1
        for (uint32_t n = 0; (bad & 1u) && n < (WAIT_LIMIT >> 2); n++) {
          bad = 0;
#pragma unroll
          for (int q = 0; q < 5; q++) { v[q] = ld_relaxed16(gdst + (j * 3 + c) * 1280 + q * 256); bad |= v[q].x ^ tag; }
        }
      };
      uint4 pa4[5], pb4[5];
      partial(0, pa4);
      wg_wait<0>();
      fence_regs(ac4);
      if (rank) {
#pragma unroll
        for (int e = 0; e < 20; e++) sn[e] = pack_bf16(ac4[2 * e], ac4[2 * e + 1]);
#pragma unroll
        for (int e = 0; e < 40; e++) kp[e] = ac4[40 + e];
      } else {
#pragma unroll
        for (int e = 0; e < 20; e++) sn[e] = pack_bf16(ac4[40 + 2 * e], ac4[41 + 2 * e]);
#pragma unroll
        for (int e = 0; e < 40; e++) kp[e] = ac4[e];
      }
      send(3);
      TSTAMP(13);
      {
        mbar_wait(bars + 8 * B_XR, 1);
        const float w0 = 1.f - st_g[0], w1s = 1.f - st_g[1];
        const uint32_t xa = sb + OFF_OUT + rloc * 160 + t * 4;
#pragma unroll
        for (int g = 0; g < 10; g++) {
          const uint32_t x0 = lds32(xa + g * 16), x1 = lds32(xa + 1280 + g * 16);
          kp[4 * g] = fmaf(w0, bf_lo(x0), kp[4 * g]); kp[4 * g + 1] = fmaf(w0, bf_hi(x0), kp[4 * g + 1]);
          kp[4 * g + 2] = fmaf(w1s, bf_lo(x1), kp[4 * g + 2]); kp[4 * g + 3] = fmaf(w1s, bf_hi(x1), kp[4 * g + 3]);
        }
      }
      partial(1, pb4);
#pragma unroll
      for (int q = 0; q < 5; q++)
        pa4[q] = make_uint4(add_bf2(pa4[q].x, pb4[q].x), add_bf2(pa4[q].y, pb4[q].y), add_bf2(pa4[q].z, pb4[q].z), add_bf2(pa4[q].w, pb4[q].w));
#pragma unroll
      for (int q = 0; q < 5; q++) add8(q, pa4[q]);
      partial(2, pb4);
      mbar_wait(bars + 8 * (B_DSR + 6 + wg), 0);
      TSTAMP(14);
#pragma unroll
      for (int q = 0; q < 5; q++) {
        const uint4 c = pb4[q], d = lds128(sb + OFF_DS + 20480 + tid * 16 + q * 4096);
        add8(q, make_uint4(add_bf2(c.x, d.x), add_bf2(c.y, d.y), add_bf2(c.z, d.z), add_bf2(c.w, d.w)));
      }
      __syncwarp();
      uint32_t ov[2][10];
#pragma unroll
      for (int g = 0; g < 10; g++) { ov[0][g] = pack_bf16(kp[4 * g], kp[4 * g + 1]); ov[1][g] = pack_bf16(kp[4 * g + 2], kp[4 * g + 3]); }
      stage_tile(sb + OFF_OUT, ov);
      __syncwarp();
      __nv_bfloat16* dst = out + (size_t)(128 * i + 16 * warp) * D_ + 80 * j;
#pragma unroll
      for (int q = 0; q < 5; q++) {
        const int id = q * 32 + lane, r = id / 10;
        *reinterpret_cast<uint4*>(dst + r * (D_ - 80) + id * 8) = lds128(sb + OFF_OUT + warp * 2560 + id * 16);
      }
    }
    TSTAMP(15);
    if (tid == 0) asm volatile("red.relaxed.gpu.global.add.u32 [%0], 1;" ::"l"(g_flags + FL_DONE * 32) : "memory");
  }
}

namespace {
typedef CUresult (*EncodeFn)(CUtensorMap*, CUtensorMapDataType, cuuint32_t, void*, const cuuint64_t*, const cuuint64_t*,
                             const cuuint32_t*, const cuuint32_t*, CUtensorMapInterleave, CUtensorMapSwizzle,
                             CUtensorMapL2promotion, CUtensorMapFloatOOBfill);

void encode(EncodeFn fn, CUtensorMap* m, const void* ptr, int rank, const cuuint64_t* dims, const cuuint64_t* strides,
            const cuuint32_t* box, CUtensorMapSwizzle swz) {
  cuuint32_t es[5] = {1, 1, 1, 1, 1};
  fn(m, CU_TENSOR_MAP_DATA_TYPE_BFLOAT16, rank, const_cast<void*>(ptr), dims, strides, box, es, CU_TENSOR_MAP_INTERLEAVE_NONE,
     swz, CU_TENSOR_MAP_L2_PROMOTION_L2_128B, CU_TENSOR_MAP_FLOAT_OOB_FILL_NONE);
}
}

extern "C" void kernel_launch(void* const* d_in, const int* in_sizes, int n_in, void* d_out, int out_size) {
  (void)in_sizes; (void)n_in; (void)out_size;
  const __nv_bfloat16* x = (const __nv_bfloat16*)d_in[0];
  const __nv_bfloat16* wqkv = (const __nv_bfloat16*)d_in[1];
  const __nv_bfloat16* wphi = (const __nv_bfloat16*)d_in[2];
  const __nv_bfloat16* wo = (const __nv_bfloat16*)d_in[3];
  const __nv_bfloat16* w1 = (const __nv_bfloat16*)d_in[5];
  const __nv_bfloat16* w2 = (const __nv_bfloat16*)d_in[6];
  const __nv_bfloat16* w3 = (const __nv_bfloat16*)d_in[7];
  const __nv_bfloat16* w4 = (const __nv_bfloat16*)d_in[8];
  const __nv_bfloat16* gate_w = (const __nv_bfloat16*)d_in[9];

  static EncodeFn enc = nullptr;
  static void *pHs = nullptr, *pX1 = nullptr;
  if (!enc) {
    cudaDriverEntryPointQueryResult qr;
    cudaGetDriverEntryPoint("cuTensorMapEncodeTiled", (void**)&enc, cudaEnableDefault, &qr);
    cudaGetSymbolAddress(&pHs, g_Hs);
    cudaGetSymbolAddress(&pX1, g_X1);
    cudaFuncSetAttribute(fused_kernel, cudaFuncAttributeMaxDynamicSharedMemorySize, SMEM_BYTES);
  }
  Maps m;
  {
    cuuint64_t dims[2] = {D_, S_}, str[1] = {D_ * 2};
    cuuint32_t box[2] = {64, 128}, boxh[2] = {64, 64};
    encode(enc, &m.x, x, 2, dims, str, boxh, CU_TENSOR_MAP_SWIZZLE_128B);
    encode(enc, &m.hs, (const char*)pHs + 2 * D_ * 2, 2, dims, str, box, CU_TENSOR_MAP_SWIZZLE_128B);
    encode(enc, &m.x1, pX1, 2, dims, str, boxh, CU_TENSOR_MAP_SWIZZLE_128B);
    cuuint32_t boxr[2] = {80, 16}, boxs[2] = {80, 128};
    cuuint64_t dimsp[2] = {D_, S_ + 4};
    encode(enc, &m.st_h, pHs, 2, dimsp, str, boxs, CU_TENSOR_MAP_SWIZZLE_NONE);
    encode(enc, &m.st_x1, pX1, 2, dims, str, boxs, CU_TENSOR_MAP_SWIZZLE_NONE);
    encode(enc, &m.xr, x, 2, dims, str, boxr, CU_TENSOR_MAP_SWIZZLE_NONE);
  }
  {
    cuuint64_t dims[3] = {80, D_, 8}, str[2] = {D_ * 2, 160};
    cuuint32_t boxm[3] = {64, 64, 1}, boxr[3] = {16, 64, 1};
    encode(enc, &m.w1m, w1, 3, dims, str, boxm, CU_TENSOR_MAP_SWIZZLE_128B);
    encode(enc, &m.w1r, w1, 3, dims, str, boxr, CU_TENSOR_MAP_SWIZZLE_32B);
  }
  {
    cuuint64_t dims[4] = {80, D_, 3, 8}, str[3] = {3 * D_ * 2, D_ * 2, 160};
    cuuint32_t boxm[4] = {64, 64, 3, 1}, boxr[4] = {16, 64, 3, 1};
    encode(enc, &m.qm, wqkv, 4, dims, str, boxm, CU_TENSOR_MAP_SWIZZLE_128B);
    encode(enc, &m.qr, wqkv, 4, dims, str, boxr, CU_TENSOR_MAP_SWIZZLE_32B);
  }
  {
    cuuint64_t dims[3] = {32, D_, 20}, dims4[3] = {32, F_, 20}, str[2] = {D_ * 2, 64};
    cuuint32_t box4[3] = {32, 64, 5}, boxo[3] = {32, 80, 5};
    encode(enc, &m.w4, w4, 3, dims4, str, box4, CU_TENSOR_MAP_SWIZZLE_64B);
    encode(enc, &m.wo, wo, 3, dims, str, boxo, CU_TENSOR_MAP_SWIZZLE_64B);
    encode(enc, &m.w2, w2, 3, dims, str, box4, CU_TENSOR_MAP_SWIZZLE_64B);
  }
  {
    cuuint64_t dims[3] = {64, D_, 24}, str[2] = {F_ * 2, 128};
    cuuint32_t box[3] = {64, 64, 3};
    encode(enc, &m.w3, w3, 3, dims, str, box, CU_TENSOR_MAP_SWIZZLE_128B);
  }
  fused_kernel<<<NCTA + NSVC, 384, SMEM_BYTES, cudaStreamPerThread>>>(m, x, wqkv, wphi, w1, w2, w3, w4, wo, gate_w, (__nv_bfloat16*)d_out);
}
```

```cpp
#include <cuda_runtime.h>
#include <cuda_bf16.h>
#include <cuda.h>
#include <stdint.h>

namespace {

constexpr int S_ = 2048, D_ = 640, F_ = 1536;
constexpr int NCTA = 128, NSVC = 4;
constexpr int KV_PAIR = 40 * 48 + 96;
constexpr int KV_J = 2 * KV_PAIR;

constexpr int SLOT_B = 49152, NB = 3;
constexpr int SLOT_A = 16384, NA = 4;
constexpr int OFF_B = 0;
constexpr int OFF_A = OFF_B + NB * SLOT_B;
constexpr int OFF_STG = OFF_A + 2 * SLOT_A;
constexpr int OFF_MISC = OFF_A + NA * SLOT_A;
constexpr int OFF_XST = OFF_MISC + 13312;
constexpr int OFF_CS = OFF_MISC + 16384;
constexpr int OFF_BAR = OFF_CS + 1088;
constexpr int SMEM_BYTES = OFF_BAR + 512 + 512 + 128;
constexpr int B_FULLA = 0, B_FULLB = 4, B_CS = 7, B_XR = 8, B_KV = 9, B_ST1 = 10, B_HST = 11, B_FULL4 = 12  , B_RDY = 20  ,
              B_DSR = 23  , B_EMPTYB = 33  , B_SIGP = 36, B_SIGH = 37, B_SIGKV = 38, B_SIGX1 = 39, B_MFREE = 40,
              B_EMPTY4 = 41  , B_EMPTYA = 49  , B_PEER = 53, B_PEER2 = 54, B_X1P = 55  , NBAR = 56;
constexpr int SPARE = 40960;
constexpr int SET4 = 87040, OFF_DS = 2 * SET4, OFF_OUT = 20480;

constexpr int FL_DONE = 0, FL_H = 1  , FL_X1 = FL_H + 32, FL_KV = FL_X1 + 16, FL_CS = FL_KV + 8, FL_CS3 = FL_CS + 1, FL_ST = FL_CS3 + 1;
constexpr int FL_S1 = FL_ST + 16, FL_COUNT = FL_S1 + 16;

struct Maps {
  CUtensorMap x, w1m, w1r, qm, qr, hs, w2, x1, w3, w4, wo, xr, st_h, st_x1;
};

}

__device__ __align__(1024) __nv_bfloat16 g_Hs[(S_ + 4) * D_];
__device__ __align__(1024) __nv_bfloat16 g_X1[S_ * D_];
__device__ __align__(128) float g_acc[2][8 * KV_J];
__device__ __align__(128) float g_cs[2][D_ + F_];
__device__ __align__(128) uint4 g_wphi[8 * 800];
__device__ __align__(128) float4 g_xstat[S_];
__device__ __align__(128) float2 g_st1[S_ * 8];
__device__ __align__(128) uint4 g_part[16 * 8 * 3 * 1280];
__device__ __align__(128) unsigned g_flags[FL_COUNT * 32];
#define TSTAMP(n) do {} while (0)
#define TSTAMPX(n) do {} while (0)
#define TRACE(n) do {} while (0)
#define TRS(n) do {} while (0)

namespace {

__device__ __forceinline__ long long gtime() { long long t; asm volatile("mov.u64 %0, %%globaltimer;" : "=l"(t)); return t; }
__device__ __forceinline__ uint32_t smem_u32(const void* p) { return (uint32_t)__cvta_generic_to_shared(p); }
__device__ __forceinline__ void mbar_init(uint32_t bar, int cnt) {
  asm volatile("mbarrier.init.shared::cta.b64 [%0], %1;" ::"r"(bar), "r"(cnt) : "memory");
}
__device__ __forceinline__ void mbar_expect_tx(uint32_t bar, int bytes) {
  asm volatile("mbarrier.arrive.expect_tx.shared::cta.b64 _, [%0], %1;" ::"r"(bar), "r"(bytes) : "memory");
}
__device__ __forceinline__ void mbar_arrive_cta(uint32_t bar, uint32_t cta) {
  asm volatile("{\n.reg .b32 ra;\nmapa.shared::cluster.u32 ra, %0, %1;\nmbarrier.arrive.shared::cluster.b64 _, [ra];\n}"
               ::"r"(bar), "r"(cta) : "memory");
}
__device__ __forceinline__ uint32_t mbar_try(uint32_t bar, uint32_t parity) {
  uint32_t ok;
  asm volatile("{\n.reg .pred p;\nmbarrier.try_wait.parity.shared::cta.b64 p, [%1], %2;\nselp.u32 %0, 1, 0, p;\n}"
               : "=r"(ok) : "r"(bar), "r"(parity) : "memory");
  return ok;
}
constexpr uint32_t WAIT_LIMIT = 1u << 18;
__device__ __forceinline__ void mbar_wait(uint32_t bar, uint32_t parity) {
  uint32_t n = 0;
  while (!mbar_try(bar, parity) && ++n < WAIT_LIMIT) {}
}
__device__ __forceinline__ unsigned ld_acquire(const unsigned* p) {
  unsigned v;
  asm volatile("ld.acquire.gpu.global.u32 %0, [%1];" : "=r"(v) : "l"(p) : "memory");
  return v;
}
__device__ __forceinline__ void flag_wait(int idx, unsigned target) {
  const unsigned* p = g_flags + idx * 32;
  uint32_t n = 0;
  while ((int)(ld_acquire(p) - target) < 0 && ++n < (WAIT_LIMIT >> 2)) {}
}
__device__ __forceinline__ void flag_add(int idx) {
  asm volatile("red.release.gpu.global.add.u32 [%0], 1;" ::"l"(g_flags + idx * 32) : "memory");
}
__device__ __forceinline__ void flag_add_relaxed(int idx) {
  asm volatile("red.relaxed.gpu.global.add.u32 [%0], 1;" ::"l"(g_flags + idx * 32) : "memory");
}
__device__ __forceinline__ uint32_t mbar_test(uint32_t bar, uint32_t parity) {
  uint32_t ok;
  asm volatile("{\n.reg .pred p;\nmbarrier.test_wait.parity.shared::cta.b64 p, [%1], %2;\nselp.u32 %0, 1, 0, p;\n}"
               : "=r"(ok) : "r"(bar), "r"(parity) : "memory");
  return ok;
}
__device__ __forceinline__ uint32_t lds32(uint32_t a) {
  uint32_t v;
  asm volatile("ld.shared.u32 %0, [%1];" : "=r"(v) : "r"(a) : "memory");
  return v;
}
__device__ __forceinline__ void mbar_arrive(uint32_t bar) {
  asm volatile("mbarrier.arrive.shared::cta.b64 _, [%0];" ::"r"(bar) : "memory");
}
__device__ __forceinline__ void fence_async_glb() { asm volatile("fence.proxy.async.global;" ::: "memory"); }
__device__ __forceinline__ void fence_async_smem() { asm volatile("fence.proxy.async.shared::cta;" ::: "memory"); }
__device__ __forceinline__ void bar_sync(int id, int n) { asm volatile("bar.sync %0, %1;" ::"r"(id), "r"(n) : "memory"); }

__device__ __forceinline__ void tma2d(uint32_t dst, const CUtensorMap* m, uint32_t bar, int c0, int c1) {
  asm volatile("cp.async.bulk.tensor.2d.shared::cluster.global.mbarrier::complete_tx::bytes [%0], [%1, {%3, %4}], [%2];"
               ::"r"(dst), "l"(m), "r"(bar), "r"(c0), "r"(c1) : "memory");
}
__device__ __forceinline__ void tma2d_mc(uint32_t dst, const CUtensorMap* m, uint32_t bar, int c0, int c1) {
  asm volatile("cp.async.bulk.tensor.2d.shared::cluster.global.mbarrier::complete_tx::bytes.multicast::cluster"
               " [%0], [%1, {%3, %4}], [%2], %5;"
               ::"r"(dst), "l"(m), "r"(bar), "r"(c0), "r"(c1), "h"((uint16_t)3) : "memory");
}
__device__ __forceinline__ void tma3d(uint32_t dst, const CUtensorMap* m, uint32_t bar, int c0, int c1, int c2) {
  asm volatile("cp.async.bulk.tensor.3d.shared::cluster.global.mbarrier::complete_tx::bytes [%0], [%1, {%3, %4, %5}], [%2];"
               ::"r"(dst), "l"(m), "r"(bar), "r"(c0), "r"(c1), "r"(c2) : "memory");
}
__device__ __forceinline__ void tma4d(uint32_t dst, const CUtensorMap* m, uint32_t bar, int c0, int c1, int c2, int c3) {
  asm volatile("cp.async.bulk.tensor.4d.shared::cluster.global.mbarrier::complete_tx::bytes [%0], [%1, {%3, %4, %5, %6}], [%2];"
               ::"r"(dst), "l"(m), "r"(bar), "r"(c0), "r"(c1), "r"(c2), "r"(c3) : "memory");
}
__device__ __forceinline__ void tma2d_store(const CUtensorMap* m, uint32_t src, int c0, int c1) {
  asm volatile("cp.async.bulk.tensor.2d.global.shared::cta.bulk_group [%0, {%2, %3}], [%1];"
               ::"l"(m), "r"(src), "r"(c0), "r"(c1) : "memory");
}
__device__ __forceinline__ void bulk_store(void* dst, uint32_t src, uint32_t bytes) {
  asm volatile("cp.async.bulk.global.shared::cta.bulk_group [%0], [%1], %2;" ::"l"(dst), "r"(src), "r"(bytes) : "memory");
}
__device__ __forceinline__ void bulk_load(uint32_t dst, const void* src, uint32_t bytes, uint32_t bar) {
  asm volatile("cp.async.bulk.shared::cluster.global.mbarrier::complete_tx::bytes [%0], [%1], %2, [%3];"
               ::"r"(dst), "l"(src), "r"(bytes), "r"(bar) : "memory");
}
__device__ __forceinline__ void bulk_commit() { asm volatile("cp.async.bulk.commit_group;" ::: "memory"); }
template <int N> __device__ __forceinline__ void bulk_wait() { asm volatile("cp.async.bulk.wait_group %0;" ::"n"(N) : "memory"); }
__device__ __forceinline__ void bulk_wait_read() { asm volatile("cp.async.bulk.wait_group.read 0;" ::: "memory"); }
__device__ __forceinline__ void bar_arrive(int id, int n) { asm volatile("bar.arrive %0, %1;" ::"r"(id), "r"(n) : "memory"); }
__device__ __forceinline__ uint4 lds128(uint32_t a) {
  uint4 v;
  asm volatile("ld.shared.v4.u32 {%0, %1, %2, %3}, [%4];" : "=r"(v.x), "=r"(v.y), "=r"(v.z), "=r"(v.w) : "r"(a) : "memory");
  return v;
}
__device__ __forceinline__ void sts128(uint32_t a, uint4 v) {
  asm volatile("st.shared.v4.u32 [%0], {%1, %2, %3, %4};" ::"r"(a), "r"(v.x), "r"(v.y), "r"(v.z), "r"(v.w) : "memory");
}
__device__ __forceinline__ uint4 ld_relaxed16(const uint4* p) {
  uint4 v;
  asm volatile("ld.relaxed.gpu.global.v4.u32 {%0, %1, %2, %3}, [%4];" : "=r"(v.x), "=r"(v.y), "=r"(v.z), "=r"(v.w) : "l"(p) : "memory");
  return v;
}
__device__ __forceinline__ void st_relaxed16(uint4* p, uint32_t a, uint32_t b, uint32_t c, uint32_t d) {
  asm volatile("st.relaxed.gpu.global.v4.u32 [%0], {%1, %2, %3, %4};" ::"l"(p), "r"(a), "r"(b), "r"(c), "r"(d) : "memory");
}
__device__ __forceinline__ uint32_t map_peer(uint32_t addr, uint32_t cta) {
  uint32_t r;
  asm("mapa.shared::cluster.u32 %0, %1, %2;" : "=r"(r) : "r"(addr), "r"(cta));
  return r;
}
__device__ __forceinline__ void st_async16(uint32_t addr, uint32_t a, uint32_t b, uint32_t c, uint32_t d, uint32_t bar) {
  asm volatile("st.async.weak.shared::cluster.mbarrier::complete_tx::bytes.v4.b32 [%0], {%1, %2, %3, %4}, [%5];"
               ::"r"(addr), "r"(a), "r"(b), "r"(c), "r"(d), "r"(bar) : "memory");
}
__device__ __forceinline__ void l2_prefetch(const void* p, uint32_t bytes) {
  asm volatile("cp.async.bulk.prefetch.L2.global [%0], %1;" ::"l"(p), "r"(bytes) : "memory");
}
__device__ __forceinline__ void prefetch_tmap(const CUtensorMap* m) {
  asm volatile("prefetch.tensormap [%0];" ::"l"(m) : "memory");
}
__device__ __forceinline__ uint64_t make_desc(uint32_t a16, uint32_t off, uint32_t lbo, uint32_t sbo, uint32_t swz) {
  const uint32_t lo = a16 + ((off >> 4) + ((lbo >> 4) << 16)), hi = (sbo >> 4) | (swz << 30);
  uint64_t d;
  asm("mov.b64 %0, {%1, %2};" : "=l"(d) : "r"(lo), "r"(hi));
  return d;
}
__device__ __forceinline__ void wg_fence() { asm volatile("wgmma.fence.sync.aligned;" ::: "memory"); }
__device__ __forceinline__ void wg_commit() { asm volatile("wgmma.commit_group.sync.aligned;" ::: "memory"); }
template <int N> __device__ __forceinline__ void wg_wait() { asm volatile("wgmma.wait_group.sync.aligned %0;" ::"n"(N) : "memory"); }
template <int N> __device__ __forceinline__ void fence_regs(float (&d)[N]) {
#pragma unroll
  for (int i = 0; i < N; i++) asm volatile("" : "+f"(d[i])::"memory");
}
template <int N> __device__ __forceinline__ void zero_regs(float (&d)[N]) {
#pragma unroll
  for (int i = 0; i < N; i++) d[i] = 0.f;
}
__device__ __forceinline__ uint32_t pack_bf16(float lo, float hi) {
  uint32_t r;
  asm("cvt.rn.bf16x2.f32 %0, %1, %2;" : "=r"(r) : "f"(hi), "f"(lo));
  return r;
}
__device__ __forceinline__ float bf_lo(uint32_t v) { return __uint_as_float(v << 16); }
__device__ __forceinline__ float bf_hi(uint32_t v) { return __uint_as_float(v & 0xffff0000u); }
__device__ __forceinline__ uint32_t max_bf2(uint32_t a, uint32_t b) {
  uint32_t r; asm("max.bf16x2 %0, %1, %2;" : "=r"(r) : "r"(a), "r"(b)); return r;
}
__device__ __forceinline__ uint32_t min_bf2(uint32_t a, uint32_t b) {
  uint32_t r; asm("min.bf16x2 %0, %1, %2;" : "=r"(r) : "r"(a), "r"(b)); return r;
}
__device__ __forceinline__ uint32_t add_bf2(uint32_t a, uint32_t b) {
  uint32_t r; asm("add.rn.bf16x2 %0, %1, %2;" : "=r"(r) : "r"(a), "r"(b)); return r;
}
__device__ __forceinline__ float ex2(float x) { float r; asm("ex2.approx.ftz.f32 %0, %1;" : "=f"(r) : "f"(x)); return r; }
__device__ __forceinline__ float rcp(float x) { float r; asm("rcp.approx.ftz.f32 %0, %1;" : "=f"(r) : "f"(x)); return r; }
__device__ __forceinline__ float tanh_ap(float x) { float r; asm("tanh.approx.f32 %0, %1;" : "=f"(r) : "f"(x)); return r; }
struct GeluC { float c0, c1, ch; };
__device__ __forceinline__ GeluC gelu_consts(float rstd, float scale) {
  return GeluC{0.7978845608f * rstd, 0.0356774081f * rstd * rstd * rstd, 0.5f * scale * rstd};
}
__device__ __forceinline__ float gelu_s(float y, const GeluC& c) {
  const float u = y * fmaf(y * y, c.c1, c.c0);
  const float hx = y * c.ch;
  return fmaf(hx, tanh_ap(u), hx);
}
__device__ __forceinline__ void stsm4(uint32_t addr, uint32_t r0, uint32_t r1, uint32_t r2, uint32_t r3) {
  asm volatile("stmatrix.sync.aligned.m8n8.x4.shared.b16 [%0], {%1, %2, %3, %4};"
               ::"r"(addr), "r"(r0), "r"(r1), "r"(r2), "r"(r3) : "memory");
}

__device__ __forceinline__ void red_add4(float* p, float a, float b, float c, float d) {
  asm volatile("red.global.add.v4.f32 [%0], {%1, %2, %3, %4};" ::"l"(p), "f"(a), "f"(b), "f"(c), "f"(d) : "memory");
}

__device__ __forceinline__ void mma_ss256(float (&d)[128], uint64_t descA, uint64_t descB) {
  asm volatile("wgmma.mma_async.sync.aligned.m64n256k16.f32.bf16.bf16 {"
      "%0, %1, %2, %3, %4, %5, %6, %7, %8, %9, %10, %11, %12, %13, %14, %15, "
      "%16, %17, %18, %19, %20, %21, %22, %23, %24, %25, %26, %27, %28, %29, %30, %31, "
      "%32, %33, %34, %35, %36, %37, %38, %39, %40, %41, %42, %43, %44, %45, %46, %47, "
      "%48, %49, %50, %51, %52, %53, %54, %55, %56, %57, %58, %59, %60, %61, %62, %63, "
      "%64, %65, %66, %67, %68, %69, %70, %71, %72, %73, %74, %75, %76, %77, %78, %79, "
      "%80, %81, %82, %83, %84, %85, %86, %87, %88, %89, %90, %91, %92, %93, %94, %95, "
      "%96, %97, %98, %99, %100, %101, %102, %103, %104, %105, %106, %107, %108, %109, %110, %111, "
      "%112, %113, %114, %115, %116, %117, %118, %119, %120, %121, %122, %123, %124, %125, %126, %127"
      "}, %128, %129, 1, 1, 1, 0, 1;\n"
      : "+f"(d[0]), "+f"(d[1]), "+f"(d[2]), "+f"(d[3]), "+f"(d[4]), "+f"(d[5]), "+f"(d[6]), "+f"(d[7]),
        "+f"(d[8]), "+f"(d[9]), "+f"(d[10]), "+f"(d[11]), "+f"(d[12]), "+f"(d[13]), "+f"(d[14]), "+f"(d[15]),
        "+f"(d[16]), "+f"(d[17]), "+f"(d[18]), "+f"(d[19]), "+f"(d[20]), "+f"(d[21]), "+f"(d[22]), "+f"(d[23]),
        "+f"(d[24]), "+f"(d[25]), "+f"(d[26]), "+f"(d[27]), "+f"(d[28]), "+f"(d[29]), "+f"(d[30]), "+f"(d[31]),
        "+f"(d[32]), "+f"(d[33]), "+f"(d[34]), "+f"(d[35]), "+f"(d[36]), "+f"(d[37]), "+f"(d[38]), "+f"(d[39]),
        "+f"(d[40]), "+f"(d[41]), "+f"(d[42]), "+f"(d[43]), "+f"(d[44]), "+f"(d[45]), "+f"(d[46]), "+f"(d[47]),
        "+f"(d[48]), "+f"(d[49]), "+f"(d[50]), "+f"(d[51]), "+f"(d[52]), "+f"(d[53]), "+f"(d[54]), "+f"(d[55]),
        "+f"(d[56]), "+f"(d[57]), "+f"(d[58]), "+f"(d[59]), "+f"(d[60]), "+f"(d[61]), "+f"(d[62]), "+f"(d[63]),
        "+f"(d[64]), "+f"(d[65]), "+f"(d[66]), "+f"(d[67]), "+f"(d[68]), "+f"(d[69]), "+f"(d[70]), "+f"(d[71]),
        "+f"(d[72]), "+f"(d[73]), "+f"(d[74]), "+f"(d[75]), "+f"(d[76]), "+f"(d[77]), "+f"(d[78]), "+f"(d[79]),
        "+f"(d[80]), "+f"(d[81]), "+f"(d[82]), "+f"(d[83]), "+f"(d[84]), "+f"(d[85]), "+f"(d[86]), "+f"(d[87]),
        "+f"(d[88]), "+f"(d[89]), "+f"(d[90]), "+f"(d[91]), "+f"(d[92]), "+f"(d[93]), "+f"(d[94]), "+f"(d[95]),
        "+f"(d[96]), "+f"(d[97]), "+f"(d[98]), "+f"(d[99]), "+f"(d[100]), "+f"(d[101]), "+f"(d[102]), "+f"(d[103]),
        "+f"(d[104]), "+f"(d[105]), "+f"(d[106]), "+f"(d[107]), "+f"(d[108]), "+f"(d[109]), "+f"(d[110]), "+f"(d[111]),
        "+f"(d[112]), "+f"(d[113]), "+f"(d[114]), "+f"(d[115]), "+f"(d[116]), "+f"(d[117]), "+f"(d[118]), "+f"(d[119]),
        "+f"(d[120]), "+f"(d[121]), "+f"(d[122]), "+f"(d[123]), "+f"(d[124]), "+f"(d[125]), "+f"(d[126]), "+f"(d[127])
      : "l"(descA), "l"(descB));
}
__device__ __forceinline__ void mma_ss256_p(float (&d)[128], uint64_t descA, uint64_t descB, int acc) {
  asm volatile("{\n.reg .pred p;\nsetp.ne.b32 p, %130, 0;\n"
      "wgmma.mma_async.sync.aligned.m64n256k16.f32.bf16.bf16 {"
      "%0, %1, %2, %3, %4, %5, %6, %7, %8, %9, %10, %11, %12, %13, %14, %15, "
      "%16, %17, %18, %19, %20, %21, %22, %23, %24, %25, %26, %27, %28, %29, %30, %31, "
      "%32, %33, %34, %35, %36, %37, %38, %39, %40, %41, %42, %43, %44, %45, %46, %47, "
      "%48, %49, %50, %51, %52, %53, %54, %55, %56, %57, %58, %59, %60, %61, %62, %63, "
      "%64, %65, %66, %67, %68, %69, %70, %71, %72, %73, %74, %75, %76, %77, %78, %79, "
      "%80, %81, %82, %83, %84, %85, %86, %87, %88, %89, %90, %91, %92, %93, %94, %95, "
      "%96, %97, %98, %99, %100, %101, %102, %103, %104, %105, %106, %107, %108, %109, %110, %111, "
      "%112, %113, %114, %115, %116, %117, %118, %119, %120, %121, %122, %123, %124, %125, %126, %127"
      "}, %128, %129, p, 1, 1, 0, 1;\n}\n"
      : "+f"(d[0]), "+f"(d[1]), "+f"(d[2]), "+f"(d[3]), "+f"(d[4]), "+f"(d[5]), "+f"(d[6]), "+f"(d[7]),
        "+f"(d[8]), "+f"(d[9]), "+f"(d[10]), "+f"(d[11]), "+f"(d[12]), "+f"(d[13]), "+f"(d[14]), "+f"(d[15]),
        "+f"(d[16]), "+f"(d[17]), "+f"(d[18]), "+f"(d[19]), "+f"(d[20]), "+f"(d[21]), "+f"(d[22]), "+f"(d[23]),
        "+f"(d[24]), "+f"(d[25]), "+f"(d[26]), "+f"(d[27]), "+f"(d[28]), "+f"(d[29]), "+f"(d[30]), "+f"(d[31]),
        "+f"(d[32]), "+f"(d[33]), "+f"(d[34]), "+f"(d[35]), "+f"(d[36]), "+f"(d[37]), "+f"(d[38]), "+f"(d[39]),
        "+f"(d[40]), "+f"(d[41]), "+f"(d[42]), "+f"(d[43]), "+f"(d[44]), "+f"(d[45]), "+f"(d[46]), "+f"(d[47]),
        "+f"(d[48]), "+f"(d[49]), "+f"(d[50]), "+f"(d[51]), "+f"(d[52]), "+f"(d[53]), "+f"(d[54]), "+f"(d[55]),
        "+f"(d[56]), "+f"(d[57]), "+f"(d[58]), "+f"(d[59]), "+f"(d[60]), "+f"(d[61]), "+f"(d[62]), "+f"(d[63]),
        "+f"(d[64]), "+f"(d[65]), "+f"(d[66]), "+f"(d[67]), "+f"(d[68]), "+f"(d[69]), "+f"(d[70]), "+f"(d[71]),
        "+f"(d[72]), "+f"(d[73]), "+f"(d[74]), "+f"(d[75]), "+f"(d[76]), "+f"(d[77]), "+f"(d[78]), "+f"(d[79]),
        "+f"(d[80]), "+f"(d[81]), "+f"(d[82]), "+f"(d[83]), "+f"(d[84]), "+f"(d[85]), "+f"(d[86]), "+f"(d[87]),
        "+f"(d[88]), "+f"(d[89]), "+f"(d[90]), "+f"(d[91]), "+f"(d[92]), "+f"(d[93]), "+f"(d[94]), "+f"(d[95]),
        "+f"(d[96]), "+f"(d[97]), "+f"(d[98]), "+f"(d[99]), "+f"(d[100]), "+f"(d[101]), "+f"(d[102]), "+f"(d[103]),
        "+f"(d[104]), "+f"(d[105]), "+f"(d[106]), "+f"(d[107]), "+f"(d[108]), "+f"(d[109]), "+f"(d[110]), "+f"(d[111]),
        "+f"(d[112]), "+f"(d[113]), "+f"(d[114]), "+f"(d[115]), "+f"(d[116]), "+f"(d[117]), "+f"(d[118]), "+f"(d[119]),
        "+f"(d[120]), "+f"(d[121]), "+f"(d[122]), "+f"(d[123]), "+f"(d[124]), "+f"(d[125]), "+f"(d[126]), "+f"(d[127])
      : "l"(descA), "l"(descB), "r"(acc));
}

__device__ __forceinline__ void mma_ss64(float (&d)[32], uint64_t descA, uint64_t descB) {
  asm volatile("wgmma.mma_async.sync.aligned.m64n64k16.f32.bf16.bf16 {"
      "%0, %1, %2, %3, %4, %5, %6, %7, %8, %9, %10, %11, %12, %13, %14, %15, "
      "%16, %17, %18, %19, %20, %21, %22, %23, %24, %25, %26, %27, %28, %29, %30, %31"
      "}, %32, %33, 1, 1, 1, 0, 1;\n"
      : "+f"(d[0]), "+f"(d[1]), "+f"(d[2]), "+f"(d[3]), "+f"(d[4]), "+f"(d[5]), "+f"(d[6]), "+f"(d[7]),
        "+f"(d[8]), "+f"(d[9]), "+f"(d[10]), "+f"(d[11]), "+f"(d[12]), "+f"(d[13]), "+f"(d[14]), "+f"(d[15]),
        "+f"(d[16]), "+f"(d[17]), "+f"(d[18]), "+f"(d[19]), "+f"(d[20]), "+f"(d[21]), "+f"(d[22]), "+f"(d[23]),
        "+f"(d[24]), "+f"(d[25]), "+f"(d[26]), "+f"(d[27]), "+f"(d[28]), "+f"(d[29]), "+f"(d[30]), "+f"(d[31])
      : "l"(descA), "l"(descB));
}
__device__ __forceinline__ void mma_ss64_p(float (&d)[32], uint64_t descA, uint64_t descB, int acc) {
  asm volatile("{\n.reg .pred p;\nsetp.ne.b32 p, %34, 0;\n"
      "wgmma.mma_async.sync.aligned.m64n64k16.f32.bf16.bf16 {"
      "%0, %1, %2, %3, %4, %5, %6, %7, %8, %9, %10, %11, %12, %13, %14, %15, "
      "%16, %17, %18, %19, %20, %21, %22, %23, %24, %25, %26, %27, %28, %29, %30, %31"
      "}, %32, %33, p, 1, 1, 0, 1;\n}\n"
      : "+f"(d[0]), "+f"(d[1]), "+f"(d[2]), "+f"(d[3]), "+f"(d[4]), "+f"(d[5]), "+f"(d[6]), "+f"(d[7]),
        "+f"(d[8]), "+f"(d[9]), "+f"(d[10]), "+f"(d[11]), "+f"(d[12]), "+f"(d[13]), "+f"(d[14]), "+f"(d[15]),
        "+f"(d[16]), "+f"(d[17]), "+f"(d[18]), "+f"(d[19]), "+f"(d[20]), "+f"(d[21]), "+f"(d[22]), "+f"(d[23]),
        "+f"(d[24]), "+f"(d[25]), "+f"(d[26]), "+f"(d[27]), "+f"(d[28]), "+f"(d[29]), "+f"(d[30]), "+f"(d[31])
      : "l"(descA), "l"(descB), "r"(acc));
}

__device__ __forceinline__ void mma_ss160(float (&d)[80], uint64_t descA, uint64_t descB) {
  asm volatile("wgmma.mma_async.sync.aligned.m64n160k16.f32.bf16.bf16 {"
      "%0, %1, %2, %3, %4, %5, %6, %7, %8, %9, %10, %11, %12, %13, %14, %15, "
      "%16, %17, %18, %19, %20, %21, %22, %23, %24, %25, %26, %27, %28, %29, %30, %31, "
      "%32, %33, %34, %35, %36, %37, %38, %39, %40, %41, %42, %43, %44, %45, %46, %47, "
      "%48, %49, %50, %51, %52, %53, %54, %55, %56, %57, %58, %59, %60, %61, %62, %63, "
      "%64, %65, %66, %67, %68, %69, %70, %71, %72, %73, %74, %75, %76, %77, %78, %79"
      "}, %80, %81, 1, 1, 1, 0, 1;\n"
      : "+f"(d[0]), "+f"(d[1]), "+f"(d[2]), "+f"(d[3]), "+f"(d[4]), "+f"(d[5]), "+f"(d[6]), "+f"(d[7]),
        "+f"(d[8]), "+f"(d[9]), "+f"(d[10]), "+f"(d[11]), "+f"(d[12]), "+f"(d[13]), "+f"(d[14]), "+f"(d[15]),
        "+f"(d[16]), "+f"(d[17]), "+f"(d[18]), "+f"(d[19]), "+f"(d[20]), "+f"(d[21]), "+f"(d[22]), "+f"(d[23]),
        "+f"(d[24]), "+f"(d[25]), "+f"(d[26]), "+f"(d[27]), "+f"(d[28]), "+f"(d[29]), "+f"(d[30]), "+f"(d[31]),
        "+f"(d[32]), "+f"(d[33]), "+f"(d[34]), "+f"(d[35]), "+f"(d[36]), "+f"(d[37]), "+f"(d[38]), "+f"(d[39]),
        "+f"(d[40]), "+f"(d[41]), "+f"(d[42]), "+f"(d[43]), "+f"(d[44]), "+f"(d[45]), "+f"(d[46]), "+f"(d[47]),
        "+f"(d[48]), "+f"(d[49]), "+f"(d[50]), "+f"(d[51]), "+f"(d[52]), "+f"(d[53]), "+f"(d[54]), "+f"(d[55]),
        "+f"(d[56]), "+f"(d[57]), "+f"(d[58]), "+f"(d[59]), "+f"(d[60]), "+f"(d[61]), "+f"(d[62]), "+f"(d[63]),
        "+f"(d[64]), "+f"(d[65]), "+f"(d[66]), "+f"(d[67]), "+f"(d[68]), "+f"(d[69]), "+f"(d[70]), "+f"(d[71]),
        "+f"(d[72]), "+f"(d[73]), "+f"(d[74]), "+f"(d[75]), "+f"(d[76]), "+f"(d[77]), "+f"(d[78]), "+f"(d[79])
      : "l"(descA), "l"(descB));
}
__device__ __forceinline__ void mma_ss160_z(float (&d)[80], uint64_t descA, uint64_t descB) {
  asm volatile("wgmma.mma_async.sync.aligned.m64n160k16.f32.bf16.bf16 {"
      "%0, %1, %2, %3, %4, %5, %6, %7, %8, %9, %10, %11, %12, %13, %14, %15, "
      "%16, %17, %18, %19, %20, %21, %22, %23, %24, %25, %26, %27, %28, %29, %30, %31, "
      "%32, %33, %34, %35, %36, %37, %38, %39, %40, %41, %42, %43, %44, %45, %46, %47, "
      "%48, %49, %50, %51, %52, %53, %54, %55, %56, %57, %58, %59, %60, %61, %62, %63, "
      "%64, %65, %66, %67, %68, %69, %70, %71, %72, %73, %74, %75, %76, %77, %78, %79"
      "}, %80, %81, 0, 1, 1, 0, 1;\n"
      : "=f"(d[0]), "=f"(d[1]), "=f"(d[2]), "=f"(d[3]), "=f"(d[4]), "=f"(d[5]), "=f"(d[6]), "=f"(d[7]),
        "=f"(d[8]), "=f"(d[9]), "=f"(d[10]), "=f"(d[11]), "=f"(d[12]), "=f"(d[13]), "=f"(d[14]), "=f"(d[15]),
        "=f"(d[16]), "=f"(d[17]), "=f"(d[18]), "=f"(d[19]), "=f"(d[20]), "=f"(d[21]), "=f"(d[22]), "=f"(d[23]),
        "=f"(d[24]), "=f"(d[25]), "=f"(d[26]), "=f"(d[27]), "=f"(d[28]), "=f"(d[29]), "=f"(d[30]), "=f"(d[31]),
        "=f"(d[32]), "=f"(d[33]), "=f"(d[34]), "=f"(d[35]), "=f"(d[36]), "=f"(d[37]), "=f"(d[38]), "=f"(d[39]),
        "=f"(d[40]), "=f"(d[41]), "=f"(d[42]), "=f"(d[43]), "=f"(d[44]), "=f"(d[45]), "=f"(d[46]), "=f"(d[47]),
        "=f"(d[48]), "=f"(d[49]), "=f"(d[50]), "=f"(d[51]), "=f"(d[52]), "=f"(d[53]), "=f"(d[54]), "=f"(d[55]),
        "=f"(d[56]), "=f"(d[57]), "=f"(d[58]), "=f"(d[59]), "=f"(d[60]), "=f"(d[61]), "=f"(d[62]), "=f"(d[63]),
        "=f"(d[64]), "=f"(d[65]), "=f"(d[66]), "=f"(d[67]), "=f"(d[68]), "=f"(d[69]), "=f"(d[70]), "=f"(d[71]),
        "=f"(d[72]), "=f"(d[73]), "=f"(d[74]), "=f"(d[75]), "=f"(d[76]), "=f"(d[77]), "=f"(d[78]), "=f"(d[79])
      : "l"(descA), "l"(descB));
}

__device__ __forceinline__ void mma_ss192(float (&d)[96], uint64_t descA, uint64_t descB) {
  asm volatile("wgmma.mma_async.sync.aligned.m64n192k16.f32.bf16.bf16 {"
      "%0, %1, %2, %3, %4, %5, %6, %7, %8, %9, %10, %11, %12, %13, %14, %15, "
      "%16, %17, %18, %19, %20, %21, %22, %23, %24, %25, %26, %27, %28, %29, %30, %31, "
      "%32, %33, %34, %35, %36, %37, %38, %39, %40, %41, %42, %43, %44, %45, %46, %47, "
      "%48, %49, %50, %51, %52, %53, %54, %55, %56, %57, %58, %59, %60, %61, %62, %63, "
      "%64, %65, %66, %67, %68, %69, %70, %71, %72, %73, %74, %75, %76, %77, %78, %79, "
      "%80, %81, %82, %83, %84, %85, %86, %87, %88, %89, %90, %91, %92, %93, %94, %95"
      "}, %96, %97, 1, 1, 1, 0, 1;\n"
      : "+f"(d[0]), "+f"(d[1]), "+f"(d[2]), "+f"(d[3]), "+f"(d[4]), "+f"(d[5]), "+f"(d[6]), "+f"(d[7]),
        "+f"(d[8]), "+f"(d[9]), "+f"(d[10]), "+f"(d[11]), "+f"(d[12]), "+f"(d[13]), "+f"(d[14]), "+f"(d[15]),
        "+f"(d[16]), "+f"(d[17]), "+f"(d[18]), "+f"(d[19]), "+f"(d[20]), "+f"(d[21]), "+f"(d[22]), "+f"(d[23]),
        "+f"(d[24]), "+f"(d[25]), "+f"(d[26]), "+f"(d[27]), "+f"(d[28]), "+f"(d[29]), "+f"(d[30]), "+f"(d[31]),
        "+f"(d[32]), "+f"(d[33]), "+f"(d[34]), "+f"(d[35]), "+f"(d[36]), "+f"(d[37]), "+f"(d[38]), "+f"(d[39]),
        "+f"(d[40]), "+f"(d[41]), "+f"(d[42]), "+f"(d[43]), "+f"(d[44]), "+f"(d[45]), "+f"(d[46]), "+f"(d[47]),
        "+f"(d[48]), "+f"(d[49]), "+f"(d[50]), "+f"(d[51]), "+f"(d[52]), "+f"(d[53]), "+f"(d[54]), "+f"(d[55]),
        "+f"(d[56]), "+f"(d[57]), "+f"(d[58]), "+f"(d[59]), "+f"(d[60]), "+f"(d[61]), "+f"(d[62]), "+f"(d[63]),
        "+f"(d[64]), "+f"(d[65]), "+f"(d[66]), "+f"(d[67]), "+f"(d[68]), "+f"(d[69]), "+f"(d[70]), "+f"(d[71]),
        "+f"(d[72]), "+f"(d[73]), "+f"(d[74]), "+f"(d[75]), "+f"(d[76]), "+f"(d[77]), "+f"(d[78]), "+f"(d[79]),
        "+f"(d[80]), "+f"(d[81]), "+f"(d[82]), "+f"(d[83]), "+f"(d[84]), "+f"(d[85]), "+f"(d[86]), "+f"(d[87]),
        "+f"(d[88]), "+f"(d[89]), "+f"(d[90]), "+f"(d[91]), "+f"(d[92]), "+f"(d[93]), "+f"(d[94]), "+f"(d[95])
      : "l"(descA), "l"(descB));
}
__device__ __forceinline__ void mma_ss192_p(float (&d)[96], uint64_t descA, uint64_t descB, int acc) {
  asm volatile("{\n.reg .pred p;\nsetp.ne.b32 p, %98, 0;\n"
      "wgmma.mma_async.sync.aligned.m64n192k16.f32.bf16.bf16 {"
      "%0, %1, %2, %3, %4, %5, %6, %7, %8, %9, %10, %11, %12, %13, %14, %15, "
      "%16, %17, %18, %19, %20, %21, %22, %23, %24, %25, %26, %27, %28, %29, %30, %31, "
      "%32, %33, %34, %35, %36, %37, %38, %39, %40, %41, %42, %43, %44, %45, %46, %47, "
      "%48, %49, %50, %51, %52, %53, %54, %55, %56, %57, %58, %59, %60, %61, %62, %63, "
      "%64, %65, %66, %67, %68, %69, %70, %71, %72, %73, %74, %75, %76, %77, %78, %79, "
      "%80, %81, %82, %83, %84, %85, %86, %87, %88, %89, %90, %91, %92, %93, %94, %95"
      "}, %96, %97, p, 1, 1, 0, 1;\n}\n"
      : "+f"(d[0]), "+f"(d[1]), "+f"(d[2]), "+f"(d[3]), "+f"(d[4]), "+f"(d[5]), "+f"(d[6]), "+f"(d[7]),
        "+f"(d[8]), "+f"(d[9]), "+f"(d[10]), "+f"(d[11]), "+f"(d[12]), "+f"(d[13]), "+f"(d[14]), "+f"(d[15]),
        "+f"(d[16]), "+f"(d[17]), "+f"(d[18]), "+f"(d[19]), "+f"(d[20]), "+f"(d[21]), "+f"(d[22]), "+f"(d[23]),
        "+f"(d[24]), "+f"(d[25]), "+f"(d[26]), "+f"(d[27]), "+f"(d[28]), "+f"(d[29]), "+f"(d[30]), "+f"(d[31]),
        "+f"(d[32]), "+f"(d[33]), "+f"(d[34]), "+f"(d[35]), "+f"(d[36]), "+f"(d[37]), "+f"(d[38]), "+f"(d[39]),
        "+f"(d[40]), "+f"(d[41]), "+f"(d[42]), "+f"(d[43]), "+f"(d[44]), "+f"(d[45]), "+f"(d[46]), "+f"(d[47]),
        "+f"(d[48]), "+f"(d[49]), "+f"(d[50]), "+f"(d[51]), "+f"(d[52]), "+f"(d[53]), "+f"(d[54]), "+f"(d[55]),
        "+f"(d[56]), "+f"(d[57]), "+f"(d[58]), "+f"(d[59]), "+f"(d[60]), "+f"(d[61]), "+f"(d[62]), "+f"(d[63]),
        "+f"(d[64]), "+f"(d[65]), "+f"(d[66]), "+f"(d[67]), "+f"(d[68]), "+f"(d[69]), "+f"(d[70]), "+f"(d[71]),
        "+f"(d[72]), "+f"(d[73]), "+f"(d[74]), "+f"(d[75]), "+f"(d[76]), "+f"(d[77]), "+f"(d[78]), "+f"(d[79]),
        "+f"(d[80]), "+f"(d[81]), "+f"(d[82]), "+f"(d[83]), "+f"(d[84]), "+f"(d[85]), "+f"(d[86]), "+f"(d[87]),
        "+f"(d[88]), "+f"(d[89]), "+f"(d[90]), "+f"(d[91]), "+f"(d[92]), "+f"(d[93]), "+f"(d[94]), "+f"(d[95])
      : "l"(descA), "l"(descB), "r"(acc));
}

__device__ __forceinline__ void mma_ss80_tt(float (&d)[40], uint64_t descA, uint64_t descB) {
  asm volatile("wgmma.mma_async.sync.aligned.m64n80k16.f32.bf16.bf16 {"
      "%0, %1, %2, %3, %4, %5, %6, %7, %8, %9, %10, %11, %12, %13, %14, %15, "
      "%16, %17, %18, %19, %20, %21, %22, %23, %24, %25, %26, %27, %28, %29, %30, %31, "
      "%32, %33, %34, %35, %36, %37, %38, %39"
      "}, %40, %41, 1, 1, 1, 1, 1;\n"
      : "+f"(d[0]), "+f"(d[1]), "+f"(d[2]), "+f"(d[3]), "+f"(d[4]), "+f"(d[5]), "+f"(d[6]), "+f"(d[7]),
        "+f"(d[8]), "+f"(d[9]), "+f"(d[10]), "+f"(d[11]), "+f"(d[12]), "+f"(d[13]), "+f"(d[14]), "+f"(d[15]),
        "+f"(d[16]), "+f"(d[17]), "+f"(d[18]), "+f"(d[19]), "+f"(d[20]), "+f"(d[21]), "+f"(d[22]), "+f"(d[23]),
        "+f"(d[24]), "+f"(d[25]), "+f"(d[26]), "+f"(d[27]), "+f"(d[28]), "+f"(d[29]), "+f"(d[30]), "+f"(d[31]),
        "+f"(d[32]), "+f"(d[33]), "+f"(d[34]), "+f"(d[35]), "+f"(d[36]), "+f"(d[37]), "+f"(d[38]), "+f"(d[39])
      : "l"(descA), "l"(descB));
}
__device__ __forceinline__ void mma_ss80_tt_z(float (&d)[40], uint64_t descA, uint64_t descB) {
  asm volatile("wgmma.mma_async.sync.aligned.m64n80k16.f32.bf16.bf16 {"
      "%0, %1, %2, %3, %4, %5, %6, %7, %8, %9, %10, %11, %12, %13, %14, %15, "
      "%16, %17, %18, %19, %20, %21, %22, %23, %24, %25, %26, %27, %28, %29, %30, %31, "
      "%32, %33, %34, %35, %36, %37, %38, %39"
      "}, %40, %41, 0, 1, 1, 1, 1;\n"
      : "=f"(d[0]), "=f"(d[1]), "=f"(d[2]), "=f"(d[3]), "=f"(d[4]), "=f"(d[5]), "=f"(d[6]), "=f"(d[7]),
        "=f"(d[8]), "=f"(d[9]), "=f"(d[10]), "=f"(d[11]), "=f"(d[12]), "=f"(d[13]), "=f"(d[14]), "=f"(d[15]),
        "=f"(d[16]), "=f"(d[17]), "=f"(d[18]), "=f"(d[19]), "=f"(d[20]), "=f"(d[21]), "=f"(d[22]), "=f"(d[23]),
        "=f"(d[24]), "=f"(d[25]), "=f"(d[26]), "=f"(d[27]), "=f"(d[28]), "=f"(d[29]), "=f"(d[30]), "=f"(d[31]),
        "=f"(d[32]), "=f"(d[33]), "=f"(d[34]), "=f"(d[35]), "=f"(d[36]), "=f"(d[37]), "=f"(d[38]), "=f"(d[39])
      : "l"(descA), "l"(descB));
}

__device__ __forceinline__ void mma_rs80_k(float (&d)[40], const uint32_t (&a)[4], uint64_t descB) {
  asm volatile("wgmma.mma_async.sync.aligned.m64n80k16.f32.bf16.bf16 {"
      "%0, %1, %2, %3, %4, %5, %6, %7, %8, %9, %10, %11, %12, %13, %14, %15, "
      "%16, %17, %18, %19, %20, %21, %22, %23, %24, %25, %26, %27, %28, %29, %30, %31, "
      "%32, %33, %34, %35, %36, %37, %38, %39"
      "}, {%40, %41, %42, %43}, %44, 1, 1, 1, 0;\n"
      : "+f"(d[0]), "+f"(d[1]), "+f"(d[2]), "+f"(d[3]), "+f"(d[4]), "+f"(d[5]), "+f"(d[6]), "+f"(d[7]),
        "+f"(d[8]), "+f"(d[9]), "+f"(d[10]), "+f"(d[11]), "+f"(d[12]), "+f"(d[13]), "+f"(d[14]), "+f"(d[15]),
        "+f"(d[16]), "+f"(d[17]), "+f"(d[18]), "+f"(d[19]), "+f"(d[20]), "+f"(d[21]), "+f"(d[22]), "+f"(d[23]),
        "+f"(d[24]), "+f"(d[25]), "+f"(d[26]), "+f"(d[27]), "+f"(d[28]), "+f"(d[29]), "+f"(d[30]), "+f"(d[31]),
        "+f"(d[32]), "+f"(d[33]), "+f"(d[34]), "+f"(d[35]), "+f"(d[36]), "+f"(d[37]), "+f"(d[38]), "+f"(d[39])
      : "r"(a[0]), "r"(a[1]), "r"(a[2]), "r"(a[3]), "l"(descB));
}
__device__ __forceinline__ void mma_rs80_k_z(float (&d)[40], const uint32_t (&a)[4], uint64_t descB) {
  asm volatile("wgmma.mma_async.sync.aligned.m64n80k16.f32.bf16.bf16 {"
      "%0, %1, %2, %3, %4, %5, %6, %7, %8, %9, %10, %11, %12, %13, %14, %15, "
      "%16, %17, %18, %19, %20, %21, %22, %23, %24, %25, %26, %27, %28, %29, %30, %31, "
      "%32, %33, %34, %35, %36, %37, %38, %39"
      "}, {%40, %41, %42, %43}, %44, 0, 1, 1, 0;\n"
      : "=f"(d[0]), "=f"(d[1]), "=f"(d[2]), "=f"(d[3]), "=f"(d[4]), "=f"(d[5]), "=f"(d[6]), "=f"(d[7]),
        "=f"(d[8]), "=f"(d[9]), "=f"(d[10]), "=f"(d[11]), "=f"(d[12]), "=f"(d[13]), "=f"(d[14]), "=f"(d[15]),
        "=f"(d[16]), "=f"(d[17]), "=f"(d[18]), "=f"(d[19]), "=f"(d[20]), "=f"(d[21]), "=f"(d[22]), "=f"(d[23]),
        "=f"(d[24]), "=f"(d[25]), "=f"(d[26]), "=f"(d[27]), "=f"(d[28]), "=f"(d[29]), "=f"(d[30]), "=f"(d[31]),
        "=f"(d[32]), "=f"(d[33]), "=f"(d[34]), "=f"(d[35]), "=f"(d[36]), "=f"(d[37]), "=f"(d[38]), "=f"(d[39])
      : "r"(a[0]), "r"(a[1]), "r"(a[2]), "r"(a[3]), "l"(descB));
}

__device__ __forceinline__ void mma_rs48_k(float (&d)[24], const uint32_t (&a)[4], uint64_t descB) {
  asm volatile("wgmma.mma_async.sync.aligned.m64n48k16.f32.bf16.bf16 {"
      "%0, %1, %2, %3, %4, %5, %6, %7, %8, %9, %10, %11, %12, %13, %14, %15, "
      "%16, %17, %18, %19, %20, %21, %22, %23"
      "}, {%24, %25, %26, %27}, %28, 1, 1, 1, 0;\n"
      : "+f"(d[0]), "+f"(d[1]), "+f"(d[2]), "+f"(d[3]), "+f"(d[4]), "+f"(d[5]), "+f"(d[6]), "+f"(d[7]),
        "+f"(d[8]), "+f"(d[9]), "+f"(d[10]), "+f"(d[11]), "+f"(d[12]), "+f"(d[13]), "+f"(d[14]), "+f"(d[15]),
        "+f"(d[16]), "+f"(d[17]), "+f"(d[18]), "+f"(d[19]), "+f"(d[20]), "+f"(d[21]), "+f"(d[22]), "+f"(d[23])
      : "r"(a[0]), "r"(a[1]), "r"(a[2]), "r"(a[3]), "l"(descB));
}
__device__ __forceinline__ void mma_rs48_k_z(float (&d)[24], const uint32_t (&a)[4], uint64_t descB) {
  asm volatile("wgmma.mma_async.sync.aligned.m64n48k16.f32.bf16.bf16 {"
      "%0, %1, %2, %3, %4, %5, %6, %7, %8, %9, %10, %11, %12, %13, %14, %15, "
      "%16, %17, %18, %19, %20, %21, %22, %23"
      "}, {%24, %25, %26, %27}, %28, 0, 1, 1, 0;\n"
      : "=f"(d[0]), "=f"(d[1]), "=f"(d[2]), "=f"(d[3]), "=f"(d[4]), "=f"(d[5]), "=f"(d[6]), "=f"(d[7]),
        "=f"(d[8]), "=f"(d[9]), "=f"(d[10]), "=f"(d[11]), "=f"(d[12]), "=f"(d[13]), "=f"(d[14]), "=f"(d[15]),
        "=f"(d[16]), "=f"(d[17]), "=f"(d[18]), "=f"(d[19]), "=f"(d[20]), "=f"(d[21]), "=f"(d[22]), "=f"(d[23])
      : "r"(a[0]), "r"(a[1]), "r"(a[2]), "r"(a[3]), "l"(descB));
}

__device__ __forceinline__ void mma_rs160_n(float (&d)[80], const uint32_t (&a)[4], uint64_t descB) {
  asm volatile("wgmma.mma_async.sync.aligned.m64n160k16.f32.bf16.bf16 {"
      "%0, %1, %2, %3, %4, %5, %6, %7, %8, %9, %10, %11, %12, %13, %14, %15, "
      "%16, %17, %18, %19, %20, %21, %22, %23, %24, %25, %26, %27, %28, %29, %30, %31, "
      "%32, %33, %34, %35, %36, %37, %38, %39, %40, %41, %42, %43, %44, %45, %46, %47, "
      "%48, %49, %50, %51, %52, %53, %54, %55, %56, %57, %58, %59, %60, %61, %62, %63, "
      "%64, %65, %66, %67, %68, %69, %70, %71, %72, %73, %74, %75, %76, %77, %78, %79"
      "}, {%80, %81, %82, %83}, %84, 1, 1, 1, 1;\n"
      : "+f"(d[0]), "+f"(d[1]), "+f"(d[2]), "+f"(d[3]), "+f"(d[4]), "+f"(d[5]), "+f"(d[6]), "+f"(d[7]),
        "+f"(d[8]), "+f"(d[9]), "+f"(d[10]), "+f"(d[11]), "+f"(d[12]), "+f"(d[13]), "+f"(d[14]), "+f"(d[15]),
        "+f"(d[16]), "+f"(d[17]), "+f"(d[18]), "+f"(d[19]), "+f"(d[20]), "+f"(d[21]), "+f"(d[22]), "+f"(d[23]),
        "+f"(d[24]), "+f"(d[25]), "+f"(d[26]), "+f"(d[27]), "+f"(d[28]), "+f"(d[29]), "+f"(d[30]), "+f"(d[31]),
        "+f"(d[32]), "+f"(d[33]), "+f"(d[34]), "+f"(d[35]), "+f"(d[36]), "+f"(d[37]), "+f"(d[38]), "+f"(d[39]),
        "+f"(d[40]), "+f"(d[41]), "+f"(d[42]), "+f"(d[43]), "+f"(d[44]), "+f"(d[45]), "+f"(d[46]), "+f"(d[47]),
        "+f"(d[48]), "+f"(d[49]), "+f"(d[50]), "+f"(d[51]), "+f"(d[52]), "+f"(d[53]), "+f"(d[54]), "+f"(d[55]),
        "+f"(d[56]), "+f"(d[57]), "+f"(d[58]), "+f"(d[59]), "+f"(d[60]), "+f"(d[61]), "+f"(d[62]), "+f"(d[63]),
        "+f"(d[64]), "+f"(d[65]), "+f"(d[66]), "+f"(d[67]), "+f"(d[68]), "+f"(d[69]), "+f"(d[70]), "+f"(d[71]),
        "+f"(d[72]), "+f"(d[73]), "+f"(d[74]), "+f"(d[75]), "+f"(d[76]), "+f"(d[77]), "+f"(d[78]), "+f"(d[79])
      : "r"(a[0]), "r"(a[1]), "r"(a[2]), "r"(a[3]), "l"(descB));
}
__device__ __forceinline__ void mma_rs160_n_z(float (&d)[80], const uint32_t (&a)[4], uint64_t descB) {
  asm volatile("wgmma.mma_async.sync.aligned.m64n160k16.f32.bf16.bf16 {"
      "%0, %1, %2, %3, %4, %5, %6, %7, %8, %9, %10, %11, %12, %13, %14, %15, "
      "%16, %17, %18, %19, %20, %21, %22, %23, %24, %25, %26, %27, %28, %29, %30, %31, "
      "%32, %33, %34, %35, %36, %37, %38, %39, %40, %41, %42, %43, %44, %45, %46, %47, "
      "%48, %49, %50, %51, %52, %53, %54, %55, %56, %57, %58, %59, %60, %61, %62, %63, "
      "%64, %65, %66, %67, %68, %69, %70, %71, %72, %73, %74, %75, %76, %77, %78, %79"
      "}, {%80, %81, %82, %83}, %84, 0, 1, 1, 1;\n"
      : "=f"(d[0]), "=f"(d[1]), "=f"(d[2]), "=f"(d[3]), "=f"(d[4]), "=f"(d[5]), "=f"(d[6]), "=f"(d[7]),
        "=f"(d[8]), "=f"(d[9]), "=f"(d[10]), "=f"(d[11]), "=f"(d[12]), "=f"(d[13]), "=f"(d[14]), "=f"(d[15]),
        "=f"(d[16]), "=f"(d[17]), "=f"(d[18]), "=f"(d[19]), "=f"(d[20]), "=f"(d[21]), "=f"(d[22]), "=f"(d[23]),
        "=f"(d[24]), "=f"(d[25]), "=f"(d[26]), "=f"(d[27]), "=f"(d[28]), "=f"(d[29]), "=f"(d[30]), "=f"(d[31]),
        "=f"(d[32]), "=f"(d[33]), "=f"(d[34]), "=f"(d[35]), "=f"(d[36]), "=f"(d[37]), "=f"(d[38]), "=f"(d[39]),
        "=f"(d[40]), "=f"(d[41]), "=f"(d[42]), "=f"(d[43]), "=f"(d[44]), "=f"(d[45]), "=f"(d[46]), "=f"(d[47]),
        "=f"(d[48]), "=f"(d[49]), "=f"(d[50]), "=f"(d[51]), "=f"(d[52]), "=f"(d[53]), "=f"(d[54]), "=f"(d[55]),
        "=f"(d[56]), "=f"(d[57]), "=f"(d[58]), "=f"(d[59]), "=f"(d[60]), "=f"(d[61]), "=f"(d[62]), "=f"(d[63]),
        "=f"(d[64]), "=f"(d[65]), "=f"(d[66]), "=f"(d[67]), "=f"(d[68]), "=f"(d[69]), "=f"(d[70]), "=f"(d[71]),
        "=f"(d[72]), "=f"(d[73]), "=f"(d[74]), "=f"(d[75]), "=f"(d[76]), "=f"(d[77]), "=f"(d[78]), "=f"(d[79])
      : "r"(a[0]), "r"(a[1]), "r"(a[2]), "r"(a[3]), "l"(descB));
}

__device__ __forceinline__ void feature_map(const uint32_t (&P)[2][10], uint32_t (&fr)[10][4]) {
  constexpr float L2E = 1.4426950408889634f;
#pragma unroll
  for (int p = 0; p < 2; p++) {
#pragma unroll
    for (int r = 0; r < 2; r++) {
      uint32_t mx = P[r][5 * p], mn = mx;
#pragma unroll
      for (int g = 1; g < 5; g++) { mx = max_bf2(mx, P[r][5 * p + g]); mn = min_bf2(mn, P[r][5 * p + g]); }
      mx = max_bf2(mx, __shfl_xor_sync(0xffffffffu, mx, 1));
      mn = min_bf2(mn, __shfl_xor_sync(0xffffffffu, mn, 1));
      mx = max_bf2(mx, __shfl_xor_sync(0xffffffffu, mx, 2));
      mn = min_bf2(mn, __shfl_xor_sync(0xffffffffu, mn, 2));
      float mx0 = -bf_lo(mx) * L2E, mx1 = -bf_hi(mx) * L2E, mn0 = bf_lo(mn) * L2E, mn1 = bf_hi(mn) * L2E;
      float ep0[5], ep1[5], en0[5], en1[5];
      float sp0 = 0.f, sp1 = 0.f, sn0 = 0.f, sn1 = 0.f;
#pragma unroll
      for (int g = 0; g < 5; g++) {
        float x0 = bf_lo(P[r][5 * p + g]), x1 = bf_hi(P[r][5 * p + g]);
        ep0[g] = ex2(fmaf(x0, L2E, mx0)); ep1[g] = ex2(fmaf(x1, L2E, mx1));
        en0[g] = ex2(fmaf(x0, -L2E, mn0)); en1[g] = ex2(fmaf(x1, -L2E, mn1));
        sp0 += ep0[g]; sp1 += ep1[g]; sn0 += en0[g]; sn1 += en1[g];
      }
      sp0 += __shfl_xor_sync(0xffffffffu, sp0, 1); sp1 += __shfl_xor_sync(0xffffffffu, sp1, 1);
      sn0 += __shfl_xor_sync(0xffffffffu, sn0, 1); sn1 += __shfl_xor_sync(0xffffffffu, sn1, 1);
      sp0 += __shfl_xor_sync(0xffffffffu, sp0, 2); sp1 += __shfl_xor_sync(0xffffffffu, sp1, 2);
      sn0 += __shfl_xor_sync(0xffffffffu, sn0, 2); sn1 += __shfl_xor_sync(0xffffffffu, sn1, 2);
      sp0 = rcp(sp0); sp1 = rcp(sp1); sn0 = rcp(sn0); sn1 = rcp(sn1);
#pragma unroll
      for (int g = 0; g < 5; g++) {
        fr[5 * p + g][r] = pack_bf16(ep0[g] * sp0, ep1[g] * sp1);
        fr[5 * p + g][2 + r] = pack_bf16(en0[g] * sn0, en1[g] * sn1);
      }
    }
  }
}

template <int V> struct IntC { static constexpr int value = V; };
struct Ring {
  uint32_t idx, phase;
  template <int N> __device__ __forceinline__ void next() { if (++idx == N) { idx = 0; phase ^= 1; } }
};

}

__global__ void __cluster_dims__(2, 1, 1) __launch_bounds__(384, 1)
fused_kernel(const __grid_constant__ Maps maps, const __nv_bfloat16* __restrict__ x, const __nv_bfloat16* __restrict__ wqkv,
             const __nv_bfloat16* __restrict__ wphi, const __nv_bfloat16* __restrict__ w1, const __nv_bfloat16* __restrict__ w2,
             const __nv_bfloat16* __restrict__ w3, const __nv_bfloat16* __restrict__ w4, const __nv_bfloat16* __restrict__ wo,
             const __nv_bfloat16* __restrict__ gate_w, __nv_bfloat16* __restrict__ out) {
  extern __shared__ __align__(1024) uint8_t sgen[];
  const uint32_t sb = smem_u32(sgen);
  const uint32_t sb16 = (sb & 0x3FFFFu) >> 4;
  const uint32_t bars = sb + OFF_BAR;
  const uint32_t fullA = bars + 8 * B_FULLA, emptyA = bars + 8 * B_EMPTYA, fullB = bars + 8 * B_FULLB, emptyB = bars + 8 * B_EMPTYB;

  const int tid = threadIdx.x;
  const int rank = blockIdx.x & 1;
  const int bid = blockIdx.x - NSVC, pairIdx = bid >> 1;
  const int i = pairIdx >> 2, j = 2 * (pairIdx & 3) + rank;
  const int k3 = (5 * (pairIdx & 3) + 1) >> 1;

  if (bid < 0) {
    const int sv = blockIdx.x;
    const unsigned epoch = *reinterpret_cast<volatile unsigned*>(g_flags + FL_DONE * 32) / NCTA;
    if (tid == 0) {
#pragma unroll
      for (int b = 0; b < 11; b++) mbar_init(bars + 8 * b, 1);
      mbar_expect_tx(bars + 80, 6400);
      bulk_load(sb + 204800, wphi + sv * 3200, 6400, bars + 80);
    }
    __syncthreads();
    float a[8];
#pragma unroll 1
    for (int rd = 0; rd < 4; rd++) {
      const int nch = rd ? 192 : 80, nth = rd ? 384 : 320, piece = rd ? 18432 : 20480, np = rd == 3 ? 7 : 10;
      if (tid == 0) {
        const char* src = reinterpret_cast<const char*>(rd ? w3 + (size_t)(160 * sv + 60 * (rd - 1)) * F_ : w1 + (size_t)160 * sv * D_);
#pragma unroll 1
        for (int p = 0; p < np; p++) {
          const int bytes = (rd == 3 && p == 6) ? 12288 : piece;
          mbar_expect_tx(bars + 8 * p, bytes);
          bulk_load(sb + p * piece, src + p * piece, bytes, bars + 8 * p);
        }
      }
      if (rd == 0) {
        if (tid < 40 && (tid < 20 || sv >= 2))
          reinterpret_cast<uint4*>(g_Hs + (size_t)(2 + ((sv & 1) ? S_ - 1 - tid / 20 : tid / 20)) * D_ + 160 * sv)[tid % 20] = make_uint4(0, 0, 0, 0);
        mbar_wait(bars + 80, 0);
#pragma unroll 1
        for (int e = tid; e < 1600; e += 384) {
          const int jj = e / 800, it = e - 800 * jj, st = it / 160, n = (it - 160 * st) >> 1, k0 = 16 * st + 8 * ((it ^ (n >> 2)) & 1);
          const int nn = n % 40, h = 2 * (n / 40) + (nn & 1), ff = 4 * (nn >> 3) + ((nn >> 1) & 3);
          uint32_t w[8];
#pragma unroll
          for (int q = 0; q < 8; q++) {
            const int k = k0 + q;
            w[q] = (unsigned)(k - 20 * h) < 20u ? reinterpret_cast<const unsigned short*>(sgen + 204800)[jj * 1600 + k * 20 + ff] : 0u;
          }
          g_wphi[sv * 1600 + e] = make_uint4(w[0] | (w[1] << 16), w[2] | (w[3] << 16), w[4] | (w[5] << 16), w[6] | (w[7] << 16));
        }
      }
      if (rd < 2) {
#pragma unroll
        for (int e = 0; e < 8; e++) a[e] = 0.f;
      }
#pragma unroll 1
      for (int p = 0; p < np; p++) {
        mbar_wait(bars + 8 * p, rd & 1);
        const int bytes = (rd == 3 && p == 6) ? 12288 : piece;
        if (tid < nth) {
#pragma unroll 1
          for (int o = tid * 16; o < bytes; o += nth * 16) {
            const uint4 v = lds128(sb + p * piece + o);
            a[0] += bf_lo(v.x); a[1] += bf_hi(v.x); a[2] += bf_lo(v.y); a[3] += bf_hi(v.y);
            a[4] += bf_lo(v.z); a[5] += bf_hi(v.z); a[6] += bf_lo(v.w); a[7] += bf_hi(v.w);
          }
        }
      }
      if (tid < nth && (rd == 0 || rd == 3)) {
        float* cd = g_cs[epoch & 1] + (rd ? D_ : 0) + 8 * (tid % nch);
        red_add4(cd, a[0], a[1], a[2], a[3]); red_add4(cd + 4, a[4], a[5], a[6], a[7]);
      }
      __syncthreads();
      if (tid == 0 && (rd == 0 || rd == 3)) {
        flag_add(rd ? FL_CS3 : FL_CS);
        if (rd == 0) l2_prefetch(w2 + (size_t)sv * (D_ * D_ / NSVC), D_ * D_ * 2 / NSVC);
      }
    }
#pragma unroll 1
    for (int e = tid; e < (D_ + F_) / NSVC; e += 384) g_cs[(epoch + 1) & 1][sv * ((D_ + F_) / NSVC) + e] = 0.f;
#pragma unroll 1
    for (int e = tid; e < 2 * KV_J; e += 384) g_acc[(epoch + 1) & 1][sv * 2 * KV_J + e] = 0.f;
    if (tid < 32) {
      l2_prefetch(w4 + (size_t)(sv * 32 + tid) * (F_ * D_ / 128), F_ * D_ * 2 / 128);
      l2_prefetch(wo + (size_t)(sv * 32 + tid) * (D_ * D_ / 128), D_ * D_ * 2 / 128);
    }
    return;
  }
  TSTAMP(0);
  if (tid >= 256) {
    asm volatile("setmaxnreg.dec.sync.aligned.u32 40;");
    if (tid == 256) {
#pragma unroll
      for (int s = 0; s < NA; s++) mbar_init(fullA + 8 * s, 1);
      asm volatile("fence.mbarrier_init.release.cluster;" ::: "memory");
#pragma unroll 1
      for (int u = 0; u < 4; u++) {
        if ((u & 1) == 0) mbar_expect_tx(fullA + 4 * u, SLOT_A);
        tma2d(sb + OFF_A + u * 8192, &maps.x, fullA + 8 * (u >> 1), 64 * (u >> 1), 128 * i + 64 * (u & 1));
      }
    } else if (tid == 288) {
#pragma unroll
      for (int s = 0; s < NB; s++) { mbar_init(fullB + 8 * s, 1); mbar_init(emptyB + 8 * s, 8); }
      asm volatile("fence.mbarrier_init.release.cluster;" ::: "memory");
    } else if (tid == 320) {
#pragma unroll
      for (int b = B_CS; b < NBAR; b++) if (b < B_EMPTYB || b >= B_EMPTYB + NB) mbar_init(bars + 8 * b, b < B_EMPTYB ? 1 : b < B_EMPTYA ? 8 : b < B_X1P ? 16 : 2);
#pragma unroll
      for (int b = B_DSR; b < B_EMPTYB; b++) mbar_expect_tx(bars + 8 * b, 10240);
      asm volatile("fence.mbarrier_init.release.cluster;" ::: "memory");
    }
    __syncwarp();
    asm volatile("barrier.cluster.arrive.relaxed.aligned;" ::: "memory");
    auto get_epoch = [&]() { return *reinterpret_cast<volatile unsigned*>(g_flags + FL_DONE * 32) / NCTA; };
    if ((tid >> 5) != 9) asm volatile("barrier.cluster.wait.aligned;" ::: "memory");
    const int lane = tid & 31, pw = (tid >> 5) & 3;
    if (pw == 0) {
      if (tid == 256) {
        Ring r{2, 1};
        unsigned ep1 = 0;
#pragma unroll 1
        for (int k = 2; k < 25; k++) {
          if (k == 4) ep1 = get_epoch() + 1;
          if (k == 10 || k == 17) {
            if (k == 10) mbar_wait(bars + 8 * B_HST, 0);
            flag_wait(k == 10 ? FL_H + 2 * i + rank : FL_X1 + i, ep1 * 8u);
            TSTAMPX(k == 10 ? 29 : 30);
          }
          if (k == 15) mbar_wait(bars + 8 * B_X1P, 0);
          mbar_wait(emptyA + 8 * r.idx, r.phase);
          const uint32_t bar = fullA + 8 * r.idx, slot = sb + OFF_A + r.idx * SLOT_A;
          mbar_expect_tx(bar, SLOT_A);
          if (k >= 10 && k < 15) tma2d(slot, &maps.hs, bar, 64 * (k - 10) + 320 * rank, 128 * i);
          else tma2d_mc(slot + rank * 8192, k < 10 ? &maps.x : &maps.x1, bar, 64 * (k < 10 ? k : (k - 15 + k3) % 10), 128 * i + 64 * rank);
          r.next<NA>();
        }
      }
    } else if (pw == 1) {
      if (tid == 288) {
        Ring r{0, 1};
#pragma unroll 1
        for (int k = 0; k < 18; k++) {
          mbar_wait(emptyB + 8 * r.idx, r.phase);
          const uint32_t bar = fullB + 8 * r.idx, slot = sb + OFF_B + r.idx * SLOT_B;
          if (k < 10) {
            mbar_expect_tx(bar, 40960);
            tma4d(slot + 8192, &maps.qm, bar, 0, 64 * k, 0, j);
            tma3d(slot, &maps.w1m, bar, 0, 64 * k, j);
            tma4d(slot + 32768 + 2048, &maps.qr, bar, 64, 64 * k, 0, j);
            tma3d(slot + 32768, &maps.w1r, bar, 64, 64 * k, j);
          } else if (k < 13) {
            mbar_expect_tx(bar, k < 12 ? 40960 : 20480);
            tma3d(slot, &maps.w2, bar, 0, 320 * rank + 128 * (k - 10), 5 * (j >> 1));
            if (k < 12) tma3d(slot + 20480, &maps.w2, bar, 0, 320 * rank + 128 * (k - 10) + 64, 5 * (j >> 1));
          } else {
            mbar_expect_tx(bar, 49152);
            tma3d(slot, &maps.w3, bar, 0, 64 * ((2 * (k - 13) + k3) % 10), 3 * j);
            tma3d(slot + 24576, &maps.w3, bar, 0, 64 * ((2 * (k - 13) + 1 + k3) % 10), 3 * j);
          }
          r.next<NB>();
        }
#pragma unroll 1
        for (int n = 0; n < 8; n++) {
          if (n < 3) { mbar_wait(emptyB + 8 * r.idx, r.phase); r.next<NB>(); }
          if (n == 0) mbar_wait(fullA, 0);
          if (n >= 4) mbar_wait(bars + 8 * (B_EMPTY4 + n - 4), 0);
          const uint32_t bar = bars + 8 * (B_FULL4 + n), set = sb + ((n >> 1) & 1) * SET4;
          const int h = n & 1, m = ((j >> 1) + 1 + (n >> 1)) & 3;
          mbar_expect_tx(bar, h ? 40960 : 46080);
          tma3d(set + (h ? 46080 : 0), h ? &maps.w4 : &maps.wo, bar, 0, h ? 192 * j + 64 : 80 * j, 5 * m);
          tma3d(set + (h ? 66560 : 25600), &maps.w4, bar, 0, 192 * j + 128 * h, 5 * m);
        }
        mbar_wait(bars + 8 * (B_EMPTY4 + 4), 0);
        mbar_expect_tx(bars + 8 * B_XR, 20480);
        tma2d(sb + OFF_OUT, &maps.st_x1, bars + 8 * B_XR, 80 * j, 128 * i);
      }
    } else {
      const unsigned epoch = get_epoch();
      float* accg = g_acc[epoch & 1];
      if (pw == 2) {
        if (tid == 320) {
          flag_wait(FL_CS, (epoch + 1) * NSVC);
          flag_wait(FL_ST + i, (epoch + 1) * 8u);
          fence_async_glb();
          *reinterpret_cast<volatile uint32_t*>(sgen + OFF_BAR + 8 * NBAR) = (epoch + 1) & 1;
          mbar_expect_tx(bars + 8 * B_CS, 320 + 2048 + 12800);
          bulk_load(sb + OFF_CS, g_cs[epoch & 1] + 80 * j, 320, bars + 8 * B_CS);
          bulk_load(sb + OFF_XST, g_xstat + 128 * i, 2048, bars + 8 * B_CS);
          bulk_load(sb + OFF_MISC, g_wphi + j * 800, 12800, bars + 8 * B_CS);
          TSTAMPX(21);
          flag_wait(FL_KV + j, (epoch + 1) * 16u);
          mbar_wait(bars + 8 * B_SIGX1, 0);
          mbar_expect_tx(bars + 8 * B_KV, KV_J * 4);
          bulk_load(sb + OFF_A + SLOT_A, accg + j * KV_J, KV_J * 4, bars + 8 * B_KV);
          TSTAMPX(22);
          flag_wait(FL_CS3, (epoch + 1) * NSVC);
          flag_wait(FL_S1 + i, (epoch + 1) * 8u);
          fence_async_glb();
          mbar_expect_tx(bars + 8 * B_ST1, 8192 + 768);
          bulk_load(sb + OFF_CS + 320, g_cs[epoch & 1] + D_ + 192 * j, 768, bars + 8 * B_ST1);
          bulk_load(sb + OFF_MISC, g_st1 + 128 * i * 8, 8192, bars + 8 * B_ST1);
        }
        __syncwarp();
#pragma unroll 1
        for (int c = 0; c < 3; c++) {
          mbar_wait(bars + 8 * (B_EMPTY4 + (c ? 5 : 4)), 0);
          const uint4* src = g_part + (size_t)((i * 8 + j) * 3 + c) * 1280;
          const unsigned* tp = reinterpret_cast<const unsigned*>(src + 1024 + (lane & 7) * 32 + 31);
          uint32_t n = 0;
          while (!__all_sync(0xffffffffu, (ld_acquire(tp) ^ epoch) & 1u) && ++n < (WAIT_LIMIT >> 2)) {}
          if (tid == 320) {
            mbar_expect_tx(bars + 8 * (B_RDY + c), 20480);
            bulk_load(sb + (c ? 25600 + 20480 * c : 0), src, 20480, bars + 8 * (B_RDY + c));
          }
        }
      }
      if (tid == 352) {
        mbar_wait(bars + 8 * B_SIGP, 0);
        flag_add(FL_ST + i);
        TSTAMPX(20);
        const int shift = (j < 2) ? 1 : (j < 4) ? -1 : (j < 6) ? 2 : -2;
        prefetch_tmap(&maps.st_h); prefetch_tmap(&maps.st_x1); prefetch_tmap(&maps.hs); prefetch_tmap(&maps.x1); prefetch_tmap(&maps.xr);
        prefetch_tmap(&maps.w2); prefetch_tmap(&maps.w3); prefetch_tmap(&maps.w4); prefetch_tmap(&maps.wo);
        mbar_wait(bars + 8 * B_SIGH, 0);
        TSTAMPX(23);
        fence_async_smem();
        tma2d_store(&maps.st_h, sb + OFF_STG, 80 * j, 128 * i + 2 + shift);
        bulk_commit(); bulk_wait<0>();
        flag_add(FL_H + 2 * i + (j >> 2));
        flag_add_relaxed(FL_H + 2 * ((i + (shift > 0 ? 1 : -1)) & 15) + (j >> 2));
        mbar_arrive(bars + 8 * B_HST);
        TSTAMPX(24);
        mbar_wait(bars + 8 * B_SIGKV, 0);
        TSTAMPX(25);
        fence_async_smem();
        asm volatile("cp.reduce.async.bulk.global.shared::cta.bulk_group.add.f32 [%0], [%1], %2;"
                     ::"l"(accg + j * KV_J), "r"(sb + OFF_MISC), "r"(KV_J * 4) : "memory");
        bulk_commit();
        mbar_expect_tx(bars + 8 * B_XR, 20480);
#pragma unroll 1
        for (int u = 0; u < 8; u++)
          tma2d(sb + OFF_B + (u / 3) * SLOT_B + SPARE + (u % 3) * 2560, &maps.xr, bars + 8 * B_XR, 80 * j, 128 * i + 16 * u);
        bulk_wait<0>();
        flag_add(FL_KV + j);
        TSTAMPX(26);
        mbar_wait(bars + 8 * B_SIGX1, 0);
        TSTAMPX(27);
        fence_async_smem();
        tma2d_store(&maps.st_x1, sb + OFF_STG, 80 * j, 128 * i);
        bulk_commit(); bulk_wait<0>();
        flag_add(FL_X1 + i);
        mbar_arrive_cta(bars + 8 * B_X1P, 0); mbar_arrive_cta(bars + 8 * B_X1P, 1);
        TSTAMPX(28);
        mbar_wait(bars + 8 * B_MFREE, 0);
        flag_add(FL_S1 + i);
      }
    }
  } else {
    uint4 pv[5], pw_[5];
    {
      const int row = 128 * i + 16 * j + (tid >> 4), l16 = tid & 15;
#pragma unroll
      for (int c = 0; c < 5; c++) pv[c] = __ldg(reinterpret_cast<const uint4*>(x + (size_t)row * D_ + c * 128 + l16 * 8));
#pragma unroll
      for (int c = 0; c < 5; c++) pw_[c] = __ldg(reinterpret_cast<const uint4*>(gate_w + c * 128 + l16 * 8));
    }
    asm volatile("barrier.cluster.arrive.relaxed.aligned;" ::: "memory");
    asm volatile("setmaxnreg.inc.sync.aligned.u32 232;");
    const int wg = tid >> 7, warp = tid >> 5, lane = tid & 31, t = lane & 3;
    const int rloc = warp * 16 + (lane >> 2);
    const float* s_cs = reinterpret_cast<const float*>(sgen + OFF_CS);
    auto signal = [&](int b) {
      __syncwarp();
      if (lane == 0) mbar_arrive(bars + 8 * b);
    };
    auto releaseB = [&](uint32_t bar) {
      __syncwarp();
      if (lane == 0) mbar_arrive(bar);
    };
    auto release = [&](uint32_t bar) {
      __syncwarp();
      if (lane < 2) mbar_arrive_cta(bar, lane);
    };
    const uint32_t stg_lane = (warp * 16 + ((lane >> 3) & 1) * 8 + (lane & 7)) * 160 + (lane >> 4) * 16;

    auto stage_tile = [&](uint32_t stg, const uint32_t (&v)[2][10]) {
#pragma unroll
      for (int s = 0; s < 5; s++) stsm4(stg + stg_lane + s * 32, v[0][2 * s], v[1][2 * s], v[0][2 * s + 1], v[1][2 * s + 1]);
    };

    {
      float f[40];
      float s = 0.f, gs = 0.f;
#pragma unroll
      for (int c = 0; c < 5; c++) {
        const uint32_t vv[4] = {pv[c].x, pv[c].y, pv[c].z, pv[c].w}, ww[4] = {pw_[c].x, pw_[c].y, pw_[c].z, pw_[c].w};
#pragma unroll
        for (int e = 0; e < 4; e++) {
          f[8 * c + 2 * e] = bf_lo(vv[e]); f[8 * c + 2 * e + 1] = bf_hi(vv[e]);
          s += f[8 * c + 2 * e] + f[8 * c + 2 * e + 1];
          gs = fmaf(f[8 * c + 2 * e], bf_lo(ww[e]), gs); gs = fmaf(f[8 * c + 2 * e + 1], bf_hi(ww[e]), gs);
        }
      }
#pragma unroll
      for (int o = 1; o < 16; o <<= 1) { s += __shfl_xor_sync(0xffffffffu, s, o); gs += __shfl_xor_sync(0xffffffffu, gs, o); }
      const float mean = s * (1.f / D_);
      float q = 0.f;
#pragma unroll
      for (int e = 0; e < 40; e++) { const float d = f[e] - mean; q = fmaf(d, d, q); }
#pragma unroll
      for (int o = 1; o < 16; o <<= 1) q += __shfl_xor_sync(0xffffffffu, q, o);
      const float rstd = rsqrtf(q * (1.f / D_) + 1e-5f);
      asm volatile("barrier.cluster.wait.aligned;" ::: "memory");
      if ((tid & 15) == 0) g_xstat[128 * i + 16 * j + (tid >> 4)] = make_float4(rstd, -mean, rcp(1.f + __expf(-gs)), 0.f);
      signal(B_SIGP);
    }
    TSTAMP(1);

    Ring ra{0, 0}, rb{0, 0};
    uint32_t qp[2][10], P[2][10];
    float st_g[2];
    {
      float accM[128], accR[32];
      uint32_t pa = 0, pb = 0;
#pragma unroll 1
      for (int k = 0; k < 10; k++) {
        mbar_wait(fullA + 8 * ra.idx, ra.phase);
        if (tid == 0) TRACE(32 + k);
        mbar_wait(fullB + 8 * rb.idx, rb.phase);
        if (tid == 0) TRACE(64 + k);
        if (k == 0) TSTAMP(2);
        const uint32_t a0 = sb16 + ((OFF_A + ra.idx * SLOT_A + wg * 8192) >> 4), b0 = sb16 + ((OFF_B + rb.idx * SLOT_B) >> 4);
        wg_fence();
#pragma unroll
        for (int kk = 0; kk < 4; kk++) {
          const uint64_t da = make_desc(a0, kk * 32, 16, 1024, 1);
          if (kk == 0) {
            mma_ss256_p(accM, da, make_desc(b0, 0, 8192, 1024, 1), k);
            mma_ss64_p(accR, da, make_desc(b0, 32768, 2048, 256, 3), k);
          } else {
            mma_ss256(accM, da, make_desc(b0, kk * 2048, 8192, 1024, 1));
            mma_ss64(accR, da, make_desc(b0, 32768 + kk * 512, 2048, 256, 3));
          }
          if (kk == 0) {
            wg_commit();
            if (k > 0) {
              wg_wait<1>();
              release(emptyA + 8 * pa);
              releaseB(emptyB + 8 * pb);
            }
          }
        }
        wg_commit();
        pa = ra.idx; pb = rb.idx;
        ra.next<NA>(); rb.next<NB>();
      }
      TSTAMP(18);
      float st_rstd[2], st_mr[2];
      mbar_wait(bars + 8 * B_CS, 0);
#pragma unroll
      for (int r = 0; r < 2; r++) {
        const uint4 st = lds128(sb + OFF_XST + (rloc + 8 * r) * 16);
        st_rstd[r] = __uint_as_float(st.x); st_mr[r] = __uint_as_float(st.y); st_g[r] = __uint_as_float(st.z);
      }
      TSTAMP(19);
      wg_wait<0>();
      fence_regs(accM); fence_regs(accR);
      TSTAMP(3);
      release(emptyA + 8 * pa);
#define ACC(P_, G, I_) ((G) < 8 ? accM[(P_) * 32 + ((G) & 7) * 4 + (I_)] : accR[(P_) * 8 + ((G) & 1) * 4 + (I_)])
      {
        uint32_t hv[2][10];
        const GeluC g0 = gelu_consts(st_rstd[0], 1.f), g1 = gelu_consts(st_rstd[1], 1.f);
#pragma unroll
        for (int g = 0; g < 10; g++) {
          const float2 cs = *reinterpret_cast<const float2*>(s_cs + 8 * g + 2 * t);
          const float v0 = gelu_s(fmaf(st_mr[0], cs.x, ACC(0, g, 0)), g0), v1 = gelu_s(fmaf(st_mr[0], cs.y, ACC(0, g, 1)), g0);
          const float v2 = gelu_s(fmaf(st_mr[1], cs.x, ACC(0, g, 2)), g1), v3 = gelu_s(fmaf(st_mr[1], cs.y, ACC(0, g, 3)), g1);
          hv[0][g] = pack_bf16(v0, v1); hv[1][g] = pack_bf16(v2, v3);
        }
        bar_sync(1, 256);
        stage_tile(sb + OFF_STG, hv);
        signal(B_SIGH);
      }
      TSTAMP(4);
      uint32_t kf[5][4], qf[5][4];
#pragma unroll
      for (int s = 0; s < 5; s++) {
        kf[s][0] = pack_bf16(ACC(2, 2 * s, 0), ACC(2, 2 * s, 1)); kf[s][1] = pack_bf16(ACC(2, 2 * s, 2), ACC(2, 2 * s, 3));
        kf[s][2] = pack_bf16(ACC(2, 2 * s + 1, 0), ACC(2, 2 * s + 1, 1)); kf[s][3] = pack_bf16(ACC(2, 2 * s + 1, 2), ACC(2, 2 * s + 1, 3));
        qf[s][0] = pack_bf16(ACC(1, 2 * s, 0), ACC(1, 2 * s, 1)); qf[s][1] = pack_bf16(ACC(1, 2 * s, 2), ACC(1, 2 * s, 3));
        qf[s][2] = pack_bf16(ACC(1, 2 * s + 1, 0), ACC(1, 2 * s + 1, 1)); qf[s][3] = pack_bf16(ACC(1, 2 * s + 1, 2), ACC(1, 2 * s + 1, 3));
      }
      float pk[40], pq[40];
      wg_fence();
#pragma unroll
      for (int s = 0; s < 5; s++) {
        if (s == 0) mma_rs80_k_z(pk, kf[s], make_desc(sb16, OFF_MISC, 16, 256, 3));
        else mma_rs80_k(pk, kf[s], make_desc(sb16, OFF_MISC + s * 2560, 16, 256, 3));
      }
      wg_commit();
#pragma unroll
      for (int s = 0; s < 5; s++) {
        if (s == 0) mma_rs80_k_z(pq, qf[s], make_desc(sb16, OFF_MISC, 16, 256, 3));
        else mma_rs80_k(pq, qf[s], make_desc(sb16, OFF_MISC + s * 2560, 16, 256, 3));
      }
      wg_commit();
      {
        const int mat = lane >> 3;
        const int tok = warp * 16 + (mat & 1) * 8 + (lane & 7);
        const uint32_t base = sb + OFF_B + SPARE + tok * 32 + (((mat >> 1) ^ ((tok >> 2) & 1)) << 4);
        const uint32_t ones = (t == 0) ? 0x00003f80u : 0u;
#pragma unroll
        for (int p = 0; p < 2; p++) {
#pragma unroll
          for (int gg = 0; gg < 3; gg++) {
            const int g0 = 5 * p + 2 * gg;
            uint32_t r0 = pack_bf16(ACC(3, g0, 0), ACC(3, g0, 1)), r1 = pack_bf16(ACC(3, g0, 2), ACC(3, g0, 3));
            uint32_t r2 = ones, r3 = ones;
            if (gg < 2) { r2 = pack_bf16(ACC(3, g0 + 1, 0), ACC(3, g0 + 1, 1)); r3 = pack_bf16(ACC(3, g0 + 1, 2), ACC(3, g0 + 1, 3)); }
            stsm4(base + gg * SLOT_B + p * 4096, r0, r1, r2, r3);
          }
        }
      }
#undef ACC
      wg_wait<1>();
      fence_regs(pk);
#pragma unroll
      for (int G = 0; G < 10; G++) {
        P[0][G] = pack_bf16(pk[4 * G], pk[4 * G + 1]); P[1][G] = pack_bf16(pk[4 * G + 2], pk[4 * G + 3]);
      }
      wg_wait<0>();
      fence_regs(pq);
#pragma unroll
      for (int G = 0; G < 10; G++) {
        qp[0][G] = pack_bf16(pq[4 * G], pq[4 * G + 1]); qp[1][G] = pack_bf16(pq[4 * G + 2], pq[4 * G + 3]);
      }
    }

    uint32_t fr[10][4];
    int pass;
    pass = gridDim.y;
#pragma unroll 1
    do {
    feature_map(P, fr);
    if (pass != 0) {
    {
      const int mat = lane >> 3;
      const int tok = warp * 16 + (mat & 1) * 8 + (lane & 7);
      const uint32_t base = sb + OFF_B + tok * 32 + (((mat >> 1) ^ ((tok >> 2) & 1)) << 4);
#pragma unroll
      for (int G = 0; G < 10; G++) stsm4(base + G * 4096, fr[G][0], fr[G][1], fr[G][2], fr[G][3]);
      fence_async_smem();
      bar_sync(1, 256);
      float kv[40];
      const uint32_t va = sb16 + ((OFF_B + SPARE + wg * 4096) >> 4), vb = sb16 + ((OFF_B + wg * 20480) >> 4);
      wg_fence();
#pragma unroll
      for (int ks = 0; ks < 8; ks++) {
        if (ks == 0) mma_ss80_tt_z(kv, make_desc(va, 0, SLOT_B, 256, 3), make_desc(vb, 0, 4096, 256, 3));
        else mma_ss80_tt(kv, make_desc(va, ks * 512, SLOT_B, 256, 3), make_desc(vb, ks * 512, 4096, 256, 3));
      }
      wg_commit();
      uint32_t xv[2][10];
      float acc[80];
      TSTAMP(5);
      mbar_wait(fullA + 8 * 2, 0);
      mbar_wait(fullB + 8 * 1, 1);
      TSTAMP(6);
      wg_fence();
#pragma unroll
      for (int kk = 0; kk < 4; kk++) {
        const uint64_t da = make_desc(sb16 + wg * 512, OFF_A + 2 * SLOT_A + kk * 32, 16, 1024, 1);
        const uint64_t db = make_desc(sb16, OFF_B + SLOT_B + kk * 1024, 4096, 512, 2);
        if (kk == 0) mma_ss160_z(acc, da, db); else mma_ss160(acc, da, db);
      }
      wg_commit();
      ra.next<NA>();
      wg_wait<1>();
      fence_regs(kv);
      TSTAMP(31);
      releaseB(emptyB); release(bars + 8 * B_PEER2);
      const uint32_t dst = sb + OFF_MISC + wg * (KV_PAIR * 4);
      const int m0 = (warp & 3) * 16 + (lane >> 2);
#pragma unroll
      for (int r = 0; r < 2; r++) {
        const int m = m0 + 8 * r;
        const bool hi = m >= 20;
        uint32_t v[10];
#pragma unroll
        for (int G = 0; G < 10; G++) v[G] = __float_as_uint(hi ? kv[4 * G + 2 * r + 1] : kv[4 * G + 2 * r]);
        const uint32_t p = dst + 4 * (m < 40 ? m * 48 + t * 12 : 1920 + t * 24 + 12);
        if (m <= 40) {
          sts128(p, make_uint4(v[0], v[1], v[2], v[3])); sts128(p + 16, make_uint4(v[4], v[5], v[6], v[7]));
          sts128(p + 32, make_uint4(v[8], v[9], 0u, 0u));
        }
      }
      if (m0 == 32) {
        const uint32_t p = dst + 4 * (1920 + t * 24);
        sts128(p, make_uint4(__float_as_uint(kv[2]), __float_as_uint(kv[6]), __float_as_uint(kv[10]), __float_as_uint(kv[14])));
        sts128(p + 16, make_uint4(__float_as_uint(kv[18]), __float_as_uint(kv[22]), __float_as_uint(kv[26]), __float_as_uint(kv[30])));
        sts128(p + 32, make_uint4(__float_as_uint(kv[34]), __float_as_uint(kv[38]), 0u, 0u));
      }
      signal(B_SIGKV);
      uint32_t pa = 2, pb = 1;
#pragma unroll 1
      for (int k = 1; k < 5; k++) {
        mbar_wait(fullA + 8 * ra.idx, ra.phase);
        if ((k & 1) == 0) mbar_wait(fullB + 8 * rb.idx, rb.phase);
        const uint32_t a0 = sb16 + ((OFF_A + ra.idx * SLOT_A + wg * 8192) >> 4);
        const uint32_t b0 = sb16 + ((OFF_B + rb.idx * SLOT_B + (k & 1) * 20480) >> 4);
        wg_fence();
#pragma unroll
        for (int kk = 0; kk < 4; kk++) {
          mma_ss160(acc, make_desc(a0, kk * 32, 16, 1024, 1), make_desc(b0, kk * 1024, 4096, 512, 2));
          if (kk == 0) {
            wg_commit();
            wg_wait<1>();
            if (k != 4) release(emptyA + 8 * pa);
          }
        }
        wg_commit();
        pa = ra.idx; pb = rb.idx;
        ra.next<NA>();
        if ((k & 1) || k == 4) rb.next<NB>();
      }
      {
        mbar_wait(bars + 8 * B_XR, 0);
        const uint32_t xa = sb + OFF_B + (warp / 3) * SLOT_B + SPARE + (warp % 3) * 2560 + (lane >> 2) * 160 + t * 4;
#pragma unroll
        for (int g = 0; g < 10; g++) { xv[0][g] = lds32(xa + g * 16); xv[1][g] = lds32(xa + 1280 + g * 16); }
      }
      releaseB(emptyB + 8); releaseB(emptyB + 16);
      mbar_wait(bars + 8 * B_PEER2, 0);
      wg_wait<0>();
      fence_regs(acc);
      release(emptyA + 8 * pa);
      TSTAMP(7);
      {
        uint32_t sn[20];
        if (rank) {
#pragma unroll
          for (int e = 0; e < 20; e++) sn[e] = pack_bf16(acc[2 * e], acc[2 * e + 1]);
#pragma unroll
          for (int e = 0; e < 40; e++) acc[e] = acc[40 + e];
        } else {
#pragma unroll
          for (int e = 0; e < 20; e++) sn[e] = pack_bf16(acc[40 + 2 * e], acc[41 + 2 * e]);
        }
        const uint32_t peer = map_peer(sb, rank ^ 1);
#pragma unroll
        for (int q = 0; q < 5; q++)
          st_async16(peer + OFF_B + 20480 + tid * 16 + q * 4096, sn[4 * q], sn[4 * q + 1], sn[4 * q + 2], sn[4 * q + 3],
                     peer + OFF_BAR + 8 * (B_DSR + 8 + wg));
#pragma unroll
        for (int g = 0; g < 10; g++) {
          acc[4 * g] += bf_lo(xv[0][g]); acc[4 * g + 1] += bf_hi(xv[0][g]);
          acc[4 * g + 2] += bf_lo(xv[1][g]); acc[4 * g + 3] += bf_hi(xv[1][g]);
        }
        bar_sync(1, 256);
        mbar_wait(bars + 8 * (B_DSR + 8 + wg), 0);
#pragma unroll
        for (int q = 0; q < 5; q++) {
          const uint4 v = lds128(sb + OFF_B + 20480 + tid * 16 + q * 4096);
          float* d = &acc[8 * q];
          d[0] += bf_lo(v.x); d[1] += bf_hi(v.x); d[2] += bf_lo(v.y); d[3] += bf_hi(v.y);
          d[4] += bf_lo(v.z); d[5] += bf_hi(v.z); d[6] += bf_lo(v.w); d[7] += bf_hi(v.w);
          xv[0][2 * q] = pack_bf16(d[0], d[1]); xv[1][2 * q] = pack_bf16(d[2], d[3]);
          xv[0][2 * q + 1] = pack_bf16(d[4], d[5]); xv[1][2 * q + 1] = pack_bf16(d[6], d[7]);
        }
        releaseB(emptyB + 8 * pb);
      }
      TSTAMP(16);
      stage_tile(sb + OFF_STG, xv);
      signal(B_SIGX1);
      TSTAMP(17);
#pragma unroll
      for (int r = 0; r < 2; r++) {
        float s = 0.f;
#pragma unroll
        for (int g = 0; g < 10; g++) s += acc[4 * g + 2 * r] + acc[4 * g + 2 * r + 1];
        s += __shfl_xor_sync(0xffffffffu, s, 1); s += __shfl_xor_sync(0xffffffffu, s, 2);
        const float mu = s * (1.f / 80.f);
        float q = 0.f;
#pragma unroll
        for (int g = 0; g < 10; g++) {
          const float d0 = acc[4 * g + 2 * r] - mu, d1 = acc[4 * g + 2 * r + 1] - mu;
          q = fmaf(d0, d0, q); q = fmaf(d1, d1, q);
        }
        q += __shfl_xor_sync(0xffffffffu, q, 1); q += __shfl_xor_sync(0xffffffffu, q, 2);
        if (t == 0) g_st1[(128 * i + rloc + 8 * r) * 8 + j] = make_float2(mu, q);
      }
    }
    TSTAMP(8);
#pragma unroll
    for (int G = 0; G < 10; G++) { P[0][G] = qp[0][G]; P[1][G] = qp[1][G]; }
    }
    asm volatile("" : "+r"(pass));
    } while (pass-- != 0);

    uint32_t of[5][4];
    {
      mbar_wait(bars + 8 * B_KV, 0);
#pragma unroll 1
      for (int it = tid; it < 384; it += 256) {
        const int p = it >= 192, rem = it - 192 * p, n = rem >> 2, tq = rem & 3;
        const uint32_t sp = sb + OFF_A + SLOT_A + 4 * (p * KV_PAIR + (n < 40 ? n * 48 + tq * 12 : 1920 + tq * 24 + (n & 1) * 12));
        const uint4 ka = lds128(sp), kb = lds128(sp + 16), kc = lds128(sp + 32);
        const uint32_t v[10] = {ka.x, ka.y, ka.z, ka.w, kb.x, kb.y, kb.z, kb.w, kc.x, kc.y};
        const int sh = (n < 40 ? (n >= 20) : (n & 1)) * 16;
        uint8_t* dst = sgen + OFF_MISC + p * 7680 + n * 32 + tq * 4;
        const int sw = ((n >> 2) & 1) << 4;
#pragma unroll
        for (int G = 0; G < 10; G++)
          *reinterpret_cast<uint32_t*>(dst + (G >> 1) * 1536 + (((G & 1) << 4) ^ sw)) = pack_bf16(__uint_as_float(v[G]), 0.f) << sh;
      }
      release(emptyA + 8);
      fence_async_smem();
      bar_sync(1, 256);
      float o0[24], o1[24];
      wg_fence();
#pragma unroll
      for (int g = 0; g < 5; g++) {
        if (g == 0) mma_rs48_k_z(o0, fr[g], make_desc(sb16, OFF_MISC, 16, 256, 3));
        else mma_rs48_k(o0, fr[g], make_desc(sb16, OFF_MISC + g * 1536, 16, 256, 3));
      }
#pragma unroll
      for (int g = 0; g < 5; g++) {
        if (g == 0) mma_rs48_k_z(o1, fr[5], make_desc(sb16, OFF_MISC + 7680, 16, 256, 3));
        else mma_rs48_k(o1, fr[5 + g], make_desc(sb16, OFF_MISC + 7680 + g * 1536, 16, 256, 3));
      }
      wg_commit();
      wg_wait<0>();
      fence_regs(o0); fence_regs(o1);
      signal(B_MFREE);
#pragma unroll
      for (int r = 0; r < 2; r++) {
        const float a0 = __fdividef(st_g[r], o0[20 + 2 * r] + 1e-6f), a1 = __fdividef(st_g[r], o0[21 + 2 * r] + 1e-6f);
        const float b0 = __fdividef(st_g[r], o1[20 + 2 * r] + 1e-6f), b1 = __fdividef(st_g[r], o1[21 + 2 * r] + 1e-6f);
        const float am = t < 2 ? a0 : a1, bm = t < 2 ? b0 : b1;
#pragma unroll
        for (int g = 0; g < 5; g++) {
          const float sa = g < 2 ? a0 : (g == 2 ? am : a1), sb2 = g < 2 ? b0 : (g == 2 ? bm : b1);
          of[g >> 1][(g & 1) * 2 + r] = pack_bf16(o0[4 * g + 2 * r] * sa, o0[4 * g + 2 * r + 1] * sa);
          of[(5 + g) >> 1][((5 + g) & 1) * 2 + r] = pack_bf16(o1[4 * g + 2 * r] * sb2, o1[4 * g + 2 * r + 1] * sb2);
        }
      }
    }
    TSTAMP(9);

    uint32_t hf[12][4];
    float ac4[80];
    auto unit = [&](auto uc, uint32_t b0) {
      constexpr int u = decltype(uc)::value;
#pragma unroll
      for (int s = 0; s < (u ? 4 : 5); s++) {
        const uint64_t db = make_desc(b0, (u ? 5120 + 20480 * u : 0) + s * 1024, u ? 4096 : 5120, 512, 2);
        if (u == 0 && s == 0) mma_rs160_n_z(ac4, of[0], db);
        else if (u == 0) mma_rs160_n(ac4, of[s], db);
        else mma_rs160_n(ac4, hf[(4 * u + 8 + s) % 12], db);
      }
      wg_commit();
    };
    {
      float acc[96];
      uint32_t pa = 0, pb = 0;
#pragma unroll 1
      for (int k = 0; k < 10; k++) {
        mbar_wait(fullA + 8 * ra.idx, ra.phase);
        if (tid == 0) TRACE(52 + k);
        if ((k & 1) == 0) mbar_wait(fullB + 8 * rb.idx, rb.phase);
        if (tid == 0) TRACE(84 + k);
        if (k == 0) TSTAMP(10);
        const uint32_t a0 = sb16 + ((OFF_A + ra.idx * SLOT_A + wg * 8192) >> 4);
        const uint32_t b0 = sb16 + ((OFF_B + rb.idx * SLOT_B + (k & 1) * 24576) >> 4);
        wg_fence();
#pragma unroll
        for (int kk = 0; kk < 4; kk++) {
          if (kk == 0) mma_ss192_p(acc, make_desc(a0, 0, 16, 1024, 1), make_desc(b0, 0, 8192, 1024, 1), k);
          else mma_ss192(acc, make_desc(a0, kk * 32, 16, 1024, 1), make_desc(b0, kk * 2048, 8192, 1024, 1));
          if (kk == 0) {
            wg_commit();
            if (k > 0) {
              wg_wait<1>();
              release(emptyA + 8 * pa);
              if ((k & 1) == 0) releaseB(emptyB + 8 * pb);
            }
          }
        }
        wg_commit();
        pa = ra.idx; pb = rb.idx;
        ra.next<NA>();
        if (k & 1) rb.next<NB>();
      }
      float rs[2], mm[2];
      mbar_wait(bars + 8 * B_ST1, 0);
#pragma unroll
      for (int r = 0; r < 2; r++) {
        const uint4 su = lds128(sb + OFF_MISC + (rloc + 8 * r) * 64 + t * 16);
        const float m0 = __uint_as_float(su.x), m1 = __uint_as_float(su.z);
        float mu = m0 + m1;
        mu += __shfl_xor_sync(0xffffffffu, mu, 1); mu += __shfl_xor_sync(0xffffffffu, mu, 2);
        mu *= 0.125f;
        const float d0 = m0 - mu, d1 = m1 - mu;
        float q = __uint_as_float(su.y) + __uint_as_float(su.w) + 80.f * (d0 * d0 + d1 * d1);
        q += __shfl_xor_sync(0xffffffffu, q, 1); q += __shfl_xor_sync(0xffffffffu, q, 2);
        rs[r] = rsqrtf(q * (1.f / D_) + 1e-5f);
        mm[r] = -mu;
      }
      mbar_wait(bars + 8 * B_FULL4, 0);
      wg_fence();
      unit(IntC<0>{}, sb16);
      wg_wait<1>();
      fence_regs(acc);
      releaseB(emptyB + 8 * pb);
      release(bars + 8 * B_PEER);
      TSTAMP(11);
      const GeluC g0 = gelu_consts(rs[0], 1.f - st_g[0]), g1 = gelu_consts(rs[1], 1.f - st_g[1]);
#pragma unroll
      for (int g = 0; g < 24; g++) {
        const float2 cs = *reinterpret_cast<const float2*>(s_cs + 80 + 8 * g + 2 * t);
        const float v0 = gelu_s(fmaf(mm[0], cs.x, acc[4 * g]), g0), v1 = gelu_s(fmaf(mm[0], cs.y, acc[4 * g + 1]), g0);
        const float v2 = gelu_s(fmaf(mm[1], cs.x, acc[4 * g + 2]), g1), v3 = gelu_s(fmaf(mm[1], cs.y, acc[4 * g + 3]), g1);
        hf[g >> 1][(g & 1) * 2] = pack_bf16(v0, v1);
        hf[g >> 1][(g & 1) * 2 + 1] = pack_bf16(v2, v3);
        if (g == 7) { wg_fence(); unit(IntC<1>{}, sb16); }
        if (g == 15) { mbar_wait(bars + 8 * (B_FULL4 + 1), 0); wg_fence(); unit(IntC<2>{}, sb16); }
        if (g == 23) { wg_wait<1>(); signal(B_EMPTY4); wg_fence(); unit(IntC<3>{}, sb16); }
      }
    }
    TSTAMP(12);

    {
      float kp[40];
      uint32_t sn[20], kb[20];
      const uint32_t peer = map_peer(sb, rank ^ 1);
      const uint32_t tag = lds32(sb + OFF_BAR + 8 * NBAR);
      auto add8 = [&](int q, const uint4 v) {
        float* d = &kp[8 * q];
        d[0] += bf_lo(v.x); d[1] += bf_hi(v.x); d[2] += bf_lo(v.y); d[3] += bf_hi(v.y);
        d[4] += bf_lo(v.z); d[5] += bf_hi(v.z); d[6] += bf_lo(v.w); d[7] += bf_hi(v.w);
      };
      auto send = [&](int c) {
        const uint32_t dso = peer + OFF_DS + (c & 1) * 20480 + tid * 16, dsb = peer + OFF_BAR + 8 * (B_DSR + 2 * c + wg);
#pragma unroll
        for (int q = 0; q < 5; q++) st_async16(dso + q * 4096, sn[4 * q], sn[4 * q + 1], sn[4 * q + 2], sn[4 * q + 3], dsb);
      };
      mbar_wait(bars + 8 * B_PEER, 0);
      uint4* gdst = g_part + (size_t)i * 8 * 3840 + tid;
#pragma unroll 1
      for (int c = 0; c < 3; c++) {
        const uint32_t b0 = sb16 + ((c & 1) ? 0 : SET4 >> 4), bc = bars + 16 * c;
        mbar_wait(bc + 8 * (B_FULL4 + 2), 0);
        wg_wait<0>();
        fence_regs(ac4);
        if (rank) {
#pragma unroll
          for (int e = 0; e < 20; e++) { sn[e] = pack_bf16(ac4[2 * e], ac4[2 * e + 1]); kb[e] = pack_bf16(ac4[40 + 2 * e], ac4[41 + 2 * e]); }
        } else {
#pragma unroll
          for (int e = 0; e < 20; e++) { kb[e] = pack_bf16(ac4[2 * e], ac4[2 * e + 1]); sn[e] = pack_bf16(ac4[40 + 2 * e], ac4[41 + 2 * e]); }
        }
#pragma unroll
        for (int e = 0; e < 20; e++) asm volatile("" : "+r"(sn[e]), "+r"(kb[e]));
        send(c);
        if (c == 0 && wg == 1) bar_sync(2, 256);
        wg_fence();
        unit(IntC<0>{}, b0);
        if (lane == 0) mbar_arrive(bc + 8 * (B_EMPTY4 + 1));
        unit(IntC<1>{}, b0);
        if (c == 0 && wg == 0) bar_arrive(2, 256);
        {
          mbar_wait(bc + 8 * (B_DSR + wg), 0);
          uint4* dst = gdst + (((j + 2 * c + 2) & 7) * 3 + c) * 1280;
#pragma unroll
          for (int q = 0; q < 5; q++) {
            const uint4 v = lds128(sb + OFF_DS + (c & 1) * 20480 + tid * 16 + q * 4096);
            st_relaxed16(dst + q * 256, (add_bf2(v.x, kb[4 * q]) & ~1u) | tag, add_bf2(v.y, kb[4 * q + 1]),
                         add_bf2(v.z, kb[4 * q + 2]), add_bf2(v.w, kb[4 * q + 3]));
          }
        }
        mbar_wait(bc + 8 * (B_FULL4 + 3), 0);
        wg_fence();
        unit(IntC<2>{}, b0);
        wg_wait<1>();
        if (lane == 0) mbar_arrive(bc + 8 * (B_EMPTY4 + 2));
        unit(IntC<3>{}, b0);
      }
      auto partial = [&](int c, uint4 (&v)[5]) {
        mbar_wait(bars + 8 * (B_RDY + c), 0);
        uint32_t bad = 0;
#pragma unroll
        for (int q = 0; q < 5; q++) { v[q] = lds128(sb + (c ? 25600 + 20480 * c : 0) + tid * 16 + q * 4096); bad |= v[q].x ^ tag; }
#pragma unroll 1
        for (uint32_t n = 0; (bad & 1u) && n < (WAIT_LIMIT >> 2); n++) {
          bad = 0;
#pragma unroll
          for (int q = 0; q < 5; q++) { v[q] = ld_relaxed16(gdst + (j * 3 + c) * 1280 + q * 256); bad |= v[q].x ^ tag; }
        }
      };
      uint4 pa4[5], pb4[5];
      partial(0, pa4);
      wg_wait<0>();
      fence_regs(ac4);
      if (rank) {
#pragma unroll
        for (int e = 0; e < 20; e++) sn[e] = pack_bf16(ac4[2 * e], ac4[2 * e + 1]);
#pragma unroll
        for (int e = 0; e < 40; e++) kp[e] = ac4[40 + e];
      } else {
#pragma unroll
        for (int e = 0; e < 20; e++) sn[e] = pack_bf16(ac4[40 + 2 * e], ac4[41 + 2 * e]);
#pragma unroll
        for (int e = 0; e < 40; e++) kp[e] = ac4[e];
      }
      send(3);
      TSTAMP(13);
      {
        mbar_wait(bars + 8 * B_XR, 1);
        const float w0 = 1.f - st_g[0], w1s = 1.f - st_g[1];
        const uint32_t xa = sb + OFF_OUT + rloc * 160 + t * 4;
#pragma unroll
        for (int g = 0; g < 10; g++) {
          const uint32_t x0 = lds32(xa + g * 16), x1 = lds32(xa + 1280 + g * 16);
          kp[4 * g] = fmaf(w0, bf_lo(x0), kp[4 * g]); kp[4 * g + 1] = fmaf(w0, bf_hi(x0), kp[4 * g + 1]);
          kp[4 * g + 2] = fmaf(w1s, bf_lo(x1), kp[4 * g + 2]); kp[4 * g + 3] = fmaf(w1s, bf_hi(x1), kp[4 * g + 3]);
        }
      }
      partial(1, pb4);
#pragma unroll
      for (int q = 0; q < 5; q++)
        pa4[q] = make_uint4(add_bf2(pa4[q].x, pb4[q].x), add_bf2(pa4[q].y, pb4[q].y), add_bf2(pa4[q].z, pb4[q].z), add_bf2(pa4[q].w, pb4[q].w));
#pragma unroll
      for (int q = 0; q < 5; q++) add8(q, pa4[q]);
      partial(2, pb4);
      mbar_wait(bars + 8 * (B_DSR + 6 + wg), 0);
      TSTAMP(14);
#pragma unroll
      for (int q = 0; q < 5; q++) {
        const uint4 c = pb4[q], d = lds128(sb + OFF_DS + 20480 + tid * 16 + q * 4096);
        add8(q, make_uint4(add_bf2(c.x, d.x), add_bf2(c.y, d.y), add_bf2(c.z, d.z), add_bf2(c.w, d.w)));
      }
      __syncwarp();
      uint32_t ov[2][10];
#pragma unroll
      for (int g = 0; g < 10; g++) { ov[0][g] = pack_bf16(kp[4 * g], kp[4 * g + 1]); ov[1][g] = pack_bf16(kp[4 * g + 2], kp[4 * g + 3]); }
      stage_tile(sb + OFF_OUT, ov);
      __syncwarp();
      __nv_bfloat16* dst = out + (size_t)(128 * i + 16 * warp) * D_ + 80 * j;
#pragma unroll
      for (int q = 0; q < 5; q++) {
        const int id = q * 32 + lane, r = id / 10;
        *reinterpret_cast<uint4*>(dst + r * (D_ - 80) + id * 8) = lds128(sb + OFF_OUT + warp * 2560 + id * 16);
      }
    }
    TSTAMP(15);
    if (tid == 0) asm volatile("red.relaxed.gpu.global.add.u32 [%0], 1;" ::"l"(g_flags + FL_DONE * 32) : "memory");
  }
}

namespace {
typedef CUresult (*EncodeFn)(CUtensorMap*, CUtensorMapDataType, cuuint32_t, void*, const cuuint64_t*, const cuuint64_t*,
                             const cuuint32_t*, const cuuint32_t*, CUtensorMapInterleave, CUtensorMapSwizzle,
                             CUtensorMapL2promotion, CUtensorMapFloatOOBfill);

void encode(EncodeFn fn, CUtensorMap* m, const void* ptr, int rank, const cuuint64_t* dims, const cuuint64_t* strides,
            const cuuint32_t* box, CUtensorMapSwizzle swz) {
  cuuint32_t es[5] = {1, 1, 1, 1, 1};
  fn(m, CU_TENSOR_MAP_DATA_TYPE_BFLOAT16, rank, const_cast<void*>(ptr), dims, strides, box, es, CU_TENSOR_MAP_INTERLEAVE_NONE,
     swz, CU_TENSOR_MAP_L2_PROMOTION_L2_128B, CU_TENSOR_MAP_FLOAT_OOB_FILL_NONE);
}
}

extern "C" void kernel_launch(void* const* d_in, const int* in_sizes, int n_in, void* d_out, int out_size) {
  (void)in_sizes; (void)n_in; (void)out_size;
  const __nv_bfloat16* x = (const __nv_bfloat16*)d_in[0];
  const __nv_bfloat16* wqkv = (const __nv_bfloat16*)d_in[1];
  const __nv_bfloat16* wphi = (const __nv_bfloat16*)d_in[2];
  const __nv_bfloat16* wo = (const __nv_bfloat16*)d_in[3];
  const __nv_bfloat16* w1 = (const __nv_bfloat16*)d_in[5];
  const __nv_bfloat16* w2 = (const __nv_bfloat16*)d_in[6];
  const __nv_bfloat16* w3 = (const __nv_bfloat16*)d_in[7];
  const __nv_bfloat16* w4 = (const __nv_bfloat16*)d_in[8];
  const __nv_bfloat16* gate_w = (const __nv_bfloat16*)d_in[9];

  static EncodeFn enc = nullptr;
  static void *pHs = nullptr, *pX1 = nullptr;
  if (!enc) {
    cudaDriverEntryPointQueryResult qr;
    cudaGetDriverEntryPoint("cuTensorMapEncodeTiled", (void**)&enc, cudaEnableDefault, &qr);
    cudaGetSymbolAddress(&pHs, g_Hs);
    cudaGetSymbolAddress(&pX1, g_X1);
    cudaFuncSetAttribute(fused_kernel, cudaFuncAttributeMaxDynamicSharedMemorySize, SMEM_BYTES);
  }
  Maps m;
  {
    cuuint64_t dims[2] = {D_, S_}, str[1] = {D_ * 2};
    cuuint32_t box[2] = {64, 128}, boxh[2] = {64, 64};
    encode(enc, &m.x, x, 2, dims, str, boxh, CU_TENSOR_MAP_SWIZZLE_128B);
    encode(enc, &m.hs, (const char*)pHs + 2 * D_ * 2, 2, dims, str, box, CU_TENSOR_MAP_SWIZZLE_128B);
    encode(enc, &m.x1, pX1, 2, dims, str, boxh, CU_TENSOR_MAP_SWIZZLE_128B);
    cuuint32_t boxr[2] = {80, 16}, boxs[2] = {80, 128};
    cuuint64_t dimsp[2] = {D_, S_ + 4};
    encode(enc, &m.st_h, pHs, 2, dimsp, str, boxs, CU_TENSOR_MAP_SWIZZLE_NONE);
    encode(enc, &m.st_x1, pX1, 2, dims, str, boxs, CU_TENSOR_MAP_SWIZZLE_NONE);
    encode(enc, &m.xr, x, 2, dims, str, boxr, CU_TENSOR_MAP_SWIZZLE_NONE);
  }
  {
    cuuint64_t dims[3] = {80, D_, 8}, str[2] = {D_ * 2, 160};
    cuuint32_t boxm[3] = {64, 64, 1}, boxr[3] = {16, 64, 1};
    encode(enc, &m.w1m, w1, 3, dims, str, boxm, CU_TENSOR_MAP_SWIZZLE_128B);
    encode(enc, &m.w1r, w1, 3, dims, str, boxr, CU_TENSOR_MAP_SWIZZLE_32B);
  }
  {
    cuuint64_t dims[4] = {80, D_, 3, 8}, str[3] = {3 * D_ * 2, D_ * 2, 160};
    cuuint32_t boxm[4] = {64, 64, 3, 1}, boxr[4] = {16, 64, 3, 1};
    encode(enc, &m.qm, wqkv, 4, dims, str, boxm, CU_TENSOR_MAP_SWIZZLE_128B);
    encode(enc, &m.qr, wqkv, 4, dims, str, boxr, CU_TENSOR_MAP_SWIZZLE_32B);
  }
  {
    cuuint64_t dims[3] = {32, D_, 20}, dims4[3] = {32, F_, 20}, str[2] = {D_ * 2, 64};
    cuuint32_t box4[3] = {32, 64, 5}, boxo[3] = {32, 80, 5};
    encode(enc, &m.w4, w4, 3, dims4, str, box4, CU_TENSOR_MAP_SWIZZLE_64B);
    encode(enc, &m.wo, wo, 3, dims, str, boxo, CU_TENSOR_MAP_SWIZZLE_64B);
    encode(enc, &m.w2, w2, 3, dims, str, box4, CU_TENSOR_MAP_SWIZZLE_64B);
  }
  {
    cuuint64_t dims[3] = {64, D_, 24}, str[2] = {F_ * 2, 128};
    cuuint32_t box[3] = {64, 64, 3};
    encode(enc, &m.w3, w3, 3, dims, str, box, CU_TENSOR_MAP_SWIZZLE_128B);
  }
  fused_kernel<<<NCTA + NSVC, 384, SMEM_BYTES, cudaStreamPerThread>>>(m, x, wqkv, wphi, w1, w2, w3, w4, wo, gate_w, (__nv_bfloat16*)d_out);
}
```

```cpp
#include <cuda_runtime.h>
#include <cuda_bf16.h>
#include <cuda.h>
#include <stdint.h>

namespace {

constexpr int S_ = 2048, D_ = 640, F_ = 1536;
constexpr int NCTA = 128, NSVC = 4;
constexpr int KV_PAIR = 40 * 48 + 96;
constexpr int KV_J = 2 * KV_PAIR;

constexpr int SLOT_B = 49152, NB = 3;
constexpr int SLOT_A = 16384, NA = 4;
constexpr int OFF_B = 0;
constexpr int OFF_A = OFF_B + NB * SLOT_B;
constexpr int OFF_STG = OFF_A + 2 * SLOT_A;
constexpr int OFF_MISC = OFF_A + NA * SLOT_A;
constexpr int OFF_XST = OFF_MISC + 13312;
constexpr int OFF_CS = OFF_MISC + 16384;
constexpr int OFF_BAR = OFF_CS + 1088;
constexpr int SMEM_BYTES = OFF_BAR + 512 + 512 + 128;
constexpr int B_FULLA = 0, B_FULLB = 4, B_CS = 7, B_XR = 8, B_KV = 9, B_ST1 = 10, B_HST = 11, B_FULL4 = 12  , B_RDY = 20  , B_T4 = 23,
              B_DSR = 24  , B_EMPTYB = 34  , B_SIGP = 37, B_SIGH = 38, B_SIGKV = 39, B_SIGX1 = 40, B_MFREE = 41,
              B_WDEAD = 42, B_EMPTY4 = 43  , B_EMPTYA = 51  , B_PEER = 55, B_PEER2 = 56, B_X1P = 57  , NBAR = 58;
constexpr int SPARE = 40960;
constexpr int SET4 = 87040, OFF_DS = 2 * SET4, OFF_OUT = 20480;

constexpr int FL_DONE = 0, FL_H = 1  , FL_X1 = FL_H + 32, FL_KV = FL_X1 + 16, FL_CS = FL_KV + 8, FL_CS3 = FL_CS + 1, FL_ST = FL_CS3 + 1;
constexpr int FL_S1 = FL_ST + 16, FL_COUNT = FL_S1 + 16;

struct Maps {
  CUtensorMap x, w1m, w1r, qm, qr, hs, w2, x1, w3, w4, wo, xr, st_h, st_x1;
};

}

__device__ __align__(1024) __nv_bfloat16 g_Hs[(S_ + 4) * D_];
__device__ __align__(1024) __nv_bfloat16 g_X1[S_ * D_];
__device__ __align__(128) float g_acc[2][8 * KV_J];
__device__ __align__(128) float g_cs[2][D_ + F_];
__device__ __align__(128) uint4 g_wphi[8 * 800];
__device__ __align__(128) float4 g_xstat[S_];
__device__ __align__(128) float2 g_st1[S_ * 8];
__device__ __align__(128) uint4 g_part[16 * 8 * 3 * 1280];
__device__ __align__(128) unsigned g_flags[FL_COUNT * 32];
#define TSTAMP(n) do {} while (0)
#define TSTAMPX(n) do {} while (0)
#define TRACE(n) do {} while (0)
#define TRS(n) do {} while (0)

namespace {

__device__ __forceinline__ long long gtime() { long long t; asm volatile("mov.u64 %0, %%globaltimer;" : "=l"(t)); return t; }
__device__ __forceinline__ uint32_t smem_u32(const void* p) { return (uint32_t)__cvta_generic_to_shared(p); }
__device__ __forceinline__ void mbar_init(uint32_t bar, int cnt) {
  asm volatile("mbarrier.init.shared::cta.b64 [%0], %1;" ::"r"(bar), "r"(cnt) : "memory");
}
__device__ __forceinline__ void mbar_expect_tx(uint32_t bar, int bytes) {
  asm volatile("mbarrier.arrive.expect_tx.shared::cta.b64 _, [%0], %1;" ::"r"(bar), "r"(bytes) : "memory");
}
__device__ __forceinline__ void mbar_arrive_cta(uint32_t bar, uint32_t cta) {
  asm volatile("{\n.reg .b32 ra;\nmapa.shared::cluster.u32 ra, %0, %1;\nmbarrier.arrive.shared::cluster.b64 _, [ra];\n}"
               ::"r"(bar), "r"(cta) : "memory");
}
__device__ __forceinline__ uint32_t mbar_try(uint32_t bar, uint32_t parity) {
  uint32_t ok;
  asm volatile("{\n.reg .pred p;\nmbarrier.try_wait.parity.shared::cta.b64 p, [%1], %2;\nselp.u32 %0, 1, 0, p;\n}"
               : "=r"(ok) : "r"(bar), "r"(parity) : "memory");
  return ok;
}
constexpr uint32_t WAIT_LIMIT = 1u << 18;
__device__ __forceinline__ void mbar_wait(uint32_t bar, uint32_t parity) {
  uint32_t n = 0;
  while (!mbar_try(bar, parity) && ++n < WAIT_LIMIT) {}
}
__device__ __forceinline__ unsigned ld_acquire(const unsigned* p) {
  unsigned v;
  asm volatile("ld.acquire.gpu.global.u32 %0, [%1];" : "=r"(v) : "l"(p) : "memory");
  return v;
}
__device__ __forceinline__ void flag_wait(int idx, unsigned target) {
  const unsigned* p = g_flags + idx * 32;
  uint32_t n = 0;
  while ((int)(ld_acquire(p) - target) < 0 && ++n < (WAIT_LIMIT >> 2)) {}
}
__device__ __forceinline__ void flag_add(int idx) {
  asm volatile("red.release.gpu.global.add.u32 [%0], 1;" ::"l"(g_flags + idx * 32) : "memory");
}
__device__ __forceinline__ void flag_add_relaxed(int idx) {
  asm volatile("red.relaxed.gpu.global.add.u32 [%0], 1;" ::"l"(g_flags + idx * 32) : "memory");
}
__device__ __forceinline__ uint32_t mbar_test(uint32_t bar, uint32_t parity) {
  uint32_t ok;
  asm volatile("{\n.reg .pred p;\nmbarrier.test_wait.parity.shared::cta.b64 p, [%1], %2;\nselp.u32 %0, 1, 0, p;\n}"
               : "=r"(ok) : "r"(bar), "r"(parity) : "memory");
  return ok;
}
__device__ __forceinline__ uint32_t lds32(uint32_t a) {
  uint32_t v;
  asm volatile("ld.shared.u32 %0, [%1];" : "=r"(v) : "r"(a) : "memory");
  return v;
}
__device__ __forceinline__ void mbar_arrive(uint32_t bar) {
  asm volatile("mbarrier.arrive.shared::cta.b64 _, [%0];" ::"r"(bar) : "memory");
}
__device__ __forceinline__ void fence_async_glb() { asm volatile("fence.proxy.async.global;" ::: "memory"); }
__device__ __forceinline__ void fence_async_smem() { asm volatile("fence.proxy.async.shared::cta;" ::: "memory"); }
__device__ __forceinline__ void bar_sync(int id, int n) { asm volatile("bar.sync %0, %1;" ::"r"(id), "r"(n) : "memory"); }

__device__ __forceinline__ void tma2d(uint32_t dst, const CUtensorMap* m, uint32_t bar, int c0, int c1) {
  asm volatile("cp.async.bulk.tensor.2d.shared::cluster.global.mbarrier::complete_tx::bytes [%0], [%1, {%3, %4}], [%2];"
               ::"r"(dst), "l"(m), "r"(bar), "r"(c0), "r"(c1) : "memory");
}
__device__ __forceinline__ void tma2d_mc(uint32_t dst, const CUtensorMap* m, uint32_t bar, int c0, int c1) {
  asm volatile("cp.async.bulk.tensor.2d.shared::cluster.global.mbarrier::complete_tx::bytes.multicast::cluster"
               " [%0], [%1, {%3, %4}], [%2], %5;"
               ::"r"(dst), "l"(m), "r"(bar), "r"(c0), "r"(c1), "h"((uint16_t)3) : "memory");
}
__device__ __forceinline__ void tma3d(uint32_t dst, const CUtensorMap* m, uint32_t bar, int c0, int c1, int c2) {
  asm volatile("cp.async.bulk.tensor.3d.shared::cluster.global.mbarrier::complete_tx::bytes [%0], [%1, {%3, %4, %5}], [%2];"
               ::"r"(dst), "l"(m), "r"(bar), "r"(c0), "r"(c1), "r"(c2) : "memory");
}
__device__ __forceinline__ void tma4d(uint32_t dst, const CUtensorMap* m, uint32_t bar, int c0, int c1, int c2, int c3) {
  asm volatile("cp.async.bulk.tensor.4d.shared::cluster.global.mbarrier::complete_tx::bytes [%0], [%1, {%3, %4, %5, %6}], [%2];"
               ::"r"(dst), "l"(m), "r"(bar), "r"(c0), "r"(c1), "r"(c2), "r"(c3) : "memory");
}
__device__ __forceinline__ void tma2d_store(const CUtensorMap* m, uint32_t src, int c0, int c1) {
  asm volatile("cp.async.bulk.tensor.2d.global.shared::cta.bulk_group [%0, {%2, %3}], [%1];"
               ::"l"(m), "r"(src), "r"(c0), "r"(c1) : "memory");
}
__device__ __forceinline__ void bulk_store(void* dst, uint32_t src, uint32_t bytes) {
  asm volatile("cp.async.bulk.global.shared::cta.bulk_group [%0], [%1], %2;" ::"l"(dst), "r"(src), "r"(bytes) : "memory");
}
__device__ __forceinline__ void bulk_load(uint32_t dst, const void* src, uint32_t bytes, uint32_t bar) {
  asm volatile("cp.async.bulk.shared::cluster.global.mbarrier::complete_tx::bytes [%0], [%1], %2, [%3];"
               ::"r"(dst), "l"(src), "r"(bytes), "r"(bar) : "memory");
}
__device__ __forceinline__ void bulk_commit() { asm volatile("cp.async.bulk.commit_group;" ::: "memory"); }
template <int N> __device__ __forceinline__ void bulk_wait() { asm volatile("cp.async.bulk.wait_group %0;" ::"n"(N) : "memory"); }
__device__ __forceinline__ void bulk_wait_read() { asm volatile("cp.async.bulk.wait_group.read 0;" ::: "memory"); }
__device__ __forceinline__ void bar_arrive(int id, int n) { asm volatile("bar.arrive %0, %1;" ::"r"(id), "r"(n) : "memory"); }
__device__ __forceinline__ uint4 lds128(uint32_t a) {
  uint4 v;
  asm volatile("ld.shared.v4.u32 {%0, %1, %2, %3}, [%4];" : "=r"(v.x), "=r"(v.y), "=r"(v.z), "=r"(v.w) : "r"(a) : "memory");
  return v;
}
__device__ __forceinline__ void sts128(uint32_t a, uint4 v) {
  asm volatile("st.shared.v4.u32 [%0], {%1, %2, %3, %4};" ::"r"(a), "r"(v.x), "r"(v.y), "r"(v.z), "r"(v.w) : "memory");
}
__device__ __forceinline__ uint4 ld_relaxed16(const uint4* p) {
  uint4 v;
  asm volatile("ld.relaxed.gpu.global.v4.u32 {%0, %1, %2, %3}, [%4];" : "=r"(v.x), "=r"(v.y), "=r"(v.z), "=r"(v.w) : "l"(p) : "memory");
  return v;
}
__device__ __forceinline__ void st_relaxed16(uint4* p, uint32_t a, uint32_t b, uint32_t c, uint32_t d) {
  asm volatile("st.relaxed.gpu.global.v4.u32 [%0], {%1, %2, %3, %4};" ::"l"(p), "r"(a), "r"(b), "r"(c), "r"(d) : "memory");
}
__device__ __forceinline__ uint32_t map_peer(uint32_t addr, uint32_t cta) {
  uint32_t r;
  asm("mapa.shared::cluster.u32 %0, %1, %2;" : "=r"(r) : "r"(addr), "r"(cta));
  return r;
}
__device__ __forceinline__ void st_async16(uint32_t addr, uint32_t a, uint32_t b, uint32_t c, uint32_t d, uint32_t bar) {
  asm volatile("st.async.weak.shared::cluster.mbarrier::complete_tx::bytes.v4.b32 [%0], {%1, %2, %3, %4}, [%5];"
               ::"r"(addr), "r"(a), "r"(b), "r"(c), "r"(d), "r"(bar) : "memory");
}
__device__ __forceinline__ void l2_prefetch(const void* p, uint32_t bytes) {
  asm volatile("cp.async.bulk.prefetch.L2.global [%0], %1;" ::"l"(p), "r"(bytes) : "memory");
}
__device__ __forceinline__ void prefetch_tmap(const CUtensorMap* m) {
  asm volatile("prefetch.tensormap [%0];" ::"l"(m) : "memory");
}
__device__ __forceinline__ uint64_t make_desc(uint32_t a16, uint32_t off, uint32_t lbo, uint32_t sbo, uint32_t swz) {
  const uint32_t lo = a16 + ((off >> 4) + ((lbo >> 4) << 16)), hi = (sbo >> 4) | (swz << 30);
  uint64_t d;
  asm("mov.b64 %0, {%1, %2};" : "=l"(d) : "r"(lo), "r"(hi));
  return d;
}
__device__ __forceinline__ void wg_fence() { asm volatile("wgmma.fence.sync.aligned;" ::: "memory"); }
__device__ __forceinline__ void wg_commit() { asm volatile("wgmma.commit_group.sync.aligned;" ::: "memory"); }
template <int N> __device__ __forceinline__ void wg_wait() { asm volatile("wgmma.wait_group.sync.aligned %0;" ::"n"(N) : "memory"); }
template <int N> __device__ __forceinline__ void fence_regs(float (&d)[N]) {
#pragma unroll
  for (int i = 0; i < N; i++) asm volatile("" : "+f"(d[i])::"memory");
}
template <int N> __device__ __forceinline__ void zero_regs(float (&d)[N]) {
#pragma unroll
  for (int i = 0; i < N; i++) d[i] = 0.f;
}
__device__ __forceinline__ uint32_t pack_bf16(float lo, float hi) {
  uint32_t r;
  asm("cvt.rn.bf16x2.f32 %0, %1, %2;" : "=r"(r) : "f"(hi), "f"(lo));
  return r;
}
__device__ __forceinline__ float bf_lo(uint32_t v) { return __uint_as_float(v << 16); }
__device__ __forceinline__ float bf_hi(uint32_t v) { return __uint_as_float(v & 0xffff0000u); }
__device__ __forceinline__ uint32_t max_bf2(uint32_t a, uint32_t b) {
  uint32_t r; asm("max.bf16x2 %0, %1, %2;" : "=r"(r) : "r"(a), "r"(b)); return r;
}
__device__ __forceinline__ uint32_t min_bf2(uint32_t a, uint32_t b) {
  uint32_t r; asm("min.bf16x2 %0, %1, %2;" : "=r"(r) : "r"(a), "r"(b)); return r;
}
__device__ __forceinline__ uint32_t add_bf2(uint32_t a, uint32_t b) {
  uint32_t r; asm("add.rn.bf16x2 %0, %1, %2;" : "=r"(r) : "r"(a), "r"(b)); return r;
}
__device__ __forceinline__ float ex2(float x) { float r; asm("ex2.approx.ftz.f32 %0, %1;" : "=f"(r) : "f"(x)); return r; }
__device__ __forceinline__ float rcp(float x) { float r; asm("rcp.approx.ftz.f32 %0, %1;" : "=f"(r) : "f"(x)); return r; }
__device__ __forceinline__ float tanh_ap(float x) { float r; asm("tanh.approx.f32 %0, %1;" : "=f"(r) : "f"(x)); return r; }
struct GeluC { float c0, c1, ch; };
__device__ __forceinline__ GeluC gelu_consts(float rstd, float scale) {
  return GeluC{0.7978845608f * rstd, 0.0356774081f * rstd * rstd * rstd, 0.5f * scale * rstd};
}
__device__ __forceinline__ float gelu_s(float y, const GeluC& c) {
  const float u = y * fmaf(y * y, c.c1, c.c0);
  const float hx = y * c.ch;
  return fmaf(hx, tanh_ap(u), hx);
}
__device__ __forceinline__ void stsm4(uint32_t addr, uint32_t r0, uint32_t r1, uint32_t r2, uint32_t r3) {
  asm volatile("stmatrix.sync.aligned.m8n8.x4.shared.b16 [%0], {%1, %2, %3, %4};"
               ::"r"(addr), "r"(r0), "r"(r1), "r"(r2), "r"(r3) : "memory");
}

__device__ __forceinline__ void red_add4(float* p, float a, float b, float c, float d) {
  asm volatile("red.global.add.v4.f32 [%0], {%1, %2, %3, %4};" ::"l"(p), "f"(a), "f"(b), "f"(c), "f"(d) : "memory");
}

__device__ __forceinline__ void mma_ss256(float (&d)[128], uint64_t descA, uint64_t descB) {
  asm volatile("wgmma.mma_async.sync.aligned.m64n256k16.f32.bf16.bf16 {"
      "%0, %1, %2, %3, %4, %5, %6, %7, %8, %9, %10, %11, %12, %13, %14, %15, "
      "%16, %17, %18, %19, %20, %21, %22, %23, %24, %25, %26, %27, %28, %29, %30, %31, "
      "%32, %33, %34, %35, %36, %37, %38, %39, %40, %41, %42, %43, %44, %45, %46, %47, "
      "%48, %49, %50, %51, %52, %53, %54, %55, %56, %57, %58, %59, %60, %61, %62, %63, "
      "%64, %65, %66, %67, %68, %69, %70, %71, %72, %73, %74, %75, %76, %77, %78, %79, "
      "%80, %81, %82, %83, %84, %85, %86, %87, %88, %89, %90, %91, %92, %93, %94, %95, "
      "%96, %97, %98, %99, %100, %101, %102, %103, %104, %105, %106, %107, %108, %109, %110, %111, "
      "%112, %113, %114, %115, %116, %117, %118, %119, %120, %121, %122, %123, %124, %125, %126, %127"
      "}, %128, %129, 1, 1, 1, 0, 1;\n"
      : "+f"(d[0]), "+f"(d[1]), "+f"(d[2]), "+f"(d[3]), "+f"(d[4]), "+f"(d[5]), "+f"(d[6]), "+f"(d[7]),
        "+f"(d[8]), "+f"(d[9]), "+f"(d[10]), "+f"(d[11]), "+f"(d[12]), "+f"(d[13]), "+f"(d[14]), "+f"(d[15]),
        "+f"(d[16]), "+f"(d[17]), "+f"(d[18]), "+f"(d[19]), "+f"(d[20]), "+f"(d[21]), "+f"(d[22]), "+f"(d[23]),
        "+f"(d[24]), "+f"(d[25]), "+f"(d[26]), "+f"(d[27]), "+f"(d[28]), "+f"(d[29]), "+f"(d[30]), "+f"(d[31]),
        "+f"(d[32]), "+f"(d[33]), "+f"(d[34]), "+f"(d[35]), "+f"(d[36]), "+f"(d[37]), "+f"(d[38]), "+f"(d[39]),
        "+f"(d[40]), "+f"(d[41]), "+f"(d[42]), "+f"(d[43]), "+f"(d[44]), "+f"(d[45]), "+f"(d[46]), "+f"(d[47]),
        "+f"(d[48]), "+f"(d[49]), "+f"(d[50]), "+f"(d[51]), "+f"(d[52]), "+f"(d[53]), "+f"(d[54]), "+f"(d[55]),
        "+f"(d[56]), "+f"(d[57]), "+f"(d[58]), "+f"(d[59]), "+f"(d[60]), "+f"(d[61]), "+f"(d[62]), "+f"(d[63]),
        "+f"(d[64]), "+f"(d[65]), "+f"(d[66]), "+f"(d[67]), "+f"(d[68]), "+f"(d[69]), "+f"(d[70]), "+f"(d[71]),
        "+f"(d[72]), "+f"(d[73]), "+f"(d[74]), "+f"(d[75]), "+f"(d[76]), "+f"(d[77]), "+f"(d[78]), "+f"(d[79]),
        "+f"(d[80]), "+f"(d[81]), "+f"(d[82]), "+f"(d[83]), "+f"(d[84]), "+f"(d[85]), "+f"(d[86]), "+f"(d[87]),
        "+f"(d[88]), "+f"(d[89]), "+f"(d[90]), "+f"(d[91]), "+f"(d[92]), "+f"(d[93]), "+f"(d[94]), "+f"(d[95]),
        "+f"(d[96]), "+f"(d[97]), "+f"(d[98]), "+f"(d[99]), "+f"(d[100]), "+f"(d[101]), "+f"(d[102]), "+f"(d[103]),
        "+f"(d[104]), "+f"(d[105]), "+f"(d[106]), "+f"(d[107]), "+f"(d[108]), "+f"(d[109]), "+f"(d[110]), "+f"(d[111]),
        "+f"(d[112]), "+f"(d[113]), "+f"(d[114]), "+f"(d[115]), "+f"(d[116]), "+f"(d[117]), "+f"(d[118]), "+f"(d[119]),
        "+f"(d[120]), "+f"(d[121]), "+f"(d[122]), "+f"(d[123]), "+f"(d[124]), "+f"(d[125]), "+f"(d[126]), "+f"(d[127])
      : "l"(descA), "l"(descB));
}
__device__ __forceinline__ void mma_ss256_p(float (&d)[128], uint64_t descA, uint64_t descB, int acc) {
  asm volatile("{\n.reg .pred p;\nsetp.ne.b32 p, %130, 0;\n"
      "wgmma.mma_async.sync.aligned.m64n256k16.f32.bf16.bf16 {"
      "%0, %1, %2, %3, %4, %5, %6, %7, %8, %9, %10, %11, %12, %13, %14, %15, "
      "%16, %17, %18, %19, %20, %21, %22, %23, %24, %25, %26, %27, %28, %29, %30, %31, "
      "%32, %33, %34, %35, %36, %37, %38, %39, %40, %41, %42, %43, %44, %45, %46, %47, "
      "%48, %49, %50, %51, %52, %53, %54, %55, %56, %57, %58, %59, %60, %61, %62, %63, "
      "%64, %65, %66, %67, %68, %69, %70, %71, %72, %73, %74, %75, %76, %77, %78, %79, "
      "%80, %81, %82, %83, %84, %85, %86, %87, %88, %89, %90, %91, %92, %93, %94, %95, "
      "%96, %97, %98, %99, %100, %101, %102, %103, %104, %105, %106, %107, %108, %109, %110, %111, "
      "%112, %113, %114, %115, %116, %117, %118, %119, %120, %121, %122, %123, %124, %125, %126, %127"
      "}, %128, %129, p, 1, 1, 0, 1;\n}\n"
      : "+f"(d[0]), "+f"(d[1]), "+f"(d[2]), "+f"(d[3]), "+f"(d[4]), "+f"(d[5]), "+f"(d[6]), "+f"(d[7]),
        "+f"(d[8]), "+f"(d[9]), "+f"(d[10]), "+f"(d[11]), "+f"(d[12]), "+f"(d[13]), "+f"(d[14]), "+f"(d[15]),
        "+f"(d[16]), "+f"(d[17]), "+f"(d[18]), "+f"(d[19]), "+f"(d[20]), "+f"(d[21]), "+f"(d[22]), "+f"(d[23]),
        "+f"(d[24]), "+f"(d[25]), "+f"(d[26]), "+f"(d[27]), "+f"(d[28]), "+f"(d[29]), "+f"(d[30]), "+f"(d[31]),
        "+f"(d[32]), "+f"(d[33]), "+f"(d[34]), "+f"(d[35]), "+f"(d[36]), "+f"(d[37]), "+f"(d[38]), "+f"(d[39]),
        "+f"(d[40]), "+f"(d[41]), "+f"(d[42]), "+f"(d[43]), "+f"(d[44]), "+f"(d[45]), "+f"(d[46]), "+f"(d[47]),
        "+f"(d[48]), "+f"(d[49]), "+f"(d[50]), "+f"(d[51]), "+f"(d[52]), "+f"(d[53]), "+f"(d[54]), "+f"(d[55]),
        "+f"(d[56]), "+f"(d[57]), "+f"(d[58]), "+f"(d[59]), "+f"(d[60]), "+f"(d[61]), "+f"(d[62]), "+f"(d[63]),
        "+f"(d[64]), "+f"(d[65]), "+f"(d[66]), "+f"(d[67]), "+f"(d[68]), "+f"(d[69]), "+f"(d[70]), "+f"(d[71]),
        "+f"(d[72]), "+f"(d[73]), "+f"(d[74]), "+f"(d[75]), "+f"(d[76]), "+f"(d[77]), "+f"(d[78]), "+f"(d[79]),
        "+f"(d[80]), "+f"(d[81]), "+f"(d[82]), "+f"(d[83]), "+f"(d[84]), "+f"(d[85]), "+f"(d[86]), "+f"(d[87]),
        "+f"(d[88]), "+f"(d[89]), "+f"(d[90]), "+f"(d[91]), "+f"(d[92]), "+f"(d[93]), "+f"(d[94]), "+f"(d[95]),
        "+f"(d[96]), "+f"(d[97]), "+f"(d[98]), "+f"(d[99]), "+f"(d[100]), "+f"(d[101]), "+f"(d[102]), "+f"(d[103]),
        "+f"(d[104]), "+f"(d[105]), "+f"(d[106]), "+f"(d[107]), "+f"(d[108]), "+f"(d[109]), "+f"(d[110]), "+f"(d[111]),
        "+f"(d[112]), "+f"(d[113]), "+f"(d[114]), "+f"(d[115]), "+f"(d[116]), "+f"(d[117]), "+f"(d[118]), "+f"(d[119]),
        "+f"(d[120]), "+f"(d[121]), "+f"(d[122]), "+f"(d[123]), "+f"(d[124]), "+f"(d[125]), "+f"(d[126]), "+f"(d[127])
      : "l"(descA), "l"(descB), "r"(acc));
}

__device__ __forceinline__ void mma_ss64(float (&d)[32], uint64_t descA, uint64_t descB) {
  asm volatile("wgmma.mma_async.sync.aligned.m64n64k16.f32.bf16.bf16 {"
      "%0, %1, %2, %3, %4, %5, %6, %7, %8, %9, %10, %11, %12, %13, %14, %15, "
      "%16, %17, %18, %19, %20, %21, %22, %23, %24, %25, %26, %27, %28, %29, %30, %31"
      "}, %32, %33, 1, 1, 1, 0, 1;\n"
      : "+f"(d[0]), "+f"(d[1]), "+f"(d[2]), "+f"(d[3]), "+f"(d[4]), "+f"(d[5]), "+f"(d[6]), "+f"(d[7]),
        "+f"(d[8]), "+f"(d[9]), "+f"(d[10]), "+f"(d[11]), "+f"(d[12]), "+f"(d[13]), "+f"(d[14]), "+f"(d[15]),
        "+f"(d[16]), "+f"(d[17]), "+f"(d[18]), "+f"(d[19]), "+f"(d[20]), "+f"(d[21]), "+f"(d[22]), "+f"(d[23]),
        "+f"(d[24]), "+f"(d[25]), "+f"(d[26]), "+f"(d[27]), "+f"(d[28]), "+f"(d[29]), "+f"(d[30]), "+f"(d[31])
      : "l"(descA), "l"(descB));
}
__device__ __forceinline__ void mma_ss64_p(float (&d)[32], uint64_t descA, uint64_t descB, int acc) {
  asm volatile("{\n.reg .pred p;\nsetp.ne.b32 p, %34, 0;\n"
      "wgmma.mma_async.sync.aligned.m64n64k16.f32.bf16.bf16 {"
      "%0, %1, %2, %3, %4, %5, %6, %7, %8, %9, %10, %11, %12, %13, %14, %15, "
      "%16, %17, %18, %19, %20, %21, %22, %23, %24, %25, %26, %27, %28, %29, %30, %31"
      "}, %32, %33, p, 1, 1, 0, 1;\n}\n"
      : "+f"(d[0]), "+f"(d[1]), "+f"(d[2]), "+f"(d[3]), "+f"(d[4]), "+f"(d[5]), "+f"(d[6]), "+f"(d[7]),
        "+f"(d[8]), "+f"(d[9]), "+f"(d[10]), "+f"(d[11]), "+f"(d[12]), "+f"(d[13]), "+f"(d[14]), "+f"(d[15]),
        "+f"(d[16]), "+f"(d[17]), "+f"(d[18]), "+f"(d[19]), "+f"(d[20]), "+f"(d[21]), "+f"(d[22]), "+f"(d[23]),
        "+f"(d[24]), "+f"(d[25]), "+f"(d[26]), "+f"(d[27]), "+f"(d[28]), "+f"(d[29]), "+f"(d[30]), "+f"(d[31])
      : "l"(descA), "l"(descB), "r"(acc));
}

__device__ __forceinline__ void mma_ss160(float (&d)[80], uint64_t descA, uint64_t descB) {
  asm volatile("wgmma.mma_async.sync.aligned.m64n160k16.f32.bf16.bf16 {"
      "%0, %1, %2, %3, %4, %5, %6, %7, %8, %9, %10, %11, %12, %13, %14, %15, "
      "%16, %17, %18, %19, %20, %21, %22, %23, %24, %25, %26, %27, %28, %29, %30, %31, "
      "%32, %33, %34, %35, %36, %37, %38, %39, %40, %41, %42, %43, %44, %45, %46, %47, "
      "%48, %49, %50, %51, %52, %53, %54, %55, %56, %57, %58, %59, %60, %61, %62, %63, "
      "%64, %65, %66, %67, %68, %69, %70, %71, %72, %73, %74, %75, %76, %77, %78, %79"
      "}, %80, %81, 1, 1, 1, 0, 1;\n"
      : "+f"(d[0]), "+f"(d[1]), "+f"(d[2]), "+f"(d[3]), "+f"(d[4]), "+f"(d[5]), "+f"(d[6]), "+f"(d[7]),
        "+f"(d[8]), "+f"(d[9]), "+f"(d[10]), "+f"(d[11]), "+f"(d[12]), "+f"(d[13]), "+f"(d[14]), "+f"(d[15]),
        "+f"(d[16]), "+f"(d[17]), "+f"(d[18]), "+f"(d[19]), "+f"(d[20]), "+f"(d[21]), "+f"(d[22]), "+f"(d[23]),
        "+f"(d[24]), "+f"(d[25]), "+f"(d[26]), "+f"(d[27]), "+f"(d[28]), "+f"(d[29]), "+f"(d[30]), "+f"(d[31]),
        "+f"(d[32]), "+f"(d[33]), "+f"(d[34]), "+f"(d[35]), "+f"(d[36]), "+f"(d[37]), "+f"(d[38]), "+f"(d[39]),
        "+f"(d[40]), "+f"(d[41]), "+f"(d[42]), "+f"(d[43]), "+f"(d[44]), "+f"(d[45]), "+f"(d[46]), "+f"(d[47]),
        "+f"(d[48]), "+f"(d[49]), "+f"(d[50]), "+f"(d[51]), "+f"(d[52]), "+f"(d[53]), "+f"(d[54]), "+f"(d[55]),
        "+f"(d[56]), "+f"(d[57]), "+f"(d[58]), "+f"(d[59]), "+f"(d[60]), "+f"(d[61]), "+f"(d[62]), "+f"(d[63]),
        "+f"(d[64]), "+f"(d[65]), "+f"(d[66]), "+f"(d[67]), "+f"(d[68]), "+f"(d[69]), "+f"(d[70]), "+f"(d[71]),
        "+f"(d[72]), "+f"(d[73]), "+f"(d[74]), "+f"(d[75]), "+f"(d[76]), "+f"(d[77]), "+f"(d[78]), "+f"(d[79])
      : "l"(descA), "l"(descB));
}
__device__ __forceinline__ void mma_ss160_z(float (&d)[80], uint64_t descA, uint64_t descB) {
  asm volatile("wgmma.mma_async.sync.aligned.m64n160k16.f32.bf16.bf16 {"
      "%0, %1, %2, %3, %4, %5, %6, %7, %8, %9, %10, %11, %12, %13, %14, %15, "
      "%16, %17, %18, %19, %20, %21, %22, %23, %24, %25, %26, %27, %28, %29, %30, %31, "
      "%32, %33, %34, %35, %36, %37, %38, %39, %40, %41, %42, %43, %44, %45, %46, %47, "
      "%48, %49, %50, %51, %52, %53, %54, %55, %56, %57, %58, %59, %60, %61, %62, %63, "
      "%64, %65, %66, %67, %68, %69, %70, %71, %72, %73, %74, %75, %76, %77, %78, %79"
      "}, %80, %81, 0, 1, 1, 0, 1;\n"
      : "=f"(d[0]), "=f"(d[1]), "=f"(d[2]), "=f"(d[3]), "=f"(d[4]), "=f"(d[5]), "=f"(d[6]), "=f"(d[7]),
        "=f"(d[8]), "=f"(d[9]), "=f"(d[10]), "=f"(d[11]), "=f"(d[12]), "=f"(d[13]), "=f"(d[14]), "=f"(d[15]),
        "=f"(d[16]), "=f"(d[17]), "=f"(d[18]), "=f"(d[19]), "=f"(d[20]), "=f"(d[21]), "=f"(d[22]), "=f"(d[23]),
        "=f"(d[24]), "=f"(d[25]), "=f"(d[26]), "=f"(d[27]), "=f"(d[28]), "=f"(d[29]), "=f"(d[30]), "=f"(d[31]),
        "=f"(d[32]), "=f"(d[33]), "=f"(d[34]), "=f"(d[35]), "=f"(d[36]), "=f"(d[37]), "=f"(d[38]), "=f"(d[39]),
        "=f"(d[40]), "=f"(d[41]), "=f"(d[42]), "=f"(d[43]), "=f"(d[44]), "=f"(d[45]), "=f"(d[46]), "=f"(d[47]),
        "=f"(d[48]), "=f"(d[49]), "=f"(d[50]), "=f"(d[51]), "=f"(d[52]), "=f"(d[53]), "=f"(d[54]), "=f"(d[55]),
        "=f"(d[56]), "=f"(d[57]), "=f"(d[58]), "=f"(d[59]), "=f"(d[60]), "=f"(d[61]), "=f"(d[62]), "=f"(d[63]),
        "=f"(d[64]), "=f"(d[65]), "=f"(d[66]), "=f"(d[67]), "=f"(d[68]), "=f"(d[69]), "=f"(d[70]), "=f"(d[71]),
        "=f"(d[72]), "=f"(d[73]), "=f"(d[74]), "=f"(d[75]), "=f"(d[76]), "=f"(d[77]), "=f"(d[78]), "=f"(d[79])
      : "l"(descA), "l"(descB));
}

__device__ __forceinline__ void mma_ss192(float (&d)[96], uint64_t descA, uint64_t descB) {
  asm volatile("wgmma.mma_async.sync.aligned.m64n192k16.f32.bf16.bf16 {"
      "%0, %1, %2, %3, %4, %5, %6, %7, %8, %9, %10, %11, %12, %13, %14, %15, "
      "%16, %17, %18, %19, %20, %21, %22, %23, %24, %25, %26, %27, %28, %29, %30, %31, "
      "%32, %33, %34, %35, %36, %37, %38, %39, %40, %41, %42, %43, %44, %45, %46, %47, "
      "%48, %49, %50, %51, %52, %53, %54, %55, %56, %57, %58, %59, %60, %61, %62, %63, "
      "%64, %65, %66, %67, %68, %69, %70, %71, %72, %73, %74, %75, %76, %77, %78, %79, "
      "%80, %81, %82, %83, %84, %85, %86, %87, %88, %89, %90, %91, %92, %93, %94, %95"
      "}, %96, %97, 1, 1, 1, 0, 1;\n"
      : "+f"(d[0]), "+f"(d[1]), "+f"(d[2]), "+f"(d[3]), "+f"(d[4]), "+f"(d[5]), "+f"(d[6]), "+f"(d[7]),
        "+f"(d[8]), "+f"(d[9]), "+f"(d[10]), "+f"(d[11]), "+f"(d[12]), "+f"(d[13]), "+f"(d[14]), "+f"(d[15]),
        "+f"(d[16]), "+f"(d[17]), "+f"(d[18]), "+f"(d[19]), "+f"(d[20]), "+f"(d[21]), "+f"(d[22]), "+f"(d[23]),
        "+f"(d[24]), "+f"(d[25]), "+f"(d[26]), "+f"(d[27]), "+f"(d[28]), "+f"(d[29]), "+f"(d[30]), "+f"(d[31]),
        "+f"(d[32]), "+f"(d[33]), "+f"(d[34]), "+f"(d[35]), "+f"(d[36]), "+f"(d[37]), "+f"(d[38]), "+f"(d[39]),
        "+f"(d[40]), "+f"(d[41]), "+f"(d[42]), "+f"(d[43]), "+f"(d[44]), "+f"(d[45]), "+f"(d[46]), "+f"(d[47]),
        "+f"(d[48]), "+f"(d[49]), "+f"(d[50]), "+f"(d[51]), "+f"(d[52]), "+f"(d[53]), "+f"(d[54]), "+f"(d[55]),
        "+f"(d[56]), "+f"(d[57]), "+f"(d[58]), "+f"(d[59]), "+f"(d[60]), "+f"(d[61]), "+f"(d[62]), "+f"(d[63]),
        "+f"(d[64]), "+f"(d[65]), "+f"(d[66]), "+f"(d[67]), "+f"(d[68]), "+f"(d[69]), "+f"(d[70]), "+f"(d[71]),
        "+f"(d[72]), "+f"(d[73]), "+f"(d[74]), "+f"(d[75]), "+f"(d[76]), "+f"(d[77]), "+f"(d[78]), "+f"(d[79]),
        "+f"(d[80]), "+f"(d[81]), "+f"(d[82]), "+f"(d[83]), "+f"(d[84]), "+f"(d[85]), "+f"(d[86]), "+f"(d[87]),
        "+f"(d[88]), "+f"(d[89]), "+f"(d[90]), "+f"(d[91]), "+f"(d[92]), "+f"(d[93]), "+f"(d[94]), "+f"(d[95])
      : "l"(descA), "l"(descB));
}
__device__ __forceinline__ void mma_ss192_p(float (&d)[96], uint64_t descA, uint64_t descB, int acc) {
  asm volatile("{\n.reg .pred p;\nsetp.ne.b32 p, %98, 0;\n"
      "wgmma.mma_async.sync.aligned.m64n192k16.f32.bf16.bf16 {"
      "%0, %1, %2, %3, %4, %5, %6, %7, %8, %9, %10, %11, %12, %13, %14, %15, "
      "%16, %17, %18, %19, %20, %21, %22, %23, %24, %25, %26, %27, %28, %29, %30, %31, "
      "%32, %33, %34, %35, %36, %37, %38, %39, %40, %41, %42, %43, %44, %45, %46, %47, "
      "%48, %49, %50, %51, %52, %53, %54, %55, %56, %57, %58, %59, %60, %61, %62, %63, "
      "%64, %65, %66, %67, %68, %69, %70, %71, %72, %73, %74, %75, %76, %77, %78, %79, "
      "%80, %81, %82, %83, %84, %85, %86, %87, %88, %89, %90, %91, %92, %93, %94, %95"
      "}, %96, %97, p, 1, 1, 0, 1;\n}\n"
      : "+f"(d[0]), "+f"(d[1]), "+f"(d[2]), "+f"(d[3]), "+f"(d[4]), "+f"(d[5]), "+f"(d[6]), "+f"(d[7]),
        "+f"(d[8]), "+f"(d[9]), "+f"(d[10]), "+f"(d[11]), "+f"(d[12]), "+f"(d[13]), "+f"(d[14]), "+f"(d[15]),
        "+f"(d[16]), "+f"(d[17]), "+f"(d[18]), "+f"(d[19]), "+f"(d[20]), "+f"(d[21]), "+f"(d[22]), "+f"(d[23]),
        "+f"(d[24]), "+f"(d[25]), "+f"(d[26]), "+f"(d[27]), "+f"(d[28]), "+f"(d[29]), "+f"(d[30]), "+f"(d[31]),
        "+f"(d[32]), "+f"(d[33]), "+f"(d[34]), "+f"(d[35]), "+f"(d[36]), "+f"(d[37]), "+f"(d[38]), "+f"(d[39]),
        "+f"(d[40]), "+f"(d[41]), "+f"(d[42]), "+f"(d[43]), "+f"(d[44]), "+f"(d[45]), "+f"(d[46]), "+f"(d[47]),
        "+f"(d[48]), "+f"(d[49]), "+f"(d[50]), "+f"(d[51]), "+f"(d[52]), "+f"(d[53]), "+f"(d[54]), "+f"(d[55]),
        "+f"(d[56]), "+f"(d[57]), "+f"(d[58]), "+f"(d[59]), "+f"(d[60]), "+f"(d[61]), "+f"(d[62]), "+f"(d[63]),
        "+f"(d[64]), "+f"(d[65]), "+f"(d[66]), "+f"(d[67]), "+f"(d[68]), "+f"(d[69]), "+f"(d[70]), "+f"(d[71]),
        "+f"(d[72]), "+f"(d[73]), "+f"(d[74]), "+f"(d[75]), "+f"(d[76]), "+f"(d[77]), "+f"(d[78]), "+f"(d[79]),
        "+f"(d[80]), "+f"(d[81]), "+f"(d[82]), "+f"(d[83]), "+f"(d[84]), "+f"(d[85]), "+f"(d[86]), "+f"(d[87]),
        "+f"(d[88]), "+f"(d[89]), "+f"(d[90]), "+f"(d[91]), "+f"(d[92]), "+f"(d[93]), "+f"(d[94]), "+f"(d[95])
      : "l"(descA), "l"(descB), "r"(acc));
}

__device__ __forceinline__ void mma_ss80_tt(float (&d)[40], uint64_t descA, uint64_t descB) {
  asm volatile("wgmma.mma_async.sync.aligned.m64n80k16.f32.bf16.bf16 {"
      "%0, %1, %2, %3, %4, %5, %6, %7, %8, %9, %10, %11, %12, %13, %14, %15, "
      "%16, %17, %18, %19, %20, %21, %22, %23, %24, %25, %26, %27, %28, %29, %30, %31, "
      "%32, %33, %34, %35, %36, %37, %38, %39"
      "}, %40, %41, 1, 1, 1, 1, 1;\n"
      : "+f"(d[0]), "+f"(d[1]), "+f"(d[2]), "+f"(d[3]), "+f"(d[4]), "+f"(d[5]), "+f"(d[6]), "+f"(d[7]),
        "+f"(d[8]), "+f"(d[9]), "+f"(d[10]), "+f"(d[11]), "+f"(d[12]), "+f"(d[13]), "+f"(d[14]), "+f"(d[15]),
        "+f"(d[16]), "+f"(d[17]), "+f"(d[18]), "+f"(d[19]), "+f"(d[20]), "+f"(d[21]), "+f"(d[22]), "+f"(d[23]),
        "+f"(d[24]), "+f"(d[25]), "+f"(d[26]), "+f"(d[27]), "+f"(d[28]), "+f"(d[29]), "+f"(d[30]), "+f"(d[31]),
        "+f"(d[32]), "+f"(d[33]), "+f"(d[34]), "+f"(d[35]), "+f"(d[36]), "+f"(d[37]), "+f"(d[38]), "+f"(d[39])
      : "l"(descA), "l"(descB));
}
__device__ __forceinline__ void mma_ss80_tt_z(float (&d)[40], uint64_t descA, uint64_t descB) {
  asm volatile("wgmma.mma_async.sync.aligned.m64n80k16.f32.bf16.bf16 {"
      "%0, %1, %2, %3, %4, %5, %6, %7, %8, %9, %10, %11, %12, %13, %14, %15, "
      "%16, %17, %18, %19, %20, %21, %22, %23, %24, %25, %26, %27, %28, %29, %30, %31, "
      "%32, %33, %34, %35, %36, %37, %38, %39"
      "}, %40, %41, 0, 1, 1, 1, 1;\n"
      : "=f"(d[0]), "=f"(d[1]), "=f"(d[2]), "=f"(d[3]), "=f"(d[4]), "=f"(d[5]), "=f"(d[6]), "=f"(d[7]),
        "=f"(d[8]), "=f"(d[9]), "=f"(d[10]), "=f"(d[11]), "=f"(d[12]), "=f"(d[13]), "=f"(d[14]), "=f"(d[15]),
        "=f"(d[16]), "=f"(d[17]), "=f"(d[18]), "=f"(d[19]), "=f"(d[20]), "=f"(d[21]), "=f"(d[22]), "=f"(d[23]),
        "=f"(d[24]), "=f"(d[25]), "=f"(d[26]), "=f"(d[27]), "=f"(d[28]), "=f"(d[29]), "=f"(d[30]), "=f"(d[31]),
        "=f"(d[32]), "=f"(d[33]), "=f"(d[34]), "=f"(d[35]), "=f"(d[36]), "=f"(d[37]), "=f"(d[38]), "=f"(d[39])
      : "l"(descA), "l"(descB));
}

__device__ __forceinline__ void mma_rs80_k(float (&d)[40], const uint32_t (&a)[4], uint64_t descB) {
  asm volatile("wgmma.mma_async.sync.aligned.m64n80k16.f32.bf16.bf16 {"
      "%0, %1, %2, %3, %4, %5, %6, %7, %8, %9, %10, %11, %12, %13, %14, %15, "
      "%16, %17, %18, %19, %20, %21, %22, %23, %24, %25, %26, %27, %28, %29, %30, %31, "
      "%32, %33, %34, %35, %36, %37, %38, %39"
      "}, {%40, %41, %42, %43}, %44, 1, 1, 1, 0;\n"
      : "+f"(d[0]), "+f"(d[1]), "+f"(d[2]), "+f"(d[3]), "+f"(d[4]), "+f"(d[5]), "+f"(d[6]), "+f"(d[7]),
        "+f"(d[8]), "+f"(d[9]), "+f"(d[10]), "+f"(d[11]), "+f"(d[12]), "+f"(d[13]), "+f"(d[14]), "+f"(d[15]),
        "+f"(d[16]), "+f"(d[17]), "+f"(d[18]), "+f"(d[19]), "+f"(d[20]), "+f"(d[21]), "+f"(d[22]), "+f"(d[23]),
        "+f"(d[24]), "+f"(d[25]), "+f"(d[26]), "+f"(d[27]), "+f"(d[28]), "+f"(d[29]), "+f"(d[30]), "+f"(d[31]),
        "+f"(d[32]), "+f"(d[33]), "+f"(d[34]), "+f"(d[35]), "+f"(d[36]), "+f"(d[37]), "+f"(d[38]), "+f"(d[39])
      : "r"(a[0]), "r"(a[1]), "r"(a[2]), "r"(a[3]), "l"(descB));
}
__device__ __forceinline__ void mma_rs80_k_z(float (&d)[40], const uint32_t (&a)[4], uint64_t descB) {
  asm volatile("wgmma.mma_async.sync.aligned.m64n80k16.f32.bf16.bf16 {"
      "%0, %1, %2, %3, %4, %5, %6, %7, %8, %9, %10, %11, %12, %13, %14, %15, "
      "%16, %17, %18, %19, %20, %21, %22, %23, %24, %25, %26, %27, %28, %29, %30, %31, "
      "%32, %33, %34, %35, %36, %37, %38, %39"
      "}, {%40, %41, %42, %43}, %44, 0, 1, 1, 0;\n"
      : "=f"(d[0]), "=f"(d[1]), "=f"(d[2]), "=f"(d[3]), "=f"(d[4]), "=f"(d[5]), "=f"(d[6]), "=f"(d[7]),
        "=f"(d[8]), "=f"(d[9]), "=f"(d[10]), "=f"(d[11]), "=f"(d[12]), "=f"(d[13]), "=f"(d[14]), "=f"(d[15]),
        "=f"(d[16]), "=f"(d[17]), "=f"(d[18]), "=f"(d[19]), "=f"(d[20]), "=f"(d[21]), "=f"(d[22]), "=f"(d[23]),
        "=f"(d[24]), "=f"(d[25]), "=f"(d[26]), "=f"(d[27]), "=f"(d[28]), "=f"(d[29]), "=f"(d[30]), "=f"(d[31]),
        "=f"(d[32]), "=f"(d[33]), "=f"(d[34]), "=f"(d[35]), "=f"(d[36]), "=f"(d[37]), "=f"(d[38]), "=f"(d[39])
      : "r"(a[0]), "r"(a[1]), "r"(a[2]), "r"(a[3]), "l"(descB));
}

__device__ __forceinline__ void mma_rs48_k(float (&d)[24], const uint32_t (&a)[4], uint64_t descB) {
  asm volatile("wgmma.mma_async.sync.aligned.m64n48k16.f32.bf16.bf16 {"
      "%0, %1, %2, %3, %4, %5, %6, %7, %8, %9, %10, %11, %12, %13, %14, %15, "
      "%16, %17, %18, %19, %20, %21, %22, %23"
      "}, {%24, %25, %26, %27}, %28, 1, 1, 1, 0;\n"
      : "+f"(d[0]), "+f"(d[1]), "+f"(d[2]), "+f"(d[3]), "+f"(d[4]), "+f"(d[5]), "+f"(d[6]), "+f"(d[7]),
        "+f"(d[8]), "+f"(d[9]), "+f"(d[10]), "+f"(d[11]), "+f"(d[12]), "+f"(d[13]), "+f"(d[14]), "+f"(d[15]),
        "+f"(d[16]), "+f"(d[17]), "+f"(d[18]), "+f"(d[19]), "+f"(d[20]), "+f"(d[21]), "+f"(d[22]), "+f"(d[23])
      : "r"(a[0]), "r"(a[1]), "r"(a[2]), "r"(a[3]), "l"(descB));
}
__device__ __forceinline__ void mma_rs48_k_z(float (&d)[24], const uint32_t (&a)[4], uint64_t descB) {
  asm volatile("wgmma.mma_async.sync.aligned.m64n48k16.f32.bf16.bf16 {"
      "%0, %1, %2, %3, %4, %5, %6, %7, %8, %9, %10, %11, %12, %13, %14, %15, "
      "%16, %17, %18, %19, %20, %21, %22, %23"
      "}, {%24, %25, %26, %27}, %28, 0, 1, 1, 0;\n"
      : "=f"(d[0]), "=f"(d[1]), "=f"(d[2]), "=f"(d[3]), "=f"(d[4]), "=f"(d[5]), "=f"(d[6]), "=f"(d[7]),
        "=f"(d[8]), "=f"(d[9]), "=f"(d[10]), "=f"(d[11]), "=f"(d[12]), "=f"(d[13]), "=f"(d[14]), "=f"(d[15]),
        "=f"(d[16]), "=f"(d[17]), "=f"(d[18]), "=f"(d[19]), "=f"(d[20]), "=f"(d[21]), "=f"(d[22]), "=f"(d[23])
      : "r"(a[0]), "r"(a[1]), "r"(a[2]), "r"(a[3]), "l"(descB));
}

__device__ __forceinline__ void mma_rs160_n(float (&d)[80], const uint32_t (&a)[4], uint64_t descB) {
  asm volatile("wgmma.mma_async.sync.aligned.m64n160k16.f32.bf16.bf16 {"
      "%0, %1, %2, %3, %4, %5, %6, %7, %8, %9, %10, %11, %12, %13, %14, %15, "
      "%16, %17, %18, %19, %20, %21, %22, %23, %24, %25, %26, %27, %28, %29, %30, %31, "
      "%32, %33, %34, %35, %36, %37, %38, %39, %40, %41, %42, %43, %44, %45, %46, %47, "
      "%48, %49, %50, %51, %52, %53, %54, %55, %56, %57, %58, %59, %60, %61, %62, %63, "
      "%64, %65, %66, %67, %68, %69, %70, %71, %72, %73, %74, %75, %76, %77, %78, %79"
      "}, {%80, %81, %82, %83}, %84, 1, 1, 1, 1;\n"
      : "+f"(d[0]), "+f"(d[1]), "+f"(d[2]), "+f"(d[3]), "+f"(d[4]), "+f"(d[5]), "+f"(d[6]), "+f"(d[7]),
        "+f"(d[8]), "+f"(d[9]), "+f"(d[10]), "+f"(d[11]), "+f"(d[12]), "+f"(d[13]), "+f"(d[14]), "+f"(d[15]),
        "+f"(d[16]), "+f"(d[17]), "+f"(d[18]), "+f"(d[19]), "+f"(d[20]), "+f"(d[21]), "+f"(d[22]), "+f"(d[23]),
        "+f"(d[24]), "+f"(d[25]), "+f"(d[26]), "+f"(d[27]), "+f"(d[28]), "+f"(d[29]), "+f"(d[30]), "+f"(d[31]),
        "+f"(d[32]), "+f"(d[33]), "+f"(d[34]), "+f"(d[35]), "+f"(d[36]), "+f"(d[37]), "+f"(d[38]), "+f"(d[39]),
        "+f"(d[40]), "+f"(d[41]), "+f"(d[42]), "+f"(d[43]), "+f"(d[44]), "+f"(d[45]), "+f"(d[46]), "+f"(d[47]),
        "+f"(d[48]), "+f"(d[49]), "+f"(d[50]), "+f"(d[51]), "+f"(d[52]), "+f"(d[53]), "+f"(d[54]), "+f"(d[55]),
        "+f"(d[56]), "+f"(d[57]), "+f"(d[58]), "+f"(d[59]), "+f"(d[60]), "+f"(d[61]), "+f"(d[62]), "+f"(d[63]),
        "+f"(d[64]), "+f"(d[65]), "+f"(d[66]), "+f"(d[67]), "+f"(d[68]), "+f"(d[69]), "+f"(d[70]), "+f"(d[71]),
        "+f"(d[72]), "+f"(d[73]), "+f"(d[74]), "+f"(d[75]), "+f"(d[76]), "+f"(d[77]), "+f"(d[78]), "+f"(d[79])
      : "r"(a[0]), "r"(a[1]), "r"(a[2]), "r"(a[3]), "l"(descB));
}
__device__ __forceinline__ void mma_rs160_n_z(float (&d)[80], const uint32_t (&a)[4], uint64_t descB) {
  asm volatile("wgmma.mma_async.sync.aligned.m64n160k16.f32.bf16.bf16 {"
      "%0, %1, %2, %3, %4, %5, %6, %7, %8, %9, %10, %11, %12, %13, %14, %15, "
      "%16, %17, %18, %19, %20, %21, %22, %23, %24, %25, %26, %27, %28, %29, %30, %31, "
      "%32, %33, %34, %35, %36, %37, %38, %39, %40, %41, %42, %43, %44, %45, %46, %47, "
      "%48, %49, %50, %51, %52, %53, %54, %55, %56, %57, %58, %59, %60, %61, %62, %63, "
      "%64, %65, %66, %67, %68, %69, %70, %71, %72, %73, %74, %75, %76, %77, %78, %79"
      "}, {%80, %81, %82, %83}, %84, 0, 1, 1, 1;\n"
      : "=f"(d[0]), "=f"(d[1]), "=f"(d[2]), "=f"(d[3]), "=f"(d[4]), "=f"(d[5]), "=f"(d[6]), "=f"(d[7]),
        "=f"(d[8]), "=f"(d[9]), "=f"(d[10]), "=f"(d[11]), "=f"(d[12]), "=f"(d[13]), "=f"(d[14]), "=f"(d[15]),
        "=f"(d[16]), "=f"(d[17]), "=f"(d[18]), "=f"(d[19]), "=f"(d[20]), "=f"(d[21]), "=f"(d[22]), "=f"(d[23]),
        "=f"(d[24]), "=f"(d[25]), "=f"(d[26]), "=f"(d[27]), "=f"(d[28]), "=f"(d[29]), "=f"(d[30]), "=f"(d[31]),
        "=f"(d[32]), "=f"(d[33]), "=f"(d[34]), "=f"(d[35]), "=f"(d[36]), "=f"(d[37]), "=f"(d[38]), "=f"(d[39]),
        "=f"(d[40]), "=f"(d[41]), "=f"(d[42]), "=f"(d[43]), "=f"(d[44]), "=f"(d[45]), "=f"(d[46]), "=f"(d[47]),
        "=f"(d[48]), "=f"(d[49]), "=f"(d[50]), "=f"(d[51]), "=f"(d[52]), "=f"(d[53]), "=f"(d[54]), "=f"(d[55]),
        "=f"(d[56]), "=f"(d[57]), "=f"(d[58]), "=f"(d[59]), "=f"(d[60]), "=f"(d[61]), "=f"(d[62]), "=f"(d[63]),
        "=f"(d[64]), "=f"(d[65]), "=f"(d[66]), "=f"(d[67]), "=f"(d[68]), "=f"(d[69]), "=f"(d[70]), "=f"(d[71]),
        "=f"(d[72]), "=f"(d[73]), "=f"(d[74]), "=f"(d[75]), "=f"(d[76]), "=f"(d[77]), "=f"(d[78]), "=f"(d[79])
      : "r"(a[0]), "r"(a[1]), "r"(a[2]), "r"(a[3]), "l"(descB));
}

__device__ __forceinline__ void feature_map(const uint32_t (&P)[2][10], uint32_t (&fr)[10][4]) {
  constexpr float L2E = 1.4426950408889634f;
#pragma unroll
  for (int p = 0; p < 2; p++) {
#pragma unroll
    for (int r = 0; r < 2; r++) {
      uint32_t mx = P[r][5 * p], mn = mx;
#pragma unroll
      for (int g = 1; g < 5; g++) { mx = max_bf2(mx, P[r][5 * p + g]); mn = min_bf2(mn, P[r][5 * p + g]); }
      mx = max_bf2(mx, __shfl_xor_sync(0xffffffffu, mx, 1));
      mn = min_bf2(mn, __shfl_xor_sync(0xffffffffu, mn, 1));
      mx = max_bf2(mx, __shfl_xor_sync(0xffffffffu, mx, 2));
      mn = min_bf2(mn, __shfl_xor_sync(0xffffffffu, mn, 2));
      float mx0 = -bf_lo(mx) * L2E, mx1 = -bf_hi(mx) * L2E, mn0 = bf_lo(mn) * L2E, mn1 = bf_hi(mn) * L2E;
      float ep0[5], ep1[5], en0[5], en1[5];
      float sp0 = 0.f, sp1 = 0.f, sn0 = 0.f, sn1 = 0.f;
#pragma unroll
      for (int g = 0; g < 5; g++) {
        float x0 = bf_lo(P[r][5 * p + g]), x1 = bf_hi(P[r][5 * p + g]);
        ep0[g] = ex2(fmaf(x0, L2E, mx0)); ep1[g] = ex2(fmaf(x1, L2E, mx1));
        en0[g] = ex2(fmaf(x0, -L2E, mn0)); en1[g] = ex2(fmaf(x1, -L2E, mn1));
        sp0 += ep0[g]; sp1 += ep1[g]; sn0 += en0[g]; sn1 += en1[g];
      }
      sp0 += __shfl_xor_sync(0xffffffffu, sp0, 1); sp1 += __shfl_xor_sync(0xffffffffu, sp1, 1);
      sn0 += __shfl_xor_sync(0xffffffffu, sn0, 1); sn1 += __shfl_xor_sync(0xffffffffu, sn1, 1);
      sp0 += __shfl_xor_sync(0xffffffffu, sp0, 2); sp1 += __shfl_xor_sync(0xffffffffu, sp1, 2);
      sn0 += __shfl_xor_sync(0xffffffffu, sn0, 2); sn1 += __shfl_xor_sync(0xffffffffu, sn1, 2);
      sp0 = rcp(sp0); sp1 = rcp(sp1); sn0 = rcp(sn0); sn1 = rcp(sn1);
#pragma unroll
      for (int g = 0; g < 5; g++) {
        fr[5 * p + g][r] = pack_bf16(ep0[g] * sp0, ep1[g] * sp1);
        fr[5 * p + g][2 + r] = pack_bf16(en0[g] * sn0, en1[g] * sn1);
      }
    }
  }
}

template <int V> struct IntC { static constexpr int value = V; };
struct Ring {
  uint32_t idx, phase;
  template <int N> __device__ __forceinline__ void next() { if (++idx == N) { idx = 0; phase ^= 1; } }
};

}

__global__ void __cluster_dims__(2, 1, 1) __launch_bounds__(384, 1)
fused_kernel(const __grid_constant__ Maps maps, const __nv_bfloat16* __restrict__ x, const __nv_bfloat16* __restrict__ wqkv,
             const __nv_bfloat16* __restrict__ wphi, const __nv_bfloat16* __restrict__ w1, const __nv_bfloat16* __restrict__ w2,
             const __nv_bfloat16* __restrict__ w3, const __nv_bfloat16* __restrict__ w4, const __nv_bfloat16* __restrict__ wo,
             const __nv_bfloat16* __restrict__ gate_w, __nv_bfloat16* __restrict__ out) {
  extern __shared__ __align__(1024) uint8_t sgen[];
  const uint32_t sb = smem_u32(sgen);
  const uint32_t sb16 = (sb & 0x3FFFFu) >> 4;
  const uint32_t bars = sb + OFF_BAR;
  const uint32_t fullA = bars + 8 * B_FULLA, emptyA = bars + 8 * B_EMPTYA, fullB = bars + 8 * B_FULLB, emptyB = bars + 8 * B_EMPTYB;

  const int tid = threadIdx.x;
  const int rank = blockIdx.x & 1;
  const int bid = blockIdx.x - NSVC, pairIdx = bid >> 1;
  const int i = pairIdx >> 2, j = 2 * (pairIdx & 3) + rank;
  const int k3 = (5 * (pairIdx & 3) + 1) >> 1;

  if (bid < 0) {
    const int sv = blockIdx.x;
    const unsigned epoch = *reinterpret_cast<volatile unsigned*>(g_flags + FL_DONE * 32) / NCTA;
    if (tid == 0) {
#pragma unroll
      for (int b = 0; b < 11; b++) mbar_init(bars + 8 * b, 1);
      mbar_expect_tx(bars + 80, 6400);
      bulk_load(sb + 204800, wphi + sv * 3200, 6400, bars + 80);
    }
    __syncthreads();
    float a[8];
#pragma unroll 1
    for (int rd = 0; rd < 4; rd++) {
      const int nch = rd ? 192 : 80, nth = rd ? 384 : 320, piece = rd ? 18432 : 20480, np = rd == 3 ? 7 : 10;
      if (tid == 0) {
        const char* src = reinterpret_cast<const char*>(rd ? w3 + (size_t)(160 * sv + 60 * (rd - 1)) * F_ : w1 + (size_t)160 * sv * D_);
#pragma unroll 1
        for (int p = 0; p < np; p++) {
          const int bytes = (rd == 3 && p == 6) ? 12288 : piece;
          mbar_expect_tx(bars + 8 * p, bytes);
          bulk_load(sb + p * piece, src + p * piece, bytes, bars + 8 * p);
        }
      }
      if (rd == 0) {
        if (tid < 40 && (tid < 20 || sv >= 2))
          reinterpret_cast<uint4*>(g_Hs + (size_t)(2 + ((sv & 1) ? S_ - 1 - tid / 20 : tid / 20)) * D_ + 160 * sv)[tid % 20] = make_uint4(0, 0, 0, 0);
        mbar_wait(bars + 80, 0);
#pragma unroll 1
        for (int e = tid; e < 1600; e += 384) {
          const int jj = e / 800, it = e - 800 * jj, st = it / 160, n = (it - 160 * st) >> 1, k0 = 16 * st + 8 * ((it ^ (n >> 2)) & 1);
          const int nn = n % 40, h = 2 * (n / 40) + (nn & 1), ff = 4 * (nn >> 3) + ((nn >> 1) & 3);
          uint32_t w[8];
#pragma unroll
          for (int q = 0; q < 8; q++) {
            const int k = k0 + q;
            w[q] = (unsigned)(k - 20 * h) < 20u ? reinterpret_cast<const unsigned short*>(sgen + 204800)[jj * 1600 + k * 20 + ff] : 0u;
          }
          g_wphi[sv * 1600 + e] = make_uint4(w[0] | (w[1] << 16), w[2] | (w[3] << 16), w[4] | (w[5] << 16), w[6] | (w[7] << 16));
        }
      }
      if (rd < 2) {
#pragma unroll
        for (int e = 0; e < 8; e++) a[e] = 0.f;
      }
#pragma unroll 1
      for (int p = 0; p < np; p++) {
        mbar_wait(bars + 8 * p, rd & 1);
        const int bytes = (rd == 3 && p == 6) ? 12288 : piece;
        if (tid < nth) {
#pragma unroll 1
          for (int o = tid * 16; o < bytes; o += nth * 16) {
            const uint4 v = lds128(sb + p * piece + o);
            a[0] += bf_lo(v.x); a[1] += bf_hi(v.x); a[2] += bf_lo(v.y); a[3] += bf_hi(v.y);
            a[4] += bf_lo(v.z); a[5] += bf_hi(v.z); a[6] += bf_lo(v.w); a[7] += bf_hi(v.w);
          }
        }
      }
      if (tid < nth && (rd == 0 || rd == 3)) {
        float* cd = g_cs[epoch & 1] + (rd ? D_ : 0) + 8 * (tid % nch);
        red_add4(cd, a[0], a[1], a[2], a[3]); red_add4(cd + 4, a[4], a[5], a[6], a[7]);
      }
      __syncthreads();
      if (tid == 0 && (rd == 0 || rd == 3)) {
        flag_add(rd ? FL_CS3 : FL_CS);
        if (rd == 0) l2_prefetch(w2 + (size_t)sv * (D_ * D_ / NSVC), D_ * D_ * 2 / NSVC);
      }
    }
#pragma unroll 1
    for (int e = tid; e < (D_ + F_) / NSVC; e += 384) g_cs[(epoch + 1) & 1][sv * ((D_ + F_) / NSVC) + e] = 0.f;
#pragma unroll 1
    for (int e = tid; e < 2 * KV_J; e += 384) g_acc[(epoch + 1) & 1][sv * 2 * KV_J + e] = 0.f;
    if (tid < 32) {
      l2_prefetch(w4 + (size_t)(sv * 32 + tid) * (F_ * D_ / 128), F_ * D_ * 2 / 128);
      l2_prefetch(wo + (size_t)(sv * 32 + tid) * (D_ * D_ / 128), D_ * D_ * 2 / 128);
    }
    return;
  }
  TSTAMP(0);
  if (tid >= 256) {
    asm volatile("setmaxnreg.dec.sync.aligned.u32 40;");
    if (tid == 256) {
#pragma unroll
      for (int s = 0; s < NA; s++) mbar_init(fullA + 8 * s, 1);
      asm volatile("fence.mbarrier_init.release.cluster;" ::: "memory");
#pragma unroll 1
      for (int u = 0; u < 4; u++) {
        if ((u & 1) == 0) mbar_expect_tx(fullA + 4 * u, SLOT_A);
        tma2d(sb + OFF_A + u * 8192, &maps.x, fullA + 8 * (u >> 1), 64 * (u >> 1), 128 * i + 64 * (u & 1));
      }
    } else if (tid == 288) {
#pragma unroll
      for (int s = 0; s < NB; s++) { mbar_init(fullB + 8 * s, 1); mbar_init(emptyB + 8 * s, 8); }
      asm volatile("fence.mbarrier_init.release.cluster;" ::: "memory");
    } else if (tid == 320) {
#pragma unroll
      for (int b = B_CS; b < NBAR; b++) if (b < B_EMPTYB || b >= B_EMPTYB + NB) mbar_init(bars + 8 * b, b < B_EMPTYB ? 1 : b < B_EMPTYA ? 8 : b < B_X1P ? 16 : 2);
#pragma unroll
      for (int b = B_DSR; b < B_EMPTYB; b++) mbar_expect_tx(bars + 8 * b, 10240);
      asm volatile("fence.mbarrier_init.release.cluster;" ::: "memory");
    }
    __syncwarp();
    asm volatile("barrier.cluster.arrive.relaxed.aligned;" ::: "memory");
    auto get_epoch = [&]() { return *reinterpret_cast<volatile unsigned*>(g_flags + FL_DONE * 32) / NCTA; };
    if ((tid >> 5) != 9) asm volatile("barrier.cluster.wait.aligned;" ::: "memory");
    const int lane = tid & 31, pw = (tid >> 5) & 3;
    if (pw == 0) {
      if (tid == 256) {
        Ring r{2, 1};
        unsigned ep1 = 0;
#pragma unroll 1
        for (int k = 2; k < 24; k++) {
          if (k == 4) ep1 = get_epoch() + 1;
          if (k == 10 || k == 16) {
            if (k == 10) mbar_wait(bars + 8 * B_HST, 0);
            flag_wait(k == 10 ? FL_H + 2 * i + rank : FL_X1 + i, ep1 * 8u);
            TSTAMPX(k == 10 ? 29 : 30);
          }
          if (k == 14) {
            mbar_wait(bars + 8 * B_WDEAD, 0);
            mbar_expect_tx(bars + 8 * B_T4, SLOT_A);
            tma2d(sb + OFF_MISC, &maps.hs, bars + 8 * B_T4, 256 + 320 * rank, 128 * i);
            mbar_wait(bars + 8 * B_X1P, 0);
          }
          mbar_wait(emptyA + 8 * r.idx, r.phase);
          const uint32_t bar = fullA + 8 * r.idx, slot = sb + OFF_A + r.idx * SLOT_A;
          mbar_expect_tx(bar, SLOT_A);
          if (k >= 10 && k < 14) tma2d(slot, &maps.hs, bar, 64 * (k - 10) + 320 * rank, 128 * i);
          else tma2d_mc(slot + rank * 8192, k < 10 ? &maps.x : &maps.x1, bar, 64 * (k < 10 ? k : (k - 14 + k3) % 10), 128 * i + 64 * rank);
          r.next<NA>();
        }
      }
    } else if (pw == 1) {
      if (tid == 288) {
        Ring r{0, 1};
#pragma unroll 1
        for (int k = 0; k < 18; k++) {
          mbar_wait(emptyB + 8 * r.idx, r.phase);
          const uint32_t bar = fullB + 8 * r.idx, slot = sb + OFF_B + r.idx * SLOT_B;
          if (k < 10) {
            mbar_expect_tx(bar, 40960);
            tma4d(slot + 8192, &maps.qm, bar, 0, 64 * k, 0, j);
            tma3d(slot, &maps.w1m, bar, 0, 64 * k, j);
            tma4d(slot + 32768 + 2048, &maps.qr, bar, 64, 64 * k, 0, j);
            tma3d(slot + 32768, &maps.w1r, bar, 64, 64 * k, j);
          } else if (k < 13) {
            mbar_expect_tx(bar, k < 12 ? 40960 : 20480);
            tma3d(slot, &maps.w2, bar, 0, 320 * rank + 128 * (k - 10), 5 * (j >> 1));
            if (k < 12) tma3d(slot + 20480, &maps.w2, bar, 0, 320 * rank + 128 * (k - 10) + 64, 5 * (j >> 1));
          } else {
            mbar_expect_tx(bar, 49152);
            tma3d(slot, &maps.w3, bar, 0, 64 * ((2 * (k - 13) + k3) % 10), 3 * j);
            tma3d(slot + 24576, &maps.w3, bar, 0, 64 * ((2 * (k - 13) + 1 + k3) % 10), 3 * j);
          }
          r.next<NB>();
        }
#pragma unroll 1
        for (int n = 0; n < 8; n++) {
          if (n < 3) { mbar_wait(emptyB + 8 * r.idx, r.phase); r.next<NB>(); }
          if (n == 0) mbar_wait(fullA + 24, 1);
          if (n >= 4) mbar_wait(bars + 8 * (B_EMPTY4 + n - 4), 0);
          const uint32_t bar = bars + 8 * (B_FULL4 + n), set = sb + ((n >> 1) & 1) * SET4;
          const int h = n & 1, m = ((j >> 1) + 1 + (n >> 1)) & 3;
          mbar_expect_tx(bar, h ? 40960 : 46080);
          tma3d(set + (h ? 46080 : 0), h ? &maps.w4 : &maps.wo, bar, 0, h ? 192 * j + 64 : 80 * j, 5 * m);
          tma3d(set + (h ? 66560 : 25600), &maps.w4, bar, 0, 192 * j + 128 * h, 5 * m);
        }
        mbar_wait(bars + 8 * (B_EMPTY4 + 4), 0);
        mbar_expect_tx(bars + 8 * B_XR, 20480);
        tma2d(sb + OFF_OUT, &maps.st_x1, bars + 8 * B_XR, 80 * j, 128 * i);
      }
    } else {
      const unsigned epoch = get_epoch();
      float* accg = g_acc[epoch & 1];
      if (pw == 2) {
        if (tid == 320) {
          flag_wait(FL_CS, (epoch + 1) * NSVC);
          flag_wait(FL_ST + i, (epoch + 1) * 8u);
          fence_async_glb();
          *reinterpret_cast<volatile uint32_t*>(sgen + OFF_BAR + 8 * NBAR) = (epoch + 1) & 1;
          mbar_expect_tx(bars + 8 * B_CS, 320 + 2048 + 12800);
          bulk_load(sb + OFF_CS, g_cs[epoch & 1] + 80 * j, 320, bars + 8 * B_CS);
          bulk_load(sb + OFF_XST, g_xstat + 128 * i, 2048, bars + 8 * B_CS);
          bulk_load(sb + OFF_MISC, g_wphi + j * 800, 12800, bars + 8 * B_CS);
          TSTAMPX(21);
          flag_wait(FL_KV + j, (epoch + 1) * 16u);
          mbar_wait(bars + 8 * B_SIGX1, 0);
          mbar_expect_tx(bars + 8 * B_KV, KV_J * 4);
          bulk_load(sb + OFF_A + SLOT_A, accg + j * KV_J, KV_J * 4, bars + 8 * B_KV);
          TSTAMPX(22);
          flag_wait(FL_CS3, (epoch + 1) * NSVC);
          flag_wait(FL_S1 + i, (epoch + 1) * 8u);
          fence_async_glb();
          mbar_expect_tx(bars + 8 * B_ST1, 8192 + 768);
          bulk_load(sb + OFF_CS + 320, g_cs[epoch & 1] + D_ + 192 * j, 768, bars + 8 * B_ST1);
          bulk_load(sb + OFF_MISC, g_st1 + 128 * i * 8, 8192, bars + 8 * B_ST1);
        }
        __syncwarp();
#pragma unroll 1
        for (int c = 0; c < 3; c++) {
          mbar_wait(bars + 8 * (B_EMPTY4 + (c ? 5 : 4)), 0);
          const uint4* src = g_part + (size_t)((i * 8 + j) * 3 + c) * 1280;
          const unsigned* tp = reinterpret_cast<const unsigned*>(src + 1024 + (lane & 7) * 32 + 31);
          uint32_t n = 0;
          while (!__all_sync(0xffffffffu, (ld_acquire(tp) ^ epoch) & 1u) && ++n < (WAIT_LIMIT >> 2)) {}
          if (tid == 320) {
            mbar_expect_tx(bars + 8 * (B_RDY + c), 20480);
            bulk_load(sb + (c ? 25600 + 20480 * c : 0), src, 20480, bars + 8 * (B_RDY + c));
          }
        }
      }
      if (tid == 352) {
        mbar_wait(bars + 8 * B_SIGP, 0);
        flag_add(FL_ST + i);
        TSTAMPX(20);
        const int shift = (j < 2) ? 1 : (j < 4) ? -1 : (j < 6) ? 2 : -2;
        prefetch_tmap(&maps.st_h); prefetch_tmap(&maps.st_x1); prefetch_tmap(&maps.hs); prefetch_tmap(&maps.x1); prefetch_tmap(&maps.xr);
        prefetch_tmap(&maps.w2); prefetch_tmap(&maps.w3); prefetch_tmap(&maps.w4); prefetch_tmap(&maps.wo);
        mbar_wait(bars + 8 * B_SIGH, 0);
        TSTAMPX(23);
        fence_async_smem();
        tma2d_store(&maps.st_h, sb + OFF_STG, 80 * j, 128 * i + 2 + shift);
        bulk_commit(); bulk_wait<0>();
        flag_add(FL_H + 2 * i + (j >> 2));
        flag_add_relaxed(FL_H + 2 * ((i + (shift > 0 ? 1 : -1)) & 15) + (j >> 2));
        mbar_arrive(bars + 8 * B_HST);
        TSTAMPX(24);
        mbar_wait(bars + 8 * B_SIGKV, 0);
        TSTAMPX(25);
        fence_async_smem();
#pragma unroll 1
        for (int u = 0; u < 4; u++)
          asm volatile("cp.reduce.async.bulk.global.shared::cta.bulk_group.add.f32 [%0], [%1], %2;"
                       ::"l"(accg + j * KV_J + (u >> 1) * KV_PAIR + (u & 1) * 1024), "r"(sb + OFF_B + SPARE + (u & 1) * SLOT_B + (u >> 1) * 4096),
                       "r"((u & 1) ? KV_PAIR * 4 - 4096 : 4096) : "memory");
        bulk_commit(); bulk_wait<0>();
        mbar_expect_tx(bars + 8 * B_XR, 20480);
#pragma unroll 1
        for (int u = 0; u < 8; u++)
          tma2d(sb + OFF_B + (u / 3) * SLOT_B + SPARE + (u % 3) * 2560, &maps.xr, bars + 8 * B_XR, 80 * j, 128 * i + 16 * u);
        flag_add(FL_KV + j);
        TSTAMPX(26);
        mbar_wait(bars + 8 * B_SIGX1, 0);
        TSTAMPX(27);
        fence_async_smem();
        tma2d_store(&maps.st_x1, sb + OFF_STG, 80 * j, 128 * i);
        bulk_commit(); bulk_wait<0>();
        flag_add(FL_X1 + i);
        mbar_arrive_cta(bars + 8 * B_X1P, 0); mbar_arrive_cta(bars + 8 * B_X1P, 1);
        TSTAMPX(28);
        mbar_wait(bars + 8 * B_MFREE, 0);
        flag_add(FL_S1 + i);
      }
    }
  } else {
    uint4 pv[5], pw_[5];
    {
      const int row = 128 * i + 16 * j + (tid >> 4), l16 = tid & 15;
#pragma unroll
      for (int c = 0; c < 5; c++) pv[c] = __ldg(reinterpret_cast<const uint4*>(x + (size_t)row * D_ + c * 128 + l16 * 8));
#pragma unroll
      for (int c = 0; c < 5; c++) pw_[c] = __ldg(reinterpret_cast<const uint4*>(gate_w + c * 128 + l16 * 8));
    }
    asm volatile("barrier.cluster.arrive.relaxed.aligned;" ::: "memory");
    asm volatile("setmaxnreg.inc.sync.aligned.u32 232;");
    const int wg = tid >> 7, warp = tid >> 5, lane = tid & 31, t = lane & 3;
    const int rloc = warp * 16 + (lane >> 2);
    const float* s_cs = reinterpret_cast<const float*>(sgen + OFF_CS);
    auto signal = [&](int b) {
      __syncwarp();
      if (lane == 0) mbar_arrive(bars + 8 * b);
    };
    auto releaseB = [&](uint32_t bar) {
      __syncwarp();
      if (lane == 0) mbar_arrive(bar);
    };
    auto release = [&](uint32_t bar) {
      __syncwarp();
      if (lane < 2) mbar_arrive_cta(bar, lane);
    };
    const uint32_t stg_lane = (warp * 16 + ((lane >> 3) & 1) * 8 + (lane & 7)) * 160 + (lane >> 4) * 16;

    auto stage_tile = [&](uint32_t stg, const uint32_t (&v)[2][10]) {
#pragma unroll
      for (int s = 0; s < 5; s++) stsm4(stg + stg_lane + s * 32, v[0][2 * s], v[1][2 * s], v[0][2 * s + 1], v[1][2 * s + 1]);
    };

    {
      float f[40];
      float s = 0.f, gs = 0.f;
#pragma unroll
      for (int c = 0; c < 5; c++) {
        const uint32_t vv[4] = {pv[c].x, pv[c].y, pv[c].z, pv[c].w}, ww[4] = {pw_[c].x, pw_[c].y, pw_[c].z, pw_[c].w};
#pragma unroll
        for (int e = 0; e < 4; e++) {
          f[8 * c + 2 * e] = bf_lo(vv[e]); f[8 * c + 2 * e + 1] = bf_hi(vv[e]);
          s += f[8 * c + 2 * e] + f[8 * c + 2 * e + 1];
          gs = fmaf(f[8 * c + 2 * e], bf_lo(ww[e]), gs); gs = fmaf(f[8 * c + 2 * e + 1], bf_hi(ww[e]), gs);
        }
      }
#pragma unroll
      for (int o = 1; o < 16; o <<= 1) { s += __shfl_xor_sync(0xffffffffu, s, o); gs += __shfl_xor_sync(0xffffffffu, gs, o); }
      const float mean = s * (1.f / D_);
      float q = 0.f;
#pragma unroll
      for (int e = 0; e < 40; e++) { const float d = f[e] - mean; q = fmaf(d, d, q); }
#pragma unroll
      for (int o = 1; o < 16; o <<= 1) q += __shfl_xor_sync(0xffffffffu, q, o);
      const float rstd = rsqrtf(q * (1.f / D_) + 1e-5f);
      asm volatile("barrier.cluster.wait.aligned;" ::: "memory");
      if ((tid & 15) == 0) g_xstat[128 * i + 16 * j + (tid >> 4)] = make_float4(rstd, -mean, rcp(1.f + __expf(-gs)), 0.f);
      signal(B_SIGP);
    }
    TSTAMP(1);

    Ring ra{0, 0}, rb{0, 0};
    uint32_t qp[2][10], P[2][10];
    float st_g[2];
    {
      float accM[128], accR[32];
      uint32_t pa = 0, pb = 0;
#pragma unroll 1
      for (int k = 0; k < 10; k++) {
        mbar_wait(fullA + 8 * ra.idx, ra.phase);
        if (tid == 0) TRACE(32 + k);
        mbar_wait(fullB + 8 * rb.idx, rb.phase);
        if (tid == 0) TRACE(64 + k);
        if (k == 0) TSTAMP(2);
        const uint32_t a0 = sb16 + ((OFF_A + ra.idx * SLOT_A + wg * 8192) >> 4), b0 = sb16 + ((OFF_B + rb.idx * SLOT_B) >> 4);
        wg_fence();
#pragma unroll
        for (int kk = 0; kk < 4; kk++) {
          const uint64_t da = make_desc(a0, kk * 32, 16, 1024, 1);
          if (kk == 0) {
            mma_ss256_p(accM, da, make_desc(b0, 0, 8192, 1024, 1), k);
            mma_ss64_p(accR, da, make_desc(b0, 32768, 2048, 256, 3), k);
          } else {
            mma_ss256(accM, da, make_desc(b0, kk * 2048, 8192, 1024, 1));
            mma_ss64(accR, da, make_desc(b0, 32768 + kk * 512, 2048, 256, 3));
          }
          if (kk == 0) {
            wg_commit();
            if (k > 0) {
              wg_wait<1>();
              release(emptyA + 8 * pa);
              releaseB(emptyB + 8 * pb);
            }
          }
        }
        wg_commit();
        pa = ra.idx; pb = rb.idx;
        ra.next<NA>(); rb.next<NB>();
      }
      TSTAMP(18);
      float st_rstd[2], st_mr[2];
      mbar_wait(bars + 8 * B_CS, 0);
#pragma unroll
      for (int r = 0; r < 2; r++) {
        const uint4 st = lds128(sb + OFF_XST + (rloc + 8 * r) * 16);
        st_rstd[r] = __uint_as_float(st.x); st_mr[r] = __uint_as_float(st.y); st_g[r] = __uint_as_float(st.z);
      }
      TSTAMP(19);
      wg_wait<0>();
      fence_regs(accM); fence_regs(accR);
      TSTAMP(3);
      release(emptyA + 8 * pa);
#define ACC(P_, G, I_) ((G) < 8 ? accM[(P_) * 32 + ((G) & 7) * 4 + (I_)] : accR[(P_) * 8 + ((G) & 1) * 4 + (I_)])
      {
        uint32_t hv[2][10];
        const GeluC g0 = gelu_consts(st_rstd[0], 1.f), g1 = gelu_consts(st_rstd[1], 1.f);
#pragma unroll
        for (int g = 0; g < 10; g++) {
          const float2 cs = *reinterpret_cast<const float2*>(s_cs + 8 * g + 2 * t);
          const float v0 = gelu_s(fmaf(st_mr[0], cs.x, ACC(0, g, 0)), g0), v1 = gelu_s(fmaf(st_mr[0], cs.y, ACC(0, g, 1)), g0);
          const float v2 = gelu_s(fmaf(st_mr[1], cs.x, ACC(0, g, 2)), g1), v3 = gelu_s(fmaf(st_mr[1], cs.y, ACC(0, g, 3)), g1);
          hv[0][g] = pack_bf16(v0, v1); hv[1][g] = pack_bf16(v2, v3);
        }
        bar_sync(1, 256);
        stage_tile(sb + OFF_STG, hv);
        signal(B_SIGH);
      }
      TSTAMP(4);
      uint32_t kf[5][4], qf[5][4];
#pragma unroll
      for (int s = 0; s < 5; s++) {
        kf[s][0] = pack_bf16(ACC(2, 2 * s, 0), ACC(2, 2 * s, 1)); kf[s][1] = pack_bf16(ACC(2, 2 * s, 2), ACC(2, 2 * s, 3));
        kf[s][2] = pack_bf16(ACC(2, 2 * s + 1, 0), ACC(2, 2 * s + 1, 1)); kf[s][3] = pack_bf16(ACC(2, 2 * s + 1, 2), ACC(2, 2 * s + 1, 3));
        qf[s][0] = pack_bf16(ACC(1, 2 * s, 0), ACC(1, 2 * s, 1)); qf[s][1] = pack_bf16(ACC(1, 2 * s, 2), ACC(1, 2 * s, 3));
        qf[s][2] = pack_bf16(ACC(1, 2 * s + 1, 0), ACC(1, 2 * s + 1, 1)); qf[s][3] = pack_bf16(ACC(1, 2 * s + 1, 2), ACC(1, 2 * s + 1, 3));
      }
      float pk[40], pq[40];
      wg_fence();
#pragma unroll
      for (int s = 0; s < 5; s++) {
        if (s == 0) mma_rs80_k_z(pk, kf[s], make_desc(sb16, OFF_MISC, 16, 256, 3));
        else mma_rs80_k(pk, kf[s], make_desc(sb16, OFF_MISC + s * 2560, 16, 256, 3));
      }
      wg_commit();
#pragma unroll
      for (int s = 0; s < 5; s++) {
        if (s == 0) mma_rs80_k_z(pq, qf[s], make_desc(sb16, OFF_MISC, 16, 256, 3));
        else mma_rs80_k(pq, qf[s], make_desc(sb16, OFF_MISC + s * 2560, 16, 256, 3));
      }
      wg_commit();
      {
        const int mat = lane >> 3;
        const int tok = warp * 16 + (mat & 1) * 8 + (lane & 7);
        const uint32_t base = sb + OFF_B + SPARE + tok * 32 + (((mat >> 1) ^ ((tok >> 2) & 1)) << 4);
        const uint32_t ones = (t == 0) ? 0x00003f80u : 0u;
#pragma unroll
        for (int p = 0; p < 2; p++) {
#pragma unroll
          for (int gg = 0; gg < 3; gg++) {
            const int g0 = 5 * p + 2 * gg;
            uint32_t r0 = pack_bf16(ACC(3, g0, 0), ACC(3, g0, 1)), r1 = pack_bf16(ACC(3, g0, 2), ACC(3, g0, 3));
            uint32_t r2 = ones, r3 = ones;
            if (gg < 2) { r2 = pack_bf16(ACC(3, g0 + 1, 0), ACC(3, g0 + 1, 1)); r3 = pack_bf16(ACC(3, g0 + 1, 2), ACC(3, g0 + 1, 3)); }
            stsm4(base + gg * SLOT_B + p * 4096, r0, r1, r2, r3);
          }
        }
      }
#undef ACC
      wg_wait<1>();
      fence_regs(pk);
#pragma unroll
      for (int G = 0; G < 10; G++) {
        P[0][G] = pack_bf16(pk[4 * G], pk[4 * G + 1]); P[1][G] = pack_bf16(pk[4 * G + 2], pk[4 * G + 3]);
      }
      wg_wait<0>();
      fence_regs(pq);
      signal(B_WDEAD);
#pragma unroll
      for (int G = 0; G < 10; G++) {
        qp[0][G] = pack_bf16(pq[4 * G], pq[4 * G + 1]); qp[1][G] = pack_bf16(pq[4 * G + 2], pq[4 * G + 3]);
      }
    }

    uint32_t fr[10][4];
    int pass;
    pass = gridDim.y;
#pragma unroll 1
    do {
    feature_map(P, fr);
    if (pass != 0) {
    {
      const int mat = lane >> 3;
      const int tok = warp * 16 + (mat & 1) * 8 + (lane & 7);
      const uint32_t base = sb + OFF_B + tok * 32 + (((mat >> 1) ^ ((tok >> 2) & 1)) << 4);
#pragma unroll
      for (int G = 0; G < 10; G++) stsm4(base + G * 4096, fr[G][0], fr[G][1], fr[G][2], fr[G][3]);
      fence_async_smem();
      bar_sync(1, 256);
      float kv[40];
      const uint32_t va = sb16 + ((OFF_B + SPARE + wg * 4096) >> 4), vb = sb16 + ((OFF_B + wg * 20480) >> 4);
      wg_fence();
#pragma unroll
      for (int ks = 0; ks < 8; ks++) {
        if (ks == 0) mma_ss80_tt_z(kv, make_desc(va, 0, SLOT_B, 256, 3), make_desc(vb, 0, 4096, 256, 3));
        else mma_ss80_tt(kv, make_desc(va, ks * 512, SLOT_B, 256, 3), make_desc(vb, ks * 512, 4096, 256, 3));
      }
      wg_commit();
      uint32_t xv[2][10];
      float acc[80];
      TSTAMP(5);
      mbar_wait(fullA + 8 * 2, 0);
      mbar_wait(fullB + 8 * 1, 1);
      TSTAMP(6);
      wg_fence();
#pragma unroll
      for (int kk = 0; kk < 4; kk++) {
        const uint64_t da = make_desc(sb16 + wg * 512, OFF_A + 2 * SLOT_A + kk * 32, 16, 1024, 1);
        const uint64_t db = make_desc(sb16, OFF_B + SLOT_B + kk * 1024, 4096, 512, 2);
        if (kk == 0) mma_ss160_z(acc, da, db); else mma_ss160(acc, da, db);
      }
      wg_commit();
      ra.next<NA>();
      wg_wait<1>();
      fence_regs(kv);
      TSTAMP(31);
      releaseB(emptyB); release(bars + 8 * B_PEER2);
      auto kv_sts = [&](uint32_t o, uint32_t a0, uint32_t a1, uint32_t a2, uint32_t a3) {
        sts128(sb + OFF_B + SPARE + wg * 4096 + o + (o >= 4096 ? SLOT_B - 4096 : 0), make_uint4(a0, a1, a2, a3));
      };
      const int m0 = (warp & 3) * 16 + (lane >> 2);
      bar_sync(4 + wg, 128);
#pragma unroll
      for (int r = 0; r < 2; r++) {
        const int m = m0 + 8 * r;
        const bool hi = m >= 20;
        uint32_t v[10];
#pragma unroll
        for (int G = 0; G < 10; G++) v[G] = __float_as_uint(hi ? kv[4 * G + 2 * r + 1] : kv[4 * G + 2 * r]);
        const uint32_t p = 4 * (m < 40 ? m * 48 + t * 12 : 1920 + t * 24 + 12);
        if (m <= 40) { kv_sts(p, v[0], v[1], v[2], v[3]); kv_sts(p + 16, v[4], v[5], v[6], v[7]); kv_sts(p + 32, v[8], v[9], 0u, 0u); }
      }
      if (m0 == 32) {
        const uint32_t p = 4 * (1920 + t * 24);
        kv_sts(p, __float_as_uint(kv[2]), __float_as_uint(kv[6]), __float_as_uint(kv[10]), __float_as_uint(kv[14]));
        kv_sts(p + 16, __float_as_uint(kv[18]), __float_as_uint(kv[22]), __float_as_uint(kv[26]), __float_as_uint(kv[30]));
        kv_sts(p + 32, __float_as_uint(kv[34]), __float_as_uint(kv[38]), 0u, 0u);
      }
      signal(B_SIGKV);
      uint32_t pa = 2, pb = 1;
#pragma unroll 1
      for (int k = 1; k < 5; k++) {
        mbar_wait(k < 4 ? fullA + 8 * ra.idx : bars + 8 * B_T4, k < 4 ? ra.phase : 0);
        if ((k & 1) == 0) mbar_wait(fullB + 8 * rb.idx, rb.phase);
        const uint32_t a0 = sb16 + ((OFF_A + (k < 4 ? ra.idx : NA) * SLOT_A + wg * 8192) >> 4);
        const uint32_t b0 = sb16 + ((OFF_B + rb.idx * SLOT_B + (k & 1) * 20480) >> 4);
        wg_fence();
#pragma unroll
        for (int kk = 0; kk < 4; kk++) {
          mma_ss160(acc, make_desc(a0, kk * 32, 16, 1024, 1), make_desc(b0, kk * 1024, 4096, 512, 2));
          if (kk == 0) {
            wg_commit();
            wg_wait<1>();
            if (k != 4) release(emptyA + 8 * pa);
          }
        }
        wg_commit();
        pa = ra.idx; pb = rb.idx;
        if (k < 4) ra.next<NA>();
        if ((k & 1) || k == 4) rb.next<NB>();
      }
      {
        mbar_wait(bars + 8 * B_XR, 0);
        const uint32_t xa = sb + OFF_B + (warp / 3) * SLOT_B + SPARE + (warp % 3) * 2560 + (lane >> 2) * 160 + t * 4;
#pragma unroll
        for (int g = 0; g < 10; g++) { xv[0][g] = lds32(xa + g * 16); xv[1][g] = lds32(xa + 1280 + g * 16); }
      }
      releaseB(emptyB + 8); releaseB(emptyB + 16);
      mbar_wait(bars + 8 * B_PEER2, 0);
      wg_wait<0>();
      fence_regs(acc);
      TSTAMP(7);
      {
        uint32_t sn[20];
        if (rank) {
#pragma unroll
          for (int e = 0; e < 20; e++) sn[e] = pack_bf16(acc[2 * e], acc[2 * e + 1]);
#pragma unroll
          for (int e = 0; e < 40; e++) acc[e] = acc[40 + e];
        } else {
#pragma unroll
          for (int e = 0; e < 20; e++) sn[e] = pack_bf16(acc[40 + 2 * e], acc[41 + 2 * e]);
        }
        const uint32_t peer = map_peer(sb, rank ^ 1);
#pragma unroll
        for (int q = 0; q < 5; q++)
          st_async16(peer + OFF_B + 20480 + tid * 16 + q * 4096, sn[4 * q], sn[4 * q + 1], sn[4 * q + 2], sn[4 * q + 3],
                     peer + OFF_BAR + 8 * (B_DSR + 8 + wg));
#pragma unroll
        for (int g = 0; g < 10; g++) {
          acc[4 * g] += bf_lo(xv[0][g]); acc[4 * g + 1] += bf_hi(xv[0][g]);
          acc[4 * g + 2] += bf_lo(xv[1][g]); acc[4 * g + 3] += bf_hi(xv[1][g]);
        }
        bar_sync(1, 256);
        mbar_wait(bars + 8 * (B_DSR + 8 + wg), 0);
#pragma unroll
        for (int q = 0; q < 5; q++) {
          const uint4 v = lds128(sb + OFF_B + 20480 + tid * 16 + q * 4096);
          float* d = &acc[8 * q];
          d[0] += bf_lo(v.x); d[1] += bf_hi(v.x); d[2] += bf_lo(v.y); d[3] += bf_hi(v.y);
          d[4] += bf_lo(v.z); d[5] += bf_hi(v.z); d[6] += bf_lo(v.w); d[7] += bf_hi(v.w);
          xv[0][2 * q] = pack_bf16(d[0], d[1]); xv[1][2 * q] = pack_bf16(d[2], d[3]);
          xv[0][2 * q + 1] = pack_bf16(d[4], d[5]); xv[1][2 * q + 1] = pack_bf16(d[6], d[7]);
        }
        releaseB(emptyB + 8 * pb);
      }
      TSTAMP(16);
      stage_tile(sb + OFF_STG, xv);
      signal(B_SIGX1);
      TSTAMP(17);
#pragma unroll
      for (int r = 0; r < 2; r++) {
        float s = 0.f;
#pragma unroll
        for (int g = 0; g < 10; g++) s += acc[4 * g + 2 * r] + acc[4 * g + 2 * r + 1];
        s += __shfl_xor_sync(0xffffffffu, s, 1); s += __shfl_xor_sync(0xffffffffu, s, 2);
        const float mu = s * (1.f / 80.f);
        float q = 0.f;
#pragma unroll
        for (int g = 0; g < 10; g++) {
          const float d0 = acc[4 * g + 2 * r] - mu, d1 = acc[4 * g + 2 * r + 1] - mu;
          q = fmaf(d0, d0, q); q = fmaf(d1, d1, q);
        }
        q += __shfl_xor_sync(0xffffffffu, q, 1); q += __shfl_xor_sync(0xffffffffu, q, 2);
        if (t == 0) g_st1[(128 * i + rloc + 8 * r) * 8 + j] = make_float2(mu, q);
      }
    }
    TSTAMP(8);
#pragma unroll
    for (int G = 0; G < 10; G++) { P[0][G] = qp[0][G]; P[1][G] = qp[1][G]; }
    }
    asm volatile("" : "+r"(pass));
    } while (pass-- != 0);

    uint32_t of[5][4];
    {
      mbar_wait(bars + 8 * B_KV, 0);
#pragma unroll 1
      for (int it = tid; it < 384; it += 256) {
        const int p = it >= 192, rem = it - 192 * p, n = rem >> 2, tq = rem & 3;
        const uint32_t sp = sb + OFF_A + SLOT_A + 4 * (p * KV_PAIR + (n < 40 ? n * 48 + tq * 12 : 1920 + tq * 24 + (n & 1) * 12));
        const uint4 ka = lds128(sp), kb = lds128(sp + 16), kc = lds128(sp + 32);
        const uint32_t v[10] = {ka.x, ka.y, ka.z, ka.w, kb.x, kb.y, kb.z, kb.w, kc.x, kc.y};
        const int sh = (n < 40 ? (n >= 20) : (n & 1)) * 16;
        uint8_t* dst = sgen + OFF_MISC + p * 7680 + n * 32 + tq * 4;
        const int sw = ((n >> 2) & 1) << 4;
#pragma unroll
        for (int G = 0; G < 10; G++)
          *reinterpret_cast<uint32_t*>(dst + (G >> 1) * 1536 + (((G & 1) << 4) ^ sw)) = pack_bf16(__uint_as_float(v[G]), 0.f) << sh;
      }
      release(emptyA + 8);
      fence_async_smem();
      bar_sync(1, 256);
      float o0[24], o1[24];
      wg_fence();
#pragma unroll
      for (int g = 0; g < 5; g++) {
        if (g == 0) mma_rs48_k_z(o0, fr[g], make_desc(sb16, OFF_MISC, 16, 256, 3));
        else mma_rs48_k(o0, fr[g], make_desc(sb16, OFF_MISC + g * 1536, 16, 256, 3));
      }
#pragma unroll
      for (int g = 0; g < 5; g++) {
        if (g == 0) mma_rs48_k_z(o1, fr[5], make_desc(sb16, OFF_MISC + 7680, 16, 256, 3));
        else mma_rs48_k(o1, fr[5 + g], make_desc(sb16, OFF_MISC + 7680 + g * 1536, 16, 256, 3));
      }
      wg_commit();
      wg_wait<0>();
      fence_regs(o0); fence_regs(o1);
      signal(B_MFREE);
#pragma unroll
      for (int r = 0; r < 2; r++) {
        const float a0 = __fdividef(st_g[r], o0[20 + 2 * r] + 1e-6f), a1 = __fdividef(st_g[r], o0[21 + 2 * r] + 1e-6f);
        const float b0 = __fdividef(st_g[r], o1[20 + 2 * r] + 1e-6f), b1 = __fdividef(st_g[r], o1[21 + 2 * r] + 1e-6f);
        const float am = t < 2 ? a0 : a1, bm = t < 2 ? b0 : b1;
#pragma unroll
        for (int g = 0; g < 5; g++) {
          const float sa = g < 2 ? a0 : (g == 2 ? am : a1), sb2 = g < 2 ? b0 : (g == 2 ? bm : b1);
          of[g >> 1][(g & 1) * 2 + r] = pack_bf16(o0[4 * g + 2 * r] * sa, o0[4 * g + 2 * r + 1] * sa);
          of[(5 + g) >> 1][((5 + g) & 1) * 2 + r] = pack_bf16(o1[4 * g + 2 * r] * sb2, o1[4 * g + 2 * r + 1] * sb2);
        }
      }
    }
    TSTAMP(9);

    uint32_t hf[12][4];
    float ac4[80];
    auto unit = [&](auto uc, uint32_t b0) {
      constexpr int u = decltype(uc)::value;
#pragma unroll
      for (int s = 0; s < (u ? 4 : 5); s++) {
        const uint64_t db = make_desc(b0, (u ? 5120 + 20480 * u : 0) + s * 1024, u ? 4096 : 5120, 512, 2);
        if (u == 0 && s == 0) mma_rs160_n_z(ac4, of[0], db);
        else if (u == 0) mma_rs160_n(ac4, of[s], db);
        else mma_rs160_n(ac4, hf[(4 * u + 8 + s) % 12], db);
      }
      wg_commit();
    };
    {
      float acc[96];
      uint32_t pa = 0, pb = 0;
#pragma unroll 1
      for (int k = 0; k < 10; k++) {
        mbar_wait(fullA + 8 * ra.idx, ra.phase);
        if (tid == 0) TRACE(52 + k);
        if ((k & 1) == 0) mbar_wait(fullB + 8 * rb.idx, rb.phase);
        if (tid == 0) TRACE(84 + k);
        if (k == 0) TSTAMP(10);
        const uint32_t a0 = sb16 + ((OFF_A + ra.idx * SLOT_A + wg * 8192) >> 4);
        const uint32_t b0 = sb16 + ((OFF_B + rb.idx * SLOT_B + (k & 1) * 24576) >> 4);
        wg_fence();
#pragma unroll
        for (int kk = 0; kk < 4; kk++) {
          if (kk == 0) mma_ss192_p(acc, make_desc(a0, 0, 16, 1024, 1), make_desc(b0, 0, 8192, 1024, 1), k);
          else mma_ss192(acc, make_desc(a0, kk * 32, 16, 1024, 1), make_desc(b0, kk * 2048, 8192, 1024, 1));
          if (kk == 0) {
            wg_commit();
            if (k > 0) {
              wg_wait<1>();
              release(emptyA + 8 * pa);
              if ((k & 1) == 0) releaseB(emptyB + 8 * pb);
            }
          }
        }
        wg_commit();
        pa = ra.idx; pb = rb.idx;
        ra.next<NA>();
        if (k & 1) rb.next<NB>();
      }
      float rs[2], mm[2];
      mbar_wait(bars + 8 * B_ST1, 0);
#pragma unroll
      for (int r = 0; r < 2; r++) {
        const uint4 su = lds128(sb + OFF_MISC + (rloc + 8 * r) * 64 + t * 16);
        const float m0 = __uint_as_float(su.x), m1 = __uint_as_float(su.z);
        float mu = m0 + m1;
        mu += __shfl_xor_sync(0xffffffffu, mu, 1); mu += __shfl_xor_sync(0xffffffffu, mu, 2);
        mu *= 0.125f;
        const float d0 = m0 - mu, d1 = m1 - mu;
        float q = __uint_as_float(su.y) + __uint_as_float(su.w) + 80.f * (d0 * d0 + d1 * d1);
        q += __shfl_xor_sync(0xffffffffu, q, 1); q += __shfl_xor_sync(0xffffffffu, q, 2);
        rs[r] = rsqrtf(q * (1.f / D_) + 1e-5f);
        mm[r] = -mu;
      }
      mbar_wait(bars + 8 * B_FULL4, 0);
      wg_fence();
      unit(IntC<0>{}, sb16);
      wg_wait<1>();
      fence_regs(acc);
      releaseB(emptyB + 8 * pb);
      release(bars + 8 * B_PEER);
      TSTAMP(11);
      const GeluC g0 = gelu_consts(rs[0], 1.f - st_g[0]), g1 = gelu_consts(rs[1], 1.f - st_g[1]);
#pragma unroll
      for (int g = 0; g < 24; g++) {
        const float2 cs = *reinterpret_cast<const float2*>(s_cs + 80 + 8 * g + 2 * t);
        const float v0 = gelu_s(fmaf(mm[0], cs.x, acc[4 * g]), g0), v1 = gelu_s(fmaf(mm[0], cs.y, acc[4 * g + 1]), g0);
        const float v2 = gelu_s(fmaf(mm[1], cs.x, acc[4 * g + 2]), g1), v3 = gelu_s(fmaf(mm[1], cs.y, acc[4 * g + 3]), g1);
        hf[g >> 1][(g & 1) * 2] = pack_bf16(v0, v1);
        hf[g >> 1][(g & 1) * 2 + 1] = pack_bf16(v2, v3);
        if (g == 7) { wg_fence(); unit(IntC<1>{}, sb16); }
        if (g == 15) { mbar_wait(bars + 8 * (B_FULL4 + 1), 0); wg_fence(); unit(IntC<2>{}, sb16); }
        if (g == 23) { wg_wait<1>(); signal(B_EMPTY4); wg_fence(); unit(IntC<3>{}, sb16); }
      }
    }
    TSTAMP(12);

    {
      float kp[40];
      uint32_t sn[20], kb[20];
      const uint32_t peer = map_peer(sb, rank ^ 1);
      const uint32_t tag = lds32(sb + OFF_BAR + 8 * NBAR);
      auto add8 = [&](int q, const uint4 v) {
        float* d = &kp[8 * q];
        d[0] += bf_lo(v.x); d[1] += bf_hi(v.x); d[2] += bf_lo(v.y); d[3] += bf_hi(v.y);
        d[4] += bf_lo(v.z); d[5] += bf_hi(v.z); d[6] += bf_lo(v.w); d[7] += bf_hi(v.w);
      };
      auto send = [&](int c) {
        const uint32_t dso = peer + OFF_DS + (c & 1) * 20480 + tid * 16, dsb = peer + OFF_BAR + 8 * (B_DSR + 2 * c + wg);
#pragma unroll
        for (int q = 0; q < 5; q++) st_async16(dso + q * 4096, sn[4 * q], sn[4 * q + 1], sn[4 * q + 2], sn[4 * q + 3], dsb);
      };
      mbar_wait(bars + 8 * B_PEER, 0);
      uint4* gdst = g_part + (size_t)i * 8 * 3840 + tid;
#pragma unroll 1
      for (int c = 0; c < 3; c++) {
        const uint32_t b0 = sb16 + ((c & 1) ? 0 : SET4 >> 4), bc = bars + 16 * c;
        mbar_wait(bc + 8 * (B_FULL4 + 2), 0);
        wg_wait<0>();
        fence_regs(ac4);
        if (rank) {
#pragma unroll
          for (int e = 0; e < 20; e++) { sn[e] = pack_bf16(ac4[2 * e], ac4[2 * e + 1]); kb[e] = pack_bf16(ac4[40 + 2 * e], ac4[41 + 2 * e]); }
        } else {
#pragma unroll
          for (int e = 0; e < 20; e++) { kb[e] = pack_bf16(ac4[2 * e], ac4[2 * e + 1]); sn[e] = pack_bf16(ac4[40 + 2 * e], ac4[41 + 2 * e]); }
        }
#pragma unroll
        for (int e = 0; e < 20; e++) asm volatile("" : "+r"(sn[e]), "+r"(kb[e]));
        send(c);
        if (c == 0 && wg == 1) bar_sync(2, 256);
        wg_fence();
        unit(IntC<0>{}, b0);
        if (lane == 0) mbar_arrive(bc + 8 * (B_EMPTY4 + 1));
        unit(IntC<1>{}, b0);
        if (c == 0 && wg == 0) bar_arrive(2, 256);
        {
          mbar_wait(bc + 8 * (B_DSR + wg), 0);
          uint4* dst = gdst + (((j + 2 * c + 2) & 7) * 3 + c) * 1280;
#pragma unroll
          for (int q = 0; q < 5; q++) {
            const uint4 v = lds128(sb + OFF_DS + (c & 1) * 20480 + tid * 16 + q * 4096);
            st_relaxed16(dst + q * 256, (add_bf2(v.x, kb[4 * q]) & ~1u) | tag, add_bf2(v.y, kb[4 * q + 1]),
                         add_bf2(v.z, kb[4 * q + 2]), add_bf2(v.w, kb[4 * q + 3]));
          }
        }
        mbar_wait(bc + 8 * (B_FULL4 + 3), 0);
        wg_fence();
        unit(IntC<2>{}, b0);
        wg_wait<1>();
        if (lane == 0) mbar_arrive(bc + 8 * (B_EMPTY4 + 2));
        unit(IntC<3>{}, b0);
      }
      auto partial = [&](int c, uint4 (&v)[5]) {
        mbar_wait(bars + 8 * (B_RDY + c), 0);
        uint32_t bad = 0;
#pragma unroll
        for (int q = 0; q < 5; q++) { v[q] = lds128(sb + (c ? 25600 + 20480 * c : 0) + tid * 16 + q * 4096); bad |= v[q].x ^ tag; }
#pragma unroll 1
        for (uint32_t n = 0; (bad & 1u) && n < (WAIT_LIMIT >> 2); n++) {
          bad = 0;
#pragma unroll
          for (int q = 0; q < 5; q++) { v[q] = ld_relaxed16(gdst + (j * 3 + c) * 1280 + q * 256); bad |= v[q].x ^ tag; }
        }
      };
      uint4 pa4[5], pb4[5];
      partial(0, pa4);
      wg_wait<0>();
      fence_regs(ac4);
      if (rank) {
#pragma unroll
        for (int e = 0; e < 20; e++) sn[e] = pack_bf16(ac4[2 * e], ac4[2 * e + 1]);
#pragma unroll
        for (int e = 0; e < 40; e++) kp[e] = ac4[40 + e];
      } else {
#pragma unroll
        for (int e = 0; e < 20; e++) sn[e] = pack_bf16(ac4[40 + 2 * e], ac4[41 + 2 * e]);
#pragma unroll
        for (int e = 0; e < 40; e++) kp[e] = ac4[e];
      }
      send(3);
      TSTAMP(13);
      {
        mbar_wait(bars + 8 * B_XR, 1);
        const float w0 = 1.f - st_g[0], w1s = 1.f - st_g[1];
        const uint32_t xa = sb + OFF_OUT + rloc * 160 + t * 4;
#pragma unroll
        for (int g = 0; g < 10; g++) {
          const uint32_t x0 = lds32(xa + g * 16), x1 = lds32(xa + 1280 + g * 16);
          kp[4 * g] = fmaf(w0, bf_lo(x0), kp[4 * g]); kp[4 * g + 1] = fmaf(w0, bf_hi(x0), kp[4 * g + 1]);
          kp[4 * g + 2] = fmaf(w1s, bf_lo(x1), kp[4 * g + 2]); kp[4 * g + 3] = fmaf(w1s, bf_hi(x1), kp[4 * g + 3]);
        }
      }
      partial(1, pb4);
#pragma unroll
      for (int q = 0; q < 5; q++)
        pa4[q] = make_uint4(add_bf2(pa4[q].x, pb4[q].x), add_bf2(pa4[q].y, pb4[q].y), add_bf2(pa4[q].z, pb4[q].z), add_bf2(pa4[q].w, pb4[q].w));
#pragma unroll
      for (int q = 0; q < 5; q++) add8(q, pa4[q]);
      partial(2, pb4);
      mbar_wait(bars + 8 * (B_DSR + 6 + wg), 0);
      TSTAMP(14);
#pragma unroll
      for (int q = 0; q < 5; q++) {
        const uint4 c = pb4[q], d = lds128(sb + OFF_DS + 20480 + tid * 16 + q * 4096);
        add8(q, make_uint4(add_bf2(c.x, d.x), add_bf2(c.y, d.y), add_bf2(c.z, d.z), add_bf2(c.w, d.w)));
      }
      __syncwarp();
      uint32_t ov[2][10];
#pragma unroll
      for (int g = 0; g < 10; g++) { ov[0][g] = pack_bf16(kp[4 * g], kp[4 * g + 1]); ov[1][g] = pack_bf16(kp[4 * g + 2], kp[4 * g + 3]); }
      stage_tile(sb + OFF_OUT, ov);
      __syncwarp();
      __nv_bfloat16* dst = out + (size_t)(128 * i + 16 * warp) * D_ + 80 * j;
#pragma unroll
      for (int q = 0; q < 5; q++) {
        const int id = q * 32 + lane, r = id / 10;
        *reinterpret_cast<uint4*>(dst + r * (D_ - 80) + id * 8) = lds128(sb + OFF_OUT + warp * 2560 + id * 16);
      }
    }
    TSTAMP(15);
    if (tid == 0) asm volatile("red.relaxed.gpu.global.add.u32 [%0], 1;" ::"l"(g_flags + FL_DONE * 32) : "memory");
  }
}

namespace {
typedef CUresult (*EncodeFn)(CUtensorMap*, CUtensorMapDataType, cuuint32_t, void*, const cuuint64_t*, const cuuint64_t*,
                             const cuuint32_t*, const cuuint32_t*, CUtensorMapInterleave, CUtensorMapSwizzle,
                             CUtensorMapL2promotion, CUtensorMapFloatOOBfill);

void encode(EncodeFn fn, CUtensorMap* m, const void* ptr, int rank, const cuuint64_t* dims, const cuuint64_t* strides,
            const cuuint32_t* box, CUtensorMapSwizzle swz) {
  cuuint32_t es[5] = {1, 1, 1, 1, 1};
  fn(m, CU_TENSOR_MAP_DATA_TYPE_BFLOAT16, rank, const_cast<void*>(ptr), dims, strides, box, es, CU_TENSOR_MAP_INTERLEAVE_NONE,
     swz, CU_TENSOR_MAP_L2_PROMOTION_L2_128B, CU_TENSOR_MAP_FLOAT_OOB_FILL_NONE);
}
}

extern "C" void kernel_launch(void* const* d_in, const int* in_sizes, int n_in, void* d_out, int out_size) {
  (void)in_sizes; (void)n_in; (void)out_size;
  const __nv_bfloat16* x = (const __nv_bfloat16*)d_in[0];
  const __nv_bfloat16* wqkv = (const __nv_bfloat16*)d_in[1];
  const __nv_bfloat16* wphi = (const __nv_bfloat16*)d_in[2];
  const __nv_bfloat16* wo = (const __nv_bfloat16*)d_in[3];
  const __nv_bfloat16* w1 = (const __nv_bfloat16*)d_in[5];
  const __nv_bfloat16* w2 = (const __nv_bfloat16*)d_in[6];
  const __nv_bfloat16* w3 = (const __nv_bfloat16*)d_in[7];
  const __nv_bfloat16* w4 = (const __nv_bfloat16*)d_in[8];
  const __nv_bfloat16* gate_w = (const __nv_bfloat16*)d_in[9];

  static EncodeFn enc = nullptr;
  static void *pHs = nullptr, *pX1 = nullptr;
  if (!enc) {
    cudaDriverEntryPointQueryResult qr;
    cudaGetDriverEntryPoint("cuTensorMapEncodeTiled", (void**)&enc, cudaEnableDefault, &qr);
    cudaGetSymbolAddress(&pHs, g_Hs);
    cudaGetSymbolAddress(&pX1, g_X1);
    cudaFuncSetAttribute(fused_kernel, cudaFuncAttributeMaxDynamicSharedMemorySize, SMEM_BYTES);
  }
  Maps m;
  {
    cuuint64_t dims[2] = {D_, S_}, str[1] = {D_ * 2};
    cuuint32_t box[2] = {64, 128}, boxh[2] = {64, 64};
    encode(enc, &m.x, x, 2, dims, str, boxh, CU_TENSOR_MAP_SWIZZLE_128B);
    encode(enc, &m.hs, (const char*)pHs + 2 * D_ * 2, 2, dims, str, box, CU_TENSOR_MAP_SWIZZLE_128B);
    encode(enc, &m.x1, pX1, 2, dims, str, boxh, CU_TENSOR_MAP_SWIZZLE_128B);
    cuuint32_t boxr[2] = {80, 16}, boxs[2] = {80, 128};
    cuuint64_t dimsp[2] = {D_, S_ + 4};
    encode(enc, &m.st_h, pHs, 2, dimsp, str, boxs, CU_TENSOR_MAP_SWIZZLE_NONE);
    encode(enc, &m.st_x1, pX1, 2, dims, str, boxs, CU_TENSOR_MAP_SWIZZLE_NONE);
    encode(enc, &m.xr, x, 2, dims, str, boxr, CU_TENSOR_MAP_SWIZZLE_NONE);
  }
  {
    cuuint64_t dims[3] = {80, D_, 8}, str[2] = {D_ * 2, 160};
    cuuint32_t boxm[3] = {64, 64, 1}, boxr[3] = {16, 64, 1};
    encode(enc, &m.w1m, w1, 3, dims, str, boxm, CU_TENSOR_MAP_SWIZZLE_128B);
    encode(enc, &m.w1r, w1, 3, dims, str, boxr, CU_TENSOR_MAP_SWIZZLE_32B);
  }
  {
    cuuint64_t dims[4] = {80, D_, 3, 8}, str[3] = {3 * D_ * 2, D_ * 2, 160};
    cuuint32_t boxm[4] = {64, 64, 3, 1}, boxr[4] = {16, 64, 3, 1};
    encode(enc, &m.qm, wqkv, 4, dims, str, boxm, CU_TENSOR_MAP_SWIZZLE_128B);
    encode(enc, &m.qr, wqkv, 4, dims, str, boxr, CU_TENSOR_MAP_SWIZZLE_32B);
  }
  {
    cuuint64_t dims[3] = {32, D_, 20}, dims4[3] = {32, F_, 20}, str[2] = {D_ * 2, 64};
    cuuint32_t box4[3] = {32, 64, 5}, boxo[3] = {32, 80, 5};
    encode(enc, &m.w4, w4, 3, dims4, str, box4, CU_TENSOR_MAP_SWIZZLE_64B);
    encode(enc, &m.wo, wo, 3, dims, str, boxo, CU_TENSOR_MAP_SWIZZLE_64B);
    encode(enc, &m.w2, w2, 3, dims, str, box4, CU_TENSOR_MAP_SWIZZLE_64B);
  }
  {
    cuuint64_t dims[3] = {64, D_, 24}, str[2] = {F_ * 2, 128};
    cuuint32_t box[3] = {64, 64, 3};
    encode(enc, &m.w3, w3, 3, dims, str, box, CU_TENSOR_MAP_SWIZZLE_128B);
  }
  fused_kernel<<<NCTA + NSVC, 384, SMEM_BYTES, cudaStreamPerThread>>>(m, x, wqkv, wphi, w1, w2, w3, w4, wo, gate_w, (__nv_bfloat16*)d_out);
}
```

```cpp
#include <cuda_runtime.h>
#include <cuda_bf16.h>
#include <cuda.h>
#include <stdint.h>

namespace {

constexpr int S_ = 2048, D_ = 640, F_ = 1536;
constexpr int NCTA = 128, NSVC = 4;
constexpr int KV_PAIR = 40 * 48 + 96;
constexpr int KV_J = 2 * KV_PAIR;

constexpr int SLOT_B = 49152, NB = 3;
constexpr int SLOT_A = 16384, NA = 4;
constexpr int OFF_B = 0;
constexpr int OFF_A = OFF_B + NB * SLOT_B;
constexpr int OFF_STG = OFF_A + 2 * SLOT_A;
constexpr int OFF_MISC = OFF_A + NA * SLOT_A;
constexpr int OFF_XST = OFF_MISC + 13312;
constexpr int OFF_CS = OFF_MISC + 16384;
constexpr int OFF_BAR = OFF_CS + 1088;
constexpr int SMEM_BYTES = OFF_BAR + 512 + 512 + 128;
constexpr int B_FULLA = 0, B_FULLB = 4, B_CS = 7, B_XR = 8, B_KV = 9, B_ST1 = 10, B_HST = 11, B_FULL4 = 12  , B_RDY = 20  , B_T4 = 23, B_KVR = 24,
              B_DSR = 25  , B_EMPTYB = 35  , B_SIGP = 38, B_SIGH = 39, B_SIGKV = 40, B_SIGX1 = 41, B_MFREE = 42,
              B_WDEAD = 43, B_EMPTY4 = 44  , B_EMPTYA = 52  , B_PEER = 56, B_PEER2 = 57, B_X1P = 58  , NBAR = 59;
constexpr int SPARE = 40960;
constexpr int SET4 = 87040, OFF_DS = 2 * SET4, OFF_OUT = 20480;

constexpr int FL_DONE = 0, FL_H = 1  , FL_X1 = FL_H + 32, FL_KV = FL_X1 + 16, FL_CS = FL_KV + 8, FL_CS3 = FL_CS + 1, FL_ST = FL_CS3 + 1;
constexpr int FL_S1 = FL_ST + 16, FL_COUNT = FL_S1 + 16;

struct Maps {
  CUtensorMap x, w1m, w1r, qm, qr, hs, w2, x1, w3, w4, wo, xr, st_h, st_x1;
};

}

__device__ __align__(1024) __nv_bfloat16 g_Hs[(S_ + 4) * D_];
__device__ __align__(1024) __nv_bfloat16 g_X1[S_ * D_];
__device__ __align__(128) float g_acc[2][8 * KV_J];
__device__ __align__(128) float g_cs[2][D_ + F_];
__device__ __align__(128) uint4 g_wphi[8 * 800];
__device__ __align__(128) float4 g_xstat[S_];
__device__ __align__(128) float2 g_st1[S_ * 8];
__device__ __align__(128) uint4 g_part[16 * 8 * 3 * 1280];
__device__ __align__(128) unsigned g_flags[FL_COUNT * 32];
#define TSTAMP(n) do {} while (0)
#define TSTAMPX(n) do {} while (0)
#define TRACE(n) do {} while (0)
#define TRS(n) do {} while (0)

namespace {

__device__ __forceinline__ long long gtime() { long long t; asm volatile("mov.u64 %0, %%globaltimer;" : "=l"(t)); return t; }
__device__ __forceinline__ uint32_t smem_u32(const void* p) { return (uint32_t)__cvta_generic_to_shared(p); }
__device__ __forceinline__ void mbar_init(uint32_t bar, int cnt) {
  asm volatile("mbarrier.init.shared::cta.b64 [%0], %1;" ::"r"(bar), "r"(cnt) : "memory");
}
__device__ __forceinline__ void mbar_expect_tx(uint32_t bar, int bytes) {
  asm volatile("mbarrier.arrive.expect_tx.shared::cta.b64 _, [%0], %1;" ::"r"(bar), "r"(bytes) : "memory");
}
__device__ __forceinline__ void mbar_arrive_cta(uint32_t bar, uint32_t cta) {
  asm volatile("{\n.reg .b32 ra;\nmapa.shared::cluster.u32 ra, %0, %1;\nmbarrier.arrive.shared::cluster.b64 _, [ra];\n}"
               ::"r"(bar), "r"(cta) : "memory");
}
__device__ __forceinline__ uint32_t mbar_try(uint32_t bar, uint32_t parity) {
  uint32_t ok;
  asm volatile("{\n.reg .pred p;\nmbarrier.try_wait.parity.shared::cta.b64 p, [%1], %2;\nselp.u32 %0, 1, 0, p;\n}"
               : "=r"(ok) : "r"(bar), "r"(parity) : "memory");
  return ok;
}
constexpr uint32_t WAIT_LIMIT = 1u << 18;
__device__ __forceinline__ void mbar_wait(uint32_t bar, uint32_t parity) {
  uint32_t n = 0;
  while (!mbar_try(bar, parity) && ++n < WAIT_LIMIT) {}
}
__device__ __forceinline__ unsigned ld_acquire(const unsigned* p) {
  unsigned v;
  asm volatile("ld.acquire.gpu.global.u32 %0, [%1];" : "=r"(v) : "l"(p) : "memory");
  return v;
}
__device__ __forceinline__ void flag_wait(int idx, unsigned target) {
  const unsigned* p = g_flags + idx * 32;
  uint32_t n = 0;
  while ((int)(ld_acquire(p) - target) < 0 && ++n < (WAIT_LIMIT >> 2)) {}
}
__device__ __forceinline__ void flag_add(int idx) {
  asm volatile("red.release.gpu.global.add.u32 [%0], 1;" ::"l"(g_flags + idx * 32) : "memory");
}
__device__ __forceinline__ void flag_add_relaxed(int idx) {
  asm volatile("red.relaxed.gpu.global.add.u32 [%0], 1;" ::"l"(g_flags + idx * 32) : "memory");
}
__device__ __forceinline__ uint32_t mbar_test(uint32_t bar, uint32_t parity) {
  uint32_t ok;
  asm volatile("{\n.reg .pred p;\nmbarrier.test_wait.parity.shared::cta.b64 p, [%1], %2;\nselp.u32 %0, 1, 0, p;\n}"
               : "=r"(ok) : "r"(bar), "r"(parity) : "memory");
  return ok;
}
__device__ __forceinline__ uint32_t lds32(uint32_t a) {
  uint32_t v;
  asm volatile("ld.shared.u32 %0, [%1];" : "=r"(v) : "r"(a) : "memory");
  return v;
}
__device__ __forceinline__ void mbar_arrive(uint32_t bar) {
  asm volatile("mbarrier.arrive.shared::cta.b64 _, [%0];" ::"r"(bar) : "memory");
}
__device__ __forceinline__ void fence_async_glb() { asm volatile("fence.proxy.async.global;" ::: "memory"); }
__device__ __forceinline__ void fence_async_smem() { asm volatile("fence.proxy.async.shared::cta;" ::: "memory"); }
__device__ __forceinline__ void bar_sync(int id, int n) { asm volatile("bar.sync %0, %1;" ::"r"(id), "r"(n) : "memory"); }

__device__ __forceinline__ void tma2d(uint32_t dst, const CUtensorMap* m, uint32_t bar, int c0, int c1) {
  asm volatile("cp.async.bulk.tensor.2d.shared::cluster.global.mbarrier::complete_tx::bytes [%0], [%1, {%3, %4}], [%2];"
               ::"r"(dst), "l"(m), "r"(bar), "r"(c0), "r"(c1) : "memory");
}
__device__ __forceinline__ void tma2d_mc(uint32_t dst, const CUtensorMap* m, uint32_t bar, int c0, int c1) {
  asm volatile("cp.async.bulk.tensor.2d.shared::cluster.global.mbarrier::complete_tx::bytes.multicast::cluster"
               " [%0], [%1, {%3, %4}], [%2], %5;"
               ::"r"(dst), "l"(m), "r"(bar), "r"(c0), "r"(c1), "h"((uint16_t)3) : "memory");
}
__device__ __forceinline__ void tma3d(uint32_t dst, const CUtensorMap* m, uint32_t bar, int c0, int c1, int c2) {
  asm volatile("cp.async.bulk.tensor.3d.shared::cluster.global.mbarrier::complete_tx::bytes [%0], [%1, {%3, %4, %5}], [%2];"
               ::"r"(dst), "l"(m), "r"(bar), "r"(c0), "r"(c1), "r"(c2) : "memory");
}
__device__ __forceinline__ void tma4d(uint32_t dst, const CUtensorMap* m, uint32_t bar, int c0, int c1, int c2, int c3) {
  asm volatile("cp.async.bulk.tensor.4d.shared::cluster.global.mbarrier::complete_tx::bytes [%0], [%1, {%3, %4, %5, %6}], [%2];"
               ::"r"(dst), "l"(m), "r"(bar), "r"(c0), "r"(c1), "r"(c2), "r"(c3) : "memory");
}
__device__ __forceinline__ void tma2d_store(const CUtensorMap* m, uint32_t src, int c0, int c1) {
  asm volatile("cp.async.bulk.tensor.2d.global.shared::cta.bulk_group [%0, {%2, %3}], [%1];"
               ::"l"(m), "r"(src), "r"(c0), "r"(c1) : "memory");
}
__device__ __forceinline__ void bulk_store(void* dst, uint32_t src, uint32_t bytes) {
  asm volatile("cp.async.bulk.global.shared::cta.bulk_group [%0], [%1], %2;" ::"l"(dst), "r"(src), "r"(bytes) : "memory");
}
__device__ __forceinline__ void bulk_load(uint32_t dst, const void* src, uint32_t bytes, uint32_t bar) {
  asm volatile("cp.async.bulk.shared::cluster.global.mbarrier::complete_tx::bytes [%0], [%1], %2, [%3];"
               ::"r"(dst), "l"(src), "r"(bytes), "r"(bar) : "memory");
}
__device__ __forceinline__ void bulk_commit() { asm volatile("cp.async.bulk.commit_group;" ::: "memory"); }
template <int N> __device__ __forceinline__ void bulk_wait() { asm volatile("cp.async.bulk.wait_group %0;" ::"n"(N) : "memory"); }
__device__ __forceinline__ void bulk_wait_read() { asm volatile("cp.async.bulk.wait_group.read 0;" ::: "memory"); }
__device__ __forceinline__ void bar_arrive(int id, int n) { asm volatile("bar.arrive %0, %1;" ::"r"(id), "r"(n) : "memory"); }
__device__ __forceinline__ uint4 lds128(uint32_t a) {
  uint4 v;
  asm volatile("ld.shared.v4.u32 {%0, %1, %2, %3}, [%4];" : "=r"(v.x), "=r"(v.y), "=r"(v.z), "=r"(v.w) : "r"(a) : "memory");
  return v;
}
__device__ __forceinline__ void sts128(uint32_t a, uint4 v) {
  asm volatile("st.shared.v4.u32 [%0], {%1, %2, %3, %4};" ::"r"(a), "r"(v.x), "r"(v.y), "r"(v.z), "r"(v.w) : "memory");
}
__device__ __forceinline__ uint4 ld_relaxed16(const uint4* p) {
  uint4 v;
  asm volatile("ld.relaxed.gpu.global.v4.u32 {%0, %1, %2, %3}, [%4];" : "=r"(v.x), "=r"(v.y), "=r"(v.z), "=r"(v.w) : "l"(p) : "memory");
  return v;
}
__device__ __forceinline__ void st_relaxed16(uint4* p, uint32_t a, uint32_t b, uint32_t c, uint32_t d) {
  asm volatile("st.relaxed.gpu.global.v4.u32 [%0], {%1, %2, %3, %4};" ::"l"(p), "r"(a), "r"(b), "r"(c), "r"(d) : "memory");
}
__device__ __forceinline__ uint32_t map_peer(uint32_t addr, uint32_t cta) {
  uint32_t r;
  asm("mapa.shared::cluster.u32 %0, %1, %2;" : "=r"(r) : "r"(addr), "r"(cta));
  return r;
}
__device__ __forceinline__ void st_async16(uint32_t addr, uint32_t a, uint32_t b, uint32_t c, uint32_t d, uint32_t bar) {
  asm volatile("st.async.weak.shared::cluster.mbarrier::complete_tx::bytes.v4.b32 [%0], {%1, %2, %3, %4}, [%5];"
               ::"r"(addr), "r"(a), "r"(b), "r"(c), "r"(d), "r"(bar) : "memory");
}
__device__ __forceinline__ void l2_prefetch(const void* p, uint32_t bytes) {
  asm volatile("cp.async.bulk.prefetch.L2.global [%0], %1;" ::"l"(p), "r"(bytes) : "memory");
}
__device__ __forceinline__ void prefetch_tmap(const CUtensorMap* m) {
  asm volatile("prefetch.tensormap [%0];" ::"l"(m) : "memory");
}
__device__ __forceinline__ uint64_t make_desc(uint32_t a16, uint32_t off, uint32_t lbo, uint32_t sbo, uint32_t swz) {
  const uint32_t lo = a16 + ((off >> 4) + ((lbo >> 4) << 16)), hi = (sbo >> 4) | (swz << 30);
  uint64_t d;
  asm("mov.b64 %0, {%1, %2};" : "=l"(d) : "r"(lo), "r"(hi));
  return d;
}
__device__ __forceinline__ void wg_fence() { asm volatile("wgmma.fence.sync.aligned;" ::: "memory"); }
__device__ __forceinline__ void wg_commit() { asm volatile("wgmma.commit_group.sync.aligned;" ::: "memory"); }
template <int N> __device__ __forceinline__ void wg_wait() { asm volatile("wgmma.wait_group.sync.aligned %0;" ::"n"(N) : "memory"); }
template <int N> __device__ __forceinline__ void fence_regs(float (&d)[N]) {
#pragma unroll
  for (int i = 0; i < N; i++) asm volatile("" : "+f"(d[i])::"memory");
}
template <int N> __device__ __forceinline__ void zero_regs(float (&d)[N]) {
#pragma unroll
  for (int i = 0; i < N; i++) d[i] = 0.f;
}
__device__ __forceinline__ uint32_t pack_bf16(float lo, float hi) {
  uint32_t r;
  asm("cvt.rn.bf16x2.f32 %0, %1, %2;" : "=r"(r) : "f"(hi), "f"(lo));
  return r;
}
__device__ __forceinline__ float bf_lo(uint32_t v) { return __uint_as_float(v << 16); }
__device__ __forceinline__ float bf_hi(uint32_t v) { return __uint_as_float(v & 0xffff0000u); }
__device__ __forceinline__ uint32_t max_bf2(uint32_t a, uint32_t b) {
  uint32_t r; asm("max.bf16x2 %0, %1, %2;" : "=r"(r) : "r"(a), "r"(b)); return r;
}
__device__ __forceinline__ uint32_t min_bf2(uint32_t a, uint32_t b) {
  uint32_t r; asm("min.bf16x2 %0, %1, %2;" : "=r"(r) : "r"(a), "r"(b)); return r;
}
__device__ __forceinline__ uint32_t add_bf2(uint32_t a, uint32_t b) {
  uint32_t r; asm("add.rn.bf16x2 %0, %1, %2;" : "=r"(r) : "r"(a), "r"(b)); return r;
}
__device__ __forceinline__ float ex2(float x) { float r; asm("ex2.approx.ftz.f32 %0, %1;" : "=f"(r) : "f"(x)); return r; }
__device__ __forceinline__ float rcp(float x) { float r; asm("rcp.approx.ftz.f32 %0, %1;" : "=f"(r) : "f"(x)); return r; }
__device__ __forceinline__ float tanh_ap(float x) { float r; asm("tanh.approx.f32 %0, %1;" : "=f"(r) : "f"(x)); return r; }
struct GeluC { float c0, c1, ch; };
__device__ __forceinline__ GeluC gelu_consts(float rstd, float scale) {
  return GeluC{0.7978845608f * rstd, 0.0356774081f * rstd * rstd * rstd, 0.5f * scale * rstd};
}
__device__ __forceinline__ float gelu_s(float y, const GeluC& c) {
  const float u = y * fmaf(y * y, c.c1, c.c0);
  const float hx = y * c.ch;
  return fmaf(hx, tanh_ap(u), hx);
}
__device__ __forceinline__ void stsm4(uint32_t addr, uint32_t r0, uint32_t r1, uint32_t r2, uint32_t r3) {
  asm volatile("stmatrix.sync.aligned.m8n8.x4.shared.b16 [%0], {%1, %2, %3, %4};"
               ::"r"(addr), "r"(r0), "r"(r1), "r"(r2), "r"(r3) : "memory");
}

__device__ __forceinline__ void red_add4(float* p, float a, float b, float c, float d) {
  asm volatile("red.global.add.v4.f32 [%0], {%1, %2, %3, %4};" ::"l"(p), "f"(a), "f"(b), "f"(c), "f"(d) : "memory");
}

__device__ __forceinline__ void mma_ss256(float (&d)[128], uint64_t descA, uint64_t descB) {
  asm volatile("wgmma.mma_async.sync.aligned.m64n256k16.f32.bf16.bf16 {"
      "%0, %1, %2, %3, %4, %5, %6, %7, %8, %9, %10, %11, %12, %13, %14, %15, "
      "%16, %17, %18, %19, %20, %21, %22, %23, %24, %25, %26, %27, %28, %29, %30, %31, "
      "%32, %33, %34, %35, %36, %37, %38, %39, %40, %41, %42, %43, %44, %45, %46, %47, "
      "%48, %49, %50, %51, %52, %53, %54, %55, %56, %57, %58, %59, %60, %61, %62, %63, "
      "%64, %65, %66, %67, %68, %69, %70, %71, %72, %73, %74, %75, %76, %77, %78, %79, "
      "%80, %81, %82, %83, %84, %85, %86, %87, %88, %89, %90, %91, %92, %93, %94, %95, "
      "%96, %97, %98, %99, %100, %101, %102, %103, %104, %105, %106, %107, %108, %109, %110, %111, "
      "%112, %113, %114, %115, %116, %117, %118, %119, %120, %121, %122, %123, %124, %125, %126, %127"
      "}, %128, %129, 1, 1, 1, 0, 1;\n"
      : "+f"(d[0]), "+f"(d[1]), "+f"(d[2]), "+f"(d[3]), "+f"(d[4]), "+f"(d[5]), "+f"(d[6]), "+f"(d[7]),
        "+f"(d[8]), "+f"(d[9]), "+f"(d[10]), "+f"(d[11]), "+f"(d[12]), "+f"(d[13]), "+f"(d[14]), "+f"(d[15]),
        "+f"(d[16]), "+f"(d[17]), "+f"(d[18]), "+f"(d[19]), "+f"(d[20]), "+f"(d[21]), "+f"(d[22]), "+f"(d[23]),
        "+f"(d[24]), "+f"(d[25]), "+f"(d[26]), "+f"(d[27]), "+f"(d[28]), "+f"(d[29]), "+f"(d[30]), "+f"(d[31]),
        "+f"(d[32]), "+f"(d[33]), "+f"(d[34]), "+f"(d[35]), "+f"(d[36]), "+f"(d[37]), "+f"(d[38]), "+f"(d[39]),
        "+f"(d[40]), "+f"(d[41]), "+f"(d[42]), "+f"(d[43]), "+f"(d[44]), "+f"(d[45]), "+f"(d[46]), "+f"(d[47]),
        "+f"(d[48]), "+f"(d[49]), "+f"(d[50]), "+f"(d[51]), "+f"(d[52]), "+f"(d[53]), "+f"(d[54]), "+f"(d[55]),
        "+f"(d[56]), "+f"(d[57]), "+f"(d[58]), "+f"(d[59]), "+f"(d[60]), "+f"(d[61]), "+f"(d[62]), "+f"(d[63]),
        "+f"(d[64]), "+f"(d[65]), "+f"(d[66]), "+f"(d[67]), "+f"(d[68]), "+f"(d[69]), "+f"(d[70]), "+f"(d[71]),
        "+f"(d[72]), "+f"(d[73]), "+f"(d[74]), "+f"(d[75]), "+f"(d[76]), "+f"(d[77]), "+f"(d[78]), "+f"(d[79]),
        "+f"(d[80]), "+f"(d[81]), "+f"(d[82]), "+f"(d[83]), "+f"(d[84]), "+f"(d[85]), "+f"(d[86]), "+f"(d[87]),
        "+f"(d[88]), "+f"(d[89]), "+f"(d[90]), "+f"(d[91]), "+f"(d[92]), "+f"(d[93]), "+f"(d[94]), "+f"(d[95]),
        "+f"(d[96]), "+f"(d[97]), "+f"(d[98]), "+f"(d[99]), "+f"(d[100]), "+f"(d[101]), "+f"(d[102]), "+f"(d[103]),
        "+f"(d[104]), "+f"(d[105]), "+f"(d[106]), "+f"(d[107]), "+f"(d[108]), "+f"(d[109]), "+f"(d[110]), "+f"(d[111]),
        "+f"(d[112]), "+f"(d[113]), "+f"(d[114]), "+f"(d[115]), "+f"(d[116]), "+f"(d[117]), "+f"(d[118]), "+f"(d[119]),
        "+f"(d[120]), "+f"(d[121]), "+f"(d[122]), "+f"(d[123]), "+f"(d[124]), "+f"(d[125]), "+f"(d[126]), "+f"(d[127])
      : "l"(descA), "l"(descB));
}
__device__ __forceinline__ void mma_ss256_p(float (&d)[128], uint64_t descA, uint64_t descB, int acc) {
  asm volatile("{\n.reg .pred p;\nsetp.ne.b32 p, %130, 0;\n"
      "wgmma.mma_async.sync.aligned.m64n256k16.f32.bf16.bf16 {"
      "%0, %1, %2, %3, %4, %5, %6, %7, %8, %9, %10, %11, %12, %13, %14, %15, "
      "%16, %17, %18, %19, %20, %21, %22, %23, %24, %25, %26, %27, %28, %29, %30, %31, "
      "%32, %33, %34, %35, %36, %37, %38, %39, %40, %41, %42, %43, %44, %45, %46, %47, "
      "%48, %49, %50, %51, %52, %53, %54, %55, %56, %57, %58, %59, %60, %61, %62, %63, "
      "%64, %65, %66, %67, %68, %69, %70, %71, %72, %73, %74, %75, %76, %77, %78, %79, "
      "%80, %81, %82, %83, %84, %85, %86, %87, %88, %89, %90, %91, %92, %93, %94, %95, "
      "%96, %97, %98, %99, %100, %101, %102, %103, %104, %105, %106, %107, %108, %109, %110, %111, "
      "%112, %113, %114, %115, %116, %117, %118, %119, %120, %121, %122, %123, %124, %125, %126, %127"
      "}, %128, %129, p, 1, 1, 0, 1;\n}\n"
      : "+f"(d[0]), "+f"(d[1]), "+f"(d[2]), "+f"(d[3]), "+f"(d[4]), "+f"(d[5]), "+f"(d[6]), "+f"(d[7]),
        "+f"(d[8]), "+f"(d[9]), "+f"(d[10]), "+f"(d[11]), "+f"(d[12]), "+f"(d[13]), "+f"(d[14]), "+f"(d[15]),
        "+f"(d[16]), "+f"(d[17]), "+f"(d[18]), "+f"(d[19]), "+f"(d[20]), "+f"(d[21]), "+f"(d[22]), "+f"(d[23]),
        "+f"(d[24]), "+f"(d[25]), "+f"(d[26]), "+f"(d[27]), "+f"(d[28]), "+f"(d[29]), "+f"(d[30]), "+f"(d[31]),
        "+f"(d[32]), "+f"(d[33]), "+f"(d[34]), "+f"(d[35]), "+f"(d[36]), "+f"(d[37]), "+f"(d[38]), "+f"(d[39]),
        "+f"(d[40]), "+f"(d[41]), "+f"(d[42]), "+f"(d[43]), "+f"(d[44]), "+f"(d[45]), "+f"(d[46]), "+f"(d[47]),
        "+f"(d[48]), "+f"(d[49]), "+f"(d[50]), "+f"(d[51]), "+f"(d[52]), "+f"(d[53]), "+f"(d[54]), "+f"(d[55]),
        "+f"(d[56]), "+f"(d[57]), "+f"(d[58]), "+f"(d[59]), "+f"(d[60]), "+f"(d[61]), "+f"(d[62]), "+f"(d[63]),
        "+f"(d[64]), "+f"(d[65]), "+f"(d[66]), "+f"(d[67]), "+f"(d[68]), "+f"(d[69]), "+f"(d[70]), "+f"(d[71]),
        "+f"(d[72]), "+f"(d[73]), "+f"(d[74]), "+f"(d[75]), "+f"(d[76]), "+f"(d[77]), "+f"(d[78]), "+f"(d[79]),
        "+f"(d[80]), "+f"(d[81]), "+f"(d[82]), "+f"(d[83]), "+f"(d[84]), "+f"(d[85]), "+f"(d[86]), "+f"(d[87]),
        "+f"(d[88]), "+f"(d[89]), "+f"(d[90]), "+f"(d[91]), "+f"(d[92]), "+f"(d[93]), "+f"(d[94]), "+f"(d[95]),
        "+f"(d[96]), "+f"(d[97]), "+f"(d[98]), "+f"(d[99]), "+f"(d[100]), "+f"(d[101]), "+f"(d[102]), "+f"(d[103]),
        "+f"(d[104]), "+f"(d[105]), "+f"(d[106]), "+f"(d[107]), "+f"(d[108]), "+f"(d[109]), "+f"(d[110]), "+f"(d[111]),
        "+f"(d[112]), "+f"(d[113]), "+f"(d[114]), "+f"(d[115]), "+f"(d[116]), "+f"(d[117]), "+f"(d[118]), "+f"(d[119]),
        "+f"(d[120]), "+f"(d[121]), "+f"(d[122]), "+f"(d[123]), "+f"(d[124]), "+f"(d[125]), "+f"(d[126]), "+f"(d[127])
      : "l"(descA), "l"(descB), "r"(acc));
}

__device__ __forceinline__ void mma_ss64(float (&d)[32], uint64_t descA, uint64_t descB) {
  asm volatile("wgmma.mma_async.sync.aligned.m64n64k16.f32.bf16.bf16 {"
      "%0, %1, %2, %3, %4, %5, %6, %7, %8, %9, %10, %11, %12, %13, %14, %15, "
      "%16, %17, %18, %19, %20, %21, %22, %23, %24, %25, %26, %27, %28, %29, %30, %31"
      "}, %32, %33, 1, 1, 1, 0, 1;\n"
      : "+f"(d[0]), "+f"(d[1]), "+f"(d[2]), "+f"(d[3]), "+f"(d[4]), "+f"(d[5]), "+f"(d[6]), "+f"(d[7]),
        "+f"(d[8]), "+f"(d[9]), "+f"(d[10]), "+f"(d[11]), "+f"(d[12]), "+f"(d[13]), "+f"(d[14]), "+f"(d[15]),
        "+f"(d[16]), "+f"(d[17]), "+f"(d[18]), "+f"(d[19]), "+f"(d[20]), "+f"(d[21]), "+f"(d[22]), "+f"(d[23]),
        "+f"(d[24]), "+f"(d[25]), "+f"(d[26]), "+f"(d[27]), "+f"(d[28]), "+f"(d[29]), "+f"(d[30]), "+f"(d[31])
      : "l"(descA), "l"(descB));
}
__device__ __forceinline__ void mma_ss64_p(float (&d)[32], uint64_t descA, uint64_t descB, int acc) {
  asm volatile("{\n.reg .pred p;\nsetp.ne.b32 p, %34, 0;\n"
      "wgmma.mma_async.sync.aligned.m64n64k16.f32.bf16.bf16 {"
      "%0, %1, %2, %3, %4, %5, %6, %7, %8, %9, %10, %11, %12, %13, %14, %15, "
      "%16, %17, %18, %19, %20, %21, %22, %23, %24, %25, %26, %27, %28, %29, %30, %31"
      "}, %32, %33, p, 1, 1, 0, 1;\n}\n"
      : "+f"(d[0]), "+f"(d[1]), "+f"(d[2]), "+f"(d[3]), "+f"(d[4]), "+f"(d[5]), "+f"(d[6]), "+f"(d[7]),
        "+f"(d[8]), "+f"(d[9]), "+f"(d[10]), "+f"(d[11]), "+f"(d[12]), "+f"(d[13]), "+f"(d[14]), "+f"(d[15]),
        "+f"(d[16]), "+f"(d[17]), "+f"(d[18]), "+f"(d[19]), "+f"(d[20]), "+f"(d[21]), "+f"(d[22]), "+f"(d[23]),
        "+f"(d[24]), "+f"(d[25]), "+f"(d[26]), "+f"(d[27]), "+f"(d[28]), "+f"(d[29]), "+f"(d[30]), "+f"(d[31])
      : "l"(descA), "l"(descB), "r"(acc));
}

__device__ __forceinline__ void mma_ss160(float (&d)[80], uint64_t descA, uint64_t descB) {
  asm volatile("wgmma.mma_async.sync.aligned.m64n160k16.f32.bf16.bf16 {"
      "%0, %1, %2, %3, %4, %5, %6, %7, %8, %9, %10, %11, %12, %13, %14, %15, "
      "%16, %17, %18, %19, %20, %21, %22, %23, %24, %25, %26, %27, %28, %29, %30, %31, "
      "%32, %33, %34, %35, %36, %37, %38, %39, %40, %41, %42, %43, %44, %45, %46, %47, "
      "%48, %49, %50, %51, %52, %53, %54, %55, %56, %57, %58, %59, %60, %61, %62, %63, "
      "%64, %65, %66, %67, %68, %69, %70, %71, %72, %73, %74, %75, %76, %77, %78, %79"
      "}, %80, %81, 1, 1, 1, 0, 1;\n"
      : "+f"(d[0]), "+f"(d[1]), "+f"(d[2]), "+f"(d[3]), "+f"(d[4]), "+f"(d[5]), "+f"(d[6]), "+f"(d[7]),
        "+f"(d[8]), "+f"(d[9]), "+f"(d[10]), "+f"(d[11]), "+f"(d[12]), "+f"(d[13]), "+f"(d[14]), "+f"(d[15]),
        "+f"(d[16]), "+f"(d[17]), "+f"(d[18]), "+f"(d[19]), "+f"(d[20]), "+f"(d[21]), "+f"(d[22]), "+f"(d[23]),
        "+f"(d[24]), "+f"(d[25]), "+f"(d[26]), "+f"(d[27]), "+f"(d[28]), "+f"(d[29]), "+f"(d[30]), "+f"(d[31]),
        "+f"(d[32]), "+f"(d[33]), "+f"(d[34]), "+f"(d[35]), "+f"(d[36]), "+f"(d[37]), "+f"(d[38]), "+f"(d[39]),
        "+f"(d[40]), "+f"(d[41]), "+f"(d[42]), "+f"(d[43]), "+f"(d[44]), "+f"(d[45]), "+f"(d[46]), "+f"(d[47]),
        "+f"(d[48]), "+f"(d[49]), "+f"(d[50]), "+f"(d[51]), "+f"(d[52]), "+f"(d[53]), "+f"(d[54]), "+f"(d[55]),
        "+f"(d[56]), "+f"(d[57]), "+f"(d[58]), "+f"(d[59]), "+f"(d[60]), "+f"(d[61]), "+f"(d[62]), "+f"(d[63]),
        "+f"(d[64]), "+f"(d[65]), "+f"(d[66]), "+f"(d[67]), "+f"(d[68]), "+f"(d[69]), "+f"(d[70]), "+f"(d[71]),
        "+f"(d[72]), "+f"(d[73]), "+f"(d[74]), "+f"(d[75]), "+f"(d[76]), "+f"(d[77]), "+f"(d[78]), "+f"(d[79])
      : "l"(descA), "l"(descB));
}
__device__ __forceinline__ void mma_ss160_z(float (&d)[80], uint64_t descA, uint64_t descB) {
  asm volatile("wgmma.mma_async.sync.aligned.m64n160k16.f32.bf16.bf16 {"
      "%0, %1, %2, %3, %4, %5, %6, %7, %8, %9, %10, %11, %12, %13, %14, %15, "
      "%16, %17, %18, %19, %20, %21, %22, %23, %24, %25, %26, %27, %28, %29, %30, %31, "
      "%32, %33, %34, %35, %36, %37, %38, %39, %40, %41, %42, %43, %44, %45, %46, %47, "
      "%48, %49, %50, %51, %52, %53, %54, %55, %56, %57, %58, %59, %60, %61, %62, %63, "
      "%64, %65, %66, %67, %68, %69, %70, %71, %72, %73, %74, %75, %76, %77, %78, %79"
      "}, %80, %81, 0, 1, 1, 0, 1;\n"
      : "=f"(d[0]), "=f"(d[1]), "=f"(d[2]), "=f"(d[3]), "=f"(d[4]), "=f"(d[5]), "=f"(d[6]), "=f"(d[7]),
        "=f"(d[8]), "=f"(d[9]), "=f"(d[10]), "=f"(d[11]), "=f"(d[12]), "=f"(d[13]), "=f"(d[14]), "=f"(d[15]),
        "=f"(d[16]), "=f"(d[17]), "=f"(d[18]), "=f"(d[19]), "=f"(d[20]), "=f"(d[21]), "=f"(d[22]), "=f"(d[23]),
        "=f"(d[24]), "=f"(d[25]), "=f"(d[26]), "=f"(d[27]), "=f"(d[28]), "=f"(d[29]), "=f"(d[30]), "=f"(d[31]),
        "=f"(d[32]), "=f"(d[33]), "=f"(d[34]), "=f"(d[35]), "=f"(d[36]), "=f"(d[37]), "=f"(d[38]), "=f"(d[39]),
        "=f"(d[40]), "=f"(d[41]), "=f"(d[42]), "=f"(d[43]), "=f"(d[44]), "=f"(d[45]), "=f"(d[46]), "=f"(d[47]),
        "=f"(d[48]), "=f"(d[49]), "=f"(d[50]), "=f"(d[51]), "=f"(d[52]), "=f"(d[53]), "=f"(d[54]), "=f"(d[55]),
        "=f"(d[56]), "=f"(d[57]), "=f"(d[58]), "=f"(d[59]), "=f"(d[60]), "=f"(d[61]), "=f"(d[62]), "=f"(d[63]),
        "=f"(d[64]), "=f"(d[65]), "=f"(d[66]), "=f"(d[67]), "=f"(d[68]), "=f"(d[69]), "=f"(d[70]), "=f"(d[71]),
        "=f"(d[72]), "=f"(d[73]), "=f"(d[74]), "=f"(d[75]), "=f"(d[76]), "=f"(d[77]), "=f"(d[78]), "=f"(d[79])
      : "l"(descA), "l"(descB));
}

__device__ __forceinline__ void mma_ss192(float (&d)[96], uint64_t descA, uint64_t descB) {
  asm volatile("wgmma.mma_async.sync.aligned.m64n192k16.f32.bf16.bf16 {"
      "%0, %1, %2, %3, %4, %5, %6, %7, %8, %9, %10, %11, %12, %13, %14, %15, "
      "%16, %17, %18, %19, %20, %21, %22, %23, %24, %25, %26, %27, %28, %29, %30, %31, "
      "%32, %33, %34, %35, %36, %37, %38, %39, %40, %41, %42, %43, %44, %45, %46, %47, "
      "%48, %49, %50, %51, %52, %53, %54, %55, %56, %57, %58, %59, %60, %61, %62, %63, "
      "%64, %65, %66, %67, %68, %69, %70, %71, %72, %73, %74, %75, %76, %77, %78, %79, "
      "%80, %81, %82, %83, %84, %85, %86, %87, %88, %89, %90, %91, %92, %93, %94, %95"
      "}, %96, %97, 1, 1, 1, 0, 1;\n"
      : "+f"(d[0]), "+f"(d[1]), "+f"(d[2]), "+f"(d[3]), "+f"(d[4]), "+f"(d[5]), "+f"(d[6]), "+f"(d[7]),
        "+f"(d[8]), "+f"(d[9]), "+f"(d[10]), "+f"(d[11]), "+f"(d[12]), "+f"(d[13]), "+f"(d[14]), "+f"(d[15]),
        "+f"(d[16]), "+f"(d[17]), "+f"(d[18]), "+f"(d[19]), "+f"(d[20]), "+f"(d[21]), "+f"(d[22]), "+f"(d[23]),
        "+f"(d[24]), "+f"(d[25]), "+f"(d[26]), "+f"(d[27]), "+f"(d[28]), "+f"(d[29]), "+f"(d[30]), "+f"(d[31]),
        "+f"(d[32]), "+f"(d[33]), "+f"(d[34]), "+f"(d[35]), "+f"(d[36]), "+f"(d[37]), "+f"(d[38]), "+f"(d[39]),
        "+f"(d[40]), "+f"(d[41]), "+f"(d[42]), "+f"(d[43]), "+f"(d[44]), "+f"(d[45]), "+f"(d[46]), "+f"(d[47]),
        "+f"(d[48]), "+f"(d[49]), "+f"(d[50]), "+f"(d[51]), "+f"(d[52]), "+f"(d[53]), "+f"(d[54]), "+f"(d[55]),
        "+f"(d[56]), "+f"(d[57]), "+f"(d[58]), "+f"(d[59]), "+f"(d[60]), "+f"(d[61]), "+f"(d[62]), "+f"(d[63]),
        "+f"(d[64]), "+f"(d[65]), "+f"(d[66]), "+f"(d[67]), "+f"(d[68]), "+f"(d[69]), "+f"(d[70]), "+f"(d[71]),
        "+f"(d[72]), "+f"(d[73]), "+f"(d[74]), "+f"(d[75]), "+f"(d[76]), "+f"(d[77]), "+f"(d[78]), "+f"(d[79]),
        "+f"(d[80]), "+f"(d[81]), "+f"(d[82]), "+f"(d[83]), "+f"(d[84]), "+f"(d[85]), "+f"(d[86]), "+f"(d[87]),
        "+f"(d[88]), "+f"(d[89]), "+f"(d[90]), "+f"(d[91]), "+f"(d[92]), "+f"(d[93]), "+f"(d[94]), "+f"(d[95])
      : "l"(descA), "l"(descB));
}
__device__ __forceinline__ void mma_ss192_p(float (&d)[96], uint64_t descA, uint64_t descB, int acc) {
  asm volatile("{\n.reg .pred p;\nsetp.ne.b32 p, %98, 0;\n"
      "wgmma.mma_async.sync.aligned.m64n192k16.f32.bf16.bf16 {"
      "%0, %1, %2, %3, %4, %5, %6, %7, %8, %9, %10, %11, %12, %13, %14, %15, "
      "%16, %17, %18, %19, %20, %21, %22, %23, %24, %25, %26, %27, %28, %29, %30, %31, "
      "%32, %33, %34, %35, %36, %37, %38, %39, %40, %41, %42, %43, %44, %45, %46, %47, "
      "%48, %49, %50, %51, %52, %53, %54, %55, %56, %57, %58, %59, %60, %61, %62, %63, "
      "%64, %65, %66, %67, %68, %69, %70, %71, %72, %73, %74, %75, %76, %77, %78, %79, "
      "%80, %81, %82, %83, %84, %85, %86, %87, %88, %89, %90, %91, %92, %93, %94, %95"
      "}, %96, %97, p, 1, 1, 0, 1;\n}\n"
      : "+f"(d[0]), "+f"(d[1]), "+f"(d[2]), "+f"(d[3]), "+f"(d[4]), "+f"(d[5]), "+f"(d[6]), "+f"(d[7]),
        "+f"(d[8]), "+f"(d[9]), "+f"(d[10]), "+f"(d[11]), "+f"(d[12]), "+f"(d[13]), "+f"(d[14]), "+f"(d[15]),
        "+f"(d[16]), "+f"(d[17]), "+f"(d[18]), "+f"(d[19]), "+f"(d[20]), "+f"(d[21]), "+f"(d[22]), "+f"(d[23]),
        "+f"(d[24]), "+f"(d[25]), "+f"(d[26]), "+f"(d[27]), "+f"(d[28]), "+f"(d[29]), "+f"(d[30]), "+f"(d[31]),
        "+f"(d[32]), "+f"(d[33]), "+f"(d[34]), "+f"(d[35]), "+f"(d[36]), "+f"(d[37]), "+f"(d[38]), "+f"(d[39]),
        "+f"(d[40]), "+f"(d[41]), "+f"(d[42]), "+f"(d[43]), "+f"(d[44]), "+f"(d[45]), "+f"(d[46]), "+f"(d[47]),
        "+f"(d[48]), "+f"(d[49]), "+f"(d[50]), "+f"(d[51]), "+f"(d[52]), "+f"(d[53]), "+f"(d[54]), "+f"(d[55]),
        "+f"(d[56]), "+f"(d[57]), "+f"(d[58]), "+f"(d[59]), "+f"(d[60]), "+f"(d[61]), "+f"(d[62]), "+f"(d[63]),
        "+f"(d[64]), "+f"(d[65]), "+f"(d[66]), "+f"(d[67]), "+f"(d[68]), "+f"(d[69]), "+f"(d[70]), "+f"(d[71]),
        "+f"(d[72]), "+f"(d[73]), "+f"(d[74]), "+f"(d[75]), "+f"(d[76]), "+f"(d[77]), "+f"(d[78]), "+f"(d[79]),
        "+f"(d[80]), "+f"(d[81]), "+f"(d[82]), "+f"(d[83]), "+f"(d[84]), "+f"(d[85]), "+f"(d[86]), "+f"(d[87]),
        "+f"(d[88]), "+f"(d[89]), "+f"(d[90]), "+f"(d[91]), "+f"(d[92]), "+f"(d[93]), "+f"(d[94]), "+f"(d[95])
      : "l"(descA), "l"(descB), "r"(acc));
}

__device__ __forceinline__ void mma_ss80_tt(float (&d)[40], uint64_t descA, uint64_t descB) {
  asm volatile("wgmma.mma_async.sync.aligned.m64n80k16.f32.bf16.bf16 {"
      "%0, %1, %2, %3, %4, %5, %6, %7, %8, %9, %10, %11, %12, %13, %14, %15, "
      "%16, %17, %18, %19, %20, %21, %22, %23, %24, %25, %26, %27, %28, %29, %30, %31, "
      "%32, %33, %34, %35, %36, %37, %38, %39"
      "}, %40, %41, 1, 1, 1, 1, 1;\n"
      : "+f"(d[0]), "+f"(d[1]), "+f"(d[2]), "+f"(d[3]), "+f"(d[4]), "+f"(d[5]), "+f"(d[6]), "+f"(d[7]),
        "+f"(d[8]), "+f"(d[9]), "+f"(d[10]), "+f"(d[11]), "+f"(d[12]), "+f"(d[13]), "+f"(d[14]), "+f"(d[15]),
        "+f"(d[16]), "+f"(d[17]), "+f"(d[18]), "+f"(d[19]), "+f"(d[20]), "+f"(d[21]), "+f"(d[22]), "+f"(d[23]),
        "+f"(d[24]), "+f"(d[25]), "+f"(d[26]), "+f"(d[27]), "+f"(d[28]), "+f"(d[29]), "+f"(d[30]), "+f"(d[31]),
        "+f"(d[32]), "+f"(d[33]), "+f"(d[34]), "+f"(d[35]), "+f"(d[36]), "+f"(d[37]), "+f"(d[38]), "+f"(d[39])
      : "l"(descA), "l"(descB));
}
__device__ __forceinline__ void mma_ss80_tt_z(float (&d)[40], uint64_t descA, uint64_t descB) {
  asm volatile("wgmma.mma_async.sync.aligned.m64n80k16.f32.bf16.bf16 {"
      "%0, %1, %2, %3, %4, %5, %6, %7, %8, %9, %10, %11, %12, %13, %14, %15, "
      "%16, %17, %18, %19, %20, %21, %22, %23, %24, %25, %26, %27, %28, %29, %30, %31, "
      "%32, %33, %34, %35, %36, %37, %38, %39"
      "}, %40, %41, 0, 1, 1, 1, 1;\n"
      : "=f"(d[0]), "=f"(d[1]), "=f"(d[2]), "=f"(d[3]), "=f"(d[4]), "=f"(d[5]), "=f"(d[6]), "=f"(d[7]),
        "=f"(d[8]), "=f"(d[9]), "=f"(d[10]), "=f"(d[11]), "=f"(d[12]), "=f"(d[13]), "=f"(d[14]), "=f"(d[15]),
        "=f"(d[16]), "=f"(d[17]), "=f"(d[18]), "=f"(d[19]), "=f"(d[20]), "=f"(d[21]), "=f"(d[22]), "=f"(d[23]),
        "=f"(d[24]), "=f"(d[25]), "=f"(d[26]), "=f"(d[27]), "=f"(d[28]), "=f"(d[29]), "=f"(d[30]), "=f"(d[31]),
        "=f"(d[32]), "=f"(d[33]), "=f"(d[34]), "=f"(d[35]), "=f"(d[36]), "=f"(d[37]), "=f"(d[38]), "=f"(d[39])
      : "l"(descA), "l"(descB));
}

__device__ __forceinline__ void mma_rs80_k(float (&d)[40], const uint32_t (&a)[4], uint64_t descB) {
  asm volatile("wgmma.mma_async.sync.aligned.m64n80k16.f32.bf16.bf16 {"
      "%0, %1, %2, %3, %4, %5, %6, %7, %8, %9, %10, %11, %12, %13, %14, %15, "
      "%16, %17, %18, %19, %20, %21, %22, %23, %24, %25, %26, %27, %28, %29, %30, %31, "
      "%32, %33, %34, %35, %36, %37, %38, %39"
      "}, {%40, %41, %42, %43}, %44, 1, 1, 1, 0;\n"
      : "+f"(d[0]), "+f"(d[1]), "+f"(d[2]), "+f"(d[3]), "+f"(d[4]), "+f"(d[5]), "+f"(d[6]), "+f"(d[7]),
        "+f"(d[8]), "+f"(d[9]), "+f"(d[10]), "+f"(d[11]), "+f"(d[12]), "+f"(d[13]), "+f"(d[14]), "+f"(d[15]),
        "+f"(d[16]), "+f"(d[17]), "+f"(d[18]), "+f"(d[19]), "+f"(d[20]), "+f"(d[21]), "+f"(d[22]), "+f"(d[23]),
        "+f"(d[24]), "+f"(d[25]), "+f"(d[26]), "+f"(d[27]), "+f"(d[28]), "+f"(d[29]), "+f"(d[30]), "+f"(d[31]),
        "+f"(d[32]), "+f"(d[33]), "+f"(d[34]), "+f"(d[35]), "+f"(d[36]), "+f"(d[37]), "+f"(d[38]), "+f"(d[39])
      : "r"(a[0]), "r"(a[1]), "r"(a[2]), "r"(a[3]), "l"(descB));
}
__device__ __forceinline__ void mma_rs80_k_z(float (&d)[40], const uint32_t (&a)[4], uint64_t descB) {
  asm volatile("wgmma.mma_async.sync.aligned.m64n80k16.f32.bf16.bf16 {"
      "%0, %1, %2, %3, %4, %5, %6, %7, %8, %9, %10, %11, %12, %13, %14, %15, "
      "%16, %17, %18, %19, %20, %21, %22, %23, %24, %25, %26, %27, %28, %29, %30, %31, "
      "%32, %33, %34, %35, %36, %37, %38, %39"
      "}, {%40, %41, %42, %43}, %44, 0, 1, 1, 0;\n"
      : "=f"(d[0]), "=f"(d[1]), "=f"(d[2]), "=f"(d[3]), "=f"(d[4]), "=f"(d[5]), "=f"(d[6]), "=f"(d[7]),
        "=f"(d[8]), "=f"(d[9]), "=f"(d[10]), "=f"(d[11]), "=f"(d[12]), "=f"(d[13]), "=f"(d[14]), "=f"(d[15]),
        "=f"(d[16]), "=f"(d[17]), "=f"(d[18]), "=f"(d[19]), "=f"(d[20]), "=f"(d[21]), "=f"(d[22]), "=f"(d[23]),
        "=f"(d[24]), "=f"(d[25]), "=f"(d[26]), "=f"(d[27]), "=f"(d[28]), "=f"(d[29]), "=f"(d[30]), "=f"(d[31]),
        "=f"(d[32]), "=f"(d[33]), "=f"(d[34]), "=f"(d[35]), "=f"(d[36]), "=f"(d[37]), "=f"(d[38]), "=f"(d[39])
      : "r"(a[0]), "r"(a[1]), "r"(a[2]), "r"(a[3]), "l"(descB));
}

__device__ __forceinline__ void mma_rs48_k(float (&d)[24], const uint32_t (&a)[4], uint64_t descB) {
  asm volatile("wgmma.mma_async.sync.aligned.m64n48k16.f32.bf16.bf16 {"
      "%0, %1, %2, %3, %4, %5, %6, %7, %8, %9, %10, %11, %12, %13, %14, %15, "
      "%16, %17, %18, %19, %20, %21, %22, %23"
      "}, {%24, %25, %26, %27}, %28, 1, 1, 1, 0;\n"
      : "+f"(d[0]), "+f"(d[1]), "+f"(d[2]), "+f"(d[3]), "+f"(d[4]), "+f"(d[5]), "+f"(d[6]), "+f"(d[7]),
        "+f"(d[8]), "+f"(d[9]), "+f"(d[10]), "+f"(d[11]), "+f"(d[12]), "+f"(d[13]), "+f"(d[14]), "+f"(d[15]),
        "+f"(d[16]), "+f"(d[17]), "+f"(d[18]), "+f"(d[19]), "+f"(d[20]), "+f"(d[21]), "+f"(d[22]), "+f"(d[23])
      : "r"(a[0]), "r"(a[1]), "r"(a[2]), "r"(a[3]), "l"(descB));
}
__device__ __forceinline__ void mma_rs48_k_z(float (&d)[24], const uint32_t (&a)[4], uint64_t descB) {
  asm volatile("wgmma.mma_async.sync.aligned.m64n48k16.f32.bf16.bf16 {"
      "%0, %1, %2, %3, %4, %5, %6, %7, %8, %9, %10, %11, %12, %13, %14, %15, "
      "%16, %17, %18, %19, %20, %21, %22, %23"
      "}, {%24, %25, %26, %27}, %28, 0, 1, 1, 0;\n"
      : "=f"(d[0]), "=f"(d[1]), "=f"(d[2]), "=f"(d[3]), "=f"(d[4]), "=f"(d[5]), "=f"(d[6]), "=f"(d[7]),
        "=f"(d[8]), "=f"(d[9]), "=f"(d[10]), "=f"(d[11]), "=f"(d[12]), "=f"(d[13]), "=f"(d[14]), "=f"(d[15]),
        "=f"(d[16]), "=f"(d[17]), "=f"(d[18]), "=f"(d[19]), "=f"(d[20]), "=f"(d[21]), "=f"(d[22]), "=f"(d[23])
      : "r"(a[0]), "r"(a[1]), "r"(a[2]), "r"(a[3]), "l"(descB));
}

__device__ __forceinline__ void mma_rs160_n(float (&d)[80], const uint32_t (&a)[4], uint64_t descB) {
  asm volatile("wgmma.mma_async.sync.aligned.m64n160k16.f32.bf16.bf16 {"
      "%0, %1, %2, %3, %4, %5, %6, %7, %8, %9, %10, %11, %12, %13, %14, %15, "
      "%16, %17, %18, %19, %20, %21, %22, %23, %24, %25, %26, %27, %28, %29, %30, %31, "
      "%32, %33, %34, %35, %36, %37, %38, %39, %40, %41, %42, %43, %44, %45, %46, %47, "
      "%48, %49, %50, %51, %52, %53, %54, %55, %56, %57, %58, %59, %60, %61, %62, %63, "
      "%64, %65, %66, %67, %68, %69, %70, %71, %72, %73, %74, %75, %76, %77, %78, %79"
      "}, {%80, %81, %82, %83}, %84, 1, 1, 1, 1;\n"
      : "+f"(d[0]), "+f"(d[1]), "+f"(d[2]), "+f"(d[3]), "+f"(d[4]), "+f"(d[5]), "+f"(d[6]), "+f"(d[7]),
        "+f"(d[8]), "+f"(d[9]), "+f"(d[10]), "+f"(d[11]), "+f"(d[12]), "+f"(d[13]), "+f"(d[14]), "+f"(d[15]),
        "+f"(d[16]), "+f"(d[17]), "+f"(d[18]), "+f"(d[19]), "+f"(d[20]), "+f"(d[21]), "+f"(d[22]), "+f"(d[23]),
        "+f"(d[24]), "+f"(d[25]), "+f"(d[26]), "+f"(d[27]), "+f"(d[28]), "+f"(d[29]), "+f"(d[30]), "+f"(d[31]),
        "+f"(d[32]), "+f"(d[33]), "+f"(d[34]), "+f"(d[35]), "+f"(d[36]), "+f"(d[37]), "+f"(d[38]), "+f"(d[39]),
        "+f"(d[40]), "+f"(d[41]), "+f"(d[42]), "+f"(d[43]), "+f"(d[44]), "+f"(d[45]), "+f"(d[46]), "+f"(d[47]),
        "+f"(d[48]), "+f"(d[49]), "+f"(d[50]), "+f"(d[51]), "+f"(d[52]), "+f"(d[53]), "+f"(d[54]), "+f"(d[55]),
        "+f"(d[56]), "+f"(d[57]), "+f"(d[58]), "+f"(d[59]), "+f"(d[60]), "+f"(d[61]), "+f"(d[62]), "+f"(d[63]),
        "+f"(d[64]), "+f"(d[65]), "+f"(d[66]), "+f"(d[67]), "+f"(d[68]), "+f"(d[69]), "+f"(d[70]), "+f"(d[71]),
        "+f"(d[72]), "+f"(d[73]), "+f"(d[74]), "+f"(d[75]), "+f"(d[76]), "+f"(d[77]), "+f"(d[78]), "+f"(d[79])
      : "r"(a[0]), "r"(a[1]), "r"(a[2]), "r"(a[3]), "l"(descB));
}
__device__ __forceinline__ void mma_rs160_n_z(float (&d)[80], const uint32_t (&a)[4], uint64_t descB) {
  asm volatile("wgmma.mma_async.sync.aligned.m64n160k16.f32.bf16.bf16 {"
      "%0, %1, %2, %3, %4, %5, %6, %7, %8, %9, %10, %11, %12, %13, %14, %15, "
      "%16, %17, %18, %19, %20, %21, %22, %23, %24, %25, %26, %27, %28, %29, %30, %31, "
      "%32, %33, %34, %35, %36, %37, %38, %39, %40, %41, %42, %43, %44, %45, %46, %47, "
      "%48, %49, %50, %51, %52, %53, %54, %55, %56, %57, %58, %59, %60, %61, %62, %63, "
      "%64, %65, %66, %67, %68, %69, %70, %71, %72, %73, %74, %75, %76, %77, %78, %79"
      "}, {%80, %81, %82, %83}, %84, 0, 1, 1, 1;\n"
      : "=f"(d[0]), "=f"(d[1]), "=f"(d[2]), "=f"(d[3]), "=f"(d[4]), "=f"(d[5]), "=f"(d[6]), "=f"(d[7]),
        "=f"(d[8]), "=f"(d[9]), "=f"(d[10]), "=f"(d[11]), "=f"(d[12]), "=f"(d[13]), "=f"(d[14]), "=f"(d[15]),
        "=f"(d[16]), "=f"(d[17]), "=f"(d[18]), "=f"(d[19]), "=f"(d[20]), "=f"(d[21]), "=f"(d[22]), "=f"(d[23]),
        "=f"(d[24]), "=f"(d[25]), "=f"(d[26]), "=f"(d[27]), "=f"(d[28]), "=f"(d[29]), "=f"(d[30]), "=f"(d[31]),
        "=f"(d[32]), "=f"(d[33]), "=f"(d[34]), "=f"(d[35]), "=f"(d[36]), "=f"(d[37]), "=f"(d[38]), "=f"(d[39]),
        "=f"(d[40]), "=f"(d[41]), "=f"(d[42]), "=f"(d[43]), "=f"(d[44]), "=f"(d[45]), "=f"(d[46]), "=f"(d[47]),
        "=f"(d[48]), "=f"(d[49]), "=f"(d[50]), "=f"(d[51]), "=f"(d[52]), "=f"(d[53]), "=f"(d[54]), "=f"(d[55]),
        "=f"(d[56]), "=f"(d[57]), "=f"(d[58]), "=f"(d[59]), "=f"(d[60]), "=f"(d[61]), "=f"(d[62]), "=f"(d[63]),
        "=f"(d[64]), "=f"(d[65]), "=f"(d[66]), "=f"(d[67]), "=f"(d[68]), "=f"(d[69]), "=f"(d[70]), "=f"(d[71]),
        "=f"(d[72]), "=f"(d[73]), "=f"(d[74]), "=f"(d[75]), "=f"(d[76]), "=f"(d[77]), "=f"(d[78]), "=f"(d[79])
      : "r"(a[0]), "r"(a[1]), "r"(a[2]), "r"(a[3]), "l"(descB));
}

__device__ __forceinline__ void feature_map(const uint32_t (&P)[2][10], uint32_t (&fr)[10][4]) {
  constexpr float L2E = 1.4426950408889634f;
#pragma unroll
  for (int p = 0; p < 2; p++) {
#pragma unroll
    for (int r = 0; r < 2; r++) {
      uint32_t mx = P[r][5 * p], mn = mx;
#pragma unroll
      for (int g = 1; g < 5; g++) { mx = max_bf2(mx, P[r][5 * p + g]); mn = min_bf2(mn, P[r][5 * p + g]); }
      mx = max_bf2(mx, __shfl_xor_sync(0xffffffffu, mx, 1));
      mn = min_bf2(mn, __shfl_xor_sync(0xffffffffu, mn, 1));
      mx = max_bf2(mx, __shfl_xor_sync(0xffffffffu, mx, 2));
      mn = min_bf2(mn, __shfl_xor_sync(0xffffffffu, mn, 2));
      float mx0 = -bf_lo(mx) * L2E, mx1 = -bf_hi(mx) * L2E, mn0 = bf_lo(mn) * L2E, mn1 = bf_hi(mn) * L2E;
      float ep0[5], ep1[5], en0[5], en1[5];
      float sp0 = 0.f, sp1 = 0.f, sn0 = 0.f, sn1 = 0.f;
#pragma unroll
      for (int g = 0; g < 5; g++) {
        float x0 = bf_lo(P[r][5 * p + g]), x1 = bf_hi(P[r][5 * p + g]);
        ep0[g] = ex2(fmaf(x0, L2E, mx0)); ep1[g] = ex2(fmaf(x1, L2E, mx1));
        en0[g] = ex2(fmaf(x0, -L2E, mn0)); en1[g] = ex2(fmaf(x1, -L2E, mn1));
        sp0 += ep0[g]; sp1 += ep1[g]; sn0 += en0[g]; sn1 += en1[g];
      }
      sp0 += __shfl_xor_sync(0xffffffffu, sp0, 1); sp1 += __shfl_xor_sync(0xffffffffu, sp1, 1);
      sn0 += __shfl_xor_sync(0xffffffffu, sn0, 1); sn1 += __shfl_xor_sync(0xffffffffu, sn1, 1);
      sp0 += __shfl_xor_sync(0xffffffffu, sp0, 2); sp1 += __shfl_xor_sync(0xffffffffu, sp1, 2);
      sn0 += __shfl_xor_sync(0xffffffffu, sn0, 2); sn1 += __shfl_xor_sync(0xffffffffu, sn1, 2);
      sp0 = rcp(sp0); sp1 = rcp(sp1); sn0 = rcp(sn0); sn1 = rcp(sn1);
#pragma unroll
      for (int g = 0; g < 5; g++) {
        fr[5 * p + g][r] = pack_bf16(ep0[g] * sp0, ep1[g] * sp1);
        fr[5 * p + g][2 + r] = pack_bf16(en0[g] * sn0, en1[g] * sn1);
      }
    }
  }
}

template <int V> struct IntC { static constexpr int value = V; };
struct Ring {
  uint32_t idx, phase;
  template <int N> __device__ __forceinline__ void next() { if (++idx == N) { idx = 0; phase ^= 1; } }
};

}

__global__ void __cluster_dims__(2, 1, 1) __launch_bounds__(384, 1)
fused_kernel(const __grid_constant__ Maps maps, const __nv_bfloat16* __restrict__ x, const __nv_bfloat16* __restrict__ wqkv,
             const __nv_bfloat16* __restrict__ wphi, const __nv_bfloat16* __restrict__ w1, const __nv_bfloat16* __restrict__ w2,
             const __nv_bfloat16* __restrict__ w3, const __nv_bfloat16* __restrict__ w4, const __nv_bfloat16* __restrict__ wo,
             const __nv_bfloat16* __restrict__ gate_w, __nv_bfloat16* __restrict__ out) {
  extern __shared__ __align__(1024) uint8_t sgen[];
  const uint32_t sb = smem_u32(sgen);
  const uint32_t sb16 = (sb & 0x3FFFFu) >> 4;
  const uint32_t bars = sb + OFF_BAR;
  const uint32_t fullA = bars + 8 * B_FULLA, emptyA = bars + 8 * B_EMPTYA, fullB = bars + 8 * B_FULLB, emptyB = bars + 8 * B_EMPTYB;

  const int tid = threadIdx.x;
  const int rank = blockIdx.x & 1;
  const int bid = blockIdx.x - NSVC, pairIdx = bid >> 1;
  const int i = pairIdx >> 2, j = 2 * (pairIdx & 3) + rank;
  const int k3 = (5 * (pairIdx & 3) + 1) >> 1;

  if (bid < 0) {
    const int sv = blockIdx.x;
    const unsigned epoch = *reinterpret_cast<volatile unsigned*>(g_flags + FL_DONE * 32) / NCTA;
    if (tid == 0) {
#pragma unroll
      for (int b = 0; b < 11; b++) mbar_init(bars + 8 * b, 1);
      mbar_expect_tx(bars + 80, 6400);
      bulk_load(sb + 204800, wphi + sv * 3200, 6400, bars + 80);
    }
    __syncthreads();
    float a[8];
#pragma unroll 1
    for (int rd = 0; rd < 4; rd++) {
      const int nch = rd ? 192 : 80, nth = rd ? 384 : 320, piece = rd ? 18432 : 20480, np = rd == 3 ? 7 : 10;
      if (tid == 0) {
        const char* src = reinterpret_cast<const char*>(rd ? w3 + (size_t)(160 * sv + 60 * (rd - 1)) * F_ : w1 + (size_t)160 * sv * D_);
#pragma unroll 1
        for (int p = 0; p < np; p++) {
          const int bytes = (rd == 3 && p == 6) ? 12288 : piece;
          mbar_expect_tx(bars + 8 * p, bytes);
          bulk_load(sb + p * piece, src + p * piece, bytes, bars + 8 * p);
        }
      }
      if (rd == 0) {
        if (tid < 40 && (tid < 20 || sv >= 2))
          reinterpret_cast<uint4*>(g_Hs + (size_t)(2 + ((sv & 1) ? S_ - 1 - tid / 20 : tid / 20)) * D_ + 160 * sv)[tid % 20] = make_uint4(0, 0, 0, 0);
        mbar_wait(bars + 80, 0);
#pragma unroll 1
        for (int e = tid; e < 1600; e += 384) {
          const int jj = e / 800, it = e - 800 * jj, st = it / 160, n = (it - 160 * st) >> 1, k0 = 16 * st + 8 * ((it ^ (n >> 2)) & 1);
          const int nn = n % 40, h = 2 * (n / 40) + (nn & 1), ff = 4 * (nn >> 3) + ((nn >> 1) & 3);
          uint32_t w[8];
#pragma unroll
          for (int q = 0; q < 8; q++) {
            const int k = k0 + q;
            w[q] = (unsigned)(k - 20 * h) < 20u ? reinterpret_cast<const unsigned short*>(sgen + 204800)[jj * 1600 + k * 20 + ff] : 0u;
          }
          g_wphi[sv * 1600 + e] = make_uint4(w[0] | (w[1] << 16), w[2] | (w[3] << 16), w[4] | (w[5] << 16), w[6] | (w[7] << 16));
        }
      }
      if (rd < 2) {
#pragma unroll
        for (int e = 0; e < 8; e++) a[e] = 0.f;
      }
#pragma unroll 1
      for (int p = 0; p < np; p++) {
        mbar_wait(bars + 8 * p, rd & 1);
        const int bytes = (rd == 3 && p == 6) ? 12288 : piece;
        if (tid < nth) {
#pragma unroll 1
          for (int o = tid * 16; o < bytes; o += nth * 16) {
            const uint4 v = lds128(sb + p * piece + o);
            a[0] += bf_lo(v.x); a[1] += bf_hi(v.x); a[2] += bf_lo(v.y); a[3] += bf_hi(v.y);
            a[4] += bf_lo(v.z); a[5] += bf_hi(v.z); a[6] += bf_lo(v.w); a[7] += bf_hi(v.w);
          }
        }
      }
      if (tid < nth && (rd == 0 || rd == 3)) {
        float* cd = g_cs[epoch & 1] + (rd ? D_ : 0) + 8 * (tid % nch);
        red_add4(cd, a[0], a[1], a[2], a[3]); red_add4(cd + 4, a[4], a[5], a[6], a[7]);
      }
      __syncthreads();
      if (tid == 0 && (rd == 0 || rd == 3)) {
        flag_add(rd ? FL_CS3 : FL_CS);
        if (rd == 0) l2_prefetch(w2 + (size_t)sv * (D_ * D_ / NSVC), D_ * D_ * 2 / NSVC);
      }
    }
#pragma unroll 1
    for (int e = tid; e < (D_ + F_) / NSVC; e += 384) g_cs[(epoch + 1) & 1][sv * ((D_ + F_) / NSVC) + e] = 0.f;
#pragma unroll 1
    for (int e = tid; e < 2 * KV_J; e += 384) g_acc[(epoch + 1) & 1][sv * 2 * KV_J + e] = 0.f;
    if (tid < 32) {
      l2_prefetch(w4 + (size_t)(sv * 32 + tid) * (F_ * D_ / 128), F_ * D_ * 2 / 128);
      l2_prefetch(wo + (size_t)(sv * 32 + tid) * (D_ * D_ / 128), D_ * D_ * 2 / 128);
    }
    return;
  }
  TSTAMP(0);
  if (tid >= 256) {
    asm volatile("setmaxnreg.dec.sync.aligned.u32 40;");
    if (tid == 256) {
#pragma unroll
      for (int s = 0; s < NA; s++) mbar_init(fullA + 8 * s, 1);
      asm volatile("fence.mbarrier_init.release.cluster;" ::: "memory");
#pragma unroll 1
      for (int u = 0; u < 4; u++) {
        if ((u & 1) == 0) mbar_expect_tx(fullA + 4 * u, SLOT_A);
        tma2d(sb + OFF_A + u * 8192, &maps.x, fullA + 8 * (u >> 1), 64 * (u >> 1), 128 * i + 64 * (u & 1));
      }
    } else if (tid == 288) {
#pragma unroll
      for (int s = 0; s < NB; s++) { mbar_init(fullB + 8 * s, 1); mbar_init(emptyB + 8 * s, 8); }
      asm volatile("fence.mbarrier_init.release.cluster;" ::: "memory");
    } else if (tid == 320) {
#pragma unroll
      for (int b = B_CS; b < NBAR; b++) if (b < B_EMPTYB || b >= B_EMPTYB + NB) mbar_init(bars + 8 * b, b < B_EMPTYB ? 1 : b < B_EMPTYA ? 8 : b < B_X1P ? 16 : 2);
#pragma unroll
      for (int b = B_DSR; b < B_EMPTYB; b++) mbar_expect_tx(bars + 8 * b, 10240);
      asm volatile("fence.mbarrier_init.release.cluster;" ::: "memory");
    }
    __syncwarp();
    asm volatile("barrier.cluster.arrive.relaxed.aligned;" ::: "memory");
    auto get_epoch = [&]() { return *reinterpret_cast<volatile unsigned*>(g_flags + FL_DONE * 32) / NCTA; };
    if ((tid >> 5) != 9) asm volatile("barrier.cluster.wait.aligned;" ::: "memory");
    const int lane = tid & 31, pw = (tid >> 5) & 3;
    if (pw == 0) {
      if (tid == 256) {
        Ring r{2, 1};
        unsigned ep1 = 0;
#pragma unroll 1
        for (int k = 2; k < 24; k++) {
          if (k == 4) ep1 = get_epoch() + 1;
          if (k == 10 || k == 16) {
            if (k == 10) mbar_wait(bars + 8 * B_HST, 0);
            flag_wait(k == 10 ? FL_H + 2 * i + rank : FL_X1 + i, ep1 * 8u);
            TSTAMPX(k == 10 ? 29 : 30);
          }
          if (k == 14) {
            mbar_wait(bars + 8 * B_WDEAD, 0);
            mbar_expect_tx(bars + 8 * B_T4, SLOT_A);
            tma2d(sb + OFF_MISC, &maps.hs, bars + 8 * B_T4, 256 + 320 * rank, 128 * i);
            mbar_wait(emptyA + 16, r.phase); mbar_wait(emptyA + 24, r.phase);
            mbar_expect_tx(bars + 8 * B_XR, 20480);
            tma2d(sb + OFF_STG, &maps.xr, bars + 8 * B_XR, 80 * j, 128 * i);
            mbar_wait(bars + 8 * B_X1P, 0);
          }
          mbar_wait(emptyA + 8 * r.idx, r.phase);
          const uint32_t bar = fullA + 8 * r.idx, slot = sb + OFF_A + r.idx * SLOT_A;
          mbar_expect_tx(bar, SLOT_A);
          if (k >= 10 && k < 14) tma2d(slot, &maps.hs, bar, 64 * (k - 10) + 320 * rank, 128 * i);
          else tma2d_mc(slot + rank * 8192, k < 10 ? &maps.x : &maps.x1, bar, 64 * (k < 10 ? k : (k - 14 + k3) % 10), 128 * i + 64 * rank);
          r.next<NA>();
        }
      }
    } else if (pw == 1) {
      if (tid == 288) {
        Ring r{0, 1};
#pragma unroll 1
        for (int k = 0; k < 18; k++) {
          mbar_wait(emptyB + 8 * r.idx, r.phase);
          const uint32_t bar = fullB + 8 * r.idx, slot = sb + OFF_B + r.idx * SLOT_B;
          if (k < 10) {
            mbar_expect_tx(bar, 40960);
            tma4d(slot + 8192, &maps.qm, bar, 0, 64 * k, 0, j);
            tma3d(slot, &maps.w1m, bar, 0, 64 * k, j);
            tma4d(slot + 32768 + 2048, &maps.qr, bar, 64, 64 * k, 0, j);
            tma3d(slot + 32768, &maps.w1r, bar, 64, 64 * k, j);
          } else if (k < 13) {
            mbar_expect_tx(bar, k < 12 ? 40960 : 20480);
            tma3d(slot, &maps.w2, bar, 0, 320 * rank + 128 * (k - 10), 5 * (j >> 1));
            if (k < 12) tma3d(slot + 20480, &maps.w2, bar, 0, 320 * rank + 128 * (k - 10) + 64, 5 * (j >> 1));
          } else {
            if (k == 13) mbar_wait(bars + 8 * B_KVR, 0);
            mbar_expect_tx(bar, 49152);
            tma3d(slot, &maps.w3, bar, 0, 64 * ((2 * (k - 13) + k3) % 10), 3 * j);
            tma3d(slot + 24576, &maps.w3, bar, 0, 64 * ((2 * (k - 13) + 1 + k3) % 10), 3 * j);
          }
          r.next<NB>();
        }
#pragma unroll 1
        for (int n = 0; n < 8; n++) {
          if (n < 3) { mbar_wait(emptyB + 8 * r.idx, r.phase); r.next<NB>(); }
          if (n == 0) mbar_wait(fullA + 24, 1);
          if (n >= 4) mbar_wait(bars + 8 * (B_EMPTY4 + n - 4), 0);
          const uint32_t bar = bars + 8 * (B_FULL4 + n), set = sb + ((n >> 1) & 1) * SET4;
          const int h = n & 1, m = ((j >> 1) + 1 + (n >> 1)) & 3;
          mbar_expect_tx(bar, h ? 40960 : 46080);
          tma3d(set + (h ? 46080 : 0), h ? &maps.w4 : &maps.wo, bar, 0, h ? 192 * j + 64 : 80 * j, 5 * m);
          tma3d(set + (h ? 66560 : 25600), &maps.w4, bar, 0, 192 * j + 128 * h, 5 * m);
        }
        mbar_wait(bars + 8 * (B_EMPTY4 + 4), 0);
        mbar_expect_tx(bars + 8 * B_XR, 20480);
        tma2d(sb + OFF_OUT, &maps.st_x1, bars + 8 * B_XR, 80 * j, 128 * i);
      }
    } else {
      const unsigned epoch = get_epoch();
      float* accg = g_acc[epoch & 1];
      if (pw == 2) {
        if (tid == 320) {
          flag_wait(FL_CS, (epoch + 1) * NSVC);
          flag_wait(FL_ST + i, (epoch + 1) * 8u);
          fence_async_glb();
          *reinterpret_cast<volatile uint32_t*>(sgen + OFF_BAR + 8 * NBAR) = (epoch + 1) & 1;
          mbar_expect_tx(bars + 8 * B_CS, 320 + 2048 + 12800);
          bulk_load(sb + OFF_CS, g_cs[epoch & 1] + 80 * j, 320, bars + 8 * B_CS);
          bulk_load(sb + OFF_XST, g_xstat + 128 * i, 2048, bars + 8 * B_CS);
          bulk_load(sb + OFF_MISC, g_wphi + j * 800, 12800, bars + 8 * B_CS);
          TSTAMPX(21);
          flag_wait(FL_KV + j, (epoch + 1) * 16u);
          mbar_wait(bars + 8 * B_SIGX1, 0);
          mbar_expect_tx(bars + 8 * B_KV, KV_J * 4);
          bulk_load(sb + OFF_A + SLOT_A, accg + j * KV_J, KV_J * 4, bars + 8 * B_KV);
          TSTAMPX(22);
          flag_wait(FL_CS3, (epoch + 1) * NSVC);
          flag_wait(FL_S1 + i, (epoch + 1) * 8u);
          fence_async_glb();
          mbar_expect_tx(bars + 8 * B_ST1, 8192 + 768);
          bulk_load(sb + OFF_CS + 320, g_cs[epoch & 1] + D_ + 192 * j, 768, bars + 8 * B_ST1);
          bulk_load(sb + OFF_MISC, g_st1 + 128 * i * 8, 8192, bars + 8 * B_ST1);
        }
        __syncwarp();
#pragma unroll 1
        for (int c = 0; c < 3; c++) {
          mbar_wait(bars + 8 * (B_EMPTY4 + (c ? 5 : 4)), 0);
          const uint4* src = g_part + (size_t)((i * 8 + j) * 3 + c) * 1280;
          const unsigned* tp = reinterpret_cast<const unsigned*>(src + 1024 + (lane & 7) * 32 + 31);
          uint32_t n = 0;
          while (!__all_sync(0xffffffffu, (ld_acquire(tp) ^ epoch) & 1u) && ++n < (WAIT_LIMIT >> 2)) {}
          if (tid == 320) {
            mbar_expect_tx(bars + 8 * (B_RDY + c), 20480);
            bulk_load(sb + (c ? 25600 + 20480 * c : 0), src, 20480, bars + 8 * (B_RDY + c));
          }
        }
      }
      if (tid == 352) {
        mbar_wait(bars + 8 * B_SIGP, 0);
        flag_add(FL_ST + i);
        TSTAMPX(20);
        const int shift = (j < 2) ? 1 : (j < 4) ? -1 : (j < 6) ? 2 : -2;
        prefetch_tmap(&maps.st_h); prefetch_tmap(&maps.st_x1); prefetch_tmap(&maps.hs); prefetch_tmap(&maps.x1); prefetch_tmap(&maps.xr);
        prefetch_tmap(&maps.w2); prefetch_tmap(&maps.w3); prefetch_tmap(&maps.w4); prefetch_tmap(&maps.wo);
        mbar_wait(bars + 8 * B_SIGH, 0);
        TSTAMPX(23);
        fence_async_smem();
        tma2d_store(&maps.st_h, sb + OFF_STG, 80 * j, 128 * i + 2 + shift);
        bulk_commit(); bulk_wait<0>();
        flag_add(FL_H + 2 * i + (j >> 2));
        flag_add_relaxed(FL_H + 2 * ((i + (shift > 0 ? 1 : -1)) & 15) + (j >> 2));
        mbar_arrive(bars + 8 * B_HST);
        TSTAMPX(24);
        mbar_wait(bars + 8 * B_SIGKV, 0);
        TSTAMPX(25);
        fence_async_smem();
#pragma unroll 1
        for (int u = 0; u < 4; u++)
          asm volatile("cp.reduce.async.bulk.global.shared::cta.bulk_group.add.f32 [%0], [%1], %2;"
                       ::"l"(accg + j * KV_J + (u >> 1) * KV_PAIR + (u & 1) * 1024), "r"(sb + OFF_B + SPARE + (u & 1) * SLOT_B + (u >> 1) * 4096),
                       "r"((u & 1) ? KV_PAIR * 4 - 4096 : 4096) : "memory");
        bulk_commit(); bulk_wait<0>();
        mbar_arrive(bars + 8 * B_KVR);
        flag_add(FL_KV + j);
        TSTAMPX(26);
        mbar_wait(bars + 8 * B_SIGX1, 0);
        TSTAMPX(27);
        fence_async_smem();
        tma2d_store(&maps.st_x1, sb + OFF_STG, 80 * j, 128 * i);
        bulk_commit(); bulk_wait<0>();
        flag_add(FL_X1 + i);
        mbar_arrive_cta(bars + 8 * B_X1P, 0); mbar_arrive_cta(bars + 8 * B_X1P, 1);
        TSTAMPX(28);
        mbar_wait(bars + 8 * B_MFREE, 0);
        flag_add(FL_S1 + i);
      }
    }
  } else {
    uint4 pv[5], pw_[5];
    {
      const int row = 128 * i + 16 * j + (tid >> 4), l16 = tid & 15;
#pragma unroll
      for (int c = 0; c < 5; c++) pv[c] = __ldg(reinterpret_cast<const uint4*>(x + (size_t)row * D_ + c * 128 + l16 * 8));
#pragma unroll
      for (int c = 0; c < 5; c++) pw_[c] = __ldg(reinterpret_cast<const uint4*>(gate_w + c * 128 + l16 * 8));
    }
    asm volatile("barrier.cluster.arrive.relaxed.aligned;" ::: "memory");
    asm volatile("setmaxnreg.inc.sync.aligned.u32 232;");
    const int wg = tid >> 7, warp = tid >> 5, lane = tid & 31, t = lane & 3;
    const int rloc = warp * 16 + (lane >> 2);
    const float* s_cs = reinterpret_cast<const float*>(sgen + OFF_CS);
    auto signal = [&](int b) {
      __syncwarp();
      if (lane == 0) mbar_arrive(bars + 8 * b);
    };
    auto releaseB = [&](uint32_t bar) {
      __syncwarp();
      if (lane == 0) mbar_arrive(bar);
    };
    auto release = [&](uint32_t bar) {
      __syncwarp();
      if (lane < 2) mbar_arrive_cta(bar, lane);
    };
    const uint32_t stg_lane = (warp * 16 + ((lane >> 3) & 1) * 8 + (lane & 7)) * 160 + (lane >> 4) * 16;

    auto stage_tile = [&](uint32_t stg, const uint32_t (&v)[2][10]) {
#pragma unroll
      for (int s = 0; s < 5; s++) stsm4(stg + stg_lane + s * 32, v[0][2 * s], v[1][2 * s], v[0][2 * s + 1], v[1][2 * s + 1]);
    };

    {
      float f[40];
      float s = 0.f, gs = 0.f;
#pragma unroll
      for (int c = 0; c < 5; c++) {
        const uint32_t vv[4] = {pv[c].x, pv[c].y, pv[c].z, pv[c].w}, ww[4] = {pw_[c].x, pw_[c].y, pw_[c].z, pw_[c].w};
#pragma unroll
        for (int e = 0; e < 4; e++) {
          f[8 * c + 2 * e] = bf_lo(vv[e]); f[8 * c + 2 * e + 1] = bf_hi(vv[e]);
          s += f[8 * c + 2 * e] + f[8 * c + 2 * e + 1];
          gs = fmaf(f[8 * c + 2 * e], bf_lo(ww[e]), gs); gs = fmaf(f[8 * c + 2 * e + 1], bf_hi(ww[e]), gs);
        }
      }
#pragma unroll
      for (int o = 1; o < 16; o <<= 1) { s += __shfl_xor_sync(0xffffffffu, s, o); gs += __shfl_xor_sync(0xffffffffu, gs, o); }
      const float mean = s * (1.f / D_);
      float q = 0.f;
#pragma unroll
      for (int e = 0; e < 40; e++) { const float d = f[e] - mean; q = fmaf(d, d, q); }
#pragma unroll
      for (int o = 1; o < 16; o <<= 1) q += __shfl_xor_sync(0xffffffffu, q, o);
      const float rstd = rsqrtf(q * (1.f / D_) + 1e-5f);
      asm volatile("barrier.cluster.wait.aligned;" ::: "memory");
      if ((tid & 15) == 0) g_xstat[128 * i + 16 * j + (tid >> 4)] = make_float4(rstd, -mean, rcp(1.f + __expf(-gs)), 0.f);
      signal(B_SIGP);
    }
    TSTAMP(1);

    Ring ra{0, 0}, rb{0, 0};
    uint32_t qp[2][10], P[2][10];
    float st_g[2];
    {
      float accM[128], accR[32];
      uint32_t pa = 0, pb = 0;
#pragma unroll 1
      for (int k = 0; k < 10; k++) {
        mbar_wait(fullA + 8 * ra.idx, ra.phase);
        if (tid == 0) TRACE(32 + k);
        mbar_wait(fullB + 8 * rb.idx, rb.phase);
        if (tid == 0) TRACE(64 + k);
        if (k == 0) TSTAMP(2);
        const uint32_t a0 = sb16 + ((OFF_A + ra.idx * SLOT_A + wg * 8192) >> 4), b0 = sb16 + ((OFF_B + rb.idx * SLOT_B) >> 4);
        wg_fence();
#pragma unroll
        for (int kk = 0; kk < 4; kk++) {
          const uint64_t da = make_desc(a0, kk * 32, 16, 1024, 1);
          if (kk == 0) {
            mma_ss256_p(accM, da, make_desc(b0, 0, 8192, 1024, 1), k);
            mma_ss64_p(accR, da, make_desc(b0, 32768, 2048, 256, 3), k);
          } else {
            mma_ss256(accM, da, make_desc(b0, kk * 2048, 8192, 1024, 1));
            mma_ss64(accR, da, make_desc(b0, 32768 + kk * 512, 2048, 256, 3));
          }
          if (kk == 0) {
            wg_commit();
            if (k > 0) {
              wg_wait<1>();
              release(emptyA + 8 * pa);
              releaseB(emptyB + 8 * pb);
            }
          }
        }
        wg_commit();
        pa = ra.idx; pb = rb.idx;
        ra.next<NA>(); rb.next<NB>();
      }
      TSTAMP(18);
      float st_rstd[2], st_mr[2];
      mbar_wait(bars + 8 * B_CS, 0);
#pragma unroll
      for (int r = 0; r < 2; r++) {
        const uint4 st = lds128(sb + OFF_XST + (rloc + 8 * r) * 16);
        st_rstd[r] = __uint_as_float(st.x); st_mr[r] = __uint_as_float(st.y); st_g[r] = __uint_as_float(st.z);
      }
      TSTAMP(19);
      wg_wait<0>();
      fence_regs(accM); fence_regs(accR);
      TSTAMP(3);
      release(emptyA + 8 * pa);
#define ACC(P_, G, I_) ((G) < 8 ? accM[(P_) * 32 + ((G) & 7) * 4 + (I_)] : accR[(P_) * 8 + ((G) & 1) * 4 + (I_)])
      {
        uint32_t hv[2][10];
        const GeluC g0 = gelu_consts(st_rstd[0], 1.f), g1 = gelu_consts(st_rstd[1], 1.f);
#pragma unroll
        for (int g = 0; g < 10; g++) {
          const float2 cs = *reinterpret_cast<const float2*>(s_cs + 8 * g + 2 * t);
          const float v0 = gelu_s(fmaf(st_mr[0], cs.x, ACC(0, g, 0)), g0), v1 = gelu_s(fmaf(st_mr[0], cs.y, ACC(0, g, 1)), g0);
          const float v2 = gelu_s(fmaf(st_mr[1], cs.x, ACC(0, g, 2)), g1), v3 = gelu_s(fmaf(st_mr[1], cs.y, ACC(0, g, 3)), g1);
          hv[0][g] = pack_bf16(v0, v1); hv[1][g] = pack_bf16(v2, v3);
        }
        bar_sync(1, 256);
        stage_tile(sb + OFF_STG, hv);
        signal(B_SIGH);
      }
      TSTAMP(4);
      uint32_t kf[5][4], qf[5][4];
#pragma unroll
      for (int s = 0; s < 5; s++) {
        kf[s][0] = pack_bf16(ACC(2, 2 * s, 0), ACC(2, 2 * s, 1)); kf[s][1] = pack_bf16(ACC(2, 2 * s, 2), ACC(2, 2 * s, 3));
        kf[s][2] = pack_bf16(ACC(2, 2 * s + 1, 0), ACC(2, 2 * s + 1, 1)); kf[s][3] = pack_bf16(ACC(2, 2 * s + 1, 2), ACC(2, 2 * s + 1, 3));
        qf[s][0] = pack_bf16(ACC(1, 2 * s, 0), ACC(1, 2 * s, 1)); qf[s][1] = pack_bf16(ACC(1, 2 * s, 2), ACC(1, 2 * s, 3));
        qf[s][2] = pack_bf16(ACC(1, 2 * s + 1, 0), ACC(1, 2 * s + 1, 1)); qf[s][3] = pack_bf16(ACC(1, 2 * s + 1, 2), ACC(1, 2 * s + 1, 3));
      }
      float pk[40], pq[40];
      wg_fence();
#pragma unroll
      for (int s = 0; s < 5; s++) {
        if (s == 0) mma_rs80_k_z(pk, kf[s], make_desc(sb16, OFF_MISC, 16, 256, 3));
        else mma_rs80_k(pk, kf[s], make_desc(sb16, OFF_MISC + s * 2560, 16, 256, 3));
      }
      wg_commit();
#pragma unroll
      for (int s = 0; s < 5; s++) {
        if (s == 0) mma_rs80_k_z(pq, qf[s], make_desc(sb16, OFF_MISC, 16, 256, 3));
        else mma_rs80_k(pq, qf[s], make_desc(sb16, OFF_MISC + s * 2560, 16, 256, 3));
      }
      wg_commit();
      {
        const int mat = lane >> 3;
        const int tok = warp * 16 + (mat & 1) * 8 + (lane & 7);
        const uint32_t base = sb + OFF_B + SPARE + tok * 32 + (((mat >> 1) ^ ((tok >> 2) & 1)) << 4);
        const uint32_t ones = (t == 0) ? 0x00003f80u : 0u;
#pragma unroll
        for (int p = 0; p < 2; p++) {
#pragma unroll
          for (int gg = 0; gg < 3; gg++) {
            const int g0 = 5 * p + 2 * gg;
            uint32_t r0 = pack_bf16(ACC(3, g0, 0), ACC(3, g0, 1)), r1 = pack_bf16(ACC(3, g0, 2), ACC(3, g0, 3));
            uint32_t r2 = ones, r3 = ones;
            if (gg < 2) { r2 = pack_bf16(ACC(3, g0 + 1, 0), ACC(3, g0 + 1, 1)); r3 = pack_bf16(ACC(3, g0 + 1, 2), ACC(3, g0 + 1, 3)); }
            stsm4(base + gg * SLOT_B + p * 4096, r0, r1, r2, r3);
          }
        }
      }
#undef ACC
      wg_wait<1>();
      fence_regs(pk);
#pragma unroll
      for (int G = 0; G < 10; G++) {
        P[0][G] = pack_bf16(pk[4 * G], pk[4 * G + 1]); P[1][G] = pack_bf16(pk[4 * G + 2], pk[4 * G + 3]);
      }
      wg_wait<0>();
      fence_regs(pq);
      signal(B_WDEAD);
#pragma unroll
      for (int G = 0; G < 10; G++) {
        qp[0][G] = pack_bf16(pq[4 * G], pq[4 * G + 1]); qp[1][G] = pack_bf16(pq[4 * G + 2], pq[4 * G + 3]);
      }
    }

    uint32_t fr[10][4];
    int pass;
    pass = gridDim.y;
#pragma unroll 1
    do {
    feature_map(P, fr);
    if (pass != 0) {
    {
      const int mat = lane >> 3;
      const int tok = warp * 16 + (mat & 1) * 8 + (lane & 7);
      const uint32_t base = sb + OFF_B + tok * 32 + (((mat >> 1) ^ ((tok >> 2) & 1)) << 4);
#pragma unroll
      for (int G = 0; G < 10; G++) stsm4(base + G * 4096, fr[G][0], fr[G][1], fr[G][2], fr[G][3]);
      fence_async_smem();
      bar_sync(1, 256);
      float kv[40];
      const uint32_t va = sb16 + ((OFF_B + SPARE + wg * 4096) >> 4), vb = sb16 + ((OFF_B + wg * 20480) >> 4);
      wg_fence();
#pragma unroll
      for (int ks = 0; ks < 8; ks++) {
        if (ks == 0) mma_ss80_tt_z(kv, make_desc(va, 0, SLOT_B, 256, 3), make_desc(vb, 0, 4096, 256, 3));
        else mma_ss80_tt(kv, make_desc(va, ks * 512, SLOT_B, 256, 3), make_desc(vb, ks * 512, 4096, 256, 3));
      }
      wg_commit();
      uint32_t xv[2][10];
      float acc[80];
      TSTAMP(5);
      mbar_wait(fullA + 8 * 2, 0);
      mbar_wait(fullB + 8 * 1, 1);
      TSTAMP(6);
      wg_fence();
#pragma unroll
      for (int kk = 0; kk < 4; kk++) {
        const uint64_t da = make_desc(sb16 + wg * 512, OFF_A + 2 * SLOT_A + kk * 32, 16, 1024, 1);
        const uint64_t db = make_desc(sb16, OFF_B + SLOT_B + kk * 1024, 4096, 512, 2);
        if (kk == 0) mma_ss160_z(acc, da, db); else mma_ss160(acc, da, db);
      }
      wg_commit();
      ra.next<NA>();
      wg_wait<1>();
      fence_regs(kv);
      TSTAMP(31);
      releaseB(emptyB); release(bars + 8 * B_PEER2);
      auto kv_sts = [&](uint32_t o, uint32_t a0, uint32_t a1, uint32_t a2, uint32_t a3) {
        sts128(sb + OFF_B + SPARE + wg * 4096 + o + (o >= 4096 ? SLOT_B - 4096 : 0), make_uint4(a0, a1, a2, a3));
      };
      const int m0 = (warp & 3) * 16 + (lane >> 2);
      bar_sync(4 + wg, 128);
#pragma unroll
      for (int r = 0; r < 2; r++) {
        const int m = m0 + 8 * r;
        const bool hi = m >= 20;
        uint32_t v[10];
#pragma unroll
        for (int G = 0; G < 10; G++) v[G] = __float_as_uint(hi ? kv[4 * G + 2 * r + 1] : kv[4 * G + 2 * r]);
        const uint32_t p = 4 * (m < 40 ? m * 48 + t * 12 : 1920 + t * 24 + 12);
        if (m <= 40) { kv_sts(p, v[0], v[1], v[2], v[3]); kv_sts(p + 16, v[4], v[5], v[6], v[7]); kv_sts(p + 32, v[8], v[9], 0u, 0u); }
      }
      if (m0 == 32) {
        const uint32_t p = 4 * (1920 + t * 24);
        kv_sts(p, __float_as_uint(kv[2]), __float_as_uint(kv[6]), __float_as_uint(kv[10]), __float_as_uint(kv[14]));
        kv_sts(p + 16, __float_as_uint(kv[18]), __float_as_uint(kv[22]), __float_as_uint(kv[26]), __float_as_uint(kv[30]));
        kv_sts(p + 32, __float_as_uint(kv[34]), __float_as_uint(kv[38]), 0u, 0u);
      }
      signal(B_SIGKV);
      uint32_t pa = 2, pb = 1;
#pragma unroll 1
      for (int k = 1; k < 5; k++) {
        mbar_wait(k < 4 ? fullA + 8 * ra.idx : bars + 8 * B_T4, k < 4 ? ra.phase : 0);
        if ((k & 1) == 0) mbar_wait(fullB + 8 * rb.idx, rb.phase);
        const uint32_t a0 = sb16 + ((OFF_A + (k < 4 ? ra.idx : NA) * SLOT_A + wg * 8192) >> 4);
        const uint32_t b0 = sb16 + ((OFF_B + rb.idx * SLOT_B + (k & 1) * 20480) >> 4);
        wg_fence();
#pragma unroll
        for (int kk = 0; kk < 4; kk++) {
          mma_ss160(acc, make_desc(a0, kk * 32, 16, 1024, 1), make_desc(b0, kk * 1024, 4096, 512, 2));
          if (kk == 0) {
            wg_commit();
            wg_wait<1>();
            if (k != 4) release(emptyA + 8 * pa);
            if ((k & 1) == 0) releaseB(emptyB + 8 * pb);
          }
        }
        wg_commit();
        pa = ra.idx; pb = rb.idx;
        if (k < 4) ra.next<NA>();
        if ((k & 1) || k == 4) rb.next<NB>();
      }
      mbar_wait(bars + 8 * B_PEER2, 0);
      wg_wait<0>();
      fence_regs(acc);
      TSTAMP(7);
      {
        uint32_t sn[20];
        if (rank) {
#pragma unroll
          for (int e = 0; e < 20; e++) sn[e] = pack_bf16(acc[2 * e], acc[2 * e + 1]);
#pragma unroll
          for (int e = 0; e < 40; e++) acc[e] = acc[40 + e];
        } else {
#pragma unroll
          for (int e = 0; e < 20; e++) sn[e] = pack_bf16(acc[40 + 2 * e], acc[41 + 2 * e]);
        }
        const uint32_t peer = map_peer(sb, rank ^ 1);
#pragma unroll
        for (int q = 0; q < 5; q++)
          st_async16(peer + OFF_B + 20480 + tid * 16 + q * 4096, sn[4 * q], sn[4 * q + 1], sn[4 * q + 2], sn[4 * q + 3],
                     peer + OFF_BAR + 8 * (B_DSR + 8 + wg));
        mbar_wait(bars + 8 * B_XR, 0);
#pragma unroll
        for (int g = 0; g < 10; g++) {
          const uint32_t x0 = lds32(sb + OFF_STG + rloc * 160 + t * 4 + g * 16), x1 = lds32(sb + OFF_STG + rloc * 160 + 1280 + t * 4 + g * 16);
          acc[4 * g] += bf_lo(x0); acc[4 * g + 1] += bf_hi(x0);
          acc[4 * g + 2] += bf_lo(x1); acc[4 * g + 3] += bf_hi(x1);
        }
        mbar_wait(bars + 8 * (B_DSR + 8 + wg), 0);
#pragma unroll
        for (int q = 0; q < 5; q++) {
          const uint4 v = lds128(sb + OFF_B + 20480 + tid * 16 + q * 4096);
          float* d = &acc[8 * q];
          d[0] += bf_lo(v.x); d[1] += bf_hi(v.x); d[2] += bf_lo(v.y); d[3] += bf_hi(v.y);
          d[4] += bf_lo(v.z); d[5] += bf_hi(v.z); d[6] += bf_lo(v.w); d[7] += bf_hi(v.w);
          xv[0][2 * q] = pack_bf16(d[0], d[1]); xv[1][2 * q] = pack_bf16(d[2], d[3]);
          xv[0][2 * q + 1] = pack_bf16(d[4], d[5]); xv[1][2 * q + 1] = pack_bf16(d[6], d[7]);
        }
        releaseB(emptyB + 8 * pb);
      }
      TSTAMP(16);
      stage_tile(sb + OFF_STG, xv);
      signal(B_SIGX1);
      TSTAMP(17);
#pragma unroll
      for (int r = 0; r < 2; r++) {
        float s = 0.f;
#pragma unroll
        for (int g = 0; g < 10; g++) s += acc[4 * g + 2 * r] + acc[4 * g + 2 * r + 1];
        s += __shfl_xor_sync(0xffffffffu, s, 1); s += __shfl_xor_sync(0xffffffffu, s, 2);
        const float mu = s * (1.f / 80.f);
        float q = 0.f;
#pragma unroll
        for (int g = 0; g < 10; g++) {
          const float d0 = acc[4 * g + 2 * r] - mu, d1 = acc[4 * g + 2 * r + 1] - mu;
          q = fmaf(d0, d0, q); q = fmaf(d1, d1, q);
        }
        q += __shfl_xor_sync(0xffffffffu, q, 1); q += __shfl_xor_sync(0xffffffffu, q, 2);
        if (t == 0) g_st1[(128 * i + rloc + 8 * r) * 8 + j] = make_float2(mu, q);
      }
    }
    TSTAMP(8);
#pragma unroll
    for (int G = 0; G < 10; G++) { P[0][G] = qp[0][G]; P[1][G] = qp[1][G]; }
    }
    asm volatile("" : "+r"(pass));
    } while (pass-- != 0);

    uint32_t of[5][4];
    {
      mbar_wait(bars + 8 * B_KV, 0);
#pragma unroll 1
      for (int it = tid; it < 384; it += 256) {
        const int p = it >= 192, rem = it - 192 * p, n = rem >> 2, tq = rem & 3;
        const uint32_t sp = sb + OFF_A + SLOT_A + 4 * (p * KV_PAIR + (n < 40 ? n * 48 + tq * 12 : 1920 + tq * 24 + (n & 1) * 12));
        const uint4 ka = lds128(sp), kb = lds128(sp + 16), kc = lds128(sp + 32);
        const uint32_t v[10] = {ka.x, ka.y, ka.z, ka.w, kb.x, kb.y, kb.z, kb.w, kc.x, kc.y};
        const int sh = (n < 40 ? (n >= 20) : (n & 1)) * 16;
        uint8_t* dst = sgen + OFF_MISC + p * 7680 + n * 32 + tq * 4;
        const int sw = ((n >> 2) & 1) << 4;
#pragma unroll
        for (int G = 0; G < 10; G++)
          *reinterpret_cast<uint32_t*>(dst + (G >> 1) * 1536 + (((G & 1) << 4) ^ sw)) = pack_bf16(__uint_as_float(v[G]), 0.f) << sh;
      }
      release(emptyA + 8);
      fence_async_smem();
      bar_sync(1, 256);
      float o0[24], o1[24];
      wg_fence();
#pragma unroll
      for (int g = 0; g < 5; g++) {
        if (g == 0) mma_rs48_k_z(o0, fr[g], make_desc(sb16, OFF_MISC, 16, 256, 3));
        else mma_rs48_k(o0, fr[g], make_desc(sb16, OFF_MISC + g * 1536, 16, 256, 3));
      }
#pragma unroll
      for (int g = 0; g < 5; g++) {
        if (g == 0) mma_rs48_k_z(o1, fr[5], make_desc(sb16, OFF_MISC + 7680, 16, 256, 3));
        else mma_rs48_k(o1, fr[5 + g], make_desc(sb16, OFF_MISC + 7680 + g * 1536, 16, 256, 3));
      }
      wg_commit();
      wg_wait<0>();
      fence_regs(o0); fence_regs(o1);
      signal(B_MFREE);
#pragma unroll
      for (int r = 0; r < 2; r++) {
        const float a0 = __fdividef(st_g[r], o0[20 + 2 * r] + 1e-6f), a1 = __fdividef(st_g[r], o0[21 + 2 * r] + 1e-6f);
        const float b0 = __fdividef(st_g[r], o1[20 + 2 * r] + 1e-6f), b1 = __fdividef(st_g[r], o1[21 + 2 * r] + 1e-6f);
        const float am = t < 2 ? a0 : a1, bm = t < 2 ? b0 : b1;
#pragma unroll
        for (int g = 0; g < 5; g++) {
          const float sa = g < 2 ? a0 : (g == 2 ? am : a1), sb2 = g < 2 ? b0 : (g == 2 ? bm : b1);
          of[g >> 1][(g & 1) * 2 + r] = pack_bf16(o0[4 * g + 2 * r] * sa, o0[4 * g + 2 * r + 1] * sa);
          of[(5 + g) >> 1][((5 + g) & 1) * 2 + r] = pack_bf16(o1[4 * g + 2 * r] * sb2, o1[4 * g + 2 * r + 1] * sb2);
        }
      }
    }
    TSTAMP(9);

    uint32_t hf[12][4];
    float ac4[80];
    auto unit = [&](auto uc, uint32_t b0) {
      constexpr int u = decltype(uc)::value;
#pragma unroll
      for (int s = 0; s < (u ? 4 : 5); s++) {
        const uint64_t db = make_desc(b0, (u ? 5120 + 20480 * u : 0) + s * 1024, u ? 4096 : 5120, 512, 2);
        if (u == 0 && s == 0) mma_rs160_n_z(ac4, of[0], db);
        else if (u == 0) mma_rs160_n(ac4, of[s], db);
        else mma_rs160_n(ac4, hf[(4 * u + 8 + s) % 12], db);
      }
      wg_commit();
    };
    {
      float acc[96];
      uint32_t pa = 0, pb = 0;
#pragma unroll 1
      for (int k = 0; k < 10; k++) {
        mbar_wait(fullA + 8 * ra.idx, ra.phase);
        if (tid == 0) TRACE(52 + k);
        if ((k & 1) == 0) mbar_wait(fullB + 8 * rb.idx, rb.phase);
        if (tid == 0) TRACE(84 + k);
        if (k == 0) TSTAMP(10);
        const uint32_t a0 = sb16 + ((OFF_A + ra.idx * SLOT_A + wg * 8192) >> 4);
        const uint32_t b0 = sb16 + ((OFF_B + rb.idx * SLOT_B + (k & 1) * 24576) >> 4);
        wg_fence();
#pragma unroll
        for (int kk = 0; kk < 4; kk++) {
          if (kk == 0) mma_ss192_p(acc, make_desc(a0, 0, 16, 1024, 1), make_desc(b0, 0, 8192, 1024, 1), k);
          else mma_ss192(acc, make_desc(a0, kk * 32, 16, 1024, 1), make_desc(b0, kk * 2048, 8192, 1024, 1));
          if (kk == 0) {
            wg_commit();
            if (k > 0) {
              wg_wait<1>();
              release(emptyA + 8 * pa);
              if ((k & 1) == 0) releaseB(emptyB + 8 * pb);
            }
          }
        }
        wg_commit();
        pa = ra.idx; pb = rb.idx;
        ra.next<NA>();
        if (k & 1) rb.next<NB>();
      }
      float rs[2], mm[2];
      mbar_wait(bars + 8 * B_ST1, 0);
#pragma unroll
      for (int r = 0; r < 2; r++) {
        const uint4 su = lds128(sb + OFF_MISC + (rloc + 8 * r) * 64 + t * 16);
        const float m0 = __uint_as_float(su.x), m1 = __uint_as_float(su.z);
        float mu = m0 + m1;
        mu += __shfl_xor_sync(0xffffffffu, mu, 1); mu += __shfl_xor_sync(0xffffffffu, mu, 2);
        mu *= 0.125f;
        const float d0 = m0 - mu, d1 = m1 - mu;
        float q = __uint_as_float(su.y) + __uint_as_float(su.w) + 80.f * (d0 * d0 + d1 * d1);
        q += __shfl_xor_sync(0xffffffffu, q, 1); q += __shfl_xor_sync(0xffffffffu, q, 2);
        rs[r] = rsqrtf(q * (1.f / D_) + 1e-5f);
        mm[r] = -mu;
      }
      mbar_wait(bars + 8 * B_FULL4, 0);
      wg_fence();
      unit(IntC<0>{}, sb16);
      wg_wait<1>();
      fence_regs(acc);
      releaseB(emptyB + 8 * pb);
      release(bars + 8 * B_PEER);
      TSTAMP(11);
      const GeluC g0 = gelu_consts(rs[0], 1.f - st_g[0]), g1 = gelu_consts(rs[1], 1.f - st_g[1]);
#pragma unroll
      for (int g = 0; g < 24; g++) {
        const float2 cs = *reinterpret_cast<const float2*>(s_cs + 80 + 8 * g + 2 * t);
        const float v0 = gelu_s(fmaf(mm[0], cs.x, acc[4 * g]), g0), v1 = gelu_s(fmaf(mm[0], cs.y, acc[4 * g + 1]), g0);
        const float v2 = gelu_s(fmaf(mm[1], cs.x, acc[4 * g + 2]), g1), v3 = gelu_s(fmaf(mm[1], cs.y, acc[4 * g + 3]), g1);
        hf[g >> 1][(g & 1) * 2] = pack_bf16(v0, v1);
        hf[g >> 1][(g & 1) * 2 + 1] = pack_bf16(v2, v3);
        if (g == 7) { wg_fence(); unit(IntC<1>{}, sb16); }
        if (g == 15) { mbar_wait(bars + 8 * (B_FULL4 + 1), 0); wg_fence(); unit(IntC<2>{}, sb16); }
        if (g == 23) { wg_wait<1>(); signal(B_EMPTY4); wg_fence(); unit(IntC<3>{}, sb16); }
      }
    }
    TSTAMP(12);

    {
      float kp[40];
      uint32_t sn[20], kb[20];
      const uint32_t peer = map_peer(sb, rank ^ 1);
      const uint32_t tag = lds32(sb + OFF_BAR + 8 * NBAR);
      auto add8 = [&](int q, const uint4 v) {
        float* d = &kp[8 * q];
        d[0] += bf_lo(v.x); d[1] += bf_hi(v.x); d[2] += bf_lo(v.y); d[3] += bf_hi(v.y);
        d[4] += bf_lo(v.z); d[5] += bf_hi(v.z); d[6] += bf_lo(v.w); d[7] += bf_hi(v.w);
      };
      auto send = [&](int c) {
        const uint32_t dso = peer + OFF_DS + (c & 1) * 20480 + tid * 16, dsb = peer + OFF_BAR + 8 * (B_DSR + 2 * c + wg);
#pragma unroll
        for (int q = 0; q < 5; q++) st_async16(dso + q * 4096, sn[4 * q], sn[4 * q + 1], sn[4 * q + 2], sn[4 * q + 3], dsb);
      };
      mbar_wait(bars + 8 * B_PEER, 0);
      uint4* gdst = g_part + (size_t)i * 8 * 3840 + tid;
#pragma unroll 1
      for (int c = 0; c < 3; c++) {
        const uint32_t b0 = sb16 + ((c & 1) ? 0 : SET4 >> 4), bc = bars + 16 * c;
        mbar_wait(bc + 8 * (B_FULL4 + 2), 0);
        wg_wait<0>();
        fence_regs(ac4);
        if (rank) {
#pragma unroll
          for (int e = 0; e < 20; e++) { sn[e] = pack_bf16(ac4[2 * e], ac4[2 * e + 1]); kb[e] = pack_bf16(ac4[40 + 2 * e], ac4[41 + 2 * e]); }
        } else {
#pragma unroll
          for (int e = 0; e < 20; e++) { kb[e] = pack_bf16(ac4[2 * e], ac4[2 * e + 1]); sn[e] = pack_bf16(ac4[40 + 2 * e], ac4[41 + 2 * e]); }
        }
#pragma unroll
        for (int e = 0; e < 20; e++) asm volatile("" : "+r"(sn[e]), "+r"(kb[e]));
        send(c);
        if (c == 0 && wg == 1) bar_sync(2, 256);
        wg_fence();
        unit(IntC<0>{}, b0);
        if (lane == 0) mbar_arrive(bc + 8 * (B_EMPTY4 + 1));
        unit(IntC<1>{}, b0);
        if (c == 0 && wg == 0) bar_arrive(2, 256);
        {
          mbar_wait(bc + 8 * (B_DSR + wg), 0);
          uint4* dst = gdst + (((j + 2 * c + 2) & 7) * 3 + c) * 1280;
#pragma unroll
          for (int q = 0; q < 5; q++) {
            const uint4 v = lds128(sb + OFF_DS + (c & 1) * 20480 + tid * 16 + q * 4096);
            st_relaxed16(dst + q * 256, (add_bf2(v.x, kb[4 * q]) & ~1u) | tag, add_bf2(v.y, kb[4 * q + 1]),
                         add_bf2(v.z, kb[4 * q + 2]), add_bf2(v.w, kb[4 * q + 3]));
          }
        }
        mbar_wait(bc + 8 * (B_FULL4 + 3), 0);
        wg_fence();
        unit(IntC<2>{}, b0);
        wg_wait<1>();
        if (lane == 0) mbar_arrive(bc + 8 * (B_EMPTY4 + 2));
        unit(IntC<3>{}, b0);
      }
      auto partial = [&](int c, uint4 (&v)[5]) {
        mbar_wait(bars + 8 * (B_RDY + c), 0);
        uint32_t bad = 0;
#pragma unroll
        for (int q = 0; q < 5; q++) { v[q] = lds128(sb + (c ? 25600 + 20480 * c : 0) + tid * 16 + q * 4096); bad |= v[q].x ^ tag; }
#pragma unroll 1
        for (uint32_t n = 0; (bad & 1u) && n < (WAIT_LIMIT >> 2); n++) {
          bad = 0;
#pragma unroll
          for (int q = 0; q < 5; q++) { v[q] = ld_relaxed16(gdst + (j * 3 + c) * 1280 + q * 256); bad |= v[q].x ^ tag; }
        }
      };
      uint4 pa4[5], pb4[5];
      partial(0, pa4);
      wg_wait<0>();
      fence_regs(ac4);
      if (rank) {
#pragma unroll
        for (int e = 0; e < 20; e++) sn[e] = pack_bf16(ac4[2 * e], ac4[2 * e + 1]);
#pragma unroll
        for (int e = 0; e < 40; e++) kp[e] = ac4[40 + e];
      } else {
#pragma unroll
        for (int e = 0; e < 20; e++) sn[e] = pack_bf16(ac4[40 + 2 * e], ac4[41 + 2 * e]);
#pragma unroll
        for (int e = 0; e < 40; e++) kp[e] = ac4[e];
      }
      send(3);
      TSTAMP(13);
      {
        mbar_wait(bars + 8 * B_XR, 1);
        const float w0 = 1.f - st_g[0], w1s = 1.f - st_g[1];
        const uint32_t xa = sb + OFF_OUT + rloc * 160 + t * 4;
#pragma unroll
        for (int g = 0; g < 10; g++) {
          const uint32_t x0 = lds32(xa + g * 16), x1 = lds32(xa + 1280 + g * 16);
          kp[4 * g] = fmaf(w0, bf_lo(x0), kp[4 * g]); kp[4 * g + 1] = fmaf(w0, bf_hi(x0), kp[4 * g + 1]);
          kp[4 * g + 2] = fmaf(w1s, bf_lo(x1), kp[4 * g + 2]); kp[4 * g + 3] = fmaf(w1s, bf_hi(x1), kp[4 * g + 3]);
        }
      }
      partial(1, pb4);
#pragma unroll
      for (int q = 0; q < 5; q++)
        pa4[q] = make_uint4(add_bf2(pa4[q].x, pb4[q].x), add_bf2(pa4[q].y, pb4[q].y), add_bf2(pa4[q].z, pb4[q].z), add_bf2(pa4[q].w, pb4[q].w));
#pragma unroll
      for (int q = 0; q < 5; q++) add8(q, pa4[q]);
      partial(2, pb4);
      mbar_wait(bars + 8 * (B_DSR + 6 + wg), 0);
      TSTAMP(14);
#pragma unroll
      for (int q = 0; q < 5; q++) {
        const uint4 c = pb4[q], d = lds128(sb + OFF_DS + 20480 + tid * 16 + q * 4096);
        add8(q, make_uint4(add_bf2(c.x, d.x), add_bf2(c.y, d.y), add_bf2(c.z, d.z), add_bf2(c.w, d.w)));
      }
      __syncwarp();
      uint32_t ov[2][10];
#pragma unroll
      for (int g = 0; g < 10; g++) { ov[0][g] = pack_bf16(kp[4 * g], kp[4 * g + 1]); ov[1][g] = pack_bf16(kp[4 * g + 2], kp[4 * g + 3]); }
      stage_tile(sb + OFF_OUT, ov);
      __syncwarp();
      __nv_bfloat16* dst = out + (size_t)(128 * i + 16 * warp) * D_ + 80 * j;
#pragma unroll
      for (int q = 0; q < 5; q++) {
        const int id = q * 32 + lane, r = id / 10;
        *reinterpret_cast<uint4*>(dst + r * (D_ - 80) + id * 8) = lds128(sb + OFF_OUT + warp * 2560 + id * 16);
      }
    }
    TSTAMP(15);
    if (tid == 0) asm volatile("red.relaxed.gpu.global.add.u32 [%0], 1;" ::"l"(g_flags + FL_DONE * 32) : "memory");
  }
}

namespace {
typedef CUresult (*EncodeFn)(CUtensorMap*, CUtensorMapDataType, cuuint32_t, void*, const cuuint64_t*, const cuuint64_t*,
                             const cuuint32_t*, const cuuint32_t*, CUtensorMapInterleave, CUtensorMapSwizzle,
                             CUtensorMapL2promotion, CUtensorMapFloatOOBfill);

void encode(EncodeFn fn, CUtensorMap* m, const void* ptr, int rank, const cuuint64_t* dims, const cuuint64_t* strides,
            const cuuint32_t* box, CUtensorMapSwizzle swz) {
  cuuint32_t es[5] = {1, 1, 1, 1, 1};
  fn(m, CU_TENSOR_MAP_DATA_TYPE_BFLOAT16, rank, const_cast<void*>(ptr), dims, strides, box, es, CU_TENSOR_MAP_INTERLEAVE_NONE,
     swz, CU_TENSOR_MAP_L2_PROMOTION_L2_128B, CU_TENSOR_MAP_FLOAT_OOB_FILL_NONE);
}
}

extern "C" void kernel_launch(void* const* d_in, const int* in_sizes, int n_in, void* d_out, int out_size) {
  (void)in_sizes; (void)n_in; (void)out_size;
  const __nv_bfloat16* x = (const __nv_bfloat16*)d_in[0];
  const __nv_bfloat16* wqkv = (const __nv_bfloat16*)d_in[1];
  const __nv_bfloat16* wphi = (const __nv_bfloat16*)d_in[2];
  const __nv_bfloat16* wo = (const __nv_bfloat16*)d_in[3];
  const __nv_bfloat16* w1 = (const __nv_bfloat16*)d_in[5];
  const __nv_bfloat16* w2 = (const __nv_bfloat16*)d_in[6];
  const __nv_bfloat16* w3 = (const __nv_bfloat16*)d_in[7];
  const __nv_bfloat16* w4 = (const __nv_bfloat16*)d_in[8];
  const __nv_bfloat16* gate_w = (const __nv_bfloat16*)d_in[9];

  static EncodeFn enc = nullptr;
  static void *pHs = nullptr, *pX1 = nullptr;
  if (!enc) {
    cudaDriverEntryPointQueryResult qr;
    cudaGetDriverEntryPoint("cuTensorMapEncodeTiled", (void**)&enc, cudaEnableDefault, &qr);
    cudaGetSymbolAddress(&pHs, g_Hs);
    cudaGetSymbolAddress(&pX1, g_X1);
    cudaFuncSetAttribute(fused_kernel, cudaFuncAttributeMaxDynamicSharedMemorySize, SMEM_BYTES);
  }
  Maps m;
  {
    cuuint64_t dims[2] = {D_, S_}, str[1] = {D_ * 2};
    cuuint32_t box[2] = {64, 128}, boxh[2] = {64, 64};
    encode(enc, &m.x, x, 2, dims, str, boxh, CU_TENSOR_MAP_SWIZZLE_128B);
    encode(enc, &m.hs, (const char*)pHs + 2 * D_ * 2, 2, dims, str, box, CU_TENSOR_MAP_SWIZZLE_128B);
    encode(enc, &m.x1, pX1, 2, dims, str, boxh, CU_TENSOR_MAP_SWIZZLE_128B);
    cuuint32_t boxs[2] = {80, 128};
    cuuint64_t dimsp[2] = {D_, S_ + 4};
    encode(enc, &m.st_h, pHs, 2, dimsp, str, boxs, CU_TENSOR_MAP_SWIZZLE_NONE);
    encode(enc, &m.st_x1, pX1, 2, dims, str, boxs, CU_TENSOR_MAP_SWIZZLE_NONE);
    encode(enc, &m.xr, x, 2, dims, str, boxs, CU_TENSOR_MAP_SWIZZLE_NONE);
  }
  {
    cuuint64_t dims[3] = {80, D_, 8}, str[2] = {D_ * 2, 160};
    cuuint32_t boxm[3] = {64, 64, 1}, boxr[3] = {16, 64, 1};
    encode(enc, &m.w1m, w1, 3, dims, str, boxm, CU_TENSOR_MAP_SWIZZLE_128B);
    encode(enc, &m.w1r, w1, 3, dims, str, boxr, CU_TENSOR_MAP_SWIZZLE_32B);
  }
  {
    cuuint64_t dims[4] = {80, D_, 3, 8}, str[3] = {3 * D_ * 2, D_ * 2, 160};
    cuuint32_t boxm[4] = {64, 64, 3, 1}, boxr[4] = {16, 64, 3, 1};
    encode(enc, &m.qm, wqkv, 4, dims, str, boxm, CU_TENSOR_MAP_SWIZZLE_128B);
    encode(enc, &m.qr, wqkv, 4, dims, str, boxr, CU_TENSOR_MAP_SWIZZLE_32B);
  }
  {
    cuuint64_t dims[3] = {32, D_, 20}, dims4[3] = {32, F_, 20}, str[2] = {D_ * 2, 64};
    cuuint32_t box4[3] = {32, 64, 5}, boxo[3] = {32, 80, 5};
    encode(enc, &m.w4, w4, 3, dims4, str, box4, CU_TENSOR_MAP_SWIZZLE_64B);
    encode(enc, &m.wo, wo, 3, dims, str, boxo, CU_TENSOR_MAP_SWIZZLE_64B);
    encode(enc, &m.w2, w2, 3, dims, str, box4, CU_TENSOR_MAP_SWIZZLE_64B);
  }
  {
    cuuint64_t dims[3] = {64, D_, 24}, str[2] = {F_ * 2, 128};
    cuuint32_t box[3] = {64, 64, 3};
    encode(enc, &m.w3, w3, 3, dims, str, box, CU_TENSOR_MAP_SWIZZLE_128B);
  }
  fused_kernel<<<NCTA + NSVC, 384, SMEM_BYTES, cudaStreamPerThread>>>(m, x, wqkv, wphi, w1, w2, w3, w4, wo, gate_w, (__nv_bfloat16*)d_out);
}
```

```cpp
#include <cuda_runtime.h>
#include <cuda_bf16.h>
#include <cuda.h>
#include <stdint.h>

namespace {

constexpr int S_ = 2048, D_ = 640, F_ = 1536;
constexpr int NCTA = 128, NSVC = 4;
constexpr int KV_PAIR = 40 * 48 + 96;
constexpr int KV_J = 2 * KV_PAIR;

constexpr int SLOT_B = 49152, NB = 3;
constexpr int SLOT_A = 16384, NA = 4;
constexpr int OFF_B = 0;
constexpr int OFF_A = OFF_B + NB * SLOT_B;
constexpr int OFF_STG = OFF_A + 2 * SLOT_A;
constexpr int OFF_MISC = OFF_A + NA * SLOT_A;
constexpr int OFF_XST = OFF_MISC + 13312;
constexpr int OFF_CS = OFF_MISC + 16384;
constexpr int OFF_BAR = OFF_CS + 1088;
constexpr int SMEM_BYTES = OFF_BAR + 512 + 512 + 128;
constexpr int B_FULLA = 0, B_FULLB = 4, B_CS = 7, B_XR = 8, B_KV = 9, B_ST1 = 10, B_HST = 11, B_FULL4 = 12  , B_RDY = 20  , B_T4 = 23, B_KVR = 24,
              B_DSR = 25  , B_EMPTYB = 35  , B_SIGP = 38, B_SIGH = 39, B_SIGKV = 40, B_SIGX1 = 41, B_MFREE = 42,
              B_WDEAD = 43, B_EMPTY4 = 44  , B_EMPTYA = 52  , B_PEER = 56, B_PEER2 = 57, B_X1P = 58  , NBAR = 59;
constexpr int SPARE = 40960;
constexpr int SET4 = 87040, OFF_DS = 2 * SET4, OFF_OUT = 20480;

constexpr int FL_DONE = 0, FL_H = 1  , FL_X1 = FL_H + 32, FL_KV = FL_X1 + 16, FL_CS = FL_KV + 8, FL_CS3 = FL_CS + 1, FL_ST = FL_CS3 + 1;
constexpr int FL_S1 = FL_ST + 16, FL_COUNT = FL_S1 + 16;

struct Maps {
  CUtensorMap x, w1m, w1r, qm, qr, hs, w2, x1, w3, w4, wo, xr, st_h, st_x1;
};

}

__device__ __align__(1024) __nv_bfloat16 g_Hs[(S_ + 4) * D_];
__device__ __align__(1024) __nv_bfloat16 g_X1[S_ * D_];
__device__ __align__(128) float g_acc[2][8 * KV_J];
__device__ __align__(128) float g_cs[2][D_ + F_];
__device__ __align__(128) uint4 g_wphi[8 * 800];
__device__ __align__(128) float4 g_xstat[S_];
__device__ __align__(128) float2 g_st1[S_ * 8];
__device__ __align__(128) uint4 g_part[16 * 8 * 3 * 1280];
__device__ __align__(128) unsigned g_flags[FL_COUNT * 32];
#define TSTAMP(n) do {} while (0)
#define TSTAMPX(n) do {} while (0)
#define TRACE(n) do {} while (0)
#define TRS(n) do {} while (0)

namespace {

__device__ __forceinline__ long long gtime() { long long t; asm volatile("mov.u64 %0, %%globaltimer;" : "=l"(t)); return t; }
__device__ __forceinline__ uint32_t smem_u32(const void* p) { return (uint32_t)__cvta_generic_to_shared(p); }
__device__ __forceinline__ void mbar_init(uint32_t bar, int cnt) {
  asm volatile("mbarrier.init.shared::cta.b64 [%0], %1;" ::"r"(bar), "r"(cnt) : "memory");
}
__device__ __forceinline__ void mbar_expect_tx(uint32_t bar, int bytes) {
  asm volatile("mbarrier.arrive.expect_tx.shared::cta.b64 _, [%0], %1;" ::"r"(bar), "r"(bytes) : "memory");
}
__device__ __forceinline__ void mbar_arrive_cta(uint32_t bar, uint32_t cta) {
  asm volatile("{\n.reg .b32 ra;\nmapa.shared::cluster.u32 ra, %0, %1;\nmbarrier.arrive.shared::cluster.b64 _, [ra];\n}"
               ::"r"(bar), "r"(cta) : "memory");
}
__device__ __forceinline__ uint32_t mbar_try(uint32_t bar, uint32_t parity) {
  uint32_t ok;
  asm volatile("{\n.reg .pred p;\nmbarrier.try_wait.parity.shared::cta.b64 p, [%1], %2;\nselp.u32 %0, 1, 0, p;\n}"
               : "=r"(ok) : "r"(bar), "r"(parity) : "memory");
  return ok;
}
constexpr uint32_t WAIT_LIMIT = 1u << 17;
__device__ __forceinline__ void mbar_wait(uint32_t bar, uint32_t parity) {
  uint32_t n = 0;
  while (!mbar_try(bar, parity) && ++n < WAIT_LIMIT) {}
}
__device__ __forceinline__ unsigned ld_acquire(const unsigned* p) {
  unsigned v;
  asm volatile("ld.acquire.gpu.global.u32 %0, [%1];" : "=r"(v) : "l"(p) : "memory");
  return v;
}
__device__ __forceinline__ void flag_wait(int idx, unsigned target) {
  const unsigned* p = g_flags + idx * 32;
  uint32_t n = 0;
  while ((int)(ld_acquire(p) - target) < 0 && ++n < (WAIT_LIMIT >> 2)) {}
}
__device__ __forceinline__ void flag_add(int idx) {
  asm volatile("red.release.gpu.global.add.u32 [%0], 1;" ::"l"(g_flags + idx * 32) : "memory");
}
__device__ __forceinline__ void flag_add_relaxed(int idx) {
  asm volatile("red.relaxed.gpu.global.add.u32 [%0], 1;" ::"l"(g_flags + idx * 32) : "memory");
}
__device__ __forceinline__ uint32_t mbar_test(uint32_t bar, uint32_t parity) {
  uint32_t ok;
  asm volatile("{\n.reg .pred p;\nmbarrier.test_wait.parity.shared::cta.b64 p, [%1], %2;\nselp.u32 %0, 1, 0, p;\n}"
               : "=r"(ok) : "r"(bar), "r"(parity) : "memory");
  return ok;
}
__device__ __forceinline__ uint32_t lds32(uint32_t a) {
  uint32_t v;
  asm volatile("ld.shared.u32 %0, [%1];" : "=r"(v) : "r"(a) : "memory");
  return v;
}
__device__ __forceinline__ void mbar_arrive(uint32_t bar) {
  asm volatile("mbarrier.arrive.shared::cta.b64 _, [%0];" ::"r"(bar) : "memory");
}
__device__ __forceinline__ void fence_async_glb() { asm volatile("fence.proxy.async.global;" ::: "memory"); }
__device__ __forceinline__ void fence_async_smem() { asm volatile("fence.proxy.async.shared::cta;" ::: "memory"); }
__device__ __forceinline__ void bar_sync(int id, int n) { asm volatile("bar.sync %0, %1;" ::"r"(id), "r"(n) : "memory"); }

__device__ __forceinline__ void tma2d(uint32_t dst, const CUtensorMap* m, uint32_t bar, int c0, int c1) {
  asm volatile("cp.async.bulk.tensor.2d.shared::cluster.global.mbarrier::complete_tx::bytes [%0], [%1, {%3, %4}], [%2];"
               ::"r"(dst), "l"(m), "r"(bar), "r"(c0), "r"(c1) : "memory");
}
__device__ __forceinline__ void tma2d_mc(uint32_t dst, const CUtensorMap* m, uint32_t bar, int c0, int c1) {
  asm volatile("cp.async.bulk.tensor.2d.shared::cluster.global.mbarrier::complete_tx::bytes.multicast::cluster"
               " [%0], [%1, {%3, %4}], [%2], %5;"
               ::"r"(dst), "l"(m), "r"(bar), "r"(c0), "r"(c1), "h"((uint16_t)3) : "memory");
}
__device__ __forceinline__ void tma3d(uint32_t dst, const CUtensorMap* m, uint32_t bar, int c0, int c1, int c2) {
  asm volatile("cp.async.bulk.tensor.3d.shared::cluster.global.mbarrier::complete_tx::bytes [%0], [%1, {%3, %4, %5}], [%2];"
               ::"r"(dst), "l"(m), "r"(bar), "r"(c0), "r"(c1), "r"(c2) : "memory");
}
__device__ __forceinline__ void tma4d(uint32_t dst, const CUtensorMap* m, uint32_t bar, int c0, int c1, int c2, int c3) {
  asm volatile("cp.async.bulk.tensor.4d.shared::cluster.global.mbarrier::complete_tx::bytes [%0], [%1, {%3, %4, %5, %6}], [%2];"
               ::"r"(dst), "l"(m), "r"(bar), "r"(c0), "r"(c1), "r"(c2), "r"(c3) : "memory");
}
__device__ __forceinline__ void tma2d_store(const CUtensorMap* m, uint32_t src, int c0, int c1) {
  asm volatile("cp.async.bulk.tensor.2d.global.shared::cta.bulk_group [%0, {%2, %3}], [%1];"
               ::"l"(m), "r"(src), "r"(c0), "r"(c1) : "memory");
}
__device__ __forceinline__ void bulk_store(void* dst, uint32_t src, uint32_t bytes) {
  asm volatile("cp.async.bulk.global.shared::cta.bulk_group [%0], [%1], %2;" ::"l"(dst), "r"(src), "r"(bytes) : "memory");
}
__device__ __forceinline__ void bulk_load(uint32_t dst, const void* src, uint32_t bytes, uint32_t bar) {
  asm volatile("cp.async.bulk.shared::cluster.global.mbarrier::complete_tx::bytes [%0], [%1], %2, [%3];"
               ::"r"(dst), "l"(src), "r"(bytes), "r"(bar) : "memory");
}
__device__ __forceinline__ void bulk_commit() { asm volatile("cp.async.bulk.commit_group;" ::: "memory"); }
template <int N> __device__ __forceinline__ void bulk_wait() { asm volatile("cp.async.bulk.wait_group %0;" ::"n"(N) : "memory"); }
__device__ __forceinline__ void bulk_wait_read() { asm volatile("cp.async.bulk.wait_group.read 0;" ::: "memory"); }
__device__ __forceinline__ void bar_arrive(int id, int n) { asm volatile("bar.arrive %0, %1;" ::"r"(id), "r"(n) : "memory"); }
__device__ __forceinline__ uint4 lds128(uint32_t a) {
  uint4 v;
  asm volatile("ld.shared.v4.u32 {%0, %1, %2, %3}, [%4];" : "=r"(v.x), "=r"(v.y), "=r"(v.z), "=r"(v.w) : "r"(a) : "memory");
  return v;
}
__device__ __forceinline__ void sts128(uint32_t a, uint4 v) {
  asm volatile("st.shared.v4.u32 [%0], {%1, %2, %3, %4};" ::"r"(a), "r"(v.x), "r"(v.y), "r"(v.z), "r"(v.w) : "memory");
}
__device__ __forceinline__ uint4 ld_relaxed16(const uint4* p) {
  uint4 v;
  asm volatile("ld.relaxed.gpu.global.v4.u32 {%0, %1, %2, %3}, [%4];" : "=r"(v.x), "=r"(v.y), "=r"(v.z), "=r"(v.w) : "l"(p) : "memory");
  return v;
}
__device__ __forceinline__ void st_relaxed16(uint4* p, uint32_t a, uint32_t b, uint32_t c, uint32_t d) {
  asm volatile("st.relaxed.gpu.global.v4.u32 [%0], {%1, %2, %3, %4};" ::"l"(p), "r"(a), "r"(b), "r"(c), "r"(d) : "memory");
}
__device__ __forceinline__ uint32_t map_peer(uint32_t addr, uint32_t cta) {
  uint32_t r;
  asm("mapa.shared::cluster.u32 %0, %1, %2;" : "=r"(r) : "r"(addr), "r"(cta));
  return r;
}
__device__ __forceinline__ void st_async16(uint32_t addr, uint32_t a, uint32_t b, uint32_t c, uint32_t d, uint32_t bar) {
  asm volatile("st.async.weak.shared::cluster.mbarrier::complete_tx::bytes.v4.b32 [%0], {%1, %2, %3, %4}, [%5];"
               ::"r"(addr), "r"(a), "r"(b), "r"(c), "r"(d), "r"(bar) : "memory");
}
__device__ __forceinline__ void l2_prefetch(const void* p, uint32_t bytes) {
  asm volatile("cp.async.bulk.prefetch.L2.global [%0], %1;" ::"l"(p), "r"(bytes) : "memory");
}
__device__ __forceinline__ void prefetch_tmap(const CUtensorMap* m) {
  asm volatile("prefetch.tensormap [%0];" ::"l"(m) : "memory");
}
__device__ __forceinline__ uint64_t make_desc(uint32_t a16, uint32_t off, uint32_t lbo, uint32_t sbo, uint32_t swz) {
  const uint32_t lo = a16 + ((off >> 4) + ((lbo >> 4) << 16)), hi = (sbo >> 4) | (swz << 30);
  uint64_t d;
  asm("mov.b64 %0, {%1, %2};" : "=l"(d) : "r"(lo), "r"(hi));
  return d;
}
__device__ __forceinline__ void wg_fence() { asm volatile("wgmma.fence.sync.aligned;" ::: "memory"); }
__device__ __forceinline__ void wg_commit() { asm volatile("wgmma.commit_group.sync.aligned;" ::: "memory"); }
template <int N> __device__ __forceinline__ void wg_wait() { asm volatile("wgmma.wait_group.sync.aligned %0;" ::"n"(N) : "memory"); }
template <int N> __device__ __forceinline__ void fence_regs(float (&d)[N]) {
#pragma unroll
  for (int i = 0; i < N; i++) asm volatile("" : "+f"(d[i])::"memory");
}
template <int N> __device__ __forceinline__ void zero_regs(float (&d)[N]) {
#pragma unroll
  for (int i = 0; i < N; i++) d[i] = 0.f;
}
__device__ __forceinline__ uint32_t pack_bf16(float lo, float hi) {
  uint32_t r;
  asm("cvt.rn.bf16x2.f32 %0, %1, %2;" : "=r"(r) : "f"(hi), "f"(lo));
  return r;
}
__device__ __forceinline__ float bf_lo(uint32_t v) { return __uint_as_float(v << 16); }
__device__ __forceinline__ float bf_hi(uint32_t v) { return __uint_as_float(v & 0xffff0000u); }
__device__ __forceinline__ uint32_t max_bf2(uint32_t a, uint32_t b) {
  uint32_t r; asm("max.bf16x2 %0, %1, %2;" : "=r"(r) : "r"(a), "r"(b)); return r;
}
__device__ __forceinline__ uint32_t min_bf2(uint32_t a, uint32_t b) {
  uint32_t r; asm("min.bf16x2 %0, %1, %2;" : "=r"(r) : "r"(a), "r"(b)); return r;
}
__device__ __forceinline__ uint32_t add_bf2(uint32_t a, uint32_t b) {
  uint32_t r; asm("add.rn.bf16x2 %0, %1, %2;" : "=r"(r) : "r"(a), "r"(b)); return r;
}
__device__ __forceinline__ float ex2(float x) { float r; asm("ex2.approx.ftz.f32 %0, %1;" : "=f"(r) : "f"(x)); return r; }
__device__ __forceinline__ float rcp(float x) { float r; asm("rcp.approx.ftz.f32 %0, %1;" : "=f"(r) : "f"(x)); return r; }
__device__ __forceinline__ float tanh_ap(float x) { float r; asm("tanh.approx.f32 %0, %1;" : "=f"(r) : "f"(x)); return r; }
struct GeluC { float c0, c1, ch; };
__device__ __forceinline__ GeluC gelu_consts(float rstd, float scale) {
  return GeluC{0.7978845608f * rstd, 0.0356774081f * rstd * rstd * rstd, 0.5f * scale * rstd};
}
__device__ __forceinline__ float gelu_s(float y, const GeluC& c) {
  const float u = y * fmaf(y * y, c.c1, c.c0);
  const float hx = y * c.ch;
  return fmaf(hx, tanh_ap(u), hx);
}
__device__ __forceinline__ void stsm4(uint32_t addr, uint32_t r0, uint32_t r1, uint32_t r2, uint32_t r3) {
  asm volatile("stmatrix.sync.aligned.m8n8.x4.shared.b16 [%0], {%1, %2, %3, %4};"
               ::"r"(addr), "r"(r0), "r"(r1), "r"(r2), "r"(r3) : "memory");
}

__device__ __forceinline__ void red_add4(float* p, float a, float b, float c, float d) {
  asm volatile("red.global.add.v4.f32 [%0], {%1, %2, %3, %4};" ::"l"(p), "f"(a), "f"(b), "f"(c), "f"(d) : "memory");
}

__device__ __forceinline__ void mma_ss256(float (&d)[128], uint64_t descA, uint64_t descB) {
  asm volatile("wgmma.mma_async.sync.aligned.m64n256k16.f32.bf16.bf16 {"
      "%0, %1, %2, %3, %4, %5, %6, %7, %8, %9, %10, %11, %12, %13, %14, %15, "
      "%16, %17, %18, %19, %20, %21, %22, %23, %24, %25, %26, %27, %28, %29, %30, %31, "
      "%32, %33, %34, %35, %36, %37, %38, %39, %40, %41, %42, %43, %44, %45, %46, %47, "
      "%48, %49, %50, %51, %52, %53, %54, %55, %56, %57, %58, %59, %60, %61, %62, %63, "
      "%64, %65, %66, %67, %68, %69, %70, %71, %72, %73, %74, %75, %76, %77, %78, %79, "
      "%80, %81, %82, %83, %84, %85, %86, %87, %88, %89, %90, %91, %92, %93, %94, %95, "
      "%96, %97, %98, %99, %100, %101, %102, %103, %104, %105, %106, %107, %108, %109, %110, %111, "
      "%112, %113, %114, %115, %116, %117, %118, %119, %120, %121, %122, %123, %124, %125, %126, %127"
      "}, %128, %129, 1, 1, 1, 0, 1;\n"
      : "+f"(d[0]), "+f"(d[1]), "+f"(d[2]), "+f"(d[3]), "+f"(d[4]), "+f"(d[5]), "+f"(d[6]), "+f"(d[7]),
        "+f"(d[8]), "+f"(d[9]), "+f"(d[10]), "+f"(d[11]), "+f"(d[12]), "+f"(d[13]), "+f"(d[14]), "+f"(d[15]),
        "+f"(d[16]), "+f"(d[17]), "+f"(d[18]), "+f"(d[19]), "+f"(d[20]), "+f"(d[21]), "+f"(d[22]), "+f"(d[23]),
        "+f"(d[24]), "+f"(d[25]), "+f"(d[26]), "+f"(d[27]), "+f"(d[28]), "+f"(d[29]), "+f"(d[30]), "+f"(d[31]),
        "+f"(d[32]), "+f"(d[33]), "+f"(d[34]), "+f"(d[35]), "+f"(d[36]), "+f"(d[37]), "+f"(d[38]), "+f"(d[39]),
        "+f"(d[40]), "+f"(d[41]), "+f"(d[42]), "+f"(d[43]), "+f"(d[44]), "+f"(d[45]), "+f"(d[46]), "+f"(d[47]),
        "+f"(d[48]), "+f"(d[49]), "+f"(d[50]), "+f"(d[51]), "+f"(d[52]), "+f"(d[53]), "+f"(d[54]), "+f"(d[55]),
        "+f"(d[56]), "+f"(d[57]), "+f"(d[58]), "+f"(d[59]), "+f"(d[60]), "+f"(d[61]), "+f"(d[62]), "+f"(d[63]),
        "+f"(d[64]), "+f"(d[65]), "+f"(d[66]), "+f"(d[67]), "+f"(d[68]), "+f"(d[69]), "+f"(d[70]), "+f"(d[71]),
        "+f"(d[72]), "+f"(d[73]), "+f"(d[74]), "+f"(d[75]), "+f"(d[76]), "+f"(d[77]), "+f"(d[78]), "+f"(d[79]),
        "+f"(d[80]), "+f"(d[81]), "+f"(d[82]), "+f"(d[83]), "+f"(d[84]), "+f"(d[85]), "+f"(d[86]), "+f"(d[87]),
        "+f"(d[88]), "+f"(d[89]), "+f"(d[90]), "+f"(d[91]), "+f"(d[92]), "+f"(d[93]), "+f"(d[94]), "+f"(d[95]),
        "+f"(d[96]), "+f"(d[97]), "+f"(d[98]), "+f"(d[99]), "+f"(d[100]), "+f"(d[101]), "+f"(d[102]), "+f"(d[103]),
        "+f"(d[104]), "+f"(d[105]), "+f"(d[106]), "+f"(d[107]), "+f"(d[108]), "+f"(d[109]), "+f"(d[110]), "+f"(d[111]),
        "+f"(d[112]), "+f"(d[113]), "+f"(d[114]), "+f"(d[115]), "+f"(d[116]), "+f"(d[117]), "+f"(d[118]), "+f"(d[119]),
        "+f"(d[120]), "+f"(d[121]), "+f"(d[122]), "+f"(d[123]), "+f"(d[124]), "+f"(d[125]), "+f"(d[126]), "+f"(d[127])
      : "l"(descA), "l"(descB));
}
__device__ __forceinline__ void mma_ss256_p(float (&d)[128], uint64_t descA, uint64_t descB, int acc) {
  asm volatile("{\n.reg .pred p;\nsetp.ne.b32 p, %130, 0;\n"
      "wgmma.mma_async.sync.aligned.m64n256k16.f32.bf16.bf16 {"
      "%0, %1, %2, %3, %4, %5, %6, %7, %8, %9, %10, %11, %12, %13, %14, %15, "
      "%16, %17, %18, %19, %20, %21, %22, %23, %24, %25, %26, %27, %28, %29, %30, %31, "
      "%32, %33, %34, %35, %36, %37, %38, %39, %40, %41, %42, %43, %44, %45, %46, %47, "
      "%48, %49, %50, %51, %52, %53, %54, %55, %56, %57, %58, %59, %60, %61, %62, %63, "
      "%64, %65, %66, %67, %68, %69, %70, %71, %72, %73, %74, %75, %76, %77, %78, %79, "
      "%80, %81, %82, %83, %84, %85, %86, %87, %88, %89, %90, %91, %92, %93, %94, %95, "
      "%96, %97, %98, %99, %100, %101, %102, %103, %104, %105, %106, %107, %108, %109, %110, %111, "
      "%112, %113, %114, %115, %116, %117, %118, %119, %120, %121, %122, %123, %124, %125, %126, %127"
      "}, %128, %129, p, 1, 1, 0, 1;\n}\n"
      : "+f"(d[0]), "+f"(d[1]), "+f"(d[2]), "+f"(d[3]), "+f"(d[4]), "+f"(d[5]), "+f"(d[6]), "+f"(d[7]),
        "+f"(d[8]), "+f"(d[9]), "+f"(d[10]), "+f"(d[11]), "+f"(d[12]), "+f"(d[13]), "+f"(d[14]), "+f"(d[15]),
        "+f"(d[16]), "+f"(d[17]), "+f"(d[18]), "+f"(d[19]), "+f"(d[20]), "+f"(d[21]), "+f"(d[22]), "+f"(d[23]),
        "+f"(d[24]), "+f"(d[25]), "+f"(d[26]), "+f"(d[27]), "+f"(d[28]), "+f"(d[29]), "+f"(d[30]), "+f"(d[31]),
        "+f"(d[32]), "+f"(d[33]), "+f"(d[34]), "+f"(d[35]), "+f"(d[36]), "+f"(d[37]), "+f"(d[38]), "+f"(d[39]),
        "+f"(d[40]), "+f"(d[41]), "+f"(d[42]), "+f"(d[43]), "+f"(d[44]), "+f"(d[45]), "+f"(d[46]), "+f"(d[47]),
        "+f"(d[48]), "+f"(d[49]), "+f"(d[50]), "+f"(d[51]), "+f"(d[52]), "+f"(d[53]), "+f"(d[54]), "+f"(d[55]),
        "+f"(d[56]), "+f"(d[57]), "+f"(d[58]), "+f"(d[59]), "+f"(d[60]), "+f"(d[61]), "+f"(d[62]), "+f"(d[63]),
        "+f"(d[64]), "+f"(d[65]), "+f"(d[66]), "+f"(d[67]), "+f"(d[68]), "+f"(d[69]), "+f"(d[70]), "+f"(d[71]),
        "+f"(d[72]), "+f"(d[73]), "+f"(d[74]), "+f"(d[75]), "+f"(d[76]), "+f"(d[77]), "+f"(d[78]), "+f"(d[79]),
        "+f"(d[80]), "+f"(d[81]), "+f"(d[82]), "+f"(d[83]), "+f"(d[84]), "+f"(d[85]), "+f"(d[86]), "+f"(d[87]),
        "+f"(d[88]), "+f"(d[89]), "+f"(d[90]), "+f"(d[91]), "+f"(d[92]), "+f"(d[93]), "+f"(d[94]), "+f"(d[95]),
        "+f"(d[96]), "+f"(d[97]), "+f"(d[98]), "+f"(d[99]), "+f"(d[100]), "+f"(d[101]), "+f"(d[102]), "+f"(d[103]),
        "+f"(d[104]), "+f"(d[105]), "+f"(d[106]), "+f"(d[107]), "+f"(d[108]), "+f"(d[109]), "+f"(d[110]), "+f"(d[111]),
        "+f"(d[112]), "+f"(d[113]), "+f"(d[114]), "+f"(d[115]), "+f"(d[116]), "+f"(d[117]), "+f"(d[118]), "+f"(d[119]),
        "+f"(d[120]), "+f"(d[121]), "+f"(d[122]), "+f"(d[123]), "+f"(d[124]), "+f"(d[125]), "+f"(d[126]), "+f"(d[127])
      : "l"(descA), "l"(descB), "r"(acc));
}

__device__ __forceinline__ void mma_ss64(float (&d)[32], uint64_t descA, uint64_t descB) {
  asm volatile("wgmma.mma_async.sync.aligned.m64n64k16.f32.bf16.bf16 {"
      "%0, %1, %2, %3, %4, %5, %6, %7, %8, %9, %10, %11, %12, %13, %14, %15, "
      "%16, %17, %18, %19, %20, %21, %22, %23, %24, %25, %26, %27, %28, %29, %30, %31"
      "}, %32, %33, 1, 1, 1, 0, 1;\n"
      : "+f"(d[0]), "+f"(d[1]), "+f"(d[2]), "+f"(d[3]), "+f"(d[4]), "+f"(d[5]), "+f"(d[6]), "+f"(d[7]),
        "+f"(d[8]), "+f"(d[9]), "+f"(d[10]), "+f"(d[11]), "+f"(d[12]), "+f"(d[13]), "+f"(d[14]), "+f"(d[15]),
        "+f"(d[16]), "+f"(d[17]), "+f"(d[18]), "+f"(d[19]), "+f"(d[20]), "+f"(d[21]), "+f"(d[22]), "+f"(d[23]),
        "+f"(d[24]), "+f"(d[25]), "+f"(d[26]), "+f"(d[27]), "+f"(d[28]), "+f"(d[29]), "+f"(d[30]), "+f"(d[31])
      : "l"(descA), "l"(descB));
}
__device__ __forceinline__ void mma_ss64_p(float (&d)[32], uint64_t descA, uint64_t descB, int acc) {
  asm volatile("{\n.reg .pred p;\nsetp.ne.b32 p, %34, 0;\n"
      "wgmma.mma_async.sync.aligned.m64n64k16.f32.bf16.bf16 {"
      "%0, %1, %2, %3, %4, %5, %6, %7, %8, %9, %10, %11, %12, %13, %14, %15, "
      "%16, %17, %18, %19, %20, %21, %22, %23, %24, %25, %26, %27, %28, %29, %30, %31"
      "}, %32, %33, p, 1, 1, 0, 1;\n}\n"
      : "+f"(d[0]), "+f"(d[1]), "+f"(d[2]), "+f"(d[3]), "+f"(d[4]), "+f"(d[5]), "+f"(d[6]), "+f"(d[7]),
        "+f"(d[8]), "+f"(d[9]), "+f"(d[10]), "+f"(d[11]), "+f"(d[12]), "+f"(d[13]), "+f"(d[14]), "+f"(d[15]),
        "+f"(d[16]), "+f"(d[17]), "+f"(d[18]), "+f"(d[19]), "+f"(d[20]), "+f"(d[21]), "+f"(d[22]), "+f"(d[23]),
        "+f"(d[24]), "+f"(d[25]), "+f"(d[26]), "+f"(d[27]), "+f"(d[28]), "+f"(d[29]), "+f"(d[30]), "+f"(d[31])
      : "l"(descA), "l"(descB), "r"(acc));
}

__device__ __forceinline__ void mma_ss160(float (&d)[80], uint64_t descA, uint64_t descB) {
  asm volatile("wgmma.mma_async.sync.aligned.m64n160k16.f32.bf16.bf16 {"
      "%0, %1, %2, %3, %4, %5, %6, %7, %8, %9, %10, %11, %12, %13, %14, %15, "
      "%16, %17, %18, %19, %20, %21, %22, %23, %24, %25, %26, %27, %28, %29, %30, %31, "
      "%32, %33, %34, %35, %36, %37, %38, %39, %40, %41, %42, %43, %44, %45, %46, %47, "
      "%48, %49, %50, %51, %52, %53, %54, %55, %56, %57, %58, %59, %60, %61, %62, %63, "
      "%64, %65, %66, %67, %68, %69, %70, %71, %72, %73, %74, %75, %76, %77, %78, %79"
      "}, %80, %81, 1, 1, 1, 0, 1;\n"
      : "+f"(d[0]), "+f"(d[1]), "+f"(d[2]), "+f"(d[3]), "+f"(d[4]), "+f"(d[5]), "+f"(d[6]), "+f"(d[7]),
        "+f"(d[8]), "+f"(d[9]), "+f"(d[10]), "+f"(d[11]), "+f"(d[12]), "+f"(d[13]), "+f"(d[14]), "+f"(d[15]),
        "+f"(d[16]), "+f"(d[17]), "+f"(d[18]), "+f"(d[19]), "+f"(d[20]), "+f"(d[21]), "+f"(d[22]), "+f"(d[23]),
        "+f"(d[24]), "+f"(d[25]), "+f"(d[26]), "+f"(d[27]), "+f"(d[28]), "+f"(d[29]), "+f"(d[30]), "+f"(d[31]),
        "+f"(d[32]), "+f"(d[33]), "+f"(d[34]), "+f"(d[35]), "+f"(d[36]), "+f"(d[37]), "+f"(d[38]), "+f"(d[39]),
        "+f"(d[40]), "+f"(d[41]), "+f"(d[42]), "+f"(d[43]), "+f"(d[44]), "+f"(d[45]), "+f"(d[46]), "+f"(d[47]),
        "+f"(d[48]), "+f"(d[49]), "+f"(d[50]), "+f"(d[51]), "+f"(d[52]), "+f"(d[53]), "+f"(d[54]), "+f"(d[55]),
        "+f"(d[56]), "+f"(d[57]), "+f"(d[58]), "+f"(d[59]), "+f"(d[60]), "+f"(d[61]), "+f"(d[62]), "+f"(d[63]),
        "+f"(d[64]), "+f"(d[65]), "+f"(d[66]), "+f"(d[67]), "+f"(d[68]), "+f"(d[69]), "+f"(d[70]), "+f"(d[71]),
        "+f"(d[72]), "+f"(d[73]), "+f"(d[74]), "+f"(d[75]), "+f"(d[76]), "+f"(d[77]), "+f"(d[78]), "+f"(d[79])
      : "l"(descA), "l"(descB));
}
__device__ __forceinline__ void mma_ss160_z(float (&d)[80], uint64_t descA, uint64_t descB) {
  asm volatile("wgmma.mma_async.sync.aligned.m64n160k16.f32.bf16.bf16 {"
      "%0, %1, %2, %3, %4, %5, %6, %7, %8, %9, %10, %11, %12, %13, %14, %15, "
      "%16, %17, %18, %19, %20, %21, %22, %23, %24, %25, %26, %27, %28, %29, %30, %31, "
      "%32, %33, %34, %35, %36, %37, %38, %39, %40, %41, %42, %43, %44, %45, %46, %47, "
      "%48, %49, %50, %51, %52, %53, %54, %55, %56, %57, %58, %59, %60, %61, %62, %63, "
      "%64, %65, %66, %67, %68, %69, %70, %71, %72, %73, %74, %75, %76, %77, %78, %79"
      "}, %80, %81, 0, 1, 1, 0, 1;\n"
      : "=f"(d[0]), "=f"(d[1]), "=f"(d[2]), "=f"(d[3]), "=f"(d[4]), "=f"(d[5]), "=f"(d[6]), "=f"(d[7]),
        "=f"(d[8]), "=f"(d[9]), "=f"(d[10]), "=f"(d[11]), "=f"(d[12]), "=f"(d[13]), "=f"(d[14]), "=f"(d[15]),
        "=f"(d[16]), "=f"(d[17]), "=f"(d[18]), "=f"(d[19]), "=f"(d[20]), "=f"(d[21]), "=f"(d[22]), "=f"(d[23]),
        "=f"(d[24]), "=f"(d[25]), "=f"(d[26]), "=f"(d[27]), "=f"(d[28]), "=f"(d[29]), "=f"(d[30]), "=f"(d[31]),
        "=f"(d[32]), "=f"(d[33]), "=f"(d[34]), "=f"(d[35]), "=f"(d[36]), "=f"(d[37]), "=f"(d[38]), "=f"(d[39]),
        "=f"(d[40]), "=f"(d[41]), "=f"(d[42]), "=f"(d[43]), "=f"(d[44]), "=f"(d[45]), "=f"(d[46]), "=f"(d[47]),
        "=f"(d[48]), "=f"(d[49]), "=f"(d[50]), "=f"(d[51]), "=f"(d[52]), "=f"(d[53]), "=f"(d[54]), "=f"(d[55]),
        "=f"(d[56]), "=f"(d[57]), "=f"(d[58]), "=f"(d[59]), "=f"(d[60]), "=f"(d[61]), "=f"(d[62]), "=f"(d[63]),
        "=f"(d[64]), "=f"(d[65]), "=f"(d[66]), "=f"(d[67]), "=f"(d[68]), "=f"(d[69]), "=f"(d[70]), "=f"(d[71]),
        "=f"(d[72]), "=f"(d[73]), "=f"(d[74]), "=f"(d[75]), "=f"(d[76]), "=f"(d[77]), "=f"(d[78]), "=f"(d[79])
      : "l"(descA), "l"(descB));
}

__device__ __forceinline__ void mma_ss192(float (&d)[96], uint64_t descA, uint64_t descB) {
  asm volatile("wgmma.mma_async.sync.aligned.m64n192k16.f32.bf16.bf16 {"
      "%0, %1, %2, %3, %4, %5, %6, %7, %8, %9, %10, %11, %12, %13, %14, %15, "
      "%16, %17, %18, %19, %20, %21, %22, %23, %24, %25, %26, %27, %28, %29, %30, %31, "
      "%32, %33, %34, %35, %36, %37, %38, %39, %40, %41, %42, %43, %44, %45, %46, %47, "
      "%48, %49, %50, %51, %52, %53, %54, %55, %56, %57, %58, %59, %60, %61, %62, %63, "
      "%64, %65, %66, %67, %68, %69, %70, %71, %72, %73, %74, %75, %76, %77, %78, %79, "
      "%80, %81, %82, %83, %84, %85, %86, %87, %88, %89, %90, %91, %92, %93, %94, %95"
      "}, %96, %97, 1, 1, 1, 0, 1;\n"
      : "+f"(d[0]), "+f"(d[1]), "+f"(d[2]), "+f"(d[3]), "+f"(d[4]), "+f"(d[5]), "+f"(d[6]), "+f"(d[7]),
        "+f"(d[8]), "+f"(d[9]), "+f"(d[10]), "+f"(d[11]), "+f"(d[12]), "+f"(d[13]), "+f"(d[14]), "+f"(d[15]),
        "+f"(d[16]), "+f"(d[17]), "+f"(d[18]), "+f"(d[19]), "+f"(d[20]), "+f"(d[21]), "+f"(d[22]), "+f"(d[23]),
        "+f"(d[24]), "+f"(d[25]), "+f"(d[26]), "+f"(d[27]), "+f"(d[28]), "+f"(d[29]), "+f"(d[30]), "+f"(d[31]),
        "+f"(d[32]), "+f"(d[33]), "+f"(d[34]), "+f"(d[35]), "+f"(d[36]), "+f"(d[37]), "+f"(d[38]), "+f"(d[39]),
        "+f"(d[40]), "+f"(d[41]), "+f"(d[42]), "+f"(d[43]), "+f"(d[44]), "+f"(d[45]), "+f"(d[46]), "+f"(d[47]),
        "+f"(d[48]), "+f"(d[49]), "+f"(d[50]), "+f"(d[51]), "+f"(d[52]), "+f"(d[53]), "+f"(d[54]), "+f"(d[55]),
        "+f"(d[56]), "+f"(d[57]), "+f"(d[58]), "+f"(d[59]), "+f"(d[60]), "+f"(d[61]), "+f"(d[62]), "+f"(d[63]),
        "+f"(d[64]), "+f"(d[65]), "+f"(d[66]), "+f"(d[67]), "+f"(d[68]), "+f"(d[69]), "+f"(d[70]), "+f"(d[71]),
        "+f"(d[72]), "+f"(d[73]), "+f"(d[74]), "+f"(d[75]), "+f"(d[76]), "+f"(d[77]), "+f"(d[78]), "+f"(d[79]),
        "+f"(d[80]), "+f"(d[81]), "+f"(d[82]), "+f"(d[83]), "+f"(d[84]), "+f"(d[85]), "+f"(d[86]), "+f"(d[87]),
        "+f"(d[88]), "+f"(d[89]), "+f"(d[90]), "+f"(d[91]), "+f"(d[92]), "+f"(d[93]), "+f"(d[94]), "+f"(d[95])
      : "l"(descA), "l"(descB));
}
__device__ __forceinline__ void mma_ss192_p(float (&d)[96], uint64_t descA, uint64_t descB, int acc) {
  asm volatile("{\n.reg .pred p;\nsetp.ne.b32 p, %98, 0;\n"
      "wgmma.mma_async.sync.aligned.m64n192k16.f32.bf16.bf16 {"
      "%0, %1, %2, %3, %4, %5, %6, %7, %8, %9, %10, %11, %12, %13, %14, %15, "
      "%16, %17, %18, %19, %20, %21, %22, %23, %24, %25, %26, %27, %28, %29, %30, %31, "
      "%32, %33, %34, %35, %36, %37, %38, %39, %40, %41, %42, %43, %44, %45, %46, %47, "
      "%48, %49, %50, %51, %52, %53, %54, %55, %56, %57, %58, %59, %60, %61, %62, %63, "
      "%64, %65, %66, %67, %68, %69, %70, %71, %72, %73, %74, %75, %76, %77, %78, %79, "
      "%80, %81, %82, %83, %84, %85, %86, %87, %88, %89, %90, %91, %92, %93, %94, %95"
      "}, %96, %97, p, 1, 1, 0, 1;\n}\n"
      : "+f"(d[0]), "+f"(d[1]), "+f"(d[2]), "+f"(d[3]), "+f"(d[4]), "+f"(d[5]), "+f"(d[6]), "+f"(d[7]),
        "+f"(d[8]), "+f"(d[9]), "+f"(d[10]), "+f"(d[11]), "+f"(d[12]), "+f"(d[13]), "+f"(d[14]), "+f"(d[15]),
        "+f"(d[16]), "+f"(d[17]), "+f"(d[18]), "+f"(d[19]), "+f"(d[20]), "+f"(d[21]), "+f"(d[22]), "+f"(d[23]),
        "+f"(d[24]), "+f"(d[25]), "+f"(d[26]), "+f"(d[27]), "+f"(d[28]), "+f"(d[29]), "+f"(d[30]), "+f"(d[31]),
        "+f"(d[32]), "+f"(d[33]), "+f"(d[34]), "+f"(d[35]), "+f"(d[36]), "+f"(d[37]), "+f"(d[38]), "+f"(d[39]),
        "+f"(d[40]), "+f"(d[41]), "+f"(d[42]), "+f"(d[43]), "+f"(d[44]), "+f"(d[45]), "+f"(d[46]), "+f"(d[47]),
        "+f"(d[48]), "+f"(d[49]), "+f"(d[50]), "+f"(d[51]), "+f"(d[52]), "+f"(d[53]), "+f"(d[54]), "+f"(d[55]),
        "+f"(d[56]), "+f"(d[57]), "+f"(d[58]), "+f"(d[59]), "+f"(d[60]), "+f"(d[61]), "+f"(d[62]), "+f"(d[63]),
        "+f"(d[64]), "+f"(d[65]), "+f"(d[66]), "+f"(d[67]), "+f"(d[68]), "+f"(d[69]), "+f"(d[70]), "+f"(d[71]),
        "+f"(d[72]), "+f"(d[73]), "+f"(d[74]), "+f"(d[75]), "+f"(d[76]), "+f"(d[77]), "+f"(d[78]), "+f"(d[79]),
        "+f"(d[80]), "+f"(d[81]), "+f"(d[82]), "+f"(d[83]), "+f"(d[84]), "+f"(d[85]), "+f"(d[86]), "+f"(d[87]),
        "+f"(d[88]), "+f"(d[89]), "+f"(d[90]), "+f"(d[91]), "+f"(d[92]), "+f"(d[93]), "+f"(d[94]), "+f"(d[95])
      : "l"(descA), "l"(descB), "r"(acc));
}

__device__ __forceinline__ void mma_ss80_tt(float (&d)[40], uint64_t descA, uint64_t descB) {
  asm volatile("wgmma.mma_async.sync.aligned.m64n80k16.f32.bf16.bf16 {"
      "%0, %1, %2, %3, %4, %5, %6, %7, %8, %9, %10, %11, %12, %13, %14, %15, "
      "%16, %17, %18, %19, %20, %21, %22, %23, %24, %25, %26, %27, %28, %29, %30, %31, "
      "%32, %33, %34, %35, %36, %37, %38, %39"
      "}, %40, %41, 1, 1, 1, 1, 1;\n"
      : "+f"(d[0]), "+f"(d[1]), "+f"(d[2]), "+f"(d[3]), "+f"(d[4]), "+f"(d[5]), "+f"(d[6]), "+f"(d[7]),
        "+f"(d[8]), "+f"(d[9]), "+f"(d[10]), "+f"(d[11]), "+f"(d[12]), "+f"(d[13]), "+f"(d[14]), "+f"(d[15]),
        "+f"(d[16]), "+f"(d[17]), "+f"(d[18]), "+f"(d[19]), "+f"(d[20]), "+f"(d[21]), "+f"(d[22]), "+f"(d[23]),
        "+f"(d[24]), "+f"(d[25]), "+f"(d[26]), "+f"(d[27]), "+f"(d[28]), "+f"(d[29]), "+f"(d[30]), "+f"(d[31]),
        "+f"(d[32]), "+f"(d[33]), "+f"(d[34]), "+f"(d[35]), "+f"(d[36]), "+f"(d[37]), "+f"(d[38]), "+f"(d[39])
      : "l"(descA), "l"(descB));
}
__device__ __forceinline__ void mma_ss80_tt_z(float (&d)[40], uint64_t descA, uint64_t descB) {
  asm volatile("wgmma.mma_async.sync.aligned.m64n80k16.f32.bf16.bf16 {"
      "%0, %1, %2, %3, %4, %5, %6, %7, %8, %9, %10, %11, %12, %13, %14, %15, "
      "%16, %17, %18, %19, %20, %21, %22, %23, %24, %25, %26, %27, %28, %29, %30, %31, "
      "%32, %33, %34, %35, %36, %37, %38, %39"
      "}, %40, %41, 0, 1, 1, 1, 1;\n"
      : "=f"(d[0]), "=f"(d[1]), "=f"(d[2]), "=f"(d[3]), "=f"(d[4]), "=f"(d[5]), "=f"(d[6]), "=f"(d[7]),
        "=f"(d[8]), "=f"(d[9]), "=f"(d[10]), "=f"(d[11]), "=f"(d[12]), "=f"(d[13]), "=f"(d[14]), "=f"(d[15]),
        "=f"(d[16]), "=f"(d[17]), "=f"(d[18]), "=f"(d[19]), "=f"(d[20]), "=f"(d[21]), "=f"(d[22]), "=f"(d[23]),
        "=f"(d[24]), "=f"(d[25]), "=f"(d[26]), "=f"(d[27]), "=f"(d[28]), "=f"(d[29]), "=f"(d[30]), "=f"(d[31]),
        "=f"(d[32]), "=f"(d[33]), "=f"(d[34]), "=f"(d[35]), "=f"(d[36]), "=f"(d[37]), "=f"(d[38]), "=f"(d[39])
      : "l"(descA), "l"(descB));
}

__device__ __forceinline__ void mma_rs80_k(float (&d)[40], const uint32_t (&a)[4], uint64_t descB) {
  asm volatile("wgmma.mma_async.sync.aligned.m64n80k16.f32.bf16.bf16 {"
      "%0, %1, %2, %3, %4, %5, %6, %7, %8, %9, %10, %11, %12, %13, %14, %15, "
      "%16, %17, %18, %19, %20, %21, %22, %23, %24, %25, %26, %27, %28, %29, %30, %31, "
      "%32, %33, %34, %35, %36, %37, %38, %39"
      "}, {%40, %41, %42, %43}, %44, 1, 1, 1, 0;\n"
      : "+f"(d[0]), "+f"(d[1]), "+f"(d[2]), "+f"(d[3]), "+f"(d[4]), "+f"(d[5]), "+f"(d[6]), "+f"(d[7]),
        "+f"(d[8]), "+f"(d[9]), "+f"(d[10]), "+f"(d[11]), "+f"(d[12]), "+f"(d[13]), "+f"(d[14]), "+f"(d[15]),
        "+f"(d[16]), "+f"(d[17]), "+f"(d[18]), "+f"(d[19]), "+f"(d[20]), "+f"(d[21]), "+f"(d[22]), "+f"(d[23]),
        "+f"(d[24]), "+f"(d[25]), "+f"(d[26]), "+f"(d[27]), "+f"(d[28]), "+f"(d[29]), "+f"(d[30]), "+f"(d[31]),
        "+f"(d[32]), "+f"(d[33]), "+f"(d[34]), "+f"(d[35]), "+f"(d[36]), "+f"(d[37]), "+f"(d[38]), "+f"(d[39])
      : "r"(a[0]), "r"(a[1]), "r"(a[2]), "r"(a[3]), "l"(descB));
}
__device__ __forceinline__ void mma_rs80_k_z(float (&d)[40], const uint32_t (&a)[4], uint64_t descB) {
  asm volatile("wgmma.mma_async.sync.aligned.m64n80k16.f32.bf16.bf16 {"
      "%0, %1, %2, %3, %4, %5, %6, %7, %8, %9, %10, %11, %12, %13, %14, %15, "
      "%16, %17, %18, %19, %20, %21, %22, %23, %24, %25, %26, %27, %28, %29, %30, %31, "
      "%32, %33, %34, %35, %36, %37, %38, %39"
      "}, {%40, %41, %42, %43}, %44, 0, 1, 1, 0;\n"
      : "=f"(d[0]), "=f"(d[1]), "=f"(d[2]), "=f"(d[3]), "=f"(d[4]), "=f"(d[5]), "=f"(d[6]), "=f"(d[7]),
        "=f"(d[8]), "=f"(d[9]), "=f"(d[10]), "=f"(d[11]), "=f"(d[12]), "=f"(d[13]), "=f"(d[14]), "=f"(d[15]),
        "=f"(d[16]), "=f"(d[17]), "=f"(d[18]), "=f"(d[19]), "=f"(d[20]), "=f"(d[21]), "=f"(d[22]), "=f"(d[23]),
        "=f"(d[24]), "=f"(d[25]), "=f"(d[26]), "=f"(d[27]), "=f"(d[28]), "=f"(d[29]), "=f"(d[30]), "=f"(d[31]),
        "=f"(d[32]), "=f"(d[33]), "=f"(d[34]), "=f"(d[35]), "=f"(d[36]), "=f"(d[37]), "=f"(d[38]), "=f"(d[39])
      : "r"(a[0]), "r"(a[1]), "r"(a[2]), "r"(a[3]), "l"(descB));
}

__device__ __forceinline__ void mma_rs48_k(float (&d)[24], const uint32_t (&a)[4], uint64_t descB) {
  asm volatile("wgmma.mma_async.sync.aligned.m64n48k16.f32.bf16.bf16 {"
      "%0, %1, %2, %3, %4, %5, %6, %7, %8, %9, %10, %11, %12, %13, %14, %15, "
      "%16, %17, %18, %19, %20, %21, %22, %23"
      "}, {%24, %25, %26, %27}, %28, 1, 1, 1, 0;\n"
      : "+f"(d[0]), "+f"(d[1]), "+f"(d[2]), "+f"(d[3]), "+f"(d[4]), "+f"(d[5]), "+f"(d[6]), "+f"(d[7]),
        "+f"(d[8]), "+f"(d[9]), "+f"(d[10]), "+f"(d[11]), "+f"(d[12]), "+f"(d[13]), "+f"(d[14]), "+f"(d[15]),
        "+f"(d[16]), "+f"(d[17]), "+f"(d[18]), "+f"(d[19]), "+f"(d[20]), "+f"(d[21]), "+f"(d[22]), "+f"(d[23])
      : "r"(a[0]), "r"(a[1]), "r"(a[2]), "r"(a[3]), "l"(descB));
}
__device__ __forceinline__ void mma_rs48_k_z(float (&d)[24], const uint32_t (&a)[4], uint64_t descB) {
  asm volatile("wgmma.mma_async.sync.aligned.m64n48k16.f32.bf16.bf16 {"
      "%0, %1, %2, %3, %4, %5, %6, %7, %8, %9, %10, %11, %12, %13, %14, %15, "
      "%16, %17, %18, %19, %20, %21, %22, %23"
      "}, {%24, %25, %26, %27}, %28, 0, 1, 1, 0;\n"
      : "=f"(d[0]), "=f"(d[1]), "=f"(d[2]), "=f"(d[3]), "=f"(d[4]), "=f"(d[5]), "=f"(d[6]), "=f"(d[7]),
        "=f"(d[8]), "=f"(d[9]), "=f"(d[10]), "=f"(d[11]), "=f"(d[12]), "=f"(d[13]), "=f"(d[14]), "=f"(d[15]),
        "=f"(d[16]), "=f"(d[17]), "=f"(d[18]), "=f"(d[19]), "=f"(d[20]), "=f"(d[21]), "=f"(d[22]), "=f"(d[23])
      : "r"(a[0]), "r"(a[1]), "r"(a[2]), "r"(a[3]), "l"(descB));
}

__device__ __forceinline__ void mma_rs160_n(float (&d)[80], const uint32_t (&a)[4], uint64_t descB) {
  asm volatile("wgmma.mma_async.sync.aligned.m64n160k16.f32.bf16.bf16 {"
      "%0, %1, %2, %3, %4, %5, %6, %7, %8, %9, %10, %11, %12, %13, %14, %15, "
      "%16, %17, %18, %19, %20, %21, %22, %23, %24, %25, %26, %27, %28, %29, %30, %31, "
      "%32, %33, %34, %35, %36, %37, %38, %39, %40, %41, %42, %43, %44, %45, %46, %47, "
      "%48, %49, %50, %51, %52, %53, %54, %55, %56, %57, %58, %59, %60, %61, %62, %63, "
      "%64, %65, %66, %67, %68, %69, %70, %71, %72, %73, %74, %75, %76, %77, %78, %79"
      "}, {%80, %81, %82, %83}, %84, 1, 1, 1, 1;\n"
      : "+f"(d[0]), "+f"(d[1]), "+f"(d[2]), "+f"(d[3]), "+f"(d[4]), "+f"(d[5]), "+f"(d[6]), "+f"(d[7]),
        "+f"(d[8]), "+f"(d[9]), "+f"(d[10]), "+f"(d[11]), "+f"(d[12]), "+f"(d[13]), "+f"(d[14]), "+f"(d[15]),
        "+f"(d[16]), "+f"(d[17]), "+f"(d[18]), "+f"(d[19]), "+f"(d[20]), "+f"(d[21]), "+f"(d[22]), "+f"(d[23]),
        "+f"(d[24]), "+f"(d[25]), "+f"(d[26]), "+f"(d[27]), "+f"(d[28]), "+f"(d[29]), "+f"(d[30]), "+f"(d[31]),
        "+f"(d[32]), "+f"(d[33]), "+f"(d[34]), "+f"(d[35]), "+f"(d[36]), "+f"(d[37]), "+f"(d[38]), "+f"(d[39]),
        "+f"(d[40]), "+f"(d[41]), "+f"(d[42]), "+f"(d[43]), "+f"(d[44]), "+f"(d[45]), "+f"(d[46]), "+f"(d[47]),
        "+f"(d[48]), "+f"(d[49]), "+f"(d[50]), "+f"(d[51]), "+f"(d[52]), "+f"(d[53]), "+f"(d[54]), "+f"(d[55]),
        "+f"(d[56]), "+f"(d[57]), "+f"(d[58]), "+f"(d[59]), "+f"(d[60]), "+f"(d[61]), "+f"(d[62]), "+f"(d[63]),
        "+f"(d[64]), "+f"(d[65]), "+f"(d[66]), "+f"(d[67]), "+f"(d[68]), "+f"(d[69]), "+f"(d[70]), "+f"(d[71]),
        "+f"(d[72]), "+f"(d[73]), "+f"(d[74]), "+f"(d[75]), "+f"(d[76]), "+f"(d[77]), "+f"(d[78]), "+f"(d[79])
      : "r"(a[0]), "r"(a[1]), "r"(a[2]), "r"(a[3]), "l"(descB));
}
__device__ __forceinline__ void mma_rs160_n_z(float (&d)[80], const uint32_t (&a)[4], uint64_t descB) {
  asm volatile("wgmma.mma_async.sync.aligned.m64n160k16.f32.bf16.bf16 {"
      "%0, %1, %2, %3, %4, %5, %6, %7, %8, %9, %10, %11, %12, %13, %14, %15, "
      "%16, %17, %18, %19, %20, %21, %22, %23, %24, %25, %26, %27, %28, %29, %30, %31, "
      "%32, %33, %34, %35, %36, %37, %38, %39, %40, %41, %42, %43, %44, %45, %46, %47, "
      "%48, %49, %50, %51, %52, %53, %54, %55, %56, %57, %58, %59, %60, %61, %62, %63, "
      "%64, %65, %66, %67, %68, %69, %70, %71, %72, %73, %74, %75, %76, %77, %78, %79"
      "}, {%80, %81, %82, %83}, %84, 0, 1, 1, 1;\n"
      : "=f"(d[0]), "=f"(d[1]), "=f"(d[2]), "=f"(d[3]), "=f"(d[4]), "=f"(d[5]), "=f"(d[6]), "=f"(d[7]),
        "=f"(d[8]), "=f"(d[9]), "=f"(d[10]), "=f"(d[11]), "=f"(d[12]), "=f"(d[13]), "=f"(d[14]), "=f"(d[15]),
        "=f"(d[16]), "=f"(d[17]), "=f"(d[18]), "=f"(d[19]), "=f"(d[20]), "=f"(d[21]), "=f"(d[22]), "=f"(d[23]),
        "=f"(d[24]), "=f"(d[25]), "=f"(d[26]), "=f"(d[27]), "=f"(d[28]), "=f"(d[29]), "=f"(d[30]), "=f"(d[31]),
        "=f"(d[32]), "=f"(d[33]), "=f"(d[34]), "=f"(d[35]), "=f"(d[36]), "=f"(d[37]), "=f"(d[38]), "=f"(d[39]),
        "=f"(d[40]), "=f"(d[41]), "=f"(d[42]), "=f"(d[43]), "=f"(d[44]), "=f"(d[45]), "=f"(d[46]), "=f"(d[47]),
        "=f"(d[48]), "=f"(d[49]), "=f"(d[50]), "=f"(d[51]), "=f"(d[52]), "=f"(d[53]), "=f"(d[54]), "=f"(d[55]),
        "=f"(d[56]), "=f"(d[57]), "=f"(d[58]), "=f"(d[59]), "=f"(d[60]), "=f"(d[61]), "=f"(d[62]), "=f"(d[63]),
        "=f"(d[64]), "=f"(d[65]), "=f"(d[66]), "=f"(d[67]), "=f"(d[68]), "=f"(d[69]), "=f"(d[70]), "=f"(d[71]),
        "=f"(d[72]), "=f"(d[73]), "=f"(d[74]), "=f"(d[75]), "=f"(d[76]), "=f"(d[77]), "=f"(d[78]), "=f"(d[79])
      : "r"(a[0]), "r"(a[1]), "r"(a[2]), "r"(a[3]), "l"(descB));
}

__device__ __forceinline__ void feature_map(const uint32_t (&P)[2][10], uint32_t (&fr)[10][4]) {
  constexpr float L2E = 1.4426950408889634f;
#pragma unroll
  for (int p = 0; p < 2; p++) {
#pragma unroll
    for (int r = 0; r < 2; r++) {
      uint32_t mx = P[r][5 * p], mn = mx;
#pragma unroll
      for (int g = 1; g < 5; g++) { mx = max_bf2(mx, P[r][5 * p + g]); mn = min_bf2(mn, P[r][5 * p + g]); }
      mx = max_bf2(mx, __shfl_xor_sync(0xffffffffu, mx, 1));
      mn = min_bf2(mn, __shfl_xor_sync(0xffffffffu, mn, 1));
      mx = max_bf2(mx, __shfl_xor_sync(0xffffffffu, mx, 2));
      mn = min_bf2(mn, __shfl_xor_sync(0xffffffffu, mn, 2));
      float mx0 = -bf_lo(mx) * L2E, mx1 = -bf_hi(mx) * L2E, mn0 = bf_lo(mn) * L2E, mn1 = bf_hi(mn) * L2E;
      float ep0[5], ep1[5], en0[5], en1[5];
      float sp0 = 0.f, sp1 = 0.f, sn0 = 0.f, sn1 = 0.f;
#pragma unroll
      for (int g = 0; g < 5; g++) {
        float x0 = bf_lo(P[r][5 * p + g]), x1 = bf_hi(P[r][5 * p + g]);
        ep0[g] = ex2(fmaf(x0, L2E, mx0)); ep1[g] = ex2(fmaf(x1, L2E, mx1));
        en0[g] = ex2(fmaf(x0, -L2E, mn0)); en1[g] = ex2(fmaf(x1, -L2E, mn1));
        sp0 += ep0[g]; sp1 += ep1[g]; sn0 += en0[g]; sn1 += en1[g];
      }
      sp0 += __shfl_xor_sync(0xffffffffu, sp0, 1); sp1 += __shfl_xor_sync(0xffffffffu, sp1, 1);
      sn0 += __shfl_xor_sync(0xffffffffu, sn0, 1); sn1 += __shfl_xor_sync(0xffffffffu, sn1, 1);
      sp0 += __shfl_xor_sync(0xffffffffu, sp0, 2); sp1 += __shfl_xor_sync(0xffffffffu, sp1, 2);
      sn0 += __shfl_xor_sync(0xffffffffu, sn0, 2); sn1 += __shfl_xor_sync(0xffffffffu, sn1, 2);
      sp0 = rcp(sp0); sp1 = rcp(sp1); sn0 = rcp(sn0); sn1 = rcp(sn1);
#pragma unroll
      for (int g = 0; g < 5; g++) {
        fr[5 * p + g][r] = pack_bf16(ep0[g] * sp0, ep1[g] * sp1);
        fr[5 * p + g][2 + r] = pack_bf16(en0[g] * sn0, en1[g] * sn1);
      }
    }
  }
}

template <int V> struct IntC { static constexpr int value = V; };
struct Ring {
  uint32_t idx, phase;
  template <int N> __device__ __forceinline__ void next() { if (++idx == N) { idx = 0; phase ^= 1; } }
};

}

__global__ void __cluster_dims__(2, 1, 1) __launch_bounds__(384, 1)
fused_kernel(const __grid_constant__ Maps maps, const __nv_bfloat16* __restrict__ x, const __nv_bfloat16* __restrict__ wqkv,
             const __nv_bfloat16* __restrict__ wphi, const __nv_bfloat16* __restrict__ w1, const __nv_bfloat16* __restrict__ w2,
             const __nv_bfloat16* __restrict__ w3, const __nv_bfloat16* __restrict__ w4, const __nv_bfloat16* __restrict__ wo,
             const __nv_bfloat16* __restrict__ gate_w, __nv_bfloat16* __restrict__ out) {
  extern __shared__ __align__(1024) uint8_t sgen[];
  const uint32_t sb = smem_u32(sgen);
  const uint32_t sb16 = (sb & 0x3FFFFu) >> 4;
  const uint32_t bars = sb + OFF_BAR;
  const uint32_t fullA = bars + 8 * B_FULLA, emptyA = bars + 8 * B_EMPTYA, fullB = bars + 8 * B_FULLB, emptyB = bars + 8 * B_EMPTYB;

  const int tid = threadIdx.x;
  const int rank = blockIdx.x & 1;
  const int bid = blockIdx.x - NSVC, pairIdx = bid >> 1;
  const int i = pairIdx >> 2, j = 2 * (pairIdx & 3) + rank;
  const int k3 = (5 * (pairIdx & 3) + 1) >> 1;

  if (bid < 0) {
    const int sv = blockIdx.x;
    const unsigned epoch = *reinterpret_cast<volatile unsigned*>(g_flags + FL_DONE * 32) / NCTA;
    if (tid == 0) {
#pragma unroll
      for (int b = 0; b < 11; b++) mbar_init(bars + 8 * b, 1);
      mbar_expect_tx(bars + 80, 6400);
      bulk_load(sb + 204800, wphi + sv * 3200, 6400, bars + 80);
    }
    __syncthreads();
    float a[8];
#pragma unroll 1
    for (int rd = 0; rd < 4; rd++) {
      const int nch = rd ? 192 : 80, nth = rd ? 384 : 320, piece = rd ? 18432 : 20480, np = rd == 3 ? 7 : 10;
      if (tid == 0) {
        const char* src = reinterpret_cast<const char*>(rd ? w3 + (size_t)(160 * sv + 60 * (rd - 1)) * F_ : w1 + (size_t)160 * sv * D_);
#pragma unroll 1
        for (int p = 0; p < np; p++) {
          const int bytes = (rd == 3 && p == 6) ? 12288 : piece;
          mbar_expect_tx(bars + 8 * p, bytes);
          bulk_load(sb + p * piece, src + p * piece, bytes, bars + 8 * p);
        }
      }
      if (rd == 0) {
        if (tid < 40 && (tid < 20 || sv >= 2))
          reinterpret_cast<uint4*>(g_Hs + (size_t)(2 + ((sv & 1) ? S_ - 1 - tid / 20 : tid / 20)) * D_ + 160 * sv)[tid % 20] = make_uint4(0, 0, 0, 0);
        mbar_wait(bars + 80, 0);
#pragma unroll 1
        for (int e = tid; e < 1600; e += 384) {
          const int jj = e / 800, it = e - 800 * jj, st = it / 160, n = (it - 160 * st) >> 1, k0 = 16 * st + 8 * ((it ^ (n >> 2)) & 1);
          const int nn = n % 40, h = 2 * (n / 40) + (nn & 1), ff = 4 * (nn >> 3) + ((nn >> 1) & 3);
          uint32_t w[8];
#pragma unroll
          for (int q = 0; q < 8; q++) {
            const int k = k0 + q;
            w[q] = (unsigned)(k - 20 * h) < 20u ? reinterpret_cast<const unsigned short*>(sgen + 204800)[jj * 1600 + k * 20 + ff] : 0u;
          }
          g_wphi[sv * 1600 + e] = make_uint4(w[0] | (w[1] << 16), w[2] | (w[3] << 16), w[4] | (w[5] << 16), w[6] | (w[7] << 16));
        }
      }
      if (rd < 2) {
#pragma unroll
        for (int e = 0; e < 8; e++) a[e] = 0.f;
      }
#pragma unroll 1
      for (int p = 0; p < np; p++) {
        mbar_wait(bars + 8 * p, rd & 1);
        const int bytes = (rd == 3 && p == 6) ? 12288 : piece;
        if (tid < nth) {
#pragma unroll 1
          for (int o = tid * 16; o < bytes; o += nth * 16) {
            const uint4 v = lds128(sb + p * piece + o);
            a[0] += bf_lo(v.x); a[1] += bf_hi(v.x); a[2] += bf_lo(v.y); a[3] += bf_hi(v.y);
            a[4] += bf_lo(v.z); a[5] += bf_hi(v.z); a[6] += bf_lo(v.w); a[7] += bf_hi(v.w);
          }
        }
      }
      if (tid < nth && (rd == 0 || rd == 3)) {
        float* cd = g_cs[epoch & 1] + (rd ? D_ : 0) + 8 * (tid % nch);
        red_add4(cd, a[0], a[1], a[2], a[3]); red_add4(cd + 4, a[4], a[5], a[6], a[7]);
      }
      __syncthreads();
      if (tid == 0 && (rd == 0 || rd == 3)) {
        flag_add(rd ? FL_CS3 : FL_CS);
        if (rd == 0) l2_prefetch(w2 + (size_t)sv * (D_ * D_ / NSVC), D_ * D_ * 2 / NSVC);
      }
    }
#pragma unroll 1
    for (int e = tid; e < (D_ + F_) / NSVC; e += 384) g_cs[(epoch + 1) & 1][sv * ((D_ + F_) / NSVC) + e] = 0.f;
#pragma unroll 1
    for (int e = tid; e < 2 * KV_J; e += 384) g_acc[(epoch + 1) & 1][sv * 2 * KV_J + e] = 0.f;
    if (tid < 32) {
      l2_prefetch(w4 + (size_t)(sv * 32 + tid) * (F_ * D_ / 128), F_ * D_ * 2 / 128);
      l2_prefetch(wo + (size_t)(sv * 32 + tid) * (D_ * D_ / 128), D_ * D_ * 2 / 128);
    }
    return;
  }
  TSTAMP(0);
  if (tid >= 256) {
    asm volatile("setmaxnreg.dec.sync.aligned.u32 40;");
    if (tid == 256) {
#pragma unroll
      for (int s = 0; s < NA; s++) mbar_init(fullA + 8 * s, 1);
      asm volatile("fence.mbarrier_init.release.cluster;" ::: "memory");
#pragma unroll 1
      for (int u = 0; u < 4; u++) {
        if ((u & 1) == 0) mbar_expect_tx(fullA + 4 * u, SLOT_A);
        tma2d(sb + OFF_A + u * 8192, &maps.x, fullA + 8 * (u >> 1), 64 * (u >> 1), 128 * i + 64 * (u & 1));
      }
    } else if (tid == 288) {
#pragma unroll
      for (int s = 0; s < NB; s++) { mbar_init(fullB + 8 * s, 1); mbar_init(emptyB + 8 * s, 8); }
      asm volatile("fence.mbarrier_init.release.cluster;" ::: "memory");
    } else if (tid == 320) {
#pragma unroll
      for (int b = B_CS; b < NBAR; b++) if (b < B_EMPTYB || b >= B_EMPTYB + NB) mbar_init(bars + 8 * b, b < B_EMPTYB ? 1 : b < B_EMPTYA ? 8 : b < B_X1P ? 16 : 2);
#pragma unroll
      for (int b = B_DSR; b < B_EMPTYB; b++) mbar_expect_tx(bars + 8 * b, 10240);
      asm volatile("fence.mbarrier_init.release.cluster;" ::: "memory");
    }
    __syncwarp();
    asm volatile("barrier.cluster.arrive.relaxed.aligned;" ::: "memory");
    auto get_epoch = [&]() { return *reinterpret_cast<volatile unsigned*>(g_flags + FL_DONE * 32) / NCTA; };
    if ((tid >> 5) != 9) asm volatile("barrier.cluster.wait.aligned;" ::: "memory");
    const int lane = tid & 31, pw = (tid >> 5) & 3;
    if (pw == 0) {
      if (tid == 256) {
        Ring r{2, 1};
#pragma unroll 1
        for (int k = 2; k < 24; k++) {
          if (k == 10 || k == 16) {
            mbar_wait(bars + 8 * B_HST, k == 16);
            TSTAMPX(k == 10 ? 29 : 30);
          }
          if (k == 14) {
            mbar_wait(bars + 8 * B_WDEAD, 0);
            mbar_expect_tx(bars + 8 * B_T4, SLOT_A);
            tma2d(sb + OFF_MISC, &maps.hs, bars + 8 * B_T4, 256 + 320 * rank, 128 * i);
            mbar_wait(emptyA + 16, r.phase); mbar_wait(emptyA + 24, r.phase);
            mbar_expect_tx(bars + 8 * B_XR, 20480);
            tma2d(sb + OFF_STG, &maps.xr, bars + 8 * B_XR, 80 * j, 128 * i);
            mbar_wait(bars + 8 * B_X1P, 0);
          }
          mbar_wait(emptyA + 8 * r.idx, r.phase);
          const uint32_t bar = fullA + 8 * r.idx, slot = sb + OFF_A + r.idx * SLOT_A;
          mbar_expect_tx(bar, SLOT_A);
          if (k >= 10 && k < 14) tma2d(slot, &maps.hs, bar, 64 * (k - 10) + 320 * rank, 128 * i);
          else tma2d_mc(slot + rank * 8192, k < 10 ? &maps.x : &maps.x1, bar, 64 * (k < 10 ? k : (k - 14 + k3) % 10), 128 * i + 64 * rank);
          r.next<NA>();
        }
      }
    } else if (pw == 1) {
      if (tid == 288) {
        Ring r{0, 1};
#pragma unroll 1
        for (int k = 0; k < 18; k++) {
          mbar_wait(emptyB + 8 * r.idx, r.phase);
          const uint32_t bar = fullB + 8 * r.idx, slot = sb + OFF_B + r.idx * SLOT_B;
          if (k < 10) {
            mbar_expect_tx(bar, 40960);
            tma4d(slot + 8192, &maps.qm, bar, 0, 64 * k, 0, j);
            tma3d(slot, &maps.w1m, bar, 0, 64 * k, j);
            tma4d(slot + 32768 + 2048, &maps.qr, bar, 64, 64 * k, 0, j);
            tma3d(slot + 32768, &maps.w1r, bar, 64, 64 * k, j);
          } else if (k < 13) {
            mbar_expect_tx(bar, k < 12 ? 40960 : 20480);
            tma3d(slot, &maps.w2, bar, 0, 320 * rank + 128 * (k - 10), 5 * (j >> 1));
            if (k < 12) tma3d(slot + 20480, &maps.w2, bar, 0, 320 * rank + 128 * (k - 10) + 64, 5 * (j >> 1));
          } else {
            if (k == 13) mbar_wait(bars + 8 * B_KVR, 0);
            mbar_expect_tx(bar, 49152);
            tma3d(slot, &maps.w3, bar, 0, 64 * ((2 * (k - 13) + k3) % 10), 3 * j);
            tma3d(slot + 24576, &maps.w3, bar, 0, 64 * ((2 * (k - 13) + 1 + k3) % 10), 3 * j);
          }
          r.next<NB>();
        }
#pragma unroll 1
        for (int n = 0; n < 8; n++) {
          if (n < 3) { mbar_wait(emptyB + 8 * r.idx, r.phase); r.next<NB>(); }
          if (n == 0) mbar_wait(fullA + 24, 1);
          if (n >= 4) mbar_wait(bars + 8 * (B_EMPTY4 + n - 4), 0);
          const uint32_t bar = bars + 8 * (B_FULL4 + n), set = sb + ((n >> 1) & 1) * SET4;
          const int h = n & 1, m = ((j >> 1) + 1 + (n >> 1)) & 3;
          mbar_expect_tx(bar, h ? 40960 : 46080);
          tma3d(set + (h ? 46080 : 0), h ? &maps.w4 : &maps.wo, bar, 0, h ? 192 * j + 64 : 80 * j, 5 * m);
          tma3d(set + (h ? 66560 : 25600), &maps.w4, bar, 0, 192 * j + 128 * h, 5 * m);
        }
        mbar_wait(bars + 8 * (B_EMPTY4 + 4), 0);
        mbar_expect_tx(bars + 8 * B_XR, 20480);
        tma2d(sb + OFF_OUT, &maps.st_x1, bars + 8 * B_XR, 80 * j, 128 * i);
      }
    } else {
      const unsigned epoch = get_epoch();
      float* accg = g_acc[epoch & 1];
      if (pw == 2) {
        if (tid == 320) {
          flag_wait(FL_CS, (epoch + 1) * NSVC);
          flag_wait(FL_ST + i, (epoch + 1) * 8u);
          fence_async_glb();
          *reinterpret_cast<volatile uint32_t*>(sgen + OFF_BAR + 8 * NBAR) = (epoch + 1) & 1;
          mbar_expect_tx(bars + 8 * B_CS, 320 + 2048 + 12800);
          bulk_load(sb + OFF_CS, g_cs[epoch & 1] + 80 * j, 320, bars + 8 * B_CS);
          bulk_load(sb + OFF_XST, g_xstat + 128 * i, 2048, bars + 8 * B_CS);
          bulk_load(sb + OFF_MISC, g_wphi + j * 800, 12800, bars + 8 * B_CS);
          TSTAMPX(21);
          mbar_wait(bars + 8 * B_SIGKV, 0);
          TSTAMPX(25);
          fence_async_smem();
#pragma unroll 1
          for (int u = 0; u < 4; u++)
            asm volatile("cp.reduce.async.bulk.global.shared::cta.bulk_group.add.f32 [%0], [%1], %2;"
                         ::"l"(accg + j * KV_J + (u >> 1) * KV_PAIR + (u & 1) * 1024), "r"(sb + OFF_B + SPARE + (u & 1) * SLOT_B + (u >> 1) * 4096),
                         "r"((u & 1) ? KV_PAIR * 4 - 4096 : 4096) : "memory");
          bulk_commit(); bulk_wait<0>();
          mbar_arrive(bars + 8 * B_KVR);
          flag_add(FL_KV + j);
          TSTAMPX(26);
          flag_wait(FL_KV + j, (epoch + 1) * 16u);
          mbar_wait(bars + 8 * B_SIGX1, 0);
          mbar_expect_tx(bars + 8 * B_KV, KV_J * 4);
          bulk_load(sb + OFF_A + SLOT_A, accg + j * KV_J, KV_J * 4, bars + 8 * B_KV);
          TSTAMPX(22);
          flag_wait(FL_CS3, (epoch + 1) * NSVC);
          flag_wait(FL_S1 + i, (epoch + 1) * 8u);
          fence_async_glb();
          mbar_expect_tx(bars + 8 * B_ST1, 8192 + 768);
          bulk_load(sb + OFF_CS + 320, g_cs[epoch & 1] + D_ + 192 * j, 768, bars + 8 * B_ST1);
          bulk_load(sb + OFF_MISC, g_st1 + 128 * i * 8, 8192, bars + 8 * B_ST1);
        }
        __syncwarp();
#pragma unroll 1
        for (int c = 0; c < 3; c++) {
          mbar_wait(bars + 8 * (B_EMPTY4 + (c ? 5 : 4)), 0);
          const uint4* src = g_part + (size_t)((i * 8 + j) * 3 + c) * 1280;
          const unsigned* tp = reinterpret_cast<const unsigned*>(src + 1024 + (lane & 7) * 32 + 31);
          uint32_t n = 0;
          while (!__all_sync(0xffffffffu, (ld_acquire(tp) ^ epoch) & 1u) && ++n < (WAIT_LIMIT >> 2)) {}
          if (tid == 320) {
            mbar_expect_tx(bars + 8 * (B_RDY + c), 20480);
            bulk_load(sb + (c ? 25600 + 20480 * c : 0), src, 20480, bars + 8 * (B_RDY + c));
          }
        }
      }
      if (tid == 352) {
        mbar_wait(bars + 8 * B_SIGP, 0);
        flag_add(FL_ST + i);
        TSTAMPX(20);
        const int shift = (j < 2) ? 1 : (j < 4) ? -1 : (j < 6) ? 2 : -2;
        prefetch_tmap(&maps.st_h); prefetch_tmap(&maps.st_x1); prefetch_tmap(&maps.hs); prefetch_tmap(&maps.x1); prefetch_tmap(&maps.xr);
        prefetch_tmap(&maps.w2); prefetch_tmap(&maps.w3); prefetch_tmap(&maps.w4); prefetch_tmap(&maps.wo);
        mbar_wait(bars + 8 * B_SIGH, 0);
        TSTAMPX(23);
        fence_async_smem();
        tma2d_store(&maps.st_h, sb + OFF_STG, 80 * j, 128 * i + 2 + shift);
        bulk_commit(); bulk_wait<0>();
        flag_add(FL_H + 2 * i + (j >> 2));
        flag_add_relaxed(FL_H + 2 * ((i + (shift > 0 ? 1 : -1)) & 15) + (j >> 2));
        TSTAMPX(24);
        flag_wait(FL_H + 2 * i + rank, (epoch + 1) * 8u);
        mbar_arrive(bars + 8 * B_HST);
        mbar_wait(bars + 8 * B_SIGX1, 0);
        TSTAMPX(27);
        fence_async_smem();
        tma2d_store(&maps.st_x1, sb + OFF_STG, 80 * j, 128 * i);
        bulk_commit(); bulk_wait<0>();
        flag_add(FL_X1 + i);
        mbar_arrive_cta(bars + 8 * B_X1P, 0); mbar_arrive_cta(bars + 8 * B_X1P, 1);
        TSTAMPX(28);
        flag_wait(FL_X1 + i, (epoch + 1) * 8u);
        mbar_arrive(bars + 8 * B_HST);
        mbar_wait(bars + 8 * B_MFREE, 0);
        flag_add(FL_S1 + i);
      }
    }
  } else {
    uint4 pv[5], pw_[5];
    {
      const int row = 128 * i + 16 * j + (tid >> 4), l16 = tid & 15;
#pragma unroll
      for (int c = 0; c < 5; c++) pv[c] = __ldg(reinterpret_cast<const uint4*>(x + (size_t)row * D_ + c * 128 + l16 * 8));
#pragma unroll
      for (int c = 0; c < 5; c++) pw_[c] = __ldg(reinterpret_cast<const uint4*>(gate_w + c * 128 + l16 * 8));
    }
    asm volatile("barrier.cluster.arrive.relaxed.aligned;" ::: "memory");
    asm volatile("setmaxnreg.inc.sync.aligned.u32 232;");
    const int wg = tid >> 7, warp = tid >> 5, lane = tid & 31, t = lane & 3;
    const int rloc = warp * 16 + (lane >> 2);
    const float* s_cs = reinterpret_cast<const float*>(sgen + OFF_CS);
    auto signal = [&](int b) {
      __syncwarp();
      if (lane == 0) mbar_arrive(bars + 8 * b);
    };
    auto releaseB = [&](uint32_t bar) {
      __syncwarp();
      if (lane == 0) mbar_arrive(bar);
    };
    auto release = [&](uint32_t bar) {
      __syncwarp();
      if (lane < 2) mbar_arrive_cta(bar, lane);
    };
    const uint32_t stg_lane = (warp * 16 + ((lane >> 3) & 1) * 8 + (lane & 7)) * 160 + (lane >> 4) * 16;

    auto stage_tile = [&](uint32_t stg, const uint32_t (&v)[2][10]) {
#pragma unroll
      for (int s = 0; s < 5; s++) stsm4(stg + stg_lane + s * 32, v[0][2 * s], v[1][2 * s], v[0][2 * s + 1], v[1][2 * s + 1]);
    };

    {
      float f[40];
      float s = 0.f, gs = 0.f;
#pragma unroll
      for (int c = 0; c < 5; c++) {
        const uint32_t vv[4] = {pv[c].x, pv[c].y, pv[c].z, pv[c].w}, ww[4] = {pw_[c].x, pw_[c].y, pw_[c].z, pw_[c].w};
#pragma unroll
        for (int e = 0; e < 4; e++) {
          f[8 * c + 2 * e] = bf_lo(vv[e]); f[8 * c + 2 * e + 1] = bf_hi(vv[e]);
          s += f[8 * c + 2 * e] + f[8 * c + 2 * e + 1];
          gs = fmaf(f[8 * c + 2 * e], bf_lo(ww[e]), gs); gs = fmaf(f[8 * c + 2 * e + 1], bf_hi(ww[e]), gs);
        }
      }
#pragma unroll
      for (int o = 1; o < 16; o <<= 1) { s += __shfl_xor_sync(0xffffffffu, s, o); gs += __shfl_xor_sync(0xffffffffu, gs, o); }
      const float mean = s * (1.f / D_);
      float q = 0.f;
#pragma unroll
      for (int e = 0; e < 40; e++) { const float d = f[e] - mean; q = fmaf(d, d, q); }
#pragma unroll
      for (int o = 1; o < 16; o <<= 1) q += __shfl_xor_sync(0xffffffffu, q, o);
      const float rstd = rsqrtf(q * (1.f / D_) + 1e-5f);
      asm volatile("barrier.cluster.wait.aligned;" ::: "memory");
      if ((tid & 15) == 0) g_xstat[128 * i + 16 * j + (tid >> 4)] = make_float4(rstd, -mean, rcp(1.f + __expf(-gs)), 0.f);
      signal(B_SIGP);
    }
    TSTAMP(1);

    Ring ra{0, 0}, rb{0, 0};
    uint32_t qp[2][10], P[2][10];
    float st_g[2];
    {
      float accM[128], accR[32];
      uint32_t pa = 0, pb = 0;
#pragma unroll 1
      for (int k = 0; k < 10; k++) {
        mbar_wait(fullA + 8 * ra.idx, ra.phase);
        if (tid == 0) TRACE(32 + k);
        mbar_wait(fullB + 8 * rb.idx, rb.phase);
        if (tid == 0) TRACE(64 + k);
        if (k == 0) TSTAMP(2);
        const uint32_t a0 = sb16 + ((OFF_A + ra.idx * SLOT_A + wg * 8192) >> 4), b0 = sb16 + ((OFF_B + rb.idx * SLOT_B) >> 4);
        wg_fence();
#pragma unroll
        for (int kk = 0; kk < 4; kk++) {
          const uint64_t da = make_desc(a0, kk * 32, 16, 1024, 1);
          if (kk == 0) {
            mma_ss256_p(accM, da, make_desc(b0, 0, 8192, 1024, 1), k);
            mma_ss64_p(accR, da, make_desc(b0, 32768, 2048, 256, 3), k);
          } else {
            mma_ss256(accM, da, make_desc(b0, kk * 2048, 8192, 1024, 1));
            mma_ss64(accR, da, make_desc(b0, 32768 + kk * 512, 2048, 256, 3));
          }
          if (kk == 0) {
            wg_commit();
            if (k > 0) {
              wg_wait<1>();
              release(emptyA + 8 * pa);
              releaseB(emptyB + 8 * pb);
            }
          }
        }
        wg_commit();
        pa = ra.idx; pb = rb.idx;
        ra.next<NA>(); rb.next<NB>();
      }
      TSTAMP(18);
      float st_rstd[2], st_mr[2];
      mbar_wait(bars + 8 * B_CS, 0);
#pragma unroll
      for (int r = 0; r < 2; r++) {
        const uint4 st = lds128(sb + OFF_XST + (rloc + 8 * r) * 16);
        st_rstd[r] = __uint_as_float(st.x); st_mr[r] = __uint_as_float(st.y); st_g[r] = __uint_as_float(st.z);
      }
      TSTAMP(19);
      wg_wait<0>();
      fence_regs(accM); fence_regs(accR);
      TSTAMP(3);
      release(emptyA + 8 * pa);
#define ACC(P_, G, I_) ((G) < 8 ? accM[(P_) * 32 + ((G) & 7) * 4 + (I_)] : accR[(P_) * 8 + ((G) & 1) * 4 + (I_)])
      {
        uint32_t hv[2][10];
        const GeluC g0 = gelu_consts(st_rstd[0], 1.f), g1 = gelu_consts(st_rstd[1], 1.f);
#pragma unroll
        for (int g = 0; g < 10; g++) {
          const float2 cs = *reinterpret_cast<const float2*>(s_cs + 8 * g + 2 * t);
          const float v0 = gelu_s(fmaf(st_mr[0], cs.x, ACC(0, g, 0)), g0), v1 = gelu_s(fmaf(st_mr[0], cs.y, ACC(0, g, 1)), g0);
          const float v2 = gelu_s(fmaf(st_mr[1], cs.x, ACC(0, g, 2)), g1), v3 = gelu_s(fmaf(st_mr[1], cs.y, ACC(0, g, 3)), g1);
          hv[0][g] = pack_bf16(v0, v1); hv[1][g] = pack_bf16(v2, v3);
        }
        bar_sync(1, 256);
        stage_tile(sb + OFF_STG, hv);
        signal(B_SIGH);
      }
      TSTAMP(4);
      uint32_t kf[5][4], qf[5][4];
#pragma unroll
      for (int s = 0; s < 5; s++) {
        kf[s][0] = pack_bf16(ACC(2, 2 * s, 0), ACC(2, 2 * s, 1)); kf[s][1] = pack_bf16(ACC(2, 2 * s, 2), ACC(2, 2 * s, 3));
        kf[s][2] = pack_bf16(ACC(2, 2 * s + 1, 0), ACC(2, 2 * s + 1, 1)); kf[s][3] = pack_bf16(ACC(2, 2 * s + 1, 2), ACC(2, 2 * s + 1, 3));
        qf[s][0] = pack_bf16(ACC(1, 2 * s, 0), ACC(1, 2 * s, 1)); qf[s][1] = pack_bf16(ACC(1, 2 * s, 2), ACC(1, 2 * s, 3));
        qf[s][2] = pack_bf16(ACC(1, 2 * s + 1, 0), ACC(1, 2 * s + 1, 1)); qf[s][3] = pack_bf16(ACC(1, 2 * s + 1, 2), ACC(1, 2 * s + 1, 3));
      }
      float pk[40], pq[40];
      wg_fence();
#pragma unroll
      for (int s = 0; s < 5; s++) {
        if (s == 0) mma_rs80_k_z(pk, kf[s], make_desc(sb16, OFF_MISC, 16, 256, 3));
        else mma_rs80_k(pk, kf[s], make_desc(sb16, OFF_MISC + s * 2560, 16, 256, 3));
      }
      wg_commit();
#pragma unroll
      for (int s = 0; s < 5; s++) {
        if (s == 0) mma_rs80_k_z(pq, qf[s], make_desc(sb16, OFF_MISC, 16, 256, 3));
        else mma_rs80_k(pq, qf[s], make_desc(sb16, OFF_MISC + s * 2560, 16, 256, 3));
      }
      wg_commit();
      {
        const int mat = lane >> 3;
        const int tok = warp * 16 + (mat & 1) * 8 + (lane & 7);
        const uint32_t base = sb + OFF_B + SPARE + tok * 32 + (((mat >> 1) ^ ((tok >> 2) & 1)) << 4);
        const uint32_t ones = (t == 0) ? 0x00003f80u : 0u;
#pragma unroll
        for (int p = 0; p < 2; p++) {
#pragma unroll
          for (int gg = 0; gg < 3; gg++) {
            const int g0 = 5 * p + 2 * gg;
            uint32_t r0 = pack_bf16(ACC(3, g0, 0), ACC(3, g0, 1)), r1 = pack_bf16(ACC(3, g0, 2), ACC(3, g0, 3));
            uint32_t r2 = ones, r3 = ones;
            if (gg < 2) { r2 = pack_bf16(ACC(3, g0 + 1, 0), ACC(3, g0 + 1, 1)); r3 = pack_bf16(ACC(3, g0 + 1, 2), ACC(3, g0 + 1, 3)); }
            stsm4(base + gg * SLOT_B + p * 4096, r0, r1, r2, r3);
          }
        }
      }
#undef ACC
      wg_wait<1>();
      fence_regs(pk);
#pragma unroll
      for (int G = 0; G < 10; G++) {
        P[0][G] = pack_bf16(pk[4 * G], pk[4 * G + 1]); P[1][G] = pack_bf16(pk[4 * G + 2], pk[4 * G + 3]);
      }
      wg_wait<0>();
      fence_regs(pq);
      signal(B_WDEAD);
#pragma unroll
      for (int G = 0; G < 10; G++) {
        qp[0][G] = pack_bf16(pq[4 * G], pq[4 * G + 1]); qp[1][G] = pack_bf16(pq[4 * G + 2], pq[4 * G + 3]);
      }
    }

    uint32_t fr[10][4];
    int pass;
    pass = gridDim.y;
#pragma unroll 1
    do {
    feature_map(P, fr);
    if (pass != 0) {
    {
      const int mat = lane >> 3;
      const int tok = warp * 16 + (mat & 1) * 8 + (lane & 7);
      const uint32_t base = sb + OFF_B + tok * 32 + (((mat >> 1) ^ ((tok >> 2) & 1)) << 4);
#pragma unroll
      for (int G = 0; G < 10; G++) stsm4(base + G * 4096, fr[G][0], fr[G][1], fr[G][2], fr[G][3]);
      fence_async_smem();
      bar_sync(1, 256);
      float kv[40];
      const uint32_t va = sb16 + ((OFF_B + SPARE + wg * 4096) >> 4), vb = sb16 + ((OFF_B + wg * 20480) >> 4);
      wg_fence();
#pragma unroll
      for (int ks = 0; ks < 8; ks++) {
        if (ks == 0) mma_ss80_tt_z(kv, make_desc(va, 0, SLOT_B, 256, 3), make_desc(vb, 0, 4096, 256, 3));
        else mma_ss80_tt(kv, make_desc(va, ks * 512, SLOT_B, 256, 3), make_desc(vb, ks * 512, 4096, 256, 3));
      }
      wg_commit();
      uint32_t xv[2][10];
      wg_wait<0>();
      fence_regs(kv);
      TSTAMP(31);
      releaseB(emptyB); release(bars + 8 * B_PEER2);
      auto kv_sts = [&](uint32_t o, uint32_t a0, uint32_t a1, uint32_t a2, uint32_t a3) {
        sts128(sb + OFF_B + SPARE + wg * 4096 + o + (o >= 4096 ? SLOT_B - 4096 : 0), make_uint4(a0, a1, a2, a3));
      };
      const int m0 = (warp & 3) * 16 + (lane >> 2);
      bar_sync(4 + wg, 128);
#pragma unroll
      for (int r = 0; r < 2; r++) {
        const int m = m0 + 8 * r;
        const bool hi = m >= 20;
        uint32_t v[10];
#pragma unroll
        for (int G = 0; G < 10; G++) v[G] = __float_as_uint(hi ? kv[4 * G + 2 * r + 1] : kv[4 * G + 2 * r]);
        const uint32_t p = 4 * (m < 40 ? m * 48 + t * 12 : 1920 + t * 24 + 12);
        if (m <= 40) { kv_sts(p, v[0], v[1], v[2], v[3]); kv_sts(p + 16, v[4], v[5], v[6], v[7]); kv_sts(p + 32, v[8], v[9], 0u, 0u); }
      }
      if (m0 == 32) {
        const uint32_t p = 4 * (1920 + t * 24);
        kv_sts(p, __float_as_uint(kv[2]), __float_as_uint(kv[6]), __float_as_uint(kv[10]), __float_as_uint(kv[14]));
        kv_sts(p + 16, __float_as_uint(kv[18]), __float_as_uint(kv[22]), __float_as_uint(kv[26]), __float_as_uint(kv[30]));
        kv_sts(p + 32, __float_as_uint(kv[34]), __float_as_uint(kv[38]), 0u, 0u);
      }
      signal(B_SIGKV);
      float acc[80];
      TSTAMP(5);
      mbar_wait(fullA + 8 * 2, 0);
      mbar_wait(fullB + 8 * 1, 1);
      TSTAMP(6);
      wg_fence();
#pragma unroll
      for (int kk = 0; kk < 4; kk++) {
        const uint64_t da = make_desc(sb16 + wg * 512, OFF_A + 2 * SLOT_A + kk * 32, 16, 1024, 1);
        const uint64_t db = make_desc(sb16, OFF_B + SLOT_B + kk * 1024, 4096, 512, 2);
        if (kk == 0) mma_ss160_z(acc, da, db); else mma_ss160(acc, da, db);
      }
      wg_commit();
      ra.next<NA>();
      uint32_t pa = 2, pb = 1;
#pragma unroll 1
      for (int k = 1; k < 5; k++) {
        mbar_wait(k < 4 ? fullA + 8 * ra.idx : bars + 8 * B_T4, k < 4 ? ra.phase : 0);
        if ((k & 1) == 0) mbar_wait(fullB + 8 * rb.idx, rb.phase);
        const uint32_t a0 = sb16 + ((OFF_A + (k < 4 ? ra.idx : NA) * SLOT_A + wg * 8192) >> 4);
        const uint32_t b0 = sb16 + ((OFF_B + rb.idx * SLOT_B + (k & 1) * 20480) >> 4);
        wg_fence();
#pragma unroll
        for (int kk = 0; kk < 4; kk++) {
          mma_ss160(acc, make_desc(a0, kk * 32, 16, 1024, 1), make_desc(b0, kk * 1024, 4096, 512, 2));
          if (kk == 0) {
            wg_commit();
            wg_wait<1>();
            if (k != 4) release(emptyA + 8 * pa);
            if ((k & 1) == 0) releaseB(emptyB + 8 * pb);
          }
        }
        wg_commit();
        pa = ra.idx; pb = rb.idx;
        if (k < 4) ra.next<NA>();
        if ((k & 1) || k == 4) rb.next<NB>();
      }
      mbar_wait(bars + 8 * B_PEER2, 0);
      wg_wait<0>();
      fence_regs(acc);
      TSTAMP(7);
      {
        uint32_t sn[20];
        if (rank) {
#pragma unroll
          for (int e = 0; e < 20; e++) sn[e] = pack_bf16(acc[2 * e], acc[2 * e + 1]);
#pragma unroll
          for (int e = 0; e < 40; e++) acc[e] = acc[40 + e];
        } else {
#pragma unroll
          for (int e = 0; e < 20; e++) sn[e] = pack_bf16(acc[40 + 2 * e], acc[41 + 2 * e]);
        }
        const uint32_t peer = map_peer(sb, rank ^ 1);
#pragma unroll
        for (int q = 0; q < 5; q++)
          st_async16(peer + OFF_B + 20480 + tid * 16 + q * 4096, sn[4 * q], sn[4 * q + 1], sn[4 * q + 2], sn[4 * q + 3],
                     peer + OFF_BAR + 8 * (B_DSR + 8 + wg));
        mbar_wait(bars + 8 * B_XR, 0);
#pragma unroll
        for (int g = 0; g < 10; g++) {
          const uint32_t x0 = lds32(sb + OFF_STG + rloc * 160 + t * 4 + g * 16), x1 = lds32(sb + OFF_STG + rloc * 160 + 1280 + t * 4 + g * 16);
          acc[4 * g] += bf_lo(x0); acc[4 * g + 1] += bf_hi(x0);
          acc[4 * g + 2] += bf_lo(x1); acc[4 * g + 3] += bf_hi(x1);
        }
        mbar_wait(bars + 8 * (B_DSR + 8 + wg), 0);
#pragma unroll
        for (int q = 0; q < 5; q++) {
          const uint4 v = lds128(sb + OFF_B + 20480 + tid * 16 + q * 4096);
          float* d = &acc[8 * q];
          d[0] += bf_lo(v.x); d[1] += bf_hi(v.x); d[2] += bf_lo(v.y); d[3] += bf_hi(v.y);
          d[4] += bf_lo(v.z); d[5] += bf_hi(v.z); d[6] += bf_lo(v.w); d[7] += bf_hi(v.w);
          xv[0][2 * q] = pack_bf16(d[0], d[1]); xv[1][2 * q] = pack_bf16(d[2], d[3]);
          xv[0][2 * q + 1] = pack_bf16(d[4], d[5]); xv[1][2 * q + 1] = pack_bf16(d[6], d[7]);
        }
        releaseB(emptyB + 8 * pb);
      }
      TSTAMP(16);
      stage_tile(sb + OFF_STG, xv);
      signal(B_SIGX1);
      TSTAMP(17);
#pragma unroll
      for (int r = 0; r < 2; r++) {
        float s = 0.f;
#pragma unroll
        for (int g = 0; g < 10; g++) s += acc[4 * g + 2 * r] + acc[4 * g + 2 * r + 1];
        s += __shfl_xor_sync(0xffffffffu, s, 1); s += __shfl_xor_sync(0xffffffffu, s, 2);
        const float mu = s * (1.f / 80.f);
        float q = 0.f;
#pragma unroll
        for (int g = 0; g < 10; g++) {
          const float d0 = acc[4 * g + 2 * r] - mu, d1 = acc[4 * g + 2 * r + 1] - mu;
          q = fmaf(d0, d0, q); q = fmaf(d1, d1, q);
        }
        q += __shfl_xor_sync(0xffffffffu, q, 1); q += __shfl_xor_sync(0xffffffffu, q, 2);
        if (t == 0) g_st1[(128 * i + rloc + 8 * r) * 8 + j] = make_float2(mu, q);
      }
    }
    TSTAMP(8);
#pragma unroll
    for (int G = 0; G < 10; G++) { P[0][G] = qp[0][G]; P[1][G] = qp[1][G]; }
    }
    asm volatile("" : "+r"(pass));
    } while (pass-- != 0);

    uint32_t of[5][4];
    {
      mbar_wait(bars + 8 * B_KV, 0);
#pragma unroll 1
      for (int it = tid; it < 384; it += 256) {
        const int p = it >= 192, rem = it - 192 * p, n = rem >> 2, tq = rem & 3;
        const uint32_t sp = sb + OFF_A + SLOT_A + 4 * (p * KV_PAIR + (n < 40 ? n * 48 + tq * 12 : 1920 + tq * 24 + (n & 1) * 12));
        const uint4 ka = lds128(sp), kb = lds128(sp + 16), kc = lds128(sp + 32);
        const uint32_t v[10] = {ka.x, ka.y, ka.z, ka.w, kb.x, kb.y, kb.z, kb.w, kc.x, kc.y};
        const int sh = (n < 40 ? (n >= 20) : (n & 1)) * 16;
        uint8_t* dst = sgen + OFF_MISC + p * 7680 + n * 32 + tq * 4;
        const int sw = ((n >> 2) & 1) << 4;
#pragma unroll
        for (int G = 0; G < 10; G++)
          *reinterpret_cast<uint32_t*>(dst + (G >> 1) * 1536 + (((G & 1) << 4) ^ sw)) = pack_bf16(__uint_as_float(v[G]), 0.f) << sh;
      }
      release(emptyA + 8);
      fence_async_smem();
      bar_sync(1, 256);
      float o0[24], o1[24];
      wg_fence();
#pragma unroll
      for (int g = 0; g < 5; g++) {
        if (g == 0) mma_rs48_k_z(o0, fr[g], make_desc(sb16, OFF_MISC, 16, 256, 3));
        else mma_rs48_k(o0, fr[g], make_desc(sb16, OFF_MISC + g * 1536, 16, 256, 3));
      }
#pragma unroll
      for (int g = 0; g < 5; g++) {
        if (g == 0) mma_rs48_k_z(o1, fr[5], make_desc(sb16, OFF_MISC + 7680, 16, 256, 3));
        else mma_rs48_k(o1, fr[5 + g], make_desc(sb16, OFF_MISC + 7680 + g * 1536, 16, 256, 3));
      }
      wg_commit();
      wg_wait<0>();
      fence_regs(o0); fence_regs(o1);
      signal(B_MFREE);
#pragma unroll
      for (int r = 0; r < 2; r++) {
        const float a0 = __fdividef(st_g[r], o0[20 + 2 * r] + 1e-6f), a1 = __fdividef(st_g[r], o0[21 + 2 * r] + 1e-6f);
        const float b0 = __fdividef(st_g[r], o1[20 + 2 * r] + 1e-6f), b1 = __fdividef(st_g[r], o1[21 + 2 * r] + 1e-6f);
        const float am = t < 2 ? a0 : a1, bm = t < 2 ? b0 : b1;
#pragma unroll
        for (int g = 0; g < 5; g++) {
          const float sa = g < 2 ? a0 : (g == 2 ? am : a1), sb2 = g < 2 ? b0 : (g == 2 ? bm : b1);
          of[g >> 1][(g & 1) * 2 + r] = pack_bf16(o0[4 * g + 2 * r] * sa, o0[4 * g + 2 * r + 1] * sa);
          of[(5 + g) >> 1][((5 + g) & 1) * 2 + r] = pack_bf16(o1[4 * g + 2 * r] * sb2, o1[4 * g + 2 * r + 1] * sb2);
        }
      }
    }
    TSTAMP(9);

    uint32_t hf[12][4];
    float ac4[80];
    auto unit = [&](auto uc, uint32_t b0) {
      constexpr int u = decltype(uc)::value;
#pragma unroll
      for (int s = 0; s < (u ? 4 : 5); s++) {
        const uint64_t db = make_desc(b0, (u ? 5120 + 20480 * u : 0) + s * 1024, u ? 4096 : 5120, 512, 2);
        if (u == 0 && s == 0) mma_rs160_n_z(ac4, of[0], db);
        else if (u == 0) mma_rs160_n(ac4, of[s], db);
        else mma_rs160_n(ac4, hf[(4 * u + 8 + s) % 12], db);
      }
      wg_commit();
    };
    {
      float acc[96];
      uint32_t pa = 0, pb = 0;
#pragma unroll 1
      for (int k = 0; k < 10; k++) {
        mbar_wait(fullA + 8 * ra.idx, ra.phase);
        if (tid == 0) TRACE(52 + k);
        if ((k & 1) == 0) mbar_wait(fullB + 8 * rb.idx, rb.phase);
        if (tid == 0) TRACE(84 + k);
        if (k == 0) TSTAMP(10);
        const uint32_t a0 = sb16 + ((OFF_A + ra.idx * SLOT_A + wg * 8192) >> 4);
        const uint32_t b0 = sb16 + ((OFF_B + rb.idx * SLOT_B + (k & 1) * 24576) >> 4);
        wg_fence();
#pragma unroll
        for (int kk = 0; kk < 4; kk++) {
          if (kk == 0) mma_ss192_p(acc, make_desc(a0, 0, 16, 1024, 1), make_desc(b0, 0, 8192, 1024, 1), k);
          else mma_ss192(acc, make_desc(a0, kk * 32, 16, 1024, 1), make_desc(b0, kk * 2048, 8192, 1024, 1));
          if (kk == 0) {
            wg_commit();
            if (k > 0) {
              wg_wait<1>();
              release(emptyA + 8 * pa);
              if ((k & 1) == 0) releaseB(emptyB + 8 * pb);
            }
          }
        }
        wg_commit();
        pa = ra.idx; pb = rb.idx;
        ra.next<NA>();
        if (k & 1) rb.next<NB>();
      }
      float rs[2], mm[2];
      mbar_wait(bars + 8 * B_ST1, 0);
#pragma unroll
      for (int r = 0; r < 2; r++) {
        const uint4 su = lds128(sb + OFF_MISC + (rloc + 8 * r) * 64 + t * 16);
        const float m0 = __uint_as_float(su.x), m1 = __uint_as_float(su.z);
        float mu = m0 + m1;
        mu += __shfl_xor_sync(0xffffffffu, mu, 1); mu += __shfl_xor_sync(0xffffffffu, mu, 2);
        mu *= 0.125f;
        const float d0 = m0 - mu, d1 = m1 - mu;
        float q = __uint_as_float(su.y) + __uint_as_float(su.w) + 80.f * (d0 * d0 + d1 * d1);
        q += __shfl_xor_sync(0xffffffffu, q, 1); q += __shfl_xor_sync(0xffffffffu, q, 2);
        rs[r] = rsqrtf(q * (1.f / D_) + 1e-5f);
        mm[r] = -mu;
      }
      mbar_wait(bars + 8 * B_FULL4, 0);
      wg_fence();
      unit(IntC<0>{}, sb16);
      wg_wait<1>();
      fence_regs(acc);
      releaseB(emptyB + 8 * pb);
      release(bars + 8 * B_PEER);
      TSTAMP(11);
      const GeluC g0 = gelu_consts(rs[0], 1.f - st_g[0]), g1 = gelu_consts(rs[1], 1.f - st_g[1]);
#pragma unroll
      for (int g = 0; g < 24; g++) {
        const float2 cs = *reinterpret_cast<const float2*>(s_cs + 80 + 8 * g + 2 * t);
        const float v0 = gelu_s(fmaf(mm[0], cs.x, acc[4 * g]), g0), v1 = gelu_s(fmaf(mm[0], cs.y, acc[4 * g + 1]), g0);
        const float v2 = gelu_s(fmaf(mm[1], cs.x, acc[4 * g + 2]), g1), v3 = gelu_s(fmaf(mm[1], cs.y, acc[4 * g + 3]), g1);
        hf[g >> 1][(g & 1) * 2] = pack_bf16(v0, v1);
        hf[g >> 1][(g & 1) * 2 + 1] = pack_bf16(v2, v3);
        if (g == 7) { wg_fence(); unit(IntC<1>{}, sb16); }
        if (g == 15) { mbar_wait(bars + 8 * (B_FULL4 + 1), 0); wg_fence(); unit(IntC<2>{}, sb16); }
        if (g == 23) { wg_wait<1>(); signal(B_EMPTY4); wg_fence(); unit(IntC<3>{}, sb16); }
      }
    }
    TSTAMP(12);

    {
      float kp[40];
      uint32_t sn[20], kb[20];
      const uint32_t peer = map_peer(sb, rank ^ 1);
      const uint32_t tag = lds32(sb + OFF_BAR + 8 * NBAR);
      auto add8 = [&](int q, const uint4 v) {
        float* d = &kp[8 * q];
        d[0] += bf_lo(v.x); d[1] += bf_hi(v.x); d[2] += bf_lo(v.y); d[3] += bf_hi(v.y);
        d[4] += bf_lo(v.z); d[5] += bf_hi(v.z); d[6] += bf_lo(v.w); d[7] += bf_hi(v.w);
      };
      auto send = [&](int c) {
        const uint32_t dso = peer + OFF_DS + (c & 1) * 20480 + tid * 16, dsb = peer + OFF_BAR + 8 * (B_DSR + 2 * c + wg);
#pragma unroll
        for (int q = 0; q < 5; q++) st_async16(dso + q * 4096, sn[4 * q], sn[4 * q + 1], sn[4 * q + 2], sn[4 * q + 3], dsb);
      };
      mbar_wait(bars + 8 * B_PEER, 0);
      uint4* gdst = g_part + (size_t)i * 8 * 3840 + tid;
#pragma unroll 1
      for (int c = 0; c < 3; c++) {
        const uint32_t b0 = sb16 + ((c & 1) ? 0 : SET4 >> 4), bc = bars + 16 * c;
        mbar_wait(bc + 8 * (B_FULL4 + 2), 0);
        wg_wait<0>();
        fence_regs(ac4);
        if (rank) {
#pragma unroll
          for (int e = 0; e < 20; e++) { sn[e] = pack_bf16(ac4[2 * e], ac4[2 * e + 1]); kb[e] = pack_bf16(ac4[40 + 2 * e], ac4[41 + 2 * e]); }
        } else {
#pragma unroll
          for (int e = 0; e < 20; e++) { kb[e] = pack_bf16(ac4[2 * e], ac4[2 * e + 1]); sn[e] = pack_bf16(ac4[40 + 2 * e], ac4[41 + 2 * e]); }
        }
#pragma unroll
        for (int e = 0; e < 20; e++) asm volatile("" : "+r"(sn[e]), "+r"(kb[e]));
        send(c);
        if (c == 0 && wg == 1) bar_sync(2, 256);
        wg_fence();
        unit(IntC<0>{}, b0);
        if (lane == 0) mbar_arrive(bc + 8 * (B_EMPTY4 + 1));
        unit(IntC<1>{}, b0);
        if (c == 0 && wg == 0) bar_arrive(2, 256);
        {
          mbar_wait(bc + 8 * (B_DSR + wg), 0);
          uint4* dst = gdst + (((j + 2 * c + 2) & 7) * 3 + c) * 1280;
#pragma unroll
          for (int q = 0; q < 5; q++) {
            const uint4 v = lds128(sb + OFF_DS + (c & 1) * 20480 + tid * 16 + q * 4096);
            st_relaxed16(dst + q * 256, (add_bf2(v.x, kb[4 * q]) & ~1u) | tag, add_bf2(v.y, kb[4 * q + 1]),
                         add_bf2(v.z, kb[4 * q + 2]), add_bf2(v.w, kb[4 * q + 3]));
          }
        }
        mbar_wait(bc + 8 * (B_FULL4 + 3), 0);
        wg_fence();
        unit(IntC<2>{}, b0);
        wg_wait<1>();
        if (lane == 0) mbar_arrive(bc + 8 * (B_EMPTY4 + 2));
        unit(IntC<3>{}, b0);
      }
      auto partial = [&](int c, uint4 (&v)[5]) {
        mbar_wait(bars + 8 * (B_RDY + c), 0);
        uint32_t bad = 0;
#pragma unroll
        for (int q = 0; q < 5; q++) { v[q] = lds128(sb + (c ? 25600 + 20480 * c : 0) + tid * 16 + q * 4096); bad |= v[q].x ^ tag; }
#pragma unroll 1
        for (uint32_t n = 0; (bad & 1u) && n < (WAIT_LIMIT >> 2); n++) {
          bad = 0;
#pragma unroll
          for (int q = 0; q < 5; q++) { v[q] = ld_relaxed16(gdst + (j * 3 + c) * 1280 + q * 256); bad |= v[q].x ^ tag; }
        }
      };
      uint4 pa4[5], pb4[5];
      partial(0, pa4);
      wg_wait<0>();
      fence_regs(ac4);
      if (rank) {
#pragma unroll
        for (int e = 0; e < 20; e++) sn[e] = pack_bf16(ac4[2 * e], ac4[2 * e + 1]);
#pragma unroll
        for (int e = 0; e < 40; e++) kp[e] = ac4[40 + e];
      } else {
#pragma unroll
        for (int e = 0; e < 20; e++) sn[e] = pack_bf16(ac4[40 + 2 * e], ac4[41 + 2 * e]);
#pragma unroll
        for (int e = 0; e < 40; e++) kp[e] = ac4[e];
      }
      send(3);
      TSTAMP(13);
      {
        mbar_wait(bars + 8 * B_XR, 1);
        const float w0 = 1.f - st_g[0], w1s = 1.f - st_g[1];
        const uint32_t xa = sb + OFF_OUT + rloc * 160 + t * 4;
#pragma unroll
        for (int g = 0; g < 10; g++) {
          const uint32_t x0 = lds32(xa + g * 16), x1 = lds32(xa + 1280 + g * 16);
          kp[4 * g] = fmaf(w0, bf_lo(x0), kp[4 * g]); kp[4 * g + 1] = fmaf(w0, bf_hi(x0), kp[4 * g + 1]);
          kp[4 * g + 2] = fmaf(w1s, bf_lo(x1), kp[4 * g + 2]); kp[4 * g + 3] = fmaf(w1s, bf_hi(x1), kp[4 * g + 3]);
        }
      }
      partial(1, pb4);
#pragma unroll
      for (int q = 0; q < 5; q++)
        pa4[q] = make_uint4(add_bf2(pa4[q].x, pb4[q].x), add_bf2(pa4[q].y, pb4[q].y), add_bf2(pa4[q].z, pb4[q].z), add_bf2(pa4[q].w, pb4[q].w));
#pragma unroll
      for (int q = 0; q < 5; q++) add8(q, pa4[q]);
      partial(2, pb4);
      mbar_wait(bars + 8 * (B_DSR + 6 + wg), 0);
      TSTAMP(14);
#pragma unroll
      for (int q = 0; q < 5; q++) {
        const uint4 c = pb4[q], d = lds128(sb + OFF_DS + 20480 + tid * 16 + q * 4096);
        add8(q, make_uint4(add_bf2(c.x, d.x), add_bf2(c.y, d.y), add_bf2(c.z, d.z), add_bf2(c.w, d.w)));
      }
      __syncwarp();
      uint32_t ov[2][10];
#pragma unroll
      for (int g = 0; g < 10; g++) { ov[0][g] = pack_bf16(kp[4 * g], kp[4 * g + 1]); ov[1][g] = pack_bf16(kp[4 * g + 2], kp[4 * g + 3]); }
      stage_tile(sb + OFF_OUT, ov);
      __syncwarp();
      __nv_bfloat16* dst = out + (size_t)(128 * i + 16 * warp) * D_ + 80 * j;
#pragma unroll
      for (int q = 0; q < 5; q++) {
        const int id = q * 32 + lane, r = id / 10;
        *reinterpret_cast<uint4*>(dst + r * (D_ - 80) + id * 8) = lds128(sb + OFF_OUT + warp * 2560 + id * 16);
      }
    }
    TSTAMP(15);
    if (tid == 0) asm volatile("red.relaxed.gpu.global.add.u32 [%0], 1;" ::"l"(g_flags + FL_DONE * 32) : "memory");
  }
}

namespace {
typedef CUresult (*EncodeFn)(CUtensorMap*, CUtensorMapDataType, cuuint32_t, void*, const cuuint64_t*, const cuuint64_t*,
                             const cuuint32_t*, const cuuint32_t*, CUtensorMapInterleave, CUtensorMapSwizzle,
                             CUtensorMapL2promotion, CUtensorMapFloatOOBfill);

void encode(EncodeFn fn, CUtensorMap* m, const void* ptr, int rank, const cuuint64_t* dims, const cuuint64_t* strides,
            const cuuint32_t* box, CUtensorMapSwizzle swz) {
  cuuint32_t es[5] = {1, 1, 1, 1, 1};
  fn(m, CU_TENSOR_MAP_DATA_TYPE_BFLOAT16, rank, const_cast<void*>(ptr), dims, strides, box, es, CU_TENSOR_MAP_INTERLEAVE_NONE,
     swz, CU_TENSOR_MAP_L2_PROMOTION_L2_128B, CU_TENSOR_MAP_FLOAT_OOB_FILL_NONE);
}
}

extern "C" void kernel_launch(void* const* d_in, const int* in_sizes, int n_in, void* d_out, int out_size) {
  (void)in_sizes; (void)n_in; (void)out_size;
  const __nv_bfloat16* x = (const __nv_bfloat16*)d_in[0];
  const __nv_bfloat16* wqkv = (const __nv_bfloat16*)d_in[1];
  const __nv_bfloat16* wphi = (const __nv_bfloat16*)d_in[2];
  const __nv_bfloat16* wo = (const __nv_bfloat16*)d_in[3];
  const __nv_bfloat16* w1 = (const __nv_bfloat16*)d_in[5];
  const __nv_bfloat16* w2 = (const __nv_bfloat16*)d_in[6];
  const __nv_bfloat16* w3 = (const __nv_bfloat16*)d_in[7];
  const __nv_bfloat16* w4 = (const __nv_bfloat16*)d_in[8];
  const __nv_bfloat16* gate_w = (const __nv_bfloat16*)d_in[9];

  static EncodeFn enc = nullptr;
  static void *pHs = nullptr, *pX1 = nullptr;
  if (!enc) {
    cudaDriverEntryPointQueryResult qr;
    cudaGetDriverEntryPoint("cuTensorMapEncodeTiled", (void**)&enc, cudaEnableDefault, &qr);
    cudaGetSymbolAddress(&pHs, g_Hs);
    cudaGetSymbolAddress(&pX1, g_X1);
    cudaFuncSetAttribute(fused_kernel, cudaFuncAttributeMaxDynamicSharedMemorySize, SMEM_BYTES);
  }
  Maps m;
  {
    cuuint64_t dims[2] = {D_, S_}, str[1] = {D_ * 2};
    cuuint32_t box[2] = {64, 128}, boxh[2] = {64, 64};
    encode(enc, &m.x, x, 2, dims, str, boxh, CU_TENSOR_MAP_SWIZZLE_128B);
    encode(enc, &m.hs, (const char*)pHs + 2 * D_ * 2, 2, dims, str, box, CU_TENSOR_MAP_SWIZZLE_128B);
    encode(enc, &m.x1, pX1, 2, dims, str, boxh, CU_TENSOR_MAP_SWIZZLE_128B);
    cuuint32_t boxs[2] = {80, 128};
    cuuint64_t dimsp[2] = {D_, S_ + 4};
    encode(enc, &m.st_h, pHs, 2, dimsp, str, boxs, CU_TENSOR_MAP_SWIZZLE_NONE);
    encode(enc, &m.st_x1, pX1, 2, dims, str, boxs, CU_TENSOR_MAP_SWIZZLE_NONE);
    encode(enc, &m.xr, x, 2, dims, str, boxs, CU_TENSOR_MAP_SWIZZLE_NONE);
  }
  {
    cuuint64_t dims[3] = {80, D_, 8}, str[2] = {D_ * 2, 160};
    cuuint32_t boxm[3] = {64, 64, 1}, boxr[3] = {16, 64, 1};
    encode(enc, &m.w1m, w1, 3, dims, str, boxm, CU_TENSOR_MAP_SWIZZLE_128B);
    encode(enc, &m.w1r, w1, 3, dims, str, boxr, CU_TENSOR_MAP_SWIZZLE_32B);
  }
  {
    cuuint64_t dims[4] = {80, D_, 3, 8}, str[3] = {3 * D_ * 2, D_ * 2, 160};
    cuuint32_t boxm[4] = {64, 64, 3, 1}, boxr[4] = {16, 64, 3, 1};
    encode(enc, &m.qm, wqkv, 4, dims, str, boxm, CU_TENSOR_MAP_SWIZZLE_128B);
    encode(enc, &m.qr, wqkv, 4, dims, str, boxr, CU_TENSOR_MAP_SWIZZLE_32B);
  }
  {
    cuuint64_t dims[3] = {32, D_, 20}, dims4[3] = {32, F_, 20}, str[2] = {D_ * 2, 64};
    cuuint32_t box4[3] = {32, 64, 5}, boxo[3] = {32, 80, 5};
    encode(enc, &m.w4, w4, 3, dims4, str, box4, CU_TENSOR_MAP_SWIZZLE_64B);
    encode(enc, &m.wo, wo, 3, dims, str, boxo, CU_TENSOR_MAP_SWIZZLE_64B);
    encode(enc, &m.w2, w2, 3, dims, str, box4, CU_TENSOR_MAP_SWIZZLE_64B);
  }
  {
    cuuint64_t dims[3] = {64, D_, 24}, str[2] = {F_ * 2, 128};
    cuuint32_t box[3] = {64, 64, 3};
    encode(enc, &m.w3, w3, 3, dims, str, box, CU_TENSOR_MAP_SWIZZLE_128B);
  }
  fused_kernel<<<NCTA + NSVC, 384, SMEM_BYTES, cudaStreamPerThread>>>(m, x, wqkv, wphi, w1, w2, w3, w4, wo, gate_w, (__nv_bfloat16*)d_out);
}
```

```cpp
#include <cuda_runtime.h>
#include <cuda_bf16.h>
#include <cuda.h>
#include <stdint.h>

namespace {

constexpr int S_ = 2048, D_ = 640, F_ = 1536;
constexpr int NCTA = 128, NSVC = 4;
constexpr int KV_PAIR = 40 * 48 + 96;
constexpr int KV_J = 2 * KV_PAIR;

constexpr int SLOT_B = 49152, NB = 3;
constexpr int SLOT_A = 16384, NA = 4;
constexpr int OFF_B = 0;
constexpr int OFF_A = OFF_B + NB * SLOT_B;
constexpr int OFF_STG = OFF_A + 2 * SLOT_A;
constexpr int OFF_MISC = OFF_A + NA * SLOT_A;
constexpr int OFF_XST = OFF_MISC + 13312;
constexpr int OFF_CS = OFF_MISC + 16384;
constexpr int OFF_BAR = OFF_CS + 1088;
constexpr int SMEM_BYTES = OFF_BAR + 512 + 512 + 128;
constexpr int B_FULLA = 0, B_FULLB = 4, B_CS = 7, B_XR = 8, B_KV = 9, B_ST1 = 10, B_HST = 11, B_FULL4 = 12  , B_RDY = 20  , B_T4 = 23, B_KVR = 24,
              B_DSR = 25  , B_EMPTYB = 35  , B_SIGP = 38, B_SIGH = 39, B_SIGKV = 40, B_SIGX1 = 41, B_MFREE = 42,
              B_WDEAD = 43, B_EMPTY4 = 44  , B_EMPTYA = 52  , B_PEER = 56, B_PEER2 = 57, B_X1P = 58  , NBAR = 59;
constexpr int SPARE = 40960;
constexpr int SET4 = 87040, OFF_DS = 2 * SET4, OFF_OUT = 20480;

constexpr int FL_DONE = 0, FL_H = 1  , FL_X1 = FL_H + 32, FL_KV = FL_X1 + 16, FL_CS = FL_KV + 8, FL_CS3 = FL_CS + 1, FL_ST = FL_CS3 + 1;
constexpr int FL_S1 = FL_ST + 16, FL_COUNT = FL_S1 + 16;

struct Maps {
  CUtensorMap x, w1m, w1r, qm, qr, hs, w2, x1, w3, w4, wo, xr, st_h, st_x1;
};

}

__device__ __align__(1024) __nv_bfloat16 g_Hs[(S_ + 4) * D_];
__device__ __align__(1024) __nv_bfloat16 g_X1[S_ * D_];
__device__ __align__(128) float g_acc[2][8 * KV_J];
__device__ __align__(128) float g_cs[2][D_ + F_];
__device__ __align__(128) uint4 g_wphi[8 * 800];
__device__ __align__(128) float4 g_xstat[S_];
__device__ __align__(128) float2 g_st1[S_ * 8];
__device__ __align__(128) uint4 g_part[16 * 8 * 3 * 1280];
__device__ __align__(128) unsigned g_flags[FL_COUNT * 32];
#define TSTAMP(n) do {} while (0)
#define TSTAMPX(n) do {} while (0)
#define TRACE(n) do {} while (0)
#define TRS(n) do {} while (0)

namespace {

__device__ __forceinline__ long long gtime() { long long t; asm volatile("mov.u64 %0, %%globaltimer;" : "=l"(t)); return t; }
__device__ __forceinline__ uint32_t smem_u32(const void* p) { return (uint32_t)__cvta_generic_to_shared(p); }
__device__ __forceinline__ void mbar_init(uint32_t bar, int cnt) {
  asm volatile("mbarrier.init.shared::cta.b64 [%0], %1;" ::"r"(bar), "r"(cnt) : "memory");
}
__device__ __forceinline__ void mbar_expect_tx(uint32_t bar, int bytes) {
  asm volatile("mbarrier.arrive.expect_tx.shared::cta.b64 _, [%0], %1;" ::"r"(bar), "r"(bytes) : "memory");
}
__device__ __forceinline__ void mbar_arrive_cta(uint32_t bar, uint32_t cta) {
  asm volatile("{\n.reg .b32 ra;\nmapa.shared::cluster.u32 ra, %0, %1;\nmbarrier.arrive.shared::cluster.b64 _, [ra];\n}"
               ::"r"(bar), "r"(cta) : "memory");
}
__device__ __forceinline__ uint32_t mbar_try(uint32_t bar, uint32_t parity) {
  uint32_t ok;
  asm volatile("{\n.reg .pred p;\nmbarrier.try_wait.parity.shared::cta.b64 p, [%1], %2;\nselp.u32 %0, 1, 0, p;\n}"
               : "=r"(ok) : "r"(bar), "r"(parity) : "memory");
  return ok;
}
constexpr uint32_t WAIT_LIMIT = 1u << 17;
__device__ __forceinline__ void mbar_wait(uint32_t bar, uint32_t parity) {
  uint32_t n = 0;
  while (!mbar_try(bar, parity) && ++n < WAIT_LIMIT) {}
}
__device__ __forceinline__ unsigned ld_acquire(const unsigned* p) {
  unsigned v;
  asm volatile("ld.acquire.gpu.global.u32 %0, [%1];" : "=r"(v) : "l"(p) : "memory");
  return v;
}
__device__ __forceinline__ void flag_wait(int idx, unsigned target) {
  const unsigned* p = g_flags + idx * 32;
  uint32_t n = 0;
  while ((int)(ld_acquire(p) - target) < 0 && ++n < (WAIT_LIMIT >> 2)) {}
}
__device__ __forceinline__ void flag_add(int idx) {
  asm volatile("red.release.gpu.global.add.u32 [%0], 1;" ::"l"(g_flags + idx * 32) : "memory");
}
__device__ __forceinline__ void flag_add_relaxed(int idx) {
  asm volatile("red.relaxed.gpu.global.add.u32 [%0], 1;" ::"l"(g_flags + idx * 32) : "memory");
}
__device__ __forceinline__ uint32_t mbar_test(uint32_t bar, uint32_t parity) {
  uint32_t ok;
  asm volatile("{\n.reg .pred p;\nmbarrier.test_wait.parity.shared::cta.b64 p, [%1], %2;\nselp.u32 %0, 1, 0, p;\n}"
               : "=r"(ok) : "r"(bar), "r"(parity) : "memory");
  return ok;
}
__device__ __forceinline__ uint32_t lds32(uint32_t a) {
  uint32_t v;
  asm volatile("ld.shared.u32 %0, [%1];" : "=r"(v) : "r"(a) : "memory");
  return v;
}
__device__ __forceinline__ void mbar_arrive(uint32_t bar) {
  asm volatile("mbarrier.arrive.shared::cta.b64 _, [%0];" ::"r"(bar) : "memory");
}
__device__ __forceinline__ void fence_async_glb() { asm volatile("fence.proxy.async.global;" ::: "memory"); }
__device__ __forceinline__ void fence_async_smem() { asm volatile("fence.proxy.async.shared::cta;" ::: "memory"); }
__device__ __forceinline__ void bar_sync(int id, int n) { asm volatile("bar.sync %0, %1;" ::"r"(id), "r"(n) : "memory"); }

__device__ __forceinline__ void tma2d(uint32_t dst, const CUtensorMap* m, uint32_t bar, int c0, int c1) {
  asm volatile("cp.async.bulk.tensor.2d.shared::cluster.global.mbarrier::complete_tx::bytes [%0], [%1, {%3, %4}], [%2];"
               ::"r"(dst), "l"(m), "r"(bar), "r"(c0), "r"(c1) : "memory");
}
__device__ __forceinline__ void tma2d_mc(uint32_t dst, const CUtensorMap* m, uint32_t bar, int c0, int c1) {
  asm volatile("cp.async.bulk.tensor.2d.shared::cluster.global.mbarrier::complete_tx::bytes.multicast::cluster"
               " [%0], [%1, {%3, %4}], [%2], %5;"
               ::"r"(dst), "l"(m), "r"(bar), "r"(c0), "r"(c1), "h"((uint16_t)3) : "memory");
}
__device__ __forceinline__ void tma3d(uint32_t dst, const CUtensorMap* m, uint32_t bar, int c0, int c1, int c2) {
  asm volatile("cp.async.bulk.tensor.3d.shared::cluster.global.mbarrier::complete_tx::bytes [%0], [%1, {%3, %4, %5}], [%2];"
               ::"r"(dst), "l"(m), "r"(bar), "r"(c0), "r"(c1), "r"(c2) : "memory");
}
__device__ __forceinline__ void tma4d(uint32_t dst, const CUtensorMap* m, uint32_t bar, int c0, int c1, int c2, int c3) {
  asm volatile("cp.async.bulk.tensor.4d.shared::cluster.global.mbarrier::complete_tx::bytes [%0], [%1, {%3, %4, %5, %6}], [%2];"
               ::"r"(dst), "l"(m), "r"(bar), "r"(c0), "r"(c1), "r"(c2), "r"(c3) : "memory");
}
__device__ __forceinline__ void tma2d_store(const CUtensorMap* m, uint32_t src, int c0, int c1) {
  asm volatile("cp.async.bulk.tensor.2d.global.shared::cta.bulk_group [%0, {%2, %3}], [%1];"
               ::"l"(m), "r"(src), "r"(c0), "r"(c1) : "memory");
}
__device__ __forceinline__ void bulk_store(void* dst, uint32_t src, uint32_t bytes) {
  asm volatile("cp.async.bulk.global.shared::cta.bulk_group [%0], [%1], %2;" ::"l"(dst), "r"(src), "r"(bytes) : "memory");
}
__device__ __forceinline__ void bulk_load(uint32_t dst, const void* src, uint32_t bytes, uint32_t bar) {
  asm volatile("cp.async.bulk.shared::cluster.global.mbarrier::complete_tx::bytes [%0], [%1], %2, [%3];"
               ::"r"(dst), "l"(src), "r"(bytes), "r"(bar) : "memory");
}
__device__ __forceinline__ void bulk_commit() { asm volatile("cp.async.bulk.commit_group;" ::: "memory"); }
template <int N> __device__ __forceinline__ void bulk_wait() { asm volatile("cp.async.bulk.wait_group %0;" ::"n"(N) : "memory"); }
__device__ __forceinline__ void bulk_wait_read() { asm volatile("cp.async.bulk.wait_group.read 0;" ::: "memory"); }
__device__ __forceinline__ void bar_arrive(int id, int n) { asm volatile("bar.arrive %0, %1;" ::"r"(id), "r"(n) : "memory"); }
__device__ __forceinline__ uint4 lds128(uint32_t a) {
  uint4 v;
  asm volatile("ld.shared.v4.u32 {%0, %1, %2, %3}, [%4];" : "=r"(v.x), "=r"(v.y), "=r"(v.z), "=r"(v.w) : "r"(a) : "memory");
  return v;
}
__device__ __forceinline__ void sts128(uint32_t a, uint4 v) {
  asm volatile("st.shared.v4.u32 [%0], {%1, %2, %3, %4};" ::"r"(a), "r"(v.x), "r"(v.y), "r"(v.z), "r"(v.w) : "memory");
}
__device__ __forceinline__ uint4 ld_relaxed16(const uint4* p) {
  uint4 v;
  asm volatile("ld.relaxed.gpu.global.v4.u32 {%0, %1, %2, %3}, [%4];" : "=r"(v.x), "=r"(v.y), "=r"(v.z), "=r"(v.w) : "l"(p) : "memory");
  return v;
}
__device__ __forceinline__ void st_relaxed16(uint4* p, uint32_t a, uint32_t b, uint32_t c, uint32_t d) {
  asm volatile("st.relaxed.gpu.global.v4.u32 [%0], {%1, %2, %3, %4};" ::"l"(p), "r"(a), "r"(b), "r"(c), "r"(d) : "memory");
}
__device__ __forceinline__ uint32_t map_peer(uint32_t addr, uint32_t cta) {
  uint32_t r;
  asm("mapa.shared::cluster.u32 %0, %1, %2;" : "=r"(r) : "r"(addr), "r"(cta));
  return r;
}
__device__ __forceinline__ void st_async16(uint32_t addr, uint32_t a, uint32_t b, uint32_t c, uint32_t d, uint32_t bar) {
  asm volatile("st.async.weak.shared::cluster.mbarrier::complete_tx::bytes.v4.b32 [%0], {%1, %2, %3, %4}, [%5];"
               ::"r"(addr), "r"(a), "r"(b), "r"(c), "r"(d), "r"(bar) : "memory");
}
__device__ __forceinline__ void l2_prefetch(const void* p, uint32_t bytes) {
  asm volatile("cp.async.bulk.prefetch.L2.global [%0], %1;" ::"l"(p), "r"(bytes) : "memory");
}
__device__ __forceinline__ void prefetch_tmap(const CUtensorMap* m) {
  asm volatile("prefetch.tensormap [%0];" ::"l"(m) : "memory");
}
__device__ __forceinline__ uint64_t make_desc(uint32_t a16, uint32_t off, uint32_t lbo, uint32_t sbo, uint32_t swz) {
  const uint32_t lo = a16 + ((off >> 4) + ((lbo >> 4) << 16)), hi = (sbo >> 4) | (swz << 30);
  uint64_t d;
  asm("mov.b64 %0, {%1, %2};" : "=l"(d) : "r"(lo), "r"(hi));
  return d;
}
__device__ __forceinline__ void wg_fence() { asm volatile("wgmma.fence.sync.aligned;" ::: "memory"); }
__device__ __forceinline__ void wg_commit() { asm volatile("wgmma.commit_group.sync.aligned;" ::: "memory"); }
template <int N> __device__ __forceinline__ void wg_wait() { asm volatile("wgmma.wait_group.sync.aligned %0;" ::"n"(N) : "memory"); }
template <int N> __device__ __forceinline__ void fence_regs(float (&d)[N]) {
#pragma unroll
  for (int i = 0; i < N; i++) asm volatile("" : "+f"(d[i])::"memory");
}
template <int N> __device__ __forceinline__ void zero_regs(float (&d)[N]) {
#pragma unroll
  for (int i = 0; i < N; i++) d[i] = 0.f;
}
__device__ __forceinline__ uint32_t pack_bf16(float lo, float hi) {
  uint32_t r;
  asm("cvt.rn.bf16x2.f32 %0, %1, %2;" : "=r"(r) : "f"(hi), "f"(lo));
  return r;
}
__device__ __forceinline__ float bf_lo(uint32_t v) { return __uint_as_float(v << 16); }
__device__ __forceinline__ float bf_hi(uint32_t v) { return __uint_as_float(v & 0xffff0000u); }
__device__ __forceinline__ uint32_t max_bf2(uint32_t a, uint32_t b) {
  uint32_t r; asm("max.bf16x2 %0, %1, %2;" : "=r"(r) : "r"(a), "r"(b)); return r;
}
__device__ __forceinline__ uint32_t min_bf2(uint32_t a, uint32_t b) {
  uint32_t r; asm("min.bf16x2 %0, %1, %2;" : "=r"(r) : "r"(a), "r"(b)); return r;
}
__device__ __forceinline__ uint32_t add_bf2(uint32_t a, uint32_t b) {
  uint32_t r; asm("add.rn.bf16x2 %0, %1, %2;" : "=r"(r) : "r"(a), "r"(b)); return r;
}
__device__ __forceinline__ uint32_t mul_bf2(uint32_t a, uint32_t b) {
  uint32_t r; asm("mul.rn.bf16x2 %0, %1, %2;" : "=r"(r) : "r"(a), "r"(b)); return r;
}
__device__ __forceinline__ float ex2(float x) { float r; asm("ex2.approx.ftz.f32 %0, %1;" : "=f"(r) : "f"(x)); return r; }
__device__ __forceinline__ float rcp(float x) { float r; asm("rcp.approx.ftz.f32 %0, %1;" : "=f"(r) : "f"(x)); return r; }
__device__ __forceinline__ float tanh_ap(float x) { float r; asm("tanh.approx.f32 %0, %1;" : "=f"(r) : "f"(x)); return r; }
struct GeluC { float c0, c1, ch; };
__device__ __forceinline__ GeluC gelu_consts(float rstd, float scale) {
  return GeluC{0.7978845608f * rstd, 0.0356774081f * rstd * rstd * rstd, 0.5f * scale * rstd};
}
__device__ __forceinline__ float gelu_s(float y, const GeluC& c) {
  const float u = y * fmaf(y * y, c.c1, c.c0);
  const float hx = y * c.ch;
  return fmaf(hx, tanh_ap(u), hx);
}
__device__ __forceinline__ void stsm4(uint32_t addr, uint32_t r0, uint32_t r1, uint32_t r2, uint32_t r3) {
  asm volatile("stmatrix.sync.aligned.m8n8.x4.shared.b16 [%0], {%1, %2, %3, %4};"
               ::"r"(addr), "r"(r0), "r"(r1), "r"(r2), "r"(r3) : "memory");
}

__device__ __forceinline__ void red_add4(float* p, float a, float b, float c, float d) {
  asm volatile("red.global.add.v4.f32 [%0], {%1, %2, %3, %4};" ::"l"(p), "f"(a), "f"(b), "f"(c), "f"(d) : "memory");
}

__device__ __forceinline__ void mma_ss256(float (&d)[128], uint64_t descA, uint64_t descB) {
  asm volatile("wgmma.mma_async.sync.aligned.m64n256k16.f32.bf16.bf16 {"
      "%0, %1, %2, %3, %4, %5, %6, %7, %8, %9, %10, %11, %12, %13, %14, %15, "
      "%16, %17, %18, %19, %20, %21, %22, %23, %24, %25, %26, %27, %28, %29, %30, %31, "
      "%32, %33, %34, %35, %36, %37, %38, %39, %40, %41, %42, %43, %44, %45, %46, %47, "
      "%48, %49, %50, %51, %52, %53, %54, %55, %56, %57, %58, %59, %60, %61, %62, %63, "
      "%64, %65, %66, %67, %68, %69, %70, %71, %72, %73, %74, %75, %76, %77, %78, %79, "
      "%80, %81, %82, %83, %84, %85, %86, %87, %88, %89, %90, %91, %92, %93, %94, %95, "
      "%96, %97, %98, %99, %100, %101, %102, %103, %104, %105, %106, %107, %108, %109, %110, %111, "
      "%112, %113, %114, %115, %116, %117, %118, %119, %120, %121, %122, %123, %124, %125, %126, %127"
      "}, %128, %129, 1, 1, 1, 0, 1;\n"
      : "+f"(d[0]), "+f"(d[1]), "+f"(d[2]), "+f"(d[3]), "+f"(d[4]), "+f"(d[5]), "+f"(d[6]), "+f"(d[7]),
        "+f"(d[8]), "+f"(d[9]), "+f"(d[10]), "+f"(d[11]), "+f"(d[12]), "+f"(d[13]), "+f"(d[14]), "+f"(d[15]),
        "+f"(d[16]), "+f"(d[17]), "+f"(d[18]), "+f"(d[19]), "+f"(d[20]), "+f"(d[21]), "+f"(d[22]), "+f"(d[23]),
        "+f"(d[24]), "+f"(d[25]), "+f"(d[26]), "+f"(d[27]), "+f"(d[28]), "+f"(d[29]), "+f"(d[30]), "+f"(d[31]),
        "+f"(d[32]), "+f"(d[33]), "+f"(d[34]), "+f"(d[35]), "+f"(d[36]), "+f"(d[37]), "+f"(d[38]), "+f"(d[39]),
        "+f"(d[40]), "+f"(d[41]), "+f"(d[42]), "+f"(d[43]), "+f"(d[44]), "+f"(d[45]), "+f"(d[46]), "+f"(d[47]),
        "+f"(d[48]), "+f"(d[49]), "+f"(d[50]), "+f"(d[51]), "+f"(d[52]), "+f"(d[53]), "+f"(d[54]), "+f"(d[55]),
        "+f"(d[56]), "+f"(d[57]), "+f"(d[58]), "+f"(d[59]), "+f"(d[60]), "+f"(d[61]), "+f"(d[62]), "+f"(d[63]),
        "+f"(d[64]), "+f"(d[65]), "+f"(d[66]), "+f"(d[67]), "+f"(d[68]), "+f"(d[69]), "+f"(d[70]), "+f"(d[71]),
        "+f"(d[72]), "+f"(d[73]), "+f"(d[74]), "+f"(d[75]), "+f"(d[76]), "+f"(d[77]), "+f"(d[78]), "+f"(d[79]),
        "+f"(d[80]), "+f"(d[81]), "+f"(d[82]), "+f"(d[83]), "+f"(d[84]), "+f"(d[85]), "+f"(d[86]), "+f"(d[87]),
        "+f"(d[88]), "+f"(d[89]), "+f"(d[90]), "+f"(d[91]), "+f"(d[92]), "+f"(d[93]), "+f"(d[94]), "+f"(d[95]),
        "+f"(d[96]), "+f"(d[97]), "+f"(d[98]), "+f"(d[99]), "+f"(d[100]), "+f"(d[101]), "+f"(d[102]), "+f"(d[103]),
        "+f"(d[104]), "+f"(d[105]), "+f"(d[106]), "+f"(d[107]), "+f"(d[108]), "+f"(d[109]), "+f"(d[110]), "+f"(d[111]),
        "+f"(d[112]), "+f"(d[113]), "+f"(d[114]), "+f"(d[115]), "+f"(d[116]), "+f"(d[117]), "+f"(d[118]), "+f"(d[119]),
        "+f"(d[120]), "+f"(d[121]), "+f"(d[122]), "+f"(d[123]), "+f"(d[124]), "+f"(d[125]), "+f"(d[126]), "+f"(d[127])
      : "l"(descA), "l"(descB));
}
__device__ __forceinline__ void mma_ss256_p(float (&d)[128], uint64_t descA, uint64_t descB, int acc) {
  asm volatile("{\n.reg .pred p;\nsetp.ne.b32 p, %130, 0;\n"
      "wgmma.mma_async.sync.aligned.m64n256k16.f32.bf16.bf16 {"
      "%0, %1, %2, %3, %4, %5, %6, %7, %8, %9, %10, %11, %12, %13, %14, %15, "
      "%16, %17, %18, %19, %20, %21, %22, %23, %24, %25, %26, %27, %28, %29, %30, %31, "
      "%32, %33, %34, %35, %36, %37, %38, %39, %40, %41, %42, %43, %44, %45, %46, %47, "
      "%48, %49, %50, %51, %52, %53, %54, %55, %56, %57, %58, %59, %60, %61, %62, %63, "
      "%64, %65, %66, %67, %68, %69, %70, %71, %72, %73, %74, %75, %76, %77, %78, %79, "
      "%80, %81, %82, %83, %84, %85, %86, %87, %88, %89, %90, %91, %92, %93, %94, %95, "
      "%96, %97, %98, %99, %100, %101, %102, %103, %104, %105, %106, %107, %108, %109, %110, %111, "
      "%112, %113, %114, %115, %116, %117, %118, %119, %120, %121, %122, %123, %124, %125, %126, %127"
      "}, %128, %129, p, 1, 1, 0, 1;\n}\n"
      : "+f"(d[0]), "+f"(d[1]), "+f"(d[2]), "+f"(d[3]), "+f"(d[4]), "+f"(d[5]), "+f"(d[6]), "+f"(d[7]),
        "+f"(d[8]), "+f"(d[9]), "+f"(d[10]), "+f"(d[11]), "+f"(d[12]), "+f"(d[13]), "+f"(d[14]), "+f"(d[15]),
        "+f"(d[16]), "+f"(d[17]), "+f"(d[18]), "+f"(d[19]), "+f"(d[20]), "+f"(d[21]), "+f"(d[22]), "+f"(d[23]),
        "+f"(d[24]), "+f"(d[25]), "+f"(d[26]), "+f"(d[27]), "+f"(d[28]), "+f"(d[29]), "+f"(d[30]), "+f"(d[31]),
        "+f"(d[32]), "+f"(d[33]), "+f"(d[34]), "+f"(d[35]), "+f"(d[36]), "+f"(d[37]), "+f"(d[38]), "+f"(d[39]),
        "+f"(d[40]), "+f"(d[41]), "+f"(d[42]), "+f"(d[43]), "+f"(d[44]), "+f"(d[45]), "+f"(d[46]), "+f"(d[47]),
        "+f"(d[48]), "+f"(d[49]), "+f"(d[50]), "+f"(d[51]), "+f"(d[52]), "+f"(d[53]), "+f"(d[54]), "+f"(d[55]),
        "+f"(d[56]), "+f"(d[57]), "+f"(d[58]), "+f"(d[59]), "+f"(d[60]), "+f"(d[61]), "+f"(d[62]), "+f"(d[63]),
        "+f"(d[64]), "+f"(d[65]), "+f"(d[66]), "+f"(d[67]), "+f"(d[68]), "+f"(d[69]), "+f"(d[70]), "+f"(d[71]),
        "+f"(d[72]), "+f"(d[73]), "+f"(d[74]), "+f"(d[75]), "+f"(d[76]), "+f"(d[77]), "+f"(d[78]), "+f"(d[79]),
        "+f"(d[80]), "+f"(d[81]), "+f"(d[82]), "+f"(d[83]), "+f"(d[84]), "+f"(d[85]), "+f"(d[86]), "+f"(d[87]),
        "+f"(d[88]), "+f"(d[89]), "+f"(d[90]), "+f"(d[91]), "+f"(d[92]), "+f"(d[93]), "+f"(d[94]), "+f"(d[95]),
        "+f"(d[96]), "+f"(d[97]), "+f"(d[98]), "+f"(d[99]), "+f"(d[100]), "+f"(d[101]), "+f"(d[102]), "+f"(d[103]),
        "+f"(d[104]), "+f"(d[105]), "+f"(d[106]), "+f"(d[107]), "+f"(d[108]), "+f"(d[109]), "+f"(d[110]), "+f"(d[111]),
        "+f"(d[112]), "+f"(d[113]), "+f"(d[114]), "+f"(d[115]), "+f"(d[116]), "+f"(d[117]), "+f"(d[118]), "+f"(d[119]),
        "+f"(d[120]), "+f"(d[121]), "+f"(d[122]), "+f"(d[123]), "+f"(d[124]), "+f"(d[125]), "+f"(d[126]), "+f"(d[127])
      : "l"(descA), "l"(descB), "r"(acc));
}

__device__ __forceinline__ void mma_ss64(float (&d)[32], uint64_t descA, uint64_t descB) {
  asm volatile("wgmma.mma_async.sync.aligned.m64n64k16.f32.bf16.bf16 {"
      "%0, %1, %2, %3, %4, %5, %6, %7, %8, %9, %10, %11, %12, %13, %14, %15, "
      "%16, %17, %18, %19, %20, %21, %22, %23, %24, %25, %26, %27, %28, %29, %30, %31"
      "}, %32, %33, 1, 1, 1, 0, 1;\n"
      : "+f"(d[0]), "+f"(d[1]), "+f"(d[2]), "+f"(d[3]), "+f"(d[4]), "+f"(d[5]), "+f"(d[6]), "+f"(d[7]),
        "+f"(d[8]), "+f"(d[9]), "+f"(d[10]), "+f"(d[11]), "+f"(d[12]), "+f"(d[13]), "+f"(d[14]), "+f"(d[15]),
        "+f"(d[16]), "+f"(d[17]), "+f"(d[18]), "+f"(d[19]), "+f"(d[20]), "+f"(d[21]), "+f"(d[22]), "+f"(d[23]),
        "+f"(d[24]), "+f"(d[25]), "+f"(d[26]), "+f"(d[27]), "+f"(d[28]), "+f"(d[29]), "+f"(d[30]), "+f"(d[31])
      : "l"(descA), "l"(descB));
}
__device__ __forceinline__ void mma_ss64_p(float (&d)[32], uint64_t descA, uint64_t descB, int acc) {
  asm volatile("{\n.reg .pred p;\nsetp.ne.b32 p, %34, 0;\n"
      "wgmma.mma_async.sync.aligned.m64n64k16.f32.bf16.bf16 {"
      "%0, %1, %2, %3, %4, %5, %6, %7, %8, %9, %10, %11, %12, %13, %14, %15, "
      "%16, %17, %18, %19, %20, %21, %22, %23, %24, %25, %26, %27, %28, %29, %30, %31"
      "}, %32, %33, p, 1, 1, 0, 1;\n}\n"
      : "+f"(d[0]), "+f"(d[1]), "+f"(d[2]), "+f"(d[3]), "+f"(d[4]), "+f"(d[5]), "+f"(d[6]), "+f"(d[7]),
        "+f"(d[8]), "+f"(d[9]), "+f"(d[10]), "+f"(d[11]), "+f"(d[12]), "+f"(d[13]), "+f"(d[14]), "+f"(d[15]),
        "+f"(d[16]), "+f"(d[17]), "+f"(d[18]), "+f"(d[19]), "+f"(d[20]), "+f"(d[21]), "+f"(d[22]), "+f"(d[23]),
        "+f"(d[24]), "+f"(d[25]), "+f"(d[26]), "+f"(d[27]), "+f"(d[28]), "+f"(d[29]), "+f"(d[30]), "+f"(d[31])
      : "l"(descA), "l"(descB), "r"(acc));
}

__device__ __forceinline__ void mma_ss160(float (&d)[80], uint64_t descA, uint64_t descB) {
  asm volatile("wgmma.mma_async.sync.aligned.m64n160k16.f32.bf16.bf16 {"
      "%0, %1, %2, %3, %4, %5, %6, %7, %8, %9, %10, %11, %12, %13, %14, %15, "
      "%16, %17, %18, %19, %20, %21, %22, %23, %24, %25, %26, %27, %28, %29, %30, %31, "
      "%32, %33, %34, %35, %36, %37, %38, %39, %40, %41, %42, %43, %44, %45, %46, %47, "
      "%48, %49, %50, %51, %52, %53, %54, %55, %56, %57, %58, %59, %60, %61, %62, %63, "
      "%64, %65, %66, %67, %68, %69, %70, %71, %72, %73, %74, %75, %76, %77, %78, %79"
      "}, %80, %81, 1, 1, 1, 0, 1;\n"
      : "+f"(d[0]), "+f"(d[1]), "+f"(d[2]), "+f"(d[3]), "+f"(d[4]), "+f"(d[5]), "+f"(d[6]), "+f"(d[7]),
        "+f"(d[8]), "+f"(d[9]), "+f"(d[10]), "+f"(d[11]), "+f"(d[12]), "+f"(d[13]), "+f"(d[14]), "+f"(d[15]),
        "+f"(d[16]), "+f"(d[17]), "+f"(d[18]), "+f"(d[19]), "+f"(d[20]), "+f"(d[21]), "+f"(d[22]), "+f"(d[23]),
        "+f"(d[24]), "+f"(d[25]), "+f"(d[26]), "+f"(d[27]), "+f"(d[28]), "+f"(d[29]), "+f"(d[30]), "+f"(d[31]),
        "+f"(d[32]), "+f"(d[33]), "+f"(d[34]), "+f"(d[35]), "+f"(d[36]), "+f"(d[37]), "+f"(d[38]), "+f"(d[39]),
        "+f"(d[40]), "+f"(d[41]), "+f"(d[42]), "+f"(d[43]), "+f"(d[44]), "+f"(d[45]), "+f"(d[46]), "+f"(d[47]),
        "+f"(d[48]), "+f"(d[49]), "+f"(d[50]), "+f"(d[51]), "+f"(d[52]), "+f"(d[53]), "+f"(d[54]), "+f"(d[55]),
        "+f"(d[56]), "+f"(d[57]), "+f"(d[58]), "+f"(d[59]), "+f"(d[60]), "+f"(d[61]), "+f"(d[62]), "+f"(d[63]),
        "+f"(d[64]), "+f"(d[65]), "+f"(d[66]), "+f"(d[67]), "+f"(d[68]), "+f"(d[69]), "+f"(d[70]), "+f"(d[71]),
        "+f"(d[72]), "+f"(d[73]), "+f"(d[74]), "+f"(d[75]), "+f"(d[76]), "+f"(d[77]), "+f"(d[78]), "+f"(d[79])
      : "l"(descA), "l"(descB));
}
__device__ __forceinline__ void mma_ss160_z(float (&d)[80], uint64_t descA, uint64_t descB) {
  asm volatile("wgmma.mma_async.sync.aligned.m64n160k16.f32.bf16.bf16 {"
      "%0, %1, %2, %3, %4, %5, %6, %7, %8, %9, %10, %11, %12, %13, %14, %15, "
      "%16, %17, %18, %19, %20, %21, %22, %23, %24, %25, %26, %27, %28, %29, %30, %31, "
      "%32, %33, %34, %35, %36, %37, %38, %39, %40, %41, %42, %43, %44, %45, %46, %47, "
      "%48, %49, %50, %51, %52, %53, %54, %55, %56, %57, %58, %59, %60, %61, %62, %63, "
      "%64, %65, %66, %67, %68, %69, %70, %71, %72, %73, %74, %75, %76, %77, %78, %79"
      "}, %80, %81, 0, 1, 1, 0, 1;\n"
      : "=f"(d[0]), "=f"(d[1]), "=f"(d[2]), "=f"(d[3]), "=f"(d[4]), "=f"(d[5]), "=f"(d[6]), "=f"(d[7]),
        "=f"(d[8]), "=f"(d[9]), "=f"(d[10]), "=f"(d[11]), "=f"(d[12]), "=f"(d[13]), "=f"(d[14]), "=f"(d[15]),
        "=f"(d[16]), "=f"(d[17]), "=f"(d[18]), "=f"(d[19]), "=f"(d[20]), "=f"(d[21]), "=f"(d[22]), "=f"(d[23]),
        "=f"(d[24]), "=f"(d[25]), "=f"(d[26]), "=f"(d[27]), "=f"(d[28]), "=f"(d[29]), "=f"(d[30]), "=f"(d[31]),
        "=f"(d[32]), "=f"(d[33]), "=f"(d[34]), "=f"(d[35]), "=f"(d[36]), "=f"(d[37]), "=f"(d[38]), "=f"(d[39]),
        "=f"(d[40]), "=f"(d[41]), "=f"(d[42]), "=f"(d[43]), "=f"(d[44]), "=f"(d[45]), "=f"(d[46]), "=f"(d[47]),
        "=f"(d[48]), "=f"(d[49]), "=f"(d[50]), "=f"(d[51]), "=f"(d[52]), "=f"(d[53]), "=f"(d[54]), "=f"(d[55]),
        "=f"(d[56]), "=f"(d[57]), "=f"(d[58]), "=f"(d[59]), "=f"(d[60]), "=f"(d[61]), "=f"(d[62]), "=f"(d[63]),
        "=f"(d[64]), "=f"(d[65]), "=f"(d[66]), "=f"(d[67]), "=f"(d[68]), "=f"(d[69]), "=f"(d[70]), "=f"(d[71]),
        "=f"(d[72]), "=f"(d[73]), "=f"(d[74]), "=f"(d[75]), "=f"(d[76]), "=f"(d[77]), "=f"(d[78]), "=f"(d[79])
      : "l"(descA), "l"(descB));
}

__device__ __forceinline__ void mma_ss192(float (&d)[96], uint64_t descA, uint64_t descB) {
  asm volatile("wgmma.mma_async.sync.aligned.m64n192k16.f32.bf16.bf16 {"
      "%0, %1, %2, %3, %4, %5, %6, %7, %8, %9, %10, %11, %12, %13, %14, %15, "
      "%16, %17, %18, %19, %20, %21, %22, %23, %24, %25, %26, %27, %28, %29, %30, %31, "
      "%32, %33, %34, %35, %36, %37, %38, %39, %40, %41, %42, %43, %44, %45, %46, %47, "
      "%48, %49, %50, %51, %52, %53, %54, %55, %56, %57, %58, %59, %60, %61, %62, %63, "
      "%64, %65, %66, %67, %68, %69, %70, %71, %72, %73, %74, %75, %76, %77, %78, %79, "
      "%80, %81, %82, %83, %84, %85, %86, %87, %88, %89, %90, %91, %92, %93, %94, %95"
      "}, %96, %97, 1, 1, 1, 0, 1;\n"
      : "+f"(d[0]), "+f"(d[1]), "+f"(d[2]), "+f"(d[3]), "+f"(d[4]), "+f"(d[5]), "+f"(d[6]), "+f"(d[7]),
        "+f"(d[8]), "+f"(d[9]), "+f"(d[10]), "+f"(d[11]), "+f"(d[12]), "+f"(d[13]), "+f"(d[14]), "+f"(d[15]),
        "+f"(d[16]), "+f"(d[17]), "+f"(d[18]), "+f"(d[19]), "+f"(d[20]), "+f"(d[21]), "+f"(d[22]), "+f"(d[23]),
        "+f"(d[24]), "+f"(d[25]), "+f"(d[26]), "+f"(d[27]), "+f"(d[28]), "+f"(d[29]), "+f"(d[30]), "+f"(d[31]),
        "+f"(d[32]), "+f"(d[33]), "+f"(d[34]), "+f"(d[35]), "+f"(d[36]), "+f"(d[37]), "+f"(d[38]), "+f"(d[39]),
        "+f"(d[40]), "+f"(d[41]), "+f"(d[42]), "+f"(d[43]), "+f"(d[44]), "+f"(d[45]), "+f"(d[46]), "+f"(d[47]),
        "+f"(d[48]), "+f"(d[49]), "+f"(d[50]), "+f"(d[51]), "+f"(d[52]), "+f"(d[53]), "+f"(d[54]), "+f"(d[55]),
        "+f"(d[56]), "+f"(d[57]), "+f"(d[58]), "+f"(d[59]), "+f"(d[60]), "+f"(d[61]), "+f"(d[62]), "+f"(d[63]),
        "+f"(d[64]), "+f"(d[65]), "+f"(d[66]), "+f"(d[67]), "+f"(d[68]), "+f"(d[69]), "+f"(d[70]), "+f"(d[71]),
        "+f"(d[72]), "+f"(d[73]), "+f"(d[74]), "+f"(d[75]), "+f"(d[76]), "+f"(d[77]), "+f"(d[78]), "+f"(d[79]),
        "+f"(d[80]), "+f"(d[81]), "+f"(d[82]), "+f"(d[83]), "+f"(d[84]), "+f"(d[85]), "+f"(d[86]), "+f"(d[87]),
        "+f"(d[88]), "+f"(d[89]), "+f"(d[90]), "+f"(d[91]), "+f"(d[92]), "+f"(d[93]), "+f"(d[94]), "+f"(d[95])
      : "l"(descA), "l"(descB));
}
__device__ __forceinline__ void mma_ss192_p(float (&d)[96], uint64_t descA, uint64_t descB, int acc) {
  asm volatile("{\n.reg .pred p;\nsetp.ne.b32 p, %98, 0;\n"
      "wgmma.mma_async.sync.aligned.m64n192k16.f32.bf16.bf16 {"
      "%0, %1, %2, %3, %4, %5, %6, %7, %8, %9, %10, %11, %12, %13, %14, %15, "
      "%16, %17, %18, %19, %20, %21, %22, %23, %24, %25, %26, %27, %28, %29, %30, %31, "
      "%32, %33, %34, %35, %36, %37, %38, %39, %40, %41, %42, %43, %44, %45, %46, %47, "
      "%48, %49, %50, %51, %52, %53, %54, %55, %56, %57, %58, %59, %60, %61, %62, %63, "
      "%64, %65, %66, %67, %68, %69, %70, %71, %72, %73, %74, %75, %76, %77, %78, %79, "
      "%80, %81, %82, %83, %84, %85, %86, %87, %88, %89, %90, %91, %92, %93, %94, %95"
      "}, %96, %97, p, 1, 1, 0, 1;\n}\n"
      : "+f"(d[0]), "+f"(d[1]), "+f"(d[2]), "+f"(d[3]), "+f"(d[4]), "+f"(d[5]), "+f"(d[6]), "+f"(d[7]),
        "+f"(d[8]), "+f"(d[9]), "+f"(d[10]), "+f"(d[11]), "+f"(d[12]), "+f"(d[13]), "+f"(d[14]), "+f"(d[15]),
        "+f"(d[16]), "+f"(d[17]), "+f"(d[18]), "+f"(d[19]), "+f"(d[20]), "+f"(d[21]), "+f"(d[22]), "+f"(d[23]),
        "+f"(d[24]), "+f"(d[25]), "+f"(d[26]), "+f"(d[27]), "+f"(d[28]), "+f"(d[29]), "+f"(d[30]), "+f"(d[31]),
        "+f"(d[32]), "+f"(d[33]), "+f"(d[34]), "+f"(d[35]), "+f"(d[36]), "+f"(d[37]), "+f"(d[38]), "+f"(d[39]),
        "+f"(d[40]), "+f"(d[41]), "+f"(d[42]), "+f"(d[43]), "+f"(d[44]), "+f"(d[45]), "+f"(d[46]), "+f"(d[47]),
        "+f"(d[48]), "+f"(d[49]), "+f"(d[50]), "+f"(d[51]), "+f"(d[52]), "+f"(d[53]), "+f"(d[54]), "+f"(d[55]),
        "+f"(d[56]), "+f"(d[57]), "+f"(d[58]), "+f"(d[59]), "+f"(d[60]), "+f"(d[61]), "+f"(d[62]), "+f"(d[63]),
        "+f"(d[64]), "+f"(d[65]), "+f"(d[66]), "+f"(d[67]), "+f"(d[68]), "+f"(d[69]), "+f"(d[70]), "+f"(d[71]),
        "+f"(d[72]), "+f"(d[73]), "+f"(d[74]), "+f"(d[75]), "+f"(d[76]), "+f"(d[77]), "+f"(d[78]), "+f"(d[79]),
        "+f"(d[80]), "+f"(d[81]), "+f"(d[82]), "+f"(d[83]), "+f"(d[84]), "+f"(d[85]), "+f"(d[86]), "+f"(d[87]),
        "+f"(d[88]), "+f"(d[89]), "+f"(d[90]), "+f"(d[91]), "+f"(d[92]), "+f"(d[93]), "+f"(d[94]), "+f"(d[95])
      : "l"(descA), "l"(descB), "r"(acc));
}

__device__ __forceinline__ void mma_ss80_tt(float (&d)[40], uint64_t descA, uint64_t descB) {
  asm volatile("wgmma.mma_async.sync.aligned.m64n80k16.f32.bf16.bf16 {"
      "%0, %1, %2, %3, %4, %5, %6, %7, %8, %9, %10, %11, %12, %13, %14, %15, "
      "%16, %17, %18, %19, %20, %21, %22, %23, %24, %25, %26, %27, %28, %29, %30, %31, "
      "%32, %33, %34, %35, %36, %37, %38, %39"
      "}, %40, %41, 1, 1, 1, 1, 1;\n"
      : "+f"(d[0]), "+f"(d[1]), "+f"(d[2]), "+f"(d[3]), "+f"(d[4]), "+f"(d[5]), "+f"(d[6]), "+f"(d[7]),
        "+f"(d[8]), "+f"(d[9]), "+f"(d[10]), "+f"(d[11]), "+f"(d[12]), "+f"(d[13]), "+f"(d[14]), "+f"(d[15]),
        "+f"(d[16]), "+f"(d[17]), "+f"(d[18]), "+f"(d[19]), "+f"(d[20]), "+f"(d[21]), "+f"(d[22]), "+f"(d[23]),
        "+f"(d[24]), "+f"(d[25]), "+f"(d[26]), "+f"(d[27]), "+f"(d[28]), "+f"(d[29]), "+f"(d[30]), "+f"(d[31]),
        "+f"(d[32]), "+f"(d[33]), "+f"(d[34]), "+f"(d[35]), "+f"(d[36]), "+f"(d[37]), "+f"(d[38]), "+f"(d[39])
      : "l"(descA), "l"(descB));
}
__device__ __forceinline__ void mma_ss80_tt_z(float (&d)[40], uint64_t descA, uint64_t descB) {
  asm volatile("wgmma.mma_async.sync.aligned.m64n80k16.f32.bf16.bf16 {"
      "%0, %1, %2, %3, %4, %5, %6, %7, %8, %9, %10, %11, %12, %13, %14, %15, "
      "%16, %17, %18, %19, %20, %21, %22, %23, %24, %25, %26, %27, %28, %29, %30, %31, "
      "%32, %33, %34, %35, %36, %37, %38, %39"
      "}, %40, %41, 0, 1, 1, 1, 1;\n"
      : "=f"(d[0]), "=f"(d[1]), "=f"(d[2]), "=f"(d[3]), "=f"(d[4]), "=f"(d[5]), "=f"(d[6]), "=f"(d[7]),
        "=f"(d[8]), "=f"(d[9]), "=f"(d[10]), "=f"(d[11]), "=f"(d[12]), "=f"(d[13]), "=f"(d[14]), "=f"(d[15]),
        "=f"(d[16]), "=f"(d[17]), "=f"(d[18]), "=f"(d[19]), "=f"(d[20]), "=f"(d[21]), "=f"(d[22]), "=f"(d[23]),
        "=f"(d[24]), "=f"(d[25]), "=f"(d[26]), "=f"(d[27]), "=f"(d[28]), "=f"(d[29]), "=f"(d[30]), "=f"(d[31]),
        "=f"(d[32]), "=f"(d[33]), "=f"(d[34]), "=f"(d[35]), "=f"(d[36]), "=f"(d[37]), "=f"(d[38]), "=f"(d[39])
      : "l"(descA), "l"(descB));
}

__device__ __forceinline__ void mma_rs80_k(float (&d)[40], const uint32_t (&a)[4], uint64_t descB) {
  asm volatile("wgmma.mma_async.sync.aligned.m64n80k16.f32.bf16.bf16 {"
      "%0, %1, %2, %3, %4, %5, %6, %7, %8, %9, %10, %11, %12, %13, %14, %15, "
      "%16, %17, %18, %19, %20, %21, %22, %23, %24, %25, %26, %27, %28, %29, %30, %31, "
      "%32, %33, %34, %35, %36, %37, %38, %39"
      "}, {%40, %41, %42, %43}, %44, 1, 1, 1, 0;\n"
      : "+f"(d[0]), "+f"(d[1]), "+f"(d[2]), "+f"(d[3]), "+f"(d[4]), "+f"(d[5]), "+f"(d[6]), "+f"(d[7]),
        "+f"(d[8]), "+f"(d[9]), "+f"(d[10]), "+f"(d[11]), "+f"(d[12]), "+f"(d[13]), "+f"(d[14]), "+f"(d[15]),
        "+f"(d[16]), "+f"(d[17]), "+f"(d[18]), "+f"(d[19]), "+f"(d[20]), "+f"(d[21]), "+f"(d[22]), "+f"(d[23]),
        "+f"(d[24]), "+f"(d[25]), "+f"(d[26]), "+f"(d[27]), "+f"(d[28]), "+f"(d[29]), "+f"(d[30]), "+f"(d[31]),
        "+f"(d[32]), "+f"(d[33]), "+f"(d[34]), "+f"(d[35]), "+f"(d[36]), "+f"(d[37]), "+f"(d[38]), "+f"(d[39])
      : "r"(a[0]), "r"(a[1]), "r"(a[2]), "r"(a[3]), "l"(descB));
}
__device__ __forceinline__ void mma_rs80_k_z(float (&d)[40], const uint32_t (&a)[4], uint64_t descB) {
  asm volatile("wgmma.mma_async.sync.aligned.m64n80k16.f32.bf16.bf16 {"
      "%0, %1, %2, %3, %4, %5, %6, %7, %8, %9, %10, %11, %12, %13, %14, %15, "
      "%16, %17, %18, %19, %20, %21, %22, %23, %24, %25, %26, %27, %28, %29, %30, %31, "
      "%32, %33, %34, %35, %36, %37, %38, %39"
      "}, {%40, %41, %42, %43}, %44, 0, 1, 1, 0;\n"
      : "=f"(d[0]), "=f"(d[1]), "=f"(d[2]), "=f"(d[3]), "=f"(d[4]), "=f"(d[5]), "=f"(d[6]), "=f"(d[7]),
        "=f"(d[8]), "=f"(d[9]), "=f"(d[10]), "=f"(d[11]), "=f"(d[12]), "=f"(d[13]), "=f"(d[14]), "=f"(d[15]),
        "=f"(d[16]), "=f"(d[17]), "=f"(d[18]), "=f"(d[19]), "=f"(d[20]), "=f"(d[21]), "=f"(d[22]), "=f"(d[23]),
        "=f"(d[24]), "=f"(d[25]), "=f"(d[26]), "=f"(d[27]), "=f"(d[28]), "=f"(d[29]), "=f"(d[30]), "=f"(d[31]),
        "=f"(d[32]), "=f"(d[33]), "=f"(d[34]), "=f"(d[35]), "=f"(d[36]), "=f"(d[37]), "=f"(d[38]), "=f"(d[39])
      : "r"(a[0]), "r"(a[1]), "r"(a[2]), "r"(a[3]), "l"(descB));
}

__device__ __forceinline__ void mma_rs48_k(float (&d)[24], const uint32_t (&a)[4], uint64_t descB) {
  asm volatile("wgmma.mma_async.sync.aligned.m64n48k16.f32.bf16.bf16 {"
      "%0, %1, %2, %3, %4, %5, %6, %7, %8, %9, %10, %11, %12, %13, %14, %15, "
      "%16, %17, %18, %19, %20, %21, %22, %23"
      "}, {%24, %25, %26, %27}, %28, 1, 1, 1, 0;\n"
      : "+f"(d[0]), "+f"(d[1]), "+f"(d[2]), "+f"(d[3]), "+f"(d[4]), "+f"(d[5]), "+f"(d[6]), "+f"(d[7]),
        "+f"(d[8]), "+f"(d[9]), "+f"(d[10]), "+f"(d[11]), "+f"(d[12]), "+f"(d[13]), "+f"(d[14]), "+f"(d[15]),
        "+f"(d[16]), "+f"(d[17]), "+f"(d[18]), "+f"(d[19]), "+f"(d[20]), "+f"(d[21]), "+f"(d[22]), "+f"(d[23])
      : "r"(a[0]), "r"(a[1]), "r"(a[2]), "r"(a[3]), "l"(descB));
}
__device__ __forceinline__ void mma_rs48_k_z(float (&d)[24], const uint32_t (&a)[4], uint64_t descB) {
  asm volatile("wgmma.mma_async.sync.aligned.m64n48k16.f32.bf16.bf16 {"
      "%0, %1, %2, %3, %4, %5, %6, %7, %8, %9, %10, %11, %12, %13, %14, %15, "
      "%16, %17, %18, %19, %20, %21, %22, %23"
      "}, {%24, %25, %26, %27}, %28, 0, 1, 1, 0;\n"
      : "=f"(d[0]), "=f"(d[1]), "=f"(d[2]), "=f"(d[3]), "=f"(d[4]), "=f"(d[5]), "=f"(d[6]), "=f"(d[7]),
        "=f"(d[8]), "=f"(d[9]), "=f"(d[10]), "=f"(d[11]), "=f"(d[12]), "=f"(d[13]), "=f"(d[14]), "=f"(d[15]),
        "=f"(d[16]), "=f"(d[17]), "=f"(d[18]), "=f"(d[19]), "=f"(d[20]), "=f"(d[21]), "=f"(d[22]), "=f"(d[23])
      : "r"(a[0]), "r"(a[1]), "r"(a[2]), "r"(a[3]), "l"(descB));
}

__device__ __forceinline__ void mma_rs160_n(float (&d)[80], const uint32_t (&a)[4], uint64_t descB) {
  asm volatile("wgmma.mma_async.sync.aligned.m64n160k16.f32.bf16.bf16 {"
      "%0, %1, %2, %3, %4, %5, %6, %7, %8, %9, %10, %11, %12, %13, %14, %15, "
      "%16, %17, %18, %19, %20, %21, %22, %23, %24, %25, %26, %27, %28, %29, %30, %31, "
      "%32, %33, %34, %35, %36, %37, %38, %39, %40, %41, %42, %43, %44, %45, %46, %47, "
      "%48, %49, %50, %51, %52, %53, %54, %55, %56, %57, %58, %59, %60, %61, %62, %63, "
      "%64, %65, %66, %67, %68, %69, %70, %71, %72, %73, %74, %75, %76, %77, %78, %79"
      "}, {%80, %81, %82, %83}, %84, 1, 1, 1, 1;\n"
      : "+f"(d[0]), "+f"(d[1]), "+f"(d[2]), "+f"(d[3]), "+f"(d[4]), "+f"(d[5]), "+f"(d[6]), "+f"(d[7]),
        "+f"(d[8]), "+f"(d[9]), "+f"(d[10]), "+f"(d[11]), "+f"(d[12]), "+f"(d[13]), "+f"(d[14]), "+f"(d[15]),
        "+f"(d[16]), "+f"(d[17]), "+f"(d[18]), "+f"(d[19]), "+f"(d[20]), "+f"(d[21]), "+f"(d[22]), "+f"(d[23]),
        "+f"(d[24]), "+f"(d[25]), "+f"(d[26]), "+f"(d[27]), "+f"(d[28]), "+f"(d[29]), "+f"(d[30]), "+f"(d[31]),
        "+f"(d[32]), "+f"(d[33]), "+f"(d[34]), "+f"(d[35]), "+f"(d[36]), "+f"(d[37]), "+f"(d[38]), "+f"(d[39]),
        "+f"(d[40]), "+f"(d[41]), "+f"(d[42]), "+f"(d[43]), "+f"(d[44]), "+f"(d[45]), "+f"(d[46]), "+f"(d[47]),
        "+f"(d[48]), "+f"(d[49]), "+f"(d[50]), "+f"(d[51]), "+f"(d[52]), "+f"(d[53]), "+f"(d[54]), "+f"(d[55]),
        "+f"(d[56]), "+f"(d[57]), "+f"(d[58]), "+f"(d[59]), "+f"(d[60]), "+f"(d[61]), "+f"(d[62]), "+f"(d[63]),
        "+f"(d[64]), "+f"(d[65]), "+f"(d[66]), "+f"(d[67]), "+f"(d[68]), "+f"(d[69]), "+f"(d[70]), "+f"(d[71]),
        "+f"(d[72]), "+f"(d[73]), "+f"(d[74]), "+f"(d[75]), "+f"(d[76]), "+f"(d[77]), "+f"(d[78]), "+f"(d[79])
      : "r"(a[0]), "r"(a[1]), "r"(a[2]), "r"(a[3]), "l"(descB));
}
__device__ __forceinline__ void mma_rs160_n_z(float (&d)[80], const uint32_t (&a)[4], uint64_t descB) {
  asm volatile("wgmma.mma_async.sync.aligned.m64n160k16.f32.bf16.bf16 {"
      "%0, %1, %2, %3, %4, %5, %6, %7, %8, %9, %10, %11, %12, %13, %14, %15, "
      "%16, %17, %18, %19, %20, %21, %22, %23, %24, %25, %26, %27, %28, %29, %30, %31, "
      "%32, %33, %34, %35, %36, %37, %38, %39, %40, %41, %42, %43, %44, %45, %46, %47, "
      "%48, %49, %50, %51, %52, %53, %54, %55, %56, %57, %58, %59, %60, %61, %62, %63, "
      "%64, %65, %66, %67, %68, %69, %70, %71, %72, %73, %74, %75, %76, %77, %78, %79"
      "}, {%80, %81, %82, %83}, %84, 0, 1, 1, 1;\n"
      : "=f"(d[0]), "=f"(d[1]), "=f"(d[2]), "=f"(d[3]), "=f"(d[4]), "=f"(d[5]), "=f"(d[6]), "=f"(d[7]),
        "=f"(d[8]), "=f"(d[9]), "=f"(d[10]), "=f"(d[11]), "=f"(d[12]), "=f"(d[13]), "=f"(d[14]), "=f"(d[15]),
        "=f"(d[16]), "=f"(d[17]), "=f"(d[18]), "=f"(d[19]), "=f"(d[20]), "=f"(d[21]), "=f"(d[22]), "=f"(d[23]),
        "=f"(d[24]), "=f"(d[25]), "=f"(d[26]), "=f"(d[27]), "=f"(d[28]), "=f"(d[29]), "=f"(d[30]), "=f"(d[31]),
        "=f"(d[32]), "=f"(d[33]), "=f"(d[34]), "=f"(d[35]), "=f"(d[36]), "=f"(d[37]), "=f"(d[38]), "=f"(d[39]),
        "=f"(d[40]), "=f"(d[41]), "=f"(d[42]), "=f"(d[43]), "=f"(d[44]), "=f"(d[45]), "=f"(d[46]), "=f"(d[47]),
        "=f"(d[48]), "=f"(d[49]), "=f"(d[50]), "=f"(d[51]), "=f"(d[52]), "=f"(d[53]), "=f"(d[54]), "=f"(d[55]),
        "=f"(d[56]), "=f"(d[57]), "=f"(d[58]), "=f"(d[59]), "=f"(d[60]), "=f"(d[61]), "=f"(d[62]), "=f"(d[63]),
        "=f"(d[64]), "=f"(d[65]), "=f"(d[66]), "=f"(d[67]), "=f"(d[68]), "=f"(d[69]), "=f"(d[70]), "=f"(d[71]),
        "=f"(d[72]), "=f"(d[73]), "=f"(d[74]), "=f"(d[75]), "=f"(d[76]), "=f"(d[77]), "=f"(d[78]), "=f"(d[79])
      : "r"(a[0]), "r"(a[1]), "r"(a[2]), "r"(a[3]), "l"(descB));
}

__device__ __forceinline__ void feature_map(const uint32_t (&P)[2][10], uint32_t (&fr)[10][4]) {
  constexpr float L2E = 1.4426950408889634f;
#pragma unroll
  for (int p = 0; p < 2; p++) {
#pragma unroll
    for (int r = 0; r < 2; r++) {
      uint32_t mx = P[r][5 * p], mn = mx;
#pragma unroll
      for (int g = 1; g < 5; g++) { mx = max_bf2(mx, P[r][5 * p + g]); mn = min_bf2(mn, P[r][5 * p + g]); }
      mx = max_bf2(mx, __shfl_xor_sync(0xffffffffu, mx, 1));
      mn = min_bf2(mn, __shfl_xor_sync(0xffffffffu, mn, 1));
      mx = max_bf2(mx, __shfl_xor_sync(0xffffffffu, mx, 2));
      mn = min_bf2(mn, __shfl_xor_sync(0xffffffffu, mn, 2));
      float mx0 = -bf_lo(mx) * L2E, mx1 = -bf_hi(mx) * L2E, mn0 = bf_lo(mn) * L2E, mn1 = bf_hi(mn) * L2E;
      float ep0[5], ep1[5], en0[5], en1[5];
      float sp0 = 0.f, sp1 = 0.f, sn0 = 0.f, sn1 = 0.f;
#pragma unroll
      for (int g = 0; g < 5; g++) {
        float x0 = bf_lo(P[r][5 * p + g]), x1 = bf_hi(P[r][5 * p + g]);
        ep0[g] = ex2(fmaf(x0, L2E, mx0)); ep1[g] = ex2(fmaf(x1, L2E, mx1));
        en0[g] = ex2(fmaf(x0, -L2E, mn0)); en1[g] = ex2(fmaf(x1, -L2E, mn1));
        sp0 += ep0[g]; sp1 += ep1[g]; sn0 += en0[g]; sn1 += en1[g];
      }
      sp0 += __shfl_xor_sync(0xffffffffu, sp0, 1); sp1 += __shfl_xor_sync(0xffffffffu, sp1, 1);
      sn0 += __shfl_xor_sync(0xffffffffu, sn0, 1); sn1 += __shfl_xor_sync(0xffffffffu, sn1, 1);
      sp0 += __shfl_xor_sync(0xffffffffu, sp0, 2); sp1 += __shfl_xor_sync(0xffffffffu, sp1, 2);
      sn0 += __shfl_xor_sync(0xffffffffu, sn0, 2); sn1 += __shfl_xor_sync(0xffffffffu, sn1, 2);
      sp0 = rcp(sp0); sp1 = rcp(sp1); sn0 = rcp(sn0); sn1 = rcp(sn1);
#pragma unroll
      for (int g = 0; g < 5; g++) {
        fr[5 * p + g][r] = pack_bf16(ep0[g] * sp0, ep1[g] * sp1);
        fr[5 * p + g][2 + r] = pack_bf16(en0[g] * sn0, en1[g] * sn1);
      }
    }
  }
}

template <int V> struct IntC { static constexpr int value = V; };
struct Ring {
  uint32_t idx, phase;
  template <int N> __device__ __forceinline__ void next() { if (++idx == N) { idx = 0; phase ^= 1; } }
};

}

__global__ void __cluster_dims__(2, 1, 1) __launch_bounds__(384, 1)
fused_kernel(const __grid_constant__ Maps maps, const __nv_bfloat16* __restrict__ x, const __nv_bfloat16* __restrict__ wqkv,
             const __nv_bfloat16* __restrict__ wphi, const __nv_bfloat16* __restrict__ w1, const __nv_bfloat16* __restrict__ w2,
             const __nv_bfloat16* __restrict__ w3, const __nv_bfloat16* __restrict__ w4, const __nv_bfloat16* __restrict__ wo,
             const __nv_bfloat16* __restrict__ gate_w, __nv_bfloat16* __restrict__ out) {
  extern __shared__ __align__(1024) uint8_t sgen[];
  const uint32_t sb = smem_u32(sgen);
  const uint32_t sb16 = (sb & 0x3FFFFu) >> 4;
  const uint32_t bars = sb + OFF_BAR;
  const uint32_t fullA = bars + 8 * B_FULLA, emptyA = bars + 8 * B_EMPTYA, fullB = bars + 8 * B_FULLB, emptyB = bars + 8 * B_EMPTYB;

  const int tid = threadIdx.x;
  const int rank = blockIdx.x & 1;
  const int bid = blockIdx.x - NSVC, pairIdx = bid >> 1;
  const int i = pairIdx >> 2, j = 2 * (pairIdx & 3) + rank;
  const int k3 = (5 * (pairIdx & 3) + 1) >> 1;

  if (bid < 0) {
    const int sv = blockIdx.x;
    const unsigned epoch = *reinterpret_cast<volatile unsigned*>(g_flags + FL_DONE * 32) / NCTA;
    if (tid == 0) {
#pragma unroll
      for (int b = 0; b < 11; b++) mbar_init(bars + 8 * b, 1);
      mbar_expect_tx(bars + 80, 6400);
      bulk_load(sb + 204800, wphi + sv * 3200, 6400, bars + 80);
    }
    __syncthreads();
    float a[8];
#pragma unroll 1
    for (int rd = 0; rd < 4; rd++) {
      const int nch = rd ? 192 : 80, nth = rd ? 384 : 320, piece = rd ? 18432 : 20480, np = rd == 3 ? 7 : 10;
      if (tid == 0) {
        const char* src = reinterpret_cast<const char*>(rd ? w3 + (size_t)(160 * sv + 60 * (rd - 1)) * F_ : w1 + (size_t)160 * sv * D_);
#pragma unroll 1
        for (int p = 0; p < np; p++) {
          const int bytes = (rd == 3 && p == 6) ? 12288 : piece;
          mbar_expect_tx(bars + 8 * p, bytes);
          bulk_load(sb + p * piece, src + p * piece, bytes, bars + 8 * p);
        }
      }
      if (rd == 0) {
        if (tid < 40 && (tid < 20 || sv >= 2))
          reinterpret_cast<uint4*>(g_Hs + (size_t)(2 + ((sv & 1) ? S_ - 1 - tid / 20 : tid / 20)) * D_ + 160 * sv)[tid % 20] = make_uint4(0, 0, 0, 0);
        mbar_wait(bars + 80, 0);
#pragma unroll 1
        for (int e = tid; e < 1600; e += 384) {
          const int jj = e / 800, it = e - 800 * jj, st = it / 160, n = (it - 160 * st) >> 1, k0 = 16 * st + 8 * ((it ^ (n >> 2)) & 1);
          const int nn = n % 40, h = 2 * (n / 40) + (nn & 1), ff = 4 * (nn >> 3) + ((nn >> 1) & 3);
          uint32_t w[8];
#pragma unroll
          for (int q = 0; q < 8; q++) {
            const int k = k0 + q;
            w[q] = (unsigned)(k - 20 * h) < 20u ? reinterpret_cast<const unsigned short*>(sgen + 204800)[jj * 1600 + k * 20 + ff] : 0u;
          }
          g_wphi[sv * 1600 + e] = make_uint4(w[0] | (w[1] << 16), w[2] | (w[3] << 16), w[4] | (w[5] << 16), w[6] | (w[7] << 16));
        }
      }
      if (rd < 2) {
#pragma unroll
        for (int e = 0; e < 8; e++) a[e] = 0.f;
      }
#pragma unroll 1
      for (int p = 0; p < np; p++) {
        mbar_wait(bars + 8 * p, rd & 1);
        const int bytes = (rd == 3 && p == 6) ? 12288 : piece;
        if (tid < nth) {
#pragma unroll 1
          for (int o = tid * 16; o < bytes; o += nth * 16) {
            const uint4 v = lds128(sb + p * piece + o);
            a[0] += bf_lo(v.x); a[1] += bf_hi(v.x); a[2] += bf_lo(v.y); a[3] += bf_hi(v.y);
            a[4] += bf_lo(v.z); a[5] += bf_hi(v.z); a[6] += bf_lo(v.w); a[7] += bf_hi(v.w);
          }
        }
      }
      if (tid < nth && (rd == 0 || rd == 3)) {
        float* cd = g_cs[epoch & 1] + (rd ? D_ : 0) + 8 * (tid % nch);
        red_add4(cd, a[0], a[1], a[2], a[3]); red_add4(cd + 4, a[4], a[5], a[6], a[7]);
      }
      __syncthreads();
      if (tid == 0 && (rd == 0 || rd == 3)) {
        flag_add(rd ? FL_CS3 : FL_CS);
        if (rd == 0) l2_prefetch(w2 + (size_t)sv * (D_ * D_ / NSVC), D_ * D_ * 2 / NSVC);
      }
    }
#pragma unroll 1
    for (int e = tid; e < (D_ + F_) / NSVC; e += 384) g_cs[(epoch + 1) & 1][sv * ((D_ + F_) / NSVC) + e] = 0.f;
#pragma unroll 1
    for (int e = tid; e < 2 * KV_J; e += 384) g_acc[(epoch + 1) & 1][sv * 2 * KV_J + e] = 0.f;
    if (tid < 32) {
      l2_prefetch(w4 + (size_t)(sv * 32 + tid) * (F_ * D_ / 128), F_ * D_ * 2 / 128);
      l2_prefetch(wo + (size_t)(sv * 32 + tid) * (D_ * D_ / 128), D_ * D_ * 2 / 128);
    }
    return;
  }
  TSTAMP(0);
  if (tid >= 256) {
    asm volatile("setmaxnreg.dec.sync.aligned.u32 40;");
    if (tid == 256) {
#pragma unroll
      for (int s = 0; s < NA; s++) mbar_init(fullA + 8 * s, 1);
      asm volatile("fence.mbarrier_init.release.cluster;" ::: "memory");
#pragma unroll 1
      for (int u = 0; u < 4; u++) {
        if ((u & 1) == 0) mbar_expect_tx(fullA + 4 * u, SLOT_A);
        tma2d(sb + OFF_A + u * 8192, &maps.x, fullA + 8 * (u >> 1), 64 * (u >> 1), 128 * i + 64 * (u & 1));
      }
    } else if (tid == 288) {
#pragma unroll
      for (int s = 0; s < NB; s++) { mbar_init(fullB + 8 * s, 1); mbar_init(emptyB + 8 * s, 8); }
      asm volatile("fence.mbarrier_init.release.cluster;" ::: "memory");
    } else if (tid == 320) {
#pragma unroll
      for (int b = B_CS; b < NBAR; b++) if (b < B_EMPTYB || b >= B_EMPTYB + NB) mbar_init(bars + 8 * b, b < B_EMPTYB ? 1 : b < B_EMPTYA ? 8 : b < B_X1P ? 16 : 2);
#pragma unroll
      for (int b = B_DSR; b < B_EMPTYB; b++) mbar_expect_tx(bars + 8 * b, 10240);
      asm volatile("fence.mbarrier_init.release.cluster;" ::: "memory");
    }
    __syncwarp();
    asm volatile("barrier.cluster.arrive.relaxed.aligned;" ::: "memory");
    auto get_epoch = [&]() { return *reinterpret_cast<volatile unsigned*>(g_flags + FL_DONE * 32) / NCTA; };
    if ((tid >> 5) != 9) asm volatile("barrier.cluster.wait.aligned;" ::: "memory");
    const int lane = tid & 31, pw = (tid >> 5) & 3;
    if (pw == 0) {
      if (tid == 256) {
        Ring r{2, 1};
#pragma unroll 1
        for (int k = 2; k < 24; k++) {
          if (k == 10 || k == 16) {
            mbar_wait(bars + 8 * B_HST, k == 16);
            TSTAMPX(k == 10 ? 29 : 30);
          }
          if (k == 14) {
            mbar_wait(bars + 8 * B_WDEAD, 0);
            mbar_expect_tx(bars + 8 * B_T4, SLOT_A);
            tma2d(sb + OFF_MISC, &maps.hs, bars + 8 * B_T4, 256 + 320 * rank, 128 * i);
            mbar_wait(emptyA + 16, r.phase); mbar_wait(emptyA + 24, r.phase);
            mbar_expect_tx(bars + 8 * B_XR, 20480);
            tma2d(sb + OFF_STG, &maps.xr, bars + 8 * B_XR, 80 * j, 128 * i);
            mbar_wait(bars + 8 * B_X1P, 0);
          }
          mbar_wait(emptyA + 8 * r.idx, r.phase);
          const uint32_t bar = fullA + 8 * r.idx, slot = sb + OFF_A + r.idx * SLOT_A;
          mbar_expect_tx(bar, SLOT_A);
          if (k >= 10 && k < 14) tma2d(slot, &maps.hs, bar, 64 * (k - 10) + 320 * rank, 128 * i);
          else tma2d_mc(slot + rank * 8192, k < 10 ? &maps.x : &maps.x1, bar, 64 * (k < 10 ? k : (k - 14 + k3) % 10), 128 * i + 64 * rank);
          r.next<NA>();
        }
      }
    } else if (pw == 1) {
      if (tid == 288) {
        Ring r{0, 1};
#pragma unroll 1
        for (int k = 0; k < 18; k++) {
          mbar_wait(emptyB + 8 * r.idx, r.phase);
          const uint32_t bar = fullB + 8 * r.idx, slot = sb + OFF_B + r.idx * SLOT_B;
          if (k < 10) {
            mbar_expect_tx(bar, 40960);
            tma4d(slot + 8192, &maps.qm, bar, 0, 64 * k, 0, j);
            tma3d(slot, &maps.w1m, bar, 0, 64 * k, j);
            tma4d(slot + 32768 + 2048, &maps.qr, bar, 64, 64 * k, 0, j);
            tma3d(slot + 32768, &maps.w1r, bar, 64, 64 * k, j);
          } else if (k < 13) {
            mbar_expect_tx(bar, k < 12 ? 40960 : 20480);
            tma3d(slot, &maps.w2, bar, 0, 320 * rank + 128 * (k - 10), 5 * (j >> 1));
            if (k < 12) tma3d(slot + 20480, &maps.w2, bar, 0, 320 * rank + 128 * (k - 10) + 64, 5 * (j >> 1));
          } else {
            if (k == 13) mbar_wait(bars + 8 * B_KVR, 0);
            mbar_expect_tx(bar, 49152);
            tma3d(slot, &maps.w3, bar, 0, 64 * ((2 * (k - 13) + k3) % 10), 3 * j);
            tma3d(slot + 24576, &maps.w3, bar, 0, 64 * ((2 * (k - 13) + 1 + k3) % 10), 3 * j);
          }
          r.next<NB>();
        }
#pragma unroll 1
        for (int n = 0; n < 8; n++) {
          if (n < 3) { mbar_wait(emptyB + 8 * r.idx, r.phase); r.next<NB>(); }
          if (n == 0) mbar_wait(fullA + 24, 1);
          if (n >= 4) mbar_wait(bars + 8 * (B_EMPTY4 + n - 4), 0);
          const uint32_t bar = bars + 8 * (B_FULL4 + n), set = sb + ((n >> 1) & 1) * SET4;
          const int h = n & 1, m = ((j >> 1) + 1 + (n >> 1)) & 3;
          mbar_expect_tx(bar, h ? 40960 : 46080);
          tma3d(set + (h ? 46080 : 0), h ? &maps.w4 : &maps.wo, bar, 0, h ? 192 * j + 64 : 80 * j, 5 * m);
          tma3d(set + (h ? 66560 : 25600), &maps.w4, bar, 0, 192 * j + 128 * h, 5 * m);
        }
        mbar_wait(bars + 8 * (B_EMPTY4 + 4), 0);
        mbar_expect_tx(bars + 8 * B_XR, 20480);
        tma2d(sb + OFF_OUT, &maps.st_x1, bars + 8 * B_XR, 80 * j, 128 * i);
      }
    } else {
      const unsigned epoch = get_epoch();
      float* accg = g_acc[epoch & 1];
      if (pw == 2) {
        if (tid == 320) {
          flag_wait(FL_CS, (epoch + 1) * NSVC);
          flag_wait(FL_ST + i, (epoch + 1) * 8u);
          fence_async_glb();
          *reinterpret_cast<volatile uint32_t*>(sgen + OFF_BAR + 8 * NBAR) = (epoch + 1) & 1;
          mbar_expect_tx(bars + 8 * B_CS, 320 + 2048 + 12800);
          bulk_load(sb + OFF_CS, g_cs[epoch & 1] + 80 * j, 320, bars + 8 * B_CS);
          bulk_load(sb + OFF_XST, g_xstat + 128 * i, 2048, bars + 8 * B_CS);
          bulk_load(sb + OFF_MISC, g_wphi + j * 800, 12800, bars + 8 * B_CS);
          TSTAMPX(21);
          mbar_wait(bars + 8 * B_SIGKV, 0);
          TSTAMPX(25);
#pragma unroll 1
          for (int u = 0; u < 4; u++)
            asm volatile("cp.reduce.async.bulk.global.shared::cta.bulk_group.add.f32 [%0], [%1], %2;"
                         ::"l"(accg + j * KV_J + (u >> 1) * KV_PAIR + (u & 1) * 1024), "r"(sb + OFF_B + SPARE + (u & 1) * SLOT_B + (u >> 1) * 4096),
                         "r"((u & 1) ? KV_PAIR * 4 - 4096 : 4096) : "memory");
          bulk_commit(); bulk_wait<0>();
          mbar_arrive(bars + 8 * B_KVR);
          flag_add(FL_KV + j);
          TSTAMPX(26);
          flag_wait(FL_KV + j, (epoch + 1) * 16u);
          mbar_wait(bars + 8 * B_SIGX1, 0);
          mbar_expect_tx(bars + 8 * B_KV, KV_J * 4);
          bulk_load(sb + OFF_A + SLOT_A, accg + j * KV_J, KV_J * 4, bars + 8 * B_KV);
          TSTAMPX(22);
          flag_wait(FL_CS3, (epoch + 1) * NSVC);
          flag_wait(FL_S1 + i, (epoch + 1) * 8u);
          fence_async_glb();
          mbar_expect_tx(bars + 8 * B_ST1, 8192 + 768);
          bulk_load(sb + OFF_CS + 320, g_cs[epoch & 1] + D_ + 192 * j, 768, bars + 8 * B_ST1);
          bulk_load(sb + OFF_MISC, g_st1 + 128 * i * 8, 8192, bars + 8 * B_ST1);
        }
        __syncwarp();
#pragma unroll 1
        for (int c = 0; c < 3; c++) {
          mbar_wait(bars + 8 * (B_EMPTY4 + (c ? 5 : 4)), 0);
          const uint4* src = g_part + (size_t)((i * 8 + j) * 3 + c) * 1280;
          const unsigned* tp = reinterpret_cast<const unsigned*>(src + 1024 + (lane & 7) * 32 + 31);
          uint32_t n = 0;
          while (!__all_sync(0xffffffffu, (ld_acquire(tp) ^ epoch) & 1u) && ++n < (WAIT_LIMIT >> 2)) {}
          if (tid == 320) {
            mbar_expect_tx(bars + 8 * (B_RDY + c), 20480);
            bulk_load(sb + (c ? 25600 + 20480 * c : 0), src, 20480, bars + 8 * (B_RDY + c));
          }
        }
      }
      if (tid == 352) {
        mbar_wait(bars + 8 * B_SIGP, 0);
        flag_add(FL_ST + i);
        TSTAMPX(20);
        const int shift = (j < 2) ? 1 : (j < 4) ? -1 : (j < 6) ? 2 : -2;
        prefetch_tmap(&maps.st_h); prefetch_tmap(&maps.st_x1); prefetch_tmap(&maps.hs); prefetch_tmap(&maps.x1); prefetch_tmap(&maps.xr);
        prefetch_tmap(&maps.w2); prefetch_tmap(&maps.w3); prefetch_tmap(&maps.w4); prefetch_tmap(&maps.wo);
        mbar_wait(bars + 8 * B_SIGH, 0);
        TSTAMPX(23);
        tma2d_store(&maps.st_h, sb + OFF_STG, 80 * j, 128 * i + 2 + shift);
        bulk_commit(); bulk_wait<0>();
        flag_add(FL_H + 2 * i + (j >> 2));
        flag_add_relaxed(FL_H + 2 * ((i + (shift > 0 ? 1 : -1)) & 15) + (j >> 2));
        TSTAMPX(24);
        flag_wait(FL_H + 2 * i + rank, (epoch + 1) * 8u);
        mbar_arrive(bars + 8 * B_HST);
        mbar_wait(bars + 8 * B_SIGX1, 0);
        TSTAMPX(27);
        tma2d_store(&maps.st_x1, sb + OFF_STG, 80 * j, 128 * i);
        bulk_commit(); bulk_wait<0>();
        flag_add(FL_X1 + i);
        mbar_arrive_cta(bars + 8 * B_X1P, 0); mbar_arrive_cta(bars + 8 * B_X1P, 1);
        TSTAMPX(28);
        flag_wait(FL_X1 + i, (epoch + 1) * 8u);
        mbar_arrive(bars + 8 * B_HST);
        mbar_wait(bars + 8 * B_MFREE, 0);
        flag_add(FL_S1 + i);
      }
    }
  } else {
    uint4 pv[5], pw_[5];
    {
      const int row = 128 * i + 16 * j + (tid >> 4), l16 = tid & 15;
#pragma unroll
      for (int c = 0; c < 5; c++) pv[c] = __ldg(reinterpret_cast<const uint4*>(x + (size_t)row * D_ + c * 128 + l16 * 8));
#pragma unroll
      for (int c = 0; c < 5; c++) pw_[c] = __ldg(reinterpret_cast<const uint4*>(gate_w + c * 128 + l16 * 8));
    }
    asm volatile("barrier.cluster.arrive.relaxed.aligned;" ::: "memory");
    asm volatile("setmaxnreg.inc.sync.aligned.u32 232;");
    const int wg = tid >> 7, warp = tid >> 5, lane = tid & 31, t = lane & 3;
    const int rloc = warp * 16 + (lane >> 2);
    const float* s_cs = reinterpret_cast<const float*>(sgen + OFF_CS);
    auto signal = [&](int b) {
      __syncwarp();
      if (lane == 0) mbar_arrive(bars + 8 * b);
    };
    auto releaseB = [&](uint32_t bar) {
      __syncwarp();
      if (lane == 0) mbar_arrive(bar);
    };
    auto release = [&](uint32_t bar) {
      __syncwarp();
      if (lane < 2) mbar_arrive_cta(bar, lane);
    };
    const uint32_t stg_lane = (warp * 16 + ((lane >> 3) & 1) * 8 + (lane & 7)) * 160 + (lane >> 4) * 16;

    auto stage_tile = [&](uint32_t stg, const uint32_t (&v)[2][10]) {
#pragma unroll
      for (int s = 0; s < 5; s++) stsm4(stg + stg_lane + s * 32, v[0][2 * s], v[1][2 * s], v[0][2 * s + 1], v[1][2 * s + 1]);
    };

    {
      float f[40];
      float s = 0.f, gs = 0.f;
#pragma unroll
      for (int c = 0; c < 5; c++) {
        const uint32_t vv[4] = {pv[c].x, pv[c].y, pv[c].z, pv[c].w}, ww[4] = {pw_[c].x, pw_[c].y, pw_[c].z, pw_[c].w};
#pragma unroll
        for (int e = 0; e < 4; e++) {
          f[8 * c + 2 * e] = bf_lo(vv[e]); f[8 * c + 2 * e + 1] = bf_hi(vv[e]);
          s += f[8 * c + 2 * e] + f[8 * c + 2 * e + 1];
          const uint32_t pr = mul_bf2(vv[e], ww[e]);
          gs += bf_lo(pr) + bf_hi(pr);
        }
      }
#pragma unroll
      for (int o = 1; o < 16; o <<= 1) { s += __shfl_xor_sync(0xffffffffu, s, o); gs += __shfl_xor_sync(0xffffffffu, gs, o); }
      const float mean = s * (1.f / D_);
      float q = 0.f;
#pragma unroll
      for (int e = 0; e < 40; e++) { const float d = f[e] - mean; q = fmaf(d, d, q); }
#pragma unroll
      for (int o = 1; o < 16; o <<= 1) q += __shfl_xor_sync(0xffffffffu, q, o);
      const float rstd = rsqrtf(q * (1.f / D_) + 1e-5f);
      const float gate = bf_lo(pack_bf16(rcp(1.f + __expf(-bf_lo(pack_bf16(gs, 0.f)))), 0.f));
      asm volatile("barrier.cluster.wait.aligned;" ::: "memory");
      if ((tid & 15) == 0) g_xstat[128 * i + 16 * j + (tid >> 4)] = make_float4(rstd, -mean, gate, 0.f);
      signal(B_SIGP);
    }
    TSTAMP(1);

    Ring ra{0, 0}, rb{0, 0};
    uint32_t qp[2][10], P[2][10];
    float st_g[2];
    {
      float accM[128], accR[32];
      uint32_t pa = 0, pb = 0;
#pragma unroll 1
      for (int k = 0; k < 10; k++) {
        mbar_wait(fullA + 8 * ra.idx, ra.phase);
        if (tid == 0) TRACE(32 + k);
        mbar_wait(fullB + 8 * rb.idx, rb.phase);
        if (tid == 0) TRACE(64 + k);
        if (k == 0) TSTAMP(2);
        const uint32_t a0 = sb16 + ((OFF_A + ra.idx * SLOT_A + wg * 8192) >> 4), b0 = sb16 + ((OFF_B + rb.idx * SLOT_B) >> 4);
        wg_fence();
#pragma unroll
        for (int kk = 0; kk < 4; kk++) {
          const uint64_t da = make_desc(a0, kk * 32, 16, 1024, 1);
          if (kk == 0) {
            mma_ss256_p(accM, da, make_desc(b0, 0, 8192, 1024, 1), k);
            mma_ss64_p(accR, da, make_desc(b0, 32768, 2048, 256, 3), k);
          } else {
            mma_ss256(accM, da, make_desc(b0, kk * 2048, 8192, 1024, 1));
            mma_ss64(accR, da, make_desc(b0, 32768 + kk * 512, 2048, 256, 3));
          }
          if (kk == 0) {
            wg_commit();
            if (k > 0) {
              wg_wait<1>();
              release(emptyA + 8 * pa);
              releaseB(emptyB + 8 * pb);
            }
          }
        }
        wg_commit();
        pa = ra.idx; pb = rb.idx;
        ra.next<NA>(); rb.next<NB>();
      }
      TSTAMP(18);
      float st_rstd[2], st_mr[2];
      mbar_wait(bars + 8 * B_CS, 0);
#pragma unroll
      for (int r = 0; r < 2; r++) {
        const uint4 st = lds128(sb + OFF_XST + (rloc + 8 * r) * 16);
        st_rstd[r] = __uint_as_float(st.x); st_mr[r] = __uint_as_float(st.y); st_g[r] = __uint_as_float(st.z);
      }
      TSTAMP(19);
      wg_wait<0>();
      fence_regs(accM); fence_regs(accR);
      TSTAMP(3);
      release(emptyA + 8 * pa);
#define ACC(P_, G, I_) ((G) < 8 ? accM[(P_) * 32 + ((G) & 7) * 4 + (I_)] : accR[(P_) * 8 + ((G) & 1) * 4 + (I_)])
      {
        uint32_t hv[2][10];
        const GeluC g0 = gelu_consts(st_rstd[0], 1.f), g1 = gelu_consts(st_rstd[1], 1.f);
#pragma unroll
        for (int g = 0; g < 10; g++) {
          const float2 cs = *reinterpret_cast<const float2*>(s_cs + 8 * g + 2 * t);
          const float v0 = gelu_s(fmaf(st_mr[0], cs.x, ACC(0, g, 0)), g0), v1 = gelu_s(fmaf(st_mr[0], cs.y, ACC(0, g, 1)), g0);
          const float v2 = gelu_s(fmaf(st_mr[1], cs.x, ACC(0, g, 2)), g1), v3 = gelu_s(fmaf(st_mr[1], cs.y, ACC(0, g, 3)), g1);
          hv[0][g] = pack_bf16(v0, v1); hv[1][g] = pack_bf16(v2, v3);
        }
        bar_sync(1, 256);
        stage_tile(sb + OFF_STG, hv);
        fence_async_smem();
        signal(B_SIGH);
      }
      TSTAMP(4);
      uint32_t kf[5][4], qf[5][4];
#pragma unroll
      for (int s = 0; s < 5; s++) {
        kf[s][0] = pack_bf16(ACC(2, 2 * s, 0), ACC(2, 2 * s, 1)); kf[s][1] = pack_bf16(ACC(2, 2 * s, 2), ACC(2, 2 * s, 3));
        kf[s][2] = pack_bf16(ACC(2, 2 * s + 1, 0), ACC(2, 2 * s + 1, 1)); kf[s][3] = pack_bf16(ACC(2, 2 * s + 1, 2), ACC(2, 2 * s + 1, 3));
        qf[s][0] = pack_bf16(ACC(1, 2 * s, 0), ACC(1, 2 * s, 1)); qf[s][1] = pack_bf16(ACC(1, 2 * s, 2), ACC(1, 2 * s, 3));
        qf[s][2] = pack_bf16(ACC(1, 2 * s + 1, 0), ACC(1, 2 * s + 1, 1)); qf[s][3] = pack_bf16(ACC(1, 2 * s + 1, 2), ACC(1, 2 * s + 1, 3));
      }
      float pk[40], pq[40];
      wg_fence();
#pragma unroll
      for (int s = 0; s < 5; s++) {
        if (s == 0) mma_rs80_k_z(pk, kf[s], make_desc(sb16, OFF_MISC, 16, 256, 3));
        else mma_rs80_k(pk, kf[s], make_desc(sb16, OFF_MISC + s * 2560, 16, 256, 3));
      }
      wg_commit();
#pragma unroll
      for (int s = 0; s < 5; s++) {
        if (s == 0) mma_rs80_k_z(pq, qf[s], make_desc(sb16, OFF_MISC, 16, 256, 3));
        else mma_rs80_k(pq, qf[s], make_desc(sb16, OFF_MISC + s * 2560, 16, 256, 3));
      }
      wg_commit();
      {
        const int mat = lane >> 3;
        const int tok = warp * 16 + (mat & 1) * 8 + (lane & 7);
        const uint32_t base = sb + OFF_B + SPARE + tok * 32 + (((mat >> 1) ^ ((tok >> 2) & 1)) << 4);
        const uint32_t ones = (t == 0) ? 0x00003f80u : 0u;
#pragma unroll
        for (int p = 0; p < 2; p++) {
#pragma unroll
          for (int gg = 0; gg < 3; gg++) {
            const int g0 = 5 * p + 2 * gg;
            uint32_t r0 = pack_bf16(ACC(3, g0, 0), ACC(3, g0, 1)), r1 = pack_bf16(ACC(3, g0, 2), ACC(3, g0, 3));
            uint32_t r2 = ones, r3 = ones;
            if (gg < 2) { r2 = pack_bf16(ACC(3, g0 + 1, 0), ACC(3, g0 + 1, 1)); r3 = pack_bf16(ACC(3, g0 + 1, 2), ACC(3, g0 + 1, 3)); }
            stsm4(base + gg * SLOT_B + p * 4096, r0, r1, r2, r3);
          }
        }
      }
#undef ACC
      wg_wait<1>();
      fence_regs(pk);
#pragma unroll
      for (int G = 0; G < 10; G++) {
        P[0][G] = pack_bf16(pk[4 * G], pk[4 * G + 1]); P[1][G] = pack_bf16(pk[4 * G + 2], pk[4 * G + 3]);
      }
      wg_wait<0>();
      fence_regs(pq);
      signal(B_WDEAD);
#pragma unroll
      for (int G = 0; G < 10; G++) {
        qp[0][G] = pack_bf16(pq[4 * G], pq[4 * G + 1]); qp[1][G] = pack_bf16(pq[4 * G + 2], pq[4 * G + 3]);
      }
    }

    uint32_t fr[10][4];
    int pass;
    pass = gridDim.y;
#pragma unroll 1
    do {
    feature_map(P, fr);
    if (pass != 0) {
    {
      const int mat = lane >> 3;
      const int tok = warp * 16 + (mat & 1) * 8 + (lane & 7);
      const uint32_t base = sb + OFF_B + tok * 32 + (((mat >> 1) ^ ((tok >> 2) & 1)) << 4);
#pragma unroll
      for (int G = 0; G < 10; G++) stsm4(base + G * 4096, fr[G][0], fr[G][1], fr[G][2], fr[G][3]);
      fence_async_smem();
      bar_sync(1, 256);
      float kv[40];
      const uint32_t va = sb16 + ((OFF_B + SPARE + wg * 4096) >> 4), vb = sb16 + ((OFF_B + wg * 20480) >> 4);
      wg_fence();
#pragma unroll
      for (int ks = 0; ks < 8; ks++) {
        if (ks == 0) mma_ss80_tt_z(kv, make_desc(va, 0, SLOT_B, 256, 3), make_desc(vb, 0, 4096, 256, 3));
        else mma_ss80_tt(kv, make_desc(va, ks * 512, SLOT_B, 256, 3), make_desc(vb, ks * 512, 4096, 256, 3));
      }
      wg_commit();
      uint32_t xv[2][10];
      wg_wait<0>();
      fence_regs(kv);
      TSTAMP(31);
      releaseB(emptyB); release(bars + 8 * B_PEER2);
      auto kv_sts = [&](uint32_t o, uint32_t a0, uint32_t a1, uint32_t a2, uint32_t a3) {
        sts128(sb + OFF_B + SPARE + wg * 4096 + o + (o >= 4096 ? SLOT_B - 4096 : 0), make_uint4(a0, a1, a2, a3));
      };
      const int m0 = (warp & 3) * 16 + (lane >> 2);
      bar_sync(4 + wg, 128);
#pragma unroll
      for (int r = 0; r < 2; r++) {
        const int m = m0 + 8 * r;
        const bool hi = m >= 20;
        uint32_t v[10];
#pragma unroll
        for (int G = 0; G < 10; G++) v[G] = __float_as_uint(hi ? kv[4 * G + 2 * r + 1] : kv[4 * G + 2 * r]);
        const uint32_t p = 4 * (m < 40 ? m * 48 + t * 12 : 1920 + t * 24 + 12);
        if (m <= 40) { kv_sts(p, v[0], v[1], v[2], v[3]); kv_sts(p + 16, v[4], v[5], v[6], v[7]); kv_sts(p + 32, v[8], v[9], 0u, 0u); }
      }
      if (m0 == 32) {
        const uint32_t p = 4 * (1920 + t * 24);
        kv_sts(p, __float_as_uint(kv[2]), __float_as_uint(kv[6]), __float_as_uint(kv[10]), __float_as_uint(kv[14]));
        kv_sts(p + 16, __float_as_uint(kv[18]), __float_as_uint(kv[22]), __float_as_uint(kv[26]), __float_as_uint(kv[30]));
        kv_sts(p + 32, __float_as_uint(kv[34]), __float_as_uint(kv[38]), 0u, 0u);
      }
      fence_async_smem();
      signal(B_SIGKV);
      float acc[80];
      TSTAMP(5);
      mbar_wait(fullA + 8 * 2, 0);
      mbar_wait(fullB + 8 * 1, 1);
      TSTAMP(6);
      wg_fence();
#pragma unroll
      for (int kk = 0; kk < 4; kk++) {
        const uint64_t da = make_desc(sb16 + wg * 512, OFF_A + 2 * SLOT_A + kk * 32, 16, 1024, 1);
        const uint64_t db = make_desc(sb16, OFF_B + SLOT_B + kk * 1024, 4096, 512, 2);
        if (kk == 0) mma_ss160_z(acc, da, db); else mma_ss160(acc, da, db);
      }
      wg_commit();
      ra.next<NA>();
      uint32_t pa = 2, pb = 1;
#pragma unroll 1
      for (int k = 1; k < 5; k++) {
        mbar_wait(k < 4 ? fullA + 8 * ra.idx : bars + 8 * B_T4, k < 4 ? ra.phase : 0);
        if ((k & 1) == 0) mbar_wait(fullB + 8 * rb.idx, rb.phase);
        const uint32_t a0 = sb16 + ((OFF_A + (k < 4 ? ra.idx : NA) * SLOT_A + wg * 8192) >> 4);
        const uint32_t b0 = sb16 + ((OFF_B + rb.idx * SLOT_B + (k & 1) * 20480) >> 4);
        wg_fence();
#pragma unroll
        for (int kk = 0; kk < 4; kk++) {
          mma_ss160(acc, make_desc(a0, kk * 32, 16, 1024, 1), make_desc(b0, kk * 1024, 4096, 512, 2));
          if (kk == 0) {
            wg_commit();
            wg_wait<1>();
            if (k != 4) release(emptyA + 8 * pa);
            if ((k & 1) == 0) releaseB(emptyB + 8 * pb);
          }
        }
        wg_commit();
        pa = ra.idx; pb = rb.idx;
        if (k < 4) ra.next<NA>();
        if ((k & 1) || k == 4) rb.next<NB>();
      }
      mbar_wait(bars + 8 * B_PEER2, 0);
      wg_wait<0>();
      fence_regs(acc);
      TSTAMP(7);
      {
        uint32_t sn[20];
        if (rank) {
#pragma unroll
          for (int e = 0; e < 20; e++) sn[e] = pack_bf16(acc[2 * e], acc[2 * e + 1]);
#pragma unroll
          for (int e = 0; e < 40; e++) acc[e] = acc[40 + e];
        } else {
#pragma unroll
          for (int e = 0; e < 20; e++) sn[e] = pack_bf16(acc[40 + 2 * e], acc[41 + 2 * e]);
        }
        const uint32_t peer = map_peer(sb, rank ^ 1);
#pragma unroll
        for (int q = 0; q < 5; q++)
          st_async16(peer + OFF_B + 20480 + tid * 16 + q * 4096, sn[4 * q], sn[4 * q + 1], sn[4 * q + 2], sn[4 * q + 3],
                     peer + OFF_BAR + 8 * (B_DSR + 8 + wg));
        mbar_wait(bars + 8 * B_XR, 0);
#pragma unroll
        for (int g = 0; g < 10; g++) {
          const uint32_t x0 = lds32(sb + OFF_STG + rloc * 160 + t * 4 + g * 16), x1 = lds32(sb + OFF_STG + rloc * 160 + 1280 + t * 4 + g * 16);
          acc[4 * g] += bf_lo(x0); acc[4 * g + 1] += bf_hi(x0);
          acc[4 * g + 2] += bf_lo(x1); acc[4 * g + 3] += bf_hi(x1);
        }
        mbar_wait(bars + 8 * (B_DSR + 8 + wg), 0);
#pragma unroll
        for (int q = 0; q < 5; q++) {
          const uint4 v = lds128(sb + OFF_B + 20480 + tid * 16 + q * 4096);
          float* d = &acc[8 * q];
          d[0] += bf_lo(v.x); d[1] += bf_hi(v.x); d[2] += bf_lo(v.y); d[3] += bf_hi(v.y);
          d[4] += bf_lo(v.z); d[5] += bf_hi(v.z); d[6] += bf_lo(v.w); d[7] += bf_hi(v.w);
          xv[0][2 * q] = pack_bf16(d[0], d[1]); xv[1][2 * q] = pack_bf16(d[2], d[3]);
          xv[0][2 * q + 1] = pack_bf16(d[4], d[5]); xv[1][2 * q + 1] = pack_bf16(d[6], d[7]);
        }
        releaseB(emptyB + 8 * pb);
      }
      TSTAMP(16);
      stage_tile(sb + OFF_STG, xv);
      fence_async_smem();
      signal(B_SIGX1);
      TSTAMP(17);
#pragma unroll
      for (int r = 0; r < 2; r++) {
        float s = 0.f;
#pragma unroll
        for (int g = 0; g < 10; g++) s += acc[4 * g + 2 * r] + acc[4 * g + 2 * r + 1];
        s += __shfl_xor_sync(0xffffffffu, s, 1); s += __shfl_xor_sync(0xffffffffu, s, 2);
        const float mu = s * (1.f / 80.f);
        float q = 0.f;
#pragma unroll
        for (int g = 0; g < 10; g++) {
          const float d0 = acc[4 * g + 2 * r] - mu, d1 = acc[4 * g + 2 * r + 1] - mu;
          q = fmaf(d0, d0, q); q = fmaf(d1, d1, q);
        }
        q += __shfl_xor_sync(0xffffffffu, q, 1); q += __shfl_xor_sync(0xffffffffu, q, 2);
        if (t == 0) g_st1[(128 * i + rloc + 8 * r) * 8 + j] = make_float2(mu, q);
      }
    }
    TSTAMP(8);
#pragma unroll
    for (int G = 0; G < 10; G++) { P[0][G] = qp[0][G]; P[1][G] = qp[1][G]; }
    }
    asm volatile("" : "+r"(pass));
    } while (pass-- != 0);

    uint32_t of[5][4];
    {
      mbar_wait(bars + 8 * B_KV, 0);
#pragma unroll 1
      for (int it = tid; it < 384; it += 256) {
        const int p = it >= 192, rem = it - 192 * p, n = rem >> 2, tq = rem & 3;
        const uint32_t sp = sb + OFF_A + SLOT_A + 4 * (p * KV_PAIR + (n < 40 ? n * 48 + tq * 12 : 1920 + tq * 24 + (n & 1) * 12));
        const uint4 ka = lds128(sp), kb = lds128(sp + 16), kc = lds128(sp + 32);
        const uint32_t v[10] = {ka.x, ka.y, ka.z, ka.w, kb.x, kb.y, kb.z, kb.w, kc.x, kc.y};
        const int sh = (n < 40 ? (n >= 20) : (n & 1)) * 16;
        uint8_t* dst = sgen + OFF_MISC + p * 7680 + n * 32 + tq * 4;
        const int sw = ((n >> 2) & 1) << 4;
#pragma unroll
        for (int G = 0; G < 10; G++)
          *reinterpret_cast<uint32_t*>(dst + (G >> 1) * 1536 + (((G & 1) << 4) ^ sw)) = pack_bf16(__uint_as_float(v[G]), 0.f) << sh;
      }
      release(emptyA + 8);
      fence_async_smem();
      bar_sync(1, 256);
      float o0[24], o1[24];
      wg_fence();
#pragma unroll
      for (int g = 0; g < 5; g++) {
        if (g == 0) mma_rs48_k_z(o0, fr[g], make_desc(sb16, OFF_MISC, 16, 256, 3));
        else mma_rs48_k(o0, fr[g], make_desc(sb16, OFF_MISC + g * 1536, 16, 256, 3));
      }
#pragma unroll
      for (int g = 0; g < 5; g++) {
        if (g == 0) mma_rs48_k_z(o1, fr[5], make_desc(sb16, OFF_MISC + 7680, 16, 256, 3));
        else mma_rs48_k(o1, fr[5 + g], make_desc(sb16, OFF_MISC + 7680 + g * 1536, 16, 256, 3));
      }
      wg_commit();
      wg_wait<0>();
      fence_regs(o0); fence_regs(o1);
      signal(B_MFREE);
#pragma unroll
      for (int r = 0; r < 2; r++) {
        const float a0 = __fdividef(st_g[r], o0[20 + 2 * r] + 1e-6f), a1 = __fdividef(st_g[r], o0[21 + 2 * r] + 1e-6f);
        const float b0 = __fdividef(st_g[r], o1[20 + 2 * r] + 1e-6f), b1 = __fdividef(st_g[r], o1[21 + 2 * r] + 1e-6f);
        const float am = t < 2 ? a0 : a1, bm = t < 2 ? b0 : b1;
#pragma unroll
        for (int g = 0; g < 5; g++) {
          const float sa = g < 2 ? a0 : (g == 2 ? am : a1), sb2 = g < 2 ? b0 : (g == 2 ? bm : b1);
          of[g >> 1][(g & 1) * 2 + r] = pack_bf16(o0[4 * g + 2 * r] * sa, o0[4 * g + 2 * r + 1] * sa);
          of[(5 + g) >> 1][((5 + g) & 1) * 2 + r] = pack_bf16(o1[4 * g + 2 * r] * sb2, o1[4 * g + 2 * r + 1] * sb2);
        }
      }
    }
    TSTAMP(9);

    uint32_t hf[12][4];
    float ac4[80];
    auto unit = [&](auto uc, uint32_t b0) {
      constexpr int u = decltype(uc)::value;
#pragma unroll
      for (int s = 0; s < (u ? 4 : 5); s++) {
        const uint64_t db = make_desc(b0, (u ? 5120 + 20480 * u : 0) + s * 1024, u ? 4096 : 5120, 512, 2);
        if (u == 0 && s == 0) mma_rs160_n_z(ac4, of[0], db);
        else if (u == 0) mma_rs160_n(ac4, of[s], db);
        else mma_rs160_n(ac4, hf[(4 * u + 8 + s) % 12], db);
      }
      wg_commit();
    };
    {
      float acc[96];
      uint32_t pa = 0, pb = 0;
#pragma unroll 1
      for (int k = 0; k < 10; k++) {
        mbar_wait(fullA + 8 * ra.idx, ra.phase);
        if (tid == 0) TRACE(52 + k);
        if ((k & 1) == 0) mbar_wait(fullB + 8 * rb.idx, rb.phase);
        if (tid == 0) TRACE(84 + k);
        if (k == 0) TSTAMP(10);
        const uint32_t a0 = sb16 + ((OFF_A + ra.idx * SLOT_A + wg * 8192) >> 4);
        const uint32_t b0 = sb16 + ((OFF_B + rb.idx * SLOT_B + (k & 1) * 24576) >> 4);
        wg_fence();
#pragma unroll
        for (int kk = 0; kk < 4; kk++) {
          if (kk == 0) mma_ss192_p(acc, make_desc(a0, 0, 16, 1024, 1), make_desc(b0, 0, 8192, 1024, 1), k);
          else mma_ss192(acc, make_desc(a0, kk * 32, 16, 1024, 1), make_desc(b0, kk * 2048, 8192, 1024, 1));
          if (kk == 0) {
            wg_commit();
            if (k > 0) {
              wg_wait<1>();
              release(emptyA + 8 * pa);
              if ((k & 1) == 0) releaseB(emptyB + 8 * pb);
            }
          }
        }
        wg_commit();
        pa = ra.idx; pb = rb.idx;
        ra.next<NA>();
        if (k & 1) rb.next<NB>();
      }
      float rs[2], mm[2];
      mbar_wait(bars + 8 * B_ST1, 0);
#pragma unroll
      for (int r = 0; r < 2; r++) {
        const uint4 su = lds128(sb + OFF_MISC + (rloc + 8 * r) * 64 + t * 16);
        const float m0 = __uint_as_float(su.x), m1 = __uint_as_float(su.z);
        float mu = m0 + m1;
        mu += __shfl_xor_sync(0xffffffffu, mu, 1); mu += __shfl_xor_sync(0xffffffffu, mu, 2);
        mu *= 0.125f;
        const float d0 = m0 - mu, d1 = m1 - mu;
        float q = __uint_as_float(su.y) + __uint_as_float(su.w) + 80.f * (d0 * d0 + d1 * d1);
        q += __shfl_xor_sync(0xffffffffu, q, 1); q += __shfl_xor_sync(0xffffffffu, q, 2);
        rs[r] = rsqrtf(q * (1.f / D_) + 1e-5f);
        mm[r] = -mu;
      }
      mbar_wait(bars + 8 * B_FULL4, 0);
      wg_fence();
      unit(IntC<0>{}, sb16);
      wg_wait<1>();
      fence_regs(acc);
      releaseB(emptyB + 8 * pb);
      release(bars + 8 * B_PEER);
      TSTAMP(11);
      const GeluC g0 = gelu_consts(rs[0], 1.f - st_g[0]), g1 = gelu_consts(rs[1], 1.f - st_g[1]);
#pragma unroll
      for (int g = 0; g < 24; g++) {
        const float2 cs = *reinterpret_cast<const float2*>(s_cs + 80 + 8 * g + 2 * t);
        const float v0 = gelu_s(fmaf(mm[0], cs.x, acc[4 * g]), g0), v1 = gelu_s(fmaf(mm[0], cs.y, acc[4 * g + 1]), g0);
        const float v2 = gelu_s(fmaf(mm[1], cs.x, acc[4 * g + 2]), g1), v3 = gelu_s(fmaf(mm[1], cs.y, acc[4 * g + 3]), g1);
        hf[g >> 1][(g & 1) * 2] = pack_bf16(v0, v1);
        hf[g >> 1][(g & 1) * 2 + 1] = pack_bf16(v2, v3);
        if (g == 7) { wg_fence(); unit(IntC<1>{}, sb16); }
        if (g == 15) { mbar_wait(bars + 8 * (B_FULL4 + 1), 0); wg_fence(); unit(IntC<2>{}, sb16); }
        if (g == 23) { wg_wait<1>(); signal(B_EMPTY4); wg_fence(); unit(IntC<3>{}, sb16); }
      }
    }
    TSTAMP(12);

    {
      float kp[40];
      uint32_t sn[20], kb[20];
      const uint32_t peer = map_peer(sb, rank ^ 1);
      const uint32_t tag = lds32(sb + OFF_BAR + 8 * NBAR);
      auto add8 = [&](int q, const uint4 v) {
        float* d = &kp[8 * q];
        d[0] += bf_lo(v.x); d[1] += bf_hi(v.x); d[2] += bf_lo(v.y); d[3] += bf_hi(v.y);
        d[4] += bf_lo(v.z); d[5] += bf_hi(v.z); d[6] += bf_lo(v.w); d[7] += bf_hi(v.w);
      };
      auto send = [&](int c) {
        const uint32_t dso = peer + OFF_DS + (c & 1) * 20480 + tid * 16, dsb = peer + OFF_BAR + 8 * (B_DSR + 2 * c + wg);
#pragma unroll
        for (int q = 0; q < 5; q++) st_async16(dso + q * 4096, sn[4 * q], sn[4 * q + 1], sn[4 * q + 2], sn[4 * q + 3], dsb);
      };
      mbar_wait(bars + 8 * B_PEER, 0);
      uint4* gdst = g_part + (size_t)i * 8 * 3840 + tid;
#pragma unroll 1
      for (int c = 0; c < 3; c++) {
        const uint32_t b0 = sb16 + ((c & 1) ? 0 : SET4 >> 4), bc = bars + 16 * c;
        mbar_wait(bc + 8 * (B_FULL4 + 2), 0);
        wg_wait<0>();
        fence_regs(ac4);
        if (rank) {
#pragma unroll
          for (int e = 0; e < 20; e++) { sn[e] = pack_bf16(ac4[2 * e], ac4[2 * e + 1]); kb[e] = pack_bf16(ac4[40 + 2 * e], ac4[41 + 2 * e]); }
        } else {
#pragma unroll
          for (int e = 0; e < 20; e++) { kb[e] = pack_bf16(ac4[2 * e], ac4[2 * e + 1]); sn[e] = pack_bf16(ac4[40 + 2 * e], ac4[41 + 2 * e]); }
        }
#pragma unroll
        for (int e = 0; e < 20; e++) asm volatile("" : "+r"(sn[e]), "+r"(kb[e]));
        send(c);
        if (c == 0 && wg == 1) bar_sync(2, 256);
        wg_fence();
        unit(IntC<0>{}, b0);
        if (lane == 0) mbar_arrive(bc + 8 * (B_EMPTY4 + 1));
        unit(IntC<1>{}, b0);
        if (c == 0 && wg == 0) bar_arrive(2, 256);
        {
          mbar_wait(bc + 8 * (B_DSR + wg), 0);
          uint4* dst = gdst + (((j + 2 * c + 2) & 7) * 3 + c) * 1280;
#pragma unroll
          for (int q = 0; q < 5; q++) {
            const uint4 v = lds128(sb + OFF_DS + (c & 1) * 20480 + tid * 16 + q * 4096);
            st_relaxed16(dst + q * 256, (add_bf2(v.x, kb[4 * q]) & ~1u) | tag, add_bf2(v.y, kb[4 * q + 1]),
                         add_bf2(v.z, kb[4 * q + 2]), add_bf2(v.w, kb[4 * q + 3]));
          }
        }
        mbar_wait(bc + 8 * (B_FULL4 + 3), 0);
        wg_fence();
        unit(IntC<2>{}, b0);
        wg_wait<1>();
        if (lane == 0) mbar_arrive(bc + 8 * (B_EMPTY4 + 2));
        unit(IntC<3>{}, b0);
      }
      auto partial = [&](int c, uint4 (&v)[5]) {
        mbar_wait(bars + 8 * (B_RDY + c), 0);
        uint32_t bad = 0;
#pragma unroll
        for (int q = 0; q < 5; q++) { v[q] = lds128(sb + (c ? 25600 + 20480 * c : 0) + tid * 16 + q * 4096); bad |= v[q].x ^ tag; }
#pragma unroll 1
        for (uint32_t n = 0; (bad & 1u) && n < (WAIT_LIMIT >> 2); n++) {
          bad = 0;
#pragma unroll
          for (int q = 0; q < 5; q++) { v[q] = ld_relaxed16(gdst + (j * 3 + c) * 1280 + q * 256); bad |= v[q].x ^ tag; }
        }
      };
      uint4 pa4[5], pb4[5];
      partial(0, pa4);
      wg_wait<0>();
      fence_regs(ac4);
      if (rank) {
#pragma unroll
        for (int e = 0; e < 20; e++) sn[e] = pack_bf16(ac4[2 * e], ac4[2 * e + 1]);
#pragma unroll
        for (int e = 0; e < 40; e++) kp[e] = ac4[40 + e];
      } else {
#pragma unroll
        for (int e = 0; e < 20; e++) sn[e] = pack_bf16(ac4[40 + 2 * e], ac4[41 + 2 * e]);
#pragma unroll
        for (int e = 0; e < 40; e++) kp[e] = ac4[e];
      }
      send(3);
      TSTAMP(13);
      {
        mbar_wait(bars + 8 * B_XR, 1);
        const float w0 = 1.f - st_g[0], w1s = 1.f - st_g[1];
        const uint32_t xa = sb + OFF_OUT + rloc * 160 + t * 4;
#pragma unroll
        for (int g = 0; g < 10; g++) {
          const uint32_t x0 = lds32(xa + g * 16), x1 = lds32(xa + 1280 + g * 16);
          kp[4 * g] = fmaf(w0, bf_lo(x0), kp[4 * g]); kp[4 * g + 1] = fmaf(w0, bf_hi(x0), kp[4 * g + 1]);
          kp[4 * g + 2] = fmaf(w1s, bf_lo(x1), kp[4 * g + 2]); kp[4 * g + 3] = fmaf(w1s, bf_hi(x1), kp[4 * g + 3]);
        }
      }
      partial(1, pb4);
#pragma unroll
      for (int q = 0; q < 5; q++)
        pa4[q] = make_uint4(add_bf2(pa4[q].x, pb4[q].x), add_bf2(pa4[q].y, pb4[q].y), add_bf2(pa4[q].z, pb4[q].z), add_bf2(pa4[q].w, pb4[q].w));
#pragma unroll
      for (int q = 0; q < 5; q++) add8(q, pa4[q]);
      partial(2, pb4);
      mbar_wait(bars + 8 * (B_DSR + 6 + wg), 0);
      TSTAMP(14);
#pragma unroll
      for (int q = 0; q < 5; q++) {
        const uint4 c = pb4[q], d = lds128(sb + OFF_DS + 20480 + tid * 16 + q * 4096);
        add8(q, make_uint4(add_bf2(c.x, d.x), add_bf2(c.y, d.y), add_bf2(c.z, d.z), add_bf2(c.w, d.w)));
      }
      __syncwarp();
      uint32_t ov[2][10];
#pragma unroll
      for (int g = 0; g < 10; g++) { ov[0][g] = pack_bf16(kp[4 * g], kp[4 * g + 1]); ov[1][g] = pack_bf16(kp[4 * g + 2], kp[4 * g + 3]); }
      stage_tile(sb + OFF_OUT, ov);
      __syncwarp();
      __nv_bfloat16* dst = out + (size_t)(128 * i + 16 * warp) * D_ + 80 * j;
#pragma unroll
      for (int q = 0; q < 5; q++) {
        const int id = q * 32 + lane, r = id / 10;
        *reinterpret_cast<uint4*>(dst + r * (D_ - 80) + id * 8) = lds128(sb + OFF_OUT + warp * 2560 + id * 16);
      }
    }
    TSTAMP(15);
    if (tid == 0) asm volatile("red.relaxed.gpu.global.add.u32 [%0], 1;" ::"l"(g_flags + FL_DONE * 32) : "memory");
  }
}

namespace {
typedef CUresult (*EncodeFn)(CUtensorMap*, CUtensorMapDataType, cuuint32_t, void*, const cuuint64_t*, const cuuint64_t*,
                             const cuuint32_t*, const cuuint32_t*, CUtensorMapInterleave, CUtensorMapSwizzle,
                             CUtensorMapL2promotion, CUtensorMapFloatOOBfill);

void encode(EncodeFn fn, CUtensorMap* m, const void* ptr, int rank, const cuuint64_t* dims, const cuuint64_t* strides,
            const cuuint32_t* box, CUtensorMapSwizzle swz) {
  cuuint32_t es[5] = {1, 1, 1, 1, 1};
  fn(m, CU_TENSOR_MAP_DATA_TYPE_BFLOAT16, rank, const_cast<void*>(ptr), dims, strides, box, es, CU_TENSOR_MAP_INTERLEAVE_NONE,
     swz, CU_TENSOR_MAP_L2_PROMOTION_L2_128B, CU_TENSOR_MAP_FLOAT_OOB_FILL_NONE);
}
}

extern "C" void kernel_launch(void* const* d_in, const int* in_sizes, int n_in, void* d_out, int out_size) {
  (void)in_sizes; (void)n_in; (void)out_size;
  const __nv_bfloat16* x = (const __nv_bfloat16*)d_in[0];
  const __nv_bfloat16* wqkv = (const __nv_bfloat16*)d_in[1];
  const __nv_bfloat16* wphi = (const __nv_bfloat16*)d_in[2];
  const __nv_bfloat16* wo = (const __nv_bfloat16*)d_in[3];
  const __nv_bfloat16* w1 = (const __nv_bfloat16*)d_in[5];
  const __nv_bfloat16* w2 = (const __nv_bfloat16*)d_in[6];
  const __nv_bfloat16* w3 = (const __nv_bfloat16*)d_in[7];
  const __nv_bfloat16* w4 = (const __nv_bfloat16*)d_in[8];
  const __nv_bfloat16* gate_w = (const __nv_bfloat16*)d_in[9];

  static EncodeFn enc = nullptr;
  static void *pHs = nullptr, *pX1 = nullptr;
  if (!enc) {
    cudaDriverEntryPointQueryResult qr;
    cudaGetDriverEntryPoint("cuTensorMapEncodeTiled", (void**)&enc, cudaEnableDefault, &qr);
    cudaGetSymbolAddress(&pHs, g_Hs);
    cudaGetSymbolAddress(&pX1, g_X1);
    cudaFuncSetAttribute(fused_kernel, cudaFuncAttributeMaxDynamicSharedMemorySize, SMEM_BYTES);
  }
  Maps m;
  {
    cuuint64_t dims[2] = {D_, S_}, str[1] = {D_ * 2};
    cuuint32_t box[2] = {64, 128}, boxh[2] = {64, 64};
    encode(enc, &m.x, x, 2, dims, str, boxh, CU_TENSOR_MAP_SWIZZLE_128B);
    encode(enc, &m.hs, (const char*)pHs + 2 * D_ * 2, 2, dims, str, box, CU_TENSOR_MAP_SWIZZLE_128B);
    encode(enc, &m.x1, pX1, 2, dims, str, boxh, CU_TENSOR_MAP_SWIZZLE_128B);
    cuuint32_t boxs[2] = {80, 128};
    cuuint64_t dimsp[2] = {D_, S_ + 4};
    encode(enc, &m.st_h, pHs, 2, dimsp, str, boxs, CU_TENSOR_MAP_SWIZZLE_NONE);
    encode(enc, &m.st_x1, pX1, 2, dims, str, boxs, CU_TENSOR_MAP_SWIZZLE_NONE);
    encode(enc, &m.xr, x, 2, dims, str, boxs, CU_TENSOR_MAP_SWIZZLE_NONE);
  }
  {
    cuuint64_t dims[3] = {80, D_, 8}, str[2] = {D_ * 2, 160};
    cuuint32_t boxm[3] = {64, 64, 1}, boxr[3] = {16, 64, 1};
    encode(enc, &m.w1m, w1, 3, dims, str, boxm, CU_TENSOR_MAP_SWIZZLE_128B);
    encode(enc, &m.w1r, w1, 3, dims, str, boxr, CU_TENSOR_MAP_SWIZZLE_32B);
  }
  {
    cuuint64_t dims[4] = {80, D_, 3, 8}, str[3] = {3 * D_ * 2, D_ * 2, 160};
    cuuint32_t boxm[4] = {64, 64, 3, 1}, boxr[4] = {16, 64, 3, 1};
    encode(enc, &m.qm, wqkv, 4, dims, str, boxm, CU_TENSOR_MAP_SWIZZLE_128B);
    encode(enc, &m.qr, wqkv, 4, dims, str, boxr, CU_TENSOR_MAP_SWIZZLE_32B);
  }
  {
    cuuint64_t dims[3] = {32, D_, 20}, dims4[3] = {32, F_, 20}, str[2] = {D_ * 2, 64};
    cuuint32_t box4[3] = {32, 64, 5}, boxo[3] = {32, 80, 5};
    encode(enc, &m.w4, w4, 3, dims4, str, box4, CU_TENSOR_MAP_SWIZZLE_64B);
    encode(enc, &m.wo, wo, 3, dims, str, boxo, CU_TENSOR_MAP_SWIZZLE_64B);
    encode(enc, &m.w2, w2, 3, dims, str, box4, CU_TENSOR_MAP_SWIZZLE_64B);
  }
  {
    cuuint64_t dims[3] = {64, D_, 24}, str[2] = {F_ * 2, 128};
    cuuint32_t box[3] = {64, 64, 3};
    encode(enc, &m.w3, w3, 3, dims, str, box, CU_TENSOR_MAP_SWIZZLE_128B);
  }
  fused_kernel<<<NCTA + NSVC, 384, SMEM_BYTES, cudaStreamPerThread>>>(m, x, wqkv, wphi, w1, w2, w3, w4, wo, gate_w, (__nv_bfloat16*)d_out);
}
```

```cpp
#include <cuda_runtime.h>
#include <cuda_bf16.h>
#include <cuda.h>
#include <stdint.h>

namespace {

constexpr int S_ = 2048, D_ = 640, F_ = 1536;
constexpr int NCTA = 128, NSVC = 4;
constexpr int KV_PAIR = 40 * 48 + 96;
constexpr int KV_J = 2 * KV_PAIR;

constexpr int SLOT_B = 49152, NB = 3;
constexpr int SLOT_A = 16384, NA = 4;
constexpr int OFF_B = 0;
constexpr int OFF_A = OFF_B + NB * SLOT_B;
constexpr int OFF_STG = OFF_A + 2 * SLOT_A;
constexpr int OFF_MISC = OFF_A + NA * SLOT_A;
constexpr int OFF_XST = OFF_MISC + 13312;
constexpr int OFF_CS = OFF_MISC + 16384;
constexpr int OFF_BAR = OFF_CS + 1088;
constexpr int SMEM_BYTES = OFF_BAR + 512 + 512 + 128;
constexpr int B_FULLA = 0, B_FULLB = 4, B_CS = 7, B_XR = 8, B_KV = 9, B_ST1 = 10, B_HST = 11, B_FULL4 = 12  , B_RDY = 20  , B_T4 = 23, B_KVR = 24,
              B_DSR = 25  , B_EMPTYB = 35  , B_SIGP = 38, B_SIGH = 39, B_SIGKV = 40, B_SIGX1 = 41, B_MFREE = 42,
              B_WDEAD = 43, B_EMPTY4 = 44  , B_EMPTYA = 52  , B_PEER = 56, B_PEER2 = 57, B_X1P = 58  , NBAR = 59;
constexpr int SPARE = 40960;
constexpr int SET4 = 87040, OFF_DS = 2 * SET4, OFF_OUT = 20480;

constexpr int FL_DONE = 0, FL_H = 1  , FL_X1 = FL_H + 32, FL_KV = FL_X1 + 16, FL_CS = FL_KV + 8, FL_CS3 = FL_CS + 1, FL_ST = FL_CS3 + 1;
constexpr int FL_S1 = FL_ST + 16, FL_COUNT = FL_S1 + 16;

struct Maps {
  CUtensorMap x, w1m, w1r, qm, qr, hs, w2, x1, w3, w4, wo, xr, st_h, st_x1;
};

}

__device__ __align__(1024) __nv_bfloat16 g_Hs[(S_ + 4) * D_];
__device__ __align__(1024) __nv_bfloat16 g_X1[S_ * D_];
__device__ __align__(128) float g_acc[2][8 * KV_J];
__device__ __align__(128) float g_cs[2][D_ + F_];
__device__ __align__(128) uint4 g_wphi[8 * 800];
__device__ __align__(128) float4 g_xstat[S_];
__device__ __align__(128) float2 g_st1[S_ * 8];
__device__ __align__(128) uint4 g_part[16 * 8 * 3 * 1280];
__device__ __align__(128) unsigned g_flags[FL_COUNT * 32];
#define TSTAMP(n) do {} while (0)
#define TSTAMPX(n) do {} while (0)
#define TRACE(n) do {} while (0)
#define TRS(n) do {} while (0)

namespace {

__device__ __forceinline__ long long gtime() { long long t; asm volatile("mov.u64 %0, %%globaltimer;" : "=l"(t)); return t; }
__device__ __forceinline__ uint32_t smem_u32(const void* p) { return (uint32_t)__cvta_generic_to_shared(p); }
__device__ __forceinline__ void mbar_init(uint32_t bar, int cnt) {
  asm volatile("mbarrier.init.shared::cta.b64 [%0], %1;" ::"r"(bar), "r"(cnt) : "memory");
}
__device__ __forceinline__ void mbar_expect_tx(uint32_t bar, int bytes) {
  asm volatile("mbarrier.arrive.expect_tx.shared::cta.b64 _, [%0], %1;" ::"r"(bar), "r"(bytes) : "memory");
}
__device__ __forceinline__ void mbar_arrive_cta(uint32_t bar, uint32_t cta) {
  asm volatile("{\n.reg .b32 ra;\nmapa.shared::cluster.u32 ra, %0, %1;\nmbarrier.arrive.shared::cluster.b64 _, [ra];\n}"
               ::"r"(bar), "r"(cta) : "memory");
}
__device__ __forceinline__ uint32_t mbar_try(uint32_t bar, uint32_t parity) {
  uint32_t ok;
  asm volatile("{\n.reg .pred p;\nmbarrier.try_wait.parity.shared::cta.b64 p, [%1], %2;\nselp.u32 %0, 1, 0, p;\n}"
               : "=r"(ok) : "r"(bar), "r"(parity) : "memory");
  return ok;
}
constexpr uint32_t WAIT_LIMIT = 1u << 17;
__device__ __forceinline__ void mbar_wait(uint32_t bar, uint32_t parity) {
  uint32_t n = 0;
  while (!mbar_try(bar, parity) && ++n < WAIT_LIMIT) {}
}
__device__ __forceinline__ unsigned ld_acquire(const unsigned* p) {
  unsigned v;
  asm volatile("ld.acquire.gpu.global.u32 %0, [%1];" : "=r"(v) : "l"(p) : "memory");
  return v;
}
__device__ __forceinline__ void flag_wait(int idx, unsigned target) {
  const unsigned* p = g_flags + idx * 32;
  uint32_t n = 0;
  while ((int)(ld_acquire(p) - target) < 0 && ++n < (WAIT_LIMIT >> 2)) {}
}
__device__ __forceinline__ void flag_add(int idx) {
  asm volatile("red.release.gpu.global.add.u32 [%0], 1;" ::"l"(g_flags + idx * 32) : "memory");
}
__device__ __forceinline__ void flag_add_relaxed(int idx) {
  asm volatile("red.relaxed.gpu.global.add.u32 [%0], 1;" ::"l"(g_flags + idx * 32) : "memory");
}
__device__ __forceinline__ uint32_t mbar_test(uint32_t bar, uint32_t parity) {
  uint32_t ok;
  asm volatile("{\n.reg .pred p;\nmbarrier.test_wait.parity.shared::cta.b64 p, [%1], %2;\nselp.u32 %0, 1, 0, p;\n}"
               : "=r"(ok) : "r"(bar), "r"(parity) : "memory");
  return ok;
}
__device__ __forceinline__ uint32_t lds32(uint32_t a) {
  uint32_t v;
  asm volatile("ld.shared.u32 %0, [%1];" : "=r"(v) : "r"(a) : "memory");
  return v;
}
__device__ __forceinline__ void mbar_arrive(uint32_t bar) {
  asm volatile("mbarrier.arrive.shared::cta.b64 _, [%0];" ::"r"(bar) : "memory");
}
__device__ __forceinline__ void fence_async_glb() { asm volatile("fence.proxy.async.global;" ::: "memory"); }
__device__ __forceinline__ void fence_async_smem() { asm volatile("fence.proxy.async.shared::cta;" ::: "memory"); }
__device__ __forceinline__ void bar_sync(int id, int n) { asm volatile("bar.sync %0, %1;" ::"r"(id), "r"(n) : "memory"); }

__device__ __forceinline__ void tma2d(uint32_t dst, const CUtensorMap* m, uint32_t bar, int c0, int c1) {
  asm volatile("cp.async.bulk.tensor.2d.shared::cluster.global.mbarrier::complete_tx::bytes [%0], [%1, {%3, %4}], [%2];"
               ::"r"(dst), "l"(m), "r"(bar), "r"(c0), "r"(c1) : "memory");
}
__device__ __forceinline__ void tma2d_mc(uint32_t dst, const CUtensorMap* m, uint32_t bar, int c0, int c1) {
  asm volatile("cp.async.bulk.tensor.2d.shared::cluster.global.mbarrier::complete_tx::bytes.multicast::cluster"
               " [%0], [%1, {%3, %4}], [%2], %5;"
               ::"r"(dst), "l"(m), "r"(bar), "r"(c0), "r"(c1), "h"((uint16_t)3) : "memory");
}
__device__ __forceinline__ void tma3d(uint32_t dst, const CUtensorMap* m, uint32_t bar, int c0, int c1, int c2) {
  asm volatile("cp.async.bulk.tensor.3d.shared::cluster.global.mbarrier::complete_tx::bytes [%0], [%1, {%3, %4, %5}], [%2];"
               ::"r"(dst), "l"(m), "r"(bar), "r"(c0), "r"(c1), "r"(c2) : "memory");
}
__device__ __forceinline__ void tma4d(uint32_t dst, const CUtensorMap* m, uint32_t bar, int c0, int c1, int c2, int c3) {
  asm volatile("cp.async.bulk.tensor.4d.shared::cluster.global.mbarrier::complete_tx::bytes [%0], [%1, {%3, %4, %5, %6}], [%2];"
               ::"r"(dst), "l"(m), "r"(bar), "r"(c0), "r"(c1), "r"(c2), "r"(c3) : "memory");
}
__device__ __forceinline__ void tma2d_store(const CUtensorMap* m, uint32_t src, int c0, int c1) {
  asm volatile("cp.async.bulk.tensor.2d.global.shared::cta.bulk_group [%0, {%2, %3}], [%1];"
               ::"l"(m), "r"(src), "r"(c0), "r"(c1) : "memory");
}
__device__ __forceinline__ void bulk_store(void* dst, uint32_t src, uint32_t bytes) {
  asm volatile("cp.async.bulk.global.shared::cta.bulk_group [%0], [%1], %2;" ::"l"(dst), "r"(src), "r"(bytes) : "memory");
}
__device__ __forceinline__ void bulk_load(uint32_t dst, const void* src, uint32_t bytes, uint32_t bar) {
  asm volatile("cp.async.bulk.shared::cluster.global.mbarrier::complete_tx::bytes [%0], [%1], %2, [%3];"
               ::"r"(dst), "l"(src), "r"(bytes), "r"(bar) : "memory");
}
__device__ __forceinline__ void bulk_commit() { asm volatile("cp.async.bulk.commit_group;" ::: "memory"); }
template <int N> __device__ __forceinline__ void bulk_wait() { asm volatile("cp.async.bulk.wait_group %0;" ::"n"(N) : "memory"); }
__device__ __forceinline__ void bulk_wait_read() { asm volatile("cp.async.bulk.wait_group.read 0;" ::: "memory"); }
__device__ __forceinline__ void bar_arrive(int id, int n) { asm volatile("bar.arrive %0, %1;" ::"r"(id), "r"(n) : "memory"); }
__device__ __forceinline__ uint4 lds128(uint32_t a) {
  uint4 v;
  asm volatile("ld.shared.v4.u32 {%0, %1, %2, %3}, [%4];" : "=r"(v.x), "=r"(v.y), "=r"(v.z), "=r"(v.w) : "r"(a) : "memory");
  return v;
}
__device__ __forceinline__ void sts128(uint32_t a, uint4 v) {
  asm volatile("st.shared.v4.u32 [%0], {%1, %2, %3, %4};" ::"r"(a), "r"(v.x), "r"(v.y), "r"(v.z), "r"(v.w) : "memory");
}
__device__ __forceinline__ uint4 ld_relaxed16(const uint4* p) {
  uint4 v;
  asm volatile("ld.relaxed.gpu.global.v4.u32 {%0, %1, %2, %3}, [%4];" : "=r"(v.x), "=r"(v.y), "=r"(v.z), "=r"(v.w) : "l"(p) : "memory");
  return v;
}
__device__ __forceinline__ void st_relaxed16(uint4* p, uint32_t a, uint32_t b, uint32_t c, uint32_t d) {
  asm volatile("st.relaxed.gpu.global.v4.u32 [%0], {%1, %2, %3, %4};" ::"l"(p), "r"(a), "r"(b), "r"(c), "r"(d) : "memory");
}
__device__ __forceinline__ uint32_t map_peer(uint32_t addr, uint32_t cta) {
  uint32_t r;
  asm("mapa.shared::cluster.u32 %0, %1, %2;" : "=r"(r) : "r"(addr), "r"(cta));
  return r;
}
__device__ __forceinline__ void st_async16(uint32_t addr, uint32_t a, uint32_t b, uint32_t c, uint32_t d, uint32_t bar) {
  asm volatile("st.async.weak.shared::cluster.mbarrier::complete_tx::bytes.v4.b32 [%0], {%1, %2, %3, %4}, [%5];"
               ::"r"(addr), "r"(a), "r"(b), "r"(c), "r"(d), "r"(bar) : "memory");
}
__device__ __forceinline__ void l2_prefetch(const void* p, uint32_t bytes) {
  asm volatile("cp.async.bulk.prefetch.L2.global [%0], %1;" ::"l"(p), "r"(bytes) : "memory");
}
__device__ __forceinline__ void prefetch_tmap(const CUtensorMap* m) {
  asm volatile("prefetch.tensormap [%0];" ::"l"(m) : "memory");
}
__device__ __forceinline__ uint64_t make_desc(uint32_t a16, uint32_t off, uint32_t lbo, uint32_t sbo, uint32_t swz) {
  const uint32_t lo = a16 + ((off >> 4) + ((lbo >> 4) << 16)), hi = (sbo >> 4) | (swz << 30);
  uint64_t d;
  asm("mov.b64 %0, {%1, %2};" : "=l"(d) : "r"(lo), "r"(hi));
  return d;
}
__device__ __forceinline__ void wg_fence() { asm volatile("wgmma.fence.sync.aligned;" ::: "memory"); }
__device__ __forceinline__ void wg_commit() { asm volatile("wgmma.commit_group.sync.aligned;" ::: "memory"); }
template <int N> __device__ __forceinline__ void wg_wait() { asm volatile("wgmma.wait_group.sync.aligned %0;" ::"n"(N) : "memory"); }
template <int N> __device__ __forceinline__ void fence_regs(float (&d)[N]) {
#pragma unroll
  for (int i = 0; i < N; i++) asm volatile("" : "+f"(d[i])::"memory");
}
template <int N> __device__ __forceinline__ void zero_regs(float (&d)[N]) {
#pragma unroll
  for (int i = 0; i < N; i++) d[i] = 0.f;
}
__device__ __forceinline__ uint32_t pack_bf16(float lo, float hi) {
  uint32_t r;
  asm("cvt.rn.bf16x2.f32 %0, %1, %2;" : "=r"(r) : "f"(hi), "f"(lo));
  return r;
}
__device__ __forceinline__ float bf_lo(uint32_t v) { return __uint_as_float(v << 16); }
__device__ __forceinline__ float bf_hi(uint32_t v) { return __uint_as_float(v & 0xffff0000u); }
__device__ __forceinline__ uint32_t max_bf2(uint32_t a, uint32_t b) {
  uint32_t r; asm("max.bf16x2 %0, %1, %2;" : "=r"(r) : "r"(a), "r"(b)); return r;
}
__device__ __forceinline__ uint32_t min_bf2(uint32_t a, uint32_t b) {
  uint32_t r; asm("min.bf16x2 %0, %1, %2;" : "=r"(r) : "r"(a), "r"(b)); return r;
}
__device__ __forceinline__ uint32_t add_bf2(uint32_t a, uint32_t b) {
  uint32_t r; asm("add.rn.bf16x2 %0, %1, %2;" : "=r"(r) : "r"(a), "r"(b)); return r;
}
__device__ __forceinline__ uint32_t mul_bf2(uint32_t a, uint32_t b) {
  uint32_t r; asm("mul.rn.bf16x2 %0, %1, %2;" : "=r"(r) : "r"(a), "r"(b)); return r;
}
__device__ __forceinline__ float ex2(float x) { float r; asm("ex2.approx.ftz.f32 %0, %1;" : "=f"(r) : "f"(x)); return r; }
__device__ __forceinline__ float rcp(float x) { float r; asm("rcp.approx.ftz.f32 %0, %1;" : "=f"(r) : "f"(x)); return r; }
__device__ __forceinline__ float tanh_ap(float x) { float r; asm("tanh.approx.f32 %0, %1;" : "=f"(r) : "f"(x)); return r; }
struct GeluC { float c0, c1, ch; };
__device__ __forceinline__ GeluC gelu_consts(float rstd, float scale) {
  return GeluC{0.7978845608f * rstd, 0.0356774081f * rstd * rstd * rstd, 0.5f * scale * rstd};
}
__device__ __forceinline__ float gelu_s(float y, const GeluC& c) {
  const float u = y * fmaf(y * y, c.c1, c.c0);
  const float hx = y * c.ch;
  return fmaf(hx, tanh_ap(u), hx);
}
__device__ __forceinline__ void stsm4(uint32_t addr, uint32_t r0, uint32_t r1, uint32_t r2, uint32_t r3) {
  asm volatile("stmatrix.sync.aligned.m8n8.x4.shared.b16 [%0], {%1, %2, %3, %4};"
               ::"r"(addr), "r"(r0), "r"(r1), "r"(r2), "r"(r3) : "memory");
}

__device__ __forceinline__ uint4 ldsm4(uint32_t addr) {
  uint4 v;
  asm volatile("ldmatrix.sync.aligned.m8n8.x4.shared.b16 {%0, %1, %2, %3}, [%4];"
               : "=r"(v.x), "=r"(v.y), "=r"(v.z), "=r"(v.w) : "r"(addr) : "memory");
  return v;
}
__device__ __forceinline__ void red_add4(float* p, float a, float b, float c, float d) {
  asm volatile("red.global.add.v4.f32 [%0], {%1, %2, %3, %4};" ::"l"(p), "f"(a), "f"(b), "f"(c), "f"(d) : "memory");
}

__device__ __forceinline__ void mma_ss256(float (&d)[128], uint64_t descA, uint64_t descB) {
  asm volatile("wgmma.mma_async.sync.aligned.m64n256k16.f32.bf16.bf16 {"
      "%0, %1, %2, %3, %4, %5, %6, %7, %8, %9, %10, %11, %12, %13, %14, %15, "
      "%16, %17, %18, %19, %20, %21, %22, %23, %24, %25, %26, %27, %28, %29, %30, %31, "
      "%32, %33, %34, %35, %36, %37, %38, %39, %40, %41, %42, %43, %44, %45, %46, %47, "
      "%48, %49, %50, %51, %52, %53, %54, %55, %56, %57, %58, %59, %60, %61, %62, %63, "
      "%64, %65, %66, %67, %68, %69, %70, %71, %72, %73, %74, %75, %76, %77, %78, %79, "
      "%80, %81, %82, %83, %84, %85, %86, %87, %88, %89, %90, %91, %92, %93, %94, %95, "
      "%96, %97, %98, %99, %100, %101, %102, %103, %104, %105, %106, %107, %108, %109, %110, %111, "
      "%112, %113, %114, %115, %116, %117, %118, %119, %120, %121, %122, %123, %124, %125, %126, %127"
      "}, %128, %129, 1, 1, 1, 0, 1;\n"
      : "+f"(d[0]), "+f"(d[1]), "+f"(d[2]), "+f"(d[3]), "+f"(d[4]), "+f"(d[5]), "+f"(d[6]), "+f"(d[7]),
        "+f"(d[8]), "+f"(d[9]), "+f"(d[10]), "+f"(d[11]), "+f"(d[12]), "+f"(d[13]), "+f"(d[14]), "+f"(d[15]),
        "+f"(d[16]), "+f"(d[17]), "+f"(d[18]), "+f"(d[19]), "+f"(d[20]), "+f"(d[21]), "+f"(d[22]), "+f"(d[23]),
        "+f"(d[24]), "+f"(d[25]), "+f"(d[26]), "+f"(d[27]), "+f"(d[28]), "+f"(d[29]), "+f"(d[30]), "+f"(d[31]),
        "+f"(d[32]), "+f"(d[33]), "+f"(d[34]), "+f"(d[35]), "+f"(d[36]), "+f"(d[37]), "+f"(d[38]), "+f"(d[39]),
        "+f"(d[40]), "+f"(d[41]), "+f"(d[42]), "+f"(d[43]), "+f"(d[44]), "+f"(d[45]), "+f"(d[46]), "+f"(d[47]),
        "+f"(d[48]), "+f"(d[49]), "+f"(d[50]), "+f"(d[51]), "+f"(d[52]), "+f"(d[53]), "+f"(d[54]), "+f"(d[55]),
        "+f"(d[56]), "+f"(d[57]), "+f"(d[58]), "+f"(d[59]), "+f"(d[60]), "+f"(d[61]), "+f"(d[62]), "+f"(d[63]),
        "+f"(d[64]), "+f"(d[65]), "+f"(d[66]), "+f"(d[67]), "+f"(d[68]), "+f"(d[69]), "+f"(d[70]), "+f"(d[71]),
        "+f"(d[72]), "+f"(d[73]), "+f"(d[74]), "+f"(d[75]), "+f"(d[76]), "+f"(d[77]), "+f"(d[78]), "+f"(d[79]),
        "+f"(d[80]), "+f"(d[81]), "+f"(d[82]), "+f"(d[83]), "+f"(d[84]), "+f"(d[85]), "+f"(d[86]), "+f"(d[87]),
        "+f"(d[88]), "+f"(d[89]), "+f"(d[90]), "+f"(d[91]), "+f"(d[92]), "+f"(d[93]), "+f"(d[94]), "+f"(d[95]),
        "+f"(d[96]), "+f"(d[97]), "+f"(d[98]), "+f"(d[99]), "+f"(d[100]), "+f"(d[101]), "+f"(d[102]), "+f"(d[103]),
        "+f"(d[104]), "+f"(d[105]), "+f"(d[106]), "+f"(d[107]), "+f"(d[108]), "+f"(d[109]), "+f"(d[110]), "+f"(d[111]),
        "+f"(d[112]), "+f"(d[113]), "+f"(d[114]), "+f"(d[115]), "+f"(d[116]), "+f"(d[117]), "+f"(d[118]), "+f"(d[119]),
        "+f"(d[120]), "+f"(d[121]), "+f"(d[122]), "+f"(d[123]), "+f"(d[124]), "+f"(d[125]), "+f"(d[126]), "+f"(d[127])
      : "l"(descA), "l"(descB));
}
__device__ __forceinline__ void mma_ss256_p(float (&d)[128], uint64_t descA, uint64_t descB, int acc) {
  asm volatile("{\n.reg .pred p;\nsetp.ne.b32 p, %130, 0;\n"
      "wgmma.mma_async.sync.aligned.m64n256k16.f32.bf16.bf16 {"
      "%0, %1, %2, %3, %4, %5, %6, %7, %8, %9, %10, %11, %12, %13, %14, %15, "
      "%16, %17, %18, %19, %20, %21, %22, %23, %24, %25, %26, %27, %28, %29, %30, %31, "
      "%32, %33, %34, %35, %36, %37, %38, %39, %40, %41, %42, %43, %44, %45, %46, %47, "
      "%48, %49, %50, %51, %52, %53, %54, %55, %56, %57, %58, %59, %60, %61, %62, %63, "
      "%64, %65, %66, %67, %68, %69, %70, %71, %72, %73, %74, %75, %76, %77, %78, %79, "
      "%80, %81, %82, %83, %84, %85, %86, %87, %88, %89, %90, %91, %92, %93, %94, %95, "
      "%96, %97, %98, %99, %100, %101, %102, %103, %104, %105, %106, %107, %108, %109, %110, %111, "
      "%112, %113, %114, %115, %116, %117, %118, %119, %120, %121, %122, %123, %124, %125, %126, %127"
      "}, %128, %129, p, 1, 1, 0, 1;\n}\n"
      : "+f"(d[0]), "+f"(d[1]), "+f"(d[2]), "+f"(d[3]), "+f"(d[4]), "+f"(d[5]), "+f"(d[6]), "+f"(d[7]),
        "+f"(d[8]), "+f"(d[9]), "+f"(d[10]), "+f"(d[11]), "+f"(d[12]), "+f"(d[13]), "+f"(d[14]), "+f"(d[15]),
        "+f"(d[16]), "+f"(d[17]), "+f"(d[18]), "+f"(d[19]), "+f"(d[20]), "+f"(d[21]), "+f"(d[22]), "+f"(d[23]),
        "+f"(d[24]), "+f"(d[25]), "+f"(d[26]), "+f"(d[27]), "+f"(d[28]), "+f"(d[29]), "+f"(d[30]), "+f"(d[31]),
        "+f"(d[32]), "+f"(d[33]), "+f"(d[34]), "+f"(d[35]), "+f"(d[36]), "+f"(d[37]), "+f"(d[38]), "+f"(d[39]),
        "+f"(d[40]), "+f"(d[41]), "+f"(d[42]), "+f"(d[43]), "+f"(d[44]), "+f"(d[45]), "+f"(d[46]), "+f"(d[47]),
        "+f"(d[48]), "+f"(d[49]), "+f"(d[50]), "+f"(d[51]), "+f"(d[52]), "+f"(d[53]), "+f"(d[54]), "+f"(d[55]),
        "+f"(d[56]), "+f"(d[57]), "+f"(d[58]), "+f"(d[59]), "+f"(d[60]), "+f"(d[61]), "+f"(d[62]), "+f"(d[63]),
        "+f"(d[64]), "+f"(d[65]), "+f"(d[66]), "+f"(d[67]), "+f"(d[68]), "+f"(d[69]), "+f"(d[70]), "+f"(d[71]),
        "+f"(d[72]), "+f"(d[73]), "+f"(d[74]), "+f"(d[75]), "+f"(d[76]), "+f"(d[77]), "+f"(d[78]), "+f"(d[79]),
        "+f"(d[80]), "+f"(d[81]), "+f"(d[82]), "+f"(d[83]), "+f"(d[84]), "+f"(d[85]), "+f"(d[86]), "+f"(d[87]),
        "+f"(d[88]), "+f"(d[89]), "+f"(d[90]), "+f"(d[91]), "+f"(d[92]), "+f"(d[93]), "+f"(d[94]), "+f"(d[95]),
        "+f"(d[96]), "+f"(d[97]), "+f"(d[98]), "+f"(d[99]), "+f"(d[100]), "+f"(d[101]), "+f"(d[102]), "+f"(d[103]),
        "+f"(d[104]), "+f"(d[105]), "+f"(d[106]), "+f"(d[107]), "+f"(d[108]), "+f"(d[109]), "+f"(d[110]), "+f"(d[111]),
        "+f"(d[112]), "+f"(d[113]), "+f"(d[114]), "+f"(d[115]), "+f"(d[116]), "+f"(d[117]), "+f"(d[118]), "+f"(d[119]),
        "+f"(d[120]), "+f"(d[121]), "+f"(d[122]), "+f"(d[123]), "+f"(d[124]), "+f"(d[125]), "+f"(d[126]), "+f"(d[127])
      : "l"(descA), "l"(descB), "r"(acc));
}

__device__ __forceinline__ void mma_ss64(float (&d)[32], uint64_t descA, uint64_t descB) {
  asm volatile("wgmma.mma_async.sync.aligned.m64n64k16.f32.bf16.bf16 {"
      "%0, %1, %2, %3, %4, %5, %6, %7, %8, %9, %10, %11, %12, %13, %14, %15, "
      "%16, %17, %18, %19, %20, %21, %22, %23, %24, %25, %26, %27, %28, %29, %30, %31"
      "}, %32, %33, 1, 1, 1, 0, 1;\n"
      : "+f"(d[0]), "+f"(d[1]), "+f"(d[2]), "+f"(d[3]), "+f"(d[4]), "+f"(d[5]), "+f"(d[6]), "+f"(d[7]),
        "+f"(d[8]), "+f"(d[9]), "+f"(d[10]), "+f"(d[11]), "+f"(d[12]), "+f"(d[13]), "+f"(d[14]), "+f"(d[15]),
        "+f"(d[16]), "+f"(d[17]), "+f"(d[18]), "+f"(d[19]), "+f"(d[20]), "+f"(d[21]), "+f"(d[22]), "+f"(d[23]),
        "+f"(d[24]), "+f"(d[25]), "+f"(d[26]), "+f"(d[27]), "+f"(d[28]), "+f"(d[29]), "+f"(d[30]), "+f"(d[31])
      : "l"(descA), "l"(descB));
}
__device__ __forceinline__ void mma_ss64_p(float (&d)[32], uint64_t descA, uint64_t descB, int acc) {
  asm volatile("{\n.reg .pred p;\nsetp.ne.b32 p, %34, 0;\n"
      "wgmma.mma_async.sync.aligned.m64n64k16.f32.bf16.bf16 {"
      "%0, %1, %2, %3, %4, %5, %6, %7, %8, %9, %10, %11, %12, %13, %14, %15, "
      "%16, %17, %18, %19, %20, %21, %22, %23, %24, %25, %26, %27, %28, %29, %30, %31"
      "}, %32, %33, p, 1, 1, 0, 1;\n}\n"
      : "+f"(d[0]), "+f"(d[1]), "+f"(d[2]), "+f"(d[3]), "+f"(d[4]), "+f"(d[5]), "+f"(d[6]), "+f"(d[7]),
        "+f"(d[8]), "+f"(d[9]), "+f"(d[10]), "+f"(d[11]), "+f"(d[12]), "+f"(d[13]), "+f"(d[14]), "+f"(d[15]),
        "+f"(d[16]), "+f"(d[17]), "+f"(d[18]), "+f"(d[19]), "+f"(d[20]), "+f"(d[21]), "+f"(d[22]), "+f"(d[23]),
        "+f"(d[24]), "+f"(d[25]), "+f"(d[26]), "+f"(d[27]), "+f"(d[28]), "+f"(d[29]), "+f"(d[30]), "+f"(d[31])
      : "l"(descA), "l"(descB), "r"(acc));
}

__device__ __forceinline__ void mma_ss96(float (&d)[48], uint64_t descA, uint64_t descB) {
  asm volatile("wgmma.mma_async.sync.aligned.m64n96k16.f32.bf16.bf16 {"
      "%0, %1, %2, %3, %4, %5, %6, %7, %8, %9, %10, %11, %12, %13, %14, %15, "
      "%16, %17, %18, %19, %20, %21, %22, %23, %24, %25, %26, %27, %28, %29, %30, %31, "
      "%32, %33, %34, %35, %36, %37, %38, %39, %40, %41, %42, %43, %44, %45, %46, %47"
      "}, %48, %49, 1, 1, 1, 0, 1;\n"
      : "+f"(d[0]), "+f"(d[1]), "+f"(d[2]), "+f"(d[3]), "+f"(d[4]), "+f"(d[5]), "+f"(d[6]), "+f"(d[7]),
        "+f"(d[8]), "+f"(d[9]), "+f"(d[10]), "+f"(d[11]), "+f"(d[12]), "+f"(d[13]), "+f"(d[14]), "+f"(d[15]),
        "+f"(d[16]), "+f"(d[17]), "+f"(d[18]), "+f"(d[19]), "+f"(d[20]), "+f"(d[21]), "+f"(d[22]), "+f"(d[23]),
        "+f"(d[24]), "+f"(d[25]), "+f"(d[26]), "+f"(d[27]), "+f"(d[28]), "+f"(d[29]), "+f"(d[30]), "+f"(d[31]),
        "+f"(d[32]), "+f"(d[33]), "+f"(d[34]), "+f"(d[35]), "+f"(d[36]), "+f"(d[37]), "+f"(d[38]), "+f"(d[39]),
        "+f"(d[40]), "+f"(d[41]), "+f"(d[42]), "+f"(d[43]), "+f"(d[44]), "+f"(d[45]), "+f"(d[46]), "+f"(d[47])
      : "l"(descA), "l"(descB));
}
__device__ __forceinline__ void mma_ss96_z(float (&d)[48], uint64_t descA, uint64_t descB) {
  asm volatile("wgmma.mma_async.sync.aligned.m64n96k16.f32.bf16.bf16 {"
      "%0, %1, %2, %3, %4, %5, %6, %7, %8, %9, %10, %11, %12, %13, %14, %15, "
      "%16, %17, %18, %19, %20, %21, %22, %23, %24, %25, %26, %27, %28, %29, %30, %31, "
      "%32, %33, %34, %35, %36, %37, %38, %39, %40, %41, %42, %43, %44, %45, %46, %47"
      "}, %48, %49, 0, 1, 1, 0, 1;\n"
      : "=f"(d[0]), "=f"(d[1]), "=f"(d[2]), "=f"(d[3]), "=f"(d[4]), "=f"(d[5]), "=f"(d[6]), "=f"(d[7]),
        "=f"(d[8]), "=f"(d[9]), "=f"(d[10]), "=f"(d[11]), "=f"(d[12]), "=f"(d[13]), "=f"(d[14]), "=f"(d[15]),
        "=f"(d[16]), "=f"(d[17]), "=f"(d[18]), "=f"(d[19]), "=f"(d[20]), "=f"(d[21]), "=f"(d[22]), "=f"(d[23]),
        "=f"(d[24]), "=f"(d[25]), "=f"(d[26]), "=f"(d[27]), "=f"(d[28]), "=f"(d[29]), "=f"(d[30]), "=f"(d[31]),
        "=f"(d[32]), "=f"(d[33]), "=f"(d[34]), "=f"(d[35]), "=f"(d[36]), "=f"(d[37]), "=f"(d[38]), "=f"(d[39]),
        "=f"(d[40]), "=f"(d[41]), "=f"(d[42]), "=f"(d[43]), "=f"(d[44]), "=f"(d[45]), "=f"(d[46]), "=f"(d[47])
      : "l"(descA), "l"(descB));
}

__device__ __forceinline__ void mma_ss64b(float (&d)[32], uint64_t descA, uint64_t descB) {
  asm volatile("wgmma.mma_async.sync.aligned.m64n64k16.f32.bf16.bf16 {"
      "%0, %1, %2, %3, %4, %5, %6, %7, %8, %9, %10, %11, %12, %13, %14, %15, "
      "%16, %17, %18, %19, %20, %21, %22, %23, %24, %25, %26, %27, %28, %29, %30, %31"
      "}, %32, %33, 1, 1, 1, 0, 1;\n"
      : "+f"(d[0]), "+f"(d[1]), "+f"(d[2]), "+f"(d[3]), "+f"(d[4]), "+f"(d[5]), "+f"(d[6]), "+f"(d[7]),
        "+f"(d[8]), "+f"(d[9]), "+f"(d[10]), "+f"(d[11]), "+f"(d[12]), "+f"(d[13]), "+f"(d[14]), "+f"(d[15]),
        "+f"(d[16]), "+f"(d[17]), "+f"(d[18]), "+f"(d[19]), "+f"(d[20]), "+f"(d[21]), "+f"(d[22]), "+f"(d[23]),
        "+f"(d[24]), "+f"(d[25]), "+f"(d[26]), "+f"(d[27]), "+f"(d[28]), "+f"(d[29]), "+f"(d[30]), "+f"(d[31])
      : "l"(descA), "l"(descB));
}
__device__ __forceinline__ void mma_ss64b_z(float (&d)[32], uint64_t descA, uint64_t descB) {
  asm volatile("wgmma.mma_async.sync.aligned.m64n64k16.f32.bf16.bf16 {"
      "%0, %1, %2, %3, %4, %5, %6, %7, %8, %9, %10, %11, %12, %13, %14, %15, "
      "%16, %17, %18, %19, %20, %21, %22, %23, %24, %25, %26, %27, %28, %29, %30, %31"
      "}, %32, %33, 0, 1, 1, 0, 1;\n"
      : "=f"(d[0]), "=f"(d[1]), "=f"(d[2]), "=f"(d[3]), "=f"(d[4]), "=f"(d[5]), "=f"(d[6]), "=f"(d[7]),
        "=f"(d[8]), "=f"(d[9]), "=f"(d[10]), "=f"(d[11]), "=f"(d[12]), "=f"(d[13]), "=f"(d[14]), "=f"(d[15]),
        "=f"(d[16]), "=f"(d[17]), "=f"(d[18]), "=f"(d[19]), "=f"(d[20]), "=f"(d[21]), "=f"(d[22]), "=f"(d[23]),
        "=f"(d[24]), "=f"(d[25]), "=f"(d[26]), "=f"(d[27]), "=f"(d[28]), "=f"(d[29]), "=f"(d[30]), "=f"(d[31])
      : "l"(descA), "l"(descB));
}

__device__ __forceinline__ void mma_ss192(float (&d)[96], uint64_t descA, uint64_t descB) {
  asm volatile("wgmma.mma_async.sync.aligned.m64n192k16.f32.bf16.bf16 {"
      "%0, %1, %2, %3, %4, %5, %6, %7, %8, %9, %10, %11, %12, %13, %14, %15, "
      "%16, %17, %18, %19, %20, %21, %22, %23, %24, %25, %26, %27, %28, %29, %30, %31, "
      "%32, %33, %34, %35, %36, %37, %38, %39, %40, %41, %42, %43, %44, %45, %46, %47, "
      "%48, %49, %50, %51, %52, %53, %54, %55, %56, %57, %58, %59, %60, %61, %62, %63, "
      "%64, %65, %66, %67, %68, %69, %70, %71, %72, %73, %74, %75, %76, %77, %78, %79, "
      "%80, %81, %82, %83, %84, %85, %86, %87, %88, %89, %90, %91, %92, %93, %94, %95"
      "}, %96, %97, 1, 1, 1, 0, 1;\n"
      : "+f"(d[0]), "+f"(d[1]), "+f"(d[2]), "+f"(d[3]), "+f"(d[4]), "+f"(d[5]), "+f"(d[6]), "+f"(d[7]),
        "+f"(d[8]), "+f"(d[9]), "+f"(d[10]), "+f"(d[11]), "+f"(d[12]), "+f"(d[13]), "+f"(d[14]), "+f"(d[15]),
        "+f"(d[16]), "+f"(d[17]), "+f"(d[18]), "+f"(d[19]), "+f"(d[20]), "+f"(d[21]), "+f"(d[22]), "+f"(d[23]),
        "+f"(d[24]), "+f"(d[25]), "+f"(d[26]), "+f"(d[27]), "+f"(d[28]), "+f"(d[29]), "+f"(d[30]), "+f"(d[31]),
        "+f"(d[32]), "+f"(d[33]), "+f"(d[34]), "+f"(d[35]), "+f"(d[36]), "+f"(d[37]), "+f"(d[38]), "+f"(d[39]),
        "+f"(d[40]), "+f"(d[41]), "+f"(d[42]), "+f"(d[43]), "+f"(d[44]), "+f"(d[45]), "+f"(d[46]), "+f"(d[47]),
        "+f"(d[48]), "+f"(d[49]), "+f"(d[50]), "+f"(d[51]), "+f"(d[52]), "+f"(d[53]), "+f"(d[54]), "+f"(d[55]),
        "+f"(d[56]), "+f"(d[57]), "+f"(d[58]), "+f"(d[59]), "+f"(d[60]), "+f"(d[61]), "+f"(d[62]), "+f"(d[63]),
        "+f"(d[64]), "+f"(d[65]), "+f"(d[66]), "+f"(d[67]), "+f"(d[68]), "+f"(d[69]), "+f"(d[70]), "+f"(d[71]),
        "+f"(d[72]), "+f"(d[73]), "+f"(d[74]), "+f"(d[75]), "+f"(d[76]), "+f"(d[77]), "+f"(d[78]), "+f"(d[79]),
        "+f"(d[80]), "+f"(d[81]), "+f"(d[82]), "+f"(d[83]), "+f"(d[84]), "+f"(d[85]), "+f"(d[86]), "+f"(d[87]),
        "+f"(d[88]), "+f"(d[89]), "+f"(d[90]), "+f"(d[91]), "+f"(d[92]), "+f"(d[93]), "+f"(d[94]), "+f"(d[95])
      : "l"(descA), "l"(descB));
}
__device__ __forceinline__ void mma_ss192_p(float (&d)[96], uint64_t descA, uint64_t descB, int acc) {
  asm volatile("{\n.reg .pred p;\nsetp.ne.b32 p, %98, 0;\n"
      "wgmma.mma_async.sync.aligned.m64n192k16.f32.bf16.bf16 {"
      "%0, %1, %2, %3, %4, %5, %6, %7, %8, %9, %10, %11, %12, %13, %14, %15, "
      "%16, %17, %18, %19, %20, %21, %22, %23, %24, %25, %26, %27, %28, %29, %30, %31, "
      "%32, %33, %34, %35, %36, %37, %38, %39, %40, %41, %42, %43, %44, %45, %46, %47, "
      "%48, %49, %50, %51, %52, %53, %54, %55, %56, %57, %58, %59, %60, %61, %62, %63, "
      "%64, %65, %66, %67, %68, %69, %70, %71, %72, %73, %74, %75, %76, %77, %78, %79, "
      "%80, %81, %82, %83, %84, %85, %86, %87, %88, %89, %90, %91, %92, %93, %94, %95"
      "}, %96, %97, p, 1, 1, 0, 1;\n}\n"
      : "+f"(d[0]), "+f"(d[1]), "+f"(d[2]), "+f"(d[3]), "+f"(d[4]), "+f"(d[5]), "+f"(d[6]), "+f"(d[7]),
        "+f"(d[8]), "+f"(d[9]), "+f"(d[10]), "+f"(d[11]), "+f"(d[12]), "+f"(d[13]), "+f"(d[14]), "+f"(d[15]),
        "+f"(d[16]), "+f"(d[17]), "+f"(d[18]), "+f"(d[19]), "+f"(d[20]), "+f"(d[21]), "+f"(d[22]), "+f"(d[23]),
        "+f"(d[24]), "+f"(d[25]), "+f"(d[26]), "+f"(d[27]), "+f"(d[28]), "+f"(d[29]), "+f"(d[30]), "+f"(d[31]),
        "+f"(d[32]), "+f"(d[33]), "+f"(d[34]), "+f"(d[35]), "+f"(d[36]), "+f"(d[37]), "+f"(d[38]), "+f"(d[39]),
        "+f"(d[40]), "+f"(d[41]), "+f"(d[42]), "+f"(d[43]), "+f"(d[44]), "+f"(d[45]), "+f"(d[46]), "+f"(d[47]),
        "+f"(d[48]), "+f"(d[49]), "+f"(d[50]), "+f"(d[51]), "+f"(d[52]), "+f"(d[53]), "+f"(d[54]), "+f"(d[55]),
        "+f"(d[56]), "+f"(d[57]), "+f"(d[58]), "+f"(d[59]), "+f"(d[60]), "+f"(d[61]), "+f"(d[62]), "+f"(d[63]),
        "+f"(d[64]), "+f"(d[65]), "+f"(d[66]), "+f"(d[67]), "+f"(d[68]), "+f"(d[69]), "+f"(d[70]), "+f"(d[71]),
        "+f"(d[72]), "+f"(d[73]), "+f"(d[74]), "+f"(d[75]), "+f"(d[76]), "+f"(d[77]), "+f"(d[78]), "+f"(d[79]),
        "+f"(d[80]), "+f"(d[81]), "+f"(d[82]), "+f"(d[83]), "+f"(d[84]), "+f"(d[85]), "+f"(d[86]), "+f"(d[87]),
        "+f"(d[88]), "+f"(d[89]), "+f"(d[90]), "+f"(d[91]), "+f"(d[92]), "+f"(d[93]), "+f"(d[94]), "+f"(d[95])
      : "l"(descA), "l"(descB), "r"(acc));
}

__device__ __forceinline__ void mma_ss80_tt(float (&d)[40], uint64_t descA, uint64_t descB) {
  asm volatile("wgmma.mma_async.sync.aligned.m64n80k16.f32.bf16.bf16 {"
      "%0, %1, %2, %3, %4, %5, %6, %7, %8, %9, %10, %11, %12, %13, %14, %15, "
      "%16, %17, %18, %19, %20, %21, %22, %23, %24, %25, %26, %27, %28, %29, %30, %31, "
      "%32, %33, %34, %35, %36, %37, %38, %39"
      "}, %40, %41, 1, 1, 1, 1, 1;\n"
      : "+f"(d[0]), "+f"(d[1]), "+f"(d[2]), "+f"(d[3]), "+f"(d[4]), "+f"(d[5]), "+f"(d[6]), "+f"(d[7]),
        "+f"(d[8]), "+f"(d[9]), "+f"(d[10]), "+f"(d[11]), "+f"(d[12]), "+f"(d[13]), "+f"(d[14]), "+f"(d[15]),
        "+f"(d[16]), "+f"(d[17]), "+f"(d[18]), "+f"(d[19]), "+f"(d[20]), "+f"(d[21]), "+f"(d[22]), "+f"(d[23]),
        "+f"(d[24]), "+f"(d[25]), "+f"(d[26]), "+f"(d[27]), "+f"(d[28]), "+f"(d[29]), "+f"(d[30]), "+f"(d[31]),
        "+f"(d[32]), "+f"(d[33]), "+f"(d[34]), "+f"(d[35]), "+f"(d[36]), "+f"(d[37]), "+f"(d[38]), "+f"(d[39])
      : "l"(descA), "l"(descB));
}
__device__ __forceinline__ void mma_ss80_tt_z(float (&d)[40], uint64_t descA, uint64_t descB) {
  asm volatile("wgmma.mma_async.sync.aligned.m64n80k16.f32.bf16.bf16 {"
      "%0, %1, %2, %3, %4, %5, %6, %7, %8, %9, %10, %11, %12, %13, %14, %15, "
      "%16, %17, %18, %19, %20, %21, %22, %23, %24, %25, %26, %27, %28, %29, %30, %31, "
      "%32, %33, %34, %35, %36, %37, %38, %39"
      "}, %40, %41, 0, 1, 1, 1, 1;\n"
      : "=f"(d[0]), "=f"(d[1]), "=f"(d[2]), "=f"(d[3]), "=f"(d[4]), "=f"(d[5]), "=f"(d[6]), "=f"(d[7]),
        "=f"(d[8]), "=f"(d[9]), "=f"(d[10]), "=f"(d[11]), "=f"(d[12]), "=f"(d[13]), "=f"(d[14]), "=f"(d[15]),
        "=f"(d[16]), "=f"(d[17]), "=f"(d[18]), "=f"(d[19]), "=f"(d[20]), "=f"(d[21]), "=f"(d[22]), "=f"(d[23]),
        "=f"(d[24]), "=f"(d[25]), "=f"(d[26]), "=f"(d[27]), "=f"(d[28]), "=f"(d[29]), "=f"(d[30]), "=f"(d[31]),
        "=f"(d[32]), "=f"(d[33]), "=f"(d[34]), "=f"(d[35]), "=f"(d[36]), "=f"(d[37]), "=f"(d[38]), "=f"(d[39])
      : "l"(descA), "l"(descB));
}

__device__ __forceinline__ void mma_rs80_k(float (&d)[40], const uint32_t (&a)[4], uint64_t descB) {
  asm volatile("wgmma.mma_async.sync.aligned.m64n80k16.f32.bf16.bf16 {"
      "%0, %1, %2, %3, %4, %5, %6, %7, %8, %9, %10, %11, %12, %13, %14, %15, "
      "%16, %17, %18, %19, %20, %21, %22, %23, %24, %25, %26, %27, %28, %29, %30, %31, "
      "%32, %33, %34, %35, %36, %37, %38, %39"
      "}, {%40, %41, %42, %43}, %44, 1, 1, 1, 0;\n"
      : "+f"(d[0]), "+f"(d[1]), "+f"(d[2]), "+f"(d[3]), "+f"(d[4]), "+f"(d[5]), "+f"(d[6]), "+f"(d[7]),
        "+f"(d[8]), "+f"(d[9]), "+f"(d[10]), "+f"(d[11]), "+f"(d[12]), "+f"(d[13]), "+f"(d[14]), "+f"(d[15]),
        "+f"(d[16]), "+f"(d[17]), "+f"(d[18]), "+f"(d[19]), "+f"(d[20]), "+f"(d[21]), "+f"(d[22]), "+f"(d[23]),
        "+f"(d[24]), "+f"(d[25]), "+f"(d[26]), "+f"(d[27]), "+f"(d[28]), "+f"(d[29]), "+f"(d[30]), "+f"(d[31]),
        "+f"(d[32]), "+f"(d[33]), "+f"(d[34]), "+f"(d[35]), "+f"(d[36]), "+f"(d[37]), "+f"(d[38]), "+f"(d[39])
      : "r"(a[0]), "r"(a[1]), "r"(a[2]), "r"(a[3]), "l"(descB));
}
__device__ __forceinline__ void mma_rs80_k_z(float (&d)[40], const uint32_t (&a)[4], uint64_t descB) {
  asm volatile("wgmma.mma_async.sync.aligned.m64n80k16.f32.bf16.bf16 {"
      "%0, %1, %2, %3, %4, %5, %6, %7, %8, %9, %10, %11, %12, %13, %14, %15, "
      "%16, %17, %18, %19, %20, %21, %22, %23, %24, %25, %26, %27, %28, %29, %30, %31, "
      "%32, %33, %34, %35, %36, %37, %38, %39"
      "}, {%40, %41, %42, %43}, %44, 0, 1, 1, 0;\n"
      : "=f"(d[0]), "=f"(d[1]), "=f"(d[2]), "=f"(d[3]), "=f"(d[4]), "=f"(d[5]), "=f"(d[6]), "=f"(d[7]),
        "=f"(d[8]), "=f"(d[9]), "=f"(d[10]), "=f"(d[11]), "=f"(d[12]), "=f"(d[13]), "=f"(d[14]), "=f"(d[15]),
        "=f"(d[16]), "=f"(d[17]), "=f"(d[18]), "=f"(d[19]), "=f"(d[20]), "=f"(d[21]), "=f"(d[22]), "=f"(d[23]),
        "=f"(d[24]), "=f"(d[25]), "=f"(d[26]), "=f"(d[27]), "=f"(d[28]), "=f"(d[29]), "=f"(d[30]), "=f"(d[31]),
        "=f"(d[32]), "=f"(d[33]), "=f"(d[34]), "=f"(d[35]), "=f"(d[36]), "=f"(d[37]), "=f"(d[38]), "=f"(d[39])
      : "r"(a[0]), "r"(a[1]), "r"(a[2]), "r"(a[3]), "l"(descB));
}

__device__ __forceinline__ void mma_rs48_k(float (&d)[24], const uint32_t (&a)[4], uint64_t descB) {
  asm volatile("wgmma.mma_async.sync.aligned.m64n48k16.f32.bf16.bf16 {"
      "%0, %1, %2, %3, %4, %5, %6, %7, %8, %9, %10, %11, %12, %13, %14, %15, "
      "%16, %17, %18, %19, %20, %21, %22, %23"
      "}, {%24, %25, %26, %27}, %28, 1, 1, 1, 0;\n"
      : "+f"(d[0]), "+f"(d[1]), "+f"(d[2]), "+f"(d[3]), "+f"(d[4]), "+f"(d[5]), "+f"(d[6]), "+f"(d[7]),
        "+f"(d[8]), "+f"(d[9]), "+f"(d[10]), "+f"(d[11]), "+f"(d[12]), "+f"(d[13]), "+f"(d[14]), "+f"(d[15]),
        "+f"(d[16]), "+f"(d[17]), "+f"(d[18]), "+f"(d[19]), "+f"(d[20]), "+f"(d[21]), "+f"(d[22]), "+f"(d[23])
      : "r"(a[0]), "r"(a[1]), "r"(a[2]), "r"(a[3]), "l"(descB));
}
__device__ __forceinline__ void mma_rs48_k_z(float (&d)[24], const uint32_t (&a)[4], uint64_t descB) {
  asm volatile("wgmma.mma_async.sync.aligned.m64n48k16.f32.bf16.bf16 {"
      "%0, %1, %2, %3, %4, %5, %6, %7, %8, %9, %10, %11, %12, %13, %14, %15, "
      "%16, %17, %18, %19, %20, %21, %22, %23"
      "}, {%24, %25, %26, %27}, %28, 0, 1, 1, 0;\n"
      : "=f"(d[0]), "=f"(d[1]), "=f"(d[2]), "=f"(d[3]), "=f"(d[4]), "=f"(d[5]), "=f"(d[6]), "=f"(d[7]),
        "=f"(d[8]), "=f"(d[9]), "=f"(d[10]), "=f"(d[11]), "=f"(d[12]), "=f"(d[13]), "=f"(d[14]), "=f"(d[15]),
        "=f"(d[16]), "=f"(d[17]), "=f"(d[18]), "=f"(d[19]), "=f"(d[20]), "=f"(d[21]), "=f"(d[22]), "=f"(d[23])
      : "r"(a[0]), "r"(a[1]), "r"(a[2]), "r"(a[3]), "l"(descB));
}

__device__ __forceinline__ void mma_rs160_n(float (&d)[80], const uint32_t (&a)[4], uint64_t descB) {
  asm volatile("wgmma.mma_async.sync.aligned.m64n160k16.f32.bf16.bf16 {"
      "%0, %1, %2, %3, %4, %5, %6, %7, %8, %9, %10, %11, %12, %13, %14, %15, "
      "%16, %17, %18, %19, %20, %21, %22, %23, %24, %25, %26, %27, %28, %29, %30, %31, "
      "%32, %33, %34, %35, %36, %37, %38, %39, %40, %41, %42, %43, %44, %45, %46, %47, "
      "%48, %49, %50, %51, %52, %53, %54, %55, %56, %57, %58, %59, %60, %61, %62, %63, "
      "%64, %65, %66, %67, %68, %69, %70, %71, %72, %73, %74, %75, %76, %77, %78, %79"
      "}, {%80, %81, %82, %83}, %84, 1, 1, 1, 1;\n"
      : "+f"(d[0]), "+f"(d[1]), "+f"(d[2]), "+f"(d[3]), "+f"(d[4]), "+f"(d[5]), "+f"(d[6]), "+f"(d[7]),
        "+f"(d[8]), "+f"(d[9]), "+f"(d[10]), "+f"(d[11]), "+f"(d[12]), "+f"(d[13]), "+f"(d[14]), "+f"(d[15]),
        "+f"(d[16]), "+f"(d[17]), "+f"(d[18]), "+f"(d[19]), "+f"(d[20]), "+f"(d[21]), "+f"(d[22]), "+f"(d[23]),
        "+f"(d[24]), "+f"(d[25]), "+f"(d[26]), "+f"(d[27]), "+f"(d[28]), "+f"(d[29]), "+f"(d[30]), "+f"(d[31]),
        "+f"(d[32]), "+f"(d[33]), "+f"(d[34]), "+f"(d[35]), "+f"(d[36]), "+f"(d[37]), "+f"(d[38]), "+f"(d[39]),
        "+f"(d[40]), "+f"(d[41]), "+f"(d[42]), "+f"(d[43]), "+f"(d[44]), "+f"(d[45]), "+f"(d[46]), "+f"(d[47]),
        "+f"(d[48]), "+f"(d[49]), "+f"(d[50]), "+f"(d[51]), "+f"(d[52]), "+f"(d[53]), "+f"(d[54]), "+f"(d[55]),
        "+f"(d[56]), "+f"(d[57]), "+f"(d[58]), "+f"(d[59]), "+f"(d[60]), "+f"(d[61]), "+f"(d[62]), "+f"(d[63]),
        "+f"(d[64]), "+f"(d[65]), "+f"(d[66]), "+f"(d[67]), "+f"(d[68]), "+f"(d[69]), "+f"(d[70]), "+f"(d[71]),
        "+f"(d[72]), "+f"(d[73]), "+f"(d[74]), "+f"(d[75]), "+f"(d[76]), "+f"(d[77]), "+f"(d[78]), "+f"(d[79])
      : "r"(a[0]), "r"(a[1]), "r"(a[2]), "r"(a[3]), "l"(descB));
}
__device__ __forceinline__ void mma_rs160_n_z(float (&d)[80], const uint32_t (&a)[4], uint64_t descB) {
  asm volatile("wgmma.mma_async.sync.aligned.m64n160k16.f32.bf16.bf16 {"
      "%0, %1, %2, %3, %4, %5, %6, %7, %8, %9, %10, %11, %12, %13, %14, %15, "
      "%16, %17, %18, %19, %20, %21, %22, %23, %24, %25, %26, %27, %28, %29, %30, %31, "
      "%32, %33, %34, %35, %36, %37, %38, %39, %40, %41, %42, %43, %44, %45, %46, %47, "
      "%48, %49, %50, %51, %52, %53, %54, %55, %56, %57, %58, %59, %60, %61, %62, %63, "
      "%64, %65, %66, %67, %68, %69, %70, %71, %72, %73, %74, %75, %76, %77, %78, %79"
      "}, {%80, %81, %82, %83}, %84, 0, 1, 1, 1;\n"
      : "=f"(d[0]), "=f"(d[1]), "=f"(d[2]), "=f"(d[3]), "=f"(d[4]), "=f"(d[5]), "=f"(d[6]), "=f"(d[7]),
        "=f"(d[8]), "=f"(d[9]), "=f"(d[10]), "=f"(d[11]), "=f"(d[12]), "=f"(d[13]), "=f"(d[14]), "=f"(d[15]),
        "=f"(d[16]), "=f"(d[17]), "=f"(d[18]), "=f"(d[19]), "=f"(d[20]), "=f"(d[21]), "=f"(d[22]), "=f"(d[23]),
        "=f"(d[24]), "=f"(d[25]), "=f"(d[26]), "=f"(d[27]), "=f"(d[28]), "=f"(d[29]), "=f"(d[30]), "=f"(d[31]),
        "=f"(d[32]), "=f"(d[33]), "=f"(d[34]), "=f"(d[35]), "=f"(d[36]), "=f"(d[37]), "=f"(d[38]), "=f"(d[39]),
        "=f"(d[40]), "=f"(d[41]), "=f"(d[42]), "=f"(d[43]), "=f"(d[44]), "=f"(d[45]), "=f"(d[46]), "=f"(d[47]),
        "=f"(d[48]), "=f"(d[49]), "=f"(d[50]), "=f"(d[51]), "=f"(d[52]), "=f"(d[53]), "=f"(d[54]), "=f"(d[55]),
        "=f"(d[56]), "=f"(d[57]), "=f"(d[58]), "=f"(d[59]), "=f"(d[60]), "=f"(d[61]), "=f"(d[62]), "=f"(d[63]),
        "=f"(d[64]), "=f"(d[65]), "=f"(d[66]), "=f"(d[67]), "=f"(d[68]), "=f"(d[69]), "=f"(d[70]), "=f"(d[71]),
        "=f"(d[72]), "=f"(d[73]), "=f"(d[74]), "=f"(d[75]), "=f"(d[76]), "=f"(d[77]), "=f"(d[78]), "=f"(d[79])
      : "r"(a[0]), "r"(a[1]), "r"(a[2]), "r"(a[3]), "l"(descB));
}

__device__ __forceinline__ void feature_map(const uint32_t (&P)[2][10], uint32_t (&fr)[10][4]) {
  constexpr float L2E = 1.4426950408889634f;
#pragma unroll
  for (int p = 0; p < 2; p++) {
#pragma unroll
    for (int r = 0; r < 2; r++) {
      uint32_t mx = P[r][5 * p], mn = mx;
#pragma unroll
      for (int g = 1; g < 5; g++) { mx = max_bf2(mx, P[r][5 * p + g]); mn = min_bf2(mn, P[r][5 * p + g]); }
      mx = max_bf2(mx, __shfl_xor_sync(0xffffffffu, mx, 1));
      mn = min_bf2(mn, __shfl_xor_sync(0xffffffffu, mn, 1));
      mx = max_bf2(mx, __shfl_xor_sync(0xffffffffu, mx, 2));
      mn = min_bf2(mn, __shfl_xor_sync(0xffffffffu, mn, 2));
      float mx0 = -bf_lo(mx) * L2E, mx1 = -bf_hi(mx) * L2E, mn0 = bf_lo(mn) * L2E, mn1 = bf_hi(mn) * L2E;
      float ep0[5], ep1[5], en0[5], en1[5];
      float sp0 = 0.f, sp1 = 0.f, sn0 = 0.f, sn1 = 0.f;
#pragma unroll
      for (int g = 0; g < 5; g++) {
        float x0 = bf_lo(P[r][5 * p + g]), x1 = bf_hi(P[r][5 * p + g]);
        ep0[g] = ex2(fmaf(x0, L2E, mx0)); ep1[g] = ex2(fmaf(x1, L2E, mx1));
        en0[g] = ex2(fmaf(x0, -L2E, mn0)); en1[g] = ex2(fmaf(x1, -L2E, mn1));
        sp0 += ep0[g]; sp1 += ep1[g]; sn0 += en0[g]; sn1 += en1[g];
      }
      sp0 += __shfl_xor_sync(0xffffffffu, sp0, 1); sp1 += __shfl_xor_sync(0xffffffffu, sp1, 1);
      sn0 += __shfl_xor_sync(0xffffffffu, sn0, 1); sn1 += __shfl_xor_sync(0xffffffffu, sn1, 1);
      sp0 += __shfl_xor_sync(0xffffffffu, sp0, 2); sp1 += __shfl_xor_sync(0xffffffffu, sp1, 2);
      sn0 += __shfl_xor_sync(0xffffffffu, sn0, 2); sn1 += __shfl_xor_sync(0xffffffffu, sn1, 2);
      {
        const float pp = sp0 * sp1, nn = sn0 * sn1, rr = rcp(pp * nn), rp = rr * nn, rn = rr * pp;
        const float a = rp * sp1, b = rp * sp0, c = rn * sn1, d = rn * sn0;
        sp0 = a; sp1 = b; sn0 = c; sn1 = d;
      }
#pragma unroll
      for (int g = 0; g < 5; g++) {
        fr[5 * p + g][r] = pack_bf16(ep0[g] * sp0, ep1[g] * sp1);
        fr[5 * p + g][2 + r] = pack_bf16(en0[g] * sn0, en1[g] * sn1);
      }
    }
  }
}

template <int V> struct IntC { static constexpr int value = V; };
struct Ring {
  uint32_t idx, phase;
  template <int N> __device__ __forceinline__ void next() { if (++idx == N) { idx = 0; phase ^= 1; } }
};

}

__global__ void __cluster_dims__(2, 1, 1) __launch_bounds__(384, 1)
fused_kernel(const __grid_constant__ Maps maps, const __nv_bfloat16* __restrict__ x, const __nv_bfloat16* __restrict__ wqkv,
             const __nv_bfloat16* __restrict__ wphi, const __nv_bfloat16* __restrict__ w1, const __nv_bfloat16* __restrict__ w2,
             const __nv_bfloat16* __restrict__ w3, const __nv_bfloat16* __restrict__ w4, const __nv_bfloat16* __restrict__ wo,
             const __nv_bfloat16* __restrict__ gate_w, __nv_bfloat16* __restrict__ out) {
  extern __shared__ __align__(1024) uint8_t sgen[];
  const uint32_t sb = smem_u32(sgen);
  const uint32_t sb16 = (sb & 0x3FFFFu) >> 4;
  const uint32_t bars = sb + OFF_BAR;
  const uint32_t fullA = bars + 8 * B_FULLA, emptyA = bars + 8 * B_EMPTYA, fullB = bars + 8 * B_FULLB, emptyB = bars + 8 * B_EMPTYB;

  const int tid = threadIdx.x;
  const int rank = blockIdx.x & 1;
  const int bid = blockIdx.x - NSVC, pairIdx = bid >> 1;
  const int i = pairIdx >> 2, j = 2 * (pairIdx & 3) + rank;
  const int k3 = (5 * (pairIdx & 3) + 1) >> 1;

  if (bid < 0) {
    const int sv = blockIdx.x;
    const unsigned epoch = *reinterpret_cast<volatile unsigned*>(g_flags + FL_DONE * 32) / NCTA;
    if (tid == 0) {
#pragma unroll
      for (int b = 0; b < 11; b++) mbar_init(bars + 8 * b, 1);
      mbar_expect_tx(bars + 80, 6400);
      bulk_load(sb + 204800, wphi + sv * 3200, 6400, bars + 80);
    }
    __syncthreads();
    float a[8];
#pragma unroll 1
    for (int rd = 0; rd < 4; rd++) {
      const int nch = rd ? 192 : 80, nth = rd ? 384 : 320, piece = rd ? 18432 : 20480, np = rd == 3 ? 7 : 10;
      if (tid == 0) {
        const char* src = reinterpret_cast<const char*>(rd ? w3 + (size_t)(160 * sv + 60 * (rd - 1)) * F_ : w1 + (size_t)160 * sv * D_);
#pragma unroll 1
        for (int p = 0; p < np; p++) {
          const int bytes = (rd == 3 && p == 6) ? 12288 : piece;
          mbar_expect_tx(bars + 8 * p, bytes);
          bulk_load(sb + p * piece, src + p * piece, bytes, bars + 8 * p);
        }
      }
      if (rd == 0) {
        if (tid < 40 && (tid < 20 || sv >= 2))
          reinterpret_cast<uint4*>(g_Hs + (size_t)(2 + ((sv & 1) ? S_ - 1 - tid / 20 : tid / 20)) * D_ + 160 * sv)[tid % 20] = make_uint4(0, 0, 0, 0);
        mbar_wait(bars + 80, 0);
#pragma unroll 1
        for (int e = tid; e < 1600; e += 384) {
          const int jj = e / 800, it = e - 800 * jj, st = it / 160, n = (it - 160 * st) >> 1, k0 = 16 * st + 8 * ((it ^ (n >> 2)) & 1);
          const int nn = n % 40, h = 2 * (n / 40) + (nn & 1), ff = 4 * (nn >> 3) + ((nn >> 1) & 3);
          uint32_t w[8];
#pragma unroll
          for (int q = 0; q < 8; q++) {
            const int k = k0 + q;
            w[q] = (unsigned)(k - 20 * h) < 20u ? reinterpret_cast<const unsigned short*>(sgen + 204800)[jj * 1600 + k * 20 + ff] : 0u;
          }
          g_wphi[sv * 1600 + e] = make_uint4(w[0] | (w[1] << 16), w[2] | (w[3] << 16), w[4] | (w[5] << 16), w[6] | (w[7] << 16));
        }
      }
      if (rd < 2) {
#pragma unroll
        for (int e = 0; e < 8; e++) a[e] = 0.f;
      }
#pragma unroll 1
      for (int p = 0; p < np; p++) {
        mbar_wait(bars + 8 * p, rd & 1);
        const int bytes = (rd == 3 && p == 6) ? 12288 : piece;
        if (tid < nth) {
#pragma unroll 1
          for (int o = tid * 16; o < bytes; o += nth * 16) {
            const uint4 v = lds128(sb + p * piece + o);
            a[0] += bf_lo(v.x); a[1] += bf_hi(v.x); a[2] += bf_lo(v.y); a[3] += bf_hi(v.y);
            a[4] += bf_lo(v.z); a[5] += bf_hi(v.z); a[6] += bf_lo(v.w); a[7] += bf_hi(v.w);
          }
        }
      }
      if (tid < nth && (rd == 0 || rd == 3)) {
        float* cd = g_cs[epoch & 1] + (rd ? D_ : 0) + 8 * (tid % nch);
        red_add4(cd, a[0], a[1], a[2], a[3]); red_add4(cd + 4, a[4], a[5], a[6], a[7]);
      }
      __syncthreads();
      if (tid == 0 && (rd == 0 || rd == 3)) {
        flag_add(rd ? FL_CS3 : FL_CS);
        if (rd == 0) l2_prefetch(w2 + (size_t)sv * (D_ * D_ / NSVC), D_ * D_ * 2 / NSVC);
      }
    }
#pragma unroll 1
    for (int e = tid; e < (D_ + F_) / NSVC; e += 384) g_cs[(epoch + 1) & 1][sv * ((D_ + F_) / NSVC) + e] = 0.f;
#pragma unroll 1
    for (int e = tid; e < 2 * KV_J; e += 384) g_acc[(epoch + 1) & 1][sv * 2 * KV_J + e] = 0.f;
    if (tid < 32) {
      l2_prefetch(w4 + (size_t)(sv * 32 + tid) * (F_ * D_ / 128), F_ * D_ * 2 / 128);
      l2_prefetch(wo + (size_t)(sv * 32 + tid) * (D_ * D_ / 128), D_ * D_ * 2 / 128);
    }
    return;
  }
  TSTAMP(0);
  if (tid >= 256) {
    asm volatile("setmaxnreg.dec.sync.aligned.u32 40;");
    if (tid == 256) {
#pragma unroll
      for (int s = 0; s < NA; s++) mbar_init(fullA + 8 * s, 1);
      asm volatile("fence.mbarrier_init.release.cluster;" ::: "memory");
#pragma unroll 1
      for (int u = 0; u < 4; u++) {
        if ((u & 1) == 0) mbar_expect_tx(fullA + 4 * u, SLOT_A);
        tma2d(sb + OFF_A + u * 8192, &maps.x, fullA + 8 * (u >> 1), 64 * (u >> 1), 128 * i + 64 * (u & 1));
      }
    } else if (tid == 288) {
#pragma unroll
      for (int s = 0; s < NB; s++) { mbar_init(fullB + 8 * s, 1); mbar_init(emptyB + 8 * s, 8); }
      asm volatile("fence.mbarrier_init.release.cluster;" ::: "memory");
    } else if (tid == 320) {
#pragma unroll
      for (int b = B_CS; b < NBAR; b++) if (b < B_EMPTYB || b >= B_EMPTYB + NB) mbar_init(bars + 8 * b, b < B_EMPTYB ? 1 : b < B_EMPTYA ? 8 : b < B_X1P ? 16 : 2);
#pragma unroll
      for (int b = B_DSR; b < B_EMPTYB; b++) mbar_expect_tx(bars + 8 * b, 10240);
      asm volatile("fence.mbarrier_init.release.cluster;" ::: "memory");
    }
    __syncwarp();
    asm volatile("barrier.cluster.arrive.relaxed.aligned;" ::: "memory");
    auto get_epoch = [&]() { return *reinterpret_cast<volatile unsigned*>(g_flags + FL_DONE * 32) / NCTA; };
    if ((tid >> 5) != 9) asm volatile("barrier.cluster.wait.aligned;" ::: "memory");
    const int lane = tid & 31, pw = (tid >> 5) & 3;
    if (pw == 0) {
      if (tid == 256) {
        Ring r{2, 1};
#pragma unroll 1
        for (int k = 2; k < 24; k++) {
          if (k == 10 || k == 16) {
            mbar_wait(bars + 8 * B_HST, k == 16);
            TSTAMPX(k == 10 ? 29 : 30);
          }
          if (k == 14) {
            mbar_wait(bars + 8 * B_WDEAD, 0);
            mbar_expect_tx(bars + 8 * B_T4, SLOT_A);
            tma2d(sb + OFF_MISC, &maps.hs, bars + 8 * B_T4, 256 + 320 * rank, 128 * i);
            mbar_wait(emptyA + 16, r.phase); mbar_wait(emptyA + 24, r.phase);
            mbar_expect_tx(bars + 8 * B_XR, 20480);
            tma2d(sb + OFF_STG, &maps.xr, bars + 8 * B_XR, 80 * j, 128 * i);
            mbar_wait(bars + 8 * B_X1P, 0);
          }
          mbar_wait(emptyA + 8 * r.idx, r.phase);
          const uint32_t bar = fullA + 8 * r.idx, slot = sb + OFF_A + r.idx * SLOT_A;
          mbar_expect_tx(bar, SLOT_A);
          if (k >= 10 && k < 14) tma2d(slot, &maps.hs, bar, 64 * (k - 10) + 320 * rank, 128 * i);
          else tma2d_mc(slot + rank * 8192, k < 10 ? &maps.x : &maps.x1, bar, 64 * (k < 10 ? k : (k - 14 + k3) % 10), 128 * i + 64 * rank);
          r.next<NA>();
        }
      }
    } else if (pw == 1) {
      if (tid == 288) {
        Ring r{0, 1};
#pragma unroll 1
        for (int k = 0; k < 18; k++) {
          mbar_wait(emptyB + 8 * r.idx, r.phase);
          const uint32_t bar = fullB + 8 * r.idx, slot = sb + OFF_B + r.idx * SLOT_B;
          if (k < 10) {
            mbar_expect_tx(bar, 40960);
            tma4d(slot + 8192, &maps.qm, bar, 0, 64 * k, 0, j);
            tma3d(slot, &maps.w1m, bar, 0, 64 * k, j);
            tma4d(slot + 32768 + 2048, &maps.qr, bar, 64, 64 * k, 0, j);
            tma3d(slot + 32768, &maps.w1r, bar, 64, 64 * k, j);
          } else if (k < 13) {
            mbar_expect_tx(bar, k < 12 ? 40960 : 20480);
            tma3d(slot, &maps.w2, bar, 0, 320 * rank + 128 * (k - 10), 5 * (j >> 1));
            if (k < 12) tma3d(slot + 20480, &maps.w2, bar, 0, 320 * rank + 128 * (k - 10) + 64, 5 * (j >> 1));
          } else {
            if (k == 13) mbar_wait(bars + 8 * B_KVR, 0);
            mbar_expect_tx(bar, 49152);
            tma3d(slot, &maps.w3, bar, 0, 64 * ((2 * (k - 13) + k3) % 10), 3 * j);
            tma3d(slot + 24576, &maps.w3, bar, 0, 64 * ((2 * (k - 13) + 1 + k3) % 10), 3 * j);
          }
          r.next<NB>();
        }
#pragma unroll 1
        for (int n = 0; n < 8; n++) {
          if (n < 3) { mbar_wait(emptyB + 8 * r.idx, r.phase); r.next<NB>(); }
          if (n == 0) mbar_wait(fullA + 24, 1);
          if (n >= 4) mbar_wait(bars + 8 * (B_EMPTY4 + n - 4), 0);
          const uint32_t bar = bars + 8 * (B_FULL4 + n), set = sb + ((n >> 1) & 1) * SET4;
          const int h = n & 1, m = ((j >> 1) + 1 + (n >> 1)) & 3;
          mbar_expect_tx(bar, h ? 40960 : 46080);
          tma3d(set + (h ? 46080 : 0), h ? &maps.w4 : &maps.wo, bar, 0, h ? 192 * j + 64 : 80 * j, 5 * m);
          tma3d(set + (h ? 66560 : 25600), &maps.w4, bar, 0, 192 * j + 128 * h, 5 * m);
        }
        mbar_wait(bars + 8 * (B_EMPTY4 + 4), 0);
        mbar_expect_tx(bars + 8 * B_XR, 20480);
        tma2d(sb + OFF_OUT, &maps.st_x1, bars + 8 * B_XR, 80 * j, 128 * i);
      }
    } else {
      const unsigned epoch = get_epoch();
      float* accg = g_acc[epoch & 1];
      if (pw == 2) {
        if (tid == 320) {
          flag_wait(FL_CS, (epoch + 1) * NSVC);
          flag_wait(FL_ST + i, (epoch + 1) * 8u);
          fence_async_glb();
          *reinterpret_cast<volatile uint32_t*>(sgen + OFF_BAR + 8 * NBAR) = (epoch + 1) & 1;
          mbar_expect_tx(bars + 8 * B_CS, 320 + 2048 + 12800);
          bulk_load(sb + OFF_CS, g_cs[epoch & 1] + 80 * j, 320, bars + 8 * B_CS);
          bulk_load(sb + OFF_XST, g_xstat + 128 * i, 2048, bars + 8 * B_CS);
          bulk_load(sb + OFF_MISC, g_wphi + j * 800, 12800, bars + 8 * B_CS);
          TSTAMPX(21);
          mbar_wait(bars + 8 * B_SIGKV, 0);
          TSTAMPX(25);
#pragma unroll 1
          for (int u = 0; u < 4; u++)
            asm volatile("cp.reduce.async.bulk.global.shared::cta.bulk_group.add.f32 [%0], [%1], %2;"
                         ::"l"(accg + j * KV_J + (u >> 1) * KV_PAIR + (u & 1) * 1024), "r"(sb + OFF_B + SPARE + (u & 1) * SLOT_B + (u >> 1) * 4096),
                         "r"((u & 1) ? KV_PAIR * 4 - 4096 : 4096) : "memory");
          bulk_commit(); bulk_wait<0>();
          mbar_arrive(bars + 8 * B_KVR);
          flag_add(FL_KV + j);
          TSTAMPX(26);
          flag_wait(FL_KV + j, (epoch + 1) * 16u);
          mbar_wait(bars + 8 * B_SIGX1, 0);
          mbar_expect_tx(bars + 8 * B_KV, KV_J * 4);
          bulk_load(sb + OFF_A + SLOT_A, accg + j * KV_J, KV_J * 4, bars + 8 * B_KV);
          TSTAMPX(22);
          flag_wait(FL_CS3, (epoch + 1) * NSVC);
          flag_wait(FL_S1 + i, (epoch + 1) * 8u);
          fence_async_glb();
          mbar_expect_tx(bars + 8 * B_ST1, 8192 + 768);
          bulk_load(sb + OFF_CS + 320, g_cs[epoch & 1] + D_ + 192 * j, 768, bars + 8 * B_ST1);
          bulk_load(sb + OFF_MISC, g_st1 + 128 * i * 8, 8192, bars + 8 * B_ST1);
        }
        __syncwarp();
#pragma unroll 1
        for (int c = 0; c < 3; c++) {
          mbar_wait(bars + 8 * (B_EMPTY4 + (c ? 5 : 4)), 0);
          const uint4* src = g_part + (size_t)((i * 8 + j) * 3 + c) * 1280;
          const unsigned* tp = reinterpret_cast<const unsigned*>(src + 1024 + (lane & 7) * 32 + 31);
          uint32_t n = 0;
          while (!__all_sync(0xffffffffu, (ld_acquire(tp) ^ epoch) & 1u) && ++n < (WAIT_LIMIT >> 2)) {}
          if (tid == 320) {
            mbar_expect_tx(bars + 8 * (B_RDY + c), 20480);
            bulk_load(sb + (c ? 25600 + 20480 * c : 0), src, 20480, bars + 8 * (B_RDY + c));
          }
        }
      }
      if (tid == 352) {
        mbar_wait(bars + 8 * B_SIGP, 0);
        flag_add(FL_ST + i);
        TSTAMPX(20);
        const int shift = (j < 2) ? 1 : (j < 4) ? -1 : (j < 6) ? 2 : -2;
        prefetch_tmap(&maps.st_h); prefetch_tmap(&maps.st_x1); prefetch_tmap(&maps.hs); prefetch_tmap(&maps.x1); prefetch_tmap(&maps.xr);
        prefetch_tmap(&maps.w2); prefetch_tmap(&maps.w3); prefetch_tmap(&maps.w4); prefetch_tmap(&maps.wo);
        mbar_wait(bars + 8 * B_SIGH, 0);
        TSTAMPX(23);
        tma2d_store(&maps.st_h, sb + OFF_STG, 80 * j, 128 * i + 2 + shift);
        bulk_commit(); bulk_wait<0>();
        flag_add(FL_H + 2 * i + (j >> 2));
        flag_add_relaxed(FL_H + 2 * ((i + (shift > 0 ? 1 : -1)) & 15) + (j >> 2));
        TSTAMPX(24);
        flag_wait(FL_H + 2 * i + rank, (epoch + 1) * 8u);
        mbar_arrive(bars + 8 * B_HST);
        mbar_wait(bars + 8 * B_SIGX1, 0);
        TSTAMPX(27);
        tma2d_store(&maps.st_x1, sb + OFF_STG, 80 * j, 128 * i);
        bulk_commit(); bulk_wait<0>();
        flag_add(FL_X1 + i);
        mbar_arrive_cta(bars + 8 * B_X1P, 0); mbar_arrive_cta(bars + 8 * B_X1P, 1);
        TSTAMPX(28);
        flag_wait(FL_X1 + i, (epoch + 1) * 8u);
        mbar_arrive(bars + 8 * B_HST);
        mbar_wait(bars + 8 * B_MFREE, 0);
        flag_add(FL_S1 + i);
      }
    }
  } else {
    uint4 pv[5], pw_[5];
    {
      const int row = 128 * i + 16 * j + (tid >> 4), l16 = tid & 15;
#pragma unroll
      for (int c = 0; c < 5; c++) pv[c] = __ldg(reinterpret_cast<const uint4*>(x + (size_t)row * D_ + c * 128 + l16 * 8));
#pragma unroll
      for (int c = 0; c < 5; c++) pw_[c] = __ldg(reinterpret_cast<const uint4*>(gate_w + c * 128 + l16 * 8));
    }
    asm volatile("barrier.cluster.arrive.relaxed.aligned;" ::: "memory");
    asm volatile("setmaxnreg.inc.sync.aligned.u32 232;");
    const int wg = tid >> 7, warp = tid >> 5, lane = tid & 31, t = lane & 3;
    const int rloc = warp * 16 + (lane >> 2);
    const float* s_cs = reinterpret_cast<const float*>(sgen + OFF_CS);
    auto signal = [&](int b) {
      __syncwarp();
      if (lane == 0) mbar_arrive(bars + 8 * b);
    };
    auto releaseB = [&](uint32_t bar) {
      __syncwarp();
      if (lane == 0) mbar_arrive(bar);
    };
    auto release = [&](uint32_t bar) {
      __syncwarp();
      if (lane < 2) mbar_arrive_cta(bar, lane);
    };
    const uint32_t stg_lane = (warp * 16 + ((lane >> 3) & 1) * 8 + (lane & 7)) * 160 + (lane >> 4) * 16;

    auto stage_tile = [&](uint32_t stg, const uint32_t (&v)[2][10]) {
#pragma unroll
      for (int s = 0; s < 5; s++) stsm4(stg + stg_lane + s * 32, v[0][2 * s], v[1][2 * s], v[0][2 * s + 1], v[1][2 * s + 1]);
    };

    {
      float f[40];
      float s = 0.f, gs = 0.f;
#pragma unroll
      for (int c = 0; c < 5; c++) {
        const uint32_t vv[4] = {pv[c].x, pv[c].y, pv[c].z, pv[c].w}, ww[4] = {pw_[c].x, pw_[c].y, pw_[c].z, pw_[c].w};
#pragma unroll
        for (int e = 0; e < 4; e++) {
          f[8 * c + 2 * e] = bf_lo(vv[e]); f[8 * c + 2 * e + 1] = bf_hi(vv[e]);
          s += f[8 * c + 2 * e] + f[8 * c + 2 * e + 1];
          const uint32_t pr = mul_bf2(vv[e], ww[e]);
          gs += bf_lo(pr) + bf_hi(pr);
        }
      }
#pragma unroll
      for (int o = 1; o < 16; o <<= 1) { s += __shfl_xor_sync(0xffffffffu, s, o); gs += __shfl_xor_sync(0xffffffffu, gs, o); }
      const float mean = s * (1.f / D_);
      float q = 0.f;
#pragma unroll
      for (int e = 0; e < 40; e++) { const float d = f[e] - mean; q = fmaf(d, d, q); }
#pragma unroll
      for (int o = 1; o < 16; o <<= 1) q += __shfl_xor_sync(0xffffffffu, q, o);
      const float rstd = rsqrtf(q * (1.f / D_) + 1e-5f);
      const float gate = bf_lo(pack_bf16(rcp(1.f + __expf(-bf_lo(pack_bf16(gs, 0.f)))), 0.f));
      asm volatile("barrier.cluster.wait.aligned;" ::: "memory");
      if ((tid & 15) == 0) g_xstat[128 * i + 16 * j + (tid >> 4)] = make_float4(rstd, -mean, gate, 0.f);
      signal(B_SIGP);
    }
    TSTAMP(1);

    Ring ra{0, 0}, rb{0, 0};
    uint32_t qp[2][10], P[2][10];
    float st_g[2];
    {
      float accM[128], accR[32];
      uint32_t pa = 0, pb = 0;
#pragma unroll 1
      for (int k = 0; k < 10; k++) {
        mbar_wait(fullA + 8 * ra.idx, ra.phase);
        if (tid == 0) TRACE(32 + k);
        mbar_wait(fullB + 8 * rb.idx, rb.phase);
        if (tid == 0) TRACE(64 + k);
        if (k == 0) TSTAMP(2);
        const uint32_t a0 = sb16 + ((OFF_A + ra.idx * SLOT_A + wg * 8192) >> 4), b0 = sb16 + ((OFF_B + rb.idx * SLOT_B) >> 4);
        wg_fence();
#pragma unroll
        for (int kk = 0; kk < 4; kk++) {
          const uint64_t da = make_desc(a0, kk * 32, 16, 1024, 1);
          if (kk == 0) {
            mma_ss256_p(accM, da, make_desc(b0, 0, 8192, 1024, 1), k);
            mma_ss64_p(accR, da, make_desc(b0, 32768, 2048, 256, 3), k);
          } else {
            mma_ss256(accM, da, make_desc(b0, kk * 2048, 8192, 1024, 1));
            mma_ss64(accR, da, make_desc(b0, 32768 + kk * 512, 2048, 256, 3));
          }
          if (kk == 0) {
            wg_commit();
            if (k > 0) {
              wg_wait<1>();
              release(emptyA + 8 * pa);
              releaseB(emptyB + 8 * pb);
            }
          }
        }
        wg_commit();
        pa = ra.idx; pb = rb.idx;
        ra.next<NA>(); rb.next<NB>();
      }
      TSTAMP(18);
      float st_rstd[2], st_mr[2];
      mbar_wait(bars + 8 * B_CS, 0);
#pragma unroll
      for (int r = 0; r < 2; r++) {
        const uint4 st = lds128(sb + OFF_XST + (rloc + 8 * r) * 16);
        st_rstd[r] = __uint_as_float(st.x); st_mr[r] = __uint_as_float(st.y); st_g[r] = __uint_as_float(st.z);
      }
      TSTAMP(19);
      wg_wait<0>();
      fence_regs(accM); fence_regs(accR);
      TSTAMP(3);
      release(emptyA + 8 * pa);
#define ACC(P_, G, I_) ((G) < 8 ? accM[(P_) * 32 + ((G) & 7) * 4 + (I_)] : accR[(P_) * 8 + ((G) & 1) * 4 + (I_)])
      {
        uint32_t hv[2][10];
        const GeluC g0 = gelu_consts(st_rstd[0], 1.f), g1 = gelu_consts(st_rstd[1], 1.f);
#pragma unroll
        for (int g = 0; g < 10; g++) {
          const float2 cs = *reinterpret_cast<const float2*>(s_cs + 8 * g + 2 * t);
          const float v0 = gelu_s(fmaf(st_mr[0], cs.x, ACC(0, g, 0)), g0), v1 = gelu_s(fmaf(st_mr[0], cs.y, ACC(0, g, 1)), g0);
          const float v2 = gelu_s(fmaf(st_mr[1], cs.x, ACC(0, g, 2)), g1), v3 = gelu_s(fmaf(st_mr[1], cs.y, ACC(0, g, 3)), g1);
          hv[0][g] = pack_bf16(v0, v1); hv[1][g] = pack_bf16(v2, v3);
        }
        bar_sync(1, 256);
        stage_tile(sb + OFF_STG, hv);
        fence_async_smem();
        signal(B_SIGH);
      }
      TSTAMP(4);
      uint32_t kf[5][4], qf[5][4];
#pragma unroll
      for (int s = 0; s < 5; s++) {
        kf[s][0] = pack_bf16(ACC(2, 2 * s, 0), ACC(2, 2 * s, 1)); kf[s][1] = pack_bf16(ACC(2, 2 * s, 2), ACC(2, 2 * s, 3));
        kf[s][2] = pack_bf16(ACC(2, 2 * s + 1, 0), ACC(2, 2 * s + 1, 1)); kf[s][3] = pack_bf16(ACC(2, 2 * s + 1, 2), ACC(2, 2 * s + 1, 3));
        qf[s][0] = pack_bf16(ACC(1, 2 * s, 0), ACC(1, 2 * s, 1)); qf[s][1] = pack_bf16(ACC(1, 2 * s, 2), ACC(1, 2 * s, 3));
        qf[s][2] = pack_bf16(ACC(1, 2 * s + 1, 0), ACC(1, 2 * s + 1, 1)); qf[s][3] = pack_bf16(ACC(1, 2 * s + 1, 2), ACC(1, 2 * s + 1, 3));
      }
      float pk[40], pq[40];
      wg_fence();
#pragma unroll
      for (int s = 0; s < 5; s++) {
        if (s == 0) mma_rs80_k_z(pk, kf[s], make_desc(sb16, OFF_MISC, 16, 256, 3));
        else mma_rs80_k(pk, kf[s], make_desc(sb16, OFF_MISC + s * 2560, 16, 256, 3));
      }
      wg_commit();
#pragma unroll
      for (int s = 0; s < 5; s++) {
        if (s == 0) mma_rs80_k_z(pq, qf[s], make_desc(sb16, OFF_MISC, 16, 256, 3));
        else mma_rs80_k(pq, qf[s], make_desc(sb16, OFF_MISC + s * 2560, 16, 256, 3));
      }
      wg_commit();
      {
        const int mat = lane >> 3;
        const int tok = warp * 16 + (mat & 1) * 8 + (lane & 7);
        const uint32_t base = sb + OFF_B + SPARE + tok * 32 + (((mat >> 1) ^ ((tok >> 2) & 1)) << 4);
        const uint32_t ones = (t == 0) ? 0x00003f80u : 0u;
#pragma unroll
        for (int p = 0; p < 2; p++) {
#pragma unroll
          for (int gg = 0; gg < 3; gg++) {
            const int g0 = 5 * p + 2 * gg;
            uint32_t r0 = pack_bf16(ACC(3, g0, 0), ACC(3, g0, 1)), r1 = pack_bf16(ACC(3, g0, 2), ACC(3, g0, 3));
            uint32_t r2 = ones, r3 = ones;
            if (gg < 2) { r2 = pack_bf16(ACC(3, g0 + 1, 0), ACC(3, g0 + 1, 1)); r3 = pack_bf16(ACC(3, g0 + 1, 2), ACC(3, g0 + 1, 3)); }
            stsm4(base + gg * SLOT_B + p * 4096, r0, r1, r2, r3);
          }
        }
      }
#undef ACC
      wg_wait<1>();
      fence_regs(pk);
#pragma unroll
      for (int G = 0; G < 10; G++) {
        P[0][G] = pack_bf16(pk[4 * G], pk[4 * G + 1]); P[1][G] = pack_bf16(pk[4 * G + 2], pk[4 * G + 3]);
      }
      wg_wait<0>();
      fence_regs(pq);
      signal(B_WDEAD);
#pragma unroll
      for (int G = 0; G < 10; G++) {
        qp[0][G] = pack_bf16(pq[4 * G], pq[4 * G + 1]); qp[1][G] = pack_bf16(pq[4 * G + 2], pq[4 * G + 3]);
      }
    }

    uint32_t fr[10][4];
    int pass;
    pass = gridDim.y;
#pragma unroll 1
    do {
    feature_map(P, fr);
    if (pass != 0) {
    {
      const int mat = lane >> 3;
      const int tok = warp * 16 + (mat & 1) * 8 + (lane & 7);
      const uint32_t base = sb + OFF_B + tok * 32 + (((mat >> 1) ^ ((tok >> 2) & 1)) << 4);
#pragma unroll
      for (int G = 0; G < 10; G++) stsm4(base + G * 4096, fr[G][0], fr[G][1], fr[G][2], fr[G][3]);
      fence_async_smem();
      bar_sync(1, 256);
      float kv[40];
      const uint32_t va = sb16 + ((OFF_B + SPARE + wg * 4096) >> 4), vb = sb16 + ((OFF_B + wg * 20480) >> 4);
      wg_fence();
#pragma unroll
      for (int ks = 0; ks < 8; ks++) {
        if (ks == 0) mma_ss80_tt_z(kv, make_desc(va, 0, SLOT_B, 256, 3), make_desc(vb, 0, 4096, 256, 3));
        else mma_ss80_tt(kv, make_desc(va, ks * 512, SLOT_B, 256, 3), make_desc(vb, ks * 512, 4096, 256, 3));
      }
      wg_commit();
      wg_wait<0>();
      fence_regs(kv);
      TSTAMP(31);
      releaseB(emptyB); release(bars + 8 * B_PEER2);
      auto kv_sts = [&](uint32_t o, uint32_t a0, uint32_t a1, uint32_t a2, uint32_t a3) {
        sts128(sb + OFF_B + SPARE + wg * 4096 + o + (o >= 4096 ? SLOT_B - 4096 : 0), make_uint4(a0, a1, a2, a3));
      };
      const int m0 = (warp & 3) * 16 + (lane >> 2);
      bar_sync(4 + wg, 128);
#pragma unroll
      for (int r = 0; r < 2; r++) {
        const int m = m0 + 8 * r;
        const bool hi = m >= 20;
        uint32_t v[10];
#pragma unroll
        for (int G = 0; G < 10; G++) v[G] = __float_as_uint(hi ? kv[4 * G + 2 * r + 1] : kv[4 * G + 2 * r]);
        const uint32_t p = 4 * (m < 40 ? m * 48 + t * 12 : 1920 + t * 24 + 12);
        if (m <= 40) { kv_sts(p, v[0], v[1], v[2], v[3]); kv_sts(p + 16, v[4], v[5], v[6], v[7]); kv_sts(p + 32, v[8], v[9], 0u, 0u); }
      }
      if (m0 == 32) {
        const uint32_t p = 4 * (1920 + t * 24);
        kv_sts(p, __float_as_uint(kv[2]), __float_as_uint(kv[6]), __float_as_uint(kv[10]), __float_as_uint(kv[14]));
        kv_sts(p + 16, __float_as_uint(kv[18]), __float_as_uint(kv[22]), __float_as_uint(kv[26]), __float_as_uint(kv[30]));
        kv_sts(p + 32, __float_as_uint(kv[34]), __float_as_uint(kv[38]), 0u, 0u);
      }
      fence_async_smem();
      signal(B_SIGKV);
      float a1[48], a2[32];
      const uint32_t aw = sb16 + wg * 512, b1 = sb16 + (rank ? 0 : 512), b2 = sb16 + (rank ? 768 : 0);
      auto g2 = [&](auto kc, bool p1, bool p2) {
        constexpr int k = decltype(kc)::value;
        constexpr int ao = k < 4 ? OFF_A + ((k + 2) & 3) * SLOT_A : OFF_MISC, bo = OFF_B + ((1 + k / 2) % 3) * SLOT_B + (k & 1) * 20480;
        wg_fence();
#pragma unroll
        for (int kk = 0; kk < 4; kk++) {
          const uint64_t da = make_desc(aw, ao + kk * 32, 16, 1024, 1);
          if (p1) { if (k + kk == 0) mma_ss96_z(a1, da, make_desc(b1, bo, 4096, 512, 2)); else mma_ss96(a1, da, make_desc(b1, bo + kk * 1024, 4096, 512, 2)); }
          if (p2) { if (k + kk == 0) mma_ss64b_z(a2, da, make_desc(b2, bo, 4096, 512, 2)); else mma_ss64b(a2, da, make_desc(b2, bo + kk * 1024, 4096, 512, 2)); }
        }
        wg_commit();
      };
      TSTAMP(5);
      mbar_wait(fullA + 16, 0); mbar_wait(fullB + 8, 1);
      TSTAMP(6);
      g2(IntC<0>{}, true, true);
      mbar_wait(fullA + 24, 0);
      g2(IntC<1>{}, true, true);
      mbar_wait(fullA, 1); mbar_wait(fullB + 16, 1);
      g2(IntC<2>{}, true, false);
      wg_wait<1>();
      release(emptyA + 16); release(emptyA + 24); releaseB(emptyB + 8);
      mbar_wait(fullA + 8, 1);
      g2(IntC<3>{}, true, false);
      mbar_wait(bars + 8 * B_T4, 0); mbar_wait(fullB, 0);
      g2(IntC<4>{}, true, false);
      mbar_wait(bars + 8 * B_PEER2, 0);
      g2(IntC<2>{}, false, true);
      wg_wait<1>();
      fence_regs(a1);
      float acc[40];
      {
        uint32_t sn[20];
        if (rank) {
#pragma unroll
          for (int e = 0; e < 20; e++) sn[e] = pack_bf16(a1[2 * e], a1[2 * e + 1]);
#pragma unroll
          for (int e = 0; e < 8; e++) acc[32 + e] = a1[40 + e];
        } else {
#pragma unroll
          for (int e = 0; e < 20; e++) sn[e] = pack_bf16(a1[8 + 2 * e], a1[9 + 2 * e]);
#pragma unroll
          for (int e = 0; e < 8; e++) acc[32 + e] = a1[e];
        }
        g2(IntC<3>{}, false, true);
        const uint32_t peer = map_peer(sb, rank ^ 1);
#pragma unroll
        for (int q = 0; q < 5; q++)
          st_async16(peer + OFF_B + 20480 + tid * 16 + q * 4096, sn[4 * q], sn[4 * q + 1], sn[4 * q + 2], sn[4 * q + 3],
                     peer + OFF_BAR + 8 * (B_DSR + 8 + wg));
        g2(IntC<4>{}, false, true);
        mbar_wait(bars + 8 * B_XR, 0);
        mbar_wait(bars + 8 * (B_DSR + 8 + wg), 0);
        __syncwarp();
        uint4 xr4[5], pr4[5];
#pragma unroll
        for (int q = 0; q < 5; q++) {
          const int qq = q < 4 ? q + rank : 4 - 4 * rank;
          xr4[q] = ldsm4(sb + OFF_STG + stg_lane + qq * 32);
          pr4[q] = lds128(sb + OFF_B + 20480 + tid * 16 + qq * 4096);
        }
        wg_wait<0>();
        fence_regs(a2);
        release(emptyA); releaseB(emptyB + 16); releaseB(emptyB);
        ra.idx = 2; ra.phase = 1; rb.idx = 1; rb.phase = 0;
        TSTAMP(7);
#pragma unroll
        for (int e = 0; e < 32; e++) acc[e] = a2[e];
#pragma unroll
        for (int q = 0; q < 5; q++) {
          const uint4 v = xr4[q], u = pr4[q];
          float* d = &acc[8 * q];
          d[0] += bf_lo(v.x) + bf_lo(u.x); d[1] += bf_hi(v.x) + bf_hi(u.x); d[2] += bf_lo(v.y) + bf_lo(u.y); d[3] += bf_hi(v.y) + bf_hi(u.y);
          d[4] += bf_lo(v.z) + bf_lo(u.z); d[5] += bf_hi(v.z) + bf_hi(u.z); d[6] += bf_lo(v.w) + bf_lo(u.w); d[7] += bf_hi(v.w) + bf_hi(u.w);
          const int qq = q < 4 ? q + rank : 4 - 4 * rank;
          stsm4(sb + OFF_STG + stg_lane + qq * 32, pack_bf16(d[0], d[1]), pack_bf16(d[2], d[3]), pack_bf16(d[4], d[5]), pack_bf16(d[6], d[7]));
        }
      }
      TSTAMP(16);
      fence_async_smem();
      signal(B_SIGX1);
      TSTAMP(17);
#pragma unroll
      for (int r = 0; r < 2; r++) {
        float s = 0.f;
#pragma unroll
        for (int g = 0; g < 10; g++) s += acc[4 * g + 2 * r] + acc[4 * g + 2 * r + 1];
        s += __shfl_xor_sync(0xffffffffu, s, 1); s += __shfl_xor_sync(0xffffffffu, s, 2);
        const float mu = s * (1.f / 80.f);
        float q = 0.f;
#pragma unroll
        for (int g = 0; g < 10; g++) {
          const float d0 = acc[4 * g + 2 * r] - mu, d1 = acc[4 * g + 2 * r + 1] - mu;
          q = fmaf(d0, d0, q); q = fmaf(d1, d1, q);
        }
        q += __shfl_xor_sync(0xffffffffu, q, 1); q += __shfl_xor_sync(0xffffffffu, q, 2);
        if (t == 0) g_st1[(128 * i + rloc + 8 * r) * 8 + j] = make_float2(mu, q);
      }
    }
    TSTAMP(8);
#pragma unroll
    for (int G = 0; G < 10; G++) { P[0][G] = qp[0][G]; P[1][G] = qp[1][G]; }
    }
    asm volatile("" : "+r"(pass));
    } while (pass-- != 0);

    uint32_t of[5][4];
    {
      mbar_wait(bars + 8 * B_KV, 0);
#pragma unroll 1
      for (int it = tid; it < 384; it += 256) {
        const int p = it >= 192, rem = it - 192 * p, n = rem >> 2, tq = rem & 3;
        const uint32_t sp = sb + OFF_A + SLOT_A + 4 * (p * KV_PAIR + (n < 40 ? n * 48 + tq * 12 : 1920 + tq * 24 + (n & 1) * 12));
        const uint4 ka = lds128(sp), kb = lds128(sp + 16), kc = lds128(sp + 32);
        const uint32_t v[10] = {ka.x, ka.y, ka.z, ka.w, kb.x, kb.y, kb.z, kb.w, kc.x, kc.y};
        const int sh = (n < 40 ? (n >= 20) : (n & 1)) * 16;
        uint8_t* dst = sgen + OFF_MISC + p * 7680 + n * 32 + tq * 4;
        const int sw = ((n >> 2) & 1) << 4;
#pragma unroll
        for (int G = 0; G < 10; G++)
          *reinterpret_cast<uint32_t*>(dst + (G >> 1) * 1536 + (((G & 1) << 4) ^ sw)) = pack_bf16(__uint_as_float(v[G]), 0.f) << sh;
      }
      release(emptyA + 8);
      fence_async_smem();
      bar_sync(1, 256);
      float o0[24], o1[24];
      wg_fence();
#pragma unroll
      for (int g = 0; g < 5; g++) {
        if (g == 0) mma_rs48_k_z(o0, fr[g], make_desc(sb16, OFF_MISC, 16, 256, 3));
        else mma_rs48_k(o0, fr[g], make_desc(sb16, OFF_MISC + g * 1536, 16, 256, 3));
      }
#pragma unroll
      for (int g = 0; g < 5; g++) {
        if (g == 0) mma_rs48_k_z(o1, fr[5], make_desc(sb16, OFF_MISC + 7680, 16, 256, 3));
        else mma_rs48_k(o1, fr[5 + g], make_desc(sb16, OFF_MISC + 7680 + g * 1536, 16, 256, 3));
      }
      wg_commit();
      wg_wait<0>();
      fence_regs(o0); fence_regs(o1);
      signal(B_MFREE);
#pragma unroll
      for (int r = 0; r < 2; r++) {
        const float a0 = __fdividef(st_g[r], o0[20 + 2 * r] + 1e-6f), a1 = __fdividef(st_g[r], o0[21 + 2 * r] + 1e-6f);
        const float b0 = __fdividef(st_g[r], o1[20 + 2 * r] + 1e-6f), b1 = __fdividef(st_g[r], o1[21 + 2 * r] + 1e-6f);
        const float am = t < 2 ? a0 : a1, bm = t < 2 ? b0 : b1;
#pragma unroll
        for (int g = 0; g < 5; g++) {
          const float sa = g < 2 ? a0 : (g == 2 ? am : a1), sb2 = g < 2 ? b0 : (g == 2 ? bm : b1);
          of[g >> 1][(g & 1) * 2 + r] = pack_bf16(o0[4 * g + 2 * r] * sa, o0[4 * g + 2 * r + 1] * sa);
          of[(5 + g) >> 1][((5 + g) & 1) * 2 + r] = pack_bf16(o1[4 * g + 2 * r] * sb2, o1[4 * g + 2 * r + 1] * sb2);
        }
      }
    }
    TSTAMP(9);

    uint32_t hf[12][4];
    float ac4[80];
    auto unit = [&](auto uc, uint32_t b0) {
      constexpr int u = decltype(uc)::value;
#pragma unroll
      for (int s = 0; s < (u ? 4 : 5); s++) {
        const uint64_t db = make_desc(b0, (u ? 5120 + 20480 * u : 0) + s * 1024, u ? 4096 : 5120, 512, 2);
        if (u == 0 && s == 0) mma_rs160_n_z(ac4, of[0], db);
        else if (u == 0) mma_rs160_n(ac4, of[s], db);
        else mma_rs160_n(ac4, hf[(4 * u + 8 + s) % 12], db);
      }
      wg_commit();
    };
    {
      float acc[96];
      uint32_t pa = 0, pb = 0;
#pragma unroll 1
      for (int k = 0; k < 10; k++) {
        mbar_wait(fullA + 8 * ra.idx, ra.phase);
        if (tid == 0) TRACE(52 + k);
        if ((k & 1) == 0) mbar_wait(fullB + 8 * rb.idx, rb.phase);
        if (tid == 0) TRACE(84 + k);
        if (k == 0) TSTAMP(10);
        const uint32_t a0 = sb16 + ((OFF_A + ra.idx * SLOT_A + wg * 8192) >> 4);
        const uint32_t b0 = sb16 + ((OFF_B + rb.idx * SLOT_B + (k & 1) * 24576) >> 4);
        wg_fence();
#pragma unroll
        for (int kk = 0; kk < 4; kk++) {
          if (kk == 0) mma_ss192_p(acc, make_desc(a0, 0, 16, 1024, 1), make_desc(b0, 0, 8192, 1024, 1), k);
          else mma_ss192(acc, make_desc(a0, kk * 32, 16, 1024, 1), make_desc(b0, kk * 2048, 8192, 1024, 1));
          if (kk == 0) {
            wg_commit();
            if (k > 0) {
              wg_wait<1>();
              release(emptyA + 8 * pa);
              if ((k & 1) == 0) releaseB(emptyB + 8 * pb);
            }
          }
        }
        wg_commit();
        pa = ra.idx; pb = rb.idx;
        ra.next<NA>();
        if (k & 1) rb.next<NB>();
      }
      float rs[2], mm[2];
      mbar_wait(bars + 8 * B_ST1, 0);
#pragma unroll
      for (int r = 0; r < 2; r++) {
        const uint4 su = lds128(sb + OFF_MISC + (rloc + 8 * r) * 64 + t * 16);
        const float m0 = __uint_as_float(su.x), m1 = __uint_as_float(su.z);
        float mu = m0 + m1;
        mu += __shfl_xor_sync(0xffffffffu, mu, 1); mu += __shfl_xor_sync(0xffffffffu, mu, 2);
        mu *= 0.125f;
        const float d0 = m0 - mu, d1 = m1 - mu;
        float q = __uint_as_float(su.y) + __uint_as_float(su.w) + 80.f * (d0 * d0 + d1 * d1);
        q += __shfl_xor_sync(0xffffffffu, q, 1); q += __shfl_xor_sync(0xffffffffu, q, 2);
        rs[r] = rsqrtf(q * (1.f / D_) + 1e-5f);
        mm[r] = -mu;
      }
      mbar_wait(bars + 8 * B_FULL4, 0);
      wg_fence();
      unit(IntC<0>{}, sb16);
      wg_wait<1>();
      fence_regs(acc);
      releaseB(emptyB + 8 * pb);
      release(bars + 8 * B_PEER);
      TSTAMP(11);
      const GeluC g0 = gelu_consts(rs[0], 1.f - st_g[0]), g1 = gelu_consts(rs[1], 1.f - st_g[1]);
#pragma unroll
      for (int g = 0; g < 24; g++) {
        const float2 cs = *reinterpret_cast<const float2*>(s_cs + 80 + 8 * g + 2 * t);
        const float v0 = gelu_s(fmaf(mm[0], cs.x, acc[4 * g]), g0), v1 = gelu_s(fmaf(mm[0], cs.y, acc[4 * g + 1]), g0);
        const float v2 = gelu_s(fmaf(mm[1], cs.x, acc[4 * g + 2]), g1), v3 = gelu_s(fmaf(mm[1], cs.y, acc[4 * g + 3]), g1);
        hf[g >> 1][(g & 1) * 2] = pack_bf16(v0, v1);
        hf[g >> 1][(g & 1) * 2 + 1] = pack_bf16(v2, v3);
        if (g == 7) { wg_fence(); unit(IntC<1>{}, sb16); }
        if (g == 15) { mbar_wait(bars + 8 * (B_FULL4 + 1), 0); wg_fence(); unit(IntC<2>{}, sb16); }
        if (g == 23) { wg_wait<1>(); signal(B_EMPTY4); wg_fence(); unit(IntC<3>{}, sb16); }
      }
    }
    TSTAMP(12);

    {
      float kp[40];
      uint32_t sn[20], kb[20];
      const uint32_t peer = map_peer(sb, rank ^ 1);
      const uint32_t tag = lds32(sb + OFF_BAR + 8 * NBAR);
      auto add8 = [&](int q, const uint4 v) {
        float* d = &kp[8 * q];
        d[0] += bf_lo(v.x); d[1] += bf_hi(v.x); d[2] += bf_lo(v.y); d[3] += bf_hi(v.y);
        d[4] += bf_lo(v.z); d[5] += bf_hi(v.z); d[6] += bf_lo(v.w); d[7] += bf_hi(v.w);
      };
      auto send = [&](int c) {
        const uint32_t dso = peer + OFF_DS + (c & 1) * 20480 + tid * 16, dsb = peer + OFF_BAR + 8 * (B_DSR + 2 * c + wg);
#pragma unroll
        for (int q = 0; q < 5; q++) st_async16(dso + q * 4096, sn[4 * q], sn[4 * q + 1], sn[4 * q + 2], sn[4 * q + 3], dsb);
      };
      mbar_wait(bars + 8 * B_PEER, 0);
      uint4* gdst = g_part + (size_t)i * 8 * 3840 + tid;
#pragma unroll 1
      for (int c = 0; c < 3; c++) {
        const uint32_t b0 = sb16 + ((c & 1) ? 0 : SET4 >> 4), bc = bars + 16 * c;
        mbar_wait(bc + 8 * (B_FULL4 + 2), 0);
        wg_wait<0>();
        fence_regs(ac4);
        if (rank) {
#pragma unroll
          for (int e = 0; e < 20; e++) { sn[e] = pack_bf16(ac4[2 * e], ac4[2 * e + 1]); kb[e] = pack_bf16(ac4[40 + 2 * e], ac4[41 + 2 * e]); }
        } else {
#pragma unroll
          for (int e = 0; e < 20; e++) { kb[e] = pack_bf16(ac4[2 * e], ac4[2 * e + 1]); sn[e] = pack_bf16(ac4[40 + 2 * e], ac4[41 + 2 * e]); }
        }
#pragma unroll
        for (int e = 0; e < 20; e++) asm volatile("" : "+r"(sn[e]), "+r"(kb[e]));
        send(c);
        if (c == 0 && wg == 1) bar_sync(2, 256);
        wg_fence();
        unit(IntC<0>{}, b0);
        if (lane == 0) mbar_arrive(bc + 8 * (B_EMPTY4 + 1));
        unit(IntC<1>{}, b0);
        if (c == 0 && wg == 0) bar_arrive(2, 256);
        {
          mbar_wait(bc + 8 * (B_DSR + wg), 0);
          uint4* dst = gdst + (((j + 2 * c + 2) & 7) * 3 + c) * 1280;
#pragma unroll
          for (int q = 0; q < 5; q++) {
            const uint4 v = lds128(sb + OFF_DS + (c & 1) * 20480 + tid * 16 + q * 4096);
            st_relaxed16(dst + q * 256, (add_bf2(v.x, kb[4 * q]) & ~1u) | tag, add_bf2(v.y, kb[4 * q + 1]),
                         add_bf2(v.z, kb[4 * q + 2]), add_bf2(v.w, kb[4 * q + 3]));
          }
        }
        mbar_wait(bc + 8 * (B_FULL4 + 3), 0);
        wg_fence();
        unit(IntC<2>{}, b0);
        wg_wait<1>();
        if (lane == 0) mbar_arrive(bc + 8 * (B_EMPTY4 + 2));
        unit(IntC<3>{}, b0);
      }
      auto partial = [&](int c, uint4 (&v)[5]) {
        mbar_wait(bars + 8 * (B_RDY + c), 0);
        uint32_t bad = 0;
#pragma unroll
        for (int q = 0; q < 5; q++) { v[q] = lds128(sb + (c ? 25600 + 20480 * c : 0) + tid * 16 + q * 4096); bad |= v[q].x ^ tag; }
#pragma unroll 1
        for (uint32_t n = 0; (bad & 1u) && n < (WAIT_LIMIT >> 2); n++) {
          bad = 0;
#pragma unroll
          for (int q = 0; q < 5; q++) { v[q] = ld_relaxed16(gdst + (j * 3 + c) * 1280 + q * 256); bad |= v[q].x ^ tag; }
        }
      };
      uint4 pa4[5], pb4[5];
      partial(0, pa4);
      wg_wait<0>();
      fence_regs(ac4);
      if (rank) {
#pragma unroll
        for (int e = 0; e < 20; e++) sn[e] = pack_bf16(ac4[2 * e], ac4[2 * e + 1]);
#pragma unroll
        for (int e = 0; e < 40; e++) kp[e] = ac4[40 + e];
      } else {
#pragma unroll
        for (int e = 0; e < 20; e++) sn[e] = pack_bf16(ac4[40 + 2 * e], ac4[41 + 2 * e]);
#pragma unroll
        for (int e = 0; e < 40; e++) kp[e] = ac4[e];
      }
      send(3);
      TSTAMP(13);
      {
        mbar_wait(bars + 8 * B_XR, 1);
        const float w0 = 1.f - st_g[0], w1s = 1.f - st_g[1];
        __syncwarp();
#pragma unroll
        for (int q = 0; q < 5; q++) {
          const uint4 v = ldsm4(sb + OFF_OUT + stg_lane + q * 32);
          float* d = &kp[8 * q];
          d[0] = fmaf(w0, bf_lo(v.x), d[0]); d[1] = fmaf(w0, bf_hi(v.x), d[1]); d[2] = fmaf(w1s, bf_lo(v.y), d[2]); d[3] = fmaf(w1s, bf_hi(v.y), d[3]);
          d[4] = fmaf(w0, bf_lo(v.z), d[4]); d[5] = fmaf(w0, bf_hi(v.z), d[5]); d[6] = fmaf(w1s, bf_lo(v.w), d[6]); d[7] = fmaf(w1s, bf_hi(v.w), d[7]);
        }
      }
      partial(1, pb4);
#pragma unroll
      for (int q = 0; q < 5; q++)
        pa4[q] = make_uint4(add_bf2(pa4[q].x, pb4[q].x), add_bf2(pa4[q].y, pb4[q].y), add_bf2(pa4[q].z, pb4[q].z), add_bf2(pa4[q].w, pb4[q].w));
#pragma unroll
      for (int q = 0; q < 5; q++) add8(q, pa4[q]);
      partial(2, pb4);
      mbar_wait(bars + 8 * (B_DSR + 6 + wg), 0);
      TSTAMP(14);
#pragma unroll
      for (int q = 0; q < 5; q++) {
        const uint4 c = pb4[q], d = lds128(sb + OFF_DS + 20480 + tid * 16 + q * 4096);
        add8(q, make_uint4(add_bf2(c.x, d.x), add_bf2(c.y, d.y), add_bf2(c.z, d.z), add_bf2(c.w, d.w)));
      }
      __syncwarp();
      uint32_t ov[2][10];
#pragma unroll
      for (int g = 0; g < 10; g++) { ov[0][g] = pack_bf16(kp[4 * g], kp[4 * g + 1]); ov[1][g] = pack_bf16(kp[4 * g + 2], kp[4 * g + 3]); }
      stage_tile(sb + OFF_OUT, ov);
      __syncwarp();
      __nv_bfloat16* dst = out + (size_t)(128 * i + 16 * warp) * D_ + 80 * j;
#pragma unroll
      for (int q = 0; q < 5; q++) {
        const int id = q * 32 + lane, r = id / 10;
        *reinterpret_cast<uint4*>(dst + r * (D_ - 80) + id * 8) = lds128(sb + OFF_OUT + warp * 2560 + id * 16);
      }
    }
    TSTAMP(15);
    if (tid == 0) asm volatile("red.relaxed.gpu.global.add.u32 [%0], 1;" ::"l"(g_flags + FL_DONE * 32) : "memory");
  }
}

namespace {
typedef CUresult (*EncodeFn)(CUtensorMap*, CUtensorMapDataType, cuuint32_t, void*, const cuuint64_t*, const cuuint64_t*,
                             const cuuint32_t*, const cuuint32_t*, CUtensorMapInterleave, CUtensorMapSwizzle,
                             CUtensorMapL2promotion, CUtensorMapFloatOOBfill);

void encode(EncodeFn fn, CUtensorMap* m, const void* ptr, int rank, const cuuint64_t* dims, const cuuint64_t* strides,
            const cuuint32_t* box, CUtensorMapSwizzle swz) {
  cuuint32_t es[5] = {1, 1, 1, 1, 1};
  fn(m, CU_TENSOR_MAP_DATA_TYPE_BFLOAT16, rank, const_cast<void*>(ptr), dims, strides, box, es, CU_TENSOR_MAP_INTERLEAVE_NONE,
     swz, CU_TENSOR_MAP_L2_PROMOTION_L2_128B, CU_TENSOR_MAP_FLOAT_OOB_FILL_NONE);
}
}

extern "C" void kernel_launch(void* const* d_in, const int* in_sizes, int n_in, void* d_out, int out_size) {
  (void)in_sizes; (void)n_in; (void)out_size;
  const __nv_bfloat16* x = (const __nv_bfloat16*)d_in[0];
  const __nv_bfloat16* wqkv = (const __nv_bfloat16*)d_in[1];
  const __nv_bfloat16* wphi = (const __nv_bfloat16*)d_in[2];
  const __nv_bfloat16* wo = (const __nv_bfloat16*)d_in[3];
  const __nv_bfloat16* w1 = (const __nv_bfloat16*)d_in[5];
  const __nv_bfloat16* w2 = (const __nv_bfloat16*)d_in[6];
  const __nv_bfloat16* w3 = (const __nv_bfloat16*)d_in[7];
  const __nv_bfloat16* w4 = (const __nv_bfloat16*)d_in[8];
  const __nv_bfloat16* gate_w = (const __nv_bfloat16*)d_in[9];

  static EncodeFn enc = nullptr;
  static void *pHs = nullptr, *pX1 = nullptr;
  if (!enc) {
    cudaDriverEntryPointQueryResult qr;
    cudaGetDriverEntryPoint("cuTensorMapEncodeTiled", (void**)&enc, cudaEnableDefault, &qr);
    cudaGetSymbolAddress(&pHs, g_Hs);
    cudaGetSymbolAddress(&pX1, g_X1);
    cudaFuncSetAttribute(fused_kernel, cudaFuncAttributeMaxDynamicSharedMemorySize, SMEM_BYTES);
  }
  Maps m;
  {
    cuuint64_t dims[2] = {D_, S_}, str[1] = {D_ * 2};
    cuuint32_t box[2] = {64, 128}, boxh[2] = {64, 64};
    encode(enc, &m.x, x, 2, dims, str, boxh, CU_TENSOR_MAP_SWIZZLE_128B);
    encode(enc, &m.hs, (const char*)pHs + 2 * D_ * 2, 2, dims, str, box, CU_TENSOR_MAP_SWIZZLE_128B);
    encode(enc, &m.x1, pX1, 2, dims, str, boxh, CU_TENSOR_MAP_SWIZZLE_128B);
    cuuint32_t boxs[2] = {80, 128};
    cuuint64_t dimsp[2] = {D_, S_ + 4};
    encode(enc, &m.st_h, pHs, 2, dimsp, str, boxs, CU_TENSOR_MAP_SWIZZLE_NONE);
    encode(enc, &m.st_x1, pX1, 2, dims, str, boxs, CU_TENSOR_MAP_SWIZZLE_NONE);
    encode(enc, &m.xr, x, 2, dims, str, boxs, CU_TENSOR_MAP_SWIZZLE_NONE);
  }
  {
    cuuint64_t dims[3] = {80, D_, 8}, str[2] = {D_ * 2, 160};
    cuuint32_t boxm[3] = {64, 64, 1}, boxr[3] = {16, 64, 1};
    encode(enc, &m.w1m, w1, 3, dims, str, boxm, CU_TENSOR_MAP_SWIZZLE_128B);
    encode(enc, &m.w1r, w1, 3, dims, str, boxr, CU_TENSOR_MAP_SWIZZLE_32B);
  }
  {
    cuuint64_t dims[4] = {80, D_, 3, 8}, str[3] = {3 * D_ * 2, D_ * 2, 160};
    cuuint32_t boxm[4] = {64, 64, 3, 1}, boxr[4] = {16, 64, 3, 1};
    encode(enc, &m.qm, wqkv, 4, dims, str, boxm, CU_TENSOR_MAP_SWIZZLE_128B);
    encode(enc, &m.qr, wqkv, 4, dims, str, boxr, CU_TENSOR_MAP_SWIZZLE_32B);
  }
  {
    cuuint64_t dims[3] = {32, D_, 20}, dims4[3] = {32, F_, 20}, str[2] = {D_ * 2, 64};
    cuuint32_t box4[3] = {32, 64, 5}, boxo[3] = {32, 80, 5};
    encode(enc, &m.w4, w4, 3, dims4, str, box4, CU_TENSOR_MAP_SWIZZLE_64B);
    encode(enc, &m.wo, wo, 3, dims, str, boxo, CU_TENSOR_MAP_SWIZZLE_64B);
    encode(enc, &m.w2, w2, 3, dims, str, box4, CU_TENSOR_MAP_SWIZZLE_64B);
  }
  {
    cuuint64_t dims[3] = {64, D_, 24}, str[2] = {F_ * 2, 128};
    cuuint32_t box[3] = {64, 64, 3};
    encode(enc, &m.w3, w3, 3, dims, str, box, CU_TENSOR_MAP_SWIZZLE_128B);
  }
  fused_kernel<<<NCTA + NSVC, 384, SMEM_BYTES, cudaStreamPerThread>>>(m, x, wqkv, wphi, w1, w2, w3, w4, wo, gate_w, (__nv_bfloat16*)d_out);
}
```

```cpp
#include <cuda_runtime.h>
#include <cuda_bf16.h>
#include <cuda.h>
#include <stdint.h>

namespace {

constexpr int S_ = 2048, D_ = 640, F_ = 1536;
constexpr int NCTA = 128, NSVC = 4;
constexpr int KV_PAIR = 40 * 48 + 96;
constexpr int KV_J = 2 * KV_PAIR;

constexpr int SLOT_B = 49152, NB = 3;
constexpr int SLOT_A = 16384, NA = 4;
constexpr int OFF_B = 0;
constexpr int OFF_A = OFF_B + NB * SLOT_B;
constexpr int OFF_STG = OFF_A + 2 * SLOT_A;
constexpr int OFF_MISC = OFF_A + NA * SLOT_A;
constexpr int OFF_XST = OFF_MISC + 13312;
constexpr int OFF_CS = OFF_MISC + 16384;
constexpr int OFF_BAR = OFF_CS + 1088;
constexpr int SMEM_BYTES = OFF_BAR + 512 + 512 + 128;
constexpr int B_FULLA = 0, B_FULLB = 4, B_CS = 7, B_XR = 8, B_KV = 9, B_ST1 = 10, B_HST = 11, B_FULL4 = 12  , B_RDY = 20  , B_T4 = 23, B_KVR = 24,
              B_DSR = 25  , B_EMPTYB = 35  , B_SIGP = 38, B_SIGH = 39, B_SIGKV = 40, B_SIGX1 = 41, B_MFREE = 42,
              B_WDEAD = 43, B_EMPTY4 = 44  , B_EMPTYA = 52  , B_PEER = 56, B_PEER2 = 57, B_X1P = 58  , NBAR = 59;
constexpr int SPARE = 40960;
constexpr int SET4 = 87040, OFF_DS = 2 * SET4, OFF_OUT = 20480;

constexpr int FL_DONE = 0, FL_H = 1  , FL_X1 = FL_H + 32, FL_KV = FL_X1 + 16, FL_CS = FL_KV + 8, FL_CS3 = FL_CS + 1, FL_ST = FL_CS3 + 1;
constexpr int FL_S1 = FL_ST + 16, FL_COUNT = FL_S1 + 16;

struct Maps {
  CUtensorMap x, w1m, w1r, qm, qr, hs, w2, x1, w3, w4, wo, xr, st_h, st_x1;
};

}

__device__ __align__(1024) __nv_bfloat16 g_Hs[(S_ + 4) * D_];
__device__ __align__(1024) __nv_bfloat16 g_X1[S_ * D_];
__device__ __align__(128) float g_acc[2][8 * KV_J];
__device__ __align__(128) float g_cs[2][D_ + F_];
__device__ __align__(128) uint4 g_wphi[8 * 800];
__device__ __align__(128) float4 g_xstat[S_];
__device__ __align__(128) float2 g_st1[S_ * 8];
__device__ __align__(128) uint4 g_part[16 * 8 * 3 * 1280];
__device__ __align__(128) unsigned g_flags[FL_COUNT * 32];
#define TSTAMP(n) do {} while (0)
#define TSTAMPX(n) do {} while (0)
#define TRACE(n) do {} while (0)
#define TRS(n) do {} while (0)

namespace {

__device__ __forceinline__ long long gtime() { long long t; asm volatile("mov.u64 %0, %%globaltimer;" : "=l"(t)); return t; }
__device__ __forceinline__ uint32_t smem_u32(const void* p) { return (uint32_t)__cvta_generic_to_shared(p); }
__device__ __forceinline__ void mbar_init(uint32_t bar, int cnt) {
  asm volatile("mbarrier.init.shared::cta.b64 [%0], %1;" ::"r"(bar), "r"(cnt) : "memory");
}
__device__ __forceinline__ void mbar_expect_tx(uint32_t bar, int bytes) {
  asm volatile("mbarrier.arrive.expect_tx.shared::cta.b64 _, [%0], %1;" ::"r"(bar), "r"(bytes) : "memory");
}
__device__ __forceinline__ void mbar_arrive_cta(uint32_t bar, uint32_t cta) {
  asm volatile("{\n.reg .b32 ra;\nmapa.shared::cluster.u32 ra, %0, %1;\nmbarrier.arrive.shared::cluster.b64 _, [ra];\n}"
               ::"r"(bar), "r"(cta) : "memory");
}
__device__ __forceinline__ uint32_t mbar_try(uint32_t bar, uint32_t parity) {
  uint32_t ok;
  asm volatile("{\n.reg .pred p;\nmbarrier.try_wait.parity.shared::cta.b64 p, [%1], %2;\nselp.u32 %0, 1, 0, p;\n}"
               : "=r"(ok) : "r"(bar), "r"(parity) : "memory");
  return ok;
}
constexpr uint32_t WAIT_LIMIT = 1u << 17;
__device__ __forceinline__ void mbar_wait(uint32_t bar, uint32_t parity) {
  uint32_t n = 0;
  while (!mbar_try(bar, parity) && ++n < WAIT_LIMIT) {}
}
__device__ __forceinline__ unsigned ld_acquire(const unsigned* p) {
  unsigned v;
  asm volatile("ld.acquire.gpu.global.u32 %0, [%1];" : "=r"(v) : "l"(p) : "memory");
  return v;
}
__device__ __forceinline__ void flag_wait(int idx, unsigned target) {
  const unsigned* p = g_flags + idx * 32;
  uint32_t n = 0;
  while ((int)(ld_acquire(p) - target) < 0 && ++n < (WAIT_LIMIT >> 2)) {}
}
__device__ __forceinline__ void flag_add(int idx) {
  asm volatile("red.release.gpu.global.add.u32 [%0], 1;" ::"l"(g_flags + idx * 32) : "memory");
}
__device__ __forceinline__ void flag_add_relaxed(int idx) {
  asm volatile("red.relaxed.gpu.global.add.u32 [%0], 1;" ::"l"(g_flags + idx * 32) : "memory");
}
__device__ __forceinline__ uint32_t mbar_test(uint32_t bar, uint32_t parity) {
  uint32_t ok;
  asm volatile("{\n.reg .pred p;\nmbarrier.test_wait.parity.shared::cta.b64 p, [%1], %2;\nselp.u32 %0, 1, 0, p;\n}"
               : "=r"(ok) : "r"(bar), "r"(parity) : "memory");
  return ok;
}
__device__ __forceinline__ uint32_t lds32(uint32_t a) {
  uint32_t v;
  asm volatile("ld.shared.u32 %0, [%1];" : "=r"(v) : "r"(a) : "memory");
  return v;
}
__device__ __forceinline__ void mbar_arrive(uint32_t bar) {
  asm volatile("mbarrier.arrive.shared::cta.b64 _, [%0];" ::"r"(bar) : "memory");
}
__device__ __forceinline__ void fence_async_glb() { asm volatile("fence.proxy.async.global;" ::: "memory"); }
__device__ __forceinline__ void fence_async_smem() { asm volatile("fence.proxy.async.shared::cta;" ::: "memory"); }
__device__ __forceinline__ void bar_sync(int id, int n) { asm volatile("bar.sync %0, %1;" ::"r"(id), "r"(n) : "memory"); }

__device__ __forceinline__ void tma2d(uint32_t dst, const CUtensorMap* m, uint32_t bar, int c0, int c1) {
  asm volatile("cp.async.bulk.tensor.2d.shared::cluster.global.mbarrier::complete_tx::bytes [%0], [%1, {%3, %4}], [%2];"
               ::"r"(dst), "l"(m), "r"(bar), "r"(c0), "r"(c1) : "memory");
}
__device__ __forceinline__ void tma2d_mc(uint32_t dst, const CUtensorMap* m, uint32_t bar, int c0, int c1) {
  asm volatile("cp.async.bulk.tensor.2d.shared::cluster.global.mbarrier::complete_tx::bytes.multicast::cluster"
               " [%0], [%1, {%3, %4}], [%2], %5;"
               ::"r"(dst), "l"(m), "r"(bar), "r"(c0), "r"(c1), "h"((uint16_t)3) : "memory");
}
__device__ __forceinline__ void tma3d(uint32_t dst, const CUtensorMap* m, uint32_t bar, int c0, int c1, int c2) {
  asm volatile("cp.async.bulk.tensor.3d.shared::cluster.global.mbarrier::complete_tx::bytes [%0], [%1, {%3, %4, %5}], [%2];"
               ::"r"(dst), "l"(m), "r"(bar), "r"(c0), "r"(c1), "r"(c2) : "memory");
}
__device__ __forceinline__ void tma4d(uint32_t dst, const CUtensorMap* m, uint32_t bar, int c0, int c1, int c2, int c3) {
  asm volatile("cp.async.bulk.tensor.4d.shared::cluster.global.mbarrier::complete_tx::bytes [%0], [%1, {%3, %4, %5, %6}], [%2];"
               ::"r"(dst), "l"(m), "r"(bar), "r"(c0), "r"(c1), "r"(c2), "r"(c3) : "memory");
}
__device__ __forceinline__ void tma2d_store(const CUtensorMap* m, uint32_t src, int c0, int c1) {
  asm volatile("cp.async.bulk.tensor.2d.global.shared::cta.bulk_group [%0, {%2, %3}], [%1];"
               ::"l"(m), "r"(src), "r"(c0), "r"(c1) : "memory");
}
__device__ __forceinline__ void bulk_store(void* dst, uint32_t src, uint32_t bytes) {
  asm volatile("cp.async.bulk.global.shared::cta.bulk_group [%0], [%1], %2;" ::"l"(dst), "r"(src), "r"(bytes) : "memory");
}
__device__ __forceinline__ void bulk_load(uint32_t dst, const void* src, uint32_t bytes, uint32_t bar) {
  asm volatile("cp.async.bulk.shared::cluster.global.mbarrier::complete_tx::bytes [%0], [%1], %2, [%3];"
               ::"r"(dst), "l"(src), "r"(bytes), "r"(bar) : "memory");
}
__device__ __forceinline__ void bulk_commit() { asm volatile("cp.async.bulk.commit_group;" ::: "memory"); }
template <int N> __device__ __forceinline__ void bulk_wait() { asm volatile("cp.async.bulk.wait_group %0;" ::"n"(N) : "memory"); }
__device__ __forceinline__ void bulk_wait_read() { asm volatile("cp.async.bulk.wait_group.read 0;" ::: "memory"); }
__device__ __forceinline__ void bar_arrive(int id, int n) { asm volatile("bar.arrive %0, %1;" ::"r"(id), "r"(n) : "memory"); }
__device__ __forceinline__ uint4 lds128(uint32_t a) {
  uint4 v;
  asm volatile("ld.shared.v4.u32 {%0, %1, %2, %3}, [%4];" : "=r"(v.x), "=r"(v.y), "=r"(v.z), "=r"(v.w) : "r"(a) : "memory");
  return v;
}
__device__ __forceinline__ void sts128(uint32_t a, uint4 v) {
  asm volatile("st.shared.v4.u32 [%0], {%1, %2, %3, %4};" ::"r"(a), "r"(v.x), "r"(v.y), "r"(v.z), "r"(v.w) : "memory");
}
__device__ __forceinline__ uint4 ld_relaxed16(const uint4* p) {
  uint4 v;
  asm volatile("ld.relaxed.gpu.global.v4.u32 {%0, %1, %2, %3}, [%4];" : "=r"(v.x), "=r"(v.y), "=r"(v.z), "=r"(v.w) : "l"(p) : "memory");
  return v;
}
__device__ __forceinline__ void st_relaxed16(uint4* p, uint32_t a, uint32_t b, uint32_t c, uint32_t d) {
  asm volatile("st.relaxed.gpu.global.v4.u32 [%0], {%1, %2, %3, %4};" ::"l"(p), "r"(a), "r"(b), "r"(c), "r"(d) : "memory");
}
__device__ __forceinline__ uint32_t map_peer(uint32_t addr, uint32_t cta) {
  uint32_t r;
  asm("mapa.shared::cluster.u32 %0, %1, %2;" : "=r"(r) : "r"(addr), "r"(cta));
  return r;
}
__device__ __forceinline__ void st_async16(uint32_t addr, uint32_t a, uint32_t b, uint32_t c, uint32_t d, uint32_t bar) {
  asm volatile("st.async.weak.shared::cluster.mbarrier::complete_tx::bytes.v4.b32 [%0], {%1, %2, %3, %4}, [%5];"
               ::"r"(addr), "r"(a), "r"(b), "r"(c), "r"(d), "r"(bar) : "memory");
}
__device__ __forceinline__ void l2_prefetch(const void* p, uint32_t bytes) {
  asm volatile("cp.async.bulk.prefetch.L2.global [%0], %1;" ::"l"(p), "r"(bytes) : "memory");
}
__device__ __forceinline__ void prefetch_tmap(const CUtensorMap* m) {
  asm volatile("prefetch.tensormap [%0];" ::"l"(m) : "memory");
}
__device__ __forceinline__ uint64_t make_desc(uint32_t a16, uint32_t off, uint32_t lbo, uint32_t sbo, uint32_t swz) {
  const uint32_t lo = a16 + ((off >> 4) + ((lbo >> 4) << 16)), hi = (sbo >> 4) | (swz << 30);
  uint64_t d;
  asm("mov.b64 %0, {%1, %2};" : "=l"(d) : "r"(lo), "r"(hi));
  return d;
}
__device__ __forceinline__ void wg_fence() { asm volatile("wgmma.fence.sync.aligned;" ::: "memory"); }
__device__ __forceinline__ void wg_commit() { asm volatile("wgmma.commit_group.sync.aligned;" ::: "memory"); }
template <int N> __device__ __forceinline__ void wg_wait() { asm volatile("wgmma.wait_group.sync.aligned %0;" ::"n"(N) : "memory"); }
template <int N> __device__ __forceinline__ void fence_regs(float (&d)[N]) {
#pragma unroll
  for (int i = 0; i < N; i++) asm volatile("" : "+f"(d[i])::"memory");
}
template <int N> __device__ __forceinline__ void zero_regs(float (&d)[N]) {
#pragma unroll
  for (int i = 0; i < N; i++) d[i] = 0.f;
}
__device__ __forceinline__ uint32_t pack_bf16(float lo, float hi) {
  uint32_t r;
  asm("cvt.rn.bf16x2.f32 %0, %1, %2;" : "=r"(r) : "f"(hi), "f"(lo));
  return r;
}
__device__ __forceinline__ float bf_lo(uint32_t v) { return __uint_as_float(v << 16); }
__device__ __forceinline__ float bf_hi(uint32_t v) { return __uint_as_float(v & 0xffff0000u); }
__device__ __forceinline__ uint32_t max_bf2(uint32_t a, uint32_t b) {
  uint32_t r; asm("max.bf16x2 %0, %1, %2;" : "=r"(r) : "r"(a), "r"(b)); return r;
}
__device__ __forceinline__ uint32_t min_bf2(uint32_t a, uint32_t b) {
  uint32_t r; asm("min.bf16x2 %0, %1, %2;" : "=r"(r) : "r"(a), "r"(b)); return r;
}
__device__ __forceinline__ uint32_t add_bf2(uint32_t a, uint32_t b) {
  uint32_t r; asm("add.rn.bf16x2 %0, %1, %2;" : "=r"(r) : "r"(a), "r"(b)); return r;
}
__device__ __forceinline__ uint32_t mul_bf2(uint32_t a, uint32_t b) {
  uint32_t r; asm("mul.rn.bf16x2 %0, %1, %2;" : "=r"(r) : "r"(a), "r"(b)); return r;
}
__device__ __forceinline__ float ex2(float x) { float r; asm("ex2.approx.ftz.f32 %0, %1;" : "=f"(r) : "f"(x)); return r; }
__device__ __forceinline__ float rcp(float x) { float r; asm("rcp.approx.ftz.f32 %0, %1;" : "=f"(r) : "f"(x)); return r; }
__device__ __forceinline__ float tanh_ap(float x) { float r; asm("tanh.approx.f32 %0, %1;" : "=f"(r) : "f"(x)); return r; }
struct GeluC { float c0, c1, ch; };
__device__ __forceinline__ GeluC gelu_consts(float rstd, float scale) {
  return GeluC{0.7978845608f * rstd, 0.0356774081f * rstd * rstd * rstd, 0.5f * scale * rstd};
}
__device__ __forceinline__ float gelu_s(float y, const GeluC& c) {
  const float u = y * fmaf(y * y, c.c1, c.c0);
  const float hx = y * c.ch;
  return fmaf(hx, tanh_ap(u), hx);
}
__device__ __forceinline__ void stsm4(uint32_t addr, uint32_t r0, uint32_t r1, uint32_t r2, uint32_t r3) {
  asm volatile("stmatrix.sync.aligned.m8n8.x4.shared.b16 [%0], {%1, %2, %3, %4};"
               ::"r"(addr), "r"(r0), "r"(r1), "r"(r2), "r"(r3) : "memory");
}

__device__ __forceinline__ uint4 ldsm4(uint32_t addr) {
  uint4 v;
  asm volatile("ldmatrix.sync.aligned.m8n8.x4.shared.b16 {%0, %1, %2, %3}, [%4];"
               : "=r"(v.x), "=r"(v.y), "=r"(v.z), "=r"(v.w) : "r"(addr) : "memory");
  return v;
}
__device__ __forceinline__ void red_add4(float* p, float a, float b, float c, float d) {
  asm volatile("red.global.add.v4.f32 [%0], {%1, %2, %3, %4};" ::"l"(p), "f"(a), "f"(b), "f"(c), "f"(d) : "memory");
}

__device__ __forceinline__ void mma_ss256(float (&d)[128], uint64_t descA, uint64_t descB) {
  asm volatile("wgmma.mma_async.sync.aligned.m64n256k16.f32.bf16.bf16 {"
      "%0, %1, %2, %3, %4, %5, %6, %7, %8, %9, %10, %11, %12, %13, %14, %15, "
      "%16, %17, %18, %19, %20, %21, %22, %23, %24, %25, %26, %27, %28, %29, %30, %31, "
      "%32, %33, %34, %35, %36, %37, %38, %39, %40, %41, %42, %43, %44, %45, %46, %47, "
      "%48, %49, %50, %51, %52, %53, %54, %55, %56, %57, %58, %59, %60, %61, %62, %63, "
      "%64, %65, %66, %67, %68, %69, %70, %71, %72, %73, %74, %75, %76, %77, %78, %79, "
      "%80, %81, %82, %83, %84, %85, %86, %87, %88, %89, %90, %91, %92, %93, %94, %95, "
      "%96, %97, %98, %99, %100, %101, %102, %103, %104, %105, %106, %107, %108, %109, %110, %111, "
      "%112, %113, %114, %115, %116, %117, %118, %119, %120, %121, %122, %123, %124, %125, %126, %127"
      "}, %128, %129, 1, 1, 1, 0, 1;\n"
      : "+f"(d[0]), "+f"(d[1]), "+f"(d[2]), "+f"(d[3]), "+f"(d[4]), "+f"(d[5]), "+f"(d[6]), "+f"(d[7]),
        "+f"(d[8]), "+f"(d[9]), "+f"(d[10]), "+f"(d[11]), "+f"(d[12]), "+f"(d[13]), "+f"(d[14]), "+f"(d[15]),
        "+f"(d[16]), "+f"(d[17]), "+f"(d[18]), "+f"(d[19]), "+f"(d[20]), "+f"(d[21]), "+f"(d[22]), "+f"(d[23]),
        "+f"(d[24]), "+f"(d[25]), "+f"(d[26]), "+f"(d[27]), "+f"(d[28]), "+f"(d[29]), "+f"(d[30]), "+f"(d[31]),
        "+f"(d[32]), "+f"(d[33]), "+f"(d[34]), "+f"(d[35]), "+f"(d[36]), "+f"(d[37]), "+f"(d[38]), "+f"(d[39]),
        "+f"(d[40]), "+f"(d[41]), "+f"(d[42]), "+f"(d[43]), "+f"(d[44]), "+f"(d[45]), "+f"(d[46]), "+f"(d[47]),
        "+f"(d[48]), "+f"(d[49]), "+f"(d[50]), "+f"(d[51]), "+f"(d[52]), "+f"(d[53]), "+f"(d[54]), "+f"(d[55]),
        "+f"(d[56]), "+f"(d[57]), "+f"(d[58]), "+f"(d[59]), "+f"(d[60]), "+f"(d[61]), "+f"(d[62]), "+f"(d[63]),
        "+f"(d[64]), "+f"(d[65]), "+f"(d[66]), "+f"(d[67]), "+f"(d[68]), "+f"(d[69]), "+f"(d[70]), "+f"(d[71]),
        "+f"(d[72]), "+f"(d[73]), "+f"(d[74]), "+f"(d[75]), "+f"(d[76]), "+f"(d[77]), "+f"(d[78]), "+f"(d[79]),
        "+f"(d[80]), "+f"(d[81]), "+f"(d[82]), "+f"(d[83]), "+f"(d[84]), "+f"(d[85]), "+f"(d[86]), "+f"(d[87]),
        "+f"(d[88]), "+f"(d[89]), "+f"(d[90]), "+f"(d[91]), "+f"(d[92]), "+f"(d[93]), "+f"(d[94]), "+f"(d[95]),
        "+f"(d[96]), "+f"(d[97]), "+f"(d[98]), "+f"(d[99]), "+f"(d[100]), "+f"(d[101]), "+f"(d[102]), "+f"(d[103]),
        "+f"(d[104]), "+f"(d[105]), "+f"(d[106]), "+f"(d[107]), "+f"(d[108]), "+f"(d[109]), "+f"(d[110]), "+f"(d[111]),
        "+f"(d[112]), "+f"(d[113]), "+f"(d[114]), "+f"(d[115]), "+f"(d[116]), "+f"(d[117]), "+f"(d[118]), "+f"(d[119]),
        "+f"(d[120]), "+f"(d[121]), "+f"(d[122]), "+f"(d[123]), "+f"(d[124]), "+f"(d[125]), "+f"(d[126]), "+f"(d[127])
      : "l"(descA), "l"(descB));
}
__device__ __forceinline__ void mma_ss256_p(float (&d)[128], uint64_t descA, uint64_t descB, int acc) {
  asm volatile("{\n.reg .pred p;\nsetp.ne.b32 p, %130, 0;\n"
      "wgmma.mma_async.sync.aligned.m64n256k16.f32.bf16.bf16 {"
      "%0, %1, %2, %3, %4, %5, %6, %7, %8, %9, %10, %11, %12, %13, %14, %15, "
      "%16, %17, %18, %19, %20, %21, %22, %23, %24, %25, %26, %27, %28, %29, %30, %31, "
      "%32, %33, %34, %35, %36, %37, %38, %39, %40, %41, %42, %43, %44, %45, %46, %47, "
      "%48, %49, %50, %51, %52, %53, %54, %55, %56, %57, %58, %59, %60, %61, %62, %63, "
      "%64, %65, %66, %67, %68, %69, %70, %71, %72, %73, %74, %75, %76, %77, %78, %79, "
      "%80, %81, %82, %83, %84, %85, %86, %87, %88, %89, %90, %91, %92, %93, %94, %95, "
      "%96, %97, %98, %99, %100, %101, %102, %103, %104, %105, %106, %107, %108, %109, %110, %111, "
      "%112, %113, %114, %115, %116, %117, %118, %119, %120, %121, %122, %123, %124, %125, %126, %127"
      "}, %128, %129, p, 1, 1, 0, 1;\n}\n"
      : "+f"(d[0]), "+f"(d[1]), "+f"(d[2]), "+f"(d[3]), "+f"(d[4]), "+f"(d[5]), "+f"(d[6]), "+f"(d[7]),
        "+f"(d[8]), "+f"(d[9]), "+f"(d[10]), "+f"(d[11]), "+f"(d[12]), "+f"(d[13]), "+f"(d[14]), "+f"(d[15]),
        "+f"(d[16]), "+f"(d[17]), "+f"(d[18]), "+f"(d[19]), "+f"(d[20]), "+f"(d[21]), "+f"(d[22]), "+f"(d[23]),
        "+f"(d[24]), "+f"(d[25]), "+f"(d[26]), "+f"(d[27]), "+f"(d[28]), "+f"(d[29]), "+f"(d[30]), "+f"(d[31]),
        "+f"(d[32]), "+f"(d[33]), "+f"(d[34]), "+f"(d[35]), "+f"(d[36]), "+f"(d[37]), "+f"(d[38]), "+f"(d[39]),
        "+f"(d[40]), "+f"(d[41]), "+f"(d[42]), "+f"(d[43]), "+f"(d[44]), "+f"(d[45]), "+f"(d[46]), "+f"(d[47]),
        "+f"(d[48]), "+f"(d[49]), "+f"(d[50]), "+f"(d[51]), "+f"(d[52]), "+f"(d[53]), "+f"(d[54]), "+f"(d[55]),
        "+f"(d[56]), "+f"(d[57]), "+f"(d[58]), "+f"(d[59]), "+f"(d[60]), "+f"(d[61]), "+f"(d[62]), "+f"(d[63]),
        "+f"(d[64]), "+f"(d[65]), "+f"(d[66]), "+f"(d[67]), "+f"(d[68]), "+f"(d[69]), "+f"(d[70]), "+f"(d[71]),
        "+f"(d[72]), "+f"(d[73]), "+f"(d[74]), "+f"(d[75]), "+f"(d[76]), "+f"(d[77]), "+f"(d[78]), "+f"(d[79]),
        "+f"(d[80]), "+f"(d[81]), "+f"(d[82]), "+f"(d[83]), "+f"(d[84]), "+f"(d[85]), "+f"(d[86]), "+f"(d[87]),
        "+f"(d[88]), "+f"(d[89]), "+f"(d[90]), "+f"(d[91]), "+f"(d[92]), "+f"(d[93]), "+f"(d[94]), "+f"(d[95]),
        "+f"(d[96]), "+f"(d[97]), "+f"(d[98]), "+f"(d[99]), "+f"(d[100]), "+f"(d[101]), "+f"(d[102]), "+f"(d[103]),
        "+f"(d[104]), "+f"(d[105]), "+f"(d[106]), "+f"(d[107]), "+f"(d[108]), "+f"(d[109]), "+f"(d[110]), "+f"(d[111]),
        "+f"(d[112]), "+f"(d[113]), "+f"(d[114]), "+f"(d[115]), "+f"(d[116]), "+f"(d[117]), "+f"(d[118]), "+f"(d[119]),
        "+f"(d[120]), "+f"(d[121]), "+f"(d[122]), "+f"(d[123]), "+f"(d[124]), "+f"(d[125]), "+f"(d[126]), "+f"(d[127])
      : "l"(descA), "l"(descB), "r"(acc));
}

__device__ __forceinline__ void mma_ss64(float (&d)[32], uint64_t descA, uint64_t descB) {
  asm volatile("wgmma.mma_async.sync.aligned.m64n64k16.f32.bf16.bf16 {"
      "%0, %1, %2, %3, %4, %5, %6, %7, %8, %9, %10, %11, %12, %13, %14, %15, "
      "%16, %17, %18, %19, %20, %21, %22, %23, %24, %25, %26, %27, %28, %29, %30, %31"
      "}, %32, %33, 1, 1, 1, 0, 1;\n"
      : "+f"(d[0]), "+f"(d[1]), "+f"(d[2]), "+f"(d[3]), "+f"(d[4]), "+f"(d[5]), "+f"(d[6]), "+f"(d[7]),
        "+f"(d[8]), "+f"(d[9]), "+f"(d[10]), "+f"(d[11]), "+f"(d[12]), "+f"(d[13]), "+f"(d[14]), "+f"(d[15]),
        "+f"(d[16]), "+f"(d[17]), "+f"(d[18]), "+f"(d[19]), "+f"(d[20]), "+f"(d[21]), "+f"(d[22]), "+f"(d[23]),
        "+f"(d[24]), "+f"(d[25]), "+f"(d[26]), "+f"(d[27]), "+f"(d[28]), "+f"(d[29]), "+f"(d[30]), "+f"(d[31])
      : "l"(descA), "l"(descB));
}
__device__ __forceinline__ void mma_ss64_p(float (&d)[32], uint64_t descA, uint64_t descB, int acc) {
  asm volatile("{\n.reg .pred p;\nsetp.ne.b32 p, %34, 0;\n"
      "wgmma.mma_async.sync.aligned.m64n64k16.f32.bf16.bf16 {"
      "%0, %1, %2, %3, %4, %5, %6, %7, %8, %9, %10, %11, %12, %13, %14, %15, "
      "%16, %17, %18, %19, %20, %21, %22, %23, %24, %25, %26, %27, %28, %29, %30, %31"
      "}, %32, %33, p, 1, 1, 0, 1;\n}\n"
      : "+f"(d[0]), "+f"(d[1]), "+f"(d[2]), "+f"(d[3]), "+f"(d[4]), "+f"(d[5]), "+f"(d[6]), "+f"(d[7]),
        "+f"(d[8]), "+f"(d[9]), "+f"(d[10]), "+f"(d[11]), "+f"(d[12]), "+f"(d[13]), "+f"(d[14]), "+f"(d[15]),
        "+f"(d[16]), "+f"(d[17]), "+f"(d[18]), "+f"(d[19]), "+f"(d[20]), "+f"(d[21]), "+f"(d[22]), "+f"(d[23]),
        "+f"(d[24]), "+f"(d[25]), "+f"(d[26]), "+f"(d[27]), "+f"(d[28]), "+f"(d[29]), "+f"(d[30]), "+f"(d[31])
      : "l"(descA), "l"(descB), "r"(acc));
}

__device__ __forceinline__ void mma_ss160(float (&d)[80], uint64_t descA, uint64_t descB) {
  asm volatile("wgmma.mma_async.sync.aligned.m64n160k16.f32.bf16.bf16 {"
      "%0, %1, %2, %3, %4, %5, %6, %7, %8, %9, %10, %11, %12, %13, %14, %15, "
      "%16, %17, %18, %19, %20, %21, %22, %23, %24, %25, %26, %27, %28, %29, %30, %31, "
      "%32, %33, %34, %35, %36, %37, %38, %39, %40, %41, %42, %43, %44, %45, %46, %47, "
      "%48, %49, %50, %51, %52, %53, %54, %55, %56, %57, %58, %59, %60, %61, %62, %63, "
      "%64, %65, %66, %67, %68, %69, %70, %71, %72, %73, %74, %75, %76, %77, %78, %79"
      "}, %80, %81, 1, 1, 1, 0, 1;\n"
      : "+f"(d[0]), "+f"(d[1]), "+f"(d[2]), "+f"(d[3]), "+f"(d[4]), "+f"(d[5]), "+f"(d[6]), "+f"(d[7]),
        "+f"(d[8]), "+f"(d[9]), "+f"(d[10]), "+f"(d[11]), "+f"(d[12]), "+f"(d[13]), "+f"(d[14]), "+f"(d[15]),
        "+f"(d[16]), "+f"(d[17]), "+f"(d[18]), "+f"(d[19]), "+f"(d[20]), "+f"(d[21]), "+f"(d[22]), "+f"(d[23]),
        "+f"(d[24]), "+f"(d[25]), "+f"(d[26]), "+f"(d[27]), "+f"(d[28]), "+f"(d[29]), "+f"(d[30]), "+f"(d[31]),
        "+f"(d[32]), "+f"(d[33]), "+f"(d[34]), "+f"(d[35]), "+f"(d[36]), "+f"(d[37]), "+f"(d[38]), "+f"(d[39]),
        "+f"(d[40]), "+f"(d[41]), "+f"(d[42]), "+f"(d[43]), "+f"(d[44]), "+f"(d[45]), "+f"(d[46]), "+f"(d[47]),
        "+f"(d[48]), "+f"(d[49]), "+f"(d[50]), "+f"(d[51]), "+f"(d[52]), "+f"(d[53]), "+f"(d[54]), "+f"(d[55]),
        "+f"(d[56]), "+f"(d[57]), "+f"(d[58]), "+f"(d[59]), "+f"(d[60]), "+f"(d[61]), "+f"(d[62]), "+f"(d[63]),
        "+f"(d[64]), "+f"(d[65]), "+f"(d[66]), "+f"(d[67]), "+f"(d[68]), "+f"(d[69]), "+f"(d[70]), "+f"(d[71]),
        "+f"(d[72]), "+f"(d[73]), "+f"(d[74]), "+f"(d[75]), "+f"(d[76]), "+f"(d[77]), "+f"(d[78]), "+f"(d[79])
      : "l"(descA), "l"(descB));
}
__device__ __forceinline__ void mma_ss160_z(float (&d)[80], uint64_t descA, uint64_t descB) {
  asm volatile("wgmma.mma_async.sync.aligned.m64n160k16.f32.bf16.bf16 {"
      "%0, %1, %2, %3, %4, %5, %6, %7, %8, %9, %10, %11, %12, %13, %14, %15, "
      "%16, %17, %18, %19, %20, %21, %22, %23, %24, %25, %26, %27, %28, %29, %30, %31, "
      "%32, %33, %34, %35, %36, %37, %38, %39, %40, %41, %42, %43, %44, %45, %46, %47, "
      "%48, %49, %50, %51, %52, %53, %54, %55, %56, %57, %58, %59, %60, %61, %62, %63, "
      "%64, %65, %66, %67, %68, %69, %70, %71, %72, %73, %74, %75, %76, %77, %78, %79"
      "}, %80, %81, 0, 1, 1, 0, 1;\n"
      : "=f"(d[0]), "=f"(d[1]), "=f"(d[2]), "=f"(d[3]), "=f"(d[4]), "=f"(d[5]), "=f"(d[6]), "=f"(d[7]),
        "=f"(d[8]), "=f"(d[9]), "=f"(d[10]), "=f"(d[11]), "=f"(d[12]), "=f"(d[13]), "=f"(d[14]), "=f"(d[15]),
        "=f"(d[16]), "=f"(d[17]), "=f"(d[18]), "=f"(d[19]), "=f"(d[20]), "=f"(d[21]), "=f"(d[22]), "=f"(d[23]),
        "=f"(d[24]), "=f"(d[25]), "=f"(d[26]), "=f"(d[27]), "=f"(d[28]), "=f"(d[29]), "=f"(d[30]), "=f"(d[31]),
        "=f"(d[32]), "=f"(d[33]), "=f"(d[34]), "=f"(d[35]), "=f"(d[36]), "=f"(d[37]), "=f"(d[38]), "=f"(d[39]),
        "=f"(d[40]), "=f"(d[41]), "=f"(d[42]), "=f"(d[43]), "=f"(d[44]), "=f"(d[45]), "=f"(d[46]), "=f"(d[47]),
        "=f"(d[48]), "=f"(d[49]), "=f"(d[50]), "=f"(d[51]), "=f"(d[52]), "=f"(d[53]), "=f"(d[54]), "=f"(d[55]),
        "=f"(d[56]), "=f"(d[57]), "=f"(d[58]), "=f"(d[59]), "=f"(d[60]), "=f"(d[61]), "=f"(d[62]), "=f"(d[63]),
        "=f"(d[64]), "=f"(d[65]), "=f"(d[66]), "=f"(d[67]), "=f"(d[68]), "=f"(d[69]), "=f"(d[70]), "=f"(d[71]),
        "=f"(d[72]), "=f"(d[73]), "=f"(d[74]), "=f"(d[75]), "=f"(d[76]), "=f"(d[77]), "=f"(d[78]), "=f"(d[79])
      : "l"(descA), "l"(descB));
}

__device__ __forceinline__ void mma_ss192(float (&d)[96], uint64_t descA, uint64_t descB) {
  asm volatile("wgmma.mma_async.sync.aligned.m64n192k16.f32.bf16.bf16 {"
      "%0, %1, %2, %3, %4, %5, %6, %7, %8, %9, %10, %11, %12, %13, %14, %15, "
      "%16, %17, %18, %19, %20, %21, %22, %23, %24, %25, %26, %27, %28, %29, %30, %31, "
      "%32, %33, %34, %35, %36, %37, %38, %39, %40, %41, %42, %43, %44, %45, %46, %47, "
      "%48, %49, %50, %51, %52, %53, %54, %55, %56, %57, %58, %59, %60, %61, %62, %63, "
      "%64, %65, %66, %67, %68, %69, %70, %71, %72, %73, %74, %75, %76, %77, %78, %79, "
      "%80, %81, %82, %83, %84, %85, %86, %87, %88, %89, %90, %91, %92, %93, %94, %95"
      "}, %96, %97, 1, 1, 1, 0, 1;\n"
      : "+f"(d[0]), "+f"(d[1]), "+f"(d[2]), "+f"(d[3]), "+f"(d[4]), "+f"(d[5]), "+f"(d[6]), "+f"(d[7]),
        "+f"(d[8]), "+f"(d[9]), "+f"(d[10]), "+f"(d[11]), "+f"(d[12]), "+f"(d[13]), "+f"(d[14]), "+f"(d[15]),
        "+f"(d[16]), "+f"(d[17]), "+f"(d[18]), "+f"(d[19]), "+f"(d[20]), "+f"(d[21]), "+f"(d[22]), "+f"(d[23]),
        "+f"(d[24]), "+f"(d[25]), "+f"(d[26]), "+f"(d[27]), "+f"(d[28]), "+f"(d[29]), "+f"(d[30]), "+f"(d[31]),
        "+f"(d[32]), "+f"(d[33]), "+f"(d[34]), "+f"(d[35]), "+f"(d[36]), "+f"(d[37]), "+f"(d[38]), "+f"(d[39]),
        "+f"(d[40]), "+f"(d[41]), "+f"(d[42]), "+f"(d[43]), "+f"(d[44]), "+f"(d[45]), "+f"(d[46]), "+f"(d[47]),
        "+f"(d[48]), "+f"(d[49]), "+f"(d[50]), "+f"(d[51]), "+f"(d[52]), "+f"(d[53]), "+f"(d[54]), "+f"(d[55]),
        "+f"(d[56]), "+f"(d[57]), "+f"(d[58]), "+f"(d[59]), "+f"(d[60]), "+f"(d[61]), "+f"(d[62]), "+f"(d[63]),
        "+f"(d[64]), "+f"(d[65]), "+f"(d[66]), "+f"(d[67]), "+f"(d[68]), "+f"(d[69]), "+f"(d[70]), "+f"(d[71]),
        "+f"(d[72]), "+f"(d[73]), "+f"(d[74]), "+f"(d[75]), "+f"(d[76]), "+f"(d[77]), "+f"(d[78]), "+f"(d[79]),
        "+f"(d[80]), "+f"(d[81]), "+f"(d[82]), "+f"(d[83]), "+f"(d[84]), "+f"(d[85]), "+f"(d[86]), "+f"(d[87]),
        "+f"(d[88]), "+f"(d[89]), "+f"(d[90]), "+f"(d[91]), "+f"(d[92]), "+f"(d[93]), "+f"(d[94]), "+f"(d[95])
      : "l"(descA), "l"(descB));
}
__device__ __forceinline__ void mma_ss192_p(float (&d)[96], uint64_t descA, uint64_t descB, int acc) {
  asm volatile("{\n.reg .pred p;\nsetp.ne.b32 p, %98, 0;\n"
      "wgmma.mma_async.sync.aligned.m64n192k16.f32.bf16.bf16 {"
      "%0, %1, %2, %3, %4, %5, %6, %7, %8, %9, %10, %11, %12, %13, %14, %15, "
      "%16, %17, %18, %19, %20, %21, %22, %23, %24, %25, %26, %27, %28, %29, %30, %31, "
      "%32, %33, %34, %35, %36, %37, %38, %39, %40, %41, %42, %43, %44, %45, %46, %47, "
      "%48, %49, %50, %51, %52, %53, %54, %55, %56, %57, %58, %59, %60, %61, %62, %63, "
      "%64, %65, %66, %67, %68, %69, %70, %71, %72, %73, %74, %75, %76, %77, %78, %79, "
      "%80, %81, %82, %83, %84, %85, %86, %87, %88, %89, %90, %91, %92, %93, %94, %95"
      "}, %96, %97, p, 1, 1, 0, 1;\n}\n"
      : "+f"(d[0]), "+f"(d[1]), "+f"(d[2]), "+f"(d[3]), "+f"(d[4]), "+f"(d[5]), "+f"(d[6]), "+f"(d[7]),
        "+f"(d[8]), "+f"(d[9]), "+f"(d[10]), "+f"(d[11]), "+f"(d[12]), "+f"(d[13]), "+f"(d[14]), "+f"(d[15]),
        "+f"(d[16]), "+f"(d[17]), "+f"(d[18]), "+f"(d[19]), "+f"(d[20]), "+f"(d[21]), "+f"(d[22]), "+f"(d[23]),
        "+f"(d[24]), "+f"(d[25]), "+f"(d[26]), "+f"(d[27]), "+f"(d[28]), "+f"(d[29]), "+f"(d[30]), "+f"(d[31]),
        "+f"(d[32]), "+f"(d[33]), "+f"(d[34]), "+f"(d[35]), "+f"(d[36]), "+f"(d[37]), "+f"(d[38]), "+f"(d[39]),
        "+f"(d[40]), "+f"(d[41]), "+f"(d[42]), "+f"(d[43]), "+f"(d[44]), "+f"(d[45]), "+f"(d[46]), "+f"(d[47]),
        "+f"(d[48]), "+f"(d[49]), "+f"(d[50]), "+f"(d[51]), "+f"(d[52]), "+f"(d[53]), "+f"(d[54]), "+f"(d[55]),
        "+f"(d[56]), "+f"(d[57]), "+f"(d[58]), "+f"(d[59]), "+f"(d[60]), "+f"(d[61]), "+f"(d[62]), "+f"(d[63]),
        "+f"(d[64]), "+f"(d[65]), "+f"(d[66]), "+f"(d[67]), "+f"(d[68]), "+f"(d[69]), "+f"(d[70]), "+f"(d[71]),
        "+f"(d[72]), "+f"(d[73]), "+f"(d[74]), "+f"(d[75]), "+f"(d[76]), "+f"(d[77]), "+f"(d[78]), "+f"(d[79]),
        "+f"(d[80]), "+f"(d[81]), "+f"(d[82]), "+f"(d[83]), "+f"(d[84]), "+f"(d[85]), "+f"(d[86]), "+f"(d[87]),
        "+f"(d[88]), "+f"(d[89]), "+f"(d[90]), "+f"(d[91]), "+f"(d[92]), "+f"(d[93]), "+f"(d[94]), "+f"(d[95])
      : "l"(descA), "l"(descB), "r"(acc));
}

__device__ __forceinline__ void mma_ss80_tt(float (&d)[40], uint64_t descA, uint64_t descB) {
  asm volatile("wgmma.mma_async.sync.aligned.m64n80k16.f32.bf16.bf16 {"
      "%0, %1, %2, %3, %4, %5, %6, %7, %8, %9, %10, %11, %12, %13, %14, %15, "
      "%16, %17, %18, %19, %20, %21, %22, %23, %24, %25, %26, %27, %28, %29, %30, %31, "
      "%32, %33, %34, %35, %36, %37, %38, %39"
      "}, %40, %41, 1, 1, 1, 1, 1;\n"
      : "+f"(d[0]), "+f"(d[1]), "+f"(d[2]), "+f"(d[3]), "+f"(d[4]), "+f"(d[5]), "+f"(d[6]), "+f"(d[7]),
        "+f"(d[8]), "+f"(d[9]), "+f"(d[10]), "+f"(d[11]), "+f"(d[12]), "+f"(d[13]), "+f"(d[14]), "+f"(d[15]),
        "+f"(d[16]), "+f"(d[17]), "+f"(d[18]), "+f"(d[19]), "+f"(d[20]), "+f"(d[21]), "+f"(d[22]), "+f"(d[23]),
        "+f"(d[24]), "+f"(d[25]), "+f"(d[26]), "+f"(d[27]), "+f"(d[28]), "+f"(d[29]), "+f"(d[30]), "+f"(d[31]),
        "+f"(d[32]), "+f"(d[33]), "+f"(d[34]), "+f"(d[35]), "+f"(d[36]), "+f"(d[37]), "+f"(d[38]), "+f"(d[39])
      : "l"(descA), "l"(descB));
}
__device__ __forceinline__ void mma_ss80_tt_z(float (&d)[40], uint64_t descA, uint64_t descB) {
  asm volatile("wgmma.mma_async.sync.aligned.m64n80k16.f32.bf16.bf16 {"
      "%0, %1, %2, %3, %4, %5, %6, %7, %8, %9, %10, %11, %12, %13, %14, %15, "
      "%16, %17, %18, %19, %20, %21, %22, %23, %24, %25, %26, %27, %28, %29, %30, %31, "
      "%32, %33, %34, %35, %36, %37, %38, %39"
      "}, %40, %41, 0, 1, 1, 1, 1;\n"
      : "=f"(d[0]), "=f"(d[1]), "=f"(d[2]), "=f"(d[3]), "=f"(d[4]), "=f"(d[5]), "=f"(d[6]), "=f"(d[7]),
        "=f"(d[8]), "=f"(d[9]), "=f"(d[10]), "=f"(d[11]), "=f"(d[12]), "=f"(d[13]), "=f"(d[14]), "=f"(d[15]),
        "=f"(d[16]), "=f"(d[17]), "=f"(d[18]), "=f"(d[19]), "=f"(d[20]), "=f"(d[21]), "=f"(d[22]), "=f"(d[23]),
        "=f"(d[24]), "=f"(d[25]), "=f"(d[26]), "=f"(d[27]), "=f"(d[28]), "=f"(d[29]), "=f"(d[30]), "=f"(d[31]),
        "=f"(d[32]), "=f"(d[33]), "=f"(d[34]), "=f"(d[35]), "=f"(d[36]), "=f"(d[37]), "=f"(d[38]), "=f"(d[39])
      : "l"(descA), "l"(descB));
}

__device__ __forceinline__ void mma_rs80_k(float (&d)[40], const uint32_t (&a)[4], uint64_t descB) {
  asm volatile("wgmma.mma_async.sync.aligned.m64n80k16.f32.bf16.bf16 {"
      "%0, %1, %2, %3, %4, %5, %6, %7, %8, %9, %10, %11, %12, %13, %14, %15, "
      "%16, %17, %18, %19, %20, %21, %22, %23, %24, %25, %26, %27, %28, %29, %30, %31, "
      "%32, %33, %34, %35, %36, %37, %38, %39"
      "}, {%40, %41, %42, %43}, %44, 1, 1, 1, 0;\n"
      : "+f"(d[0]), "+f"(d[1]), "+f"(d[2]), "+f"(d[3]), "+f"(d[4]), "+f"(d[5]), "+f"(d[6]), "+f"(d[7]),
        "+f"(d[8]), "+f"(d[9]), "+f"(d[10]), "+f"(d[11]), "+f"(d[12]), "+f"(d[13]), "+f"(d[14]), "+f"(d[15]),
        "+f"(d[16]), "+f"(d[17]), "+f"(d[18]), "+f"(d[19]), "+f"(d[20]), "+f"(d[21]), "+f"(d[22]), "+f"(d[23]),
        "+f"(d[24]), "+f"(d[25]), "+f"(d[26]), "+f"(d[27]), "+f"(d[28]), "+f"(d[29]), "+f"(d[30]), "+f"(d[31]),
        "+f"(d[32]), "+f"(d[33]), "+f"(d[34]), "+f"(d[35]), "+f"(d[36]), "+f"(d[37]), "+f"(d[38]), "+f"(d[39])
      : "r"(a[0]), "r"(a[1]), "r"(a[2]), "r"(a[3]), "l"(descB));
}
__device__ __forceinline__ void mma_rs80_k_z(float (&d)[40], const uint32_t (&a)[4], uint64_t descB) {
  asm volatile("wgmma.mma_async.sync.aligned.m64n80k16.f32.bf16.bf16 {"
      "%0, %1, %2, %3, %4, %5, %6, %7, %8, %9, %10, %11, %12, %13, %14, %15, "
      "%16, %17, %18, %19, %20, %21, %22, %23, %24, %25, %26, %27, %28, %29, %30, %31, "
      "%32, %33, %34, %35, %36, %37, %38, %39"
      "}, {%40, %41, %42, %43}, %44, 0, 1, 1, 0;\n"
      : "=f"(d[0]), "=f"(d[1]), "=f"(d[2]), "=f"(d[3]), "=f"(d[4]), "=f"(d[5]), "=f"(d[6]), "=f"(d[7]),
        "=f"(d[8]), "=f"(d[9]), "=f"(d[10]), "=f"(d[11]), "=f"(d[12]), "=f"(d[13]), "=f"(d[14]), "=f"(d[15]),
        "=f"(d[16]), "=f"(d[17]), "=f"(d[18]), "=f"(d[19]), "=f"(d[20]), "=f"(d[21]), "=f"(d[22]), "=f"(d[23]),
        "=f"(d[24]), "=f"(d[25]), "=f"(d[26]), "=f"(d[27]), "=f"(d[28]), "=f"(d[29]), "=f"(d[30]), "=f"(d[31]),
        "=f"(d[32]), "=f"(d[33]), "=f"(d[34]), "=f"(d[35]), "=f"(d[36]), "=f"(d[37]), "=f"(d[38]), "=f"(d[39])
      : "r"(a[0]), "r"(a[1]), "r"(a[2]), "r"(a[3]), "l"(descB));
}

__device__ __forceinline__ void mma_rs48_k(float (&d)[24], const uint32_t (&a)[4], uint64_t descB) {
  asm volatile("wgmma.mma_async.sync.aligned.m64n48k16.f32.bf16.bf16 {"
      "%0, %1, %2, %3, %4, %5, %6, %7, %8, %9, %10, %11, %12, %13, %14, %15, "
      "%16, %17, %18, %19, %20, %21, %22, %23"
      "}, {%24, %25, %26, %27}, %28, 1, 1, 1, 0;\n"
      : "+f"(d[0]), "+f"(d[1]), "+f"(d[2]), "+f"(d[3]), "+f"(d[4]), "+f"(d[5]), "+f"(d[6]), "+f"(d[7]),
        "+f"(d[8]), "+f"(d[9]), "+f"(d[10]), "+f"(d[11]), "+f"(d[12]), "+f"(d[13]), "+f"(d[14]), "+f"(d[15]),
        "+f"(d[16]), "+f"(d[17]), "+f"(d[18]), "+f"(d[19]), "+f"(d[20]), "+f"(d[21]), "+f"(d[22]), "+f"(d[23])
      : "r"(a[0]), "r"(a[1]), "r"(a[2]), "r"(a[3]), "l"(descB));
}
__device__ __forceinline__ void mma_rs48_k_z(float (&d)[24], const uint32_t (&a)[4], uint64_t descB) {
  asm volatile("wgmma.mma_async.sync.aligned.m64n48k16.f32.bf16.bf16 {"
      "%0, %1, %2, %3, %4, %5, %6, %7, %8, %9, %10, %11, %12, %13, %14, %15, "
      "%16, %17, %18, %19, %20, %21, %22, %23"
      "}, {%24, %25, %26, %27}, %28, 0, 1, 1, 0;\n"
      : "=f"(d[0]), "=f"(d[1]), "=f"(d[2]), "=f"(d[3]), "=f"(d[4]), "=f"(d[5]), "=f"(d[6]), "=f"(d[7]),
        "=f"(d[8]), "=f"(d[9]), "=f"(d[10]), "=f"(d[11]), "=f"(d[12]), "=f"(d[13]), "=f"(d[14]), "=f"(d[15]),
        "=f"(d[16]), "=f"(d[17]), "=f"(d[18]), "=f"(d[19]), "=f"(d[20]), "=f"(d[21]), "=f"(d[22]), "=f"(d[23])
      : "r"(a[0]), "r"(a[1]), "r"(a[2]), "r"(a[3]), "l"(descB));
}

__device__ __forceinline__ void mma_rs160_n(float (&d)[80], const uint32_t (&a)[4], uint64_t descB) {
  asm volatile("wgmma.mma_async.sync.aligned.m64n160k16.f32.bf16.bf16 {"
      "%0, %1, %2, %3, %4, %5, %6, %7, %8, %9, %10, %11, %12, %13, %14, %15, "
      "%16, %17, %18, %19, %20, %21, %22, %23, %24, %25, %26, %27, %28, %29, %30, %31, "
      "%32, %33, %34, %35, %36, %37, %38, %39, %40, %41, %42, %43, %44, %45, %46, %47, "
      "%48, %49, %50, %51, %52, %53, %54, %55, %56, %57, %58, %59, %60, %61, %62, %63, "
      "%64, %65, %66, %67, %68, %69, %70, %71, %72, %73, %74, %75, %76, %77, %78, %79"
      "}, {%80, %81, %82, %83}, %84, 1, 1, 1, 1;\n"
      : "+f"(d[0]), "+f"(d[1]), "+f"(d[2]), "+f"(d[3]), "+f"(d[4]), "+f"(d[5]), "+f"(d[6]), "+f"(d[7]),
        "+f"(d[8]), "+f"(d[9]), "+f"(d[10]), "+f"(d[11]), "+f"(d[12]), "+f"(d[13]), "+f"(d[14]), "+f"(d[15]),
        "+f"(d[16]), "+f"(d[17]), "+f"(d[18]), "+f"(d[19]), "+f"(d[20]), "+f"(d[21]), "+f"(d[22]), "+f"(d[23]),
        "+f"(d[24]), "+f"(d[25]), "+f"(d[26]), "+f"(d[27]), "+f"(d[28]), "+f"(d[29]), "+f"(d[30]), "+f"(d[31]),
        "+f"(d[32]), "+f"(d[33]), "+f"(d[34]), "+f"(d[35]), "+f"(d[36]), "+f"(d[37]), "+f"(d[38]), "+f"(d[39]),
        "+f"(d[40]), "+f"(d[41]), "+f"(d[42]), "+f"(d[43]), "+f"(d[44]), "+f"(d[45]), "+f"(d[46]), "+f"(d[47]),
        "+f"(d[48]), "+f"(d[49]), "+f"(d[50]), "+f"(d[51]), "+f"(d[52]), "+f"(d[53]), "+f"(d[54]), "+f"(d[55]),
        "+f"(d[56]), "+f"(d[57]), "+f"(d[58]), "+f"(d[59]), "+f"(d[60]), "+f"(d[61]), "+f"(d[62]), "+f"(d[63]),
        "+f"(d[64]), "+f"(d[65]), "+f"(d[66]), "+f"(d[67]), "+f"(d[68]), "+f"(d[69]), "+f"(d[70]), "+f"(d[71]),
        "+f"(d[72]), "+f"(d[73]), "+f"(d[74]), "+f"(d[75]), "+f"(d[76]), "+f"(d[77]), "+f"(d[78]), "+f"(d[79])
      : "r"(a[0]), "r"(a[1]), "r"(a[2]), "r"(a[3]), "l"(descB));
}
__device__ __forceinline__ void mma_rs160_n_z(float (&d)[80], const uint32_t (&a)[4], uint64_t descB) {
  asm volatile("wgmma.mma_async.sync.aligned.m64n160k16.f32.bf16.bf16 {"
      "%0, %1, %2, %3, %4, %5, %6, %7, %8, %9, %10, %11, %12, %13, %14, %15, "
      "%16, %17, %18, %19, %20, %21, %22, %23, %24, %25, %26, %27, %28, %29, %30, %31, "
      "%32, %33, %34, %35, %36, %37, %38, %39, %40, %41, %42, %43, %44, %45, %46, %47, "
      "%48, %49, %50, %51, %52, %53, %54, %55, %56, %57, %58, %59, %60, %61, %62, %63, "
      "%64, %65, %66, %67, %68, %69, %70, %71, %72, %73, %74, %75, %76, %77, %78, %79"
      "}, {%80, %81, %82, %83}, %84, 0, 1, 1, 1;\n"
      : "=f"(d[0]), "=f"(d[1]), "=f"(d[2]), "=f"(d[3]), "=f"(d[4]), "=f"(d[5]), "=f"(d[6]), "=f"(d[7]),
        "=f"(d[8]), "=f"(d[9]), "=f"(d[10]), "=f"(d[11]), "=f"(d[12]), "=f"(d[13]), "=f"(d[14]), "=f"(d[15]),
        "=f"(d[16]), "=f"(d[17]), "=f"(d[18]), "=f"(d[19]), "=f"(d[20]), "=f"(d[21]), "=f"(d[22]), "=f"(d[23]),
        "=f"(d[24]), "=f"(d[25]), "=f"(d[26]), "=f"(d[27]), "=f"(d[28]), "=f"(d[29]), "=f"(d[30]), "=f"(d[31]),
        "=f"(d[32]), "=f"(d[33]), "=f"(d[34]), "=f"(d[35]), "=f"(d[36]), "=f"(d[37]), "=f"(d[38]), "=f"(d[39]),
        "=f"(d[40]), "=f"(d[41]), "=f"(d[42]), "=f"(d[43]), "=f"(d[44]), "=f"(d[45]), "=f"(d[46]), "=f"(d[47]),
        "=f"(d[48]), "=f"(d[49]), "=f"(d[50]), "=f"(d[51]), "=f"(d[52]), "=f"(d[53]), "=f"(d[54]), "=f"(d[55]),
        "=f"(d[56]), "=f"(d[57]), "=f"(d[58]), "=f"(d[59]), "=f"(d[60]), "=f"(d[61]), "=f"(d[62]), "=f"(d[63]),
        "=f"(d[64]), "=f"(d[65]), "=f"(d[66]), "=f"(d[67]), "=f"(d[68]), "=f"(d[69]), "=f"(d[70]), "=f"(d[71]),
        "=f"(d[72]), "=f"(d[73]), "=f"(d[74]), "=f"(d[75]), "=f"(d[76]), "=f"(d[77]), "=f"(d[78]), "=f"(d[79])
      : "r"(a[0]), "r"(a[1]), "r"(a[2]), "r"(a[3]), "l"(descB));
}

__device__ __forceinline__ void feature_map(const uint32_t (&P)[2][10], uint32_t (&fr)[10][4]) {
  constexpr float L2E = 1.4426950408889634f;
#pragma unroll
  for (int p = 0; p < 2; p++) {
#pragma unroll
    for (int r = 0; r < 2; r++) {
      uint32_t mx = P[r][5 * p], mn = mx;
#pragma unroll
      for (int g = 1; g < 5; g++) { mx = max_bf2(mx, P[r][5 * p + g]); mn = min_bf2(mn, P[r][5 * p + g]); }
      mx = max_bf2(mx, __shfl_xor_sync(0xffffffffu, mx, 1));
      mn = min_bf2(mn, __shfl_xor_sync(0xffffffffu, mn, 1));
      mx = max_bf2(mx, __shfl_xor_sync(0xffffffffu, mx, 2));
      mn = min_bf2(mn, __shfl_xor_sync(0xffffffffu, mn, 2));
      float mx0 = -bf_lo(mx) * L2E, mx1 = -bf_hi(mx) * L2E, mn0 = bf_lo(mn) * L2E, mn1 = bf_hi(mn) * L2E;
      float ep0[5], ep1[5], en0[5], en1[5];
      float sp0 = 0.f, sp1 = 0.f, sn0 = 0.f, sn1 = 0.f;
#pragma unroll
      for (int g = 0; g < 5; g++) {
        float x0 = bf_lo(P[r][5 * p + g]), x1 = bf_hi(P[r][5 * p + g]);
        ep0[g] = ex2(fmaf(x0, L2E, mx0)); ep1[g] = ex2(fmaf(x1, L2E, mx1));
        en0[g] = ex2(fmaf(x0, -L2E, mn0)); en1[g] = ex2(fmaf(x1, -L2E, mn1));
        sp0 += ep0[g]; sp1 += ep1[g]; sn0 += en0[g]; sn1 += en1[g];
      }
      sp0 += __shfl_xor_sync(0xffffffffu, sp0, 1); sp1 += __shfl_xor_sync(0xffffffffu, sp1, 1);
      sn0 += __shfl_xor_sync(0xffffffffu, sn0, 1); sn1 += __shfl_xor_sync(0xffffffffu, sn1, 1);
      sp0 += __shfl_xor_sync(0xffffffffu, sp0, 2); sp1 += __shfl_xor_sync(0xffffffffu, sp1, 2);
      sn0 += __shfl_xor_sync(0xffffffffu, sn0, 2); sn1 += __shfl_xor_sync(0xffffffffu, sn1, 2);
      {
        const float pp = sp0 * sp1, nn = sn0 * sn1, rr = rcp(pp * nn), rp = rr * nn, rn = rr * pp;
        const float a = rp * sp1, b = rp * sp0, c = rn * sn1, d = rn * sn0;
        sp0 = a; sp1 = b; sn0 = c; sn1 = d;
      }
#pragma unroll
      for (int g = 0; g < 5; g++) {
        fr[5 * p + g][r] = pack_bf16(ep0[g] * sp0, ep1[g] * sp1);
        fr[5 * p + g][2 + r] = pack_bf16(en0[g] * sn0, en1[g] * sn1);
      }
    }
  }
}

template <int V> struct IntC { static constexpr int value = V; };
struct Ring {
  uint32_t idx, phase;
  template <int N> __device__ __forceinline__ void next() { if (++idx == N) { idx = 0; phase ^= 1; } }
};

}

__global__ void __cluster_dims__(2, 1, 1) __launch_bounds__(384, 1)
fused_kernel(const __grid_constant__ Maps maps, const __nv_bfloat16* __restrict__ x, const __nv_bfloat16* __restrict__ wqkv,
             const __nv_bfloat16* __restrict__ wphi, const __nv_bfloat16* __restrict__ w1, const __nv_bfloat16* __restrict__ w2,
             const __nv_bfloat16* __restrict__ w3, const __nv_bfloat16* __restrict__ w4, const __nv_bfloat16* __restrict__ wo,
             const __nv_bfloat16* __restrict__ gate_w, __nv_bfloat16* __restrict__ out) {
  extern __shared__ __align__(1024) uint8_t sgen[];
  const uint32_t sb = smem_u32(sgen);
  const uint32_t sb16 = (sb & 0x3FFFFu) >> 4;
  const uint32_t bars = sb + OFF_BAR;
  const uint32_t fullA = bars + 8 * B_FULLA, emptyA = bars + 8 * B_EMPTYA, fullB = bars + 8 * B_FULLB, emptyB = bars + 8 * B_EMPTYB;

  const int tid = threadIdx.x;
  const int rank = blockIdx.x & 1;
  const int bid = blockIdx.x - NSVC, pairIdx = bid >> 1;
  const int i = pairIdx >> 2, j = 2 * (pairIdx & 3) + rank;
  const int k3 = (5 * (pairIdx & 3) + 1) >> 1;

  if (bid < 0) {
    const int sv = blockIdx.x;
    const unsigned epoch = *reinterpret_cast<volatile unsigned*>(g_flags + FL_DONE * 32) / NCTA;
    if (tid == 0) {
#pragma unroll
      for (int b = 0; b < 11; b++) mbar_init(bars + 8 * b, 1);
      mbar_expect_tx(bars + 80, 6400);
      bulk_load(sb + 204800, wphi + sv * 3200, 6400, bars + 80);
    }
    __syncthreads();
    float a[8];
#pragma unroll 1
    for (int rd = 0; rd < 4; rd++) {
      const int nch = rd ? 192 : 80, nth = rd ? 384 : 320, piece = rd ? 18432 : 20480, np = rd == 3 ? 7 : 10;
      if (tid == 0) {
        const char* src = reinterpret_cast<const char*>(rd ? w3 + (size_t)(160 * sv + 60 * (rd - 1)) * F_ : w1 + (size_t)160 * sv * D_);
#pragma unroll 1
        for (int p = 0; p < np; p++) {
          const int bytes = (rd == 3 && p == 6) ? 12288 : piece;
          mbar_expect_tx(bars + 8 * p, bytes);
          bulk_load(sb + p * piece, src + p * piece, bytes, bars + 8 * p);
        }
      }
      if (rd == 0) {
        if (tid < 40 && (tid < 20 || sv >= 2))
          reinterpret_cast<uint4*>(g_Hs + (size_t)(2 + ((sv & 1) ? S_ - 1 - tid / 20 : tid / 20)) * D_ + 160 * sv)[tid % 20] = make_uint4(0, 0, 0, 0);
        mbar_wait(bars + 80, 0);
#pragma unroll 1
        for (int e = tid; e < 1600; e += 384) {
          const int jj = e / 800, it = e - 800 * jj, st = it / 160, n = (it - 160 * st) >> 1, k0 = 16 * st + 8 * ((it ^ (n >> 2)) & 1);
          const int nn = n % 40, h = 2 * (n / 40) + (nn & 1), ff = 4 * (nn >> 3) + ((nn >> 1) & 3);
          uint32_t w[8];
#pragma unroll
          for (int q = 0; q < 8; q++) {
            const int k = k0 + q;
            w[q] = (unsigned)(k - 20 * h) < 20u ? reinterpret_cast<const unsigned short*>(sgen + 204800)[jj * 1600 + k * 20 + ff] : 0u;
          }
          g_wphi[sv * 1600 + e] = make_uint4(w[0] | (w[1] << 16), w[2] | (w[3] << 16), w[4] | (w[5] << 16), w[6] | (w[7] << 16));
        }
      }
      if (rd < 2) {
#pragma unroll
        for (int e = 0; e < 8; e++) a[e] = 0.f;
      }
#pragma unroll 1
      for (int p = 0; p < np; p++) {
        mbar_wait(bars + 8 * p, rd & 1);
        const int bytes = (rd == 3 && p == 6) ? 12288 : piece;
        if (tid < nth) {
#pragma unroll 1
          for (int o = tid * 16; o < bytes; o += nth * 16) {
            const uint4 v = lds128(sb + p * piece + o);
            a[0] += bf_lo(v.x); a[1] += bf_hi(v.x); a[2] += bf_lo(v.y); a[3] += bf_hi(v.y);
            a[4] += bf_lo(v.z); a[5] += bf_hi(v.z); a[6] += bf_lo(v.w); a[7] += bf_hi(v.w);
          }
        }
      }
      if (tid < nth && (rd == 0 || rd == 3)) {
        float* cd = g_cs[epoch & 1] + (rd ? D_ : 0) + 8 * (tid % nch);
        red_add4(cd, a[0], a[1], a[2], a[3]); red_add4(cd + 4, a[4], a[5], a[6], a[7]);
      }
      __syncthreads();
      if (tid == 0 && (rd == 0 || rd == 3)) {
        flag_add(rd ? FL_CS3 : FL_CS);
        if (rd == 0) l2_prefetch(w2 + (size_t)sv * (D_ * D_ / NSVC), D_ * D_ * 2 / NSVC);
      }
    }
#pragma unroll 1
    for (int e = tid; e < (D_ + F_) / NSVC; e += 384) g_cs[(epoch + 1) & 1][sv * ((D_ + F_) / NSVC) + e] = 0.f;
#pragma unroll 1
    for (int e = tid; e < 2 * KV_J; e += 384) g_acc[(epoch + 1) & 1][sv * 2 * KV_J + e] = 0.f;
    if (tid < 32) {
      l2_prefetch(w4 + (size_t)(sv * 32 + tid) * (F_ * D_ / 128), F_ * D_ * 2 / 128);
      l2_prefetch(wo + (size_t)(sv * 32 + tid) * (D_ * D_ / 128), D_ * D_ * 2 / 128);
    }
    return;
  }
  TSTAMP(0);
  if (tid >= 256) {
    asm volatile("setmaxnreg.dec.sync.aligned.u32 40;");
    if (tid == 256) {
#pragma unroll
      for (int s = 0; s < NA; s++) mbar_init(fullA + 8 * s, 1);
      asm volatile("fence.mbarrier_init.release.cluster;" ::: "memory");
#pragma unroll 1
      for (int u = 0; u < 4; u++) {
        if ((u & 1) == 0) mbar_expect_tx(fullA + 4 * u, SLOT_A);
        tma2d(sb + OFF_A + u * 8192, &maps.x, fullA + 8 * (u >> 1), 64 * (u >> 1), 128 * i + 64 * (u & 1));
      }
    } else if (tid == 288) {
#pragma unroll
      for (int s = 0; s < NB; s++) { mbar_init(fullB + 8 * s, 1); mbar_init(emptyB + 8 * s, 8); }
      asm volatile("fence.mbarrier_init.release.cluster;" ::: "memory");
    } else if (tid == 320) {
#pragma unroll
      for (int b = B_CS; b < NBAR; b++) if (b < B_EMPTYB || b >= B_EMPTYB + NB) mbar_init(bars + 8 * b, b < B_EMPTYB ? 1 : b < B_EMPTYA ? 8 : b < B_X1P ? 16 : 2);
#pragma unroll
      for (int b = B_DSR; b < B_EMPTYB; b++) mbar_expect_tx(bars + 8 * b, 10240);
      asm volatile("fence.mbarrier_init.release.cluster;" ::: "memory");
    }
    __syncwarp();
    asm volatile("barrier.cluster.arrive.relaxed.aligned;" ::: "memory");
    auto get_epoch = [&]() { return *reinterpret_cast<volatile unsigned*>(g_flags + FL_DONE * 32) / NCTA; };
    if ((tid >> 5) != 9) asm volatile("barrier.cluster.wait.aligned;" ::: "memory");
    const int lane = tid & 31, pw = (tid >> 5) & 3;
    if (pw == 0) {
      if (tid == 256) {
        Ring r{2, 1};
#pragma unroll 1
        for (int k = 2; k < 24; k++) {
          if (k == 10 || k == 16) {
            mbar_wait(bars + 8 * B_HST, k == 16);
            TSTAMPX(k == 10 ? 29 : 30);
          }
          if (k == 14) {
            mbar_wait(bars + 8 * B_WDEAD, 0);
            mbar_expect_tx(bars + 8 * B_T4, SLOT_A);
            tma2d(sb + OFF_MISC, &maps.hs, bars + 8 * B_T4, 256 + 320 * rank, 128 * i);
            mbar_wait(emptyA + 16, r.phase); mbar_wait(emptyA + 24, r.phase);
            mbar_expect_tx(bars + 8 * B_XR, 20480);
            tma2d(sb + OFF_STG, &maps.xr, bars + 8 * B_XR, 80 * j, 128 * i);
            mbar_wait(bars + 8 * B_X1P, 0);
          }
          mbar_wait(emptyA + 8 * r.idx, r.phase);
          const uint32_t bar = fullA + 8 * r.idx, slot = sb + OFF_A + r.idx * SLOT_A;
          mbar_expect_tx(bar, SLOT_A);
          if (k >= 10 && k < 14) tma2d(slot, &maps.hs, bar, 64 * (k - 10) + 320 * rank, 128 * i);
          else tma2d_mc(slot + rank * 8192, k < 10 ? &maps.x : &maps.x1, bar, 64 * (k < 10 ? k : (k - 14 + k3) % 10), 128 * i + 64 * rank);
          r.next<NA>();
        }
      }
    } else if (pw == 1) {
      if (tid == 288) {
        Ring r{0, 1};
#pragma unroll 1
        for (int k = 0; k < 18; k++) {
          mbar_wait(emptyB + 8 * r.idx, r.phase);
          const uint32_t bar = fullB + 8 * r.idx, slot = sb + OFF_B + r.idx * SLOT_B;
          if (k < 10) {
            mbar_expect_tx(bar, 40960);
            tma4d(slot + 8192, &maps.qm, bar, 0, 64 * k, 0, j);
            tma3d(slot, &maps.w1m, bar, 0, 64 * k, j);
            tma4d(slot + 32768 + 2048, &maps.qr, bar, 64, 64 * k, 0, j);
            tma3d(slot + 32768, &maps.w1r, bar, 64, 64 * k, j);
          } else if (k < 13) {
            mbar_expect_tx(bar, k < 12 ? 40960 : 20480);
            tma3d(slot, &maps.w2, bar, 0, 320 * rank + 128 * (k - 10), 5 * (j >> 1));
            if (k < 12) tma3d(slot + 20480, &maps.w2, bar, 0, 320 * rank + 128 * (k - 10) + 64, 5 * (j >> 1));
          } else {
            if (k == 13) mbar_wait(bars + 8 * B_KVR, 0);
            mbar_expect_tx(bar, 49152);
            tma3d(slot, &maps.w3, bar, 0, 64 * ((2 * (k - 13) + k3) % 10), 3 * j);
            tma3d(slot + 24576, &maps.w3, bar, 0, 64 * ((2 * (k - 13) + 1 + k3) % 10), 3 * j);
          }
          r.next<NB>();
        }
#pragma unroll 1
        for (int n = 0; n < 8; n++) {
          if (n < 3) { mbar_wait(emptyB + 8 * r.idx, r.phase); r.next<NB>(); }
          if (n == 0) mbar_wait(fullA + 24, 1);
          if (n >= 4) mbar_wait(bars + 8 * (B_EMPTY4 + n - 4), 0);
          const uint32_t bar = bars + 8 * (B_FULL4 + n), set = sb + ((n >> 1) & 1) * SET4;
          const int h = n & 1, m = ((j >> 1) + 1 + (n >> 1)) & 3;
          mbar_expect_tx(bar, h ? 40960 : 46080);
          tma3d(set + (h ? 46080 : 0), h ? &maps.w4 : &maps.wo, bar, 0, h ? 192 * j + 64 : 80 * j, 5 * m);
          tma3d(set + (h ? 66560 : 25600), &maps.w4, bar, 0, 192 * j + 128 * h, 5 * m);
        }
        mbar_wait(bars + 8 * (B_EMPTY4 + 4), 0);
        mbar_expect_tx(bars + 8 * B_XR, 20480);
        tma2d(sb + OFF_OUT, &maps.st_x1, bars + 8 * B_XR, 80 * j, 128 * i);
      }
    } else {
      const unsigned epoch = get_epoch();
      float* accg = g_acc[epoch & 1];
      if (pw == 2) {
        if (tid == 320) {
          flag_wait(FL_CS, (epoch + 1) * NSVC);
          flag_wait(FL_ST + i, (epoch + 1) * 8u);
          fence_async_glb();
          *reinterpret_cast<volatile uint32_t*>(sgen + OFF_BAR + 8 * NBAR) = (epoch + 1) & 1;
          mbar_expect_tx(bars + 8 * B_CS, 320 + 2048 + 12800);
          bulk_load(sb + OFF_CS, g_cs[epoch & 1] + 80 * j, 320, bars + 8 * B_CS);
          bulk_load(sb + OFF_XST, g_xstat + 128 * i, 2048, bars + 8 * B_CS);
          bulk_load(sb + OFF_MISC, g_wphi + j * 800, 12800, bars + 8 * B_CS);
          TSTAMPX(21);
          mbar_wait(bars + 8 * B_SIGKV, 0);
          TSTAMPX(25);
#pragma unroll 1
          for (int u = 0; u < 4; u++)
            asm volatile("cp.reduce.async.bulk.global.shared::cta.bulk_group.add.f32 [%0], [%1], %2;"
                         ::"l"(accg + j * KV_J + (u >> 1) * KV_PAIR + (u & 1) * 1024), "r"(sb + OFF_B + SPARE + (u & 1) * SLOT_B + (u >> 1) * 4096),
                         "r"((u & 1) ? KV_PAIR * 4 - 4096 : 4096) : "memory");
          bulk_commit(); bulk_wait<0>();
          mbar_arrive(bars + 8 * B_KVR);
          flag_add(FL_KV + j);
          TSTAMPX(26);
          flag_wait(FL_KV + j, (epoch + 1) * 16u);
          mbar_wait(bars + 8 * B_SIGX1, 0);
          mbar_expect_tx(bars + 8 * B_KV, KV_J * 4);
          bulk_load(sb + OFF_A + SLOT_A, accg + j * KV_J, KV_J * 4, bars + 8 * B_KV);
          TSTAMPX(22);
          flag_wait(FL_CS3, (epoch + 1) * NSVC);
          flag_wait(FL_S1 + i, (epoch + 1) * 8u);
          fence_async_glb();
          mbar_expect_tx(bars + 8 * B_ST1, 8192 + 768);
          bulk_load(sb + OFF_CS + 320, g_cs[epoch & 1] + D_ + 192 * j, 768, bars + 8 * B_ST1);
          bulk_load(sb + OFF_MISC, g_st1 + 128 * i * 8, 8192, bars + 8 * B_ST1);
        }
        __syncwarp();
#pragma unroll 1
        for (int c = 0; c < 3; c++) {
          mbar_wait(bars + 8 * (B_EMPTY4 + (c ? 5 : 4)), 0);
          const uint4* src = g_part + (size_t)((i * 8 + j) * 3 + c) * 1280;
          const unsigned* tp = reinterpret_cast<const unsigned*>(src + 1024 + (lane & 7) * 32 + 31);
          uint32_t n = 0;
          while (!__all_sync(0xffffffffu, (ld_acquire(tp) ^ epoch) & 1u) && ++n < (WAIT_LIMIT >> 2)) {}
          if (tid == 320) {
            mbar_expect_tx(bars + 8 * (B_RDY + c), 20480);
            bulk_load(sb + (c ? 25600 + 20480 * c : 0), src, 20480, bars + 8 * (B_RDY + c));
          }
        }
      }
      if (tid == 352) {
        mbar_wait(bars + 8 * B_SIGP, 0);
        flag_add(FL_ST + i);
        TSTAMPX(20);
        const int shift = (j < 2) ? 1 : (j < 4) ? -1 : (j < 6) ? 2 : -2;
        prefetch_tmap(&maps.st_h); prefetch_tmap(&maps.st_x1); prefetch_tmap(&maps.hs); prefetch_tmap(&maps.x1); prefetch_tmap(&maps.xr);
        prefetch_tmap(&maps.w2); prefetch_tmap(&maps.w3); prefetch_tmap(&maps.w4); prefetch_tmap(&maps.wo);
        mbar_wait(bars + 8 * B_SIGH, 0);
        TSTAMPX(23);
        tma2d_store(&maps.st_h, sb + OFF_STG, 80 * j, 128 * i + 2 + shift);
        bulk_commit(); bulk_wait<0>();
        flag_add(FL_H + 2 * i + (j >> 2));
        flag_add_relaxed(FL_H + 2 * ((i + (shift > 0 ? 1 : -1)) & 15) + (j >> 2));
        TSTAMPX(24);
        flag_wait(FL_H + 2 * i + rank, (epoch + 1) * 8u);
        mbar_arrive(bars + 8 * B_HST);
        mbar_wait(bars + 8 * B_SIGX1, 0);
        TSTAMPX(27);
        tma2d_store(&maps.st_x1, sb + OFF_STG, 80 * j, 128 * i);
        bulk_commit(); bulk_wait<0>();
        flag_add(FL_X1 + i);
        mbar_arrive_cta(bars + 8 * B_X1P, 0); mbar_arrive_cta(bars + 8 * B_X1P, 1);
        TSTAMPX(28);
        flag_wait(FL_X1 + i, (epoch + 1) * 8u);
        mbar_arrive(bars + 8 * B_HST);
        mbar_wait(bars + 8 * B_MFREE, 0);
        flag_add(FL_S1 + i);
      }
    }
  } else {
    uint4 pv[5], pw_[5];
    {
      const int row = 128 * i + 16 * j + (tid >> 4), l16 = tid & 15;
#pragma unroll
      for (int c = 0; c < 5; c++) pv[c] = __ldg(reinterpret_cast<const uint4*>(x + (size_t)row * D_ + c * 128 + l16 * 8));
#pragma unroll
      for (int c = 0; c < 5; c++) pw_[c] = __ldg(reinterpret_cast<const uint4*>(gate_w + c * 128 + l16 * 8));
    }
    asm volatile("barrier.cluster.arrive.relaxed.aligned;" ::: "memory");
    asm volatile("setmaxnreg.inc.sync.aligned.u32 232;");
    const int wg = tid >> 7, warp = tid >> 5, lane = tid & 31, t = lane & 3;
    const int rloc = warp * 16 + (lane >> 2);
    const float* s_cs = reinterpret_cast<const float*>(sgen + OFF_CS);
    auto signal = [&](int b) {
      __syncwarp();
      if (lane == 0) mbar_arrive(bars + 8 * b);
    };
    auto releaseB = [&](uint32_t bar) {
      __syncwarp();
      if (lane == 0) mbar_arrive(bar);
    };
    auto release = [&](uint32_t bar) {
      __syncwarp();
      if (lane < 2) mbar_arrive_cta(bar, lane);
    };
    const uint32_t stg_lane = (warp * 16 + ((lane >> 3) & 1) * 8 + (lane & 7)) * 160 + (lane >> 4) * 16;

    auto stage_tile = [&](uint32_t stg, const uint32_t (&v)[2][10]) {
#pragma unroll
      for (int s = 0; s < 5; s++) stsm4(stg + stg_lane + s * 32, v[0][2 * s], v[1][2 * s], v[0][2 * s + 1], v[1][2 * s + 1]);
    };

    {
      float f[40];
      float s = 0.f, gs = 0.f;
#pragma unroll
      for (int c = 0; c < 5; c++) {
        const uint32_t vv[4] = {pv[c].x, pv[c].y, pv[c].z, pv[c].w}, ww[4] = {pw_[c].x, pw_[c].y, pw_[c].z, pw_[c].w};
#pragma unroll
        for (int e = 0; e < 4; e++) {
          f[8 * c + 2 * e] = bf_lo(vv[e]); f[8 * c + 2 * e + 1] = bf_hi(vv[e]);
          s += f[8 * c + 2 * e] + f[8 * c + 2 * e + 1];
          const uint32_t pr = mul_bf2(vv[e], ww[e]);
          gs += bf_lo(pr) + bf_hi(pr);
        }
      }
#pragma unroll
      for (int o = 1; o < 16; o <<= 1) { s += __shfl_xor_sync(0xffffffffu, s, o); gs += __shfl_xor_sync(0xffffffffu, gs, o); }
      const float mean = s * (1.f / D_);
      float q = 0.f;
#pragma unroll
      for (int e = 0; e < 40; e++) { const float d = f[e] - mean; q = fmaf(d, d, q); }
#pragma unroll
      for (int o = 1; o < 16; o <<= 1) q += __shfl_xor_sync(0xffffffffu, q, o);
      const float rstd = rsqrtf(q * (1.f / D_) + 1e-5f);
      const float gate = bf_lo(pack_bf16(rcp(1.f + __expf(-bf_lo(pack_bf16(gs, 0.f)))), 0.f));
      asm volatile("barrier.cluster.wait.aligned;" ::: "memory");
      if ((tid & 15) == 0) g_xstat[128 * i + 16 * j + (tid >> 4)] = make_float4(rstd, -mean, gate, 0.f);
      signal(B_SIGP);
    }
    TSTAMP(1);

    Ring ra{0, 0}, rb{0, 0};
    uint32_t qp[2][10], P[2][10];
    float st_g[2];
    {
      float accM[128], accR[32];
      uint32_t pa = 0, pb = 0;
#pragma unroll 1
      for (int k = 0; k < 10; k++) {
        mbar_wait(fullA + 8 * ra.idx, ra.phase);
        if (tid == 0) TRACE(32 + k);
        mbar_wait(fullB + 8 * rb.idx, rb.phase);
        if (tid == 0) TRACE(64 + k);
        if (k == 0) TSTAMP(2);
        const uint32_t a0 = sb16 + ((OFF_A + ra.idx * SLOT_A + wg * 8192) >> 4), b0 = sb16 + ((OFF_B + rb.idx * SLOT_B) >> 4);
        wg_fence();
#pragma unroll
        for (int kk = 0; kk < 4; kk++) {
          const uint64_t da = make_desc(a0, kk * 32, 16, 1024, 1);
          if (kk == 0) {
            mma_ss256_p(accM, da, make_desc(b0, 0, 8192, 1024, 1), k);
            mma_ss64_p(accR, da, make_desc(b0, 32768, 2048, 256, 3), k);
          } else {
            mma_ss256(accM, da, make_desc(b0, kk * 2048, 8192, 1024, 1));
            mma_ss64(accR, da, make_desc(b0, 32768 + kk * 512, 2048, 256, 3));
          }
          if (kk == 0) {
            wg_commit();
            if (k > 0) {
              wg_wait<1>();
              release(emptyA + 8 * pa);
              releaseB(emptyB + 8 * pb);
            }
          }
        }
        wg_commit();
        pa = ra.idx; pb = rb.idx;
        ra.next<NA>(); rb.next<NB>();
      }
      TSTAMP(18);
      float st_rstd[2], st_mr[2];
      mbar_wait(bars + 8 * B_CS, 0);
#pragma unroll
      for (int r = 0; r < 2; r++) {
        const uint4 st = lds128(sb + OFF_XST + (rloc + 8 * r) * 16);
        st_rstd[r] = __uint_as_float(st.x); st_mr[r] = __uint_as_float(st.y); st_g[r] = __uint_as_float(st.z);
      }
      TSTAMP(19);
      wg_wait<0>();
      fence_regs(accM); fence_regs(accR);
      TSTAMP(3);
      release(emptyA + 8 * pa);
#define ACC(P_, G, I_) ((G) < 8 ? accM[(P_) * 32 + ((G) & 7) * 4 + (I_)] : accR[(P_) * 8 + ((G) & 1) * 4 + (I_)])
      {
        uint32_t hv[2][10];
        const GeluC g0 = gelu_consts(st_rstd[0], 1.f), g1 = gelu_consts(st_rstd[1], 1.f);
#pragma unroll
        for (int g = 0; g < 10; g++) {
          const float2 cs = *reinterpret_cast<const float2*>(s_cs + 8 * g + 2 * t);
          const float v0 = gelu_s(fmaf(st_mr[0], cs.x, ACC(0, g, 0)), g0), v1 = gelu_s(fmaf(st_mr[0], cs.y, ACC(0, g, 1)), g0);
          const float v2 = gelu_s(fmaf(st_mr[1], cs.x, ACC(0, g, 2)), g1), v3 = gelu_s(fmaf(st_mr[1], cs.y, ACC(0, g, 3)), g1);
          hv[0][g] = pack_bf16(v0, v1); hv[1][g] = pack_bf16(v2, v3);
        }
        bar_sync(1, 256);
        stage_tile(sb + OFF_STG, hv);
        fence_async_smem();
        signal(B_SIGH);
      }
      TSTAMP(4);
      uint32_t kf[5][4], qf[5][4];
#pragma unroll
      for (int s = 0; s < 5; s++) {
        kf[s][0] = pack_bf16(ACC(2, 2 * s, 0), ACC(2, 2 * s, 1)); kf[s][1] = pack_bf16(ACC(2, 2 * s, 2), ACC(2, 2 * s, 3));
        kf[s][2] = pack_bf16(ACC(2, 2 * s + 1, 0), ACC(2, 2 * s + 1, 1)); kf[s][3] = pack_bf16(ACC(2, 2 * s + 1, 2), ACC(2, 2 * s + 1, 3));
        qf[s][0] = pack_bf16(ACC(1, 2 * s, 0), ACC(1, 2 * s, 1)); qf[s][1] = pack_bf16(ACC(1, 2 * s, 2), ACC(1, 2 * s, 3));
        qf[s][2] = pack_bf16(ACC(1, 2 * s + 1, 0), ACC(1, 2 * s + 1, 1)); qf[s][3] = pack_bf16(ACC(1, 2 * s + 1, 2), ACC(1, 2 * s + 1, 3));
      }
      float pk[40], pq[40];
      wg_fence();
#pragma unroll
      for (int s = 0; s < 5; s++) {
        if (s == 0) mma_rs80_k_z(pk, kf[s], make_desc(sb16, OFF_MISC, 16, 256, 3));
        else mma_rs80_k(pk, kf[s], make_desc(sb16, OFF_MISC + s * 2560, 16, 256, 3));
      }
      wg_commit();
#pragma unroll
      for (int s = 0; s < 5; s++) {
        if (s == 0) mma_rs80_k_z(pq, qf[s], make_desc(sb16, OFF_MISC, 16, 256, 3));
        else mma_rs80_k(pq, qf[s], make_desc(sb16, OFF_MISC + s * 2560, 16, 256, 3));
      }
      wg_commit();
      {
        const int mat = lane >> 3;
        const int tok = warp * 16 + (mat & 1) * 8 + (lane & 7);
        const uint32_t base = sb + OFF_B + SPARE + tok * 32 + (((mat >> 1) ^ ((tok >> 2) & 1)) << 4);
        const uint32_t ones = (t == 0) ? 0x00003f80u : 0u;
#pragma unroll
        for (int p = 0; p < 2; p++) {
#pragma unroll
          for (int gg = 0; gg < 3; gg++) {
            const int g0 = 5 * p + 2 * gg;
            uint32_t r0 = pack_bf16(ACC(3, g0, 0), ACC(3, g0, 1)), r1 = pack_bf16(ACC(3, g0, 2), ACC(3, g0, 3));
            uint32_t r2 = ones, r3 = ones;
            if (gg < 2) { r2 = pack_bf16(ACC(3, g0 + 1, 0), ACC(3, g0 + 1, 1)); r3 = pack_bf16(ACC(3, g0 + 1, 2), ACC(3, g0 + 1, 3)); }
            stsm4(base + gg * SLOT_B + p * 4096, r0, r1, r2, r3);
          }
        }
      }
#undef ACC
      wg_wait<1>();
      fence_regs(pk);
#pragma unroll
      for (int G = 0; G < 10; G++) {
        P[0][G] = pack_bf16(pk[4 * G], pk[4 * G + 1]); P[1][G] = pack_bf16(pk[4 * G + 2], pk[4 * G + 3]);
      }
      wg_wait<0>();
      fence_regs(pq);
      signal(B_WDEAD);
#pragma unroll
      for (int G = 0; G < 10; G++) {
        qp[0][G] = pack_bf16(pq[4 * G], pq[4 * G + 1]); qp[1][G] = pack_bf16(pq[4 * G + 2], pq[4 * G + 3]);
      }
    }

    uint32_t fr[10][4];
    int pass;
    pass = gridDim.y;
#pragma unroll 1
    do {
    feature_map(P, fr);
    if (pass != 0) {
    {
      const int mat = lane >> 3;
      const int tok = warp * 16 + (mat & 1) * 8 + (lane & 7);
      const uint32_t base = sb + OFF_B + tok * 32 + (((mat >> 1) ^ ((tok >> 2) & 1)) << 4);
#pragma unroll
      for (int G = 0; G < 10; G++) stsm4(base + G * 4096, fr[G][0], fr[G][1], fr[G][2], fr[G][3]);
      fence_async_smem();
      bar_sync(1, 256);
      float kv[40];
      const uint32_t va = sb16 + ((OFF_B + SPARE + wg * 4096) >> 4), vb = sb16 + ((OFF_B + wg * 20480) >> 4);
      wg_fence();
#pragma unroll
      for (int ks = 0; ks < 8; ks++) {
        if (ks == 0) mma_ss80_tt_z(kv, make_desc(va, 0, SLOT_B, 256, 3), make_desc(vb, 0, 4096, 256, 3));
        else mma_ss80_tt(kv, make_desc(va, ks * 512, SLOT_B, 256, 3), make_desc(vb, ks * 512, 4096, 256, 3));
      }
      wg_commit();
      uint32_t xv[2][10];
      wg_wait<0>();
      fence_regs(kv);
      TSTAMP(31);
      releaseB(emptyB); release(bars + 8 * B_PEER2);
      auto kv_sts = [&](uint32_t o, uint32_t a0, uint32_t a1, uint32_t a2, uint32_t a3) {
        sts128(sb + OFF_B + SPARE + wg * 4096 + o + (o >= 4096 ? SLOT_B - 4096 : 0), make_uint4(a0, a1, a2, a3));
      };
      const int m0 = (warp & 3) * 16 + (lane >> 2);
      bar_sync(4 + wg, 128);
#pragma unroll
      for (int r = 0; r < 2; r++) {
        const int m = m0 + 8 * r;
        const bool hi = m >= 20;
        uint32_t v[10];
#pragma unroll
        for (int G = 0; G < 10; G++) v[G] = __float_as_uint(hi ? kv[4 * G + 2 * r + 1] : kv[4 * G + 2 * r]);
        const uint32_t p = 4 * (m < 40 ? m * 48 + t * 12 : 1920 + t * 24 + 12);
        if (m <= 40) { kv_sts(p, v[0], v[1], v[2], v[3]); kv_sts(p + 16, v[4], v[5], v[6], v[7]); kv_sts(p + 32, v[8], v[9], 0u, 0u); }
      }
      if (m0 == 32) {
        const uint32_t p = 4 * (1920 + t * 24);
        kv_sts(p, __float_as_uint(kv[2]), __float_as_uint(kv[6]), __float_as_uint(kv[10]), __float_as_uint(kv[14]));
        kv_sts(p + 16, __float_as_uint(kv[18]), __float_as_uint(kv[22]), __float_as_uint(kv[26]), __float_as_uint(kv[30]));
        kv_sts(p + 32, __float_as_uint(kv[34]), __float_as_uint(kv[38]), 0u, 0u);
      }
      fence_async_smem();
      signal(B_SIGKV);
      float acc[80];
      TSTAMP(5);
      mbar_wait(fullA + 8 * 2, 0);
      mbar_wait(fullB + 8 * 1, 1);
      TSTAMP(6);
      wg_fence();
#pragma unroll
      for (int kk = 0; kk < 4; kk++) {
        const uint64_t da = make_desc(sb16 + wg * 512, OFF_A + 2 * SLOT_A + kk * 32, 16, 1024, 1);
        const uint64_t db = make_desc(sb16, OFF_B + SLOT_B + kk * 1024, 4096, 512, 2);
        if (kk == 0) mma_ss160_z(acc, da, db); else mma_ss160(acc, da, db);
      }
      wg_commit();
      ra.next<NA>();
      uint32_t pa = 2, pb = 1;
#pragma unroll 1
      for (int k = 1; k < 5; k++) {
        mbar_wait(k < 4 ? fullA + 8 * ra.idx : bars + 8 * B_T4, k < 4 ? ra.phase : 0);
        if ((k & 1) == 0) mbar_wait(fullB + 8 * rb.idx, rb.phase);
        const uint32_t a0 = sb16 + ((OFF_A + (k < 4 ? ra.idx : NA) * SLOT_A + wg * 8192) >> 4);
        const uint32_t b0 = sb16 + ((OFF_B + rb.idx * SLOT_B + (k & 1) * 20480) >> 4);
        wg_fence();
#pragma unroll
        for (int kk = 0; kk < 4; kk++) {
          mma_ss160(acc, make_desc(a0, kk * 32, 16, 1024, 1), make_desc(b0, kk * 1024, 4096, 512, 2));
          if (kk == 0) {
            wg_commit();
            wg_wait<1>();
            if (k != 4) release(emptyA + 8 * pa);
            if ((k & 1) == 0) releaseB(emptyB + 8 * pb);
          }
        }
        wg_commit();
        pa = ra.idx; pb = rb.idx;
        if (k < 4) ra.next<NA>();
        if ((k & 1) || k == 4) rb.next<NB>();
      }
      mbar_wait(bars + 8 * B_PEER2, 0);
      wg_wait<0>();
      fence_regs(acc);
      TSTAMP(7);
      {
        uint32_t sn[20];
        if (rank) {
#pragma unroll
          for (int e = 0; e < 20; e++) sn[e] = pack_bf16(acc[2 * e], acc[2 * e + 1]);
#pragma unroll
          for (int e = 0; e < 40; e++) acc[e] = acc[40 + e];
        } else {
#pragma unroll
          for (int e = 0; e < 20; e++) sn[e] = pack_bf16(acc[40 + 2 * e], acc[41 + 2 * e]);
        }
        const uint32_t peer = map_peer(sb, rank ^ 1);
#pragma unroll
        for (int q = 0; q < 5; q++)
          st_async16(peer + OFF_B + 20480 + tid * 16 + q * 4096, sn[4 * q], sn[4 * q + 1], sn[4 * q + 2], sn[4 * q + 3],
                     peer + OFF_BAR + 8 * (B_DSR + 8 + wg));
        mbar_wait(bars + 8 * B_XR, 0);
        __syncwarp();
#pragma unroll
        for (int q = 0; q < 5; q++) {
          const uint4 v = ldsm4(sb + OFF_STG + stg_lane + q * 32);
          float* d = &acc[8 * q];
          d[0] += bf_lo(v.x); d[1] += bf_hi(v.x); d[2] += bf_lo(v.y); d[3] += bf_hi(v.y);
          d[4] += bf_lo(v.z); d[5] += bf_hi(v.z); d[6] += bf_lo(v.w); d[7] += bf_hi(v.w);
        }
        mbar_wait(bars + 8 * (B_DSR + 8 + wg), 0);
#pragma unroll
        for (int q = 0; q < 5; q++) {
          const uint4 v = lds128(sb + OFF_B + 20480 + tid * 16 + q * 4096);
          float* d = &acc[8 * q];
          d[0] += bf_lo(v.x); d[1] += bf_hi(v.x); d[2] += bf_lo(v.y); d[3] += bf_hi(v.y);
          d[4] += bf_lo(v.z); d[5] += bf_hi(v.z); d[6] += bf_lo(v.w); d[7] += bf_hi(v.w);
          xv[0][2 * q] = pack_bf16(d[0], d[1]); xv[1][2 * q] = pack_bf16(d[2], d[3]);
          xv[0][2 * q + 1] = pack_bf16(d[4], d[5]); xv[1][2 * q + 1] = pack_bf16(d[6], d[7]);
        }
        releaseB(emptyB + 8 * pb);
      }
      TSTAMP(16);
      stage_tile(sb + OFF_STG, xv);
      fence_async_smem();
      signal(B_SIGX1);
      TSTAMP(17);
#pragma unroll
      for (int r = 0; r < 2; r++) {
        float s = 0.f;
#pragma unroll
        for (int g = 0; g < 10; g++) s += acc[4 * g + 2 * r] + acc[4 * g + 2 * r + 1];
        s += __shfl_xor_sync(0xffffffffu, s, 1); s += __shfl_xor_sync(0xffffffffu, s, 2);
        const float mu = s * (1.f / 80.f);
        float q = 0.f;
#pragma unroll
        for (int g = 0; g < 10; g++) {
          const float d0 = acc[4 * g + 2 * r] - mu, d1 = acc[4 * g + 2 * r + 1] - mu;
          q = fmaf(d0, d0, q); q = fmaf(d1, d1, q);
        }
        q += __shfl_xor_sync(0xffffffffu, q, 1); q += __shfl_xor_sync(0xffffffffu, q, 2);
        if (t == 0) g_st1[(128 * i + rloc + 8 * r) * 8 + j] = make_float2(mu, q);
      }
    }
    TSTAMP(8);
#pragma unroll
    for (int G = 0; G < 10; G++) { P[0][G] = qp[0][G]; P[1][G] = qp[1][G]; }
    }
    asm volatile("" : "+r"(pass));
    } while (pass-- != 0);

    uint32_t of[5][4];
    {
      mbar_wait(bars + 8 * B_KV, 0);
#pragma unroll 1
      for (int it = tid; it < 384; it += 256) {
        const int p = it >= 192, rem = it - 192 * p, n = rem >> 2, tq = rem & 3;
        const uint32_t sp = sb + OFF_A + SLOT_A + 4 * (p * KV_PAIR + (n < 40 ? n * 48 + tq * 12 : 1920 + tq * 24 + (n & 1) * 12));
        const uint4 ka = lds128(sp), kb = lds128(sp + 16), kc = lds128(sp + 32);
        const uint32_t v[10] = {ka.x, ka.y, ka.z, ka.w, kb.x, kb.y, kb.z, kb.w, kc.x, kc.y};
        const int sh = (n < 40 ? (n >= 20) : (n & 1)) * 16;
        uint8_t* dst = sgen + OFF_MISC + p * 7680 + n * 32 + tq * 4;
        const int sw = ((n >> 2) & 1) << 4;
#pragma unroll
        for (int G = 0; G < 10; G++)
          *reinterpret_cast<uint32_t*>(dst + (G >> 1) * 1536 + (((G & 1) << 4) ^ sw)) = pack_bf16(__uint_as_float(v[G]), 0.f) << sh;
      }
      release(emptyA + 8);
      fence_async_smem();
      bar_sync(1, 256);
      float o0[24], o1[24];
      wg_fence();
#pragma unroll
      for (int g = 0; g < 5; g++) {
        if (g == 0) mma_rs48_k_z(o0, fr[g], make_desc(sb16, OFF_MISC, 16, 256, 3));
        else mma_rs48_k(o0, fr[g], make_desc(sb16, OFF_MISC + g * 1536, 16, 256, 3));
      }
#pragma unroll
      for (int g = 0; g < 5; g++) {
        if (g == 0) mma_rs48_k_z(o1, fr[5], make_desc(sb16, OFF_MISC + 7680, 16, 256, 3));
        else mma_rs48_k(o1, fr[5 + g], make_desc(sb16, OFF_MISC + 7680 + g * 1536, 16, 256, 3));
      }
      wg_commit();
      wg_wait<0>();
      fence_regs(o0); fence_regs(o1);
      signal(B_MFREE);
#pragma unroll
      for (int r = 0; r < 2; r++) {
        const float a0 = __fdividef(st_g[r], o0[20 + 2 * r] + 1e-6f), a1 = __fdividef(st_g[r], o0[21 + 2 * r] + 1e-6f);
        const float b0 = __fdividef(st_g[r], o1[20 + 2 * r] + 1e-6f), b1 = __fdividef(st_g[r], o1[21 + 2 * r] + 1e-6f);
        const float am = t < 2 ? a0 : a1, bm = t < 2 ? b0 : b1;
#pragma unroll
        for (int g = 0; g < 5; g++) {
          const float sa = g < 2 ? a0 : (g == 2 ? am : a1), sb2 = g < 2 ? b0 : (g == 2 ? bm : b1);
          of[g >> 1][(g & 1) * 2 + r] = pack_bf16(o0[4 * g + 2 * r] * sa, o0[4 * g + 2 * r + 1] * sa);
          of[(5 + g) >> 1][((5 + g) & 1) * 2 + r] = pack_bf16(o1[4 * g + 2 * r] * sb2, o1[4 * g + 2 * r + 1] * sb2);
        }
      }
    }
    TSTAMP(9);

    uint32_t hf[12][4];
    float ac4[80];
    auto unit = [&](auto uc, uint32_t b0) {
      constexpr int u = decltype(uc)::value;
#pragma unroll
      for (int s = 0; s < (u ? 4 : 5); s++) {
        const uint64_t db = make_desc(b0, (u ? 5120 + 20480 * u : 0) + s * 1024, u ? 4096 : 5120, 512, 2);
        if (u == 0 && s == 0) mma_rs160_n_z(ac4, of[0], db);
        else if (u == 0) mma_rs160_n(ac4, of[s], db);
        else mma_rs160_n(ac4, hf[(4 * u + 8 + s) % 12], db);
      }
      wg_commit();
    };
    {
      float acc[96];
      uint32_t pa = 0, pb = 0;
#pragma unroll 1
      for (int k = 0; k < 10; k++) {
        mbar_wait(fullA + 8 * ra.idx, ra.phase);
        if (tid == 0) TRACE(52 + k);
        if ((k & 1) == 0) mbar_wait(fullB + 8 * rb.idx, rb.phase);
        if (tid == 0) TRACE(84 + k);
        if (k == 0) TSTAMP(10);
        const uint32_t a0 = sb16 + ((OFF_A + ra.idx * SLOT_A + wg * 8192) >> 4);
        const uint32_t b0 = sb16 + ((OFF_B + rb.idx * SLOT_B + (k & 1) * 24576) >> 4);
        wg_fence();
#pragma unroll
        for (int kk = 0; kk < 4; kk++) {
          if (kk == 0) mma_ss192_p(acc, make_desc(a0, 0, 16, 1024, 1), make_desc(b0, 0, 8192, 1024, 1), k);
          else mma_ss192(acc, make_desc(a0, kk * 32, 16, 1024, 1), make_desc(b0, kk * 2048, 8192, 1024, 1));
          if (kk == 0) {
            wg_commit();
            if (k > 0) {
              wg_wait<1>();
              release(emptyA + 8 * pa);
              if ((k & 1) == 0) releaseB(emptyB + 8 * pb);
            }
          }
        }
        wg_commit();
        pa = ra.idx; pb = rb.idx;
        ra.next<NA>();
        if (k & 1) rb.next<NB>();
      }
      float rs[2], mm[2];
      mbar_wait(bars + 8 * B_ST1, 0);
#pragma unroll
      for (int r = 0; r < 2; r++) {
        const uint4 su = lds128(sb + OFF_MISC + (rloc + 8 * r) * 64 + t * 16);
        const float m0 = __uint_as_float(su.x), m1 = __uint_as_float(su.z);
        float mu = m0 + m1;
        mu += __shfl_xor_sync(0xffffffffu, mu, 1); mu += __shfl_xor_sync(0xffffffffu, mu, 2);
        mu *= 0.125f;
        const float d0 = m0 - mu, d1 = m1 - mu;
        float q = __uint_as_float(su.y) + __uint_as_float(su.w) + 80.f * (d0 * d0 + d1 * d1);
        q += __shfl_xor_sync(0xffffffffu, q, 1); q += __shfl_xor_sync(0xffffffffu, q, 2);
        rs[r] = rsqrtf(q * (1.f / D_) + 1e-5f);
        mm[r] = -mu;
      }
      mbar_wait(bars + 8 * B_FULL4, 0);
      wg_fence();
      unit(IntC<0>{}, sb16);
      wg_wait<1>();
      fence_regs(acc);
      releaseB(emptyB + 8 * pb);
      release(bars + 8 * B_PEER);
      TSTAMP(11);
      const GeluC g0 = gelu_consts(rs[0], 1.f - st_g[0]), g1 = gelu_consts(rs[1], 1.f - st_g[1]);
#pragma unroll
      for (int g = 0; g < 24; g++) {
        const float2 cs = *reinterpret_cast<const float2*>(s_cs + 80 + 8 * g + 2 * t);
        const float v0 = gelu_s(fmaf(mm[0], cs.x, acc[4 * g]), g0), v1 = gelu_s(fmaf(mm[0], cs.y, acc[4 * g + 1]), g0);
        const float v2 = gelu_s(fmaf(mm[1], cs.x, acc[4 * g + 2]), g1), v3 = gelu_s(fmaf(mm[1], cs.y, acc[4 * g + 3]), g1);
        hf[g >> 1][(g & 1) * 2] = pack_bf16(v0, v1);
        hf[g >> 1][(g & 1) * 2 + 1] = pack_bf16(v2, v3);
        if (g == 7) { wg_fence(); unit(IntC<1>{}, sb16); }
        if (g == 15) { mbar_wait(bars + 8 * (B_FULL4 + 1), 0); wg_fence(); unit(IntC<2>{}, sb16); }
        if (g == 23) { wg_wait<1>(); signal(B_EMPTY4); wg_fence(); unit(IntC<3>{}, sb16); }
      }
    }
    TSTAMP(12);

    {
      float kp[40];
      uint32_t sn[20], kb[20];
      const uint32_t peer = map_peer(sb, rank ^ 1);
      const uint32_t tag = lds32(sb + OFF_BAR + 8 * NBAR);
      auto add8 = [&](int q, const uint4 v) {
        float* d = &kp[8 * q];
        d[0] += bf_lo(v.x); d[1] += bf_hi(v.x); d[2] += bf_lo(v.y); d[3] += bf_hi(v.y);
        d[4] += bf_lo(v.z); d[5] += bf_hi(v.z); d[6] += bf_lo(v.w); d[7] += bf_hi(v.w);
      };
      auto send = [&](int c) {
        const uint32_t dso = peer + OFF_DS + (c & 1) * 20480 + tid * 16, dsb = peer + OFF_BAR + 8 * (B_DSR + 2 * c + wg);
#pragma unroll
        for (int q = 0; q < 5; q++) st_async16(dso + q * 4096, sn[4 * q], sn[4 * q + 1], sn[4 * q + 2], sn[4 * q + 3], dsb);
      };
      mbar_wait(bars + 8 * B_PEER, 0);
      uint4* gdst = g_part + (size_t)i * 8 * 3840 + tid;
#pragma unroll 1
      for (int c = 0; c < 3; c++) {
        const uint32_t b0 = sb16 + ((c & 1) ? 0 : SET4 >> 4), bc = bars + 16 * c;
        mbar_wait(bc + 8 * (B_FULL4 + 2), 0);
        wg_wait<0>();
        fence_regs(ac4);
        if (rank) {
#pragma unroll
          for (int e = 0; e < 20; e++) { sn[e] = pack_bf16(ac4[2 * e], ac4[2 * e + 1]); kb[e] = pack_bf16(ac4[40 + 2 * e], ac4[41 + 2 * e]); }
        } else {
#pragma unroll
          for (int e = 0; e < 20; e++) { kb[e] = pack_bf16(ac4[2 * e], ac4[2 * e + 1]); sn[e] = pack_bf16(ac4[40 + 2 * e], ac4[41 + 2 * e]); }
        }
#pragma unroll
        for (int e = 0; e < 20; e++) asm volatile("" : "+r"(sn[e]), "+r"(kb[e]));
        send(c);
        if (c == 0 && wg == 1) bar_sync(2, 256);
        wg_fence();
        unit(IntC<0>{}, b0);
        if (lane == 0) mbar_arrive(bc + 8 * (B_EMPTY4 + 1));
        unit(IntC<1>{}, b0);
        if (c == 0 && wg == 0) bar_arrive(2, 256);
        {
          mbar_wait(bc + 8 * (B_DSR + wg), 0);
          uint4* dst = gdst + (((j + 2 * c + 2) & 7) * 3 + c) * 1280;
#pragma unroll
          for (int q = 0; q < 5; q++) {
            const uint4 v = lds128(sb + OFF_DS + (c & 1) * 20480 + tid * 16 + q * 4096);
            st_relaxed16(dst + q * 256, (add_bf2(v.x, kb[4 * q]) & ~1u) | tag, add_bf2(v.y, kb[4 * q + 1]),
                         add_bf2(v.z, kb[4 * q + 2]), add_bf2(v.w, kb[4 * q + 3]));
          }
        }
        mbar_wait(bc + 8 * (B_FULL4 + 3), 0);
        wg_fence();
        unit(IntC<2>{}, b0);
        wg_wait<1>();
        if (lane == 0) mbar_arrive(bc + 8 * (B_EMPTY4 + 2));
        unit(IntC<3>{}, b0);
      }
      auto partial = [&](int c, uint4 (&v)[5]) {
        mbar_wait(bars + 8 * (B_RDY + c), 0);
        uint32_t bad = 0;
#pragma unroll
        for (int q = 0; q < 5; q++) { v[q] = lds128(sb + (c ? 25600 + 20480 * c : 0) + tid * 16 + q * 4096); bad |= v[q].x ^ tag; }
#pragma unroll 1
        for (uint32_t n = 0; (bad & 1u) && n < (WAIT_LIMIT >> 2); n++) {
          bad = 0;
#pragma unroll
          for (int q = 0; q < 5; q++) { v[q] = ld_relaxed16(gdst + (j * 3 + c) * 1280 + q * 256); bad |= v[q].x ^ tag; }
        }
      };
      uint4 pa4[5], pb4[5];
      partial(0, pa4);
      wg_wait<0>();
      fence_regs(ac4);
      if (rank) {
#pragma unroll
        for (int e = 0; e < 20; e++) sn[e] = pack_bf16(ac4[2 * e], ac4[2 * e + 1]);
#pragma unroll
        for (int e = 0; e < 40; e++) kp[e] = ac4[40 + e];
      } else {
#pragma unroll
        for (int e = 0; e < 20; e++) sn[e] = pack_bf16(ac4[40 + 2 * e], ac4[41 + 2 * e]);
#pragma unroll
        for (int e = 0; e < 40; e++) kp[e] = ac4[e];
      }
      send(3);
      TSTAMP(13);
      {
        mbar_wait(bars + 8 * B_XR, 1);
        const float w0 = 1.f - st_g[0], w1s = 1.f - st_g[1];
        __syncwarp();
#pragma unroll
        for (int q = 0; q < 5; q++) {
          const uint4 v = ldsm4(sb + OFF_OUT + stg_lane + q * 32);
          float* d = &kp[8 * q];
          d[0] = fmaf(w0, bf_lo(v.x), d[0]); d[1] = fmaf(w0, bf_hi(v.x), d[1]); d[2] = fmaf(w1s, bf_lo(v.y), d[2]); d[3] = fmaf(w1s, bf_hi(v.y), d[3]);
          d[4] = fmaf(w0, bf_lo(v.z), d[4]); d[5] = fmaf(w0, bf_hi(v.z), d[5]); d[6] = fmaf(w1s, bf_lo(v.w), d[6]); d[7] = fmaf(w1s, bf_hi(v.w), d[7]);
        }
      }
      partial(1, pb4);
#pragma unroll
      for (int q = 0; q < 5; q++)
        pa4[q] = make_uint4(add_bf2(pa4[q].x, pb4[q].x), add_bf2(pa4[q].y, pb4[q].y), add_bf2(pa4[q].z, pb4[q].z), add_bf2(pa4[q].w, pb4[q].w));
#pragma unroll
      for (int q = 0; q < 5; q++) add8(q, pa4[q]);
      partial(2, pb4);
      mbar_wait(bars + 8 * (B_DSR + 6 + wg), 0);
      TSTAMP(14);
#pragma unroll
      for (int q = 0; q < 5; q++) {
        const uint4 c = pb4[q], d = lds128(sb + OFF_DS + 20480 + tid * 16 + q * 4096);
        add8(q, make_uint4(add_bf2(c.x, d.x), add_bf2(c.y, d.y), add_bf2(c.z, d.z), add_bf2(c.w, d.w)));
      }
      __syncwarp();
      uint32_t ov[2][10];
#pragma unroll
      for (int g = 0; g < 10; g++) { ov[0][g] = pack_bf16(kp[4 * g], kp[4 * g + 1]); ov[1][g] = pack_bf16(kp[4 * g + 2], kp[4 * g + 3]); }
      stage_tile(sb + OFF_OUT, ov);
      __syncwarp();
      __nv_bfloat16* dst = out + (size_t)(128 * i + 16 * warp) * D_ + 80 * j;
#pragma unroll
      for (int q = 0; q < 5; q++) {
        const int id = q * 32 + lane, r = id / 10;
        *reinterpret_cast<uint4*>(dst + r * (D_ - 80) + id * 8) = lds128(sb + OFF_OUT + warp * 2560 + id * 16);
      }
    }
    TSTAMP(15);
    if (tid == 0) asm volatile("red.relaxed.gpu.global.add.u32 [%0], 1;" ::"l"(g_flags + FL_DONE * 32) : "memory");
  }
}

namespace {
typedef CUresult (*EncodeFn)(CUtensorMap*, CUtensorMapDataType, cuuint32_t, void*, const cuuint64_t*, const cuuint64_t*,
                             const cuuint32_t*, const cuuint32_t*, CUtensorMapInterleave, CUtensorMapSwizzle,
                             CUtensorMapL2promotion, CUtensorMapFloatOOBfill);

void encode(EncodeFn fn, CUtensorMap* m, const void* ptr, int rank, const cuuint64_t* dims, const cuuint64_t* strides,
            const cuuint32_t* box, CUtensorMapSwizzle swz) {
  cuuint32_t es[5] = {1, 1, 1, 1, 1};
  fn(m, CU_TENSOR_MAP_DATA_TYPE_BFLOAT16, rank, const_cast<void*>(ptr), dims, strides, box, es, CU_TENSOR_MAP_INTERLEAVE_NONE,
     swz, CU_TENSOR_MAP_L2_PROMOTION_L2_128B, CU_TENSOR_MAP_FLOAT_OOB_FILL_NONE);
}
}

extern "C" void kernel_launch(void* const* d_in, const int* in_sizes, int n_in, void* d_out, int out_size) {
  (void)in_sizes; (void)n_in; (void)out_size;
  const __nv_bfloat16* x = (const __nv_bfloat16*)d_in[0];
  const __nv_bfloat16* wqkv = (const __nv_bfloat16*)d_in[1];
  const __nv_bfloat16* wphi = (const __nv_bfloat16*)d_in[2];
  const __nv_bfloat16* wo = (const __nv_bfloat16*)d_in[3];
  const __nv_bfloat16* w1 = (const __nv_bfloat16*)d_in[5];
  const __nv_bfloat16* w2 = (const __nv_bfloat16*)d_in[6];
  const __nv_bfloat16* w3 = (const __nv_bfloat16*)d_in[7];
  const __nv_bfloat16* w4 = (const __nv_bfloat16*)d_in[8];
  const __nv_bfloat16* gate_w = (const __nv_bfloat16*)d_in[9];

  static EncodeFn enc = nullptr;
  static void *pHs = nullptr, *pX1 = nullptr;
  if (!enc) {
    cudaDriverEntryPointQueryResult qr;
    cudaGetDriverEntryPoint("cuTensorMapEncodeTiled", (void**)&enc, cudaEnableDefault, &qr);
    cudaGetSymbolAddress(&pHs, g_Hs);
    cudaGetSymbolAddress(&pX1, g_X1);
    cudaFuncSetAttribute(fused_kernel, cudaFuncAttributeMaxDynamicSharedMemorySize, SMEM_BYTES);
  }
  Maps m;
  {
    cuuint64_t dims[2] = {D_, S_}, str[1] = {D_ * 2};
    cuuint32_t box[2] = {64, 128}, boxh[2] = {64, 64};
    encode(enc, &m.x, x, 2, dims, str, boxh, CU_TENSOR_MAP_SWIZZLE_128B);
    encode(enc, &m.hs, (const char*)pHs + 2 * D_ * 2, 2, dims, str, box, CU_TENSOR_MAP_SWIZZLE_128B);
    encode(enc, &m.x1, pX1, 2, dims, str, boxh, CU_TENSOR_MAP_SWIZZLE_128B);
    cuuint32_t boxs[2] = {80, 128};
    cuuint64_t dimsp[2] = {D_, S_ + 4};
    encode(enc, &m.st_h, pHs, 2, dimsp, str, boxs, CU_TENSOR_MAP_SWIZZLE_NONE);
    encode(enc, &m.st_x1, pX1, 2, dims, str, boxs, CU_TENSOR_MAP_SWIZZLE_NONE);
    encode(enc, &m.xr, x, 2, dims, str, boxs, CU_TENSOR_MAP_SWIZZLE_NONE);
  }
  {
    cuuint64_t dims[3] = {80, D_, 8}, str[2] = {D_ * 2, 160};
    cuuint32_t boxm[3] = {64, 64, 1}, boxr[3] = {16, 64, 1};
    encode(enc, &m.w1m, w1, 3, dims, str, boxm, CU_TENSOR_MAP_SWIZZLE_128B);
    encode(enc, &m.w1r, w1, 3, dims, str, boxr, CU_TENSOR_MAP_SWIZZLE_32B);
  }
  {
    cuuint64_t dims[4] = {80, D_, 3, 8}, str[3] = {3 * D_ * 2, D_ * 2, 160};
    cuuint32_t boxm[4] = {64, 64, 3, 1}, boxr[4] = {16, 64, 3, 1};
    encode(enc, &m.qm, wqkv, 4, dims, str, boxm, CU_TENSOR_MAP_SWIZZLE_128B);
    encode(enc, &m.qr, wqkv, 4, dims, str, boxr, CU_TENSOR_MAP_SWIZZLE_32B);
  }
  {
    cuuint64_t dims[3] = {32, D_, 20}, dims4[3] = {32, F_, 20}, str[2] = {D_ * 2, 64};
    cuuint32_t box4[3] = {32, 64, 5}, boxo[3] = {32, 80, 5};
    encode(enc, &m.w4, w4, 3, dims4, str, box4, CU_TENSOR_MAP_SWIZZLE_64B);
    encode(enc, &m.wo, wo, 3, dims, str, boxo, CU_TENSOR_MAP_SWIZZLE_64B);
    encode(enc, &m.w2, w2, 3, dims, str, box4, CU_TENSOR_MAP_SWIZZLE_64B);
  }
  {
    cuuint64_t dims[3] = {64, D_, 24}, str[2] = {F_ * 2, 128};
    cuuint32_t box[3] = {64, 64, 3};
    encode(enc, &m.w3, w3, 3, dims, str, box, CU_TENSOR_MAP_SWIZZLE_128B);
  }
  fused_kernel<<<NCTA + NSVC, 384, SMEM_BYTES, cudaStreamPerThread>>>(m, x, wqkv, wphi, w1, w2, w3, w4, wo, gate_w, (__nv_bfloat16*)d_out);
}
```
